```python
import torch

def _softmax(x, axis=-1):
    return torch.softmax(x, dim=axis)
def _gelu(x):
    return torch.nn.functional.gelu(x, approximate="tanh")
def _silu(x):
    return torch.nn.functional.silu(x)
def _sigmoid(x):
    return torch.sigmoid(x)
def _layernorm(x, axis=-1, eps=1e-5):
    m = x.mean(dim=axis, keepdim=True)
    v = x.var(dim=axis, keepdim=True, unbiased=False)
    return (x - m) / torch.sqrt(v + eps)
def _scatter_add(tgt, idx, src, axis=0):
    return tgt.clone().index_add_(axis, idx, src)
def _segment_sum(src, seg, n):
    out = torch.zeros((n,) + src.shape[1:], dtype=src.dtype)
    return out.index_add_(0, seg, src)
def _pad(x, pw):
    flat = tuple(v for pair in reversed(pw) for v in pair)
    return torch.nn.functional.pad(x, flat)

kernel_name = 'interleave_layers__linear_kernel_hedgehog__glu_gated_geglu__prompt'

def setup_inputs():

    _w = (lambda a: (lambda t: t.to(torch.bfloat16) if t.is_floating_point() else t)(torch.as_tensor(a)))
    def _A_setup():
        B, S, D, H = 1, 2048, 448, 16
        Dh = D // H
        return {
            "x": _w((lambda *s: torch.randn(*s, dtype=torch.bfloat16) * 0.05)(B, S, D)),
            "wqkv": _w((lambda *s: torch.randn(*s, dtype=torch.bfloat16) * 0.4)(D, 3 * D)),
            "w_phi": _w((lambda *s: torch.randn(*s, dtype=torch.bfloat16) * 0.4)(H, Dh, Dh) * (Dh ** -0.5)),
            "wo": _w((lambda *s: torch.randn(*s, dtype=torch.bfloat16) * 0.05)(D, D)),
        }
    _A_in = _A_setup()

    def _B_setup():
        B, S, Dm, Df = 1, 2048, 448, 1792
        return {
            "x": _w((lambda *s: torch.randn(*s, dtype=torch.bfloat16) * 0.05)(B, S, Dm)),
            "w_gate": _w((lambda *s: torch.randn(*s, dtype=torch.bfloat16) * 0.8)(Dm, Df) * (Dm ** -0.5)),
            "w_up": _w((lambda *s: torch.randn(*s, dtype=torch.bfloat16) * 0.8)(Dm, Df) * (Dm ** -0.5)),
            "w_down": _w((lambda *s: torch.randn(*s, dtype=torch.bfloat16) * 0.8)(Df, Dm) * (Df ** -0.5)),
        }
    _B_in = _B_setup()

    return {
        "A_x": _A_in["x"],
        "A_wqkv": _A_in["wqkv"],
        "A_w_phi": _A_in["w_phi"],
        "A_wo": _A_in["wo"],
        "B_x": _B_in["x"],
        "B_w_gate": _B_in["w_gate"],
        "B_w_up": _B_in["w_up"],
        "B_w_down": _B_in["w_down"],
    }

def reference(A_x, A_wqkv, A_w_phi, A_wo, B_x, B_w_gate, B_w_up, B_w_down):
    def _A_ref(x, wqkv, w_phi, wo):
        B, S, D = x.shape
        H = 16; Dh = D // H
        qkv = (lambda x, *d: x.permute(*d))((x @ wqkv).reshape(B, S, 3, H, Dh), 2, 0, 3, 1, 4)
        q, k, v = qkv[0], qkv[1], qkv[2]
        pq = torch.einsum("bhsd,hdf->bhsf", q, w_phi)
        pk = torch.einsum("bhsd,hdf->bhsf", k, w_phi)
        phi_q = torch.concatenate([_softmax(pq, axis=-1), _softmax(-pq, axis=-1)], axis=-1)
        phi_k = torch.concatenate([_softmax(pk, axis=-1), _softmax(-pk, axis=-1)], axis=-1)
        kv = torch.einsum("bhsf,bhsd->bhfd", phi_k, v)
        z  = torch.einsum("bhsf->bhf", phi_k)
        num = torch.einsum("bhqf,bhfd->bhqd", phi_q, kv)
        den = torch.einsum("bhqf,bhf->bhq", phi_q, z)[..., None] + 1e-6
        o = num / den
        return (lambda x, *d: x.permute(*d))(o, 0, 2, 1, 3).reshape(B, S, D) @ wo

    def _B_ref(x, w_gate, w_up, w_down):
        g = torch.einsum("bsd,df->bsf", x, w_gate)
        u = torch.einsum("bsd,df->bsf", x, w_up)
        h = _gelu(g) * u
        return torch.einsum("bsf,fd->bsd", h, w_down)

    x = A_x
    x = x + _A_ref(_layernorm(x, axis=-1), A_wqkv, A_w_phi, A_wo)
    x = x + _B_ref(_layernorm(x, axis=-1), B_w_gate, B_w_up, B_w_down)
    x = x + _A_ref(_layernorm(x, axis=-1), A_wqkv, A_w_phi, A_wo)
    x = x + _B_ref(_layernorm(x, axis=-1), B_w_gate, B_w_up, B_w_down)
    return x
```

```cpp
#include <cuda_runtime.h>
#include <cuda.h>
#include <cuda_bf16.h>
#include <stdint.h>
#include <type_traits>

#define PP

namespace {

constexpr uint32_t STAGE = 28672, HALF = 14336;
constexpr int NST = 5;
constexpr uint32_t OFF_H = NST * STAGE;
constexpr uint32_t OFF_KVB = OFF_H + 2 * STAGE;
constexpr uint32_t OFF_WPHI = OFF_KVB + 16384;
constexpr uint32_t OFF_XR = OFF_WPHI + 7168;
constexpr uint32_t OFF_BAR = OFF_XR + 6144;
constexpr uint32_t SMEM_BYTES = OFF_BAR + 256 + 1536;
constexpr int B_EMPTY = NST, B_RECV = 2 * NST, B_RECV2 = B_RECV + 2, B_PACK = B_RECV2 + 2, B_ACK = B_PACK + 1, B_ACK2 = B_ACK + 2, B_COUNT = B_ACK2 + 2;

constexpr int PACK = 14;

struct Maps { CUtensorMap x, qkv, wo, wg, wu, wg32, wu32, wd, out; int role[64]; int flag[5]; };

}

constexpr int PLANE = 16 * 2 * 8 * 512;
__device__ uint4 g_ex[6 * PLANE];
__device__ uint4 g_kv1[8 * 16 * 16 * 32];
__device__ uint4 g_kv2[8 * 512];
__device__ uint32_t g_c1[8 * 8 * 16 * 32];
__device__ uint32_t g_c2[8 * 4 * 16 * 32];
__device__ uint4 g_wp[8 * 32 * (HALF / 16)];
__device__ uint32_t g_cw[8 * 32];
#define STAMP(i)
#define GSTAMP(i)
#define PDUMP()
#define ASTAMP(i)

namespace {

__device__ __forceinline__ int fresh_tid() { int t; asm volatile("mov.u32 %0, %%tid.x;" : "=r"(t)); return t; }
__device__ __forceinline__ uint4* again(uint4* p) { asm volatile("" : "+l"(p)); return p; }
template <int N> __device__ __forceinline__ void kill(uint32_t* v) {
#pragma unroll
    for (int i = 0; i < N; i++) v[i] = 0;
}
template <int N> __device__ __forceinline__ void kill(float* v) {
#pragma unroll
    for (int i = 0; i < N; i++) v[i] = 0.f;
}
__device__ __forceinline__ uint32_t s2u(const void* p) { return (uint32_t)__cvta_generic_to_shared(p); }
__device__ __forceinline__ void mbar_init(uint32_t a, uint32_t c) { asm volatile("mbarrier.init.shared::cta.b64 [%0], %1;" ::"r"(a), "r"(c) : "memory"); }
__device__ __forceinline__ void mbar_expect_tx(uint32_t a, uint32_t b) { asm volatile("mbarrier.arrive.expect_tx.shared::cta.b64 _, [%0], %1;" ::"r"(a), "r"(b) : "memory"); }
__device__ __forceinline__ void mbar_arrive(uint32_t a) { asm volatile("mbarrier.arrive.shared::cta.b64 _, [%0];" ::"r"(a) : "memory"); }
#define GIVE_UP(id) "trap;\n"
#define SPIN_MAX "0x400000"
#define SPIN_TAIL(id) "add.u32 n, n, 1;\n setp.lt.u32 p, n, " SPIN_MAX ";\n @p bra.uni LP;\n" GIVE_UP(id) " DN:\n }"
__device__ __forceinline__ void mbar_wait(uint32_t a, uint32_t ph) {
    asm volatile("{ .reg .pred p; .reg .b32 n; mov.u32 n, 0;\n LP:\n"
                 "mbarrier.try_wait.parity.shared::cta.b64 p, [%0], %1;\n @p bra DN;\n"
                 "add.u32 n, n, 1;\n setp.lt.u32 p, n, " SPIN_MAX ";\n @p bra LP;\n"
                 GIVE_UP("")
                 " DN:\n }" ::"r"(a), "r"(ph) : "memory");
}
#define ELECT "{ .reg .pred e; elect.sync _|e, 0xffffffff; @e "
__device__ __forceinline__ void tma2d(uint32_t dst, const CUtensorMap* m, int c0, int c1, uint32_t bar) {
    asm volatile(ELECT "cp.async.bulk.tensor.2d.shared::cluster.global.mbarrier::complete_tx::bytes [%0], [%1, {%3, %4}], [%2]; }" ::"r"(dst), "l"(m), "r"(bar), "r"(c0), "r"(c1) : "memory");
}
__device__ __forceinline__ void tma3x(uint32_t dst, const CUtensorMap* m, int row, uint32_t bar) {
    asm volatile(ELECT "cp.async.bulk.tensor.3d.shared::cluster.global.mbarrier::complete_tx::bytes [%0], [%1, {0, %3, 0}], [%2]; }" ::"r"(dst), "l"(m), "r"(bar), "r"(row) : "memory");
}
template <int OFF>
__device__ __forceinline__ void ld_pkt(uint32_t* v, const uint4* p) {
    asm volatile("{ .reg .b128 t; ld.relaxed.gpu.global.b128 t, [%4+%5]; mov.b128 {%0,%1,%2,%3}, t; }" : "=r"(v[0]), "=r"(v[1]), "=r"(v[2]), "=r"(v[3]) : "l"(p), "n"(OFF * 16) : "memory");
}
template <int OFF>
__device__ __forceinline__ void st_pkt(uint4* p, uint32_t a, uint32_t b, uint32_t c, uint32_t d) {
    asm volatile("{ .reg .b128 t; mov.b128 t, {%1,%2,%3,%4}; st.relaxed.gpu.global.b128 [%0+%5], t; }" ::"l"(p), "r"(a), "r"(b), "r"(c), "r"(d), "n"(OFF * 16) : "memory");
}
__device__ __forceinline__ uint32_t pack2(float lo, float hi) {
    uint32_t r;
    asm("cvt.rn.bf16x2.f32 %0, %1, %2;" : "=r"(r) : "f"(hi), "f"(lo));
    return r;
}
__device__ __forceinline__ float bf_lo(uint32_t w) { return __uint_as_float(w << 16); }
__device__ __forceinline__ float bf_hi(uint32_t w) { return __uint_as_float(w & 0xffff0000u); }
__device__ __forceinline__ uint32_t settag(uint32_t w, uint32_t tag) { return (w & ~1u) | tag; }
__device__ __forceinline__ float ex2(float x) { float y; asm("ex2.approx.ftz.f32 %0, %1;" : "=f"(y) : "f"(x)); return y; }
__device__ __forceinline__ float rcp(float x) { float y; asm("rcp.approx.ftz.f32 %0, %1;" : "=f"(y) : "f"(x)); return y; }
__device__ __forceinline__ float tanh_hw(float x) { float y; asm("tanh.approx.f32 %0, %1;" : "=f"(y) : "f"(x)); return y; }
__device__ __forceinline__ void stsm4(uint32_t addr, uint32_t a, uint32_t b, uint32_t c, uint32_t d) {
    asm volatile("stmatrix.sync.aligned.m8n8.x4.shared.b16 [%0], {%1,%2,%3,%4};" ::"r"(addr), "r"(a), "r"(b), "r"(c), "r"(d) : "memory");
}
__device__ __forceinline__ void fence_async() { asm volatile("fence.proxy.async.shared::cta;" ::: "memory"); }
__device__ __forceinline__ void bar_sync(int id, int n) { asm volatile("bar.sync %0, %1;" ::"r"(id), "r"(n) : "memory"); }
__device__ __forceinline__ void bar_arrive(int id, int n) { asm volatile("bar.arrive %0, %1;" ::"r"(id), "r"(n) : "memory"); }
__device__ __forceinline__ void wg_fence() { asm volatile("wgmma.fence.sync.aligned;" ::: "memory"); }
__device__ __forceinline__ void wg_commit() { asm volatile("wgmma.commit_group.sync.aligned;" ::: "memory"); }
template <int N> __device__ __forceinline__ void wg_wait() { asm volatile("wgmma.wait_group.sync.aligned %0;" ::"n"(N) : "memory"); }

constexpr uint32_t SB0 = 1024;
__host__ __device__ constexpr uint32_t dlo(uint32_t off, uint32_t lbo) { return ((SB0 + off) >> 4) | ((lbo >> 4) << 16); }
__host__ __device__ constexpr uint32_t dhi(uint32_t sbo, uint32_t sw) { return (sbo >> 4) | (sw << 30); }
__device__ __forceinline__ uint64_t dbase(uint32_t lo, uint32_t hi) { uint64_t d; asm volatile("mov.b64 %0, {%1, %2};" : "=l"(d) : "r"(lo), "r"(hi)); return d; }
#define BASE128(off, lbo, adj) dbase(dlo(off, lbo) + (adj), dhi(1024, 1))
#define BASE64(off, lbo, adj) dbase(dlo(off, lbo) + (adj), dhi(512, 2))

#define ACC4(d, o) "+f"(d[o]), "+f"(d[o + 1]), "+f"(d[o + 2]), "+f"(d[o + 3])
#define ACC28(d) ACC4(d, 0), ACC4(d, 4), ACC4(d, 8), ACC4(d, 12), ACC4(d, 16), ACC4(d, 20), ACC4(d, 24)
#define ACC32(d, o) ACC4(d, o), ACC4(d, o + 4), ACC4(d, o + 8), ACC4(d, o + 12), ACC4(d, o + 16), ACC4(d, o + 20), ACC4(d, o + 24), ACC4(d, o + 28)

template <int TB, uint64_t D>
__device__ __forceinline__ void mma_rs56(float* d, uint32_t a0, uint32_t a1, uint32_t a2, uint32_t a3, int sd, uint64_t base) {
    asm volatile("{ .reg .pred p; .reg .b64 db; setp.ne.b32 p, %32, 0; add.u64 db, %33, %34;\n"
                 "wgmma.mma_async.sync.aligned.m64n56k16.f32.bf16.bf16 "
                 "{%0,%1,%2,%3,%4,%5,%6,%7,%8,%9,%10,%11,%12,%13,%14,%15,%16,%17,%18,%19,%20,%21,%22,%23,%24,%25,%26,%27}, "
                 "{%28,%29,%30,%31}, db, p, 1, 1, %35; }\n"
                 : ACC28(d)
                 : "r"(a0), "r"(a1), "r"(a2), "r"(a3), "r"(sd), "l"(base), "n"(D), "n"(TB));
}
template <int TB, uint64_t D>
__device__ __forceinline__ void mma_rs64(float* d, uint32_t a0, uint32_t a1, uint32_t a2, uint32_t a3, int sd, uint64_t base) {
    asm volatile("{ .reg .pred p; .reg .b64 db; setp.ne.b32 p, %36, 0; add.u64 db, %37, %38;\n"
                 "wgmma.mma_async.sync.aligned.m64n64k16.f32.bf16.bf16 "
                 "{%0,%1,%2,%3,%4,%5,%6,%7,%8,%9,%10,%11,%12,%13,%14,%15,%16,%17,%18,%19,%20,%21,%22,%23,%24,%25,%26,%27,%28,%29,%30,%31}, "
                 "{%32,%33,%34,%35}, db, p, 1, 1, %39; }\n"
                 : ACC32(d, 0)
                 : "r"(a0), "r"(a1), "r"(a2), "r"(a3), "r"(sd), "l"(base), "n"(D), "n"(TB));
}
template <int TB, uint64_t D>
__device__ __forceinline__ void mma_rs128(float* d, uint32_t a0, uint32_t a1, uint32_t a2, uint32_t a3, int sd, uint64_t base) {
    asm volatile("{ .reg .pred p; .reg .b64 db; setp.ne.b32 p, %68, 0; add.u64 db, %69, %70;\n"
                 "wgmma.mma_async.sync.aligned.m64n128k16.f32.bf16.bf16 "
                 "{%0,%1,%2,%3,%4,%5,%6,%7,%8,%9,%10,%11,%12,%13,%14,%15,%16,%17,%18,%19,%20,%21,%22,%23,%24,%25,%26,%27,%28,%29,%30,%31,%32,%33,%34,%35,%36,%37,%38,%39,%40,%41,%42,%43,%44,%45,%46,%47,%48,%49,%50,%51,%52,%53,%54,%55,%56,%57,%58,%59,%60,%61,%62,%63}, "
                 "{%64,%65,%66,%67}, db, p, 1, 1, %71; }\n"
                 : ACC32(d, 0), ACC32(d, 32)
                 : "r"(a0), "r"(a1), "r"(a2), "r"(a3), "r"(sd), "l"(base), "n"(D), "n"(TB));
}
template <uint64_t DA, uint64_t DB>
__device__ __forceinline__ void mma_ss56_tt(float* d, int sd, uint64_t ba, uint64_t bb) {
    asm volatile("{ .reg .pred p; .reg .b64 da, db; setp.ne.b32 p, %28, 0; add.u64 da, %29, %31; add.u64 db, %30, %32;\n"
                 "wgmma.mma_async.sync.aligned.m64n56k16.f32.bf16.bf16 "
                 "{%0,%1,%2,%3,%4,%5,%6,%7,%8,%9,%10,%11,%12,%13,%14,%15,%16,%17,%18,%19,%20,%21,%22,%23,%24,%25,%26,%27}, "
                 "da, db, p, 1, 1, 1, 1; }\n"
                 : ACC28(d)
                 : "r"(sd), "l"(ba), "l"(bb), "n"(DA), "n"(DB));
}
template <int... I> struct Seq {};
template <class F, int... I> __device__ __forceinline__ void static_for_impl(F&& f, Seq<I...>) { (f(std::integral_constant<int, I>{}), ...); }
#define FOR7(...) static_for_impl([&](auto T_) { constexpr int t = decltype(T_)::value; __VA_ARGS__; }, Seq<0, 1, 2, 3, 4, 5, 6>{})
#define FOR8(...) static_for_impl([&](auto T_) { constexpr int t = decltype(T_)::value; __VA_ARGS__; }, Seq<0, 1, 2, 3, 4, 5, 6, 7>{})
#define FOR14(...) static_for_impl([&](auto T_) { constexpr int t = decltype(T_)::value; __VA_ARGS__; }, Seq<0, 1, 2, 3, 4, 5, 6, 7, 8, 9, 10, 11, 12, 13>{})

__host__ __device__ constexpr int krow(int t) { return t < 3 ? 16 * t : (t < 6 ? 56 + 16 * (t - 3) : 48); }
#define AQ(A, b, t) ((t) < 3 ? A[2 * (b)][4 * (t)] : (t) < 6 ? A[2 * (b) + 1][4 * ((t) - 3)] : A[2 * (b)][12]), \
                    ((t) < 3 ? A[2 * (b)][4 * (t) + 1] : (t) < 6 ? A[2 * (b) + 1][4 * ((t) - 3) + 1] : A[2 * (b)][13]), \
                    ((t) < 3 ? A[2 * (b)][4 * (t) + 2] : (t) < 6 ? A[2 * (b) + 1][4 * ((t) - 3) + 2] : A[2 * (b) + 1][12]), \
                    ((t) < 3 ? A[2 * (b)][4 * (t) + 3] : (t) < 6 ? A[2 * (b) + 1][4 * ((t) - 3) + 3] : A[2 * (b) + 1][13])
#define D128(off, t) ((uint64_t)(((off) + krow(t) * 128) >> 4) + ((uint64_t)((t) == 6 ? (7168 - 1024) >> 4 : 0) << 32))
#define D64(off, t) ((uint64_t)(((off) + krow(t) * 64) >> 4) + ((uint64_t)((t) == 6 ? (3584 - 512) >> 4 : 0) << 32))

#define PL(k) (((k) - 3) * PLANE)
__device__ __forceinline__ void st_word(uint32_t* p, uint32_t v) { asm volatile("st.relaxed.gpu.global.u32 [%0], %1;" ::"l"(p), "r"(v) : "memory"); }
__device__ __forceinline__ uint32_t ld_word(const uint32_t* p) { uint32_t v; asm volatile("ld.relaxed.gpu.global.u32 %0, [%1];" : "=r"(v) : "l"(p) : "memory"); return v; }
template <int O>
__device__ __forceinline__ void send_slice(uint4* dst, int lane, const uint32_t* w, uint32_t tag) {
    st_pkt<O>(dst, settag(w[0], tag), w[1], w[2], w[3]);
    st_pkt<O + 32>(dst, settag(w[4], tag), w[5], w[6], w[7]);
    st_pkt<O + 64>(dst, settag(w[8], tag), w[9], w[10], w[11]);
    asm volatile("{ .reg .b64 t; mov.b64 t, {%1,%2}; st.relaxed.gpu.global.b64 [%0+%3], t; }" ::"l"((char*)dst - lane * 8), "r"(settag(w[12], tag)), "r"(w[13]), "n"(16 * (O + 96)) : "memory");
}
#define RW4(v, o) "+r"(v[o]), "+r"(v[(o) + 1]), "+r"(v[(o) + 2]), "+r"(v[(o) + 3])
#define RW2(v, o) "+r"(v[o]), "+r"(v[(o) + 1])
#define WR4(v, o) "=&r"(v[o]), "=&r"(v[(o) + 1]), "=&r"(v[(o) + 2]), "=&r"(v[(o) + 3])
#define LDP(a, b, c, d, addr, off) "ld.relaxed.gpu.global.b128 q, [" addr "+" off "];\n mov.b128 {" a "," b "," c "," d "}, q;\n"
#define LDH(a, b, addr, off) "ld.relaxed.gpu.global.b64 h, [" addr "+" off "];\n mov.b64 {" a "," b "}, h;\n"
#define VOTE_OK "and.b32 t, t, 1;\n setp.ne.u32 p, t, 0;\n vote.sync.any.pred p, p, 0xffffffff;\n @!p bra.uni DN;\n"
#define CHK(x, tag) "lop3.b32 t, " x ", " tag ", t, 0xBE;\n"
__device__ __forceinline__ void poll_cnt(const uint32_t* p, uint32_t target) {
    asm volatile("{ .reg .pred p; .reg .b32 n, t; mov.u32 n, 0;\n LP:\n"
                 "ld.relaxed.gpu.global.u32 t, [%0];\n sub.s32 t, t, %1;\n setp.lt.s32 p, t, 0;\n vote.sync.any.pred p, p, 0xffffffff;\n @!p bra.uni DN;\n" SPIN_TAIL("1")
                 ::"l"(p), "r"(target) : "memory");
}
template <int STR>
__device__ __forceinline__ void poll4_kv(uint32_t* v, const uint4* p, uint32_t tag) {
    asm volatile("{ .reg .pred p; .reg .b32 n, t; .reg .b128 q; mov.u32 n, 0;\n LP:\n"
                 LDP("%0", "%1", "%2", "%3", "%16", "0") LDP("%4", "%5", "%6", "%7", "%16", "%18")
                 LDP("%8", "%9", "%10", "%11", "%16", "%19") LDP("%12", "%13", "%14", "%15", "%16", "%20")
                 "xor.b32 t, %0, %17;\n" CHK("%4", "%17") CHK("%8", "%17") CHK("%12", "%17") VOTE_OK SPIN_TAIL("2")
                 : WR4(v, 0), WR4(v, 4), WR4(v, 8), WR4(v, 12)
                 : "l"(p), "r"(tag), "n"(16 * STR), "n"(32 * STR), "n"(48 * STR)
                 : "memory");
}
__device__ __forceinline__ void poll2_kv(uint32_t* v, const uint4* p, uint32_t tag) {
    asm volatile("{ .reg .pred p; .reg .b32 n, t; .reg .b128 q; mov.u32 n, 0;\n LP:\n"
                 LDP("%0", "%1", "%2", "%3", "%8", "0") LDP("%4", "%5", "%6", "%7", "%8", "128")
                 "xor.b32 t, %0, %9;\n" CHK("%4", "%9") VOTE_OK SPIN_TAIL("6")
                 : WR4(v, 0), WR4(v, 4) : "l"(p), "r"(tag) : "memory");
}
template <int B>
__device__ __forceinline__ void blk_load(uint32_t (&A)[8][14], const uint4* src, int lane) {
    ld_pkt<0>(&A[2 * B][0], src); ld_pkt<32>(&A[2 * B][4], src); ld_pkt<64>(&A[2 * B][8], src);
    ld_pkt<512>(&A[2 * B + 1][0], src); ld_pkt<544>(&A[2 * B + 1][4], src); ld_pkt<576>(&A[2 * B + 1][8], src);
    asm volatile("{ .reg .b64 h;\n" LDH("%0", "%1", "%4", "1536") LDH("%2", "%3", "%4", "9728") "}"
                 : "=&r"(A[2 * B][12]), "=&r"(A[2 * B][13]), "=&r"(A[2 * B + 1][12]), "=&r"(A[2 * B + 1][13])
                 : "l"((const char*)src - lane * 8) : "memory");
}
template <int B>
__device__ __forceinline__ void blk_check(uint32_t (&A)[8][14], const uint4* src, int lane, uint32_t tag) {
    asm volatile("{ .reg .pred p; .reg .b32 n, t; .reg .b128 q; .reg .b64 h, a8; mov.u32 n, 0;\n LP:\n"
                 "xor.b32 t, %0, %30;\n" CHK("%4", "%30") CHK("%8", "%30") CHK("%12", "%30") CHK("%16", "%30") CHK("%20", "%30") CHK("%24", "%30") CHK("%26", "%30") VOTE_OK
                 LDP("%0", "%1", "%2", "%3", "%28", "0") LDP("%4", "%5", "%6", "%7", "%28", "512") LDP("%8", "%9", "%10", "%11", "%28", "1024")
                 LDP("%12", "%13", "%14", "%15", "%28", "8192") LDP("%16", "%17", "%18", "%19", "%28", "8704") LDP("%20", "%21", "%22", "%23", "%28", "9216")
                 "mad.wide.s32 a8, %29, -8, %28;\n" LDH("%24", "%25", "a8", "1536") LDH("%26", "%27", "a8", "9728") SPIN_TAIL("3")
                 : RW4(A[2 * B], 0), RW4(A[2 * B], 4), RW4(A[2 * B], 8), RW4(A[2 * B + 1], 0), RW4(A[2 * B + 1], 4), RW4(A[2 * B + 1], 8),
                   RW2(A[2 * B], 12), RW2(A[2 * B + 1], 12)
                 : "l"(src), "r"(lane), "r"(tag)
                 : "memory");
}
__device__ __forceinline__ void st_async4(uint32_t a, uint32_t x, uint32_t y, uint32_t z, uint32_t w, uint32_t bar) {
    asm volatile("st.async.weak.shared::cluster.mbarrier::complete_tx::bytes.v4.b32 [%0], {%1,%2,%3,%4}, [%5];" ::"r"(a), "r"(x), "r"(y), "r"(z), "r"(w), "r"(bar) : "memory");
}
__device__ __forceinline__ uint32_t mapa(uint32_t a, uint32_t cta) { uint32_t r; asm("mapa.shared::cluster.u32 %0, %1, %2;" : "=r"(r) : "r"(a), "r"(cta)); return r; }
__device__ __forceinline__ void stat_poll(uint32_t* v, const uint4* p, uint32_t tag) {
    asm volatile("{ .reg .pred p; .reg .b32 n, t; .reg .b128 q; mov.u32 n, 0;\n LP:\n"
                 LDP("%0", "%1", "%2", "%3", "%8", "0") LDP("%4", "%5", "%6", "%7", "%8", "8192")
                 "xor.b32 t, %3, %9;\n" CHK("%7", "%9") VOTE_OK SPIN_TAIL("4")
                 : WR4(v, 0), WR4(v, 4) : "l"(p), "r"(tag) : "memory");
}
__device__ __forceinline__ uint32_t x_bits(const uint32_t* X) {
    uint32_t r;
    asm volatile("{ .reg .b32 a, b; prmt.b32 a, %1, %2, 0x0040; prmt.b32 b, %3, %4, 0x0040; prmt.b32 %0, a, b, 0x5410; }" : "=r"(r) : "r"(X[0]), "r"(X[4]), "r"(X[8]), "r"(X[12]));
    return r;
}
template <int O>
__device__ __forceinline__ void slice_load(uint32_t* v, const uint4* p, int lane) {
    ld_pkt<O>(v, p); ld_pkt<O + 32>(v + 4, p); ld_pkt<O + 64>(v + 8, p);
    asm volatile("{ .reg .b64 h;\n" LDH("%0", "%1", "%2", "%3") "}" : "=r"(v[12]), "=r"(v[13]) : "l"((const char*)p - lane * 8), "n"(16 * (O + 96)) : "memory");
}
template <int O>
__device__ __forceinline__ void slice_check(uint32_t* v, const uint4* p, int lane, uint32_t tag) {
    asm volatile("{ .reg .pred p; .reg .b32 n, t; .reg .b128 q; .reg .b64 h; mov.u32 n, 0;\n LP:\n"
                 "xor.b32 t, %0, %16;\n" CHK("%4", "%16") CHK("%8", "%16") CHK("%12", "%16") VOTE_OK
                 LDP("%0", "%1", "%2", "%3", "%14", "%17") LDP("%4", "%5", "%6", "%7", "%14", "%18") LDP("%8", "%9", "%10", "%11", "%14", "%19")
                 LDH("%12", "%13", "%15", "%20") SPIN_TAIL("5")
                 : RW4(v, 0), RW4(v, 4), RW4(v, 8), RW2(v, 12)
                 : "l"(p), "l"((const char*)p - lane * 8), "r"(tag), "n"(16 * O), "n"(16 * (O + 32)), "n"(16 * (O + 64)), "n"(16 * (O + 96))
                 : "memory");
}
__device__ __forceinline__ void x_fix(uint32_t* X, uint32_t bits) {
    X[0] = __byte_perm(X[0], bits, 0x3214); X[4] = __byte_perm(X[4], bits, 0x3215); X[8] = __byte_perm(X[8], bits, 0x3216); X[12] = __byte_perm(X[12], bits, 0x3217);
}
__device__ __forceinline__ void sts4(uint32_t a, uint32_t x, uint32_t y, uint32_t z, uint32_t w) {
    asm volatile("st.shared.v4.u32 [%0], {%1,%2,%3,%4};" ::"r"(a), "r"(x), "r"(y), "r"(z), "r"(w) : "memory");
}
__device__ __forceinline__ void lds4(uint32_t* v, uint32_t a) {
    asm volatile("ld.shared.v4.u32 {%0,%1,%2,%3}, [%4];" : "=r"(v[0]), "=r"(v[1]), "=r"(v[2]), "=r"(v[3]) : "r"(a) : "memory");
}
struct LnCoef { uint32_t hi, lo, sh; };
__device__ __forceinline__ LnCoef ln_coef(float sum, float sq) {
    sum += __shfl_xor_sync(0xffffffffu, sum, 1); sq += __shfl_xor_sync(0xffffffffu, sq, 1);
    sum += __shfl_xor_sync(0xffffffffu, sum, 2); sq += __shfl_xor_sync(0xffffffffu, sq, 2);
    const float mean = sum * (1.f / 448.f);
    const float var = fmaxf(fmaf(-mean, mean, sq * (1.f / 448.f)), 0.f);
    const float sc = rsqrtf(var + 1e-5f);
    LnCoef r;
    r.hi = pack2(sc, sc);
    const float lo = sc - bf_lo(r.hi), sh = -mean * sc;
    r.lo = pack2(lo, lo);
    r.sh = pack2(sh, sh);
    return r;
}
__device__ __forceinline__ uint32_t fma2(uint32_t a, uint32_t b, uint32_t c) {
    uint32_t d;
    asm("fma.rn.bf16x2 %0, %1, %2, %3;" : "=r"(d) : "r"(a), "r"(b), "r"(c));
    return d;
}
template <int B>
__device__ __forceinline__ void normalize(uint32_t (&A)[8][14], const LnCoef& c0, const LnCoef& c1) {
#pragma unroll
    for (int s = 2 * B; s < 2 * B + 2; s++)
#pragma unroll
        for (int i = 0; i < 14; i++) {
            const LnCoef& k = (i & 1) ? c1 : c0;
            A[s][i] = fma2(A[s][i], k.hi, fma2(A[s][i], k.lo, k.sh));
        }
}
template <int B, int Q>
__device__ __forceinline__ void normalize_part(uint32_t (&A)[8][14], const LnCoef& c0, const LnCoef& c1) {
#pragma unroll
    for (int k = 7 * Q; k < 7 * Q + 7; k++) {
        const LnCoef& c = (k & 1) ? c1 : c0;
        asm volatile("{ .reg .b32 t; fma.rn.bf16x2 t, %0, %2, %3; fma.rn.bf16x2 %0, %0, %1, t; }" : "+r"(A[2 * B + k / 14][k % 14]) : "r"(c.hi), "r"(c.lo), "r"(c.sh));
    }
}
__device__ __forceinline__ void slice_stats(const uint32_t* w, float* st) {
    float a = 0.f, b = 0.f, p = 0.f, q = 0.f;
#pragma unroll
    for (int i = 0; i < 7; i++) {
        const float e0 = bf_lo(w[2 * i]), e1 = bf_hi(w[2 * i]), e2 = bf_lo(w[2 * i + 1]), e3 = bf_hi(w[2 * i + 1]);
        a += e0 + e1; b += e2 + e3;
        p = fmaf(e0, e0, p); p = fmaf(e1, e1, p); q = fmaf(e2, e2, q); q = fmaf(e3, e3, q);
    }
    a += __shfl_xor_sync(0xffffffffu, a, 1); p += __shfl_xor_sync(0xffffffffu, p, 1); b += __shfl_xor_sync(0xffffffffu, b, 1); q += __shfl_xor_sync(0xffffffffu, q, 1);
    a += __shfl_xor_sync(0xffffffffu, a, 2); p += __shfl_xor_sync(0xffffffffu, p, 2); b += __shfl_xor_sync(0xffffffffu, b, 2); q += __shfl_xor_sync(0xffffffffu, q, 2);
    st[0] = a; st[1] = p; st[2] = b; st[3] = q;
}
__device__ __forceinline__ void dual_softmax(const float* p, uint32_t* out) {
    constexpr float L = 1.4426950408889634f;
#pragma unroll
    for (int r = 0; r < 2; r++) {
        float mx = fmaxf(p[2 * r], p[2 * r + 1]), mn = fminf(p[2 * r], p[2 * r + 1]);
#pragma unroll
        for (int i = 1; i < 7; i++) {
            mx = fmaxf(mx, fmaxf(p[4 * i + 2 * r], p[4 * i + 2 * r + 1]));
            mn = fminf(mn, fminf(p[4 * i + 2 * r], p[4 * i + 2 * r + 1]));
        }
        mx = fmaxf(mx, __shfl_xor_sync(0xffffffffu, mx, 1));
        mn = fminf(mn, __shfl_xor_sync(0xffffffffu, mn, 1));
        const float bx = -mx * L, bn = mn * L;
        float ep[14], en[14], sp = 0.f, sn = 0.f;
#pragma unroll
        for (int i = 0; i < 14; i++) {
            const float v = p[4 * (i >> 1) + 2 * r + (i & 1)];
            ep[i] = ex2(fmaf(v, L, bx));
            en[i] = ex2(fmaf(v, -L, bn));
            sp += ep[i]; sn += en[i];
        }
        sp += __shfl_xor_sync(0xffffffffu, sp, 1);
        sn += __shfl_xor_sync(0xffffffffu, sn, 1);
        const float ip = rcp(sp), in = rcp(sn);
#pragma unroll
        for (int i = 0; i < 7; i++) {
            out[4 * i + r] = pack2(ep[2 * i] * ip, ep[2 * i + 1] * ip);
            out[4 * i + 2 + r] = pack2(en[2 * i] * in, en[2 * i + 1] * in);
        }
    }
}
__device__ __forceinline__ float geglu(float g, float u) {
    const float t = tanh_hw(g * fmaf(g * g, 0.7978845608028654f * 0.044715f, 0.7978845608028654f));
    const float hu = 0.5f * g * u;
    return fmaf(t, hu, hu);
}
__device__ __forceinline__ void phi_gemm(const float* t, float* p) {
    uint32_t w[14];
#pragma unroll
    for (int i = 0; i < 14; i++) w[i] = pack2(t[2 * i], t[2 * i + 1]);
    const uint64_t db = BASE128(OFF_WPHI, 16, 0);
    wg_fence();
    mma_rs56<0, 0>(p, w[0], w[1], w[2], w[3], 0, db);
    mma_rs56<0, 2>(p, w[4], w[5], w[6], w[7], 1, db);
    mma_rs56<0, 4>(p, w[8], w[9], w[10], w[11], 1, db);
    mma_rs56<0, 6>(p, w[12], w[13], 0u, 0u, 1, db);
    wg_commit();
    wg_wait<0>();
}

}

#define BAR(i) (bars + 8 * (i))
#define R_WAIT() mbar_wait(BAR(slot), ph)
#define WSUM(i)
#define R_ADJ (slot * (STAGE >> 4))
#define R_NEXT() do { eb2 = eb1; eb1 = BAR(B_EMPTY + slot); if (++slot == NST) { slot = 0; ph ^= 1; } } while (0)
#define R_RELEASE(k) do { if (lane == 0) mbar_arrive((k) == 1 ? eb1 : eb2); } while (0)
#define PUSH_BEGIN() do { mbar_wait(BAR(B_ACK + wgi), ackph); ackph ^= 1; } while (0)
#define PUSH_ACK() do { __syncwarp(); if (lane == 0) asm volatile("mbarrier.arrive.shared::cluster.b64 _, [%0];" ::"r"(mapa(BAR(B_ACK + wgi), hr ^ 1)) : "memory"); } while (0)

__global__ void __cluster_dims__(2, 1, 1) __launch_bounds__(384, 1)
fused_kernel(const __grid_constant__ Maps maps, const __nv_bfloat16* __restrict__ x_in, const __nv_bfloat16* __restrict__ w_phi,
             const __nv_bfloat16* __restrict__ wg, const __nv_bfloat16* __restrict__ wu, const __nv_bfloat16* __restrict__ wd) {
    extern __shared__ __align__(1024) unsigned char smem_raw[];
    const uint32_t sb = s2u(smem_raw);
    const uint32_t bars = sb + OFF_BAR;
    const int wgi = __shfl_sync(0xffffffffu, threadIdx.x >> 7, 0);
    const int hr = blockIdx.x & 1, role = maps.role[blockIdx.x >> 1];
    const int tile = role >> 2, pr = role & 3;
    const int sl = 2 * pr + hr;
    STAMP(0);
    GSTAMP(60);
    uint32_t X[14];
    if (wgi < 2) {
        const int row0 = tile * 128 + (threadIdx.x >> 5) * 16 + ((threadIdx.x & 31) >> 2);
        const uint32_t* xp = reinterpret_cast<const uint32_t*>(x_in + (size_t)row0 * 448 + 56 * sl + 2 * (threadIdx.x & 3));
#pragma unroll
        for (int i = 0; i < 7; i++) { X[2 * i] = __ldg(xp + 4 * i); X[2 * i + 1] = __ldg(xp + 4 * i + 8 * 224); }
    }
    if (threadIdx.x == 256) {
        if ((sb & 0x3FFFF) != SB0) asm volatile("trap;");
        asm volatile("prefetch.tensormap [%0];" ::"l"(&maps.x) : "memory");
        asm volatile("prefetch.tensormap [%0];" ::"l"(&maps.qkv) : "memory");
        for (int i = 0; i < B_COUNT; i++) mbar_init(BAR(i), i >= B_ACK ? 4 : (i >= B_EMPTY && i < B_RECV ? 8 : 1));
        asm volatile("fence.mbarrier_init.release.cluster;" ::: "memory");
    }
    __syncthreads();
    asm volatile("barrier.cluster.arrive.relaxed.aligned;" ::: "memory");

    if (wgi == 2) {
        asm volatile("setmaxnreg.dec.sync.aligned.u32 40;");
        const int t128 = fresh_tid() & 127, w = __shfl_sync(0xffffffffu, t128 >> 5, 0), lane = t128 & 31;
        uint32_t kseq = 0;
        auto kv_job = [&](int layer) {
            const uint32_t tag = layer ^ 1;
            kseq++;
            bar_sync(7, 384);
            ASTAMP(0);
            if (tile < 15) {
                const int sq = lane >> 3, pk = 8 * w + (lane & (tile == 14 ? 3 : 7));
                uint32_t v[16];
                poll_cnt(g_c1 + ((sl * 8 + (w >> 1) * 4 + (tile >> 2)) * 16 + (lane & 15)) * 32, kseq);
                ASTAMP(1);
                poll4_kv<32>(v, g_kv1 + ((sl * 16 + tile) * 16 + 4 * sq) * 32 + pk, tag);
#pragma unroll
                for (int k = 0; k < 4; k++) {
                    float lo = (bf_lo(v[k]) + bf_lo(v[4 + k])) + (bf_lo(v[8 + k]) + bf_lo(v[12 + k]));
                    float hi = (bf_hi(v[k]) + bf_hi(v[4 + k])) + (bf_hi(v[8 + k]) + bf_hi(v[12 + k]));
                    lo += __shfl_xor_sync(0xffffffffu, lo, 8); hi += __shfl_xor_sync(0xffffffffu, hi, 8);
                    lo += __shfl_xor_sync(0xffffffffu, lo, 16); hi += __shfl_xor_sync(0xffffffffu, hi, 16);
                    v[k] = pack2(lo, hi);
                }
                if (sq == 0) st_pkt<0>(g_kv2 + sl * 512 + 32 * tile + pk, settag(v[0], tag), v[1], v[2], v[3]);
            }
            if (lane == 0) st_word(g_c2 + ((sl * 4 + w) * 16 + tile) * 32, kseq);
            ASTAMP(2);
            poll_cnt(g_c2 + ((sl * 4 + w) * 16 + (lane & 15)) * 32, kseq);
            bar_arrive(3, 384);
            ASTAMP(3);
        };
        if (w == 0) {
#pragma unroll 1
            for (int n = 0; n < NST; n++) {
                const uint32_t dst = sb + n * STAGE, fb = BAR(n);
                asm volatile(ELECT "mbarrier.arrive.expect_tx.shared::cta.b64 _, [%0], %1; }" ::"r"(fb), "r"(n < 2 ? 2 * STAGE : STAGE) : "memory");
                if (n < 2) {
                    tma3x(sb + OFF_H + n * STAGE, &maps.x, tile * 128 + n * 64, fb);
                    tma3x(dst, &maps.x, tile * 128 + n * 64 + 32, fb);
                } else {
                    const int ra = 112 * (n - 2);
                    tma2d(dst, &maps.qkv, 448 + 56 * sl, ra, fb);
                    tma2d(dst + HALF, &maps.qkv, 896 + 56 * sl, ra, fb);
                }
            }
            const uint32_t cw_target = (ld_word(g_cw + sl * 32) & ~15u) + 16;
            uint32_t e0[2], e1[2];
#pragma unroll
            for (int k = 0; k < 2; k++) {
                const int n = t128 + 32 * k;
                int m = n - 2 - (n > PACK);
                const bool packed = m >= 30 ? (m < 38 || m >= 52) : m >= 22;
                if (m >= 30) m -= 30;
                if (n == PACK) m = tile < 8 ? tile : tile + 14;
                const int rot = n < 8 ? 0 : pr;
                const int ra = 112 * ((rot + m) & 3), rb = 112 * ((rot + 2 * m) & 3), rc = 112 * ((rot + 2 * m + 1) & 3);
                int kind = 0, m0, m1, c0, c1, r0, r1;
                if (m < 4) { m0 = m1 = 1; c0 = 448 + 56 * sl; c1 = c0 + 448; r0 = r1 = ra; }
                else if (m < 8) { m0 = m1 = m < 6 ? 1 : 2; c0 = c1 = 56 * sl; r0 = rb; r1 = rc; }
                else if (m < 20) { m0 = 3; m1 = 4; c0 = c1 = 224 * sl + 32 * hr + 64 * ((m - 8) >> 2); r0 = r1 = ra; }
                else if (m < 22) { kind = 2; m0 = 5; m1 = 6; c0 = c1 = 224 * sl + (hr ? 0 : 192); r0 = rb; r1 = rc; }
                else { m0 = m1 = 7; c0 = c1 = 56 * (2 * ((pr + (m >> 1) - 10) & 3) + hr); r0 = 224 * (sl ^ (m & 1)); r1 = r0 + 112; }
                if (packed) { kind = 1; r0 = sl * 16 + (m < 8 ? m : m - 14); r1 = 0; }
                e0[k] = kind | (m0 << 2) | (m1 << 6) | (c0 << 10) | (c1 << 21);
                e1[k] = r0 | (r1 << 16);
            }
            kseq = ld_word(g_c2 + (sl * 64 + tile) * 32);
            int slot = 0, ph = 0;
#pragma unroll 1
            for (int n = NST; n < 63; n++) {
                if (n == 11 || n == 42) kv_job(n == 42);
                const uint32_t w0 = __shfl_sync(0xffffffffu, n < 32 ? e0[0] : e0[1], n & 31), w1 = __shfl_sync(0xffffffffu, n < 32 ? e1[0] : e1[1], n & 31);
                const uint32_t dst = sb + slot * STAGE, fb = BAR(n == PACK ? B_PACK : slot);
                const CUtensorMap* m0 = &maps.x + ((w0 >> 2) & 15);
                const CUtensorMap* m1 = &maps.x + ((w0 >> 6) & 15);
                const int c0 = (w0 >> 10) & 2047, c1 = w0 >> 21, r0 = w1 & 0xffff, r1 = w1 >> 16;
                if (n == 25) {
                    int it = 0;
                    uint32_t v;
                    do { asm volatile("ld.acquire.gpu.global.u32 %0, [%1];" : "=r"(v) : "l"(g_cw + sl * 32) : "memory"); } while ((int)(v - cw_target) < 0 && ++it < 0x400000);
                    asm volatile("fence.proxy.async.global;" ::: "memory");
                    __syncwarp();
                }
                mbar_wait(BAR(B_EMPTY + slot), ph);
                __syncwarp();
                asm volatile(ELECT "mbarrier.arrive.expect_tx.shared::cta.b64 _, [%0], %1; }" ::"r"(fb), "r"(STAGE) : "memory");
                if ((w0 & 3) == 0) {
                    tma2d(dst, m0, c0, r0, fb);
                    tma2d(dst + HALF, m1, c1, r1, fb);
                } else if (w0 & 1) {
                    asm volatile(ELECT "cp.async.bulk.shared::cluster.global.mbarrier::complete_tx::bytes [%0], [%1], %2, [%3]; }"
                                 ::"r"(dst), "l"(reinterpret_cast<const char*>(g_wp) + (size_t)r0 * STAGE), "r"(STAGE), "r"(fb) : "memory");
                } else {
                    tma2d(dst, m0, c0, r0, fb); tma2d(dst + 7168, m0, c0, r1, fb);
                    tma2d(dst + HALF, m1, c0, r0, fb); tma2d(dst + HALF + 7168, m1, c0, r1, fb);
                }
                if (n == PACK) asm volatile(ELECT "mbarrier.arrive.shared::cta.b64 _, [%0]; }" ::"r"(BAR(slot)) : "memory");
                if (++slot == NST) { slot = 0; ph ^= 1; }
            }
        } else {
            const int j = t128 - 32;
            uint2 wv[7];
            const int k = j < 56 ? j : 55, hh = k >= 28;
#pragma unroll
            for (int i = 0; i < 7; i++) wv[i] = __ldg(reinterpret_cast<const uint2*>(w_phi + (sl * 56 + k) * 28) + i);
#pragma unroll 1
            for (int i = j; i < 7168 / 16; i += 96) sts4(sb + OFF_WPHI + i * 16, 0, 0, 0, 0);
            bar_sync(5, 96);
            if (j < 56) {
                uint32_t a4[4];
#pragma unroll
                for (int q = 0; q < 4; q++) a4[q] = sb + OFF_WPHI + (4 * hh + q) * 128 + ((((k >> 3) ^ (4 * hh + q)) & 7) << 4) + (k & 7) * 2;
                FOR14(const uint32_t v = (t & 1) ? wv[t >> 1].y : wv[t >> 1].x;
                      asm volatile("{ .reg .b16 l, h; mov.b32 {l, h}, %2; st.shared.u16 [%0+%3], l; st.shared.u16 [%1+%3], h; }"
                                   ::"r"(a4[t >= 7 ? 2 : 0]), "r"(a4[t >= 7 ? 3 : 1]), "r"(v), "n"((t % 7) * 1024) : "memory"));
            }
            __syncwarp();
            fence_async();
            bar_arrive(1, 352);
            if (j == 0) {
                mbar_wait(BAR(2), 0);
                const int b = blockIdx.x;
                asm volatile("cp.async.bulk.prefetch.L2.global [%0], %1;" ::"l"(wg + b * 6272), "r"(12544) : "memory");
                asm volatile("cp.async.bulk.prefetch.L2.global [%0], %1;" ::"l"(wu + b * 6272), "r"(12544) : "memory");
                asm volatile("cp.async.bulk.prefetch.L2.global [%0], %1;" ::"l"(wd + b * 6272), "r"(12544) : "memory");
            }
            __syncwarp();
            kseq = ld_word(g_c2 + ((sl * 4 + w) * 16 + tile) * 32);
#pragma unroll 1
            for (int layer = 0; layer < 2; layer++) {
                kv_job(layer);
                if (layer == 0 && j == 0) {
                    constexpr int ps = PACK % NST;
                    mbar_wait(BAR(B_PACK), 0);
                    asm volatile("cp.async.bulk.global.shared::cta.bulk_group [%0], [%1], %2;"
                                 ::"l"(reinterpret_cast<char*>(g_wp) + (size_t)(sl * 16 + tile) * STAGE), "r"(sb + ps * STAGE), "r"(STAGE) : "memory");
                    asm volatile("cp.async.bulk.commit_group;" ::: "memory");
                    asm volatile("cp.async.bulk.wait_group.read 0;" ::: "memory");
                    asm volatile("mbarrier.arrive.shared::cta.b64 _, [%0], 8;" ::"r"(BAR(B_EMPTY + ps)) : "memory");
                    asm volatile("cp.async.bulk.wait_group 0;" ::: "memory");
                    asm volatile("fence.proxy.async.global;" ::: "memory");
                    asm volatile("red.release.gpu.global.add.u32 [%0], 1;" ::"l"(g_cw + sl * 32) : "memory");
                }
                __syncwarp();
            }
        }
        __syncwarp();
        asm volatile("barrier.cluster.wait.aligned;" ::: "memory");
    } else {
        asm volatile("setmaxnreg.inc.sync.aligned.u32 232;");
        const int tid = fresh_tid(), lane = tid & 31, t128 = tid & 127, w = t128 >> 5, g = lane >> 2, c = lane & 3;
        uint4* const xp0 = g_ex + 3 * PLANE + ((tile * 2 + wgi) * 8) * 512 + w * 128 + lane;
        const uint32_t hbuf = sb + OFF_H + wgi * STAGE;
        uint32_t slot = 0, ph = 0, eb1 = 0, eb2 = 0, ackph = 0, rcvph = 0;
        uint32_t ppid = 6;
#define cx(s) (reinterpret_cast<uint32_t*>(again(xp0) - lane + PL(1) + 112 + (s) * 512))
#define stp (again(xp0) - lane + g + PL(0) + 112)
        uint32_t seq = ld_word(cx(sl));
        uint32_t kseq = ld_word(g_c1 + ((sl * 8 + (tid >> 5)) * 16 + tile) * 32);
        uint32_t stag = ld_word(reinterpret_cast<const uint32_t*>(stp + sl * 512) + 3) & 1;
        asm volatile("barrier.cluster.wait.aligned;" ::: "memory");
        STAMP(1);
#define PUSH_SLICE(W)                                                                          \
    {                                                                                          \
        if (t128 == 0) mbar_expect_tx(BAR(B_RECV + wgi), 7168);                                \
        PUSH_BEGIN();                                                                          \
        const uint32_t ra = mapa(hbuf + 24576 + t128 * 16, hr ^ 1), rb = mapa(sb + OFF_XR + wgi * 3072, hr ^ 1), rbar = mapa(BAR(B_RECV + wgi), hr ^ 1); \
        st_async4(ra, W[0], W[1], W[2], W[3], rbar);                                           \
        st_async4(ra + 2048, W[4], W[5], W[6], W[7], rbar);                                    \
        st_async4(rb + t128 * 16, W[8], W[9], W[10], W[11], rbar);                             \
        asm volatile("st.async.weak.shared::cluster.mbarrier::complete_tx::bytes.v2.b32 [%0], {%1,%2}, [%3];" ::"r"(rb + 2048 + t128 * 8), "r"(W[12]), "r"(W[13]), "r"(rbar) : "memory"); \
    }
#define PULL_SLICE(W)                                                                          \
    {                                                                                          \
        uint32_t T[14];                                                                        \
        mbar_wait(BAR(B_RECV + wgi), rcvph);                                           \
        rcvph ^= 1;                                                                            \
        lds4(T, hbuf + 24576 + t128 * 16);                                                     \
        lds4(T + 4, hbuf + 26624 + t128 * 16);                                                 \
        lds4(T + 8, sb + OFF_XR + wgi * 3072 + t128 * 16);                                     \
        asm volatile("ld.shared.v2.u32 {%0,%1}, [%2];" : "=r"(T[12]), "=r"(T[13]) : "r"(sb + OFF_XR + wgi * 3072 + 2048 + t128 * 8) : "memory"); \
        _Pragma("unroll") for (int i = 0; i < 14; i++) { A[0][i] = hr ? T[i] : W[i]; A[1][i] = hr ? W[i] : T[i]; } \
        asm volatile("" : RW4(A[0], 0), RW4(A[0], 4), RW4(A[0], 8), RW2(A[0], 12), RW4(A[1], 0), RW4(A[1], 4), RW4(A[1], 8), RW2(A[1], 12)); \
        PUSH_ACK();                                                                            \
    }
#define EARLY 1
#define EARLYK 1
#define PPB 2
#define PP_WAIT() if (wgi == 1) { bar_sync(ppid, 256); ppid ^= 14; }
#define PP_GO() if (wgi == 0) { bar_arrive(ppid, 256); ppid ^= 14; }
#define PREP(b, t, remote)                                                                     \
    if constexpr ((b) < 2 && (t) == 0) { if (remote) blk_load<((b) + 2) & 3>(A, BLK(xsrc, (b) + 2), lane); } \
    if constexpr ((b) < 3 && (t) == 1) { if (remote) blk_check<((b) + 1) & 3>(A, BLK(xsrc, (b) + 1), lane, tag); } \
    if constexpr ((b) < 3 && (t) >= 2 && (t) < 6) normalize_part<((b) + 1) & 3, ((t) - 2) & 3>(A, k0, k1);
#define BLK(base, b) ((base) + ((pr + (b)) & 3) * 1024)

#pragma unroll 1
        for (int step = 0; step < 4; step++) {
            const uint32_t tag = (step >> 1) ^ 1;
            const int so = (step >> 1) * 24 + (step & 1) * 12;
            (void)so;
            uint32_t A[8][14];
            uint4* const xsrc = xp0 + ((step & 1) ? PL(2) : PL(0));
            {
                float st[4];
                slice_stats(X, st);
                stag ^= 1;
                if (step) send_slice<0>(xsrc + sl * 512, lane, X, tag);
                if (c == 0) st_pkt<0>(stp + sl * 512, __float_as_uint(st[0]), __float_as_uint(st[1]), __float_as_uint(st[2]), settag(__float_as_uint(st[3]), stag));
            }
            const uint32_t xbits = x_bits(X);
            STAMP(2 + so);
            uint32_t sv[8];
            if (step == 0) {
                send_slice<0>(xsrc + sl * 512, lane, X, tag);
                mbar_wait(BAR(wgi), 0);
                const int m = lane >> 3, rr = lane & 7;
                const uint32_t rowa = (w < 2 ? hbuf : sb + wgi * STAGE) + ((w & 1) * 16 + rr + 8 * (m & 1)) * 128;
                const int hi = m >> 1;
                uint32_t xr[8];
#pragma unroll
                for (int j = 0; j < 8; j++) xr[j] = rowa + ((((j + hi) ^ rr) & 7) << 4) + (j == 7 ? hi * 4096 : 0);
#define X0_BLOCK(b)                                                                            \
    FOR7(constexpr int G = 14 * (b) + (t < 3 ? 2 * t : (t < 6 ? 2 * t + 1 : 6));               \
         uint32_t q0, q1, q2, q3;                                                              \
         const uint32_t ad = t < 6 ? xr[G & 7] : rowa + ((G + 7 * hi) >> 3) * 4096 + ((((G + 7 * hi) ^ rr) & 7) << 4); \
         asm volatile("ldmatrix.sync.aligned.m8n8.x4.shared.b16 {%0,%1,%2,%3}, [%4+%5];" : "=r"(q0), "=r"(q1), "=r"(q2), "=r"(q3) \
                      : "r"(ad), "n"(t < 6 ? (G >> 3) * 4096 : 0) : "memory");                 \
         if (t < 3) { A[2 * (b)][4 * t] = q0; A[2 * (b)][4 * t + 1] = q1; A[2 * (b)][4 * t + 2] = q2; A[2 * (b)][4 * t + 3] = q3; } \
         else if (t < 6) { A[2 * (b) + 1][(4 * t - 12) & 15] = q0; A[2 * (b) + 1][((4 * t - 12) & 15) + 1] = q1; A[2 * (b) + 1][((4 * t - 12) & 15) + 2] = q2; A[2 * (b) + 1][((4 * t - 12) & 15) + 3] = q3; } \
         else { A[2 * (b)][12] = q0; A[2 * (b)][13] = q1; A[2 * (b) + 1][12] = q2; A[2 * (b) + 1][13] = q3; });
                X0_BLOCK(0) X0_BLOCK(1) X0_BLOCK(2) X0_BLOCK(3)
                PUSH_ACK();
                mbar_wait(BAR(wgi ^ 1), 0);
                R_NEXT();
                R_NEXT();
                stat_poll(sv, stp + c * 1024, stag);
                STAMP(52 + step);
            } else {
                PUSH_SLICE(X)
                kill<14>(A[4]); kill<14>(A[5]); kill<14>(A[6]); kill<14>(A[7]);
                stat_poll(sv, stp + c * 1024, stag);
                STAMP(52 + step);
                blk_load<1>(A, BLK(xsrc, 1), lane);
                PULL_SLICE(X)
            }
            LnCoef k0, k1;
            {
                k0 = ln_coef(__uint_as_float(sv[0]) + __uint_as_float(sv[4]), __uint_as_float(sv[1]) + __uint_as_float(sv[5]));
                k1 = ln_coef(__uint_as_float(sv[2]) + __uint_as_float(sv[6]), __uint_as_float(sv[3]) + __uint_as_float(sv[7]));
            }
            STAMP(3 + so);

            if ((step & 1) == 0) {
                float tq[28];
                {
                    float av[28];
#define KV_BLOCK(b)                                                                           \
    R_WAIT();                                                                                 \
    { const uint64_t db = BASE128(0, 16, R_ADJ);                                              \
    wg_fence();                                                                               \
    FOR7(mma_rs56<1, D128(0, t)>(tq, AQ(A, b, t), (b) + t > 0, db);                           \
         mma_rs56<1, D128(HALF, t)>(av, AQ(A, b, t), (b) + t > 0, db);                        \
         PREP(b, t, step)); }                                                                 \
    wg_commit();                                                                              \
    R_NEXT();
                    if (EARLYK == 0 || step == 0) R_RELEASE(2);
                    normalize<0>(A, k0, k1);
                    KV_BLOCK(0) KV_BLOCK(1) KV_BLOCK(2) KV_BLOCK(3)
                    wg_wait<0>();
                    if (lane < NST) mbar_arrive(BAR(B_EMPTY + lane));
                    STAMP(4 + so);
                    WSUM(80 + 7 * (step >> 1));
                    const int m = lane >> 3, rr = lane & 7;
                    const uint32_t rowa = hbuf + 16384 + (w * 16 + rr + 8 * (m & 1)) * 128;
                    const uint32_t one = c == 0 ? 0x00003f80u : 0u;
                    if (step == 0) { bar_sync(1, 352); }
#pragma unroll
                    for (int j = 0; j < 4; j++) {
                        const uint32_t a = rowa + (((2 * j + (m >> 1)) ^ rr) << 4);
                        if (j < 3) stsm4(a, pack2(av[8 * j], av[8 * j + 1]), pack2(av[8 * j + 2], av[8 * j + 3]), pack2(av[8 * j + 4], av[8 * j + 5]), pack2(av[8 * j + 6], av[8 * j + 7]));
                        else stsm4(a, pack2(av[24], av[25]), pack2(av[26], av[27]), one, one);
                    }
                }
                uint32_t PH[28];
                int it = 1;
#pragma unroll 1
                do {
                    float pp[28];
                    phi_gemm(tq, pp);
                    dual_softmax(pp, PH);
                    if (maps.flag[it + 1] == 0) continue;
                    {
                        const int m = lane >> 3, rr = lane & 7;
                        const uint32_t rowa = hbuf + (w * 16 + rr + 8 * (m & 1)) * 128;
#pragma unroll
                        for (int j = 0; j < 7; j++) {
                            const int cg = 2 * j + (m >> 1), hi = cg >= 7;
                            stsm4(rowa + hi * 8192 + (((cg - 7 * hi) ^ rr) << 4), PH[4 * j], PH[4 * j + 1], PH[4 * j + 2], PH[4 * j + 3]);
                        }
                    }
                    fence_async();
                    STAMP(5 + so);
                    bar_sync(2, 256);
                    kill<28>(tq);
                    const uint64_t da = BASE128(OFF_H + 16384, 16, 0), dbk = BASE128(OFF_H, 16, wgi * 512);
                    wg_fence();
                    FOR8(constexpr uint64_t o = ((t >> 2) * STAGE + (t & 3) * 2048) >> 4; mma_ss56_tt<o, o>(tq, t > 0, da, dbk));
                    wg_commit();
                    wg_wait<0>();
#pragma unroll
                    for (int hf = 0; hf < 2; hf++) {
                        const int d = 16 * w + g + 8 * hf;
                        if ((d < 56 && (d >= 28) == (c >= 2)) || d == 56) {
                            const int item = d < 56 ? 2 * d + (c & 1) : 112 + c;
                            uint4* dst = g_kv1 + ((sl * 16 + (item >> 3)) * 16 + tile) * 32 + wgi * 16 + (item & 7);
#define KVW(i) pack2(tq[4 * (i) + 2 * hf], tq[4 * (i) + 2 * hf + 1])
                            st_pkt<0>(dst, settag(KVW(0), tag), KVW(1), KVW(2), KVW(3));
                            st_pkt<8>(dst, settag(KVW(4), tag), KVW(5), KVW(6), 0u);
                        }
                    }
                    __syncwarp();
                    kseq++;
                    if (lane == 0) st_word(g_c1 + ((sl * 8 + (tid >> 5)) * 16 + tile) * 32, kseq);
                    bar_arrive(7, 384);
                    STAMP(6 + so);
#define Q_STAGE(b0)                                                                           \
    R_WAIT();                                                                                 \
    { const uint64_t db = BASE128(0, 16, R_ADJ);                                              \
    wg_fence();                                                                               \
    FOR7(mma_rs56<1, D128(0, t)>(tq, AQ(A, b0, t), (b0) + t > 0, db));                        \
    FOR7(mma_rs56<1, D128(HALF, t)>(tq, AQ(A, (b0) + 1, t), 1, db)); }                        \
    wg_commit();                                                                              \
    R_NEXT();
                    kill<28>(tq);
                    Q_STAGE(0)
                    Q_STAGE(2)
                    wg_wait<1>();
                    R_RELEASE(2);
                    wg_wait<0>();
                    R_RELEASE(1);
                    STAMP(7 + so);
                    kill<28>(PH);
                } while (maps.flag[++it]);
                STAMP(8 + so);
                {
                    const int item = t128 < 112 ? t128 : 112 + (t128 & 3), d = item >> 1;
                    const int cc = t128 < 112 ? 2 * (d >= 28) + (item & 1) : item - 112;
                    const int r = t128 < 112 ? d : 56 + (cc >> 1) + 2 * ((t128 - 112) >> 2);
                    const uint32_t ra = sb + OFF_KVB + r * 128 + 4 * cc;
#pragma unroll
                    for (int i = 0; i < 7; i++) {
                        const int ii = i + 7 * wgi;
                        asm volatile("st.shared.u32 [%0], %1;" ::"r"((ra ^ 8) + (ii >> 3) * 8192 + (((ii ^ r) & 7) << 4)), "r"(0) : "memory");
                    }
                    uint32_t v[8];
                    bar_sync(3, 384);
                    poll2_kv(v, g_kv2 + sl * 512 + (item >> 3) * 32 + wgi * 16 + (item & 7), tag);
#pragma unroll
                    for (int i = 0; i < 7; i++) {
                        const int ii = i + 7 * wgi;
                        asm volatile("st.shared.u32 [%0], %1;" ::"r"(ra + (ii >> 3) * 8192 + (((ii ^ r) & 7) << 4)), "r"(v[i]) : "memory");
                    }
                    fence_async();
                    bar_sync(4, 256);
                }
                STAMP(9 + so);
                {
                    float nm[32];
                    const uint64_t db = BASE128(OFF_KVB, 16, 0);
                    wg_fence();
                    FOR7(mma_rs64<0, ((t >> 2) * 8192 + (t & 3) * 32) / 16>(nm, PH[4 * t], PH[4 * t + 1], PH[4 * t + 2], PH[4 * t + 3], t > 0, db));
                    wg_commit();
                    wg_wait<0>();
                    const float i00 = rcp(nm[28] + 1e-6f), i01 = rcp(nm[29] + 1e-6f), i10 = rcp(nm[30] + 1e-6f), i11 = rcp(nm[31] + 1e-6f);
                    const float m0 = c >= 2 ? i01 : i00, m1 = c >= 2 ? i11 : i10;
                    uint32_t O[14];
#pragma unroll
                    for (int i = 0; i < 7; i++) {
                        const float f0 = i < 3 ? i00 : (i > 3 ? i01 : m0), f1 = i < 3 ? i10 : (i > 3 ? i11 : m1);
                        O[2 * i] = pack2(nm[4 * i] * f0, nm[4 * i + 1] * f0);
                        O[2 * i + 1] = pack2(nm[4 * i + 2] * f1, nm[4 * i + 3] * f1);
                    }
                    send_slice<PL(1)>(xp0 + sl * 512, lane, O, tag);
                    seq++;
                    if (lane == 0) st_word(cx(sl), seq);
                    STAMP(10 + so);
                    PUSH_SLICE(O)
                    PULL_SLICE(O)
                }
                float ao[28];
                const uint4* const osrc = xp0 + PL(1);
#define WO_BLOCK(b)                                                                           \
    if ((b) > 0) blk_check<b>(A, BLK(osrc, b), lane, tag);                                    \
    if (((b) & 1) == 0) R_WAIT();                                                             \
    { const uint64_t db = BASE128(0, 16, R_ADJ);                                              \
    wg_fence();                                                                               \
    FOR7(mma_rs56<1, D128(((b) & 1) * HALF, t)>(ao, AQ(A, b, t), (b) + t > 0, db)); }         \
    wg_commit();                                                                              \
    if ((b) & 1) R_NEXT();
                WO_BLOCK(0)
                poll_cnt(cx(lane & 7), seq);
                STAMP(56 + (step >> 1));
                blk_load<1>(A, BLK(osrc, 1), lane);
                blk_load<2>(A, BLK(osrc, 2), lane);
                STAMP(11 + so);
                blk_load<3>(A, BLK(osrc, 3), lane);
                WO_BLOCK(1)
                slice_load<PL(0)>(X, xp0 + sl * 512, lane);
                WO_BLOCK(2)
                WO_BLOCK(3)
                wg_wait<0>();
                if (EARLY >= 1) R_RELEASE(2);
                if (EARLY >= 2) R_RELEASE(1);
                STAMP(12 + so);
                WSUM(86 + 7 * (step >> 1));
                x_fix(X, xbits);
#pragma unroll
                for (int i = 0; i < 14; i++) X[i] = pack2(bf_lo(X[i]) + ao[2 * i], bf_hi(X[i]) + ao[2 * i + 1]);
            } else {
                uint32_t H[56];
                float ag[64];
#define F1_EPI(dst, ng, ag)                                                                    \
    _Pragma("unroll") for (int i = 0; i < 2 * (ng); i++)                                       \
        (dst)[i] = pack2(geglu(ag[2 * i], ag[4 * (ng) + 2 * i]), geglu(ag[2 * i + 1], ag[4 * (ng) + 2 * i + 1]));
#define H_PUSH(h0, off) st_async4(rem_h + (off), H[h0], H[(h0) + 1], H[(h0) + 2], H[(h0) + 3], mapa(BAR(B_RECV2 + wgi), hr ^ 1));
#define F1_BLOCK(b, first)                                                                     \
    if ((first) && (b) < 2 && (b) >= EARLY) R_RELEASE(2);                                      \
    R_WAIT();                                                                                  \
    if ((b) == PPB) { PP_WAIT() }                                                              \
    { const uint64_t db = BASE128(0, HALF, R_ADJ);                                             \
    wg_fence();                                                                                \
    FOR7(mma_rs128<1, D128(0, t)>(ag, AQ(A, b, t), (b) + t > 0, db);                           \
         if constexpr (first) { PREP(b, t, true) }); }                                         \
    wg_commit();                                                                               \
    if ((b) == 3) { PP_GO() }                                                                  \
    if ((b) > 0) { wg_wait<1>(); R_RELEASE(1); }       \
    R_NEXT();
                normalize<0>(A, k0, k1);
                F1_BLOCK(0, true) F1_BLOCK(1, true) F1_BLOCK(2, true) F1_BLOCK(3, true)
                if (t128 == 0) { mbar_expect_tx(BAR(B_RECV + wgi), 16384); mbar_expect_tx(BAR(B_RECV2 + wgi), 12288); }
                PUSH_BEGIN();
                wg_wait<0>();
                R_RELEASE(1);
                if (step == 1) R_NEXT();
                int p = 0;
#pragma unroll 1
                do {
                    STAMP(68 + p);
                    F1_EPI(H + 32, 8, ag)
                    STAMP(4 + p + so);
                    WSUM(81 + p + 7 * (step >> 1));
                    if (maps.flag[p + 1] == 0) continue;
                    {
                        const uint32_t pk = (p ? hbuf + 16384 : sb + OFF_KVB + wgi * 8192) + w * 2048;
#pragma unroll
                        for (int k = 0; k < 4; k++) sts4(pk + k * 512 + lane * 16, H[32 + 4 * k], H[33 + 4 * k], H[34 + 4 * k], H[35 + 4 * k]);
                        fence_async();
                        __syncwarp();
                        asm volatile(ELECT "cp.async.bulk.shared::cluster.shared::cta.mbarrier::complete_tx::bytes [%0], [%1], 2048, [%2]; }"
                                     ::"r"(mapa(hbuf + p * 8192 + w * 2048, hr ^ 1)), "r"(pk), "r"(mapa(BAR(B_RECV + wgi), hr ^ 1)) : "memory");
                    }
                    kill<64>(ag);
                    F1_BLOCK(0, false) F1_BLOCK(1, false) F1_BLOCK(2, false) F1_BLOCK(3, false)
                    wg_wait<0>();
                    R_RELEASE(1);
                    kill<16>(H + 32);
                } while (maps.flag[++p]);
#pragma unroll
                for (int k = 0; k < 4; k++) lds4(H + 16 + 4 * k, hbuf + 16384 + w * 2048 + k * 512 + lane * 16);
                __syncwarp();
                if (lane == 0) asm volatile("mbarrier.arrive.shared::cluster.b64 _, [%0];" ::"r"(mapa(BAR(B_ACK2 + wgi), hr ^ 1)) : "memory");
                const uint32_t rem_h = mapa(hbuf + w * 2048 + lane * 16, hr ^ 1);
#define F1_LAST(b0)                                                                            \
    R_WAIT();                                                                                  \
    if (b0) { PP_WAIT() }                                                                      \
    { const uint64_t db = BASE64(0, HALF, R_ADJ);                                              \
    wg_fence();                                                                                \
    FOR7(mma_rs64<1, D64(0, t)>(al, AQ(A, b0, t), (b0) + t > 0, db));                          \
    FOR7(mma_rs64<1, D64(7168, t)>(al, AQ(A, (b0) + 1, t), 1, db)); }                          \
    wg_commit();                                                                               \
    if (b0) { PP_GO() }                                                                        \
    R_NEXT();
                float al[32];
                F1_LAST(0)
                mbar_wait(BAR(B_RECV + wgi), rcvph);
                rcvph ^= 1;
                mbar_wait(BAR(B_ACK2 + wgi), step >> 1);
                H_PUSH(32, 16384) H_PUSH(36, 16896)
                F1_LAST(2)
                H_PUSH(40, 17408) H_PUSH(44, 17920)
                wg_wait<1>();
                R_RELEASE(2);
                wg_wait<0>();
                R_RELEASE(1);
                uint32_t HP[56];
#pragma unroll
                for (int k = 0; k < 4; k++) lds4(H + 4 * k, sb + OFF_KVB + wgi * 8192 + w * 2048 + k * 512 + lane * 16);
#pragma unroll
                for (int t = 0; t < 8; t++) lds4(HP + 4 * t, hbuf + (t >> 2) * 8192 + w * 2048 + (t & 3) * 512 + lane * 16);
                F1_EPI(H + 48, 4, al)
                H_PUSH(48, 24576 - w * 1024) H_PUSH(52, 25088 - w * 1024)
                STAMP(7 + so);
                WSUM(84 + 7 * (step >> 1));
                float acc[28];
                const uint32_t roA = hr ? 256u : 0u, roB = hr ? (uint32_t)-1536 : 0u;
                const uint32_t rpA = hr ? 0u : 256u, rpB = hr ? 0u : (uint32_t)-1536;
                kill<24>(HP + 32);
                float res[28];
                uint32_t v0[14], v1[14];
                const uint4* ps = xp0 + sl * 512;
#define F2_OWN()                                                                               \
    R_WAIT();                                                                                  \
    { const uint64_t d0 = BASE128(0, 16, R_ADJ + roA), d1 = BASE128(0, 16, R_ADJ + roB);       \
    wg_fence();                                                                                \
    FOR14(mma_rs56<1, t * 128>(acc, H[4 * t], H[4 * t + 1], H[4 * t + 2], H[4 * t + 3], t > 0, t < 12 ? d0 : d1)); } \
    wg_commit();                                                                               \
    R_NEXT();
#define F2_PEER()                                                                              \
    R_WAIT();                                                                                  \
    PP_WAIT()                                                                                  \
    { const uint64_t d0 = BASE128(0, 16, R_ADJ + rpA), d1 = BASE128(0, 16, R_ADJ + rpB);       \
    wg_fence();                                                                                \
    FOR14(mma_rs56<1, t * 128>(acc, HP[4 * t], HP[4 * t + 1], HP[4 * t + 2], HP[4 * t + 3], 1, t < 12 ? d0 : d1)); } \
    wg_commit();                                                                               \
    PP_GO()                                                                                    \
    R_NEXT();
#pragma unroll 1
                for (int u = 0; u < 3; u++) {
                    kill<28>(acc);
                    F2_OWN()
                    if (u == 0) {
                        mbar_wait(BAR(B_RECV2 + wgi), step >> 1);
#pragma unroll
                        for (int k = 0; k < 4; k++) lds4(HP + 32 + 4 * k, hbuf + 16384 + w * 2048 + k * 512 + lane * 16);
                        lds4(HP + 48, hbuf + 24576 + w * 1024 + lane * 16);
                        lds4(HP + 52, hbuf + 25088 + w * 1024 + lane * 16);
                        asm volatile("" ::"r"(HP[48]), "r"(HP[52]) : "memory");
                        if (step == 1) PUSH_ACK();
                    }
                    F2_PEER()
                    wg_wait<1>();
                    R_RELEASE(2);
                    wg_wait<0>();
                    R_RELEASE(1);
                    uint32_t P[14];
#pragma unroll
                    for (int i = 0; i < 14; i++) P[i] = pack2(acc[2 * i], acc[2 * i + 1]);
                    send_slice<0>(xp0 + u * PLANE + (2 * ((pr + u + 1) & 3) + hr) * 512, lane, P, tag);
                    seq++;
                    if (lane == 0) st_word(cx(sl), seq);
                    STAMP(8 + u + so);
                }
                slice_load<PL(2)>(X, ps, lane);
                slice_load<PL(3)>(v0, ps, lane);
                slice_load<PL(4)>(v1, ps, lane);
                kill<28>(acc);
                F2_OWN()
                STAMP(64 + 8 * (step >> 1));
                slice_check<PL(3)>(v0, ps, lane, tag);
                slice_check<PL(4)>(v1, ps, lane, tag);
                x_fix(X, xbits);
#pragma unroll
                for (int i = 0; i < 14; i++) { res[2 * i] = bf_lo(X[i]) + (bf_lo(v0[i]) + bf_lo(v1[i])); res[2 * i + 1] = bf_hi(X[i]) + (bf_hi(v0[i]) + bf_hi(v1[i])); }
                STAMP(65 + 8 * (step >> 1));
                F2_PEER()
                STAMP(66 + 8 * (step >> 1));
                poll_cnt(cx(2 * ((pr + 1) & 3) + hr), seq);
                STAMP(67 + 8 * (step >> 1));
                slice_load<PL(5)>(v0, ps, lane);
                slice_check<PL(5)>(v0, ps, lane, tag);
#pragma unroll
                for (int i = 0; i < 14; i++) { res[2 * i] += bf_lo(v0[i]); res[2 * i + 1] += bf_hi(v0[i]); }
                STAMP(11 + so);
                wg_wait<0>();
                if (EARLYK >= 1) R_RELEASE(2);
                STAMP(12 + so);
                WSUM(85 + 7 * (step >> 1));
#pragma unroll
                for (int i = 0; i < 14; i++) X[i] = pack2(res[2 * i] + acc[2 * i], res[2 * i + 1] + acc[2 * i + 1]);
            }
        }
        {
            const int m = lane >> 3, rr = lane & 7;
            const uint32_t ob = hbuf + w * 2048, rowa = ob + (rr + 8 * (m & 1)) * 112 + (m >> 1) * 16;
#pragma unroll
            for (int j = 0; j < 3; j++) stsm4(rowa + 32 * j, X[4 * j], X[4 * j + 1], X[4 * j + 2], X[4 * j + 3]);
            asm volatile("stmatrix.sync.aligned.m8n8.x2.shared.b16 [%0], {%1,%2};" ::"r"(ob + (rr + 8 * (m & 1)) * 112 + 96), "r"(X[12]), "r"(X[13]) : "memory");
            fence_async();
            __syncwarp();
            if (lane == 0) {
                asm volatile("cp.async.bulk.tensor.2d.global.shared::cta.bulk_group [%0, {%2, %3}], [%1];" ::"l"(&maps.out), "r"(ob), "r"(56 * sl), "r"(tile * 128 + (tid >> 5) * 16) : "memory");
                asm volatile("cp.async.bulk.commit_group;" ::: "memory");
                asm volatile("cp.async.bulk.wait_group.read 0;" ::: "memory");
            }
        }
        STAMP(50);
        GSTAMP(61);
        PDUMP();
    }
}

typedef CUresult (*EncodeFn)(CUtensorMap*, CUtensorMapDataType, cuuint32_t, void*, const cuuint64_t*, const cuuint64_t*, const cuuint32_t*,
                             const cuuint32_t*, CUtensorMapInterleave, CUtensorMapSwizzle, CUtensorMapL2promotion, CUtensorMapFloatOOBfill);

static void make_map(EncodeFn enc, CUtensorMap* m, const void* p, uint64_t cols, uint64_t rows, uint32_t bc, uint32_t br, CUtensorMapSwizzle sw) {
    cuuint64_t gd[2] = {cols, rows};
    cuuint64_t gs[1] = {cols * 2};
    cuuint32_t bd[2] = {bc, br};
    cuuint32_t es[2] = {1, 1};
    enc(m, CU_TENSOR_MAP_DATA_TYPE_BFLOAT16, 2, const_cast<void*>(p), gd, gs, bd, es, CU_TENSOR_MAP_INTERLEAVE_NONE, sw,
        CU_TENSOR_MAP_L2_PROMOTION_L2_128B, CU_TENSOR_MAP_FLOAT_OOB_FILL_NONE);
}

extern "C" void kernel_launch(void* const* d_in, const int* in_sizes, int n_in, void* d_out, int out_size) {
    (void)in_sizes; (void)n_in; (void)out_size;
    static EncodeFn enc = nullptr;
    if (!enc) {
        void* fn = nullptr;
        cudaDriverEntryPointQueryResult qr;
        cudaGetDriverEntryPoint("cuTensorMapEncodeTiled", &fn, cudaEnableDefault, &qr);
        enc = (EncodeFn)fn;
        cudaFuncSetAttribute(fused_kernel, cudaFuncAttributeMaxDynamicSharedMemorySize, SMEM_BYTES);
    }
    Maps maps;
    {
        cuuint64_t gd[3] = {64, 2048, 7};
        cuuint64_t gs[2] = {896, 128};
        cuuint32_t bd[3] = {64, 32, 7};
        cuuint32_t es[3] = {1, 1, 1};
        enc(&maps.x, CU_TENSOR_MAP_DATA_TYPE_BFLOAT16, 3, d_in[0], gd, gs, bd, es, CU_TENSOR_MAP_INTERLEAVE_NONE, CU_TENSOR_MAP_SWIZZLE_128B,
            CU_TENSOR_MAP_L2_PROMOTION_L2_128B, CU_TENSOR_MAP_FLOAT_OOB_FILL_NONE);
    }
    make_map(enc, &maps.out, d_out, 448, 2048, 56, 16, CU_TENSOR_MAP_SWIZZLE_NONE);
    make_map(enc, &maps.qkv, d_in[1], 1344, 448, 64, 112, CU_TENSOR_MAP_SWIZZLE_128B);
    make_map(enc, &maps.wo, d_in[3], 448, 448, 64, 112, CU_TENSOR_MAP_SWIZZLE_128B);
    make_map(enc, &maps.wg, d_in[5], 1792, 448, 64, 112, CU_TENSOR_MAP_SWIZZLE_128B);
    make_map(enc, &maps.wu, d_in[6], 1792, 448, 64, 112, CU_TENSOR_MAP_SWIZZLE_128B);
    make_map(enc, &maps.wg32, d_in[5], 1792, 448, 32, 112, CU_TENSOR_MAP_SWIZZLE_64B);
    make_map(enc, &maps.wu32, d_in[6], 1792, 448, 32, 112, CU_TENSOR_MAP_SWIZZLE_64B);
    make_map(enc, &maps.wd, d_in[7], 448, 1792, 64, 112, CU_TENSOR_MAP_SWIZZLE_128B);
    for (int ck = 0; ck < 64; ck++) {
        int tile, pr;
        if (ck < 4) { tile = 0; pr = ck; }
        else if (ck < 36) { const int gp = (ck - 4) & 7; pr = (ck - 4) >> 3; tile = gp ? 2 * gp : 1; }
        else { pr = (ck - 36) / 7; tile = 2 * (ck - 36 - 7 * pr) + 3; }
        maps.role[ck] = tile * 4 + pr;
    }
    maps.flag[0] = maps.flag[1] = maps.flag[2] = 1; maps.flag[3] = maps.flag[4] = 0;
    fused_kernel<<<128, 384, SMEM_BYTES>>>(maps, (const __nv_bfloat16*)d_in[0], (const __nv_bfloat16*)d_in[2],
                                           (const __nv_bfloat16*)d_in[5], (const __nv_bfloat16*)d_in[6], (const __nv_bfloat16*)d_in[7]);
}
```

```cpp
#include <cuda_runtime.h>
#include <cuda.h>
#include <cuda_bf16.h>
#include <stdint.h>
#include <type_traits>

#define B3T 6
#define CANARY 1
#define PP

namespace {

constexpr uint32_t STAGE = 28672, HALF = 14336;
constexpr int NST = 5;
constexpr uint32_t OFF_H = NST * STAGE;
constexpr uint32_t OFF_KVB = OFF_H + 2 * STAGE;
constexpr uint32_t OFF_WPHI = OFF_KVB + 16384;
constexpr uint32_t OFF_XR = OFF_WPHI + 7168;
constexpr uint32_t OFF_BAR = OFF_XR + 6144;
constexpr uint32_t SMEM_BYTES = OFF_BAR + 256 + 1536;
constexpr int B_EMPTY = NST, B_RECV = 2 * NST, B_RECV2 = B_RECV + 2, B_PACK = B_RECV2 + 2, B_GAT = B_PACK + 1, B_ACK = B_GAT + 8, B_ACK2 = B_ACK + 2, B_COUNT = B_ACK2 + 2;

constexpr int PACK = 14;

struct Maps { CUtensorMap x, qkv, wo, wg, wu, wg32, wu32, wd, out; };

}

constexpr int PLANE = 16 * 2 * 8 * 512;
struct Scratch {
    uint4 ex[6 * PLANE];
    uint4 kv1[8 * 16 * 16 * 32];
    uint4 kv2[8 * 512];
    uint32_t c1[8 * 8 * 16 * 32];
    uint32_t c2[8 * 4 * 16 * 32];
    uint32_t cw[8 * 32];
    uint4 wp[8 * 32 * (HALF / 16)];
};
__device__ __align__(1024) Scratch g_scratch;
#define g_ex (sc->ex)
#define g_kv1 (sc->kv1)
#define g_kv2 (sc->kv2)
#define g_c1 (sc->c1)
#define g_c2 (sc->c2)
#define g_cw (sc->cw)
#define g_wp (sc->wp)
#define STAMP(i)
#define GSTAMP(i)
#define PDUMP()
#define ASTAMP(i)

namespace {

__device__ __forceinline__ int fresh_tid() { int t; asm volatile("mov.u32 %0, %%tid.x;" : "=r"(t)); return t; }
__device__ __forceinline__ uint4* again(uint4* p) { asm volatile("" : "+l"(p)); return p; }
template <int N> __device__ __forceinline__ void kill(uint32_t* v) {
#pragma unroll
    for (int i = 0; i < N; i++) v[i] = 0;
}
template <int N> __device__ __forceinline__ void kill(float* v) {
#pragma unroll
    for (int i = 0; i < N; i++) v[i] = 0.f;
}
__device__ __forceinline__ uint32_t s2u(const void* p) { return (uint32_t)__cvta_generic_to_shared(p); }
__device__ __forceinline__ void mbar_init(uint32_t a, uint32_t c) { asm volatile("mbarrier.init.shared::cta.b64 [%0], %1;" ::"r"(a), "r"(c) : "memory"); }
__device__ __forceinline__ void mbar_expect_tx(uint32_t a, uint32_t b) { asm volatile("mbarrier.arrive.expect_tx.shared::cta.b64 _, [%0], %1;" ::"r"(a), "r"(b) : "memory"); }
__device__ __forceinline__ void mbar_arrive(uint32_t a) { asm volatile("mbarrier.arrive.shared::cta.b64 _, [%0];" ::"r"(a) : "memory"); }
#define GIVE_UP(id) "trap;\n"
#define SPIN_MAX "0x400000"
#define SPIN_TAIL(id) "add.u32 n, n, 1;\n setp.lt.u32 p, n, " SPIN_MAX ";\n @p bra.uni LP;\n" GIVE_UP(id) " DN:\n }"
__device__ __forceinline__ void mbar_wait(uint32_t a, uint32_t ph) {
    asm volatile("{ .reg .pred p; .reg .b32 n; mov.u32 n, 0;\n LP:\n"
                 "mbarrier.try_wait.parity.shared::cta.b64 p, [%0], %1;\n @p bra DN;\n"
                 "add.u32 n, n, 1;\n setp.lt.u32 p, n, " SPIN_MAX ";\n @p bra LP;\n"
                 GIVE_UP("")
                 " DN:\n }" ::"r"(a), "r"(ph) : "memory");
}
#define ELECT "{ .reg .pred e; elect.sync _|e, 0xffffffff; @e "
__device__ __forceinline__ void tma2d(uint32_t dst, const CUtensorMap* m, int c0, int c1, uint32_t bar) {
    asm volatile(ELECT "cp.async.bulk.tensor.2d.shared::cluster.global.mbarrier::complete_tx::bytes [%0], [%1, {%3, %4}], [%2]; }" ::"r"(dst), "l"(m), "r"(bar), "r"(c0), "r"(c1) : "memory");
}
__device__ __forceinline__ void tma3x(uint32_t dst, const CUtensorMap* m, int row, uint32_t bar) {
    asm volatile(ELECT "cp.async.bulk.tensor.3d.shared::cluster.global.mbarrier::complete_tx::bytes [%0], [%1, {0, %3, 0}], [%2]; }" ::"r"(dst), "l"(m), "r"(bar), "r"(row) : "memory");
}
template <int OFF>
__device__ __forceinline__ void ld_pkt(uint32_t* v, const uint4* p) {
    asm volatile("{ .reg .b128 t; ld.relaxed.gpu.global.b128 t, [%4+%5]; mov.b128 {%0,%1,%2,%3}, t; }" : "=r"(v[0]), "=r"(v[1]), "=r"(v[2]), "=r"(v[3]) : "l"(p), "n"(OFF * 16) : "memory");
}
template <int OFF>
__device__ __forceinline__ void st_pkt(uint4* p, uint32_t a, uint32_t b, uint32_t c, uint32_t d) {
    asm volatile("{ .reg .b128 t; mov.b128 t, {%1,%2,%3,%4}; st.relaxed.gpu.global.b128 [%0+%5], t; }" ::"l"(p), "r"(a), "r"(b), "r"(c), "r"(d), "n"(OFF * 16) : "memory");
}
__device__ __forceinline__ uint32_t pack2(float lo, float hi) {
    uint32_t r;
    asm("cvt.rn.bf16x2.f32 %0, %1, %2;" : "=r"(r) : "f"(hi), "f"(lo));
    return r;
}
__device__ __forceinline__ float bf_lo(uint32_t w) { return __uint_as_float(w << 16); }
__device__ __forceinline__ float bf_hi(uint32_t w) { return __uint_as_float(w & 0xffff0000u); }
__device__ __forceinline__ uint32_t settag(uint32_t w, uint32_t tag) { return (w & ~1u) | tag; }
__device__ __forceinline__ float ex2(float x) { float y; asm("ex2.approx.ftz.f32 %0, %1;" : "=f"(y) : "f"(x)); return y; }
__device__ __forceinline__ float rcp(float x) { float y; asm("rcp.approx.ftz.f32 %0, %1;" : "=f"(y) : "f"(x)); return y; }
__device__ __forceinline__ float tanh_hw(float x) { float y; asm("tanh.approx.f32 %0, %1;" : "=f"(y) : "f"(x)); return y; }
__device__ __forceinline__ void stsm4(uint32_t addr, uint32_t a, uint32_t b, uint32_t c, uint32_t d) {
    asm volatile("stmatrix.sync.aligned.m8n8.x4.shared.b16 [%0], {%1,%2,%3,%4};" ::"r"(addr), "r"(a), "r"(b), "r"(c), "r"(d) : "memory");
}
__device__ __forceinline__ void fence_async() { asm volatile("fence.proxy.async.shared::cta;" ::: "memory"); }
__device__ __forceinline__ void bar_sync(int id, int n) { asm volatile("bar.sync %0, %1;" ::"r"(id), "r"(n) : "memory"); }
__device__ __forceinline__ void bar_arrive(int id, int n) { asm volatile("bar.arrive %0, %1;" ::"r"(id), "r"(n) : "memory"); }
__device__ __forceinline__ void wg_fence() { asm volatile("wgmma.fence.sync.aligned;" ::: "memory"); }
__device__ __forceinline__ void wg_commit() { asm volatile("wgmma.commit_group.sync.aligned;" ::: "memory"); }
template <int N> __device__ __forceinline__ void wg_wait() { asm volatile("wgmma.wait_group.sync.aligned %0;" ::"n"(N) : "memory"); }

constexpr uint32_t SB0 = 1024;
__host__ __device__ constexpr uint32_t dlo(uint32_t off, uint32_t lbo) { return ((SB0 + off) >> 4) | ((lbo >> 4) << 16); }
__host__ __device__ constexpr uint32_t dhi(uint32_t sbo, uint32_t sw) { return (sbo >> 4) | (sw << 30); }
__device__ __forceinline__ uint64_t dbase(uint32_t lo, uint32_t hi) { uint64_t d; asm volatile("mov.b64 %0, {%1, %2};" : "=l"(d) : "r"(lo), "r"(hi)); return d; }
#define BASE128(off, lbo, adj) dbase(dlo(off, lbo) + (adj), dhi(1024, 1))
#define BASE64(off, lbo, adj) dbase(dlo(off, lbo) + (adj), dhi(512, 2))

#define ACC4(d, o) "+f"(d[o]), "+f"(d[o + 1]), "+f"(d[o + 2]), "+f"(d[o + 3])
#define ACC28(d) ACC4(d, 0), ACC4(d, 4), ACC4(d, 8), ACC4(d, 12), ACC4(d, 16), ACC4(d, 20), ACC4(d, 24)
#define ACC32(d, o) ACC4(d, o), ACC4(d, o + 4), ACC4(d, o + 8), ACC4(d, o + 12), ACC4(d, o + 16), ACC4(d, o + 20), ACC4(d, o + 24), ACC4(d, o + 28)

template <int TB, uint64_t D>
__device__ __forceinline__ void mma_rs56(float* d, uint32_t a0, uint32_t a1, uint32_t a2, uint32_t a3, int sd, uint64_t base) {
    asm volatile("{ .reg .pred p; .reg .b64 db; setp.ne.b32 p, %32, 0; add.u64 db, %33, %34;\n"
                 "wgmma.mma_async.sync.aligned.m64n56k16.f32.bf16.bf16 "
                 "{%0,%1,%2,%3,%4,%5,%6,%7,%8,%9,%10,%11,%12,%13,%14,%15,%16,%17,%18,%19,%20,%21,%22,%23,%24,%25,%26,%27}, "
                 "{%28,%29,%30,%31}, db, p, 1, 1, %35; }\n"
                 : ACC28(d)
                 : "r"(a0), "r"(a1), "r"(a2), "r"(a3), "r"(sd), "l"(base), "n"(D), "n"(TB));
}
template <int TB, uint64_t D>
__device__ __forceinline__ void mma_rs64(float* d, uint32_t a0, uint32_t a1, uint32_t a2, uint32_t a3, int sd, uint64_t base) {
    asm volatile("{ .reg .pred p; .reg .b64 db; setp.ne.b32 p, %36, 0; add.u64 db, %37, %38;\n"
                 "wgmma.mma_async.sync.aligned.m64n64k16.f32.bf16.bf16 "
                 "{%0,%1,%2,%3,%4,%5,%6,%7,%8,%9,%10,%11,%12,%13,%14,%15,%16,%17,%18,%19,%20,%21,%22,%23,%24,%25,%26,%27,%28,%29,%30,%31}, "
                 "{%32,%33,%34,%35}, db, p, 1, 1, %39; }\n"
                 : ACC32(d, 0)
                 : "r"(a0), "r"(a1), "r"(a2), "r"(a3), "r"(sd), "l"(base), "n"(D), "n"(TB));
}
template <int TB, uint64_t D>
__device__ __forceinline__ void mma_rs128(float* d, uint32_t a0, uint32_t a1, uint32_t a2, uint32_t a3, int sd, uint64_t base) {
    asm volatile("{ .reg .pred p; .reg .b64 db; setp.ne.b32 p, %68, 0; add.u64 db, %69, %70;\n"
                 "wgmma.mma_async.sync.aligned.m64n128k16.f32.bf16.bf16 "
                 "{%0,%1,%2,%3,%4,%5,%6,%7,%8,%9,%10,%11,%12,%13,%14,%15,%16,%17,%18,%19,%20,%21,%22,%23,%24,%25,%26,%27,%28,%29,%30,%31,%32,%33,%34,%35,%36,%37,%38,%39,%40,%41,%42,%43,%44,%45,%46,%47,%48,%49,%50,%51,%52,%53,%54,%55,%56,%57,%58,%59,%60,%61,%62,%63}, "
                 "{%64,%65,%66,%67}, db, p, 1, 1, %71; }\n"
                 : ACC32(d, 0), ACC32(d, 32)
                 : "r"(a0), "r"(a1), "r"(a2), "r"(a3), "r"(sd), "l"(base), "n"(D), "n"(TB));
}
template <uint64_t DA, uint64_t DB>
__device__ __forceinline__ void mma_ss56_tt(float* d, int sd, uint64_t ba, uint64_t bb) {
    asm volatile("{ .reg .pred p; .reg .b64 da, db; setp.ne.b32 p, %28, 0; add.u64 da, %29, %31; add.u64 db, %30, %32;\n"
                 "wgmma.mma_async.sync.aligned.m64n56k16.f32.bf16.bf16 "
                 "{%0,%1,%2,%3,%4,%5,%6,%7,%8,%9,%10,%11,%12,%13,%14,%15,%16,%17,%18,%19,%20,%21,%22,%23,%24,%25,%26,%27}, "
                 "da, db, p, 1, 1, 1, 1; }\n"
                 : ACC28(d)
                 : "r"(sd), "l"(ba), "l"(bb), "n"(DA), "n"(DB));
}
template <int... I> struct Seq {};
template <class F, int... I> __device__ __forceinline__ void static_for_impl(F&& f, Seq<I...>) { (f(std::integral_constant<int, I>{}), ...); }
#define FOR7(...) static_for_impl([&](auto T_) { constexpr int t = decltype(T_)::value; __VA_ARGS__; }, Seq<0, 1, 2, 3, 4, 5, 6>{})
#define FOR8(...) static_for_impl([&](auto T_) { constexpr int t = decltype(T_)::value; __VA_ARGS__; }, Seq<0, 1, 2, 3, 4, 5, 6, 7>{})
#define FOR14(...) static_for_impl([&](auto T_) { constexpr int t = decltype(T_)::value; __VA_ARGS__; }, Seq<0, 1, 2, 3, 4, 5, 6, 7, 8, 9, 10, 11, 12, 13>{})

__device__ __forceinline__ int kblk(int p, int b) { return b == 0 ? p : b - (b <= p); }
__host__ __device__ constexpr int krow(int t) { return t < 3 ? 16 * t : (t < 6 ? 56 + 16 * (t - 3) : 48); }
#define AQ(A, b, t) ((t) < 3 ? A[2 * (b)][4 * (t)] : (t) < 6 ? A[2 * (b) + 1][4 * ((t) - 3)] : A[2 * (b)][12]), \
                    ((t) < 3 ? A[2 * (b)][4 * (t) + 1] : (t) < 6 ? A[2 * (b) + 1][4 * ((t) - 3) + 1] : A[2 * (b)][13]), \
                    ((t) < 3 ? A[2 * (b)][4 * (t) + 2] : (t) < 6 ? A[2 * (b) + 1][4 * ((t) - 3) + 2] : A[2 * (b) + 1][12]), \
                    ((t) < 3 ? A[2 * (b)][4 * (t) + 3] : (t) < 6 ? A[2 * (b) + 1][4 * ((t) - 3) + 3] : A[2 * (b) + 1][13])
#define D128(off, t) ((uint64_t)(((off) + krow(t) * 128) >> 4) + ((uint64_t)((t) == 6 ? (7168 - 1024) >> 4 : 0) << 32))
#define D64(off, t) ((uint64_t)(((off) + krow(t) * 64) >> 4) + ((uint64_t)((t) == 6 ? (3584 - 512) >> 4 : 0) << 32))

#define PL(k) (((k) - 3) * PLANE)
__device__ __forceinline__ void st_word(uint32_t* p, uint32_t v) { asm volatile("st.relaxed.gpu.global.u32 [%0], %1;" ::"l"(p), "r"(v) : "memory"); }
__device__ __forceinline__ uint32_t ld_word(const uint32_t* p) { uint32_t v; asm volatile("ld.relaxed.gpu.global.u32 %0, [%1];" : "=r"(v) : "l"(p) : "memory"); return v; }
template <int O>
__device__ __forceinline__ void send_slice(uint4* dst, int lane, const uint32_t* w, uint32_t tag) {
    st_pkt<O>(dst, settag(w[0], tag), w[1], w[2], w[3]);
    st_pkt<O + 32>(dst, settag(w[4], tag), w[5], w[6], w[7]);
    st_pkt<O + 64>(dst, settag(w[8], tag), w[9], w[10], w[11]);
    asm volatile("{ .reg .b64 t; mov.b64 t, {%1,%2}; st.relaxed.gpu.global.b64 [%0+%3], t; }" ::"l"((char*)dst - lane * 8), "r"(settag(w[12], tag)), "r"(w[13]), "n"(16 * (O + 96)) : "memory");
}
#define RW4(v, o) "+r"(v[o]), "+r"(v[(o) + 1]), "+r"(v[(o) + 2]), "+r"(v[(o) + 3])
#define RW2(v, o) "+r"(v[o]), "+r"(v[(o) + 1])
#define WR4(v, o) "=&r"(v[o]), "=&r"(v[(o) + 1]), "=&r"(v[(o) + 2]), "=&r"(v[(o) + 3])
#define LDP(a, b, c, d, addr, off) "ld.relaxed.gpu.global.b128 q, [" addr "+" off "];\n mov.b128 {" a "," b "," c "," d "}, q;\n"
#define LDH(a, b, addr, off) "ld.relaxed.gpu.global.b64 h, [" addr "+" off "];\n mov.b64 {" a "," b "}, h;\n"
#define VOTE_OK "and.b32 t, t, 1;\n setp.ne.u32 p, t, 0;\n vote.sync.any.pred p, p, 0xffffffff;\n @!p bra.uni DN;\n"
#define CHK(x, tag) "lop3.b32 t, " x ", " tag ", t, 0xBE;\n"
__device__ __forceinline__ void poll_cnt(const uint32_t* p, uint32_t target) {
    asm volatile("{ .reg .pred p; .reg .b32 n, t; mov.u32 n, 0;\n LP:\n"
                 "ld.relaxed.gpu.global.u32 t, [%0];\n sub.s32 t, t, %1;\n setp.lt.s32 p, t, 0;\n vote.sync.any.pred p, p, 0xffffffff;\n @!p bra.uni DN;\n" SPIN_TAIL("1")
                 ::"l"(p), "r"(target) : "memory");
}
template <int STR>
__device__ __forceinline__ void poll4_kv(uint32_t* v, const uint4* p, uint32_t tag) {
    asm volatile("{ .reg .pred p; .reg .b32 n, t; .reg .b128 q; mov.u32 n, 0;\n LP:\n"
                 LDP("%0", "%1", "%2", "%3", "%16", "0") LDP("%4", "%5", "%6", "%7", "%16", "%18")
                 LDP("%8", "%9", "%10", "%11", "%16", "%19") LDP("%12", "%13", "%14", "%15", "%16", "%20")
                 "xor.b32 t, %0, %17;\n" CHK("%4", "%17") CHK("%8", "%17") CHK("%12", "%17") VOTE_OK SPIN_TAIL("2")
                 : WR4(v, 0), WR4(v, 4), WR4(v, 8), WR4(v, 12)
                 : "l"(p), "r"(tag), "n"(16 * STR), "n"(32 * STR), "n"(48 * STR)
                 : "memory");
}
__device__ __forceinline__ void poll2_kv(uint32_t* v, const uint4* p, uint32_t tag) {
    asm volatile("{ .reg .pred p; .reg .b32 n, t; .reg .b128 q; mov.u32 n, 0;\n LP:\n"
                 LDP("%0", "%1", "%2", "%3", "%8", "0") LDP("%4", "%5", "%6", "%7", "%8", "128")
                 "xor.b32 t, %0, %9;\n" CHK("%4", "%9") VOTE_OK SPIN_TAIL("6")
                 : WR4(v, 0), WR4(v, 4) : "l"(p), "r"(tag) : "memory");
}
template <int B>
__device__ __forceinline__ void blk_load(uint32_t (&A)[8][14], const uint4* src, int lane) {
    ld_pkt<0>(&A[2 * B][0], src); ld_pkt<32>(&A[2 * B][4], src); ld_pkt<64>(&A[2 * B][8], src);
    ld_pkt<512>(&A[2 * B + 1][0], src); ld_pkt<544>(&A[2 * B + 1][4], src); ld_pkt<576>(&A[2 * B + 1][8], src);
    asm volatile("{ .reg .b64 h;\n" LDH("%0", "%1", "%4", "1536") LDH("%2", "%3", "%4", "9728") "}"
                 : "=&r"(A[2 * B][12]), "=&r"(A[2 * B][13]), "=&r"(A[2 * B + 1][12]), "=&r"(A[2 * B + 1][13])
                 : "l"((const char*)src - lane * 8) : "memory");
}
template <int B>
__device__ __forceinline__ void blk_check(uint32_t (&A)[8][14], const uint4* src, int lane, uint32_t tag) {
    asm volatile("{ .reg .pred p; .reg .b32 n, t; .reg .b128 q; .reg .b64 h, a8; mov.u32 n, 0;\n LP:\n"
                 "xor.b32 t, %0, %30;\n" CHK("%4", "%30") CHK("%8", "%30") CHK("%12", "%30") CHK("%16", "%30") CHK("%20", "%30") CHK("%24", "%30") CHK("%26", "%30") VOTE_OK
                 LDP("%0", "%1", "%2", "%3", "%28", "0") LDP("%4", "%5", "%6", "%7", "%28", "512") LDP("%8", "%9", "%10", "%11", "%28", "1024")
                 LDP("%12", "%13", "%14", "%15", "%28", "8192") LDP("%16", "%17", "%18", "%19", "%28", "8704") LDP("%20", "%21", "%22", "%23", "%28", "9216")
                 "mad.wide.s32 a8, %29, -8, %28;\n" LDH("%24", "%25", "a8", "1536") LDH("%26", "%27", "a8", "9728") SPIN_TAIL("3")
                 "\n and.b32 %0, %0, -2; and.b32 %4, %4, -2; and.b32 %8, %8, -2; and.b32 %12, %12, -2; and.b32 %16, %16, -2; and.b32 %20, %20, -2; and.b32 %24, %24, -2; and.b32 %26, %26, -2;"
                 : RW4(A[2 * B], 0), RW4(A[2 * B], 4), RW4(A[2 * B], 8), RW4(A[2 * B + 1], 0), RW4(A[2 * B + 1], 4), RW4(A[2 * B + 1], 8),
                   RW2(A[2 * B], 12), RW2(A[2 * B + 1], 12)
                 : "l"(src), "r"(lane), "r"(tag)
                 : "memory");
}
__device__ __forceinline__ void st_async4(uint32_t a, uint32_t x, uint32_t y, uint32_t z, uint32_t w, uint32_t bar) {
    asm volatile("st.async.weak.shared::cluster.mbarrier::complete_tx::bytes.v4.b32 [%0], {%1,%2,%3,%4}, [%5];" ::"r"(a), "r"(x), "r"(y), "r"(z), "r"(w), "r"(bar) : "memory");
}
__device__ __forceinline__ uint32_t mapa(uint32_t a, uint32_t cta) { uint32_t r; asm("mapa.shared::cluster.u32 %0, %1, %2;" : "=r"(r) : "r"(a), "r"(cta)); return r; }
__device__ __forceinline__ void stat_poll(uint32_t* v, const uint4* p, uint32_t tag) {
    asm volatile("{ .reg .pred p; .reg .b32 n, t; .reg .b128 q; mov.u32 n, 0;\n LP:\n"
                 LDP("%0", "%1", "%2", "%3", "%8", "0") LDP("%4", "%5", "%6", "%7", "%8", "8192")
                 "xor.b32 t, %3, %9;\n" CHK("%7", "%9") VOTE_OK SPIN_TAIL("4")
                 : WR4(v, 0), WR4(v, 4) : "l"(p), "r"(tag) : "memory");
}
__device__ __forceinline__ uint32_t x_bits(const uint32_t* X) {
    uint32_t r;
    asm volatile("{ .reg .b32 a, b; prmt.b32 a, %1, %2, 0x0040; prmt.b32 b, %3, %4, 0x0040; prmt.b32 %0, a, b, 0x5410; }" : "=r"(r) : "r"(X[0]), "r"(X[4]), "r"(X[8]), "r"(X[12]));
    return r;
}
template <int O>
__device__ __forceinline__ void slice_load(uint32_t* v, const uint4* p, int lane) {
    ld_pkt<O>(v, p); ld_pkt<O + 32>(v + 4, p); ld_pkt<O + 64>(v + 8, p);
    asm volatile("{ .reg .b64 h;\n" LDH("%0", "%1", "%2", "%3") "}" : "=r"(v[12]), "=r"(v[13]) : "l"((const char*)p - lane * 8), "n"(16 * (O + 96)) : "memory");
}
template <int O>
__device__ __forceinline__ void slice_check(uint32_t* v, const uint4* p, int lane, uint32_t tag) {
    asm volatile("{ .reg .pred p; .reg .b32 n, t; .reg .b128 q; .reg .b64 h; mov.u32 n, 0;\n LP:\n"
                 "xor.b32 t, %0, %16;\n" CHK("%4", "%16") CHK("%8", "%16") CHK("%12", "%16") VOTE_OK
                 LDP("%0", "%1", "%2", "%3", "%14", "%17") LDP("%4", "%5", "%6", "%7", "%14", "%18") LDP("%8", "%9", "%10", "%11", "%14", "%19")
                 LDH("%12", "%13", "%15", "%20") SPIN_TAIL("5")
                 : RW4(v, 0), RW4(v, 4), RW4(v, 8), RW2(v, 12)
                 : "l"(p), "l"((const char*)p - lane * 8), "r"(tag), "n"(16 * O), "n"(16 * (O + 32)), "n"(16 * (O + 64)), "n"(16 * (O + 96))
                 : "memory");
}
__device__ __forceinline__ void x_fix(uint32_t* X, uint32_t bits) {
    X[0] = __byte_perm(X[0], bits, 0x3214); X[4] = __byte_perm(X[4], bits, 0x3215); X[8] = __byte_perm(X[8], bits, 0x3216); X[12] = __byte_perm(X[12], bits, 0x3217);
}
__device__ __forceinline__ void sts4(uint32_t a, uint32_t x, uint32_t y, uint32_t z, uint32_t w) {
    asm volatile("st.shared.v4.u32 [%0], {%1,%2,%3,%4};" ::"r"(a), "r"(x), "r"(y), "r"(z), "r"(w) : "memory");
}
__device__ __forceinline__ void lds4(uint32_t* v, uint32_t a) {
    asm volatile("ld.shared.v4.u32 {%0,%1,%2,%3}, [%4];" : "=r"(v[0]), "=r"(v[1]), "=r"(v[2]), "=r"(v[3]) : "r"(a) : "memory");
}
struct LnCoef { uint32_t hi, lo, sh; };
__device__ __forceinline__ LnCoef ln_coef(float sum, float sq) {
    sum += __shfl_xor_sync(0xffffffffu, sum, 1); sq += __shfl_xor_sync(0xffffffffu, sq, 1);
    sum += __shfl_xor_sync(0xffffffffu, sum, 2); sq += __shfl_xor_sync(0xffffffffu, sq, 2);
    const float mean = sum * (1.f / 448.f);
    const float var = fmaxf(fmaf(-mean, mean, sq * (1.f / 448.f)), 0.f);
    const float sc = rsqrtf(var + 1e-5f);
    LnCoef r;
    r.hi = pack2(sc, sc);
    const float lo = sc - bf_lo(r.hi), sh = -mean * sc;
    r.lo = pack2(lo, lo);
    r.sh = pack2(sh, sh);
    return r;
}
__device__ __forceinline__ uint32_t fma2(uint32_t a, uint32_t b, uint32_t c) {
    uint32_t d;
    asm("fma.rn.bf16x2 %0, %1, %2, %3;" : "=r"(d) : "r"(a), "r"(b), "r"(c));
    return d;
}
template <int B>
__device__ __forceinline__ void normalize(uint32_t (&A)[8][14], const LnCoef& c0, const LnCoef& c1) {
#pragma unroll
    for (int s = 2 * B; s < 2 * B + 2; s++)
#pragma unroll
        for (int i = 0; i < 14; i++) {
            const LnCoef& k = (i & 1) ? c1 : c0;
            A[s][i] = fma2(A[s][i], k.hi, fma2(A[s][i], k.lo, k.sh));
        }
}
template <int B, int Q>
__device__ __forceinline__ void normalize_part(uint32_t (&A)[8][14], const LnCoef& c0, const LnCoef& c1) {
#pragma unroll
    for (int k = 7 * Q; k < 7 * Q + 7; k++) {
        const LnCoef& c = (k & 1) ? c1 : c0;
        asm volatile("{ .reg .b32 t; fma.rn.bf16x2 t, %0, %2, %3; fma.rn.bf16x2 %0, %0, %1, t; }" : "+r"(A[2 * B + k / 14][k % 14]) : "r"(c.hi), "r"(c.lo), "r"(c.sh));
    }
}
__device__ __forceinline__ void slice_stats(const uint32_t* w, float* st) {
    float a = 0.f, b = 0.f, p = 0.f, q = 0.f;
#pragma unroll
    for (int i = 0; i < 7; i++) {
        const float e0 = bf_lo(w[2 * i]), e1 = bf_hi(w[2 * i]), e2 = bf_lo(w[2 * i + 1]), e3 = bf_hi(w[2 * i + 1]);
        a += e0 + e1; b += e2 + e3;
        p = fmaf(e0, e0, p); p = fmaf(e1, e1, p); q = fmaf(e2, e2, q); q = fmaf(e3, e3, q);
    }
    a += __shfl_xor_sync(0xffffffffu, a, 1); p += __shfl_xor_sync(0xffffffffu, p, 1); b += __shfl_xor_sync(0xffffffffu, b, 1); q += __shfl_xor_sync(0xffffffffu, q, 1);
    a += __shfl_xor_sync(0xffffffffu, a, 2); p += __shfl_xor_sync(0xffffffffu, p, 2); b += __shfl_xor_sync(0xffffffffu, b, 2); q += __shfl_xor_sync(0xffffffffu, q, 2);
    st[0] = a; st[1] = p; st[2] = b; st[3] = q;
}
__device__ __forceinline__ void dual_softmax(const float* p, uint32_t* out) {
    constexpr float L = 1.4426950408889634f;
#pragma unroll
    for (int r = 0; r < 2; r++) {
        float mx = fmaxf(p[2 * r], p[2 * r + 1]), mn = fminf(p[2 * r], p[2 * r + 1]);
#pragma unroll
        for (int i = 1; i < 7; i++) {
            mx = fmaxf(mx, fmaxf(p[4 * i + 2 * r], p[4 * i + 2 * r + 1]));
            mn = fminf(mn, fminf(p[4 * i + 2 * r], p[4 * i + 2 * r + 1]));
        }
        mx = fmaxf(mx, __shfl_xor_sync(0xffffffffu, mx, 1));
        mn = fminf(mn, __shfl_xor_sync(0xffffffffu, mn, 1));
        const float bx = -mx * L, bn = mn * L;
        float ep[14], en[14], sp = 0.f, sn = 0.f;
#pragma unroll
        for (int i = 0; i < 14; i++) {
            const float v = p[4 * (i >> 1) + 2 * r + (i & 1)];
            ep[i] = ex2(fmaf(v, L, bx));
            en[i] = ex2(fmaf(v, -L, bn));
            sp += ep[i]; sn += en[i];
        }
        sp += __shfl_xor_sync(0xffffffffu, sp, 1);
        sn += __shfl_xor_sync(0xffffffffu, sn, 1);
        const float ip = rcp(sp), in = rcp(sn);
#pragma unroll
        for (int i = 0; i < 7; i++) {
            out[4 * i + r] = pack2(ep[2 * i] * ip, ep[2 * i + 1] * ip);
            out[4 * i + 2 + r] = pack2(en[2 * i] * in, en[2 * i + 1] * in);
        }
    }
}
__device__ __forceinline__ float geglu(float g, float u) {
    const float t = tanh_hw(g * fmaf(g * g, 0.7978845608028654f * 0.044715f, 0.7978845608028654f));
    const float hu = 0.5f * g * u;
    return fmaf(t, hu, hu);
}
__device__ __forceinline__ void phi_gemm(const float* t, float* p) {
    uint32_t w[14];
#pragma unroll
    for (int i = 0; i < 14; i++) w[i] = pack2(t[2 * i], t[2 * i + 1]);
    const uint64_t db = BASE128(OFF_WPHI, 16, 0);
    wg_fence();
    mma_rs56<0, 0>(p, w[0], w[1], w[2], w[3], 0, db);
    mma_rs56<0, 2>(p, w[4], w[5], w[6], w[7], 1, db);
    mma_rs56<0, 4>(p, w[8], w[9], w[10], w[11], 1, db);
    mma_rs56<0, 6>(p, w[12], w[13], 0u, 0u, 1, db);
    wg_commit();
    wg_wait<0>();
}

}

#define BAR(i) (bars + 8 * (i))
#define R_WAIT() mbar_wait(BAR(slot), ph)
#define WSUM(i)
#define R_ADJ (slot * (STAGE >> 4))
#define R_NEXT() do { eb2 = eb1; eb1 = BAR(B_EMPTY + slot); if (++slot == NST) { slot = 0; ph ^= 1; } } while (0)
#define R_RELEASE(k) do { if (lane == 0) mbar_arrive((k) == 1 ? eb1 : eb2); } while (0)
#define PUSH_BEGIN() do { mbar_wait(BAR(B_ACK + wgi), ackph); ackph ^= 1; } while (0)
#define PUSH_ACK() do { __syncwarp(); if (lane == 0) asm volatile("mbarrier.arrive.shared::cluster.b64 _, [%0];" ::"r"(mapa(BAR(B_ACK + wgi), hr ^ 1)) : "memory"); } while (0)

__global__ void __cluster_dims__(2, 1, 1) __launch_bounds__(384, 1)
fused_kernel(Scratch* const sc, const __nv_bfloat16* __restrict__ x_in, const __nv_bfloat16* __restrict__ w_phi, const int trips,
             const __nv_bfloat16* __restrict__ wg, const __nv_bfloat16* __restrict__ wu, const __nv_bfloat16* __restrict__ wd,
             const __grid_constant__ Maps maps) {
    extern __shared__ __align__(1024) unsigned char smem_raw[];
    const uint32_t sb = s2u(smem_raw);
    const uint32_t bars = sb + OFF_BAR;
    const int wgi = __shfl_sync(0xffffffffu, threadIdx.x >> 7, 0);
    const int hr = blockIdx.x & 1, ck = blockIdx.x >> 1;
    const int gp = (ck - 4) & 7, q7 = ((ck - 36) * 37) >> 8;
    const int pr = ck < 4 ? ck : (ck < 36 ? (ck - 4) >> 3 : q7);
    const int tile = ck < 4 ? 0 : (ck < 36 ? (gp ? 2 * gp : 1) : 2 * (ck - 36 - 7 * q7) + 3);
    const int sl = 2 * pr + hr;
    STAMP(0);
    GSTAMP(60);
    if (threadIdx.x == 256) {
#pragma unroll
        for (int i = 0; i < NST; i++) mbar_init(BAR(i), 1);
        asm volatile("fence.mbarrier_init.release.cluster;" ::: "memory");
    }
    if (threadIdx.x == 288) {
        if ((sb & 0x3FFFF) != SB0) asm volatile("trap;");
#pragma unroll
        for (int i = NST; i < B_COUNT; i++) mbar_init(BAR(i), i >= B_ACK ? 4 : (i < B_RECV ? 8 : 1));
        asm volatile("fence.mbarrier_init.release.cluster;" ::: "memory");
    }
    __syncwarp();
    asm volatile("barrier.cluster.arrive.relaxed.aligned;" ::: "memory");

    if (wgi == 2) {
        asm volatile("setmaxnreg.dec.sync.aligned.u32 40;");
        const int t128 = fresh_tid() & 127, w = __shfl_sync(0xffffffffu, t128 >> 5, 0), lane = t128 & 31;
        uint32_t kseq = 0;
        auto kv_job = [&](int layer) {
            const uint32_t tag = layer ^ 1;
            kseq++;
            bar_sync(7, 384);
            ASTAMP(0);
            if (tile < 15) {
                const int sq = lane >> 3, pk = 8 * w + (lane & (tile == 14 ? 3 : 7));
                uint32_t v[16];
                if (layer == 0 || CANARY) poll_cnt(g_c1 + ((sl * 8 + (w >> 1) * 4 + (tile >> 2)) * 16 + (lane & 15)) * 32, kseq);
                ASTAMP(1);
                poll4_kv<32>(v, g_kv1 + ((sl * 16 + tile) * 16 + 4 * sq) * 32 + pk, tag);
#pragma unroll
                for (int k = 0; k < 4; k++) {
                    float lo = (bf_lo(v[k]) + bf_lo(v[4 + k])) + (bf_lo(v[8 + k]) + bf_lo(v[12 + k]));
                    float hi = (bf_hi(v[k]) + bf_hi(v[4 + k])) + (bf_hi(v[8 + k]) + bf_hi(v[12 + k]));
                    lo += __shfl_xor_sync(0xffffffffu, lo, 8); hi += __shfl_xor_sync(0xffffffffu, hi, 8);
                    lo += __shfl_xor_sync(0xffffffffu, lo, 16); hi += __shfl_xor_sync(0xffffffffu, hi, 16);
                    v[k] = pack2(lo, hi);
                }
                if (sq == 0) st_pkt<0>(g_kv2 + sl * 512 + 32 * tile + pk, settag(v[0], tag), v[1], v[2], v[3]);
            }
            if (lane == 0) st_word(g_c2 + ((sl * 4 + w) * 16 + tile) * 32, kseq);
            ASTAMP(2);
            poll_cnt(g_c2 + ((sl * 4 + w) * 16 + (lane & 15)) * 32, kseq);
            bar_arrive(3, 384);
            ASTAMP(3);
        };
        if (w == 0) {
#pragma unroll 1
            for (int n = 0; n < NST; n++) {
                const uint32_t dst = sb + n * STAGE, fb = BAR(n);
                asm volatile(ELECT "mbarrier.arrive.expect_tx.shared::cta.b64 _, [%0], %1; }" ::"r"(fb), "r"(n < 2 ? 2 * STAGE : STAGE) : "memory");
                if (n < 2) {
                    tma3x(sb + OFF_H + n * STAGE, &maps.x, tile * 128 + n * 64, fb);
                    tma3x(dst, &maps.x, tile * 128 + n * 64 + 32, fb);
                } else {
                    const int ra = 112 * (n - 2);
                    tma2d(dst, &maps.qkv, 448 + 56 * sl, ra, fb);
                    tma2d(dst + HALF, &maps.qkv, 896 + 56 * sl, ra, fb);
                }
            }
            asm volatile("barrier.cluster.wait.aligned;" ::: "memory");
            const uint32_t cw_target = (ld_word(g_cw + sl * 32) & ~15u) + 16;
            uint32_t e0[2], e1[2];
#pragma unroll
            for (int k = 0; k < 2; k++) {
                const int n = t128 + 32 * k;
                int m = n - 2 - (n > PACK);
                const bool packed = m >= 30 ? (m < 38 || m >= 52) : m >= 22;
                if (m >= 30) m -= 30;
                if (n == PACK) m = tile < 8 ? tile : tile + 14;
                const int rot = n < 8 ? 0 : pr;
                const int ra = 112 * kblk(rot, m & 3), rb = 112 * kblk(rot, 2 * m & 3), rc = 112 * kblk(rot, (2 * m + 1) & 3);
                int kind = 0, m0, m1, c0, c1, r0, r1;
                if (m < 4) { m0 = m1 = 1; c0 = 448 + 56 * sl; c1 = c0 + 448; r0 = r1 = ra; }
                else if (m < 8) { m0 = m1 = m < 6 ? 1 : 2; c0 = c1 = 56 * sl; r0 = rb; r1 = rc; }
                else if (m < 20) { m0 = 3; m1 = 4; c0 = c1 = 224 * sl + 32 * hr + 64 * ((m - 8) >> 2); r0 = r1 = ra; }
                else if (m < 22) { kind = 2; m0 = 5; m1 = 6; c0 = c1 = 224 * sl + (hr ? 0 : 192); r0 = rb; r1 = rc; }
                else { m0 = m1 = 7; c0 = c1 = 56 * (2 * ((pr + (m >> 1) - 10) & 3) + hr); r0 = 224 * (sl ^ (m & 1)); r1 = r0 + 112; }
                if (packed) { kind = 1; r0 = sl * 16 + (m < 8 ? m : m - 14); r1 = 0; }
                e0[k] = kind | (m0 << 2) | (m1 << 6) | (c0 << 10) | (c1 << 21);
                e1[k] = r0 | (r1 << 16);
            }
            kseq = ld_word(g_c2 + (sl * 64 + tile) * 32);
            int slot = 0, ph = 0;
#pragma unroll 1
            for (int n = NST; n < 63; n++) {
                if (n == 11 || n == 42) kv_job(n == 42);
                const uint32_t w0 = __shfl_sync(0xffffffffu, n < 32 ? e0[0] : e0[1], n & 31), w1 = __shfl_sync(0xffffffffu, n < 32 ? e1[0] : e1[1], n & 31);
                const uint32_t dst = sb + slot * STAGE, fb = BAR(n == PACK ? B_PACK : slot);
                const CUtensorMap* m0 = &maps.x + ((w0 >> 2) & 15);
                const CUtensorMap* m1 = &maps.x + ((w0 >> 6) & 15);
                const int c0 = (w0 >> 10) & 2047, c1 = w0 >> 21, r0 = w1 & 0xffff, r1 = w1 >> 16;
                if (n == 25) {
                    int it = 0;
                    uint32_t v;
                    do { asm volatile("ld.acquire.gpu.global.u32 %0, [%1];" : "=r"(v) : "l"(g_cw + sl * 32) : "memory"); } while ((int)(v - cw_target) < 0 && ++it < 0x400000);
                    asm volatile("fence.proxy.async.global;" ::: "memory");
                    __syncwarp();
                }
                mbar_wait(BAR(B_EMPTY + slot), ph);
                __syncwarp();
                asm volatile(ELECT "mbarrier.arrive.expect_tx.shared::cta.b64 _, [%0], %1; }" ::"r"(fb), "r"(STAGE) : "memory");
                if ((w0 & 3) == 0) {
                    tma2d(dst, m0, c0, r0, fb);
                    tma2d(dst + HALF, m1, c1, r1, fb);
                } else if (w0 & 1) {
                    asm volatile(ELECT "cp.async.bulk.shared::cluster.global.mbarrier::complete_tx::bytes [%0], [%1], %2, [%3]; }"
                                 ::"r"(dst), "l"(reinterpret_cast<const char*>(g_wp) + (size_t)r0 * STAGE), "r"(STAGE), "r"(fb) : "memory");
                } else {
                    tma2d(dst, m0, c0, r0, fb); tma2d(dst + 7168, m0, c0, r1, fb);
                    tma2d(dst + HALF, m1, c0, r0, fb); tma2d(dst + HALF + 7168, m1, c0, r1, fb);
                }
                if (n == PACK) asm volatile(ELECT "mbarrier.arrive.shared::cta.b64 _, [%0]; }" ::"r"(BAR(slot)) : "memory");
                if (++slot == NST) { slot = 0; ph ^= 1; }
            }
        } else {
            const int j = t128 - 32;
            asm volatile("barrier.cluster.wait.aligned;" ::: "memory");
            uint2 wv[7];
            const int k = j < 56 ? j : 55, hh = k >= 28;
#pragma unroll
            for (int i = 0; i < 7; i++) wv[i] = __ldg(reinterpret_cast<const uint2*>(w_phi + (sl * 56 + k) * 28) + i);
#pragma unroll 1
            for (int i = j; i < 7168 / 16; i += 96) sts4(sb + OFF_WPHI + i * 16, 0, 0, 0, 0);
            bar_sync(5, 96);
            if (j < 56) {
                uint32_t a4[4];
#pragma unroll
                for (int q = 0; q < 4; q++) a4[q] = sb + OFF_WPHI + (4 * hh + q) * 128 + ((((k >> 3) ^ (4 * hh + q)) & 7) << 4) + (k & 7) * 2;
                FOR14(const uint32_t v = (t & 1) ? wv[t >> 1].y : wv[t >> 1].x;
                      asm volatile("{ .reg .b16 l, h; mov.b32 {l, h}, %2; st.shared.u16 [%0+%3], l; st.shared.u16 [%1+%3], h; }"
                                   ::"r"(a4[t >= 7 ? 2 : 0]), "r"(a4[t >= 7 ? 3 : 1]), "r"(v), "n"((t % 7) * 1024) : "memory"));
            }
            __syncwarp();
            fence_async();
            bar_arrive(1, 352);
            if (j == 0) {
                mbar_wait(BAR(2), 0);
                mbar_wait(BAR(2), 1);
                const int b = blockIdx.x;
                asm volatile("cp.async.bulk.prefetch.L2.global [%0], %1;" ::"l"(wg + b * 6272), "r"(12544) : "memory");
                asm volatile("cp.async.bulk.prefetch.L2.global [%0], %1;" ::"l"(wu + b * 6272), "r"(12544) : "memory");
                asm volatile("cp.async.bulk.prefetch.L2.global [%0], %1;" ::"l"(wd + b * 6272), "r"(12544) : "memory");
            }
            __syncwarp();
            kseq = ld_word(g_c2 + ((sl * 4 + w) * 16 + tile) * 32);
#pragma unroll 1
            for (int layer = 0; layer < 2; layer++) {
                kv_job(layer);
                if (layer == 0 && j == 0) {
                    constexpr int ps = PACK % NST;
                    mbar_wait(BAR(B_PACK), 0);
                    asm volatile("cp.async.bulk.global.shared::cta.bulk_group [%0], [%1], %2;"
                                 ::"l"(reinterpret_cast<char*>(g_wp) + (size_t)(sl * 16 + tile) * STAGE), "r"(sb + ps * STAGE), "r"(STAGE) : "memory");
                    asm volatile("cp.async.bulk.commit_group;" ::: "memory");
                    asm volatile("cp.async.bulk.wait_group.read 0;" ::: "memory");
                    asm volatile("mbarrier.arrive.shared::cta.b64 _, [%0], 8;" ::"r"(BAR(B_EMPTY + ps)) : "memory");
                    asm volatile("cp.async.bulk.wait_group 0;" ::: "memory");
                    asm volatile("fence.proxy.async.global;" ::: "memory");
                    asm volatile("red.release.gpu.global.add.u32 [%0], 1;" ::"l"(g_cw + sl * 32) : "memory");
                }
                __syncwarp();
            }
        }
    } else {
        asm volatile("setmaxnreg.inc.sync.aligned.u32 232;");
        const int tid = fresh_tid(), lane = tid & 31, t128 = tid & 127, g = lane >> 2, c = lane & 3;
        const int wu = __shfl_sync(0xffffffffu, tid >> 5, 0), w = wu & 3;
        uint4* const xp0 = g_ex + 3 * PLANE + ((tile * 2 + wgi) * 8) * 512 + w * 128 + lane;
        const uint32_t hbuf = sb + OFF_H + wgi * STAGE;
        uint32_t slot = 0, ph = 0, eb1 = 0, eb2 = 0, ackph = 0, rcvph = 0, gatph = 0;
        uint32_t ppid = 6;
#define cx(s) (reinterpret_cast<uint32_t*>(again(xp0) - lane + PL(1) + 112 + (s) * 512))
#define stp (again(xp0) - lane + g + PL(0) + 112)
        uint32_t seq = ld_word(cx(sl));
        uint32_t kseq = ld_word(g_c1 + ((sl * 8 + (tid >> 5)) * 16 + tile) * 32);
        uint32_t stag = ld_word(reinterpret_cast<const uint32_t*>(stp + sl * 512) + 3) & 1;
        asm volatile("barrier.cluster.wait.aligned;" ::: "memory");
        STAMP(1);
        uint32_t X[14];
        const uint32_t x0row = (w < 2 ? hbuf : sb + wgi * STAGE) + ((w & 1) * 16 + (lane & 15)) * 128;
        mbar_wait(BAR(wgi), 0);
        STAMP(51);
#pragma unroll
        for (int j = 0; j < 4; j++) {
            const int G = 7 * sl + min(2 * j + (lane >> 4), 6);
            uint32_t q2, q3;
            asm volatile("ldmatrix.sync.aligned.m8n8.x4.shared.b16 {%0,%1,%2,%3}, [%4];" : "=r"(X[4 * j]), "=r"(X[4 * j + 1]), "=r"(q2), "=r"(q3)
                         : "r"(x0row + (G >> 3) * 4096 + (((G ^ lane) & 7) << 4)) : "memory");
            if (j < 3) { X[(4 * j + 2) % 14] = q2; X[(4 * j + 3) % 14] = q3; }
        }
#define PUSH_SLICE(W)                                                                          \
    {                                                                                          \
        if (t128 == 0) mbar_expect_tx(BAR(B_RECV + wgi), 7168);                                \
        PUSH_BEGIN();                                                                          \
        const uint32_t ra = mapa(hbuf + 24576 + t128 * 16, hr ^ 1), rb = mapa(sb + OFF_XR + wgi * 3072, hr ^ 1), rbar = mapa(BAR(B_RECV + wgi), hr ^ 1); \
        st_async4(ra, W[0], W[1], W[2], W[3], rbar);                                           \
        st_async4(ra + 2048, W[4], W[5], W[6], W[7], rbar);                                    \
        st_async4(rb + t128 * 16, W[8], W[9], W[10], W[11], rbar);                             \
        asm volatile("st.async.weak.shared::cluster.mbarrier::complete_tx::bytes.v2.b32 [%0], {%1,%2}, [%3];" ::"r"(rb + 2048 + t128 * 8), "r"(W[12]), "r"(W[13]), "r"(rbar) : "memory"); \
    }
#define PULL_SLICE(W)                                                                          \
    {                                                                                          \
        uint32_t T[14];                                                                        \
        mbar_wait(BAR(B_RECV + wgi), rcvph);                                           \
        rcvph ^= 1;                                                                            \
        lds4(T, hbuf + 24576 + t128 * 16);                                                     \
        lds4(T + 4, hbuf + 26624 + t128 * 16);                                                 \
        lds4(T + 8, sb + OFF_XR + wgi * 3072 + t128 * 16);                                     \
        asm volatile("ld.shared.v2.u32 {%0,%1}, [%2];" : "=r"(T[12]), "=r"(T[13]) : "r"(sb + OFF_XR + wgi * 3072 + 2048 + t128 * 8) : "memory"); \
        _Pragma("unroll") for (int i = 0; i < 14; i++) { A[0][i] = hr ? T[i] : W[i]; A[1][i] = hr ? W[i] : T[i]; } \
        asm volatile("" : RW4(A[0], 0), RW4(A[0], 4), RW4(A[0], 8), RW2(A[0], 12), RW4(A[1], 0), RW4(A[1], 4), RW4(A[1], 8), RW2(A[1], 12)); \
    }
#define EARLY 1
#define EARLYK 1
#define PPB 2
#define PP_WAIT() if (wgi == 1) { bar_sync(ppid, 256); ppid ^= 14; }
#define PP_GO() if (wgi == 0) { bar_arrive(ppid, 256); ppid ^= 14; }
#define GAT_ISSUE(base)                                                                        \
    {                                                                                          \
        const char* gs = reinterpret_cast<const char*>(g_ex + 3 * PLANE + (base) + (tile * 16 + wgi * 8 + 2 * kblk(pr, 2)) * 512 + w * 128); \
        const uint32_t gd = hbuf + w * 3584, gb = BAR(B_GAT + wu);                     \
        asm volatile("{ .reg .pred e; elect.sync _|e, 0xffffffff;\n"                           \
                     "@e mbarrier.arrive.expect_tx.shared::cta.b64 _, [%2], 3584;\n"           \
                     "@e cp.async.bulk.shared::cluster.global.mbarrier::complete_tx::bytes [%0], [%1], 1792, [%2];\n" \
                     "@e cp.async.bulk.shared::cluster.global.mbarrier::complete_tx::bytes [%0+1792], [%1+8192], 1792, [%2]; }" \
                     ::"r"(gd), "l"(gs), "r"(gb) : "memory");                                  \
        __syncwarp();                                                                          \
    }
#define GAT_FETCH()                                                                            \
    {                                                                                          \
        mbar_wait(BAR(B_GAT + wu), gatph);                                             \
        gatph ^= 1;                                                                            \
        const uint32_t ga = hbuf + w * 3584 + lane * 16;                                       \
        _Pragma("unroll") for (int s2 = 0; s2 < 2; s2++) {                                     \
            lds4(&A[4 + s2][0], ga + s2 * 1792); lds4(&A[4 + s2][4], ga + s2 * 1792 + 512); lds4(&A[4 + s2][8], ga + s2 * 1792 + 1024); \
            asm volatile("ld.shared.v2.u32 {%0,%1}, [%2];" : "=r"(A[4 + s2][12]), "=r"(A[4 + s2][13]) : "r"(ga - lane * 8 + s2 * 1792 + 1536) : "memory"); \
        }                                                                                      \
    }
#define PREP(b, t, remote)                                                                     \
    if constexpr ((b) == 0 && (t) == B3T) { if (remote) blk_load<3>(A, BLK(xsrc, 3), lane); }    \
    if constexpr ((b) < 3 && (t) == 1) { STAMP(80 + 8 * (step & 1) + 2 * (b)); if (remote) blk_check<((b) + 1) & 3>(A, BLK(xsrc, (b) + 1), lane, xtag); STAMP(81 + 8 * (step & 1) + 2 * (b)); } \
    if constexpr ((b) == 3 && ((t) == 0 || (t) == 6)) { STAMP(86 + 8 * (step & 1) + (t) / 6); } \
    if constexpr ((b) < 3 && (t) >= 2 && (t) < 6) normalize_part<((b) + 1) & 3, ((t) - 2) & 3>(A, k0, k1);
#define BLK(base, b) ((base) + kblk(pr, b) * 1024)

#pragma unroll 1
        for (int step = 0; step < 4; step++) {
            const uint32_t tag = (step >> 1) ^ 1;
            const int so = (step >> 1) * 24 + (step & 1) * 12;
            (void)so;
            uint32_t A[8][14];
            uint4* const xsrc = xp0 + ((step & 1) ? PL(2) : PL(0));
            const uint32_t xtag = (step & 1) ? tag : ((seq >> 3) & 1) ^ 1;
            {
                float st[4];
                slice_stats(X, st);
                stag ^= 1;
                if (step) send_slice<0>(xsrc + sl * 512, lane, X, xtag);
                if (c == 0) st_pkt<0>(stp + sl * 512, __float_as_uint(st[0]), __float_as_uint(st[1]), __float_as_uint(st[2]), settag(__float_as_uint(st[3]), stag));
            }
            const uint32_t xbits = x_bits(X);
            STAMP(2 + so);
            uint32_t sv[8];
            if (step == 0) {
                const int rr = lane & 7, hi = lane >> 4;
                const uint32_t rowa = (w < 2 ? hbuf : sb + wgi * STAGE) + ((w & 1) * 16 + (lane & 15)) * 128;
                uint32_t xr[8];
#pragma unroll
                for (int j = 0; j < 8; j++) xr[j] = rowa + ((((j + hi) ^ rr) & 7) << 4) + (j == 7 ? hi * 4096 : 0);
#define X0_BLOCK(b)                                                                            \
    FOR7(constexpr int G = 14 * (b) + (t < 3 ? 2 * t : (t < 6 ? 2 * t + 1 : 6));               \
         uint32_t q0, q1, q2, q3;                                                              \
         const uint32_t ad = t < 6 ? xr[G & 7] : rowa + ((G + 7 * hi) >> 3) * 4096 + ((((G + 7 * hi) ^ rr) & 7) << 4); \
         asm volatile("ldmatrix.sync.aligned.m8n8.x4.shared.b16 {%0,%1,%2,%3}, [%4+%5];" : "=r"(q0), "=r"(q1), "=r"(q2), "=r"(q3) \
                      : "r"(ad), "n"(t < 6 ? (G >> 3) * 4096 : 0) : "memory");                 \
         if (t < 3) { A[2 * (b)][4 * t] = q0; A[2 * (b)][4 * t + 1] = q1; A[2 * (b)][4 * t + 2] = q2; A[2 * (b)][4 * t + 3] = q3; } \
         else if (t < 6) { A[2 * (b) + 1][(4 * t - 12) & 15] = q0; A[2 * (b) + 1][((4 * t - 12) & 15) + 1] = q1; A[2 * (b) + 1][((4 * t - 12) & 15) + 2] = q2; A[2 * (b) + 1][((4 * t - 12) & 15) + 3] = q3; } \
         else { A[2 * (b)][12] = q0; A[2 * (b)][13] = q1; A[2 * (b) + 1][12] = q2; A[2 * (b) + 1][13] = q3; });
                X0_BLOCK(0) X0_BLOCK(1) X0_BLOCK(2) X0_BLOCK(3)
                mbar_wait(BAR(wgi ^ 1), 0);
                R_NEXT();
                R_NEXT();
                stat_poll(sv, stp + c * 1024, stag);
                STAMP(52 + step);
            } else {
                PUSH_SLICE(X)
                kill<14>(A[4]); kill<14>(A[5]); kill<14>(A[6]); kill<14>(A[7]);
                stat_poll(sv, stp + c * 1024, stag);
                STAMP(52 + step);
                blk_load<1>(A, BLK(xsrc, 1), lane);
                PULL_SLICE(X)
            }
            LnCoef k0, k1;
            {
                k0 = ln_coef(__uint_as_float(sv[0]) + __uint_as_float(sv[4]), __uint_as_float(sv[1]) + __uint_as_float(sv[5]));
                k1 = ln_coef(__uint_as_float(sv[2]) + __uint_as_float(sv[6]), __uint_as_float(sv[3]) + __uint_as_float(sv[7]));
            }
            if (step) GAT_ISSUE((step & 1) ? PL(2) : PL(0))
            STAMP(3 + so);

            if ((step & 1) == 0) {
                float tq[28];
                {
                    float av[28];
#define KV_BLOCK(b)                                                                           \
    if ((b) == 1 && step) GAT_FETCH()                                                         \
    if ((b) == 2) PUSH_ACK();                                                                 \
    R_WAIT();                                                                                 \
    { const uint64_t db = BASE128(0, 16, R_ADJ);                                              \
    wg_fence();                                                                               \
    FOR7(mma_rs56<1, D128(0, t)>(tq, AQ(A, b, t), (b) + t > 0, db);                           \
         mma_rs56<1, D128(HALF, t)>(av, AQ(A, b, t), (b) + t > 0, db);                        \
         PREP(b, t, step)); }                                                                 \
    wg_commit();                                                                              \
    R_NEXT();
                    if (EARLYK == 0 || step == 0) R_RELEASE(2);
                    normalize<0>(A, k0, k1);
                    KV_BLOCK(0) KV_BLOCK(1) KV_BLOCK(2) KV_BLOCK(3)
                    wg_wait<0>();
                    if (lane < NST) mbar_arrive(BAR(B_EMPTY + lane));
                    STAMP(4 + so);
                    WSUM(80 + 7 * (step >> 1));
                    const int m = lane >> 3, rr = lane & 7;
                    const uint32_t rowa = hbuf + 16384 + (w * 16 + rr + 8 * (m & 1)) * 128;
                    const uint32_t one = c == 0 ? 0x00003f80u : 0u;
                    if (step == 0) { bar_sync(1, 352); }
#pragma unroll
                    for (int j = 0; j < 4; j++) {
                        const uint32_t a = rowa + (((2 * j + (m >> 1)) ^ rr) << 4);
                        if (j < 3) stsm4(a, pack2(av[8 * j], av[8 * j + 1]), pack2(av[8 * j + 2], av[8 * j + 3]), pack2(av[8 * j + 4], av[8 * j + 5]), pack2(av[8 * j + 6], av[8 * j + 7]));
                        else stsm4(a, pack2(av[24], av[25]), pack2(av[26], av[27]), one, one);
                    }
                }
                uint32_t PH[28];
                int it = 1;
#pragma unroll 1
                do {
                    float pp[28];
                    phi_gemm(tq, pp);
                    dual_softmax(pp, PH);
                    if (((trips >> (it + 1)) & 1) == 0) continue;
                    {
                        const int m = lane >> 3, rr = lane & 7;
                        const uint32_t rowa = hbuf + (w * 16 + rr + 8 * (m & 1)) * 128;
#pragma unroll
                        for (int j = 0; j < 7; j++) {
                            const int cg = 2 * j + (m >> 1), hi = cg >= 7;
                            stsm4(rowa + hi * 8192 + (((cg - 7 * hi) ^ rr) << 4), PH[4 * j], PH[4 * j + 1], PH[4 * j + 2], PH[4 * j + 3]);
                        }
                    }
                    fence_async();
                    STAMP(5 + so);
                    bar_sync(2, 256);
                    kill<28>(tq);
                    const uint64_t da = BASE128(OFF_H + 16384, 16, 0), dbk = BASE128(OFF_H, 16, wgi * 512);
                    wg_fence();
                    FOR8(constexpr uint64_t o = ((t >> 2) * STAGE + (t & 3) * 2048) >> 4; mma_ss56_tt<o, o>(tq, t > 0, da, dbk));
                    wg_commit();
                    wg_wait<0>();
#pragma unroll
                    for (int hf = 0; hf < 2; hf++) {
                        const int d = 16 * w + g + 8 * hf;
                        if ((d < 56 && (d >= 28) == (c >= 2)) || d == 56) {
                            const int item = d < 56 ? 2 * d + (c & 1) : 112 + c;
                            uint4* dst = g_kv1 + ((sl * 16 + (item >> 3)) * 16 + tile) * 32 + wgi * 16 + (item & 7);
#define KVW(i) pack2(tq[4 * (i) + 2 * hf], tq[4 * (i) + 2 * hf + 1])
                            st_pkt<0>(dst, settag(KVW(0), tag), KVW(1), KVW(2), KVW(3));
                            st_pkt<8>(dst, settag(KVW(4), tag), KVW(5), KVW(6), 0u);
                        }
                    }
                    __syncwarp();
                    kseq++;
                    if (lane == 0) st_word(g_c1 + ((sl * 8 + (tid >> 5)) * 16 + tile) * 32, kseq);
                    bar_arrive(7, 384);
                    STAMP(6 + so);
#define Q_STAGE(b0)                                                                           \
    R_WAIT();                                                                                 \
    { const uint64_t db = BASE128(0, 16, R_ADJ);                                              \
    wg_fence();                                                                               \
    FOR7(mma_rs56<1, D128(0, t)>(tq, AQ(A, b0, t), (b0) + t > 0, db));                        \
    FOR7(mma_rs56<1, D128(HALF, t)>(tq, AQ(A, (b0) + 1, t), 1, db)); }                        \
    wg_commit();                                                                              \
    R_NEXT();
                    kill<28>(tq);
                    Q_STAGE(0)
                    Q_STAGE(2)
                    wg_wait<1>();
                    R_RELEASE(2);
                    wg_wait<0>();
                    R_RELEASE(1);
                    STAMP(7 + so);
                    kill<28>(PH);
                } while (((trips >> (++it)) & 1));
                STAMP(8 + so);
                {
                    const int item = t128 < 112 ? t128 : 112 + (t128 & 3), d = item >> 1;
                    const int cc = t128 < 112 ? 2 * (d >= 28) + (item & 1) : item - 112;
                    const int r = t128 < 112 ? d : 56 + (cc >> 1) + 2 * ((t128 - 112) >> 2);
                    const uint32_t ra = sb + OFF_KVB + r * 128 + 4 * cc;
#pragma unroll
                    for (int i = 0; i < 7; i++) {
                        const int ii = i + 7 * wgi;
                        asm volatile("st.shared.u32 [%0], %1;" ::"r"((ra ^ 8) + (ii >> 3) * 8192 + (((ii ^ r) & 7) << 4)), "r"(0) : "memory");
                    }
                    uint32_t v[8];
                    bar_sync(3, 384);
                    poll2_kv(v, g_kv2 + sl * 512 + (item >> 3) * 32 + wgi * 16 + (item & 7), tag);
#pragma unroll
                    for (int i = 0; i < 7; i++) {
                        const int ii = i + 7 * wgi;
                        asm volatile("st.shared.u32 [%0], %1;" ::"r"(ra + (ii >> 3) * 8192 + (((ii ^ r) & 7) << 4)), "r"(v[i]) : "memory");
                    }
                    fence_async();
                    bar_sync(4, 256);
                }
                STAMP(9 + so);
                const uint4* const osrc = xp0 + PL(1);
                {
                    float nm[32];
                    const uint64_t db = BASE128(OFF_KVB, 16, 0);
                    wg_fence();
                    FOR7(mma_rs64<0, ((t >> 2) * 8192 + (t & 3) * 32) / 16>(nm, PH[4 * t], PH[4 * t + 1], PH[4 * t + 2], PH[4 * t + 3], t > 0, db));
                    wg_commit();
                    wg_wait<0>();
                    const float i00 = rcp(nm[28] + 1e-6f), i01 = rcp(nm[29] + 1e-6f), i10 = rcp(nm[30] + 1e-6f), i11 = rcp(nm[31] + 1e-6f);
                    const float m0 = c >= 2 ? i01 : i00, m1 = c >= 2 ? i11 : i10;
                    uint32_t O[14];
#pragma unroll
                    for (int i = 0; i < 7; i++) {
                        const float f0 = i < 3 ? i00 : (i > 3 ? i01 : m0), f1 = i < 3 ? i10 : (i > 3 ? i11 : m1);
                        O[2 * i] = pack2(nm[4 * i] * f0, nm[4 * i + 1] * f0);
                        O[2 * i + 1] = pack2(nm[4 * i + 2] * f1, nm[4 * i + 3] * f1);
                    }
                    send_slice<PL(1)>(xp0 + sl * 512, lane, O, tag);
                    seq++;
                    if (lane == 0) st_word(cx(sl), seq);
                    STAMP(10 + so);
                    PUSH_SLICE(O)
                    poll_cnt(cx(lane & 7), seq);
                    STAMP(56 + (step >> 1));
                    blk_load<1>(A, BLK(osrc, 1), lane);
                    GAT_ISSUE(PL(1))
                    PULL_SLICE(O)
                }
                float ao[28];
#define WO_BLOCK(b)                                                                           \
    if ((b) > 0) blk_check<b>(A, BLK(osrc, b), lane, tag);                                    \
    if (((b) & 1) == 0) R_WAIT();                                                             \
    { const uint64_t db = BASE128(0, 16, R_ADJ);                                              \
    wg_fence();                                                                               \
    FOR7(mma_rs56<1, D128(((b) & 1) * HALF, t)>(ao, AQ(A, b, t), (b) + t > 0, db)); }         \
    wg_commit();                                                                              \
    if ((b) & 1) R_NEXT();
                WO_BLOCK(0)
                STAMP(11 + so);
                blk_load<3>(A, BLK(osrc, 3), lane);
                WO_BLOCK(1)
                GAT_FETCH()
                if (step) {
                    slice_load<PL(0)>(X, xp0 + sl * 512, lane);
                } else {
                    const uint32_t* xp = reinterpret_cast<const uint32_t*>(x_in + (size_t)(tile * 128 + wu * 16 + g) * 448 + 56 * sl + 2 * c);
#pragma unroll
                    for (int i = 0; i < 7; i++) { X[2 * i] = __ldg(xp + 4 * i); X[2 * i + 1] = __ldg(xp + 4 * i + 8 * 224); }
                }
                WO_BLOCK(2)
                PUSH_ACK();
                WO_BLOCK(3)
                wg_wait<0>();
                if (EARLY >= 1) R_RELEASE(2);
                if (EARLY >= 2) R_RELEASE(1);
                STAMP(12 + so);
                WSUM(86 + 7 * (step >> 1));
                x_fix(X, xbits);
#pragma unroll
                for (int i = 0; i < 14; i++) X[i] = pack2(bf_lo(X[i]) + ao[2 * i], bf_hi(X[i]) + ao[2 * i + 1]);
            } else {
                uint32_t H[56];
                float ag[64];
#define F1_EPI(dst, ng, ag)                                                                    \
    _Pragma("unroll") for (int i = 0; i < 2 * (ng); i++)                                       \
        (dst)[i] = pack2(geglu(ag[2 * i], ag[4 * (ng) + 2 * i]), geglu(ag[2 * i + 1], ag[4 * (ng) + 2 * i + 1]));
#define H_PUSH(h0, off) st_async4(rem_h + (off), H[h0], H[(h0) + 1], H[(h0) + 2], H[(h0) + 3], mapa(BAR(B_RECV2 + wgi), hr ^ 1));
#define F1_BLOCK(b, first)                                                                     \
    if ((first) && (b) < 2 && (b) >= EARLY) R_RELEASE(2);                                      \
    if ((first) && (b) == 1) GAT_FETCH()                                                       \
    if ((first) && (b) == 2) PUSH_ACK();                                                       \
    R_WAIT();                                                                                  \
    if ((b) == PPB) { PP_WAIT() }                                                              \
    { const uint64_t db = BASE128(0, HALF, R_ADJ);                                             \
    wg_fence();                                                                                \
    FOR7(mma_rs128<1, D128(0, t)>(ag, AQ(A, b, t), (b) + t > 0, db);                           \
         if constexpr (first) { PREP(b, t, true) }); }                                         \
    wg_commit();                                                                               \
    if ((b) == 3) { PP_GO() }                                                                  \
    if ((b) > 0) { wg_wait<1>(); R_RELEASE(1); }       \
    R_NEXT();
                normalize<0>(A, k0, k1);
                F1_BLOCK(0, true) F1_BLOCK(1, true) F1_BLOCK(2, true) F1_BLOCK(3, true)
                if (t128 == 0) { mbar_expect_tx(BAR(B_RECV + wgi), 16384); mbar_expect_tx(BAR(B_RECV2 + wgi), 12288); }
                PUSH_BEGIN();
                wg_wait<0>();
                R_RELEASE(1);
                if (step == 1) R_NEXT();
                int p = 0;
#pragma unroll 1
                do {
                    STAMP(68 + p);
                    F1_EPI(H + 32, 8, ag)
                    STAMP(4 + p + so);
                    WSUM(81 + p + 7 * (step >> 1));
                    if (((trips >> (p + 1)) & 1) == 0) continue;
                    {
                        const uint32_t pk = (p ? hbuf + 16384 : sb + OFF_KVB + wgi * 8192) + w * 2048;
#pragma unroll
                        for (int k = 0; k < 4; k++) sts4(pk + k * 512 + lane * 16, H[32 + 4 * k], H[33 + 4 * k], H[34 + 4 * k], H[35 + 4 * k]);
                        fence_async();
                        __syncwarp();
                        asm volatile(ELECT "cp.async.bulk.shared::cluster.shared::cta.mbarrier::complete_tx::bytes [%0], [%1], 2048, [%2]; }"
                                     ::"r"(mapa(hbuf + p * 8192 + w * 2048, hr ^ 1)), "r"(pk), "r"(mapa(BAR(B_RECV + wgi), hr ^ 1)) : "memory");
                    }
                    kill<64>(ag);
                    F1_BLOCK(0, false) F1_BLOCK(1, false) F1_BLOCK(2, false) F1_BLOCK(3, false)
                    wg_wait<0>();
                    R_RELEASE(1);
                    kill<16>(H + 32);
                } while (((trips >> (++p)) & 1));
#pragma unroll
                for (int k = 0; k < 4; k++) lds4(H + 16 + 4 * k, hbuf + 16384 + w * 2048 + k * 512 + lane * 16);
                __syncwarp();
                if (lane == 0) asm volatile("mbarrier.arrive.shared::cluster.b64 _, [%0];" ::"r"(mapa(BAR(B_ACK2 + wgi), hr ^ 1)) : "memory");
                const uint32_t rem_h = mapa(hbuf + w * 2048 + lane * 16, hr ^ 1);
#define F1_LAST(b0)                                                                            \
    R_WAIT();                                                                                  \
    if (b0) { PP_WAIT() }                                                                      \
    { const uint64_t db = BASE64(0, HALF, R_ADJ);                                              \
    wg_fence();                                                                                \
    FOR7(mma_rs64<1, D64(0, t)>(al, AQ(A, b0, t), (b0) + t > 0, db));                          \
    FOR7(mma_rs64<1, D64(7168, t)>(al, AQ(A, (b0) + 1, t), 1, db)); }                          \
    wg_commit();                                                                               \
    if (b0) { PP_GO() }                                                                        \
    R_NEXT();
                float al[32];
                F1_LAST(0)
                mbar_wait(BAR(B_RECV + wgi), rcvph);
                rcvph ^= 1;
                mbar_wait(BAR(B_ACK2 + wgi), step >> 1);
                H_PUSH(32, 16384) H_PUSH(36, 16896)
                F1_LAST(2)
                H_PUSH(40, 17408) H_PUSH(44, 17920)
                wg_wait<1>();
                R_RELEASE(2);
                wg_wait<0>();
                R_RELEASE(1);
                uint32_t HP[56];
#pragma unroll
                for (int k = 0; k < 4; k++) lds4(H + 4 * k, sb + OFF_KVB + wgi * 8192 + w * 2048 + k * 512 + lane * 16);
#pragma unroll
                for (int t = 0; t < 8; t++) lds4(HP + 4 * t, hbuf + (t >> 2) * 8192 + w * 2048 + (t & 3) * 512 + lane * 16);
                F1_EPI(H + 48, 4, al)
                H_PUSH(48, 24576 - w * 1024) H_PUSH(52, 25088 - w * 1024)
                STAMP(7 + so);
                WSUM(84 + 7 * (step >> 1));
                float acc[28];
                const uint32_t roA = hr ? 256u : 0u, roB = hr ? (uint32_t)-1536 : 0u;
                const uint32_t rpA = hr ? 0u : 256u, rpB = hr ? 0u : (uint32_t)-1536;
                kill<24>(HP + 32);
                float res[28];
                uint32_t v0[14], v1[14];
                const uint4* ps = xp0 + sl * 512;
#define F2_OWN()                                                                               \
    R_WAIT();                                                                                  \
    { const uint64_t d0 = BASE128(0, 16, R_ADJ + roA), d1 = BASE128(0, 16, R_ADJ + roB);       \
    wg_fence();                                                                                \
    FOR14(mma_rs56<1, t * 128>(acc, H[4 * t], H[4 * t + 1], H[4 * t + 2], H[4 * t + 3], t > 0, t < 12 ? d0 : d1)); } \
    wg_commit();                                                                               \
    R_NEXT();
#define F2_PEER()                                                                              \
    R_WAIT();                                                                                  \
    PP_WAIT()                                                                                  \
    { const uint64_t d0 = BASE128(0, 16, R_ADJ + rpA), d1 = BASE128(0, 16, R_ADJ + rpB);       \
    wg_fence();                                                                                \
    FOR14(mma_rs56<1, t * 128>(acc, HP[4 * t], HP[4 * t + 1], HP[4 * t + 2], HP[4 * t + 3], 1, t < 12 ? d0 : d1)); } \
    wg_commit();                                                                               \
    PP_GO()                                                                                    \
    R_NEXT();
#pragma unroll 1
                for (int u = 0; u < 3; u++) {
                    kill<28>(acc);
                    F2_OWN()
                    if (u == 0) {
                        mbar_wait(BAR(B_RECV2 + wgi), step >> 1);
#pragma unroll
                        for (int k = 0; k < 4; k++) lds4(HP + 32 + 4 * k, hbuf + 16384 + w * 2048 + k * 512 + lane * 16);
                        lds4(HP + 48, hbuf + 24576 + w * 1024 + lane * 16);
                        lds4(HP + 52, hbuf + 25088 + w * 1024 + lane * 16);
                        asm volatile("" ::"r"(HP[48]), "r"(HP[52]) : "memory");
                        if (step == 1) PUSH_ACK();
                    }
                    F2_PEER()
                    wg_wait<1>();
                    R_RELEASE(2);
                    wg_wait<0>();
                    R_RELEASE(1);
                    uint32_t P[14];
#pragma unroll
                    for (int i = 0; i < 14; i++) P[i] = pack2(acc[2 * i], acc[2 * i + 1]);
                    send_slice<0>(xp0 + u * PLANE + (2 * ((pr + u + 1) & 3) + hr) * 512, lane, P, tag);
                    seq++;
                    if (lane == 0) st_word(cx(sl), seq);
                    STAMP(8 + u + so);
                }
                slice_load<PL(2)>(X, ps, lane);
                slice_load<PL(3)>(v0, ps, lane);
                slice_load<PL(4)>(v1, ps, lane);
                kill<28>(acc);
                F2_OWN()
                STAMP(64 + 8 * (step >> 1));
                slice_check<PL(3)>(v0, ps, lane, tag);
                slice_check<PL(4)>(v1, ps, lane, tag);
                x_fix(X, xbits);
#pragma unroll
                for (int i = 0; i < 14; i++) { res[2 * i] = bf_lo(X[i]) + (bf_lo(v0[i]) + bf_lo(v1[i])); res[2 * i + 1] = bf_hi(X[i]) + (bf_hi(v0[i]) + bf_hi(v1[i])); }
                STAMP(65 + 8 * (step >> 1));
                F2_PEER()
                STAMP(66 + 8 * (step >> 1));
                poll_cnt(cx(2 * ((pr + 1) & 3) + hr), seq);
                STAMP(67 + 8 * (step >> 1));
                slice_load<PL(5)>(v0, ps, lane);
                slice_check<PL(5)>(v0, ps, lane, tag);
#pragma unroll
                for (int i = 0; i < 14; i++) { res[2 * i] += bf_lo(v0[i]); res[2 * i + 1] += bf_hi(v0[i]); }
                STAMP(11 + so);
                wg_wait<0>();
                if (EARLYK >= 1) R_RELEASE(2);
                STAMP(12 + so);
                WSUM(85 + 7 * (step >> 1));
#pragma unroll
                for (int i = 0; i < 14; i++) X[i] = pack2(res[2 * i] + acc[2 * i], res[2 * i + 1] + acc[2 * i + 1]);
            }
        }
        {
            const int m = lane >> 3, rr = lane & 7;
            const uint32_t ob = hbuf + w * 2048, rowa = ob + (rr + 8 * (m & 1)) * 112 + (m >> 1) * 16;
#pragma unroll
            for (int j = 0; j < 3; j++) stsm4(rowa + 32 * j, X[4 * j], X[4 * j + 1], X[4 * j + 2], X[4 * j + 3]);
            asm volatile("stmatrix.sync.aligned.m8n8.x2.shared.b16 [%0], {%1,%2};" ::"r"(ob + (rr + 8 * (m & 1)) * 112 + 96), "r"(X[12]), "r"(X[13]) : "memory");
            fence_async();
            __syncwarp();
            if (lane == 0) {
                asm volatile("cp.async.bulk.tensor.2d.global.shared::cta.bulk_group [%0, {%2, %3}], [%1];" ::"l"(&maps.out), "r"(ob), "r"(56 * sl), "r"(tile * 128 + (tid >> 5) * 16) : "memory");
                asm volatile("cp.async.bulk.commit_group;" ::: "memory");
                asm volatile("cp.async.bulk.wait_group.read 0;" ::: "memory");
            }
        }
        STAMP(50);
        GSTAMP(61);
        PDUMP();
    }
}

typedef CUresult (*EncodeFn)(CUtensorMap*, CUtensorMapDataType, cuuint32_t, void*, const cuuint64_t*, const cuuint64_t*, const cuuint32_t*,
                             const cuuint32_t*, CUtensorMapInterleave, CUtensorMapSwizzle, CUtensorMapL2promotion, CUtensorMapFloatOOBfill);

static void make_map(EncodeFn enc, CUtensorMap* m, const void* p, uint64_t cols, uint64_t rows, uint32_t bc, uint32_t br, CUtensorMapSwizzle sw) {
    cuuint64_t gd[2] = {cols, rows};
    cuuint64_t gs[1] = {cols * 2};
    cuuint32_t bd[2] = {bc, br};
    cuuint32_t es[2] = {1, 1};
    enc(m, CU_TENSOR_MAP_DATA_TYPE_BFLOAT16, 2, const_cast<void*>(p), gd, gs, bd, es, CU_TENSOR_MAP_INTERLEAVE_NONE, sw,
        CU_TENSOR_MAP_L2_PROMOTION_L2_128B, CU_TENSOR_MAP_FLOAT_OOB_FILL_NONE);
}

extern "C" void kernel_launch(void* const* d_in, const int* in_sizes, int n_in, void* d_out, int out_size) {
    (void)in_sizes; (void)n_in; (void)out_size;
    static EncodeFn enc = nullptr;
    static Scratch* scratch = nullptr;
    if (!enc) {
        void* fn = nullptr;
        cudaDriverEntryPointQueryResult qr;
        cudaGetDriverEntryPoint("cuTensorMapEncodeTiled", &fn, cudaEnableDefault, &qr);
        enc = (EncodeFn)fn;
        cudaGetSymbolAddress((void**)&scratch, g_scratch);
        cudaFuncSetAttribute(fused_kernel, cudaFuncAttributeMaxDynamicSharedMemorySize, SMEM_BYTES);
    }
    Maps maps;
    {
        cuuint64_t gd[3] = {64, 2048, 7};
        cuuint64_t gs[2] = {896, 128};
        cuuint32_t bd[3] = {64, 32, 7};
        cuuint32_t es[3] = {1, 1, 1};
        enc(&maps.x, CU_TENSOR_MAP_DATA_TYPE_BFLOAT16, 3, d_in[0], gd, gs, bd, es, CU_TENSOR_MAP_INTERLEAVE_NONE, CU_TENSOR_MAP_SWIZZLE_128B,
            CU_TENSOR_MAP_L2_PROMOTION_L2_128B, CU_TENSOR_MAP_FLOAT_OOB_FILL_NONE);
    }
    make_map(enc, &maps.out, d_out, 448, 2048, 56, 16, CU_TENSOR_MAP_SWIZZLE_NONE);
    make_map(enc, &maps.qkv, d_in[1], 1344, 448, 64, 112, CU_TENSOR_MAP_SWIZZLE_128B);
    make_map(enc, &maps.wo, d_in[3], 448, 448, 64, 112, CU_TENSOR_MAP_SWIZZLE_128B);
    make_map(enc, &maps.wg, d_in[5], 1792, 448, 64, 112, CU_TENSOR_MAP_SWIZZLE_128B);
    make_map(enc, &maps.wu, d_in[6], 1792, 448, 64, 112, CU_TENSOR_MAP_SWIZZLE_128B);
    make_map(enc, &maps.wg32, d_in[5], 1792, 448, 32, 112, CU_TENSOR_MAP_SWIZZLE_64B);
    make_map(enc, &maps.wu32, d_in[6], 1792, 448, 32, 112, CU_TENSOR_MAP_SWIZZLE_64B);
    make_map(enc, &maps.wd, d_in[7], 448, 1792, 64, 112, CU_TENSOR_MAP_SWIZZLE_128B);
    fused_kernel<<<128, 384, SMEM_BYTES>>>(scratch, (const __nv_bfloat16*)d_in[0], (const __nv_bfloat16*)d_in[2], 7, (const __nv_bfloat16*)d_in[5],
                                           (const __nv_bfloat16*)d_in[6], (const __nv_bfloat16*)d_in[7], maps);
}
```

```cpp
#include <cuda_runtime.h>
#include <cuda.h>
#include <cuda_bf16.h>
#include <stdint.h>
#include <type_traits>

#define OT 2
#define F2PP 0
#define PPK 2
#define QE 1
#define OST 1
#define GB 1
#define B3T 6
#define CANARY 1
#define PP

namespace {

constexpr uint32_t STAGE = 28672, HALF = 14336;
constexpr int NST = 5;
constexpr uint32_t OFF_H = NST * STAGE;
constexpr uint32_t OFF_KVB = OFF_H + 2 * STAGE;
constexpr uint32_t OFF_WPHI = OFF_KVB + 16384;
constexpr uint32_t OFF_XR = OFF_WPHI + 7168;
constexpr uint32_t OFF_BAR = OFF_XR + 6144;
constexpr uint32_t SMEM_BYTES = OFF_BAR + 256 + 1536;
constexpr int B_EMPTY = NST, B_RECV = 2 * NST, B_RECV2 = B_RECV + 2, B_PACK = B_RECV2 + 2, B_GAT = B_PACK + 1, B_ACK = B_GAT + 8, B_ACK2 = B_ACK + 2, B_COUNT = B_ACK2 + 2;

constexpr int PACK = 14;

struct Maps { CUtensorMap x, qkv, wo, wg, wu, wg32, wu32, wd, out; };

}

constexpr int PLANE = 16 * 2 * 8 * 512;
struct Scratch {
    uint4 ex[6 * PLANE];
    uint4 kv1[8 * 16 * 16 * 32];
    uint4 kv2[8 * 512];
    uint32_t c1[8 * 8 * 16 * 32];
    uint32_t c2[8 * 4 * 16 * 32];
    uint32_t cw[8 * 32];
    uint4 wp[8 * 32 * (HALF / 16)];
};
__device__ __align__(1024) Scratch g_scratch;
#define g_ex (sc->ex)
#define g_kv1 (sc->kv1)
#define g_kv2 (sc->kv2)
#define g_c1 (sc->c1)
#define g_c2 (sc->c2)
#define g_cw (sc->cw)
#define g_wp (sc->wp)
#define STAMP(i)
#define GSTAMP(i)
#define PDUMP()
#define ASTAMP(i)

namespace {

__device__ __forceinline__ int fresh_tid() { int t; asm volatile("mov.u32 %0, %%tid.x;" : "=r"(t)); return t; }
__device__ __forceinline__ uint4* again(uint4* p) { asm volatile("" : "+l"(p)); return p; }
template <int N> __device__ __forceinline__ void kill(uint32_t* v) {
#pragma unroll
    for (int i = 0; i < N; i++) v[i] = 0;
}
template <int N> __device__ __forceinline__ void kill(float* v) {
#pragma unroll
    for (int i = 0; i < N; i++) v[i] = 0.f;
}
__device__ __forceinline__ uint32_t s2u(const void* p) { return (uint32_t)__cvta_generic_to_shared(p); }
__device__ __forceinline__ void mbar_init(uint32_t a, uint32_t c) { asm volatile("mbarrier.init.shared::cta.b64 [%0], %1;" ::"r"(a), "r"(c) : "memory"); }
__device__ __forceinline__ void mbar_expect_tx(uint32_t a, uint32_t b) { asm volatile("mbarrier.arrive.expect_tx.shared::cta.b64 _, [%0], %1;" ::"r"(a), "r"(b) : "memory"); }
__device__ __forceinline__ void mbar_arrive(uint32_t a) { asm volatile("mbarrier.arrive.shared::cta.b64 _, [%0];" ::"r"(a) : "memory"); }
#define GIVE_UP(id) "trap;\n"
#define SPIN_MAX "0x400000"
#define SPIN_TAIL(id) "add.u32 n, n, 1;\n setp.lt.u32 p, n, " SPIN_MAX ";\n @p bra.uni LP;\n" GIVE_UP(id) " DN:\n }"
__device__ __forceinline__ void mbar_wait(uint32_t a, uint32_t ph) {
    asm volatile("{ .reg .pred p; .reg .b32 n; mov.u32 n, 0;\n LP:\n"
                 "mbarrier.try_wait.parity.shared::cta.b64 p, [%0], %1;\n @p bra DN;\n"
                 "add.u32 n, n, 1;\n setp.lt.u32 p, n, " SPIN_MAX ";\n @p bra LP;\n"
                 GIVE_UP("")
                 " DN:\n }" ::"r"(a), "r"(ph) : "memory");
}
#define ELECT "{ .reg .pred e; elect.sync _|e, 0xffffffff; @e "
__device__ __forceinline__ void tma2d(uint32_t dst, const CUtensorMap* m, int c0, int c1, uint32_t bar) {
    asm volatile(ELECT "cp.async.bulk.tensor.2d.shared::cluster.global.mbarrier::complete_tx::bytes [%0], [%1, {%3, %4}], [%2]; }" ::"r"(dst), "l"(m), "r"(bar), "r"(c0), "r"(c1) : "memory");
}
__device__ __forceinline__ void tma3x(uint32_t dst, const CUtensorMap* m, int row, uint32_t bar) {
    asm volatile(ELECT "cp.async.bulk.tensor.3d.shared::cluster.global.mbarrier::complete_tx::bytes [%0], [%1, {0, %3, 0}], [%2]; }" ::"r"(dst), "l"(m), "r"(bar), "r"(row) : "memory");
}
template <int OFF>
__device__ __forceinline__ void ld_pkt(uint32_t* v, const uint4* p) {
    asm volatile("{ .reg .b128 t; ld.relaxed.gpu.global.b128 t, [%4+%5]; mov.b128 {%0,%1,%2,%3}, t; }" : "=r"(v[0]), "=r"(v[1]), "=r"(v[2]), "=r"(v[3]) : "l"(p), "n"(OFF * 16) : "memory");
}
template <int OFF>
__device__ __forceinline__ void st_pkt(uint4* p, uint32_t a, uint32_t b, uint32_t c, uint32_t d) {
    asm volatile("{ .reg .b128 t; mov.b128 t, {%1,%2,%3,%4}; st.relaxed.gpu.global.b128 [%0+%5], t; }" ::"l"(p), "r"(a), "r"(b), "r"(c), "r"(d), "n"(OFF * 16) : "memory");
}
__device__ __forceinline__ uint32_t pack2(float lo, float hi) {
    uint32_t r;
    asm("cvt.rn.bf16x2.f32 %0, %1, %2;" : "=r"(r) : "f"(hi), "f"(lo));
    return r;
}
__device__ __forceinline__ float bf_lo(uint32_t w) { return __uint_as_float(w << 16); }
__device__ __forceinline__ float bf_hi(uint32_t w) { return __uint_as_float(w & 0xffff0000u); }
__device__ __forceinline__ uint32_t settag(uint32_t w, uint32_t tag) { return (w & ~1u) | tag; }
__device__ __forceinline__ float ex2(float x) { float y; asm("ex2.approx.ftz.f32 %0, %1;" : "=f"(y) : "f"(x)); return y; }
__device__ __forceinline__ float rcp(float x) { float y; asm("rcp.approx.ftz.f32 %0, %1;" : "=f"(y) : "f"(x)); return y; }
__device__ __forceinline__ float tanh_hw(float x) { float y; asm("tanh.approx.f32 %0, %1;" : "=f"(y) : "f"(x)); return y; }
__device__ __forceinline__ void stsm4(uint32_t addr, uint32_t a, uint32_t b, uint32_t c, uint32_t d) {
    asm volatile("stmatrix.sync.aligned.m8n8.x4.shared.b16 [%0], {%1,%2,%3,%4};" ::"r"(addr), "r"(a), "r"(b), "r"(c), "r"(d) : "memory");
}
__device__ __forceinline__ void fence_async() { asm volatile("fence.proxy.async.shared::cta;" ::: "memory"); }
__device__ __forceinline__ void bar_sync(int id, int n) { asm volatile("bar.sync %0, %1;" ::"r"(id), "r"(n) : "memory"); }
__device__ __forceinline__ void bar_arrive(int id, int n) { asm volatile("bar.arrive %0, %1;" ::"r"(id), "r"(n) : "memory"); }
__device__ __forceinline__ void wg_fence() { asm volatile("wgmma.fence.sync.aligned;" ::: "memory"); }
__device__ __forceinline__ void wg_commit() { asm volatile("wgmma.commit_group.sync.aligned;" ::: "memory"); }
template <int N> __device__ __forceinline__ void wg_wait() { asm volatile("wgmma.wait_group.sync.aligned %0;" ::"n"(N) : "memory"); }

constexpr uint32_t SB0 = 1024;
__host__ __device__ constexpr uint32_t dlo(uint32_t off, uint32_t lbo) { return ((SB0 + off) >> 4) | ((lbo >> 4) << 16); }
__host__ __device__ constexpr uint32_t dhi(uint32_t sbo, uint32_t sw) { return (sbo >> 4) | (sw << 30); }
__device__ __forceinline__ uint64_t dbase(uint32_t lo, uint32_t hi) { uint64_t d; asm volatile("mov.b64 %0, {%1, %2};" : "=l"(d) : "r"(lo), "r"(hi)); return d; }
#define BASE128(off, lbo, adj) dbase(dlo(off, lbo) + (adj), dhi(1024, 1))
#define BASE64(off, lbo, adj) dbase(dlo(off, lbo) + (adj), dhi(512, 2))

#define ACC4(d, o) "+f"(d[o]), "+f"(d[o + 1]), "+f"(d[o + 2]), "+f"(d[o + 3])
#define ACC28(d) ACC4(d, 0), ACC4(d, 4), ACC4(d, 8), ACC4(d, 12), ACC4(d, 16), ACC4(d, 20), ACC4(d, 24)
#define ACC32(d, o) ACC4(d, o), ACC4(d, o + 4), ACC4(d, o + 8), ACC4(d, o + 12), ACC4(d, o + 16), ACC4(d, o + 20), ACC4(d, o + 24), ACC4(d, o + 28)

template <int TB, uint64_t D>
__device__ __forceinline__ void mma_rs56(float* d, uint32_t a0, uint32_t a1, uint32_t a2, uint32_t a3, int sd, uint64_t base) {
    asm volatile("{ .reg .pred p; .reg .b64 db; setp.ne.b32 p, %32, 0; add.u64 db, %33, %34;\n"
                 "wgmma.mma_async.sync.aligned.m64n56k16.f32.bf16.bf16 "
                 "{%0,%1,%2,%3,%4,%5,%6,%7,%8,%9,%10,%11,%12,%13,%14,%15,%16,%17,%18,%19,%20,%21,%22,%23,%24,%25,%26,%27}, "
                 "{%28,%29,%30,%31}, db, p, 1, 1, %35; }\n"
                 : ACC28(d)
                 : "r"(a0), "r"(a1), "r"(a2), "r"(a3), "r"(sd), "l"(base), "n"(D), "n"(TB));
}
template <int TB, uint64_t D>
__device__ __forceinline__ void mma_rs64(float* d, uint32_t a0, uint32_t a1, uint32_t a2, uint32_t a3, int sd, uint64_t base) {
    asm volatile("{ .reg .pred p; .reg .b64 db; setp.ne.b32 p, %36, 0; add.u64 db, %37, %38;\n"
                 "wgmma.mma_async.sync.aligned.m64n64k16.f32.bf16.bf16 "
                 "{%0,%1,%2,%3,%4,%5,%6,%7,%8,%9,%10,%11,%12,%13,%14,%15,%16,%17,%18,%19,%20,%21,%22,%23,%24,%25,%26,%27,%28,%29,%30,%31}, "
                 "{%32,%33,%34,%35}, db, p, 1, 1, %39; }\n"
                 : ACC32(d, 0)
                 : "r"(a0), "r"(a1), "r"(a2), "r"(a3), "r"(sd), "l"(base), "n"(D), "n"(TB));
}
template <int TB, uint64_t D>
__device__ __forceinline__ void mma_rs128(float* d, uint32_t a0, uint32_t a1, uint32_t a2, uint32_t a3, int sd, uint64_t base) {
    asm volatile("{ .reg .pred p; .reg .b64 db; setp.ne.b32 p, %68, 0; add.u64 db, %69, %70;\n"
                 "wgmma.mma_async.sync.aligned.m64n128k16.f32.bf16.bf16 "
                 "{%0,%1,%2,%3,%4,%5,%6,%7,%8,%9,%10,%11,%12,%13,%14,%15,%16,%17,%18,%19,%20,%21,%22,%23,%24,%25,%26,%27,%28,%29,%30,%31,%32,%33,%34,%35,%36,%37,%38,%39,%40,%41,%42,%43,%44,%45,%46,%47,%48,%49,%50,%51,%52,%53,%54,%55,%56,%57,%58,%59,%60,%61,%62,%63}, "
                 "{%64,%65,%66,%67}, db, p, 1, 1, %71; }\n"
                 : ACC32(d, 0), ACC32(d, 32)
                 : "r"(a0), "r"(a1), "r"(a2), "r"(a3), "r"(sd), "l"(base), "n"(D), "n"(TB));
}
template <uint64_t DA, uint64_t DB>
__device__ __forceinline__ void mma_ss56_tt(float* d, int sd, uint64_t ba, uint64_t bb) {
    asm volatile("{ .reg .pred p; .reg .b64 da, db; setp.ne.b32 p, %28, 0; add.u64 da, %29, %31; add.u64 db, %30, %32;\n"
                 "wgmma.mma_async.sync.aligned.m64n56k16.f32.bf16.bf16 "
                 "{%0,%1,%2,%3,%4,%5,%6,%7,%8,%9,%10,%11,%12,%13,%14,%15,%16,%17,%18,%19,%20,%21,%22,%23,%24,%25,%26,%27}, "
                 "da, db, p, 1, 1, 1, 1; }\n"
                 : ACC28(d)
                 : "r"(sd), "l"(ba), "l"(bb), "n"(DA), "n"(DB));
}
template <int... I> struct Seq {};
template <class F, int... I> __device__ __forceinline__ void static_for_impl(F&& f, Seq<I...>) { (f(std::integral_constant<int, I>{}), ...); }
#define FOR7(...) static_for_impl([&](auto T_) { constexpr int t = decltype(T_)::value; __VA_ARGS__; }, Seq<0, 1, 2, 3, 4, 5, 6>{})
#define FOR8(...) static_for_impl([&](auto T_) { constexpr int t = decltype(T_)::value; __VA_ARGS__; }, Seq<0, 1, 2, 3, 4, 5, 6, 7>{})
#define FOR14(...) static_for_impl([&](auto T_) { constexpr int t = decltype(T_)::value; __VA_ARGS__; }, Seq<0, 1, 2, 3, 4, 5, 6, 7, 8, 9, 10, 11, 12, 13>{})

__device__ __forceinline__ int kblk(int p, int b) { return b == 0 ? p : b - (b <= p); }
__host__ __device__ constexpr int krow(int t) { return t < 3 ? 16 * t : (t < 6 ? 56 + 16 * (t - 3) : 48); }
#define AQ(A, b, t) ((t) < 3 ? A[2 * (b)][4 * (t)] : (t) < 6 ? A[2 * (b) + 1][4 * ((t) - 3)] : A[2 * (b)][12]), \
                    ((t) < 3 ? A[2 * (b)][4 * (t) + 1] : (t) < 6 ? A[2 * (b) + 1][4 * ((t) - 3) + 1] : A[2 * (b)][13]), \
                    ((t) < 3 ? A[2 * (b)][4 * (t) + 2] : (t) < 6 ? A[2 * (b) + 1][4 * ((t) - 3) + 2] : A[2 * (b) + 1][12]), \
                    ((t) < 3 ? A[2 * (b)][4 * (t) + 3] : (t) < 6 ? A[2 * (b) + 1][4 * ((t) - 3) + 3] : A[2 * (b) + 1][13])
#define D128(off, t) ((uint64_t)(((off) + krow(t) * 128) >> 4) + ((uint64_t)((t) == 6 ? (7168 - 1024) >> 4 : 0) << 32))
#define D64(off, t) ((uint64_t)(((off) + krow(t) * 64) >> 4) + ((uint64_t)((t) == 6 ? (3584 - 512) >> 4 : 0) << 32))

#define PL(k) (((k) - 3) * PLANE)
__device__ __forceinline__ void st_word(uint32_t* p, uint32_t v) { asm volatile("st.relaxed.gpu.global.u32 [%0], %1;" ::"l"(p), "r"(v) : "memory"); }
__device__ __forceinline__ uint32_t ld_word(const uint32_t* p) { uint32_t v; asm volatile("ld.relaxed.gpu.global.u32 %0, [%1];" : "=r"(v) : "l"(p) : "memory"); return v; }
__device__ __forceinline__ void tag_slice(uint32_t* w, uint32_t tag) { w[0] = settag(w[0], tag); w[4] = settag(w[4], tag); w[8] = settag(w[8], tag); w[12] = settag(w[12], tag); }
template <int O>
__device__ __forceinline__ void send_slice(uint4* dst, int lane, const uint32_t* w) {
    st_pkt<O>(dst, w[0], w[1], w[2], w[3]);
    st_pkt<O + 32>(dst, w[4], w[5], w[6], w[7]);
    st_pkt<O + 64>(dst, w[8], w[9], w[10], w[11]);
    asm volatile("{ .reg .b64 t; mov.b64 t, {%1,%2}; st.relaxed.gpu.global.b64 [%0+%3], t; }" ::"l"((char*)dst - lane * 8), "r"(w[12]), "r"(w[13]), "n"(16 * (O + 96)) : "memory");
}
#define RW4(v, o) "+r"(v[o]), "+r"(v[(o) + 1]), "+r"(v[(o) + 2]), "+r"(v[(o) + 3])
#define RW2(v, o) "+r"(v[o]), "+r"(v[(o) + 1])
#define WR4(v, o) "=&r"(v[o]), "=&r"(v[(o) + 1]), "=&r"(v[(o) + 2]), "=&r"(v[(o) + 3])
#define LDP(a, b, c, d, addr, off) "ld.relaxed.gpu.global.b128 q, [" addr "+" off "];\n mov.b128 {" a "," b "," c "," d "}, q;\n"
#define LDH(a, b, addr, off) "ld.relaxed.gpu.global.b64 h, [" addr "+" off "];\n mov.b64 {" a "," b "}, h;\n"
#define VOTE_OK "and.b32 t, t, 1;\n setp.ne.u32 p, t, 0;\n vote.sync.any.pred p, p, 0xffffffff;\n @!p bra.uni DN;\n"
#define CHK(x, tag) "lop3.b32 t, " x ", " tag ", t, 0xBE;\n"
__device__ __forceinline__ void check_cnt(uint32_t v, const uint32_t* p, uint32_t target) {
    asm volatile("{ .reg .pred p; .reg .b32 n, t; mov.u32 n, 0; mov.u32 t, %2;\n LP:\n"
                 "sub.s32 t, t, %1;\n setp.lt.s32 p, t, 0;\n vote.sync.any.pred p, p, 0xffffffff;\n @!p bra.uni DN;\n ld.relaxed.gpu.global.u32 t, [%0];\n" SPIN_TAIL("7")
                 ::"l"(p), "r"(target), "r"(v) : "memory");
}
__device__ __forceinline__ void poll_cnt(const uint32_t* p, uint32_t target) {
    asm volatile("{ .reg .pred p; .reg .b32 n, t; mov.u32 n, 0;\n LP:\n"
                 "ld.relaxed.gpu.global.u32 t, [%0];\n sub.s32 t, t, %1;\n setp.lt.s32 p, t, 0;\n vote.sync.any.pred p, p, 0xffffffff;\n @!p bra.uni DN;\n" SPIN_TAIL("1")
                 ::"l"(p), "r"(target) : "memory");
}
template <int STR>
__device__ __forceinline__ void poll4_kv(uint32_t* v, const uint4* p, uint32_t tag) {
    asm volatile("{ .reg .pred p; .reg .b32 n, t; .reg .b128 q; mov.u32 n, 0;\n LP:\n"
                 LDP("%0", "%1", "%2", "%3", "%16", "0") LDP("%4", "%5", "%6", "%7", "%16", "%18")
                 LDP("%8", "%9", "%10", "%11", "%16", "%19") LDP("%12", "%13", "%14", "%15", "%16", "%20")
                 "xor.b32 t, %0, %17;\n" CHK("%4", "%17") CHK("%8", "%17") CHK("%12", "%17") VOTE_OK SPIN_TAIL("2")
                 : WR4(v, 0), WR4(v, 4), WR4(v, 8), WR4(v, 12)
                 : "l"(p), "r"(tag), "n"(16 * STR), "n"(32 * STR), "n"(48 * STR)
                 : "memory");
}
__device__ __forceinline__ void poll2_kv(uint32_t* v, const uint4* p, uint32_t tag) {
    asm volatile("{ .reg .pred p; .reg .b32 n, t; .reg .b128 q; mov.u32 n, 0;\n LP:\n"
                 LDP("%0", "%1", "%2", "%3", "%8", "0") LDP("%4", "%5", "%6", "%7", "%8", "128")
                 "xor.b32 t, %0, %9;\n" CHK("%4", "%9") VOTE_OK SPIN_TAIL("6")
                 : WR4(v, 0), WR4(v, 4) : "l"(p), "r"(tag) : "memory");
}
template <int B>
__device__ __forceinline__ void blk_load(uint32_t (&A)[8][14], const uint4* src, int lane) {
    ld_pkt<0>(&A[2 * B][0], src); ld_pkt<32>(&A[2 * B][4], src); ld_pkt<64>(&A[2 * B][8], src);
    ld_pkt<512>(&A[2 * B + 1][0], src); ld_pkt<544>(&A[2 * B + 1][4], src); ld_pkt<576>(&A[2 * B + 1][8], src);
    asm volatile("{ .reg .b64 h;\n" LDH("%0", "%1", "%4", "1536") LDH("%2", "%3", "%4", "9728") "}"
                 : "=&r"(A[2 * B][12]), "=&r"(A[2 * B][13]), "=&r"(A[2 * B + 1][12]), "=&r"(A[2 * B + 1][13])
                 : "l"((const char*)src - lane * 8) : "memory");
}
template <int B>
__device__ __forceinline__ void blk_check(uint32_t (&A)[8][14], const uint4* src, int lane, uint32_t tag) {
    asm volatile("{ .reg .pred p; .reg .b32 n, t; .reg .b128 q; .reg .b64 h, a8; mov.u32 n, 0;\n LP:\n"
                 "xor.b32 t, %0, %30;\n" CHK("%4", "%30") CHK("%8", "%30") CHK("%12", "%30") CHK("%16", "%30") CHK("%20", "%30") CHK("%24", "%30") CHK("%26", "%30") VOTE_OK
                 LDP("%0", "%1", "%2", "%3", "%28", "0") LDP("%4", "%5", "%6", "%7", "%28", "512") LDP("%8", "%9", "%10", "%11", "%28", "1024")
                 LDP("%12", "%13", "%14", "%15", "%28", "8192") LDP("%16", "%17", "%18", "%19", "%28", "8704") LDP("%20", "%21", "%22", "%23", "%28", "9216")
                 "mad.wide.s32 a8, %29, -8, %28;\n" LDH("%24", "%25", "a8", "1536") LDH("%26", "%27", "a8", "9728") SPIN_TAIL("3")
                 "\n and.b32 %0, %0, -2; and.b32 %4, %4, -2; and.b32 %8, %8, -2; and.b32 %12, %12, -2; and.b32 %16, %16, -2; and.b32 %20, %20, -2; and.b32 %24, %24, -2; and.b32 %26, %26, -2;"
                 : RW4(A[2 * B], 0), RW4(A[2 * B], 4), RW4(A[2 * B], 8), RW4(A[2 * B + 1], 0), RW4(A[2 * B + 1], 4), RW4(A[2 * B + 1], 8),
                   RW2(A[2 * B], 12), RW2(A[2 * B + 1], 12)
                 : "l"(src), "r"(lane), "r"(tag)
                 : "memory");
}
__device__ __forceinline__ void st_async4(uint32_t a, uint32_t x, uint32_t y, uint32_t z, uint32_t w, uint32_t bar) {
    asm volatile("st.async.weak.shared::cluster.mbarrier::complete_tx::bytes.v4.b32 [%0], {%1,%2,%3,%4}, [%5];" ::"r"(a), "r"(x), "r"(y), "r"(z), "r"(w), "r"(bar) : "memory");
}
__device__ __forceinline__ uint32_t mapa(uint32_t a, uint32_t cta) { uint32_t r; asm("mapa.shared::cluster.u32 %0, %1, %2;" : "=r"(r) : "r"(a), "r"(cta)); return r; }
__device__ __forceinline__ void stat_load(uint32_t* v, const uint4* p) { ld_pkt<0>(v, p); ld_pkt<512>(v + 4, p); }
__device__ __forceinline__ void stat_check(uint32_t* v, const uint4* p, uint32_t tag) {
    asm volatile("{ .reg .pred p; .reg .b32 n, t; .reg .b128 q; mov.u32 n, 0;\n LP:\n"
                 "xor.b32 t, %3, %9;\n" CHK("%7", "%9") VOTE_OK
                 LDP("%0", "%1", "%2", "%3", "%8", "0") LDP("%4", "%5", "%6", "%7", "%8", "8192") SPIN_TAIL("4")
                 : RW4(v, 0), RW4(v, 4) : "l"(p), "r"(tag) : "memory");
}
__device__ __forceinline__ uint32_t x_bits(const uint32_t* X) {
    uint32_t r;
    asm volatile("{ .reg .b32 a, b; prmt.b32 a, %1, %2, 0x0040; prmt.b32 b, %3, %4, 0x0040; prmt.b32 %0, a, b, 0x5410; }" : "=r"(r) : "r"(X[0]), "r"(X[4]), "r"(X[8]), "r"(X[12]));
    return r;
}
template <int O>
__device__ __forceinline__ void slice_load(uint32_t* v, const uint4* p, int lane) {
    ld_pkt<O>(v, p); ld_pkt<O + 32>(v + 4, p); ld_pkt<O + 64>(v + 8, p);
    asm volatile("{ .reg .b64 h;\n" LDH("%0", "%1", "%2", "%3") "}" : "=r"(v[12]), "=r"(v[13]) : "l"((const char*)p - lane * 8), "n"(16 * (O + 96)) : "memory");
}
template <int O>
__device__ __forceinline__ void slice_check(uint32_t* v, const uint4* p, int lane, uint32_t tag) {
    asm volatile("{ .reg .pred p; .reg .b32 n, t; .reg .b128 q; .reg .b64 h; mov.u32 n, 0;\n LP:\n"
                 "xor.b32 t, %0, %16;\n" CHK("%4", "%16") CHK("%8", "%16") CHK("%12", "%16") VOTE_OK
                 LDP("%0", "%1", "%2", "%3", "%14", "%17") LDP("%4", "%5", "%6", "%7", "%14", "%18") LDP("%8", "%9", "%10", "%11", "%14", "%19")
                 LDH("%12", "%13", "%15", "%20") SPIN_TAIL("5")
                 : RW4(v, 0), RW4(v, 4), RW4(v, 8), RW2(v, 12)
                 : "l"(p), "l"((const char*)p - lane * 8), "r"(tag), "n"(16 * O), "n"(16 * (O + 32)), "n"(16 * (O + 64)), "n"(16 * (O + 96))
                 : "memory");
}
__device__ __forceinline__ void x_fix(uint32_t* X, uint32_t bits) {
    X[0] = __byte_perm(X[0], bits, 0x3214); X[4] = __byte_perm(X[4], bits, 0x3215); X[8] = __byte_perm(X[8], bits, 0x3216); X[12] = __byte_perm(X[12], bits, 0x3217);
}
__device__ __forceinline__ void sts4(uint32_t a, uint32_t x, uint32_t y, uint32_t z, uint32_t w) {
    asm volatile("st.shared.v4.u32 [%0], {%1,%2,%3,%4};" ::"r"(a), "r"(x), "r"(y), "r"(z), "r"(w) : "memory");
}
__device__ __forceinline__ void lds4(uint32_t* v, uint32_t a) {
    asm volatile("ld.shared.v4.u32 {%0,%1,%2,%3}, [%4];" : "=r"(v[0]), "=r"(v[1]), "=r"(v[2]), "=r"(v[3]) : "r"(a) : "memory");
}
struct LnCoef { uint32_t hi, lo, sh; };
__device__ __forceinline__ LnCoef ln_coef(float sum, float sq) {
    sum += __shfl_xor_sync(0xffffffffu, sum, 1); sq += __shfl_xor_sync(0xffffffffu, sq, 1);
    sum += __shfl_xor_sync(0xffffffffu, sum, 2); sq += __shfl_xor_sync(0xffffffffu, sq, 2);
    const float mean = sum * (1.f / 448.f);
    const float var = fmaxf(fmaf(-mean, mean, sq * (1.f / 448.f)), 0.f);
    const float sc = rsqrtf(var + 1e-5f);
    LnCoef r;
    r.hi = pack2(sc, sc);
    const float lo = sc - bf_lo(r.hi), sh = -mean * sc;
    r.lo = pack2(lo, lo);
    r.sh = pack2(sh, sh);
    return r;
}
template <int B>
__device__ __forceinline__ void normalize(uint32_t (&A)[8][14], const LnCoef& c0, const LnCoef& c1) {
#pragma unroll
    for (int s = 2 * B; s < 2 * B + 2; s++)
#pragma unroll
        for (int i = 0; i < 14; i++) {
            const LnCoef& k = (i & 1) ? c1 : c0;
            asm("{ .reg .b32 t; fma.rn.bf16x2 t, %0, %2, %3; fma.rn.bf16x2 %0, %0, %1, t; }" : "+r"(A[s][i]) : "r"(k.hi), "r"(k.lo), "r"(k.sh));
        }
}
__device__ __forceinline__ void slice_stats(const uint32_t* w, float* st) {
    float a = 0.f, b = 0.f, p = 0.f, q = 0.f;
#pragma unroll
    for (int i = 0; i < 7; i++) {
        const float e0 = bf_lo(w[2 * i]), e1 = bf_hi(w[2 * i]), e2 = bf_lo(w[2 * i + 1]), e3 = bf_hi(w[2 * i + 1]);
        a += e0 + e1; b += e2 + e3;
        p = fmaf(e0, e0, p); p = fmaf(e1, e1, p); q = fmaf(e2, e2, q); q = fmaf(e3, e3, q);
    }
    a += __shfl_xor_sync(0xffffffffu, a, 1); p += __shfl_xor_sync(0xffffffffu, p, 1); b += __shfl_xor_sync(0xffffffffu, b, 1); q += __shfl_xor_sync(0xffffffffu, q, 1);
    a += __shfl_xor_sync(0xffffffffu, a, 2); p += __shfl_xor_sync(0xffffffffu, p, 2); b += __shfl_xor_sync(0xffffffffu, b, 2); q += __shfl_xor_sync(0xffffffffu, q, 2);
    st[0] = a; st[1] = p; st[2] = b; st[3] = q;
}
__device__ __forceinline__ void dual_softmax(const float* p, uint32_t* out) {
    constexpr float L = 1.4426950408889634f;
#pragma unroll
    for (int r = 0; r < 2; r++) {
        float mx = fmaxf(p[2 * r], p[2 * r + 1]), mn = fminf(p[2 * r], p[2 * r + 1]);
#pragma unroll
        for (int i = 1; i < 7; i++) {
            mx = fmaxf(mx, fmaxf(p[4 * i + 2 * r], p[4 * i + 2 * r + 1]));
            mn = fminf(mn, fminf(p[4 * i + 2 * r], p[4 * i + 2 * r + 1]));
        }
        mx = fmaxf(mx, __shfl_xor_sync(0xffffffffu, mx, 1));
        mn = fminf(mn, __shfl_xor_sync(0xffffffffu, mn, 1));
        const float bx = -mx * L, bn = mn * L;
        float ep[14], en[14], sp = 0.f, sn = 0.f;
#pragma unroll
        for (int i = 0; i < 14; i++) {
            const float v = p[4 * (i >> 1) + 2 * r + (i & 1)];
            ep[i] = ex2(fmaf(v, L, bx));
            en[i] = ex2(fmaf(v, -L, bn));
            sp += ep[i]; sn += en[i];
        }
        sp += __shfl_xor_sync(0xffffffffu, sp, 1);
        sn += __shfl_xor_sync(0xffffffffu, sn, 1);
        const float ip = rcp(sp), in = rcp(sn);
#pragma unroll
        for (int i = 0; i < 7; i++) {
            out[4 * i + r] = pack2(ep[2 * i] * ip, ep[2 * i + 1] * ip);
            out[4 * i + 2 + r] = pack2(en[2 * i] * in, en[2 * i + 1] * in);
        }
    }
}
__device__ __forceinline__ float geglu(float g, float u) {
    const float t = tanh_hw(g * fmaf(g * g, 0.7978845608028654f * 0.044715f, 0.7978845608028654f));
    const float gu = g * u;
    return fmaf(t, gu, gu);
}
__device__ __forceinline__ void phi_gemm(const float* t, float* p) {
    uint32_t w[14];
#pragma unroll
    for (int i = 0; i < 14; i++) w[i] = pack2(t[2 * i], t[2 * i + 1]);
    const uint64_t db = BASE128(OFF_WPHI, 16, 0);
    wg_fence();
    mma_rs56<0, 0>(p, w[0], w[1], w[2], w[3], 0, db);
    mma_rs56<0, 2>(p, w[4], w[5], w[6], w[7], 1, db);
    mma_rs56<0, 4>(p, w[8], w[9], w[10], w[11], 1, db);
    mma_rs56<0, 6>(p, w[12], w[13], 0u, 0u, 1, db);
    wg_commit();
    wg_wait<0>();
}

}

#define BAR(i) (bars + 8 * (i))
#define R_WAIT() mbar_wait(BAR(slot), ph)
#define WSUM(i)
#define R_ADJ (slot * (STAGE >> 4))
#define R_NEXT() do { eb2 = eb1; eb1 = BAR(B_EMPTY + slot); if (++slot == NST) { slot = 0; ph ^= 1; } } while (0)
#define R_RELEASE(k) do { if (lane == 0) mbar_arrive((k) == 1 ? eb1 : eb2); } while (0)
#define PUSH_BEGIN() do { mbar_wait(BAR(B_ACK + wgi), ackph); ackph ^= 1; } while (0)
#define PUSH_ACK() do { __syncwarp(); if (lane == 0) asm volatile("mbarrier.arrive.shared::cluster.b64 _, [%0];" ::"r"(mapa(BAR(B_ACK + wgi), hr ^ 1)) : "memory"); } while (0)

__global__ void __cluster_dims__(2, 1, 1) __launch_bounds__(384, 1)
fused_kernel(Scratch* const sc, const __nv_bfloat16* __restrict__ x_in, const __nv_bfloat16* __restrict__ w_phi, const int trips,
             const __nv_bfloat16* __restrict__ wg, const __nv_bfloat16* __restrict__ wu, const __nv_bfloat16* __restrict__ wd,
             const __grid_constant__ Maps maps) {
    extern __shared__ __align__(1024) unsigned char smem_raw[];
    const uint32_t sb = s2u(smem_raw);
    const uint32_t bars = sb + OFF_BAR;
    const int wgi = __shfl_sync(0xffffffffu, threadIdx.x >> 7, 0);
    const int hr = blockIdx.x & 1, ck = blockIdx.x >> 1;
    const int gp = (ck - 4) & 7, q7 = ((ck - 36) * 37) >> 8;
    const int pr = ck < 4 ? ck : (ck < 36 ? (ck - 4) >> 3 : q7);
    const int tile = ck < 4 ? 0 : (ck < 36 ? (gp ? 2 * gp : 1) : 2 * (ck - 36 - 7 * q7) + 3);
    const int sl = 2 * pr + hr;
    STAMP(0);
    GSTAMP(60);
    if (threadIdx.x == 256) {
#pragma unroll
        for (int i = 0; i < NST; i++) mbar_init(BAR(i), 1);
        asm volatile("fence.mbarrier_init.release.cluster;" ::: "memory");
    }
    if (threadIdx.x == 288) {
        if ((sb & 0x3FFFF) != SB0) asm volatile("trap;");
#pragma unroll
        for (int i = NST; i < B_COUNT; i++) mbar_init(BAR(i), i >= B_ACK ? 4 : (i < B_RECV ? 8 : 1));
        asm volatile("fence.mbarrier_init.release.cluster;" ::: "memory");
    }
    __syncwarp();
    asm volatile("barrier.cluster.arrive.relaxed.aligned;" ::: "memory");

    if (wgi == 2) {
        asm volatile("setmaxnreg.dec.sync.aligned.u32 40;");
        const int t128 = fresh_tid() & 127, w = __shfl_sync(0xffffffffu, t128 >> 5, 0), lane = t128 & 31;
        uint32_t kseq = 0;
        auto kv_job = [&](int layer) {
            const uint32_t tag = layer ^ 1;
            kseq++;
            bar_sync(7, 384);
            ASTAMP(0);
            if (tile < 15) {
                const int sq = lane >> 3, pk = 8 * w + (lane & (tile == 14 ? 3 : 7));
                uint32_t v[16];
                if (layer == 0 || CANARY) poll_cnt(g_c1 + ((sl * 8 + (w >> 1) * 4 + (tile >> 2)) * 16 + (lane & 15)) * 32, kseq);
                ASTAMP(1);
                poll4_kv<32>(v, g_kv1 + ((sl * 16 + tile) * 16 + 4 * sq) * 32 + pk, tag);
#pragma unroll
                for (int k = 0; k < 4; k++) {
                    float lo = (bf_lo(v[k]) + bf_lo(v[4 + k])) + (bf_lo(v[8 + k]) + bf_lo(v[12 + k]));
                    float hi = (bf_hi(v[k]) + bf_hi(v[4 + k])) + (bf_hi(v[8 + k]) + bf_hi(v[12 + k]));
                    lo += __shfl_xor_sync(0xffffffffu, lo, 8); hi += __shfl_xor_sync(0xffffffffu, hi, 8);
                    lo += __shfl_xor_sync(0xffffffffu, lo, 16); hi += __shfl_xor_sync(0xffffffffu, hi, 16);
                    v[k] = pack2(lo, hi);
                }
                if (sq == 0) st_pkt<0>(g_kv2 + sl * 512 + 32 * tile + pk, settag(v[0], tag), v[1], v[2], v[3]);
            }
            if (lane == 0) st_word(g_c2 + ((sl * 4 + w) * 16 + tile) * 32, kseq);
            ASTAMP(2);
            poll_cnt(g_c2 + ((sl * 4 + w) * 16 + (lane & 15)) * 32, kseq);
            bar_arrive(3, 384);
            ASTAMP(3);
        };
        if (w == 0) {
#pragma unroll 1
            for (int n = 0; n < NST; n++) {
                const uint32_t dst = sb + n * STAGE, fb = BAR(n);
                asm volatile(ELECT "mbarrier.arrive.expect_tx.shared::cta.b64 _, [%0], %1; }" ::"r"(fb), "r"(n < 2 ? 2 * STAGE : STAGE) : "memory");
                if (n < 2) {
                    tma3x(sb + OFF_H + n * STAGE, &maps.x, tile * 128 + n * 64, fb);
                    tma3x(dst, &maps.x, tile * 128 + n * 64 + 32, fb);
                } else {
                    if (n == 3) mbar_wait(BAR(1), 0);
                    const int ra = 112 * (n - 2);
                    tma2d(dst, &maps.qkv, 448 + 56 * sl, ra, fb);
                    tma2d(dst + HALF, &maps.qkv, 896 + 56 * sl, ra, fb);
                }
            }
            asm volatile("barrier.cluster.wait.aligned;" ::: "memory");
            const uint32_t cw_target = (ld_word(g_cw + sl * 32) & ~15u) + 16;
            uint32_t e0[2] = {0, 0}, e1[2] = {0, 0};
#pragma unroll 1
            for (int k = 0; k < 2; k++) {
                const int n = t128 + 32 * k;
                int m = n - 2 - (n > PACK);
                const bool packed = m >= 30 ? (m < 38 || m >= 52) : m >= 22;
                if (m >= 30) m -= 30;
                if (n == PACK) m = tile < 8 ? tile : tile + 14;
                const int rot = n < 8 ? 0 : pr;
                const int ra = 112 * kblk(rot, m & 3), rb = 112 * kblk(rot, 2 * m & 3), rc = 112 * kblk(rot, (2 * m + 1) & 3);
                int kind = 0, m0, m1, c0, c1, r0, r1;
                if (m < 4) { m0 = m1 = 1; c0 = 448 + 56 * sl; c1 = c0 + 448; r0 = r1 = ra; }
                else if (m < 8) { m0 = m1 = m < 6 ? 1 : 2; c0 = c1 = 56 * sl; r0 = rb; r1 = rc; }
                else if (m < 20) { m0 = 3; m1 = 4; c0 = c1 = 224 * sl + 32 * hr + 64 * ((m - 8) >> 2); r0 = r1 = ra; }
                else if (m < 22) { kind = 2; m0 = 5; m1 = 6; c0 = c1 = 224 * sl + (hr ? 0 : 192); r0 = rb; r1 = rc; }
                else { m0 = m1 = 7; c0 = c1 = 56 * (2 * ((pr + (m >> 1) - 10) & 3) + hr); r0 = 224 * (sl ^ (m & 1)); r1 = r0 + 112; }
                if (packed) { kind = 1; r0 = sl * 16 + (m < 8 ? m : m - 14); r1 = 0; }
                e0[0] = e0[1]; e1[0] = e1[1];
                e0[1] = kind | (m0 << 2) | (m1 << 6) | (c0 << 10) | (c1 << 21);
                e1[1] = r0 | (r1 << 16);
            }
            kseq = ld_word(g_c2 + (sl * 64 + tile) * 32);
            int slot = 0, ph = 0;
#pragma unroll 1
            for (int n = NST; n < 63; n++) {
                if (n == 11 || n == 42) kv_job(n == 42);
                const uint32_t w0 = __shfl_sync(0xffffffffu, n < 32 ? e0[0] : e0[1], n & 31), w1 = __shfl_sync(0xffffffffu, n < 32 ? e1[0] : e1[1], n & 31);
                const uint32_t dst = sb + slot * STAGE, fb = BAR(n == PACK ? B_PACK : slot);
                const CUtensorMap* m0 = &maps.x + ((w0 >> 2) & 15);
                const CUtensorMap* m1 = &maps.x + ((w0 >> 6) & 15);
                const int c0 = (w0 >> 10) & 2047, c1 = w0 >> 21, r0 = w1 & 0xffff, r1 = w1 >> 16;
                if (n == 25) {
                    int it = 0;
                    uint32_t v;
                    do { asm volatile("ld.acquire.gpu.global.u32 %0, [%1];" : "=r"(v) : "l"(g_cw + sl * 32) : "memory"); } while ((int)(v - cw_target) < 0 && ++it < 0x400000);
                    asm volatile("fence.proxy.async.global;" ::: "memory");
                    __syncwarp();
                }
                mbar_wait(BAR(B_EMPTY + slot), ph);
                __syncwarp();
                asm volatile(ELECT "mbarrier.arrive.expect_tx.shared::cta.b64 _, [%0], %1; }" ::"r"(fb), "r"(STAGE) : "memory");
                if ((w0 & 3) == 0) {
                    tma2d(dst, m0, c0, r0, fb);
                    tma2d(dst + HALF, m1, c1, r1, fb);
                } else if (w0 & 1) {
                    asm volatile(ELECT "cp.async.bulk.shared::cluster.global.mbarrier::complete_tx::bytes [%0], [%1], %2, [%3]; }"
                                 ::"r"(dst), "l"(reinterpret_cast<const char*>(g_wp) + (size_t)r0 * STAGE), "r"(STAGE), "r"(fb) : "memory");
                } else {
                    tma2d(dst, m0, c0, r0, fb); tma2d(dst + 7168, m0, c0, r1, fb);
                    tma2d(dst + HALF, m1, c0, r0, fb); tma2d(dst + HALF + 7168, m1, c0, r1, fb);
                }
                if (n == PACK) asm volatile(ELECT "mbarrier.arrive.shared::cta.b64 _, [%0]; }" ::"r"(BAR(slot)) : "memory");
                if (++slot == NST) { slot = 0; ph ^= 1; }
            }
        } else {
            const int j = t128 - 32;
            asm volatile("barrier.cluster.wait.aligned;" ::: "memory");
            uint2 wv[7];
            const int k = j < 56 ? j : 55, hh = k >= 28;
#pragma unroll
            for (int i = 0; i < 7; i++) wv[i] = __ldg(reinterpret_cast<const uint2*>(w_phi + (sl * 56 + k) * 28) + i);
#pragma unroll 1
            for (int i = j; i < 7168 / 16; i += 96) sts4(sb + OFF_WPHI + i * 16, 0, 0, 0, 0);
            bar_sync(5, 96);
            if (j < 56) {
                uint32_t a4[4];
#pragma unroll
                for (int q = 0; q < 4; q++) a4[q] = sb + OFF_WPHI + (4 * hh + q) * 128 + ((((k >> 3) ^ (4 * hh + q)) & 7) << 4) + (k & 7) * 2;
                FOR14(const uint32_t v = (t & 1) ? wv[t >> 1].y : wv[t >> 1].x;
                      asm volatile("{ .reg .b16 l, h; mov.b32 {l, h}, %2; st.shared.u16 [%0+%3], l; st.shared.u16 [%1+%3], h; }"
                                   ::"r"(a4[t >= 7 ? 2 : 0]), "r"(a4[t >= 7 ? 3 : 1]), "r"(v), "n"((t % 7) * 1024) : "memory"));
            }
            __syncwarp();
            fence_async();
            bar_arrive(1, 224);
            bar_arrive(9, 224);
            if (j == 0) {
                mbar_wait(BAR(2), 0);
                mbar_wait(BAR(2), 1);
                const int b = blockIdx.x;
                asm volatile("cp.async.bulk.prefetch.L2.global [%0], %1;" ::"l"(wg + b * 6272), "r"(12544) : "memory");
                asm volatile("cp.async.bulk.prefetch.L2.global [%0], %1;" ::"l"(wu + b * 6272), "r"(12544) : "memory");
                asm volatile("cp.async.bulk.prefetch.L2.global [%0], %1;" ::"l"(wd + b * 6272), "r"(12544) : "memory");
            }
            __syncwarp();
            kseq = ld_word(g_c2 + ((sl * 4 + w) * 16 + tile) * 32);
#pragma unroll 1
            for (int layer = 0; layer < 2; layer++) {
                kv_job(layer);
                if (layer == 0 && j == 0) {
                    constexpr int ps = PACK % NST;
                    mbar_wait(BAR(B_PACK), 0);
                    asm volatile("cp.async.bulk.global.shared::cta.bulk_group [%0], [%1], %2;"
                                 ::"l"(reinterpret_cast<char*>(g_wp) + (size_t)(sl * 16 + tile) * STAGE), "r"(sb + ps * STAGE), "r"(STAGE) : "memory");
                    asm volatile("cp.async.bulk.commit_group;" ::: "memory");
                    asm volatile("cp.async.bulk.wait_group.read 0;" ::: "memory");
                    asm volatile("mbarrier.arrive.shared::cta.b64 _, [%0], 8;" ::"r"(BAR(B_EMPTY + ps)) : "memory");
                    asm volatile("cp.async.bulk.wait_group 0;" ::: "memory");
                    asm volatile("fence.proxy.async.global;" ::: "memory");
                    asm volatile("red.release.gpu.global.add.u32 [%0], 1;" ::"l"(g_cw + sl * 32) : "memory");
                }
                __syncwarp();
            }
        }
    } else {
        asm volatile("setmaxnreg.inc.sync.aligned.u32 232;");
        const int tid = fresh_tid(), lane = tid & 31, t128 = tid & 127, g = lane >> 2, c = lane & 3;
        const int wu = __shfl_sync(0xffffffffu, tid >> 5, 0), w = wu & 3;
        uint4* const xp0 = g_ex + 3 * PLANE + ((tile * 2 + wgi) * 8) * 512 + w * 128 + lane;
        const uint32_t hbuf = sb + OFF_H + wgi * STAGE;
        uint32_t slot = 0, ph = 0, eb1 = 0, eb2 = 0, ackph = 0, rcvph = 0, gatph = 0, swp = 0;
        uint32_t ppid = 6;
#define cx(s) (reinterpret_cast<uint32_t*>(again(xp0) - lane + PL(1) + 112 + (s) * 512))
#define stp (again(xp0) - lane + g + PL(0) + 112)
        uint32_t seq = ld_word(cx(sl));
        uint32_t kseq = ld_word(g_c1 + ((sl * 8 + (tid >> 5)) * 16 + tile) * 32);
        uint32_t stag = ld_word(reinterpret_cast<const uint32_t*>(stp + sl * 512) + 3) & 1;
        asm volatile("barrier.cluster.wait.aligned;" ::: "memory");
        STAMP(1);
        uint32_t X[14];
        const uint32_t x0row = (w < 2 ? hbuf : sb + wgi * STAGE) + ((w & 1) * 16 + (lane & 15)) * 128;
        mbar_wait(BAR(wgi), 0);
        STAMP(51);
#pragma unroll
        for (int j = 0; j < 4; j++) {
            const int G = 7 * sl + min(2 * j + (lane >> 4), 6);
            uint32_t q2, q3;
            asm volatile("ldmatrix.sync.aligned.m8n8.x4.shared.b16 {%0,%1,%2,%3}, [%4];" : "=r"(X[4 * j]), "=r"(X[4 * j + 1]), "=r"(q2), "=r"(q3)
                         : "r"(x0row + (G >> 3) * 4096 + (((G ^ lane) & 7) << 4)) : "memory");
            if (j < 3) { X[(4 * j + 2) % 14] = q2; X[(4 * j + 3) % 14] = q3; }
        }
#define PUSH_SLICE(W)                                                                          \
    {                                                                                          \
        if (t128 == 0) mbar_expect_tx(BAR(B_RECV + wgi), 7168);                                \
        PUSH_BEGIN();                                                                          \
        const uint32_t ra = mapa(hbuf + 24576 + t128 * 16, hr ^ 1), rb = mapa(sb + OFF_XR + wgi * 3072, hr ^ 1), rbar = mapa(BAR(B_RECV + wgi), hr ^ 1); \
        st_async4(ra, W[0], W[1], W[2], W[3], rbar);                                           \
        st_async4(ra + 2048, W[4], W[5], W[6], W[7], rbar);                                    \
        st_async4(rb + t128 * 16, W[8], W[9], W[10], W[11], rbar);                             \
        asm volatile("st.async.weak.shared::cluster.mbarrier::complete_tx::bytes.v2.b32 [%0], {%1,%2}, [%3];" ::"r"(rb + 2048 + t128 * 8), "r"(W[12]), "r"(W[13]), "r"(rbar) : "memory"); \
    }
#define PULL_SLICE(W)                                                                          \
    {                                                                                          \
        uint32_t t0, t1;                                                                       \
        mbar_wait(BAR(B_RECV + wgi), rcvph);                                                   \
        rcvph ^= 1;                                                                            \
        lds4(&A[1][0], hbuf + 24576 + t128 * 16);                                              \
        lds4(&A[1][4], hbuf + 26624 + t128 * 16);                                              \
        lds4(&A[1][8], sb + OFF_XR + wgi * 3072 + t128 * 16);                                  \
        asm volatile("ld.shared.v2.u32 {%0,%1}, [%2];" : "=r"(t0), "=r"(t1) : "r"(sb + OFF_XR + wgi * 3072 + 2048 + t128 * 8) : "memory"); \
        _Pragma("unroll") for (int i = 0; i < 12; i++) A[0][i] = (i & 3) ? W[i] : W[i] & ~1u;  \
        A[1][0] &= ~1u; A[1][4] &= ~1u; A[1][8] &= ~1u;                                        \
        A[0][12] = (hr ? t0 : W[12]) & ~1u; A[0][13] = hr ? t1 : W[13];                        \
        A[1][12] = (hr ? W[12] : t0) & ~1u; A[1][13] = hr ? W[13] : t1;                        \
        asm volatile("" : RW4(A[0], 0), RW4(A[0], 4), RW4(A[0], 8), RW2(A[0], 12), RW4(A[1], 0), RW4(A[1], 4), RW4(A[1], 8), RW2(A[1], 12)); \
        swp = hr * 448;                                                                        \
    }
#define SWB(b, t, db, sh) ((b) == 0 && (t) < 6 ? ((t) < 3 ? db##p : db##m) : db)
#define DECL_DB(b, MK, lbo, sh) const uint64_t db = MK(0, lbo, R_ADJ), dbp = (b) == 0 ? MK(0, lbo, R_ADJ + (swp >> (sh))) : db, dbm = (b) == 0 ? MK(0, lbo, R_ADJ - (swp >> (sh))) : db;
#define EARLY 1
#define EARLYK 1
#define PPB 2
#define PP_WAIT() if (wgi == 1) { bar_sync(ppid, 256); ppid ^= 14; }
#define PP_GO() if (wgi == 0) { bar_arrive(ppid, 256); ppid ^= 14; }
#define GAT_ISSUE(base)                                                                        \
    {                                                                                          \
        const char* gs = reinterpret_cast<const char*>(g_ex + 3 * PLANE + (base) + (tile * 16 + wgi * 8 + 2 * kblk(pr, GB)) * 512 + w * 128); \
        const uint32_t gd = hbuf + w * 3584, gb = BAR(B_GAT + wu);                     \
        asm volatile("{ .reg .pred e; elect.sync _|e, 0xffffffff;\n"                           \
                     "@e mbarrier.arrive.expect_tx.shared::cta.b64 _, [%2], 3584;\n"           \
                     "@e cp.async.bulk.shared::cluster.global.mbarrier::complete_tx::bytes [%0], [%1], 1792, [%2];\n" \
                     "@e cp.async.bulk.shared::cluster.global.mbarrier::complete_tx::bytes [%0+1792], [%1+8192], 1792, [%2]; }" \
                     ::"r"(gd), "l"(gs), "r"(gb) : "memory");                                  \
        __syncwarp();                                                                          \
    }
#define GAT_FETCH()                                                                            \
    {                                                                                          \
        mbar_wait(BAR(B_GAT + wu), gatph);                                             \
        gatph ^= 1;                                                                            \
        const uint32_t ga = hbuf + w * 3584 + lane * 16;                                       \
        _Pragma("unroll") for (int s2 = 0; s2 < 2; s2++) {                                     \
            lds4(&A[2 * GB + s2][0], ga + s2 * 1792); lds4(&A[2 * GB + s2][4], ga + s2 * 1792 + 512); lds4(&A[2 * GB + s2][8], ga + s2 * 1792 + 1024); \
            asm volatile("ld.shared.v2.u32 {%0,%1}, [%2];" : "=r"(A[2 * GB + s2][12]), "=r"(A[2 * GB + s2][13]) : "r"(ga - lane * 8 + s2 * 1792 + 1536) : "memory"); \
        }                                                                                      \
    }
#define PT 3
#define PREP(b, t, remote)                                                                     \
    if constexpr ((b) < 3 && (t) == PT) {                                                      \
        wg_commit();                                                                           \
        STAMP(80 + 8 * (step & 1) + 2 * (b));                                                  \
        if constexpr (GB == 1 && (b) == 0) { if (remote) GAT_FETCH() }                         \
        if (remote) blk_check<((b) + 1) & 3>(A, BLK(xsrc, (b) + 1), lane, xtag);               \
        STAMP(81 + 8 * (step & 1) + 2 * (b));                                                  \
        if constexpr ((b) == 0) { if (remote) blk_load<3>(A, BLK(xsrc, 3), lane); }            \
        normalize<((b) + 1) & 3>(A, k0, k1);                                                   \
        asm volatile("" : RW4(A[(2 * (b) + 2) & 7], 0), RW4(A[(2 * (b) + 2) & 7], 4), RW4(A[(2 * (b) + 2) & 7], 8), RW2(A[(2 * (b) + 2) & 7], 12), \
                          RW4(A[(2 * (b) + 3) & 7], 0), RW4(A[(2 * (b) + 3) & 7], 4), RW4(A[(2 * (b) + 3) & 7], 8), RW2(A[(2 * (b) + 3) & 7], 12)); \
        wg_fence();                                                                            \
    }                                                                                          \
    if constexpr ((b) == 3 && ((t) == 0 || (t) == 6)) { STAMP(86 + 8 * (step & 1) + (t) / 6); }
#define BLK(base, b) ((base) + kblk(pr, b) * 1024)

#pragma unroll 1
        for (int step = 0; step < 4; step++) {
            const uint32_t tag = (step >> 1) ^ 1;
            const int so = (step >> 1) * 24 + (step & 1) * 12;
            (void)so;
            uint32_t A[8][14];
            uint4* const xsrc = xp0 + ((step & 1) ? PL(2) : PL(0));
            const uint32_t xtag = (step & 1) ? tag : ((seq >> 3) & 1) ^ 1;
            uint32_t xbits;
            {
                float st[4];
                slice_stats(X, st);
                stag ^= 1;
                xbits = x_bits(X);
                tag_slice(X, xtag);
                if (step) send_slice<0>(xsrc + sl * 512, lane, X);
                if (c == 0) st_pkt<0>(stp + sl * 512, __float_as_uint(st[0]), __float_as_uint(st[1]), __float_as_uint(st[2]), settag(__float_as_uint(st[3]), stag));
            }
            STAMP(2 + so);
            uint32_t sv[8];
            if (step == 0) {
                const int rr = lane & 7, hi = lane >> 4;
                const uint32_t rowa = (w < 2 ? hbuf : sb + wgi * STAGE) + ((w & 1) * 16 + (lane & 15)) * 128;
                uint32_t xr[8];
#pragma unroll
                for (int j = 0; j < 8; j++) xr[j] = rowa + ((((j + hi) ^ rr) & 7) << 4) + (j == 7 ? hi * 4096 : 0);
#define X0_BLOCK(b)                                                                            \
    FOR7(constexpr int G = 14 * (b) + (t < 3 ? 2 * t : (t < 6 ? 2 * t + 1 : 6));               \
         uint32_t q0, q1, q2, q3;                                                              \
         const uint32_t ad = t < 6 ? xr[G & 7] : rowa + ((G + 7 * hi) >> 3) * 4096 + ((((G + 7 * hi) ^ rr) & 7) << 4); \
         asm volatile("ldmatrix.sync.aligned.m8n8.x4.shared.b16 {%0,%1,%2,%3}, [%4+%5];" : "=r"(q0), "=r"(q1), "=r"(q2), "=r"(q3) \
                      : "r"(ad), "n"(t < 6 ? (G >> 3) * 4096 : 0) : "memory");                 \
         if (t < 3) { A[2 * (b)][4 * t] = q0; A[2 * (b)][4 * t + 1] = q1; A[2 * (b)][4 * t + 2] = q2; A[2 * (b)][4 * t + 3] = q3; } \
         else if (t < 6) { A[2 * (b) + 1][(4 * t - 12) & 15] = q0; A[2 * (b) + 1][((4 * t - 12) & 15) + 1] = q1; A[2 * (b) + 1][((4 * t - 12) & 15) + 2] = q2; A[2 * (b) + 1][((4 * t - 12) & 15) + 3] = q3; } \
         else { A[2 * (b)][12] = q0; A[2 * (b)][13] = q1; A[2 * (b) + 1][12] = q2; A[2 * (b) + 1][13] = q3; });
                X0_BLOCK(0) X0_BLOCK(1) X0_BLOCK(2) X0_BLOCK(3)
                mbar_wait(BAR(wgi ^ 1), 0);
                R_NEXT();
                R_NEXT();
                stat_load(sv, stp + c * 1024);
                stat_check(sv, stp + c * 1024, stag);
                STAMP(52 + step);
            } else {
                PUSH_SLICE(X)
                stat_load(sv, stp + c * 1024);
                kill<14>(A[2]); kill<14>(A[3]); kill<14>(A[4]); kill<14>(A[5]); kill<14>(A[6]); kill<14>(A[7]);
                PULL_SLICE(X)
                stat_check(sv, stp + c * 1024, stag);
                STAMP(52 + step);
                if (GB == 1) GAT_ISSUE((step & 1) ? PL(2) : PL(0))
                else blk_load<1>(A, BLK(xsrc, 1), lane);
            }
            LnCoef k0, k1;
            {
                k0 = ln_coef(__uint_as_float(sv[0]) + __uint_as_float(sv[4]), __uint_as_float(sv[1]) + __uint_as_float(sv[5]));
                k1 = ln_coef(__uint_as_float(sv[2]) + __uint_as_float(sv[6]), __uint_as_float(sv[3]) + __uint_as_float(sv[7]));
            }
            if (step) {
                if (GB == 2) GAT_ISSUE((step & 1) ? PL(2) : PL(0))
                else blk_load<2>(A, BLK(xsrc, 2), lane);
            }
            STAMP(3 + so);
            GSTAMP(76 + step);

            float ag[64];
#define F1_BLOCK(b, first)                                                                     \
    if ((first) && (b) < 2 && (b) >= EARLY) R_RELEASE(2);                                      \
    if (GB == 2 && (first) && (b) == 1 && step) GAT_FETCH()                                                       \
    if ((first) && (b) == 2) PUSH_ACK();                                                       \
    R_WAIT();                                                                                  \
    if ((b) == PPB) { PP_WAIT() }                                                              \
    { DECL_DB(b, BASE128, HALF, 0)                                                             \
    wg_fence();                                                                                \
    FOR7(mma_rs128<1, D128(0, t)>(ag, AQ(A, b, t), (b) + t > 0, SWB(b, t, db, 0));             \
         if constexpr (first) { PREP(b, t, step) }); }                                         \
    wg_commit();                                                                               \
    if ((b) == 3) { PP_GO() }                                                                  \
    if ((b) > 0) { wg_wait<1>(); R_RELEASE(1); }       \
    R_NEXT();
            if (step == 0) R_RELEASE(2);
            normalize<0>(A, k0, k1);
            F1_BLOCK(0, true) F1_BLOCK(1, true) F1_BLOCK(2, true) F1_BLOCK(3, true)
            if ((step & 1) == 0) {
                float tq[28];
                {
                    const float* const av = ag + 32;
                    wg_wait<0>();
                    R_RELEASE(1);
#pragma unroll
                    for (int i = 0; i < 28; i++) tq[i] = ag[i];
                    STAMP(4 + so);
                    WSUM(80 + 7 * (step >> 1));
                    const int m = lane >> 3, rr = lane & 7;
                    const uint32_t rowa = hbuf + 16384 + (w * 16 + rr + 8 * (m & 1)) * 128;
                    const uint32_t one = c == 0 ? 0x00003f80u : 0u;
                    if (step == 0) { bar_sync(wgi ? 9 : 1, 224); }
#pragma unroll
                    for (int j = 0; j < 4; j++) {
                        const uint32_t a = rowa + (((2 * j + (m >> 1)) ^ rr) << 4);
                        if (j < 3) stsm4(a, pack2(av[8 * j], av[8 * j + 1]), pack2(av[8 * j + 2], av[8 * j + 3]), pack2(av[8 * j + 4], av[8 * j + 5]), pack2(av[8 * j + 6], av[8 * j + 7]));
                        else stsm4(a, pack2(av[24], av[25]), pack2(av[26], av[27]), one, one);
                    }
                }
                uint32_t PH[28];
                int it = 1;
#pragma unroll 1
                do {
                    float pp[28];
                    phi_gemm(tq, pp);
                    dual_softmax(pp, PH);
                    if (((trips >> (it + 1)) & 1) == 0) continue;
                    {
                        const int m = lane >> 3, rr = lane & 7;
                        const uint32_t rowa = hbuf + (w * 16 + rr + 8 * (m & 1)) * 128;
#pragma unroll
                        for (int j = 0; j < 7; j++) {
                            const int cg = 2 * j + (m >> 1), hi = cg >= 7;
                            stsm4(rowa + hi * 8192 + (((cg - 7 * hi) ^ rr) << 4), PH[4 * j], PH[4 * j + 1], PH[4 * j + 2], PH[4 * j + 3]);
                        }
                    }
                    fence_async();
                    STAMP(5 + so);
#define Q_STAGE(b0)                                                                           \
    R_WAIT();                                                                                 \
    { DECL_DB(b0, BASE128, 16, 0)                                                             \
    wg_fence();                                                                               \
    FOR7(mma_rs56<1, D128(0, t)>(tq, AQ(A, b0, t), (b0) + t > 0, SWB(b0, t, db, 0)));         \
    FOR7(mma_rs56<1, D128(HALF, t)>(tq, AQ(A, (b0) + 1, t), 1, db)); }                        \
    wg_commit();                                                                              \
    R_NEXT();
                    if (QE && wgi == 0) { kill<28>(tq); Q_STAGE(0) Q_STAGE(2) wg_wait<1>(); R_RELEASE(2); wg_wait<0>(); R_RELEASE(1); }
                    bar_sync(2, 256);
                    float kv[28];
                    const uint64_t da = BASE128(OFF_H + 16384, 16, 0), dbk = BASE128(OFF_H, 16, wgi * 512);
                    wg_fence();
                    FOR8(constexpr uint64_t o = ((t >> 2) * STAGE + (t & 3) * 2048) >> 4; mma_ss56_tt<o, o>(kv, t > 0, da, dbk));
                    wg_commit();
                    wg_wait<0>();
#pragma unroll
                    for (int hf = 0; hf < 2; hf++) {
                        const int d = 16 * w + g + 8 * hf;
                        if ((d < 56 && (d >= 28) == (c >= 2)) || d == 56) {
                            const int item = d < 56 ? 2 * d + (c & 1) : 112 + c;
                            uint4* dst = g_kv1 + ((sl * 16 + (item >> 3)) * 16 + tile) * 32 + wgi * 16 + (item & 7);
#define KVW(i) pack2(kv[4 * (i) + 2 * hf], kv[4 * (i) + 2 * hf + 1])
                            st_pkt<0>(dst, settag(KVW(0), tag), KVW(1), KVW(2), KVW(3));
                            st_pkt<8>(dst, settag(KVW(4), tag), KVW(5), KVW(6), 0u);
                        }
                    }
                    __syncwarp();
                    kseq++;
                    if (lane == 0) st_word(g_c1 + ((sl * 8 + (tid >> 5)) * 16 + tile) * 32, kseq);
                    bar_arrive(7, 384);
                    STAMP(6 + so);
                    if (!QE || wgi == 1) { kill<28>(tq); Q_STAGE(0) Q_STAGE(2) wg_wait<1>(); R_RELEASE(2); wg_wait<0>(); R_RELEASE(1); }
                    STAMP(7 + so);
                    kill<28>(PH);
                } while (((trips >> (++it)) & 1));
                STAMP(8 + so);
                if (step) {
                    slice_load<PL(0)>(X, xp0 + sl * 512, lane);
                } else {
                    const uint32_t* xp = reinterpret_cast<const uint32_t*>(x_in + (size_t)(tile * 128 + wu * 16 + g) * 448 + 56 * sl + 2 * c);
#pragma unroll
                    for (int i = 0; i < 7; i++) { X[2 * i] = __ldg(xp + 4 * i); X[2 * i + 1] = __ldg(xp + 4 * i + 8 * 224); }
                }
                {
                    const int item = t128 < 112 ? t128 : 112 + (t128 & 3), d = item >> 1;
                    const int cc = t128 < 112 ? 2 * (d >= 28) + (item & 1) : item - 112;
                    const int r = t128 < 112 ? d : 56 + (cc >> 1) + 2 * ((t128 - 112) >> 2);
                    const uint32_t ra = sb + OFF_KVB + r * 128 + 4 * cc;
#pragma unroll
                    for (int i = 0; i < 7; i++) {
                        const int ii = i + 7 * wgi;
                        asm volatile("st.shared.u32 [%0], %1;" ::"r"((ra ^ 8) + (ii >> 3) * 8192 + (((ii ^ r) & 7) << 4)), "r"(0) : "memory");
                    }
                    uint32_t v[8];
                    bar_sync(3, 384);
                    poll2_kv(v, g_kv2 + sl * 512 + (item >> 3) * 32 + wgi * 16 + (item & 7), tag);
#pragma unroll
                    for (int i = 0; i < 7; i++) {
                        const int ii = i + 7 * wgi;
                        asm volatile("st.shared.u32 [%0], %1;" ::"r"(ra + (ii >> 3) * 8192 + (((ii ^ r) & 7) << 4)), "r"(v[i]) : "memory");
                    }
                    fence_async();
                    bar_sync(4, 256);
                }
                STAMP(9 + so);
                const uint4* const osrc = xp0 + PL(1);
                {
                    float nm[32];
                    const uint64_t db = BASE128(OFF_KVB, 16, 0);
                    wg_fence();
                    FOR7(mma_rs64<0, ((t >> 2) * 8192 + (t & 3) * 32) / 16>(nm, PH[4 * t], PH[4 * t + 1], PH[4 * t + 2], PH[4 * t + 3], t > 0, db));
                    wg_commit();
                    wg_wait<0>();
                    const float i00 = rcp(nm[28] + 1e-6f), i01 = rcp(nm[29] + 1e-6f), i10 = rcp(nm[30] + 1e-6f), i11 = rcp(nm[31] + 1e-6f);
                    const float m0 = c >= 2 ? i01 : i00, m1 = c >= 2 ? i11 : i10;
                    uint32_t O[14];
#pragma unroll
                    for (int i = 0; i < 7; i++) {
                        const float f0 = i < 3 ? i00 : (i > 3 ? i01 : m0), f1 = i < 3 ? i10 : (i > 3 ? i11 : m1);
                        O[2 * i] = pack2(nm[4 * i] * f0, nm[4 * i + 1] * f0);
                        O[2 * i + 1] = pack2(nm[4 * i + 2] * f1, nm[4 * i + 3] * f1);
                    }
                    if (OST) { PP_WAIT() }
                    tag_slice(O, tag);
                    send_slice<PL(1)>(xp0 + sl * 512, lane, O);
                    seq++;
                    if (lane == 0) st_word(cx(sl), seq);
                    STAMP(10 + so);
                    PUSH_SLICE(O)
                    if (OST == 1) { PP_GO() }
                    const uint32_t cv = ld_word(cx(lane & 7));
                    PULL_SLICE(O)
                    check_cnt(cv, cx(lane & 7), seq);
                    if (OST == 2) { PP_GO() }
                    STAMP(56 + (step >> 1));
                    GAT_ISSUE(PL(1))
                    blk_load<3 - GB>(A, BLK(osrc, 3 - GB), lane);
                }
                float ao[28];
#define WO_BLOCK(b)                                                                           \
    if ((b) > 0) blk_check<b>(A, BLK(osrc, b), lane, tag);                                    \
    if (((b) & 1) == 0) R_WAIT();                                                             \
    { DECL_DB(b, BASE128, 16, 0)                                                              \
    wg_fence();                                                                               \
    FOR7(mma_rs56<1, D128(((b) & 1) * HALF, t)>(ao, AQ(A, b, t), (b) + t > 0, SWB(b, t, db, 0))); } \
    wg_commit();                                                                              \
    if ((b) & 1) R_NEXT();
                WO_BLOCK(0)
                STAMP(11 + so);
                blk_load<3>(A, BLK(osrc, 3), lane);
                if (GB == 1) GAT_FETCH()
                WO_BLOCK(1)
                if (GB == 2) GAT_FETCH()
                WO_BLOCK(2)
                PUSH_ACK();
                WO_BLOCK(3)
                wg_wait<0>();
                if (EARLY >= 1) R_RELEASE(2);
                if (EARLY >= 2) R_RELEASE(1);
                STAMP(12 + so);
                WSUM(86 + 7 * (step >> 1));
                x_fix(X, xbits);
#pragma unroll
                for (int i = 0; i < 14; i++) X[i] = pack2(bf_lo(X[i]) + ao[2 * i], bf_hi(X[i]) + ao[2 * i + 1]);
            } else {
                uint32_t H[56];
#define F1_EPI(dst, ng, ag)                                                                    \
    _Pragma("unroll") for (int i = 0; i < 2 * (ng); i++)                                       \
        (dst)[i] = pack2(geglu(ag[2 * i], ag[4 * (ng) + 2 * i]), geglu(ag[2 * i + 1], ag[4 * (ng) + 2 * i + 1]));
#define H_PUSH(h0, off) st_async4(rem_h + (off), H[h0], H[(h0) + 1], H[(h0) + 2], H[(h0) + 3], mapa(BAR(B_RECV2 + wgi), hr ^ 1));
                if (t128 == 0) { mbar_expect_tx(BAR(B_RECV + wgi), 16384); mbar_expect_tx(BAR(B_RECV2 + wgi), 12288); }
                PUSH_BEGIN();
                wg_wait<0>();
                R_RELEASE(1);
                if (step == 1) R_NEXT();
                int p = 0;
#pragma unroll 1
                do {
                    STAMP(68 + p);
                    F1_EPI(H + 32, 8, ag)
                    STAMP(4 + p + so);
                    WSUM(81 + p + 7 * (step >> 1));
                    if (((trips >> (p + 1)) & 1) == 0) continue;
                    {
                        const uint32_t pk = (p ? hbuf + 16384 : sb + OFF_KVB + wgi * 8192) + w * 2048;
#pragma unroll
                        for (int k = 0; k < 4; k++) sts4(pk + k * 512 + lane * 16, H[32 + 4 * k], H[33 + 4 * k], H[34 + 4 * k], H[35 + 4 * k]);
                        fence_async();
                        __syncwarp();
                        asm volatile(ELECT "cp.async.bulk.shared::cluster.shared::cta.mbarrier::complete_tx::bytes [%0], [%1], 2048, [%2]; }"
                                     ::"r"(mapa(hbuf + p * 8192 + w * 2048, hr ^ 1)), "r"(pk), "r"(mapa(BAR(B_RECV + wgi), hr ^ 1)) : "memory");
                    }
                    kill<64>(ag);
                    F1_BLOCK(0, false) F1_BLOCK(1, false) F1_BLOCK(2, false) F1_BLOCK(3, false)
                    wg_wait<0>();
                    R_RELEASE(1);
                    kill<16>(H + 32);
                } while (((trips >> (++p)) & 1));
#pragma unroll
                for (int k = 0; k < 4; k++) lds4(H + 16 + 4 * k, hbuf + 16384 + w * 2048 + k * 512 + lane * 16);
                __syncwarp();
                if (lane == 0) asm volatile("mbarrier.arrive.shared::cluster.b64 _, [%0];" ::"r"(mapa(BAR(B_ACK2 + wgi), hr ^ 1)) : "memory");
                const uint32_t rem_h = mapa(hbuf + w * 2048 + lane * 16, hr ^ 1);
#define F1_LAST(b0)                                                                            \
    R_WAIT();                                                                                  \
    if (b0) { PP_WAIT() }                                                                      \
    { DECL_DB(b0, BASE64, HALF, 1)                                                             \
    wg_fence();                                                                                \
    FOR7(mma_rs64<1, D64(0, t)>(al, AQ(A, b0, t), (b0) + t > 0, SWB(b0, t, db, 1)));           \
    FOR7(mma_rs64<1, D64(7168, t)>(al, AQ(A, (b0) + 1, t), 1, db)); }                          \
    wg_commit();                                                                               \
    if (b0) { PP_GO() }                                                                        \
    R_NEXT();
                float al[32];
                F1_LAST(0)
                mbar_wait(BAR(B_RECV + wgi), rcvph);
                rcvph ^= 1;
                mbar_wait(BAR(B_ACK2 + wgi), step >> 1);
                H_PUSH(32, 16384) H_PUSH(36, 16896)
                F1_LAST(2)
                H_PUSH(40, 17408) H_PUSH(44, 17920)
                wg_wait<1>();
                R_RELEASE(2);
                wg_wait<0>();
                R_RELEASE(1);
                uint32_t HP[56];
#pragma unroll
                for (int k = 0; k < 4; k++) lds4(H + 4 * k, sb + OFF_KVB + wgi * 8192 + w * 2048 + k * 512 + lane * 16);
#pragma unroll
                for (int t = 0; t < 8; t++) lds4(HP + 4 * t, hbuf + (t >> 2) * 8192 + w * 2048 + (t & 3) * 512 + lane * 16);
                F1_EPI(H + 48, 4, al)
                H_PUSH(48, 24576 - w * 1024) H_PUSH(52, 25088 - w * 1024)
                STAMP(7 + so);
                WSUM(84 + 7 * (step >> 1));
                float acc[28];
                const uint32_t roA = hr ? 256u : 0u, roB = hr ? (uint32_t)-1536 : 0u;
                const uint32_t rpA = hr ? 0u : 256u, rpB = hr ? 0u : (uint32_t)-1536;
                float res[28];
                uint32_t v0[14], v1[14], P[14];
                const uint4* ps = xp0 + sl * 512;
#define F2_OWN_A()                                                                             \
    R_WAIT();                                                                                  \
    d0 = BASE128(0, 16, R_ADJ + roA); d1 = BASE128(0, 16, R_ADJ + roB);                        \
    wg_fence();                                                                                \
    FOR14(if constexpr (t < OT) mma_rs56<1, t * 128>(acc, H[4 * t], H[4 * t + 1], H[4 * t + 2], H[4 * t + 3], t > 0, d0)); \
    wg_commit();
#define F2_OWN_B()                                                                             \
    wg_fence();                                                                                \
    FOR14(if constexpr (t >= OT) mma_rs56<1, t * 128>(acc, H[4 * t], H[4 * t + 1], H[4 * t + 2], H[4 * t + 3], 1, t < 12 ? d0 : d1)); \
    wg_commit();                                                                               \
    R_NEXT();
#define F2_PEER()                                                                              \
    R_WAIT();                                                                                  \
    if (F2PP) { PP_WAIT() }                                                                    \
    d0 = BASE128(0, 16, R_ADJ + rpA); d1 = BASE128(0, 16, R_ADJ + rpB);                        \
    wg_fence();                                                                                \
    FOR14(mma_rs56<1, t * 128>(acc, HP[4 * t], HP[4 * t + 1], HP[4 * t + 2], HP[4 * t + 3], 1, t < 12 ? d0 : d1)); \
    wg_commit();                                                                               \
    if (F2PP) { PP_GO() }                                                                      \
    R_NEXT();
#define F2_TURN(u)                                                                             \
    wg_wait<1>();                                                                              \
    R_RELEASE(2);                                                                              \
    wg_wait<0>();                                                                              \
    R_RELEASE(1);                                                                              \
    _Pragma("unroll") for (int i = 0; i < 14; i++) P[i] = pack2(acc[2 * i], acc[2 * i + 1]);   \
    tag_slice(P, tag);                                                                         \
    asm volatile("" : RW4(P, 0), RW4(P, 4), RW4(P, 8), RW2(P, 12));                            \
    kill<28>(acc);                                                                             \
    F2_OWN_A()                                                                                 \
    if ((u) == 2) { slice_load<PL(3)>(v0, ps, lane); slice_load<PL(4)>(v1, ps, lane); } \
    send_slice<PL(3 + (u))>(xp0 + (2 * ((pr + (u) + 1) & 3) + hr) * 512, lane, P);             \
    seq++;                                                                                     \
    if (lane == 0) st_word(cx(sl), seq);                                                       \
    __syncwarp();                                                                              \
    STAMP(8 + (u) + so);                                                                       \
    F2_OWN_B()
                uint64_t d0, d1;
                F2_OWN_A()
                F2_OWN_B()
                mbar_wait(BAR(B_RECV2 + wgi), step >> 1);
#pragma unroll
                for (int k = 0; k < 4; k++) lds4(HP + 32 + 4 * k, hbuf + 16384 + w * 2048 + k * 512 + lane * 16);
                lds4(HP + 48, hbuf + 24576 + w * 1024 + lane * 16);
                lds4(HP + 52, hbuf + 25088 + w * 1024 + lane * 16);
                if (step == 1) PUSH_ACK();
                F2_PEER()
                F2_TURN(0)
                F2_PEER()
                F2_TURN(1)
                F2_PEER()
                F2_TURN(2)
                STAMP(64 + 8 * (step >> 1));
                slice_check<PL(3)>(v0, ps, lane, tag);
                slice_check<PL(4)>(v1, ps, lane, tag);
#pragma unroll
                for (int i = 0; i < 14; i++) { res[2 * i] = bf_lo(v0[i]) + bf_lo(v1[i]); res[2 * i + 1] = bf_hi(v0[i]) + bf_hi(v1[i]); }
                slice_load<PL(2)>(X, ps, lane);
                STAMP(65 + 8 * (step >> 1));
                F2_PEER()
                STAMP(66 + 8 * (step >> 1));
                poll_cnt(cx(2 * ((pr + 1) & 3) + hr), seq);
                STAMP(67 + 8 * (step >> 1));
                slice_load<PL(5)>(v0, ps, lane);
                x_fix(X, xbits);
                slice_check<PL(5)>(v0, ps, lane, tag);
#pragma unroll
                for (int i = 0; i < 14; i++) { res[2 * i] += bf_lo(v0[i]); res[2 * i + 1] += bf_hi(v0[i]); }
                STAMP(11 + so);
                wg_wait<0>();
                if (EARLYK >= 1) R_RELEASE(2);
                STAMP(12 + so);
                WSUM(85 + 7 * (step >> 1));
#pragma unroll
                for (int i = 0; i < 14; i++) X[i] = pack2(fmaf(res[2 * i] + acc[2 * i], 0.5f, bf_lo(X[i])), fmaf(res[2 * i + 1] + acc[2 * i + 1], 0.5f, bf_hi(X[i])));
            }
        }
        {
            const int m = lane >> 3, rr = lane & 7;
            const uint32_t ob = hbuf + w * 2048, rowa = ob + (rr + 8 * (m & 1)) * 112 + (m >> 1) * 16;
#pragma unroll
            for (int j = 0; j < 3; j++) stsm4(rowa + 32 * j, X[4 * j], X[4 * j + 1], X[4 * j + 2], X[4 * j + 3]);
            asm volatile("stmatrix.sync.aligned.m8n8.x2.shared.b16 [%0], {%1,%2};" ::"r"(ob + (rr + 8 * (m & 1)) * 112 + 96), "r"(X[12]), "r"(X[13]) : "memory");
            fence_async();
            __syncwarp();
            if (lane == 0) {
                asm volatile("cp.async.bulk.tensor.2d.global.shared::cta.bulk_group [%0, {%2, %3}], [%1];" ::"l"(&maps.out), "r"(ob), "r"(56 * sl), "r"(tile * 128 + (tid >> 5) * 16) : "memory");
                asm volatile("cp.async.bulk.commit_group;" ::: "memory");
                asm volatile("cp.async.bulk.wait_group.read 0;" ::: "memory");
            }
        }
        STAMP(50);
        GSTAMP(61);
        PDUMP();
    }
}

typedef CUresult (*EncodeFn)(CUtensorMap*, CUtensorMapDataType, cuuint32_t, void*, const cuuint64_t*, const cuuint64_t*, const cuuint32_t*,
                             const cuuint32_t*, CUtensorMapInterleave, CUtensorMapSwizzle, CUtensorMapL2promotion, CUtensorMapFloatOOBfill);

static void make_map(EncodeFn enc, CUtensorMap* m, const void* p, uint64_t cols, uint64_t rows, uint32_t bc, uint32_t br, CUtensorMapSwizzle sw) {
    cuuint64_t gd[2] = {cols, rows};
    cuuint64_t gs[1] = {cols * 2};
    cuuint32_t bd[2] = {bc, br};
    cuuint32_t es[2] = {1, 1};
    enc(m, CU_TENSOR_MAP_DATA_TYPE_BFLOAT16, 2, const_cast<void*>(p), gd, gs, bd, es, CU_TENSOR_MAP_INTERLEAVE_NONE, sw,
        CU_TENSOR_MAP_L2_PROMOTION_L2_128B, CU_TENSOR_MAP_FLOAT_OOB_FILL_NONE);
}

extern "C" void kernel_launch(void* const* d_in, const int* in_sizes, int n_in, void* d_out, int out_size) {
    (void)in_sizes; (void)n_in; (void)out_size;
    static EncodeFn enc = nullptr;
    static Scratch* scratch = nullptr;
    if (!enc) {
        void* fn = nullptr;
        cudaDriverEntryPointQueryResult qr;
        cudaGetDriverEntryPoint("cuTensorMapEncodeTiled", &fn, cudaEnableDefault, &qr);
        enc = (EncodeFn)fn;
        cudaGetSymbolAddress((void**)&scratch, g_scratch);
        cudaFuncSetAttribute(fused_kernel, cudaFuncAttributeMaxDynamicSharedMemorySize, SMEM_BYTES);
    }
    Maps maps;
    {
        cuuint64_t gd[3] = {64, 2048, 7};
        cuuint64_t gs[2] = {896, 128};
        cuuint32_t bd[3] = {64, 32, 7};
        cuuint32_t es[3] = {1, 1, 1};
        enc(&maps.x, CU_TENSOR_MAP_DATA_TYPE_BFLOAT16, 3, d_in[0], gd, gs, bd, es, CU_TENSOR_MAP_INTERLEAVE_NONE, CU_TENSOR_MAP_SWIZZLE_128B,
            CU_TENSOR_MAP_L2_PROMOTION_L2_128B, CU_TENSOR_MAP_FLOAT_OOB_FILL_NONE);
    }
    make_map(enc, &maps.out, d_out, 448, 2048, 56, 16, CU_TENSOR_MAP_SWIZZLE_NONE);
    make_map(enc, &maps.qkv, d_in[1], 1344, 448, 64, 112, CU_TENSOR_MAP_SWIZZLE_128B);
    make_map(enc, &maps.wo, d_in[3], 448, 448, 64, 112, CU_TENSOR_MAP_SWIZZLE_128B);
    make_map(enc, &maps.wg, d_in[5], 1792, 448, 64, 112, CU_TENSOR_MAP_SWIZZLE_128B);
    make_map(enc, &maps.wu, d_in[6], 1792, 448, 64, 112, CU_TENSOR_MAP_SWIZZLE_128B);
    make_map(enc, &maps.wg32, d_in[5], 1792, 448, 32, 112, CU_TENSOR_MAP_SWIZZLE_64B);
    make_map(enc, &maps.wu32, d_in[6], 1792, 448, 32, 112, CU_TENSOR_MAP_SWIZZLE_64B);
    make_map(enc, &maps.wd, d_in[7], 448, 1792, 64, 112, CU_TENSOR_MAP_SWIZZLE_128B);
    fused_kernel<<<128, 384, SMEM_BYTES>>>(scratch, (const __nv_bfloat16*)d_in[0], (const __nv_bfloat16*)d_in[2], 7, (const __nv_bfloat16*)d_in[5],
                                           (const __nv_bfloat16*)d_in[6], (const __nv_bfloat16*)d_in[7], maps);
}
```

```cpp
#include <cuda_runtime.h>
#include <cuda.h>
#include <cuda_bf16.h>
#include <stdint.h>
#include <type_traits>

#define ACAN 1
#define SPLIT0 1
#define AUXB 1
#define CAN2 0
#define OT 2
#define F2PP 0
#define PPK 2
#define QE 1
#define OST 1
#define GB 1
#define B3T 6
#define CANARY 1
#define PP

namespace {

constexpr uint32_t STAGE = 28672, HALF = 14336;
constexpr int NST = 5;
constexpr uint32_t OFF_H = NST * STAGE;
constexpr uint32_t OFF_KVB = OFF_H + 2 * STAGE;
constexpr uint32_t OFF_WPHI = OFF_KVB + 16384;
constexpr uint32_t OFF_XR = OFF_WPHI + 7168;
constexpr uint32_t OFF_BAR = OFF_XR + 6144;
constexpr uint32_t SMEM_BYTES = OFF_BAR + 256 + 1536;
constexpr int B_EMPTY = NST, B_RECV = 2 * NST, B_RECV2 = B_RECV + 2, B_PACK = B_RECV2 + 2, B_GAT = B_PACK + 1, B_ACK = B_GAT + 8, B_ACK2 = B_ACK + 2, B_COUNT = B_ACK2 + 2;

constexpr int PACK = 14;

struct Maps { CUtensorMap x, qkv, wo, wg, wu, wg32, wu32, wd, out; };

}

constexpr int PLANE = 16 * 2 * 8 * 512;
struct Scratch {
    uint4 ex[6 * PLANE];
    uint4 kv1[8 * 16 * 16 * 32];
    uint4 kv2[8 * 512];
    uint32_t c1[8 * 8 * 16 * 32];
    uint32_t c2[8 * 4 * 16 * 32];
    uint32_t cw[8 * 32];
    uint4 wp[8 * 32 * (HALF / 16)];
};
__device__ __align__(1024) Scratch g_scratch;
#define g_ex (sc->ex)
#define g_kv1 (sc->kv1)
#define g_kv2 (sc->kv2)
#define g_c1 (sc->c1)
#define g_c2 (sc->c2)
#define g_cw (sc->cw)
#define g_wp (sc->wp)
#define STAMP(i)
#define GSTAMP(i)
#define PDUMP()
#define ASTAMP(i)

namespace {

__device__ __forceinline__ int fresh_tid() { int t; asm volatile("mov.u32 %0, %%tid.x;" : "=r"(t)); return t; }
__device__ __forceinline__ uint4* again(uint4* p) { asm volatile("" : "+l"(p)); return p; }
template <int N> __device__ __forceinline__ void kill(uint32_t* v) {
#pragma unroll
    for (int i = 0; i < N; i++) v[i] = 0;
}
template <int N> __device__ __forceinline__ void kill(float* v) {
#pragma unroll
    for (int i = 0; i < N; i++) v[i] = 0.f;
}
__device__ __forceinline__ uint32_t s2u(const void* p) { return (uint32_t)__cvta_generic_to_shared(p); }
__device__ __forceinline__ void mbar_init(uint32_t a, uint32_t c) { asm volatile("mbarrier.init.shared::cta.b64 [%0], %1;" ::"r"(a), "r"(c) : "memory"); }
__device__ __forceinline__ void mbar_expect_tx(uint32_t a, uint32_t b) { asm volatile("mbarrier.arrive.expect_tx.shared::cta.b64 _, [%0], %1;" ::"r"(a), "r"(b) : "memory"); }
__device__ __forceinline__ void mbar_arrive(uint32_t a) { asm volatile("mbarrier.arrive.shared::cta.b64 _, [%0];" ::"r"(a) : "memory"); }
#define GIVE_UP(id) "trap;\n"
#define SPIN_MAX "0x400000"
#define SPIN_TAIL(id) "add.u32 n, n, 1;\n setp.lt.u32 p, n, " SPIN_MAX ";\n @p bra.uni LP;\n" GIVE_UP(id) " DN:\n }"
__device__ __forceinline__ void mbar_wait(uint32_t a, uint32_t ph) {
    asm volatile("{ .reg .pred p; .reg .b32 n; mov.u32 n, 0;\n LP:\n"
                 "mbarrier.try_wait.parity.shared::cta.b64 p, [%0], %1;\n @p bra DN;\n"
                 "add.u32 n, n, 1;\n setp.lt.u32 p, n, " SPIN_MAX ";\n @p bra LP;\n"
                 GIVE_UP("")
                 " DN:\n }" ::"r"(a), "r"(ph) : "memory");
}
#define ELECT "{ .reg .pred e; elect.sync _|e, 0xffffffff; @e "
__device__ __forceinline__ void tma2d(uint32_t dst, const CUtensorMap* m, int c0, int c1, uint32_t bar) {
    asm volatile(ELECT "cp.async.bulk.tensor.2d.shared::cluster.global.mbarrier::complete_tx::bytes [%0], [%1, {%3, %4}], [%2]; }" ::"r"(dst), "l"(m), "r"(bar), "r"(c0), "r"(c1) : "memory");
}
__device__ __forceinline__ void tma3x(uint32_t dst, const CUtensorMap* m, int row, uint32_t bar) {
    asm volatile(ELECT "cp.async.bulk.tensor.3d.shared::cluster.global.mbarrier::complete_tx::bytes [%0], [%1, {0, %3, 0}], [%2]; }" ::"r"(dst), "l"(m), "r"(bar), "r"(row) : "memory");
}
template <int OFF>
__device__ __forceinline__ void ld_pkt(uint32_t* v, const uint4* p) {
    asm volatile("{ .reg .b128 t; ld.relaxed.gpu.global.b128 t, [%4+%5]; mov.b128 {%0,%1,%2,%3}, t; }" : "=r"(v[0]), "=r"(v[1]), "=r"(v[2]), "=r"(v[3]) : "l"(p), "n"(OFF * 16) : "memory");
}
template <int OFF>
__device__ __forceinline__ void st_pkt(uint4* p, uint32_t a, uint32_t b, uint32_t c, uint32_t d) {
    asm volatile("{ .reg .b128 t; mov.b128 t, {%1,%2,%3,%4}; st.relaxed.gpu.global.b128 [%0+%5], t; }" ::"l"(p), "r"(a), "r"(b), "r"(c), "r"(d), "n"(OFF * 16) : "memory");
}
__device__ __forceinline__ uint32_t pack2(float lo, float hi) {
    uint32_t r;
    asm("cvt.rn.bf16x2.f32 %0, %1, %2;" : "=r"(r) : "f"(hi), "f"(lo));
    return r;
}
__device__ __forceinline__ float bf_lo(uint32_t w) { return __uint_as_float(w << 16); }
__device__ __forceinline__ float bf_hi(uint32_t w) { return __uint_as_float(w & 0xffff0000u); }
__device__ __forceinline__ uint32_t settag(uint32_t w, uint32_t tag) { return (w & ~1u) | tag; }
__device__ __forceinline__ float ex2(float x) { float y; asm("ex2.approx.ftz.f32 %0, %1;" : "=f"(y) : "f"(x)); return y; }
__device__ __forceinline__ float rcp(float x) { float y; asm("rcp.approx.ftz.f32 %0, %1;" : "=f"(y) : "f"(x)); return y; }
__device__ __forceinline__ float tanh_hw(float x) { float y; asm("tanh.approx.f32 %0, %1;" : "=f"(y) : "f"(x)); return y; }
__device__ __forceinline__ void stsm4(uint32_t addr, uint32_t a, uint32_t b, uint32_t c, uint32_t d) {
    asm volatile("stmatrix.sync.aligned.m8n8.x4.shared.b16 [%0], {%1,%2,%3,%4};" ::"r"(addr), "r"(a), "r"(b), "r"(c), "r"(d) : "memory");
}
__device__ __forceinline__ void fence_async() { asm volatile("fence.proxy.async.shared::cta;" ::: "memory"); }
__device__ __forceinline__ void bar_sync(int id, int n) { asm volatile("bar.sync %0, %1;" ::"r"(id), "r"(n) : "memory"); }
__device__ __forceinline__ void bar_arrive(int id, int n) { asm volatile("bar.arrive %0, %1;" ::"r"(id), "r"(n) : "memory"); }
__device__ __forceinline__ void wg_fence() { asm volatile("wgmma.fence.sync.aligned;" ::: "memory"); }
__device__ __forceinline__ void wg_commit() { asm volatile("wgmma.commit_group.sync.aligned;" ::: "memory"); }
template <int N> __device__ __forceinline__ void wg_wait() { asm volatile("wgmma.wait_group.sync.aligned %0;" ::"n"(N) : "memory"); }

constexpr uint32_t SB0 = 1024;
__host__ __device__ constexpr uint32_t dlo(uint32_t off, uint32_t lbo) { return ((SB0 + off) >> 4) | ((lbo >> 4) << 16); }
__host__ __device__ constexpr uint32_t dhi(uint32_t sbo, uint32_t sw) { return (sbo >> 4) | (sw << 30); }
__device__ __forceinline__ uint64_t dbase(uint32_t lo, uint32_t hi) { uint64_t d; asm volatile("mov.b64 %0, {%1, %2};" : "=l"(d) : "r"(lo), "r"(hi)); return d; }
#define BASE128(off, lbo, adj) dbase(dlo(off, lbo) + (adj), dhi(1024, 1))
#define BASE64(off, lbo, adj) dbase(dlo(off, lbo) + (adj), dhi(512, 2))

#define ACC4(d, o) "+f"(d[o]), "+f"(d[o + 1]), "+f"(d[o + 2]), "+f"(d[o + 3])
#define ACC28(d) ACC4(d, 0), ACC4(d, 4), ACC4(d, 8), ACC4(d, 12), ACC4(d, 16), ACC4(d, 20), ACC4(d, 24)
#define ACC32(d, o) ACC4(d, o), ACC4(d, o + 4), ACC4(d, o + 8), ACC4(d, o + 12), ACC4(d, o + 16), ACC4(d, o + 20), ACC4(d, o + 24), ACC4(d, o + 28)

template <int TB, uint64_t D>
__device__ __forceinline__ void mma_rs56(float* d, uint32_t a0, uint32_t a1, uint32_t a2, uint32_t a3, int sd, uint64_t base) {
    asm volatile("{ .reg .pred p; .reg .b64 db; setp.ne.b32 p, %32, 0; add.u64 db, %33, %34;\n"
                 "wgmma.mma_async.sync.aligned.m64n56k16.f32.bf16.bf16 "
                 "{%0,%1,%2,%3,%4,%5,%6,%7,%8,%9,%10,%11,%12,%13,%14,%15,%16,%17,%18,%19,%20,%21,%22,%23,%24,%25,%26,%27}, "
                 "{%28,%29,%30,%31}, db, p, 1, 1, %35; }\n"
                 : ACC28(d)
                 : "r"(a0), "r"(a1), "r"(a2), "r"(a3), "r"(sd), "l"(base), "n"(D), "n"(TB));
}
template <int TB, uint64_t D>
__device__ __forceinline__ void mma_rs64(float* d, uint32_t a0, uint32_t a1, uint32_t a2, uint32_t a3, int sd, uint64_t base) {
    asm volatile("{ .reg .pred p; .reg .b64 db; setp.ne.b32 p, %36, 0; add.u64 db, %37, %38;\n"
                 "wgmma.mma_async.sync.aligned.m64n64k16.f32.bf16.bf16 "
                 "{%0,%1,%2,%3,%4,%5,%6,%7,%8,%9,%10,%11,%12,%13,%14,%15,%16,%17,%18,%19,%20,%21,%22,%23,%24,%25,%26,%27,%28,%29,%30,%31}, "
                 "{%32,%33,%34,%35}, db, p, 1, 1, %39; }\n"
                 : ACC32(d, 0)
                 : "r"(a0), "r"(a1), "r"(a2), "r"(a3), "r"(sd), "l"(base), "n"(D), "n"(TB));
}
template <int TB, uint64_t D>
__device__ __forceinline__ void mma_rs128(float* d, uint32_t a0, uint32_t a1, uint32_t a2, uint32_t a3, int sd, uint64_t base) {
    asm volatile("{ .reg .pred p; .reg .b64 db; setp.ne.b32 p, %68, 0; add.u64 db, %69, %70;\n"
                 "wgmma.mma_async.sync.aligned.m64n128k16.f32.bf16.bf16 "
                 "{%0,%1,%2,%3,%4,%5,%6,%7,%8,%9,%10,%11,%12,%13,%14,%15,%16,%17,%18,%19,%20,%21,%22,%23,%24,%25,%26,%27,%28,%29,%30,%31,%32,%33,%34,%35,%36,%37,%38,%39,%40,%41,%42,%43,%44,%45,%46,%47,%48,%49,%50,%51,%52,%53,%54,%55,%56,%57,%58,%59,%60,%61,%62,%63}, "
                 "{%64,%65,%66,%67}, db, p, 1, 1, %71; }\n"
                 : ACC32(d, 0), ACC32(d, 32)
                 : "r"(a0), "r"(a1), "r"(a2), "r"(a3), "r"(sd), "l"(base), "n"(D), "n"(TB));
}
template <uint64_t DA, uint64_t DB>
__device__ __forceinline__ void mma_ss56_tt(float* d, int sd, uint64_t ba, uint64_t bb) {
    asm volatile("{ .reg .pred p; .reg .b64 da, db; setp.ne.b32 p, %28, 0; add.u64 da, %29, %31; add.u64 db, %30, %32;\n"
                 "wgmma.mma_async.sync.aligned.m64n56k16.f32.bf16.bf16 "
                 "{%0,%1,%2,%3,%4,%5,%6,%7,%8,%9,%10,%11,%12,%13,%14,%15,%16,%17,%18,%19,%20,%21,%22,%23,%24,%25,%26,%27}, "
                 "da, db, p, 1, 1, 1, 1; }\n"
                 : ACC28(d)
                 : "r"(sd), "l"(ba), "l"(bb), "n"(DA), "n"(DB));
}
template <int... I> struct Seq {};
template <class F, int... I> __device__ __forceinline__ void static_for_impl(F&& f, Seq<I...>) { (f(std::integral_constant<int, I>{}), ...); }
#define FOR7(...) static_for_impl([&](auto T_) { constexpr int t = decltype(T_)::value; __VA_ARGS__; }, Seq<0, 1, 2, 3, 4, 5, 6>{})
#define FOR8(...) static_for_impl([&](auto T_) { constexpr int t = decltype(T_)::value; __VA_ARGS__; }, Seq<0, 1, 2, 3, 4, 5, 6, 7>{})
#define FOR14(...) static_for_impl([&](auto T_) { constexpr int t = decltype(T_)::value; __VA_ARGS__; }, Seq<0, 1, 2, 3, 4, 5, 6, 7, 8, 9, 10, 11, 12, 13>{})

__device__ __forceinline__ int kblk(int p, int b) { return b == 0 ? p : b - (b <= p); }
__host__ __device__ constexpr int krow(int t) { return t < 3 ? 16 * t : (t < 6 ? 56 + 16 * (t - 3) : 48); }
#define AQ(A, b, t) ((t) < 3 ? A[2 * (b)][4 * (t)] : (t) < 6 ? A[2 * (b) + 1][4 * ((t) - 3)] : A[2 * (b)][12]), \
                    ((t) < 3 ? A[2 * (b)][4 * (t) + 1] : (t) < 6 ? A[2 * (b) + 1][4 * ((t) - 3) + 1] : A[2 * (b)][13]), \
                    ((t) < 3 ? A[2 * (b)][4 * (t) + 2] : (t) < 6 ? A[2 * (b) + 1][4 * ((t) - 3) + 2] : A[2 * (b) + 1][12]), \
                    ((t) < 3 ? A[2 * (b)][4 * (t) + 3] : (t) < 6 ? A[2 * (b) + 1][4 * ((t) - 3) + 3] : A[2 * (b) + 1][13])
#define D128(off, t) ((uint64_t)(((off) + krow(t) * 128) >> 4) + ((uint64_t)((t) == 6 ? (7168 - 1024) >> 4 : 0) << 32))
#define D64(off, t) ((uint64_t)(((off) + krow(t) * 64) >> 4) + ((uint64_t)((t) == 6 ? (3584 - 512) >> 4 : 0) << 32))

#define PL(k) (((k) - 3) * PLANE)
__device__ __forceinline__ void st_word(uint32_t* p, uint32_t v) { asm volatile("st.relaxed.gpu.global.u32 [%0], %1;" ::"l"(p), "r"(v) : "memory"); }
__device__ __forceinline__ uint32_t ld_word(const uint32_t* p) { uint32_t v; asm volatile("ld.relaxed.gpu.global.u32 %0, [%1];" : "=r"(v) : "l"(p) : "memory"); return v; }
__device__ __forceinline__ void tag_slice(uint32_t* w, uint32_t tag) { w[0] = settag(w[0], tag); w[4] = settag(w[4], tag); w[8] = settag(w[8], tag); w[12] = settag(w[12], tag); }
template <int O>
__device__ __forceinline__ void send_slice(uint4* dst, int lane, const uint32_t* w) {
    st_pkt<O>(dst, w[0], w[1], w[2], w[3]);
    st_pkt<O + 32>(dst, w[4], w[5], w[6], w[7]);
    st_pkt<O + 64>(dst, w[8], w[9], w[10], w[11]);
    asm volatile("{ .reg .b64 t; mov.b64 t, {%1,%2}; st.relaxed.gpu.global.b64 [%0+%3], t; }" ::"l"((char*)dst - lane * 8), "r"(w[12]), "r"(w[13]), "n"(16 * (O + 96)) : "memory");
}
#define RW4(v, o) "+r"(v[o]), "+r"(v[(o) + 1]), "+r"(v[(o) + 2]), "+r"(v[(o) + 3])
#define RW2(v, o) "+r"(v[o]), "+r"(v[(o) + 1])
#define WR4(v, o) "=&r"(v[o]), "=&r"(v[(o) + 1]), "=&r"(v[(o) + 2]), "=&r"(v[(o) + 3])
#define LDP(a, b, c, d, addr, off) "ld.relaxed.gpu.global.b128 q, [" addr "+" off "];\n mov.b128 {" a "," b "," c "," d "}, q;\n"
#define LDH(a, b, addr, off) "ld.relaxed.gpu.global.b64 h, [" addr "+" off "];\n mov.b64 {" a "," b "}, h;\n"
#define VOTE_OK "and.b32 t, t, 1;\n setp.ne.u32 p, t, 0;\n vote.sync.any.pred p, p, 0xffffffff;\n @!p bra.uni DN;\n"
#define CHK(x, tag) "lop3.b32 t, " x ", " tag ", t, 0xBE;\n"
__device__ __forceinline__ void check_cnt(uint32_t v, const uint32_t* p, uint32_t target) {
    asm volatile("{ .reg .pred p; .reg .b32 n, t; mov.u32 n, 0; mov.u32 t, %2;\n LP:\n"
                 "sub.s32 t, t, %1;\n setp.lt.s32 p, t, 0;\n vote.sync.any.pred p, p, 0xffffffff;\n @!p bra.uni DN;\n ld.relaxed.gpu.global.u32 t, [%0];\n" SPIN_TAIL("7")
                 ::"l"(p), "r"(target), "r"(v) : "memory");
}
__device__ __forceinline__ void poll_cnt(const uint32_t* p, uint32_t target) {
    asm volatile("{ .reg .pred p; .reg .b32 n, t; mov.u32 n, 0;\n LP:\n"
                 "ld.relaxed.gpu.global.u32 t, [%0];\n sub.s32 t, t, %1;\n setp.lt.s32 p, t, 0;\n vote.sync.any.pred p, p, 0xffffffff;\n @!p bra.uni DN;\n" SPIN_TAIL("1")
                 ::"l"(p), "r"(target) : "memory");
}
template <int STR>
__device__ __forceinline__ void poll4_kv(uint32_t* v, const uint4* p, uint32_t tag) {
    asm volatile("{ .reg .pred p; .reg .b32 n, t; .reg .b128 q; mov.u32 n, 0;\n LP:\n"
                 LDP("%0", "%1", "%2", "%3", "%16", "0") LDP("%4", "%5", "%6", "%7", "%16", "%18")
                 LDP("%8", "%9", "%10", "%11", "%16", "%19") LDP("%12", "%13", "%14", "%15", "%16", "%20")
                 "xor.b32 t, %0, %17;\n" CHK("%4", "%17") CHK("%8", "%17") CHK("%12", "%17") VOTE_OK SPIN_TAIL("2")
                 : WR4(v, 0), WR4(v, 4), WR4(v, 8), WR4(v, 12)
                 : "l"(p), "r"(tag), "n"(16 * STR), "n"(32 * STR), "n"(48 * STR)
                 : "memory");
}
__device__ __forceinline__ void poll2_kv(uint32_t* v, const uint4* p, uint32_t tag) {
    asm volatile("{ .reg .pred p; .reg .b32 n, t; .reg .b128 q; mov.u32 n, 0;\n LP:\n"
                 LDP("%0", "%1", "%2", "%3", "%8", "0") LDP("%4", "%5", "%6", "%7", "%8", "128")
                 "xor.b32 t, %0, %9;\n" CHK("%4", "%9") VOTE_OK SPIN_TAIL("6")
                 : WR4(v, 0), WR4(v, 4) : "l"(p), "r"(tag) : "memory");
}
template <int B>
__device__ __forceinline__ void blk_load(uint32_t (&A)[8][14], const uint4* src, int lane) {
    ld_pkt<0>(&A[2 * B][0], src); ld_pkt<32>(&A[2 * B][4], src); ld_pkt<64>(&A[2 * B][8], src);
    ld_pkt<512>(&A[2 * B + 1][0], src); ld_pkt<544>(&A[2 * B + 1][4], src); ld_pkt<576>(&A[2 * B + 1][8], src);
    asm volatile("{ .reg .b64 h;\n" LDH("%0", "%1", "%4", "1536") LDH("%2", "%3", "%4", "9728") "}"
                 : "=&r"(A[2 * B][12]), "=&r"(A[2 * B][13]), "=&r"(A[2 * B + 1][12]), "=&r"(A[2 * B + 1][13])
                 : "l"((const char*)src - lane * 8) : "memory");
}
template <int B>
__device__ __forceinline__ void blk_check(uint32_t (&A)[8][14], const uint4* src, int lane, uint32_t tag) {
    asm volatile("{ .reg .pred p; .reg .b32 n, t; .reg .b128 q; .reg .b64 h, a8; mov.u32 n, 0;\n LP:\n"
                 "xor.b32 t, %0, %30;\n" CHK("%4", "%30") CHK("%8", "%30") CHK("%12", "%30") CHK("%16", "%30") CHK("%20", "%30") CHK("%24", "%30") CHK("%26", "%30") VOTE_OK
                 LDP("%0", "%1", "%2", "%3", "%28", "0") LDP("%4", "%5", "%6", "%7", "%28", "512") LDP("%8", "%9", "%10", "%11", "%28", "1024")
                 LDP("%12", "%13", "%14", "%15", "%28", "8192") LDP("%16", "%17", "%18", "%19", "%28", "8704") LDP("%20", "%21", "%22", "%23", "%28", "9216")
                 "mad.wide.s32 a8, %29, -8, %28;\n" LDH("%24", "%25", "a8", "1536") LDH("%26", "%27", "a8", "9728") SPIN_TAIL("3")
                 "\n and.b32 %0, %0, -2; and.b32 %4, %4, -2; and.b32 %8, %8, -2; and.b32 %12, %12, -2; and.b32 %16, %16, -2; and.b32 %20, %20, -2; and.b32 %24, %24, -2; and.b32 %26, %26, -2;"
                 : RW4(A[2 * B], 0), RW4(A[2 * B], 4), RW4(A[2 * B], 8), RW4(A[2 * B + 1], 0), RW4(A[2 * B + 1], 4), RW4(A[2 * B + 1], 8),
                   RW2(A[2 * B], 12), RW2(A[2 * B + 1], 12)
                 : "l"(src), "r"(lane), "r"(tag)
                 : "memory");
}
__device__ __forceinline__ void st_async4(uint32_t a, uint32_t x, uint32_t y, uint32_t z, uint32_t w, uint32_t bar) {
    asm volatile("st.async.weak.shared::cluster.mbarrier::complete_tx::bytes.v4.b32 [%0], {%1,%2,%3,%4}, [%5];" ::"r"(a), "r"(x), "r"(y), "r"(z), "r"(w), "r"(bar) : "memory");
}
__device__ __forceinline__ uint32_t mapa(uint32_t a, uint32_t cta) { uint32_t r; asm("mapa.shared::cluster.u32 %0, %1, %2;" : "=r"(r) : "r"(a), "r"(cta)); return r; }
__device__ __forceinline__ void stat_load(uint32_t* v, const uint4* p) { ld_pkt<0>(v, p); ld_pkt<512>(v + 4, p); }
__device__ __forceinline__ void stat_check(uint32_t* v, const uint4* p, uint32_t tag) {
    asm volatile("{ .reg .pred p; .reg .b32 n, t; .reg .b128 q; mov.u32 n, 0;\n LP:\n"
                 "xor.b32 t, %3, %9;\n" CHK("%7", "%9") VOTE_OK
                 LDP("%0", "%1", "%2", "%3", "%8", "0") LDP("%4", "%5", "%6", "%7", "%8", "8192") SPIN_TAIL("4")
                 : RW4(v, 0), RW4(v, 4) : "l"(p), "r"(tag) : "memory");
}
__device__ __forceinline__ uint32_t x_bits(const uint32_t* X) {
    uint32_t r;
    asm volatile("{ .reg .b32 a, b; prmt.b32 a, %1, %2, 0x0040; prmt.b32 b, %3, %4, 0x0040; prmt.b32 %0, a, b, 0x5410; }" : "=r"(r) : "r"(X[0]), "r"(X[4]), "r"(X[8]), "r"(X[12]));
    return r;
}
template <int O>
__device__ __forceinline__ void slice_load(uint32_t* v, const uint4* p, int lane) {
    ld_pkt<O>(v, p); ld_pkt<O + 32>(v + 4, p); ld_pkt<O + 64>(v + 8, p);
    asm volatile("{ .reg .b64 h;\n" LDH("%0", "%1", "%2", "%3") "}" : "=r"(v[12]), "=r"(v[13]) : "l"((const char*)p - lane * 8), "n"(16 * (O + 96)) : "memory");
}
template <int O>
__device__ __forceinline__ void slice_check(uint32_t* v, const uint4* p, int lane, uint32_t tag) {
    asm volatile("{ .reg .pred p; .reg .b32 n, t; .reg .b128 q; .reg .b64 h; mov.u32 n, 0;\n LP:\n"
                 "xor.b32 t, %0, %16;\n" CHK("%4", "%16") CHK("%8", "%16") CHK("%12", "%16") VOTE_OK
                 LDP("%0", "%1", "%2", "%3", "%14", "%17") LDP("%4", "%5", "%6", "%7", "%14", "%18") LDP("%8", "%9", "%10", "%11", "%14", "%19")
                 LDH("%12", "%13", "%15", "%20") SPIN_TAIL("5")
                 : RW4(v, 0), RW4(v, 4), RW4(v, 8), RW2(v, 12)
                 : "l"(p), "l"((const char*)p - lane * 8), "r"(tag), "n"(16 * O), "n"(16 * (O + 32)), "n"(16 * (O + 64)), "n"(16 * (O + 96))
                 : "memory");
}
__device__ __forceinline__ void x_fix(uint32_t* X, uint32_t bits) {
    X[0] = __byte_perm(X[0], bits, 0x3214); X[4] = __byte_perm(X[4], bits, 0x3215); X[8] = __byte_perm(X[8], bits, 0x3216); X[12] = __byte_perm(X[12], bits, 0x3217);
}
__device__ __forceinline__ void sts4(uint32_t a, uint32_t x, uint32_t y, uint32_t z, uint32_t w) {
    asm volatile("st.shared.v4.u32 [%0], {%1,%2,%3,%4};" ::"r"(a), "r"(x), "r"(y), "r"(z), "r"(w) : "memory");
}
__device__ __forceinline__ void lds4(uint32_t* v, uint32_t a) {
    asm volatile("ld.shared.v4.u32 {%0,%1,%2,%3}, [%4];" : "=r"(v[0]), "=r"(v[1]), "=r"(v[2]), "=r"(v[3]) : "r"(a) : "memory");
}
struct LnCoef { uint32_t hi, lo, sh; };
__device__ __forceinline__ LnCoef ln_coef(float sum, float sq) {
    sum += __shfl_xor_sync(0xffffffffu, sum, 1); sq += __shfl_xor_sync(0xffffffffu, sq, 1);
    sum += __shfl_xor_sync(0xffffffffu, sum, 2); sq += __shfl_xor_sync(0xffffffffu, sq, 2);
    const float mean = sum * (1.f / 448.f);
    const float var = fmaxf(fmaf(-mean, mean, sq * (1.f / 448.f)), 0.f);
    const float sc = rsqrtf(var + 1e-5f);
    LnCoef r;
    r.hi = pack2(sc, sc);
    const float lo = sc - bf_lo(r.hi), sh = -mean * sc;
    r.lo = pack2(lo, lo);
    r.sh = pack2(sh, sh);
    return r;
}
template <int B>
__device__ __forceinline__ void normalize(uint32_t (&A)[8][14], const LnCoef& c0, const LnCoef& c1) {
#pragma unroll
    for (int s = 2 * B; s < 2 * B + 2; s++)
#pragma unroll
        for (int i = 0; i < 14; i++) {
            const LnCoef& k = (i & 1) ? c1 : c0;
            asm("{ .reg .b32 t; fma.rn.bf16x2 t, %0, %2, %3; fma.rn.bf16x2 %0, %0, %1, t; }" : "+r"(A[s][i]) : "r"(k.hi), "r"(k.lo), "r"(k.sh));
        }
}
__device__ __forceinline__ void slice_stats(const uint32_t* w, float* st) {
    float a = 0.f, b = 0.f, p = 0.f, q = 0.f;
#pragma unroll
    for (int i = 0; i < 7; i++) {
        const float e0 = bf_lo(w[2 * i]), e1 = bf_hi(w[2 * i]), e2 = bf_lo(w[2 * i + 1]), e3 = bf_hi(w[2 * i + 1]);
        a += e0 + e1; b += e2 + e3;
        p = fmaf(e0, e0, p); p = fmaf(e1, e1, p); q = fmaf(e2, e2, q); q = fmaf(e3, e3, q);
    }
    a += __shfl_xor_sync(0xffffffffu, a, 1); p += __shfl_xor_sync(0xffffffffu, p, 1); b += __shfl_xor_sync(0xffffffffu, b, 1); q += __shfl_xor_sync(0xffffffffu, q, 1);
    a += __shfl_xor_sync(0xffffffffu, a, 2); p += __shfl_xor_sync(0xffffffffu, p, 2); b += __shfl_xor_sync(0xffffffffu, b, 2); q += __shfl_xor_sync(0xffffffffu, q, 2);
    st[0] = a; st[1] = p; st[2] = b; st[3] = q;
}
__device__ __forceinline__ void dual_softmax(const float* p, uint32_t* out) {
    constexpr float L = 1.4426950408889634f;
#pragma unroll
    for (int r = 0; r < 2; r++) {
        float mx = fmaxf(p[2 * r], p[2 * r + 1]), mn = fminf(p[2 * r], p[2 * r + 1]);
#pragma unroll
        for (int i = 1; i < 7; i++) {
            mx = fmaxf(mx, fmaxf(p[4 * i + 2 * r], p[4 * i + 2 * r + 1]));
            mn = fminf(mn, fminf(p[4 * i + 2 * r], p[4 * i + 2 * r + 1]));
        }
        mx = fmaxf(mx, __shfl_xor_sync(0xffffffffu, mx, 1));
        mn = fminf(mn, __shfl_xor_sync(0xffffffffu, mn, 1));
        const float bx = -mx * L, bn = mn * L;
        float ep[14], en[14], sp = 0.f, sn = 0.f;
#pragma unroll
        for (int i = 0; i < 14; i++) {
            const float v = p[4 * (i >> 1) + 2 * r + (i & 1)];
            ep[i] = ex2(fmaf(v, L, bx));
            en[i] = ex2(fmaf(v, -L, bn));
            sp += ep[i]; sn += en[i];
        }
        sp += __shfl_xor_sync(0xffffffffu, sp, 1);
        sn += __shfl_xor_sync(0xffffffffu, sn, 1);
        const float ip = rcp(sp), in = rcp(sn);
#pragma unroll
        for (int i = 0; i < 7; i++) {
            out[4 * i + r] = pack2(ep[2 * i] * ip, ep[2 * i + 1] * ip);
            out[4 * i + 2 + r] = pack2(en[2 * i] * in, en[2 * i + 1] * in);
        }
    }
}
__device__ __forceinline__ float geglu(float g, float u) {
    const float t = tanh_hw(g * fmaf(g * g, 0.7978845608028654f * 0.044715f, 0.7978845608028654f));
    const float gu = g * u;
    return fmaf(t, gu, gu);
}
__device__ __forceinline__ void phi_gemm(const float* t, float* p) {
    uint32_t w[14];
#pragma unroll
    for (int i = 0; i < 14; i++) w[i] = pack2(t[2 * i], t[2 * i + 1]);
    const uint64_t db = BASE128(OFF_WPHI, 16, 0);
    wg_fence();
    mma_rs56<0, 0>(p, w[0], w[1], w[2], w[3], 0, db);
    mma_rs56<0, 2>(p, w[4], w[5], w[6], w[7], 1, db);
    mma_rs56<0, 4>(p, w[8], w[9], w[10], w[11], 1, db);
    mma_rs56<0, 6>(p, w[12], w[13], 0u, 0u, 1, db);
    wg_commit();
    wg_wait<0>();
}

}

#define BAR(i) (bars + 8 * (i))
#define R_WAIT() mbar_wait(BAR(slot), ph)
#define WSUM(i)
#define R_ADJ (slot * (STAGE >> 4))
#define R_NEXT() do { eb2 = eb1; eb1 = BAR(B_EMPTY + slot); if (++slot == NST) { slot = 0; ph ^= 1; } } while (0)
#define R_RELEASE(k) do { if (lane == 0) mbar_arrive((k) == 1 ? eb1 : eb2); } while (0)
#define PUSH_BEGIN() do { mbar_wait(BAR(B_ACK + wgi), ackph); ackph ^= 1; } while (0)
#define PUSH_ACK() do { __syncwarp(); if (lane == 0) asm volatile("mbarrier.arrive.shared::cluster.b64 _, [%0];" ::"r"(mapa(BAR(B_ACK + wgi), hr ^ 1)) : "memory"); } while (0)

__global__ void __cluster_dims__(2, 1, 1) __launch_bounds__(384, 1)
fused_kernel(Scratch* const sc, const __nv_bfloat16* __restrict__ x_in, const __nv_bfloat16* __restrict__ w_phi, const int trips,
             const __nv_bfloat16* __restrict__ wg, const __nv_bfloat16* __restrict__ wu, const __nv_bfloat16* __restrict__ wd,
             const __grid_constant__ Maps maps) {
    extern __shared__ __align__(1024) unsigned char smem_raw[];
    const uint32_t sb = s2u(smem_raw);
    const uint32_t bars = sb + OFF_BAR;
    const int wgi = __shfl_sync(0xffffffffu, threadIdx.x >> 7, 0);
    const int hr = blockIdx.x & 1, ck = blockIdx.x >> 1;
    const int gp = (ck - 4) & 7, q7 = ((ck - 36) * 37) >> 8;
    const int pr = ck < 4 ? ck : (ck < 36 ? (ck - 4) >> 3 : q7);
    const int tile = ck < 4 ? 0 : (ck < 36 ? (gp ? 2 * gp : 1) : 2 * (ck - 36 - 7 * q7) + 3);
    const int sl = 2 * pr + hr;
    STAMP(0);
    GSTAMP(60);
    if (threadIdx.x == 256) {
#pragma unroll
        for (int i = 0; i < NST; i++) mbar_init(BAR(i), 1);
        asm volatile("fence.mbarrier_init.release.cluster;" ::: "memory");
    }
    if (threadIdx.x == 288) {
        if ((sb & 0x3FFFF) != SB0) asm volatile("trap;");
#pragma unroll
        for (int i = NST; i < B_COUNT; i++) mbar_init(BAR(i), i >= B_ACK ? 4 : (i < B_RECV ? 8 : 1));
        asm volatile("fence.mbarrier_init.release.cluster;" ::: "memory");
    }
    __syncwarp();
    asm volatile("barrier.cluster.arrive.relaxed.aligned;" ::: "memory");

    if (wgi == 2) {
        asm volatile("setmaxnreg.dec.sync.aligned.u32 40;");
        const int t128 = fresh_tid() & 127, w = __shfl_sync(0xffffffffu, t128 >> 5, 0), lane = t128 & 31;
        uint32_t e0[2] = {0, 0}, e1[2] = {0, 0}, cw_target = 0;
        if (w == 0) {
#pragma unroll 1
            for (int n = 0; n < NST; n++) {
                const uint32_t dst = sb + n * STAGE, fb = BAR(n);
                asm volatile(ELECT "mbarrier.arrive.expect_tx.shared::cta.b64 _, [%0], %1; }" ::"r"(fb), "r"(n < 2 ? 2 * STAGE : STAGE) : "memory");
                if (n < 2) {
                    tma3x(sb + OFF_H + n * STAGE, &maps.x, tile * 128 + n * 64, fb);
                    tma3x(dst, &maps.x, tile * 128 + n * 64 + 32, fb);
                } else {
                    if (n == 3) mbar_wait(BAR(1), 0);
                    const int ra = 112 * (n - 2);
                    tma2d(dst, &maps.qkv, 448 + 56 * sl, ra, fb);
                    tma2d(dst + HALF, &maps.qkv, 896 + 56 * sl, ra, fb);
                }
            }
            asm volatile("barrier.cluster.wait.aligned;" ::: "memory");
            cw_target = (ld_word(g_cw + sl * 32) & ~15u) + 16;
#pragma unroll 1
            for (int k = 0; k < 2; k++) {
                const int n = t128 + 32 * k;
                int m = n - 2 - (n > PACK);
                const bool packed = m >= 30 ? (m < 38 || m >= 52) : m >= 22;
                if (m >= 30) m -= 30;
                if (n == PACK) m = tile < 8 ? tile : tile + 14;
                const int rot = n < 8 ? 0 : pr;
                const int ra = 112 * kblk(rot, m & 3), rb = 112 * kblk(rot, 2 * m & 3), rc = 112 * kblk(rot, (2 * m + 1) & 3);
                int kind = 0, m0, m1, c0, c1, r0, r1;
                if (m < 4) { m0 = m1 = 1; c0 = 448 + 56 * sl; c1 = c0 + 448; r0 = r1 = ra; }
                else if (m < 8) { m0 = m1 = m < 6 ? 1 : 2; c0 = c1 = 56 * sl; r0 = rb; r1 = rc; }
                else if (m < 20) { m0 = 3; m1 = 4; c0 = c1 = 224 * sl + 32 * hr + 64 * ((m - 8) >> 2); r0 = r1 = ra; }
                else if (m < 22) { kind = 2; m0 = 5; m1 = 6; c0 = c1 = 224 * sl + (hr ? 0 : 192); r0 = rb; r1 = rc; }
                else { m0 = m1 = 7; c0 = c1 = 56 * (2 * ((pr + (m >> 1) - 10) & 3) + hr); r0 = 224 * (sl ^ (m & 1)); r1 = r0 + 112; }
                if (packed) { kind = 1; r0 = sl * 16 + (m < 8 ? m : m - 14); r1 = 0; }
                e0[0] = e0[1]; e1[0] = e1[1];
                e0[1] = kind | (m0 << 2) | (m1 << 6) | (c0 << 10) | (c1 << 21);
                e1[1] = r0 | (r1 << 16);
            }
        } else {
            const int j = t128 - 32;
            asm volatile("barrier.cluster.wait.aligned;" ::: "memory");
            uint2 wv[7];
            const int k = j < 56 ? j : 55, hh = k >= 28;
#pragma unroll
            for (int i = 0; i < 7; i++) wv[i] = __ldg(reinterpret_cast<const uint2*>(w_phi + (sl * 56 + k) * 28) + i);
#pragma unroll 1
            for (int i = j; i < 7168 / 16; i += 96) sts4(sb + OFF_WPHI + i * 16, 0, 0, 0, 0);
            bar_sync(5, 96);
            if (j < 56) {
                uint32_t a4[4];
#pragma unroll
                for (int q = 0; q < 4; q++) a4[q] = sb + OFF_WPHI + (4 * hh + q) * 128 + ((((k >> 3) ^ (4 * hh + q)) & 7) << 4) + (k & 7) * 2;
                FOR14(const uint32_t v = (t & 1) ? wv[t >> 1].y : wv[t >> 1].x;
                      asm volatile("{ .reg .b16 l, h; mov.b32 {l, h}, %2; st.shared.u16 [%0+%3], l; st.shared.u16 [%1+%3], h; }"
                                   ::"r"(a4[t >= 7 ? 2 : 0]), "r"(a4[t >= 7 ? 3 : 1]), "r"(v), "n"((t % 7) * 1024) : "memory"));
            }
            __syncwarp();
            fence_async();
            bar_arrive(1, 224);
            bar_arrive(9, 224);
            if (w == 1) {
                mbar_wait(BAR(2), 0);
                mbar_wait(BAR(2), 1);
                const int b = blockIdx.x;
                asm volatile(ELECT "cp.async.bulk.prefetch.L2.global [%0], %1; }" ::"l"(wg + b * 6272), "r"(12544) : "memory");
                asm volatile(ELECT "cp.async.bulk.prefetch.L2.global [%0], %1; }" ::"l"(wu + b * 6272), "r"(12544) : "memory");
                asm volatile(ELECT "cp.async.bulk.prefetch.L2.global [%0], %1; }" ::"l"(wd + b * 6272), "r"(12544) : "memory");
            }
        }
        uint32_t kseq = ld_word(g_c2 + ((sl * 4 + w) * 16 + tile) * 32);
        int slot = 0, ph = 0, n = NST;
#pragma unroll 1
        for (int layer = 0; layer < 3; layer++) {
            if (w == 0) {
                const int nend = layer == 0 ? 11 : (layer == 1 ? 42 : 63);
#pragma unroll 1
                for (; n < nend; n++) {
                const uint32_t w0 = __shfl_sync(0xffffffffu, n < 32 ? e0[0] : e0[1], n & 31), w1 = __shfl_sync(0xffffffffu, n < 32 ? e1[0] : e1[1], n & 31);
                const uint32_t dst = sb + slot * STAGE, fb = BAR(n == PACK ? B_PACK : slot);
                const CUtensorMap* m0 = &maps.x + ((w0 >> 2) & 15);
                const CUtensorMap* m1 = &maps.x + ((w0 >> 6) & 15);
                const int c0 = (w0 >> 10) & 2047, c1 = w0 >> 21, r0 = w1 & 0xffff, r1 = w1 >> 16;
                if (n == 25) {
                    int it = 0;
                    uint32_t v;
                    do { asm volatile("ld.acquire.gpu.global.u32 %0, [%1];" : "=r"(v) : "l"(g_cw + sl * 32) : "memory"); } while ((int)(v - cw_target) < 0 && ++it < 0x400000);
                    asm volatile("fence.proxy.async.global;" ::: "memory");
                    __syncwarp();
                }
                mbar_wait(BAR(B_EMPTY + slot), ph);
                __syncwarp();
                asm volatile(ELECT "mbarrier.arrive.expect_tx.shared::cta.b64 _, [%0], %1; }" ::"r"(fb), "r"(STAGE) : "memory");
                if ((w0 & 3) == 0) {
                    tma2d(dst, m0, c0, r0, fb);
                    tma2d(dst + HALF, m1, c1, r1, fb);
                } else if (w0 & 1) {
                    asm volatile(ELECT "cp.async.bulk.shared::cluster.global.mbarrier::complete_tx::bytes [%0], [%1], %2, [%3]; }"
                                 ::"r"(dst), "l"(reinterpret_cast<const char*>(g_wp) + (size_t)r0 * STAGE), "r"(STAGE), "r"(fb) : "memory");
                } else {
                    tma2d(dst, m0, c0, r0, fb); tma2d(dst + 7168, m0, c0, r1, fb);
                    tma2d(dst + HALF, m1, c0, r0, fb); tma2d(dst + HALF + 7168, m1, c0, r1, fb);
                }
                if (n == PACK) asm volatile(ELECT "mbarrier.arrive.shared::cta.b64 _, [%0]; }" ::"r"(BAR(slot)) : "memory");
                if (++slot == NST) { slot = 0; ph ^= 1; }
                }
            } else if (w == 1 && layer == 1) {
                constexpr int ps = PACK % NST;
                mbar_wait(BAR(B_PACK), 0);
                asm volatile("{ .reg .pred e; elect.sync _|e, 0xffffffff;\n"
                             "@e cp.async.bulk.global.shared::cta.bulk_group [%0], [%1], %2;\n"
                             "@e cp.async.bulk.commit_group;\n"
                             "@e cp.async.bulk.wait_group.read 0;\n"
                             "@e mbarrier.arrive.shared::cta.b64 _, [%3], 8;\n"
                             "@e cp.async.bulk.wait_group 0;\n"
                             "@e fence.proxy.async.global;\n"
                             "@e red.release.gpu.global.add.u32 [%4], 1; }"
                             ::"l"(reinterpret_cast<char*>(g_wp) + (size_t)(sl * 16 + tile) * STAGE), "r"(sb + ps * STAGE), "r"(STAGE), "r"(BAR(B_EMPTY + ps)), "l"(g_cw + sl * 32) : "memory");
                __syncwarp();
            }
            if (layer < 2) {
            const uint32_t tag = layer ^ 1;
            kseq++;
            bar_sync(7, 384);
            ASTAMP(0);
            if (tile < 15) {
                const int sq = lane >> 3, pk = 8 * w + (lane & (tile == 14 ? 3 : 7));
                uint32_t v[16];
                if (layer == 0 || CANARY) poll_cnt(g_c1 + ((sl * 8 + (w >> 1) * 4 + (tile >> 2)) * 16 + (lane & 15)) * 32, kseq);
                ASTAMP(1);
                poll4_kv<32>(v, g_kv1 + ((sl * 16 + tile) * 16 + 4 * sq) * 32 + pk, tag);
#pragma unroll
                for (int k = 0; k < 4; k++) {
                    float lo = (bf_lo(v[k]) + bf_lo(v[4 + k])) + (bf_lo(v[8 + k]) + bf_lo(v[12 + k]));
                    float hi = (bf_hi(v[k]) + bf_hi(v[4 + k])) + (bf_hi(v[8 + k]) + bf_hi(v[12 + k]));
                    lo += __shfl_xor_sync(0xffffffffu, lo, 8); hi += __shfl_xor_sync(0xffffffffu, hi, 8);
                    lo += __shfl_xor_sync(0xffffffffu, lo, 16); hi += __shfl_xor_sync(0xffffffffu, hi, 16);
                    v[k] = pack2(lo, hi);
                }
                if (sq == 0) st_pkt<0>(g_kv2 + sl * 512 + 32 * tile + pk, settag(v[0], tag), v[1], v[2], v[3]);
            }
            if (lane == 0) st_word(g_c2 + ((sl * 4 + w) * 16 + tile) * 32, kseq);
            ASTAMP(2);
            {
                const int item = t128 < 112 ? t128 : 112 + (t128 & 3), d = item >> 1;
                const int cc = t128 < 112 ? 2 * (d >= 28) + (item & 1) : item - 112;
                const int r = t128 < 112 ? d : 56 + (cc >> 1) + 2 * ((t128 - 112) >> 2);
                uint32_t ra = sb + OFF_KVB + r * 128 + 4 * cc, rx = (r & 7) << 4;
                asm volatile("" : "+r"(ra), "+r"(rx));
                FOR14(asm volatile("st.shared.u32 [%0+%2], %1;" ::"r"((ra ^ 8) + (((t & 7) << 4) ^ rx)), "r"(0), "n"((t >> 3) * 8192) : "memory"));
                uint32_t v[16];
                asm volatile("" : "+r"(ra), "+r"(rx));
                if (layer == 0 || CAN2) poll_cnt(g_c2 + ((sl * 4 + (lane >> 3)) * 16 + min(4 * w + (lane & 3), 15)) * 32, kseq);
                poll4_kv<8>(v, g_kv2 + sl * 512 + (item >> 3) * 32 + (item & 7), tag);
                FOR14(asm volatile("st.shared.u32 [%0+%2], %1;" ::"r"(ra + (((t & 7) << 4) ^ rx)), "r"(v[t < 7 ? t : t + 1]), "n"((t >> 3) * 8192) : "memory"));
                fence_async();
            }
            bar_arrive(3, 384);
            ASTAMP(3);
            }
        }
    } else {
        asm volatile("setmaxnreg.inc.sync.aligned.u32 232;");
        const int tid = fresh_tid(), lane = tid & 31, t128 = tid & 127, g = lane >> 2, c = lane & 3;
        const int wu = __shfl_sync(0xffffffffu, tid >> 5, 0), w = wu & 3;
        uint4* const xp0 = g_ex + 3 * PLANE + ((tile * 2 + wgi) * 8) * 512 + w * 128 + lane;
        const uint32_t hbuf = sb + OFF_H + wgi * STAGE;
        uint32_t slot = 0, ph = 0, eb1 = 0, eb2 = 0, ackph = 0, rcvph = 0, gatph = 0, swp = 0;
        uint32_t ppid = 6;
#define cx(s) (reinterpret_cast<uint32_t*>(again(xp0) - lane + PL(1) + 112 + (s) * 512))
#define stp (again(xp0) - lane + g + PL(0) + 112)
        uint32_t seq = ld_word(cx(sl));
        uint32_t kseq = ld_word(g_c1 + ((sl * 8 + (tid >> 5)) * 16 + tile) * 32);
        uint32_t stag = ld_word(reinterpret_cast<const uint32_t*>(stp + sl * 512) + 3) & 1;
        asm volatile("barrier.cluster.wait.aligned;" ::: "memory");
        STAMP(1);
        uint32_t X[14];
        const uint32_t x0row = (w < 2 ? hbuf : sb + wgi * STAGE) + ((w & 1) * 16 + (lane & 15)) * 128;
        mbar_wait(BAR(wgi), 0);
        STAMP(51);
#pragma unroll
        for (int j = 0; j < 4; j++) {
            const int G = 7 * sl + min(2 * j + (lane >> 4), 6);
            uint32_t q2, q3;
            asm volatile("ldmatrix.sync.aligned.m8n8.x4.shared.b16 {%0,%1,%2,%3}, [%4];" : "=r"(X[4 * j]), "=r"(X[4 * j + 1]), "=r"(q2), "=r"(q3)
                         : "r"(x0row + (G >> 3) * 4096 + (((G ^ lane) & 7) << 4)) : "memory");
            if (j < 3) { X[(4 * j + 2) % 14] = q2; X[(4 * j + 3) % 14] = q3; }
        }
#define PUSH_SLICE(W)                                                                          \
    {                                                                                          \
        if (t128 == 0) mbar_expect_tx(BAR(B_RECV + wgi), 7168);                                \
        PUSH_BEGIN();                                                                          \
        const uint32_t ra = mapa(hbuf + 24576 + t128 * 16, hr ^ 1), rb = mapa(sb + OFF_XR + wgi * 3072, hr ^ 1), rbar = mapa(BAR(B_RECV + wgi), hr ^ 1); \
        st_async4(ra, W[0], W[1], W[2], W[3], rbar);                                           \
        st_async4(ra + 2048, W[4], W[5], W[6], W[7], rbar);                                    \
        st_async4(rb + t128 * 16, W[8], W[9], W[10], W[11], rbar);                             \
        asm volatile("st.async.weak.shared::cluster.mbarrier::complete_tx::bytes.v2.b32 [%0], {%1,%2}, [%3];" ::"r"(rb + 2048 + t128 * 8), "r"(W[12]), "r"(W[13]), "r"(rbar) : "memory"); \
    }
#define PULL_SLICE(W)                                                                          \
    {                                                                                          \
        uint32_t t0, t1;                                                                       \
        mbar_wait(BAR(B_RECV + wgi), rcvph);                                                   \
        rcvph ^= 1;                                                                            \
        lds4(&A[1][0], hbuf + 24576 + t128 * 16);                                              \
        lds4(&A[1][4], hbuf + 26624 + t128 * 16);                                              \
        lds4(&A[1][8], sb + OFF_XR + wgi * 3072 + t128 * 16);                                  \
        asm volatile("ld.shared.v2.u32 {%0,%1}, [%2];" : "=r"(t0), "=r"(t1) : "r"(sb + OFF_XR + wgi * 3072 + 2048 + t128 * 8) : "memory"); \
        _Pragma("unroll") for (int i = 0; i < 12; i++) A[0][i] = (i & 3) ? W[i] : W[i] & ~1u;  \
        A[1][0] &= ~1u; A[1][4] &= ~1u; A[1][8] &= ~1u;                                        \
        A[0][12] = (hr ? t0 : W[12]) & ~1u; A[0][13] = hr ? t1 : W[13];                        \
        A[1][12] = (hr ? W[12] : t0) & ~1u; A[1][13] = hr ? W[13] : t1;                        \
        asm volatile("" : RW4(A[0], 0), RW4(A[0], 4), RW4(A[0], 8), RW2(A[0], 12), RW4(A[1], 0), RW4(A[1], 4), RW4(A[1], 8), RW2(A[1], 12)); \
        swp = hr * 448;                                                                        \
    }
#define SWB(b, t, db, sh) ((b) == 0 && (t) < 6 ? ((t) < 3 ? db##p : db##m) : db)
#define DECL_DB(b, MK, lbo, sh) const uint64_t db = MK(0, lbo, R_ADJ), dbp = (b) == 0 ? MK(0, lbo, R_ADJ + (swp >> (sh))) : db, dbm = (b) == 0 ? MK(0, lbo, R_ADJ - (swp >> (sh))) : db;
#define EARLY 1
#define EARLYK 1
#define PPB 2
#define PP_WAIT() if (wgi == 1) { bar_sync(ppid, 256); ppid ^= 14; }
#define PP_GO() if (wgi == 0) { bar_arrive(ppid, 256); ppid ^= 14; }
#define GAT_ISSUE(base)                                                                        \
    {                                                                                          \
        const char* gs = reinterpret_cast<const char*>(g_ex + 3 * PLANE + (base) + (tile * 16 + wgi * 8 + 2 * kblk(pr, GB)) * 512 + w * 128); \
        const uint32_t gd = hbuf + w * 3584, gb = BAR(B_GAT + wu);                     \
        asm volatile("{ .reg .pred e; elect.sync _|e, 0xffffffff;\n"                           \
                     "@e mbarrier.arrive.expect_tx.shared::cta.b64 _, [%2], 3584;\n"           \
                     "@e cp.async.bulk.shared::cluster.global.mbarrier::complete_tx::bytes [%0], [%1], 1792, [%2];\n" \
                     "@e cp.async.bulk.shared::cluster.global.mbarrier::complete_tx::bytes [%0+1792], [%1+8192], 1792, [%2]; }" \
                     ::"r"(gd), "l"(gs), "r"(gb) : "memory");                                  \
        __syncwarp();                                                                          \
    }
#define GAT_FETCH()                                                                            \
    {                                                                                          \
        mbar_wait(BAR(B_GAT + wu), gatph);                                             \
        gatph ^= 1;                                                                            \
        const uint32_t ga = hbuf + w * 3584 + lane * 16;                                       \
        _Pragma("unroll") for (int s2 = 0; s2 < 2; s2++) {                                     \
            lds4(&A[2 * GB + s2][0], ga + s2 * 1792); lds4(&A[2 * GB + s2][4], ga + s2 * 1792 + 512); lds4(&A[2 * GB + s2][8], ga + s2 * 1792 + 1024); \
            asm volatile("ld.shared.v2.u32 {%0,%1}, [%2];" : "=r"(A[2 * GB + s2][12]), "=r"(A[2 * GB + s2][13]) : "r"(ga - lane * 8 + s2 * 1792 + 1536) : "memory"); \
        }                                                                                      \
    }
#define PT 3
#define PREP(b, t, remote)                                                                     \
    if constexpr ((b) < 3 && (t) == PT) {                                                      \
        wg_commit();                                                                           \
        STAMP(80 + 8 * (step & 1) + 2 * (b));                                                  \
        if constexpr (GB == 1 && (b) == 0) { if (remote) GAT_FETCH() }                         \
        if (remote) blk_check<((b) + 1) & 3>(A, BLK(xsrc, (b) + 1), lane, xtag);               \
        STAMP(81 + 8 * (step & 1) + 2 * (b));                                                  \
        if constexpr ((b) == 0) { if (remote) blk_load<3>(A, BLK(xsrc, 3), lane); }            \
        normalize<((b) + 1) & 3>(A, k0, k1);                                                   \
        asm volatile("" : RW4(A[(2 * (b) + 2) & 7], 0), RW4(A[(2 * (b) + 2) & 7], 4), RW4(A[(2 * (b) + 2) & 7], 8), RW2(A[(2 * (b) + 2) & 7], 12), \
                          RW4(A[(2 * (b) + 3) & 7], 0), RW4(A[(2 * (b) + 3) & 7], 4), RW4(A[(2 * (b) + 3) & 7], 8), RW2(A[(2 * (b) + 3) & 7], 12)); \
        wg_fence();                                                                            \
    }                                                                                          \
    if constexpr ((b) == 3 && ((t) == 0 || (t) == 6)) { STAMP(86 + 8 * (step & 1) + (t) / 6); }
#define BLK(base, b) ((base) + kblk(pr, b) * 1024)

#pragma unroll 1
        for (int step = 0; step < 4; step++) {
            const uint32_t tag = (step >> 1) ^ 1;
            const int so = (step >> 1) * 24 + (step & 1) * 12;
            (void)so;
            uint32_t A[8][14];
            uint4* const xsrc = xp0 + ((step & 1) ? PL(2) : PL(0));
            const uint32_t xtag = (step & 1) ? tag : ((seq >> 3) & 1) ^ 1;
            uint32_t xbits;
            {
                float st[4];
                slice_stats(X, st);
                stag ^= 1;
                xbits = x_bits(X);
                tag_slice(X, xtag);
                if (step) send_slice<0>(xsrc + sl * 512, lane, X);
                if (c == 0) st_pkt<0>(stp + sl * 512, __float_as_uint(st[0]), __float_as_uint(st[1]), __float_as_uint(st[2]), settag(__float_as_uint(st[3]), stag));
            }
            STAMP(2 + so);
            uint32_t sv[8];
            if (step == 0) {
                const int rr = lane & 7, hi = lane >> 4;
                const uint32_t rowa = (w < 2 ? hbuf : sb + wgi * STAGE) + ((w & 1) * 16 + (lane & 15)) * 128;
                uint32_t xr[8];
#pragma unroll
                for (int j = 0; j < 8; j++) xr[j] = rowa + ((((j + hi) ^ rr) & 7) << 4) + (j == 7 ? hi * 4096 : 0);
#define X0_BLOCK(b)                                                                            \
    FOR7(constexpr int G = 14 * (b) + (t < 3 ? 2 * t : (t < 6 ? 2 * t + 1 : 6));               \
         uint32_t q0, q1, q2, q3;                                                              \
         const uint32_t ad = t < 6 ? xr[G & 7] : rowa + ((G + 7 * hi) >> 3) * 4096 + ((((G + 7 * hi) ^ rr) & 7) << 4); \
         asm volatile("ldmatrix.sync.aligned.m8n8.x4.shared.b16 {%0,%1,%2,%3}, [%4+%5];" : "=r"(q0), "=r"(q1), "=r"(q2), "=r"(q3) \
                      : "r"(ad), "n"(t < 6 ? (G >> 3) * 4096 : 0) : "memory");                 \
         if (t < 3) { A[2 * (b)][4 * t] = q0; A[2 * (b)][4 * t + 1] = q1; A[2 * (b)][4 * t + 2] = q2; A[2 * (b)][4 * t + 3] = q3; } \
         else if (t < 6) { A[2 * (b) + 1][(4 * t - 12) & 15] = q0; A[2 * (b) + 1][((4 * t - 12) & 15) + 1] = q1; A[2 * (b) + 1][((4 * t - 12) & 15) + 2] = q2; A[2 * (b) + 1][((4 * t - 12) & 15) + 3] = q3; } \
         else { A[2 * (b)][12] = q0; A[2 * (b)][13] = q1; A[2 * (b) + 1][12] = q2; A[2 * (b) + 1][13] = q3; });
                X0_BLOCK(0) X0_BLOCK(1) X0_BLOCK(2) X0_BLOCK(3)
                mbar_wait(BAR(wgi ^ 1), 0);
                R_NEXT();
                R_NEXT();
                stat_load(sv, stp + c * 1024);
                stat_check(sv, stp + c * 1024, stag);
                STAMP(52 + step);
            } else {
                PUSH_SLICE(X)
                stat_load(sv, stp + c * 1024);
                kill<14>(A[2]); kill<14>(A[3]); kill<14>(A[4]); kill<14>(A[5]); kill<14>(A[6]); kill<14>(A[7]);
                PULL_SLICE(X)
                stat_check(sv, stp + c * 1024, stag);
                STAMP(52 + step);
                if (GB == 1) GAT_ISSUE((step & 1) ? PL(2) : PL(0))
                else blk_load<1>(A, BLK(xsrc, 1), lane);
            }
            LnCoef k0, k1;
            {
                k0 = ln_coef(__uint_as_float(sv[0]) + __uint_as_float(sv[4]), __uint_as_float(sv[1]) + __uint_as_float(sv[5]));
                k1 = ln_coef(__uint_as_float(sv[2]) + __uint_as_float(sv[6]), __uint_as_float(sv[3]) + __uint_as_float(sv[7]));
            }
            if (step) {
                if (GB == 2) GAT_ISSUE((step & 1) ? PL(2) : PL(0))
                else blk_load<2>(A, BLK(xsrc, 2), lane);
            }
            STAMP(3 + so);
            GSTAMP(76 + step);

            if ((step & 1) == 0) {
                float tq[28];
                {
                    float av[28];
#define KV_BLOCK(b)                                                                           \
    if (GB == 2 && (b) == 1 && step) GAT_FETCH()                                                         \
    if ((b) == 2) PUSH_ACK();                                                                 \
    if (QE && (b) == 1) R_RELEASE(2);                                                         \
    if (QE && (b) == 2) { wg_wait<2>(); R_RELEASE(2); }                                       \
    R_WAIT();                                                                                 \
    if ((b) == PPK) { PP_WAIT() }                                                             \
    { DECL_DB(b, BASE128, 16, 0)                                                              \
    wg_fence();                                                                               \
    FOR7(mma_rs56<1, D128(0, t)>(tq, AQ(A, b, t), (b) + t > 0, SWB(b, t, db, 0));             \
         mma_rs56<1, D128(HALF, t)>(av, AQ(A, b, t), (b) + t > 0, SWB(b, t, db, 0));          \
         PREP(b, t, step)); }                                                                 \
    wg_commit();                                                                              \
    if ((b) == 3 && PPK < 4) { PP_GO() }                                                      \
    R_NEXT();
                    if (EARLYK == 0 || step == 0) R_RELEASE(2);
                    normalize<0>(A, k0, k1);
                    KV_BLOCK(0) KV_BLOCK(1) KV_BLOCK(2) KV_BLOCK(3)
                    wg_wait<0>();
                    if (lane < (QE ? 3 : NST)) mbar_arrive(BAR(B_EMPTY + (slot + NST - 1 - lane) % NST));
                    STAMP(4 + so);
                    WSUM(80 + 7 * (step >> 1));
                    const int m = lane >> 3, rr = lane & 7;
                    const uint32_t rowa = hbuf + 16384 + (w * 16 + rr + 8 * (m & 1)) * 128;
                    const uint32_t one = c == 0 ? 0x00003f80u : 0u;
                    if (step == 0) { bar_sync(wgi ? 9 : 1, 224); }
#pragma unroll
                    for (int j = 0; j < 4; j++) {
                        const uint32_t a = rowa + (((2 * j + (m >> 1)) ^ rr) << 4);
                        if (j < 3) stsm4(a, pack2(av[8 * j], av[8 * j + 1]), pack2(av[8 * j + 2], av[8 * j + 3]), pack2(av[8 * j + 4], av[8 * j + 5]), pack2(av[8 * j + 6], av[8 * j + 7]));
                        else stsm4(a, pack2(av[24], av[25]), pack2(av[26], av[27]), one, one);
                    }
                }
                uint32_t PH[28];
                int it = 1;
#pragma unroll 1
                do {
                    float pp[28];
                    phi_gemm(tq, pp);
                    dual_softmax(pp, PH);
                    if (((trips >> (it + 1)) & 1) == 0) continue;
                    {
                        const int m = lane >> 3, rr = lane & 7;
                        const uint32_t rowa = hbuf + (w * 16 + rr + 8 * (m & 1)) * 128;
#pragma unroll
                        for (int j = 0; j < 7; j++) {
                            const int cg = 2 * j + (m >> 1), hi = cg >= 7;
                            stsm4(rowa + hi * 8192 + (((cg - 7 * hi) ^ rr) << 4), PH[4 * j], PH[4 * j + 1], PH[4 * j + 2], PH[4 * j + 3]);
                        }
                    }
                    fence_async();
                    STAMP(5 + so);
#define Q_STAGE(b0)                                                                           \
    R_WAIT();                                                                                 \
    { DECL_DB(b0, BASE128, 16, 0)                                                             \
    wg_fence();                                                                               \
    FOR7(mma_rs56<1, D128(0, t)>(tq, AQ(A, b0, t), (b0) + t > 0, SWB(b0, t, db, 0)));         \
    FOR7(mma_rs56<1, D128(HALF, t)>(tq, AQ(A, (b0) + 1, t), 1, db)); }                        \
    wg_commit();                                                                              \
    R_NEXT();
                    if (QE && wgi == 0) { kill<28>(tq); Q_STAGE(0) Q_STAGE(2) wg_wait<1>(); R_RELEASE(2); wg_wait<0>(); R_RELEASE(1); }
                    bar_sync(2, 256);
                    float kv[28];
                    const uint64_t da = BASE128(OFF_H + 16384, 16, 0), dbk = BASE128(OFF_H, 16, wgi * 512);
                    wg_fence();
                    FOR8(constexpr uint64_t o = ((t >> 2) * STAGE + (t & 3) * 2048) >> 4; mma_ss56_tt<o, o>(kv, t > 0, da, dbk));
                    wg_commit();
                    wg_wait<0>();
#pragma unroll
                    for (int hf = 0; hf < 2; hf++) {
                        const int d = 16 * w + g + 8 * hf;
                        if ((d < 56 && (d >= 28) == (c >= 2)) || d == 56) {
                            const int item = d < 56 ? 2 * d + (c & 1) : 112 + c;
                            uint4* dst = g_kv1 + ((sl * 16 + (item >> 3)) * 16 + tile) * 32 + wgi * 16 + (item & 7);
#define KVW(i) pack2(kv[4 * (i) + 2 * hf], kv[4 * (i) + 2 * hf + 1])
                            st_pkt<0>(dst, settag(KVW(0), tag), KVW(1), KVW(2), KVW(3));
                            st_pkt<8>(dst, settag(KVW(4), tag), KVW(5), KVW(6), 0u);
                        }
                    }
                    __syncwarp();
                    kseq++;
                    if (lane == 0) st_word(g_c1 + ((sl * 8 + (tid >> 5)) * 16 + tile) * 32, kseq);
                    bar_arrive(7, 384);
                    STAMP(6 + so);
                    if (!QE || wgi == 1) { kill<28>(tq); Q_STAGE(0) Q_STAGE(2) wg_wait<1>(); R_RELEASE(2); wg_wait<0>(); R_RELEASE(1); }
                    STAMP(7 + so);
                    kill<28>(PH);
                } while (((trips >> (++it)) & 1));
                STAMP(8 + so);
                if (step) {
                    slice_load<PL(0)>(X, xp0 + sl * 512, lane);
                } else {
                    const uint32_t* xp = reinterpret_cast<const uint32_t*>(x_in + (size_t)(tile * 128 + wu * 16 + g) * 448 + 56 * sl + 2 * c);
#pragma unroll
                    for (int i = 0; i < 7; i++) { X[2 * i] = __ldg(xp + 4 * i); X[2 * i + 1] = __ldg(xp + 4 * i + 8 * 224); }
                }
                bar_sync(3, 384);
                STAMP(9 + so);
                const uint4* const osrc = xp0 + PL(1);
                {
                    float nm[32];
                    const uint64_t db = BASE128(OFF_KVB, 16, 0);
                    wg_fence();
                    FOR7(mma_rs64<0, ((t >> 2) * 8192 + (t & 3) * 32) / 16>(nm, PH[4 * t], PH[4 * t + 1], PH[4 * t + 2], PH[4 * t + 3], t > 0, db));
                    wg_commit();
                    wg_wait<0>();
                    const float i00 = rcp(nm[28] + 1e-6f), i01 = rcp(nm[29] + 1e-6f), i10 = rcp(nm[30] + 1e-6f), i11 = rcp(nm[31] + 1e-6f);
                    const float m0 = c >= 2 ? i01 : i00, m1 = c >= 2 ? i11 : i10;
                    uint32_t O[14];
#pragma unroll
                    for (int i = 0; i < 7; i++) {
                        const float f0 = i < 3 ? i00 : (i > 3 ? i01 : m0), f1 = i < 3 ? i10 : (i > 3 ? i11 : m1);
                        O[2 * i] = pack2(nm[4 * i] * f0, nm[4 * i + 1] * f0);
                        O[2 * i + 1] = pack2(nm[4 * i + 2] * f1, nm[4 * i + 3] * f1);
                    }
                    if (OST) { PP_WAIT() }
                    tag_slice(O, tag);
                    send_slice<PL(1)>(xp0 + sl * 512, lane, O);
                    seq++;
                    if (lane == 0) st_word(cx(sl), seq);
                    STAMP(10 + so);
                    PUSH_SLICE(O)
                    if (OST == 1) { PP_GO() }
                    const uint32_t cv = ld_word(cx(lane & 7));
                    PULL_SLICE(O)
                    check_cnt(cv, cx(lane & 7), seq);
                    if (OST == 2) { PP_GO() }
                    STAMP(56 + (step >> 1));
                    GAT_ISSUE(PL(1))
                    blk_load<3 - GB>(A, BLK(osrc, 3 - GB), lane);
                }
                float ao[28];
#define WO_BLOCK(b)                                                                           \
    if ((b) > 0) blk_check<b>(A, BLK(osrc, b), lane, tag);                                    \
    if (((b) & 1) == 0) R_WAIT();                                                             \
    { DECL_DB(b, BASE128, 16, 0)                                                              \
    wg_fence();                                                                               \
    FOR7(mma_rs56<1, D128(((b) & 1) * HALF, t)>(ao, AQ(A, b, t), (b) + t > 0, SWB(b, t, db, 0))); } \
    wg_commit();                                                                              \
    if ((b) & 1) R_NEXT();
                WO_BLOCK(0)
                STAMP(11 + so);
                blk_load<3>(A, BLK(osrc, 3), lane);
                if (GB == 1) GAT_FETCH()
                WO_BLOCK(1)
                if (GB == 2) GAT_FETCH()
                WO_BLOCK(2)
                PUSH_ACK();
                WO_BLOCK(3)
                wg_wait<0>();
                if (EARLY >= 1) R_RELEASE(2);
                if (EARLY >= 2) R_RELEASE(1);
                STAMP(12 + so);
                WSUM(86 + 7 * (step >> 1));
                x_fix(X, xbits);
#pragma unroll
                for (int i = 0; i < 14; i++) X[i] = pack2(bf_lo(X[i]) + ao[2 * i], bf_hi(X[i]) + ao[2 * i + 1]);
            } else {
                uint32_t H[56];
                float ag[64];
#define F1_EPI(dst, ng, ag)                                                                    \
    _Pragma("unroll") for (int i = 0; i < 2 * (ng); i++)                                       \
        (dst)[i] = pack2(geglu(ag[2 * i], ag[4 * (ng) + 2 * i]), geglu(ag[2 * i + 1], ag[4 * (ng) + 2 * i + 1]));
#define H_PUSH(h0, off) st_async4(rem_h + (off), H[h0], H[(h0) + 1], H[(h0) + 2], H[(h0) + 3], mapa(BAR(B_RECV2 + wgi), hr ^ 1));
#define F1_BLOCK(b, first)                                                                     \
    if ((first) && (b) < 2 && (b) >= EARLY) R_RELEASE(2);                                      \
    if (GB == 2 && (first) && (b) == 1) GAT_FETCH()                                                       \
    if ((first) && (b) == 2) PUSH_ACK();                                                       \
    R_WAIT();                                                                                  \
    if ((b) == PPB) { PP_WAIT() }                                                              \
    { DECL_DB(b, BASE128, HALF, 0)                                                             \
    wg_fence();                                                                                \
    FOR7(mma_rs128<1, D128(0, t)>(ag, AQ(A, b, t), (b) + t > 0, SWB(b, t, db, 0));             \
         if constexpr (first) { PREP(b, t, true) }); }                                         \
    wg_commit();                                                                               \
    if ((b) == 3) { PP_GO() }                                                                  \
    if ((b) > 0) { wg_wait<1>(); R_RELEASE(1); }       \
    R_NEXT();
                normalize<0>(A, k0, k1);
                F1_BLOCK(0, true) F1_BLOCK(1, true) F1_BLOCK(2, true) F1_BLOCK(3, true)
                if (t128 == 0) { mbar_expect_tx(BAR(B_RECV + wgi), 16384); mbar_expect_tx(BAR(B_RECV2 + wgi), 12288); }
                PUSH_BEGIN();
                wg_wait<0>();
                R_RELEASE(1);
                if (step == 1) R_NEXT();
                int p = 0;
#pragma unroll 1
                do {
                    STAMP(68 + p);
                    F1_EPI(H + 32, 8, ag)
                    STAMP(4 + p + so);
                    WSUM(81 + p + 7 * (step >> 1));
                    if (((trips >> (p + 1)) & 1) == 0) continue;
                    {
                        const uint32_t pk = (p ? hbuf + 16384 : sb + OFF_KVB + wgi * 8192) + w * 2048;
#pragma unroll
                        for (int k = 0; k < 4; k++) sts4(pk + k * 512 + lane * 16, H[32 + 4 * k], H[33 + 4 * k], H[34 + 4 * k], H[35 + 4 * k]);
                        fence_async();
                        __syncwarp();
                        asm volatile(ELECT "cp.async.bulk.shared::cluster.shared::cta.mbarrier::complete_tx::bytes [%0], [%1], 2048, [%2]; }"
                                     ::"r"(mapa(hbuf + p * 8192 + w * 2048, hr ^ 1)), "r"(pk), "r"(mapa(BAR(B_RECV + wgi), hr ^ 1)) : "memory");
                    }
                    kill<64>(ag);
                    F1_BLOCK(0, false) F1_BLOCK(1, false) F1_BLOCK(2, false) F1_BLOCK(3, false)
                    wg_wait<0>();
                    R_RELEASE(1);
                    kill<16>(H + 32);
                } while (((trips >> (++p)) & 1));
#pragma unroll
                for (int k = 0; k < 4; k++) lds4(H + 16 + 4 * k, hbuf + 16384 + w * 2048 + k * 512 + lane * 16);
                __syncwarp();
                if (lane == 0) asm volatile("mbarrier.arrive.shared::cluster.b64 _, [%0];" ::"r"(mapa(BAR(B_ACK2 + wgi), hr ^ 1)) : "memory");
                const uint32_t rem_h = mapa(hbuf + w * 2048 + lane * 16, hr ^ 1);
#define F1_LAST(b0)                                                                            \
    R_WAIT();                                                                                  \
    if (b0) { PP_WAIT() }                                                                      \
    { DECL_DB(b0, BASE64, HALF, 1)                                                             \
    wg_fence();                                                                                \
    FOR7(mma_rs64<1, D64(0, t)>(al, AQ(A, b0, t), (b0) + t > 0, SWB(b0, t, db, 1)));           \
    FOR7(mma_rs64<1, D64(7168, t)>(al, AQ(A, (b0) + 1, t), 1, db)); }                          \
    wg_commit();                                                                               \
    if (b0) { PP_GO() }                                                                        \
    R_NEXT();
                float al[32];
                F1_LAST(0)
                mbar_wait(BAR(B_RECV + wgi), rcvph);
                rcvph ^= 1;
                mbar_wait(BAR(B_ACK2 + wgi), step >> 1);
                H_PUSH(32, 16384) H_PUSH(36, 16896)
                F1_LAST(2)
                H_PUSH(40, 17408) H_PUSH(44, 17920)
                wg_wait<1>();
                R_RELEASE(2);
                wg_wait<0>();
                R_RELEASE(1);
                uint32_t HP[56];
#pragma unroll
                for (int k = 0; k < 4; k++) lds4(H + 4 * k, sb + OFF_KVB + wgi * 8192 + w * 2048 + k * 512 + lane * 16);
#pragma unroll
                for (int t = 0; t < 8; t++) lds4(HP + 4 * t, hbuf + (t >> 2) * 8192 + w * 2048 + (t & 3) * 512 + lane * 16);
                F1_EPI(H + 48, 4, al)
                H_PUSH(48, 24576 - w * 1024) H_PUSH(52, 25088 - w * 1024)
                STAMP(7 + so);
                WSUM(84 + 7 * (step >> 1));
                float acc[28];
                const uint32_t roA = hr ? 256u : 0u, roB = hr ? (uint32_t)-1536 : 0u;
                const uint32_t rpA = hr ? 0u : 256u, rpB = hr ? 0u : (uint32_t)-1536;
                float res[28];
                uint32_t v0[14], v1[14], P[14];
                const uint4* ps = xp0 + sl * 512;
#define F2_OWN_A()                                                                             \
    R_WAIT();                                                                                  \
    d0 = BASE128(0, 16, R_ADJ + roA); d1 = BASE128(0, 16, R_ADJ + roB);                        \
    wg_fence();                                                                                \
    FOR14(if constexpr (t < OT) mma_rs56<1, t * 128>(acc, H[4 * t], H[4 * t + 1], H[4 * t + 2], H[4 * t + 3], t > 0, d0)); \
    wg_commit();
#define F2_OWN_B()                                                                             \
    wg_fence();                                                                                \
    FOR14(if constexpr (t >= OT) mma_rs56<1, t * 128>(acc, H[4 * t], H[4 * t + 1], H[4 * t + 2], H[4 * t + 3], 1, t < 12 ? d0 : d1)); \
    wg_commit();                                                                               \
    R_NEXT();
#define F2_PEER()                                                                              \
    R_WAIT();                                                                                  \
    if (F2PP) { PP_WAIT() }                                                                    \
    d0 = BASE128(0, 16, R_ADJ + rpA); d1 = BASE128(0, 16, R_ADJ + rpB);                        \
    wg_fence();                                                                                \
    FOR14(mma_rs56<1, t * 128>(acc, HP[4 * t], HP[4 * t + 1], HP[4 * t + 2], HP[4 * t + 3], 1, t < 12 ? d0 : d1)); \
    wg_commit();                                                                               \
    if (F2PP) { PP_GO() }                                                                      \
    R_NEXT();
#define F2_TURN(u)                                                                             \
    wg_wait<1>();                                                                              \
    R_RELEASE(2);                                                                              \
    wg_wait<0>();                                                                              \
    R_RELEASE(1);                                                                              \
    _Pragma("unroll") for (int i = 0; i < 14; i++) P[i] = pack2(acc[2 * i], acc[2 * i + 1]);   \
    tag_slice(P, tag);                                                                         \
    asm volatile("" : RW4(P, 0), RW4(P, 4), RW4(P, 8), RW2(P, 12));                            \
    kill<28>(acc);                                                                             \
    F2_OWN_A()                                                                                 \
    if ((u) == 2) { slice_load<PL(3)>(v0, ps, lane); slice_load<PL(4)>(v1, ps, lane); } \
    send_slice<PL(3 + (u))>(xp0 + (2 * ((pr + (u) + 1) & 3) + hr) * 512, lane, P);             \
    seq++;                                                                                     \
    if (lane == 0) st_word(cx(sl), seq);                                                       \
    __syncwarp();                                                                              \
    STAMP(8 + (u) + so);                                                                       \
    F2_OWN_B()
                uint64_t d0, d1;
                F2_OWN_A()
                F2_OWN_B()
                R_WAIT();
                d0 = BASE128(0, 16, R_ADJ + rpA); d1 = BASE128(0, 16, R_ADJ + rpB);
                wg_fence();
                FOR8(mma_rs56<1, t * 128>(acc, HP[4 * t], HP[4 * t + 1], HP[4 * t + 2], HP[4 * t + 3], 1, d0));
                wg_commit();
                mbar_wait(BAR(B_RECV2 + wgi), step >> 1);
#pragma unroll
                for (int k = 0; k < 4; k++) lds4(HP + 32 + 4 * k, hbuf + 16384 + w * 2048 + k * 512 + lane * 16);
                lds4(HP + 48, hbuf + 24576 + w * 1024 + lane * 16);
                lds4(HP + 52, hbuf + 25088 + w * 1024 + lane * 16);
                if (step == 1) PUSH_ACK();
                wg_fence();
                FOR14(if constexpr (t >= 8) mma_rs56<1, t * 128>(acc, HP[4 * t], HP[4 * t + 1], HP[4 * t + 2], HP[4 * t + 3], 1, t < 12 ? d0 : d1));
                wg_commit();
                R_NEXT();
                F2_TURN(0)
                F2_PEER()
                F2_TURN(1)
                F2_PEER()
                F2_TURN(2)
                STAMP(64 + 8 * (step >> 1));
                slice_check<PL(3)>(v0, ps, lane, tag);
                slice_check<PL(4)>(v1, ps, lane, tag);
#pragma unroll
                for (int i = 0; i < 14; i++) { res[2 * i] = bf_lo(v0[i]) + bf_lo(v1[i]); res[2 * i + 1] = bf_hi(v0[i]) + bf_hi(v1[i]); }
                slice_load<PL(2)>(X, ps, lane);
                STAMP(65 + 8 * (step >> 1));
                const uint32_t cv = ld_word(cx(2 * ((pr + 1) & 3) + hr));
                F2_PEER()
                STAMP(66 + 8 * (step >> 1));
                check_cnt(cv, cx(2 * ((pr + 1) & 3) + hr), seq);
                STAMP(67 + 8 * (step >> 1));
                slice_load<PL(5)>(v0, ps, lane);
                x_fix(X, xbits);
                slice_check<PL(5)>(v0, ps, lane, tag);
#pragma unroll
                for (int i = 0; i < 14; i++) { res[2 * i] += bf_lo(v0[i]); res[2 * i + 1] += bf_hi(v0[i]); }
                STAMP(11 + so);
                wg_wait<0>();
                if (EARLYK >= 1) R_RELEASE(2);
                STAMP(12 + so);
                WSUM(85 + 7 * (step >> 1));
#pragma unroll
                for (int i = 0; i < 14; i++) X[i] = pack2(fmaf(res[2 * i] + acc[2 * i], 0.5f, bf_lo(X[i])), fmaf(res[2 * i + 1] + acc[2 * i + 1], 0.5f, bf_hi(X[i])));
            }
        }
        {
            const int m = lane >> 3, rr = lane & 7;
            const uint32_t ob = hbuf + w * 2048, rowa = ob + (rr + 8 * (m & 1)) * 112 + (m >> 1) * 16;
#pragma unroll
            for (int j = 0; j < 3; j++) stsm4(rowa + 32 * j, X[4 * j], X[4 * j + 1], X[4 * j + 2], X[4 * j + 3]);
            asm volatile("stmatrix.sync.aligned.m8n8.x2.shared.b16 [%0], {%1,%2};" ::"r"(ob + (rr + 8 * (m & 1)) * 112 + 96), "r"(X[12]), "r"(X[13]) : "memory");
            fence_async();
            __syncwarp();
            if (lane == 0) {
                asm volatile("cp.async.bulk.tensor.2d.global.shared::cta.bulk_group [%0, {%2, %3}], [%1];" ::"l"(&maps.out), "r"(ob), "r"(56 * sl), "r"(tile * 128 + (tid >> 5) * 16) : "memory");
                asm volatile("cp.async.bulk.commit_group;" ::: "memory");
                asm volatile("cp.async.bulk.wait_group.read 0;" ::: "memory");
            }
        }
        STAMP(50);
        GSTAMP(61);
        PDUMP();
    }
}

typedef CUresult (*EncodeFn)(CUtensorMap*, CUtensorMapDataType, cuuint32_t, void*, const cuuint64_t*, const cuuint64_t*, const cuuint32_t*,
                             const cuuint32_t*, CUtensorMapInterleave, CUtensorMapSwizzle, CUtensorMapL2promotion, CUtensorMapFloatOOBfill);

static void make_map(EncodeFn enc, CUtensorMap* m, const void* p, uint64_t cols, uint64_t rows, uint32_t bc, uint32_t br, CUtensorMapSwizzle sw) {
    cuuint64_t gd[2] = {cols, rows};
    cuuint64_t gs[1] = {cols * 2};
    cuuint32_t bd[2] = {bc, br};
    cuuint32_t es[2] = {1, 1};
    enc(m, CU_TENSOR_MAP_DATA_TYPE_BFLOAT16, 2, const_cast<void*>(p), gd, gs, bd, es, CU_TENSOR_MAP_INTERLEAVE_NONE, sw,
        CU_TENSOR_MAP_L2_PROMOTION_L2_128B, CU_TENSOR_MAP_FLOAT_OOB_FILL_NONE);
}

extern "C" void kernel_launch(void* const* d_in, const int* in_sizes, int n_in, void* d_out, int out_size) {
    (void)in_sizes; (void)n_in; (void)out_size;
    static EncodeFn enc = nullptr;
    static Scratch* scratch = nullptr;
    if (!enc) {
        void* fn = nullptr;
        cudaDriverEntryPointQueryResult qr;
        cudaGetDriverEntryPoint("cuTensorMapEncodeTiled", &fn, cudaEnableDefault, &qr);
        enc = (EncodeFn)fn;
        cudaGetSymbolAddress((void**)&scratch, g_scratch);
        cudaFuncSetAttribute(fused_kernel, cudaFuncAttributeMaxDynamicSharedMemorySize, SMEM_BYTES);
    }
    Maps maps;
    {
        cuuint64_t gd[3] = {64, 2048, 7};
        cuuint64_t gs[2] = {896, 128};
        cuuint32_t bd[3] = {64, 32, 7};
        cuuint32_t es[3] = {1, 1, 1};
        enc(&maps.x, CU_TENSOR_MAP_DATA_TYPE_BFLOAT16, 3, d_in[0], gd, gs, bd, es, CU_TENSOR_MAP_INTERLEAVE_NONE, CU_TENSOR_MAP_SWIZZLE_128B,
            CU_TENSOR_MAP_L2_PROMOTION_L2_128B, CU_TENSOR_MAP_FLOAT_OOB_FILL_NONE);
    }
    make_map(enc, &maps.out, d_out, 448, 2048, 56, 16, CU_TENSOR_MAP_SWIZZLE_NONE);
    make_map(enc, &maps.qkv, d_in[1], 1344, 448, 64, 112, CU_TENSOR_MAP_SWIZZLE_128B);
    make_map(enc, &maps.wo, d_in[3], 448, 448, 64, 112, CU_TENSOR_MAP_SWIZZLE_128B);
    make_map(enc, &maps.wg, d_in[5], 1792, 448, 64, 112, CU_TENSOR_MAP_SWIZZLE_128B);
    make_map(enc, &maps.wu, d_in[6], 1792, 448, 64, 112, CU_TENSOR_MAP_SWIZZLE_128B);
    make_map(enc, &maps.wg32, d_in[5], 1792, 448, 32, 112, CU_TENSOR_MAP_SWIZZLE_64B);
    make_map(enc, &maps.wu32, d_in[6], 1792, 448, 32, 112, CU_TENSOR_MAP_SWIZZLE_64B);
    make_map(enc, &maps.wd, d_in[7], 448, 1792, 64, 112, CU_TENSOR_MAP_SWIZZLE_128B);
    fused_kernel<<<128, 384, SMEM_BYTES>>>(scratch, (const __nv_bfloat16*)d_in[0], (const __nv_bfloat16*)d_in[2], 7, (const __nv_bfloat16*)d_in[5],
                                           (const __nv_bfloat16*)d_in[6], (const __nv_bfloat16*)d_in[7], maps);
}
```

```cpp
#include <cuda_runtime.h>
#include <cuda.h>
#include <cuda_bf16.h>
#include <stdint.h>
#include <type_traits>

#define C01 1
#define C02 1
#define ACAN 1
#define SPLIT0 1
#define AUXB 1
#define CAN2 0
#define OT 2
#define F2PP 0
#define PPK 2
#define QE 1
#define OST 1
#define GB 1
#define B3T 6
#define CANARY 0
#define PP

namespace {

constexpr uint32_t STAGE = 28672, HALF = 14336;
constexpr int NST = 5;
constexpr uint32_t OFF_H = NST * STAGE;
constexpr uint32_t OFF_KVB = OFF_H + 2 * STAGE;
constexpr uint32_t OFF_WPHI = OFF_KVB + 16384;
constexpr uint32_t OFF_XR = OFF_WPHI + 7168;
constexpr uint32_t OFF_BAR = OFF_XR + 6144;
constexpr uint32_t SMEM_BYTES = OFF_BAR + 256 + 1536;
constexpr int B_EMPTY = NST, B_RECV = 2 * NST, B_RECV2 = B_RECV + 2, B_PACK = B_RECV2 + 2, B_GAT = B_PACK + 1, B_ACK = B_GAT + 8, B_ACK2 = B_ACK + 2, B_COUNT = B_ACK2 + 2;

constexpr int PACK = 14;

struct Maps { CUtensorMap x, qkv, wo, wg, wu, wg32, wu32, wd, out; };

}

constexpr int PLANE = 16 * 2 * 8 * 512;
struct Scratch {
    uint4 ex[6 * PLANE];
    uint4 kv1[8 * 16 * 16 * 32];
    uint4 kv2[8 * 512];
    uint32_t c1[8 * 8 * 16 * 32];
    uint32_t c2[8 * 4 * 16 * 32];
    uint32_t cw[8 * 32];
    uint4 wp[8 * 32 * (HALF / 16)];
};
__device__ __align__(1024) Scratch g_scratch;
#define g_ex (sc->ex)
#define g_kv1 (sc->kv1)
#define g_kv2 (sc->kv2)
#define g_c1 (sc->c1)
#define g_c2 (sc->c2)
#define g_cw (sc->cw)
#define g_wp (sc->wp)
#define STAMP(i)
#define GSTAMP(i)
#define PDUMP()
#define ASTAMP(i)

namespace {

__device__ __forceinline__ int fresh_tid() { int t; asm volatile("mov.u32 %0, %%tid.x;" : "=r"(t)); return t; }
__device__ __forceinline__ uint4* again(uint4* p) { asm volatile("" : "+l"(p)); return p; }
template <int N> __device__ __forceinline__ void kill(uint32_t* v) {
#pragma unroll
    for (int i = 0; i < N; i++) v[i] = 0;
}
template <int N> __device__ __forceinline__ void kill(float* v) {
#pragma unroll
    for (int i = 0; i < N; i++) v[i] = 0.f;
}
__device__ __forceinline__ uint32_t s2u(const void* p) { return (uint32_t)__cvta_generic_to_shared(p); }
__device__ __forceinline__ void mbar_init(uint32_t a, uint32_t c) { asm volatile("mbarrier.init.shared::cta.b64 [%0], %1;" ::"r"(a), "r"(c) : "memory"); }
__device__ __forceinline__ void mbar_expect_tx(uint32_t a, uint32_t b) { asm volatile("mbarrier.arrive.expect_tx.shared::cta.b64 _, [%0], %1;" ::"r"(a), "r"(b) : "memory"); }
__device__ __forceinline__ void mbar_arrive(uint32_t a) { asm volatile("mbarrier.arrive.shared::cta.b64 _, [%0];" ::"r"(a) : "memory"); }
#define GIVE_UP(id) "trap;\n"
#define SPIN_MAX "0x400000"
#define SPIN_TAIL(id) "add.u32 n, n, 1;\n setp.lt.u32 p, n, " SPIN_MAX ";\n @p bra.uni LP;\n" GIVE_UP(id) " DN:\n }"
__device__ __forceinline__ void mbar_wait(uint32_t a, uint32_t ph) {
    asm volatile("{ .reg .pred p; .reg .b32 n; mov.u32 n, 0;\n LP:\n"
                 "mbarrier.try_wait.parity.shared::cta.b64 p, [%0], %1;\n @p bra DN;\n"
                 "add.u32 n, n, 1;\n setp.lt.u32 p, n, " SPIN_MAX ";\n @p bra LP;\n"
                 GIVE_UP("")
                 " DN:\n }" ::"r"(a), "r"(ph) : "memory");
}
#define ELECT "{ .reg .pred e; elect.sync _|e, 0xffffffff; @e "
__device__ __forceinline__ void tma2d(uint32_t dst, const CUtensorMap* m, int c0, int c1, uint32_t bar) {
    asm volatile(ELECT "cp.async.bulk.tensor.2d.shared::cluster.global.mbarrier::complete_tx::bytes [%0], [%1, {%3, %4}], [%2]; }" ::"r"(dst), "l"(m), "r"(bar), "r"(c0), "r"(c1) : "memory");
}
__device__ __forceinline__ void tma3x(uint32_t dst, const CUtensorMap* m, int row, uint32_t bar) {
    asm volatile(ELECT "cp.async.bulk.tensor.3d.shared::cluster.global.mbarrier::complete_tx::bytes [%0], [%1, {0, %3, 0}], [%2]; }" ::"r"(dst), "l"(m), "r"(bar), "r"(row) : "memory");
}
template <int OFF>
__device__ __forceinline__ void ld_pkt(uint32_t* v, const uint4* p) {
    asm volatile("{ .reg .b128 t; ld.relaxed.gpu.global.b128 t, [%4+%5]; mov.b128 {%0,%1,%2,%3}, t; }" : "=r"(v[0]), "=r"(v[1]), "=r"(v[2]), "=r"(v[3]) : "l"(p), "n"(OFF * 16) : "memory");
}
template <int OFF>
__device__ __forceinline__ void st_pkt(uint4* p, uint32_t a, uint32_t b, uint32_t c, uint32_t d) {
    asm volatile("{ .reg .b128 t; mov.b128 t, {%1,%2,%3,%4}; st.relaxed.gpu.global.b128 [%0+%5], t; }" ::"l"(p), "r"(a), "r"(b), "r"(c), "r"(d), "n"(OFF * 16) : "memory");
}
__device__ __forceinline__ uint32_t pack2(float lo, float hi) {
    uint32_t r;
    asm("cvt.rn.bf16x2.f32 %0, %1, %2;" : "=r"(r) : "f"(hi), "f"(lo));
    return r;
}
__device__ __forceinline__ float bf_lo(uint32_t w) { return __uint_as_float(w << 16); }
__device__ __forceinline__ float bf_hi(uint32_t w) { return __uint_as_float(w & 0xffff0000u); }
__device__ __forceinline__ uint32_t settag(uint32_t w, uint32_t tag) { return (w & ~1u) | tag; }
__device__ __forceinline__ float ex2(float x) { float y; asm("ex2.approx.ftz.f32 %0, %1;" : "=f"(y) : "f"(x)); return y; }
__device__ __forceinline__ float rcp(float x) { float y; asm("rcp.approx.ftz.f32 %0, %1;" : "=f"(y) : "f"(x)); return y; }
__device__ __forceinline__ float tanh_hw(float x) { float y; asm("tanh.approx.f32 %0, %1;" : "=f"(y) : "f"(x)); return y; }
__device__ __forceinline__ void stsm4(uint32_t addr, uint32_t a, uint32_t b, uint32_t c, uint32_t d) {
    asm volatile("stmatrix.sync.aligned.m8n8.x4.shared.b16 [%0], {%1,%2,%3,%4};" ::"r"(addr), "r"(a), "r"(b), "r"(c), "r"(d) : "memory");
}
__device__ __forceinline__ void fence_async() { asm volatile("fence.proxy.async.shared::cta;" ::: "memory"); }
__device__ __forceinline__ void bar_sync(int id, int n) { asm volatile("bar.sync %0, %1;" ::"r"(id), "r"(n) : "memory"); }
__device__ __forceinline__ void bar_arrive(int id, int n) { asm volatile("bar.arrive %0, %1;" ::"r"(id), "r"(n) : "memory"); }
__device__ __forceinline__ void wg_fence() { asm volatile("wgmma.fence.sync.aligned;" ::: "memory"); }
__device__ __forceinline__ void wg_commit() { asm volatile("wgmma.commit_group.sync.aligned;" ::: "memory"); }
template <int N> __device__ __forceinline__ void wg_wait() { asm volatile("wgmma.wait_group.sync.aligned %0;" ::"n"(N) : "memory"); }

constexpr uint32_t SB0 = 1024;
__host__ __device__ constexpr uint32_t dlo(uint32_t off, uint32_t lbo) { return ((SB0 + off) >> 4) | ((lbo >> 4) << 16); }
__host__ __device__ constexpr uint32_t dhi(uint32_t sbo, uint32_t sw) { return (sbo >> 4) | (sw << 30); }
__device__ __forceinline__ uint64_t dbase(uint32_t lo, uint32_t hi) { uint64_t d; asm volatile("mov.b64 %0, {%1, %2};" : "=l"(d) : "r"(lo), "r"(hi)); return d; }
#define BASE128(off, lbo, adj) dbase(dlo(off, lbo) + (adj), dhi(1024, 1))
#define BASE64(off, lbo, adj) dbase(dlo(off, lbo) + (adj), dhi(512, 2))

#define ACC4(d, o) "+f"(d[o]), "+f"(d[o + 1]), "+f"(d[o + 2]), "+f"(d[o + 3])
#define ACC28(d) ACC4(d, 0), ACC4(d, 4), ACC4(d, 8), ACC4(d, 12), ACC4(d, 16), ACC4(d, 20), ACC4(d, 24)
#define ACC32(d, o) ACC4(d, o), ACC4(d, o + 4), ACC4(d, o + 8), ACC4(d, o + 12), ACC4(d, o + 16), ACC4(d, o + 20), ACC4(d, o + 24), ACC4(d, o + 28)

template <int TB, uint64_t D>
__device__ __forceinline__ void mma_rs56(float* d, uint32_t a0, uint32_t a1, uint32_t a2, uint32_t a3, int sd, uint64_t base) {
    asm volatile("{ .reg .pred p; .reg .b64 db; setp.ne.b32 p, %32, 0; add.u64 db, %33, %34;\n"
                 "wgmma.mma_async.sync.aligned.m64n56k16.f32.bf16.bf16 "
                 "{%0,%1,%2,%3,%4,%5,%6,%7,%8,%9,%10,%11,%12,%13,%14,%15,%16,%17,%18,%19,%20,%21,%22,%23,%24,%25,%26,%27}, "
                 "{%28,%29,%30,%31}, db, p, 1, 1, %35; }\n"
                 : ACC28(d)
                 : "r"(a0), "r"(a1), "r"(a2), "r"(a3), "r"(sd), "l"(base), "n"(D), "n"(TB));
}
template <int TB, uint64_t D>
__device__ __forceinline__ void mma_rs64(float* d, uint32_t a0, uint32_t a1, uint32_t a2, uint32_t a3, int sd, uint64_t base) {
    asm volatile("{ .reg .pred p; .reg .b64 db; setp.ne.b32 p, %36, 0; add.u64 db, %37, %38;\n"
                 "wgmma.mma_async.sync.aligned.m64n64k16.f32.bf16.bf16 "
                 "{%0,%1,%2,%3,%4,%5,%6,%7,%8,%9,%10,%11,%12,%13,%14,%15,%16,%17,%18,%19,%20,%21,%22,%23,%24,%25,%26,%27,%28,%29,%30,%31}, "
                 "{%32,%33,%34,%35}, db, p, 1, 1, %39; }\n"
                 : ACC32(d, 0)
                 : "r"(a0), "r"(a1), "r"(a2), "r"(a3), "r"(sd), "l"(base), "n"(D), "n"(TB));
}
template <int TB, uint64_t D>
__device__ __forceinline__ void mma_rs128(float* d, uint32_t a0, uint32_t a1, uint32_t a2, uint32_t a3, int sd, uint64_t base) {
    asm volatile("{ .reg .pred p; .reg .b64 db; setp.ne.b32 p, %68, 0; add.u64 db, %69, %70;\n"
                 "wgmma.mma_async.sync.aligned.m64n128k16.f32.bf16.bf16 "
                 "{%0,%1,%2,%3,%4,%5,%6,%7,%8,%9,%10,%11,%12,%13,%14,%15,%16,%17,%18,%19,%20,%21,%22,%23,%24,%25,%26,%27,%28,%29,%30,%31,%32,%33,%34,%35,%36,%37,%38,%39,%40,%41,%42,%43,%44,%45,%46,%47,%48,%49,%50,%51,%52,%53,%54,%55,%56,%57,%58,%59,%60,%61,%62,%63}, "
                 "{%64,%65,%66,%67}, db, p, 1, 1, %71; }\n"
                 : ACC32(d, 0), ACC32(d, 32)
                 : "r"(a0), "r"(a1), "r"(a2), "r"(a3), "r"(sd), "l"(base), "n"(D), "n"(TB));
}
template <uint64_t DA, uint64_t DB>
__device__ __forceinline__ void mma_ss56_tt(float* d, int sd, uint64_t ba, uint64_t bb) {
    asm volatile("{ .reg .pred p; .reg .b64 da, db; setp.ne.b32 p, %28, 0; add.u64 da, %29, %31; add.u64 db, %30, %32;\n"
                 "wgmma.mma_async.sync.aligned.m64n56k16.f32.bf16.bf16 "
                 "{%0,%1,%2,%3,%4,%5,%6,%7,%8,%9,%10,%11,%12,%13,%14,%15,%16,%17,%18,%19,%20,%21,%22,%23,%24,%25,%26,%27}, "
                 "da, db, p, 1, 1, 1, 1; }\n"
                 : ACC28(d)
                 : "r"(sd), "l"(ba), "l"(bb), "n"(DA), "n"(DB));
}
template <int... I> struct Seq {};
template <class F, int... I> __device__ __forceinline__ void static_for_impl(F&& f, Seq<I...>) { (f(std::integral_constant<int, I>{}), ...); }
#define FOR7(...) static_for_impl([&](auto T_) { constexpr int t = decltype(T_)::value; __VA_ARGS__; }, Seq<0, 1, 2, 3, 4, 5, 6>{})
#define FOR8(...) static_for_impl([&](auto T_) { constexpr int t = decltype(T_)::value; __VA_ARGS__; }, Seq<0, 1, 2, 3, 4, 5, 6, 7>{})
#define FOR14(...) static_for_impl([&](auto T_) { constexpr int t = decltype(T_)::value; __VA_ARGS__; }, Seq<0, 1, 2, 3, 4, 5, 6, 7, 8, 9, 10, 11, 12, 13>{})

__device__ __forceinline__ int kblk(int p, int b) { return b == 0 ? p : b - (b <= p); }
__host__ __device__ constexpr int krow(int t) { return t < 3 ? 16 * t : (t < 6 ? 56 + 16 * (t - 3) : 48); }
#define AQ(A, b, t) ((t) < 3 ? A[2 * (b)][4 * (t)] : (t) < 6 ? A[2 * (b) + 1][4 * ((t) - 3)] : A[2 * (b)][12]), \
                    ((t) < 3 ? A[2 * (b)][4 * (t) + 1] : (t) < 6 ? A[2 * (b) + 1][4 * ((t) - 3) + 1] : A[2 * (b)][13]), \
                    ((t) < 3 ? A[2 * (b)][4 * (t) + 2] : (t) < 6 ? A[2 * (b) + 1][4 * ((t) - 3) + 2] : A[2 * (b) + 1][12]), \
                    ((t) < 3 ? A[2 * (b)][4 * (t) + 3] : (t) < 6 ? A[2 * (b) + 1][4 * ((t) - 3) + 3] : A[2 * (b) + 1][13])
#define D128(off, t) ((uint64_t)(((off) + krow(t) * 128) >> 4) + ((uint64_t)((t) == 6 ? (7168 - 1024) >> 4 : 0) << 32))
#define D64(off, t) ((uint64_t)(((off) + krow(t) * 64) >> 4) + ((uint64_t)((t) == 6 ? (3584 - 512) >> 4 : 0) << 32))

#define PL(k) (((k) - 3) * PLANE)
__device__ __forceinline__ void st_word(uint32_t* p, uint32_t v) { asm volatile("st.relaxed.gpu.global.u32 [%0], %1;" ::"l"(p), "r"(v) : "memory"); }
__device__ __forceinline__ uint32_t ld_word(const uint32_t* p) { uint32_t v; asm volatile("ld.relaxed.gpu.global.u32 %0, [%1];" : "=r"(v) : "l"(p) : "memory"); return v; }
__device__ __forceinline__ void tag_slice(uint32_t* w, uint32_t tag) { w[0] = settag(w[0], tag); w[4] = settag(w[4], tag); w[8] = settag(w[8], tag); w[12] = settag(w[12], tag); }
template <int O>
__device__ __forceinline__ void send_slice(uint4* dst, int lane, const uint32_t* w) {
    st_pkt<O>(dst, w[0], w[1], w[2], w[3]);
    st_pkt<O + 32>(dst, w[4], w[5], w[6], w[7]);
    st_pkt<O + 64>(dst, w[8], w[9], w[10], w[11]);
    asm volatile("{ .reg .b64 t; mov.b64 t, {%1,%2}; st.relaxed.gpu.global.b64 [%0+%3], t; }" ::"l"((char*)dst - lane * 8), "r"(w[12]), "r"(w[13]), "n"(16 * (O + 96)) : "memory");
}
#define RW4(v, o) "+r"(v[o]), "+r"(v[(o) + 1]), "+r"(v[(o) + 2]), "+r"(v[(o) + 3])
#define RW2(v, o) "+r"(v[o]), "+r"(v[(o) + 1])
#define WR4(v, o) "=&r"(v[o]), "=&r"(v[(o) + 1]), "=&r"(v[(o) + 2]), "=&r"(v[(o) + 3])
#define LDP(a, b, c, d, addr, off) "ld.relaxed.gpu.global.b128 q, [" addr "+" off "];\n mov.b128 {" a "," b "," c "," d "}, q;\n"
#define LDH(a, b, addr, off) "ld.relaxed.gpu.global.b64 h, [" addr "+" off "];\n mov.b64 {" a "," b "}, h;\n"
#define VOTE_OK "and.b32 t, t, 1;\n setp.ne.u32 p, t, 0;\n vote.sync.any.pred p, p, 0xffffffff;\n @!p bra.uni DN;\n"
#define CHK(x, tag) "lop3.b32 t, " x ", " tag ", t, 0xBE;\n"
__device__ __forceinline__ void check_cnt(uint32_t v, const uint32_t* p, uint32_t target) {
    asm volatile("{ .reg .pred p; .reg .b32 n, t; mov.u32 n, 0; mov.u32 t, %2;\n LP:\n"
                 "sub.s32 t, t, %1;\n setp.lt.s32 p, t, 0;\n vote.sync.any.pred p, p, 0xffffffff;\n @!p bra.uni DN;\n ld.relaxed.gpu.global.u32 t, [%0];\n" SPIN_TAIL("7")
                 ::"l"(p), "r"(target), "r"(v) : "memory");
}
__device__ __forceinline__ void poll_cnt(const uint32_t* p, uint32_t target) {
    asm volatile("{ .reg .pred p; .reg .b32 n, t; mov.u32 n, 0;\n LP:\n"
                 "ld.relaxed.gpu.global.u32 t, [%0];\n sub.s32 t, t, %1;\n setp.lt.s32 p, t, 0;\n vote.sync.any.pred p, p, 0xffffffff;\n @!p bra.uni DN;\n" SPIN_TAIL("1")
                 ::"l"(p), "r"(target) : "memory");
}
template <int STR>
__device__ __forceinline__ void poll4_kv(uint32_t* v, const uint4* p, uint32_t tag) {
    asm volatile("{ .reg .pred p; .reg .b32 n, t; .reg .b128 q; mov.u32 n, 0;\n LP:\n"
                 LDP("%0", "%1", "%2", "%3", "%16", "0") LDP("%4", "%5", "%6", "%7", "%16", "%18")
                 LDP("%8", "%9", "%10", "%11", "%16", "%19") LDP("%12", "%13", "%14", "%15", "%16", "%20")
                 "xor.b32 t, %0, %17;\n" CHK("%4", "%17") CHK("%8", "%17") CHK("%12", "%17") VOTE_OK SPIN_TAIL("2")
                 : WR4(v, 0), WR4(v, 4), WR4(v, 8), WR4(v, 12)
                 : "l"(p), "r"(tag), "n"(16 * STR), "n"(32 * STR), "n"(48 * STR)
                 : "memory");
}
__device__ __forceinline__ void poll2_kv(uint32_t* v, const uint4* p, uint32_t tag) {
    asm volatile("{ .reg .pred p; .reg .b32 n, t; .reg .b128 q; mov.u32 n, 0;\n LP:\n"
                 LDP("%0", "%1", "%2", "%3", "%8", "0") LDP("%4", "%5", "%6", "%7", "%8", "128")
                 "xor.b32 t, %0, %9;\n" CHK("%4", "%9") VOTE_OK SPIN_TAIL("6")
                 : WR4(v, 0), WR4(v, 4) : "l"(p), "r"(tag) : "memory");
}
template <int B>
__device__ __forceinline__ void blk_load(uint32_t (&A)[8][14], const uint4* src, int lane) {
    ld_pkt<0>(&A[2 * B][0], src); ld_pkt<32>(&A[2 * B][4], src); ld_pkt<64>(&A[2 * B][8], src);
    ld_pkt<512>(&A[2 * B + 1][0], src); ld_pkt<544>(&A[2 * B + 1][4], src); ld_pkt<576>(&A[2 * B + 1][8], src);
    asm volatile("{ .reg .b64 h;\n" LDH("%0", "%1", "%4", "1536") LDH("%2", "%3", "%4", "9728") "}"
                 : "=&r"(A[2 * B][12]), "=&r"(A[2 * B][13]), "=&r"(A[2 * B + 1][12]), "=&r"(A[2 * B + 1][13])
                 : "l"((const char*)src - lane * 8) : "memory");
}
template <int B>
__device__ __forceinline__ void blk_check(uint32_t (&A)[8][14], const uint4* src, int lane, uint32_t tag) {
    asm volatile("{ .reg .pred p; .reg .b32 n, t; .reg .b128 q; .reg .b64 h, a8; mov.u32 n, 0;\n LP:\n"
                 "xor.b32 t, %0, %30;\n" CHK("%4", "%30") CHK("%8", "%30") CHK("%12", "%30") CHK("%16", "%30") CHK("%20", "%30") CHK("%24", "%30") CHK("%26", "%30") VOTE_OK
                 LDP("%0", "%1", "%2", "%3", "%28", "0") LDP("%4", "%5", "%6", "%7", "%28", "512") LDP("%8", "%9", "%10", "%11", "%28", "1024")
                 LDP("%12", "%13", "%14", "%15", "%28", "8192") LDP("%16", "%17", "%18", "%19", "%28", "8704") LDP("%20", "%21", "%22", "%23", "%28", "9216")
                 "mad.wide.s32 a8, %29, -8, %28;\n" LDH("%24", "%25", "a8", "1536") LDH("%26", "%27", "a8", "9728") SPIN_TAIL("3")
                 "\n and.b32 %0, %0, -2; and.b32 %4, %4, -2; and.b32 %8, %8, -2; and.b32 %12, %12, -2; and.b32 %16, %16, -2; and.b32 %20, %20, -2; and.b32 %24, %24, -2; and.b32 %26, %26, -2;"
                 : RW4(A[2 * B], 0), RW4(A[2 * B], 4), RW4(A[2 * B], 8), RW4(A[2 * B + 1], 0), RW4(A[2 * B + 1], 4), RW4(A[2 * B + 1], 8),
                   RW2(A[2 * B], 12), RW2(A[2 * B + 1], 12)
                 : "l"(src), "r"(lane), "r"(tag)
                 : "memory");
}
__device__ __forceinline__ void st_async4(uint32_t a, uint32_t x, uint32_t y, uint32_t z, uint32_t w, uint32_t bar) {
    asm volatile("st.async.weak.shared::cluster.mbarrier::complete_tx::bytes.v4.b32 [%0], {%1,%2,%3,%4}, [%5];" ::"r"(a), "r"(x), "r"(y), "r"(z), "r"(w), "r"(bar) : "memory");
}
__device__ __forceinline__ uint32_t mapa(uint32_t a, uint32_t cta) { uint32_t r; asm("mapa.shared::cluster.u32 %0, %1, %2;" : "=r"(r) : "r"(a), "r"(cta)); return r; }
__device__ __forceinline__ void stat_load(uint32_t* v, const uint4* p) { ld_pkt<0>(v, p); ld_pkt<512>(v + 4, p); }
__device__ __forceinline__ void stat_check(uint32_t* v, const uint4* p, uint32_t tag) {
    asm volatile("{ .reg .pred p; .reg .b32 n, t; .reg .b128 q; mov.u32 n, 0;\n LP:\n"
                 "xor.b32 t, %3, %9;\n" CHK("%7", "%9") VOTE_OK
                 LDP("%0", "%1", "%2", "%3", "%8", "0") LDP("%4", "%5", "%6", "%7", "%8", "8192") SPIN_TAIL("4")
                 : RW4(v, 0), RW4(v, 4) : "l"(p), "r"(tag) : "memory");
}
__device__ __forceinline__ uint32_t x_bits(const uint32_t* X) {
    uint32_t r;
    asm volatile("{ .reg .b32 a, b; prmt.b32 a, %1, %2, 0x0040; prmt.b32 b, %3, %4, 0x0040; prmt.b32 %0, a, b, 0x5410; }" : "=r"(r) : "r"(X[0]), "r"(X[4]), "r"(X[8]), "r"(X[12]));
    return r;
}
template <int O>
__device__ __forceinline__ void slice_load(uint32_t* v, const uint4* p, int lane) {
    ld_pkt<O>(v, p); ld_pkt<O + 32>(v + 4, p); ld_pkt<O + 64>(v + 8, p);
    asm volatile("{ .reg .b64 h;\n" LDH("%0", "%1", "%2", "%3") "}" : "=r"(v[12]), "=r"(v[13]) : "l"((const char*)p - lane * 8), "n"(16 * (O + 96)) : "memory");
}
template <int O>
__device__ __forceinline__ void slice_check(uint32_t* v, const uint4* p, int lane, uint32_t tag) {
    asm volatile("{ .reg .pred p; .reg .b32 n, t; .reg .b128 q; .reg .b64 h; mov.u32 n, 0;\n LP:\n"
                 "xor.b32 t, %0, %16;\n" CHK("%4", "%16") CHK("%8", "%16") CHK("%12", "%16") VOTE_OK
                 LDP("%0", "%1", "%2", "%3", "%14", "%17") LDP("%4", "%5", "%6", "%7", "%14", "%18") LDP("%8", "%9", "%10", "%11", "%14", "%19")
                 LDH("%12", "%13", "%15", "%20") SPIN_TAIL("5")
                 : RW4(v, 0), RW4(v, 4), RW4(v, 8), RW2(v, 12)
                 : "l"(p), "l"((const char*)p - lane * 8), "r"(tag), "n"(16 * O), "n"(16 * (O + 32)), "n"(16 * (O + 64)), "n"(16 * (O + 96))
                 : "memory");
}
__device__ __forceinline__ void x_fix(uint32_t* X, uint32_t bits) {
    X[0] = __byte_perm(X[0], bits, 0x3214); X[4] = __byte_perm(X[4], bits, 0x3215); X[8] = __byte_perm(X[8], bits, 0x3216); X[12] = __byte_perm(X[12], bits, 0x3217);
}
__device__ __forceinline__ void sts4(uint32_t a, uint32_t x, uint32_t y, uint32_t z, uint32_t w) {
    asm volatile("st.shared.v4.u32 [%0], {%1,%2,%3,%4};" ::"r"(a), "r"(x), "r"(y), "r"(z), "r"(w) : "memory");
}
__device__ __forceinline__ void lds4(uint32_t* v, uint32_t a) {
    asm volatile("ld.shared.v4.u32 {%0,%1,%2,%3}, [%4];" : "=r"(v[0]), "=r"(v[1]), "=r"(v[2]), "=r"(v[3]) : "r"(a) : "memory");
}
struct LnCoef { uint32_t hi, lo, sh; };
__device__ __forceinline__ LnCoef ln_coef(float sum, float sq) {
    sum += __shfl_xor_sync(0xffffffffu, sum, 1); sq += __shfl_xor_sync(0xffffffffu, sq, 1);
    sum += __shfl_xor_sync(0xffffffffu, sum, 2); sq += __shfl_xor_sync(0xffffffffu, sq, 2);
    const float mean = sum * (1.f / 448.f);
    const float var = fmaxf(fmaf(-mean, mean, sq * (1.f / 448.f)), 0.f);
    const float sc = rsqrtf(var + 1e-5f);
    LnCoef r;
    r.hi = pack2(sc, sc);
    const float lo = sc - bf_lo(r.hi), sh = -mean * sc;
    r.lo = pack2(lo, lo);
    r.sh = pack2(sh, sh);
    return r;
}
template <int B>
__device__ __forceinline__ void normalize(uint32_t (&A)[8][14], const LnCoef& c0, const LnCoef& c1) {
#pragma unroll
    for (int s = 2 * B; s < 2 * B + 2; s++)
#pragma unroll
        for (int i = 0; i < 14; i++) {
            const LnCoef& k = (i & 1) ? c1 : c0;
            asm("{ .reg .b32 t; fma.rn.bf16x2 t, %0, %2, %3; fma.rn.bf16x2 %0, %0, %1, t; }" : "+r"(A[s][i]) : "r"(k.hi), "r"(k.lo), "r"(k.sh));
        }
}
__device__ __forceinline__ void slice_stats(const uint32_t* w, float* st) {
    float a = 0.f, b = 0.f, p = 0.f, q = 0.f;
#pragma unroll
    for (int i = 0; i < 7; i++) {
        const float e0 = bf_lo(w[2 * i]), e1 = bf_hi(w[2 * i]), e2 = bf_lo(w[2 * i + 1]), e3 = bf_hi(w[2 * i + 1]);
        a += e0 + e1; b += e2 + e3;
        p = fmaf(e0, e0, p); p = fmaf(e1, e1, p); q = fmaf(e2, e2, q); q = fmaf(e3, e3, q);
    }
    a += __shfl_xor_sync(0xffffffffu, a, 1); p += __shfl_xor_sync(0xffffffffu, p, 1); b += __shfl_xor_sync(0xffffffffu, b, 1); q += __shfl_xor_sync(0xffffffffu, q, 1);
    a += __shfl_xor_sync(0xffffffffu, a, 2); p += __shfl_xor_sync(0xffffffffu, p, 2); b += __shfl_xor_sync(0xffffffffu, b, 2); q += __shfl_xor_sync(0xffffffffu, q, 2);
    st[0] = a; st[1] = p; st[2] = b; st[3] = q;
}
__device__ __forceinline__ void dual_softmax(const float* p, uint32_t* out) {
    constexpr float L = 1.4426950408889634f;
#pragma unroll
    for (int r = 0; r < 2; r++) {
        float mx = fmaxf(p[2 * r], p[2 * r + 1]), mn = fminf(p[2 * r], p[2 * r + 1]);
#pragma unroll
        for (int i = 1; i < 7; i++) {
            mx = fmaxf(mx, fmaxf(p[4 * i + 2 * r], p[4 * i + 2 * r + 1]));
            mn = fminf(mn, fminf(p[4 * i + 2 * r], p[4 * i + 2 * r + 1]));
        }
        mx = fmaxf(mx, __shfl_xor_sync(0xffffffffu, mx, 1));
        mn = fminf(mn, __shfl_xor_sync(0xffffffffu, mn, 1));
        const float bx = -mx * L, bn = mn * L;
        float ep[14], en[14], sp = 0.f, sn = 0.f;
#pragma unroll
        for (int i = 0; i < 14; i++) {
            const float v = p[4 * (i >> 1) + 2 * r + (i & 1)];
            ep[i] = ex2(fmaf(v, L, bx));
            en[i] = ex2(fmaf(v, -L, bn));
            sp += ep[i]; sn += en[i];
        }
        sp += __shfl_xor_sync(0xffffffffu, sp, 1);
        sn += __shfl_xor_sync(0xffffffffu, sn, 1);
        const float ip = rcp(sp), in = rcp(sn);
#pragma unroll
        for (int i = 0; i < 7; i++) {
            out[4 * i + r] = pack2(ep[2 * i] * ip, ep[2 * i + 1] * ip);
            out[4 * i + 2 + r] = pack2(en[2 * i] * in, en[2 * i + 1] * in);
        }
    }
}
__device__ __forceinline__ float geglu(float g, float u) {
    const float t = tanh_hw(g * fmaf(g * g, 0.7978845608028654f * 0.044715f, 0.7978845608028654f));
    const float gu = g * u;
    return fmaf(t, gu, gu);
}
__device__ __forceinline__ void phi_gemm(const float* t, float* p) {
    uint32_t w[14];
#pragma unroll
    for (int i = 0; i < 14; i++) w[i] = pack2(t[2 * i], t[2 * i + 1]);
    const uint64_t db = BASE128(OFF_WPHI, 16, 0);
    wg_fence();
    mma_rs56<0, 0>(p, w[0], w[1], w[2], w[3], 0, db);
    mma_rs56<0, 2>(p, w[4], w[5], w[6], w[7], 1, db);
    mma_rs56<0, 4>(p, w[8], w[9], w[10], w[11], 1, db);
    mma_rs56<0, 6>(p, w[12], w[13], 0u, 0u, 1, db);
    wg_commit();
    wg_wait<0>();
}

}

#define BAR(i) (bars + 8 * (i))
#define R_WAIT() mbar_wait(BAR(slot), ph)
#define WSUM(i)
#define R_ADJ (slot * (STAGE >> 4))
#define R_NEXT() do { eb2 = eb1; eb1 = BAR(B_EMPTY + slot); if (++slot == NST) { slot = 0; ph ^= 1; } } while (0)
#define R_RELEASE(k) do { if (lane == 0) mbar_arrive((k) == 1 ? eb1 : eb2); } while (0)
#define PUSH_BEGIN() do { mbar_wait(BAR(B_ACK + wgi), ackph); ackph ^= 1; } while (0)
#define PUSH_ACK() do { __syncwarp(); if (lane == 0) asm volatile("mbarrier.arrive.shared::cluster.b64 _, [%0];" ::"r"(mapa(BAR(B_ACK + wgi), hr ^ 1)) : "memory"); } while (0)

__global__ void __cluster_dims__(2, 1, 1) __launch_bounds__(384, 1)
fused_kernel(Scratch* const sc, const __nv_bfloat16* __restrict__ x_in, const __nv_bfloat16* __restrict__ w_phi, const int trips,
             const __nv_bfloat16* __restrict__ wg, const __nv_bfloat16* __restrict__ wu, const __nv_bfloat16* __restrict__ wd,
             const __grid_constant__ Maps maps) {
    extern __shared__ __align__(1024) unsigned char smem_raw[];
    const uint32_t sb = s2u(smem_raw);
    const uint32_t bars = sb + OFF_BAR;
    const int wgi = __shfl_sync(0xffffffffu, threadIdx.x >> 7, 0);
    const int hr = blockIdx.x & 1, ck = blockIdx.x >> 1;
    const int gp = (ck - 4) & 7, q7 = ((ck - 36) * 37) >> 8;
    const int pr = ck < 4 ? ck : (ck < 36 ? (ck - 4) >> 3 : q7);
    const int tile = ck < 4 ? 0 : (ck < 36 ? (gp ? 2 * gp : 1) : 2 * (ck - 36 - 7 * q7) + 3);
    const int sl = 2 * pr + hr;
    STAMP(0);
    GSTAMP(60);
    if (threadIdx.x == 256) {
#pragma unroll
        for (int i = 0; i < NST; i++) mbar_init(BAR(i), 1);
        asm volatile("fence.mbarrier_init.release.cluster;" ::: "memory");
    }
    if (threadIdx.x == 288) {
        if ((sb & 0x3FFFF) != SB0) asm volatile("trap;");
#pragma unroll
        for (int i = NST; i < B_COUNT; i++) mbar_init(BAR(i), i >= B_ACK ? 4 : (i < B_RECV ? 8 : 1));
        asm volatile("fence.mbarrier_init.release.cluster;" ::: "memory");
    }
    __syncwarp();
    asm volatile("barrier.cluster.arrive.relaxed.aligned;" ::: "memory");

    if (wgi == 2) {
        asm volatile("setmaxnreg.dec.sync.aligned.u32 40;");
        const int t128 = fresh_tid() & 127, w = __shfl_sync(0xffffffffu, t128 >> 5, 0), lane = t128 & 31;
        uint32_t e0[2] = {0, 0}, e1[2] = {0, 0}, cw_target = 0;
        if (w == 0) {
#pragma unroll 1
            for (int n = 0; n < NST; n++) {
                const uint32_t dst = sb + n * STAGE, fb = BAR(n);
                asm volatile(ELECT "mbarrier.arrive.expect_tx.shared::cta.b64 _, [%0], %1; }" ::"r"(fb), "r"(n < 2 ? 2 * STAGE : STAGE) : "memory");
                if (n < 2) {
                    tma3x(sb + OFF_H + n * STAGE, &maps.x, tile * 128 + n * 64, fb);
                    tma3x(dst, &maps.x, tile * 128 + n * 64 + 32, fb);
                } else {
                    if (n == 3) mbar_wait(BAR(1), 0);
                    const int ra = 112 * (n - 2);
                    tma2d(dst, &maps.qkv, 448 + 56 * sl, ra, fb);
                    tma2d(dst + HALF, &maps.qkv, 896 + 56 * sl, ra, fb);
                }
            }
            asm volatile("barrier.cluster.wait.aligned;" ::: "memory");
            cw_target = (ld_word(g_cw + sl * 32) & ~15u) + 16;
#pragma unroll 1
            for (int k = 0; k < 2; k++) {
                const int n = t128 + 32 * k;
                int m = n - 2 - (n > PACK);
                const bool packed = m >= 30 ? (m < 38 || m >= 52) : m >= 22;
                if (m >= 30) m -= 30;
                if (n == PACK) m = tile < 8 ? tile : tile + 14;
                const int rot = n < 8 ? 0 : pr;
                const int ra = 112 * kblk(rot, m & 3), rb = 112 * kblk(rot, 2 * m & 3), rc = 112 * kblk(rot, (2 * m + 1) & 3);
                int kind = 0, m0, m1, c0, c1, r0, r1;
                if (m < 4) { m0 = m1 = 1; c0 = 448 + 56 * sl; c1 = c0 + 448; r0 = r1 = ra; }
                else if (m < 8) { m0 = m1 = m < 6 ? 1 : 2; c0 = c1 = 56 * sl; r0 = rb; r1 = rc; }
                else if (m < 20) { m0 = 3; m1 = 4; c0 = c1 = 224 * sl + 32 * hr + 64 * ((m - 8) >> 2); r0 = r1 = ra; }
                else if (m < 22) { kind = 2; m0 = 5; m1 = 6; c0 = c1 = 224 * sl + (hr ? 0 : 192); r0 = rb; r1 = rc; }
                else { m0 = m1 = 7; c0 = c1 = 56 * (2 * ((pr + (m >> 1) - 10) & 3) + hr); r0 = 224 * (sl ^ (m & 1)); r1 = r0 + 112; }
                if (packed) { kind = 1; r0 = sl * 16 + (m < 8 ? m : m - 14); r1 = 0; }
                e0[0] = e0[1]; e1[0] = e1[1];
                e0[1] = kind | (m0 << 2) | (m1 << 6) | (c0 << 10) | (c1 << 21);
                e1[1] = r0 | (r1 << 16);
            }
        } else {
            const int j = t128 - 32;
            asm volatile("barrier.cluster.wait.aligned;" ::: "memory");
            uint2 wv[7];
            const int k = j < 56 ? j : 55, hh = k >= 28;
#pragma unroll
            for (int i = 0; i < 7; i++) wv[i] = __ldg(reinterpret_cast<const uint2*>(w_phi + (sl * 56 + k) * 28) + i);
#pragma unroll 1
            for (int i = j; i < 7168 / 16; i += 96) sts4(sb + OFF_WPHI + i * 16, 0, 0, 0, 0);
            bar_sync(5, 96);
            if (j < 56) {
                uint32_t a4[4];
#pragma unroll
                for (int q = 0; q < 4; q++) a4[q] = sb + OFF_WPHI + (4 * hh + q) * 128 + ((((k >> 3) ^ (4 * hh + q)) & 7) << 4) + (k & 7) * 2;
                FOR14(const uint32_t v = (t & 1) ? wv[t >> 1].y : wv[t >> 1].x;
                      asm volatile("{ .reg .b16 l, h; mov.b32 {l, h}, %2; st.shared.u16 [%0+%3], l; st.shared.u16 [%1+%3], h; }"
                                   ::"r"(a4[t >= 7 ? 2 : 0]), "r"(a4[t >= 7 ? 3 : 1]), "r"(v), "n"((t % 7) * 1024) : "memory"));
            }
            __syncwarp();
            fence_async();
            bar_arrive(1, 224);
            bar_arrive(9, 224);
            if (w == 1) {
                mbar_wait(BAR(2), 0);
                mbar_wait(BAR(2), 1);
                const int b = blockIdx.x;
                asm volatile(ELECT "cp.async.bulk.prefetch.L2.global [%0], %1; }" ::"l"(wg + b * 6272), "r"(12544) : "memory");
                asm volatile(ELECT "cp.async.bulk.prefetch.L2.global [%0], %1; }" ::"l"(wu + b * 6272), "r"(12544) : "memory");
                asm volatile(ELECT "cp.async.bulk.prefetch.L2.global [%0], %1; }" ::"l"(wd + b * 6272), "r"(12544) : "memory");
            }
        }
        uint32_t kseq = ld_word(g_c2 + ((sl * 4 + w) * 16 + tile) * 32);
        int slot = 0, ph = 0, n = NST;
#pragma unroll 1
        for (int layer = 0; layer < 3; layer++) {
            if (w == 0) {
                const int nend = layer == 0 ? 11 : (layer == 1 ? 42 : 63);
#pragma unroll 1
                for (; n < nend; n++) {
                const uint32_t w0 = __shfl_sync(0xffffffffu, n < 32 ? e0[0] : e0[1], n & 31), w1 = __shfl_sync(0xffffffffu, n < 32 ? e1[0] : e1[1], n & 31);
                const uint32_t dst = sb + slot * STAGE, fb = BAR(n == PACK ? B_PACK : slot);
                const CUtensorMap* m0 = &maps.x + ((w0 >> 2) & 15);
                const CUtensorMap* m1 = &maps.x + ((w0 >> 6) & 15);
                const int c0 = (w0 >> 10) & 2047, c1 = w0 >> 21, r0 = w1 & 0xffff, r1 = w1 >> 16;
                if (n == 25) {
                    int it = 0;
                    uint32_t v;
                    do { asm volatile("ld.acquire.gpu.global.u32 %0, [%1];" : "=r"(v) : "l"(g_cw + sl * 32) : "memory"); } while ((int)(v - cw_target) < 0 && ++it < 0x400000);
                    asm volatile("fence.proxy.async.global;" ::: "memory");
                    __syncwarp();
                }
                mbar_wait(BAR(B_EMPTY + slot), ph);
                __syncwarp();
                asm volatile(ELECT "mbarrier.arrive.expect_tx.shared::cta.b64 _, [%0], %1; }" ::"r"(fb), "r"(STAGE) : "memory");
                if ((w0 & 3) == 0) {
                    tma2d(dst, m0, c0, r0, fb);
                    tma2d(dst + HALF, m1, c1, r1, fb);
                } else if (w0 & 1) {
                    asm volatile(ELECT "cp.async.bulk.shared::cluster.global.mbarrier::complete_tx::bytes [%0], [%1], %2, [%3]; }"
                                 ::"r"(dst), "l"(reinterpret_cast<const char*>(g_wp) + (size_t)r0 * STAGE), "r"(STAGE), "r"(fb) : "memory");
                } else {
                    tma2d(dst, m0, c0, r0, fb); tma2d(dst + 7168, m0, c0, r1, fb);
                    tma2d(dst + HALF, m1, c0, r0, fb); tma2d(dst + HALF + 7168, m1, c0, r1, fb);
                }
                if (n == PACK) asm volatile(ELECT "mbarrier.arrive.shared::cta.b64 _, [%0]; }" ::"r"(BAR(slot)) : "memory");
                if (++slot == NST) { slot = 0; ph ^= 1; }
                }
            } else if (w == 1 && layer == 1) {
                constexpr int ps = PACK % NST;
                mbar_wait(BAR(B_PACK), 0);
                asm volatile("{ .reg .pred e; elect.sync _|e, 0xffffffff;\n"
                             "@e cp.async.bulk.global.shared::cta.bulk_group [%0], [%1], %2;\n"
                             "@e cp.async.bulk.commit_group;\n"
                             "@e cp.async.bulk.wait_group.read 0;\n"
                             "@e mbarrier.arrive.shared::cta.b64 _, [%3], 8;\n"
                             "@e cp.async.bulk.wait_group 0;\n"
                             "@e fence.proxy.async.global;\n"
                             "@e red.release.gpu.global.add.u32 [%4], 1; }"
                             ::"l"(reinterpret_cast<char*>(g_wp) + (size_t)(sl * 16 + tile) * STAGE), "r"(sb + ps * STAGE), "r"(STAGE), "r"(BAR(B_EMPTY + ps)), "l"(g_cw + sl * 32) : "memory");
                __syncwarp();
            }
            if (layer < 2) {
            const uint32_t tag = layer ^ 1;
            kseq++;
            bar_sync(7, 384);
            ASTAMP(0);
            if (tile < 15) {
                const int sq = lane >> 3, pk = 8 * w + (lane & (tile == 14 ? 3 : 7));
                uint32_t v[16];
                if ((layer == 0 && C01) || CANARY) poll_cnt(g_c1 + ((sl * 8 + (w >> 1) * 4 + (tile >> 2)) * 16 + (lane & 15)) * 32, kseq);
                ASTAMP(1);
                poll4_kv<32>(v, g_kv1 + ((sl * 16 + tile) * 16 + 4 * sq) * 32 + pk, tag);
#pragma unroll
                for (int k = 0; k < 4; k++) {
                    float lo = (bf_lo(v[k]) + bf_lo(v[4 + k])) + (bf_lo(v[8 + k]) + bf_lo(v[12 + k]));
                    float hi = (bf_hi(v[k]) + bf_hi(v[4 + k])) + (bf_hi(v[8 + k]) + bf_hi(v[12 + k]));
                    lo += __shfl_xor_sync(0xffffffffu, lo, 8); hi += __shfl_xor_sync(0xffffffffu, hi, 8);
                    lo += __shfl_xor_sync(0xffffffffu, lo, 16); hi += __shfl_xor_sync(0xffffffffu, hi, 16);
                    v[k] = pack2(lo, hi);
                }
                if (sq == 0) st_pkt<0>(g_kv2 + sl * 512 + 32 * tile + pk, settag(v[0], tag), v[1], v[2], v[3]);
            }
            if (lane == 0) st_word(g_c2 + ((sl * 4 + w) * 16 + tile) * 32, kseq);
            ASTAMP(2);
            {
                const int item = t128 < 112 ? t128 : 112 + (t128 & 3), d = item >> 1;
                const int cc = t128 < 112 ? 2 * (d >= 28) + (item & 1) : item - 112;
                const int r = t128 < 112 ? d : 56 + (cc >> 1) + 2 * ((t128 - 112) >> 2);
                uint32_t ra = sb + OFF_KVB + r * 128 + 4 * cc, rx = (r & 7) << 4;
                asm volatile("" : "+r"(ra), "+r"(rx));
                FOR14(asm volatile("st.shared.u32 [%0+%2], %1;" ::"r"((ra ^ 8) + (((t & 7) << 4) ^ rx)), "r"(0), "n"((t >> 3) * 8192) : "memory"));
                uint32_t v[16];
                asm volatile("" : "+r"(ra), "+r"(rx));
                if ((layer == 0 && C02) || CAN2) poll_cnt(g_c2 + ((sl * 4 + (lane >> 3)) * 16 + min(4 * w + (lane & 3), 15)) * 32, kseq);
                poll4_kv<8>(v, g_kv2 + sl * 512 + (item >> 3) * 32 + (item & 7), tag);
                FOR14(asm volatile("st.shared.u32 [%0+%2], %1;" ::"r"(ra + (((t & 7) << 4) ^ rx)), "r"(v[t < 7 ? t : t + 1]), "n"((t >> 3) * 8192) : "memory"));
                fence_async();
            }
            bar_arrive(3, 384);
            ASTAMP(3);
            }
        }
    } else {
        asm volatile("setmaxnreg.inc.sync.aligned.u32 232;");
        const int tid = fresh_tid(), lane = tid & 31, t128 = tid & 127, g = lane >> 2, c = lane & 3;
        const int wu = __shfl_sync(0xffffffffu, tid >> 5, 0), w = wu & 3;
        uint4* const xp0 = g_ex + 3 * PLANE + ((tile * 2 + wgi) * 8) * 512 + w * 128 + lane;
        const uint32_t hbuf = sb + OFF_H + wgi * STAGE;
        uint32_t slot = 0, ph = 0, eb1 = 0, eb2 = 0, ackph = 0, rcvph = 0, gatph = 0, swp = 0;
        uint32_t ppid = 6;
#define cx(s) (reinterpret_cast<uint32_t*>(again(xp0) - lane + PL(1) + 112 + (s) * 512))
#define stp (again(xp0) - lane + g + PL(0) + 112)
        uint32_t seq = ld_word(cx(sl));
        uint32_t kseq = ld_word(g_c1 + ((sl * 8 + (tid >> 5)) * 16 + tile) * 32);
        uint32_t stag = ld_word(reinterpret_cast<const uint32_t*>(stp + sl * 512) + 3) & 1;
        asm volatile("barrier.cluster.wait.aligned;" ::: "memory");
        STAMP(1);
        uint32_t X[14];
        const uint32_t x0row = (w < 2 ? hbuf : sb + wgi * STAGE) + ((w & 1) * 16 + (lane & 15)) * 128;
        mbar_wait(BAR(wgi), 0);
        STAMP(51);
#pragma unroll
        for (int j = 0; j < 4; j++) {
            const int G = 7 * sl + min(2 * j + (lane >> 4), 6);
            uint32_t q2, q3;
            asm volatile("ldmatrix.sync.aligned.m8n8.x4.shared.b16 {%0,%1,%2,%3}, [%4];" : "=r"(X[4 * j]), "=r"(X[4 * j + 1]), "=r"(q2), "=r"(q3)
                         : "r"(x0row + (G >> 3) * 4096 + (((G ^ lane) & 7) << 4)) : "memory");
            if (j < 3) { X[(4 * j + 2) % 14] = q2; X[(4 * j + 3) % 14] = q3; }
        }
#define PUSH_SLICE(W)                                                                          \
    {                                                                                          \
        if (t128 == 0) mbar_expect_tx(BAR(B_RECV + wgi), 7168);                                \
        PUSH_BEGIN();                                                                          \
        const uint32_t ra = mapa(hbuf + 24576 + t128 * 16, hr ^ 1), rb = mapa(sb + OFF_XR + wgi * 3072, hr ^ 1), rbar = mapa(BAR(B_RECV + wgi), hr ^ 1); \
        st_async4(ra, W[0], W[1], W[2], W[3], rbar);                                           \
        st_async4(ra + 2048, W[4], W[5], W[6], W[7], rbar);                                    \
        st_async4(rb + t128 * 16, W[8], W[9], W[10], W[11], rbar);                             \
        asm volatile("st.async.weak.shared::cluster.mbarrier::complete_tx::bytes.v2.b32 [%0], {%1,%2}, [%3];" ::"r"(rb + 2048 + t128 * 8), "r"(W[12]), "r"(W[13]), "r"(rbar) : "memory"); \
    }
#define PULL_SLICE(W)                                                                          \
    {                                                                                          \
        uint32_t t0, t1;                                                                       \
        mbar_wait(BAR(B_RECV + wgi), rcvph);                                                   \
        rcvph ^= 1;                                                                            \
        lds4(&A[1][0], hbuf + 24576 + t128 * 16);                                              \
        lds4(&A[1][4], hbuf + 26624 + t128 * 16);                                              \
        lds4(&A[1][8], sb + OFF_XR + wgi * 3072 + t128 * 16);                                  \
        asm volatile("ld.shared.v2.u32 {%0,%1}, [%2];" : "=r"(t0), "=r"(t1) : "r"(sb + OFF_XR + wgi * 3072 + 2048 + t128 * 8) : "memory"); \
        _Pragma("unroll") for (int i = 0; i < 12; i++) A[0][i] = (i & 3) ? W[i] : W[i] & ~1u;  \
        A[1][0] &= ~1u; A[1][4] &= ~1u; A[1][8] &= ~1u;                                        \
        A[0][12] = (hr ? t0 : W[12]) & ~1u; A[0][13] = hr ? t1 : W[13];                        \
        A[1][12] = (hr ? W[12] : t0) & ~1u; A[1][13] = hr ? W[13] : t1;                        \
        asm volatile("" : RW4(A[0], 0), RW4(A[0], 4), RW4(A[0], 8), RW2(A[0], 12), RW4(A[1], 0), RW4(A[1], 4), RW4(A[1], 8), RW2(A[1], 12)); \
        swp = hr * 448;                                                                        \
    }
#define SWB(b, t, db, sh) ((b) == 0 && (t) < 6 ? ((t) < 3 ? db##p : db##m) : db)
#define DECL_DB(b, MK, lbo, sh) const uint64_t db = MK(0, lbo, R_ADJ), dbp = (b) == 0 ? MK(0, lbo, R_ADJ + (swp >> (sh))) : db, dbm = (b) == 0 ? MK(0, lbo, R_ADJ - (swp >> (sh))) : db;
#define EARLY 1
#define EARLYK 1
#define PPB 2
#define PP_WAIT() if (wgi == 1) { bar_sync(ppid, 256); ppid ^= 14; }
#define PP_GO() if (wgi == 0) { bar_arrive(ppid, 256); ppid ^= 14; }
#define GAT_ISSUE(base)                                                                        \
    {                                                                                          \
        const char* gs = reinterpret_cast<const char*>(g_ex + 3 * PLANE + (base) + (tile * 16 + wgi * 8 + 2 * kblk(pr, GB)) * 512 + w * 128); \
        const uint32_t gd = hbuf + w * 3584, gb = BAR(B_GAT + wu);                     \
        asm volatile("{ .reg .pred e; elect.sync _|e, 0xffffffff;\n"                           \
                     "@e mbarrier.arrive.expect_tx.shared::cta.b64 _, [%2], 3584;\n"           \
                     "@e cp.async.bulk.shared::cluster.global.mbarrier::complete_tx::bytes [%0], [%1], 1792, [%2];\n" \
                     "@e cp.async.bulk.shared::cluster.global.mbarrier::complete_tx::bytes [%0+1792], [%1+8192], 1792, [%2]; }" \
                     ::"r"(gd), "l"(gs), "r"(gb) : "memory");                                  \
        __syncwarp();                                                                          \
    }
#define GAT_FETCH()                                                                            \
    {                                                                                          \
        mbar_wait(BAR(B_GAT + wu), gatph);                                             \
        gatph ^= 1;                                                                            \
        const uint32_t ga = hbuf + w * 3584 + lane * 16;                                       \
        _Pragma("unroll") for (int s2 = 0; s2 < 2; s2++) {                                     \
            lds4(&A[2 * GB + s2][0], ga + s2 * 1792); lds4(&A[2 * GB + s2][4], ga + s2 * 1792 + 512); lds4(&A[2 * GB + s2][8], ga + s2 * 1792 + 1024); \
            asm volatile("ld.shared.v2.u32 {%0,%1}, [%2];" : "=r"(A[2 * GB + s2][12]), "=r"(A[2 * GB + s2][13]) : "r"(ga - lane * 8 + s2 * 1792 + 1536) : "memory"); \
        }                                                                                      \
    }
#define PT 3
#define PREP(b, t, remote)                                                                     \
    if constexpr ((b) < 3 && (t) == PT) {                                                      \
        wg_commit();                                                                           \
        STAMP(80 + 8 * (step & 1) + 2 * (b));                                                  \
        if constexpr (GB == 1 && (b) == 0) { if (remote) GAT_FETCH() }                         \
        if (remote) blk_check<((b) + 1) & 3>(A, BLK(xsrc, (b) + 1), lane, xtag);               \
        STAMP(81 + 8 * (step & 1) + 2 * (b));                                                  \
        if constexpr ((b) == 0) { if (remote) blk_load<3>(A, BLK(xsrc, 3), lane); }            \
        normalize<((b) + 1) & 3>(A, k0, k1);                                                   \
        asm volatile("" : RW4(A[(2 * (b) + 2) & 7], 0), RW4(A[(2 * (b) + 2) & 7], 4), RW4(A[(2 * (b) + 2) & 7], 8), RW2(A[(2 * (b) + 2) & 7], 12), \
                          RW4(A[(2 * (b) + 3) & 7], 0), RW4(A[(2 * (b) + 3) & 7], 4), RW4(A[(2 * (b) + 3) & 7], 8), RW2(A[(2 * (b) + 3) & 7], 12)); \
        wg_fence();                                                                            \
    }                                                                                          \
    if constexpr ((b) == 3 && ((t) == 0 || (t) == 6)) { STAMP(86 + 8 * (step & 1) + (t) / 6); }
#define BLK(base, b) ((base) + kblk(pr, b) * 1024)

#pragma unroll 1
        for (int step = 0; step < 4; step++) {
            const uint32_t tag = (step >> 1) ^ 1;
            const int so = (step >> 1) * 24 + (step & 1) * 12;
            (void)so;
            uint32_t A[8][14];
            uint4* const xsrc = xp0 + ((step & 1) ? PL(2) : PL(0));
            const uint32_t xtag = (step & 1) ? tag : ((seq >> 3) & 1) ^ 1;
            uint32_t xbits;
            {
                float st[4];
                slice_stats(X, st);
                stag ^= 1;
                xbits = x_bits(X);
                tag_slice(X, xtag);
                if (step) send_slice<0>(xsrc + sl * 512, lane, X);
                if (c == 0) st_pkt<0>(stp + sl * 512, __float_as_uint(st[0]), __float_as_uint(st[1]), __float_as_uint(st[2]), settag(__float_as_uint(st[3]), stag));
            }
            STAMP(2 + so);
            uint32_t sv[8];
            if (step == 0) {
                const int rr = lane & 7, hi = lane >> 4;
                const uint32_t rowa = (w < 2 ? hbuf : sb + wgi * STAGE) + ((w & 1) * 16 + (lane & 15)) * 128;
                uint32_t xr[8];
#pragma unroll
                for (int j = 0; j < 8; j++) xr[j] = rowa + ((((j + hi) ^ rr) & 7) << 4) + (j == 7 ? hi * 4096 : 0);
#define X0_BLOCK(b)                                                                            \
    FOR7(constexpr int G = 14 * (b) + (t < 3 ? 2 * t : (t < 6 ? 2 * t + 1 : 6));               \
         uint32_t q0, q1, q2, q3;                                                              \
         const uint32_t ad = t < 6 ? xr[G & 7] : rowa + ((G + 7 * hi) >> 3) * 4096 + ((((G + 7 * hi) ^ rr) & 7) << 4); \
         asm volatile("ldmatrix.sync.aligned.m8n8.x4.shared.b16 {%0,%1,%2,%3}, [%4+%5];" : "=r"(q0), "=r"(q1), "=r"(q2), "=r"(q3) \
                      : "r"(ad), "n"(t < 6 ? (G >> 3) * 4096 : 0) : "memory");                 \
         if (t < 3) { A[2 * (b)][4 * t] = q0; A[2 * (b)][4 * t + 1] = q1; A[2 * (b)][4 * t + 2] = q2; A[2 * (b)][4 * t + 3] = q3; } \
         else if (t < 6) { A[2 * (b) + 1][(4 * t - 12) & 15] = q0; A[2 * (b) + 1][((4 * t - 12) & 15) + 1] = q1; A[2 * (b) + 1][((4 * t - 12) & 15) + 2] = q2; A[2 * (b) + 1][((4 * t - 12) & 15) + 3] = q3; } \
         else { A[2 * (b)][12] = q0; A[2 * (b)][13] = q1; A[2 * (b) + 1][12] = q2; A[2 * (b) + 1][13] = q3; });
                X0_BLOCK(0) X0_BLOCK(1) X0_BLOCK(2) X0_BLOCK(3)
                mbar_wait(BAR(wgi ^ 1), 0);
                R_NEXT();
                R_NEXT();
                stat_load(sv, stp + c * 1024);
                stat_check(sv, stp + c * 1024, stag);
                STAMP(52 + step);
            } else {
                PUSH_SLICE(X)
                stat_load(sv, stp + c * 1024);
                kill<14>(A[2]); kill<14>(A[3]); kill<14>(A[4]); kill<14>(A[5]); kill<14>(A[6]); kill<14>(A[7]);
                PULL_SLICE(X)
                stat_check(sv, stp + c * 1024, stag);
                STAMP(52 + step);
                if (GB == 1) GAT_ISSUE((step & 1) ? PL(2) : PL(0))
                else blk_load<1>(A, BLK(xsrc, 1), lane);
            }
            LnCoef k0, k1;
            {
                k0 = ln_coef(__uint_as_float(sv[0]) + __uint_as_float(sv[4]), __uint_as_float(sv[1]) + __uint_as_float(sv[5]));
                k1 = ln_coef(__uint_as_float(sv[2]) + __uint_as_float(sv[6]), __uint_as_float(sv[3]) + __uint_as_float(sv[7]));
            }
            if (step) {
                if (GB == 2) GAT_ISSUE((step & 1) ? PL(2) : PL(0))
                else blk_load<2>(A, BLK(xsrc, 2), lane);
            }
            STAMP(3 + so);
            GSTAMP(76 + step);

            if ((step & 1) == 0) {
                float tq[28];
                {
                    float av[28];
#define KV_BLOCK(b)                                                                           \
    if (GB == 2 && (b) == 1 && step) GAT_FETCH()                                                         \
    if ((b) == 2) PUSH_ACK();                                                                 \
    if (QE && (b) == 1) R_RELEASE(2);                                                         \
    if (QE && (b) == 2) { wg_wait<2>(); R_RELEASE(2); }                                       \
    R_WAIT();                                                                                 \
    if ((b) == PPK) { PP_WAIT() }                                                             \
    { DECL_DB(b, BASE128, 16, 0)                                                              \
    wg_fence();                                                                               \
    FOR7(mma_rs56<1, D128(0, t)>(tq, AQ(A, b, t), (b) + t > 0, SWB(b, t, db, 0));             \
         mma_rs56<1, D128(HALF, t)>(av, AQ(A, b, t), (b) + t > 0, SWB(b, t, db, 0));          \
         PREP(b, t, step)); }                                                                 \
    wg_commit();                                                                              \
    if ((b) == 3 && PPK < 4) { PP_GO() }                                                      \
    R_NEXT();
                    if (EARLYK == 0 || step == 0) R_RELEASE(2);
                    normalize<0>(A, k0, k1);
                    KV_BLOCK(0) KV_BLOCK(1) KV_BLOCK(2) KV_BLOCK(3)
                    wg_wait<0>();
                    if (lane < (QE ? 3 : NST)) mbar_arrive(BAR(B_EMPTY + (slot + NST - 1 - lane) % NST));
                    STAMP(4 + so);
                    WSUM(80 + 7 * (step >> 1));
                    const int m = lane >> 3, rr = lane & 7;
                    const uint32_t rowa = hbuf + 16384 + (w * 16 + rr + 8 * (m & 1)) * 128;
                    const uint32_t one = c == 0 ? 0x00003f80u : 0u;
                    if (step == 0) { bar_sync(wgi ? 9 : 1, 224); }
#pragma unroll
                    for (int j = 0; j < 4; j++) {
                        const uint32_t a = rowa + (((2 * j + (m >> 1)) ^ rr) << 4);
                        if (j < 3) stsm4(a, pack2(av[8 * j], av[8 * j + 1]), pack2(av[8 * j + 2], av[8 * j + 3]), pack2(av[8 * j + 4], av[8 * j + 5]), pack2(av[8 * j + 6], av[8 * j + 7]));
                        else stsm4(a, pack2(av[24], av[25]), pack2(av[26], av[27]), one, one);
                    }
                }
                uint32_t PH[28];
                int it = 1;
#pragma unroll 1
                do {
                    float pp[28];
                    phi_gemm(tq, pp);
                    dual_softmax(pp, PH);
                    if (((trips >> (it + 1)) & 1) == 0) continue;
                    {
                        const int m = lane >> 3, rr = lane & 7;
                        const uint32_t rowa = hbuf + (w * 16 + rr + 8 * (m & 1)) * 128;
#pragma unroll
                        for (int j = 0; j < 7; j++) {
                            const int cg = 2 * j + (m >> 1), hi = cg >= 7;
                            stsm4(rowa + hi * 8192 + (((cg - 7 * hi) ^ rr) << 4), PH[4 * j], PH[4 * j + 1], PH[4 * j + 2], PH[4 * j + 3]);
                        }
                    }
                    fence_async();
                    STAMP(5 + so);
#define Q_STAGE(b0)                                                                           \
    R_WAIT();                                                                                 \
    { DECL_DB(b0, BASE128, 16, 0)                                                             \
    wg_fence();                                                                               \
    FOR7(mma_rs56<1, D128(0, t)>(tq, AQ(A, b0, t), (b0) + t > 0, SWB(b0, t, db, 0)));         \
    FOR7(mma_rs56<1, D128(HALF, t)>(tq, AQ(A, (b0) + 1, t), 1, db)); }                        \
    wg_commit();                                                                              \
    R_NEXT();
                    if (QE && wgi == 0) { kill<28>(tq); Q_STAGE(0) Q_STAGE(2) wg_wait<1>(); R_RELEASE(2); wg_wait<0>(); R_RELEASE(1); }
                    bar_sync(2, 256);
                    float kv[28];
                    const uint64_t da = BASE128(OFF_H + 16384, 16, 0), dbk = BASE128(OFF_H, 16, wgi * 512);
                    wg_fence();
                    FOR8(constexpr uint64_t o = ((t >> 2) * STAGE + (t & 3) * 2048) >> 4; mma_ss56_tt<o, o>(kv, t > 0, da, dbk));
                    wg_commit();
                    wg_wait<0>();
#pragma unroll
                    for (int hf = 0; hf < 2; hf++) {
                        const int d = 16 * w + g + 8 * hf;
                        if ((d < 56 && (d >= 28) == (c >= 2)) || d == 56) {
                            const int item = d < 56 ? 2 * d + (c & 1) : 112 + c;
                            uint4* dst = g_kv1 + ((sl * 16 + (item >> 3)) * 16 + tile) * 32 + wgi * 16 + (item & 7);
#define KVW(i) pack2(kv[4 * (i) + 2 * hf], kv[4 * (i) + 2 * hf + 1])
                            st_pkt<0>(dst, settag(KVW(0), tag), KVW(1), KVW(2), KVW(3));
                            st_pkt<8>(dst, settag(KVW(4), tag), KVW(5), KVW(6), 0u);
                        }
                    }
                    __syncwarp();
                    kseq++;
                    if (lane == 0) st_word(g_c1 + ((sl * 8 + (tid >> 5)) * 16 + tile) * 32, kseq);
                    bar_arrive(7, 384);
                    STAMP(6 + so);
                    if (!QE || wgi == 1) { kill<28>(tq); Q_STAGE(0) Q_STAGE(2) wg_wait<1>(); R_RELEASE(2); wg_wait<0>(); R_RELEASE(1); }
                    STAMP(7 + so);
                    kill<28>(PH);
                } while (((trips >> (++it)) & 1));
                STAMP(8 + so);
                if (step) {
                    slice_load<PL(0)>(X, xp0 + sl * 512, lane);
                } else {
                    const uint32_t* xp = reinterpret_cast<const uint32_t*>(x_in + (size_t)(tile * 128 + wu * 16 + g) * 448 + 56 * sl + 2 * c);
#pragma unroll
                    for (int i = 0; i < 7; i++) { X[2 * i] = __ldg(xp + 4 * i); X[2 * i + 1] = __ldg(xp + 4 * i + 8 * 224); }
                }
                bar_sync(3, 384);
                STAMP(9 + so);
                const uint4* const osrc = xp0 + PL(1);
                {
                    float nm[32];
                    const uint64_t db = BASE128(OFF_KVB, 16, 0);
                    wg_fence();
                    FOR7(mma_rs64<0, ((t >> 2) * 8192 + (t & 3) * 32) / 16>(nm, PH[4 * t], PH[4 * t + 1], PH[4 * t + 2], PH[4 * t + 3], t > 0, db));
                    wg_commit();
                    wg_wait<0>();
                    const float i00 = rcp(nm[28] + 1e-6f), i01 = rcp(nm[29] + 1e-6f), i10 = rcp(nm[30] + 1e-6f), i11 = rcp(nm[31] + 1e-6f);
                    const float m0 = c >= 2 ? i01 : i00, m1 = c >= 2 ? i11 : i10;
                    uint32_t O[14];
#pragma unroll
                    for (int i = 0; i < 7; i++) {
                        const float f0 = i < 3 ? i00 : (i > 3 ? i01 : m0), f1 = i < 3 ? i10 : (i > 3 ? i11 : m1);
                        O[2 * i] = pack2(nm[4 * i] * f0, nm[4 * i + 1] * f0);
                        O[2 * i + 1] = pack2(nm[4 * i + 2] * f1, nm[4 * i + 3] * f1);
                    }
                    if (OST) { PP_WAIT() }
                    tag_slice(O, tag);
                    send_slice<PL(1)>(xp0 + sl * 512, lane, O);
                    seq++;
                    if (lane == 0) st_word(cx(sl), seq);
                    STAMP(10 + so);
                    PUSH_SLICE(O)
                    if (OST == 1) { PP_GO() }
                    const uint32_t cv = ld_word(cx(lane & 7));
                    PULL_SLICE(O)
                    check_cnt(cv, cx(lane & 7), seq);
                    if (OST == 2) { PP_GO() }
                    STAMP(56 + (step >> 1));
                    GAT_ISSUE(PL(1))
                    blk_load<3 - GB>(A, BLK(osrc, 3 - GB), lane);
                }
                float ao[28];
#define WO_BLOCK(b)                                                                           \
    if ((b) > 0) blk_check<b>(A, BLK(osrc, b), lane, tag);                                    \
    if (((b) & 1) == 0) R_WAIT();                                                             \
    { DECL_DB(b, BASE128, 16, 0)                                                              \
    wg_fence();                                                                               \
    FOR7(mma_rs56<1, D128(((b) & 1) * HALF, t)>(ao, AQ(A, b, t), (b) + t > 0, SWB(b, t, db, 0))); } \
    wg_commit();                                                                              \
    if ((b) & 1) R_NEXT();
                WO_BLOCK(0)
                STAMP(11 + so);
                blk_load<3>(A, BLK(osrc, 3), lane);
                if (GB == 1) GAT_FETCH()
                WO_BLOCK(1)
                if (GB == 2) GAT_FETCH()
                WO_BLOCK(2)
                PUSH_ACK();
                WO_BLOCK(3)
                wg_wait<0>();
                if (EARLY >= 1) R_RELEASE(2);
                if (EARLY >= 2) R_RELEASE(1);
                STAMP(12 + so);
                WSUM(86 + 7 * (step >> 1));
                x_fix(X, xbits);
#pragma unroll
                for (int i = 0; i < 14; i++) X[i] = pack2(bf_lo(X[i]) + ao[2 * i], bf_hi(X[i]) + ao[2 * i + 1]);
            } else {
                uint32_t H[56];
                float ag[64];
#define F1_EPI(dst, ng, ag)                                                                    \
    _Pragma("unroll") for (int i = 0; i < 2 * (ng); i++)                                       \
        (dst)[i] = pack2(geglu(ag[2 * i], ag[4 * (ng) + 2 * i]), geglu(ag[2 * i + 1], ag[4 * (ng) + 2 * i + 1]));
#define H_PUSH(h0, off) st_async4(rem_h + (off), H[h0], H[(h0) + 1], H[(h0) + 2], H[(h0) + 3], mapa(BAR(B_RECV2 + wgi), hr ^ 1));
#define F1_BLOCK(b, first)                                                                     \
    if ((first) && (b) < 2 && (b) >= EARLY) R_RELEASE(2);                                      \
    if (GB == 2 && (first) && (b) == 1) GAT_FETCH()                                                       \
    if ((first) && (b) == 2) PUSH_ACK();                                                       \
    R_WAIT();                                                                                  \
    if ((b) == PPB) { PP_WAIT() }                                                              \
    { DECL_DB(b, BASE128, HALF, 0)                                                             \
    wg_fence();                                                                                \
    FOR7(mma_rs128<1, D128(0, t)>(ag, AQ(A, b, t), (b) + t > 0, SWB(b, t, db, 0));             \
         if constexpr (first) { PREP(b, t, true) }); }                                         \
    wg_commit();                                                                               \
    if ((b) == 3) { PP_GO() }                                                                  \
    if ((b) > 0) { wg_wait<1>(); R_RELEASE(1); }       \
    R_NEXT();
                normalize<0>(A, k0, k1);
                F1_BLOCK(0, true) F1_BLOCK(1, true) F1_BLOCK(2, true) F1_BLOCK(3, true)
                if (t128 == 0) { mbar_expect_tx(BAR(B_RECV + wgi), 16384); mbar_expect_tx(BAR(B_RECV2 + wgi), 12288); }
                PUSH_BEGIN();
                wg_wait<0>();
                R_RELEASE(1);
                if (step == 1) R_NEXT();
                int p = 0;
#pragma unroll 1
                do {
                    STAMP(68 + p);
                    F1_EPI(H + 32, 8, ag)
                    STAMP(4 + p + so);
                    WSUM(81 + p + 7 * (step >> 1));
                    if (((trips >> (p + 1)) & 1) == 0) continue;
                    {
                        const uint32_t pk = (p ? hbuf + 16384 : sb + OFF_KVB + wgi * 8192) + w * 2048;
#pragma unroll
                        for (int k = 0; k < 4; k++) sts4(pk + k * 512 + lane * 16, H[32 + 4 * k], H[33 + 4 * k], H[34 + 4 * k], H[35 + 4 * k]);
                        fence_async();
                        __syncwarp();
                        asm volatile(ELECT "cp.async.bulk.shared::cluster.shared::cta.mbarrier::complete_tx::bytes [%0], [%1], 2048, [%2]; }"
                                     ::"r"(mapa(hbuf + p * 8192 + w * 2048, hr ^ 1)), "r"(pk), "r"(mapa(BAR(B_RECV + wgi), hr ^ 1)) : "memory");
                    }
                    kill<64>(ag);
                    F1_BLOCK(0, false) F1_BLOCK(1, false) F1_BLOCK(2, false) F1_BLOCK(3, false)
                    wg_wait<0>();
                    R_RELEASE(1);
                    kill<16>(H + 32);
                } while (((trips >> (++p)) & 1));
#pragma unroll
                for (int k = 0; k < 4; k++) lds4(H + 16 + 4 * k, hbuf + 16384 + w * 2048 + k * 512 + lane * 16);
                __syncwarp();
                if (lane == 0) asm volatile("mbarrier.arrive.shared::cluster.b64 _, [%0];" ::"r"(mapa(BAR(B_ACK2 + wgi), hr ^ 1)) : "memory");
                const uint32_t rem_h = mapa(hbuf + w * 2048 + lane * 16, hr ^ 1);
#define F1_LAST(b0)                                                                            \
    R_WAIT();                                                                                  \
    if (b0) { PP_WAIT() }                                                                      \
    { DECL_DB(b0, BASE64, HALF, 1)                                                             \
    wg_fence();                                                                                \
    FOR7(mma_rs64<1, D64(0, t)>(al, AQ(A, b0, t), (b0) + t > 0, SWB(b0, t, db, 1)));           \
    FOR7(mma_rs64<1, D64(7168, t)>(al, AQ(A, (b0) + 1, t), 1, db)); }                          \
    wg_commit();                                                                               \
    if (b0) { PP_GO() }                                                                        \
    R_NEXT();
                float al[32];
                F1_LAST(0)
                mbar_wait(BAR(B_RECV + wgi), rcvph);
                rcvph ^= 1;
                mbar_wait(BAR(B_ACK2 + wgi), step >> 1);
                H_PUSH(32, 16384) H_PUSH(36, 16896)
                F1_LAST(2)
                H_PUSH(40, 17408) H_PUSH(44, 17920)
                wg_wait<1>();
                R_RELEASE(2);
                wg_wait<0>();
                R_RELEASE(1);
                uint32_t HP[56];
#pragma unroll
                for (int k = 0; k < 4; k++) lds4(H + 4 * k, sb + OFF_KVB + wgi * 8192 + w * 2048 + k * 512 + lane * 16);
#pragma unroll
                for (int t = 0; t < 8; t++) lds4(HP + 4 * t, hbuf + (t >> 2) * 8192 + w * 2048 + (t & 3) * 512 + lane * 16);
                F1_EPI(H + 48, 4, al)
                H_PUSH(48, 24576 - w * 1024) H_PUSH(52, 25088 - w * 1024)
                STAMP(7 + so);
                WSUM(84 + 7 * (step >> 1));
                float acc[28];
                const uint32_t roA = hr ? 256u : 0u, roB = hr ? (uint32_t)-1536 : 0u;
                const uint32_t rpA = hr ? 0u : 256u, rpB = hr ? 0u : (uint32_t)-1536;
                float res[28];
                uint32_t v0[14], v1[14], P[14];
                const uint4* ps = xp0 + sl * 512;
#define F2_OWN_A()                                                                             \
    R_WAIT();                                                                                  \
    d0 = BASE128(0, 16, R_ADJ + roA); d1 = BASE128(0, 16, R_ADJ + roB);                        \
    wg_fence();                                                                                \
    FOR14(if constexpr (t < OT) mma_rs56<1, t * 128>(acc, H[4 * t], H[4 * t + 1], H[4 * t + 2], H[4 * t + 3], t > 0, d0)); \
    wg_commit();
#define F2_OWN_B()                                                                             \
    wg_fence();                                                                                \
    FOR14(if constexpr (t >= OT) mma_rs56<1, t * 128>(acc, H[4 * t], H[4 * t + 1], H[4 * t + 2], H[4 * t + 3], 1, t < 12 ? d0 : d1)); \
    wg_commit();                                                                               \
    R_NEXT();
#define F2_PEER()                                                                              \
    R_WAIT();                                                                                  \
    if (F2PP) { PP_WAIT() }                                                                    \
    d0 = BASE128(0, 16, R_ADJ + rpA); d1 = BASE128(0, 16, R_ADJ + rpB);                        \
    wg_fence();                                                                                \
    FOR14(mma_rs56<1, t * 128>(acc, HP[4 * t], HP[4 * t + 1], HP[4 * t + 2], HP[4 * t + 3], 1, t < 12 ? d0 : d1)); \
    wg_commit();                                                                               \
    if (F2PP) { PP_GO() }                                                                      \
    R_NEXT();
#define F2_TURN(u)                                                                             \
    wg_wait<1>();                                                                              \
    R_RELEASE(2);                                                                              \
    wg_wait<0>();                                                                              \
    R_RELEASE(1);                                                                              \
    _Pragma("unroll") for (int i = 0; i < 14; i++) P[i] = pack2(acc[2 * i], acc[2 * i + 1]);   \
    tag_slice(P, tag);                                                                         \
    asm volatile("" : RW4(P, 0), RW4(P, 4), RW4(P, 8), RW2(P, 12));                            \
    kill<28>(acc);                                                                             \
    F2_OWN_A()                                                                                 \
    if ((u) == 2) { slice_load<PL(3)>(v0, ps, lane); slice_load<PL(4)>(v1, ps, lane); } \
    send_slice<PL(3 + (u))>(xp0 + (2 * ((pr + (u) + 1) & 3) + hr) * 512, lane, P);             \
    seq++;                                                                                     \
    if (lane == 0) st_word(cx(sl), seq);                                                       \
    __syncwarp();                                                                              \
    STAMP(8 + (u) + so);                                                                       \
    F2_OWN_B()
                uint64_t d0, d1;
                F2_OWN_A()
                F2_OWN_B()
                R_WAIT();
                d0 = BASE128(0, 16, R_ADJ + rpA); d1 = BASE128(0, 16, R_ADJ + rpB);
                wg_fence();
                FOR8(mma_rs56<1, t * 128>(acc, HP[4 * t], HP[4 * t + 1], HP[4 * t + 2], HP[4 * t + 3], 1, d0));
                wg_commit();
                mbar_wait(BAR(B_RECV2 + wgi), step >> 1);
#pragma unroll
                for (int k = 0; k < 4; k++) lds4(HP + 32 + 4 * k, hbuf + 16384 + w * 2048 + k * 512 + lane * 16);
                lds4(HP + 48, hbuf + 24576 + w * 1024 + lane * 16);
                lds4(HP + 52, hbuf + 25088 + w * 1024 + lane * 16);
                if (step == 1) PUSH_ACK();
                wg_fence();
                FOR14(if constexpr (t >= 8) mma_rs56<1, t * 128>(acc, HP[4 * t], HP[4 * t + 1], HP[4 * t + 2], HP[4 * t + 3], 1, t < 12 ? d0 : d1));
                wg_commit();
                R_NEXT();
                F2_TURN(0)
                F2_PEER()
                F2_TURN(1)
                F2_PEER()
                F2_TURN(2)
                STAMP(64 + 8 * (step >> 1));
                slice_check<PL(3)>(v0, ps, lane, tag);
                slice_check<PL(4)>(v1, ps, lane, tag);
#pragma unroll
                for (int i = 0; i < 14; i++) { res[2 * i] = bf_lo(v0[i]) + bf_lo(v1[i]); res[2 * i + 1] = bf_hi(v0[i]) + bf_hi(v1[i]); }
                slice_load<PL(2)>(X, ps, lane);
                STAMP(65 + 8 * (step >> 1));
                const uint32_t cv = ld_word(cx(2 * ((pr + 1) & 3) + hr));
                F2_PEER()
                STAMP(66 + 8 * (step >> 1));
                check_cnt(cv, cx(2 * ((pr + 1) & 3) + hr), seq);
                STAMP(67 + 8 * (step >> 1));
                slice_load<PL(5)>(v0, ps, lane);
                x_fix(X, xbits);
                slice_check<PL(5)>(v0, ps, lane, tag);
#pragma unroll
                for (int i = 0; i < 14; i++) { res[2 * i] += bf_lo(v0[i]); res[2 * i + 1] += bf_hi(v0[i]); }
                STAMP(11 + so);
                wg_wait<0>();
                if (EARLYK >= 1) R_RELEASE(2);
                STAMP(12 + so);
                WSUM(85 + 7 * (step >> 1));
#pragma unroll
                for (int i = 0; i < 14; i++) X[i] = pack2(fmaf(res[2 * i] + acc[2 * i], 0.5f, bf_lo(X[i])), fmaf(res[2 * i + 1] + acc[2 * i + 1], 0.5f, bf_hi(X[i])));
            }
        }
        {
            const int m = lane >> 3, rr = lane & 7;
            const uint32_t ob = hbuf + w * 2048, rowa = ob + (rr + 8 * (m & 1)) * 112 + (m >> 1) * 16;
#pragma unroll
            for (int j = 0; j < 3; j++) stsm4(rowa + 32 * j, X[4 * j], X[4 * j + 1], X[4 * j + 2], X[4 * j + 3]);
            asm volatile("stmatrix.sync.aligned.m8n8.x2.shared.b16 [%0], {%1,%2};" ::"r"(ob + (rr + 8 * (m & 1)) * 112 + 96), "r"(X[12]), "r"(X[13]) : "memory");
            fence_async();
            __syncwarp();
            if (lane == 0) {
                asm volatile("cp.async.bulk.tensor.2d.global.shared::cta.bulk_group [%0, {%2, %3}], [%1];" ::"l"(&maps.out), "r"(ob), "r"(56 * sl), "r"(tile * 128 + (tid >> 5) * 16) : "memory");
                asm volatile("cp.async.bulk.commit_group;" ::: "memory");
                asm volatile("cp.async.bulk.wait_group.read 0;" ::: "memory");
            }
        }
        STAMP(50);
        GSTAMP(61);
        PDUMP();
    }
}

typedef CUresult (*EncodeFn)(CUtensorMap*, CUtensorMapDataType, cuuint32_t, void*, const cuuint64_t*, const cuuint64_t*, const cuuint32_t*,
                             const cuuint32_t*, CUtensorMapInterleave, CUtensorMapSwizzle, CUtensorMapL2promotion, CUtensorMapFloatOOBfill);

static void make_map(EncodeFn enc, CUtensorMap* m, const void* p, uint64_t cols, uint64_t rows, uint32_t bc, uint32_t br, CUtensorMapSwizzle sw) {
    cuuint64_t gd[2] = {cols, rows};
    cuuint64_t gs[1] = {cols * 2};
    cuuint32_t bd[2] = {bc, br};
    cuuint32_t es[2] = {1, 1};
    enc(m, CU_TENSOR_MAP_DATA_TYPE_BFLOAT16, 2, const_cast<void*>(p), gd, gs, bd, es, CU_TENSOR_MAP_INTERLEAVE_NONE, sw,
        CU_TENSOR_MAP_L2_PROMOTION_L2_128B, CU_TENSOR_MAP_FLOAT_OOB_FILL_NONE);
}

extern "C" void kernel_launch(void* const* d_in, const int* in_sizes, int n_in, void* d_out, int out_size) {
    (void)in_sizes; (void)n_in; (void)out_size;
    static EncodeFn enc = nullptr;
    static Scratch* scratch = nullptr;
    if (!enc) {
        void* fn = nullptr;
        cudaDriverEntryPointQueryResult qr;
        cudaGetDriverEntryPoint("cuTensorMapEncodeTiled", &fn, cudaEnableDefault, &qr);
        enc = (EncodeFn)fn;
        cudaGetSymbolAddress((void**)&scratch, g_scratch);
        cudaFuncSetAttribute(fused_kernel, cudaFuncAttributeMaxDynamicSharedMemorySize, SMEM_BYTES);
    }
    Maps maps;
    {
        cuuint64_t gd[3] = {64, 2048, 7};
        cuuint64_t gs[2] = {896, 128};
        cuuint32_t bd[3] = {64, 32, 7};
        cuuint32_t es[3] = {1, 1, 1};
        enc(&maps.x, CU_TENSOR_MAP_DATA_TYPE_BFLOAT16, 3, d_in[0], gd, gs, bd, es, CU_TENSOR_MAP_INTERLEAVE_NONE, CU_TENSOR_MAP_SWIZZLE_128B,
            CU_TENSOR_MAP_L2_PROMOTION_L2_128B, CU_TENSOR_MAP_FLOAT_OOB_FILL_NONE);
    }
    make_map(enc, &maps.out, d_out, 448, 2048, 56, 16, CU_TENSOR_MAP_SWIZZLE_NONE);
    make_map(enc, &maps.qkv, d_in[1], 1344, 448, 64, 112, CU_TENSOR_MAP_SWIZZLE_128B);
    make_map(enc, &maps.wo, d_in[3], 448, 448, 64, 112, CU_TENSOR_MAP_SWIZZLE_128B);
    make_map(enc, &maps.wg, d_in[5], 1792, 448, 64, 112, CU_TENSOR_MAP_SWIZZLE_128B);
    make_map(enc, &maps.wu, d_in[6], 1792, 448, 64, 112, CU_TENSOR_MAP_SWIZZLE_128B);
    make_map(enc, &maps.wg32, d_in[5], 1792, 448, 32, 112, CU_TENSOR_MAP_SWIZZLE_64B);
    make_map(enc, &maps.wu32, d_in[6], 1792, 448, 32, 112, CU_TENSOR_MAP_SWIZZLE_64B);
    make_map(enc, &maps.wd, d_in[7], 448, 1792, 64, 112, CU_TENSOR_MAP_SWIZZLE_128B);
    fused_kernel<<<128, 384, SMEM_BYTES>>>(scratch, (const __nv_bfloat16*)d_in[0], (const __nv_bfloat16*)d_in[2], 7, (const __nv_bfloat16*)d_in[5],
                                           (const __nv_bfloat16*)d_in[6], (const __nv_bfloat16*)d_in[7], maps);
}
```

```cpp
#include <cuda_runtime.h>
#include <cuda.h>
#include <cuda_bf16.h>
#include <stdint.h>
#include <type_traits>

#define EPOLL 1
#define ACAN 1
#define SPLIT0 1
#define OT 2
#define F2PP 0
#define PPK 2
#define QE 1
#define OST 1
#define GB 1
#define B3T 6
#define PP

namespace {

constexpr uint32_t STAGE = 28672, HALF = 14336;
constexpr int NST = 5;
constexpr uint32_t OFF_H = NST * STAGE;
constexpr uint32_t OFF_KVB = OFF_H + 2 * STAGE;
constexpr uint32_t OFF_WPHI = OFF_KVB + 16384;
constexpr uint32_t OFF_XR = OFF_WPHI + 7168;
constexpr uint32_t OFF_BAR = OFF_XR + 6144;
constexpr uint32_t SMEM_BYTES = OFF_BAR + 256 + 1536;
constexpr int B_EMPTY = NST, B_RECV = 2 * NST, B_RECV2 = B_RECV + 2, B_PACK = B_RECV2 + 2, B_GAT = B_PACK + 1, B_ACK = B_GAT + 8, B_ACK2 = B_ACK + 2, B_COUNT = B_ACK2 + 2;

constexpr int PACK = 14;

struct Maps { CUtensorMap x, qkv, wo, wg, wu, wg32, wu32, wd, out; };

}

constexpr int PLANE = 16 * 2 * 8 * 512;
struct Scratch {
    uint4 ex[6 * PLANE];
    uint4 kv1[8 * 16 * 16 * 32];
    uint4 kv2[8 * 512];
    uint32_t c1[8 * 8 * 16 * 32];
    uint32_t cw[8 * 32];
    uint4 wp[8 * 32 * (HALF / 16)];
};
__device__ __align__(1024) Scratch g_scratch;
#define g_ex (sc->ex)
#define g_kv1 (sc->kv1)
#define g_kv2 (sc->kv2)
#define g_c1 (sc->c1)
#define g_cw (sc->cw)
#define g_wp (sc->wp)
#define STAMP(i)
#define GSTAMP(i)
#define PDUMP()
#define ASTAMP(i)

namespace {

__device__ __forceinline__ int fresh_tid() { int t; asm volatile("mov.u32 %0, %%tid.x;" : "=r"(t)); return t; }
__device__ __forceinline__ uint4* again(uint4* p) { asm volatile("" : "+l"(p)); return p; }
template <int N> __device__ __forceinline__ void kill(uint32_t* v) {
#pragma unroll
    for (int i = 0; i < N; i++) v[i] = 0;
}
template <int N> __device__ __forceinline__ void kill(float* v) {
#pragma unroll
    for (int i = 0; i < N; i++) v[i] = 0.f;
}
__device__ __forceinline__ uint32_t s2u(const void* p) { return (uint32_t)__cvta_generic_to_shared(p); }
__device__ __forceinline__ void mbar_init(uint32_t a, uint32_t c) { asm volatile("mbarrier.init.shared::cta.b64 [%0], %1;" ::"r"(a), "r"(c) : "memory"); }
__device__ __forceinline__ void mbar_expect_tx(uint32_t a, uint32_t b) { asm volatile("mbarrier.arrive.expect_tx.shared::cta.b64 _, [%0], %1;" ::"r"(a), "r"(b) : "memory"); }
__device__ __forceinline__ void mbar_arrive(uint32_t a) { asm volatile("mbarrier.arrive.shared::cta.b64 _, [%0];" ::"r"(a) : "memory"); }
#define GIVE_UP(id) "trap;\n"
#define SPIN_MAX "0x400000"
#define SPIN_TAIL(id) "add.u32 n, n, 1;\n setp.lt.u32 p, n, " SPIN_MAX ";\n @p bra.uni LP;\n" GIVE_UP(id) " DN:\n }"
__device__ __forceinline__ void mbar_wait(uint32_t a, uint32_t ph) {
    asm volatile("{ .reg .pred p; .reg .b32 n; mov.u32 n, 0;\n LP:\n"
                 "mbarrier.try_wait.parity.shared::cta.b64 p, [%0], %1;\n @p bra DN;\n"
                 "add.u32 n, n, 1;\n setp.lt.u32 p, n, " SPIN_MAX ";\n @p bra LP;\n"
                 GIVE_UP("")
                 " DN:\n }" ::"r"(a), "r"(ph) : "memory");
}
#define ELECT "{ .reg .pred e; elect.sync _|e, 0xffffffff; @e "
__device__ __forceinline__ void tma2d(uint32_t dst, const CUtensorMap* m, int c0, int c1, uint32_t bar) {
    asm volatile(ELECT "cp.async.bulk.tensor.2d.shared::cluster.global.mbarrier::complete_tx::bytes [%0], [%1, {%3, %4}], [%2]; }" ::"r"(dst), "l"(m), "r"(bar), "r"(c0), "r"(c1) : "memory");
}
__device__ __forceinline__ void tma3x(uint32_t dst, const CUtensorMap* m, int row, uint32_t bar) {
    asm volatile(ELECT "cp.async.bulk.tensor.3d.shared::cluster.global.mbarrier::complete_tx::bytes [%0], [%1, {0, %3, 0}], [%2]; }" ::"r"(dst), "l"(m), "r"(bar), "r"(row) : "memory");
}
template <int OFF>
__device__ __forceinline__ void ld_pkt(uint32_t* v, const uint4* p) {
    asm volatile("{ .reg .b128 t; ld.relaxed.gpu.global.b128 t, [%4+%5]; mov.b128 {%0,%1,%2,%3}, t; }" : "=r"(v[0]), "=r"(v[1]), "=r"(v[2]), "=r"(v[3]) : "l"(p), "n"(OFF * 16) : "memory");
}
template <int OFF>
__device__ __forceinline__ void st_pkt(uint4* p, uint32_t a, uint32_t b, uint32_t c, uint32_t d) {
    asm volatile("{ .reg .b128 t; mov.b128 t, {%1,%2,%3,%4}; st.relaxed.gpu.global.b128 [%0+%5], t; }" ::"l"(p), "r"(a), "r"(b), "r"(c), "r"(d), "n"(OFF * 16) : "memory");
}
__device__ __forceinline__ uint32_t pack2(float lo, float hi) {
    uint32_t r;
    asm("cvt.rn.bf16x2.f32 %0, %1, %2;" : "=r"(r) : "f"(hi), "f"(lo));
    return r;
}
__device__ __forceinline__ float bf_lo(uint32_t w) { return __uint_as_float(w << 16); }
__device__ __forceinline__ float bf_hi(uint32_t w) { return __uint_as_float(w & 0xffff0000u); }
__device__ __forceinline__ uint32_t settag(uint32_t w, uint32_t tag) { return (w & ~1u) | tag; }
__device__ __forceinline__ float ex2(float x) { float y; asm("ex2.approx.ftz.f32 %0, %1;" : "=f"(y) : "f"(x)); return y; }
__device__ __forceinline__ float rcp(float x) { float y; asm("rcp.approx.ftz.f32 %0, %1;" : "=f"(y) : "f"(x)); return y; }
__device__ __forceinline__ float tanh_hw(float x) { float y; asm("tanh.approx.f32 %0, %1;" : "=f"(y) : "f"(x)); return y; }
__device__ __forceinline__ void stsm4(uint32_t addr, uint32_t a, uint32_t b, uint32_t c, uint32_t d) {
    asm volatile("stmatrix.sync.aligned.m8n8.x4.shared.b16 [%0], {%1,%2,%3,%4};" ::"r"(addr), "r"(a), "r"(b), "r"(c), "r"(d) : "memory");
}
__device__ __forceinline__ void fence_async() { asm volatile("fence.proxy.async.shared::cta;" ::: "memory"); }
__device__ __forceinline__ void bar_sync(int id, int n) { asm volatile("bar.sync %0, %1;" ::"r"(id), "r"(n) : "memory"); }
__device__ __forceinline__ void bar_arrive(int id, int n) { asm volatile("bar.arrive %0, %1;" ::"r"(id), "r"(n) : "memory"); }
__device__ __forceinline__ void wg_fence() { asm volatile("wgmma.fence.sync.aligned;" ::: "memory"); }
__device__ __forceinline__ void wg_commit() { asm volatile("wgmma.commit_group.sync.aligned;" ::: "memory"); }
template <int N> __device__ __forceinline__ void wg_wait() { asm volatile("wgmma.wait_group.sync.aligned %0;" ::"n"(N) : "memory"); }

constexpr uint32_t SB0 = 1024;
__host__ __device__ constexpr uint32_t dlo(uint32_t off, uint32_t lbo) { return ((SB0 + off) >> 4) | ((lbo >> 4) << 16); }
__host__ __device__ constexpr uint32_t dhi(uint32_t sbo, uint32_t sw) { return (sbo >> 4) | (sw << 30); }
__device__ __forceinline__ uint64_t dbase(uint32_t lo, uint32_t hi) { uint64_t d; asm volatile("mov.b64 %0, {%1, %2};" : "=l"(d) : "r"(lo), "r"(hi)); return d; }
#define BASE128(off, lbo, adj) dbase(dlo(off, lbo) + (adj), dhi(1024, 1))
#define BASE64(off, lbo, adj) dbase(dlo(off, lbo) + (adj), dhi(512, 2))

#define ACC4(d, o) "+f"(d[o]), "+f"(d[o + 1]), "+f"(d[o + 2]), "+f"(d[o + 3])
#define ACC28(d) ACC4(d, 0), ACC4(d, 4), ACC4(d, 8), ACC4(d, 12), ACC4(d, 16), ACC4(d, 20), ACC4(d, 24)
#define ACC32(d, o) ACC4(d, o), ACC4(d, o + 4), ACC4(d, o + 8), ACC4(d, o + 12), ACC4(d, o + 16), ACC4(d, o + 20), ACC4(d, o + 24), ACC4(d, o + 28)

template <int TB, uint64_t D>
__device__ __forceinline__ void mma_rs56(float* d, uint32_t a0, uint32_t a1, uint32_t a2, uint32_t a3, int sd, uint64_t base) {
    asm volatile("{ .reg .pred p; .reg .b64 db; setp.ne.b32 p, %32, 0; add.u64 db, %33, %34;\n"
                 "wgmma.mma_async.sync.aligned.m64n56k16.f32.bf16.bf16 "
                 "{%0,%1,%2,%3,%4,%5,%6,%7,%8,%9,%10,%11,%12,%13,%14,%15,%16,%17,%18,%19,%20,%21,%22,%23,%24,%25,%26,%27}, "
                 "{%28,%29,%30,%31}, db, p, 1, 1, %35; }\n"
                 : ACC28(d)
                 : "r"(a0), "r"(a1), "r"(a2), "r"(a3), "r"(sd), "l"(base), "n"(D), "n"(TB));
}
template <int TB, uint64_t D>
__device__ __forceinline__ void mma_rs64(float* d, uint32_t a0, uint32_t a1, uint32_t a2, uint32_t a3, int sd, uint64_t base) {
    asm volatile("{ .reg .pred p; .reg .b64 db; setp.ne.b32 p, %36, 0; add.u64 db, %37, %38;\n"
                 "wgmma.mma_async.sync.aligned.m64n64k16.f32.bf16.bf16 "
                 "{%0,%1,%2,%3,%4,%5,%6,%7,%8,%9,%10,%11,%12,%13,%14,%15,%16,%17,%18,%19,%20,%21,%22,%23,%24,%25,%26,%27,%28,%29,%30,%31}, "
                 "{%32,%33,%34,%35}, db, p, 1, 1, %39; }\n"
                 : ACC32(d, 0)
                 : "r"(a0), "r"(a1), "r"(a2), "r"(a3), "r"(sd), "l"(base), "n"(D), "n"(TB));
}
template <int TB, uint64_t D>
__device__ __forceinline__ void mma_rs128(float* d, uint32_t a0, uint32_t a1, uint32_t a2, uint32_t a3, int sd, uint64_t base) {
    asm volatile("{ .reg .pred p; .reg .b64 db; setp.ne.b32 p, %68, 0; add.u64 db, %69, %70;\n"
                 "wgmma.mma_async.sync.aligned.m64n128k16.f32.bf16.bf16 "
                 "{%0,%1,%2,%3,%4,%5,%6,%7,%8,%9,%10,%11,%12,%13,%14,%15,%16,%17,%18,%19,%20,%21,%22,%23,%24,%25,%26,%27,%28,%29,%30,%31,%32,%33,%34,%35,%36,%37,%38,%39,%40,%41,%42,%43,%44,%45,%46,%47,%48,%49,%50,%51,%52,%53,%54,%55,%56,%57,%58,%59,%60,%61,%62,%63}, "
                 "{%64,%65,%66,%67}, db, p, 1, 1, %71; }\n"
                 : ACC32(d, 0), ACC32(d, 32)
                 : "r"(a0), "r"(a1), "r"(a2), "r"(a3), "r"(sd), "l"(base), "n"(D), "n"(TB));
}
template <uint64_t DA, uint64_t DB>
__device__ __forceinline__ void mma_ss56_tt(float* d, int sd, uint64_t ba, uint64_t bb) {
    asm volatile("{ .reg .pred p; .reg .b64 da, db; setp.ne.b32 p, %28, 0; add.u64 da, %29, %31; add.u64 db, %30, %32;\n"
                 "wgmma.mma_async.sync.aligned.m64n56k16.f32.bf16.bf16 "
                 "{%0,%1,%2,%3,%4,%5,%6,%7,%8,%9,%10,%11,%12,%13,%14,%15,%16,%17,%18,%19,%20,%21,%22,%23,%24,%25,%26,%27}, "
                 "da, db, p, 1, 1, 1, 1; }\n"
                 : ACC28(d)
                 : "r"(sd), "l"(ba), "l"(bb), "n"(DA), "n"(DB));
}
template <int... I> struct Seq {};
template <class F, int... I> __device__ __forceinline__ void static_for_impl(F&& f, Seq<I...>) { (f(std::integral_constant<int, I>{}), ...); }
#define FOR7(...) static_for_impl([&](auto T_) { constexpr int t = decltype(T_)::value; __VA_ARGS__; }, Seq<0, 1, 2, 3, 4, 5, 6>{})
#define FOR8(...) static_for_impl([&](auto T_) { constexpr int t = decltype(T_)::value; __VA_ARGS__; }, Seq<0, 1, 2, 3, 4, 5, 6, 7>{})
#define FOR14(...) static_for_impl([&](auto T_) { constexpr int t = decltype(T_)::value; __VA_ARGS__; }, Seq<0, 1, 2, 3, 4, 5, 6, 7, 8, 9, 10, 11, 12, 13>{})

__device__ __forceinline__ int kblk(int p, int b) { return b == 0 ? p : b - (b <= p); }
__host__ __device__ constexpr int krow(int t) { return t < 3 ? 16 * t : (t < 6 ? 56 + 16 * (t - 3) : 48); }
#define AQ(A, b, t) ((t) < 3 ? A[2 * (b)][4 * (t)] : (t) < 6 ? A[2 * (b) + 1][4 * ((t) - 3)] : A[2 * (b)][12]), \
                    ((t) < 3 ? A[2 * (b)][4 * (t) + 1] : (t) < 6 ? A[2 * (b) + 1][4 * ((t) - 3) + 1] : A[2 * (b)][13]), \
                    ((t) < 3 ? A[2 * (b)][4 * (t) + 2] : (t) < 6 ? A[2 * (b) + 1][4 * ((t) - 3) + 2] : A[2 * (b) + 1][12]), \
                    ((t) < 3 ? A[2 * (b)][4 * (t) + 3] : (t) < 6 ? A[2 * (b) + 1][4 * ((t) - 3) + 3] : A[2 * (b) + 1][13])
#define D128(off, t) ((uint64_t)(((off) + krow(t) * 128) >> 4) + ((uint64_t)((t) == 6 ? (7168 - 1024) >> 4 : 0) << 32))
#define D64(off, t) ((uint64_t)(((off) + krow(t) * 64) >> 4) + ((uint64_t)((t) == 6 ? (3584 - 512) >> 4 : 0) << 32))

#define PL(k) (((k) - 3) * PLANE)
__device__ __forceinline__ void st_word(uint32_t* p, uint32_t v) { asm volatile("st.relaxed.gpu.global.u32 [%0], %1;" ::"l"(p), "r"(v) : "memory"); }
__device__ __forceinline__ uint32_t ld_word(const uint32_t* p) { uint32_t v; asm volatile("ld.relaxed.gpu.global.u32 %0, [%1];" : "=r"(v) : "l"(p) : "memory"); return v; }
__device__ __forceinline__ void tag_slice(uint32_t* w, uint32_t tag) { w[0] = settag(w[0], tag); w[4] = settag(w[4], tag); w[8] = settag(w[8], tag); w[12] = settag(w[12], tag); }
template <int O>
__device__ __forceinline__ void send_slice(uint4* dst, int lane, const uint32_t* w) {
    st_pkt<O>(dst, w[0], w[1], w[2], w[3]);
    st_pkt<O + 32>(dst, w[4], w[5], w[6], w[7]);
    st_pkt<O + 64>(dst, w[8], w[9], w[10], w[11]);
    asm volatile("{ .reg .b64 t; mov.b64 t, {%1,%2}; st.relaxed.gpu.global.b64 [%0+%3], t; }" ::"l"((char*)dst - lane * 8), "r"(w[12]), "r"(w[13]), "n"(16 * (O + 96)) : "memory");
}
#define RW4(v, o) "+r"(v[o]), "+r"(v[(o) + 1]), "+r"(v[(o) + 2]), "+r"(v[(o) + 3])
#define RW2(v, o) "+r"(v[o]), "+r"(v[(o) + 1])
#define WR4(v, o) "=&r"(v[o]), "=&r"(v[(o) + 1]), "=&r"(v[(o) + 2]), "=&r"(v[(o) + 3])
#define LDP(a, b, c, d, addr, off) "ld.relaxed.gpu.global.b128 q, [" addr "+" off "];\n mov.b128 {" a "," b "," c "," d "}, q;\n"
#define LDH(a, b, addr, off) "ld.relaxed.gpu.global.b64 h, [" addr "+" off "];\n mov.b64 {" a "," b "}, h;\n"
#define VOTE_OK "and.b32 t, t, 1;\n setp.ne.u32 p, t, 0;\n vote.sync.any.pred p, p, 0xffffffff;\n @!p bra.uni DN;\n"
#define CHK(x, tag) "lop3.b32 t, " x ", " tag ", t, 0xBE;\n"
__device__ __forceinline__ void check_cnt(uint32_t v, const uint32_t* p, uint32_t target) {
    asm volatile("{ .reg .pred p; .reg .b32 n, t; mov.u32 n, 0; mov.u32 t, %2;\n LP:\n"
                 "sub.s32 t, t, %1;\n setp.lt.s32 p, t, 0;\n vote.sync.any.pred p, p, 0xffffffff;\n @!p bra.uni DN;\n ld.relaxed.gpu.global.u32 t, [%0];\n" SPIN_TAIL("7")
                 ::"l"(p), "r"(target), "r"(v) : "memory");
}
__device__ __forceinline__ void poll_cnt(const uint32_t* p, uint32_t target) {
    asm volatile("{ .reg .pred p; .reg .b32 n, t; mov.u32 n, 0;\n LP:\n"
                 "ld.relaxed.gpu.global.u32 t, [%0];\n sub.s32 t, t, %1;\n setp.lt.s32 p, t, 0;\n vote.sync.any.pred p, p, 0xffffffff;\n @!p bra.uni DN;\n" SPIN_TAIL("1")
                 ::"l"(p), "r"(target) : "memory");
}
template <int STR>
__device__ __forceinline__ void poll4_kv(uint32_t* v, const uint4* p, uint32_t tag) {
    asm volatile("{ .reg .pred p; .reg .b32 n, t; .reg .b128 q; mov.u32 n, 0;\n LP:\n"
                 LDP("%0", "%1", "%2", "%3", "%16", "0") LDP("%4", "%5", "%6", "%7", "%16", "%18")
                 LDP("%8", "%9", "%10", "%11", "%16", "%19") LDP("%12", "%13", "%14", "%15", "%16", "%20")
                 "xor.b32 t, %0, %17;\n" CHK("%4", "%17") CHK("%8", "%17") CHK("%12", "%17") VOTE_OK SPIN_TAIL("2")
                 : WR4(v, 0), WR4(v, 4), WR4(v, 8), WR4(v, 12)
                 : "l"(p), "r"(tag), "n"(16 * STR), "n"(32 * STR), "n"(48 * STR)
                 : "memory");
}
template <int STR>
__device__ __forceinline__ void check4_kv(uint32_t* v, const uint4* p, uint32_t tag) {
    asm volatile("{ .reg .pred p; .reg .b32 n, t; .reg .b128 q; mov.u32 n, 0;\n LP:\n"
                 "xor.b32 t, %0, %17;\n" CHK("%4", "%17") CHK("%8", "%17") CHK("%12", "%17") VOTE_OK
                 LDP("%0", "%1", "%2", "%3", "%16", "0") LDP("%4", "%5", "%6", "%7", "%16", "%18")
                 LDP("%8", "%9", "%10", "%11", "%16", "%19") LDP("%12", "%13", "%14", "%15", "%16", "%20") SPIN_TAIL("8")
                 : RW4(v, 0), RW4(v, 4), RW4(v, 8), RW4(v, 12)
                 : "l"(p), "r"(tag), "n"(16 * STR), "n"(32 * STR), "n"(48 * STR)
                 : "memory");
}
template <int B>
__device__ __forceinline__ void blk_load(uint32_t (&A)[8][14], const uint4* src, int lane) {
    ld_pkt<0>(&A[2 * B][0], src); ld_pkt<32>(&A[2 * B][4], src); ld_pkt<64>(&A[2 * B][8], src);
    ld_pkt<512>(&A[2 * B + 1][0], src); ld_pkt<544>(&A[2 * B + 1][4], src); ld_pkt<576>(&A[2 * B + 1][8], src);
    asm volatile("{ .reg .b64 h;\n" LDH("%0", "%1", "%4", "1536") LDH("%2", "%3", "%4", "9728") "}"
                 : "=&r"(A[2 * B][12]), "=&r"(A[2 * B][13]), "=&r"(A[2 * B + 1][12]), "=&r"(A[2 * B + 1][13])
                 : "l"((const char*)src - lane * 8) : "memory");
}
template <int B>
__device__ __forceinline__ void blk_check(uint32_t (&A)[8][14], const uint4* src, int lane, uint32_t tag) {
    asm volatile("{ .reg .pred p; .reg .b32 n, t; .reg .b128 q; .reg .b64 h, a8; mov.u32 n, 0;\n LP:\n"
                 "xor.b32 t, %0, %30;\n" CHK("%4", "%30") CHK("%8", "%30") CHK("%12", "%30") CHK("%16", "%30") CHK("%20", "%30") CHK("%24", "%30") CHK("%26", "%30") VOTE_OK
                 LDP("%0", "%1", "%2", "%3", "%28", "0") LDP("%4", "%5", "%6", "%7", "%28", "512") LDP("%8", "%9", "%10", "%11", "%28", "1024")
                 LDP("%12", "%13", "%14", "%15", "%28", "8192") LDP("%16", "%17", "%18", "%19", "%28", "8704") LDP("%20", "%21", "%22", "%23", "%28", "9216")
                 "mad.wide.s32 a8, %29, -8, %28;\n" LDH("%24", "%25", "a8", "1536") LDH("%26", "%27", "a8", "9728") SPIN_TAIL("3")
                 "\n and.b32 %0, %0, -2; and.b32 %4, %4, -2; and.b32 %8, %8, -2; and.b32 %12, %12, -2; and.b32 %16, %16, -2; and.b32 %20, %20, -2; and.b32 %24, %24, -2; and.b32 %26, %26, -2;"
                 : RW4(A[2 * B], 0), RW4(A[2 * B], 4), RW4(A[2 * B], 8), RW4(A[2 * B + 1], 0), RW4(A[2 * B + 1], 4), RW4(A[2 * B + 1], 8),
                   RW2(A[2 * B], 12), RW2(A[2 * B + 1], 12)
                 : "l"(src), "r"(lane), "r"(tag)
                 : "memory");
}
__device__ __forceinline__ void st_async4(uint32_t a, uint32_t x, uint32_t y, uint32_t z, uint32_t w, uint32_t bar) {
    asm volatile("st.async.weak.shared::cluster.mbarrier::complete_tx::bytes.v4.b32 [%0], {%1,%2,%3,%4}, [%5];" ::"r"(a), "r"(x), "r"(y), "r"(z), "r"(w), "r"(bar) : "memory");
}
__device__ __forceinline__ uint32_t mapa(uint32_t a, uint32_t cta) { uint32_t r; asm("mapa.shared::cluster.u32 %0, %1, %2;" : "=r"(r) : "r"(a), "r"(cta)); return r; }
__device__ __forceinline__ void stat_load(uint32_t* v, const uint4* p) { ld_pkt<0>(v, p); ld_pkt<512>(v + 4, p); }
__device__ __forceinline__ void stat_check(uint32_t* v, const uint4* p, uint32_t tag) {
    asm volatile("{ .reg .pred p; .reg .b32 n, t; .reg .b128 q; mov.u32 n, 0;\n LP:\n"
                 "xor.b32 t, %3, %9;\n" CHK("%7", "%9") VOTE_OK
                 LDP("%0", "%1", "%2", "%3", "%8", "0") LDP("%4", "%5", "%6", "%7", "%8", "8192") SPIN_TAIL("4")
                 : RW4(v, 0), RW4(v, 4) : "l"(p), "r"(tag) : "memory");
}
__device__ __forceinline__ uint32_t x_bits(const uint32_t* X) {
    uint32_t r;
    asm volatile("{ .reg .b32 a, b; prmt.b32 a, %1, %2, 0x0040; prmt.b32 b, %3, %4, 0x0040; prmt.b32 %0, a, b, 0x5410; }" : "=r"(r) : "r"(X[0]), "r"(X[4]), "r"(X[8]), "r"(X[12]));
    return r;
}
template <int O>
__device__ __forceinline__ void slice_load(uint32_t* v, const uint4* p, int lane) {
    ld_pkt<O>(v, p); ld_pkt<O + 32>(v + 4, p); ld_pkt<O + 64>(v + 8, p);
    asm volatile("{ .reg .b64 h;\n" LDH("%0", "%1", "%2", "%3") "}" : "=r"(v[12]), "=r"(v[13]) : "l"((const char*)p - lane * 8), "n"(16 * (O + 96)) : "memory");
}
template <int O>
__device__ __forceinline__ void slice_check(uint32_t* v, const uint4* p, int lane, uint32_t tag) {
    asm volatile("{ .reg .pred p; .reg .b32 n, t; .reg .b128 q; .reg .b64 h; mov.u32 n, 0;\n LP:\n"
                 "xor.b32 t, %0, %16;\n" CHK("%4", "%16") CHK("%8", "%16") CHK("%12", "%16") VOTE_OK
                 LDP("%0", "%1", "%2", "%3", "%14", "%17") LDP("%4", "%5", "%6", "%7", "%14", "%18") LDP("%8", "%9", "%10", "%11", "%14", "%19")
                 LDH("%12", "%13", "%15", "%20") SPIN_TAIL("5")
                 : RW4(v, 0), RW4(v, 4), RW4(v, 8), RW2(v, 12)
                 : "l"(p), "l"((const char*)p - lane * 8), "r"(tag), "n"(16 * O), "n"(16 * (O + 32)), "n"(16 * (O + 64)), "n"(16 * (O + 96))
                 : "memory");
}
__device__ __forceinline__ void x_fix(uint32_t* X, uint32_t bits) {
    X[0] = __byte_perm(X[0], bits, 0x3214); X[4] = __byte_perm(X[4], bits, 0x3215); X[8] = __byte_perm(X[8], bits, 0x3216); X[12] = __byte_perm(X[12], bits, 0x3217);
}
__device__ __forceinline__ void sts4(uint32_t a, uint32_t x, uint32_t y, uint32_t z, uint32_t w) {
    asm volatile("st.shared.v4.u32 [%0], {%1,%2,%3,%4};" ::"r"(a), "r"(x), "r"(y), "r"(z), "r"(w) : "memory");
}
__device__ __forceinline__ void lds4(uint32_t* v, uint32_t a) {
    asm volatile("ld.shared.v4.u32 {%0,%1,%2,%3}, [%4];" : "=r"(v[0]), "=r"(v[1]), "=r"(v[2]), "=r"(v[3]) : "r"(a) : "memory");
}
struct LnCoef { uint32_t hi, lo, sh; };
__device__ __forceinline__ LnCoef ln_coef(float sum, float sq) {
    sum += __shfl_xor_sync(0xffffffffu, sum, 1); sq += __shfl_xor_sync(0xffffffffu, sq, 1);
    sum += __shfl_xor_sync(0xffffffffu, sum, 2); sq += __shfl_xor_sync(0xffffffffu, sq, 2);
    const float mean = sum * (1.f / 448.f);
    const float var = fmaxf(fmaf(-mean, mean, sq * (1.f / 448.f)), 0.f);
    const float sc = rsqrtf(var + 1e-5f);
    LnCoef r;
    r.hi = pack2(sc, sc);
    const float lo = sc - bf_lo(r.hi), sh = -mean * sc;
    r.lo = pack2(lo, lo);
    r.sh = pack2(sh, sh);
    return r;
}
template <int B>
__device__ __forceinline__ void normalize(uint32_t (&A)[8][14], const LnCoef& c0, const LnCoef& c1) {
#pragma unroll
    for (int s = 2 * B; s < 2 * B + 2; s++)
#pragma unroll
        for (int i = 0; i < 14; i++) {
            const LnCoef& k = (i & 1) ? c1 : c0;
            asm("{ .reg .b32 t; fma.rn.bf16x2 t, %0, %2, %3; fma.rn.bf16x2 %0, %0, %1, t; }" : "+r"(A[s][i]) : "r"(k.hi), "r"(k.lo), "r"(k.sh));
        }
}
__device__ __forceinline__ void slice_stats(const uint32_t* w, float* st) {
    float a = 0.f, b = 0.f, p = 0.f, q = 0.f;
#pragma unroll
    for (int i = 0; i < 7; i++) {
        const float e0 = bf_lo(w[2 * i]), e1 = bf_hi(w[2 * i]), e2 = bf_lo(w[2 * i + 1]), e3 = bf_hi(w[2 * i + 1]);
        a += e0 + e1; b += e2 + e3;
        p = fmaf(e0, e0, p); p = fmaf(e1, e1, p); q = fmaf(e2, e2, q); q = fmaf(e3, e3, q);
    }
    a += __shfl_xor_sync(0xffffffffu, a, 1); p += __shfl_xor_sync(0xffffffffu, p, 1); b += __shfl_xor_sync(0xffffffffu, b, 1); q += __shfl_xor_sync(0xffffffffu, q, 1);
    a += __shfl_xor_sync(0xffffffffu, a, 2); p += __shfl_xor_sync(0xffffffffu, p, 2); b += __shfl_xor_sync(0xffffffffu, b, 2); q += __shfl_xor_sync(0xffffffffu, q, 2);
    st[0] = a; st[1] = p; st[2] = b; st[3] = q;
}
__device__ __forceinline__ void dual_softmax(const float* p, uint32_t* out) {
    constexpr float L = 1.4426950408889634f;
#pragma unroll
    for (int r = 0; r < 2; r++) {
        float mx = fmaxf(p[2 * r], p[2 * r + 1]), mn = fminf(p[2 * r], p[2 * r + 1]);
#pragma unroll
        for (int i = 1; i < 7; i++) {
            mx = fmaxf(mx, fmaxf(p[4 * i + 2 * r], p[4 * i + 2 * r + 1]));
            mn = fminf(mn, fminf(p[4 * i + 2 * r], p[4 * i + 2 * r + 1]));
        }
        mx = fmaxf(mx, __shfl_xor_sync(0xffffffffu, mx, 1));
        mn = fminf(mn, __shfl_xor_sync(0xffffffffu, mn, 1));
        const float bx = -mx * L, bn = mn * L;
        float ep[14], en[14], sp = 0.f, sn = 0.f;
#pragma unroll
        for (int i = 0; i < 14; i++) {
            const float v = p[4 * (i >> 1) + 2 * r + (i & 1)];
            ep[i] = ex2(fmaf(v, L, bx));
            en[i] = ex2(fmaf(v, -L, bn));
            sp += ep[i]; sn += en[i];
        }
        sp += __shfl_xor_sync(0xffffffffu, sp, 1);
        sn += __shfl_xor_sync(0xffffffffu, sn, 1);
        const float ip = rcp(sp), in = rcp(sn);
#pragma unroll
        for (int i = 0; i < 7; i++) {
            out[4 * i + r] = pack2(ep[2 * i] * ip, ep[2 * i + 1] * ip);
            out[4 * i + 2 + r] = pack2(en[2 * i] * in, en[2 * i + 1] * in);
        }
    }
}
__device__ __forceinline__ float geglu(float g, float u) {
    const float t = tanh_hw(g * fmaf(g * g, 0.7978845608028654f * 0.044715f, 0.7978845608028654f));
    const float gu = g * u;
    return fmaf(t, gu, gu);
}
__device__ __forceinline__ void phi_gemm(const float* t, float* p) {
    uint32_t w[14];
#pragma unroll
    for (int i = 0; i < 14; i++) w[i] = pack2(t[2 * i], t[2 * i + 1]);
    const uint64_t db = BASE128(OFF_WPHI, 16, 0);
    wg_fence();
    mma_rs56<0, 0>(p, w[0], w[1], w[2], w[3], 0, db);
    mma_rs56<0, 2>(p, w[4], w[5], w[6], w[7], 1, db);
    mma_rs56<0, 4>(p, w[8], w[9], w[10], w[11], 1, db);
    mma_rs56<0, 6>(p, w[12], w[13], 0u, 0u, 1, db);
    wg_commit();
    wg_wait<0>();
}

}

#define BAR(i) (bars + 8 * (i))
#define R_WAIT() mbar_wait(BAR(slot), ph)
#define WSUM(i)
#define R_ADJ (slot * (STAGE >> 4))
#define R_NEXT() do { eb2 = eb1; eb1 = BAR(B_EMPTY + slot); if (++slot == NST) { slot = 0; ph ^= 1; } } while (0)
#define R_RELEASE(k) do { if (lane == 0) mbar_arrive((k) == 1 ? eb1 : eb2); } while (0)
#define PUSH_BEGIN() do { mbar_wait(BAR(B_ACK + wgi), ackph); ackph ^= 1; } while (0)
#define PUSH_ACK() do { __syncwarp(); if (lane == 0) asm volatile("mbarrier.arrive.shared::cluster.b64 _, [%0];" ::"r"(mapa(BAR(B_ACK + wgi), hr ^ 1)) : "memory"); } while (0)

__global__ void __cluster_dims__(2, 1, 1) __launch_bounds__(384, 1)
fused_kernel(Scratch* const sc, const __nv_bfloat16* __restrict__ x_in, const __nv_bfloat16* __restrict__ w_phi, const int trips,
             const __nv_bfloat16* __restrict__ wg, const __nv_bfloat16* __restrict__ wu, const __nv_bfloat16* __restrict__ wd,
             const __grid_constant__ Maps maps) {
    extern __shared__ __align__(1024) unsigned char smem_raw[];
    const uint32_t sb = s2u(smem_raw);
    const uint32_t bars = sb + OFF_BAR;
    const int wgi = __shfl_sync(0xffffffffu, threadIdx.x >> 7, 0);
    const int hr = blockIdx.x & 1, ck = blockIdx.x >> 1;
    const int gp = (ck - 4) & 7, q7 = ((ck - 36) * 37) >> 8;
    const int pr = ck < 4 ? ck : (ck < 36 ? (ck - 4) >> 3 : q7);
    const int tile = ck < 4 ? 0 : (ck < 36 ? (gp ? 2 * gp : 1) : 2 * (ck - 36 - 7 * q7) + 3);
    const int sl = 2 * pr + hr;
    STAMP(0);
    GSTAMP(60);
    if (threadIdx.x == 256) {
#pragma unroll
        for (int i = 0; i < NST; i++) mbar_init(BAR(i), 1);
        asm volatile("fence.mbarrier_init.release.cluster;" ::: "memory");
    }
    if (threadIdx.x == 288) {
        if ((sb & 0x3FFFF) != SB0) asm volatile("trap;");
#pragma unroll
        for (int i = NST; i < B_COUNT; i++) mbar_init(BAR(i), i >= B_ACK ? 4 : (i < B_RECV ? 8 : 1));
        asm volatile("fence.mbarrier_init.release.cluster;" ::: "memory");
    }
    __syncwarp();
    asm volatile("barrier.cluster.arrive.relaxed.aligned;" ::: "memory");

    if (wgi == 2) {
        asm volatile("setmaxnreg.dec.sync.aligned.u32 40;");
        const int t128 = fresh_tid() & 127, w = __shfl_sync(0xffffffffu, t128 >> 5, 0), lane = t128 & 31;
        uint32_t e0[2] = {0, 0}, e1[2] = {0, 0}, cw_target = 0;
        if (w == 0) {
#pragma unroll 1
            for (int n = 0; n < NST; n++) {
                const uint32_t dst = sb + n * STAGE, fb = BAR(n);
                asm volatile(ELECT "mbarrier.arrive.expect_tx.shared::cta.b64 _, [%0], %1; }" ::"r"(fb), "r"(n < 2 ? 2 * STAGE : STAGE) : "memory");
                if (n < 2) {
                    tma3x(sb + OFF_H + n * STAGE, &maps.x, tile * 128 + n * 64, fb);
                    tma3x(dst, &maps.x, tile * 128 + n * 64 + 32, fb);
                } else {
                    if (n == 3) mbar_wait(BAR(1), 0);
                    const int ra = 112 * (n - 2);
                    tma2d(dst, &maps.qkv, 448 + 56 * sl, ra, fb);
                    tma2d(dst + HALF, &maps.qkv, 896 + 56 * sl, ra, fb);
                }
            }
            asm volatile("barrier.cluster.wait.aligned;" ::: "memory");
            cw_target = (ld_word(g_cw + sl * 32) & ~15u) + 16;
#pragma unroll 1
            for (int k = 0; k < 2; k++) {
                const int n = t128 + 32 * k;
                int m = n - 2 - (n > PACK);
                const bool packed = m >= 30 ? (m < 38 || m >= 52) : m >= 22;
                if (m >= 30) m -= 30;
                if (n == PACK) m = tile < 8 ? tile : tile + 14;
                const int rot = n < 8 ? 0 : pr;
                const int ra = 112 * kblk(rot, m & 3), rb = 112 * kblk(rot, 2 * m & 3), rc = 112 * kblk(rot, (2 * m + 1) & 3);
                int kind = 0, m0, m1, c0, c1, r0, r1;
                if (m < 4) { m0 = m1 = 1; c0 = 448 + 56 * sl; c1 = c0 + 448; r0 = r1 = ra; }
                else if (m < 8) { m0 = m1 = m < 6 ? 1 : 2; c0 = c1 = 56 * sl; r0 = rb; r1 = rc; }
                else if (m < 20) { m0 = 3; m1 = 4; c0 = c1 = 224 * sl + 32 * hr + 64 * ((m - 8) >> 2); r0 = r1 = ra; }
                else if (m < 22) { kind = 2; m0 = 5; m1 = 6; c0 = c1 = 224 * sl + (hr ? 0 : 192); r0 = rb; r1 = rc; }
                else { m0 = m1 = 7; c0 = c1 = 56 * (2 * ((pr + (m >> 1) - 10) & 3) + hr); r0 = 224 * (sl ^ (m & 1)); r1 = r0 + 112; }
                if (packed) { kind = 1; r0 = sl * 16 + (m < 8 ? m : m - 14); r1 = 0; }
                e0[0] = e0[1]; e1[0] = e1[1];
                e0[1] = kind | (m0 << 2) | (m1 << 6) | (c0 << 10) | (c1 << 21);
                e1[1] = r0 | (r1 << 16);
            }
        } else {
            const int j = t128 - 32;
            asm volatile("barrier.cluster.wait.aligned;" ::: "memory");
            uint2 wv[7];
            const int k = j < 56 ? j : 55, hh = k >= 28;
#pragma unroll
            for (int i = 0; i < 7; i++) wv[i] = __ldg(reinterpret_cast<const uint2*>(w_phi + (sl * 56 + k) * 28) + i);
#pragma unroll 1
            for (int i = j; i < 7168 / 16; i += 96) sts4(sb + OFF_WPHI + i * 16, 0, 0, 0, 0);
            bar_sync(5, 96);
            if (j < 56) {
                uint32_t a4[4];
#pragma unroll
                for (int q = 0; q < 4; q++) a4[q] = sb + OFF_WPHI + (4 * hh + q) * 128 + ((((k >> 3) ^ (4 * hh + q)) & 7) << 4) + (k & 7) * 2;
                FOR14(const uint32_t v = (t & 1) ? wv[t >> 1].y : wv[t >> 1].x;
                      asm volatile("{ .reg .b16 l, h; mov.b32 {l, h}, %2; st.shared.u16 [%0+%3], l; st.shared.u16 [%1+%3], h; }"
                                   ::"r"(a4[t >= 7 ? 2 : 0]), "r"(a4[t >= 7 ? 3 : 1]), "r"(v), "n"((t % 7) * 1024) : "memory"));
            }
            __syncwarp();
            fence_async();
            bar_arrive(1, 224);
            bar_arrive(9, 224);
            if (w == 1) {
                mbar_wait(BAR(2), 0);
                mbar_wait(BAR(2), 1);
                const int b = blockIdx.x;
                asm volatile(ELECT "cp.async.bulk.prefetch.L2.global [%0], %1; }" ::"l"(wg + b * 6272), "r"(12544) : "memory");
                asm volatile(ELECT "cp.async.bulk.prefetch.L2.global [%0], %1; }" ::"l"(wu + b * 6272), "r"(12544) : "memory");
                asm volatile(ELECT "cp.async.bulk.prefetch.L2.global [%0], %1; }" ::"l"(wd + b * 6272), "r"(12544) : "memory");
            }
        }
        int slot = 0, ph = 0, n = NST;
#pragma unroll 1
        for (int layer = 0; layer < 3; layer++) {
            if (w == 0) {
                const int nend = layer == 0 ? 11 : (layer == 1 ? 42 : 63);
#pragma unroll 1
                for (; n < nend; n++) {
                const uint32_t w0 = __shfl_sync(0xffffffffu, n < 32 ? e0[0] : e0[1], n & 31), w1 = __shfl_sync(0xffffffffu, n < 32 ? e1[0] : e1[1], n & 31);
                const uint32_t dst = sb + slot * STAGE, fb = BAR(n == PACK ? B_PACK : slot);
                const CUtensorMap* m0 = &maps.x + ((w0 >> 2) & 15);
                const CUtensorMap* m1 = &maps.x + ((w0 >> 6) & 15);
                const int c0 = (w0 >> 10) & 2047, c1 = w0 >> 21, r0 = w1 & 0xffff, r1 = w1 >> 16;
                if (n == 25) {
                    int it = 0;
                    uint32_t v;
                    do { asm volatile("ld.acquire.gpu.global.u32 %0, [%1];" : "=r"(v) : "l"(g_cw + sl * 32) : "memory"); } while ((int)(v - cw_target) < 0 && ++it < 0x400000);
                    asm volatile("fence.proxy.async.global;" ::: "memory");
                    __syncwarp();
                }
                mbar_wait(BAR(B_EMPTY + slot), ph);
                __syncwarp();
                asm volatile(ELECT "mbarrier.arrive.expect_tx.shared::cta.b64 _, [%0], %1; }" ::"r"(fb), "r"(STAGE) : "memory");
                if ((w0 & 3) == 0) {
                    tma2d(dst, m0, c0, r0, fb);
                    tma2d(dst + HALF, m1, c1, r1, fb);
                } else if (w0 & 1) {
                    asm volatile(ELECT "cp.async.bulk.shared::cluster.global.mbarrier::complete_tx::bytes [%0], [%1], %2, [%3]; }"
                                 ::"r"(dst), "l"(reinterpret_cast<const char*>(g_wp) + (size_t)r0 * STAGE), "r"(STAGE), "r"(fb) : "memory");
                } else {
                    tma2d(dst, m0, c0, r0, fb); tma2d(dst + 7168, m0, c0, r1, fb);
                    tma2d(dst + HALF, m1, c0, r0, fb); tma2d(dst + HALF + 7168, m1, c0, r1, fb);
                }
                if (n == PACK) asm volatile(ELECT "mbarrier.arrive.shared::cta.b64 _, [%0]; }" ::"r"(BAR(slot)) : "memory");
                if (++slot == NST) { slot = 0; ph ^= 1; }
                }
            } else if (w == 1 && layer == 1) {
                constexpr int ps = PACK % NST;
                mbar_wait(BAR(B_PACK), 0);
                asm volatile("{ .reg .pred e; elect.sync _|e, 0xffffffff;\n"
                             "@e cp.async.bulk.global.shared::cta.bulk_group [%0], [%1], %2;\n"
                             "@e cp.async.bulk.commit_group;\n"
                             "@e cp.async.bulk.wait_group.read 0;\n"
                             "@e mbarrier.arrive.shared::cta.b64 _, [%3], 8;\n"
                             "@e cp.async.bulk.wait_group 0;\n"
                             "@e fence.proxy.async.global;\n"
                             "@e red.release.gpu.global.add.u32 [%4], 1; }"
                             ::"l"(reinterpret_cast<char*>(g_wp) + (size_t)(sl * 16 + tile) * STAGE), "r"(sb + ps * STAGE), "r"(STAGE), "r"(BAR(B_EMPTY + ps)), "l"(g_cw + sl * 32) : "memory");
                __syncwarp();
            }
            if (layer < 2) {
            const uint32_t tag = layer ^ 1;
            if (tile == 15) bar_sync(7, 384);
            if (tile < 15) {
                const int sq = lane >> 3, pk = 8 * w + (lane & (tile == 14 ? 3 : 7));
                uint32_t v[16];
                const uint4* src = g_kv1 + ((sl * 16 + tile) * 16 + 4 * sq) * 32 + pk;
                ld_pkt<0>(v, src); ld_pkt<32>(v + 4, src); ld_pkt<64>(v + 8, src); ld_pkt<96>(v + 12, src);
                bar_sync(7, 384);
                ASTAMP(0);
                check4_kv<32>(v, src, tag);
                ASTAMP(1);
#pragma unroll
                for (int k = 0; k < 4; k++) {
                    float lo = (bf_lo(v[k]) + bf_lo(v[4 + k])) + (bf_lo(v[8 + k]) + bf_lo(v[12 + k]));
                    float hi = (bf_hi(v[k]) + bf_hi(v[4 + k])) + (bf_hi(v[8 + k]) + bf_hi(v[12 + k]));
                    lo += __shfl_xor_sync(0xffffffffu, lo, 8); hi += __shfl_xor_sync(0xffffffffu, hi, 8);
                    lo += __shfl_xor_sync(0xffffffffu, lo, 16); hi += __shfl_xor_sync(0xffffffffu, hi, 16);
                    v[k] = pack2(lo, hi);
                }
                if (sq == 0) st_pkt<0>(g_kv2 + sl * 512 + 32 * tile + pk, settag(v[0], tag), v[1], v[2], v[3]);
            }
            ASTAMP(2);
            {
                const int item = t128 < 112 ? t128 : 112 + (t128 & 3), d = item >> 1;
                const int cc = t128 < 112 ? 2 * (d >= 28) + (item & 1) : item - 112;
                const int r = t128 < 112 ? d : 56 + (cc >> 1) + 2 * ((t128 - 112) >> 2);
                uint32_t ra = sb + OFF_KVB + r * 128 + 4 * cc, rx = (r & 7) << 4;
                asm volatile("" : "+r"(ra), "+r"(rx));
                FOR14(asm volatile("st.shared.u32 [%0+%2], %1;" ::"r"((ra ^ 8) + (((t & 7) << 4) ^ rx)), "r"(0), "n"((t >> 3) * 8192) : "memory"));
                uint32_t v[16];
                asm volatile("" : "+r"(ra), "+r"(rx));
                poll4_kv<8>(v, g_kv2 + sl * 512 + (item >> 3) * 32 + (item & 7), tag);
                FOR14(asm volatile("st.shared.u32 [%0+%2], %1;" ::"r"(ra + (((t & 7) << 4) ^ rx)), "r"(v[t < 7 ? t : t + 1]), "n"((t >> 3) * 8192) : "memory"));
                fence_async();
            }
            bar_arrive(3, 384);
            ASTAMP(3);
            }
        }
    } else {
        asm volatile("setmaxnreg.inc.sync.aligned.u32 232;");
        const int tid = fresh_tid(), lane = tid & 31, t128 = tid & 127, g = lane >> 2, c = lane & 3;
        const int wu = __shfl_sync(0xffffffffu, tid >> 5, 0), w = wu & 3;
        uint4* const xp0 = g_ex + 3 * PLANE + ((tile * 2 + wgi) * 8) * 512 + w * 128 + lane;
        const uint32_t hbuf = sb + OFF_H + wgi * STAGE;
        uint32_t slot = 0, ph = 0, eb1 = 0, eb2 = 0, ackph = 0, rcvph = 0, gatph = 0, swp = 0;
        uint32_t ppid = 6;
#define cx(s) (reinterpret_cast<uint32_t*>(again(xp0) - lane + PL(1) + 112 + (s) * 512))
#define stp (again(xp0) - lane + g + PL(0) + 112)
        uint32_t seq = ld_word(cx(sl));
        uint32_t stag = ld_word(reinterpret_cast<const uint32_t*>(stp + sl * 512) + 3) & 1;
        asm volatile("barrier.cluster.wait.aligned;" ::: "memory");
        STAMP(1);
        uint32_t X[14];
        const uint32_t x0row = (w < 2 ? hbuf : sb + wgi * STAGE) + ((w & 1) * 16 + (lane & 15)) * 128;
        mbar_wait(BAR(wgi), 0);
        STAMP(51);
#pragma unroll
        for (int j = 0; j < 4; j++) {
            const int G = 7 * sl + min(2 * j + (lane >> 4), 6);
            uint32_t q2, q3;
            asm volatile("ldmatrix.sync.aligned.m8n8.x4.shared.b16 {%0,%1,%2,%3}, [%4];" : "=r"(X[4 * j]), "=r"(X[4 * j + 1]), "=r"(q2), "=r"(q3)
                         : "r"(x0row + (G >> 3) * 4096 + (((G ^ lane) & 7) << 4)) : "memory");
            if (j < 3) { X[(4 * j + 2) % 14] = q2; X[(4 * j + 3) % 14] = q3; }
        }
#define PUSH_SLICE(W)                                                                          \
    {                                                                                          \
        if (t128 == 0) mbar_expect_tx(BAR(B_RECV + wgi), 7168);                                \
        PUSH_BEGIN();                                                                          \
        const uint32_t ra = mapa(hbuf + 24576 + t128 * 16, hr ^ 1), rb = mapa(sb + OFF_XR + wgi * 3072, hr ^ 1), rbar = mapa(BAR(B_RECV + wgi), hr ^ 1); \
        st_async4(ra, W[0], W[1], W[2], W[3], rbar);                                           \
        st_async4(ra + 2048, W[4], W[5], W[6], W[7], rbar);                                    \
        st_async4(rb + t128 * 16, W[8], W[9], W[10], W[11], rbar);                             \
        asm volatile("st.async.weak.shared::cluster.mbarrier::complete_tx::bytes.v2.b32 [%0], {%1,%2}, [%3];" ::"r"(rb + 2048 + t128 * 8), "r"(W[12]), "r"(W[13]), "r"(rbar) : "memory"); \
    }
#define PULL_SLICE(W)                                                                          \
    {                                                                                          \
        uint32_t t0, t1;                                                                       \
        mbar_wait(BAR(B_RECV + wgi), rcvph);                                                   \
        rcvph ^= 1;                                                                            \
        lds4(&A[1][0], hbuf + 24576 + t128 * 16);                                              \
        lds4(&A[1][4], hbuf + 26624 + t128 * 16);                                              \
        lds4(&A[1][8], sb + OFF_XR + wgi * 3072 + t128 * 16);                                  \
        asm volatile("ld.shared.v2.u32 {%0,%1}, [%2];" : "=r"(t0), "=r"(t1) : "r"(sb + OFF_XR + wgi * 3072 + 2048 + t128 * 8) : "memory"); \
        _Pragma("unroll") for (int i = 0; i < 12; i++) A[0][i] = (i & 3) ? W[i] : W[i] & ~1u;  \
        A[1][0] &= ~1u; A[1][4] &= ~1u; A[1][8] &= ~1u;                                        \
        A[0][12] = (hr ? t0 : W[12]) & ~1u; A[0][13] = hr ? t1 : W[13];                        \
        A[1][12] = (hr ? W[12] : t0) & ~1u; A[1][13] = hr ? W[13] : t1;                        \
        asm volatile("" : RW4(A[0], 0), RW4(A[0], 4), RW4(A[0], 8), RW2(A[0], 12), RW4(A[1], 0), RW4(A[1], 4), RW4(A[1], 8), RW2(A[1], 12)); \
        swp = hr * 448;                                                                        \
    }
#define SWB(b, t, db, sh) ((b) == 0 && (t) < 6 ? ((t) < 3 ? db##p : db##m) : db)
#define DECL_DB(b, MK, lbo, sh) const uint64_t db = MK(0, lbo, R_ADJ), dbp = (b) == 0 ? MK(0, lbo, R_ADJ + (swp >> (sh))) : db, dbm = (b) == 0 ? MK(0, lbo, R_ADJ - (swp >> (sh))) : db;
#define EARLY 1
#define EARLYK 1
#define PPB 2
#define PP_WAIT() if (wgi == 1) { bar_sync(ppid, 256); ppid ^= 14; }
#define PP_GO() if (wgi == 0) { bar_arrive(ppid, 256); ppid ^= 14; }
#define GAT_ISSUE(base)                                                                        \
    {                                                                                          \
        const char* gs = reinterpret_cast<const char*>(g_ex + 3 * PLANE + (base) + (tile * 16 + wgi * 8 + 2 * kblk(pr, GB)) * 512 + w * 128); \
        const uint32_t gd = hbuf + w * 3584, gb = BAR(B_GAT + wu);                     \
        asm volatile("{ .reg .pred e; elect.sync _|e, 0xffffffff;\n"                           \
                     "@e mbarrier.arrive.expect_tx.shared::cta.b64 _, [%2], 3584;\n"           \
                     "@e cp.async.bulk.shared::cluster.global.mbarrier::complete_tx::bytes [%0], [%1], 1792, [%2];\n" \
                     "@e cp.async.bulk.shared::cluster.global.mbarrier::complete_tx::bytes [%0+1792], [%1+8192], 1792, [%2]; }" \
                     ::"r"(gd), "l"(gs), "r"(gb) : "memory");                                  \
        __syncwarp();                                                                          \
    }
#define GAT_FETCH()                                                                            \
    {                                                                                          \
        mbar_wait(BAR(B_GAT + wu), gatph);                                             \
        gatph ^= 1;                                                                            \
        const uint32_t ga = hbuf + w * 3584 + lane * 16;                                       \
        _Pragma("unroll") for (int s2 = 0; s2 < 2; s2++) {                                     \
            lds4(&A[2 * GB + s2][0], ga + s2 * 1792); lds4(&A[2 * GB + s2][4], ga + s2 * 1792 + 512); lds4(&A[2 * GB + s2][8], ga + s2 * 1792 + 1024); \
            asm volatile("ld.shared.v2.u32 {%0,%1}, [%2];" : "=r"(A[2 * GB + s2][12]), "=r"(A[2 * GB + s2][13]) : "r"(ga - lane * 8 + s2 * 1792 + 1536) : "memory"); \
        }                                                                                      \
    }
#define PT 3
#define PREP(b, t, remote)                                                                     \
    if constexpr ((b) < 3 && (t) == PT) {                                                      \
        wg_commit();                                                                           \
        STAMP(80 + 8 * (step & 1) + 2 * (b));                                                  \
        if constexpr (GB == 1 && (b) == 0) { if (remote) GAT_FETCH() }                         \
        if (remote) blk_check<((b) + 1) & 3>(A, BLK(xsrc, (b) + 1), lane, xtag);               \
        STAMP(81 + 8 * (step & 1) + 2 * (b));                                                  \
        if constexpr ((b) == 0) { if (remote) blk_load<3>(A, BLK(xsrc, 3), lane); }            \
        normalize<((b) + 1) & 3>(A, k0, k1);                                                   \
        asm volatile("" : RW4(A[(2 * (b) + 2) & 7], 0), RW4(A[(2 * (b) + 2) & 7], 4), RW4(A[(2 * (b) + 2) & 7], 8), RW2(A[(2 * (b) + 2) & 7], 12), \
                          RW4(A[(2 * (b) + 3) & 7], 0), RW4(A[(2 * (b) + 3) & 7], 4), RW4(A[(2 * (b) + 3) & 7], 8), RW2(A[(2 * (b) + 3) & 7], 12)); \
        wg_fence();                                                                            \
    }                                                                                          \
    if constexpr ((b) == 3 && ((t) == 0 || (t) == 6)) { STAMP(86 + 8 * (step & 1) + (t) / 6); }
#define BLK(base, b) ((base) + kblk(pr, b) * 1024)

#pragma unroll 1
        for (int step = 0; step < 4; step++) {
            const uint32_t tag = (step >> 1) ^ 1;
            const int so = (step >> 1) * 24 + (step & 1) * 12;
            (void)so;
            uint32_t A[8][14];
            uint4* const xsrc = xp0 + ((step & 1) ? PL(2) : PL(0));
            const uint32_t xtag = (step & 1) ? tag : ((seq >> 3) & 1) ^ 1;
            uint32_t xbits;
            {
                float st[4];
                slice_stats(X, st);
                stag ^= 1;
                xbits = x_bits(X);
                tag_slice(X, xtag);
                if (step) send_slice<0>(xsrc + sl * 512, lane, X);
                if (c == 0) st_pkt<0>(stp + sl * 512, __float_as_uint(st[0]), __float_as_uint(st[1]), __float_as_uint(st[2]), settag(__float_as_uint(st[3]), stag));
            }
            STAMP(2 + so);
            uint32_t sv[8];
            if (step == 0) {
                const int rr = lane & 7, hi = lane >> 4;
                const uint32_t rowa = (w < 2 ? hbuf : sb + wgi * STAGE) + ((w & 1) * 16 + (lane & 15)) * 128;
                uint32_t xr[8];
#pragma unroll
                for (int j = 0; j < 8; j++) xr[j] = rowa + ((((j + hi) ^ rr) & 7) << 4) + (j == 7 ? hi * 4096 : 0);
#define X0_BLOCK(b)                                                                            \
    FOR7(constexpr int G = 14 * (b) + (t < 3 ? 2 * t : (t < 6 ? 2 * t + 1 : 6));               \
         uint32_t q0, q1, q2, q3;                                                              \
         const uint32_t ad = t < 6 ? xr[G & 7] : rowa + ((G + 7 * hi) >> 3) * 4096 + ((((G + 7 * hi) ^ rr) & 7) << 4); \
         asm volatile("ldmatrix.sync.aligned.m8n8.x4.shared.b16 {%0,%1,%2,%3}, [%4+%5];" : "=r"(q0), "=r"(q1), "=r"(q2), "=r"(q3) \
                      : "r"(ad), "n"(t < 6 ? (G >> 3) * 4096 : 0) : "memory");                 \
         if (t < 3) { A[2 * (b)][4 * t] = q0; A[2 * (b)][4 * t + 1] = q1; A[2 * (b)][4 * t + 2] = q2; A[2 * (b)][4 * t + 3] = q3; } \
         else if (t < 6) { A[2 * (b) + 1][(4 * t - 12) & 15] = q0; A[2 * (b) + 1][((4 * t - 12) & 15) + 1] = q1; A[2 * (b) + 1][((4 * t - 12) & 15) + 2] = q2; A[2 * (b) + 1][((4 * t - 12) & 15) + 3] = q3; } \
         else { A[2 * (b)][12] = q0; A[2 * (b)][13] = q1; A[2 * (b) + 1][12] = q2; A[2 * (b) + 1][13] = q3; });
                X0_BLOCK(0) X0_BLOCK(1) X0_BLOCK(2) X0_BLOCK(3)
                mbar_wait(BAR(wgi ^ 1), 0);
                R_NEXT();
                R_NEXT();
                stat_load(sv, stp + c * 1024);
                stat_check(sv, stp + c * 1024, stag);
                STAMP(52 + step);
            } else {
                PUSH_SLICE(X)
                stat_load(sv, stp + c * 1024);
                kill<14>(A[2]); kill<14>(A[3]); kill<14>(A[4]); kill<14>(A[5]); kill<14>(A[6]); kill<14>(A[7]);
                PULL_SLICE(X)
                stat_check(sv, stp + c * 1024, stag);
                STAMP(52 + step);
                if (GB == 1) GAT_ISSUE((step & 1) ? PL(2) : PL(0))
                else blk_load<1>(A, BLK(xsrc, 1), lane);
            }
            LnCoef k0, k1;
            {
                k0 = ln_coef(__uint_as_float(sv[0]) + __uint_as_float(sv[4]), __uint_as_float(sv[1]) + __uint_as_float(sv[5]));
                k1 = ln_coef(__uint_as_float(sv[2]) + __uint_as_float(sv[6]), __uint_as_float(sv[3]) + __uint_as_float(sv[7]));
            }
            if (step) {
                if (GB == 2) GAT_ISSUE((step & 1) ? PL(2) : PL(0))
                else blk_load<2>(A, BLK(xsrc, 2), lane);
            }
            STAMP(3 + so);
            GSTAMP(76 + step);

            if ((step & 1) == 0) {
                float tq[28];
                {
                    float av[28];
#define KV_BLOCK(b)                                                                           \
    if (GB == 2 && (b) == 1 && step) GAT_FETCH()                                                         \
    if ((b) == 2) PUSH_ACK();                                                                 \
    if (QE && (b) == 1) R_RELEASE(2);                                                         \
    if (QE && (b) == 2) { wg_wait<2>(); R_RELEASE(2); }                                       \
    R_WAIT();                                                                                 \
    if ((b) == PPK) { PP_WAIT() }                                                             \
    { DECL_DB(b, BASE128, 16, 0)                                                              \
    wg_fence();                                                                               \
    FOR7(mma_rs56<1, D128(0, t)>(tq, AQ(A, b, t), (b) + t > 0, SWB(b, t, db, 0));             \
         mma_rs56<1, D128(HALF, t)>(av, AQ(A, b, t), (b) + t > 0, SWB(b, t, db, 0));          \
         PREP(b, t, step)); }                                                                 \
    wg_commit();                                                                              \
    if ((b) == 3 && PPK < 4) { PP_GO() }                                                      \
    R_NEXT();
                    if (EARLYK == 0 || step == 0) R_RELEASE(2);
                    normalize<0>(A, k0, k1);
                    KV_BLOCK(0) KV_BLOCK(1) KV_BLOCK(2) KV_BLOCK(3)
                    wg_wait<0>();
                    if (lane < (QE ? 3 : NST)) mbar_arrive(BAR(B_EMPTY + (slot + NST - 1 - lane) % NST));
                    STAMP(4 + so);
                    WSUM(80 + 7 * (step >> 1));
                    const int m = lane >> 3, rr = lane & 7;
                    const uint32_t rowa = hbuf + 16384 + (w * 16 + rr + 8 * (m & 1)) * 128;
                    const uint32_t one = c == 0 ? 0x00003f80u : 0u;
                    if (step == 0) { bar_sync(wgi ? 9 : 1, 224); }
#pragma unroll
                    for (int j = 0; j < 4; j++) {
                        const uint32_t a = rowa + (((2 * j + (m >> 1)) ^ rr) << 4);
                        if (j < 3) stsm4(a, pack2(av[8 * j], av[8 * j + 1]), pack2(av[8 * j + 2], av[8 * j + 3]), pack2(av[8 * j + 4], av[8 * j + 5]), pack2(av[8 * j + 6], av[8 * j + 7]));
                        else stsm4(a, pack2(av[24], av[25]), pack2(av[26], av[27]), one, one);
                    }
                }
                uint32_t PH[28];
                int it = 1;
#pragma unroll 1
                do {
                    float pp[28];
                    phi_gemm(tq, pp);
                    dual_softmax(pp, PH);
                    if (((trips >> (it + 1)) & 1) == 0) continue;
                    {
                        const int m = lane >> 3, rr = lane & 7;
                        const uint32_t rowa = hbuf + (w * 16 + rr + 8 * (m & 1)) * 128;
#pragma unroll
                        for (int j = 0; j < 7; j++) {
                            const int cg = 2 * j + (m >> 1), hi = cg >= 7;
                            stsm4(rowa + hi * 8192 + (((cg - 7 * hi) ^ rr) << 4), PH[4 * j], PH[4 * j + 1], PH[4 * j + 2], PH[4 * j + 3]);
                        }
                    }
                    fence_async();
                    STAMP(5 + so);
#define Q_STAGE(b0)                                                                           \
    R_WAIT();                                                                                 \
    { DECL_DB(b0, BASE128, 16, 0)                                                             \
    wg_fence();                                                                               \
    FOR7(mma_rs56<1, D128(0, t)>(tq, AQ(A, b0, t), (b0) + t > 0, SWB(b0, t, db, 0)));         \
    FOR7(mma_rs56<1, D128(HALF, t)>(tq, AQ(A, (b0) + 1, t), 1, db)); }                        \
    wg_commit();                                                                              \
    R_NEXT();
                    if (QE && wgi == 0) { kill<28>(tq); Q_STAGE(0) Q_STAGE(2) wg_wait<1>(); R_RELEASE(2); wg_wait<0>(); R_RELEASE(1); }
                    bar_sync(2, 256);
                    float kv[28];
                    const uint64_t da = BASE128(OFF_H + 16384, 16, 0), dbk = BASE128(OFF_H, 16, wgi * 512);
                    wg_fence();
                    FOR8(constexpr uint64_t o = ((t >> 2) * STAGE + (t & 3) * 2048) >> 4; mma_ss56_tt<o, o>(kv, t > 0, da, dbk));
                    wg_commit();
                    wg_wait<0>();
#pragma unroll
                    for (int hf = 0; hf < 2; hf++) {
                        const int d = 16 * w + g + 8 * hf;
                        if ((d < 56 && (d >= 28) == (c >= 2)) || d == 56) {
                            const int item = d < 56 ? 2 * d + (c & 1) : 112 + c;
                            uint4* dst = g_kv1 + ((sl * 16 + (item >> 3)) * 16 + tile) * 32 + wgi * 16 + (item & 7);
#define KVW(i) pack2(kv[4 * (i) + 2 * hf], kv[4 * (i) + 2 * hf + 1])
                            st_pkt<0>(dst, settag(KVW(0), tag), KVW(1), KVW(2), KVW(3));
                            st_pkt<8>(dst, settag(KVW(4), tag), KVW(5), KVW(6), 0u);
                        }
                    }
                    __syncwarp();
                    bar_arrive(7, 384);
                    STAMP(6 + so);
                    if (!QE || wgi == 1) { kill<28>(tq); Q_STAGE(0) Q_STAGE(2) wg_wait<1>(); R_RELEASE(2); wg_wait<0>(); R_RELEASE(1); }
                    STAMP(7 + so);
                    kill<28>(PH);
                } while (((trips >> (++it)) & 1));
                STAMP(8 + so);
                if (step) {
                    slice_load<PL(0)>(X, xp0 + sl * 512, lane);
                } else {
                    const uint32_t* xp = reinterpret_cast<const uint32_t*>(x_in + (size_t)(tile * 128 + wu * 16 + g) * 448 + 56 * sl + 2 * c);
#pragma unroll
                    for (int i = 0; i < 7; i++) { X[2 * i] = __ldg(xp + 4 * i); X[2 * i + 1] = __ldg(xp + 4 * i + 8 * 224); }
                }
                bar_sync(3, 384);
                STAMP(9 + so);
                const uint4* const osrc = xp0 + PL(1);
                {
                    float nm[32];
                    const uint64_t db = BASE128(OFF_KVB, 16, 0);
                    wg_fence();
                    FOR7(mma_rs64<0, ((t >> 2) * 8192 + (t & 3) * 32) / 16>(nm, PH[4 * t], PH[4 * t + 1], PH[4 * t + 2], PH[4 * t + 3], t > 0, db));
                    wg_commit();
                    wg_wait<0>();
                    const float i00 = rcp(nm[28] + 1e-6f), i01 = rcp(nm[29] + 1e-6f), i10 = rcp(nm[30] + 1e-6f), i11 = rcp(nm[31] + 1e-6f);
                    const float m0 = c >= 2 ? i01 : i00, m1 = c >= 2 ? i11 : i10;
                    uint32_t O[14];
#pragma unroll
                    for (int i = 0; i < 7; i++) {
                        const float f0 = i < 3 ? i00 : (i > 3 ? i01 : m0), f1 = i < 3 ? i10 : (i > 3 ? i11 : m1);
                        O[2 * i] = pack2(nm[4 * i] * f0, nm[4 * i + 1] * f0);
                        O[2 * i + 1] = pack2(nm[4 * i + 2] * f1, nm[4 * i + 3] * f1);
                    }
                    if (OST) { PP_WAIT() }
                    tag_slice(O, tag);
                    send_slice<PL(1)>(xp0 + sl * 512, lane, O);
                    seq++;
                    if (lane == 0) st_word(cx(sl), seq);
                    STAMP(10 + so);
                    PUSH_SLICE(O)
                    if (OST == 1) { PP_GO() }
                    const uint32_t cv = ld_word(cx(lane & 7));
                    PULL_SLICE(O)
                    check_cnt(cv, cx(lane & 7), seq);
                    if (OST == 2) { PP_GO() }
                    STAMP(56 + (step >> 1));
                    GAT_ISSUE(PL(1))
                    blk_load<3 - GB>(A, BLK(osrc, 3 - GB), lane);
                }
                float ao[28];
#define WO_BLOCK(b)                                                                           \
    if ((b) > 0) blk_check<b>(A, BLK(osrc, b), lane, tag);                                    \
    if (((b) & 1) == 0) R_WAIT();                                                             \
    { DECL_DB(b, BASE128, 16, 0)                                                              \
    wg_fence();                                                                               \
    FOR7(mma_rs56<1, D128(((b) & 1) * HALF, t)>(ao, AQ(A, b, t), (b) + t > 0, SWB(b, t, db, 0))); } \
    wg_commit();                                                                              \
    if ((b) & 1) R_NEXT();
                WO_BLOCK(0)
                STAMP(11 + so);
                blk_load<3>(A, BLK(osrc, 3), lane);
                if (GB == 1) GAT_FETCH()
                WO_BLOCK(1)
                if (GB == 2) GAT_FETCH()
                WO_BLOCK(2)
                PUSH_ACK();
                WO_BLOCK(3)
                wg_wait<0>();
                if (EARLY >= 1) R_RELEASE(2);
                if (EARLY >= 2) R_RELEASE(1);
                STAMP(12 + so);
                WSUM(86 + 7 * (step >> 1));
                x_fix(X, xbits);
#pragma unroll
                for (int i = 0; i < 14; i++) X[i] = pack2(bf_lo(X[i]) + ao[2 * i], bf_hi(X[i]) + ao[2 * i + 1]);
            } else {
                uint32_t H[56];
                float ag[64];
#define F1_EPI(dst, ng, ag)                                                                    \
    _Pragma("unroll") for (int i = 0; i < 2 * (ng); i++)                                       \
        (dst)[i] = pack2(geglu(ag[2 * i], ag[4 * (ng) + 2 * i]), geglu(ag[2 * i + 1], ag[4 * (ng) + 2 * i + 1]));
#define H_PUSH(h0, off) st_async4(rem_h + (off), H[h0], H[(h0) + 1], H[(h0) + 2], H[(h0) + 3], mapa(BAR(B_RECV2 + wgi), hr ^ 1));
#define F1_BLOCK(b, first)                                                                     \
    if ((first) && (b) < 2 && (b) >= EARLY) R_RELEASE(2);                                      \
    if (GB == 2 && (first) && (b) == 1) GAT_FETCH()                                                       \
    if ((first) && (b) == 2) PUSH_ACK();                                                       \
    R_WAIT();                                                                                  \
    if ((b) == PPB) { PP_WAIT() }                                                              \
    { DECL_DB(b, BASE128, HALF, 0)                                                             \
    wg_fence();                                                                                \
    FOR7(mma_rs128<1, D128(0, t)>(ag, AQ(A, b, t), (b) + t > 0, SWB(b, t, db, 0));             \
         if constexpr (first) { PREP(b, t, true) }); }                                         \
    wg_commit();                                                                               \
    if ((b) == 3) { PP_GO() }                                                                  \
    if ((b) > 0) { wg_wait<1>(); R_RELEASE(1); }       \
    R_NEXT();
                normalize<0>(A, k0, k1);
                F1_BLOCK(0, true) F1_BLOCK(1, true) F1_BLOCK(2, true) F1_BLOCK(3, true)
                if (t128 == 0) { mbar_expect_tx(BAR(B_RECV + wgi), 16384); mbar_expect_tx(BAR(B_RECV2 + wgi), 12288); }
                PUSH_BEGIN();
                wg_wait<0>();
                R_RELEASE(1);
                if (step == 1) R_NEXT();
                int p = 0;
#pragma unroll 1
                do {
                    STAMP(68 + p);
                    F1_EPI(H + 32, 8, ag)
                    STAMP(4 + p + so);
                    WSUM(81 + p + 7 * (step >> 1));
                    if (((trips >> (p + 1)) & 1) == 0) continue;
                    {
                        const uint32_t pk = (p ? hbuf + 16384 : sb + OFF_KVB + wgi * 8192) + w * 2048;
#pragma unroll
                        for (int k = 0; k < 4; k++) sts4(pk + k * 512 + lane * 16, H[32 + 4 * k], H[33 + 4 * k], H[34 + 4 * k], H[35 + 4 * k]);
                        fence_async();
                        __syncwarp();
                        asm volatile(ELECT "cp.async.bulk.shared::cluster.shared::cta.mbarrier::complete_tx::bytes [%0], [%1], 2048, [%2]; }"
                                     ::"r"(mapa(hbuf + p * 8192 + w * 2048, hr ^ 1)), "r"(pk), "r"(mapa(BAR(B_RECV + wgi), hr ^ 1)) : "memory");
                    }
                    kill<64>(ag);
                    F1_BLOCK(0, false) F1_BLOCK(1, false) F1_BLOCK(2, false) F1_BLOCK(3, false)
                    wg_wait<0>();
                    R_RELEASE(1);
                    kill<16>(H + 32);
                } while (((trips >> (++p)) & 1));
#pragma unroll
                for (int k = 0; k < 4; k++) lds4(H + 16 + 4 * k, hbuf + 16384 + w * 2048 + k * 512 + lane * 16);
                __syncwarp();
                if (lane == 0) asm volatile("mbarrier.arrive.shared::cluster.b64 _, [%0];" ::"r"(mapa(BAR(B_ACK2 + wgi), hr ^ 1)) : "memory");
                const uint32_t rem_h = mapa(hbuf + w * 2048 + lane * 16, hr ^ 1);
#define F1_LAST(b0)                                                                            \
    R_WAIT();                                                                                  \
    if (b0) { PP_WAIT() }                                                                      \
    { DECL_DB(b0, BASE64, HALF, 1)                                                             \
    wg_fence();                                                                                \
    FOR7(mma_rs64<1, D64(0, t)>(al, AQ(A, b0, t), (b0) + t > 0, SWB(b0, t, db, 1)));           \
    FOR7(mma_rs64<1, D64(7168, t)>(al, AQ(A, (b0) + 1, t), 1, db)); }                          \
    wg_commit();                                                                               \
    if (b0) { PP_GO() }                                                                        \
    R_NEXT();
                float al[32];
                F1_LAST(0)
                mbar_wait(BAR(B_RECV + wgi), rcvph);
                rcvph ^= 1;
                mbar_wait(BAR(B_ACK2 + wgi), step >> 1);
                H_PUSH(32, 16384) H_PUSH(36, 16896)
                F1_LAST(2)
                H_PUSH(40, 17408) H_PUSH(44, 17920)
                wg_wait<1>();
                R_RELEASE(2);
                wg_wait<0>();
                R_RELEASE(1);
                uint32_t HP[56];
#pragma unroll
                for (int k = 0; k < 4; k++) lds4(H + 4 * k, sb + OFF_KVB + wgi * 8192 + w * 2048 + k * 512 + lane * 16);
#pragma unroll
                for (int t = 0; t < 8; t++) lds4(HP + 4 * t, hbuf + (t >> 2) * 8192 + w * 2048 + (t & 3) * 512 + lane * 16);
                F1_EPI(H + 48, 4, al)
                H_PUSH(48, 24576 - w * 1024) H_PUSH(52, 25088 - w * 1024)
                STAMP(7 + so);
                WSUM(84 + 7 * (step >> 1));
                float acc[28];
                const uint32_t roA = hr ? 256u : 0u, roB = hr ? (uint32_t)-1536 : 0u;
                const uint32_t rpA = hr ? 0u : 256u, rpB = hr ? 0u : (uint32_t)-1536;
                float res[28];
                uint32_t v0[14], v1[14], P[14];
                const uint4* ps = xp0 + sl * 512;
#define F2_OWN_A()                                                                             \
    R_WAIT();                                                                                  \
    d0 = BASE128(0, 16, R_ADJ + roA); d1 = BASE128(0, 16, R_ADJ + roB);                        \
    wg_fence();                                                                                \
    FOR14(if constexpr (t < OT) mma_rs56<1, t * 128>(acc, H[4 * t], H[4 * t + 1], H[4 * t + 2], H[4 * t + 3], t > 0, d0)); \
    wg_commit();
#define F2_OWN_B()                                                                             \
    wg_fence();                                                                                \
    FOR14(if constexpr (t >= OT) mma_rs56<1, t * 128>(acc, H[4 * t], H[4 * t + 1], H[4 * t + 2], H[4 * t + 3], 1, t < 12 ? d0 : d1)); \
    wg_commit();                                                                               \
    R_NEXT();
#define F2_PEER()                                                                              \
    R_WAIT();                                                                                  \
    if (F2PP) { PP_WAIT() }                                                                    \
    d0 = BASE128(0, 16, R_ADJ + rpA); d1 = BASE128(0, 16, R_ADJ + rpB);                        \
    wg_fence();                                                                                \
    FOR14(mma_rs56<1, t * 128>(acc, HP[4 * t], HP[4 * t + 1], HP[4 * t + 2], HP[4 * t + 3], 1, t < 12 ? d0 : d1)); \
    wg_commit();                                                                               \
    if (F2PP) { PP_GO() }                                                                      \
    R_NEXT();
#define F2_TURN(u)                                                                             \
    wg_wait<1>();                                                                              \
    R_RELEASE(2);                                                                              \
    wg_wait<0>();                                                                              \
    R_RELEASE(1);                                                                              \
    _Pragma("unroll") for (int i = 0; i < 14; i++) P[i] = pack2(acc[2 * i], acc[2 * i + 1]);   \
    tag_slice(P, tag);                                                                         \
    asm volatile("" : RW4(P, 0), RW4(P, 4), RW4(P, 8), RW2(P, 12));                            \
    kill<28>(acc);                                                                             \
    F2_OWN_A()                                                                                 \
    if ((u) == 2) { slice_load<PL(3)>(v0, ps, lane); slice_load<PL(4)>(v1, ps, lane); } \
    send_slice<PL(3 + (u))>(xp0 + (2 * ((pr + (u) + 1) & 3) + hr) * 512, lane, P);             \
    seq++;                                                                                     \
    if (lane == 0) st_word(cx(sl), seq);                                                       \
    __syncwarp();                                                                              \
    STAMP(8 + (u) + so);                                                                       \
    F2_OWN_B()
                uint64_t d0, d1;
                F2_OWN_A()
                F2_OWN_B()
                R_WAIT();
                d0 = BASE128(0, 16, R_ADJ + rpA); d1 = BASE128(0, 16, R_ADJ + rpB);
                wg_fence();
                FOR8(mma_rs56<1, t * 128>(acc, HP[4 * t], HP[4 * t + 1], HP[4 * t + 2], HP[4 * t + 3], 1, d0));
                wg_commit();
                mbar_wait(BAR(B_RECV2 + wgi), step >> 1);
#pragma unroll
                for (int k = 0; k < 4; k++) lds4(HP + 32 + 4 * k, hbuf + 16384 + w * 2048 + k * 512 + lane * 16);
                lds4(HP + 48, hbuf + 24576 + w * 1024 + lane * 16);
                lds4(HP + 52, hbuf + 25088 + w * 1024 + lane * 16);
                if (step == 1) PUSH_ACK();
                wg_fence();
                FOR14(if constexpr (t >= 8) mma_rs56<1, t * 128>(acc, HP[4 * t], HP[4 * t + 1], HP[4 * t + 2], HP[4 * t + 3], 1, t < 12 ? d0 : d1));
                wg_commit();
                R_NEXT();
                F2_TURN(0)
                F2_PEER()
                F2_TURN(1)
                F2_PEER()
                F2_TURN(2)
                STAMP(64 + 8 * (step >> 1));
                slice_check<PL(3)>(v0, ps, lane, tag);
                slice_check<PL(4)>(v1, ps, lane, tag);
#pragma unroll
                for (int i = 0; i < 14; i++) { res[2 * i] = bf_lo(v0[i]) + bf_lo(v1[i]); res[2 * i + 1] = bf_hi(v0[i]) + bf_hi(v1[i]); }
                slice_load<PL(2)>(X, ps, lane);
                STAMP(65 + 8 * (step >> 1));
                const uint32_t cv = ld_word(cx(2 * ((pr + 1) & 3) + hr));
                F2_PEER()
                STAMP(66 + 8 * (step >> 1));
                check_cnt(cv, cx(2 * ((pr + 1) & 3) + hr), seq);
                STAMP(67 + 8 * (step >> 1));
                slice_load<PL(5)>(v0, ps, lane);
                x_fix(X, xbits);
                slice_check<PL(5)>(v0, ps, lane, tag);
#pragma unroll
                for (int i = 0; i < 14; i++) { res[2 * i] += bf_lo(v0[i]); res[2 * i + 1] += bf_hi(v0[i]); }
                STAMP(11 + so);
                wg_wait<0>();
                if (EARLYK >= 1) R_RELEASE(2);
                STAMP(12 + so);
                WSUM(85 + 7 * (step >> 1));
#pragma unroll
                for (int i = 0; i < 14; i++) X[i] = pack2(fmaf(res[2 * i] + acc[2 * i], 0.5f, bf_lo(X[i])), fmaf(res[2 * i + 1] + acc[2 * i + 1], 0.5f, bf_hi(X[i])));
            }
        }
        {
            const int m = lane >> 3, rr = lane & 7;
            const uint32_t ob = hbuf + w * 2048, rowa = ob + (rr + 8 * (m & 1)) * 112 + (m >> 1) * 16;
#pragma unroll
            for (int j = 0; j < 3; j++) stsm4(rowa + 32 * j, X[4 * j], X[4 * j + 1], X[4 * j + 2], X[4 * j + 3]);
            asm volatile("stmatrix.sync.aligned.m8n8.x2.shared.b16 [%0], {%1,%2};" ::"r"(ob + (rr + 8 * (m & 1)) * 112 + 96), "r"(X[12]), "r"(X[13]) : "memory");
            fence_async();
            __syncwarp();
            if (lane == 0) {
                asm volatile("cp.async.bulk.tensor.2d.global.shared::cta.bulk_group [%0, {%2, %3}], [%1];" ::"l"(&maps.out), "r"(ob), "r"(56 * sl), "r"(tile * 128 + (tid >> 5) * 16) : "memory");
                asm volatile("cp.async.bulk.commit_group;" ::: "memory");
                asm volatile("cp.async.bulk.wait_group.read 0;" ::: "memory");
            }
        }
        STAMP(50);
        GSTAMP(61);
        PDUMP();
    }
}

typedef CUresult (*EncodeFn)(CUtensorMap*, CUtensorMapDataType, cuuint32_t, void*, const cuuint64_t*, const cuuint64_t*, const cuuint32_t*,
                             const cuuint32_t*, CUtensorMapInterleave, CUtensorMapSwizzle, CUtensorMapL2promotion, CUtensorMapFloatOOBfill);

static void make_map(EncodeFn enc, CUtensorMap* m, const void* p, uint64_t cols, uint64_t rows, uint32_t bc, uint32_t br, CUtensorMapSwizzle sw) {
    cuuint64_t gd[2] = {cols, rows};
    cuuint64_t gs[1] = {cols * 2};
    cuuint32_t bd[2] = {bc, br};
    cuuint32_t es[2] = {1, 1};
    enc(m, CU_TENSOR_MAP_DATA_TYPE_BFLOAT16, 2, const_cast<void*>(p), gd, gs, bd, es, CU_TENSOR_MAP_INTERLEAVE_NONE, sw,
        CU_TENSOR_MAP_L2_PROMOTION_L2_128B, CU_TENSOR_MAP_FLOAT_OOB_FILL_NONE);
}

extern "C" void kernel_launch(void* const* d_in, const int* in_sizes, int n_in, void* d_out, int out_size) {
    (void)in_sizes; (void)n_in; (void)out_size;
    static EncodeFn enc = nullptr;
    static Scratch* scratch = nullptr;
    if (!enc) {
        void* fn = nullptr;
        cudaDriverEntryPointQueryResult qr;
        cudaGetDriverEntryPoint("cuTensorMapEncodeTiled", &fn, cudaEnableDefault, &qr);
        enc = (EncodeFn)fn;
        cudaGetSymbolAddress((void**)&scratch, g_scratch);
        cudaFuncSetAttribute(fused_kernel, cudaFuncAttributeMaxDynamicSharedMemorySize, SMEM_BYTES);
    }
    Maps maps;
    {
        cuuint64_t gd[3] = {64, 2048, 7};
        cuuint64_t gs[2] = {896, 128};
        cuuint32_t bd[3] = {64, 32, 7};
        cuuint32_t es[3] = {1, 1, 1};
        enc(&maps.x, CU_TENSOR_MAP_DATA_TYPE_BFLOAT16, 3, d_in[0], gd, gs, bd, es, CU_TENSOR_MAP_INTERLEAVE_NONE, CU_TENSOR_MAP_SWIZZLE_128B,
            CU_TENSOR_MAP_L2_PROMOTION_L2_128B, CU_TENSOR_MAP_FLOAT_OOB_FILL_NONE);
    }
    make_map(enc, &maps.out, d_out, 448, 2048, 56, 16, CU_TENSOR_MAP_SWIZZLE_NONE);
    make_map(enc, &maps.qkv, d_in[1], 1344, 448, 64, 112, CU_TENSOR_MAP_SWIZZLE_128B);
    make_map(enc, &maps.wo, d_in[3], 448, 448, 64, 112, CU_TENSOR_MAP_SWIZZLE_128B);
    make_map(enc, &maps.wg, d_in[5], 1792, 448, 64, 112, CU_TENSOR_MAP_SWIZZLE_128B);
    make_map(enc, &maps.wu, d_in[6], 1792, 448, 64, 112, CU_TENSOR_MAP_SWIZZLE_128B);
    make_map(enc, &maps.wg32, d_in[5], 1792, 448, 32, 112, CU_TENSOR_MAP_SWIZZLE_64B);
    make_map(enc, &maps.wu32, d_in[6], 1792, 448, 32, 112, CU_TENSOR_MAP_SWIZZLE_64B);
    make_map(enc, &maps.wd, d_in[7], 448, 1792, 64, 112, CU_TENSOR_MAP_SWIZZLE_128B);
    fused_kernel<<<128, 384, SMEM_BYTES>>>(scratch, (const __nv_bfloat16*)d_in[0], (const __nv_bfloat16*)d_in[2], 7, (const __nv_bfloat16*)d_in[5],
                                           (const __nv_bfloat16*)d_in[6], (const __nv_bfloat16*)d_in[7], maps);
}
```

```cpp
#include <cuda_runtime.h>
#include <cuda.h>
#include <cuda_bf16.h>
#include <stdint.h>
#include <type_traits>

#define LSTAT 1
#define ACAN 1
#define SPLIT0 1
#define OT 2
#define F2PP 0
#define PPK 2
#define QE 1
#define OST 1
#define GB 1
#define B3T 6
#define PP

namespace {

constexpr uint32_t STAGE = 28672, HALF = 14336;
constexpr int NST = 5;
constexpr uint32_t OFF_H = NST * STAGE;
constexpr uint32_t OFF_KVB = OFF_H + 2 * STAGE;
constexpr uint32_t OFF_WPHI = OFF_KVB + 16384;
constexpr uint32_t OFF_XR = OFF_WPHI + 7168;
constexpr uint32_t OFF_BAR = OFF_XR + 6144;
constexpr uint32_t SMEM_BYTES = OFF_BAR + 256 + 1536;
constexpr int B_EMPTY = NST, B_RECV = 2 * NST, B_RECV2 = B_RECV + 2, B_PACK = B_RECV2 + 2, B_GAT = B_PACK + 1, B_ACK = B_GAT + 8, B_ACK2 = B_ACK + 2, B_COUNT = B_ACK2 + 2;

constexpr int PACK = 14;

struct Maps { CUtensorMap x, qkv, wo, wg, wu, wg32, wu32, wd, out; };

}

constexpr int PLANE = 16 * 2 * 8 * 512;
struct Scratch {
    uint4 ex[6 * PLANE];
    uint4 kv1[8 * 16 * 16 * 32];
    uint4 kv2[8 * 512];
    uint32_t c1[8 * 8 * 16 * 32];
    uint32_t cw[8 * 32];
    uint4 wp[8 * 32 * (HALF / 16)];
};
__device__ __align__(1024) Scratch g_scratch;
#define g_ex (sc->ex)
#define g_kv1 (sc->kv1)
#define g_kv2 (sc->kv2)
#define g_c1 (sc->c1)
#define g_cw (sc->cw)
#define g_wp (sc->wp)
#define STAMP(i)
#define GSTAMP(i)
#define PDUMP()
#define ASTAMP(i)

namespace {

__device__ __forceinline__ int fresh_tid() { int t; asm volatile("mov.u32 %0, %%tid.x;" : "=r"(t)); return t; }
__device__ __forceinline__ uint4* again(uint4* p) { asm volatile("" : "+l"(p)); return p; }
template <int N> __device__ __forceinline__ void kill(uint32_t* v) {
#pragma unroll
    for (int i = 0; i < N; i++) v[i] = 0;
}
template <int N> __device__ __forceinline__ void kill(float* v) {
#pragma unroll
    for (int i = 0; i < N; i++) v[i] = 0.f;
}
__device__ __forceinline__ uint32_t s2u(const void* p) { return (uint32_t)__cvta_generic_to_shared(p); }
__device__ __forceinline__ void mbar_init(uint32_t a, uint32_t c) { asm volatile("mbarrier.init.shared::cta.b64 [%0], %1;" ::"r"(a), "r"(c) : "memory"); }
__device__ __forceinline__ void mbar_expect_tx(uint32_t a, uint32_t b) { asm volatile("mbarrier.arrive.expect_tx.shared::cta.b64 _, [%0], %1;" ::"r"(a), "r"(b) : "memory"); }
__device__ __forceinline__ void mbar_arrive(uint32_t a) { asm volatile("mbarrier.arrive.shared::cta.b64 _, [%0];" ::"r"(a) : "memory"); }
#define GIVE_UP(id) "trap;\n"
#define SPIN_MAX "0x400000"
#define SPIN_TAIL(id) "add.u32 n, n, 1;\n setp.lt.u32 p, n, " SPIN_MAX ";\n @p bra.uni LP;\n" GIVE_UP(id) " DN:\n }"
__device__ __forceinline__ void mbar_wait(uint32_t a, uint32_t ph) {
    asm volatile("{ .reg .pred p; .reg .b32 n; mov.u32 n, 0;\n LP:\n"
                 "mbarrier.try_wait.parity.shared::cta.b64 p, [%0], %1;\n @p bra DN;\n"
                 "add.u32 n, n, 1;\n setp.lt.u32 p, n, " SPIN_MAX ";\n @p bra LP;\n"
                 GIVE_UP("")
                 " DN:\n }" ::"r"(a), "r"(ph) : "memory");
}
#define ELECT "{ .reg .pred e; elect.sync _|e, 0xffffffff; @e "
__device__ __forceinline__ void tma2d(uint32_t dst, const CUtensorMap* m, int c0, int c1, uint32_t bar) {
    asm volatile(ELECT "cp.async.bulk.tensor.2d.shared::cluster.global.mbarrier::complete_tx::bytes [%0], [%1, {%3, %4}], [%2]; }" ::"r"(dst), "l"(m), "r"(bar), "r"(c0), "r"(c1) : "memory");
}
__device__ __forceinline__ void tma3x(uint32_t dst, const CUtensorMap* m, int row, uint32_t bar) {
    asm volatile(ELECT "cp.async.bulk.tensor.3d.shared::cluster.global.mbarrier::complete_tx::bytes [%0], [%1, {0, %3, 0}], [%2]; }" ::"r"(dst), "l"(m), "r"(bar), "r"(row) : "memory");
}
template <int OFF>
__device__ __forceinline__ void ld_pkt(uint32_t* v, const uint4* p) {
    asm volatile("{ .reg .b128 t; ld.relaxed.gpu.global.b128 t, [%4+%5]; mov.b128 {%0,%1,%2,%3}, t; }" : "=r"(v[0]), "=r"(v[1]), "=r"(v[2]), "=r"(v[3]) : "l"(p), "n"(OFF * 16) : "memory");
}
template <int OFF>
__device__ __forceinline__ void st_pkt(uint4* p, uint32_t a, uint32_t b, uint32_t c, uint32_t d) {
    asm volatile("{ .reg .b128 t; mov.b128 t, {%1,%2,%3,%4}; st.relaxed.gpu.global.b128 [%0+%5], t; }" ::"l"(p), "r"(a), "r"(b), "r"(c), "r"(d), "n"(OFF * 16) : "memory");
}
__device__ __forceinline__ uint32_t pack2(float lo, float hi) {
    uint32_t r;
    asm("cvt.rn.bf16x2.f32 %0, %1, %2;" : "=r"(r) : "f"(hi), "f"(lo));
    return r;
}
__device__ __forceinline__ float bf_lo(uint32_t w) { return __uint_as_float(w << 16); }
__device__ __forceinline__ float bf_hi(uint32_t w) { return __uint_as_float(w & 0xffff0000u); }
__device__ __forceinline__ uint32_t settag(uint32_t w, uint32_t tag) { return (w & ~1u) | tag; }
__device__ __forceinline__ float ex2(float x) { float y; asm("ex2.approx.ftz.f32 %0, %1;" : "=f"(y) : "f"(x)); return y; }
__device__ __forceinline__ float rcp(float x) { float y; asm("rcp.approx.ftz.f32 %0, %1;" : "=f"(y) : "f"(x)); return y; }
__device__ __forceinline__ float tanh_hw(float x) { float y; asm("tanh.approx.f32 %0, %1;" : "=f"(y) : "f"(x)); return y; }
__device__ __forceinline__ void stsm4(uint32_t addr, uint32_t a, uint32_t b, uint32_t c, uint32_t d) {
    asm volatile("stmatrix.sync.aligned.m8n8.x4.shared.b16 [%0], {%1,%2,%3,%4};" ::"r"(addr), "r"(a), "r"(b), "r"(c), "r"(d) : "memory");
}
__device__ __forceinline__ void fence_async() { asm volatile("fence.proxy.async.shared::cta;" ::: "memory"); }
__device__ __forceinline__ void bar_sync(int id, int n) { asm volatile("bar.sync %0, %1;" ::"r"(id), "r"(n) : "memory"); }
__device__ __forceinline__ void bar_arrive(int id, int n) { asm volatile("bar.arrive %0, %1;" ::"r"(id), "r"(n) : "memory"); }
__device__ __forceinline__ void wg_fence() { asm volatile("wgmma.fence.sync.aligned;" ::: "memory"); }
__device__ __forceinline__ void wg_commit() { asm volatile("wgmma.commit_group.sync.aligned;" ::: "memory"); }
template <int N> __device__ __forceinline__ void wg_wait() { asm volatile("wgmma.wait_group.sync.aligned %0;" ::"n"(N) : "memory"); }

constexpr uint32_t SB0 = 1024;
__host__ __device__ constexpr uint32_t dlo(uint32_t off, uint32_t lbo) { return ((SB0 + off) >> 4) | ((lbo >> 4) << 16); }
__host__ __device__ constexpr uint32_t dhi(uint32_t sbo, uint32_t sw) { return (sbo >> 4) | (sw << 30); }
__device__ __forceinline__ uint64_t dbase(uint32_t lo, uint32_t hi) { uint64_t d; asm volatile("mov.b64 %0, {%1, %2};" : "=l"(d) : "r"(lo), "r"(hi)); return d; }
#define BASE128(off, lbo, adj) dbase(dlo(off, lbo) + (adj), dhi(1024, 1))
#define BASE64(off, lbo, adj) dbase(dlo(off, lbo) + (adj), dhi(512, 2))

#define ACC4(d, o) "+f"(d[o]), "+f"(d[o + 1]), "+f"(d[o + 2]), "+f"(d[o + 3])
#define ACC28(d) ACC4(d, 0), ACC4(d, 4), ACC4(d, 8), ACC4(d, 12), ACC4(d, 16), ACC4(d, 20), ACC4(d, 24)
#define ACC32(d, o) ACC4(d, o), ACC4(d, o + 4), ACC4(d, o + 8), ACC4(d, o + 12), ACC4(d, o + 16), ACC4(d, o + 20), ACC4(d, o + 24), ACC4(d, o + 28)

template <int TB, uint64_t D>
__device__ __forceinline__ void mma_rs56(float* d, uint32_t a0, uint32_t a1, uint32_t a2, uint32_t a3, int sd, uint64_t base) {
    asm volatile("{ .reg .pred p; .reg .b64 db; setp.ne.b32 p, %32, 0; add.u64 db, %33, %34;\n"
                 "wgmma.mma_async.sync.aligned.m64n56k16.f32.bf16.bf16 "
                 "{%0,%1,%2,%3,%4,%5,%6,%7,%8,%9,%10,%11,%12,%13,%14,%15,%16,%17,%18,%19,%20,%21,%22,%23,%24,%25,%26,%27}, "
                 "{%28,%29,%30,%31}, db, p, 1, 1, %35; }\n"
                 : ACC28(d)
                 : "r"(a0), "r"(a1), "r"(a2), "r"(a3), "r"(sd), "l"(base), "n"(D), "n"(TB));
}
template <int TB, uint64_t D>
__device__ __forceinline__ void mma_rs64(float* d, uint32_t a0, uint32_t a1, uint32_t a2, uint32_t a3, int sd, uint64_t base) {
    asm volatile("{ .reg .pred p; .reg .b64 db; setp.ne.b32 p, %36, 0; add.u64 db, %37, %38;\n"
                 "wgmma.mma_async.sync.aligned.m64n64k16.f32.bf16.bf16 "
                 "{%0,%1,%2,%3,%4,%5,%6,%7,%8,%9,%10,%11,%12,%13,%14,%15,%16,%17,%18,%19,%20,%21,%22,%23,%24,%25,%26,%27,%28,%29,%30,%31}, "
                 "{%32,%33,%34,%35}, db, p, 1, 1, %39; }\n"
                 : ACC32(d, 0)
                 : "r"(a0), "r"(a1), "r"(a2), "r"(a3), "r"(sd), "l"(base), "n"(D), "n"(TB));
}
template <int TB, uint64_t D>
__device__ __forceinline__ void mma_rs128(float* d, uint32_t a0, uint32_t a1, uint32_t a2, uint32_t a3, int sd, uint64_t base) {
    asm volatile("{ .reg .pred p; .reg .b64 db; setp.ne.b32 p, %68, 0; add.u64 db, %69, %70;\n"
                 "wgmma.mma_async.sync.aligned.m64n128k16.f32.bf16.bf16 "
                 "{%0,%1,%2,%3,%4,%5,%6,%7,%8,%9,%10,%11,%12,%13,%14,%15,%16,%17,%18,%19,%20,%21,%22,%23,%24,%25,%26,%27,%28,%29,%30,%31,%32,%33,%34,%35,%36,%37,%38,%39,%40,%41,%42,%43,%44,%45,%46,%47,%48,%49,%50,%51,%52,%53,%54,%55,%56,%57,%58,%59,%60,%61,%62,%63}, "
                 "{%64,%65,%66,%67}, db, p, 1, 1, %71; }\n"
                 : ACC32(d, 0), ACC32(d, 32)
                 : "r"(a0), "r"(a1), "r"(a2), "r"(a3), "r"(sd), "l"(base), "n"(D), "n"(TB));
}
template <uint64_t DA, uint64_t DB>
__device__ __forceinline__ void mma_ss56_tt(float* d, int sd, uint64_t ba, uint64_t bb) {
    asm volatile("{ .reg .pred p; .reg .b64 da, db; setp.ne.b32 p, %28, 0; add.u64 da, %29, %31; add.u64 db, %30, %32;\n"
                 "wgmma.mma_async.sync.aligned.m64n56k16.f32.bf16.bf16 "
                 "{%0,%1,%2,%3,%4,%5,%6,%7,%8,%9,%10,%11,%12,%13,%14,%15,%16,%17,%18,%19,%20,%21,%22,%23,%24,%25,%26,%27}, "
                 "da, db, p, 1, 1, 1, 1; }\n"
                 : ACC28(d)
                 : "r"(sd), "l"(ba), "l"(bb), "n"(DA), "n"(DB));
}
template <int... I> struct Seq {};
template <class F, int... I> __device__ __forceinline__ void static_for_impl(F&& f, Seq<I...>) { (f(std::integral_constant<int, I>{}), ...); }
#define FOR7(...) static_for_impl([&](auto T_) { constexpr int t = decltype(T_)::value; __VA_ARGS__; }, Seq<0, 1, 2, 3, 4, 5, 6>{})
#define FOR8(...) static_for_impl([&](auto T_) { constexpr int t = decltype(T_)::value; __VA_ARGS__; }, Seq<0, 1, 2, 3, 4, 5, 6, 7>{})
#define FOR14(...) static_for_impl([&](auto T_) { constexpr int t = decltype(T_)::value; __VA_ARGS__; }, Seq<0, 1, 2, 3, 4, 5, 6, 7, 8, 9, 10, 11, 12, 13>{})

__device__ __forceinline__ int kblk(int p, int b) { return b == 0 ? p : b - (b <= p); }
__host__ __device__ constexpr int krow(int t) { return t < 3 ? 16 * t : (t < 6 ? 56 + 16 * (t - 3) : 48); }
#define AQ(A, b, t) ((t) < 3 ? A[2 * (b)][4 * (t)] : (t) < 6 ? A[2 * (b) + 1][4 * ((t) - 3)] : A[2 * (b)][12]), \
                    ((t) < 3 ? A[2 * (b)][4 * (t) + 1] : (t) < 6 ? A[2 * (b) + 1][4 * ((t) - 3) + 1] : A[2 * (b)][13]), \
                    ((t) < 3 ? A[2 * (b)][4 * (t) + 2] : (t) < 6 ? A[2 * (b) + 1][4 * ((t) - 3) + 2] : A[2 * (b) + 1][12]), \
                    ((t) < 3 ? A[2 * (b)][4 * (t) + 3] : (t) < 6 ? A[2 * (b) + 1][4 * ((t) - 3) + 3] : A[2 * (b) + 1][13])
#define D128(off, t) ((uint64_t)(((off) + krow(t) * 128) >> 4) + ((uint64_t)((t) == 6 ? (7168 - 1024) >> 4 : 0) << 32))
#define D64(off, t) ((uint64_t)(((off) + krow(t) * 64) >> 4) + ((uint64_t)((t) == 6 ? (3584 - 512) >> 4 : 0) << 32))

#define PL(k) (((k) - 3) * PLANE)
__device__ __forceinline__ void st_word(uint32_t* p, uint32_t v) { asm volatile("st.relaxed.gpu.global.u32 [%0], %1;" ::"l"(p), "r"(v) : "memory"); }
__device__ __forceinline__ uint32_t ld_word(const uint32_t* p) { uint32_t v; asm volatile("ld.relaxed.gpu.global.u32 %0, [%1];" : "=r"(v) : "l"(p) : "memory"); return v; }
__device__ __forceinline__ void tag_slice(uint32_t* w, uint32_t tag) { w[0] = settag(w[0], tag); w[4] = settag(w[4], tag); w[8] = settag(w[8], tag); w[12] = settag(w[12], tag); }
template <int O>
__device__ __forceinline__ void send_slice(uint4* dst, int lane, const uint32_t* w) {
    st_pkt<O>(dst, w[0], w[1], w[2], w[3]);
    st_pkt<O + 32>(dst, w[4], w[5], w[6], w[7]);
    st_pkt<O + 64>(dst, w[8], w[9], w[10], w[11]);
    asm volatile("{ .reg .b64 t; mov.b64 t, {%1,%2}; st.relaxed.gpu.global.b64 [%0+%3], t; }" ::"l"((char*)dst - lane * 8), "r"(w[12]), "r"(w[13]), "n"(16 * (O + 96)) : "memory");
}
#define RW4(v, o) "+r"(v[o]), "+r"(v[(o) + 1]), "+r"(v[(o) + 2]), "+r"(v[(o) + 3])
#define RW2(v, o) "+r"(v[o]), "+r"(v[(o) + 1])
#define WR4(v, o) "=&r"(v[o]), "=&r"(v[(o) + 1]), "=&r"(v[(o) + 2]), "=&r"(v[(o) + 3])
#define LDP(a, b, c, d, addr, off) "ld.relaxed.gpu.global.b128 q, [" addr "+" off "];\n mov.b128 {" a "," b "," c "," d "}, q;\n"
#define LDH(a, b, addr, off) "ld.relaxed.gpu.global.b64 h, [" addr "+" off "];\n mov.b64 {" a "," b "}, h;\n"
#define VOTE_OK "and.b32 t, t, 1;\n setp.ne.u32 p, t, 0;\n vote.sync.any.pred p, p, 0xffffffff;\n @!p bra.uni DN;\n"
#define CHK(x, tag) "lop3.b32 t, " x ", " tag ", t, 0xBE;\n"
__device__ __forceinline__ void check_cnt(uint32_t v, const uint32_t* p, uint32_t target) {
    asm volatile("{ .reg .pred p; .reg .b32 n, t; mov.u32 n, 0; mov.u32 t, %2;\n LP:\n"
                 "sub.s32 t, t, %1;\n setp.lt.s32 p, t, 0;\n vote.sync.any.pred p, p, 0xffffffff;\n @!p bra.uni DN;\n ld.relaxed.gpu.global.u32 t, [%0];\n" SPIN_TAIL("7")
                 ::"l"(p), "r"(target), "r"(v) : "memory");
}
__device__ __forceinline__ void poll_cnt(const uint32_t* p, uint32_t target) {
    asm volatile("{ .reg .pred p; .reg .b32 n, t; mov.u32 n, 0;\n LP:\n"
                 "ld.relaxed.gpu.global.u32 t, [%0];\n sub.s32 t, t, %1;\n setp.lt.s32 p, t, 0;\n vote.sync.any.pred p, p, 0xffffffff;\n @!p bra.uni DN;\n" SPIN_TAIL("1")
                 ::"l"(p), "r"(target) : "memory");
}
template <int STR>
__device__ __forceinline__ void poll4_kv(uint32_t* v, const uint4* p, uint32_t tag) {
    asm volatile("{ .reg .pred p; .reg .b32 n, t; .reg .b128 q; mov.u32 n, 0;\n LP:\n"
                 LDP("%0", "%1", "%2", "%3", "%16", "0") LDP("%4", "%5", "%6", "%7", "%16", "%18")
                 LDP("%8", "%9", "%10", "%11", "%16", "%19") LDP("%12", "%13", "%14", "%15", "%16", "%20")
                 "xor.b32 t, %0, %17;\n" CHK("%4", "%17") CHK("%8", "%17") CHK("%12", "%17") VOTE_OK SPIN_TAIL("2")
                 : WR4(v, 0), WR4(v, 4), WR4(v, 8), WR4(v, 12)
                 : "l"(p), "r"(tag), "n"(16 * STR), "n"(32 * STR), "n"(48 * STR)
                 : "memory");
}
template <int B>
__device__ __forceinline__ void blk_load(uint32_t (&A)[8][14], const uint4* src, int lane) {
    ld_pkt<0>(&A[2 * B][0], src); ld_pkt<32>(&A[2 * B][4], src); ld_pkt<64>(&A[2 * B][8], src);
    ld_pkt<512>(&A[2 * B + 1][0], src); ld_pkt<544>(&A[2 * B + 1][4], src); ld_pkt<576>(&A[2 * B + 1][8], src);
    asm volatile("{ .reg .b64 h;\n" LDH("%0", "%1", "%4", "1536") LDH("%2", "%3", "%4", "9728") "}"
                 : "=&r"(A[2 * B][12]), "=&r"(A[2 * B][13]), "=&r"(A[2 * B + 1][12]), "=&r"(A[2 * B + 1][13])
                 : "l"((const char*)src - lane * 8) : "memory");
}
template <int B>
__device__ __forceinline__ void blk_check(uint32_t (&A)[8][14], const uint4* src, int lane, uint32_t tag) {
    asm volatile("{ .reg .pred p; .reg .b32 n, t; .reg .b128 q; .reg .b64 h, a8; mov.u32 n, 0;\n LP:\n"
                 "xor.b32 t, %0, %30;\n" CHK("%4", "%30") CHK("%8", "%30") CHK("%12", "%30") CHK("%16", "%30") CHK("%20", "%30") CHK("%24", "%30") CHK("%26", "%30") VOTE_OK
                 LDP("%0", "%1", "%2", "%3", "%28", "0") LDP("%4", "%5", "%6", "%7", "%28", "512") LDP("%8", "%9", "%10", "%11", "%28", "1024")
                 LDP("%12", "%13", "%14", "%15", "%28", "8192") LDP("%16", "%17", "%18", "%19", "%28", "8704") LDP("%20", "%21", "%22", "%23", "%28", "9216")
                 "mad.wide.s32 a8, %29, -8, %28;\n" LDH("%24", "%25", "a8", "1536") LDH("%26", "%27", "a8", "9728") SPIN_TAIL("3")
                 "\n and.b32 %0, %0, -2; and.b32 %4, %4, -2; and.b32 %8, %8, -2; and.b32 %12, %12, -2; and.b32 %16, %16, -2; and.b32 %20, %20, -2; and.b32 %24, %24, -2; and.b32 %26, %26, -2;"
                 : RW4(A[2 * B], 0), RW4(A[2 * B], 4), RW4(A[2 * B], 8), RW4(A[2 * B + 1], 0), RW4(A[2 * B + 1], 4), RW4(A[2 * B + 1], 8),
                   RW2(A[2 * B], 12), RW2(A[2 * B + 1], 12)
                 : "l"(src), "r"(lane), "r"(tag)
                 : "memory");
}
__device__ __forceinline__ void st_async4(uint32_t a, uint32_t x, uint32_t y, uint32_t z, uint32_t w, uint32_t bar) {
    asm volatile("st.async.weak.shared::cluster.mbarrier::complete_tx::bytes.v4.b32 [%0], {%1,%2,%3,%4}, [%5];" ::"r"(a), "r"(x), "r"(y), "r"(z), "r"(w), "r"(bar) : "memory");
}
__device__ __forceinline__ uint32_t mapa(uint32_t a, uint32_t cta) { uint32_t r; asm("mapa.shared::cluster.u32 %0, %1, %2;" : "=r"(r) : "r"(a), "r"(cta)); return r; }
__device__ __forceinline__ void stat_load(uint32_t* v, const uint4* p) { ld_pkt<0>(v, p); ld_pkt<512>(v + 4, p); }
__device__ __forceinline__ void stat_check(uint32_t* v, const uint4* p, uint32_t tag) {
    asm volatile("{ .reg .pred p; .reg .b32 n, t; .reg .b128 q; mov.u32 n, 0;\n LP:\n"
                 "xor.b32 t, %3, %9;\n" CHK("%7", "%9") VOTE_OK
                 LDP("%0", "%1", "%2", "%3", "%8", "0") LDP("%4", "%5", "%6", "%7", "%8", "8192") SPIN_TAIL("4")
                 : RW4(v, 0), RW4(v, 4) : "l"(p), "r"(tag) : "memory");
}
__device__ __forceinline__ uint32_t x_bits(const uint32_t* X) {
    uint32_t r;
    asm volatile("{ .reg .b32 a, b; prmt.b32 a, %1, %2, 0x0040; prmt.b32 b, %3, %4, 0x0040; prmt.b32 %0, a, b, 0x5410; }" : "=r"(r) : "r"(X[0]), "r"(X[4]), "r"(X[8]), "r"(X[12]));
    return r;
}
template <int O>
__device__ __forceinline__ void slice_load(uint32_t* v, const uint4* p, int lane) {
    ld_pkt<O>(v, p); ld_pkt<O + 32>(v + 4, p); ld_pkt<O + 64>(v + 8, p);
    asm volatile("{ .reg .b64 h;\n" LDH("%0", "%1", "%2", "%3") "}" : "=r"(v[12]), "=r"(v[13]) : "l"((const char*)p - lane * 8), "n"(16 * (O + 96)) : "memory");
}
template <int O>
__device__ __forceinline__ void slice_check(uint32_t* v, const uint4* p, int lane, uint32_t tag) {
    asm volatile("{ .reg .pred p; .reg .b32 n, t; .reg .b128 q; .reg .b64 h; mov.u32 n, 0;\n LP:\n"
                 "xor.b32 t, %0, %16;\n" CHK("%4", "%16") CHK("%8", "%16") CHK("%12", "%16") VOTE_OK
                 LDP("%0", "%1", "%2", "%3", "%14", "%17") LDP("%4", "%5", "%6", "%7", "%14", "%18") LDP("%8", "%9", "%10", "%11", "%14", "%19")
                 LDH("%12", "%13", "%15", "%20") SPIN_TAIL("5")
                 : RW4(v, 0), RW4(v, 4), RW4(v, 8), RW2(v, 12)
                 : "l"(p), "l"((const char*)p - lane * 8), "r"(tag), "n"(16 * O), "n"(16 * (O + 32)), "n"(16 * (O + 64)), "n"(16 * (O + 96))
                 : "memory");
}
__device__ __forceinline__ void x_fix(uint32_t* X, uint32_t bits) {
    X[0] = __byte_perm(X[0], bits, 0x3214); X[4] = __byte_perm(X[4], bits, 0x3215); X[8] = __byte_perm(X[8], bits, 0x3216); X[12] = __byte_perm(X[12], bits, 0x3217);
}
__device__ __forceinline__ void sts4(uint32_t a, uint32_t x, uint32_t y, uint32_t z, uint32_t w) {
    asm volatile("st.shared.v4.u32 [%0], {%1,%2,%3,%4};" ::"r"(a), "r"(x), "r"(y), "r"(z), "r"(w) : "memory");
}
__device__ __forceinline__ void lds4(uint32_t* v, uint32_t a) {
    asm volatile("ld.shared.v4.u32 {%0,%1,%2,%3}, [%4];" : "=r"(v[0]), "=r"(v[1]), "=r"(v[2]), "=r"(v[3]) : "r"(a) : "memory");
}
struct LnCoef { uint32_t hi, lo, sh; };
__device__ __forceinline__ LnCoef ln_coef(float sum, float sq) {
    sum += __shfl_xor_sync(0xffffffffu, sum, 1); sq += __shfl_xor_sync(0xffffffffu, sq, 1);
    sum += __shfl_xor_sync(0xffffffffu, sum, 2); sq += __shfl_xor_sync(0xffffffffu, sq, 2);
    const float mean = sum * (1.f / 448.f);
    const float var = fmaxf(fmaf(-mean, mean, sq * (1.f / 448.f)), 0.f);
    const float sc = rsqrtf(var + 1e-5f);
    LnCoef r;
    r.hi = pack2(sc, sc);
    const float lo = sc - bf_lo(r.hi), sh = -mean * sc;
    r.lo = pack2(lo, lo);
    r.sh = pack2(sh, sh);
    return r;
}
template <int B>
__device__ __forceinline__ void normalize(uint32_t (&A)[8][14], const LnCoef& c0, const LnCoef& c1) {
#pragma unroll
    for (int s = 2 * B; s < 2 * B + 2; s++)
#pragma unroll
        for (int i = 0; i < 14; i++) {
            const LnCoef& k = (i & 1) ? c1 : c0;
            asm("{ .reg .b32 t; fma.rn.bf16x2 t, %0, %2, %3; fma.rn.bf16x2 %0, %0, %1, t; }" : "+r"(A[s][i]) : "r"(k.hi), "r"(k.lo), "r"(k.sh));
        }
}
__device__ __forceinline__ void slice_stats(const uint32_t* w, float* st) {
    float a = 0.f, b = 0.f, p = 0.f, q = 0.f;
#pragma unroll
    for (int i = 0; i < 7; i++) {
        const float e0 = bf_lo(w[2 * i]), e1 = bf_hi(w[2 * i]), e2 = bf_lo(w[2 * i + 1]), e3 = bf_hi(w[2 * i + 1]);
        a += e0 + e1; b += e2 + e3;
        p = fmaf(e0, e0, p); p = fmaf(e1, e1, p); q = fmaf(e2, e2, q); q = fmaf(e3, e3, q);
    }
    a += __shfl_xor_sync(0xffffffffu, a, 1); p += __shfl_xor_sync(0xffffffffu, p, 1); b += __shfl_xor_sync(0xffffffffu, b, 1); q += __shfl_xor_sync(0xffffffffu, q, 1);
    a += __shfl_xor_sync(0xffffffffu, a, 2); p += __shfl_xor_sync(0xffffffffu, p, 2); b += __shfl_xor_sync(0xffffffffu, b, 2); q += __shfl_xor_sync(0xffffffffu, q, 2);
    st[0] = a; st[1] = p; st[2] = b; st[3] = q;
}
__device__ __forceinline__ void dual_softmax(const float* p, uint32_t* out) {
    constexpr float L = 1.4426950408889634f;
#pragma unroll
    for (int r = 0; r < 2; r++) {
        float mx = fmaxf(p[2 * r], p[2 * r + 1]), mn = fminf(p[2 * r], p[2 * r + 1]);
#pragma unroll
        for (int i = 1; i < 7; i++) {
            mx = fmaxf(mx, fmaxf(p[4 * i + 2 * r], p[4 * i + 2 * r + 1]));
            mn = fminf(mn, fminf(p[4 * i + 2 * r], p[4 * i + 2 * r + 1]));
        }
        mx = fmaxf(mx, __shfl_xor_sync(0xffffffffu, mx, 1));
        mn = fminf(mn, __shfl_xor_sync(0xffffffffu, mn, 1));
        const float bx = -mx * L, bn = mn * L;
        float ep[14], en[14], sp = 0.f, sn = 0.f;
#pragma unroll
        for (int i = 0; i < 14; i++) {
            const float v = p[4 * (i >> 1) + 2 * r + (i & 1)];
            ep[i] = ex2(fmaf(v, L, bx));
            en[i] = ex2(fmaf(v, -L, bn));
            sp += ep[i]; sn += en[i];
        }
        sp += __shfl_xor_sync(0xffffffffu, sp, 1);
        sn += __shfl_xor_sync(0xffffffffu, sn, 1);
        const float ip = rcp(sp), in = rcp(sn);
#pragma unroll
        for (int i = 0; i < 7; i++) {
            out[4 * i + r] = pack2(ep[2 * i] * ip, ep[2 * i + 1] * ip);
            out[4 * i + 2 + r] = pack2(en[2 * i] * in, en[2 * i + 1] * in);
        }
    }
}
__device__ __forceinline__ float geglu(float g, float u) {
    const float t = tanh_hw(g * fmaf(g * g, 0.7978845608028654f * 0.044715f, 0.7978845608028654f));
    const float gu = g * u;
    return fmaf(t, gu, gu);
}
__device__ __forceinline__ void phi_gemm(const float* t, float* p) {
    uint32_t w[14];
#pragma unroll
    for (int i = 0; i < 14; i++) w[i] = pack2(t[2 * i], t[2 * i + 1]);
    const uint64_t db = BASE128(OFF_WPHI, 16, 0);
    wg_fence();
    mma_rs56<0, 0>(p, w[0], w[1], w[2], w[3], 0, db);
    mma_rs56<0, 2>(p, w[4], w[5], w[6], w[7], 1, db);
    mma_rs56<0, 4>(p, w[8], w[9], w[10], w[11], 1, db);
    mma_rs56<0, 6>(p, w[12], w[13], 0u, 0u, 1, db);
    wg_commit();
    wg_wait<0>();
}

}

#define BAR(i) (bars + 8 * (i))
#define R_WAIT() mbar_wait(BAR(slot), ph)
#define WSUM(i)
#define R_ADJ (slot * (STAGE >> 4))
#define R_NEXT() do { eb2 = eb1; eb1 = BAR(B_EMPTY + slot); if (++slot == NST) { slot = 0; ph ^= 1; } } while (0)
#define R_RELEASE(k) do { if (lane == 0) mbar_arrive((k) == 1 ? eb1 : eb2); } while (0)
#define PUSH_BEGIN() do { mbar_wait(BAR(B_ACK + wgi), ackph); ackph ^= 1; } while (0)
#define PUSH_ACK() do { __syncwarp(); if (lane == 0) asm volatile("mbarrier.arrive.shared::cluster.b64 _, [%0];" ::"r"(mapa(BAR(B_ACK + wgi), hr ^ 1)) : "memory"); } while (0)

__global__ void __cluster_dims__(2, 1, 1) __launch_bounds__(384, 1)
fused_kernel(Scratch* const sc, const __nv_bfloat16* __restrict__ x_in, const __nv_bfloat16* __restrict__ w_phi, const int trips,
             const __nv_bfloat16* __restrict__ wg, const __nv_bfloat16* __restrict__ wu, const __nv_bfloat16* __restrict__ wd,
             const __grid_constant__ Maps maps) {
    extern __shared__ __align__(1024) unsigned char smem_raw[];
    const uint32_t sb = s2u(smem_raw);
    const uint32_t bars = sb + OFF_BAR;
    const int wgi = __shfl_sync(0xffffffffu, threadIdx.x >> 7, 0);
    const int hr = blockIdx.x & 1, ck = blockIdx.x >> 1;
    const int gp = (ck - 4) & 7, q7 = ((ck - 36) * 37) >> 8;
    const int pr = ck < 4 ? ck : (ck < 36 ? (ck - 4) >> 3 : q7);
    const int tile = ck < 4 ? 0 : (ck < 36 ? (gp ? 2 * gp : 1) : 2 * (ck - 36 - 7 * q7) + 3);
    const int sl = 2 * pr + hr;
    STAMP(0);
    GSTAMP(60);
    if (threadIdx.x == 256) {
#pragma unroll
        for (int i = 0; i < NST; i++) mbar_init(BAR(i), 1);
        asm volatile("fence.mbarrier_init.release.cluster;" ::: "memory");
    }
    if (threadIdx.x == 288) {
        if ((sb & 0x3FFFF) != SB0) asm volatile("trap;");
#pragma unroll
        for (int i = NST; i < B_COUNT; i++) mbar_init(BAR(i), i >= B_ACK ? 4 : (i < B_RECV ? 8 : 1));
        asm volatile("fence.mbarrier_init.release.cluster;" ::: "memory");
    }
    __syncwarp();
    asm volatile("barrier.cluster.arrive.relaxed.aligned;" ::: "memory");

    if (wgi == 2) {
        asm volatile("setmaxnreg.dec.sync.aligned.u32 40;");
        const int t128 = fresh_tid() & 127, w = __shfl_sync(0xffffffffu, t128 >> 5, 0), lane = t128 & 31;
        uint32_t e0[2] = {0, 0}, e1[2] = {0, 0}, cw_target = 0;
        if (w == 0) {
#define SORD 0
#pragma unroll 1
            for (int i = 0; i < NST; i++) {
                const int n = SORD == 2 ? (i + 2) % NST : (SORD == 3 ? (i == 0 ? 2 : (i < 3 ? i - 1 : i)) : i);
                const uint32_t dst = sb + n * STAGE, fb = BAR(n);
                asm volatile(ELECT "mbarrier.arrive.expect_tx.shared::cta.b64 _, [%0], %1; }" ::"r"(fb), "r"(n < 2 ? 2 * STAGE : STAGE) : "memory");
                if (n < 2) {
                    tma3x(sb + OFF_H + n * STAGE, &maps.x, tile * 128 + n * 64, fb);
                    tma3x(dst, &maps.x, tile * 128 + n * 64 + 32, fb);
                } else {
                    if (SORD == 0 && n == 3) mbar_wait(BAR(1), 0);
                    const int ra = 112 * (n - 2);
                    tma2d(dst, &maps.qkv, 448 + 56 * sl, ra, fb);
                    tma2d(dst + HALF, &maps.qkv, 896 + 56 * sl, ra, fb);
                }
            }
            asm volatile("barrier.cluster.wait.aligned;" ::: "memory");
            cw_target = (ld_word(g_cw + sl * 32) & ~15u) + 16;
#pragma unroll 1
            for (int k = 0; k < 2; k++) {
                const int n = t128 + 32 * k;
                int m = n - 2 - (n > PACK);
                const bool packed = m >= 30 ? (m < 38 || m >= 52) : m >= 22;
                if (m >= 30) m -= 30;
                if (n == PACK) m = tile < 8 ? tile : tile + 14;
                const int rot = n < 8 ? 0 : pr;
                const int ra = 112 * kblk(rot, m & 3), rb = 112 * kblk(rot, 2 * m & 3), rc = 112 * kblk(rot, (2 * m + 1) & 3);
                int kind = 0, m0, m1, c0, c1, r0, r1;
                if (m < 4) { m0 = m1 = 1; c0 = 448 + 56 * sl; c1 = c0 + 448; r0 = r1 = ra; }
                else if (m < 8) { m0 = m1 = m < 6 ? 1 : 2; c0 = c1 = 56 * sl; r0 = rb; r1 = rc; }
                else if (m < 20) { m0 = 3; m1 = 4; c0 = c1 = 224 * sl + 32 * hr + 64 * ((m - 8) >> 2); r0 = r1 = ra; }
                else if (m < 22) { kind = 2; m0 = 5; m1 = 6; c0 = c1 = 224 * sl + (hr ? 0 : 192); r0 = rb; r1 = rc; }
                else { m0 = m1 = 7; c0 = c1 = 56 * (2 * ((pr + (m >> 1) - 10) & 3) + hr); r0 = 224 * (sl ^ (m & 1)); r1 = r0 + 112; }
                if (packed) { kind = 1; r0 = sl * 16 + (m < 8 ? m : m - 14); r1 = 0; }
                e0[0] = e0[1]; e1[0] = e1[1];
                e0[1] = kind | (m0 << 2) | (m1 << 6) | (c0 << 10) | (c1 << 21);
                e1[1] = r0 | (r1 << 16);
            }
        } else {
            const int j = t128 - 32;
            asm volatile("barrier.cluster.wait.aligned;" ::: "memory");
            uint2 wv[7];
            const int k = j < 56 ? j : 55, hh = k >= 28;
#pragma unroll
            for (int i = 0; i < 7; i++) wv[i] = __ldg(reinterpret_cast<const uint2*>(w_phi + (sl * 56 + k) * 28) + i);
#pragma unroll 1
            for (int i = j; i < 7168 / 16; i += 96) sts4(sb + OFF_WPHI + i * 16, 0, 0, 0, 0);
            bar_sync(5, 96);
            if (j < 56) {
                uint32_t a4[4];
#pragma unroll
                for (int q = 0; q < 4; q++) a4[q] = sb + OFF_WPHI + (4 * hh + q) * 128 + ((((k >> 3) ^ (4 * hh + q)) & 7) << 4) + (k & 7) * 2;
                FOR14(const uint32_t v = (t & 1) ? wv[t >> 1].y : wv[t >> 1].x;
                      asm volatile("{ .reg .b16 l, h; mov.b32 {l, h}, %2; st.shared.u16 [%0+%3], l; st.shared.u16 [%1+%3], h; }"
                                   ::"r"(a4[t >= 7 ? 2 : 0]), "r"(a4[t >= 7 ? 3 : 1]), "r"(v), "n"((t % 7) * 1024) : "memory"));
            }
            __syncwarp();
            fence_async();
            bar_arrive(1, 224);
            bar_arrive(9, 224);
            if (w == 1) {
                mbar_wait(BAR(2), 0);
                mbar_wait(BAR(2), 1);
                const int b = blockIdx.x;
                asm volatile(ELECT "cp.async.bulk.prefetch.L2.global [%0], %1; }" ::"l"(wg + b * 6272), "r"(12544) : "memory");
                asm volatile(ELECT "cp.async.bulk.prefetch.L2.global [%0], %1; }" ::"l"(wu + b * 6272), "r"(12544) : "memory");
                asm volatile(ELECT "cp.async.bulk.prefetch.L2.global [%0], %1; }" ::"l"(wd + b * 6272), "r"(12544) : "memory");
            }
        }
        uint32_t kseq = ld_word(g_c1 + (sl * 8 * 16 + tile) * 32);
        int slot = 0, ph = 0, n = NST;
#pragma unroll 1
        for (int layer = 0; layer < 3; layer++) {
            if (w == 0) {
                const int nend = layer == 0 ? 11 : (layer == 1 ? 42 : 63);
#pragma unroll 1
                for (; n < nend; n++) {
                const uint32_t w0 = __shfl_sync(0xffffffffu, n < 32 ? e0[0] : e0[1], n & 31), w1 = __shfl_sync(0xffffffffu, n < 32 ? e1[0] : e1[1], n & 31);
                const uint32_t dst = sb + slot * STAGE, fb = BAR(n == PACK ? B_PACK : slot);
                const CUtensorMap* m0 = &maps.x + ((w0 >> 2) & 15);
                const CUtensorMap* m1 = &maps.x + ((w0 >> 6) & 15);
                const int c0 = (w0 >> 10) & 2047, c1 = w0 >> 21, r0 = w1 & 0xffff, r1 = w1 >> 16;
                if (n == 25) {
                    int it = 0;
                    uint32_t v;
                    do { asm volatile("ld.acquire.gpu.global.u32 %0, [%1];" : "=r"(v) : "l"(g_cw + sl * 32) : "memory"); } while ((int)(v - cw_target) < 0 && ++it < 0x400000);
                    asm volatile("fence.proxy.async.global;" ::: "memory");
                    __syncwarp();
                }
                mbar_wait(BAR(B_EMPTY + slot), ph);
                __syncwarp();
                asm volatile(ELECT "mbarrier.arrive.expect_tx.shared::cta.b64 _, [%0], %1; }" ::"r"(fb), "r"(STAGE) : "memory");
                if ((w0 & 3) == 0) {
                    tma2d(dst, m0, c0, r0, fb);
                    tma2d(dst + HALF, m1, c1, r1, fb);
                } else if (w0 & 1) {
                    asm volatile(ELECT "cp.async.bulk.shared::cluster.global.mbarrier::complete_tx::bytes [%0], [%1], %2, [%3]; }"
                                 ::"r"(dst), "l"(reinterpret_cast<const char*>(g_wp) + (size_t)r0 * STAGE), "r"(STAGE), "r"(fb) : "memory");
                } else {
                    tma2d(dst, m0, c0, r0, fb); tma2d(dst + 7168, m0, c0, r1, fb);
                    tma2d(dst + HALF, m1, c0, r0, fb); tma2d(dst + HALF + 7168, m1, c0, r1, fb);
                }
                if (n == PACK) asm volatile(ELECT "mbarrier.arrive.shared::cta.b64 _, [%0]; }" ::"r"(BAR(slot)) : "memory");
                if (++slot == NST) { slot = 0; ph ^= 1; }
                }
            } else if (w == 1 && layer == 1) {
                constexpr int ps = PACK % NST;
                mbar_wait(BAR(B_PACK), 0);
                asm volatile("{ .reg .pred e; elect.sync _|e, 0xffffffff;\n"
                             "@e cp.async.bulk.global.shared::cta.bulk_group [%0], [%1], %2;\n"
                             "@e cp.async.bulk.commit_group;\n"
                             "@e cp.async.bulk.wait_group.read 0;\n"
                             "@e mbarrier.arrive.shared::cta.b64 _, [%3], 8;\n"
                             "@e cp.async.bulk.wait_group 0;\n"
                             "@e fence.proxy.async.global;\n"
                             "@e red.release.gpu.global.add.u32 [%4], 1; }"
                             ::"l"(reinterpret_cast<char*>(g_wp) + (size_t)(sl * 16 + tile) * STAGE), "r"(sb + ps * STAGE), "r"(STAGE), "r"(BAR(B_EMPTY + ps)), "l"(g_cw + sl * 32) : "memory");
                __syncwarp();
            }
            if (layer < 2) {
            const uint32_t tag = layer ^ 1;
            kseq++;
            bar_sync(7, 384);
            ASTAMP(0);
            if (tile < 15) {
                const int sq = lane >> 3, pk = 8 * w + (lane & (tile == 14 ? 3 : 7));
                uint32_t v[16];
                if (layer == 0) poll_cnt(g_c1 + ((sl * 8 + (w >> 1) * 4 + (tile >> 2)) * 16 + (lane & 15)) * 32, kseq);
                ASTAMP(1);
                poll4_kv<32>(v, g_kv1 + ((sl * 16 + tile) * 16 + 4 * sq) * 32 + pk, tag);
#pragma unroll
                for (int k = 0; k < 4; k++) {
                    float lo = (bf_lo(v[k]) + bf_lo(v[4 + k])) + (bf_lo(v[8 + k]) + bf_lo(v[12 + k]));
                    float hi = (bf_hi(v[k]) + bf_hi(v[4 + k])) + (bf_hi(v[8 + k]) + bf_hi(v[12 + k]));
                    lo += __shfl_xor_sync(0xffffffffu, lo, 8); hi += __shfl_xor_sync(0xffffffffu, hi, 8);
                    lo += __shfl_xor_sync(0xffffffffu, lo, 16); hi += __shfl_xor_sync(0xffffffffu, hi, 16);
                    v[k] = pack2(lo, hi);
                }
                if (sq == 0) st_pkt<0>(g_kv2 + sl * 512 + 32 * tile + pk, settag(v[0], tag), v[1], v[2], v[3]);
            }
            ASTAMP(2);
            {
                const int item = t128 < 112 ? t128 : 112 + (t128 & 3), d = item >> 1;
                const int cc = t128 < 112 ? 2 * (d >= 28) + (item & 1) : item - 112;
                const int r = t128 < 112 ? d : 56 + (cc >> 1) + 2 * ((t128 - 112) >> 2);
                uint32_t ra = sb + OFF_KVB + r * 128 + 4 * cc, rx = (r & 7) << 4;
                asm volatile("" : "+r"(ra), "+r"(rx));
                FOR14(asm volatile("st.shared.u32 [%0+%2], %1;" ::"r"((ra ^ 8) + (((t & 7) << 4) ^ rx)), "r"(0), "n"((t >> 3) * 8192) : "memory"));
                uint32_t v[16];
                asm volatile("" : "+r"(ra), "+r"(rx));
                poll4_kv<8>(v, g_kv2 + sl * 512 + (item >> 3) * 32 + (item & 7), tag);
                FOR14(asm volatile("st.shared.u32 [%0+%2], %1;" ::"r"(ra + (((t & 7) << 4) ^ rx)), "r"(v[t < 7 ? t : t + 1]), "n"((t >> 3) * 8192) : "memory"));
                fence_async();
            }
            bar_arrive(3, 384);
            ASTAMP(3);
            }
        }
    } else {
        asm volatile("setmaxnreg.inc.sync.aligned.u32 232;");
        const int tid = fresh_tid(), lane = tid & 31, t128 = tid & 127, g = lane >> 2, c = lane & 3;
        const int wu = __shfl_sync(0xffffffffu, tid >> 5, 0), w = wu & 3;
        uint4* const xp0 = g_ex + 3 * PLANE + ((tile * 2 + wgi) * 8) * 512 + w * 128 + lane;
        const uint32_t hbuf = sb + OFF_H + wgi * STAGE;
        uint32_t slot = 0, ph = 0, eb1 = 0, eb2 = 0, ackph = 0, rcvph = 0, gatph = 0, swp = 0;
        uint32_t ppid = 6;
#define cx(s) (reinterpret_cast<uint32_t*>(again(xp0) - lane + PL(1) + 112 + (s) * 512))
#define stp (again(xp0) - lane + g + PL(0) + 112)
        uint32_t seq = ld_word(cx(sl));
        uint32_t kseq = ld_word(g_c1 + ((sl * 8 + (tid >> 5)) * 16 + tile) * 32);
        uint32_t stag = ld_word(reinterpret_cast<const uint32_t*>(stp + sl * 512) + 3) & 1;
        asm volatile("barrier.cluster.wait.aligned;" ::: "memory");
        STAMP(1);
        uint32_t X[14];
        [[maybe_unused]] const uint32_t x0row = (w < 2 ? hbuf : sb + wgi * STAGE) + ((w & 1) * 16 + (lane & 15)) * 128;
        mbar_wait(BAR(wgi), 0);
        STAMP(51);
        kill<14>(X);
#define PUSH_SLICE(W)                                                                          \
    {                                                                                          \
        if (t128 == 0) mbar_expect_tx(BAR(B_RECV + wgi), 7168);                                \
        PUSH_BEGIN();                                                                          \
        const uint32_t ra = mapa(hbuf + 24576 + t128 * 16, hr ^ 1), rb = mapa(sb + OFF_XR + wgi * 3072, hr ^ 1), rbar = mapa(BAR(B_RECV + wgi), hr ^ 1); \
        st_async4(ra, W[0], W[1], W[2], W[3], rbar);                                           \
        st_async4(ra + 2048, W[4], W[5], W[6], W[7], rbar);                                    \
        st_async4(rb + t128 * 16, W[8], W[9], W[10], W[11], rbar);                             \
        asm volatile("st.async.weak.shared::cluster.mbarrier::complete_tx::bytes.v2.b32 [%0], {%1,%2}, [%3];" ::"r"(rb + 2048 + t128 * 8), "r"(W[12]), "r"(W[13]), "r"(rbar) : "memory"); \
    }
#define PULL_SLICE(W)                                                                          \
    {                                                                                          \
        uint32_t t0, t1;                                                                       \
        mbar_wait(BAR(B_RECV + wgi), rcvph);                                                   \
        rcvph ^= 1;                                                                            \
        lds4(&A[1][0], hbuf + 24576 + t128 * 16);                                              \
        lds4(&A[1][4], hbuf + 26624 + t128 * 16);                                              \
        lds4(&A[1][8], sb + OFF_XR + wgi * 3072 + t128 * 16);                                  \
        asm volatile("ld.shared.v2.u32 {%0,%1}, [%2];" : "=r"(t0), "=r"(t1) : "r"(sb + OFF_XR + wgi * 3072 + 2048 + t128 * 8) : "memory"); \
        _Pragma("unroll") for (int i = 0; i < 12; i++) A[0][i] = (i & 3) ? W[i] : W[i] & ~1u;  \
        A[1][0] &= ~1u; A[1][4] &= ~1u; A[1][8] &= ~1u;                                        \
        A[0][12] = (hr ? t0 : W[12]) & ~1u; A[0][13] = hr ? t1 : W[13];                        \
        A[1][12] = (hr ? W[12] : t0) & ~1u; A[1][13] = hr ? W[13] : t1;                        \
        asm volatile("" : RW4(A[0], 0), RW4(A[0], 4), RW4(A[0], 8), RW2(A[0], 12), RW4(A[1], 0), RW4(A[1], 4), RW4(A[1], 8), RW2(A[1], 12)); \
        swp = hr * 448;                                                                        \
    }
#define SWB(b, t, db, sh) ((b) == 0 && (t) < 6 ? ((t) < 3 ? db##p : db##m) : db)
#define DECL_DB(b, MK, lbo, sh) const uint64_t db = MK(0, lbo, R_ADJ), dbp = (b) == 0 ? MK(0, lbo, R_ADJ + (swp >> (sh))) : db, dbm = (b) == 0 ? MK(0, lbo, R_ADJ - (swp >> (sh))) : db;
#define EARLY 1
#define EARLYK 1
#define PPB 2
#define PP_WAIT() if (wgi == 1) { bar_sync(ppid, 256); ppid ^= 14; }
#define PP_GO() if (wgi == 0) { bar_arrive(ppid, 256); ppid ^= 14; }
#define GAT_ISSUE(base)                                                                        \
    {                                                                                          \
        const char* gs = reinterpret_cast<const char*>(g_ex + 3 * PLANE + (base) + (tile * 16 + wgi * 8 + 2 * kblk(pr, GB)) * 512 + w * 128); \
        const uint32_t gd = hbuf + w * 3584, gb = BAR(B_GAT + wu);                     \
        asm volatile("{ .reg .pred e; elect.sync _|e, 0xffffffff;\n"                           \
                     "@e mbarrier.arrive.expect_tx.shared::cta.b64 _, [%2], 3584;\n"           \
                     "@e cp.async.bulk.shared::cluster.global.mbarrier::complete_tx::bytes [%0], [%1], 1792, [%2];\n" \
                     "@e cp.async.bulk.shared::cluster.global.mbarrier::complete_tx::bytes [%0+1792], [%1+8192], 1792, [%2]; }" \
                     ::"r"(gd), "l"(gs), "r"(gb) : "memory");                                  \
        __syncwarp();                                                                          \
    }
#define GAT_FETCH()                                                                            \
    {                                                                                          \
        mbar_wait(BAR(B_GAT + wu), gatph);                                             \
        gatph ^= 1;                                                                            \
        const uint32_t ga = hbuf + w * 3584 + lane * 16;                                       \
        _Pragma("unroll") for (int s2 = 0; s2 < 2; s2++) {                                     \
            lds4(&A[2 * GB + s2][0], ga + s2 * 1792); lds4(&A[2 * GB + s2][4], ga + s2 * 1792 + 512); lds4(&A[2 * GB + s2][8], ga + s2 * 1792 + 1024); \
            asm volatile("ld.shared.v2.u32 {%0,%1}, [%2];" : "=r"(A[2 * GB + s2][12]), "=r"(A[2 * GB + s2][13]) : "r"(ga - lane * 8 + s2 * 1792 + 1536) : "memory"); \
        }                                                                                      \
    }
#define PT 3
#define PREP(b, t, remote)                                                                     \
    if constexpr ((b) < 3 && (t) == PT) {                                                      \
        wg_commit();                                                                           \
        STAMP(80 + 8 * (step & 1) + 2 * (b));                                                  \
        if constexpr (GB == 1 && (b) == 0) { if (remote) GAT_FETCH() }                         \
        if (remote) blk_check<((b) + 1) & 3>(A, BLK(xsrc, (b) + 1), lane, xtag);               \
        STAMP(81 + 8 * (step & 1) + 2 * (b));                                                  \
        if constexpr ((b) == 0) { if (remote) blk_load<3>(A, BLK(xsrc, 3), lane); }            \
        normalize<((b) + 1) & 3>(A, k0, k1);                                                   \
        asm volatile("" : RW4(A[(2 * (b) + 2) & 7], 0), RW4(A[(2 * (b) + 2) & 7], 4), RW4(A[(2 * (b) + 2) & 7], 8), RW2(A[(2 * (b) + 2) & 7], 12), \
                          RW4(A[(2 * (b) + 3) & 7], 0), RW4(A[(2 * (b) + 3) & 7], 4), RW4(A[(2 * (b) + 3) & 7], 8), RW2(A[(2 * (b) + 3) & 7], 12)); \
        wg_fence();                                                                            \
    }                                                                                          \
    if constexpr ((b) == 3 && ((t) == 0 || (t) == 6)) { STAMP(86 + 8 * (step & 1) + (t) / 6); }
#define BLK(base, b) ((base) + kblk(pr, b) * 1024)

#pragma unroll 1
        for (int step = 0; step < 4; step++) {
            const uint32_t tag = (step >> 1) ^ 1;
            const int so = (step >> 1) * 24 + (step & 1) * 12;
            (void)so;
            uint32_t A[8][14];
            uint4* const xsrc = xp0 + ((step & 1) ? PL(2) : PL(0));
            const uint32_t xtag = (step & 1) ? tag : ((seq >> 3) & 1) ^ 1;
            uint32_t xbits = 0;
            if (step || !LSTAT) {
                float st[4];
                slice_stats(X, st);
                stag ^= 1;
                xbits = x_bits(X);
                tag_slice(X, xtag);
                if (step) send_slice<0>(xsrc + sl * 512, lane, X);
                if (c == 0) st_pkt<0>(stp + sl * 512, __float_as_uint(st[0]), __float_as_uint(st[1]), __float_as_uint(st[2]), settag(__float_as_uint(st[3]), stag));
            }
            STAMP(2 + so);
            uint32_t sv[8];
            if (step == 0) {
                const int rr = lane & 7, hi = lane >> 4;
                const uint32_t rowa = (w < 2 ? hbuf : sb + wgi * STAGE) + ((w & 1) * 16 + (lane & 15)) * 128;
                uint32_t xr[8];
#pragma unroll
                for (int j = 0; j < 8; j++) xr[j] = rowa + ((((j + hi) ^ rr) & 7) << 4) + (j == 7 ? hi * 4096 : 0);
#define X0_BLOCK(b)                                                                            \
    FOR7(constexpr int G = 14 * (b) + (t < 3 ? 2 * t : (t < 6 ? 2 * t + 1 : 6));               \
         uint32_t q0, q1, q2, q3;                                                              \
         const uint32_t ad = t < 6 ? xr[G & 7] : rowa + ((G + 7 * hi) >> 3) * 4096 + ((((G + 7 * hi) ^ rr) & 7) << 4); \
         asm volatile("ldmatrix.sync.aligned.m8n8.x4.shared.b16 {%0,%1,%2,%3}, [%4+%5];" : "=r"(q0), "=r"(q1), "=r"(q2), "=r"(q3) \
                      : "r"(ad), "n"(t < 6 ? (G >> 3) * 4096 : 0) : "memory");                 \
         if (t < 3) { A[2 * (b)][4 * t] = q0; A[2 * (b)][4 * t + 1] = q1; A[2 * (b)][4 * t + 2] = q2; A[2 * (b)][4 * t + 3] = q3; } \
         else if (t < 6) { A[2 * (b) + 1][(4 * t - 12) & 15] = q0; A[2 * (b) + 1][((4 * t - 12) & 15) + 1] = q1; A[2 * (b) + 1][((4 * t - 12) & 15) + 2] = q2; A[2 * (b) + 1][((4 * t - 12) & 15) + 3] = q3; } \
         else { A[2 * (b)][12] = q0; A[2 * (b)][13] = q1; A[2 * (b) + 1][12] = q2; A[2 * (b) + 1][13] = q3; });
                X0_BLOCK(0) X0_BLOCK(1) X0_BLOCK(2) X0_BLOCK(3)
                mbar_wait(BAR(wgi ^ 1), 0);
                R_NEXT();
                R_NEXT();
                {
                    float sa = 0.f, sq = 0.f;
                    const uint32_t rb = (w < 2 ? hbuf : sb + wgi * STAGE) + ((w & 1) * 16 + (lane >> 1)) * 128;
#pragma unroll 2
                    for (int i = 0; i < 28; i++) {
                        uint32_t q[4];
                        lds4(q, rb + (i >> 2) * 4096 + ((((i & 3) * 2 + lane) & 7) << 4));
#pragma unroll
                        for (int k = 0; k < 4; k++) {
                            const float e0 = bf_lo(q[k]), e1 = bf_hi(q[k]);
                            sa += e0 + e1; sq = fmaf(e0, e0, sq); sq = fmaf(e1, e1, sq);
                        }
                    }
                    const int s0 = 2 * g + (c & 1);
                    const float a0 = __shfl_sync(0xffffffffu, sa, s0), q0 = __shfl_sync(0xffffffffu, sq, s0);
                    const float a1 = __shfl_sync(0xffffffffu, sa, s0 + 16), q1 = __shfl_sync(0xffffffffu, sq, s0 + 16);
                    sv[0] = c < 2 ? __float_as_uint(a0) : 0u; sv[1] = c < 2 ? __float_as_uint(q0) : 0u;
                    sv[2] = c < 2 ? __float_as_uint(a1) : 0u; sv[3] = c < 2 ? __float_as_uint(q1) : 0u;
                    sv[4] = sv[5] = sv[6] = sv[7] = 0u;
                }
                STAMP(52 + step);
            } else {
                PUSH_SLICE(X)
                stat_load(sv, stp + c * 1024);
                kill<14>(A[2]); kill<14>(A[3]); kill<14>(A[4]); kill<14>(A[5]); kill<14>(A[6]); kill<14>(A[7]);
                PULL_SLICE(X)
                stat_check(sv, stp + c * 1024, stag);
                STAMP(52 + step);
                if (GB == 1) GAT_ISSUE((step & 1) ? PL(2) : PL(0))
                else blk_load<1>(A, BLK(xsrc, 1), lane);
            }
            LnCoef k0, k1;
            {
                k0 = ln_coef(__uint_as_float(sv[0]) + __uint_as_float(sv[4]), __uint_as_float(sv[1]) + __uint_as_float(sv[5]));
                k1 = ln_coef(__uint_as_float(sv[2]) + __uint_as_float(sv[6]), __uint_as_float(sv[3] & ~1u) + __uint_as_float(sv[7] & ~1u));
            }
            if (step) {
                if (GB == 2) GAT_ISSUE((step & 1) ? PL(2) : PL(0))
                else blk_load<2>(A, BLK(xsrc, 2), lane);
            }
            STAMP(3 + so);
            GSTAMP(76 + step);

            if ((step & 1) == 0) {
                float tq[28];
                {
                    float av[28];
#define KV_BLOCK(b)                                                                           \
    if (GB == 2 && (b) == 1 && step) GAT_FETCH()                                                         \
    if ((b) == 2) PUSH_ACK();                                                                 \
    if (QE && (b) == 1) R_RELEASE(2);                                                         \
    if (QE && (b) == 2) { wg_wait<2>(); R_RELEASE(2); }                                       \
    R_WAIT();                                                                                 \
    if ((b) == PPK) { PP_WAIT() }                                                             \
    { DECL_DB(b, BASE128, 16, 0)                                                              \
    wg_fence();                                                                               \
    FOR7(mma_rs56<1, D128(0, t)>(tq, AQ(A, b, t), (b) + t > 0, SWB(b, t, db, 0));             \
         mma_rs56<1, D128(HALF, t)>(av, AQ(A, b, t), (b) + t > 0, SWB(b, t, db, 0));          \
         PREP(b, t, step)); }                                                                 \
    wg_commit();                                                                              \
    if ((b) == 3 && PPK < 4) { PP_GO() }                                                      \
    R_NEXT();
                    if (EARLYK == 0 || step == 0) R_RELEASE(2);
                    normalize<0>(A, k0, k1);
                    KV_BLOCK(0) KV_BLOCK(1) KV_BLOCK(2) KV_BLOCK(3)
                    wg_wait<0>();
                    if (lane < (QE ? 3 : NST)) mbar_arrive(BAR(B_EMPTY + (slot + NST - 1 - lane) % NST));
                    STAMP(4 + so);
                    WSUM(80 + 7 * (step >> 1));
                    const int m = lane >> 3, rr = lane & 7;
                    const uint32_t rowa = hbuf + 16384 + (w * 16 + rr + 8 * (m & 1)) * 128;
                    const uint32_t one = c == 0 ? 0x00003f80u : 0u;
                    if (step == 0) { bar_sync(wgi ? 9 : 1, 224); }
#pragma unroll
                    for (int j = 0; j < 4; j++) {
                        const uint32_t a = rowa + (((2 * j + (m >> 1)) ^ rr) << 4);
                        if (j < 3) stsm4(a, pack2(av[8 * j], av[8 * j + 1]), pack2(av[8 * j + 2], av[8 * j + 3]), pack2(av[8 * j + 4], av[8 * j + 5]), pack2(av[8 * j + 6], av[8 * j + 7]));
                        else stsm4(a, pack2(av[24], av[25]), pack2(av[26], av[27]), one, one);
                    }
                }
                uint32_t PH[28];
                int it = 1;
#pragma unroll 1
                do {
                    float pp[28];
                    phi_gemm(tq, pp);
                    dual_softmax(pp, PH);
                    if (((trips >> (it + 1)) & 1) == 0) continue;
                    {
                        const int m = lane >> 3, rr = lane & 7;
                        const uint32_t rowa = hbuf + (w * 16 + rr + 8 * (m & 1)) * 128;
#pragma unroll
                        for (int j = 0; j < 7; j++) {
                            const int cg = 2 * j + (m >> 1), hi = cg >= 7;
                            stsm4(rowa + hi * 8192 + (((cg - 7 * hi) ^ rr) << 4), PH[4 * j], PH[4 * j + 1], PH[4 * j + 2], PH[4 * j + 3]);
                        }
                    }
                    fence_async();
                    STAMP(5 + so);
#define Q_STAGE(b0)                                                                           \
    R_WAIT();                                                                                 \
    { DECL_DB(b0, BASE128, 16, 0)                                                             \
    wg_fence();                                                                               \
    FOR7(mma_rs56<1, D128(0, t)>(tq, AQ(A, b0, t), (b0) + t > 0, SWB(b0, t, db, 0)));         \
    FOR7(mma_rs56<1, D128(HALF, t)>(tq, AQ(A, (b0) + 1, t), 1, db)); }                        \
    wg_commit();                                                                              \
    R_NEXT();
                    if (QE && wgi == 0) { kill<28>(tq); Q_STAGE(0) Q_STAGE(2) wg_wait<1>(); R_RELEASE(2); wg_wait<0>(); R_RELEASE(1); }
                    bar_sync(2, 256);
                    float kv[28];
                    const uint64_t da = BASE128(OFF_H + 16384, 16, 0), dbk = BASE128(OFF_H, 16, wgi * 512);
                    wg_fence();
                    FOR8(constexpr uint64_t o = ((t >> 2) * STAGE + (t & 3) * 2048) >> 4; mma_ss56_tt<o, o>(kv, t > 0, da, dbk));
                    wg_commit();
                    wg_wait<0>();
#pragma unroll
                    for (int hf = 0; hf < 2; hf++) {
                        const int d = 16 * w + g + 8 * hf;
                        if ((d < 56 && (d >= 28) == (c >= 2)) || d == 56) {
                            const int item = d < 56 ? 2 * d + (c & 1) : 112 + c;
                            uint4* dst = g_kv1 + ((sl * 16 + (item >> 3)) * 16 + tile) * 32 + wgi * 16 + (item & 7);
#define KVW(i) pack2(kv[4 * (i) + 2 * hf], kv[4 * (i) + 2 * hf + 1])
                            st_pkt<0>(dst, settag(KVW(0), tag), KVW(1), KVW(2), KVW(3));
                            st_pkt<8>(dst, settag(KVW(4), tag), KVW(5), KVW(6), 0u);
                        }
                    }
                    __syncwarp();
                    kseq++;
                    if (lane == 0) st_word(g_c1 + ((sl * 8 + (tid >> 5)) * 16 + tile) * 32, kseq);
                    bar_arrive(7, 384);
                    STAMP(6 + so);
                    if (!QE || wgi == 1) { kill<28>(tq); Q_STAGE(0) Q_STAGE(2) wg_wait<1>(); R_RELEASE(2); wg_wait<0>(); R_RELEASE(1); }
                    STAMP(7 + so);
                    kill<28>(PH);
                } while (((trips >> (++it)) & 1));
                STAMP(8 + so);
                if (step) {
                    slice_load<PL(0)>(X, xp0 + sl * 512, lane);
                } else {
                    const uint32_t* xp = reinterpret_cast<const uint32_t*>(x_in + (size_t)(tile * 128 + wu * 16 + g) * 448 + 56 * sl + 2 * c);
#pragma unroll
                    for (int i = 0; i < 7; i++) { X[2 * i] = __ldg(xp + 4 * i); X[2 * i + 1] = __ldg(xp + 4 * i + 8 * 224); }
                }
                bar_sync(3, 384);
                STAMP(9 + so);
                const uint4* const osrc = xp0 + PL(1);
                {
                    float nm[32];
                    const uint64_t db = BASE128(OFF_KVB, 16, 0);
                    wg_fence();
                    FOR7(mma_rs64<0, ((t >> 2) * 8192 + (t & 3) * 32) / 16>(nm, PH[4 * t], PH[4 * t + 1], PH[4 * t + 2], PH[4 * t + 3], t > 0, db));
                    wg_commit();
                    wg_wait<0>();
                    const float i00 = rcp(nm[28] + 1e-6f), i01 = rcp(nm[29] + 1e-6f), i10 = rcp(nm[30] + 1e-6f), i11 = rcp(nm[31] + 1e-6f);
                    const float m0 = c >= 2 ? i01 : i00, m1 = c >= 2 ? i11 : i10;
                    uint32_t O[14];
#pragma unroll
                    for (int i = 0; i < 7; i++) {
                        const float f0 = i < 3 ? i00 : (i > 3 ? i01 : m0), f1 = i < 3 ? i10 : (i > 3 ? i11 : m1);
                        O[2 * i] = pack2(nm[4 * i] * f0, nm[4 * i + 1] * f0);
                        O[2 * i + 1] = pack2(nm[4 * i + 2] * f1, nm[4 * i + 3] * f1);
                    }
                    if (OST) { PP_WAIT() }
                    tag_slice(O, tag);
                    send_slice<PL(1)>(xp0 + sl * 512, lane, O);
                    seq++;
                    if (lane == 0) st_word(cx(sl), seq);
                    STAMP(10 + so);
                    PUSH_SLICE(O)
                    if (OST == 1) { PP_GO() }
                    const uint32_t cv = ld_word(cx(lane & 7));
                    PULL_SLICE(O)
                    check_cnt(cv, cx(lane & 7), seq);
                    if (OST == 2) { PP_GO() }
                    STAMP(56 + (step >> 1));
                    GAT_ISSUE(PL(1))
                    blk_load<3 - GB>(A, BLK(osrc, 3 - GB), lane);
                }
                float ao[28];
#define WO_BLOCK(b)                                                                           \
    if ((b) > 0) blk_check<b>(A, BLK(osrc, b), lane, tag);                                    \
    if (((b) & 1) == 0) R_WAIT();                                                             \
    { DECL_DB(b, BASE128, 16, 0)                                                              \
    wg_fence();                                                                               \
    FOR7(mma_rs56<1, D128(((b) & 1) * HALF, t)>(ao, AQ(A, b, t), (b) + t > 0, SWB(b, t, db, 0))); } \
    wg_commit();                                                                              \
    if ((b) & 1) R_NEXT();
                WO_BLOCK(0)
                STAMP(11 + so);
                blk_load<3>(A, BLK(osrc, 3), lane);
                if (GB == 1) GAT_FETCH()
                WO_BLOCK(1)
                if (GB == 2) GAT_FETCH()
                WO_BLOCK(2)
                PUSH_ACK();
                WO_BLOCK(3)
                wg_wait<0>();
                if (EARLY >= 1) R_RELEASE(2);
                if (EARLY >= 2) R_RELEASE(1);
                STAMP(12 + so);
                WSUM(86 + 7 * (step >> 1));
                if (step) x_fix(X, xbits);
#pragma unroll
                for (int i = 0; i < 14; i++) X[i] = pack2(bf_lo(X[i]) + ao[2 * i], bf_hi(X[i]) + ao[2 * i + 1]);
            } else {
                uint32_t H[56];
                float ag[64];
#define F1_EPI(dst, ng, ag)                                                                    \
    _Pragma("unroll") for (int i = 0; i < 2 * (ng); i++)                                       \
        (dst)[i] = pack2(geglu(ag[2 * i], ag[4 * (ng) + 2 * i]), geglu(ag[2 * i + 1], ag[4 * (ng) + 2 * i + 1]));
#define H_PUSH(h0, off) st_async4(rem_h + (off), H[h0], H[(h0) + 1], H[(h0) + 2], H[(h0) + 3], mapa(BAR(B_RECV2 + wgi), hr ^ 1));
#define F1_BLOCK(b, first)                                                                     \
    if ((first) && (b) < 2 && (b) >= EARLY) R_RELEASE(2);                                      \
    if (GB == 2 && (first) && (b) == 1) GAT_FETCH()                                                       \
    if ((first) && (b) == 2) PUSH_ACK();                                                       \
    R_WAIT();                                                                                  \
    if ((b) == PPB) { PP_WAIT() }                                                              \
    { DECL_DB(b, BASE128, HALF, 0)                                                             \
    wg_fence();                                                                                \
    FOR7(mma_rs128<1, D128(0, t)>(ag, AQ(A, b, t), (b) + t > 0, SWB(b, t, db, 0));             \
         if constexpr (first) { PREP(b, t, true) }); }                                         \
    wg_commit();                                                                               \
    if ((b) == 3) { PP_GO() }                                                                  \
    if ((b) > 0) { wg_wait<1>(); R_RELEASE(1); }       \
    R_NEXT();
                normalize<0>(A, k0, k1);
                F1_BLOCK(0, true) F1_BLOCK(1, true) F1_BLOCK(2, true) F1_BLOCK(3, true)
                if (t128 == 0) { mbar_expect_tx(BAR(B_RECV + wgi), 16384); mbar_expect_tx(BAR(B_RECV2 + wgi), 12288); }
                PUSH_BEGIN();
                wg_wait<0>();
                R_RELEASE(1);
                if (step == 1) R_NEXT();
                int p = 0;
#pragma unroll 1
                do {
                    STAMP(68 + p);
                    F1_EPI(H + 32, 8, ag)
                    STAMP(4 + p + so);
                    WSUM(81 + p + 7 * (step >> 1));
                    if (((trips >> (p + 1)) & 1) == 0) continue;
                    {
                        const uint32_t pk = (p ? hbuf + 16384 : sb + OFF_KVB + wgi * 8192) + w * 2048;
#pragma unroll
                        for (int k = 0; k < 4; k++) sts4(pk + k * 512 + lane * 16, H[32 + 4 * k], H[33 + 4 * k], H[34 + 4 * k], H[35 + 4 * k]);
                        fence_async();
                        __syncwarp();
                        asm volatile(ELECT "cp.async.bulk.shared::cluster.shared::cta.mbarrier::complete_tx::bytes [%0], [%1], 2048, [%2]; }"
                                     ::"r"(mapa(hbuf + p * 8192 + w * 2048, hr ^ 1)), "r"(pk), "r"(mapa(BAR(B_RECV + wgi), hr ^ 1)) : "memory");
                    }
                    kill<64>(ag);
                    F1_BLOCK(0, false) F1_BLOCK(1, false) F1_BLOCK(2, false) F1_BLOCK(3, false)
                    wg_wait<0>();
                    R_RELEASE(1);
                    kill<16>(H + 32);
                } while (((trips >> (++p)) & 1));
#pragma unroll
                for (int k = 0; k < 4; k++) lds4(H + 16 + 4 * k, hbuf + 16384 + w * 2048 + k * 512 + lane * 16);
                __syncwarp();
                if (lane == 0) asm volatile("mbarrier.arrive.shared::cluster.b64 _, [%0];" ::"r"(mapa(BAR(B_ACK2 + wgi), hr ^ 1)) : "memory");
                const uint32_t rem_h = mapa(hbuf + w * 2048 + lane * 16, hr ^ 1);
#define F1_LAST(b0)                                                                            \
    R_WAIT();                                                                                  \
    if (b0) { PP_WAIT() }                                                                      \
    { DECL_DB(b0, BASE64, HALF, 1)                                                             \
    wg_fence();                                                                                \
    FOR7(mma_rs64<1, D64(0, t)>(al, AQ(A, b0, t), (b0) + t > 0, SWB(b0, t, db, 1)));           \
    FOR7(mma_rs64<1, D64(7168, t)>(al, AQ(A, (b0) + 1, t), 1, db)); }                          \
    wg_commit();                                                                               \
    if (b0) { PP_GO() }                                                                        \
    R_NEXT();
                float al[32];
                F1_LAST(0)
                mbar_wait(BAR(B_RECV + wgi), rcvph);
                rcvph ^= 1;
                mbar_wait(BAR(B_ACK2 + wgi), step >> 1);
                H_PUSH(32, 16384) H_PUSH(36, 16896)
                F1_LAST(2)
                H_PUSH(40, 17408) H_PUSH(44, 17920)
                wg_wait<1>();
                R_RELEASE(2);
                wg_wait<0>();
                R_RELEASE(1);
                uint32_t HP[56];
#pragma unroll
                for (int k = 0; k < 4; k++) lds4(H + 4 * k, sb + OFF_KVB + wgi * 8192 + w * 2048 + k * 512 + lane * 16);
#pragma unroll
                for (int t = 0; t < 8; t++) lds4(HP + 4 * t, hbuf + (t >> 2) * 8192 + w * 2048 + (t & 3) * 512 + lane * 16);
                F1_EPI(H + 48, 4, al)
                H_PUSH(48, 24576 - w * 1024) H_PUSH(52, 25088 - w * 1024)
                STAMP(7 + so);
                WSUM(84 + 7 * (step >> 1));
                float acc[28];
                const uint32_t roA = hr ? 256u : 0u, roB = hr ? (uint32_t)-1536 : 0u;
                const uint32_t rpA = hr ? 0u : 256u, rpB = hr ? 0u : (uint32_t)-1536;
                float res[28];
                uint32_t v0[14], v1[14], P[14];
                const uint4* ps = xp0 + sl * 512;
#define F2_OWN_A()                                                                             \
    R_WAIT();                                                                                  \
    d0 = BASE128(0, 16, R_ADJ + roA); d1 = BASE128(0, 16, R_ADJ + roB);                        \
    wg_fence();                                                                                \
    FOR14(if constexpr (t < OT) mma_rs56<1, t * 128>(acc, H[4 * t], H[4 * t + 1], H[4 * t + 2], H[4 * t + 3], t > 0, d0)); \
    wg_commit();
#define F2_OWN_B()                                                                             \
    wg_fence();                                                                                \
    FOR14(if constexpr (t >= OT) mma_rs56<1, t * 128>(acc, H[4 * t], H[4 * t + 1], H[4 * t + 2], H[4 * t + 3], 1, t < 12 ? d0 : d1)); \
    wg_commit();                                                                               \
    R_NEXT();
#define F2_PEER()                                                                              \
    R_WAIT();                                                                                  \
    if (F2PP) { PP_WAIT() }                                                                    \
    d0 = BASE128(0, 16, R_ADJ + rpA); d1 = BASE128(0, 16, R_ADJ + rpB);                        \
    wg_fence();                                                                                \
    FOR14(mma_rs56<1, t * 128>(acc, HP[4 * t], HP[4 * t + 1], HP[4 * t + 2], HP[4 * t + 3], 1, t < 12 ? d0 : d1)); \
    wg_commit();                                                                               \
    if (F2PP) { PP_GO() }                                                                      \
    R_NEXT();
#define F2_TURN(u)                                                                             \
    wg_wait<1>();                                                                              \
    R_RELEASE(2);                                                                              \
    wg_wait<0>();                                                                              \
    R_RELEASE(1);                                                                              \
    _Pragma("unroll") for (int i = 0; i < 14; i++) P[i] = pack2(acc[2 * i], acc[2 * i + 1]);   \
    tag_slice(P, tag);                                                                         \
    asm volatile("" : RW4(P, 0), RW4(P, 4), RW4(P, 8), RW2(P, 12));                            \
    kill<28>(acc);                                                                             \
    F2_OWN_A()                                                                                 \
    if ((u) == 2) { slice_load<PL(3)>(v0, ps, lane); slice_load<PL(4)>(v1, ps, lane); } \
    send_slice<PL(3 + (u))>(xp0 + (2 * ((pr + (u) + 1) & 3) + hr) * 512, lane, P);             \
    seq++;                                                                                     \
    if (lane == 0) st_word(cx(sl), seq);                                                       \
    __syncwarp();                                                                              \
    STAMP(8 + (u) + so);                                                                       \
    F2_OWN_B()
                uint64_t d0, d1;
                F2_OWN_A()
                F2_OWN_B()
                R_WAIT();
                d0 = BASE128(0, 16, R_ADJ + rpA); d1 = BASE128(0, 16, R_ADJ + rpB);
                wg_fence();
                FOR8(mma_rs56<1, t * 128>(acc, HP[4 * t], HP[4 * t + 1], HP[4 * t + 2], HP[4 * t + 3], 1, d0));
                wg_commit();
                mbar_wait(BAR(B_RECV2 + wgi), step >> 1);
#pragma unroll
                for (int k = 0; k < 4; k++) lds4(HP + 32 + 4 * k, hbuf + 16384 + w * 2048 + k * 512 + lane * 16);
                lds4(HP + 48, hbuf + 24576 + w * 1024 + lane * 16);
                lds4(HP + 52, hbuf + 25088 + w * 1024 + lane * 16);
                if (step == 1) PUSH_ACK();
                wg_fence();
                FOR14(if constexpr (t >= 8) mma_rs56<1, t * 128>(acc, HP[4 * t], HP[4 * t + 1], HP[4 * t + 2], HP[4 * t + 3], 1, t < 12 ? d0 : d1));
                wg_commit();
                R_NEXT();
                F2_TURN(0)
                F2_PEER()
                F2_TURN(1)
                F2_PEER()
                F2_TURN(2)
                STAMP(64 + 8 * (step >> 1));
                slice_check<PL(3)>(v0, ps, lane, tag);
                slice_check<PL(4)>(v1, ps, lane, tag);
#pragma unroll
                for (int i = 0; i < 14; i++) { res[2 * i] = bf_lo(v0[i]) + bf_lo(v1[i]); res[2 * i + 1] = bf_hi(v0[i]) + bf_hi(v1[i]); }
                slice_load<PL(2)>(X, ps, lane);
                STAMP(65 + 8 * (step >> 1));
                const uint32_t cv = ld_word(cx(2 * ((pr + 1) & 3) + hr));
                F2_PEER()
                STAMP(66 + 8 * (step >> 1));
                check_cnt(cv, cx(2 * ((pr + 1) & 3) + hr), seq);
                STAMP(67 + 8 * (step >> 1));
                slice_load<PL(5)>(v0, ps, lane);
                x_fix(X, xbits);
                slice_check<PL(5)>(v0, ps, lane, tag);
#pragma unroll
                for (int i = 0; i < 14; i++) { res[2 * i] += bf_lo(v0[i]); res[2 * i + 1] += bf_hi(v0[i]); }
                STAMP(11 + so);
                wg_wait<0>();
                if (EARLYK >= 1) R_RELEASE(2);
                STAMP(12 + so);
                WSUM(85 + 7 * (step >> 1));
#pragma unroll
                for (int i = 0; i < 14; i++) X[i] = pack2(fmaf(res[2 * i] + acc[2 * i], 0.5f, bf_lo(X[i])), fmaf(res[2 * i + 1] + acc[2 * i + 1], 0.5f, bf_hi(X[i])));
            }
        }
        {
            const int m = lane >> 3, rr = lane & 7;
            const uint32_t ob = hbuf + w * 2048, rowa = ob + (rr + 8 * (m & 1)) * 112 + (m >> 1) * 16;
#pragma unroll
            for (int j = 0; j < 3; j++) stsm4(rowa + 32 * j, X[4 * j], X[4 * j + 1], X[4 * j + 2], X[4 * j + 3]);
            asm volatile("stmatrix.sync.aligned.m8n8.x2.shared.b16 [%0], {%1,%2};" ::"r"(ob + (rr + 8 * (m & 1)) * 112 + 96), "r"(X[12]), "r"(X[13]) : "memory");
            fence_async();
            __syncwarp();
            if (lane == 0) {
                asm volatile("cp.async.bulk.tensor.2d.global.shared::cta.bulk_group [%0, {%2, %3}], [%1];" ::"l"(&maps.out), "r"(ob), "r"(56 * sl), "r"(tile * 128 + (tid >> 5) * 16) : "memory");
                asm volatile("cp.async.bulk.commit_group;" ::: "memory");
                asm volatile("cp.async.bulk.wait_group.read 0;" ::: "memory");
            }
        }
        STAMP(50);
        GSTAMP(61);
        PDUMP();
    }
}

typedef CUresult (*EncodeFn)(CUtensorMap*, CUtensorMapDataType, cuuint32_t, void*, const cuuint64_t*, const cuuint64_t*, const cuuint32_t*,
                             const cuuint32_t*, CUtensorMapInterleave, CUtensorMapSwizzle, CUtensorMapL2promotion, CUtensorMapFloatOOBfill);

static void make_map(EncodeFn enc, CUtensorMap* m, const void* p, uint64_t cols, uint64_t rows, uint32_t bc, uint32_t br, CUtensorMapSwizzle sw) {
    cuuint64_t gd[2] = {cols, rows};
    cuuint64_t gs[1] = {cols * 2};
    cuuint32_t bd[2] = {bc, br};
    cuuint32_t es[2] = {1, 1};
    enc(m, CU_TENSOR_MAP_DATA_TYPE_BFLOAT16, 2, const_cast<void*>(p), gd, gs, bd, es, CU_TENSOR_MAP_INTERLEAVE_NONE, sw,
        CU_TENSOR_MAP_L2_PROMOTION_L2_128B, CU_TENSOR_MAP_FLOAT_OOB_FILL_NONE);
}

extern "C" void kernel_launch(void* const* d_in, const int* in_sizes, int n_in, void* d_out, int out_size) {
    (void)in_sizes; (void)n_in; (void)out_size;
    static EncodeFn enc = nullptr;
    static Scratch* scratch = nullptr;
    if (!enc) {
        void* fn = nullptr;
        cudaDriverEntryPointQueryResult qr;
        cudaGetDriverEntryPoint("cuTensorMapEncodeTiled", &fn, cudaEnableDefault, &qr);
        enc = (EncodeFn)fn;
        cudaGetSymbolAddress((void**)&scratch, g_scratch);
        cudaFuncSetAttribute(fused_kernel, cudaFuncAttributeMaxDynamicSharedMemorySize, SMEM_BYTES);
    }
    Maps maps;
    {
        cuuint64_t gd[3] = {64, 2048, 7};
        cuuint64_t gs[2] = {896, 128};
        cuuint32_t bd[3] = {64, 32, 7};
        cuuint32_t es[3] = {1, 1, 1};
        enc(&maps.x, CU_TENSOR_MAP_DATA_TYPE_BFLOAT16, 3, d_in[0], gd, gs, bd, es, CU_TENSOR_MAP_INTERLEAVE_NONE, CU_TENSOR_MAP_SWIZZLE_128B,
            CU_TENSOR_MAP_L2_PROMOTION_L2_128B, CU_TENSOR_MAP_FLOAT_OOB_FILL_NONE);
    }
    make_map(enc, &maps.out, d_out, 448, 2048, 56, 16, CU_TENSOR_MAP_SWIZZLE_NONE);
    make_map(enc, &maps.qkv, d_in[1], 1344, 448, 64, 112, CU_TENSOR_MAP_SWIZZLE_128B);
    make_map(enc, &maps.wo, d_in[3], 448, 448, 64, 112, CU_TENSOR_MAP_SWIZZLE_128B);
    make_map(enc, &maps.wg, d_in[5], 1792, 448, 64, 112, CU_TENSOR_MAP_SWIZZLE_128B);
    make_map(enc, &maps.wu, d_in[6], 1792, 448, 64, 112, CU_TENSOR_MAP_SWIZZLE_128B);
    make_map(enc, &maps.wg32, d_in[5], 1792, 448, 32, 112, CU_TENSOR_MAP_SWIZZLE_64B);
    make_map(enc, &maps.wu32, d_in[6], 1792, 448, 32, 112, CU_TENSOR_MAP_SWIZZLE_64B);
    make_map(enc, &maps.wd, d_in[7], 448, 1792, 64, 112, CU_TENSOR_MAP_SWIZZLE_128B);
    fused_kernel<<<128, 384, SMEM_BYTES>>>(scratch, (const __nv_bfloat16*)d_in[0], (const __nv_bfloat16*)d_in[2], 7, (const __nv_bfloat16*)d_in[5],
                                           (const __nv_bfloat16*)d_in[6], (const __nv_bfloat16*)d_in[7], maps);
}
```

```cpp
#include <cuda_runtime.h>
#include <cuda.h>
#include <cuda_bf16.h>
#include <stdint.h>
#include <type_traits>

#define LSTAT 1
#define ACAN 1
#define SPLIT0 1
#define OT 2
#define F2PP 0
#define PPK 2
#define QE 1
#define OST 1
#define GB 1
#define B3T 6
#define PP

namespace {

constexpr uint32_t STAGE = 28672, HALF = 14336;
constexpr int NST = 5;
constexpr uint32_t OFF_H = NST * STAGE;
constexpr uint32_t OFF_KVB = OFF_H + 2 * STAGE;
constexpr uint32_t OFF_WPHI = OFF_KVB + 16384;
constexpr uint32_t OFF_XR = OFF_WPHI + 7168;
constexpr uint32_t OFF_BAR = OFF_XR + 6144;
constexpr uint32_t SMEM_BYTES = OFF_BAR + 256 + 1536;
constexpr int B_EMPTY = NST, B_RECV = 2 * NST, B_RECV2 = B_RECV + 2, B_PACK = B_RECV2 + 2, B_GAT = B_PACK + 1, B_ACK = B_GAT + 8, B_ACK2 = B_ACK + 2, B_COUNT = B_ACK2 + 2;

constexpr int PACK = 14;

struct Maps { CUtensorMap x, qkv, wo, wg, wu, wg32, wu32, wd, out; };

}

constexpr int PLANE = 16 * 2 * 8 * 512;
struct Scratch {
    uint4 ex[6 * PLANE];
    uint4 kv1[8 * 16 * 16 * 32];
    uint4 kv2[8 * 512];
    uint32_t c1[8 * 8 * 16 * 32];
    uint32_t cw[8 * 32];
    uint4 wp[8 * 32 * (HALF / 16)];
};
__device__ __align__(1024) Scratch g_scratch;
#define g_ex (sc->ex)
#define g_kv1 (sc->kv1)
#define g_kv2 (sc->kv2)
#define g_c1 (sc->c1)
#define g_cw (sc->cw)
#define g_wp (sc->wp)
#define STAMP(i)
#define GSTAMP(i)
#define PDUMP()
#define ASTAMP(i)

namespace {

__device__ __forceinline__ int fresh_tid() { int t; asm volatile("mov.u32 %0, %%tid.x;" : "=r"(t)); return t; }
__device__ __forceinline__ uint4* again(uint4* p) { asm volatile("" : "+l"(p)); return p; }
template <int N> __device__ __forceinline__ void kill(uint32_t* v) {
#pragma unroll
    for (int i = 0; i < N; i++) v[i] = 0;
}
template <int N> __device__ __forceinline__ void kill(float* v) {
#pragma unroll
    for (int i = 0; i < N; i++) v[i] = 0.f;
}
__device__ __forceinline__ uint32_t s2u(const void* p) { return (uint32_t)__cvta_generic_to_shared(p); }
__device__ __forceinline__ void mbar_init(uint32_t a, uint32_t c) { asm volatile("mbarrier.init.shared::cta.b64 [%0], %1;" ::"r"(a), "r"(c) : "memory"); }
__device__ __forceinline__ void mbar_expect_tx(uint32_t a, uint32_t b) { asm volatile("mbarrier.arrive.expect_tx.shared::cta.b64 _, [%0], %1;" ::"r"(a), "r"(b) : "memory"); }
__device__ __forceinline__ void mbar_arrive(uint32_t a) { asm volatile("mbarrier.arrive.shared::cta.b64 _, [%0];" ::"r"(a) : "memory"); }
#define GIVE_UP(id) "trap;\n"
#define SPIN_MAX "0x400000"
#define SPIN_TAIL(id) "add.u32 n, n, 1;\n setp.lt.u32 p, n, " SPIN_MAX ";\n @p bra.uni LP;\n" GIVE_UP(id) " DN:\n }"
__device__ __forceinline__ void mbar_wait(uint32_t a, uint32_t ph) {
    asm volatile("{ .reg .pred p; .reg .b32 n; mov.u32 n, 0;\n LP:\n"
                 "mbarrier.try_wait.parity.shared::cta.b64 p, [%0], %1;\n @p bra DN;\n"
                 "add.u32 n, n, 1;\n setp.lt.u32 p, n, " SPIN_MAX ";\n @p bra LP;\n"
                 GIVE_UP("")
                 " DN:\n }" ::"r"(a), "r"(ph) : "memory");
}
#define ELECT "{ .reg .pred e; elect.sync _|e, 0xffffffff; @e "
__device__ __forceinline__ void tma2d(uint32_t dst, const CUtensorMap* m, int c0, int c1, uint32_t bar) {
    asm volatile(ELECT "cp.async.bulk.tensor.2d.shared::cluster.global.mbarrier::complete_tx::bytes [%0], [%1, {%3, %4}], [%2]; }" ::"r"(dst), "l"(m), "r"(bar), "r"(c0), "r"(c1) : "memory");
}
__device__ __forceinline__ void tma3x(uint32_t dst, const CUtensorMap* m, int row, uint32_t bar) {
    asm volatile(ELECT "cp.async.bulk.tensor.3d.shared::cluster.global.mbarrier::complete_tx::bytes [%0], [%1, {0, %3, 0}], [%2]; }" ::"r"(dst), "l"(m), "r"(bar), "r"(row) : "memory");
}
template <int OFF>
__device__ __forceinline__ void ld_pkt(uint32_t* v, const uint4* p) {
    asm volatile("{ .reg .b128 t; ld.relaxed.gpu.global.b128 t, [%4+%5]; mov.b128 {%0,%1,%2,%3}, t; }" : "=r"(v[0]), "=r"(v[1]), "=r"(v[2]), "=r"(v[3]) : "l"(p), "n"(OFF * 16) : "memory");
}
template <int OFF>
__device__ __forceinline__ void st_pkt(uint4* p, uint32_t a, uint32_t b, uint32_t c, uint32_t d) {
    asm volatile("{ .reg .b128 t; mov.b128 t, {%1,%2,%3,%4}; st.relaxed.gpu.global.b128 [%0+%5], t; }" ::"l"(p), "r"(a), "r"(b), "r"(c), "r"(d), "n"(OFF * 16) : "memory");
}
__device__ __forceinline__ uint32_t pack2(float lo, float hi) {
    uint32_t r;
    asm("cvt.rn.bf16x2.f32 %0, %1, %2;" : "=r"(r) : "f"(hi), "f"(lo));
    return r;
}
__device__ __forceinline__ float bf_lo(uint32_t w) { return __uint_as_float(w << 16); }
__device__ __forceinline__ float bf_hi(uint32_t w) { return __uint_as_float(w & 0xffff0000u); }
__device__ __forceinline__ uint32_t settag(uint32_t w, uint32_t tag) { return (w & ~1u) | tag; }
__device__ __forceinline__ float ex2(float x) { float y; asm("ex2.approx.ftz.f32 %0, %1;" : "=f"(y) : "f"(x)); return y; }
__device__ __forceinline__ float rcp(float x) { float y; asm("rcp.approx.ftz.f32 %0, %1;" : "=f"(y) : "f"(x)); return y; }
__device__ __forceinline__ float tanh_hw(float x) { float y; asm("tanh.approx.f32 %0, %1;" : "=f"(y) : "f"(x)); return y; }
__device__ __forceinline__ void stsm4(uint32_t addr, uint32_t a, uint32_t b, uint32_t c, uint32_t d) {
    asm volatile("stmatrix.sync.aligned.m8n8.x4.shared.b16 [%0], {%1,%2,%3,%4};" ::"r"(addr), "r"(a), "r"(b), "r"(c), "r"(d) : "memory");
}
__device__ __forceinline__ void fence_async() { asm volatile("fence.proxy.async.shared::cta;" ::: "memory"); }
__device__ __forceinline__ void bar_sync(int id, int n) { asm volatile("bar.sync %0, %1;" ::"r"(id), "r"(n) : "memory"); }
__device__ __forceinline__ void bar_arrive(int id, int n) { asm volatile("bar.arrive %0, %1;" ::"r"(id), "r"(n) : "memory"); }
__device__ __forceinline__ void wg_fence() { asm volatile("wgmma.fence.sync.aligned;" ::: "memory"); }
__device__ __forceinline__ void wg_commit() { asm volatile("wgmma.commit_group.sync.aligned;" ::: "memory"); }
template <int N> __device__ __forceinline__ void wg_wait() { asm volatile("wgmma.wait_group.sync.aligned %0;" ::"n"(N) : "memory"); }

constexpr uint32_t SB0 = 1024;
__host__ __device__ constexpr uint32_t dlo(uint32_t off, uint32_t lbo) { return ((SB0 + off) >> 4) | ((lbo >> 4) << 16); }
__host__ __device__ constexpr uint32_t dhi(uint32_t sbo, uint32_t sw) { return (sbo >> 4) | (sw << 30); }
__device__ __forceinline__ uint64_t dbase(uint32_t lo, uint32_t hi) { uint64_t d; asm volatile("mov.b64 %0, {%1, %2};" : "=l"(d) : "r"(lo), "r"(hi)); return d; }
#define BASE128(off, lbo, adj) dbase(dlo(off, lbo) + (adj), dhi(1024, 1))
#define BASE64(off, lbo, adj) dbase(dlo(off, lbo) + (adj), dhi(512, 2))

#define ACC4(d, o) "+f"(d[o]), "+f"(d[o + 1]), "+f"(d[o + 2]), "+f"(d[o + 3])
#define ACC28(d) ACC4(d, 0), ACC4(d, 4), ACC4(d, 8), ACC4(d, 12), ACC4(d, 16), ACC4(d, 20), ACC4(d, 24)
#define ACC32(d, o) ACC4(d, o), ACC4(d, o + 4), ACC4(d, o + 8), ACC4(d, o + 12), ACC4(d, o + 16), ACC4(d, o + 20), ACC4(d, o + 24), ACC4(d, o + 28)

template <int TB, uint64_t D>
__device__ __forceinline__ void mma_rs56(float* d, uint32_t a0, uint32_t a1, uint32_t a2, uint32_t a3, int sd, uint64_t base) {
    asm volatile("{ .reg .pred p; .reg .b64 db; setp.ne.b32 p, %32, 0; add.u64 db, %33, %34;\n"
                 "wgmma.mma_async.sync.aligned.m64n56k16.f32.bf16.bf16 "
                 "{%0,%1,%2,%3,%4,%5,%6,%7,%8,%9,%10,%11,%12,%13,%14,%15,%16,%17,%18,%19,%20,%21,%22,%23,%24,%25,%26,%27}, "
                 "{%28,%29,%30,%31}, db, p, 1, 1, %35; }\n"
                 : ACC28(d)
                 : "r"(a0), "r"(a1), "r"(a2), "r"(a3), "r"(sd), "l"(base), "n"(D), "n"(TB));
}
template <int TB, uint64_t D>
__device__ __forceinline__ void mma_rs64(float* d, uint32_t a0, uint32_t a1, uint32_t a2, uint32_t a3, int sd, uint64_t base) {
    asm volatile("{ .reg .pred p; .reg .b64 db; setp.ne.b32 p, %36, 0; add.u64 db, %37, %38;\n"
                 "wgmma.mma_async.sync.aligned.m64n64k16.f32.bf16.bf16 "
                 "{%0,%1,%2,%3,%4,%5,%6,%7,%8,%9,%10,%11,%12,%13,%14,%15,%16,%17,%18,%19,%20,%21,%22,%23,%24,%25,%26,%27,%28,%29,%30,%31}, "
                 "{%32,%33,%34,%35}, db, p, 1, 1, %39; }\n"
                 : ACC32(d, 0)
                 : "r"(a0), "r"(a1), "r"(a2), "r"(a3), "r"(sd), "l"(base), "n"(D), "n"(TB));
}
template <int TB, uint64_t D>
__device__ __forceinline__ void mma_rs128(float* d, uint32_t a0, uint32_t a1, uint32_t a2, uint32_t a3, int sd, uint64_t base) {
    asm volatile("{ .reg .pred p; .reg .b64 db; setp.ne.b32 p, %68, 0; add.u64 db, %69, %70;\n"
                 "wgmma.mma_async.sync.aligned.m64n128k16.f32.bf16.bf16 "
                 "{%0,%1,%2,%3,%4,%5,%6,%7,%8,%9,%10,%11,%12,%13,%14,%15,%16,%17,%18,%19,%20,%21,%22,%23,%24,%25,%26,%27,%28,%29,%30,%31,%32,%33,%34,%35,%36,%37,%38,%39,%40,%41,%42,%43,%44,%45,%46,%47,%48,%49,%50,%51,%52,%53,%54,%55,%56,%57,%58,%59,%60,%61,%62,%63}, "
                 "{%64,%65,%66,%67}, db, p, 1, 1, %71; }\n"
                 : ACC32(d, 0), ACC32(d, 32)
                 : "r"(a0), "r"(a1), "r"(a2), "r"(a3), "r"(sd), "l"(base), "n"(D), "n"(TB));
}
template <uint64_t DA, uint64_t DB>
__device__ __forceinline__ void mma_ss56_tt(float* d, int sd, uint64_t ba, uint64_t bb) {
    asm volatile("{ .reg .pred p; .reg .b64 da, db; setp.ne.b32 p, %28, 0; add.u64 da, %29, %31; add.u64 db, %30, %32;\n"
                 "wgmma.mma_async.sync.aligned.m64n56k16.f32.bf16.bf16 "
                 "{%0,%1,%2,%3,%4,%5,%6,%7,%8,%9,%10,%11,%12,%13,%14,%15,%16,%17,%18,%19,%20,%21,%22,%23,%24,%25,%26,%27}, "
                 "da, db, p, 1, 1, 1, 1; }\n"
                 : ACC28(d)
                 : "r"(sd), "l"(ba), "l"(bb), "n"(DA), "n"(DB));
}
template <int... I> struct Seq {};
template <class F, int... I> __device__ __forceinline__ void static_for_impl(F&& f, Seq<I...>) { (f(std::integral_constant<int, I>{}), ...); }
#define FOR7(...) static_for_impl([&](auto T_) { constexpr int t = decltype(T_)::value; __VA_ARGS__; }, Seq<0, 1, 2, 3, 4, 5, 6>{})
#define FOR8(...) static_for_impl([&](auto T_) { constexpr int t = decltype(T_)::value; __VA_ARGS__; }, Seq<0, 1, 2, 3, 4, 5, 6, 7>{})
#define FOR14(...) static_for_impl([&](auto T_) { constexpr int t = decltype(T_)::value; __VA_ARGS__; }, Seq<0, 1, 2, 3, 4, 5, 6, 7, 8, 9, 10, 11, 12, 13>{})

__device__ __forceinline__ int kblk(int p, int b) { return b == 0 ? p : b - (b <= p); }
__host__ __device__ constexpr int krow(int t) { return t < 3 ? 16 * t : (t < 6 ? 56 + 16 * (t - 3) : 48); }
#define AQ(A, b, t) ((t) < 3 ? A[2 * (b)][4 * (t)] : (t) < 6 ? A[2 * (b) + 1][4 * ((t) - 3)] : A[2 * (b)][12]), \
                    ((t) < 3 ? A[2 * (b)][4 * (t) + 1] : (t) < 6 ? A[2 * (b) + 1][4 * ((t) - 3) + 1] : A[2 * (b)][13]), \
                    ((t) < 3 ? A[2 * (b)][4 * (t) + 2] : (t) < 6 ? A[2 * (b) + 1][4 * ((t) - 3) + 2] : A[2 * (b) + 1][12]), \
                    ((t) < 3 ? A[2 * (b)][4 * (t) + 3] : (t) < 6 ? A[2 * (b) + 1][4 * ((t) - 3) + 3] : A[2 * (b) + 1][13])
#define D128(off, t) ((uint64_t)(((off) + krow(t) * 128) >> 4) + ((uint64_t)((t) == 6 ? (7168 - 1024) >> 4 : 0) << 32))
#define D64(off, t) ((uint64_t)(((off) + krow(t) * 64) >> 4) + ((uint64_t)((t) == 6 ? (3584 - 512) >> 4 : 0) << 32))

#define PL(k) (((k) - 3) * PLANE)
__device__ __forceinline__ void st_word(uint32_t* p, uint32_t v) { asm volatile("st.relaxed.gpu.global.u32 [%0], %1;" ::"l"(p), "r"(v) : "memory"); }
__device__ __forceinline__ uint32_t ld_word(const uint32_t* p) { uint32_t v; asm volatile("ld.relaxed.gpu.global.u32 %0, [%1];" : "=r"(v) : "l"(p) : "memory"); return v; }
__device__ __forceinline__ void tag_slice(uint32_t* w, uint32_t tag) { w[0] = settag(w[0], tag); w[4] = settag(w[4], tag); w[8] = settag(w[8], tag); w[12] = settag(w[12], tag); }
template <int O>
__device__ __forceinline__ void send_slice(uint4* dst, int lane, const uint32_t* w) {
    st_pkt<O>(dst, w[0], w[1], w[2], w[3]);
    st_pkt<O + 32>(dst, w[4], w[5], w[6], w[7]);
    st_pkt<O + 64>(dst, w[8], w[9], w[10], w[11]);
    asm volatile("{ .reg .b64 t; mov.b64 t, {%1,%2}; st.relaxed.gpu.global.b64 [%0+%3], t; }" ::"l"((char*)dst - lane * 8), "r"(w[12]), "r"(w[13]), "n"(16 * (O + 96)) : "memory");
}
#define RW4(v, o) "+r"(v[o]), "+r"(v[(o) + 1]), "+r"(v[(o) + 2]), "+r"(v[(o) + 3])
#define RW2(v, o) "+r"(v[o]), "+r"(v[(o) + 1])
#define WR4(v, o) "=&r"(v[o]), "=&r"(v[(o) + 1]), "=&r"(v[(o) + 2]), "=&r"(v[(o) + 3])
#define LDP(a, b, c, d, addr, off) "ld.relaxed.gpu.global.b128 q, [" addr "+" off "];\n mov.b128 {" a "," b "," c "," d "}, q;\n"
#define LDH(a, b, addr, off) "ld.relaxed.gpu.global.b64 h, [" addr "+" off "];\n mov.b64 {" a "," b "}, h;\n"
#define VOTE_OK "and.b32 t, t, 1;\n setp.ne.u32 p, t, 0;\n vote.sync.any.pred p, p, 0xffffffff;\n @!p bra.uni DN;\n"
#define CHK(x, tag) "lop3.b32 t, " x ", " tag ", t, 0xBE;\n"
__device__ __forceinline__ void check_cnt(uint32_t v, const uint32_t* p, uint32_t target) {
    asm volatile("{ .reg .pred p; .reg .b32 n, t; mov.u32 n, 0; mov.u32 t, %2;\n LP:\n"
                 "sub.s32 t, t, %1;\n setp.lt.s32 p, t, 0;\n vote.sync.any.pred p, p, 0xffffffff;\n @!p bra.uni DN;\n ld.relaxed.gpu.global.u32 t, [%0];\n" SPIN_TAIL("7")
                 ::"l"(p), "r"(target), "r"(v) : "memory");
}
__device__ __forceinline__ void poll_cnt(const uint32_t* p, uint32_t target) {
    asm volatile("{ .reg .pred p; .reg .b32 n, t; mov.u32 n, 0;\n LP:\n"
                 "ld.relaxed.gpu.global.u32 t, [%0];\n sub.s32 t, t, %1;\n setp.lt.s32 p, t, 0;\n vote.sync.any.pred p, p, 0xffffffff;\n @!p bra.uni DN;\n" SPIN_TAIL("1")
                 ::"l"(p), "r"(target) : "memory");
}
template <int STR>
__device__ __forceinline__ void poll4_kv(uint32_t* v, const uint4* p, uint32_t tag) {
    asm volatile("{ .reg .pred p; .reg .b32 n, t; .reg .b128 q; mov.u32 n, 0;\n LP:\n"
                 LDP("%0", "%1", "%2", "%3", "%16", "0") LDP("%4", "%5", "%6", "%7", "%16", "%18")
                 LDP("%8", "%9", "%10", "%11", "%16", "%19") LDP("%12", "%13", "%14", "%15", "%16", "%20")
                 "xor.b32 t, %0, %17;\n" CHK("%4", "%17") CHK("%8", "%17") CHK("%12", "%17") VOTE_OK SPIN_TAIL("2")
                 : WR4(v, 0), WR4(v, 4), WR4(v, 8), WR4(v, 12)
                 : "l"(p), "r"(tag), "n"(16 * STR), "n"(32 * STR), "n"(48 * STR)
                 : "memory");
}
template <int B>
__device__ __forceinline__ void blk_load(uint32_t (&A)[8][14], const uint4* src, int lane) {
    ld_pkt<0>(&A[2 * B][0], src); ld_pkt<32>(&A[2 * B][4], src); ld_pkt<64>(&A[2 * B][8], src);
    ld_pkt<512>(&A[2 * B + 1][0], src); ld_pkt<544>(&A[2 * B + 1][4], src); ld_pkt<576>(&A[2 * B + 1][8], src);
    asm volatile("{ .reg .b64 h;\n" LDH("%0", "%1", "%4", "1536") LDH("%2", "%3", "%4", "9728") "}"
                 : "=&r"(A[2 * B][12]), "=&r"(A[2 * B][13]), "=&r"(A[2 * B + 1][12]), "=&r"(A[2 * B + 1][13])
                 : "l"((const char*)src - lane * 8) : "memory");
}
template <int B>
__device__ __forceinline__ void blk_check(uint32_t (&A)[8][14], const uint4* src, int lane, uint32_t tag) {
    asm volatile("{ .reg .pred p; .reg .b32 n, t; .reg .b128 q; .reg .b64 h, a8; mov.u32 n, 0;\n LP:\n"
                 "xor.b32 t, %0, %30;\n" CHK("%4", "%30") CHK("%8", "%30") CHK("%12", "%30") CHK("%16", "%30") CHK("%20", "%30") CHK("%24", "%30") CHK("%26", "%30") VOTE_OK
                 LDP("%0", "%1", "%2", "%3", "%28", "0") LDP("%4", "%5", "%6", "%7", "%28", "512") LDP("%8", "%9", "%10", "%11", "%28", "1024")
                 LDP("%12", "%13", "%14", "%15", "%28", "8192") LDP("%16", "%17", "%18", "%19", "%28", "8704") LDP("%20", "%21", "%22", "%23", "%28", "9216")
                 "mad.wide.s32 a8, %29, -8, %28;\n" LDH("%24", "%25", "a8", "1536") LDH("%26", "%27", "a8", "9728") SPIN_TAIL("3")
                 "\n and.b32 %0, %0, -2; and.b32 %4, %4, -2; and.b32 %8, %8, -2; and.b32 %12, %12, -2; and.b32 %16, %16, -2; and.b32 %20, %20, -2; and.b32 %24, %24, -2; and.b32 %26, %26, -2;"
                 : RW4(A[2 * B], 0), RW4(A[2 * B], 4), RW4(A[2 * B], 8), RW4(A[2 * B + 1], 0), RW4(A[2 * B + 1], 4), RW4(A[2 * B + 1], 8),
                   RW2(A[2 * B], 12), RW2(A[2 * B + 1], 12)
                 : "l"(src), "r"(lane), "r"(tag)
                 : "memory");
}
__device__ __forceinline__ void st_async4(uint32_t a, uint32_t x, uint32_t y, uint32_t z, uint32_t w, uint32_t bar) {
    asm volatile("st.async.weak.shared::cluster.mbarrier::complete_tx::bytes.v4.b32 [%0], {%1,%2,%3,%4}, [%5];" ::"r"(a), "r"(x), "r"(y), "r"(z), "r"(w), "r"(bar) : "memory");
}
__device__ __forceinline__ uint32_t mapa(uint32_t a, uint32_t cta) { uint32_t r; asm("mapa.shared::cluster.u32 %0, %1, %2;" : "=r"(r) : "r"(a), "r"(cta)); return r; }
__device__ __forceinline__ void stat_load(uint32_t* v, const uint4* p) { ld_pkt<0>(v, p); ld_pkt<512>(v + 4, p); }
__device__ __forceinline__ void stat_check(uint32_t* v, const uint4* p, uint32_t tag) {
    asm volatile("{ .reg .pred p; .reg .b32 n, t; .reg .b128 q; mov.u32 n, 0;\n LP:\n"
                 "xor.b32 t, %3, %9;\n" CHK("%7", "%9") VOTE_OK
                 LDP("%0", "%1", "%2", "%3", "%8", "0") LDP("%4", "%5", "%6", "%7", "%8", "8192") SPIN_TAIL("4")
                 : RW4(v, 0), RW4(v, 4) : "l"(p), "r"(tag) : "memory");
}
__device__ __forceinline__ uint32_t x_bits(const uint32_t* X) {
    uint32_t r;
    asm volatile("{ .reg .b32 a, b; prmt.b32 a, %1, %2, 0x0040; prmt.b32 b, %3, %4, 0x0040; prmt.b32 %0, a, b, 0x5410; }" : "=r"(r) : "r"(X[0]), "r"(X[4]), "r"(X[8]), "r"(X[12]));
    return r;
}
template <int O>
__device__ __forceinline__ void slice_load(uint32_t* v, const uint4* p, int lane) {
    ld_pkt<O>(v, p); ld_pkt<O + 32>(v + 4, p); ld_pkt<O + 64>(v + 8, p);
    asm volatile("{ .reg .b64 h;\n" LDH("%0", "%1", "%2", "%3") "}" : "=r"(v[12]), "=r"(v[13]) : "l"((const char*)p - lane * 8), "n"(16 * (O + 96)) : "memory");
}
template <int O>
__device__ __forceinline__ void slice_check(uint32_t* v, const uint4* p, int lane, uint32_t tag) {
    asm volatile("{ .reg .pred p; .reg .b32 n, t; .reg .b128 q; .reg .b64 h; mov.u32 n, 0;\n LP:\n"
                 "xor.b32 t, %0, %16;\n" CHK("%4", "%16") CHK("%8", "%16") CHK("%12", "%16") VOTE_OK
                 LDP("%0", "%1", "%2", "%3", "%14", "%17") LDP("%4", "%5", "%6", "%7", "%14", "%18") LDP("%8", "%9", "%10", "%11", "%14", "%19")
                 LDH("%12", "%13", "%15", "%20") SPIN_TAIL("5")
                 : RW4(v, 0), RW4(v, 4), RW4(v, 8), RW2(v, 12)
                 : "l"(p), "l"((const char*)p - lane * 8), "r"(tag), "n"(16 * O), "n"(16 * (O + 32)), "n"(16 * (O + 64)), "n"(16 * (O + 96))
                 : "memory");
}
__device__ __forceinline__ void x_fix(uint32_t* X, uint32_t bits) {
    X[0] = __byte_perm(X[0], bits, 0x3214); X[4] = __byte_perm(X[4], bits, 0x3215); X[8] = __byte_perm(X[8], bits, 0x3216); X[12] = __byte_perm(X[12], bits, 0x3217);
}
__device__ __forceinline__ void sts4(uint32_t a, uint32_t x, uint32_t y, uint32_t z, uint32_t w) {
    asm volatile("st.shared.v4.u32 [%0], {%1,%2,%3,%4};" ::"r"(a), "r"(x), "r"(y), "r"(z), "r"(w) : "memory");
}
__device__ __forceinline__ void lds4(uint32_t* v, uint32_t a) {
    asm volatile("ld.shared.v4.u32 {%0,%1,%2,%3}, [%4];" : "=r"(v[0]), "=r"(v[1]), "=r"(v[2]), "=r"(v[3]) : "r"(a) : "memory");
}
struct LnCoef { uint32_t hi, lo, sh; };
__device__ __forceinline__ LnCoef ln_coef(float sum, float sq) {
    sum += __shfl_xor_sync(0xffffffffu, sum, 1); sq += __shfl_xor_sync(0xffffffffu, sq, 1);
    sum += __shfl_xor_sync(0xffffffffu, sum, 2); sq += __shfl_xor_sync(0xffffffffu, sq, 2);
    const float mean = sum * (1.f / 448.f);
    const float var = fmaxf(fmaf(-mean, mean, sq * (1.f / 448.f)), 0.f);
    const float sc = rsqrtf(var + 1e-5f);
    LnCoef r;
    r.hi = pack2(sc, sc);
    const float lo = sc - bf_lo(r.hi), sh = -mean * sc;
    r.lo = pack2(lo, lo);
    r.sh = pack2(sh, sh);
    return r;
}
template <int B>
__device__ __forceinline__ void normalize(uint32_t (&A)[8][14], const LnCoef& c0, const LnCoef& c1) {
#pragma unroll
    for (int s = 2 * B; s < 2 * B + 2; s++)
#pragma unroll
        for (int i = 0; i < 14; i++) {
            const LnCoef& k = (i & 1) ? c1 : c0;
            asm("{ .reg .b32 t; fma.rn.bf16x2 t, %0, %2, %3; fma.rn.bf16x2 %0, %0, %1, t; }" : "+r"(A[s][i]) : "r"(k.hi), "r"(k.lo), "r"(k.sh));
        }
}
__device__ __forceinline__ void slice_stats(const uint32_t* w, float* st) {
    float a = 0.f, b = 0.f, p = 0.f, q = 0.f;
#pragma unroll
    for (int i = 0; i < 7; i++) {
        const float e0 = bf_lo(w[2 * i]), e1 = bf_hi(w[2 * i]), e2 = bf_lo(w[2 * i + 1]), e3 = bf_hi(w[2 * i + 1]);
        a += e0 + e1; b += e2 + e3;
        p = fmaf(e0, e0, p); p = fmaf(e1, e1, p); q = fmaf(e2, e2, q); q = fmaf(e3, e3, q);
    }
    a += __shfl_xor_sync(0xffffffffu, a, 1); p += __shfl_xor_sync(0xffffffffu, p, 1); b += __shfl_xor_sync(0xffffffffu, b, 1); q += __shfl_xor_sync(0xffffffffu, q, 1);
    a += __shfl_xor_sync(0xffffffffu, a, 2); p += __shfl_xor_sync(0xffffffffu, p, 2); b += __shfl_xor_sync(0xffffffffu, b, 2); q += __shfl_xor_sync(0xffffffffu, q, 2);
    st[0] = a; st[1] = p; st[2] = b; st[3] = q;
}
__device__ __forceinline__ void dual_softmax(const float* p, uint32_t* out) {
    constexpr float L = 1.4426950408889634f;
#pragma unroll
    for (int r = 0; r < 2; r++) {
        float mx = fmaxf(p[2 * r], p[2 * r + 1]), mn = fminf(p[2 * r], p[2 * r + 1]);
#pragma unroll
        for (int i = 1; i < 7; i++) {
            mx = fmaxf(mx, fmaxf(p[4 * i + 2 * r], p[4 * i + 2 * r + 1]));
            mn = fminf(mn, fminf(p[4 * i + 2 * r], p[4 * i + 2 * r + 1]));
        }
        mx = fmaxf(mx, __shfl_xor_sync(0xffffffffu, mx, 1));
        mn = fminf(mn, __shfl_xor_sync(0xffffffffu, mn, 1));
        const float bx = -mx * L, bn = mn * L;
        float ep[14], en[14], sp = 0.f, sn = 0.f;
#pragma unroll
        for (int i = 0; i < 14; i++) {
            const float v = p[4 * (i >> 1) + 2 * r + (i & 1)];
            ep[i] = ex2(fmaf(v, L, bx));
            en[i] = ex2(fmaf(v, -L, bn));
            sp += ep[i]; sn += en[i];
        }
        sp += __shfl_xor_sync(0xffffffffu, sp, 1);
        sn += __shfl_xor_sync(0xffffffffu, sn, 1);
        const float ip = rcp(sp), in = rcp(sn);
#pragma unroll
        for (int i = 0; i < 7; i++) {
            out[4 * i + r] = pack2(ep[2 * i] * ip, ep[2 * i + 1] * ip);
            out[4 * i + 2 + r] = pack2(en[2 * i] * in, en[2 * i + 1] * in);
        }
    }
}
__device__ __forceinline__ float geglu(float g, float u) {
    const float t = tanh_hw(g * fmaf(g * g, 0.7978845608028654f * 0.044715f, 0.7978845608028654f));
    const float gu = g * u;
    return fmaf(t, gu, gu);
}
__device__ __forceinline__ void phi_gemm(const float* t, float* p) {
    uint32_t w[14];
#pragma unroll
    for (int i = 0; i < 14; i++) w[i] = pack2(t[2 * i], t[2 * i + 1]);
    const uint64_t db = BASE128(OFF_WPHI, 16, 0);
    wg_fence();
    mma_rs56<0, 0>(p, w[0], w[1], w[2], w[3], 0, db);
    mma_rs56<0, 2>(p, w[4], w[5], w[6], w[7], 1, db);
    mma_rs56<0, 4>(p, w[8], w[9], w[10], w[11], 1, db);
    mma_rs56<0, 6>(p, w[12], w[13], 0u, 0u, 1, db);
    wg_commit();
    wg_wait<0>();
}

}

#define BAR(i) (bars + 8 * (i))
#define R_WAIT() mbar_wait(BAR(slot), ph)
#define WSUM(i)
#define R_ADJ (slot * (STAGE >> 4))
#define R_NEXT() do { eb2 = eb1; eb1 = BAR(B_EMPTY + slot); if (++slot == NST) { slot = 0; ph ^= 1; } } while (0)
#define R_RELEASE(k) do { if (lane == 0) mbar_arrive((k) == 1 ? eb1 : eb2); } while (0)
#define PUSH_BEGIN() do { mbar_wait(BAR(B_ACK + wgi), ackph); ackph ^= 1; } while (0)
#define PUSH_ACK() do { __syncwarp(); if (lane == 0) asm volatile("mbarrier.arrive.shared::cluster.b64 _, [%0];" ::"r"(mapa(BAR(B_ACK + wgi), hr ^ 1)) : "memory"); } while (0)

__global__ void __cluster_dims__(2, 1, 1) __launch_bounds__(384, 1)
fused_kernel(Scratch* const sc, const __nv_bfloat16* __restrict__ x_in, const __nv_bfloat16* __restrict__ w_phi, const int trips,
             const __nv_bfloat16* __restrict__ wg, const __nv_bfloat16* __restrict__ wu, const __nv_bfloat16* __restrict__ wd,
             const __grid_constant__ Maps maps) {
    extern __shared__ __align__(1024) unsigned char smem_raw[];
    const uint32_t sb = s2u(smem_raw);
    const uint32_t bars = sb + OFF_BAR;
    const int wgi = __shfl_sync(0xffffffffu, threadIdx.x >> 7, 0);
    const int hr = blockIdx.x & 1, ck = blockIdx.x >> 1;
    const int gp = (ck - 4) & 7, q7 = ((ck - 36) * 37) >> 8;
    const int pr = ck < 4 ? ck : (ck < 36 ? (ck - 4) >> 3 : q7);
    const int tile = ck < 4 ? 0 : (ck < 36 ? (gp ? 2 * gp : 1) : 2 * (ck - 36 - 7 * q7) + 3);
    const int sl = 2 * pr + hr;
    STAMP(0);
    GSTAMP(60);
    if (threadIdx.x == 256) {
#pragma unroll
        for (int i = 0; i < NST; i++) mbar_init(BAR(i), 1);
        asm volatile("fence.mbarrier_init.release.cluster;" ::: "memory");
    }
    if (threadIdx.x == 288) {
        if ((sb & 0x3FFFF) != SB0) asm volatile("trap;");
#pragma unroll
        for (int i = NST; i < B_COUNT; i++) mbar_init(BAR(i), i >= B_ACK ? 4 : (i < B_RECV ? 8 : 1));
        asm volatile("fence.mbarrier_init.release.cluster;" ::: "memory");
    }
    __syncwarp();
    asm volatile("barrier.cluster.arrive.relaxed.aligned;" ::: "memory");

    if (wgi == 2) {
        asm volatile("setmaxnreg.dec.sync.aligned.u32 40;");
        const int t128 = fresh_tid() & 127, w = __shfl_sync(0xffffffffu, t128 >> 5, 0), lane = t128 & 31;
        uint32_t e0[2] = {0, 0}, e1[2] = {0, 0}, cw_target = 0;
        if (w == 0) {
#define SORD 0
#pragma unroll 1
            for (int i = 0; i < NST; i++) {
                const int n = SORD == 2 ? (i + 2) % NST : (SORD == 3 ? (i == 0 ? 2 : (i < 3 ? i - 1 : i)) : i);
                const uint32_t dst = sb + n * STAGE, fb = BAR(n);
                asm volatile(ELECT "mbarrier.arrive.expect_tx.shared::cta.b64 _, [%0], %1; }" ::"r"(fb), "r"(n < 2 ? 2 * STAGE : STAGE) : "memory");
                if (n < 2) {
                    tma3x(sb + OFF_H + n * STAGE, &maps.x, tile * 128 + n * 64, fb);
                    tma3x(dst, &maps.x, tile * 128 + n * 64 + 32, fb);
                } else {
                    if (SORD == 0 && n == 3) mbar_wait(BAR(1), 0);
                    const int ra = 112 * (n - 2);
                    tma2d(dst, &maps.qkv, 448 + 56 * sl, ra, fb);
                    tma2d(dst + HALF, &maps.qkv, 896 + 56 * sl, ra, fb);
                }
            }
            asm volatile("barrier.cluster.wait.aligned;" ::: "memory");
            cw_target = (ld_word(g_cw + sl * 32) & ~15u) + 16;
#pragma unroll 1
            for (int k = 0; k < 2; k++) {
                const int n = t128 + 32 * k;
                int m = n - 2 - (n > PACK);
                const bool packed = m >= 30 ? (m < 38 || m >= 52) : m >= 22;
                if (m >= 30) m -= 30;
                if (n == PACK) m = tile < 8 ? tile : tile + 14;
                const int rot = n < 8 ? 0 : pr;
                const int ra = 112 * kblk(rot, m & 3), rb = 112 * kblk(rot, 2 * m & 3), rc = 112 * kblk(rot, (2 * m + 1) & 3);
                int kind = 0, m0, m1, c0, c1, r0, r1;
                if (m < 4) { m0 = m1 = 1; c0 = 448 + 56 * sl; c1 = c0 + 448; r0 = r1 = ra; }
                else if (m < 8) { m0 = m1 = m < 6 ? 1 : 2; c0 = c1 = 56 * sl; r0 = rb; r1 = rc; }
                else if (m < 20) { m0 = 3; m1 = 4; c0 = c1 = 224 * sl + 32 * hr + 64 * ((m - 8) >> 2); r0 = r1 = ra; }
                else if (m < 22) { kind = 2; m0 = 5; m1 = 6; c0 = c1 = 224 * sl + (hr ? 0 : 192); r0 = rb; r1 = rc; }
                else { m0 = m1 = 7; c0 = c1 = 56 * (2 * ((pr + (m >> 1) - 10) & 3) + hr); r0 = 224 * (sl ^ (m & 1)); r1 = r0 + 112; }
                if (packed) { kind = 1; r0 = sl * 16 + (m < 8 ? m : m - 14); r1 = 0; }
                e0[0] = e0[1]; e1[0] = e1[1];
                e0[1] = kind | (m0 << 2) | (m1 << 6) | (c0 << 10) | (c1 << 21);
                e1[1] = r0 | (r1 << 16);
            }
        } else {
            const int j = t128 - 32;
            asm volatile("barrier.cluster.wait.aligned;" ::: "memory");
            uint2 wv[7];
            const int k = j < 56 ? j : 55, hh = k >= 28;
#pragma unroll
            for (int i = 0; i < 7; i++) wv[i] = __ldg(reinterpret_cast<const uint2*>(w_phi + (sl * 56 + k) * 28) + i);
#pragma unroll 1
            for (int i = j; i < 7168 / 16; i += 96) sts4(sb + OFF_WPHI + i * 16, 0, 0, 0, 0);
            bar_sync(5, 96);
            if (j < 56) {
                uint32_t a4[4];
#pragma unroll
                for (int q = 0; q < 4; q++) a4[q] = sb + OFF_WPHI + (4 * hh + q) * 128 + ((((k >> 3) ^ (4 * hh + q)) & 7) << 4) + (k & 7) * 2;
                FOR14(const uint32_t v = (t & 1) ? wv[t >> 1].y : wv[t >> 1].x;
                      asm volatile("{ .reg .b16 l, h; mov.b32 {l, h}, %2; st.shared.u16 [%0+%3], l; st.shared.u16 [%1+%3], h; }"
                                   ::"r"(a4[t >= 7 ? 2 : 0]), "r"(a4[t >= 7 ? 3 : 1]), "r"(v), "n"((t % 7) * 1024) : "memory"));
            }
            __syncwarp();
            fence_async();
            bar_arrive(1, 224);
            bar_arrive(9, 224);
            if (w == 1) {
                mbar_wait(BAR(2), 0);
                mbar_wait(BAR(2), 1);
                const int b = blockIdx.x;
                asm volatile(ELECT "cp.async.bulk.prefetch.L2.global [%0], %1; }" ::"l"(wg + b * 6272), "r"(12544) : "memory");
                asm volatile(ELECT "cp.async.bulk.prefetch.L2.global [%0], %1; }" ::"l"(wu + b * 6272), "r"(12544) : "memory");
                asm volatile(ELECT "cp.async.bulk.prefetch.L2.global [%0], %1; }" ::"l"(wd + b * 6272), "r"(12544) : "memory");
            }
        }
        uint32_t kseq = ld_word(g_c1 + (sl * 8 * 16 + tile) * 32);
        int slot = 0, ph = 0, n = NST;
#pragma unroll 1
        for (int layer = 0; layer < 3; layer++) {
            if (w == 0) {
                const int nend = layer == 0 ? 11 : (layer == 1 ? 42 : 63);
#pragma unroll 1
                for (; n < nend; n++) {
                const uint32_t w0 = __shfl_sync(0xffffffffu, n < 32 ? e0[0] : e0[1], n & 31), w1 = __shfl_sync(0xffffffffu, n < 32 ? e1[0] : e1[1], n & 31);
                const uint32_t dst = sb + slot * STAGE, fb = BAR(n == PACK ? B_PACK : slot);
                const CUtensorMap* m0 = &maps.x + ((w0 >> 2) & 15);
                const CUtensorMap* m1 = &maps.x + ((w0 >> 6) & 15);
                const int c0 = (w0 >> 10) & 2047, c1 = w0 >> 21, r0 = w1 & 0xffff, r1 = w1 >> 16;
                if (n == 25) {
                    int it = 0;
                    uint32_t v;
                    do { asm volatile("ld.acquire.gpu.global.u32 %0, [%1];" : "=r"(v) : "l"(g_cw + sl * 32) : "memory"); } while ((int)(v - cw_target) < 0 && ++it < 0x400000);
                    asm volatile("fence.proxy.async.global;" ::: "memory");
                    __syncwarp();
                }
                mbar_wait(BAR(B_EMPTY + slot), ph);
                __syncwarp();
                asm volatile(ELECT "mbarrier.arrive.expect_tx.shared::cta.b64 _, [%0], %1; }" ::"r"(fb), "r"(STAGE) : "memory");
                if ((w0 & 3) == 0) {
                    tma2d(dst, m0, c0, r0, fb);
                    tma2d(dst + HALF, m1, c1, r1, fb);
                } else if (w0 & 1) {
                    asm volatile(ELECT "cp.async.bulk.shared::cluster.global.mbarrier::complete_tx::bytes [%0], [%1], %2, [%3]; }"
                                 ::"r"(dst), "l"(reinterpret_cast<const char*>(g_wp) + (size_t)r0 * STAGE), "r"(STAGE), "r"(fb) : "memory");
                } else {
                    tma2d(dst, m0, c0, r0, fb); tma2d(dst + 7168, m0, c0, r1, fb);
                    tma2d(dst + HALF, m1, c0, r0, fb); tma2d(dst + HALF + 7168, m1, c0, r1, fb);
                }
                if (n == PACK) asm volatile(ELECT "mbarrier.arrive.shared::cta.b64 _, [%0]; }" ::"r"(BAR(slot)) : "memory");
                if (++slot == NST) { slot = 0; ph ^= 1; }
                }
            } else if (w == 1 && layer == 1) {
                constexpr int ps = PACK % NST;
                mbar_wait(BAR(B_PACK), 0);
                asm volatile("{ .reg .pred e; elect.sync _|e, 0xffffffff;\n"
                             "@e cp.async.bulk.global.shared::cta.bulk_group [%0], [%1], %2;\n"
                             "@e cp.async.bulk.commit_group;\n"
                             "@e cp.async.bulk.wait_group.read 0;\n"
                             "@e mbarrier.arrive.shared::cta.b64 _, [%3], 8;\n"
                             "@e cp.async.bulk.wait_group 0;\n"
                             "@e fence.proxy.async.global;\n"
                             "@e red.release.gpu.global.add.u32 [%4], 1; }"
                             ::"l"(reinterpret_cast<char*>(g_wp) + (size_t)(sl * 16 + tile) * STAGE), "r"(sb + ps * STAGE), "r"(STAGE), "r"(BAR(B_EMPTY + ps)), "l"(g_cw + sl * 32) : "memory");
                __syncwarp();
            }
            if (layer < 2) {
            const uint32_t tag = layer ^ 1;
            kseq++;
            bar_sync(7, 384);
            ASTAMP(0);
            if (tile < 15) {
                const int sq = lane >> 3, pk = 8 * w + (lane & (tile == 14 ? 3 : 7));
                uint32_t v[16];
                if (layer == 0) poll_cnt(g_c1 + ((sl * 8 + (w >> 1) * 4 + (tile >> 2)) * 16 + (lane & 15)) * 32, kseq);
                ASTAMP(1);
                poll4_kv<32>(v, g_kv1 + ((sl * 16 + tile) * 16 + 4 * sq) * 32 + pk, tag);
#pragma unroll
                for (int k = 0; k < 4; k++) {
                    float lo = (bf_lo(v[k]) + bf_lo(v[4 + k])) + (bf_lo(v[8 + k]) + bf_lo(v[12 + k]));
                    float hi = (bf_hi(v[k]) + bf_hi(v[4 + k])) + (bf_hi(v[8 + k]) + bf_hi(v[12 + k]));
                    lo += __shfl_xor_sync(0xffffffffu, lo, 8); hi += __shfl_xor_sync(0xffffffffu, hi, 8);
                    lo += __shfl_xor_sync(0xffffffffu, lo, 16); hi += __shfl_xor_sync(0xffffffffu, hi, 16);
                    v[k] = pack2(lo, hi);
                }
                if (sq == 0) st_pkt<0>(g_kv2 + sl * 512 + 32 * tile + pk, settag(v[0], tag), v[1], v[2], v[3]);
            }
            ASTAMP(2);
            {
                const int item = t128 < 112 ? t128 : 112 + (t128 & 3), d = item >> 1;
                const int cc = t128 < 112 ? 2 * (d >= 28) + (item & 1) : item - 112;
                const int r = t128 < 112 ? d : 56 + (cc >> 1) + 2 * ((t128 - 112) >> 2);
                uint32_t ra = sb + OFF_KVB + r * 128 + 4 * cc, rx = (r & 7) << 4;
                asm volatile("" : "+r"(ra), "+r"(rx));
                FOR14(asm volatile("st.shared.u32 [%0+%2], %1;" ::"r"((ra ^ 8) + (((t & 7) << 4) ^ rx)), "r"(0), "n"((t >> 3) * 8192) : "memory"));
                uint32_t v[16];
                asm volatile("" : "+r"(ra), "+r"(rx));
                poll4_kv<8>(v, g_kv2 + sl * 512 + (item >> 3) * 32 + (item & 7), tag);
                FOR14(asm volatile("st.shared.u32 [%0+%2], %1;" ::"r"(ra + (((t & 7) << 4) ^ rx)), "r"(v[t < 7 ? t : t + 1]), "n"((t >> 3) * 8192) : "memory"));
                fence_async();
            }
            bar_arrive(3, 384);
            ASTAMP(3);
            }
        }
    } else {
        asm volatile("setmaxnreg.inc.sync.aligned.u32 232;");
        const int tid = fresh_tid(), lane = tid & 31, t128 = tid & 127, g = lane >> 2, c = lane & 3;
        const int wu = __shfl_sync(0xffffffffu, tid >> 5, 0), w = wu & 3;
        uint4* const xp0 = g_ex + 3 * PLANE + ((tile * 2 + wgi) * 8) * 512 + w * 128 + lane;
        const uint32_t hbuf = sb + OFF_H + wgi * STAGE;
        uint32_t slot = 0, ph = 0, eb1 = 0, eb2 = 0, ackph = 0, rcvph = 0, gatph = 0, swp = 0;
        uint32_t ppid = 6;
#define cx(s) (reinterpret_cast<uint32_t*>(again(xp0) - lane + PL(1) + 112 + (s) * 512))
#define stp (again(xp0) - lane + g + PL(0) + 112)
        uint32_t seq = ld_word(cx(sl));
        uint32_t kseq = ld_word(g_c1 + ((sl * 8 + (tid >> 5)) * 16 + tile) * 32);
        uint32_t stag = ld_word(reinterpret_cast<const uint32_t*>(stp + sl * 512) + 3) & 1;
        asm volatile("barrier.cluster.wait.aligned;" ::: "memory");
        STAMP(1);
        uint32_t X[14];
        [[maybe_unused]] const uint32_t x0row = (w < 2 ? hbuf : sb + wgi * STAGE) + ((w & 1) * 16 + (lane & 15)) * 128;
        mbar_wait(BAR(wgi), 0);
        STAMP(51);
        kill<14>(X);
#define PUSH_SLICE(W)                                                                          \
    {                                                                                          \
        if (t128 == 0) mbar_expect_tx(BAR(B_RECV + wgi), 7168);                                \
        PUSH_BEGIN();                                                                          \
        const uint32_t ra = mapa(hbuf + 24576 + t128 * 16, hr ^ 1), rb = mapa(sb + OFF_XR + wgi * 3072, hr ^ 1), rbar = mapa(BAR(B_RECV + wgi), hr ^ 1); \
        st_async4(ra, W[0], W[1], W[2], W[3], rbar);                                           \
        st_async4(ra + 2048, W[4], W[5], W[6], W[7], rbar);                                    \
        st_async4(rb + t128 * 16, W[8], W[9], W[10], W[11], rbar);                             \
        asm volatile("st.async.weak.shared::cluster.mbarrier::complete_tx::bytes.v2.b32 [%0], {%1,%2}, [%3];" ::"r"(rb + 2048 + t128 * 8), "r"(W[12]), "r"(W[13]), "r"(rbar) : "memory"); \
    }
#define PULL_SLICE(W)                                                                          \
    {                                                                                          \
        uint32_t t0, t1;                                                                       \
        mbar_wait(BAR(B_RECV + wgi), rcvph);                                                   \
        rcvph ^= 1;                                                                            \
        lds4(&A[1][0], hbuf + 24576 + t128 * 16);                                              \
        lds4(&A[1][4], hbuf + 26624 + t128 * 16);                                              \
        lds4(&A[1][8], sb + OFF_XR + wgi * 3072 + t128 * 16);                                  \
        asm volatile("ld.shared.v2.u32 {%0,%1}, [%2];" : "=r"(t0), "=r"(t1) : "r"(sb + OFF_XR + wgi * 3072 + 2048 + t128 * 8) : "memory"); \
        _Pragma("unroll") for (int i = 0; i < 12; i++) A[0][i] = (i & 3) ? W[i] : W[i] & ~1u;  \
        A[1][0] &= ~1u; A[1][4] &= ~1u; A[1][8] &= ~1u;                                        \
        A[0][12] = (hr ? t0 : W[12]) & ~1u; A[0][13] = hr ? t1 : W[13];                        \
        A[1][12] = (hr ? W[12] : t0) & ~1u; A[1][13] = hr ? W[13] : t1;                        \
        asm volatile("" : RW4(A[0], 0), RW4(A[0], 4), RW4(A[0], 8), RW2(A[0], 12), RW4(A[1], 0), RW4(A[1], 4), RW4(A[1], 8), RW2(A[1], 12)); \
        swp = hr * 448;                                                                        \
    }
#define SWB(b, t, db, sh) ((b) == 0 && (t) < 6 ? ((t) < 3 ? db##p : db##m) : db)
#define DECL_DB(b, MK, lbo, sh) const uint64_t db = MK(0, lbo, R_ADJ), dbp = (b) == 0 ? MK(0, lbo, R_ADJ + (swp >> (sh))) : db, dbm = (b) == 0 ? MK(0, lbo, R_ADJ - (swp >> (sh))) : db;
#define EARLY 1
#define EARLYK 1
#define PPB 2
#define PP_WAIT() if (wgi == 1) { bar_sync(ppid, 256); ppid ^= 14; }
#define PP_GO() if (wgi == 0) { bar_arrive(ppid, 256); ppid ^= 14; }
#define GAT_ISSUE(base)                                                                        \
    {                                                                                          \
        const char* gs = reinterpret_cast<const char*>(g_ex + 3 * PLANE + (base) + (tile * 16 + wgi * 8 + 2 * kblk(pr, GB)) * 512 + w * 128); \
        const uint32_t gd = hbuf + w * 3584, gb = BAR(B_GAT + wu);                     \
        asm volatile("{ .reg .pred e; elect.sync _|e, 0xffffffff;\n"                           \
                     "@e mbarrier.arrive.expect_tx.shared::cta.b64 _, [%2], 3584;\n"           \
                     "@e cp.async.bulk.shared::cluster.global.mbarrier::complete_tx::bytes [%0], [%1], 1792, [%2];\n" \
                     "@e cp.async.bulk.shared::cluster.global.mbarrier::complete_tx::bytes [%0+1792], [%1+8192], 1792, [%2]; }" \
                     ::"r"(gd), "l"(gs), "r"(gb) : "memory");                                  \
        __syncwarp();                                                                          \
    }
#define GAT_FETCH()                                                                            \
    {                                                                                          \
        mbar_wait(BAR(B_GAT + wu), gatph);                                             \
        gatph ^= 1;                                                                            \
        const uint32_t ga = hbuf + w * 3584 + lane * 16;                                       \
        _Pragma("unroll") for (int s2 = 0; s2 < 2; s2++) {                                     \
            lds4(&A[2 * GB + s2][0], ga + s2 * 1792); lds4(&A[2 * GB + s2][4], ga + s2 * 1792 + 512); lds4(&A[2 * GB + s2][8], ga + s2 * 1792 + 1024); \
            asm volatile("ld.shared.v2.u32 {%0,%1}, [%2];" : "=r"(A[2 * GB + s2][12]), "=r"(A[2 * GB + s2][13]) : "r"(ga - lane * 8 + s2 * 1792 + 1536) : "memory"); \
        }                                                                                      \
    }
#define PT 3
#define PREP(b, t, remote)                                                                     \
    if constexpr ((b) < 3 && (t) == PT) {                                                      \
        wg_commit();                                                                           \
        STAMP(80 + 8 * (step & 1) + 2 * (b));                                                  \
        if constexpr (GB == 1 && (b) == 0) { if (remote) GAT_FETCH() }                         \
        if (remote) blk_check<((b) + 1) & 3>(A, BLK(xsrc, (b) + 1), lane, xtag);               \
        STAMP(81 + 8 * (step & 1) + 2 * (b));                                                  \
        if constexpr ((b) == 0) { if (remote) blk_load<3>(A, BLK(xsrc, 3), lane); }            \
        normalize<((b) + 1) & 3>(A, k0, k1);                                                   \
        asm volatile("" : RW4(A[(2 * (b) + 2) & 7], 0), RW4(A[(2 * (b) + 2) & 7], 4), RW4(A[(2 * (b) + 2) & 7], 8), RW2(A[(2 * (b) + 2) & 7], 12), \
                          RW4(A[(2 * (b) + 3) & 7], 0), RW4(A[(2 * (b) + 3) & 7], 4), RW4(A[(2 * (b) + 3) & 7], 8), RW2(A[(2 * (b) + 3) & 7], 12)); \
        wg_fence();                                                                            \
    }                                                                                          \
    if constexpr ((b) == 3 && ((t) == 0 || (t) == 6)) { STAMP(86 + 8 * (step & 1) + (t) / 6); }
#define BLK(base, b) ((base) + kblk(pr, b) * 1024)

#pragma unroll 1
        for (int step = 0; step < 4; step++) {
            const uint32_t tag = (step >> 1) ^ 1;
            const int so = (step >> 1) * 24 + (step & 1) * 12;
            (void)so;
            uint32_t A[8][14];
            uint4* const xsrc = xp0 + ((step & 1) ? PL(2) : PL(0));
            const uint32_t xtag = (step & 1) ? tag : ((seq >> 3) & 1) ^ 1;
            uint32_t xbits = 0;
            if (step || !LSTAT) {
                float st[4];
                slice_stats(X, st);
                stag ^= 1;
                xbits = x_bits(X);
                tag_slice(X, xtag);
                if (step) send_slice<0>(xsrc + sl * 512, lane, X);
                if (c == 0) st_pkt<0>(stp + sl * 512, __float_as_uint(st[0]), __float_as_uint(st[1]), __float_as_uint(st[2]), settag(__float_as_uint(st[3]), stag));
            }
            STAMP(2 + so);
            uint32_t sv[8];
            if (step == 0) {
                const int rr = lane & 7, hi = lane >> 4;
                const uint32_t rowa = (w < 2 ? hbuf : sb + wgi * STAGE) + ((w & 1) * 16 + (lane & 15)) * 128;
                uint32_t xr[8];
#pragma unroll
                for (int j = 0; j < 8; j++) xr[j] = rowa + ((((j + hi) ^ rr) & 7) << 4) + (j == 7 ? hi * 4096 : 0);
#define X0_BLOCK(b)                                                                            \
    FOR7(constexpr int G = 14 * (b) + (t < 3 ? 2 * t : (t < 6 ? 2 * t + 1 : 6));               \
         uint32_t q0, q1, q2, q3;                                                              \
         const uint32_t ad = t < 6 ? xr[G & 7] : rowa + ((G + 7 * hi) >> 3) * 4096 + ((((G + 7 * hi) ^ rr) & 7) << 4); \
         asm volatile("ldmatrix.sync.aligned.m8n8.x4.shared.b16 {%0,%1,%2,%3}, [%4+%5];" : "=r"(q0), "=r"(q1), "=r"(q2), "=r"(q3) \
                      : "r"(ad), "n"(t < 6 ? (G >> 3) * 4096 : 0) : "memory");                 \
         if (t < 3) { A[2 * (b)][4 * t] = q0; A[2 * (b)][4 * t + 1] = q1; A[2 * (b)][4 * t + 2] = q2; A[2 * (b)][4 * t + 3] = q3; } \
         else if (t < 6) { A[2 * (b) + 1][(4 * t - 12) & 15] = q0; A[2 * (b) + 1][((4 * t - 12) & 15) + 1] = q1; A[2 * (b) + 1][((4 * t - 12) & 15) + 2] = q2; A[2 * (b) + 1][((4 * t - 12) & 15) + 3] = q3; } \
         else { A[2 * (b)][12] = q0; A[2 * (b)][13] = q1; A[2 * (b) + 1][12] = q2; A[2 * (b) + 1][13] = q3; });
                X0_BLOCK(0) X0_BLOCK(1) X0_BLOCK(2) X0_BLOCK(3)
                mbar_wait(BAR(wgi ^ 1), 0);
                R_NEXT();
                R_NEXT();
                {
                    float sv4[4] = {0.f, 0.f, 0.f, 0.f}, sq4[8] = {0.f, 0.f, 0.f, 0.f, 0.f, 0.f, 0.f, 0.f};
                    const uint32_t rb = (w < 2 ? hbuf : sb + wgi * STAGE) + ((w & 1) * 16 + (lane >> 1)) * 128;
#pragma unroll 1
                    for (int i = 0; i < 7; i++) {
                        uint32_t q[16];
#pragma unroll
                        for (int j = 0; j < 4; j++) lds4(q + 4 * j, rb + i * 4096 + (((j * 2 + lane) & 7) << 4));
#pragma unroll
                        for (int k = 0; k < 16; k++) {
                            const float e0 = bf_lo(q[k]), e1 = bf_hi(q[k]);
                            sv4[k & 3] += e0 + e1; sq4[(2 * k) & 7] = fmaf(e0, e0, sq4[(2 * k) & 7]); sq4[(2 * k + 1) & 7] = fmaf(e1, e1, sq4[(2 * k + 1) & 7]);
                        }
                    }
                    const float sa = (sv4[0] + sv4[1]) + (sv4[2] + sv4[3]);
                    const float sq = ((sq4[0] + sq4[1]) + (sq4[2] + sq4[3])) + ((sq4[4] + sq4[5]) + (sq4[6] + sq4[7]));
                    const int s0 = 2 * g + (c & 1);
                    const float a0 = __shfl_sync(0xffffffffu, sa, s0), q0 = __shfl_sync(0xffffffffu, sq, s0);
                    const float a1 = __shfl_sync(0xffffffffu, sa, s0 + 16), q1 = __shfl_sync(0xffffffffu, sq, s0 + 16);
                    sv[0] = c < 2 ? __float_as_uint(a0) : 0u; sv[1] = c < 2 ? __float_as_uint(q0) : 0u;
                    sv[2] = c < 2 ? __float_as_uint(a1) : 0u; sv[3] = c < 2 ? __float_as_uint(q1) : 0u;
                    sv[4] = sv[5] = sv[6] = sv[7] = 0u;
                }
                STAMP(52 + step);
            } else {
                PUSH_SLICE(X)
                stat_load(sv, stp + c * 1024);
                kill<14>(A[2]); kill<14>(A[3]); kill<14>(A[4]); kill<14>(A[5]); kill<14>(A[6]); kill<14>(A[7]);
                PULL_SLICE(X)
                stat_check(sv, stp + c * 1024, stag);
                STAMP(52 + step);
                if (GB == 1) GAT_ISSUE((step & 1) ? PL(2) : PL(0))
                else blk_load<1>(A, BLK(xsrc, 1), lane);
            }
            LnCoef k0, k1;
            {
                k0 = ln_coef(__uint_as_float(sv[0]) + __uint_as_float(sv[4]), __uint_as_float(sv[1]) + __uint_as_float(sv[5]));
                k1 = ln_coef(__uint_as_float(sv[2]) + __uint_as_float(sv[6]), __uint_as_float(sv[3] & ~1u) + __uint_as_float(sv[7] & ~1u));
            }
            if (step) {
                if (GB == 2) GAT_ISSUE((step & 1) ? PL(2) : PL(0))
                else blk_load<2>(A, BLK(xsrc, 2), lane);
            }
            STAMP(3 + so);
            GSTAMP(76 + step);

            if ((step & 1) == 0) {
                float tq[28];
                {
                    float av[28];
#define KV_BLOCK(b)                                                                           \
    if (GB == 2 && (b) == 1 && step) GAT_FETCH()                                                         \
    if ((b) == 2) PUSH_ACK();                                                                 \
    if (QE && (b) == 1) R_RELEASE(2);                                                         \
    if (QE && (b) == 2) { wg_wait<2>(); R_RELEASE(2); }                                       \
    R_WAIT();                                                                                 \
    if ((b) == PPK) { PP_WAIT() }                                                             \
    { DECL_DB(b, BASE128, 16, 0)                                                              \
    wg_fence();                                                                               \
    FOR7(mma_rs56<1, D128(0, t)>(tq, AQ(A, b, t), (b) + t > 0, SWB(b, t, db, 0));             \
         mma_rs56<1, D128(HALF, t)>(av, AQ(A, b, t), (b) + t > 0, SWB(b, t, db, 0));          \
         PREP(b, t, step)); }                                                                 \
    wg_commit();                                                                              \
    if ((b) == 3 && PPK < 4) { PP_GO() }                                                      \
    R_NEXT();
                    if (EARLYK == 0 || step == 0) R_RELEASE(2);
                    normalize<0>(A, k0, k1);
                    KV_BLOCK(0) KV_BLOCK(1) KV_BLOCK(2) KV_BLOCK(3)
                    wg_wait<0>();
                    if (lane < (QE ? 3 : NST)) mbar_arrive(BAR(B_EMPTY + (slot + NST - 1 - lane) % NST));
                    STAMP(4 + so);
                    WSUM(80 + 7 * (step >> 1));
                    const int m = lane >> 3, rr = lane & 7;
                    const uint32_t rowa = hbuf + 16384 + (w * 16 + rr + 8 * (m & 1)) * 128;
                    const uint32_t one = c == 0 ? 0x00003f80u : 0u;
                    if (step == 0) { bar_sync(wgi ? 9 : 1, 224); }
#pragma unroll
                    for (int j = 0; j < 4; j++) {
                        const uint32_t a = rowa + (((2 * j + (m >> 1)) ^ rr) << 4);
                        if (j < 3) stsm4(a, pack2(av[8 * j], av[8 * j + 1]), pack2(av[8 * j + 2], av[8 * j + 3]), pack2(av[8 * j + 4], av[8 * j + 5]), pack2(av[8 * j + 6], av[8 * j + 7]));
                        else stsm4(a, pack2(av[24], av[25]), pack2(av[26], av[27]), one, one);
                    }
                }
                uint32_t PH[28];
                int it = 1;
#pragma unroll 1
                do {
                    float pp[28];
                    phi_gemm(tq, pp);
                    dual_softmax(pp, PH);
                    if (((trips >> (it + 1)) & 1) == 0) continue;
                    {
                        const int m = lane >> 3, rr = lane & 7;
                        const uint32_t rowa = hbuf + (w * 16 + rr + 8 * (m & 1)) * 128;
#pragma unroll
                        for (int j = 0; j < 7; j++) {
                            const int cg = 2 * j + (m >> 1), hi = cg >= 7;
                            stsm4(rowa + hi * 8192 + (((cg - 7 * hi) ^ rr) << 4), PH[4 * j], PH[4 * j + 1], PH[4 * j + 2], PH[4 * j + 3]);
                        }
                    }
                    fence_async();
                    STAMP(5 + so);
#define Q_STAGE(b0)                                                                           \
    R_WAIT();                                                                                 \
    { DECL_DB(b0, BASE128, 16, 0)                                                             \
    wg_fence();                                                                               \
    FOR7(mma_rs56<1, D128(0, t)>(tq, AQ(A, b0, t), (b0) + t > 0, SWB(b0, t, db, 0)));         \
    FOR7(mma_rs56<1, D128(HALF, t)>(tq, AQ(A, (b0) + 1, t), 1, db)); }                        \
    wg_commit();                                                                              \
    R_NEXT();
                    if (QE && wgi == 0) { kill<28>(tq); Q_STAGE(0) Q_STAGE(2) wg_wait<1>(); R_RELEASE(2); wg_wait<0>(); R_RELEASE(1); }
                    bar_sync(2, 256);
                    float kv[28];
                    const uint64_t da = BASE128(OFF_H + 16384, 16, 0), dbk = BASE128(OFF_H, 16, wgi * 512);
                    wg_fence();
                    FOR8(constexpr uint64_t o = ((t >> 2) * STAGE + (t & 3) * 2048) >> 4; mma_ss56_tt<o, o>(kv, t > 0, da, dbk));
                    wg_commit();
                    wg_wait<0>();
#pragma unroll
                    for (int hf = 0; hf < 2; hf++) {
                        const int d = 16 * w + g + 8 * hf;
                        if ((d < 56 && (d >= 28) == (c >= 2)) || d == 56) {
                            const int item = d < 56 ? 2 * d + (c & 1) : 112 + c;
                            uint4* dst = g_kv1 + ((sl * 16 + (item >> 3)) * 16 + tile) * 32 + wgi * 16 + (item & 7);
#define KVW(i) pack2(kv[4 * (i) + 2 * hf], kv[4 * (i) + 2 * hf + 1])
                            st_pkt<0>(dst, settag(KVW(0), tag), KVW(1), KVW(2), KVW(3));
                            st_pkt<8>(dst, settag(KVW(4), tag), KVW(5), KVW(6), 0u);
                        }
                    }
                    __syncwarp();
                    kseq++;
                    if (lane == 0) st_word(g_c1 + ((sl * 8 + (tid >> 5)) * 16 + tile) * 32, kseq);
                    bar_arrive(7, 384);
                    STAMP(6 + so);
                    if (!QE || wgi == 1) { kill<28>(tq); Q_STAGE(0) Q_STAGE(2) wg_wait<1>(); R_RELEASE(2); wg_wait<0>(); R_RELEASE(1); }
                    STAMP(7 + so);
                    kill<28>(PH);
                } while (((trips >> (++it)) & 1));
                STAMP(8 + so);
                if (step) {
                    slice_load<PL(0)>(X, xp0 + sl * 512, lane);
                } else {
                    const uint32_t* xp = reinterpret_cast<const uint32_t*>(x_in + (size_t)(tile * 128 + wu * 16 + g) * 448 + 56 * sl + 2 * c);
#pragma unroll
                    for (int i = 0; i < 7; i++) { X[2 * i] = __ldg(xp + 4 * i); X[2 * i + 1] = __ldg(xp + 4 * i + 8 * 224); }
                }
                bar_sync(3, 384);
                STAMP(9 + so);
                const uint4* const osrc = xp0 + PL(1);
                {
                    float nm[32];
                    const uint64_t db = BASE128(OFF_KVB, 16, 0);
                    wg_fence();
                    FOR7(mma_rs64<0, ((t >> 2) * 8192 + (t & 3) * 32) / 16>(nm, PH[4 * t], PH[4 * t + 1], PH[4 * t + 2], PH[4 * t + 3], t > 0, db));
                    wg_commit();
                    wg_wait<0>();
                    const float i00 = rcp(nm[28] + 1e-6f), i01 = rcp(nm[29] + 1e-6f), i10 = rcp(nm[30] + 1e-6f), i11 = rcp(nm[31] + 1e-6f);
                    const float m0 = c >= 2 ? i01 : i00, m1 = c >= 2 ? i11 : i10;
                    uint32_t O[14];
#pragma unroll
                    for (int i = 0; i < 7; i++) {
                        const float f0 = i < 3 ? i00 : (i > 3 ? i01 : m0), f1 = i < 3 ? i10 : (i > 3 ? i11 : m1);
                        O[2 * i] = pack2(nm[4 * i] * f0, nm[4 * i + 1] * f0);
                        O[2 * i + 1] = pack2(nm[4 * i + 2] * f1, nm[4 * i + 3] * f1);
                    }
                    if (OST) { PP_WAIT() }
                    tag_slice(O, tag);
                    send_slice<PL(1)>(xp0 + sl * 512, lane, O);
                    seq++;
                    if (lane == 0) st_word(cx(sl), seq);
                    STAMP(10 + so);
                    PUSH_SLICE(O)
                    if (OST == 1) { PP_GO() }
                    const uint32_t cv = ld_word(cx(lane & 7));
                    PULL_SLICE(O)
                    check_cnt(cv, cx(lane & 7), seq);
                    if (OST == 2) { PP_GO() }
                    STAMP(56 + (step >> 1));
                    GAT_ISSUE(PL(1))
                    blk_load<3 - GB>(A, BLK(osrc, 3 - GB), lane);
                }
                float ao[28];
#define WO_BLOCK(b)                                                                           \
    if ((b) > 0) blk_check<b>(A, BLK(osrc, b), lane, tag);                                    \
    if (((b) & 1) == 0) R_WAIT();                                                             \
    { DECL_DB(b, BASE128, 16, 0)                                                              \
    wg_fence();                                                                               \
    FOR7(mma_rs56<1, D128(((b) & 1) * HALF, t)>(ao, AQ(A, b, t), (b) + t > 0, SWB(b, t, db, 0))); } \
    wg_commit();                                                                              \
    if ((b) & 1) R_NEXT();
                WO_BLOCK(0)
                STAMP(11 + so);
                blk_load<3>(A, BLK(osrc, 3), lane);
                if (GB == 1) GAT_FETCH()
                WO_BLOCK(1)
                if (GB == 2) GAT_FETCH()
                WO_BLOCK(2)
                PUSH_ACK();
                WO_BLOCK(3)
                wg_wait<0>();
                if (EARLY >= 1) R_RELEASE(2);
                if (EARLY >= 2) R_RELEASE(1);
                STAMP(12 + so);
                WSUM(86 + 7 * (step >> 1));
                if (step) x_fix(X, xbits);
#pragma unroll
                for (int i = 0; i < 14; i++) X[i] = pack2(bf_lo(X[i]) + ao[2 * i], bf_hi(X[i]) + ao[2 * i + 1]);
            } else {
                uint32_t H[56];
                float ag[64];
#define F1_EPI(dst, ng, ag)                                                                    \
    _Pragma("unroll") for (int i = 0; i < 2 * (ng); i++)                                       \
        (dst)[i] = pack2(geglu(ag[2 * i], ag[4 * (ng) + 2 * i]), geglu(ag[2 * i + 1], ag[4 * (ng) + 2 * i + 1]));
#define H_PUSH(h0, off) st_async4(rem_h + (off), H[h0], H[(h0) + 1], H[(h0) + 2], H[(h0) + 3], mapa(BAR(B_RECV2 + wgi), hr ^ 1));
#define F1_BLOCK(b, first)                                                                     \
    if ((first) && (b) < 2 && (b) >= EARLY) R_RELEASE(2);                                      \
    if (GB == 2 && (first) && (b) == 1) GAT_FETCH()                                                       \
    if ((first) && (b) == 2) PUSH_ACK();                                                       \
    R_WAIT();                                                                                  \
    if ((b) == PPB) { PP_WAIT() }                                                              \
    { DECL_DB(b, BASE128, HALF, 0)                                                             \
    wg_fence();                                                                                \
    FOR7(mma_rs128<1, D128(0, t)>(ag, AQ(A, b, t), (b) + t > 0, SWB(b, t, db, 0));             \
         if constexpr (first) { PREP(b, t, true) }); }                                         \
    wg_commit();                                                                               \
    if ((b) == 3) { PP_GO() }                                                                  \
    if ((b) > 0) { wg_wait<1>(); R_RELEASE(1); }       \
    R_NEXT();
                normalize<0>(A, k0, k1);
                F1_BLOCK(0, true) F1_BLOCK(1, true) F1_BLOCK(2, true) F1_BLOCK(3, true)
                if (t128 == 0) { mbar_expect_tx(BAR(B_RECV + wgi), 16384); mbar_expect_tx(BAR(B_RECV2 + wgi), 12288); }
                PUSH_BEGIN();
                wg_wait<0>();
                R_RELEASE(1);
                if (step == 1) R_NEXT();
                int p = 0;
#pragma unroll 1
                do {
                    STAMP(68 + p);
                    F1_EPI(H + 32, 8, ag)
                    STAMP(4 + p + so);
                    WSUM(81 + p + 7 * (step >> 1));
                    if (((trips >> (p + 1)) & 1) == 0) continue;
                    {
                        const uint32_t pk = (p ? hbuf + 16384 : sb + OFF_KVB + wgi * 8192) + w * 2048;
#pragma unroll
                        for (int k = 0; k < 4; k++) sts4(pk + k * 512 + lane * 16, H[32 + 4 * k], H[33 + 4 * k], H[34 + 4 * k], H[35 + 4 * k]);
                        fence_async();
                        __syncwarp();
                        asm volatile(ELECT "cp.async.bulk.shared::cluster.shared::cta.mbarrier::complete_tx::bytes [%0], [%1], 2048, [%2]; }"
                                     ::"r"(mapa(hbuf + p * 8192 + w * 2048, hr ^ 1)), "r"(pk), "r"(mapa(BAR(B_RECV + wgi), hr ^ 1)) : "memory");
                    }
                    kill<64>(ag);
                    F1_BLOCK(0, false) F1_BLOCK(1, false) F1_BLOCK(2, false) F1_BLOCK(3, false)
                    wg_wait<0>();
                    R_RELEASE(1);
                    kill<16>(H + 32);
                } while (((trips >> (++p)) & 1));
#pragma unroll
                for (int k = 0; k < 4; k++) lds4(H + 16 + 4 * k, hbuf + 16384 + w * 2048 + k * 512 + lane * 16);
                __syncwarp();
                if (lane == 0) asm volatile("mbarrier.arrive.shared::cluster.b64 _, [%0];" ::"r"(mapa(BAR(B_ACK2 + wgi), hr ^ 1)) : "memory");
                const uint32_t rem_h = mapa(hbuf + w * 2048 + lane * 16, hr ^ 1);
#define F1_LAST(b0)                                                                            \
    R_WAIT();                                                                                  \
    if (b0) { PP_WAIT() }                                                                      \
    { DECL_DB(b0, BASE64, HALF, 1)                                                             \
    wg_fence();                                                                                \
    FOR7(mma_rs64<1, D64(0, t)>(al, AQ(A, b0, t), (b0) + t > 0, SWB(b0, t, db, 1)));           \
    FOR7(mma_rs64<1, D64(7168, t)>(al, AQ(A, (b0) + 1, t), 1, db)); }                          \
    wg_commit();                                                                               \
    if (b0) { PP_GO() }                                                                        \
    R_NEXT();
                float al[32];
                F1_LAST(0)
                mbar_wait(BAR(B_RECV + wgi), rcvph);
                rcvph ^= 1;
                mbar_wait(BAR(B_ACK2 + wgi), step >> 1);
                H_PUSH(32, 16384) H_PUSH(36, 16896)
                F1_LAST(2)
                H_PUSH(40, 17408) H_PUSH(44, 17920)
                wg_wait<1>();
                R_RELEASE(2);
                wg_wait<0>();
                R_RELEASE(1);
                uint32_t HP[56];
#pragma unroll
                for (int k = 0; k < 4; k++) lds4(H + 4 * k, sb + OFF_KVB + wgi * 8192 + w * 2048 + k * 512 + lane * 16);
#pragma unroll
                for (int t = 0; t < 8; t++) lds4(HP + 4 * t, hbuf + (t >> 2) * 8192 + w * 2048 + (t & 3) * 512 + lane * 16);
                F1_EPI(H + 48, 4, al)
                H_PUSH(48, 24576 - w * 1024) H_PUSH(52, 25088 - w * 1024)
                STAMP(7 + so);
                WSUM(84 + 7 * (step >> 1));
                float acc[28];
                const uint32_t roA = hr ? 256u : 0u, roB = hr ? (uint32_t)-1536 : 0u;
                const uint32_t rpA = hr ? 0u : 256u, rpB = hr ? 0u : (uint32_t)-1536;
                float res[28];
                uint32_t v0[14], v1[14], P[14];
                const uint4* ps = xp0 + sl * 512;
#define F2_OWN_A()                                                                             \
    R_WAIT();                                                                                  \
    d0 = BASE128(0, 16, R_ADJ + roA); d1 = BASE128(0, 16, R_ADJ + roB);                        \
    wg_fence();                                                                                \
    FOR14(if constexpr (t < OT) mma_rs56<1, t * 128>(acc, H[4 * t], H[4 * t + 1], H[4 * t + 2], H[4 * t + 3], t > 0, d0)); \
    wg_commit();
#define F2_OWN_B()                                                                             \
    wg_fence();                                                                                \
    FOR14(if constexpr (t >= OT) mma_rs56<1, t * 128>(acc, H[4 * t], H[4 * t + 1], H[4 * t + 2], H[4 * t + 3], 1, t < 12 ? d0 : d1)); \
    wg_commit();                                                                               \
    R_NEXT();
#define F2_PEER()                                                                              \
    R_WAIT();                                                                                  \
    if (F2PP) { PP_WAIT() }                                                                    \
    d0 = BASE128(0, 16, R_ADJ + rpA); d1 = BASE128(0, 16, R_ADJ + rpB);                        \
    wg_fence();                                                                                \
    FOR14(mma_rs56<1, t * 128>(acc, HP[4 * t], HP[4 * t + 1], HP[4 * t + 2], HP[4 * t + 3], 1, t < 12 ? d0 : d1)); \
    wg_commit();                                                                               \
    if (F2PP) { PP_GO() }                                                                      \
    R_NEXT();
#define F2_TURN(u)                                                                             \
    wg_wait<1>();                                                                              \
    R_RELEASE(2);                                                                              \
    wg_wait<0>();                                                                              \
    R_RELEASE(1);                                                                              \
    _Pragma("unroll") for (int i = 0; i < 14; i++) P[i] = pack2(acc[2 * i], acc[2 * i + 1]);   \
    tag_slice(P, tag);                                                                         \
    asm volatile("" : RW4(P, 0), RW4(P, 4), RW4(P, 8), RW2(P, 12));                            \
    kill<28>(acc);                                                                             \
    F2_OWN_A()                                                                                 \
    if ((u) == 2) { slice_load<PL(3)>(v0, ps, lane); slice_load<PL(4)>(v1, ps, lane); } \
    send_slice<PL(3 + (u))>(xp0 + (2 * ((pr + (u) + 1) & 3) + hr) * 512, lane, P);             \
    seq++;                                                                                     \
    if (lane == 0) st_word(cx(sl), seq);                                                       \
    __syncwarp();                                                                              \
    STAMP(8 + (u) + so);                                                                       \
    F2_OWN_B()
                uint64_t d0, d1;
                F2_OWN_A()
                F2_OWN_B()
                R_WAIT();
                d0 = BASE128(0, 16, R_ADJ + rpA); d1 = BASE128(0, 16, R_ADJ + rpB);
                wg_fence();
                FOR8(mma_rs56<1, t * 128>(acc, HP[4 * t], HP[4 * t + 1], HP[4 * t + 2], HP[4 * t + 3], 1, d0));
                wg_commit();
                mbar_wait(BAR(B_RECV2 + wgi), step >> 1);
#pragma unroll
                for (int k = 0; k < 4; k++) lds4(HP + 32 + 4 * k, hbuf + 16384 + w * 2048 + k * 512 + lane * 16);
                lds4(HP + 48, hbuf + 24576 + w * 1024 + lane * 16);
                lds4(HP + 52, hbuf + 25088 + w * 1024 + lane * 16);
                if (step == 1) PUSH_ACK();
                wg_fence();
                FOR14(if constexpr (t >= 8) mma_rs56<1, t * 128>(acc, HP[4 * t], HP[4 * t + 1], HP[4 * t + 2], HP[4 * t + 3], 1, t < 12 ? d0 : d1));
                wg_commit();
                R_NEXT();
                F2_TURN(0)
                F2_PEER()
                F2_TURN(1)
                F2_PEER()
                F2_TURN(2)
                STAMP(64 + 8 * (step >> 1));
                slice_check<PL(3)>(v0, ps, lane, tag);
                slice_check<PL(4)>(v1, ps, lane, tag);
#pragma unroll
                for (int i = 0; i < 14; i++) { res[2 * i] = bf_lo(v0[i]) + bf_lo(v1[i]); res[2 * i + 1] = bf_hi(v0[i]) + bf_hi(v1[i]); }
                slice_load<PL(2)>(X, ps, lane);
                STAMP(65 + 8 * (step >> 1));
                const uint32_t cv = ld_word(cx(2 * ((pr + 1) & 3) + hr));
                F2_PEER()
                STAMP(66 + 8 * (step >> 1));
                check_cnt(cv, cx(2 * ((pr + 1) & 3) + hr), seq);
                STAMP(67 + 8 * (step >> 1));
                slice_load<PL(5)>(v0, ps, lane);
                x_fix(X, xbits);
                slice_check<PL(5)>(v0, ps, lane, tag);
#pragma unroll
                for (int i = 0; i < 14; i++) { res[2 * i] += bf_lo(v0[i]); res[2 * i + 1] += bf_hi(v0[i]); }
                STAMP(11 + so);
                wg_wait<0>();
                if (EARLYK >= 1) R_RELEASE(2);
                STAMP(12 + so);
                WSUM(85 + 7 * (step >> 1));
#pragma unroll
                for (int i = 0; i < 14; i++) X[i] = pack2(fmaf(res[2 * i] + acc[2 * i], 0.5f, bf_lo(X[i])), fmaf(res[2 * i + 1] + acc[2 * i + 1], 0.5f, bf_hi(X[i])));
            }
        }
        {
            const int m = lane >> 3, rr = lane & 7;
            const uint32_t ob = hbuf + w * 2048, rowa = ob + (rr + 8 * (m & 1)) * 112 + (m >> 1) * 16;
#pragma unroll
            for (int j = 0; j < 3; j++) stsm4(rowa + 32 * j, X[4 * j], X[4 * j + 1], X[4 * j + 2], X[4 * j + 3]);
            asm volatile("stmatrix.sync.aligned.m8n8.x2.shared.b16 [%0], {%1,%2};" ::"r"(ob + (rr + 8 * (m & 1)) * 112 + 96), "r"(X[12]), "r"(X[13]) : "memory");
            fence_async();
            __syncwarp();
            if (lane == 0) {
                asm volatile("cp.async.bulk.tensor.2d.global.shared::cta.bulk_group [%0, {%2, %3}], [%1];" ::"l"(&maps.out), "r"(ob), "r"(56 * sl), "r"(tile * 128 + (tid >> 5) * 16) : "memory");
                asm volatile("cp.async.bulk.commit_group;" ::: "memory");
                asm volatile("cp.async.bulk.wait_group.read 0;" ::: "memory");
            }
        }
        STAMP(50);
        GSTAMP(61);
        PDUMP();
    }
}

typedef CUresult (*EncodeFn)(CUtensorMap*, CUtensorMapDataType, cuuint32_t, void*, const cuuint64_t*, const cuuint64_t*, const cuuint32_t*,
                             const cuuint32_t*, CUtensorMapInterleave, CUtensorMapSwizzle, CUtensorMapL2promotion, CUtensorMapFloatOOBfill);

static void make_map(EncodeFn enc, CUtensorMap* m, const void* p, uint64_t cols, uint64_t rows, uint32_t bc, uint32_t br, CUtensorMapSwizzle sw) {
    cuuint64_t gd[2] = {cols, rows};
    cuuint64_t gs[1] = {cols * 2};
    cuuint32_t bd[2] = {bc, br};
    cuuint32_t es[2] = {1, 1};
    enc(m, CU_TENSOR_MAP_DATA_TYPE_BFLOAT16, 2, const_cast<void*>(p), gd, gs, bd, es, CU_TENSOR_MAP_INTERLEAVE_NONE, sw,
        CU_TENSOR_MAP_L2_PROMOTION_L2_128B, CU_TENSOR_MAP_FLOAT_OOB_FILL_NONE);
}

extern "C" void kernel_launch(void* const* d_in, const int* in_sizes, int n_in, void* d_out, int out_size) {
    (void)in_sizes; (void)n_in; (void)out_size;
    static EncodeFn enc = nullptr;
    static Scratch* scratch = nullptr;
    if (!enc) {
        void* fn = nullptr;
        cudaDriverEntryPointQueryResult qr;
        cudaGetDriverEntryPoint("cuTensorMapEncodeTiled", &fn, cudaEnableDefault, &qr);
        enc = (EncodeFn)fn;
        cudaGetSymbolAddress((void**)&scratch, g_scratch);
        cudaFuncSetAttribute(fused_kernel, cudaFuncAttributeMaxDynamicSharedMemorySize, SMEM_BYTES);
    }
    Maps maps;
    {
        cuuint64_t gd[3] = {64, 2048, 7};
        cuuint64_t gs[2] = {896, 128};
        cuuint32_t bd[3] = {64, 32, 7};
        cuuint32_t es[3] = {1, 1, 1};
        enc(&maps.x, CU_TENSOR_MAP_DATA_TYPE_BFLOAT16, 3, d_in[0], gd, gs, bd, es, CU_TENSOR_MAP_INTERLEAVE_NONE, CU_TENSOR_MAP_SWIZZLE_128B,
            CU_TENSOR_MAP_L2_PROMOTION_L2_128B, CU_TENSOR_MAP_FLOAT_OOB_FILL_NONE);
    }
    make_map(enc, &maps.out, d_out, 448, 2048, 56, 16, CU_TENSOR_MAP_SWIZZLE_NONE);
    make_map(enc, &maps.qkv, d_in[1], 1344, 448, 64, 112, CU_TENSOR_MAP_SWIZZLE_128B);
    make_map(enc, &maps.wo, d_in[3], 448, 448, 64, 112, CU_TENSOR_MAP_SWIZZLE_128B);
    make_map(enc, &maps.wg, d_in[5], 1792, 448, 64, 112, CU_TENSOR_MAP_SWIZZLE_128B);
    make_map(enc, &maps.wu, d_in[6], 1792, 448, 64, 112, CU_TENSOR_MAP_SWIZZLE_128B);
    make_map(enc, &maps.wg32, d_in[5], 1792, 448, 32, 112, CU_TENSOR_MAP_SWIZZLE_64B);
    make_map(enc, &maps.wu32, d_in[6], 1792, 448, 32, 112, CU_TENSOR_MAP_SWIZZLE_64B);
    make_map(enc, &maps.wd, d_in[7], 448, 1792, 64, 112, CU_TENSOR_MAP_SWIZZLE_128B);
    fused_kernel<<<128, 384, SMEM_BYTES>>>(scratch, (const __nv_bfloat16*)d_in[0], (const __nv_bfloat16*)d_in[2], 7, (const __nv_bfloat16*)d_in[5],
                                           (const __nv_bfloat16*)d_in[6], (const __nv_bfloat16*)d_in[7], maps);
}
```

```cpp
#include <cuda_runtime.h>
#include <cuda.h>
#include <cuda_bf16.h>
#include <stdint.h>
#include <type_traits>

#define MC 1
#define ACAN 1
#define SPLIT0 1
#define OT 2
#define F2PP 0
#define PPK 2
#define QE 1
#define OST 1
#define GB 1
#define B3T 6
#define PP

namespace {

constexpr uint32_t STAGE = 28672, HALF = 14336;
constexpr int NST = 5;
constexpr uint32_t OFF_H = NST * STAGE;
constexpr uint32_t OFF_KVB = OFF_H + 2 * STAGE;
constexpr uint32_t OFF_WPHI = OFF_KVB + 16384;
constexpr uint32_t OFF_XR = OFF_WPHI + 7168;
constexpr uint32_t OFF_BAR = OFF_XR + 6144;
constexpr uint32_t SMEM_BYTES = OFF_BAR + 256 + 1536;
constexpr int B_EMPTY = NST, B_RECV = 2 * NST, B_RECV2 = B_RECV + 2, B_PACK = B_RECV2 + 2, B_GAT = B_PACK + 1, B_ACK = B_GAT + 8, B_ACK2 = B_ACK + 2, B_COUNT = B_ACK2 + 2;

constexpr int PACK = 14;

struct Maps { CUtensorMap x, qkv, wo, wg, wu, wg32, wu32, wd, out; };

}

constexpr int PLANE = 16 * 2 * 8 * 512;
struct Scratch {
    uint4 ex[6 * PLANE];
    uint4 kv1[8 * 16 * 16 * 32];
    uint4 kv2[8 * 512];
    uint32_t c1[8 * 8 * 16 * 32];
    uint32_t cw[8 * 32];
    uint4 wp[8 * 32 * (HALF / 16)];
};
__device__ __align__(1024) Scratch g_scratch;
#define g_ex (sc->ex)
#define g_kv1 (sc->kv1)
#define g_kv2 (sc->kv2)
#define g_c1 (sc->c1)
#define g_cw (sc->cw)
#define g_wp (sc->wp)
#define STAMP(i)
#define GSTAMP(i)
#define PDUMP()
#define ASTAMP(i)

namespace {

__device__ __forceinline__ int fresh_tid() { int t; asm volatile("mov.u32 %0, %%tid.x;" : "=r"(t)); return t; }
__device__ __forceinline__ uint4* again(uint4* p) { asm volatile("" : "+l"(p)); return p; }
template <int N> __device__ __forceinline__ void kill(uint32_t* v) {
#pragma unroll
    for (int i = 0; i < N; i++) v[i] = 0;
}
template <int N> __device__ __forceinline__ void kill(float* v) {
#pragma unroll
    for (int i = 0; i < N; i++) v[i] = 0.f;
}
__device__ __forceinline__ uint32_t s2u(const void* p) { return (uint32_t)__cvta_generic_to_shared(p); }
__device__ __forceinline__ void mbar_init(uint32_t a, uint32_t c) { asm volatile("mbarrier.init.shared::cta.b64 [%0], %1;" ::"r"(a), "r"(c) : "memory"); }
__device__ __forceinline__ void mbar_expect_tx(uint32_t a, uint32_t b) { asm volatile("mbarrier.arrive.expect_tx.shared::cta.b64 _, [%0], %1;" ::"r"(a), "r"(b) : "memory"); }
__device__ __forceinline__ void mbar_arrive(uint32_t a) { asm volatile("mbarrier.arrive.shared::cta.b64 _, [%0];" ::"r"(a) : "memory"); }
#define GIVE_UP(id) "trap;\n"
#define SPIN_MAX "0x400000"
#define SPIN_TAIL(id) "add.u32 n, n, 1;\n setp.lt.u32 p, n, " SPIN_MAX ";\n @p bra.uni LP;\n" GIVE_UP(id) " DN:\n }"
__device__ __forceinline__ void mbar_wait(uint32_t a, uint32_t ph) {
    asm volatile("{ .reg .pred p; .reg .b32 n; mov.u32 n, 0;\n LP:\n"
                 "mbarrier.try_wait.parity.shared::cta.b64 p, [%0], %1;\n @p bra DN;\n"
                 "add.u32 n, n, 1;\n setp.lt.u32 p, n, " SPIN_MAX ";\n @p bra LP;\n"
                 GIVE_UP("")
                 " DN:\n }" ::"r"(a), "r"(ph) : "memory");
}
#define ELECT "{ .reg .pred e; elect.sync _|e, 0xffffffff; @e "
__device__ __forceinline__ void tma2d(uint32_t dst, const CUtensorMap* m, int c0, int c1, uint32_t bar) {
    asm volatile(ELECT "cp.async.bulk.tensor.2d.shared::cluster.global.mbarrier::complete_tx::bytes [%0], [%1, {%3, %4}], [%2]; }" ::"r"(dst), "l"(m), "r"(bar), "r"(c0), "r"(c1) : "memory");
}
__device__ __forceinline__ void tma3x(uint32_t dst, const CUtensorMap* m, int row, uint32_t bar) {
    asm volatile(ELECT "cp.async.bulk.tensor.3d.shared::cluster.global.mbarrier::complete_tx::bytes [%0], [%1, {0, %3, 0}], [%2]; }" ::"r"(dst), "l"(m), "r"(bar), "r"(row) : "memory");
}
template <int OFF>
__device__ __forceinline__ void ld_pkt(uint32_t* v, const uint4* p) {
    asm volatile("{ .reg .b128 t; ld.relaxed.gpu.global.b128 t, [%4+%5]; mov.b128 {%0,%1,%2,%3}, t; }" : "=r"(v[0]), "=r"(v[1]), "=r"(v[2]), "=r"(v[3]) : "l"(p), "n"(OFF * 16) : "memory");
}
template <int OFF>
__device__ __forceinline__ void st_pkt(uint4* p, uint32_t a, uint32_t b, uint32_t c, uint32_t d) {
    asm volatile("{ .reg .b128 t; mov.b128 t, {%1,%2,%3,%4}; st.relaxed.gpu.global.b128 [%0+%5], t; }" ::"l"(p), "r"(a), "r"(b), "r"(c), "r"(d), "n"(OFF * 16) : "memory");
}
__device__ __forceinline__ uint32_t pack2(float lo, float hi) {
    uint32_t r;
    asm("cvt.rn.bf16x2.f32 %0, %1, %2;" : "=r"(r) : "f"(hi), "f"(lo));
    return r;
}
__device__ __forceinline__ float bf_lo(uint32_t w) { return __uint_as_float(w << 16); }
__device__ __forceinline__ float bf_hi(uint32_t w) { return __uint_as_float(w & 0xffff0000u); }
__device__ __forceinline__ uint32_t settag(uint32_t w, uint32_t tag) { return (w & ~1u) | tag; }
__device__ __forceinline__ float ex2(float x) { float y; asm("ex2.approx.ftz.f32 %0, %1;" : "=f"(y) : "f"(x)); return y; }
__device__ __forceinline__ float rcp(float x) { float y; asm("rcp.approx.ftz.f32 %0, %1;" : "=f"(y) : "f"(x)); return y; }
__device__ __forceinline__ float tanh_hw(float x) { float y; asm("tanh.approx.f32 %0, %1;" : "=f"(y) : "f"(x)); return y; }
__device__ __forceinline__ void stsm4(uint32_t addr, uint32_t a, uint32_t b, uint32_t c, uint32_t d) {
    asm volatile("stmatrix.sync.aligned.m8n8.x4.shared.b16 [%0], {%1,%2,%3,%4};" ::"r"(addr), "r"(a), "r"(b), "r"(c), "r"(d) : "memory");
}
__device__ __forceinline__ void fence_async() { asm volatile("fence.proxy.async.shared::cta;" ::: "memory"); }
__device__ __forceinline__ void bar_sync(int id, int n) { asm volatile("bar.sync %0, %1;" ::"r"(id), "r"(n) : "memory"); }
__device__ __forceinline__ void bar_arrive(int id, int n) { asm volatile("bar.arrive %0, %1;" ::"r"(id), "r"(n) : "memory"); }
__device__ __forceinline__ void wg_fence() { asm volatile("wgmma.fence.sync.aligned;" ::: "memory"); }
__device__ __forceinline__ void wg_commit() { asm volatile("wgmma.commit_group.sync.aligned;" ::: "memory"); }
template <int N> __device__ __forceinline__ void wg_wait() { asm volatile("wgmma.wait_group.sync.aligned %0;" ::"n"(N) : "memory"); }

constexpr uint32_t SB0 = 1024;
__host__ __device__ constexpr uint32_t dlo(uint32_t off, uint32_t lbo) { return ((SB0 + off) >> 4) | ((lbo >> 4) << 16); }
__host__ __device__ constexpr uint32_t dhi(uint32_t sbo, uint32_t sw) { return (sbo >> 4) | (sw << 30); }
__device__ __forceinline__ uint64_t dbase(uint32_t lo, uint32_t hi) { uint64_t d; asm volatile("mov.b64 %0, {%1, %2};" : "=l"(d) : "r"(lo), "r"(hi)); return d; }
#define BASE128(off, lbo, adj) dbase(dlo(off, lbo) + (adj), dhi(1024, 1))
#define BASE64(off, lbo, adj) dbase(dlo(off, lbo) + (adj), dhi(512, 2))

#define ACC4(d, o) "+f"(d[o]), "+f"(d[o + 1]), "+f"(d[o + 2]), "+f"(d[o + 3])
#define ACC28(d) ACC4(d, 0), ACC4(d, 4), ACC4(d, 8), ACC4(d, 12), ACC4(d, 16), ACC4(d, 20), ACC4(d, 24)
#define ACC32(d, o) ACC4(d, o), ACC4(d, o + 4), ACC4(d, o + 8), ACC4(d, o + 12), ACC4(d, o + 16), ACC4(d, o + 20), ACC4(d, o + 24), ACC4(d, o + 28)

template <int TB, uint64_t D>
__device__ __forceinline__ void mma_rs56(float* d, uint32_t a0, uint32_t a1, uint32_t a2, uint32_t a3, int sd, uint64_t base) {
    asm volatile("{ .reg .pred p; .reg .b64 db; setp.ne.b32 p, %32, 0; add.u64 db, %33, %34;\n"
                 "wgmma.mma_async.sync.aligned.m64n56k16.f32.bf16.bf16 "
                 "{%0,%1,%2,%3,%4,%5,%6,%7,%8,%9,%10,%11,%12,%13,%14,%15,%16,%17,%18,%19,%20,%21,%22,%23,%24,%25,%26,%27}, "
                 "{%28,%29,%30,%31}, db, p, 1, 1, %35; }\n"
                 : ACC28(d)
                 : "r"(a0), "r"(a1), "r"(a2), "r"(a3), "r"(sd), "l"(base), "n"(D), "n"(TB));
}
template <int TB, uint64_t D>
__device__ __forceinline__ void mma_rs64(float* d, uint32_t a0, uint32_t a1, uint32_t a2, uint32_t a3, int sd, uint64_t base) {
    asm volatile("{ .reg .pred p; .reg .b64 db; setp.ne.b32 p, %36, 0; add.u64 db, %37, %38;\n"
                 "wgmma.mma_async.sync.aligned.m64n64k16.f32.bf16.bf16 "
                 "{%0,%1,%2,%3,%4,%5,%6,%7,%8,%9,%10,%11,%12,%13,%14,%15,%16,%17,%18,%19,%20,%21,%22,%23,%24,%25,%26,%27,%28,%29,%30,%31}, "
                 "{%32,%33,%34,%35}, db, p, 1, 1, %39; }\n"
                 : ACC32(d, 0)
                 : "r"(a0), "r"(a1), "r"(a2), "r"(a3), "r"(sd), "l"(base), "n"(D), "n"(TB));
}
template <int TB, uint64_t D>
__device__ __forceinline__ void mma_rs128(float* d, uint32_t a0, uint32_t a1, uint32_t a2, uint32_t a3, int sd, uint64_t base) {
    asm volatile("{ .reg .pred p; .reg .b64 db; setp.ne.b32 p, %68, 0; add.u64 db, %69, %70;\n"
                 "wgmma.mma_async.sync.aligned.m64n128k16.f32.bf16.bf16 "
                 "{%0,%1,%2,%3,%4,%5,%6,%7,%8,%9,%10,%11,%12,%13,%14,%15,%16,%17,%18,%19,%20,%21,%22,%23,%24,%25,%26,%27,%28,%29,%30,%31,%32,%33,%34,%35,%36,%37,%38,%39,%40,%41,%42,%43,%44,%45,%46,%47,%48,%49,%50,%51,%52,%53,%54,%55,%56,%57,%58,%59,%60,%61,%62,%63}, "
                 "{%64,%65,%66,%67}, db, p, 1, 1, %71; }\n"
                 : ACC32(d, 0), ACC32(d, 32)
                 : "r"(a0), "r"(a1), "r"(a2), "r"(a3), "r"(sd), "l"(base), "n"(D), "n"(TB));
}
template <uint64_t DA, uint64_t DB>
__device__ __forceinline__ void mma_ss56_tt(float* d, int sd, uint64_t ba, uint64_t bb) {
    asm volatile("{ .reg .pred p; .reg .b64 da, db; setp.ne.b32 p, %28, 0; add.u64 da, %29, %31; add.u64 db, %30, %32;\n"
                 "wgmma.mma_async.sync.aligned.m64n56k16.f32.bf16.bf16 "
                 "{%0,%1,%2,%3,%4,%5,%6,%7,%8,%9,%10,%11,%12,%13,%14,%15,%16,%17,%18,%19,%20,%21,%22,%23,%24,%25,%26,%27}, "
                 "da, db, p, 1, 1, 1, 1; }\n"
                 : ACC28(d)
                 : "r"(sd), "l"(ba), "l"(bb), "n"(DA), "n"(DB));
}
template <int... I> struct Seq {};
template <class F, int... I> __device__ __forceinline__ void static_for_impl(F&& f, Seq<I...>) { (f(std::integral_constant<int, I>{}), ...); }
#define FOR7(...) static_for_impl([&](auto T_) { constexpr int t = decltype(T_)::value; __VA_ARGS__; }, Seq<0, 1, 2, 3, 4, 5, 6>{})
#define FOR8(...) static_for_impl([&](auto T_) { constexpr int t = decltype(T_)::value; __VA_ARGS__; }, Seq<0, 1, 2, 3, 4, 5, 6, 7>{})
#define FOR14(...) static_for_impl([&](auto T_) { constexpr int t = decltype(T_)::value; __VA_ARGS__; }, Seq<0, 1, 2, 3, 4, 5, 6, 7, 8, 9, 10, 11, 12, 13>{})

__device__ __forceinline__ int kblk(int p, int b) { return b == 0 ? p : b - (b <= p); }
__host__ __device__ constexpr int krow(int t) { return t < 3 ? 16 * t : (t < 6 ? 56 + 16 * (t - 3) : 48); }
#define AQ(A, b, t) ((t) < 3 ? A[2 * (b)][4 * (t)] : (t) < 6 ? A[2 * (b) + 1][4 * ((t) - 3)] : A[2 * (b)][12]), \
                    ((t) < 3 ? A[2 * (b)][4 * (t) + 1] : (t) < 6 ? A[2 * (b) + 1][4 * ((t) - 3) + 1] : A[2 * (b)][13]), \
                    ((t) < 3 ? A[2 * (b)][4 * (t) + 2] : (t) < 6 ? A[2 * (b) + 1][4 * ((t) - 3) + 2] : A[2 * (b) + 1][12]), \
                    ((t) < 3 ? A[2 * (b)][4 * (t) + 3] : (t) < 6 ? A[2 * (b) + 1][4 * ((t) - 3) + 3] : A[2 * (b) + 1][13])
#define D128(off, t) ((uint64_t)(((off) + krow(t) * 128) >> 4) + ((uint64_t)((t) == 6 ? (7168 - 1024) >> 4 : 0) << 32))
#define D64(off, t) ((uint64_t)(((off) + krow(t) * 64) >> 4) + ((uint64_t)((t) == 6 ? (3584 - 512) >> 4 : 0) << 32))

#define PL(k) (((k) - 3) * PLANE)
__device__ __forceinline__ void st_word(uint32_t* p, uint32_t v) { asm volatile("st.relaxed.gpu.global.u32 [%0], %1;" ::"l"(p), "r"(v) : "memory"); }
__device__ __forceinline__ uint32_t ld_word(const uint32_t* p) { uint32_t v; asm volatile("ld.relaxed.gpu.global.u32 %0, [%1];" : "=r"(v) : "l"(p) : "memory"); return v; }
__device__ __forceinline__ void tag_slice(uint32_t* w, uint32_t tag) { w[0] = settag(w[0], tag); w[4] = settag(w[4], tag); w[8] = settag(w[8], tag); w[12] = settag(w[12], tag); }
template <int O>
__device__ __forceinline__ void send_slice(uint4* dst, int lane, const uint32_t* w) {
    st_pkt<O>(dst, w[0], w[1], w[2], w[3]);
    st_pkt<O + 32>(dst, w[4], w[5], w[6], w[7]);
    st_pkt<O + 64>(dst, w[8], w[9], w[10], w[11]);
    asm volatile("{ .reg .b64 t; mov.b64 t, {%1,%2}; st.relaxed.gpu.global.b64 [%0+%3], t; }" ::"l"((char*)dst - lane * 8), "r"(w[12]), "r"(w[13]), "n"(16 * (O + 96)) : "memory");
}
#define RW4(v, o) "+r"(v[o]), "+r"(v[(o) + 1]), "+r"(v[(o) + 2]), "+r"(v[(o) + 3])
#define RW2(v, o) "+r"(v[o]), "+r"(v[(o) + 1])
#define WR4(v, o) "=&r"(v[o]), "=&r"(v[(o) + 1]), "=&r"(v[(o) + 2]), "=&r"(v[(o) + 3])
#define LDP(a, b, c, d, addr, off) "ld.relaxed.gpu.global.b128 q, [" addr "+" off "];\n mov.b128 {" a "," b "," c "," d "}, q;\n"
#define LDH(a, b, addr, off) "ld.relaxed.gpu.global.b64 h, [" addr "+" off "];\n mov.b64 {" a "," b "}, h;\n"
#define VOTE_OK "and.b32 t, t, 1;\n setp.ne.u32 p, t, 0;\n vote.sync.any.pred p, p, 0xffffffff;\n @!p bra.uni DN;\n"
#define CHK(x, tag) "lop3.b32 t, " x ", " tag ", t, 0xBE;\n"
__device__ __forceinline__ void check_cnt(uint32_t v, const uint32_t* p, uint32_t target) {
    asm volatile("{ .reg .pred p; .reg .b32 n, t; mov.u32 n, 0; mov.u32 t, %2;\n LP:\n"
                 "sub.s32 t, t, %1;\n setp.lt.s32 p, t, 0;\n vote.sync.any.pred p, p, 0xffffffff;\n @!p bra.uni DN;\n ld.relaxed.gpu.global.u32 t, [%0];\n" SPIN_TAIL("7")
                 ::"l"(p), "r"(target), "r"(v) : "memory");
}
__device__ __forceinline__ void poll_cnt(const uint32_t* p, uint32_t target) {
    asm volatile("{ .reg .pred p; .reg .b32 n, t; mov.u32 n, 0;\n LP:\n"
                 "ld.relaxed.gpu.global.u32 t, [%0];\n sub.s32 t, t, %1;\n setp.lt.s32 p, t, 0;\n vote.sync.any.pred p, p, 0xffffffff;\n @!p bra.uni DN;\n" SPIN_TAIL("1")
                 ::"l"(p), "r"(target) : "memory");
}
template <int STR>
__device__ __forceinline__ void poll4_kv(uint32_t* v, const uint4* p, uint32_t tag) {
    asm volatile("{ .reg .pred p; .reg .b32 n, t; .reg .b128 q; mov.u32 n, 0;\n LP:\n"
                 LDP("%0", "%1", "%2", "%3", "%16", "0") LDP("%4", "%5", "%6", "%7", "%16", "%18")
                 LDP("%8", "%9", "%10", "%11", "%16", "%19") LDP("%12", "%13", "%14", "%15", "%16", "%20")
                 "xor.b32 t, %0, %17;\n" CHK("%4", "%17") CHK("%8", "%17") CHK("%12", "%17") VOTE_OK SPIN_TAIL("2")
                 : WR4(v, 0), WR4(v, 4), WR4(v, 8), WR4(v, 12)
                 : "l"(p), "r"(tag), "n"(16 * STR), "n"(32 * STR), "n"(48 * STR)
                 : "memory");
}
template <int B>
__device__ __forceinline__ void blk_load(uint32_t (&A)[8][14], const uint4* src, int lane) {
    ld_pkt<0>(&A[2 * B][0], src); ld_pkt<32>(&A[2 * B][4], src); ld_pkt<64>(&A[2 * B][8], src);
    ld_pkt<512>(&A[2 * B + 1][0], src); ld_pkt<544>(&A[2 * B + 1][4], src); ld_pkt<576>(&A[2 * B + 1][8], src);
    asm volatile("{ .reg .b64 h;\n" LDH("%0", "%1", "%4", "1536") LDH("%2", "%3", "%4", "9728") "}"
                 : "=&r"(A[2 * B][12]), "=&r"(A[2 * B][13]), "=&r"(A[2 * B + 1][12]), "=&r"(A[2 * B + 1][13])
                 : "l"((const char*)src - lane * 8) : "memory");
}
template <int B>
__device__ __forceinline__ void blk_check(uint32_t (&A)[8][14], const uint4* src, int lane, uint32_t tag) {
    asm volatile("{ .reg .pred p; .reg .b32 n, t; .reg .b128 q; .reg .b64 h, a8; mov.u32 n, 0;\n LP:\n"
                 "xor.b32 t, %0, %30;\n" CHK("%4", "%30") CHK("%8", "%30") CHK("%12", "%30") CHK("%16", "%30") CHK("%20", "%30") CHK("%24", "%30") CHK("%26", "%30") VOTE_OK
                 LDP("%0", "%1", "%2", "%3", "%28", "0") LDP("%4", "%5", "%6", "%7", "%28", "512") LDP("%8", "%9", "%10", "%11", "%28", "1024")
                 LDP("%12", "%13", "%14", "%15", "%28", "8192") LDP("%16", "%17", "%18", "%19", "%28", "8704") LDP("%20", "%21", "%22", "%23", "%28", "9216")
                 "mad.wide.s32 a8, %29, -8, %28;\n" LDH("%24", "%25", "a8", "1536") LDH("%26", "%27", "a8", "9728") SPIN_TAIL("3")
                 "\n and.b32 %0, %0, -2; and.b32 %4, %4, -2; and.b32 %8, %8, -2; and.b32 %12, %12, -2; and.b32 %16, %16, -2; and.b32 %20, %20, -2; and.b32 %24, %24, -2; and.b32 %26, %26, -2;"
                 : RW4(A[2 * B], 0), RW4(A[2 * B], 4), RW4(A[2 * B], 8), RW4(A[2 * B + 1], 0), RW4(A[2 * B + 1], 4), RW4(A[2 * B + 1], 8),
                   RW2(A[2 * B], 12), RW2(A[2 * B + 1], 12)
                 : "l"(src), "r"(lane), "r"(tag)
                 : "memory");
}
__device__ __forceinline__ void st_async4(uint32_t a, uint32_t x, uint32_t y, uint32_t z, uint32_t w, uint32_t bar) {
    asm volatile("st.async.weak.shared::cluster.mbarrier::complete_tx::bytes.v4.b32 [%0], {%1,%2,%3,%4}, [%5];" ::"r"(a), "r"(x), "r"(y), "r"(z), "r"(w), "r"(bar) : "memory");
}
__device__ __forceinline__ uint32_t mapa(uint32_t a, uint32_t cta) { uint32_t r; asm("mapa.shared::cluster.u32 %0, %1, %2;" : "=r"(r) : "r"(a), "r"(cta)); return r; }
__device__ __forceinline__ void stat_load(uint32_t* v, const uint4* p) { ld_pkt<0>(v, p); ld_pkt<512>(v + 4, p); }
__device__ __forceinline__ void stat_check(uint32_t* v, const uint4* p, uint32_t tag) {
    asm volatile("{ .reg .pred p; .reg .b32 n, t; .reg .b128 q; mov.u32 n, 0;\n LP:\n"
                 "xor.b32 t, %3, %9;\n" CHK("%7", "%9") VOTE_OK
                 LDP("%0", "%1", "%2", "%3", "%8", "0") LDP("%4", "%5", "%6", "%7", "%8", "8192") SPIN_TAIL("4")
                 : RW4(v, 0), RW4(v, 4) : "l"(p), "r"(tag) : "memory");
}
__device__ __forceinline__ uint32_t x_bits(const uint32_t* X) {
    uint32_t r;
    asm volatile("{ .reg .b32 a, b; prmt.b32 a, %1, %2, 0x0040; prmt.b32 b, %3, %4, 0x0040; prmt.b32 %0, a, b, 0x5410; }" : "=r"(r) : "r"(X[0]), "r"(X[4]), "r"(X[8]), "r"(X[12]));
    return r;
}
template <int O>
__device__ __forceinline__ void slice_load(uint32_t* v, const uint4* p, int lane) {
    ld_pkt<O>(v, p); ld_pkt<O + 32>(v + 4, p); ld_pkt<O + 64>(v + 8, p);
    asm volatile("{ .reg .b64 h;\n" LDH("%0", "%1", "%2", "%3") "}" : "=r"(v[12]), "=r"(v[13]) : "l"((const char*)p - lane * 8), "n"(16 * (O + 96)) : "memory");
}
template <int O>
__device__ __forceinline__ void slice_check(uint32_t* v, const uint4* p, int lane, uint32_t tag) {
    asm volatile("{ .reg .pred p; .reg .b32 n, t; .reg .b128 q; .reg .b64 h; mov.u32 n, 0;\n LP:\n"
                 "xor.b32 t, %0, %16;\n" CHK("%4", "%16") CHK("%8", "%16") CHK("%12", "%16") VOTE_OK
                 LDP("%0", "%1", "%2", "%3", "%14", "%17") LDP("%4", "%5", "%6", "%7", "%14", "%18") LDP("%8", "%9", "%10", "%11", "%14", "%19")
                 LDH("%12", "%13", "%15", "%20") SPIN_TAIL("5")
                 : RW4(v, 0), RW4(v, 4), RW4(v, 8), RW2(v, 12)
                 : "l"(p), "l"((const char*)p - lane * 8), "r"(tag), "n"(16 * O), "n"(16 * (O + 32)), "n"(16 * (O + 64)), "n"(16 * (O + 96))
                 : "memory");
}
__device__ __forceinline__ void x_fix(uint32_t* X, uint32_t bits) {
    X[0] = __byte_perm(X[0], bits, 0x3214); X[4] = __byte_perm(X[4], bits, 0x3215); X[8] = __byte_perm(X[8], bits, 0x3216); X[12] = __byte_perm(X[12], bits, 0x3217);
}
__device__ __forceinline__ void sts4(uint32_t a, uint32_t x, uint32_t y, uint32_t z, uint32_t w) {
    asm volatile("st.shared.v4.u32 [%0], {%1,%2,%3,%4};" ::"r"(a), "r"(x), "r"(y), "r"(z), "r"(w) : "memory");
}
__device__ __forceinline__ void lds4(uint32_t* v, uint32_t a) {
    asm volatile("ld.shared.v4.u32 {%0,%1,%2,%3}, [%4];" : "=r"(v[0]), "=r"(v[1]), "=r"(v[2]), "=r"(v[3]) : "r"(a) : "memory");
}
struct LnCoef { uint32_t hi, lo, sh; };
__device__ __forceinline__ LnCoef ln_coef(float sum, float sq) {
    sum += __shfl_xor_sync(0xffffffffu, sum, 1); sq += __shfl_xor_sync(0xffffffffu, sq, 1);
    sum += __shfl_xor_sync(0xffffffffu, sum, 2); sq += __shfl_xor_sync(0xffffffffu, sq, 2);
    const float mean = sum * (1.f / 448.f);
    const float var = fmaxf(fmaf(-mean, mean, sq * (1.f / 448.f)), 0.f);
    const float sc = rsqrtf(var + 1e-5f);
    LnCoef r;
    r.hi = pack2(sc, sc);
    const float lo = sc - bf_lo(r.hi), sh = -mean * sc;
    r.lo = pack2(lo, lo);
    r.sh = pack2(sh, sh);
    return r;
}
template <int B>
__device__ __forceinline__ void normalize(uint32_t (&A)[8][14], const LnCoef& c0, const LnCoef& c1) {
#pragma unroll
    for (int s = 2 * B; s < 2 * B + 2; s++)
#pragma unroll
        for (int i = 0; i < 14; i++) {
            const LnCoef& k = (i & 1) ? c1 : c0;
            asm("{ .reg .b32 t; fma.rn.bf16x2 t, %0, %2, %3; fma.rn.bf16x2 %0, %0, %1, t; }" : "+r"(A[s][i]) : "r"(k.hi), "r"(k.lo), "r"(k.sh));
        }
}
__device__ __forceinline__ void slice_stats(const uint32_t* w, float* st) {
    float a = 0.f, b = 0.f, p = 0.f, q = 0.f;
#pragma unroll
    for (int i = 0; i < 7; i++) {
        const float e0 = bf_lo(w[2 * i]), e1 = bf_hi(w[2 * i]), e2 = bf_lo(w[2 * i + 1]), e3 = bf_hi(w[2 * i + 1]);
        a += e0 + e1; b += e2 + e3;
        p = fmaf(e0, e0, p); p = fmaf(e1, e1, p); q = fmaf(e2, e2, q); q = fmaf(e3, e3, q);
    }
    a += __shfl_xor_sync(0xffffffffu, a, 1); p += __shfl_xor_sync(0xffffffffu, p, 1); b += __shfl_xor_sync(0xffffffffu, b, 1); q += __shfl_xor_sync(0xffffffffu, q, 1);
    a += __shfl_xor_sync(0xffffffffu, a, 2); p += __shfl_xor_sync(0xffffffffu, p, 2); b += __shfl_xor_sync(0xffffffffu, b, 2); q += __shfl_xor_sync(0xffffffffu, q, 2);
    st[0] = a; st[1] = p; st[2] = b; st[3] = q;
}
__device__ __forceinline__ void dual_softmax(const float* p, uint32_t* out) {
    constexpr float L = 1.4426950408889634f;
#pragma unroll
    for (int r = 0; r < 2; r++) {
        float mx = fmaxf(p[2 * r], p[2 * r + 1]), mn = fminf(p[2 * r], p[2 * r + 1]);
#pragma unroll
        for (int i = 1; i < 7; i++) {
            mx = fmaxf(mx, fmaxf(p[4 * i + 2 * r], p[4 * i + 2 * r + 1]));
            mn = fminf(mn, fminf(p[4 * i + 2 * r], p[4 * i + 2 * r + 1]));
        }
        mx = fmaxf(mx, __shfl_xor_sync(0xffffffffu, mx, 1));
        mn = fminf(mn, __shfl_xor_sync(0xffffffffu, mn, 1));
        const float bx = -mx * L, bn = mn * L;
        float ep[14], en[14], sp = 0.f, sn = 0.f;
#pragma unroll
        for (int i = 0; i < 14; i++) {
            const float v = p[4 * (i >> 1) + 2 * r + (i & 1)];
            ep[i] = ex2(fmaf(v, L, bx));
            en[i] = ex2(fmaf(v, -L, bn));
            sp += ep[i]; sn += en[i];
        }
        sp += __shfl_xor_sync(0xffffffffu, sp, 1);
        sn += __shfl_xor_sync(0xffffffffu, sn, 1);
        const float ip = rcp(sp), in = rcp(sn);
#pragma unroll
        for (int i = 0; i < 7; i++) {
            out[4 * i + r] = pack2(ep[2 * i] * ip, ep[2 * i + 1] * ip);
            out[4 * i + 2 + r] = pack2(en[2 * i] * in, en[2 * i + 1] * in);
        }
    }
}
__device__ __forceinline__ float geglu(float g, float u) {
    const float t = tanh_hw(g * fmaf(g * g, 0.7978845608028654f * 0.044715f, 0.7978845608028654f));
    const float gu = g * u;
    return fmaf(t, gu, gu);
}
__device__ __forceinline__ void phi_gemm(const float* t, float* p) {
    uint32_t w[14];
#pragma unroll
    for (int i = 0; i < 14; i++) w[i] = pack2(t[2 * i], t[2 * i + 1]);
    const uint64_t db = BASE128(OFF_WPHI, 16, 0);
    wg_fence();
    mma_rs56<0, 0>(p, w[0], w[1], w[2], w[3], 0, db);
    mma_rs56<0, 2>(p, w[4], w[5], w[6], w[7], 1, db);
    mma_rs56<0, 4>(p, w[8], w[9], w[10], w[11], 1, db);
    mma_rs56<0, 6>(p, w[12], w[13], 0u, 0u, 1, db);
    wg_commit();
    wg_wait<0>();
}

}

#define BAR(i) (bars + 8 * (i))
#define R_WAIT() mbar_wait(BAR(slot), ph)
#define WSUM(i)
#define R_ADJ (slot * (STAGE >> 4))
#define R_NEXT() do { eb2 = eb1; eb1 = BAR(B_EMPTY + slot); if (++slot == NST) { slot = 0; ph ^= 1; } } while (0)
#define R_RELEASE(k) do { if (lane == 0) mbar_arrive((k) == 1 ? eb1 : eb2); } while (0)
#define PUSH_BEGIN() do { mbar_wait(BAR(B_ACK + wgi), ackph); ackph ^= 1; } while (0)
#define PUSH_ACK() do { __syncwarp(); if (lane == 0) asm volatile("mbarrier.arrive.shared::cluster.b64 _, [%0];" ::"r"(mapa(BAR(B_ACK + wgi), hr ^ 1)) : "memory"); } while (0)

__global__ void __cluster_dims__(2, 1, 1) __launch_bounds__(384, 1)
fused_kernel(Scratch* const sc, const __nv_bfloat16* __restrict__ x_in, const __nv_bfloat16* __restrict__ w_phi, const int trips,
             const __nv_bfloat16* __restrict__ wg, const __nv_bfloat16* __restrict__ wu, const __nv_bfloat16* __restrict__ wd,
             const __grid_constant__ Maps maps) {
    extern __shared__ __align__(1024) unsigned char smem_raw[];
    const uint32_t sb = s2u(smem_raw);
    const uint32_t bars = sb + OFF_BAR;
    const int wgi = __shfl_sync(0xffffffffu, threadIdx.x >> 7, 0);
    const int hr = blockIdx.x & 1, ck = blockIdx.x >> 1;
    const int gp = (ck - 4) & 7, q7 = ((ck - 36) * 37) >> 8;
    const int pr = ck < 4 ? ck : (ck < 36 ? (ck - 4) >> 3 : q7);
    const int tile = ck < 4 ? 0 : (ck < 36 ? (gp ? 2 * gp : 1) : 2 * (ck - 36 - 7 * q7) + 3);
    const int sl = 2 * pr + hr;
    STAMP(0);
    GSTAMP(60);
    if (threadIdx.x == 256) {
#pragma unroll
        for (int i = 0; i < NST; i++) mbar_init(BAR(i), 1);
        asm volatile("fence.mbarrier_init.release.cluster;" ::: "memory");
    }
    if (threadIdx.x == 288) {
        if ((sb & 0x3FFFF) != SB0) asm volatile("trap;");
#pragma unroll
        for (int i = NST; i < B_COUNT; i++) mbar_init(BAR(i), i >= B_ACK ? 4 : (i < B_RECV ? 8 : 1));
        asm volatile("fence.mbarrier_init.release.cluster;" ::: "memory");
    }
    __syncwarp();
    asm volatile("barrier.cluster.arrive.relaxed.aligned;" ::: "memory");

    if (wgi == 2) {
        asm volatile("setmaxnreg.dec.sync.aligned.u32 40;");
        const int t128 = fresh_tid() & 127, w = __shfl_sync(0xffffffffu, t128 >> 5, 0), lane = t128 & 31;
        uint32_t e0[2] = {0, 0}, e1[2] = {0, 0}, cw_target = 0;
        if (w == 0) {
#pragma unroll 1
            for (int n = 0; n < NST; n++) {
                const uint32_t dst = sb + n * STAGE, fb = BAR(n);
                asm volatile(ELECT "mbarrier.arrive.expect_tx.shared::cta.b64 _, [%0], %1; }" ::"r"(fb), "r"(n < 2 ? 2 * STAGE : STAGE) : "memory");
                if (n < 2) {
                    tma3x(sb + OFF_H + n * STAGE, &maps.x, tile * 128 + n * 64, fb);
                    tma3x(dst, &maps.x, tile * 128 + n * 64 + 32, fb);
                } else {
                    if (n == 3) mbar_wait(BAR(1), 0);
                    const int ra = 112 * (n - 2);
                    tma2d(dst, &maps.qkv, 448 + 56 * sl, ra, fb);
                    tma2d(dst + HALF, &maps.qkv, 896 + 56 * sl, ra, fb);
                }
            }
            asm volatile("barrier.cluster.wait.aligned;" ::: "memory");
            cw_target = (ld_word(g_cw + sl * 32) & ~15u) + 16;
#pragma unroll 1
            for (int k = 0; k < 2; k++) {
                const int n = t128 + 32 * k;
                int m = n - 2 - (n > PACK);
                const bool packed = m >= 30 ? (m < 38 || m >= 52) : m >= 22;
                if (m >= 30) m -= 30;
                if (n == PACK) m = tile < 8 ? tile : tile + 14;
                const int rot = n < 8 ? 0 : pr;
                const int ra = 112 * kblk(rot, m & 3), rb = 112 * kblk(rot, 2 * m & 3), rc = 112 * kblk(rot, (2 * m + 1) & 3);
                int kind = 0, m0, m1, c0, c1, r0, r1;
                if (m < 4) { m0 = m1 = 1; c0 = 448 + 56 * sl; c1 = c0 + 448; r0 = r1 = ra; }
                else if (m < 8) { m0 = m1 = m < 6 ? 1 : 2; c0 = c1 = 56 * sl; r0 = rb; r1 = rc; }
                else if (m < 20) { m0 = 3; m1 = 4; c0 = c1 = 224 * sl + 32 * hr + 64 * ((m - 8) >> 2); r0 = r1 = ra; }
                else if (m < 22) { kind = 2; m0 = 5; m1 = 6; c0 = c1 = 224 * sl + (hr ? 0 : 192); r0 = rb; r1 = rc; }
                else { m0 = m1 = 7; c0 = c1 = 56 * (2 * ((pr + (m >> 1) - 10) & 3) + hr); r0 = 224 * (sl ^ (m & 1)); r1 = r0 + 112; }
                if (packed) { kind = 1; r0 = sl * 16 + (m < 8 ? m : m - 14); r1 = 0; }
                e0[0] = e0[1]; e1[0] = e1[1];
                e0[1] = kind | (m0 << 2) | (m1 << 6) | (c0 << 10) | (c1 << 21);
                e1[1] = r0 | (r1 << 16);
            }
        } else {
            const int j = t128 - 32;
            asm volatile("barrier.cluster.wait.aligned;" ::: "memory");
            uint2 wv[7];
            const int k = j < 56 ? j : 55, hh = k >= 28;
#pragma unroll
            for (int i = 0; i < 7; i++) wv[i] = __ldg(reinterpret_cast<const uint2*>(w_phi + (sl * 56 + k) * 28) + i);
#pragma unroll 1
            for (int i = j; i < 7168 / 16; i += 96) sts4(sb + OFF_WPHI + i * 16, 0, 0, 0, 0);
            bar_sync(5, 96);
            if (j < 56) {
                uint32_t a4[4];
#pragma unroll
                for (int q = 0; q < 4; q++) a4[q] = sb + OFF_WPHI + (4 * hh + q) * 128 + ((((k >> 3) ^ (4 * hh + q)) & 7) << 4) + (k & 7) * 2;
                FOR14(const uint32_t v = (t & 1) ? wv[t >> 1].y : wv[t >> 1].x;
                      asm volatile("{ .reg .b16 l, h; mov.b32 {l, h}, %2; st.shared.u16 [%0+%3], l; st.shared.u16 [%1+%3], h; }"
                                   ::"r"(a4[t >= 7 ? 2 : 0]), "r"(a4[t >= 7 ? 3 : 1]), "r"(v), "n"((t % 7) * 1024) : "memory"));
            }
            __syncwarp();
            fence_async();
            bar_arrive(1, 224);
            bar_arrive(9, 224);
            if (w == 1) {
                mbar_wait(BAR(2), 0);
                mbar_wait(BAR(2), 1);
                const int b = blockIdx.x;
                asm volatile(ELECT "cp.async.bulk.prefetch.L2.global [%0], %1; }" ::"l"(wg + b * 6272), "r"(12544) : "memory");
                asm volatile(ELECT "cp.async.bulk.prefetch.L2.global [%0], %1; }" ::"l"(wu + b * 6272), "r"(12544) : "memory");
                asm volatile(ELECT "cp.async.bulk.prefetch.L2.global [%0], %1; }" ::"l"(wd + b * 6272), "r"(12544) : "memory");
            }
        }
        uint32_t kseq = ld_word(g_c1 + (sl * 8 * 16 + tile) * 32);
        int slot = 0, ph = 0, n = NST;
#pragma unroll 1
        for (int layer = 0; layer < 3; layer++) {
            if (w == 0) {
                const int nend = layer == 0 ? 11 : (layer == 1 ? 42 : 63);
#pragma unroll 1
                for (; n < nend; n++) {
                const uint32_t w0 = __shfl_sync(0xffffffffu, n < 32 ? e0[0] : e0[1], n & 31), w1 = __shfl_sync(0xffffffffu, n < 32 ? e1[0] : e1[1], n & 31);
                const uint32_t dst = sb + slot * STAGE, fb = BAR(n == PACK ? B_PACK : slot);
                const CUtensorMap* m0 = &maps.x + ((w0 >> 2) & 15);
                const CUtensorMap* m1 = &maps.x + ((w0 >> 6) & 15);
                const int c0 = (w0 >> 10) & 2047, c1 = w0 >> 21, r0 = w1 & 0xffff, r1 = w1 >> 16;
                if (n == 25) {
                    int it = 0;
                    uint32_t v;
                    do { asm volatile("ld.acquire.gpu.global.u32 %0, [%1];" : "=r"(v) : "l"(g_cw + sl * 32) : "memory"); } while ((int)(v - cw_target) < 0 && ++it < 0x400000);
                    asm volatile("fence.proxy.async.global;" ::: "memory");
                    __syncwarp();
                }
                mbar_wait(BAR(B_EMPTY + slot), ph);
                __syncwarp();
                asm volatile(ELECT "mbarrier.arrive.expect_tx.shared::cta.b64 _, [%0], %1; }" ::"r"(fb), "r"(STAGE) : "memory");
                if ((w0 & 3) == 0) {
                    tma2d(dst, m0, c0, r0, fb);
                    tma2d(dst + HALF, m1, c1, r1, fb);
                } else if (w0 & 1) {
                    asm volatile(ELECT "cp.async.bulk.shared::cluster.global.mbarrier::complete_tx::bytes [%0], [%1], %2, [%3]; }"
                                 ::"r"(dst), "l"(reinterpret_cast<const char*>(g_wp) + (size_t)r0 * STAGE), "r"(STAGE), "r"(fb) : "memory");
                } else {
                    tma2d(dst, m0, c0, r0, fb); tma2d(dst + 7168, m0, c0, r1, fb);
                    tma2d(dst + HALF, m1, c0, r0, fb); tma2d(dst + HALF + 7168, m1, c0, r1, fb);
                }
                if (n == PACK) asm volatile(ELECT "mbarrier.arrive.shared::cta.b64 _, [%0]; }" ::"r"(BAR(slot)) : "memory");
                if (++slot == NST) { slot = 0; ph ^= 1; }
                }
            } else if (w == 1 && layer == 1) {
                constexpr int ps = PACK % NST;
                mbar_wait(BAR(B_PACK), 0);
                asm volatile("{ .reg .pred e; elect.sync _|e, 0xffffffff;\n"
                             "@e cp.async.bulk.global.shared::cta.bulk_group [%0], [%1], %2;\n"
                             "@e cp.async.bulk.commit_group;\n"
                             "@e cp.async.bulk.wait_group.read 0;\n"
                             "@e mbarrier.arrive.shared::cta.b64 _, [%3], 8;\n"
                             "@e cp.async.bulk.wait_group 0;\n"
                             "@e fence.proxy.async.global;\n"
                             "@e red.release.gpu.global.add.u32 [%4], 1; }"
                             ::"l"(reinterpret_cast<char*>(g_wp) + (size_t)(sl * 16 + tile) * STAGE), "r"(sb + ps * STAGE), "r"(STAGE), "r"(BAR(B_EMPTY + ps)), "l"(g_cw + sl * 32) : "memory");
                __syncwarp();
            }
            if (layer < 2) {
            const uint32_t tag = layer ^ 1;
            kseq++;
            bar_sync(7, 384);
            ASTAMP(0);
            if (tile < 15) {
                const int sq = lane >> 3, pk = 8 * w + (lane & (tile == 14 ? 3 : 7));
                uint32_t v[16];
                if (layer == 0) poll_cnt(g_c1 + ((sl * 8 + (w >> 1) * 4 + (tile >> 2)) * 16 + (lane & 15)) * 32, kseq);
                ASTAMP(1);
                poll4_kv<32>(v, g_kv1 + ((sl * 16 + tile) * 16 + 4 * sq) * 32 + pk, tag);
#pragma unroll
                for (int k = 0; k < 4; k++) {
                    float lo = (bf_lo(v[k]) + bf_lo(v[4 + k])) + (bf_lo(v[8 + k]) + bf_lo(v[12 + k]));
                    float hi = (bf_hi(v[k]) + bf_hi(v[4 + k])) + (bf_hi(v[8 + k]) + bf_hi(v[12 + k]));
                    lo += __shfl_xor_sync(0xffffffffu, lo, 8); hi += __shfl_xor_sync(0xffffffffu, hi, 8);
                    lo += __shfl_xor_sync(0xffffffffu, lo, 16); hi += __shfl_xor_sync(0xffffffffu, hi, 16);
                    v[k] = pack2(lo, hi);
                }
                if (sq == 0) st_pkt<0>(g_kv2 + sl * 512 + 32 * tile + pk, settag(v[0], tag), v[1], v[2], v[3]);
            }
            ASTAMP(2);
            {
                const int item = t128 < 112 ? t128 : 112 + (t128 & 3), d = item >> 1;
                const int cc = t128 < 112 ? 2 * (d >= 28) + (item & 1) : item - 112;
                const int r = t128 < 112 ? d : 56 + (cc >> 1) + 2 * ((t128 - 112) >> 2);
                uint32_t ra = sb + OFF_KVB + r * 128 + 4 * cc, rx = (r & 7) << 4;
                asm volatile("" : "+r"(ra), "+r"(rx));
                FOR14(asm volatile("st.shared.u32 [%0+%2], %1;" ::"r"((ra ^ 8) + (((t & 7) << 4) ^ rx)), "r"(0), "n"((t >> 3) * 8192) : "memory"));
                uint32_t v[16];
                asm volatile("" : "+r"(ra), "+r"(rx));
                poll4_kv<8>(v, g_kv2 + sl * 512 + (item >> 3) * 32 + (item & 7), tag);
                FOR14(asm volatile("st.shared.u32 [%0+%2], %1;" ::"r"(ra + (((t & 7) << 4) ^ rx)), "r"(v[t < 7 ? t : t + 1]), "n"((t >> 3) * 8192) : "memory"));
                fence_async();
            }
            bar_arrive(3, 384);
            ASTAMP(3);
            }
        }
    } else {
        asm volatile("setmaxnreg.inc.sync.aligned.u32 232;");
        const int tid = fresh_tid(), lane = tid & 31, t128 = tid & 127, g = lane >> 2, c = lane & 3;
        const int wu = __shfl_sync(0xffffffffu, tid >> 5, 0), w = wu & 3;
        uint4* const xp0 = g_ex + 3 * PLANE + ((tile * 2 + wgi) * 8) * 512 + w * 128 + lane;
        const uint32_t hbuf = sb + OFF_H + wgi * STAGE;
        uint32_t slot = 0, ph = 0, eb1 = 0, eb2 = 0, ackph = 0, rcvph = 0, gatph = 0, swp = 0;
        uint32_t ppid = 6;
#define cx(s) (reinterpret_cast<uint32_t*>(again(xp0) - lane + PL(1) + 112 + (s) * 512))
#define stp (again(xp0) - lane + g + PL(0) + 112)
        uint32_t seq = ld_word(cx(sl));
        uint32_t kseq = ld_word(g_c1 + ((sl * 8 + (tid >> 5)) * 16 + tile) * 32);
        uint32_t stag = ld_word(reinterpret_cast<const uint32_t*>(stp + sl * 512) + 3) & 1;
        asm volatile("barrier.cluster.wait.aligned;" ::: "memory");
        STAMP(1);
        uint32_t X[14];
        const uint32_t x0row = (w < 2 ? hbuf : sb + wgi * STAGE) + ((w & 1) * 16 + (lane & 15)) * 128;
        mbar_wait(BAR(wgi), 0);
        STAMP(51);
#pragma unroll
        for (int j = 0; j < 4; j++) {
            const int G = 7 * sl + min(2 * j + (lane >> 4), 6);
            uint32_t q2, q3;
            asm volatile("ldmatrix.sync.aligned.m8n8.x4.shared.b16 {%0,%1,%2,%3}, [%4];" : "=r"(X[4 * j]), "=r"(X[4 * j + 1]), "=r"(q2), "=r"(q3)
                         : "r"(x0row + (G >> 3) * 4096 + (((G ^ lane) & 7) << 4)) : "memory");
            if (j < 3) { X[(4 * j + 2) % 14] = q2; X[(4 * j + 3) % 14] = q3; }
        }
#define PUSH_SLICE(W)                                                                          \
    {                                                                                          \
        if (t128 == 0) mbar_expect_tx(BAR(B_RECV + wgi), 7168);                                \
        PUSH_BEGIN();                                                                          \
        const uint32_t ra = mapa(hbuf + 24576 + t128 * 16, hr ^ 1), rb = mapa(sb + OFF_XR + wgi * 3072, hr ^ 1), rbar = mapa(BAR(B_RECV + wgi), hr ^ 1); \
        st_async4(ra, W[0], W[1], W[2], W[3], rbar);                                           \
        st_async4(ra + 2048, W[4], W[5], W[6], W[7], rbar);                                    \
        st_async4(rb + t128 * 16, W[8], W[9], W[10], W[11], rbar);                             \
        asm volatile("st.async.weak.shared::cluster.mbarrier::complete_tx::bytes.v2.b32 [%0], {%1,%2}, [%3];" ::"r"(rb + 2048 + t128 * 8), "r"(W[12]), "r"(W[13]), "r"(rbar) : "memory"); \
    }
#define PULL_SLICE(W)                                                                          \
    {                                                                                          \
        uint32_t t0, t1;                                                                       \
        mbar_wait(BAR(B_RECV + wgi), rcvph);                                                   \
        rcvph ^= 1;                                                                            \
        lds4(&A[1][0], hbuf + 24576 + t128 * 16);                                              \
        lds4(&A[1][4], hbuf + 26624 + t128 * 16);                                              \
        lds4(&A[1][8], sb + OFF_XR + wgi * 3072 + t128 * 16);                                  \
        asm volatile("ld.shared.v2.u32 {%0,%1}, [%2];" : "=r"(t0), "=r"(t1) : "r"(sb + OFF_XR + wgi * 3072 + 2048 + t128 * 8) : "memory"); \
        _Pragma("unroll") for (int i = 0; i < 12; i++) A[0][i] = (i & 3) ? W[i] : W[i] & ~1u;  \
        A[1][0] &= ~1u; A[1][4] &= ~1u; A[1][8] &= ~1u;                                        \
        A[0][12] = (hr ? t0 : W[12]) & ~1u; A[0][13] = hr ? t1 : W[13];                        \
        A[1][12] = (hr ? W[12] : t0) & ~1u; A[1][13] = hr ? W[13] : t1;                        \
        asm volatile("" : RW4(A[0], 0), RW4(A[0], 4), RW4(A[0], 8), RW2(A[0], 12), RW4(A[1], 0), RW4(A[1], 4), RW4(A[1], 8), RW2(A[1], 12)); \
        swp = hr * 448;                                                                        \
    }
#define SWB(b, t, db, sh) ((b) == 0 && (t) < 6 ? ((t) < 3 ? db##p : db##m) : db)
#define DECL_DB(b, MK, lbo, sh) const uint64_t db = MK(0, lbo, R_ADJ), dbp = (b) == 0 ? MK(0, lbo, R_ADJ + (swp >> (sh))) : db, dbm = (b) == 0 ? MK(0, lbo, R_ADJ - (swp >> (sh))) : db;
#define EARLY 1
#define EARLYK 1
#define PPB 2
#define PP_WAIT() if (wgi == 1) { bar_sync(ppid, 256); ppid ^= 14; }
#define PP_GO() if (wgi == 0) { bar_arrive(ppid, 256); ppid ^= 14; }
#define GAT_ISSUE(base)                                                                        \
    {                                                                                          \
        const char* gs = reinterpret_cast<const char*>(g_ex + 3 * PLANE + (base) + (tile * 16 + wgi * 8 + 2 * kblk(pr, GB) + hr) * 512 + w * 128); \
        const uint32_t gd = hbuf + w * 3584 + hr * 1792, gb = BAR(B_GAT + wu);                 \
        asm volatile("{ .reg .pred e; elect.sync _|e, 0xffffffff;\n"                           \
                     "@e mbarrier.arrive.expect_tx.shared::cta.b64 _, [%2], 3584;\n"           \
                     "@e cp.async.bulk.shared::cluster.global.mbarrier::complete_tx::bytes.multicast::cluster [%0], [%1], 1792, [%2], %3; }" \
                     ::"r"(gd), "l"(gs), "r"(gb), "h"((uint16_t)3) : "memory");                \
        __syncwarp();                                                                          \
    }
#define GAT_FETCH()                                                                            \
    {                                                                                          \
        mbar_wait(BAR(B_GAT + wu), gatph);                                             \
        gatph ^= 1;                                                                            \
        const uint32_t ga = hbuf + w * 3584 + lane * 16;                                       \
        _Pragma("unroll") for (int s2 = 0; s2 < 2; s2++) {                                     \
            lds4(&A[2 * GB + s2][0], ga + s2 * 1792); lds4(&A[2 * GB + s2][4], ga + s2 * 1792 + 512); lds4(&A[2 * GB + s2][8], ga + s2 * 1792 + 1024); \
            asm volatile("ld.shared.v2.u32 {%0,%1}, [%2];" : "=r"(A[2 * GB + s2][12]), "=r"(A[2 * GB + s2][13]) : "r"(ga - lane * 8 + s2 * 1792 + 1536) : "memory"); \
        }                                                                                      \
    }
#define PT 3
#define PREP(b, t, remote)                                                                     \
    if constexpr ((b) < 3 && (t) == PT) {                                                      \
        wg_commit();                                                                           \
        STAMP(80 + 8 * (step & 1) + 2 * (b));                                                  \
        if constexpr (GB == 1 && (b) == 0) { if (remote) GAT_FETCH() }                         \
        if (remote) blk_check<((b) + 1) & 3>(A, BLK(xsrc, (b) + 1), lane, xtag);               \
        STAMP(81 + 8 * (step & 1) + 2 * (b));                                                  \
        if constexpr ((b) == 0) { if (remote) blk_load<3>(A, BLK(xsrc, 3), lane); }            \
        normalize<((b) + 1) & 3>(A, k0, k1);                                                   \
        asm volatile("" : RW4(A[(2 * (b) + 2) & 7], 0), RW4(A[(2 * (b) + 2) & 7], 4), RW4(A[(2 * (b) + 2) & 7], 8), RW2(A[(2 * (b) + 2) & 7], 12), \
                          RW4(A[(2 * (b) + 3) & 7], 0), RW4(A[(2 * (b) + 3) & 7], 4), RW4(A[(2 * (b) + 3) & 7], 8), RW2(A[(2 * (b) + 3) & 7], 12)); \
        wg_fence();                                                                            \
    }                                                                                          \
    if constexpr ((b) == 3 && ((t) == 0 || (t) == 6)) { STAMP(86 + 8 * (step & 1) + (t) / 6); }
#define BLK(base, b) ((base) + kblk(pr, b) * 1024)

#pragma unroll 1
        for (int step = 0; step < 4; step++) {
            const uint32_t tag = (step >> 1) ^ 1;
            const int so = (step >> 1) * 24 + (step & 1) * 12;
            (void)so;
            uint32_t A[8][14];
            uint4* const xsrc = xp0 + ((step & 1) ? PL(2) : PL(0));
            const uint32_t xtag = (step & 1) ? tag : ((seq >> 3) & 1) ^ 1;
            uint32_t xbits;
            {
                float st[4];
                slice_stats(X, st);
                stag ^= 1;
                xbits = x_bits(X);
                tag_slice(X, xtag);
                if (step) send_slice<0>(xsrc + sl * 512, lane, X);
                if (c == 0) st_pkt<0>(stp + sl * 512, __float_as_uint(st[0]), __float_as_uint(st[1]), __float_as_uint(st[2]), settag(__float_as_uint(st[3]), stag));
            }
            STAMP(2 + so);
            uint32_t sv[8];
            if (step == 0) {
                const int rr = lane & 7, hi = lane >> 4;
                const uint32_t rowa = (w < 2 ? hbuf : sb + wgi * STAGE) + ((w & 1) * 16 + (lane & 15)) * 128;
                uint32_t xr[8];
#pragma unroll
                for (int j = 0; j < 8; j++) xr[j] = rowa + ((((j + hi) ^ rr) & 7) << 4) + (j == 7 ? hi * 4096 : 0);
#define X0_BLOCK(b)                                                                            \
    FOR7(constexpr int G = 14 * (b) + (t < 3 ? 2 * t : (t < 6 ? 2 * t + 1 : 6));               \
         uint32_t q0, q1, q2, q3;                                                              \
         const uint32_t ad = t < 6 ? xr[G & 7] : rowa + ((G + 7 * hi) >> 3) * 4096 + ((((G + 7 * hi) ^ rr) & 7) << 4); \
         asm volatile("ldmatrix.sync.aligned.m8n8.x4.shared.b16 {%0,%1,%2,%3}, [%4+%5];" : "=r"(q0), "=r"(q1), "=r"(q2), "=r"(q3) \
                      : "r"(ad), "n"(t < 6 ? (G >> 3) * 4096 : 0) : "memory");                 \
         if (t < 3) { A[2 * (b)][4 * t] = q0; A[2 * (b)][4 * t + 1] = q1; A[2 * (b)][4 * t + 2] = q2; A[2 * (b)][4 * t + 3] = q3; } \
         else if (t < 6) { A[2 * (b) + 1][(4 * t - 12) & 15] = q0; A[2 * (b) + 1][((4 * t - 12) & 15) + 1] = q1; A[2 * (b) + 1][((4 * t - 12) & 15) + 2] = q2; A[2 * (b) + 1][((4 * t - 12) & 15) + 3] = q3; } \
         else { A[2 * (b)][12] = q0; A[2 * (b)][13] = q1; A[2 * (b) + 1][12] = q2; A[2 * (b) + 1][13] = q3; });
                X0_BLOCK(0) X0_BLOCK(1) X0_BLOCK(2) X0_BLOCK(3)
                mbar_wait(BAR(wgi ^ 1), 0);
                R_NEXT();
                R_NEXT();
                stat_load(sv, stp + c * 1024);
                stat_check(sv, stp + c * 1024, stag);
                STAMP(52 + step);
            } else {
                PUSH_SLICE(X)
                stat_load(sv, stp + c * 1024);
                kill<14>(A[2]); kill<14>(A[3]); kill<14>(A[4]); kill<14>(A[5]); kill<14>(A[6]); kill<14>(A[7]);
                PULL_SLICE(X)
                stat_check(sv, stp + c * 1024, stag);
                STAMP(52 + step);
                if (GB == 1) GAT_ISSUE((step & 1) ? PL(2) : PL(0))
                else blk_load<1>(A, BLK(xsrc, 1), lane);
            }
            LnCoef k0, k1;
            {
                k0 = ln_coef(__uint_as_float(sv[0]) + __uint_as_float(sv[4]), __uint_as_float(sv[1]) + __uint_as_float(sv[5]));
                k1 = ln_coef(__uint_as_float(sv[2]) + __uint_as_float(sv[6]), __uint_as_float(sv[3] & ~1u) + __uint_as_float(sv[7] & ~1u));
            }
            if (step) {
                if (GB == 2) GAT_ISSUE((step & 1) ? PL(2) : PL(0))
                else blk_load<2>(A, BLK(xsrc, 2), lane);
            }
            STAMP(3 + so);
            GSTAMP(76 + step);

            if ((step & 1) == 0) {
                float tq[28];
                {
                    float av[28];
#define KV_BLOCK(b)                                                                           \
    if (GB == 2 && (b) == 1 && step) GAT_FETCH()                                                         \
    if ((b) == 2) PUSH_ACK();                                                                 \
    if (QE && (b) == 1) R_RELEASE(2);                                                         \
    if (QE && (b) == 2) { wg_wait<2>(); R_RELEASE(2); }                                       \
    R_WAIT();                                                                                 \
    if ((b) == PPK) { PP_WAIT() }                                                             \
    { DECL_DB(b, BASE128, 16, 0)                                                              \
    wg_fence();                                                                               \
    FOR7(mma_rs56<1, D128(0, t)>(tq, AQ(A, b, t), (b) + t > 0, SWB(b, t, db, 0));             \
         mma_rs56<1, D128(HALF, t)>(av, AQ(A, b, t), (b) + t > 0, SWB(b, t, db, 0));          \
         PREP(b, t, step)); }                                                                 \
    wg_commit();                                                                              \
    if ((b) == 3 && PPK < 4) { PP_GO() }                                                      \
    R_NEXT();
                    if (EARLYK == 0 || step == 0) R_RELEASE(2);
                    normalize<0>(A, k0, k1);
                    KV_BLOCK(0) KV_BLOCK(1) KV_BLOCK(2) KV_BLOCK(3)
                    wg_wait<0>();
                    if (lane < (QE ? 3 : NST)) mbar_arrive(BAR(B_EMPTY + (slot + NST - 1 - lane) % NST));
                    STAMP(4 + so);
                    WSUM(80 + 7 * (step >> 1));
                    const int m = lane >> 3, rr = lane & 7;
                    const uint32_t rowa = hbuf + 16384 + (w * 16 + rr + 8 * (m & 1)) * 128;
                    const uint32_t one = c == 0 ? 0x00003f80u : 0u;
                    if (step == 0) { bar_sync(wgi ? 9 : 1, 224); }
#pragma unroll
                    for (int j = 0; j < 4; j++) {
                        const uint32_t a = rowa + (((2 * j + (m >> 1)) ^ rr) << 4);
                        if (j < 3) stsm4(a, pack2(av[8 * j], av[8 * j + 1]), pack2(av[8 * j + 2], av[8 * j + 3]), pack2(av[8 * j + 4], av[8 * j + 5]), pack2(av[8 * j + 6], av[8 * j + 7]));
                        else stsm4(a, pack2(av[24], av[25]), pack2(av[26], av[27]), one, one);
                    }
                }
                uint32_t PH[28];
                int it = 1;
#pragma unroll 1
                do {
                    float pp[28];
                    phi_gemm(tq, pp);
                    dual_softmax(pp, PH);
                    if (((trips >> (it + 1)) & 1) == 0) continue;
                    {
                        const int m = lane >> 3, rr = lane & 7;
                        const uint32_t rowa = hbuf + (w * 16 + rr + 8 * (m & 1)) * 128;
#pragma unroll
                        for (int j = 0; j < 7; j++) {
                            const int cg = 2 * j + (m >> 1), hi = cg >= 7;
                            stsm4(rowa + hi * 8192 + (((cg - 7 * hi) ^ rr) << 4), PH[4 * j], PH[4 * j + 1], PH[4 * j + 2], PH[4 * j + 3]);
                        }
                    }
                    fence_async();
                    STAMP(5 + so);
#define Q_STAGE(b0)                                                                           \
    R_WAIT();                                                                                 \
    { DECL_DB(b0, BASE128, 16, 0)                                                             \
    wg_fence();                                                                               \
    FOR7(mma_rs56<1, D128(0, t)>(tq, AQ(A, b0, t), (b0) + t > 0, SWB(b0, t, db, 0)));         \
    FOR7(mma_rs56<1, D128(HALF, t)>(tq, AQ(A, (b0) + 1, t), 1, db)); }                        \
    wg_commit();                                                                              \
    R_NEXT();
                    if (QE && wgi == 0) { kill<28>(tq); Q_STAGE(0) Q_STAGE(2) wg_wait<1>(); R_RELEASE(2); wg_wait<0>(); R_RELEASE(1); }
                    bar_sync(2, 256);
                    float kv[28];
                    const uint64_t da = BASE128(OFF_H + 16384, 16, 0), dbk = BASE128(OFF_H, 16, wgi * 512);
                    wg_fence();
                    FOR8(constexpr uint64_t o = ((t >> 2) * STAGE + (t & 3) * 2048) >> 4; mma_ss56_tt<o, o>(kv, t > 0, da, dbk));
                    wg_commit();
                    wg_wait<0>();
#pragma unroll
                    for (int hf = 0; hf < 2; hf++) {
                        const int d = 16 * w + g + 8 * hf;
                        if ((d < 56 && (d >= 28) == (c >= 2)) || d == 56) {
                            const int item = d < 56 ? 2 * d + (c & 1) : 112 + c;
                            uint4* dst = g_kv1 + ((sl * 16 + (item >> 3)) * 16 + tile) * 32 + wgi * 16 + (item & 7);
#define KVW(i) pack2(kv[4 * (i) + 2 * hf], kv[4 * (i) + 2 * hf + 1])
                            st_pkt<0>(dst, settag(KVW(0), tag), KVW(1), KVW(2), KVW(3));
                            st_pkt<8>(dst, settag(KVW(4), tag), KVW(5), KVW(6), 0u);
                        }
                    }
                    __syncwarp();
                    kseq++;
                    if (lane == 0) st_word(g_c1 + ((sl * 8 + (tid >> 5)) * 16 + tile) * 32, kseq);
                    bar_arrive(7, 384);
                    STAMP(6 + so);
                    if (!QE || wgi == 1) { kill<28>(tq); Q_STAGE(0) Q_STAGE(2) wg_wait<1>(); R_RELEASE(2); wg_wait<0>(); R_RELEASE(1); }
                    STAMP(7 + so);
                    kill<28>(PH);
                } while (((trips >> (++it)) & 1));
                STAMP(8 + so);
                if (step) {
                    slice_load<PL(0)>(X, xp0 + sl * 512, lane);
                } else {
                    const uint32_t* xp = reinterpret_cast<const uint32_t*>(x_in + (size_t)(tile * 128 + wu * 16 + g) * 448 + 56 * sl + 2 * c);
#pragma unroll
                    for (int i = 0; i < 7; i++) { X[2 * i] = __ldg(xp + 4 * i); X[2 * i + 1] = __ldg(xp + 4 * i + 8 * 224); }
                }
                bar_sync(3, 384);
                STAMP(9 + so);
                const uint4* const osrc = xp0 + PL(1);
                {
                    float nm[32];
                    const uint64_t db = BASE128(OFF_KVB, 16, 0);
                    wg_fence();
                    FOR7(mma_rs64<0, ((t >> 2) * 8192 + (t & 3) * 32) / 16>(nm, PH[4 * t], PH[4 * t + 1], PH[4 * t + 2], PH[4 * t + 3], t > 0, db));
                    wg_commit();
                    wg_wait<0>();
                    const float i00 = rcp(nm[28] + 1e-6f), i01 = rcp(nm[29] + 1e-6f), i10 = rcp(nm[30] + 1e-6f), i11 = rcp(nm[31] + 1e-6f);
                    const float m0 = c >= 2 ? i01 : i00, m1 = c >= 2 ? i11 : i10;
                    uint32_t O[14];
#pragma unroll
                    for (int i = 0; i < 7; i++) {
                        const float f0 = i < 3 ? i00 : (i > 3 ? i01 : m0), f1 = i < 3 ? i10 : (i > 3 ? i11 : m1);
                        O[2 * i] = pack2(nm[4 * i] * f0, nm[4 * i + 1] * f0);
                        O[2 * i + 1] = pack2(nm[4 * i + 2] * f1, nm[4 * i + 3] * f1);
                    }
                    if (OST) { PP_WAIT() }
                    tag_slice(O, tag);
                    send_slice<PL(1)>(xp0 + sl * 512, lane, O);
                    seq++;
                    if (lane == 0) st_word(cx(sl), seq);
                    STAMP(10 + so);
                    PUSH_SLICE(O)
                    if (OST == 1) { PP_GO() }
                    const uint32_t cv = ld_word(cx(lane & 7));
                    PULL_SLICE(O)
                    check_cnt(cv, cx(lane & 7), seq);
                    if (OST == 2) { PP_GO() }
                    STAMP(56 + (step >> 1));
                    GAT_ISSUE(PL(1))
                    blk_load<3 - GB>(A, BLK(osrc, 3 - GB), lane);
                }
                float ao[28];
#define WO_BLOCK(b)                                                                           \
    if ((b) > 0) blk_check<b>(A, BLK(osrc, b), lane, tag);                                    \
    if (((b) & 1) == 0) R_WAIT();                                                             \
    { DECL_DB(b, BASE128, 16, 0)                                                              \
    wg_fence();                                                                               \
    FOR7(mma_rs56<1, D128(((b) & 1) * HALF, t)>(ao, AQ(A, b, t), (b) + t > 0, SWB(b, t, db, 0))); } \
    wg_commit();                                                                              \
    if ((b) & 1) R_NEXT();
                WO_BLOCK(0)
                STAMP(11 + so);
                blk_load<3>(A, BLK(osrc, 3), lane);
                if (GB == 1) GAT_FETCH()
                WO_BLOCK(1)
                if (GB == 2) GAT_FETCH()
                WO_BLOCK(2)
                PUSH_ACK();
                WO_BLOCK(3)
                wg_wait<0>();
                if (EARLY >= 1) R_RELEASE(2);
                if (EARLY >= 2) R_RELEASE(1);
                STAMP(12 + so);
                WSUM(86 + 7 * (step >> 1));
                x_fix(X, xbits);
#pragma unroll
                for (int i = 0; i < 14; i++) X[i] = pack2(bf_lo(X[i]) + ao[2 * i], bf_hi(X[i]) + ao[2 * i + 1]);
            } else {
                uint32_t H[56];
                float ag[64];
#define F1_EPI(dst, ng, ag)                                                                    \
    _Pragma("unroll") for (int i = 0; i < 2 * (ng); i++)                                       \
        (dst)[i] = pack2(geglu(ag[2 * i], ag[4 * (ng) + 2 * i]), geglu(ag[2 * i + 1], ag[4 * (ng) + 2 * i + 1]));
#define H_PUSH(h0, off) st_async4(rem_h + (off), H[h0], H[(h0) + 1], H[(h0) + 2], H[(h0) + 3], mapa(BAR(B_RECV2 + wgi), hr ^ 1));
#define F1_BLOCK(b, first)                                                                     \
    if ((first) && (b) < 2 && (b) >= EARLY) R_RELEASE(2);                                      \
    if (GB == 2 && (first) && (b) == 1) GAT_FETCH()                                                       \
    if ((first) && (b) == 2) PUSH_ACK();                                                       \
    R_WAIT();                                                                                  \
    if ((b) == PPB) { PP_WAIT() }                                                              \
    { DECL_DB(b, BASE128, HALF, 0)                                                             \
    wg_fence();                                                                                \
    FOR7(mma_rs128<1, D128(0, t)>(ag, AQ(A, b, t), (b) + t > 0, SWB(b, t, db, 0));             \
         if constexpr (first) { PREP(b, t, true) }); }                                         \
    wg_commit();                                                                               \
    if ((b) == 3) { PP_GO() }                                                                  \
    if ((b) > 0) { wg_wait<1>(); R_RELEASE(1); }       \
    R_NEXT();
                normalize<0>(A, k0, k1);
                F1_BLOCK(0, true) F1_BLOCK(1, true) F1_BLOCK(2, true) F1_BLOCK(3, true)
                if (t128 == 0) { mbar_expect_tx(BAR(B_RECV + wgi), 16384); mbar_expect_tx(BAR(B_RECV2 + wgi), 12288); }
                PUSH_BEGIN();
                wg_wait<0>();
                R_RELEASE(1);
                if (step == 1) R_NEXT();
                int p = 0;
#pragma unroll 1
                do {
                    STAMP(68 + p);
                    F1_EPI(H + 32, 8, ag)
                    STAMP(4 + p + so);
                    WSUM(81 + p + 7 * (step >> 1));
                    if (((trips >> (p + 1)) & 1) == 0) continue;
                    {
                        const uint32_t pk = (p ? hbuf + 16384 : sb + OFF_KVB + wgi * 8192) + w * 2048;
#pragma unroll
                        for (int k = 0; k < 4; k++) sts4(pk + k * 512 + lane * 16, H[32 + 4 * k], H[33 + 4 * k], H[34 + 4 * k], H[35 + 4 * k]);
                        fence_async();
                        __syncwarp();
                        asm volatile(ELECT "cp.async.bulk.shared::cluster.shared::cta.mbarrier::complete_tx::bytes [%0], [%1], 2048, [%2]; }"
                                     ::"r"(mapa(hbuf + p * 8192 + w * 2048, hr ^ 1)), "r"(pk), "r"(mapa(BAR(B_RECV + wgi), hr ^ 1)) : "memory");
                    }
                    kill<64>(ag);
                    F1_BLOCK(0, false) F1_BLOCK(1, false) F1_BLOCK(2, false) F1_BLOCK(3, false)
                    wg_wait<0>();
                    R_RELEASE(1);
                    kill<16>(H + 32);
                } while (((trips >> (++p)) & 1));
#pragma unroll
                for (int k = 0; k < 4; k++) lds4(H + 16 + 4 * k, hbuf + 16384 + w * 2048 + k * 512 + lane * 16);
                __syncwarp();
                if (lane == 0) asm volatile("mbarrier.arrive.shared::cluster.b64 _, [%0];" ::"r"(mapa(BAR(B_ACK2 + wgi), hr ^ 1)) : "memory");
                const uint32_t rem_h = mapa(hbuf + w * 2048 + lane * 16, hr ^ 1);
#define F1_LAST(b0)                                                                            \
    R_WAIT();                                                                                  \
    if (b0) { PP_WAIT() }                                                                      \
    { DECL_DB(b0, BASE64, HALF, 1)                                                             \
    wg_fence();                                                                                \
    FOR7(mma_rs64<1, D64(0, t)>(al, AQ(A, b0, t), (b0) + t > 0, SWB(b0, t, db, 1)));           \
    FOR7(mma_rs64<1, D64(7168, t)>(al, AQ(A, (b0) + 1, t), 1, db)); }                          \
    wg_commit();                                                                               \
    if (b0) { PP_GO() }                                                                        \
    R_NEXT();
                float al[32];
                F1_LAST(0)
                mbar_wait(BAR(B_RECV + wgi), rcvph);
                rcvph ^= 1;
                mbar_wait(BAR(B_ACK2 + wgi), step >> 1);
                H_PUSH(32, 16384) H_PUSH(36, 16896)
                F1_LAST(2)
                H_PUSH(40, 17408) H_PUSH(44, 17920)
                wg_wait<1>();
                R_RELEASE(2);
                wg_wait<0>();
                R_RELEASE(1);
                uint32_t HP[56];
#pragma unroll
                for (int k = 0; k < 4; k++) lds4(H + 4 * k, sb + OFF_KVB + wgi * 8192 + w * 2048 + k * 512 + lane * 16);
#pragma unroll
                for (int t = 0; t < 8; t++) lds4(HP + 4 * t, hbuf + (t >> 2) * 8192 + w * 2048 + (t & 3) * 512 + lane * 16);
                F1_EPI(H + 48, 4, al)
                H_PUSH(48, 24576 - w * 1024) H_PUSH(52, 25088 - w * 1024)
                STAMP(7 + so);
                WSUM(84 + 7 * (step >> 1));
                float acc[28];
                const uint32_t roA = hr ? 256u : 0u, roB = hr ? (uint32_t)-1536 : 0u;
                const uint32_t rpA = hr ? 0u : 256u, rpB = hr ? 0u : (uint32_t)-1536;
                float res[28];
                uint32_t v0[14], v1[14], P[14];
                const uint4* ps = xp0 + sl * 512;
#define F2_OWN_A()                                                                             \
    R_WAIT();                                                                                  \
    d0 = BASE128(0, 16, R_ADJ + roA); d1 = BASE128(0, 16, R_ADJ + roB);                        \
    wg_fence();                                                                                \
    FOR14(if constexpr (t < OT) mma_rs56<1, t * 128>(acc, H[4 * t], H[4 * t + 1], H[4 * t + 2], H[4 * t + 3], t > 0, d0)); \
    wg_commit();
#define F2_OWN_B()                                                                             \
    wg_fence();                                                                                \
    FOR14(if constexpr (t >= OT) mma_rs56<1, t * 128>(acc, H[4 * t], H[4 * t + 1], H[4 * t + 2], H[4 * t + 3], 1, t < 12 ? d0 : d1)); \
    wg_commit();                                                                               \
    R_NEXT();
#define F2_PEER()                                                                              \
    R_WAIT();                                                                                  \
    if (F2PP) { PP_WAIT() }                                                                    \
    d0 = BASE128(0, 16, R_ADJ + rpA); d1 = BASE128(0, 16, R_ADJ + rpB);                        \
    wg_fence();                                                                                \
    FOR14(mma_rs56<1, t * 128>(acc, HP[4 * t], HP[4 * t + 1], HP[4 * t + 2], HP[4 * t + 3], 1, t < 12 ? d0 : d1)); \
    wg_commit();                                                                               \
    if (F2PP) { PP_GO() }                                                                      \
    R_NEXT();
#define F2_TURN(u)                                                                             \
    wg_wait<1>();                                                                              \
    R_RELEASE(2);                                                                              \
    wg_wait<0>();                                                                              \
    R_RELEASE(1);                                                                              \
    _Pragma("unroll") for (int i = 0; i < 14; i++) P[i] = pack2(acc[2 * i], acc[2 * i + 1]);   \
    tag_slice(P, tag);                                                                         \
    asm volatile("" : RW4(P, 0), RW4(P, 4), RW4(P, 8), RW2(P, 12));                            \
    kill<28>(acc);                                                                             \
    F2_OWN_A()                                                                                 \
    if ((u) == 2) { slice_load<PL(3)>(v0, ps, lane); slice_load<PL(4)>(v1, ps, lane); } \
    send_slice<PL(3 + (u))>(xp0 + (2 * ((pr + (u) + 1) & 3) + hr) * 512, lane, P);             \
    seq++;                                                                                     \
    if (lane == 0) st_word(cx(sl), seq);                                                       \
    __syncwarp();                                                                              \
    STAMP(8 + (u) + so);                                                                       \
    F2_OWN_B()
                uint64_t d0, d1;
                F2_OWN_A()
                F2_OWN_B()
                R_WAIT();
                d0 = BASE128(0, 16, R_ADJ + rpA); d1 = BASE128(0, 16, R_ADJ + rpB);
                wg_fence();
                FOR8(mma_rs56<1, t * 128>(acc, HP[4 * t], HP[4 * t + 1], HP[4 * t + 2], HP[4 * t + 3], 1, d0));
                wg_commit();
                mbar_wait(BAR(B_RECV2 + wgi), step >> 1);
#pragma unroll
                for (int k = 0; k < 4; k++) lds4(HP + 32 + 4 * k, hbuf + 16384 + w * 2048 + k * 512 + lane * 16);
                lds4(HP + 48, hbuf + 24576 + w * 1024 + lane * 16);
                lds4(HP + 52, hbuf + 25088 + w * 1024 + lane * 16);
                if (step == 1) PUSH_ACK();
                wg_fence();
                FOR14(if constexpr (t >= 8) mma_rs56<1, t * 128>(acc, HP[4 * t], HP[4 * t + 1], HP[4 * t + 2], HP[4 * t + 3], 1, t < 12 ? d0 : d1));
                wg_commit();
                R_NEXT();
                F2_TURN(0)
                F2_PEER()
                F2_TURN(1)
                F2_PEER()
                F2_TURN(2)
                STAMP(64 + 8 * (step >> 1));
                slice_check<PL(3)>(v0, ps, lane, tag);
                slice_check<PL(4)>(v1, ps, lane, tag);
#pragma unroll
                for (int i = 0; i < 14; i++) { res[2 * i] = bf_lo(v0[i]) + bf_lo(v1[i]); res[2 * i + 1] = bf_hi(v0[i]) + bf_hi(v1[i]); }
                slice_load<PL(2)>(X, ps, lane);
                STAMP(65 + 8 * (step >> 1));
                const uint32_t cv = ld_word(cx(2 * ((pr + 1) & 3) + hr));
                F2_PEER()
                STAMP(66 + 8 * (step >> 1));
                check_cnt(cv, cx(2 * ((pr + 1) & 3) + hr), seq);
                STAMP(67 + 8 * (step >> 1));
                slice_load<PL(5)>(v0, ps, lane);
                x_fix(X, xbits);
                slice_check<PL(5)>(v0, ps, lane, tag);
#pragma unroll
                for (int i = 0; i < 14; i++) { res[2 * i] += bf_lo(v0[i]); res[2 * i + 1] += bf_hi(v0[i]); }
                STAMP(11 + so);
                wg_wait<0>();
                if (EARLYK >= 1) R_RELEASE(2);
                STAMP(12 + so);
                WSUM(85 + 7 * (step >> 1));
#pragma unroll
                for (int i = 0; i < 14; i++) X[i] = pack2(fmaf(res[2 * i] + acc[2 * i], 0.5f, bf_lo(X[i])), fmaf(res[2 * i + 1] + acc[2 * i + 1], 0.5f, bf_hi(X[i])));
            }
        }
        {
            const int m = lane >> 3, rr = lane & 7;
            const uint32_t ob = hbuf + w * 2048, rowa = ob + (rr + 8 * (m & 1)) * 112 + (m >> 1) * 16;
#pragma unroll
            for (int j = 0; j < 3; j++) stsm4(rowa + 32 * j, X[4 * j], X[4 * j + 1], X[4 * j + 2], X[4 * j + 3]);
            asm volatile("stmatrix.sync.aligned.m8n8.x2.shared.b16 [%0], {%1,%2};" ::"r"(ob + (rr + 8 * (m & 1)) * 112 + 96), "r"(X[12]), "r"(X[13]) : "memory");
            fence_async();
            __syncwarp();
            if (lane == 0) {
                asm volatile("cp.async.bulk.tensor.2d.global.shared::cta.bulk_group [%0, {%2, %3}], [%1];" ::"l"(&maps.out), "r"(ob), "r"(56 * sl), "r"(tile * 128 + (tid >> 5) * 16) : "memory");
                asm volatile("cp.async.bulk.commit_group;" ::: "memory");
                asm volatile("cp.async.bulk.wait_group.read 0;" ::: "memory");
            }
        }
        STAMP(50);
        GSTAMP(61);
        PDUMP();
    }
}

typedef CUresult (*EncodeFn)(CUtensorMap*, CUtensorMapDataType, cuuint32_t, void*, const cuuint64_t*, const cuuint64_t*, const cuuint32_t*,
                             const cuuint32_t*, CUtensorMapInterleave, CUtensorMapSwizzle, CUtensorMapL2promotion, CUtensorMapFloatOOBfill);

static void make_map(EncodeFn enc, CUtensorMap* m, const void* p, uint64_t cols, uint64_t rows, uint32_t bc, uint32_t br, CUtensorMapSwizzle sw) {
    cuuint64_t gd[2] = {cols, rows};
    cuuint64_t gs[1] = {cols * 2};
    cuuint32_t bd[2] = {bc, br};
    cuuint32_t es[2] = {1, 1};
    enc(m, CU_TENSOR_MAP_DATA_TYPE_BFLOAT16, 2, const_cast<void*>(p), gd, gs, bd, es, CU_TENSOR_MAP_INTERLEAVE_NONE, sw,
        CU_TENSOR_MAP_L2_PROMOTION_L2_128B, CU_TENSOR_MAP_FLOAT_OOB_FILL_NONE);
}

extern "C" void kernel_launch(void* const* d_in, const int* in_sizes, int n_in, void* d_out, int out_size) {
    (void)in_sizes; (void)n_in; (void)out_size;
    static EncodeFn enc = nullptr;
    static Scratch* scratch = nullptr;
    if (!enc) {
        void* fn = nullptr;
        cudaDriverEntryPointQueryResult qr;
        cudaGetDriverEntryPoint("cuTensorMapEncodeTiled", &fn, cudaEnableDefault, &qr);
        enc = (EncodeFn)fn;
        cudaGetSymbolAddress((void**)&scratch, g_scratch);
        cudaFuncSetAttribute(fused_kernel, cudaFuncAttributeMaxDynamicSharedMemorySize, SMEM_BYTES);
    }
    Maps maps;
    {
        cuuint64_t gd[3] = {64, 2048, 7};
        cuuint64_t gs[2] = {896, 128};
        cuuint32_t bd[3] = {64, 32, 7};
        cuuint32_t es[3] = {1, 1, 1};
        enc(&maps.x, CU_TENSOR_MAP_DATA_TYPE_BFLOAT16, 3, d_in[0], gd, gs, bd, es, CU_TENSOR_MAP_INTERLEAVE_NONE, CU_TENSOR_MAP_SWIZZLE_128B,
            CU_TENSOR_MAP_L2_PROMOTION_L2_128B, CU_TENSOR_MAP_FLOAT_OOB_FILL_NONE);
    }
    make_map(enc, &maps.out, d_out, 448, 2048, 56, 16, CU_TENSOR_MAP_SWIZZLE_NONE);
    make_map(enc, &maps.qkv, d_in[1], 1344, 448, 64, 112, CU_TENSOR_MAP_SWIZZLE_128B);
    make_map(enc, &maps.wo, d_in[3], 448, 448, 64, 112, CU_TENSOR_MAP_SWIZZLE_128B);
    make_map(enc, &maps.wg, d_in[5], 1792, 448, 64, 112, CU_TENSOR_MAP_SWIZZLE_128B);
    make_map(enc, &maps.wu, d_in[6], 1792, 448, 64, 112, CU_TENSOR_MAP_SWIZZLE_128B);
    make_map(enc, &maps.wg32, d_in[5], 1792, 448, 32, 112, CU_TENSOR_MAP_SWIZZLE_64B);
    make_map(enc, &maps.wu32, d_in[6], 1792, 448, 32, 112, CU_TENSOR_MAP_SWIZZLE_64B);
    make_map(enc, &maps.wd, d_in[7], 448, 1792, 64, 112, CU_TENSOR_MAP_SWIZZLE_128B);
    fused_kernel<<<128, 384, SMEM_BYTES>>>(scratch, (const __nv_bfloat16*)d_in[0], (const __nv_bfloat16*)d_in[2], 7, (const __nv_bfloat16*)d_in[5],
                                           (const __nv_bfloat16*)d_in[6], (const __nv_bfloat16*)d_in[7], maps);
}
```

```cpp
#include <cuda_runtime.h>
#include <cuda.h>
#include <cuda_bf16.h>
#include <stdint.h>
#include <type_traits>

#define MC 1
#define PPF 2
#define GE 0
#define ACAN 1
#define SPLIT0 1
#define OT 2
#define F2PP 0
#define PPK 2
#define QE 1
#define OST 1
#define GB 1
#define B3T 6
#define PP

namespace {

constexpr uint32_t STAGE = 28672, HALF = 14336;
constexpr int NST = 5;
constexpr uint32_t OFF_H = NST * STAGE;
constexpr uint32_t OFF_KVB = OFF_H + 2 * STAGE;
constexpr uint32_t OFF_WPHI = OFF_KVB + 16384;
constexpr uint32_t OFF_XR = OFF_WPHI + 7168;
constexpr uint32_t OFF_BAR = OFF_XR + 6144;
constexpr uint32_t SMEM_BYTES = OFF_BAR + 256 + 1536;
constexpr int B_EMPTY = NST, B_RECV = 2 * NST, B_RECV2 = B_RECV + 2, B_PACK = B_RECV2 + 2, B_GAT = B_PACK + 1, B_ACK = B_GAT + 8, B_ACK2 = B_ACK + 2, B_COUNT = B_ACK2 + 2;

constexpr int PACK = 14;

struct Maps { CUtensorMap x, qkv, wo, wg, wu, wg32, wu32, wd, out; };

}

constexpr int PLANE = 16 * 2 * 8 * 512;
struct Scratch {
    uint4 ex[6 * PLANE];
    uint4 kv1[8 * 16 * 16 * 32];
    uint4 kv2[8 * 512];
    uint32_t c1[8 * 8 * 16 * 32];
    uint32_t cw[8 * 32];
    uint4 wp[8 * 32 * (HALF / 16)];
};
__device__ __align__(1024) Scratch g_scratch;
#define g_ex (sc->ex)
#define g_kv1 (sc->kv1)
#define g_kv2 (sc->kv2)
#define g_c1 (sc->c1)
#define g_cw (sc->cw)
#define g_wp (sc->wp)
#define STAMP(i)
#define GSTAMP(i)
#define PDUMP()
#define ASTAMP(i)

namespace {

__device__ __forceinline__ int fresh_tid() { int t; asm volatile("mov.u32 %0, %%tid.x;" : "=r"(t)); return t; }
__device__ __forceinline__ uint4* again(uint4* p) { asm volatile("" : "+l"(p)); return p; }
template <int N> __device__ __forceinline__ void kill(uint32_t* v) {
#pragma unroll
    for (int i = 0; i < N; i++) v[i] = 0;
}
template <int N> __device__ __forceinline__ void kill(float* v) {
#pragma unroll
    for (int i = 0; i < N; i++) v[i] = 0.f;
}
__device__ __forceinline__ uint32_t s2u(const void* p) { return (uint32_t)__cvta_generic_to_shared(p); }
__device__ __forceinline__ void mbar_init(uint32_t a, uint32_t c) { asm volatile("mbarrier.init.shared::cta.b64 [%0], %1;" ::"r"(a), "r"(c) : "memory"); }
__device__ __forceinline__ void mbar_expect_tx(uint32_t a, uint32_t b) { asm volatile("mbarrier.arrive.expect_tx.shared::cta.b64 _, [%0], %1;" ::"r"(a), "r"(b) : "memory"); }
__device__ __forceinline__ void mbar_arrive(uint32_t a) { asm volatile("mbarrier.arrive.shared::cta.b64 _, [%0];" ::"r"(a) : "memory"); }
#define GIVE_UP(id) "trap;\n"
#define SPIN_MAX "0x400000"
#define SPIN_TAIL(id) "add.u32 n, n, 1;\n setp.lt.u32 p, n, " SPIN_MAX ";\n @p bra.uni LP;\n" GIVE_UP(id) " DN:\n }"
__device__ __forceinline__ void mbar_wait(uint32_t a, uint32_t ph) {
    asm volatile("{ .reg .pred p; .reg .b32 n; mov.u32 n, 0;\n LP:\n"
                 "mbarrier.try_wait.parity.shared::cta.b64 p, [%0], %1;\n @p bra DN;\n"
                 "add.u32 n, n, 1;\n setp.lt.u32 p, n, " SPIN_MAX ";\n @p bra LP;\n"
                 GIVE_UP("")
                 " DN:\n }" ::"r"(a), "r"(ph) : "memory");
}
#define ELECT "{ .reg .pred e; elect.sync _|e, 0xffffffff; @e "
__device__ __forceinline__ void tma2d(uint32_t dst, const CUtensorMap* m, int c0, int c1, uint32_t bar) {
    asm volatile(ELECT "cp.async.bulk.tensor.2d.shared::cluster.global.mbarrier::complete_tx::bytes [%0], [%1, {%3, %4}], [%2]; }" ::"r"(dst), "l"(m), "r"(bar), "r"(c0), "r"(c1) : "memory");
}
__device__ __forceinline__ void tma3x(uint32_t dst, const CUtensorMap* m, int row, uint32_t bar) {
    asm volatile(ELECT "cp.async.bulk.tensor.3d.shared::cluster.global.mbarrier::complete_tx::bytes [%0], [%1, {0, %3, 0}], [%2]; }" ::"r"(dst), "l"(m), "r"(bar), "r"(row) : "memory");
}
template <int OFF>
__device__ __forceinline__ void ld_pkt(uint32_t* v, const uint4* p) {
    asm volatile("{ .reg .b128 t; ld.relaxed.gpu.global.b128 t, [%4+%5]; mov.b128 {%0,%1,%2,%3}, t; }" : "=r"(v[0]), "=r"(v[1]), "=r"(v[2]), "=r"(v[3]) : "l"(p), "n"(OFF * 16) : "memory");
}
template <int OFF>
__device__ __forceinline__ void st_pkt(uint4* p, uint32_t a, uint32_t b, uint32_t c, uint32_t d) {
    asm volatile("{ .reg .b128 t; mov.b128 t, {%1,%2,%3,%4}; st.relaxed.gpu.global.b128 [%0+%5], t; }" ::"l"(p), "r"(a), "r"(b), "r"(c), "r"(d), "n"(OFF * 16) : "memory");
}
__device__ __forceinline__ uint32_t pack2(float lo, float hi) {
    uint32_t r;
    asm("cvt.rn.bf16x2.f32 %0, %1, %2;" : "=r"(r) : "f"(hi), "f"(lo));
    return r;
}
__device__ __forceinline__ float bf_lo(uint32_t w) { return __uint_as_float(w << 16); }
__device__ __forceinline__ float bf_hi(uint32_t w) { return __uint_as_float(w & 0xffff0000u); }
__device__ __forceinline__ uint32_t settag(uint32_t w, uint32_t tag) { return (w & ~1u) | tag; }
__device__ __forceinline__ float ex2(float x) { float y; asm("ex2.approx.ftz.f32 %0, %1;" : "=f"(y) : "f"(x)); return y; }
__device__ __forceinline__ float rcp(float x) { float y; asm("rcp.approx.ftz.f32 %0, %1;" : "=f"(y) : "f"(x)); return y; }
__device__ __forceinline__ float tanh_hw(float x) { float y; asm("tanh.approx.f32 %0, %1;" : "=f"(y) : "f"(x)); return y; }
__device__ __forceinline__ void stsm4(uint32_t addr, uint32_t a, uint32_t b, uint32_t c, uint32_t d) {
    asm volatile("stmatrix.sync.aligned.m8n8.x4.shared.b16 [%0], {%1,%2,%3,%4};" ::"r"(addr), "r"(a), "r"(b), "r"(c), "r"(d) : "memory");
}
__device__ __forceinline__ void fence_async() { asm volatile("fence.proxy.async.shared::cta;" ::: "memory"); }
__device__ __forceinline__ void bar_sync(int id, int n) { asm volatile("bar.sync %0, %1;" ::"r"(id), "r"(n) : "memory"); }
__device__ __forceinline__ void bar_arrive(int id, int n) { asm volatile("bar.arrive %0, %1;" ::"r"(id), "r"(n) : "memory"); }
__device__ __forceinline__ void wg_fence() { asm volatile("wgmma.fence.sync.aligned;" ::: "memory"); }
__device__ __forceinline__ void wg_commit() { asm volatile("wgmma.commit_group.sync.aligned;" ::: "memory"); }
template <int N> __device__ __forceinline__ void wg_wait() { asm volatile("wgmma.wait_group.sync.aligned %0;" ::"n"(N) : "memory"); }

constexpr uint32_t SB0 = 1024;
__host__ __device__ constexpr uint32_t dlo(uint32_t off, uint32_t lbo) { return ((SB0 + off) >> 4) | ((lbo >> 4) << 16); }
__host__ __device__ constexpr uint32_t dhi(uint32_t sbo, uint32_t sw) { return (sbo >> 4) | (sw << 30); }
__device__ __forceinline__ uint64_t dbase(uint32_t lo, uint32_t hi) { uint64_t d; asm volatile("mov.b64 %0, {%1, %2};" : "=l"(d) : "r"(lo), "r"(hi)); return d; }
#define BASE128(off, lbo, adj) dbase(dlo(off, lbo) + (adj), dhi(1024, 1))
#define BASE64(off, lbo, adj) dbase(dlo(off, lbo) + (adj), dhi(512, 2))

#define ACC4(d, o) "+f"(d[o]), "+f"(d[o + 1]), "+f"(d[o + 2]), "+f"(d[o + 3])
#define ACC28(d) ACC4(d, 0), ACC4(d, 4), ACC4(d, 8), ACC4(d, 12), ACC4(d, 16), ACC4(d, 20), ACC4(d, 24)
#define ACC32(d, o) ACC4(d, o), ACC4(d, o + 4), ACC4(d, o + 8), ACC4(d, o + 12), ACC4(d, o + 16), ACC4(d, o + 20), ACC4(d, o + 24), ACC4(d, o + 28)

template <int TB, uint64_t D>
__device__ __forceinline__ void mma_rs56(float* d, uint32_t a0, uint32_t a1, uint32_t a2, uint32_t a3, int sd, uint64_t base) {
    asm volatile("{ .reg .pred p; .reg .b64 db; setp.ne.b32 p, %32, 0; add.u64 db, %33, %34;\n"
                 "wgmma.mma_async.sync.aligned.m64n56k16.f32.bf16.bf16 "
                 "{%0,%1,%2,%3,%4,%5,%6,%7,%8,%9,%10,%11,%12,%13,%14,%15,%16,%17,%18,%19,%20,%21,%22,%23,%24,%25,%26,%27}, "
                 "{%28,%29,%30,%31}, db, p, 1, 1, %35; }\n"
                 : ACC28(d)
                 : "r"(a0), "r"(a1), "r"(a2), "r"(a3), "r"(sd), "l"(base), "n"(D), "n"(TB));
}
template <int TB, uint64_t D>
__device__ __forceinline__ void mma_rs64(float* d, uint32_t a0, uint32_t a1, uint32_t a2, uint32_t a3, int sd, uint64_t base) {
    asm volatile("{ .reg .pred p; .reg .b64 db; setp.ne.b32 p, %36, 0; add.u64 db, %37, %38;\n"
                 "wgmma.mma_async.sync.aligned.m64n64k16.f32.bf16.bf16 "
                 "{%0,%1,%2,%3,%4,%5,%6,%7,%8,%9,%10,%11,%12,%13,%14,%15,%16,%17,%18,%19,%20,%21,%22,%23,%24,%25,%26,%27,%28,%29,%30,%31}, "
                 "{%32,%33,%34,%35}, db, p, 1, 1, %39; }\n"
                 : ACC32(d, 0)
                 : "r"(a0), "r"(a1), "r"(a2), "r"(a3), "r"(sd), "l"(base), "n"(D), "n"(TB));
}
template <int TB, uint64_t D>
__device__ __forceinline__ void mma_rs128(float* d, uint32_t a0, uint32_t a1, uint32_t a2, uint32_t a3, int sd, uint64_t base) {
    asm volatile("{ .reg .pred p; .reg .b64 db; setp.ne.b32 p, %68, 0; add.u64 db, %69, %70;\n"
                 "wgmma.mma_async.sync.aligned.m64n128k16.f32.bf16.bf16 "
                 "{%0,%1,%2,%3,%4,%5,%6,%7,%8,%9,%10,%11,%12,%13,%14,%15,%16,%17,%18,%19,%20,%21,%22,%23,%24,%25,%26,%27,%28,%29,%30,%31,%32,%33,%34,%35,%36,%37,%38,%39,%40,%41,%42,%43,%44,%45,%46,%47,%48,%49,%50,%51,%52,%53,%54,%55,%56,%57,%58,%59,%60,%61,%62,%63}, "
                 "{%64,%65,%66,%67}, db, p, 1, 1, %71; }\n"
                 : ACC32(d, 0), ACC32(d, 32)
                 : "r"(a0), "r"(a1), "r"(a2), "r"(a3), "r"(sd), "l"(base), "n"(D), "n"(TB));
}
template <uint64_t DA, uint64_t DB>
__device__ __forceinline__ void mma_ss56_tt(float* d, int sd, uint64_t ba, uint64_t bb) {
    asm volatile("{ .reg .pred p; .reg .b64 da, db; setp.ne.b32 p, %28, 0; add.u64 da, %29, %31; add.u64 db, %30, %32;\n"
                 "wgmma.mma_async.sync.aligned.m64n56k16.f32.bf16.bf16 "
                 "{%0,%1,%2,%3,%4,%5,%6,%7,%8,%9,%10,%11,%12,%13,%14,%15,%16,%17,%18,%19,%20,%21,%22,%23,%24,%25,%26,%27}, "
                 "da, db, p, 1, 1, 1, 1; }\n"
                 : ACC28(d)
                 : "r"(sd), "l"(ba), "l"(bb), "n"(DA), "n"(DB));
}
template <int... I> struct Seq {};
template <class F, int... I> __device__ __forceinline__ void static_for_impl(F&& f, Seq<I...>) { (f(std::integral_constant<int, I>{}), ...); }
#define FOR7(...) static_for_impl([&](auto T_) { constexpr int t = decltype(T_)::value; __VA_ARGS__; }, Seq<0, 1, 2, 3, 4, 5, 6>{})
#define FOR8(...) static_for_impl([&](auto T_) { constexpr int t = decltype(T_)::value; __VA_ARGS__; }, Seq<0, 1, 2, 3, 4, 5, 6, 7>{})
#define FOR14(...) static_for_impl([&](auto T_) { constexpr int t = decltype(T_)::value; __VA_ARGS__; }, Seq<0, 1, 2, 3, 4, 5, 6, 7, 8, 9, 10, 11, 12, 13>{})

__device__ __forceinline__ int kblk(int p, int b) { return b == 0 ? p : b - (b <= p); }
__host__ __device__ constexpr int krow(int t) { return t < 3 ? 16 * t : (t < 6 ? 56 + 16 * (t - 3) : 48); }
#define AQ(A, b, t) ((t) < 3 ? A[2 * (b)][4 * (t)] : (t) < 6 ? A[2 * (b) + 1][4 * ((t) - 3)] : A[2 * (b)][12]), \
                    ((t) < 3 ? A[2 * (b)][4 * (t) + 1] : (t) < 6 ? A[2 * (b) + 1][4 * ((t) - 3) + 1] : A[2 * (b)][13]), \
                    ((t) < 3 ? A[2 * (b)][4 * (t) + 2] : (t) < 6 ? A[2 * (b) + 1][4 * ((t) - 3) + 2] : A[2 * (b) + 1][12]), \
                    ((t) < 3 ? A[2 * (b)][4 * (t) + 3] : (t) < 6 ? A[2 * (b) + 1][4 * ((t) - 3) + 3] : A[2 * (b) + 1][13])
#define D128(off, t) ((uint64_t)(((off) + krow(t) * 128) >> 4) + ((uint64_t)((t) == 6 ? (7168 - 1024) >> 4 : 0) << 32))
#define D64(off, t) ((uint64_t)(((off) + krow(t) * 64) >> 4) + ((uint64_t)((t) == 6 ? (3584 - 512) >> 4 : 0) << 32))

#define PL(k) (((k) - 3) * PLANE)
__device__ __forceinline__ void st_word(uint32_t* p, uint32_t v) { asm volatile("st.relaxed.gpu.global.u32 [%0], %1;" ::"l"(p), "r"(v) : "memory"); }
__device__ __forceinline__ uint32_t ld_word(const uint32_t* p) { uint32_t v; asm volatile("ld.relaxed.gpu.global.u32 %0, [%1];" : "=r"(v) : "l"(p) : "memory"); return v; }
__device__ __forceinline__ void tag_slice(uint32_t* w, uint32_t tag) { w[0] = settag(w[0], tag); w[4] = settag(w[4], tag); w[8] = settag(w[8], tag); w[12] = settag(w[12], tag); }
template <int O>
__device__ __forceinline__ void send_slice(uint4* dst, int lane, const uint32_t* w) {
    st_pkt<O>(dst, w[0], w[1], w[2], w[3]);
    st_pkt<O + 32>(dst, w[4], w[5], w[6], w[7]);
    st_pkt<O + 64>(dst, w[8], w[9], w[10], w[11]);
    asm volatile("{ .reg .b64 t; mov.b64 t, {%1,%2}; st.relaxed.gpu.global.b64 [%0+%3], t; }" ::"l"((char*)dst - lane * 8), "r"(w[12]), "r"(w[13]), "n"(16 * (O + 96)) : "memory");
}
#define RW4(v, o) "+r"(v[o]), "+r"(v[(o) + 1]), "+r"(v[(o) + 2]), "+r"(v[(o) + 3])
#define RW2(v, o) "+r"(v[o]), "+r"(v[(o) + 1])
#define WR4(v, o) "=&r"(v[o]), "=&r"(v[(o) + 1]), "=&r"(v[(o) + 2]), "=&r"(v[(o) + 3])
#define LDP(a, b, c, d, addr, off) "ld.relaxed.gpu.global.b128 q, [" addr "+" off "];\n mov.b128 {" a "," b "," c "," d "}, q;\n"
#define LDH(a, b, addr, off) "ld.relaxed.gpu.global.b64 h, [" addr "+" off "];\n mov.b64 {" a "," b "}, h;\n"
#define VOTE_OK "and.b32 t, t, 1;\n setp.ne.u32 p, t, 0;\n vote.sync.any.pred p, p, 0xffffffff;\n @!p bra.uni DN;\n"
#define CHK(x, tag) "lop3.b32 t, " x ", " tag ", t, 0xBE;\n"
__device__ __forceinline__ void check_cnt(uint32_t v, const uint32_t* p, uint32_t target) {
    asm volatile("{ .reg .pred p; .reg .b32 n, t; mov.u32 n, 0; mov.u32 t, %2;\n LP:\n"
                 "sub.s32 t, t, %1;\n setp.lt.s32 p, t, 0;\n vote.sync.any.pred p, p, 0xffffffff;\n @!p bra.uni DN;\n ld.relaxed.gpu.global.u32 t, [%0];\n" SPIN_TAIL("7")
                 ::"l"(p), "r"(target), "r"(v) : "memory");
}
__device__ __forceinline__ void poll_cnt(const uint32_t* p, uint32_t target) {
    asm volatile("{ .reg .pred p; .reg .b32 n, t; mov.u32 n, 0;\n LP:\n"
                 "ld.relaxed.gpu.global.u32 t, [%0];\n sub.s32 t, t, %1;\n setp.lt.s32 p, t, 0;\n vote.sync.any.pred p, p, 0xffffffff;\n @!p bra.uni DN;\n" SPIN_TAIL("1")
                 ::"l"(p), "r"(target) : "memory");
}
template <int STR>
__device__ __forceinline__ void poll4_kv(uint32_t* v, const uint4* p, uint32_t tag) {
    asm volatile("{ .reg .pred p; .reg .b32 n, t; .reg .b128 q; mov.u32 n, 0;\n LP:\n"
                 LDP("%0", "%1", "%2", "%3", "%16", "0") LDP("%4", "%5", "%6", "%7", "%16", "%18")
                 LDP("%8", "%9", "%10", "%11", "%16", "%19") LDP("%12", "%13", "%14", "%15", "%16", "%20")
                 "xor.b32 t, %0, %17;\n" CHK("%4", "%17") CHK("%8", "%17") CHK("%12", "%17") VOTE_OK SPIN_TAIL("2")
                 : WR4(v, 0), WR4(v, 4), WR4(v, 8), WR4(v, 12)
                 : "l"(p), "r"(tag), "n"(16 * STR), "n"(32 * STR), "n"(48 * STR)
                 : "memory");
}
template <int B>
__device__ __forceinline__ void blk_load(uint32_t (&A)[8][14], const uint4* src, int lane) {
    ld_pkt<0>(&A[2 * B][0], src); ld_pkt<32>(&A[2 * B][4], src); ld_pkt<64>(&A[2 * B][8], src);
    ld_pkt<512>(&A[2 * B + 1][0], src); ld_pkt<544>(&A[2 * B + 1][4], src); ld_pkt<576>(&A[2 * B + 1][8], src);
    asm volatile("{ .reg .b64 h;\n" LDH("%0", "%1", "%4", "1536") LDH("%2", "%3", "%4", "9728") "}"
                 : "=&r"(A[2 * B][12]), "=&r"(A[2 * B][13]), "=&r"(A[2 * B + 1][12]), "=&r"(A[2 * B + 1][13])
                 : "l"((const char*)src - lane * 8) : "memory");
}
template <int B>
__device__ __forceinline__ void blk_check(uint32_t (&A)[8][14], const uint4* src, int lane, uint32_t tag) {
    asm volatile("{ .reg .pred p; .reg .b32 n, t; .reg .b128 q; .reg .b64 h, a8; mov.u32 n, 0;\n LP:\n"
                 "xor.b32 t, %0, %30;\n" CHK("%4", "%30") CHK("%8", "%30") CHK("%12", "%30") CHK("%16", "%30") CHK("%20", "%30") CHK("%24", "%30") CHK("%26", "%30") VOTE_OK
                 LDP("%0", "%1", "%2", "%3", "%28", "0") LDP("%4", "%5", "%6", "%7", "%28", "512") LDP("%8", "%9", "%10", "%11", "%28", "1024")
                 LDP("%12", "%13", "%14", "%15", "%28", "8192") LDP("%16", "%17", "%18", "%19", "%28", "8704") LDP("%20", "%21", "%22", "%23", "%28", "9216")
                 "mad.wide.s32 a8, %29, -8, %28;\n" LDH("%24", "%25", "a8", "1536") LDH("%26", "%27", "a8", "9728") SPIN_TAIL("3")
                 "\n and.b32 %0, %0, -2; and.b32 %4, %4, -2; and.b32 %8, %8, -2; and.b32 %12, %12, -2; and.b32 %16, %16, -2; and.b32 %20, %20, -2; and.b32 %24, %24, -2; and.b32 %26, %26, -2;"
                 : RW4(A[2 * B], 0), RW4(A[2 * B], 4), RW4(A[2 * B], 8), RW4(A[2 * B + 1], 0), RW4(A[2 * B + 1], 4), RW4(A[2 * B + 1], 8),
                   RW2(A[2 * B], 12), RW2(A[2 * B + 1], 12)
                 : "l"(src), "r"(lane), "r"(tag)
                 : "memory");
}
__device__ __forceinline__ void st_async4(uint32_t a, uint32_t x, uint32_t y, uint32_t z, uint32_t w, uint32_t bar) {
    asm volatile("st.async.weak.shared::cluster.mbarrier::complete_tx::bytes.v4.b32 [%0], {%1,%2,%3,%4}, [%5];" ::"r"(a), "r"(x), "r"(y), "r"(z), "r"(w), "r"(bar) : "memory");
}
__device__ __forceinline__ uint32_t mapa(uint32_t a, uint32_t cta) { uint32_t r; asm("mapa.shared::cluster.u32 %0, %1, %2;" : "=r"(r) : "r"(a), "r"(cta)); return r; }
__device__ __forceinline__ void stat_load(uint32_t* v, const uint4* p) { ld_pkt<0>(v, p); ld_pkt<512>(v + 4, p); }
__device__ __forceinline__ void stat_check(uint32_t* v, const uint4* p, uint32_t tag) {
    asm volatile("{ .reg .pred p; .reg .b32 n, t; .reg .b128 q; mov.u32 n, 0;\n LP:\n"
                 "xor.b32 t, %3, %9;\n" CHK("%7", "%9") VOTE_OK
                 LDP("%0", "%1", "%2", "%3", "%8", "0") LDP("%4", "%5", "%6", "%7", "%8", "8192") SPIN_TAIL("4")
                 : RW4(v, 0), RW4(v, 4) : "l"(p), "r"(tag) : "memory");
}
__device__ __forceinline__ uint32_t x_bits(const uint32_t* X) {
    uint32_t r;
    asm volatile("{ .reg .b32 a, b; prmt.b32 a, %1, %2, 0x0040; prmt.b32 b, %3, %4, 0x0040; prmt.b32 %0, a, b, 0x5410; }" : "=r"(r) : "r"(X[0]), "r"(X[4]), "r"(X[8]), "r"(X[12]));
    return r;
}
template <int O>
__device__ __forceinline__ void slice_load(uint32_t* v, const uint4* p, int lane) {
    ld_pkt<O>(v, p); ld_pkt<O + 32>(v + 4, p); ld_pkt<O + 64>(v + 8, p);
    asm volatile("{ .reg .b64 h;\n" LDH("%0", "%1", "%2", "%3") "}" : "=r"(v[12]), "=r"(v[13]) : "l"((const char*)p - lane * 8), "n"(16 * (O + 96)) : "memory");
}
template <int O>
__device__ __forceinline__ void slice_check(uint32_t* v, const uint4* p, int lane, uint32_t tag) {
    asm volatile("{ .reg .pred p; .reg .b32 n, t; .reg .b128 q; .reg .b64 h; mov.u32 n, 0;\n LP:\n"
                 "xor.b32 t, %0, %16;\n" CHK("%4", "%16") CHK("%8", "%16") CHK("%12", "%16") VOTE_OK
                 LDP("%0", "%1", "%2", "%3", "%14", "%17") LDP("%4", "%5", "%6", "%7", "%14", "%18") LDP("%8", "%9", "%10", "%11", "%14", "%19")
                 LDH("%12", "%13", "%15", "%20") SPIN_TAIL("5")
                 : RW4(v, 0), RW4(v, 4), RW4(v, 8), RW2(v, 12)
                 : "l"(p), "l"((const char*)p - lane * 8), "r"(tag), "n"(16 * O), "n"(16 * (O + 32)), "n"(16 * (O + 64)), "n"(16 * (O + 96))
                 : "memory");
}
__device__ __forceinline__ void x_fix(uint32_t* X, uint32_t bits) {
    X[0] = __byte_perm(X[0], bits, 0x3214); X[4] = __byte_perm(X[4], bits, 0x3215); X[8] = __byte_perm(X[8], bits, 0x3216); X[12] = __byte_perm(X[12], bits, 0x3217);
}
__device__ __forceinline__ void sts4(uint32_t a, uint32_t x, uint32_t y, uint32_t z, uint32_t w) {
    asm volatile("st.shared.v4.u32 [%0], {%1,%2,%3,%4};" ::"r"(a), "r"(x), "r"(y), "r"(z), "r"(w) : "memory");
}
__device__ __forceinline__ void lds4(uint32_t* v, uint32_t a) {
    asm volatile("ld.shared.v4.u32 {%0,%1,%2,%3}, [%4];" : "=r"(v[0]), "=r"(v[1]), "=r"(v[2]), "=r"(v[3]) : "r"(a) : "memory");
}
struct LnCoef { uint32_t hi, lo, sh; };
__device__ __forceinline__ LnCoef ln_coef(float sum, float sq) {
    sum += __shfl_xor_sync(0xffffffffu, sum, 1); sq += __shfl_xor_sync(0xffffffffu, sq, 1);
    sum += __shfl_xor_sync(0xffffffffu, sum, 2); sq += __shfl_xor_sync(0xffffffffu, sq, 2);
    const float mean = sum * (1.f / 448.f);
    const float var = fmaxf(fmaf(-mean, mean, sq * (1.f / 448.f)), 0.f);
    const float sc = rsqrtf(var + 1e-5f);
    LnCoef r;
    r.hi = pack2(sc, sc);
    const float lo = sc - bf_lo(r.hi), sh = -mean * sc;
    r.lo = pack2(lo, lo);
    r.sh = pack2(sh, sh);
    return r;
}
template <int B>
__device__ __forceinline__ void normalize(uint32_t (&A)[8][14], const LnCoef& c0, const LnCoef& c1) {
#pragma unroll
    for (int s = 2 * B; s < 2 * B + 2; s++)
#pragma unroll
        for (int i = 0; i < 14; i++) {
            const LnCoef& k = (i & 1) ? c1 : c0;
            asm("{ .reg .b32 t; fma.rn.bf16x2 t, %0, %2, %3; fma.rn.bf16x2 %0, %0, %1, t; }" : "+r"(A[s][i]) : "r"(k.hi), "r"(k.lo), "r"(k.sh));
        }
}
__device__ __forceinline__ void slice_stats(const uint32_t* w, float* st) {
    float a = 0.f, b = 0.f, p = 0.f, q = 0.f;
#pragma unroll
    for (int i = 0; i < 7; i++) {
        const float e0 = bf_lo(w[2 * i]), e1 = bf_hi(w[2 * i]), e2 = bf_lo(w[2 * i + 1]), e3 = bf_hi(w[2 * i + 1]);
        a += e0 + e1; b += e2 + e3;
        p = fmaf(e0, e0, p); p = fmaf(e1, e1, p); q = fmaf(e2, e2, q); q = fmaf(e3, e3, q);
    }
    a += __shfl_xor_sync(0xffffffffu, a, 1); p += __shfl_xor_sync(0xffffffffu, p, 1); b += __shfl_xor_sync(0xffffffffu, b, 1); q += __shfl_xor_sync(0xffffffffu, q, 1);
    a += __shfl_xor_sync(0xffffffffu, a, 2); p += __shfl_xor_sync(0xffffffffu, p, 2); b += __shfl_xor_sync(0xffffffffu, b, 2); q += __shfl_xor_sync(0xffffffffu, q, 2);
    st[0] = a; st[1] = p; st[2] = b; st[3] = q;
}
__device__ __forceinline__ void dual_softmax(const float* p, uint32_t* out) {
    constexpr float L = 1.4426950408889634f;
#pragma unroll
    for (int r = 0; r < 2; r++) {
        float mx = fmaxf(p[2 * r], p[2 * r + 1]), mn = fminf(p[2 * r], p[2 * r + 1]);
#pragma unroll
        for (int i = 1; i < 7; i++) {
            mx = fmaxf(mx, fmaxf(p[4 * i + 2 * r], p[4 * i + 2 * r + 1]));
            mn = fminf(mn, fminf(p[4 * i + 2 * r], p[4 * i + 2 * r + 1]));
        }
        mx = fmaxf(mx, __shfl_xor_sync(0xffffffffu, mx, 1));
        mn = fminf(mn, __shfl_xor_sync(0xffffffffu, mn, 1));
        const float bx = -mx * L, bn = mn * L;
        float ep[14], en[14], sp = 0.f, sn = 0.f;
#pragma unroll
        for (int i = 0; i < 14; i++) {
            const float v = p[4 * (i >> 1) + 2 * r + (i & 1)];
            ep[i] = ex2(fmaf(v, L, bx));
            en[i] = ex2(fmaf(v, -L, bn));
            sp += ep[i]; sn += en[i];
        }
        sp += __shfl_xor_sync(0xffffffffu, sp, 1);
        sn += __shfl_xor_sync(0xffffffffu, sn, 1);
        const float ip = rcp(sp), in = rcp(sn);
#pragma unroll
        for (int i = 0; i < 7; i++) {
            out[4 * i + r] = pack2(ep[2 * i] * ip, ep[2 * i + 1] * ip);
            out[4 * i + 2 + r] = pack2(en[2 * i] * in, en[2 * i + 1] * in);
        }
    }
}
__device__ __forceinline__ float geglu(float g, float u) {
    const float t = tanh_hw(g * fmaf(g * g, 0.7978845608028654f * 0.044715f, 0.7978845608028654f));
    const float gu = g * u;
    return fmaf(t, gu, gu);
}
__device__ __forceinline__ void phi_gemm(const float* t, float* p) {
    uint32_t w[14];
#pragma unroll
    for (int i = 0; i < 14; i++) w[i] = pack2(t[2 * i], t[2 * i + 1]);
    const uint64_t db = BASE128(OFF_WPHI, 16, 0);
    wg_fence();
    mma_rs56<0, 0>(p, w[0], w[1], w[2], w[3], 0, db);
    mma_rs56<0, 2>(p, w[4], w[5], w[6], w[7], 1, db);
    mma_rs56<0, 4>(p, w[8], w[9], w[10], w[11], 1, db);
    mma_rs56<0, 6>(p, w[12], w[13], 0u, 0u, 1, db);
    wg_commit();
    wg_wait<0>();
}

}

#define BAR(i) (bars + 8 * (i))
#define R_WAIT() mbar_wait(BAR(slot), ph)
#define WSUM(i)
#define R_ADJ (slot * (STAGE >> 4))
#define R_NEXT() do { eb2 = eb1; eb1 = BAR(B_EMPTY + slot); if (++slot == NST) { slot = 0; ph ^= 1; } } while (0)
#define R_RELEASE(k) do { if (lane == 0) mbar_arrive((k) == 1 ? eb1 : eb2); } while (0)
#define PUSH_BEGIN() do { mbar_wait(BAR(B_ACK + wgi), ackph); ackph ^= 1; } while (0)
#define PUSH_ACK() do { __syncwarp(); if (lane == 0) asm volatile("mbarrier.arrive.shared::cluster.b64 _, [%0];" ::"r"(mapa(BAR(B_ACK + wgi), hr ^ 1)) : "memory"); } while (0)

__global__ void __cluster_dims__(2, 1, 1) __launch_bounds__(384, 1)
fused_kernel(Scratch* const sc, const __nv_bfloat16* __restrict__ x_in, const __nv_bfloat16* __restrict__ w_phi, const int trips,
             const __nv_bfloat16* __restrict__ wg, const __nv_bfloat16* __restrict__ wu, const __nv_bfloat16* __restrict__ wd,
             const __grid_constant__ Maps maps) {
    extern __shared__ __align__(1024) unsigned char smem_raw[];
    const uint32_t sb = s2u(smem_raw);
    const uint32_t bars = sb + OFF_BAR;
    const int wgi = __shfl_sync(0xffffffffu, threadIdx.x >> 7, 0);
    const int hr = blockIdx.x & 1, ck = blockIdx.x >> 1;
    const int gp = (ck - 4) & 7, q7 = ((ck - 36) * 37) >> 8;
    const int pr = ck < 4 ? ck : (ck < 36 ? (ck - 4) >> 3 : q7);
    const int tile = ck < 4 ? 0 : (ck < 36 ? (gp ? 2 * gp : 1) : 2 * (ck - 36 - 7 * q7) + 3);
    const int sl = 2 * pr + hr;
    STAMP(0);
    GSTAMP(60);
    if (threadIdx.x == 256) {
#pragma unroll
        for (int i = 0; i < NST; i++) mbar_init(BAR(i), 1);
        asm volatile("fence.mbarrier_init.release.cluster;" ::: "memory");
    }
    if (threadIdx.x == 288) {
        if ((sb & 0x3FFFF) != SB0) asm volatile("trap;");
#pragma unroll
        for (int i = NST; i < B_COUNT; i++) mbar_init(BAR(i), i >= B_ACK ? 4 : (i < B_RECV ? 8 : 1));
        asm volatile("fence.mbarrier_init.release.cluster;" ::: "memory");
    }
    __syncwarp();
    asm volatile("barrier.cluster.arrive.relaxed.aligned;" ::: "memory");

    if (wgi == 2) {
        asm volatile("setmaxnreg.dec.sync.aligned.u32 40;");
        const int t128 = fresh_tid() & 127, w = __shfl_sync(0xffffffffu, t128 >> 5, 0), lane = t128 & 31;
        uint32_t e0[2] = {0, 0}, e1[2] = {0, 0}, cw_target = 0;
        if (w == 0) {
#pragma unroll 1
            for (int n = 0; n < NST; n++) {
                const uint32_t dst = sb + n * STAGE, fb = BAR(n);
                asm volatile(ELECT "mbarrier.arrive.expect_tx.shared::cta.b64 _, [%0], %1; }" ::"r"(fb), "r"(n < 2 ? 2 * STAGE : STAGE) : "memory");
                if (n < 2) {
                    tma3x(sb + OFF_H + n * STAGE, &maps.x, tile * 128 + n * 64, fb);
                    tma3x(dst, &maps.x, tile * 128 + n * 64 + 32, fb);
                } else {
                    if (n == 3) mbar_wait(BAR(1), 0);
                    const int ra = 112 * (n - 2);
                    tma2d(dst, &maps.qkv, 448 + 56 * sl, ra, fb);
                    tma2d(dst + HALF, &maps.qkv, 896 + 56 * sl, ra, fb);
                }
            }
            asm volatile("barrier.cluster.wait.aligned;" ::: "memory");
            cw_target = (ld_word(g_cw + sl * 32) & ~15u) + 16;
#pragma unroll 1
            for (int k = 0; k < 2; k++) {
                const int n = t128 + 32 * k;
                int m = n - 2 - (n > PACK);
                const bool packed = m >= 30 ? (m < 38 || m >= 52) : m >= 22;
                if (m >= 30) m -= 30;
                if (n == PACK) m = tile < 8 ? tile : tile + 14;
                const int rot = n < 8 ? 0 : pr;
                const int ra = 112 * kblk(rot, m & 3), rb = 112 * kblk(rot, 2 * m & 3), rc = 112 * kblk(rot, (2 * m + 1) & 3);
                int kind = 0, m0, m1, c0, c1, r0, r1;
                if (m < 4) { m0 = m1 = 1; c0 = 448 + 56 * sl; c1 = c0 + 448; r0 = r1 = ra; }
                else if (m < 8) { m0 = m1 = m < 6 ? 1 : 2; c0 = c1 = 56 * sl; r0 = rb; r1 = rc; }
                else if (m < 20) { m0 = 3; m1 = 4; c0 = c1 = 224 * sl + 32 * hr + 64 * ((m - 8) >> 2); r0 = r1 = ra; }
                else if (m < 22) { kind = 2; m0 = 5; m1 = 6; c0 = c1 = 224 * sl + (hr ? 0 : 192); r0 = rb; r1 = rc; }
                else { m0 = m1 = 7; c0 = c1 = 56 * (2 * ((pr + (m >> 1) - 10) & 3) + hr); r0 = 224 * (sl ^ (m & 1)); r1 = r0 + 112; }
                if (packed) { kind = 1; r0 = sl * 16 + (m < 8 ? m : m - 14); r1 = 0; }
                e0[0] = e0[1]; e1[0] = e1[1];
                e0[1] = kind | (m0 << 2) | (m1 << 6) | (c0 << 10) | (c1 << 21);
                e1[1] = r0 | (r1 << 16);
            }
        } else {
            const int j = t128 - 32;
            asm volatile("barrier.cluster.wait.aligned;" ::: "memory");
            uint2 wv[7];
            const int k = j < 56 ? j : 55, hh = k >= 28;
#pragma unroll
            for (int i = 0; i < 7; i++) wv[i] = __ldg(reinterpret_cast<const uint2*>(w_phi + (sl * 56 + k) * 28) + i);
#pragma unroll 1
            for (int i = j; i < 7168 / 16; i += 96) sts4(sb + OFF_WPHI + i * 16, 0, 0, 0, 0);
            bar_sync(5, 96);
            if (j < 56) {
                uint32_t a4[4];
#pragma unroll
                for (int q = 0; q < 4; q++) a4[q] = sb + OFF_WPHI + (4 * hh + q) * 128 + ((((k >> 3) ^ (4 * hh + q)) & 7) << 4) + (k & 7) * 2;
                FOR14(const uint32_t v = (t & 1) ? wv[t >> 1].y : wv[t >> 1].x;
                      asm volatile("{ .reg .b16 l, h; mov.b32 {l, h}, %2; st.shared.u16 [%0+%3], l; st.shared.u16 [%1+%3], h; }"
                                   ::"r"(a4[t >= 7 ? 2 : 0]), "r"(a4[t >= 7 ? 3 : 1]), "r"(v), "n"((t % 7) * 1024) : "memory"));
            }
            __syncwarp();
            fence_async();
            bar_arrive(1, 224);
            bar_arrive(9, 224);
            if (w == 1) {
                mbar_wait(BAR(2), 0);
                mbar_wait(BAR(2), 1);
                const int b = blockIdx.x;
                asm volatile(ELECT "cp.async.bulk.prefetch.L2.global [%0], %1; }" ::"l"(wg + b * 6272), "r"(12544) : "memory");
                asm volatile(ELECT "cp.async.bulk.prefetch.L2.global [%0], %1; }" ::"l"(wu + b * 6272), "r"(12544) : "memory");
                asm volatile(ELECT "cp.async.bulk.prefetch.L2.global [%0], %1; }" ::"l"(wd + b * 6272), "r"(12544) : "memory");
            }
        }
        uint32_t kseq = ld_word(g_c1 + (sl * 8 * 16 + tile) * 32);
        int slot = 0, ph = 0, n = NST;
#pragma unroll 1
        for (int layer = 0; layer < 3; layer++) {
            if (w == 0) {
                const int nend = layer == 0 ? 11 : (layer == 1 ? 42 : 63);
#pragma unroll 1
                for (; n < nend; n++) {
                const uint32_t w0 = __shfl_sync(0xffffffffu, n < 32 ? e0[0] : e0[1], n & 31), w1 = __shfl_sync(0xffffffffu, n < 32 ? e1[0] : e1[1], n & 31);
                const uint32_t dst = sb + slot * STAGE, fb = BAR(n == PACK ? B_PACK : slot);
                const CUtensorMap* m0 = &maps.x + ((w0 >> 2) & 15);
                const CUtensorMap* m1 = &maps.x + ((w0 >> 6) & 15);
                const int c0 = (w0 >> 10) & 2047, c1 = w0 >> 21, r0 = w1 & 0xffff, r1 = w1 >> 16;
                if (n == 25) {
                    int it = 0;
                    uint32_t v;
                    do { asm volatile("ld.acquire.gpu.global.u32 %0, [%1];" : "=r"(v) : "l"(g_cw + sl * 32) : "memory"); } while ((int)(v - cw_target) < 0 && ++it < 0x400000);
                    asm volatile("fence.proxy.async.global;" ::: "memory");
                    __syncwarp();
                }
                mbar_wait(BAR(B_EMPTY + slot), ph);
                __syncwarp();
                asm volatile(ELECT "mbarrier.arrive.expect_tx.shared::cta.b64 _, [%0], %1; }" ::"r"(fb), "r"(STAGE) : "memory");
                if ((w0 & 3) == 0) {
                    tma2d(dst, m0, c0, r0, fb);
                    tma2d(dst + HALF, m1, c1, r1, fb);
                } else if (w0 & 1) {
                    asm volatile(ELECT "cp.async.bulk.shared::cluster.global.mbarrier::complete_tx::bytes [%0], [%1], %2, [%3]; }"
                                 ::"r"(dst), "l"(reinterpret_cast<const char*>(g_wp) + (size_t)r0 * STAGE), "r"(STAGE), "r"(fb) : "memory");
                } else {
                    tma2d(dst, m0, c0, r0, fb); tma2d(dst + 7168, m0, c0, r1, fb);
                    tma2d(dst + HALF, m1, c0, r0, fb); tma2d(dst + HALF + 7168, m1, c0, r1, fb);
                }
                if (n == PACK) asm volatile(ELECT "mbarrier.arrive.shared::cta.b64 _, [%0]; }" ::"r"(BAR(slot)) : "memory");
                if (++slot == NST) { slot = 0; ph ^= 1; }
                }
            } else if (w == 1 && layer == 1) {
                constexpr int ps = PACK % NST;
                mbar_wait(BAR(B_PACK), 0);
                asm volatile("{ .reg .pred e; elect.sync _|e, 0xffffffff;\n"
                             "@e cp.async.bulk.global.shared::cta.bulk_group [%0], [%1], %2;\n"
                             "@e cp.async.bulk.commit_group;\n"
                             "@e cp.async.bulk.wait_group.read 0;\n"
                             "@e mbarrier.arrive.shared::cta.b64 _, [%3], 8;\n"
                             "@e cp.async.bulk.wait_group 0;\n"
                             "@e fence.proxy.async.global;\n"
                             "@e red.release.gpu.global.add.u32 [%4], 1; }"
                             ::"l"(reinterpret_cast<char*>(g_wp) + (size_t)(sl * 16 + tile) * STAGE), "r"(sb + ps * STAGE), "r"(STAGE), "r"(BAR(B_EMPTY + ps)), "l"(g_cw + sl * 32) : "memory");
                __syncwarp();
            }
            if (layer < 2) {
            const uint32_t tag = layer ^ 1;
            kseq++;
            bar_sync(7, 384);
            ASTAMP(0);
            if (tile < 15) {
                const int sq = lane >> 3, pk = 8 * w + (lane & (tile == 14 ? 3 : 7));
                uint32_t v[16];
                if (layer == 0) poll_cnt(g_c1 + ((sl * 8 + (w >> 1) * 4 + (tile >> 2)) * 16 + (lane & 15)) * 32, kseq);
                ASTAMP(1);
                poll4_kv<32>(v, g_kv1 + ((sl * 16 + tile) * 16 + 4 * sq) * 32 + pk, tag);
#pragma unroll
                for (int k = 0; k < 4; k++) {
                    float lo = (bf_lo(v[k]) + bf_lo(v[4 + k])) + (bf_lo(v[8 + k]) + bf_lo(v[12 + k]));
                    float hi = (bf_hi(v[k]) + bf_hi(v[4 + k])) + (bf_hi(v[8 + k]) + bf_hi(v[12 + k]));
                    lo += __shfl_xor_sync(0xffffffffu, lo, 8); hi += __shfl_xor_sync(0xffffffffu, hi, 8);
                    lo += __shfl_xor_sync(0xffffffffu, lo, 16); hi += __shfl_xor_sync(0xffffffffu, hi, 16);
                    v[k] = pack2(lo, hi);
                }
                if (sq == 0) st_pkt<0>(g_kv2 + sl * 512 + 32 * tile + pk, settag(v[0], tag), v[1], v[2], v[3]);
            }
            ASTAMP(2);
            {
                const int item = t128 < 112 ? t128 : 112 + (t128 & 3), d = item >> 1;
                const int cc = t128 < 112 ? 2 * (d >= 28) + (item & 1) : item - 112;
                const int r = t128 < 112 ? d : 56 + (cc >> 1) + 2 * ((t128 - 112) >> 2);
                uint32_t ra = sb + OFF_KVB + r * 128 + 4 * cc, rx = (r & 7) << 4;
                asm volatile("" : "+r"(ra), "+r"(rx));
                FOR14(asm volatile("st.shared.u32 [%0+%2], %1;" ::"r"((ra ^ 8) + (((t & 7) << 4) ^ rx)), "r"(0), "n"((t >> 3) * 8192) : "memory"));
                uint32_t v[16];
                asm volatile("" : "+r"(ra), "+r"(rx));
                poll4_kv<8>(v, g_kv2 + sl * 512 + (item >> 3) * 32 + (item & 7), tag);
                FOR14(asm volatile("st.shared.u32 [%0+%2], %1;" ::"r"(ra + (((t & 7) << 4) ^ rx)), "r"(v[t < 7 ? t : t + 1]), "n"((t >> 3) * 8192) : "memory"));
                fence_async();
            }
            bar_arrive(3, 384);
            ASTAMP(3);
            }
        }
    } else {
        asm volatile("setmaxnreg.inc.sync.aligned.u32 232;");
        const int tid = fresh_tid(), lane = tid & 31, t128 = tid & 127, g = lane >> 2, c = lane & 3;
        const int wu = __shfl_sync(0xffffffffu, tid >> 5, 0), w = wu & 3;
        uint4* const xp0 = g_ex + 3 * PLANE + ((tile * 2 + wgi) * 8) * 512 + w * 128 + lane;
        const uint32_t hbuf = sb + OFF_H + wgi * STAGE;
        uint32_t slot = 0, ph = 0, eb1 = 0, eb2 = 0, ackph = 0, rcvph = 0, gatph = 0, swp = 0;
        uint32_t ppid = 6;
#define cx(s) (reinterpret_cast<uint32_t*>(again(xp0) - lane + PL(1) + 112 + (s) * 512))
#define stp (again(xp0) - lane + g + PL(0) + 112)
        uint32_t seq = ld_word(cx(sl));
        uint32_t kseq = ld_word(g_c1 + ((sl * 8 + (tid >> 5)) * 16 + tile) * 32);
        uint32_t stag = ld_word(reinterpret_cast<const uint32_t*>(stp + sl * 512) + 3) & 1;
        asm volatile("barrier.cluster.wait.aligned;" ::: "memory");
        STAMP(1);
        uint32_t X[14];
        const uint32_t x0row = (w < 2 ? hbuf : sb + wgi * STAGE) + ((w & 1) * 16 + (lane & 15)) * 128;
        mbar_wait(BAR(wgi), 0);
        STAMP(51);
#pragma unroll
        for (int j = 0; j < 4; j++) {
            const int G = 7 * sl + min(2 * j + (lane >> 4), 6);
            uint32_t q2, q3;
            asm volatile("ldmatrix.sync.aligned.m8n8.x4.shared.b16 {%0,%1,%2,%3}, [%4];" : "=r"(X[4 * j]), "=r"(X[4 * j + 1]), "=r"(q2), "=r"(q3)
                         : "r"(x0row + (G >> 3) * 4096 + (((G ^ lane) & 7) << 4)) : "memory");
            if (j < 3) { X[(4 * j + 2) % 14] = q2; X[(4 * j + 3) % 14] = q3; }
        }
#define PUSH_SLICE(W)                                                                          \
    {                                                                                          \
        if (t128 == 0) mbar_expect_tx(BAR(B_RECV + wgi), 7168);                                \
        PUSH_BEGIN();                                                                          \
        const uint32_t ra = mapa(hbuf + 24576 + t128 * 16, hr ^ 1), rb = mapa(sb + OFF_XR + wgi * 3072, hr ^ 1), rbar = mapa(BAR(B_RECV + wgi), hr ^ 1); \
        st_async4(ra, W[0], W[1], W[2], W[3], rbar);                                           \
        st_async4(ra + 2048, W[4], W[5], W[6], W[7], rbar);                                    \
        st_async4(rb + t128 * 16, W[8], W[9], W[10], W[11], rbar);                             \
        asm volatile("st.async.weak.shared::cluster.mbarrier::complete_tx::bytes.v2.b32 [%0], {%1,%2}, [%3];" ::"r"(rb + 2048 + t128 * 8), "r"(W[12]), "r"(W[13]), "r"(rbar) : "memory"); \
    }
#define PULL_SLICE(W)                                                                          \
    {                                                                                          \
        uint32_t t0, t1;                                                                       \
        mbar_wait(BAR(B_RECV + wgi), rcvph);                                                   \
        rcvph ^= 1;                                                                            \
        lds4(&A[1][0], hbuf + 24576 + t128 * 16);                                              \
        lds4(&A[1][4], hbuf + 26624 + t128 * 16);                                              \
        lds4(&A[1][8], sb + OFF_XR + wgi * 3072 + t128 * 16);                                  \
        asm volatile("ld.shared.v2.u32 {%0,%1}, [%2];" : "=r"(t0), "=r"(t1) : "r"(sb + OFF_XR + wgi * 3072 + 2048 + t128 * 8) : "memory"); \
        _Pragma("unroll") for (int i = 0; i < 12; i++) A[0][i] = (i & 3) ? W[i] : W[i] & ~1u;  \
        A[1][0] &= ~1u; A[1][4] &= ~1u; A[1][8] &= ~1u;                                        \
        A[0][12] = (hr ? t0 : W[12]) & ~1u; A[0][13] = hr ? t1 : W[13];                        \
        A[1][12] = (hr ? W[12] : t0) & ~1u; A[1][13] = hr ? W[13] : t1;                        \
        asm volatile("" : RW4(A[0], 0), RW4(A[0], 4), RW4(A[0], 8), RW2(A[0], 12), RW4(A[1], 0), RW4(A[1], 4), RW4(A[1], 8), RW2(A[1], 12)); \
        swp = hr * 448;                                                                        \
    }
#define SWB(b, t, db, sh) ((b) == 0 && (t) < 6 ? ((t) < 3 ? db##p : db##m) : db)
#define DECL_DB(b, MK, lbo, sh) const uint64_t db = MK(0, lbo, R_ADJ), dbp = (b) == 0 ? MK(0, lbo, R_ADJ + (swp >> (sh))) : db, dbm = (b) == 0 ? MK(0, lbo, R_ADJ - (swp >> (sh))) : db;
#define EARLY 1
#define EARLYK 1
#define PPB 2
#define PP_WAIT() if (wgi == 1) { bar_sync(ppid, 256); ppid ^= 14; }
#define PP_GO() if (wgi == 0) { bar_arrive(ppid, 256); ppid ^= 14; }
#define GAT_ISSUE(base)                                                                        \
    {                                                                                          \
        const char* gs = reinterpret_cast<const char*>(g_ex + 3 * PLANE + (base) + (tile * 16 + wgi * 8 + 2 * kblk(pr, GB) + hr) * 512 + w * 128); \
        const uint32_t gd = hbuf + w * 3584 + hr * 1792, gb = BAR(B_GAT + wu);                 \
        asm volatile("{ .reg .pred e; elect.sync _|e, 0xffffffff;\n"                           \
                     "@e mbarrier.arrive.expect_tx.shared::cta.b64 _, [%2], 3584;\n"           \
                     "@e cp.async.bulk.shared::cluster.global.mbarrier::complete_tx::bytes.multicast::cluster [%0], [%1], 1792, [%2], %3; }" \
                     ::"r"(gd), "l"(gs), "r"(gb), "h"((uint16_t)3) : "memory");                \
        __syncwarp();                                                                          \
    }
#define GAT_FETCH()                                                                            \
    {                                                                                          \
        mbar_wait(BAR(B_GAT + wu), gatph);                                             \
        gatph ^= 1;                                                                            \
        const uint32_t ga = hbuf + w * 3584 + lane * 16;                                       \
        _Pragma("unroll") for (int s2 = 0; s2 < 2; s2++) {                                     \
            lds4(&A[2 * GB + s2][0], ga + s2 * 1792); lds4(&A[2 * GB + s2][4], ga + s2 * 1792 + 512); lds4(&A[2 * GB + s2][8], ga + s2 * 1792 + 1024); \
            asm volatile("ld.shared.v2.u32 {%0,%1}, [%2];" : "=r"(A[2 * GB + s2][12]), "=r"(A[2 * GB + s2][13]) : "r"(ga - lane * 8 + s2 * 1792 + 1536) : "memory"); \
        }                                                                                      \
    }
#define PT 3
#define PREP(b, t, remote)                                                                     \
    if constexpr ((b) < 3 && (t) == PT) {                                                      \
        wg_commit();                                                                           \
        STAMP(80 + 8 * (step & 1) + 2 * (b));                                                  \
        if constexpr (GB == 1 && (b) == 0) { if (remote) GAT_FETCH() }                         \
        if (remote) blk_check<((b) + 1) & 3>(A, BLK(xsrc, (b) + 1), lane, xtag);               \
        STAMP(81 + 8 * (step & 1) + 2 * (b));                                                  \
        if constexpr ((b) == 0) { if (remote) blk_load<3>(A, BLK(xsrc, 3), lane); }            \
        normalize<((b) + 1) & 3>(A, k0, k1);                                                   \
        asm volatile("" : RW4(A[(2 * (b) + 2) & 7], 0), RW4(A[(2 * (b) + 2) & 7], 4), RW4(A[(2 * (b) + 2) & 7], 8), RW2(A[(2 * (b) + 2) & 7], 12), \
                          RW4(A[(2 * (b) + 3) & 7], 0), RW4(A[(2 * (b) + 3) & 7], 4), RW4(A[(2 * (b) + 3) & 7], 8), RW2(A[(2 * (b) + 3) & 7], 12)); \
        wg_fence();                                                                            \
    }                                                                                          \
    if constexpr ((b) == 3 && ((t) == 0 || (t) == 6)) { STAMP(86 + 8 * (step & 1) + (t) / 6); }
#define BLK(base, b) ((base) + kblk(pr, b) * 1024)

#pragma unroll 1
        for (int step = 0; step < 4; step++) {
            const uint32_t tag = (step >> 1) ^ 1;
            const int so = (step >> 1) * 24 + (step & 1) * 12;
            (void)so;
            uint32_t A[8][14];
            uint4* const xsrc = xp0 + ((step & 1) ? PL(2) : PL(0));
            const uint32_t xtag = (step & 1) ? tag : ((seq >> 3) & 1) ^ 1;
            uint32_t xbits;
            {
                float st[4];
                slice_stats(X, st);
                stag ^= 1;
                xbits = x_bits(X);
                tag_slice(X, xtag);
                if (step) send_slice<0>(xsrc + sl * 512, lane, X);
                if (c == 0) st_pkt<0>(stp + sl * 512, __float_as_uint(st[0]), __float_as_uint(st[1]), __float_as_uint(st[2]), settag(__float_as_uint(st[3]), stag));
            }
            STAMP(2 + so);
            uint32_t sv[8];
            if (step == 0) {
                const int rr = lane & 7, hi = lane >> 4;
                const uint32_t rowa = (w < 2 ? hbuf : sb + wgi * STAGE) + ((w & 1) * 16 + (lane & 15)) * 128;
                uint32_t xr[8];
#pragma unroll
                for (int j = 0; j < 8; j++) xr[j] = rowa + ((((j + hi) ^ rr) & 7) << 4) + (j == 7 ? hi * 4096 : 0);
#define X0_BLOCK(b)                                                                            \
    FOR7(constexpr int G = 14 * (b) + (t < 3 ? 2 * t : (t < 6 ? 2 * t + 1 : 6));               \
         uint32_t q0, q1, q2, q3;                                                              \
         const uint32_t ad = t < 6 ? xr[G & 7] : rowa + ((G + 7 * hi) >> 3) * 4096 + ((((G + 7 * hi) ^ rr) & 7) << 4); \
         asm volatile("ldmatrix.sync.aligned.m8n8.x4.shared.b16 {%0,%1,%2,%3}, [%4+%5];" : "=r"(q0), "=r"(q1), "=r"(q2), "=r"(q3) \
                      : "r"(ad), "n"(t < 6 ? (G >> 3) * 4096 : 0) : "memory");                 \
         if (t < 3) { A[2 * (b)][4 * t] = q0; A[2 * (b)][4 * t + 1] = q1; A[2 * (b)][4 * t + 2] = q2; A[2 * (b)][4 * t + 3] = q3; } \
         else if (t < 6) { A[2 * (b) + 1][(4 * t - 12) & 15] = q0; A[2 * (b) + 1][((4 * t - 12) & 15) + 1] = q1; A[2 * (b) + 1][((4 * t - 12) & 15) + 2] = q2; A[2 * (b) + 1][((4 * t - 12) & 15) + 3] = q3; } \
         else { A[2 * (b)][12] = q0; A[2 * (b)][13] = q1; A[2 * (b) + 1][12] = q2; A[2 * (b) + 1][13] = q3; });
                X0_BLOCK(0) X0_BLOCK(1) X0_BLOCK(2) X0_BLOCK(3)
                mbar_wait(BAR(wgi ^ 1), 0);
                R_NEXT();
                R_NEXT();
                stat_load(sv, stp + c * 1024);
                stat_check(sv, stp + c * 1024, stag);
                STAMP(52 + step);
            } else {
                PUSH_SLICE(X)
                stat_load(sv, stp + c * 1024);
                kill<14>(A[2]); kill<14>(A[3]); kill<14>(A[4]); kill<14>(A[5]); kill<14>(A[6]); kill<14>(A[7]);
                PULL_SLICE(X)
                stat_check(sv, stp + c * 1024, stag);
                STAMP(52 + step);
                if (GB == 1) GAT_ISSUE((step & 1) ? PL(2) : PL(0))
                else { blk_load<1>(A, BLK(xsrc, 1), lane); if (GE) GAT_ISSUE((step & 1) ? PL(2) : PL(0)) }
            }
            LnCoef k0, k1;
            {
                k0 = ln_coef(__uint_as_float(sv[0]) + __uint_as_float(sv[4]), __uint_as_float(sv[1]) + __uint_as_float(sv[5]));
                k1 = ln_coef(__uint_as_float(sv[2]) + __uint_as_float(sv[6]), __uint_as_float(sv[3] & ~1u) + __uint_as_float(sv[7] & ~1u));
            }
            if (step) {
                if (GB == 2) { if (!GE) GAT_ISSUE((step & 1) ? PL(2) : PL(0)) }
                else blk_load<2>(A, BLK(xsrc, 2), lane);
            }
            STAMP(3 + so);
            GSTAMP(76 + step);

            if ((step & 1) == 0) {
                float tq[28];
                {
                    float av[28];
#define KV_BLOCK(b)                                                                           \
    if (GB == 2 && (b) == 1 && step) GAT_FETCH()                                                         \
    if ((b) == 2) PUSH_ACK();                                                                 \
    if (QE && (b) == 1) R_RELEASE(2);                                                         \
    if (QE && (b) == 2) { wg_wait<2>(); R_RELEASE(2); }                                       \
    R_WAIT();                                                                                 \
    if ((b) == PPK) { PP_WAIT() }                                                             \
    { DECL_DB(b, BASE128, 16, 0)                                                              \
    wg_fence();                                                                               \
    FOR7(mma_rs56<1, D128(0, t)>(tq, AQ(A, b, t), (b) + t > 0, SWB(b, t, db, 0));             \
         mma_rs56<1, D128(HALF, t)>(av, AQ(A, b, t), (b) + t > 0, SWB(b, t, db, 0));          \
         PREP(b, t, step)); }                                                                 \
    wg_commit();                                                                              \
    if ((b) == 3 && PPK < 4) { PP_GO() }                                                      \
    R_NEXT();
                    if (EARLYK == 0 || step == 0) R_RELEASE(2);
                    normalize<0>(A, k0, k1);
                    KV_BLOCK(0) KV_BLOCK(1) KV_BLOCK(2) KV_BLOCK(3)
                    wg_wait<0>();
                    if (lane < (QE ? 3 : NST)) mbar_arrive(BAR(B_EMPTY + (slot + NST - 1 - lane) % NST));
                    STAMP(4 + so);
                    WSUM(80 + 7 * (step >> 1));
                    const int m = lane >> 3, rr = lane & 7;
                    const uint32_t rowa = hbuf + 16384 + (w * 16 + rr + 8 * (m & 1)) * 128;
                    const uint32_t one = c == 0 ? 0x00003f80u : 0u;
                    if (step == 0) { bar_sync(wgi ? 9 : 1, 224); }
#pragma unroll
                    for (int j = 0; j < 4; j++) {
                        const uint32_t a = rowa + (((2 * j + (m >> 1)) ^ rr) << 4);
                        if (j < 3) stsm4(a, pack2(av[8 * j], av[8 * j + 1]), pack2(av[8 * j + 2], av[8 * j + 3]), pack2(av[8 * j + 4], av[8 * j + 5]), pack2(av[8 * j + 6], av[8 * j + 7]));
                        else stsm4(a, pack2(av[24], av[25]), pack2(av[26], av[27]), one, one);
                    }
                }
                uint32_t PH[28];
                int it = 1;
#pragma unroll 1
                do {
                    float pp[28];
                    phi_gemm(tq, pp);
                    dual_softmax(pp, PH);
                    if (((trips >> (it + 1)) & 1) == 0) continue;
                    {
                        const int m = lane >> 3, rr = lane & 7;
                        const uint32_t rowa = hbuf + (w * 16 + rr + 8 * (m & 1)) * 128;
#pragma unroll
                        for (int j = 0; j < 7; j++) {
                            const int cg = 2 * j + (m >> 1), hi = cg >= 7;
                            stsm4(rowa + hi * 8192 + (((cg - 7 * hi) ^ rr) << 4), PH[4 * j], PH[4 * j + 1], PH[4 * j + 2], PH[4 * j + 3]);
                        }
                    }
                    fence_async();
                    STAMP(5 + so);
#define Q_STAGE(b0)                                                                           \
    R_WAIT();                                                                                 \
    { DECL_DB(b0, BASE128, 16, 0)                                                             \
    wg_fence();                                                                               \
    FOR7(mma_rs56<1, D128(0, t)>(tq, AQ(A, b0, t), (b0) + t > 0, SWB(b0, t, db, 0)));         \
    FOR7(mma_rs56<1, D128(HALF, t)>(tq, AQ(A, (b0) + 1, t), 1, db)); }                        \
    wg_commit();                                                                              \
    R_NEXT();
                    if (QE && wgi == 0) { kill<28>(tq); Q_STAGE(0) Q_STAGE(2) wg_wait<1>(); R_RELEASE(2); wg_wait<0>(); R_RELEASE(1); }
                    bar_sync(2, 256);
                    float kv[28];
                    const uint64_t da = BASE128(OFF_H + 16384, 16, 0), dbk = BASE128(OFF_H, 16, wgi * 512);
                    wg_fence();
                    FOR8(constexpr uint64_t o = ((t >> 2) * STAGE + (t & 3) * 2048) >> 4; mma_ss56_tt<o, o>(kv, t > 0, da, dbk));
                    wg_commit();
                    wg_wait<0>();
#pragma unroll
                    for (int hf = 0; hf < 2; hf++) {
                        const int d = 16 * w + g + 8 * hf;
                        if ((d < 56 && (d >= 28) == (c >= 2)) || d == 56) {
                            const int item = d < 56 ? 2 * d + (c & 1) : 112 + c;
                            uint4* dst = g_kv1 + ((sl * 16 + (item >> 3)) * 16 + tile) * 32 + wgi * 16 + (item & 7);
#define KVW(i) pack2(kv[4 * (i) + 2 * hf], kv[4 * (i) + 2 * hf + 1])
                            st_pkt<0>(dst, settag(KVW(0), tag), KVW(1), KVW(2), KVW(3));
                            st_pkt<8>(dst, settag(KVW(4), tag), KVW(5), KVW(6), 0u);
                        }
                    }
                    __syncwarp();
                    kseq++;
                    if (lane == 0) st_word(g_c1 + ((sl * 8 + (tid >> 5)) * 16 + tile) * 32, kseq);
                    bar_arrive(7, 384);
                    STAMP(6 + so);
                    if (!QE || wgi == 1) { kill<28>(tq); Q_STAGE(0) Q_STAGE(2) wg_wait<1>(); R_RELEASE(2); wg_wait<0>(); R_RELEASE(1); }
                    STAMP(7 + so);
                    kill<28>(PH);
                } while (((trips >> (++it)) & 1));
                STAMP(8 + so);
                if (step) {
                    slice_load<PL(0)>(X, xp0 + sl * 512, lane);
                } else {
                    const uint32_t* xp = reinterpret_cast<const uint32_t*>(x_in + (size_t)(tile * 128 + wu * 16 + g) * 448 + 56 * sl + 2 * c);
#pragma unroll
                    for (int i = 0; i < 7; i++) { X[2 * i] = __ldg(xp + 4 * i); X[2 * i + 1] = __ldg(xp + 4 * i + 8 * 224); }
                }
                bar_sync(3, 384);
                STAMP(9 + so);
                const uint4* const osrc = xp0 + PL(1);
                {
                    float nm[32];
                    const uint64_t db = BASE128(OFF_KVB, 16, 0);
                    wg_fence();
                    FOR7(mma_rs64<0, ((t >> 2) * 8192 + (t & 3) * 32) / 16>(nm, PH[4 * t], PH[4 * t + 1], PH[4 * t + 2], PH[4 * t + 3], t > 0, db));
                    wg_commit();
                    wg_wait<0>();
                    const float i00 = rcp(nm[28] + 1e-6f), i01 = rcp(nm[29] + 1e-6f), i10 = rcp(nm[30] + 1e-6f), i11 = rcp(nm[31] + 1e-6f);
                    const float m0 = c >= 2 ? i01 : i00, m1 = c >= 2 ? i11 : i10;
                    uint32_t O[14];
#pragma unroll
                    for (int i = 0; i < 7; i++) {
                        const float f0 = i < 3 ? i00 : (i > 3 ? i01 : m0), f1 = i < 3 ? i10 : (i > 3 ? i11 : m1);
                        O[2 * i] = pack2(nm[4 * i] * f0, nm[4 * i + 1] * f0);
                        O[2 * i + 1] = pack2(nm[4 * i + 2] * f1, nm[4 * i + 3] * f1);
                    }
                    if (OST) { PP_WAIT() }
                    tag_slice(O, tag);
                    send_slice<PL(1)>(xp0 + sl * 512, lane, O);
                    seq++;
                    if (lane == 0) st_word(cx(sl), seq);
                    STAMP(10 + so);
                    PUSH_SLICE(O)
                    if (OST == 1) { PP_GO() }
                    const uint32_t cv = ld_word(cx(lane & 7));
                    PULL_SLICE(O)
                    check_cnt(cv, cx(lane & 7), seq);
                    if (OST == 2) { PP_GO() }
                    STAMP(56 + (step >> 1));
                    GAT_ISSUE(PL(1))
                    blk_load<3 - GB>(A, BLK(osrc, 3 - GB), lane);
                }
                float ao[28];
#define WO_BLOCK(b)                                                                           \
    if ((b) > 0) blk_check<b>(A, BLK(osrc, b), lane, tag);                                    \
    if (((b) & 1) == 0) R_WAIT();                                                             \
    { DECL_DB(b, BASE128, 16, 0)                                                              \
    wg_fence();                                                                               \
    FOR7(mma_rs56<1, D128(((b) & 1) * HALF, t)>(ao, AQ(A, b, t), (b) + t > 0, SWB(b, t, db, 0))); } \
    wg_commit();                                                                              \
    if ((b) & 1) R_NEXT();
                WO_BLOCK(0)
                STAMP(11 + so);
                blk_load<3>(A, BLK(osrc, 3), lane);
                if (GB == 1) GAT_FETCH()
                WO_BLOCK(1)
                if (GB == 2) GAT_FETCH()
                WO_BLOCK(2)
                PUSH_ACK();
                WO_BLOCK(3)
                wg_wait<0>();
                if (EARLY >= 1) R_RELEASE(2);
                if (EARLY >= 2) R_RELEASE(1);
                STAMP(12 + so);
                WSUM(86 + 7 * (step >> 1));
                x_fix(X, xbits);
#pragma unroll
                for (int i = 0; i < 14; i++) X[i] = pack2(bf_lo(X[i]) + ao[2 * i], bf_hi(X[i]) + ao[2 * i + 1]);
            } else {
                uint32_t H[56];
                float ag[64];
#define F1_EPI(dst, ng, ag)                                                                    \
    _Pragma("unroll") for (int i = 0; i < 2 * (ng); i++)                                       \
        (dst)[i] = pack2(geglu(ag[2 * i], ag[4 * (ng) + 2 * i]), geglu(ag[2 * i + 1], ag[4 * (ng) + 2 * i + 1]));
#define H_PUSH(h0, off) st_async4(rem_h + (off), H[h0], H[(h0) + 1], H[(h0) + 2], H[(h0) + 3], mapa(BAR(B_RECV2 + wgi), hr ^ 1));
#define F1_BLOCK(b, first)                                                                     \
    if ((first) && (b) < 2 && (b) >= EARLY) R_RELEASE(2);                                      \
    if (GB == 2 && (first) && (b) == 1) GAT_FETCH()                                                       \
    if ((first) && (b) == 2) PUSH_ACK();                                                       \
    R_WAIT();                                                                                  \
    if ((b) == ((first) ? PPF : PPB)) { PP_WAIT() }                                            \
    { DECL_DB(b, BASE128, HALF, 0)                                                             \
    wg_fence();                                                                                \
    FOR7(mma_rs128<1, D128(0, t)>(ag, AQ(A, b, t), (b) + t > 0, SWB(b, t, db, 0));             \
         if constexpr (first) { PREP(b, t, true) }); }                                         \
    wg_commit();                                                                               \
    if ((b) == 3) { PP_GO() }                                                                  \
    if ((b) > 0) { wg_wait<1>(); R_RELEASE(1); }       \
    R_NEXT();
                normalize<0>(A, k0, k1);
                F1_BLOCK(0, true) F1_BLOCK(1, true) F1_BLOCK(2, true) F1_BLOCK(3, true)
                if (t128 == 0) { mbar_expect_tx(BAR(B_RECV + wgi), 16384); mbar_expect_tx(BAR(B_RECV2 + wgi), 12288); }
                PUSH_BEGIN();
                wg_wait<0>();
                R_RELEASE(1);
                if (step == 1) R_NEXT();
                int p = 0;
#pragma unroll 1
                do {
                    STAMP(68 + p);
                    F1_EPI(H + 32, 8, ag)
                    STAMP(4 + p + so);
                    WSUM(81 + p + 7 * (step >> 1));
                    if (((trips >> (p + 1)) & 1) == 0) continue;
                    {
                        const uint32_t pk = (p ? hbuf + 16384 : sb + OFF_KVB + wgi * 8192) + w * 2048;
#pragma unroll
                        for (int k = 0; k < 4; k++) sts4(pk + k * 512 + lane * 16, H[32 + 4 * k], H[33 + 4 * k], H[34 + 4 * k], H[35 + 4 * k]);
                        fence_async();
                        __syncwarp();
                        asm volatile(ELECT "cp.async.bulk.shared::cluster.shared::cta.mbarrier::complete_tx::bytes [%0], [%1], 2048, [%2]; }"
                                     ::"r"(mapa(hbuf + p * 8192 + w * 2048, hr ^ 1)), "r"(pk), "r"(mapa(BAR(B_RECV + wgi), hr ^ 1)) : "memory");
                    }
                    kill<64>(ag);
                    F1_BLOCK(0, false) F1_BLOCK(1, false) F1_BLOCK(2, false) F1_BLOCK(3, false)
                    wg_wait<0>();
                    R_RELEASE(1);
                    kill<16>(H + 32);
                } while (((trips >> (++p)) & 1));
#pragma unroll
                for (int k = 0; k < 4; k++) lds4(H + 16 + 4 * k, hbuf + 16384 + w * 2048 + k * 512 + lane * 16);
                __syncwarp();
                if (lane == 0) asm volatile("mbarrier.arrive.shared::cluster.b64 _, [%0];" ::"r"(mapa(BAR(B_ACK2 + wgi), hr ^ 1)) : "memory");
                const uint32_t rem_h = mapa(hbuf + w * 2048 + lane * 16, hr ^ 1);
#define F1_LAST(b0)                                                                            \
    R_WAIT();                                                                                  \
    if (b0) { PP_WAIT() }                                                                      \
    { DECL_DB(b0, BASE64, HALF, 1)                                                             \
    wg_fence();                                                                                \
    FOR7(mma_rs64<1, D64(0, t)>(al, AQ(A, b0, t), (b0) + t > 0, SWB(b0, t, db, 1)));           \
    FOR7(mma_rs64<1, D64(7168, t)>(al, AQ(A, (b0) + 1, t), 1, db)); }                          \
    wg_commit();                                                                               \
    if (b0) { PP_GO() }                                                                        \
    R_NEXT();
                float al[32];
                F1_LAST(0)
                mbar_wait(BAR(B_RECV + wgi), rcvph);
                rcvph ^= 1;
                mbar_wait(BAR(B_ACK2 + wgi), step >> 1);
                H_PUSH(32, 16384) H_PUSH(36, 16896)
                F1_LAST(2)
                H_PUSH(40, 17408) H_PUSH(44, 17920)
                wg_wait<1>();
                R_RELEASE(2);
                wg_wait<0>();
                R_RELEASE(1);
                uint32_t HP[56];
#pragma unroll
                for (int k = 0; k < 4; k++) lds4(H + 4 * k, sb + OFF_KVB + wgi * 8192 + w * 2048 + k * 512 + lane * 16);
#pragma unroll
                for (int t = 0; t < 8; t++) lds4(HP + 4 * t, hbuf + (t >> 2) * 8192 + w * 2048 + (t & 3) * 512 + lane * 16);
                F1_EPI(H + 48, 4, al)
                H_PUSH(48, 24576 - w * 1024) H_PUSH(52, 25088 - w * 1024)
                STAMP(7 + so);
                WSUM(84 + 7 * (step >> 1));
                float acc[28];
                const uint32_t roA = hr ? 256u : 0u, roB = hr ? (uint32_t)-1536 : 0u;
                const uint32_t rpA = hr ? 0u : 256u, rpB = hr ? 0u : (uint32_t)-1536;
                float res[28];
                uint32_t v0[14], v1[14], P[14];
                const uint4* ps = xp0 + sl * 512;
#define F2_OWN_A()                                                                             \
    R_WAIT();                                                                                  \
    d0 = BASE128(0, 16, R_ADJ + roA); d1 = BASE128(0, 16, R_ADJ + roB);                        \
    wg_fence();                                                                                \
    FOR14(if constexpr (t < OT) mma_rs56<1, t * 128>(acc, H[4 * t], H[4 * t + 1], H[4 * t + 2], H[4 * t + 3], t > 0, d0)); \
    wg_commit();
#define F2_OWN_B()                                                                             \
    wg_fence();                                                                                \
    FOR14(if constexpr (t >= OT) mma_rs56<1, t * 128>(acc, H[4 * t], H[4 * t + 1], H[4 * t + 2], H[4 * t + 3], 1, t < 12 ? d0 : d1)); \
    wg_commit();                                                                               \
    R_NEXT();
#define F2_PEER()                                                                              \
    R_WAIT();                                                                                  \
    if (F2PP) { PP_WAIT() }                                                                    \
    d0 = BASE128(0, 16, R_ADJ + rpA); d1 = BASE128(0, 16, R_ADJ + rpB);                        \
    wg_fence();                                                                                \
    FOR14(mma_rs56<1, t * 128>(acc, HP[4 * t], HP[4 * t + 1], HP[4 * t + 2], HP[4 * t + 3], 1, t < 12 ? d0 : d1)); \
    wg_commit();                                                                               \
    if (F2PP) { PP_GO() }                                                                      \
    R_NEXT();
#define F2_TURN(u)                                                                             \
    wg_wait<1>();                                                                              \
    R_RELEASE(2);                                                                              \
    wg_wait<0>();                                                                              \
    R_RELEASE(1);                                                                              \
    _Pragma("unroll") for (int i = 0; i < 14; i++) P[i] = pack2(acc[2 * i], acc[2 * i + 1]);   \
    tag_slice(P, tag);                                                                         \
    asm volatile("" : RW4(P, 0), RW4(P, 4), RW4(P, 8), RW2(P, 12));                            \
    kill<28>(acc);                                                                             \
    F2_OWN_A()                                                                                 \
    if ((u) == 2) { slice_load<PL(3)>(v0, ps, lane); slice_load<PL(4)>(v1, ps, lane); } \
    send_slice<PL(3 + (u))>(xp0 + (2 * ((pr + (u) + 1) & 3) + hr) * 512, lane, P);             \
    seq++;                                                                                     \
    if (lane == 0) st_word(cx(sl), seq);                                                       \
    __syncwarp();                                                                              \
    STAMP(8 + (u) + so);                                                                       \
    F2_OWN_B()
                uint64_t d0, d1;
                F2_OWN_A()
                F2_OWN_B()
                R_WAIT();
                d0 = BASE128(0, 16, R_ADJ + rpA); d1 = BASE128(0, 16, R_ADJ + rpB);
                wg_fence();
                FOR8(mma_rs56<1, t * 128>(acc, HP[4 * t], HP[4 * t + 1], HP[4 * t + 2], HP[4 * t + 3], 1, d0));
                wg_commit();
                mbar_wait(BAR(B_RECV2 + wgi), step >> 1);
#pragma unroll
                for (int k = 0; k < 4; k++) lds4(HP + 32 + 4 * k, hbuf + 16384 + w * 2048 + k * 512 + lane * 16);
                lds4(HP + 48, hbuf + 24576 + w * 1024 + lane * 16);
                lds4(HP + 52, hbuf + 25088 + w * 1024 + lane * 16);
                if (step == 1) PUSH_ACK();
                wg_fence();
                FOR14(if constexpr (t >= 8) mma_rs56<1, t * 128>(acc, HP[4 * t], HP[4 * t + 1], HP[4 * t + 2], HP[4 * t + 3], 1, t < 12 ? d0 : d1));
                wg_commit();
                R_NEXT();
                F2_TURN(0)
                F2_PEER()
                F2_TURN(1)
                F2_PEER()
                F2_TURN(2)
                STAMP(64 + 8 * (step >> 1));
                slice_check<PL(3)>(v0, ps, lane, tag);
                slice_check<PL(4)>(v1, ps, lane, tag);
#pragma unroll
                for (int i = 0; i < 14; i++) { res[2 * i] = bf_lo(v0[i]) + bf_lo(v1[i]); res[2 * i + 1] = bf_hi(v0[i]) + bf_hi(v1[i]); }
                slice_load<PL(2)>(X, ps, lane);
                STAMP(65 + 8 * (step >> 1));
                const uint32_t cv = ld_word(cx(2 * ((pr + 1) & 3) + hr));
                F2_PEER()
                STAMP(66 + 8 * (step >> 1));
                check_cnt(cv, cx(2 * ((pr + 1) & 3) + hr), seq);
                STAMP(67 + 8 * (step >> 1));
                slice_load<PL(5)>(v0, ps, lane);
                x_fix(X, xbits);
                slice_check<PL(5)>(v0, ps, lane, tag);
#pragma unroll
                for (int i = 0; i < 14; i++) { res[2 * i] += bf_lo(v0[i]); res[2 * i + 1] += bf_hi(v0[i]); }
                STAMP(11 + so);
                wg_wait<0>();
                if (EARLYK >= 1) R_RELEASE(2);
                STAMP(12 + so);
                WSUM(85 + 7 * (step >> 1));
#pragma unroll
                for (int i = 0; i < 14; i++) X[i] = pack2(fmaf(res[2 * i] + acc[2 * i], 0.5f, bf_lo(X[i])), fmaf(res[2 * i + 1] + acc[2 * i + 1], 0.5f, bf_hi(X[i])));
            }
        }
        {
            const int m = lane >> 3, rr = lane & 7;
            const uint32_t ob = hbuf + w * 2048, rowa = ob + (rr + 8 * (m & 1)) * 112 + (m >> 1) * 16;
#pragma unroll
            for (int j = 0; j < 3; j++) stsm4(rowa + 32 * j, X[4 * j], X[4 * j + 1], X[4 * j + 2], X[4 * j + 3]);
            asm volatile("stmatrix.sync.aligned.m8n8.x2.shared.b16 [%0], {%1,%2};" ::"r"(ob + (rr + 8 * (m & 1)) * 112 + 96), "r"(X[12]), "r"(X[13]) : "memory");
            fence_async();
            __syncwarp();
            if (lane == 0) {
                asm volatile("cp.async.bulk.tensor.2d.global.shared::cta.bulk_group [%0, {%2, %3}], [%1];" ::"l"(&maps.out), "r"(ob), "r"(56 * sl), "r"(tile * 128 + (tid >> 5) * 16) : "memory");
                asm volatile("cp.async.bulk.commit_group;" ::: "memory");
                asm volatile("cp.async.bulk.wait_group.read 0;" ::: "memory");
            }
        }
        STAMP(50);
        GSTAMP(61);
        PDUMP();
    }
}

typedef CUresult (*EncodeFn)(CUtensorMap*, CUtensorMapDataType, cuuint32_t, void*, const cuuint64_t*, const cuuint64_t*, const cuuint32_t*,
                             const cuuint32_t*, CUtensorMapInterleave, CUtensorMapSwizzle, CUtensorMapL2promotion, CUtensorMapFloatOOBfill);

static void make_map(EncodeFn enc, CUtensorMap* m, const void* p, uint64_t cols, uint64_t rows, uint32_t bc, uint32_t br, CUtensorMapSwizzle sw) {
    cuuint64_t gd[2] = {cols, rows};
    cuuint64_t gs[1] = {cols * 2};
    cuuint32_t bd[2] = {bc, br};
    cuuint32_t es[2] = {1, 1};
    enc(m, CU_TENSOR_MAP_DATA_TYPE_BFLOAT16, 2, const_cast<void*>(p), gd, gs, bd, es, CU_TENSOR_MAP_INTERLEAVE_NONE, sw,
        CU_TENSOR_MAP_L2_PROMOTION_L2_128B, CU_TENSOR_MAP_FLOAT_OOB_FILL_NONE);
}

extern "C" void kernel_launch(void* const* d_in, const int* in_sizes, int n_in, void* d_out, int out_size) {
    (void)in_sizes; (void)n_in; (void)out_size;
    static EncodeFn enc = nullptr;
    static Scratch* scratch = nullptr;
    if (!enc) {
        void* fn = nullptr;
        cudaDriverEntryPointQueryResult qr;
        cudaGetDriverEntryPoint("cuTensorMapEncodeTiled", &fn, cudaEnableDefault, &qr);
        enc = (EncodeFn)fn;
        cudaGetSymbolAddress((void**)&scratch, g_scratch);
        cudaFuncSetAttribute(fused_kernel, cudaFuncAttributeMaxDynamicSharedMemorySize, SMEM_BYTES);
    }
    Maps maps;
    {
        cuuint64_t gd[3] = {64, 2048, 7};
        cuuint64_t gs[2] = {896, 128};
        cuuint32_t bd[3] = {64, 32, 7};
        cuuint32_t es[3] = {1, 1, 1};
        enc(&maps.x, CU_TENSOR_MAP_DATA_TYPE_BFLOAT16, 3, d_in[0], gd, gs, bd, es, CU_TENSOR_MAP_INTERLEAVE_NONE, CU_TENSOR_MAP_SWIZZLE_128B,
            CU_TENSOR_MAP_L2_PROMOTION_L2_128B, CU_TENSOR_MAP_FLOAT_OOB_FILL_NONE);
    }
    make_map(enc, &maps.out, d_out, 448, 2048, 56, 16, CU_TENSOR_MAP_SWIZZLE_NONE);
    make_map(enc, &maps.qkv, d_in[1], 1344, 448, 64, 112, CU_TENSOR_MAP_SWIZZLE_128B);
    make_map(enc, &maps.wo, d_in[3], 448, 448, 64, 112, CU_TENSOR_MAP_SWIZZLE_128B);
    make_map(enc, &maps.wg, d_in[5], 1792, 448, 64, 112, CU_TENSOR_MAP_SWIZZLE_128B);
    make_map(enc, &maps.wu, d_in[6], 1792, 448, 64, 112, CU_TENSOR_MAP_SWIZZLE_128B);
    make_map(enc, &maps.wg32, d_in[5], 1792, 448, 32, 112, CU_TENSOR_MAP_SWIZZLE_64B);
    make_map(enc, &maps.wu32, d_in[6], 1792, 448, 32, 112, CU_TENSOR_MAP_SWIZZLE_64B);
    make_map(enc, &maps.wd, d_in[7], 448, 1792, 64, 112, CU_TENSOR_MAP_SWIZZLE_128B);
    fused_kernel<<<128, 384, SMEM_BYTES>>>(scratch, (const __nv_bfloat16*)d_in[0], (const __nv_bfloat16*)d_in[2], 7, (const __nv_bfloat16*)d_in[5],
                                           (const __nv_bfloat16*)d_in[6], (const __nv_bfloat16*)d_in[7], maps);
}
```

```cpp
#include <cuda_runtime.h>
#include <cuda.h>
#include <cuda_bf16.h>
#include <stdint.h>
#include <type_traits>

#define MC 1
#define PPF 2
#define GE 0
#define ACAN 1
#define SPLIT0 1
#define OT 2
#define F2PP 0
#define PPK 2
#define QE 1
#define OST 1
#define GB 1
#define B3T 6
#define PP

namespace {

constexpr uint32_t STAGE = 28672, HALF = 14336;
constexpr int NST = 5;
constexpr uint32_t OFF_H = NST * STAGE;
constexpr uint32_t OFF_KVB = OFF_H + 2 * STAGE;
constexpr uint32_t OFF_WPHI = OFF_KVB + 16384;
constexpr uint32_t OFF_XR = OFF_WPHI + 7168;
constexpr uint32_t OFF_BAR = OFF_XR + 6144;
constexpr uint32_t SMEM_BYTES = OFF_BAR + 256 + 1536;
constexpr int B_EMPTY = NST, B_RECV = 2 * NST, B_RECV2 = B_RECV + 2, B_PACK = B_RECV2 + 2, B_GAT = B_PACK + 1, B_ACK = B_GAT + 8, B_ACK2 = B_ACK + 2, B_COUNT = B_ACK2 + 2;

constexpr int PACK = 14;

struct Maps { CUtensorMap x, qkv, wo, wg, wu, wg32, wu32, wd, out; };

}

constexpr int PLANE = 16 * 2 * 8 * 512;
struct Scratch {
    uint4 ex[6 * PLANE];
    uint4 kv1[8 * 16 * 16 * 32];
    uint4 kv2[8 * 512];
    uint32_t c1[8 * 8 * 16 * 32];
    uint32_t cw[8 * 32];
    uint4 wp[8 * 32 * (HALF / 16)];
};
__device__ __align__(1024) Scratch g_scratch;
#define g_ex (sc->ex)
#define g_kv1 (sc->kv1)
#define g_kv2 (sc->kv2)
#define g_c1 (sc->c1)
#define g_cw (sc->cw)
#define g_wp (sc->wp)
#define STAMP(i)
#define GSTAMP(i)
#define PDUMP()
#define ASTAMP(i)

namespace {

__device__ __forceinline__ int fresh_tid() { int t; asm volatile("mov.u32 %0, %%tid.x;" : "=r"(t)); return t; }
__device__ __forceinline__ uint4* again(uint4* p) { asm volatile("" : "+l"(p)); return p; }
template <int N> __device__ __forceinline__ void kill(uint32_t* v) {
#pragma unroll
    for (int i = 0; i < N; i++) v[i] = 0;
}
template <int N> __device__ __forceinline__ void kill(float* v) {
#pragma unroll
    for (int i = 0; i < N; i++) v[i] = 0.f;
}
__device__ __forceinline__ uint32_t s2u(const void* p) { return (uint32_t)__cvta_generic_to_shared(p); }
__device__ __forceinline__ void mbar_init(uint32_t a, uint32_t c) { asm volatile("mbarrier.init.shared::cta.b64 [%0], %1;" ::"r"(a), "r"(c) : "memory"); }
__device__ __forceinline__ void mbar_expect_tx(uint32_t a, uint32_t b) { asm volatile("mbarrier.arrive.expect_tx.shared::cta.b64 _, [%0], %1;" ::"r"(a), "r"(b) : "memory"); }
__device__ __forceinline__ void mbar_arrive(uint32_t a) { asm volatile("mbarrier.arrive.shared::cta.b64 _, [%0];" ::"r"(a) : "memory"); }
#define GIVE_UP(id) "trap;\n"
#define SPIN_MAX "0x400000"
#define SPIN_TAIL(id) "add.u32 n, n, 1;\n setp.lt.u32 p, n, " SPIN_MAX ";\n @p bra.uni LP;\n" GIVE_UP(id) " DN:\n }"
__device__ __forceinline__ void mbar_wait(uint32_t a, uint32_t ph) {
    asm volatile("{ .reg .pred p; .reg .b32 n; mov.u32 n, 0;\n LP:\n"
                 "mbarrier.try_wait.parity.shared::cta.b64 p, [%0], %1;\n @p bra DN;\n"
                 "add.u32 n, n, 1;\n setp.lt.u32 p, n, " SPIN_MAX ";\n @p bra LP;\n"
                 GIVE_UP("")
                 " DN:\n }" ::"r"(a), "r"(ph) : "memory");
}
#define ELECT "{ .reg .pred e; elect.sync _|e, 0xffffffff; @e "
__device__ __forceinline__ void tma2d(uint32_t dst, const CUtensorMap* m, int c0, int c1, uint32_t bar) {
    asm volatile(ELECT "cp.async.bulk.tensor.2d.shared::cluster.global.mbarrier::complete_tx::bytes [%0], [%1, {%3, %4}], [%2]; }" ::"r"(dst), "l"(m), "r"(bar), "r"(c0), "r"(c1) : "memory");
}
__device__ __forceinline__ void tma3x(uint32_t dst, const CUtensorMap* m, int row, uint32_t bar) {
    asm volatile(ELECT "cp.async.bulk.tensor.3d.shared::cluster.global.mbarrier::complete_tx::bytes [%0], [%1, {0, %3, 0}], [%2]; }" ::"r"(dst), "l"(m), "r"(bar), "r"(row) : "memory");
}
template <int OFF>
__device__ __forceinline__ void ld_pkt(uint32_t* v, const uint4* p) {
    asm volatile("{ .reg .b128 t; ld.relaxed.gpu.global.b128 t, [%4+%5]; mov.b128 {%0,%1,%2,%3}, t; }" : "=r"(v[0]), "=r"(v[1]), "=r"(v[2]), "=r"(v[3]) : "l"(p), "n"(OFF * 16) : "memory");
}
template <int OFF>
__device__ __forceinline__ void st_pkt(uint4* p, uint32_t a, uint32_t b, uint32_t c, uint32_t d) {
    asm volatile("{ .reg .b128 t; mov.b128 t, {%1,%2,%3,%4}; st.relaxed.gpu.global.b128 [%0+%5], t; }" ::"l"(p), "r"(a), "r"(b), "r"(c), "r"(d), "n"(OFF * 16) : "memory");
}
__device__ __forceinline__ uint32_t pack2(float lo, float hi) {
    uint32_t r;
    asm("cvt.rn.bf16x2.f32 %0, %1, %2;" : "=r"(r) : "f"(hi), "f"(lo));
    return r;
}
__device__ __forceinline__ float bf_lo(uint32_t w) { return __uint_as_float(w << 16); }
__device__ __forceinline__ float bf_hi(uint32_t w) { return __uint_as_float(w & 0xffff0000u); }
__device__ __forceinline__ uint32_t settag(uint32_t w, uint32_t tag) { return (w & ~1u) | tag; }
__device__ __forceinline__ float ex2(float x) { float y; asm("ex2.approx.ftz.f32 %0, %1;" : "=f"(y) : "f"(x)); return y; }
__device__ __forceinline__ float rcp(float x) { float y; asm("rcp.approx.ftz.f32 %0, %1;" : "=f"(y) : "f"(x)); return y; }
__device__ __forceinline__ float tanh_hw(float x) { float y; asm("tanh.approx.f32 %0, %1;" : "=f"(y) : "f"(x)); return y; }
__device__ __forceinline__ void stsm4(uint32_t addr, uint32_t a, uint32_t b, uint32_t c, uint32_t d) {
    asm volatile("stmatrix.sync.aligned.m8n8.x4.shared.b16 [%0], {%1,%2,%3,%4};" ::"r"(addr), "r"(a), "r"(b), "r"(c), "r"(d) : "memory");
}
__device__ __forceinline__ void fence_async() { asm volatile("fence.proxy.async.shared::cta;" ::: "memory"); }
__device__ __forceinline__ void bar_sync(int id, int n) { asm volatile("bar.sync %0, %1;" ::"r"(id), "r"(n) : "memory"); }
__device__ __forceinline__ void bar_arrive(int id, int n) { asm volatile("bar.arrive %0, %1;" ::"r"(id), "r"(n) : "memory"); }
__device__ __forceinline__ void wg_fence() { asm volatile("wgmma.fence.sync.aligned;" ::: "memory"); }
__device__ __forceinline__ void wg_commit() { asm volatile("wgmma.commit_group.sync.aligned;" ::: "memory"); }
template <int N> __device__ __forceinline__ void wg_wait() { asm volatile("wgmma.wait_group.sync.aligned %0;" ::"n"(N) : "memory"); }

constexpr uint32_t SB0 = 1024;
__host__ __device__ constexpr uint32_t dlo(uint32_t off, uint32_t lbo) { return ((SB0 + off) >> 4) | ((lbo >> 4) << 16); }
__host__ __device__ constexpr uint32_t dhi(uint32_t sbo, uint32_t sw) { return (sbo >> 4) | (sw << 30); }
__device__ __forceinline__ uint64_t dbase(uint32_t lo, uint32_t hi) { uint64_t d; asm volatile("mov.b64 %0, {%1, %2};" : "=l"(d) : "r"(lo), "r"(hi)); return d; }
#define BASE128(off, lbo, adj) dbase(dlo(off, lbo) + (adj), dhi(1024, 1))
#define BASE64(off, lbo, adj) dbase(dlo(off, lbo) + (adj), dhi(512, 2))

#define ACC4(d, o) "+f"(d[o]), "+f"(d[o + 1]), "+f"(d[o + 2]), "+f"(d[o + 3])
#define ACC28(d) ACC4(d, 0), ACC4(d, 4), ACC4(d, 8), ACC4(d, 12), ACC4(d, 16), ACC4(d, 20), ACC4(d, 24)
#define ACC32(d, o) ACC4(d, o), ACC4(d, o + 4), ACC4(d, o + 8), ACC4(d, o + 12), ACC4(d, o + 16), ACC4(d, o + 20), ACC4(d, o + 24), ACC4(d, o + 28)

template <int TB, uint64_t D>
__device__ __forceinline__ void mma_rs56(float* d, uint32_t a0, uint32_t a1, uint32_t a2, uint32_t a3, int sd, uint64_t base) {
    asm volatile("{ .reg .pred p; .reg .b64 db; setp.ne.b32 p, %32, 0; add.u64 db, %33, %34;\n"
                 "wgmma.mma_async.sync.aligned.m64n56k16.f32.bf16.bf16 "
                 "{%0,%1,%2,%3,%4,%5,%6,%7,%8,%9,%10,%11,%12,%13,%14,%15,%16,%17,%18,%19,%20,%21,%22,%23,%24,%25,%26,%27}, "
                 "{%28,%29,%30,%31}, db, p, 1, 1, %35; }\n"
                 : ACC28(d)
                 : "r"(a0), "r"(a1), "r"(a2), "r"(a3), "r"(sd), "l"(base), "n"(D), "n"(TB));
}
template <int TB, uint64_t D>
__device__ __forceinline__ void mma_rs64(float* d, uint32_t a0, uint32_t a1, uint32_t a2, uint32_t a3, int sd, uint64_t base) {
    asm volatile("{ .reg .pred p; .reg .b64 db; setp.ne.b32 p, %36, 0; add.u64 db, %37, %38;\n"
                 "wgmma.mma_async.sync.aligned.m64n64k16.f32.bf16.bf16 "
                 "{%0,%1,%2,%3,%4,%5,%6,%7,%8,%9,%10,%11,%12,%13,%14,%15,%16,%17,%18,%19,%20,%21,%22,%23,%24,%25,%26,%27,%28,%29,%30,%31}, "
                 "{%32,%33,%34,%35}, db, p, 1, 1, %39; }\n"
                 : ACC32(d, 0)
                 : "r"(a0), "r"(a1), "r"(a2), "r"(a3), "r"(sd), "l"(base), "n"(D), "n"(TB));
}
template <int TB, uint64_t D>
__device__ __forceinline__ void mma_rs128(float* d, uint32_t a0, uint32_t a1, uint32_t a2, uint32_t a3, int sd, uint64_t base) {
    asm volatile("{ .reg .pred p; .reg .b64 db; setp.ne.b32 p, %68, 0; add.u64 db, %69, %70;\n"
                 "wgmma.mma_async.sync.aligned.m64n128k16.f32.bf16.bf16 "
                 "{%0,%1,%2,%3,%4,%5,%6,%7,%8,%9,%10,%11,%12,%13,%14,%15,%16,%17,%18,%19,%20,%21,%22,%23,%24,%25,%26,%27,%28,%29,%30,%31,%32,%33,%34,%35,%36,%37,%38,%39,%40,%41,%42,%43,%44,%45,%46,%47,%48,%49,%50,%51,%52,%53,%54,%55,%56,%57,%58,%59,%60,%61,%62,%63}, "
                 "{%64,%65,%66,%67}, db, p, 1, 1, %71; }\n"
                 : ACC32(d, 0), ACC32(d, 32)
                 : "r"(a0), "r"(a1), "r"(a2), "r"(a3), "r"(sd), "l"(base), "n"(D), "n"(TB));
}
template <uint64_t DA, uint64_t DB>
__device__ __forceinline__ void mma_ss56_tt(float* d, int sd, uint64_t ba, uint64_t bb) {
    asm volatile("{ .reg .pred p; .reg .b64 da, db; setp.ne.b32 p, %28, 0; add.u64 da, %29, %31; add.u64 db, %30, %32;\n"
                 "wgmma.mma_async.sync.aligned.m64n56k16.f32.bf16.bf16 "
                 "{%0,%1,%2,%3,%4,%5,%6,%7,%8,%9,%10,%11,%12,%13,%14,%15,%16,%17,%18,%19,%20,%21,%22,%23,%24,%25,%26,%27}, "
                 "da, db, p, 1, 1, 1, 1; }\n"
                 : ACC28(d)
                 : "r"(sd), "l"(ba), "l"(bb), "n"(DA), "n"(DB));
}
template <int... I> struct Seq {};
template <class F, int... I> __device__ __forceinline__ void static_for_impl(F&& f, Seq<I...>) { (f(std::integral_constant<int, I>{}), ...); }
#define FOR7(...) static_for_impl([&](auto T_) { constexpr int t = decltype(T_)::value; __VA_ARGS__; }, Seq<0, 1, 2, 3, 4, 5, 6>{})
#define FOR8(...) static_for_impl([&](auto T_) { constexpr int t = decltype(T_)::value; __VA_ARGS__; }, Seq<0, 1, 2, 3, 4, 5, 6, 7>{})
#define FOR14(...) static_for_impl([&](auto T_) { constexpr int t = decltype(T_)::value; __VA_ARGS__; }, Seq<0, 1, 2, 3, 4, 5, 6, 7, 8, 9, 10, 11, 12, 13>{})

__device__ __forceinline__ int kblk(int p, int b) { return b == 0 ? p : b - (b <= p); }
__host__ __device__ constexpr int krow(int t) { return t < 3 ? 16 * t : (t < 6 ? 56 + 16 * (t - 3) : 48); }
#define AQ(A, b, t) ((t) < 3 ? A[2 * (b)][4 * (t)] : (t) < 6 ? A[2 * (b) + 1][4 * ((t) - 3)] : A[2 * (b)][12]), \
                    ((t) < 3 ? A[2 * (b)][4 * (t) + 1] : (t) < 6 ? A[2 * (b) + 1][4 * ((t) - 3) + 1] : A[2 * (b)][13]), \
                    ((t) < 3 ? A[2 * (b)][4 * (t) + 2] : (t) < 6 ? A[2 * (b) + 1][4 * ((t) - 3) + 2] : A[2 * (b) + 1][12]), \
                    ((t) < 3 ? A[2 * (b)][4 * (t) + 3] : (t) < 6 ? A[2 * (b) + 1][4 * ((t) - 3) + 3] : A[2 * (b) + 1][13])
#define D128(off, t) ((uint64_t)(((off) + krow(t) * 128) >> 4) + ((uint64_t)((t) == 6 ? (7168 - 1024) >> 4 : 0) << 32))
#define D64(off, t) ((uint64_t)(((off) + krow(t) * 64) >> 4) + ((uint64_t)((t) == 6 ? (3584 - 512) >> 4 : 0) << 32))

#define PL(k) (((k) - 3) * PLANE)
__device__ __forceinline__ void st_word(uint32_t* p, uint32_t v) { asm volatile("st.relaxed.gpu.global.u32 [%0], %1;" ::"l"(p), "r"(v) : "memory"); }
__device__ __forceinline__ uint32_t ld_word(const uint32_t* p) { uint32_t v; asm volatile("ld.relaxed.gpu.global.u32 %0, [%1];" : "=r"(v) : "l"(p) : "memory"); return v; }
__device__ __forceinline__ void tag_slice(uint32_t* w, uint32_t tag) { w[0] = settag(w[0], tag); w[4] = settag(w[4], tag); w[8] = settag(w[8], tag); w[12] = settag(w[12], tag); }
template <int O>
__device__ __forceinline__ void send_slice(uint4* dst, int lane, const uint32_t* w) {
    st_pkt<O>(dst, w[0], w[1], w[2], w[3]);
    st_pkt<O + 32>(dst, w[4], w[5], w[6], w[7]);
    st_pkt<O + 64>(dst, w[8], w[9], w[10], w[11]);
    asm volatile("{ .reg .b64 t; mov.b64 t, {%1,%2}; st.relaxed.gpu.global.b64 [%0+%3], t; }" ::"l"((char*)dst - lane * 8), "r"(w[12]), "r"(w[13]), "n"(16 * (O + 96)) : "memory");
}
#define RW4(v, o) "+r"(v[o]), "+r"(v[(o) + 1]), "+r"(v[(o) + 2]), "+r"(v[(o) + 3])
#define RW2(v, o) "+r"(v[o]), "+r"(v[(o) + 1])
#define WR4(v, o) "=&r"(v[o]), "=&r"(v[(o) + 1]), "=&r"(v[(o) + 2]), "=&r"(v[(o) + 3])
#define LDP(a, b, c, d, addr, off) "ld.relaxed.gpu.global.b128 q, [" addr "+" off "];\n mov.b128 {" a "," b "," c "," d "}, q;\n"
#define LDH(a, b, addr, off) "ld.relaxed.gpu.global.b64 h, [" addr "+" off "];\n mov.b64 {" a "," b "}, h;\n"
#define VOTE_OK "and.b32 t, t, 1;\n setp.ne.u32 p, t, 0;\n vote.sync.any.pred p, p, 0xffffffff;\n @!p bra.uni DN;\n"
#define CHK(x, tag) "lop3.b32 t, " x ", " tag ", t, 0xBE;\n"
__device__ __forceinline__ void check_cnt(uint32_t v, const uint32_t* p, uint32_t target) {
    asm volatile("{ .reg .pred p; .reg .b32 n, t; mov.u32 n, 0; mov.u32 t, %2;\n LP:\n"
                 "sub.s32 t, t, %1;\n setp.lt.s32 p, t, 0;\n vote.sync.any.pred p, p, 0xffffffff;\n @!p bra.uni DN;\n ld.relaxed.gpu.global.u32 t, [%0];\n" SPIN_TAIL("7")
                 ::"l"(p), "r"(target), "r"(v) : "memory");
}
__device__ __forceinline__ void poll_cnt(const uint32_t* p, uint32_t target) {
    asm volatile("{ .reg .pred p; .reg .b32 n, t; mov.u32 n, 0;\n LP:\n"
                 "ld.relaxed.gpu.global.u32 t, [%0];\n sub.s32 t, t, %1;\n setp.lt.s32 p, t, 0;\n vote.sync.any.pred p, p, 0xffffffff;\n @!p bra.uni DN;\n" SPIN_TAIL("1")
                 ::"l"(p), "r"(target) : "memory");
}
template <int STR>
__device__ __forceinline__ void poll4_kv(uint32_t* v, const uint4* p, uint32_t tag) {
    asm volatile("{ .reg .pred p; .reg .b32 n, t; .reg .b128 q; mov.u32 n, 0;\n LP:\n"
                 LDP("%0", "%1", "%2", "%3", "%16", "0") LDP("%4", "%5", "%6", "%7", "%16", "%18")
                 LDP("%8", "%9", "%10", "%11", "%16", "%19") LDP("%12", "%13", "%14", "%15", "%16", "%20")
                 "xor.b32 t, %0, %17;\n" CHK("%4", "%17") CHK("%8", "%17") CHK("%12", "%17") VOTE_OK SPIN_TAIL("2")
                 : WR4(v, 0), WR4(v, 4), WR4(v, 8), WR4(v, 12)
                 : "l"(p), "r"(tag), "n"(16 * STR), "n"(32 * STR), "n"(48 * STR)
                 : "memory");
}
template <int B>
__device__ __forceinline__ void blk_load(uint32_t (&A)[8][14], const uint4* src, int lane) {
    ld_pkt<0>(&A[2 * B][0], src); ld_pkt<32>(&A[2 * B][4], src); ld_pkt<64>(&A[2 * B][8], src);
    ld_pkt<512>(&A[2 * B + 1][0], src); ld_pkt<544>(&A[2 * B + 1][4], src); ld_pkt<576>(&A[2 * B + 1][8], src);
    asm volatile("{ .reg .b64 h;\n" LDH("%0", "%1", "%4", "1536") LDH("%2", "%3", "%4", "9728") "}"
                 : "=&r"(A[2 * B][12]), "=&r"(A[2 * B][13]), "=&r"(A[2 * B + 1][12]), "=&r"(A[2 * B + 1][13])
                 : "l"((const char*)src - lane * 8) : "memory");
}
template <int B>
__device__ __forceinline__ void blk_check(uint32_t (&A)[8][14], const uint4* src, int lane, uint32_t tag) {
    asm volatile("{ .reg .pred p; .reg .b32 n, t; .reg .b128 q; .reg .b64 h, a8; mov.u32 n, 0;\n LP:\n"
                 "xor.b32 t, %0, %30;\n" CHK("%4", "%30") CHK("%8", "%30") CHK("%12", "%30") CHK("%16", "%30") CHK("%20", "%30") CHK("%24", "%30") CHK("%26", "%30") VOTE_OK
                 LDP("%0", "%1", "%2", "%3", "%28", "0") LDP("%4", "%5", "%6", "%7", "%28", "512") LDP("%8", "%9", "%10", "%11", "%28", "1024")
                 LDP("%12", "%13", "%14", "%15", "%28", "8192") LDP("%16", "%17", "%18", "%19", "%28", "8704") LDP("%20", "%21", "%22", "%23", "%28", "9216")
                 "mad.wide.s32 a8, %29, -8, %28;\n" LDH("%24", "%25", "a8", "1536") LDH("%26", "%27", "a8", "9728") SPIN_TAIL("3")
                 "\n and.b32 %0, %0, -2; and.b32 %4, %4, -2; and.b32 %8, %8, -2; and.b32 %12, %12, -2; and.b32 %16, %16, -2; and.b32 %20, %20, -2; and.b32 %24, %24, -2; and.b32 %26, %26, -2;"
                 : RW4(A[2 * B], 0), RW4(A[2 * B], 4), RW4(A[2 * B], 8), RW4(A[2 * B + 1], 0), RW4(A[2 * B + 1], 4), RW4(A[2 * B + 1], 8),
                   RW2(A[2 * B], 12), RW2(A[2 * B + 1], 12)
                 : "l"(src), "r"(lane), "r"(tag)
                 : "memory");
}
__device__ __forceinline__ void st_async4(uint32_t a, uint32_t x, uint32_t y, uint32_t z, uint32_t w, uint32_t bar) {
    asm volatile("st.async.weak.shared::cluster.mbarrier::complete_tx::bytes.v4.b32 [%0], {%1,%2,%3,%4}, [%5];" ::"r"(a), "r"(x), "r"(y), "r"(z), "r"(w), "r"(bar) : "memory");
}
__device__ __forceinline__ uint32_t mapa(uint32_t a, uint32_t cta) { uint32_t r; asm("mapa.shared::cluster.u32 %0, %1, %2;" : "=r"(r) : "r"(a), "r"(cta)); return r; }
__device__ __forceinline__ void stat_load(uint32_t* v, const uint4* p) { ld_pkt<0>(v, p); ld_pkt<512>(v + 4, p); }
__device__ __forceinline__ void stat_check(uint32_t* v, const uint4* p, uint32_t tag) {
    asm volatile("{ .reg .pred p; .reg .b32 n, t; .reg .b128 q; mov.u32 n, 0;\n LP:\n"
                 "xor.b32 t, %3, %9;\n" CHK("%7", "%9") VOTE_OK
                 LDP("%0", "%1", "%2", "%3", "%8", "0") LDP("%4", "%5", "%6", "%7", "%8", "8192") SPIN_TAIL("4")
                 : RW4(v, 0), RW4(v, 4) : "l"(p), "r"(tag) : "memory");
}
__device__ __forceinline__ uint32_t x_bits(const uint32_t* X) {
    uint32_t r;
    asm volatile("{ .reg .b32 a, b; prmt.b32 a, %1, %2, 0x0040; prmt.b32 b, %3, %4, 0x0040; prmt.b32 %0, a, b, 0x5410; }" : "=r"(r) : "r"(X[0]), "r"(X[4]), "r"(X[8]), "r"(X[12]));
    return r;
}
template <int O>
__device__ __forceinline__ void slice_load(uint32_t* v, const uint4* p, int lane) {
    ld_pkt<O>(v, p); ld_pkt<O + 32>(v + 4, p); ld_pkt<O + 64>(v + 8, p);
    asm volatile("{ .reg .b64 h;\n" LDH("%0", "%1", "%2", "%3") "}" : "=r"(v[12]), "=r"(v[13]) : "l"((const char*)p - lane * 8), "n"(16 * (O + 96)) : "memory");
}
template <int O>
__device__ __forceinline__ void slice_check(uint32_t* v, const uint4* p, int lane, uint32_t tag) {
    asm volatile("{ .reg .pred p; .reg .b32 n, t; .reg .b128 q; .reg .b64 h; mov.u32 n, 0;\n LP:\n"
                 "xor.b32 t, %0, %16;\n" CHK("%4", "%16") CHK("%8", "%16") CHK("%12", "%16") VOTE_OK
                 LDP("%0", "%1", "%2", "%3", "%14", "%17") LDP("%4", "%5", "%6", "%7", "%14", "%18") LDP("%8", "%9", "%10", "%11", "%14", "%19")
                 LDH("%12", "%13", "%15", "%20") SPIN_TAIL("5")
                 : RW4(v, 0), RW4(v, 4), RW4(v, 8), RW2(v, 12)
                 : "l"(p), "l"((const char*)p - lane * 8), "r"(tag), "n"(16 * O), "n"(16 * (O + 32)), "n"(16 * (O + 64)), "n"(16 * (O + 96))
                 : "memory");
}
__device__ __forceinline__ void x_fix(uint32_t* X, uint32_t bits) {
    X[0] = __byte_perm(X[0], bits, 0x3214); X[4] = __byte_perm(X[4], bits, 0x3215); X[8] = __byte_perm(X[8], bits, 0x3216); X[12] = __byte_perm(X[12], bits, 0x3217);
}
__device__ __forceinline__ void sts4(uint32_t a, uint32_t x, uint32_t y, uint32_t z, uint32_t w) {
    asm volatile("st.shared.v4.u32 [%0], {%1,%2,%3,%4};" ::"r"(a), "r"(x), "r"(y), "r"(z), "r"(w) : "memory");
}
__device__ __forceinline__ void lds4(uint32_t* v, uint32_t a) {
    asm volatile("ld.shared.v4.u32 {%0,%1,%2,%3}, [%4];" : "=r"(v[0]), "=r"(v[1]), "=r"(v[2]), "=r"(v[3]) : "r"(a) : "memory");
}
struct LnCoef { uint32_t hi, lo, sh; };
__device__ __forceinline__ LnCoef ln_coef(float sum, float sq) {
    sum += __shfl_xor_sync(0xffffffffu, sum, 1); sq += __shfl_xor_sync(0xffffffffu, sq, 1);
    sum += __shfl_xor_sync(0xffffffffu, sum, 2); sq += __shfl_xor_sync(0xffffffffu, sq, 2);
    const float mean = sum * (1.f / 448.f);
    const float var = fmaxf(fmaf(-mean, mean, sq * (1.f / 448.f)), 0.f);
    const float sc = rsqrtf(var + 1e-5f);
    LnCoef r;
    r.hi = pack2(sc, sc);
    const float lo = sc - bf_lo(r.hi), sh = -mean * sc;
    r.lo = pack2(lo, lo);
    r.sh = pack2(sh, sh);
    return r;
}
template <int B>
__device__ __forceinline__ void normalize(uint32_t (&A)[8][14], const LnCoef& c0, const LnCoef& c1) {
#pragma unroll
    for (int s = 2 * B; s < 2 * B + 2; s++)
#pragma unroll
        for (int i = 0; i < 14; i++) {
            const LnCoef& k = (i & 1) ? c1 : c0;
            asm("{ .reg .b32 t; fma.rn.bf16x2 t, %0, %2, %3; fma.rn.bf16x2 %0, %0, %1, t; }" : "+r"(A[s][i]) : "r"(k.hi), "r"(k.lo), "r"(k.sh));
        }
}
__device__ __forceinline__ void slice_stats(const uint32_t* w, float* st) {
    float a = 0.f, b = 0.f, p = 0.f, q = 0.f;
#pragma unroll
    for (int i = 0; i < 7; i++) {
        const float e0 = bf_lo(w[2 * i]), e1 = bf_hi(w[2 * i]), e2 = bf_lo(w[2 * i + 1]), e3 = bf_hi(w[2 * i + 1]);
        a += e0 + e1; b += e2 + e3;
        p = fmaf(e0, e0, p); p = fmaf(e1, e1, p); q = fmaf(e2, e2, q); q = fmaf(e3, e3, q);
    }
    a += __shfl_xor_sync(0xffffffffu, a, 1); p += __shfl_xor_sync(0xffffffffu, p, 1); b += __shfl_xor_sync(0xffffffffu, b, 1); q += __shfl_xor_sync(0xffffffffu, q, 1);
    a += __shfl_xor_sync(0xffffffffu, a, 2); p += __shfl_xor_sync(0xffffffffu, p, 2); b += __shfl_xor_sync(0xffffffffu, b, 2); q += __shfl_xor_sync(0xffffffffu, q, 2);
    st[0] = a; st[1] = p; st[2] = b; st[3] = q;
}
__device__ __forceinline__ void dual_softmax(const float* p, uint32_t* out) {
    constexpr float L = 1.4426950408889634f;
#pragma unroll
    for (int r = 0; r < 2; r++) {
        float mx = fmaxf(p[2 * r], p[2 * r + 1]), mn = fminf(p[2 * r], p[2 * r + 1]);
#pragma unroll
        for (int i = 1; i < 7; i++) {
            mx = fmaxf(mx, fmaxf(p[4 * i + 2 * r], p[4 * i + 2 * r + 1]));
            mn = fminf(mn, fminf(p[4 * i + 2 * r], p[4 * i + 2 * r + 1]));
        }
        mx = fmaxf(mx, __shfl_xor_sync(0xffffffffu, mx, 1));
        mn = fminf(mn, __shfl_xor_sync(0xffffffffu, mn, 1));
        const float bx = -mx * L, bn = mn * L;
        float ep[14], en[14], sp = 0.f, sn = 0.f;
#pragma unroll
        for (int i = 0; i < 14; i++) {
            const float v = p[4 * (i >> 1) + 2 * r + (i & 1)];
            ep[i] = ex2(fmaf(v, L, bx));
            en[i] = ex2(fmaf(v, -L, bn));
            sp += ep[i]; sn += en[i];
        }
        sp += __shfl_xor_sync(0xffffffffu, sp, 1);
        sn += __shfl_xor_sync(0xffffffffu, sn, 1);
        const float ip = rcp(sp), in = rcp(sn);
#pragma unroll
        for (int i = 0; i < 7; i++) {
            out[4 * i + r] = pack2(ep[2 * i] * ip, ep[2 * i + 1] * ip);
            out[4 * i + 2 + r] = pack2(en[2 * i] * in, en[2 * i + 1] * in);
        }
    }
}
__device__ __forceinline__ float geglu(float g, float u) {
    const float t = tanh_hw(g * fmaf(g * g, 0.7978845608028654f * 0.044715f, 0.7978845608028654f));
    const float gu = g * u;
    return fmaf(t, gu, gu);
}
__device__ __forceinline__ void phi_gemm(const float* t, float* p) {
    uint32_t w[14];
#pragma unroll
    for (int i = 0; i < 14; i++) w[i] = pack2(t[2 * i], t[2 * i + 1]);
    const uint64_t db = BASE128(OFF_WPHI, 16, 0);
    wg_fence();
    mma_rs56<0, 0>(p, w[0], w[1], w[2], w[3], 0, db);
    mma_rs56<0, 2>(p, w[4], w[5], w[6], w[7], 1, db);
    mma_rs56<0, 4>(p, w[8], w[9], w[10], w[11], 1, db);
    mma_rs56<0, 6>(p, w[12], w[13], 0u, 0u, 1, db);
    wg_commit();
    wg_wait<0>();
}

}

#define BAR(i) (bars + 8 * (i))
#define R_WAIT() mbar_wait(BAR(slot), ph)
#define WSUM(i)
#define R_ADJ (slot * (STAGE >> 4))
#define R_NEXT() do { eb2 = eb1; eb1 = BAR(B_EMPTY + slot); if (++slot == NST) { slot = 0; ph ^= 1; } } while (0)
#define R_RELEASE(k) do { if (lane == 0) mbar_arrive((k) == 1 ? eb1 : eb2); } while (0)
#define PUSH_BEGIN() do { mbar_wait(BAR(B_ACK + wgi), ackph); ackph ^= 1; } while (0)
#define PUSH_ACK() do { __syncwarp(); if (lane == 0) asm volatile("mbarrier.arrive.shared::cluster.b64 _, [%0];" ::"r"(mapa(BAR(B_ACK + wgi), hr ^ 1)) : "memory"); } while (0)

__global__ void __cluster_dims__(2, 1, 1) __launch_bounds__(384, 1)
fused_kernel(Scratch* const sc, const __nv_bfloat16* __restrict__ x_in, const __nv_bfloat16* __restrict__ w_phi, const int trips,
             const __nv_bfloat16* __restrict__ wg, const __nv_bfloat16* __restrict__ wu, const __nv_bfloat16* __restrict__ wd,
             const __grid_constant__ Maps maps) {
    extern __shared__ __align__(1024) unsigned char smem_raw[];
    const uint32_t sb = s2u(smem_raw);
    const uint32_t bars = sb + OFF_BAR;
    const int wgi = __shfl_sync(0xffffffffu, threadIdx.x >> 7, 0);
    const int hr = blockIdx.x & 1, ck = blockIdx.x >> 1;
    const int gp = (ck - 4) & 7, q7 = ((ck - 36) * 37) >> 8;
    const int pr = ck < 4 ? ck : (ck < 36 ? (ck - 4) >> 3 : q7);
    const int tile = ck < 4 ? 0 : (ck < 36 ? (gp ? 2 * gp : 1) : 2 * (ck - 36 - 7 * q7) + 3);
    const int sl = 2 * pr + hr;
    STAMP(0);
    GSTAMP(60);
    if (threadIdx.x == 256) {
#pragma unroll
        for (int i = 0; i < NST; i++) mbar_init(BAR(i), 1);
        asm volatile("fence.mbarrier_init.release.cluster;" ::: "memory");
    }
    if (threadIdx.x == 288) {
        if ((sb & 0x3FFFF) != SB0) asm volatile("trap;");
#pragma unroll
        for (int i = NST; i < B_COUNT; i++) mbar_init(BAR(i), i >= B_ACK ? 4 : (i < B_RECV ? 8 : 1));
        asm volatile("fence.mbarrier_init.release.cluster;" ::: "memory");
    }
    __syncwarp();
    asm volatile("barrier.cluster.arrive.relaxed.aligned;" ::: "memory");

    if (wgi == 2) {
        asm volatile("setmaxnreg.dec.sync.aligned.u32 40;");
        const int t128 = fresh_tid() & 127, w = __shfl_sync(0xffffffffu, t128 >> 5, 0), lane = t128 & 31;
        uint32_t e0[2] = {0, 0}, e1[2] = {0, 0}, cw_target = 0;
        if (w == 0) {
#pragma unroll 1
            for (int n = 0; n < NST; n++) {
                const uint32_t dst = sb + n * STAGE, fb = BAR(n);
                asm volatile(ELECT "mbarrier.arrive.expect_tx.shared::cta.b64 _, [%0], %1; }" ::"r"(fb), "r"(n < 2 ? 2 * STAGE : STAGE) : "memory");
                if (n < 2) {
                    tma3x(sb + OFF_H + n * STAGE, &maps.x, tile * 128 + n * 64, fb);
                    tma3x(dst, &maps.x, tile * 128 + n * 64 + 32, fb);
                } else {
                    if (n == 3) mbar_wait(BAR(1), 0);
                    const int ra = 112 * (n - 2);
                    tma2d(dst, &maps.qkv, 448 + 56 * sl, ra, fb);
                    tma2d(dst + HALF, &maps.qkv, 896 + 56 * sl, ra, fb);
                }
            }
            asm volatile("barrier.cluster.wait.aligned;" ::: "memory");
            cw_target = (ld_word(g_cw + sl * 32) & ~15u) + 16;
#pragma unroll 1
            for (int k = 0; k < 2; k++) {
                const int n = t128 + 32 * k;
                int m = n - 2 - (n > PACK);
                const bool packed = m >= 30 ? (m < 38 || m >= 52) : m >= 22;
                if (m >= 30) m -= 30;
                if (n == PACK) m = tile < 8 ? tile : tile + 14;
                const int rot = n < 8 ? 0 : pr;
                const int ra = 112 * kblk(rot, m & 3), rb = 112 * kblk(rot, 2 * m & 3), rc = 112 * kblk(rot, (2 * m + 1) & 3);
                int kind = 0, m0, m1, c0, c1, r0, r1;
                if (m < 4) { m0 = m1 = 1; c0 = 448 + 56 * sl; c1 = c0 + 448; r0 = r1 = ra; }
                else if (m < 8) { m0 = m1 = m < 6 ? 1 : 2; c0 = c1 = 56 * sl; r0 = rb; r1 = rc; }
                else if (m < 20) { m0 = 3; m1 = 4; c0 = c1 = 224 * sl + 32 * hr + 64 * ((m - 8) >> 2); r0 = r1 = ra; }
                else if (m < 22) { kind = 2; m0 = 5; m1 = 6; c0 = c1 = 224 * sl + (hr ? 0 : 192); r0 = rb; r1 = rc; }
                else { m0 = m1 = 7; c0 = c1 = 56 * (2 * ((pr + (m >> 1) - 10) & 3) + hr); r0 = 224 * (sl ^ (m & 1)); r1 = r0 + 112; }
                if (packed) { kind = 1; r0 = sl * 16 + (m < 8 ? m : m - 14); r1 = 0; }
                e0[0] = e0[1]; e1[0] = e1[1];
                e0[1] = kind | (m0 << 2) | (m1 << 6) | (c0 << 10) | (c1 << 21);
                e1[1] = r0 | (r1 << 16);
            }
        } else {
            const int j = t128 - 32;
            asm volatile("barrier.cluster.wait.aligned;" ::: "memory");
            uint2 wv[7];
            const int k = j < 56 ? j : 55, hh = k >= 28;
#pragma unroll
            for (int i = 0; i < 7; i++) wv[i] = __ldg(reinterpret_cast<const uint2*>(w_phi + (sl * 56 + k) * 28) + i);
#pragma unroll 1
            for (int i = j; i < 7168 / 16; i += 96) sts4(sb + OFF_WPHI + i * 16, 0, 0, 0, 0);
            bar_sync(5, 96);
            if (j < 56) {
                uint32_t a4[4];
#pragma unroll
                for (int q = 0; q < 4; q++) a4[q] = sb + OFF_WPHI + (4 * hh + q) * 128 + ((((k >> 3) ^ (4 * hh + q)) & 7) << 4) + (k & 7) * 2;
                FOR14(const uint32_t v = (t & 1) ? wv[t >> 1].y : wv[t >> 1].x;
                      asm volatile("{ .reg .b16 l, h; mov.b32 {l, h}, %2; st.shared.u16 [%0+%3], l; st.shared.u16 [%1+%3], h; }"
                                   ::"r"(a4[t >= 7 ? 2 : 0]), "r"(a4[t >= 7 ? 3 : 1]), "r"(v), "n"((t % 7) * 1024) : "memory"));
            }
            __syncwarp();
            fence_async();
            bar_arrive(1, 224);
            bar_arrive(9, 224);
            if (w == 1) {
                mbar_wait(BAR(2), 0);
                mbar_wait(BAR(2), 1);
                const int b = blockIdx.x;
                asm volatile(ELECT "cp.async.bulk.prefetch.L2.global [%0], %1; }" ::"l"(wg + b * 6272), "r"(12544) : "memory");
                asm volatile(ELECT "cp.async.bulk.prefetch.L2.global [%0], %1; }" ::"l"(wu + b * 6272), "r"(12544) : "memory");
                asm volatile(ELECT "cp.async.bulk.prefetch.L2.global [%0], %1; }" ::"l"(wd + b * 6272), "r"(12544) : "memory");
            }
        }
        uint32_t kseq = ld_word(g_c1 + (sl * 8 * 16 + tile) * 32);
        int slot = 0, ph = 0, n = NST;
#pragma unroll 1
        for (int layer = 0; layer < 3; layer++) {
            if (w == 0) {
                const int nend = layer == 0 ? 11 : (layer == 1 ? 42 : 63);
#pragma unroll 1
                for (; n < nend; n++) {
                const uint32_t w0 = __shfl_sync(0xffffffffu, n < 32 ? e0[0] : e0[1], n & 31), w1 = __shfl_sync(0xffffffffu, n < 32 ? e1[0] : e1[1], n & 31);
                const uint32_t dst = sb + slot * STAGE, fb = BAR(n == PACK ? B_PACK : slot);
                const CUtensorMap* m0 = &maps.x + ((w0 >> 2) & 15);
                const CUtensorMap* m1 = &maps.x + ((w0 >> 6) & 15);
                const int c0 = (w0 >> 10) & 2047, c1 = w0 >> 21, r0 = w1 & 0xffff, r1 = w1 >> 16;
                if (n == 25) {
                    int it = 0;
                    uint32_t v;
                    do { asm volatile("ld.acquire.gpu.global.u32 %0, [%1];" : "=r"(v) : "l"(g_cw + sl * 32) : "memory"); } while ((int)(v - cw_target) < 0 && ++it < 0x400000);
                    asm volatile("fence.proxy.async.global;" ::: "memory");
                    __syncwarp();
                }
                mbar_wait(BAR(B_EMPTY + slot), ph);
                __syncwarp();
                asm volatile(ELECT "mbarrier.arrive.expect_tx.shared::cta.b64 _, [%0], %1; }" ::"r"(fb), "r"(STAGE) : "memory");
                if ((w0 & 3) == 0) {
                    tma2d(dst, m0, c0, r0, fb);
                    tma2d(dst + HALF, m1, c1, r1, fb);
                } else if (w0 & 1) {
                    asm volatile(ELECT "cp.async.bulk.shared::cluster.global.mbarrier::complete_tx::bytes [%0], [%1], %2, [%3]; }"
                                 ::"r"(dst), "l"(reinterpret_cast<const char*>(g_wp) + (size_t)r0 * STAGE), "r"(STAGE), "r"(fb) : "memory");
                } else {
                    tma2d(dst, m0, c0, r0, fb); tma2d(dst + 7168, m0, c0, r1, fb);
                    tma2d(dst + HALF, m1, c0, r0, fb); tma2d(dst + HALF + 7168, m1, c0, r1, fb);
                }
                if (n == PACK) asm volatile(ELECT "mbarrier.arrive.shared::cta.b64 _, [%0]; }" ::"r"(BAR(slot)) : "memory");
                if (++slot == NST) { slot = 0; ph ^= 1; }
                }
            } else if (w == 1 && layer == 1) {
                constexpr int ps = PACK % NST;
                mbar_wait(BAR(B_PACK), 0);
                asm volatile("{ .reg .pred e; elect.sync _|e, 0xffffffff;\n"
                             "@e cp.async.bulk.global.shared::cta.bulk_group [%0], [%1], %2;\n"
                             "@e cp.async.bulk.commit_group;\n"
                             "@e cp.async.bulk.wait_group.read 0;\n"
                             "@e mbarrier.arrive.shared::cta.b64 _, [%3], 8;\n"
                             "@e cp.async.bulk.wait_group 0;\n"
                             "@e fence.proxy.async.global;\n"
                             "@e red.release.gpu.global.add.u32 [%4], 1; }"
                             ::"l"(reinterpret_cast<char*>(g_wp) + (size_t)(sl * 16 + tile) * STAGE), "r"(sb + ps * STAGE), "r"(STAGE), "r"(BAR(B_EMPTY + ps)), "l"(g_cw + sl * 32) : "memory");
                __syncwarp();
            }
            if (layer < 2) {
            const uint32_t tag = layer ^ 1;
            kseq++;
            bar_sync(7, 384);
            ASTAMP(0);
            if (tile < 15) {
                const int sq = lane >> 3, pk = 8 * w + (lane & (tile == 14 ? 3 : 7));
                uint32_t v[16];
                if (layer == 0) poll_cnt(g_c1 + ((sl * 8 + (w >> 1) * 4 + (tile >> 2)) * 16 + (lane & 15)) * 32, kseq);
                ASTAMP(1);
                poll4_kv<32>(v, g_kv1 + ((sl * 16 + tile) * 16 + 4 * sq) * 32 + pk, tag);
#pragma unroll
                for (int k = 0; k < 4; k++) {
                    float lo = (bf_lo(v[k]) + bf_lo(v[4 + k])) + (bf_lo(v[8 + k]) + bf_lo(v[12 + k]));
                    float hi = (bf_hi(v[k]) + bf_hi(v[4 + k])) + (bf_hi(v[8 + k]) + bf_hi(v[12 + k]));
                    lo += __shfl_xor_sync(0xffffffffu, lo, 8); hi += __shfl_xor_sync(0xffffffffu, hi, 8);
                    lo += __shfl_xor_sync(0xffffffffu, lo, 16); hi += __shfl_xor_sync(0xffffffffu, hi, 16);
                    v[k] = pack2(lo, hi);
                }
                if (sq == 0) st_pkt<0>(g_kv2 + sl * 512 + 32 * tile + pk, settag(v[0], tag), v[1], v[2], v[3]);
            }
            ASTAMP(2);
            {
                const int item = t128 < 112 ? t128 : 112 + (t128 & 3), d = item >> 1;
                const int cc = t128 < 112 ? 2 * (d >= 28) + (item & 1) : item - 112;
                const int r = t128 < 112 ? d : 56 + (cc >> 1) + 2 * ((t128 - 112) >> 2);
                uint32_t ra = sb + OFF_KVB + r * 128 + 4 * cc, rx = (r & 7) << 4;
                asm volatile("" : "+r"(ra), "+r"(rx));
                FOR14(asm volatile("st.shared.u32 [%0+%2], %1;" ::"r"((ra ^ 8) + (((t & 7) << 4) ^ rx)), "r"(0), "n"((t >> 3) * 8192) : "memory"));
                uint32_t v[16];
                asm volatile("" : "+r"(ra), "+r"(rx));
                poll4_kv<8>(v, g_kv2 + sl * 512 + (item >> 3) * 32 + (item & 7), tag);
                FOR14(asm volatile("st.shared.u32 [%0+%2], %1;" ::"r"(ra + (((t & 7) << 4) ^ rx)), "r"(v[t < 7 ? t : t + 1]), "n"((t >> 3) * 8192) : "memory"));
                fence_async();
            }
            bar_arrive(3, 384);
            ASTAMP(3);
            }
        }
    } else {
        asm volatile("setmaxnreg.inc.sync.aligned.u32 232;");
        const int tid = fresh_tid(), lane = tid & 31, t128 = tid & 127, g = lane >> 2, c = lane & 3;
        const int wu = __shfl_sync(0xffffffffu, tid >> 5, 0), w = wu & 3;
        uint4* const xp0 = g_ex + 3 * PLANE + ((tile * 2 + wgi) * 8) * 512 + w * 128 + lane;
        const uint32_t hbuf = sb + OFF_H + wgi * STAGE;
        uint32_t slot = 0, ph = 0, eb1 = 0, eb2 = 0, ackph = 0, rcvph = 0, gatph = 0, swp = 0;
        uint32_t ppid = 6;
#define cx(s) (reinterpret_cast<uint32_t*>(again(xp0) - lane + PL(1) + 112 + (s) * 512))
#define stp (again(xp0) - lane + g + PL(0) + 112)
        uint32_t seq = ld_word(cx(sl));
        uint32_t kseq = ld_word(g_c1 + ((sl * 8 + (tid >> 5)) * 16 + tile) * 32);
        uint32_t stag = ld_word(reinterpret_cast<const uint32_t*>(stp + sl * 512) + 3) & 1;
        asm volatile("barrier.cluster.wait.aligned;" ::: "memory");
        STAMP(1);
        uint32_t X[14];
        const uint32_t x0row = (w < 2 ? hbuf : sb + wgi * STAGE) + ((w & 1) * 16 + (lane & 15)) * 128;
        mbar_wait(BAR(wgi), 0);
        STAMP(51);
#pragma unroll
        for (int j = 0; j < 4; j++) {
            const int G = 7 * sl + min(2 * j + (lane >> 4), 6);
            uint32_t q2, q3;
            asm volatile("ldmatrix.sync.aligned.m8n8.x4.shared.b16 {%0,%1,%2,%3}, [%4];" : "=r"(X[4 * j]), "=r"(X[4 * j + 1]), "=r"(q2), "=r"(q3)
                         : "r"(x0row + (G >> 3) * 4096 + (((G ^ lane) & 7) << 4)) : "memory");
            if (j < 3) { X[(4 * j + 2) % 14] = q2; X[(4 * j + 3) % 14] = q3; }
        }
#define PUSH_SLICE(W)                                                                          \
    {                                                                                          \
        if (t128 == 0) mbar_expect_tx(BAR(B_RECV + wgi), 7168);                                \
        PUSH_BEGIN();                                                                          \
        const uint32_t ra = mapa(hbuf + 24576 + t128 * 16, hr ^ 1), rb = mapa(sb + OFF_XR + wgi * 3072, hr ^ 1), rbar = mapa(BAR(B_RECV + wgi), hr ^ 1); \
        st_async4(ra, W[0], W[1], W[2], W[3], rbar);                                           \
        st_async4(ra + 2048, W[4], W[5], W[6], W[7], rbar);                                    \
        st_async4(rb + t128 * 16, W[8], W[9], W[10], W[11], rbar);                             \
        asm volatile("st.async.weak.shared::cluster.mbarrier::complete_tx::bytes.v2.b32 [%0], {%1,%2}, [%3];" ::"r"(rb + 2048 + t128 * 8), "r"(W[12]), "r"(W[13]), "r"(rbar) : "memory"); \
    }
#define PULL_SLICE(W)                                                                          \
    {                                                                                          \
        uint32_t t0, t1;                                                                       \
        mbar_wait(BAR(B_RECV + wgi), rcvph);                                                   \
        rcvph ^= 1;                                                                            \
        lds4(&A[1][0], hbuf + 24576 + t128 * 16);                                              \
        lds4(&A[1][4], hbuf + 26624 + t128 * 16);                                              \
        lds4(&A[1][8], sb + OFF_XR + wgi * 3072 + t128 * 16);                                  \
        asm volatile("ld.shared.v2.u32 {%0,%1}, [%2];" : "=r"(t0), "=r"(t1) : "r"(sb + OFF_XR + wgi * 3072 + 2048 + t128 * 8) : "memory"); \
        _Pragma("unroll") for (int i = 0; i < 12; i++) A[0][i] = (i & 3) ? W[i] : W[i] & ~1u;  \
        A[1][0] &= ~1u; A[1][4] &= ~1u; A[1][8] &= ~1u;                                        \
        A[0][12] = (hr ? t0 : W[12]) & ~1u; A[0][13] = hr ? t1 : W[13];                        \
        A[1][12] = (hr ? W[12] : t0) & ~1u; A[1][13] = hr ? W[13] : t1;                        \
        asm volatile("" : RW4(A[0], 0), RW4(A[0], 4), RW4(A[0], 8), RW2(A[0], 12), RW4(A[1], 0), RW4(A[1], 4), RW4(A[1], 8), RW2(A[1], 12)); \
        swp = hr * 448;                                                                        \
    }
#define SWB(b, t, db, sh) ((b) == 0 && (t) < 6 ? ((t) < 3 ? db##p : db##m) : db)
#define DECL_DB(b, MK, lbo, sh) const uint64_t db = MK(0, lbo, R_ADJ), dbp = (b) == 0 ? MK(0, lbo, R_ADJ + (swp >> (sh))) : db, dbm = (b) == 0 ? MK(0, lbo, R_ADJ - (swp >> (sh))) : db;
#define EARLY 1
#define EARLYK 1
#define PPB 2
#define PP_WAIT() if (wgi == 1) { bar_sync(ppid, 256); ppid ^= 14; }
#define PP_GO() if (wgi == 0) { bar_arrive(ppid, 256); ppid ^= 14; }
#define GAT_ISSUE(base)                                                                        \
    {                                                                                          \
        const char* gs = reinterpret_cast<const char*>(g_ex + 3 * PLANE + (base) + (tile * 16 + wgi * 8 + 2 * kblk(pr, GB) + hr) * 512 + w * 128); \
        const uint32_t gd = hbuf + w * 3584 + hr * 1792, gb = BAR(B_GAT + wu);                 \
        asm volatile("{ .reg .pred e; elect.sync _|e, 0xffffffff;\n"                           \
                     "@e mbarrier.arrive.expect_tx.shared::cta.b64 _, [%2], 3584;\n"           \
                     "@e cp.async.bulk.shared::cluster.global.mbarrier::complete_tx::bytes.multicast::cluster [%0], [%1], 1792, [%2], %3; }" \
                     ::"r"(gd), "l"(gs), "r"(gb), "h"((uint16_t)3) : "memory");                \
        __syncwarp();                                                                          \
    }
#define GAT_FETCH()                                                                            \
    {                                                                                          \
        mbar_wait(BAR(B_GAT + wu), gatph);                                             \
        gatph ^= 1;                                                                            \
        const uint32_t ga = hbuf + w * 3584 + lane * 16;                                       \
        _Pragma("unroll") for (int s2 = 0; s2 < 2; s2++) {                                     \
            lds4(&A[2 * GB + s2][0], ga + s2 * 1792); lds4(&A[2 * GB + s2][4], ga + s2 * 1792 + 512); lds4(&A[2 * GB + s2][8], ga + s2 * 1792 + 1024); \
            asm volatile("ld.shared.v2.u32 {%0,%1}, [%2];" : "=r"(A[2 * GB + s2][12]), "=r"(A[2 * GB + s2][13]) : "r"(ga - lane * 8 + s2 * 1792 + 1536) : "memory"); \
        }                                                                                      \
    }
#define PT 3
#define PREP(b, t, remote)                                                                     \
    if constexpr ((b) < 3 && (t) == PT) {                                                      \
        wg_commit();                                                                           \
        STAMP(80 + 8 * (step & 1) + 2 * (b));                                                  \
        if constexpr (GB == 1 && (b) == 0) { if (remote) GAT_FETCH() }                         \
        if (remote) blk_check<((b) + 1) & 3>(A, BLK(xsrc, (b) + 1), lane, xtag);               \
        STAMP(81 + 8 * (step & 1) + 2 * (b));                                                  \
        if constexpr ((b) == 0) { if (remote) blk_load<3>(A, BLK(xsrc, 3), lane); }            \
        normalize<((b) + 1) & 3>(A, k0, k1);                                                   \
        asm volatile("" : RW4(A[(2 * (b) + 2) & 7], 0), RW4(A[(2 * (b) + 2) & 7], 4), RW4(A[(2 * (b) + 2) & 7], 8), RW2(A[(2 * (b) + 2) & 7], 12), \
                          RW4(A[(2 * (b) + 3) & 7], 0), RW4(A[(2 * (b) + 3) & 7], 4), RW4(A[(2 * (b) + 3) & 7], 8), RW2(A[(2 * (b) + 3) & 7], 12)); \
        wg_fence();                                                                            \
    }                                                                                          \
    if constexpr ((b) == 3 && ((t) == 0 || (t) == 6)) { STAMP(86 + 8 * (step & 1) + (t) / 6); }
#define BLK(base, b) ((base) + kblk(pr, b) * 1024)

#pragma unroll 1
        for (int step = 0; step < 4; step++) {
            const uint32_t tag = (step >> 1) ^ 1;
            const int so = (step >> 1) * 24 + (step & 1) * 12;
            (void)so;
            uint32_t A[8][14];
            uint4* const xsrc = xp0 + ((step & 1) ? PL(2) : PL(0));
            const uint32_t xtag = (step & 1) ? tag : ((seq >> 3) & 1) ^ 1;
            uint32_t xbits;
            {
                float st[4];
                slice_stats(X, st);
                stag ^= 1;
                xbits = x_bits(X);
                tag_slice(X, xtag);
                if (step) send_slice<0>(xsrc + sl * 512, lane, X);
                if (c == 0) st_pkt<0>(stp + sl * 512, __float_as_uint(st[0]), __float_as_uint(st[1]), __float_as_uint(st[2]), settag(__float_as_uint(st[3]), stag));
            }
            STAMP(2 + so);
            uint32_t sv[8];
            if (step == 0) {
                const int rr = lane & 7, hi = lane >> 4;
                const uint32_t rowa = (w < 2 ? hbuf : sb + wgi * STAGE) + ((w & 1) * 16 + (lane & 15)) * 128;
                uint32_t xr[8];
#pragma unroll
                for (int j = 0; j < 8; j++) xr[j] = rowa + ((((j + hi) ^ rr) & 7) << 4) + (j == 7 ? hi * 4096 : 0);
#define X0_BLOCK(b)                                                                            \
    FOR7(constexpr int G = 14 * (b) + (t < 3 ? 2 * t : (t < 6 ? 2 * t + 1 : 6));               \
         uint32_t q0, q1, q2, q3;                                                              \
         const uint32_t ad = t < 6 ? xr[G & 7] : rowa + ((G + 7 * hi) >> 3) * 4096 + ((((G + 7 * hi) ^ rr) & 7) << 4); \
         asm volatile("ldmatrix.sync.aligned.m8n8.x4.shared.b16 {%0,%1,%2,%3}, [%4+%5];" : "=r"(q0), "=r"(q1), "=r"(q2), "=r"(q3) \
                      : "r"(ad), "n"(t < 6 ? (G >> 3) * 4096 : 0) : "memory");                 \
         if (t < 3) { A[2 * (b)][4 * t] = q0; A[2 * (b)][4 * t + 1] = q1; A[2 * (b)][4 * t + 2] = q2; A[2 * (b)][4 * t + 3] = q3; } \
         else if (t < 6) { A[2 * (b) + 1][(4 * t - 12) & 15] = q0; A[2 * (b) + 1][((4 * t - 12) & 15) + 1] = q1; A[2 * (b) + 1][((4 * t - 12) & 15) + 2] = q2; A[2 * (b) + 1][((4 * t - 12) & 15) + 3] = q3; } \
         else { A[2 * (b)][12] = q0; A[2 * (b)][13] = q1; A[2 * (b) + 1][12] = q2; A[2 * (b) + 1][13] = q3; });
                X0_BLOCK(0) X0_BLOCK(1) X0_BLOCK(2) X0_BLOCK(3)
                mbar_wait(BAR(wgi ^ 1), 0);
                R_NEXT();
                R_NEXT();
                stat_load(sv, stp + c * 1024);
                stat_check(sv, stp + c * 1024, stag);
                STAMP(52 + step);
            } else {
                PUSH_SLICE(X)
                stat_load(sv, stp + c * 1024);
                kill<14>(A[2]); kill<14>(A[3]); kill<14>(A[4]); kill<14>(A[5]); kill<14>(A[6]); kill<14>(A[7]);
                PULL_SLICE(X)
                stat_check(sv, stp + c * 1024, stag);
                STAMP(52 + step);
                if (GB == 1) GAT_ISSUE((step & 1) ? PL(2) : PL(0))
                else { blk_load<1>(A, BLK(xsrc, 1), lane); if (GE) GAT_ISSUE((step & 1) ? PL(2) : PL(0)) }
            }
            LnCoef k0, k1;
            {
                k0 = ln_coef(__uint_as_float(sv[0]) + __uint_as_float(sv[4]), __uint_as_float(sv[1]) + __uint_as_float(sv[5]));
                k1 = ln_coef(__uint_as_float(sv[2]) + __uint_as_float(sv[6]), __uint_as_float(sv[3] & ~1u) + __uint_as_float(sv[7] & ~1u));
            }
            if (step) {
                if (GB == 2) { if (!GE) GAT_ISSUE((step & 1) ? PL(2) : PL(0)) }
                else blk_load<2>(A, BLK(xsrc, 2), lane);
            }
            STAMP(3 + so);
            GSTAMP(76 + step);

            if ((step & 1) == 0) {
                float tq[28];
                {
                    float av[28];
#define KV_BLOCK(b)                                                                           \
    if (GB == 2 && (b) == 1 && step) GAT_FETCH()                                                         \
    if ((b) == 2) PUSH_ACK();                                                                 \
    if (QE && (b) == 1) R_RELEASE(2);                                                         \
    if (QE && (b) == 2) { wg_wait<2>(); R_RELEASE(2); }                                       \
    R_WAIT();                                                                                 \
    if ((b) == PPK) { PP_WAIT() }                                                             \
    { DECL_DB(b, BASE128, 16, 0)                                                              \
    wg_fence();                                                                               \
    FOR7(mma_rs56<1, D128(0, t)>(tq, AQ(A, b, t), (b) + t > 0, SWB(b, t, db, 0));             \
         mma_rs56<1, D128(HALF, t)>(av, AQ(A, b, t), (b) + t > 0, SWB(b, t, db, 0));          \
         PREP(b, t, step)); }                                                                 \
    wg_commit();                                                                              \
    if ((b) == 3 && PPK < 4) { PP_GO() }                                                      \
    R_NEXT();
                    if (EARLYK == 0 || step == 0) R_RELEASE(2);
                    normalize<0>(A, k0, k1);
                    KV_BLOCK(0) KV_BLOCK(1) KV_BLOCK(2) KV_BLOCK(3)
                    wg_wait<0>();
                    if (lane < (QE ? 3 : NST)) mbar_arrive(BAR(B_EMPTY + (slot + NST - 1 - lane) % NST));
                    STAMP(4 + so);
                    WSUM(80 + 7 * (step >> 1));
                    const int m = lane >> 3, rr = lane & 7;
                    const uint32_t rowa = hbuf + 16384 + (w * 16 + rr + 8 * (m & 1)) * 128;
                    const uint32_t one = c == 0 ? 0x00003f80u : 0u;
                    if (step == 0) { bar_sync(wgi ? 9 : 1, 224); }
#pragma unroll
                    for (int j = 0; j < 4; j++) {
                        const uint32_t a = rowa + (((2 * j + (m >> 1)) ^ rr) << 4);
                        if (j < 3) stsm4(a, pack2(av[8 * j], av[8 * j + 1]), pack2(av[8 * j + 2], av[8 * j + 3]), pack2(av[8 * j + 4], av[8 * j + 5]), pack2(av[8 * j + 6], av[8 * j + 7]));
                        else stsm4(a, pack2(av[24], av[25]), pack2(av[26], av[27]), one, one);
                    }
                }
                uint32_t PH[28];
                int it = 1;
#pragma unroll 1
                do {
                    float pp[28];
                    phi_gemm(tq, pp);
                    dual_softmax(pp, PH);
                    if (((trips >> (it + 1)) & 1) == 0) continue;
                    {
                        const int m = lane >> 3, rr = lane & 7;
                        const uint32_t rowa = hbuf + (w * 16 + rr + 8 * (m & 1)) * 128;
#pragma unroll
                        for (int j = 0; j < 7; j++) {
                            const int cg = 2 * j + (m >> 1), hi = cg >= 7;
                            stsm4(rowa + hi * 8192 + (((cg - 7 * hi) ^ rr) << 4), PH[4 * j], PH[4 * j + 1], PH[4 * j + 2], PH[4 * j + 3]);
                        }
                    }
                    fence_async();
                    STAMP(5 + so);
#define Q_STAGE(b0)                                                                           \
    R_WAIT();                                                                                 \
    { DECL_DB(b0, BASE128, 16, 0)                                                             \
    wg_fence();                                                                               \
    FOR7(mma_rs56<1, D128(0, t)>(tq, AQ(A, b0, t), (b0) + t > 0, SWB(b0, t, db, 0)));         \
    FOR7(mma_rs56<1, D128(HALF, t)>(tq, AQ(A, (b0) + 1, t), 1, db)); }                        \
    wg_commit();                                                                              \
    R_NEXT();
                    if (QE && wgi == 0) { kill<28>(tq); Q_STAGE(0) Q_STAGE(2) wg_wait<1>(); R_RELEASE(2); wg_wait<0>(); R_RELEASE(1); }
                    bar_sync(2, 256);
                    float kv[28];
                    const uint64_t da = BASE128(OFF_H + 16384, 16, 0), dbk = BASE128(OFF_H, 16, wgi * 512);
                    wg_fence();
                    FOR8(constexpr uint64_t o = ((t >> 2) * STAGE + (t & 3) * 2048) >> 4; mma_ss56_tt<o, o>(kv, t > 0, da, dbk));
                    wg_commit();
                    wg_wait<0>();
#pragma unroll
                    for (int hf = 0; hf < 2; hf++) {
                        const int d = 16 * w + g + 8 * hf;
                        if ((d < 56 && (d >= 28) == (c >= 2)) || d == 56) {
                            const int item = d < 56 ? 2 * d + (c & 1) : 112 + c;
                            uint4* dst = g_kv1 + ((sl * 16 + (item >> 3)) * 16 + tile) * 32 + wgi * 16 + (item & 7);
#define KVW(i) pack2(kv[4 * (i) + 2 * hf], kv[4 * (i) + 2 * hf + 1])
                            st_pkt<0>(dst, settag(KVW(0), tag), KVW(1), KVW(2), KVW(3));
                            st_pkt<8>(dst, settag(KVW(4), tag), KVW(5), KVW(6), 0u);
                        }
                    }
                    __syncwarp();
                    kseq++;
                    if (lane == 0) st_word(g_c1 + ((sl * 8 + (tid >> 5)) * 16 + tile) * 32, kseq);
                    bar_arrive(7, 384);
                    STAMP(6 + so);
                    if (!QE || wgi == 1) { kill<28>(tq); Q_STAGE(0) Q_STAGE(2) wg_wait<1>(); R_RELEASE(2); wg_wait<0>(); R_RELEASE(1); }
                    STAMP(7 + so);
                    kill<28>(PH);
                } while (((trips >> (++it)) & 1));
                STAMP(8 + so);
                if (step) {
                    slice_load<PL(0)>(X, xp0 + sl * 512, lane);
                } else {
                    const uint32_t* xp = reinterpret_cast<const uint32_t*>(x_in + (size_t)(tile * 128 + wu * 16 + g) * 448 + 56 * sl + 2 * c);
#pragma unroll
                    for (int i = 0; i < 7; i++) { X[2 * i] = __ldg(xp + 4 * i); X[2 * i + 1] = __ldg(xp + 4 * i + 8 * 224); }
                }
                bar_sync(3, 384);
                STAMP(9 + so);
                const uint4* const osrc = xp0 + PL(1);
                {
                    float nm[32];
                    const uint64_t db = BASE128(OFF_KVB, 16, 0);
                    wg_fence();
                    FOR7(mma_rs64<0, ((t >> 2) * 8192 + (t & 3) * 32) / 16>(nm, PH[4 * t], PH[4 * t + 1], PH[4 * t + 2], PH[4 * t + 3], t > 0, db));
                    wg_commit();
                    wg_wait<0>();
                    const float i00 = rcp(nm[28] + 1e-6f), i01 = rcp(nm[29] + 1e-6f), i10 = rcp(nm[30] + 1e-6f), i11 = rcp(nm[31] + 1e-6f);
                    const float m0 = c >= 2 ? i01 : i00, m1 = c >= 2 ? i11 : i10;
                    uint32_t O[14];
#pragma unroll
                    for (int i = 0; i < 7; i++) {
                        const float f0 = i < 3 ? i00 : (i > 3 ? i01 : m0), f1 = i < 3 ? i10 : (i > 3 ? i11 : m1);
                        O[2 * i] = pack2(nm[4 * i] * f0, nm[4 * i + 1] * f0);
                        O[2 * i + 1] = pack2(nm[4 * i + 2] * f1, nm[4 * i + 3] * f1);
                    }
                    if (OST) { PP_WAIT() }
                    tag_slice(O, tag);
                    send_slice<PL(1)>(xp0 + sl * 512, lane, O);
                    seq++;
                    if (lane == 0) st_word(cx(sl), seq);
                    STAMP(10 + so);
                    PUSH_SLICE(O)
                    if (OST == 1) { PP_GO() }
                    PULL_SLICE(O)
                }
                float ao[28];
#define WO_BLOCK(b)                                                                           \
    if ((b) > 0) blk_check<b>(A, BLK(osrc, b), lane, tag);                                    \
    if (((b) & 1) == 0) R_WAIT();                                                             \
    { DECL_DB(b, BASE128, 16, 0)                                                              \
    wg_fence();                                                                               \
    FOR7(mma_rs56<1, D128(((b) & 1) * HALF, t)>(ao, AQ(A, b, t), (b) + t > 0, SWB(b, t, db, 0))); } \
    wg_commit();                                                                              \
    if ((b) & 1) R_NEXT();
                {
                    const uint32_t cv = ld_word(cx(lane & 7));
                    WO_BLOCK(0)
                    check_cnt(cv, cx(lane & 7), seq);
                }
                if (OST == 2) { PP_GO() }
                STAMP(56 + (step >> 1));
                GAT_ISSUE(PL(1))
                blk_load<3 - GB>(A, BLK(osrc, 3 - GB), lane);
                STAMP(11 + so);
                blk_load<3>(A, BLK(osrc, 3), lane);
                if (GB == 1) GAT_FETCH()
                WO_BLOCK(1)
                if (GB == 2) GAT_FETCH()
                WO_BLOCK(2)
                PUSH_ACK();
                WO_BLOCK(3)
                wg_wait<0>();
                if (EARLY >= 1) R_RELEASE(2);
                if (EARLY >= 2) R_RELEASE(1);
                STAMP(12 + so);
                WSUM(86 + 7 * (step >> 1));
                x_fix(X, xbits);
#pragma unroll
                for (int i = 0; i < 14; i++) X[i] = pack2(bf_lo(X[i]) + ao[2 * i], bf_hi(X[i]) + ao[2 * i + 1]);
            } else {
                uint32_t H[56];
                float ag[64];
#define F1_EPI(dst, ng, ag)                                                                    \
    _Pragma("unroll") for (int i = 0; i < 2 * (ng); i++)                                       \
        (dst)[i] = pack2(geglu(ag[2 * i], ag[4 * (ng) + 2 * i]), geglu(ag[2 * i + 1], ag[4 * (ng) + 2 * i + 1]));
#define H_PUSH(h0, off) st_async4(rem_h + (off), H[h0], H[(h0) + 1], H[(h0) + 2], H[(h0) + 3], mapa(BAR(B_RECV2 + wgi), hr ^ 1));
#define F1_BLOCK(b, first)                                                                     \
    if ((first) && (b) < 2 && (b) >= EARLY) R_RELEASE(2);                                      \
    if (GB == 2 && (first) && (b) == 1) GAT_FETCH()                                                       \
    if ((first) && (b) == 2) PUSH_ACK();                                                       \
    R_WAIT();                                                                                  \
    if ((b) == ((first) ? PPF : PPB)) { PP_WAIT() }                                            \
    { DECL_DB(b, BASE128, HALF, 0)                                                             \
    wg_fence();                                                                                \
    FOR7(mma_rs128<1, D128(0, t)>(ag, AQ(A, b, t), (b) + t > 0, SWB(b, t, db, 0));             \
         if constexpr (first) { PREP(b, t, true) }); }                                         \
    wg_commit();                                                                               \
    if ((b) == 3) { PP_GO() }                                                                  \
    if ((b) > 0) { wg_wait<1>(); R_RELEASE(1); }       \
    R_NEXT();
                normalize<0>(A, k0, k1);
                F1_BLOCK(0, true) F1_BLOCK(1, true) F1_BLOCK(2, true) F1_BLOCK(3, true)
                if (t128 == 0) { mbar_expect_tx(BAR(B_RECV + wgi), 16384); mbar_expect_tx(BAR(B_RECV2 + wgi), 12288); }
                PUSH_BEGIN();
                wg_wait<0>();
                R_RELEASE(1);
                if (step == 1) R_NEXT();
                int p = 0;
#pragma unroll 1
                do {
                    STAMP(68 + p);
                    F1_EPI(H + 32, 8, ag)
                    STAMP(4 + p + so);
                    WSUM(81 + p + 7 * (step >> 1));
                    if (((trips >> (p + 1)) & 1) == 0) continue;
                    {
                        const uint32_t pk = (p ? hbuf + 16384 : sb + OFF_KVB + wgi * 8192) + w * 2048;
#pragma unroll
                        for (int k = 0; k < 4; k++) sts4(pk + k * 512 + lane * 16, H[32 + 4 * k], H[33 + 4 * k], H[34 + 4 * k], H[35 + 4 * k]);
                        fence_async();
                        __syncwarp();
                        asm volatile(ELECT "cp.async.bulk.shared::cluster.shared::cta.mbarrier::complete_tx::bytes [%0], [%1], 2048, [%2]; }"
                                     ::"r"(mapa(hbuf + p * 8192 + w * 2048, hr ^ 1)), "r"(pk), "r"(mapa(BAR(B_RECV + wgi), hr ^ 1)) : "memory");
                    }
                    kill<64>(ag);
                    F1_BLOCK(0, false) F1_BLOCK(1, false) F1_BLOCK(2, false) F1_BLOCK(3, false)
                    wg_wait<0>();
                    R_RELEASE(1);
                    kill<16>(H + 32);
                } while (((trips >> (++p)) & 1));
#pragma unroll
                for (int k = 0; k < 4; k++) lds4(H + 16 + 4 * k, hbuf + 16384 + w * 2048 + k * 512 + lane * 16);
                __syncwarp();
                if (lane == 0) asm volatile("mbarrier.arrive.shared::cluster.b64 _, [%0];" ::"r"(mapa(BAR(B_ACK2 + wgi), hr ^ 1)) : "memory");
                const uint32_t rem_h = mapa(hbuf + w * 2048 + lane * 16, hr ^ 1);
#define F1_LAST(b0)                                                                            \
    R_WAIT();                                                                                  \
    if (b0) { PP_WAIT() }                                                                      \
    { DECL_DB(b0, BASE64, HALF, 1)                                                             \
    wg_fence();                                                                                \
    FOR7(mma_rs64<1, D64(0, t)>(al, AQ(A, b0, t), (b0) + t > 0, SWB(b0, t, db, 1)));           \
    FOR7(mma_rs64<1, D64(7168, t)>(al, AQ(A, (b0) + 1, t), 1, db)); }                          \
    wg_commit();                                                                               \
    if (b0) { PP_GO() }                                                                        \
    R_NEXT();
                float al[32];
                F1_LAST(0)
                mbar_wait(BAR(B_RECV + wgi), rcvph);
                rcvph ^= 1;
                mbar_wait(BAR(B_ACK2 + wgi), step >> 1);
                H_PUSH(32, 16384) H_PUSH(36, 16896)
                F1_LAST(2)
                H_PUSH(40, 17408) H_PUSH(44, 17920)
                wg_wait<1>();
                R_RELEASE(2);
                wg_wait<0>();
                R_RELEASE(1);
                uint32_t HP[56];
#pragma unroll
                for (int k = 0; k < 4; k++) lds4(H + 4 * k, sb + OFF_KVB + wgi * 8192 + w * 2048 + k * 512 + lane * 16);
#pragma unroll
                for (int t = 0; t < 8; t++) lds4(HP + 4 * t, hbuf + (t >> 2) * 8192 + w * 2048 + (t & 3) * 512 + lane * 16);
                F1_EPI(H + 48, 4, al)
                H_PUSH(48, 24576 - w * 1024) H_PUSH(52, 25088 - w * 1024)
                STAMP(7 + so);
                WSUM(84 + 7 * (step >> 1));
                float acc[28];
                const uint32_t roA = hr ? 256u : 0u, roB = hr ? (uint32_t)-1536 : 0u;
                const uint32_t rpA = hr ? 0u : 256u, rpB = hr ? 0u : (uint32_t)-1536;
                float res[28];
                uint32_t v0[14], v1[14], P[14];
                const uint4* ps = xp0 + sl * 512;
#define F2_OWN_A()                                                                             \
    R_WAIT();                                                                                  \
    d0 = BASE128(0, 16, R_ADJ + roA); d1 = BASE128(0, 16, R_ADJ + roB);                        \
    wg_fence();                                                                                \
    FOR14(if constexpr (t < OT) mma_rs56<1, t * 128>(acc, H[4 * t], H[4 * t + 1], H[4 * t + 2], H[4 * t + 3], t > 0, d0)); \
    wg_commit();
#define F2_OWN_B()                                                                             \
    wg_fence();                                                                                \
    FOR14(if constexpr (t >= OT) mma_rs56<1, t * 128>(acc, H[4 * t], H[4 * t + 1], H[4 * t + 2], H[4 * t + 3], 1, t < 12 ? d0 : d1)); \
    wg_commit();                                                                               \
    R_NEXT();
#define F2_PEER()                                                                              \
    R_WAIT();                                                                                  \
    if (F2PP) { PP_WAIT() }                                                                    \
    d0 = BASE128(0, 16, R_ADJ + rpA); d1 = BASE128(0, 16, R_ADJ + rpB);                        \
    wg_fence();                                                                                \
    FOR14(mma_rs56<1, t * 128>(acc, HP[4 * t], HP[4 * t + 1], HP[4 * t + 2], HP[4 * t + 3], 1, t < 12 ? d0 : d1)); \
    wg_commit();                                                                               \
    if (F2PP) { PP_GO() }                                                                      \
    R_NEXT();
#define F2_TURN(u)                                                                             \
    wg_wait<1>();                                                                              \
    R_RELEASE(2);                                                                              \
    wg_wait<0>();                                                                              \
    R_RELEASE(1);                                                                              \
    _Pragma("unroll") for (int i = 0; i < 14; i++) P[i] = pack2(acc[2 * i], acc[2 * i + 1]);   \
    tag_slice(P, tag);                                                                         \
    asm volatile("" : RW4(P, 0), RW4(P, 4), RW4(P, 8), RW2(P, 12));                            \
    kill<28>(acc);                                                                             \
    F2_OWN_A()                                                                                 \
    if ((u) == 2) { slice_load<PL(3)>(v0, ps, lane); slice_load<PL(4)>(v1, ps, lane); } \
    send_slice<PL(3 + (u))>(xp0 + (2 * ((pr + (u) + 1) & 3) + hr) * 512, lane, P);             \
    seq++;                                                                                     \
    if (lane == 0) st_word(cx(sl), seq);                                                       \
    __syncwarp();                                                                              \
    STAMP(8 + (u) + so);                                                                       \
    F2_OWN_B()
                uint64_t d0, d1;
                F2_OWN_A()
                F2_OWN_B()
                R_WAIT();
                d0 = BASE128(0, 16, R_ADJ + rpA); d1 = BASE128(0, 16, R_ADJ + rpB);
                wg_fence();
                FOR8(mma_rs56<1, t * 128>(acc, HP[4 * t], HP[4 * t + 1], HP[4 * t + 2], HP[4 * t + 3], 1, d0));
                wg_commit();
                mbar_wait(BAR(B_RECV2 + wgi), step >> 1);
#pragma unroll
                for (int k = 0; k < 4; k++) lds4(HP + 32 + 4 * k, hbuf + 16384 + w * 2048 + k * 512 + lane * 16);
                lds4(HP + 48, hbuf + 24576 + w * 1024 + lane * 16);
                lds4(HP + 52, hbuf + 25088 + w * 1024 + lane * 16);
                if (step == 1) PUSH_ACK();
                wg_fence();
                FOR14(if constexpr (t >= 8) mma_rs56<1, t * 128>(acc, HP[4 * t], HP[4 * t + 1], HP[4 * t + 2], HP[4 * t + 3], 1, t < 12 ? d0 : d1));
                wg_commit();
                R_NEXT();
                F2_TURN(0)
                F2_PEER()
                F2_TURN(1)
                F2_PEER()
                F2_TURN(2)
                STAMP(64 + 8 * (step >> 1));
                slice_check<PL(3)>(v0, ps, lane, tag);
                slice_check<PL(4)>(v1, ps, lane, tag);
#pragma unroll
                for (int i = 0; i < 14; i++) { res[2 * i] = bf_lo(v0[i]) + bf_lo(v1[i]); res[2 * i + 1] = bf_hi(v0[i]) + bf_hi(v1[i]); }
                slice_load<PL(2)>(X, ps, lane);
                STAMP(65 + 8 * (step >> 1));
                const uint32_t cv = ld_word(cx(2 * ((pr + 1) & 3) + hr));
                F2_PEER()
                STAMP(66 + 8 * (step >> 1));
                check_cnt(cv, cx(2 * ((pr + 1) & 3) + hr), seq);
                STAMP(67 + 8 * (step >> 1));
                slice_load<PL(5)>(v0, ps, lane);
                x_fix(X, xbits);
                slice_check<PL(5)>(v0, ps, lane, tag);
#pragma unroll
                for (int i = 0; i < 14; i++) { res[2 * i] += bf_lo(v0[i]); res[2 * i + 1] += bf_hi(v0[i]); }
                STAMP(11 + so);
                wg_wait<0>();
                if (EARLYK >= 1) R_RELEASE(2);
                STAMP(12 + so);
                WSUM(85 + 7 * (step >> 1));
#pragma unroll
                for (int i = 0; i < 14; i++) X[i] = pack2(fmaf(res[2 * i] + acc[2 * i], 0.5f, bf_lo(X[i])), fmaf(res[2 * i + 1] + acc[2 * i + 1], 0.5f, bf_hi(X[i])));
            }
        }
        {
            const int m = lane >> 3, rr = lane & 7;
            const uint32_t ob = hbuf + w * 2048, rowa = ob + (rr + 8 * (m & 1)) * 112 + (m >> 1) * 16;
#pragma unroll
            for (int j = 0; j < 3; j++) stsm4(rowa + 32 * j, X[4 * j], X[4 * j + 1], X[4 * j + 2], X[4 * j + 3]);
            asm volatile("stmatrix.sync.aligned.m8n8.x2.shared.b16 [%0], {%1,%2};" ::"r"(ob + (rr + 8 * (m & 1)) * 112 + 96), "r"(X[12]), "r"(X[13]) : "memory");
            fence_async();
            __syncwarp();
            if (lane == 0) {
                asm volatile("cp.async.bulk.tensor.2d.global.shared::cta.bulk_group [%0, {%2, %3}], [%1];" ::"l"(&maps.out), "r"(ob), "r"(56 * sl), "r"(tile * 128 + (tid >> 5) * 16) : "memory");
                asm volatile("cp.async.bulk.commit_group;" ::: "memory");
                asm volatile("cp.async.bulk.wait_group.read 0;" ::: "memory");
            }
        }
        STAMP(50);
        GSTAMP(61);
        PDUMP();
    }
}

typedef CUresult (*EncodeFn)(CUtensorMap*, CUtensorMapDataType, cuuint32_t, void*, const cuuint64_t*, const cuuint64_t*, const cuuint32_t*,
                             const cuuint32_t*, CUtensorMapInterleave, CUtensorMapSwizzle, CUtensorMapL2promotion, CUtensorMapFloatOOBfill);

static void make_map(EncodeFn enc, CUtensorMap* m, const void* p, uint64_t cols, uint64_t rows, uint32_t bc, uint32_t br, CUtensorMapSwizzle sw) {
    cuuint64_t gd[2] = {cols, rows};
    cuuint64_t gs[1] = {cols * 2};
    cuuint32_t bd[2] = {bc, br};
    cuuint32_t es[2] = {1, 1};
    enc(m, CU_TENSOR_MAP_DATA_TYPE_BFLOAT16, 2, const_cast<void*>(p), gd, gs, bd, es, CU_TENSOR_MAP_INTERLEAVE_NONE, sw,
        CU_TENSOR_MAP_L2_PROMOTION_L2_128B, CU_TENSOR_MAP_FLOAT_OOB_FILL_NONE);
}

extern "C" void kernel_launch(void* const* d_in, const int* in_sizes, int n_in, void* d_out, int out_size) {
    (void)in_sizes; (void)n_in; (void)out_size;
    static EncodeFn enc = nullptr;
    static Scratch* scratch = nullptr;
    if (!enc) {
        void* fn = nullptr;
        cudaDriverEntryPointQueryResult qr;
        cudaGetDriverEntryPoint("cuTensorMapEncodeTiled", &fn, cudaEnableDefault, &qr);
        enc = (EncodeFn)fn;
        cudaGetSymbolAddress((void**)&scratch, g_scratch);
        cudaFuncSetAttribute(fused_kernel, cudaFuncAttributeMaxDynamicSharedMemorySize, SMEM_BYTES);
    }
    Maps maps;
    {
        cuuint64_t gd[3] = {64, 2048, 7};
        cuuint64_t gs[2] = {896, 128};
        cuuint32_t bd[3] = {64, 32, 7};
        cuuint32_t es[3] = {1, 1, 1};
        enc(&maps.x, CU_TENSOR_MAP_DATA_TYPE_BFLOAT16, 3, d_in[0], gd, gs, bd, es, CU_TENSOR_MAP_INTERLEAVE_NONE, CU_TENSOR_MAP_SWIZZLE_128B,
            CU_TENSOR_MAP_L2_PROMOTION_L2_128B, CU_TENSOR_MAP_FLOAT_OOB_FILL_NONE);
    }
    make_map(enc, &maps.out, d_out, 448, 2048, 56, 16, CU_TENSOR_MAP_SWIZZLE_NONE);
    make_map(enc, &maps.qkv, d_in[1], 1344, 448, 64, 112, CU_TENSOR_MAP_SWIZZLE_128B);
    make_map(enc, &maps.wo, d_in[3], 448, 448, 64, 112, CU_TENSOR_MAP_SWIZZLE_128B);
    make_map(enc, &maps.wg, d_in[5], 1792, 448, 64, 112, CU_TENSOR_MAP_SWIZZLE_128B);
    make_map(enc, &maps.wu, d_in[6], 1792, 448, 64, 112, CU_TENSOR_MAP_SWIZZLE_128B);
    make_map(enc, &maps.wg32, d_in[5], 1792, 448, 32, 112, CU_TENSOR_MAP_SWIZZLE_64B);
    make_map(enc, &maps.wu32, d_in[6], 1792, 448, 32, 112, CU_TENSOR_MAP_SWIZZLE_64B);
    make_map(enc, &maps.wd, d_in[7], 448, 1792, 64, 112, CU_TENSOR_MAP_SWIZZLE_128B);
    fused_kernel<<<128, 384, SMEM_BYTES>>>(scratch, (const __nv_bfloat16*)d_in[0], (const __nv_bfloat16*)d_in[2], 7, (const __nv_bfloat16*)d_in[5],
                                           (const __nv_bfloat16*)d_in[6], (const __nv_bfloat16*)d_in[7], maps);
}
```

```cpp
#include <cuda_runtime.h>
#include <cuda.h>
#include <cuda_bf16.h>
#include <stdint.h>
#include <type_traits>

#define MC 0
#define PPF 2
#define GE 0
#define ACAN 1
#define SPLIT0 1
#define OT 2
#define F2PP 0
#define PPK 2
#define QE 1
#define OST 1
#define GB 1
#define B3T 6
#define PP

namespace {

constexpr uint32_t STAGE = 28672, HALF = 14336;
constexpr int NST = 5;
constexpr uint32_t OFF_H = NST * STAGE;
constexpr uint32_t OFF_KVB = OFF_H + 2 * STAGE;
constexpr uint32_t OFF_WPHI = OFF_KVB + 16384;
constexpr uint32_t OFF_XR = OFF_WPHI + 7168;
constexpr uint32_t OFF_BAR = OFF_XR + 6144;
constexpr uint32_t SMEM_BYTES = OFF_BAR + 256 + 1536;
constexpr int B_EMPTY = NST, B_RECV = 2 * NST, B_RECV2 = B_RECV + 2, B_PACK = B_RECV2 + 2, B_GAT = B_PACK + 1, B_ACK = B_GAT + 8, B_ACK2 = B_ACK + 2, B_COUNT = B_ACK2 + 2;

constexpr int PACK = 14;

struct Maps { CUtensorMap x, qkv, wo, wg, wu, wg32, wu32, wd, out; };

}

constexpr int PLANE = 16 * 2 * 8 * 512;
struct Scratch {
    uint4 ex[6 * PLANE];
    uint4 kv1[8 * 16 * 16 * 32];
    uint4 kv2[8 * 512];
    uint32_t c1[8 * 8 * 16 * 32];
    uint32_t cw[8 * 32];
    uint4 wp[8 * 32 * (HALF / 16)];
};
__device__ __align__(1024) Scratch g_scratch;
#define g_ex (sc->ex)
#define g_kv1 (sc->kv1)
#define g_kv2 (sc->kv2)
#define g_c1 (sc->c1)
#define g_cw (sc->cw)
#define g_wp (sc->wp)
#define STAMP(i)
#define GSTAMP(i)
#define PDUMP()
#define ASTAMP(i)

namespace {

__device__ __forceinline__ int fresh_tid() { int t; asm volatile("mov.u32 %0, %%tid.x;" : "=r"(t)); return t; }
__device__ __forceinline__ uint4* again(uint4* p) { asm volatile("" : "+l"(p)); return p; }
template <int N> __device__ __forceinline__ void kill(uint32_t* v) {
#pragma unroll
    for (int i = 0; i < N; i++) v[i] = 0;
}
template <int N> __device__ __forceinline__ void kill(float* v) {
#pragma unroll
    for (int i = 0; i < N; i++) v[i] = 0.f;
}
__device__ __forceinline__ uint32_t s2u(const void* p) { return (uint32_t)__cvta_generic_to_shared(p); }
__device__ __forceinline__ void mbar_init(uint32_t a, uint32_t c) { asm volatile("mbarrier.init.shared::cta.b64 [%0], %1;" ::"r"(a), "r"(c) : "memory"); }
__device__ __forceinline__ void mbar_expect_tx(uint32_t a, uint32_t b) { asm volatile("mbarrier.arrive.expect_tx.shared::cta.b64 _, [%0], %1;" ::"r"(a), "r"(b) : "memory"); }
__device__ __forceinline__ void mbar_arrive(uint32_t a) { asm volatile("mbarrier.arrive.shared::cta.b64 _, [%0];" ::"r"(a) : "memory"); }
#define GIVE_UP(id) "trap;\n"
#define SPIN_MAX "0x400000"
#define SPIN_TAIL(id) "add.u32 n, n, 1;\n setp.lt.u32 p, n, " SPIN_MAX ";\n @p bra.uni LP;\n" GIVE_UP(id) " DN:\n }"
__device__ __forceinline__ void mbar_wait(uint32_t a, uint32_t ph) {
    asm volatile("{ .reg .pred p; .reg .b32 n; mov.u32 n, 0;\n LP:\n"
                 "mbarrier.try_wait.parity.shared::cta.b64 p, [%0], %1;\n @p bra DN;\n"
                 "add.u32 n, n, 1;\n setp.lt.u32 p, n, " SPIN_MAX ";\n @p bra LP;\n"
                 GIVE_UP("")
                 " DN:\n }" ::"r"(a), "r"(ph) : "memory");
}
#define ELECT "{ .reg .pred e; elect.sync _|e, 0xffffffff; @e "
__device__ __forceinline__ void tma2d(uint32_t dst, const CUtensorMap* m, int c0, int c1, uint32_t bar) {
    asm volatile(ELECT "cp.async.bulk.tensor.2d.shared::cluster.global.mbarrier::complete_tx::bytes [%0], [%1, {%3, %4}], [%2]; }" ::"r"(dst), "l"(m), "r"(bar), "r"(c0), "r"(c1) : "memory");
}
__device__ __forceinline__ void tma3x(uint32_t dst, const CUtensorMap* m, int row, uint32_t bar) {
    asm volatile(ELECT "cp.async.bulk.tensor.3d.shared::cluster.global.mbarrier::complete_tx::bytes [%0], [%1, {0, %3, 0}], [%2]; }" ::"r"(dst), "l"(m), "r"(bar), "r"(row) : "memory");
}
template <int OFF>
__device__ __forceinline__ void ld_pkt(uint32_t* v, const uint4* p) {
    asm volatile("{ .reg .b128 t; ld.relaxed.gpu.global.b128 t, [%4+%5]; mov.b128 {%0,%1,%2,%3}, t; }" : "=r"(v[0]), "=r"(v[1]), "=r"(v[2]), "=r"(v[3]) : "l"(p), "n"(OFF * 16) : "memory");
}
template <int OFF>
__device__ __forceinline__ void st_pkt(uint4* p, uint32_t a, uint32_t b, uint32_t c, uint32_t d) {
    asm volatile("{ .reg .b128 t; mov.b128 t, {%1,%2,%3,%4}; st.relaxed.gpu.global.b128 [%0+%5], t; }" ::"l"(p), "r"(a), "r"(b), "r"(c), "r"(d), "n"(OFF * 16) : "memory");
}
__device__ __forceinline__ uint32_t pack2(float lo, float hi) {
    uint32_t r;
    asm("cvt.rn.bf16x2.f32 %0, %1, %2;" : "=r"(r) : "f"(hi), "f"(lo));
    return r;
}
__device__ __forceinline__ float bf_lo(uint32_t w) { return __uint_as_float(w << 16); }
__device__ __forceinline__ float bf_hi(uint32_t w) { return __uint_as_float(w & 0xffff0000u); }
__device__ __forceinline__ uint32_t settag(uint32_t w, uint32_t tag) { return (w & ~1u) | tag; }
__device__ __forceinline__ float ex2(float x) { float y; asm("ex2.approx.ftz.f32 %0, %1;" : "=f"(y) : "f"(x)); return y; }
__device__ __forceinline__ float rcp(float x) { float y; asm("rcp.approx.ftz.f32 %0, %1;" : "=f"(y) : "f"(x)); return y; }
__device__ __forceinline__ float tanh_hw(float x) { float y; asm("tanh.approx.f32 %0, %1;" : "=f"(y) : "f"(x)); return y; }
__device__ __forceinline__ void stsm4(uint32_t addr, uint32_t a, uint32_t b, uint32_t c, uint32_t d) {
    asm volatile("stmatrix.sync.aligned.m8n8.x4.shared.b16 [%0], {%1,%2,%3,%4};" ::"r"(addr), "r"(a), "r"(b), "r"(c), "r"(d) : "memory");
}
__device__ __forceinline__ void fence_async() { asm volatile("fence.proxy.async.shared::cta;" ::: "memory"); }
__device__ __forceinline__ void bar_sync(int id, int n) { asm volatile("bar.sync %0, %1;" ::"r"(id), "r"(n) : "memory"); }
__device__ __forceinline__ void bar_arrive(int id, int n) { asm volatile("bar.arrive %0, %1;" ::"r"(id), "r"(n) : "memory"); }
__device__ __forceinline__ void wg_fence() { asm volatile("wgmma.fence.sync.aligned;" ::: "memory"); }
__device__ __forceinline__ void wg_commit() { asm volatile("wgmma.commit_group.sync.aligned;" ::: "memory"); }
template <int N> __device__ __forceinline__ void wg_wait() { asm volatile("wgmma.wait_group.sync.aligned %0;" ::"n"(N) : "memory"); }

constexpr uint32_t SB0 = 1024;
__host__ __device__ constexpr uint32_t dlo(uint32_t off, uint32_t lbo) { return ((SB0 + off) >> 4) | ((lbo >> 4) << 16); }
__host__ __device__ constexpr uint32_t dhi(uint32_t sbo, uint32_t sw) { return (sbo >> 4) | (sw << 30); }
__device__ __forceinline__ uint64_t dbase(uint32_t lo, uint32_t hi) { uint64_t d; asm volatile("mov.b64 %0, {%1, %2};" : "=l"(d) : "r"(lo), "r"(hi)); return d; }
#define BASE128(off, lbo, adj) dbase(dlo(off, lbo) + (adj), dhi(1024, 1))
#define BASE64(off, lbo, adj) dbase(dlo(off, lbo) + (adj), dhi(512, 2))

#define ACC4(d, o) "+f"(d[o]), "+f"(d[o + 1]), "+f"(d[o + 2]), "+f"(d[o + 3])
#define ACC28(d) ACC4(d, 0), ACC4(d, 4), ACC4(d, 8), ACC4(d, 12), ACC4(d, 16), ACC4(d, 20), ACC4(d, 24)
#define ACC32(d, o) ACC4(d, o), ACC4(d, o + 4), ACC4(d, o + 8), ACC4(d, o + 12), ACC4(d, o + 16), ACC4(d, o + 20), ACC4(d, o + 24), ACC4(d, o + 28)

template <int TB, uint64_t D>
__device__ __forceinline__ void mma_rs56(float* d, uint32_t a0, uint32_t a1, uint32_t a2, uint32_t a3, int sd, uint64_t base) {
    asm volatile("{ .reg .pred p; .reg .b64 db; setp.ne.b32 p, %32, 0; add.u64 db, %33, %34;\n"
                 "wgmma.mma_async.sync.aligned.m64n56k16.f32.bf16.bf16 "
                 "{%0,%1,%2,%3,%4,%5,%6,%7,%8,%9,%10,%11,%12,%13,%14,%15,%16,%17,%18,%19,%20,%21,%22,%23,%24,%25,%26,%27}, "
                 "{%28,%29,%30,%31}, db, p, 1, 1, %35; }\n"
                 : ACC28(d)
                 : "r"(a0), "r"(a1), "r"(a2), "r"(a3), "r"(sd), "l"(base), "n"(D), "n"(TB));
}
template <int TB, uint64_t D>
__device__ __forceinline__ void mma_rs64(float* d, uint32_t a0, uint32_t a1, uint32_t a2, uint32_t a3, int sd, uint64_t base) {
    asm volatile("{ .reg .pred p; .reg .b64 db; setp.ne.b32 p, %36, 0; add.u64 db, %37, %38;\n"
                 "wgmma.mma_async.sync.aligned.m64n64k16.f32.bf16.bf16 "
                 "{%0,%1,%2,%3,%4,%5,%6,%7,%8,%9,%10,%11,%12,%13,%14,%15,%16,%17,%18,%19,%20,%21,%22,%23,%24,%25,%26,%27,%28,%29,%30,%31}, "
                 "{%32,%33,%34,%35}, db, p, 1, 1, %39; }\n"
                 : ACC32(d, 0)
                 : "r"(a0), "r"(a1), "r"(a2), "r"(a3), "r"(sd), "l"(base), "n"(D), "n"(TB));
}
template <int TB, uint64_t D>
__device__ __forceinline__ void mma_rs128(float* d, uint32_t a0, uint32_t a1, uint32_t a2, uint32_t a3, int sd, uint64_t base) {
    asm volatile("{ .reg .pred p; .reg .b64 db; setp.ne.b32 p, %68, 0; add.u64 db, %69, %70;\n"
                 "wgmma.mma_async.sync.aligned.m64n128k16.f32.bf16.bf16 "
                 "{%0,%1,%2,%3,%4,%5,%6,%7,%8,%9,%10,%11,%12,%13,%14,%15,%16,%17,%18,%19,%20,%21,%22,%23,%24,%25,%26,%27,%28,%29,%30,%31,%32,%33,%34,%35,%36,%37,%38,%39,%40,%41,%42,%43,%44,%45,%46,%47,%48,%49,%50,%51,%52,%53,%54,%55,%56,%57,%58,%59,%60,%61,%62,%63}, "
                 "{%64,%65,%66,%67}, db, p, 1, 1, %71; }\n"
                 : ACC32(d, 0), ACC32(d, 32)
                 : "r"(a0), "r"(a1), "r"(a2), "r"(a3), "r"(sd), "l"(base), "n"(D), "n"(TB));
}
template <uint64_t DA, uint64_t DB>
__device__ __forceinline__ void mma_ss56_tt(float* d, int sd, uint64_t ba, uint64_t bb) {
    asm volatile("{ .reg .pred p; .reg .b64 da, db; setp.ne.b32 p, %28, 0; add.u64 da, %29, %31; add.u64 db, %30, %32;\n"
                 "wgmma.mma_async.sync.aligned.m64n56k16.f32.bf16.bf16 "
                 "{%0,%1,%2,%3,%4,%5,%6,%7,%8,%9,%10,%11,%12,%13,%14,%15,%16,%17,%18,%19,%20,%21,%22,%23,%24,%25,%26,%27}, "
                 "da, db, p, 1, 1, 1, 1; }\n"
                 : ACC28(d)
                 : "r"(sd), "l"(ba), "l"(bb), "n"(DA), "n"(DB));
}
template <int... I> struct Seq {};
template <class F, int... I> __device__ __forceinline__ void static_for_impl(F&& f, Seq<I...>) { (f(std::integral_constant<int, I>{}), ...); }
#define FOR7(...) static_for_impl([&](auto T_) { constexpr int t = decltype(T_)::value; __VA_ARGS__; }, Seq<0, 1, 2, 3, 4, 5, 6>{})
#define FOR8(...) static_for_impl([&](auto T_) { constexpr int t = decltype(T_)::value; __VA_ARGS__; }, Seq<0, 1, 2, 3, 4, 5, 6, 7>{})
#define FOR14(...) static_for_impl([&](auto T_) { constexpr int t = decltype(T_)::value; __VA_ARGS__; }, Seq<0, 1, 2, 3, 4, 5, 6, 7, 8, 9, 10, 11, 12, 13>{})

__device__ __forceinline__ int kblk(int p, int b) { return b == 0 ? p : b - (b <= p); }
__host__ __device__ constexpr int krow(int t) { return t < 3 ? 16 * t : (t < 6 ? 56 + 16 * (t - 3) : 48); }
#define AQ(A, b, t) ((t) < 3 ? A[2 * (b)][4 * (t)] : (t) < 6 ? A[2 * (b) + 1][4 * ((t) - 3)] : A[2 * (b)][12]), \
                    ((t) < 3 ? A[2 * (b)][4 * (t) + 1] : (t) < 6 ? A[2 * (b) + 1][4 * ((t) - 3) + 1] : A[2 * (b)][13]), \
                    ((t) < 3 ? A[2 * (b)][4 * (t) + 2] : (t) < 6 ? A[2 * (b) + 1][4 * ((t) - 3) + 2] : A[2 * (b) + 1][12]), \
                    ((t) < 3 ? A[2 * (b)][4 * (t) + 3] : (t) < 6 ? A[2 * (b) + 1][4 * ((t) - 3) + 3] : A[2 * (b) + 1][13])
#define D128(off, t) ((uint64_t)(((off) + krow(t) * 128) >> 4) + ((uint64_t)((t) == 6 ? (7168 - 1024) >> 4 : 0) << 32))
#define D64(off, t) ((uint64_t)(((off) + krow(t) * 64) >> 4) + ((uint64_t)((t) == 6 ? (3584 - 512) >> 4 : 0) << 32))

#define PL(k) (((k) - 3) * PLANE)
__device__ __forceinline__ void st_word(uint32_t* p, uint32_t v) { asm volatile("st.relaxed.gpu.global.u32 [%0], %1;" ::"l"(p), "r"(v) : "memory"); }
__device__ __forceinline__ uint32_t ld_word(const uint32_t* p) { uint32_t v; asm volatile("ld.relaxed.gpu.global.u32 %0, [%1];" : "=r"(v) : "l"(p) : "memory"); return v; }
__device__ __forceinline__ void tag_slice(uint32_t* w, uint32_t tag) { w[0] = settag(w[0], tag); w[4] = settag(w[4], tag); w[8] = settag(w[8], tag); w[12] = settag(w[12], tag); }
template <int O>
__device__ __forceinline__ void send_slice(uint4* dst, int lane, const uint32_t* w) {
    st_pkt<O>(dst, w[0], w[1], w[2], w[3]);
    st_pkt<O + 32>(dst, w[4], w[5], w[6], w[7]);
    st_pkt<O + 64>(dst, w[8], w[9], w[10], w[11]);
    asm volatile("{ .reg .b64 t; mov.b64 t, {%1,%2}; st.relaxed.gpu.global.b64 [%0+%3], t; }" ::"l"((char*)dst - lane * 8), "r"(w[12]), "r"(w[13]), "n"(16 * (O + 96)) : "memory");
}
#define RW4(v, o) "+r"(v[o]), "+r"(v[(o) + 1]), "+r"(v[(o) + 2]), "+r"(v[(o) + 3])
#define RW2(v, o) "+r"(v[o]), "+r"(v[(o) + 1])
#define WR4(v, o) "=&r"(v[o]), "=&r"(v[(o) + 1]), "=&r"(v[(o) + 2]), "=&r"(v[(o) + 3])
#define LDP(a, b, c, d, addr, off) "ld.relaxed.gpu.global.b128 q, [" addr "+" off "];\n mov.b128 {" a "," b "," c "," d "}, q;\n"
#define LDH(a, b, addr, off) "ld.relaxed.gpu.global.b64 h, [" addr "+" off "];\n mov.b64 {" a "," b "}, h;\n"
#define VOTE_OK "and.b32 t, t, 1;\n setp.ne.u32 p, t, 0;\n vote.sync.any.pred p, p, 0xffffffff;\n @!p bra.uni DN;\n"
#define CHK(x, tag) "lop3.b32 t, " x ", " tag ", t, 0xBE;\n"
__device__ __forceinline__ void check_cnt(uint32_t v, const uint32_t* p, uint32_t target) {
    asm volatile("{ .reg .pred p; .reg .b32 n, t; mov.u32 n, 0; mov.u32 t, %2;\n LP:\n"
                 "sub.s32 t, t, %1;\n setp.lt.s32 p, t, 0;\n vote.sync.any.pred p, p, 0xffffffff;\n @!p bra.uni DN;\n ld.relaxed.gpu.global.u32 t, [%0];\n" SPIN_TAIL("7")
                 ::"l"(p), "r"(target), "r"(v) : "memory");
}
__device__ __forceinline__ void poll_cnt(const uint32_t* p, uint32_t target) {
    asm volatile("{ .reg .pred p; .reg .b32 n, t; mov.u32 n, 0;\n LP:\n"
                 "ld.relaxed.gpu.global.u32 t, [%0];\n sub.s32 t, t, %1;\n setp.lt.s32 p, t, 0;\n vote.sync.any.pred p, p, 0xffffffff;\n @!p bra.uni DN;\n" SPIN_TAIL("1")
                 ::"l"(p), "r"(target) : "memory");
}
template <int STR>
__device__ __forceinline__ void poll4_kv(uint32_t* v, const uint4* p, uint32_t tag) {
    asm volatile("{ .reg .pred p; .reg .b32 n, t; .reg .b128 q; mov.u32 n, 0;\n LP:\n"
                 LDP("%0", "%1", "%2", "%3", "%16", "0") LDP("%4", "%5", "%6", "%7", "%16", "%18")
                 LDP("%8", "%9", "%10", "%11", "%16", "%19") LDP("%12", "%13", "%14", "%15", "%16", "%20")
                 "xor.b32 t, %0, %17;\n" CHK("%4", "%17") CHK("%8", "%17") CHK("%12", "%17") VOTE_OK SPIN_TAIL("2")
                 : WR4(v, 0), WR4(v, 4), WR4(v, 8), WR4(v, 12)
                 : "l"(p), "r"(tag), "n"(16 * STR), "n"(32 * STR), "n"(48 * STR)
                 : "memory");
}
template <int B>
__device__ __forceinline__ void blk_load(uint32_t (&A)[8][14], const uint4* src, int lane) {
    ld_pkt<0>(&A[2 * B][0], src); ld_pkt<32>(&A[2 * B][4], src); ld_pkt<64>(&A[2 * B][8], src);
    ld_pkt<512>(&A[2 * B + 1][0], src); ld_pkt<544>(&A[2 * B + 1][4], src); ld_pkt<576>(&A[2 * B + 1][8], src);
    asm volatile("{ .reg .b64 h;\n" LDH("%0", "%1", "%4", "1536") LDH("%2", "%3", "%4", "9728") "}"
                 : "=&r"(A[2 * B][12]), "=&r"(A[2 * B][13]), "=&r"(A[2 * B + 1][12]), "=&r"(A[2 * B + 1][13])
                 : "l"((const char*)src - lane * 8) : "memory");
}
template <int B>
__device__ __forceinline__ void blk_check(uint32_t (&A)[8][14], const uint4* src, int lane, uint32_t tag) {
    asm volatile("{ .reg .pred p; .reg .b32 n, t; .reg .b128 q; .reg .b64 h, a8; mov.u32 n, 0;\n LP:\n"
                 "xor.b32 t, %0, %30;\n" CHK("%4", "%30") CHK("%8", "%30") CHK("%12", "%30") CHK("%16", "%30") CHK("%20", "%30") CHK("%24", "%30") CHK("%26", "%30") VOTE_OK
                 LDP("%0", "%1", "%2", "%3", "%28", "0") LDP("%4", "%5", "%6", "%7", "%28", "512") LDP("%8", "%9", "%10", "%11", "%28", "1024")
                 LDP("%12", "%13", "%14", "%15", "%28", "8192") LDP("%16", "%17", "%18", "%19", "%28", "8704") LDP("%20", "%21", "%22", "%23", "%28", "9216")
                 "mad.wide.s32 a8, %29, -8, %28;\n" LDH("%24", "%25", "a8", "1536") LDH("%26", "%27", "a8", "9728") SPIN_TAIL("3")
                 "\n and.b32 %0, %0, -2; and.b32 %4, %4, -2; and.b32 %8, %8, -2; and.b32 %12, %12, -2; and.b32 %16, %16, -2; and.b32 %20, %20, -2; and.b32 %24, %24, -2; and.b32 %26, %26, -2;"
                 : RW4(A[2 * B], 0), RW4(A[2 * B], 4), RW4(A[2 * B], 8), RW4(A[2 * B + 1], 0), RW4(A[2 * B + 1], 4), RW4(A[2 * B + 1], 8),
                   RW2(A[2 * B], 12), RW2(A[2 * B + 1], 12)
                 : "l"(src), "r"(lane), "r"(tag)
                 : "memory");
}
__device__ __forceinline__ void st_async4(uint32_t a, uint32_t x, uint32_t y, uint32_t z, uint32_t w, uint32_t bar) {
    asm volatile("st.async.weak.shared::cluster.mbarrier::complete_tx::bytes.v4.b32 [%0], {%1,%2,%3,%4}, [%5];" ::"r"(a), "r"(x), "r"(y), "r"(z), "r"(w), "r"(bar) : "memory");
}
__device__ __forceinline__ uint32_t mapa(uint32_t a, uint32_t cta) { uint32_t r; asm("mapa.shared::cluster.u32 %0, %1, %2;" : "=r"(r) : "r"(a), "r"(cta)); return r; }
__device__ __forceinline__ void stat_load(uint32_t* v, const uint4* p) { ld_pkt<0>(v, p); ld_pkt<512>(v + 4, p); }
__device__ __forceinline__ void stat_check(uint32_t* v, const uint4* p, uint32_t tag) {
    asm volatile("{ .reg .pred p; .reg .b32 n, t; .reg .b128 q; mov.u32 n, 0;\n LP:\n"
                 "xor.b32 t, %3, %9;\n" CHK("%7", "%9") VOTE_OK
                 LDP("%0", "%1", "%2", "%3", "%8", "0") LDP("%4", "%5", "%6", "%7", "%8", "8192") SPIN_TAIL("4")
                 : RW4(v, 0), RW4(v, 4) : "l"(p), "r"(tag) : "memory");
}
__device__ __forceinline__ uint32_t x_bits(const uint32_t* X) {
    uint32_t r;
    asm volatile("{ .reg .b32 a, b; prmt.b32 a, %1, %2, 0x0040; prmt.b32 b, %3, %4, 0x0040; prmt.b32 %0, a, b, 0x5410; }" : "=r"(r) : "r"(X[0]), "r"(X[4]), "r"(X[8]), "r"(X[12]));
    return r;
}
template <int O>
__device__ __forceinline__ void slice_load(uint32_t* v, const uint4* p, int lane) {
    ld_pkt<O>(v, p); ld_pkt<O + 32>(v + 4, p); ld_pkt<O + 64>(v + 8, p);
    asm volatile("{ .reg .b64 h;\n" LDH("%0", "%1", "%2", "%3") "}" : "=r"(v[12]), "=r"(v[13]) : "l"((const char*)p - lane * 8), "n"(16 * (O + 96)) : "memory");
}
template <int O>
__device__ __forceinline__ void slice_check(uint32_t* v, const uint4* p, int lane, uint32_t tag) {
    asm volatile("{ .reg .pred p; .reg .b32 n, t; .reg .b128 q; .reg .b64 h; mov.u32 n, 0;\n LP:\n"
                 "xor.b32 t, %0, %16;\n" CHK("%4", "%16") CHK("%8", "%16") CHK("%12", "%16") VOTE_OK
                 LDP("%0", "%1", "%2", "%3", "%14", "%17") LDP("%4", "%5", "%6", "%7", "%14", "%18") LDP("%8", "%9", "%10", "%11", "%14", "%19")
                 LDH("%12", "%13", "%15", "%20") SPIN_TAIL("5")
                 : RW4(v, 0), RW4(v, 4), RW4(v, 8), RW2(v, 12)
                 : "l"(p), "l"((const char*)p - lane * 8), "r"(tag), "n"(16 * O), "n"(16 * (O + 32)), "n"(16 * (O + 64)), "n"(16 * (O + 96))
                 : "memory");
}
__device__ __forceinline__ void x_fix(uint32_t* X, uint32_t bits) {
    X[0] = __byte_perm(X[0], bits, 0x3214); X[4] = __byte_perm(X[4], bits, 0x3215); X[8] = __byte_perm(X[8], bits, 0x3216); X[12] = __byte_perm(X[12], bits, 0x3217);
}
__device__ __forceinline__ void sts4(uint32_t a, uint32_t x, uint32_t y, uint32_t z, uint32_t w) {
    asm volatile("st.shared.v4.u32 [%0], {%1,%2,%3,%4};" ::"r"(a), "r"(x), "r"(y), "r"(z), "r"(w) : "memory");
}
__device__ __forceinline__ void lds4(uint32_t* v, uint32_t a) {
    asm volatile("ld.shared.v4.u32 {%0,%1,%2,%3}, [%4];" : "=r"(v[0]), "=r"(v[1]), "=r"(v[2]), "=r"(v[3]) : "r"(a) : "memory");
}
struct LnCoef { uint32_t hi, lo, sh; };
__device__ __forceinline__ LnCoef ln_coef(float sum, float sq) {
    sum += __shfl_xor_sync(0xffffffffu, sum, 1); sq += __shfl_xor_sync(0xffffffffu, sq, 1);
    sum += __shfl_xor_sync(0xffffffffu, sum, 2); sq += __shfl_xor_sync(0xffffffffu, sq, 2);
    const float mean = sum * (1.f / 448.f);
    const float var = fmaxf(fmaf(-mean, mean, sq * (1.f / 448.f)), 0.f);
    const float sc = rsqrtf(var + 1e-5f);
    LnCoef r;
    r.hi = pack2(sc, sc);
    const float lo = sc - bf_lo(r.hi), sh = -mean * sc;
    r.lo = pack2(lo, lo);
    r.sh = pack2(sh, sh);
    return r;
}
template <int B>
__device__ __forceinline__ void normalize(uint32_t (&A)[8][14], const LnCoef& c0, const LnCoef& c1) {
#pragma unroll
    for (int s = 2 * B; s < 2 * B + 2; s++)
#pragma unroll
        for (int i = 0; i < 14; i++) {
            const LnCoef& k = (i & 1) ? c1 : c0;
            asm("{ .reg .b32 t; fma.rn.bf16x2 t, %0, %2, %3; fma.rn.bf16x2 %0, %0, %1, t; }" : "+r"(A[s][i]) : "r"(k.hi), "r"(k.lo), "r"(k.sh));
        }
}
__device__ __forceinline__ void slice_stats(const uint32_t* w, float* st) {
    float a = 0.f, b = 0.f, p = 0.f, q = 0.f;
#pragma unroll
    for (int i = 0; i < 7; i++) {
        const float e0 = bf_lo(w[2 * i]), e1 = bf_hi(w[2 * i]), e2 = bf_lo(w[2 * i + 1]), e3 = bf_hi(w[2 * i + 1]);
        a += e0 + e1; b += e2 + e3;
        p = fmaf(e0, e0, p); p = fmaf(e1, e1, p); q = fmaf(e2, e2, q); q = fmaf(e3, e3, q);
    }
    a += __shfl_xor_sync(0xffffffffu, a, 1); p += __shfl_xor_sync(0xffffffffu, p, 1); b += __shfl_xor_sync(0xffffffffu, b, 1); q += __shfl_xor_sync(0xffffffffu, q, 1);
    a += __shfl_xor_sync(0xffffffffu, a, 2); p += __shfl_xor_sync(0xffffffffu, p, 2); b += __shfl_xor_sync(0xffffffffu, b, 2); q += __shfl_xor_sync(0xffffffffu, q, 2);
    st[0] = a; st[1] = p; st[2] = b; st[3] = q;
}
__device__ __forceinline__ void dual_softmax(const float* p, uint32_t* out) {
    constexpr float L = 1.4426950408889634f;
#pragma unroll
    for (int r = 0; r < 2; r++) {
        float mx = fmaxf(p[2 * r], p[2 * r + 1]), mn = fminf(p[2 * r], p[2 * r + 1]);
#pragma unroll
        for (int i = 1; i < 7; i++) {
            mx = fmaxf(mx, fmaxf(p[4 * i + 2 * r], p[4 * i + 2 * r + 1]));
            mn = fminf(mn, fminf(p[4 * i + 2 * r], p[4 * i + 2 * r + 1]));
        }
        mx = fmaxf(mx, __shfl_xor_sync(0xffffffffu, mx, 1));
        mn = fminf(mn, __shfl_xor_sync(0xffffffffu, mn, 1));
        const float bx = -mx * L, bn = mn * L;
        float ep[14], en[14], sp = 0.f, sn = 0.f;
#pragma unroll
        for (int i = 0; i < 14; i++) {
            const float v = p[4 * (i >> 1) + 2 * r + (i & 1)];
            ep[i] = ex2(fmaf(v, L, bx));
            en[i] = ex2(fmaf(v, -L, bn));
            sp += ep[i]; sn += en[i];
        }
        sp += __shfl_xor_sync(0xffffffffu, sp, 1);
        sn += __shfl_xor_sync(0xffffffffu, sn, 1);
        const float ip = rcp(sp), in = rcp(sn);
#pragma unroll
        for (int i = 0; i < 7; i++) {
            out[4 * i + r] = pack2(ep[2 * i] * ip, ep[2 * i + 1] * ip);
            out[4 * i + 2 + r] = pack2(en[2 * i] * in, en[2 * i + 1] * in);
        }
    }
}
__device__ __forceinline__ float geglu(float g, float u) {
    const float t = tanh_hw(g * fmaf(g * g, 0.7978845608028654f * 0.044715f, 0.7978845608028654f));
    const float gu = g * u;
    return fmaf(t, gu, gu);
}
__device__ __forceinline__ void phi_gemm(const float* t, float* p) {
    uint32_t w[14];
#pragma unroll
    for (int i = 0; i < 14; i++) w[i] = pack2(t[2 * i], t[2 * i + 1]);
    const uint64_t db = BASE128(OFF_WPHI, 16, 0);
    wg_fence();
    mma_rs56<0, 0>(p, w[0], w[1], w[2], w[3], 0, db);
    mma_rs56<0, 2>(p, w[4], w[5], w[6], w[7], 1, db);
    mma_rs56<0, 4>(p, w[8], w[9], w[10], w[11], 1, db);
    mma_rs56<0, 6>(p, w[12], w[13], 0u, 0u, 1, db);
    wg_commit();
    wg_wait<0>();
}

}

#define BAR(i) (bars + 8 * (i))
#define R_WAIT() mbar_wait(BAR(slot), ph)
#define WSUM(i)
#define R_ADJ (slot * (STAGE >> 4))
#define R_NEXT() do { eb2 = eb1; eb1 = BAR(B_EMPTY + slot); if (++slot == NST) { slot = 0; ph ^= 1; } } while (0)
#define R_RELEASE(k) do { if (lane == 0) mbar_arrive((k) == 1 ? eb1 : eb2); } while (0)
#define PUSH_BEGIN() do { mbar_wait(BAR(B_ACK + wgi), ackph); ackph ^= 1; } while (0)
#define PUSH_ACK() do { __syncwarp(); if (lane == 0) asm volatile("mbarrier.arrive.shared::cluster.b64 _, [%0];" ::"r"(mapa(BAR(B_ACK + wgi), hr ^ 1)) : "memory"); } while (0)

__global__ void __cluster_dims__(2, 1, 1) __launch_bounds__(384, 1)
fused_kernel(Scratch* const sc, const __nv_bfloat16* __restrict__ x_in, const __nv_bfloat16* __restrict__ w_phi, const int trips,
             const __nv_bfloat16* __restrict__ wg, const __nv_bfloat16* __restrict__ wu, const __nv_bfloat16* __restrict__ wd,
             const __grid_constant__ Maps maps) {
    extern __shared__ __align__(1024) unsigned char smem_raw[];
    const uint32_t sb = s2u(smem_raw);
    const uint32_t bars = sb + OFF_BAR;
    const int wgi = __shfl_sync(0xffffffffu, threadIdx.x >> 7, 0);
    const int hr = blockIdx.x & 1, ck = blockIdx.x >> 1;
    const int gp = (ck - 4) & 7, q7 = ((ck - 36) * 37) >> 8;
    const int pr = ck < 4 ? ck : (ck < 36 ? (ck - 4) >> 3 : q7);
    const int tile = ck < 4 ? 0 : (ck < 36 ? (gp ? 2 * gp : 1) : 2 * (ck - 36 - 7 * q7) + 3);
    const int sl = 2 * pr + hr;
    STAMP(0);
    GSTAMP(60);
    if (threadIdx.x == 256) {
#pragma unroll
        for (int i = 0; i < NST; i++) mbar_init(BAR(i), 1);
        asm volatile("fence.mbarrier_init.release.cluster;" ::: "memory");
    }
    if (threadIdx.x == 288) {
        if ((sb & 0x3FFFF) != SB0) asm volatile("trap;");
#pragma unroll
        for (int i = NST; i < B_COUNT; i++) mbar_init(BAR(i), i >= B_ACK ? 4 : (i < B_RECV ? 8 : 1));
        asm volatile("fence.mbarrier_init.release.cluster;" ::: "memory");
    }
    __syncwarp();
    asm volatile("barrier.cluster.arrive.relaxed.aligned;" ::: "memory");

    if (wgi == 2) {
        asm volatile("setmaxnreg.dec.sync.aligned.u32 40;");
        const int t128 = fresh_tid() & 127, w = __shfl_sync(0xffffffffu, t128 >> 5, 0), lane = t128 & 31;
        uint32_t e0[2] = {0, 0}, e1[2] = {0, 0}, cw_target = 0;
        if (w == 0) {
#pragma unroll 1
            for (int n = 0; n < NST; n++) {
                const uint32_t dst = sb + n * STAGE, fb = BAR(n);
                asm volatile(ELECT "mbarrier.arrive.expect_tx.shared::cta.b64 _, [%0], %1; }" ::"r"(fb), "r"(n < 2 ? 2 * STAGE : STAGE) : "memory");
                if (n < 2) {
                    tma3x(sb + OFF_H + n * STAGE, &maps.x, tile * 128 + n * 64, fb);
                    tma3x(dst, &maps.x, tile * 128 + n * 64 + 32, fb);
                } else {
                    if (n == 3) mbar_wait(BAR(1), 0);
                    const int ra = 112 * (n - 2);
                    tma2d(dst, &maps.qkv, 448 + 56 * sl, ra, fb);
                    tma2d(dst + HALF, &maps.qkv, 896 + 56 * sl, ra, fb);
                }
            }
            asm volatile("barrier.cluster.wait.aligned;" ::: "memory");
            cw_target = (ld_word(g_cw + sl * 32) & ~15u) + 16;
#pragma unroll 1
            for (int k = 0; k < 2; k++) {
                const int n = t128 + 32 * k;
                int m = n - 2 - (n > PACK);
                const bool packed = m >= 30 ? (m < 38 || m >= 52) : m >= 22;
                if (m >= 30) m -= 30;
                if (n == PACK) m = tile < 8 ? tile : tile + 14;
                const int rot = n < 8 ? 0 : pr;
                const int ra = 112 * kblk(rot, m & 3), rb = 112 * kblk(rot, 2 * m & 3), rc = 112 * kblk(rot, (2 * m + 1) & 3);
                int kind = 0, m0, m1, c0, c1, r0, r1;
                if (m < 4) { m0 = m1 = 1; c0 = 448 + 56 * sl; c1 = c0 + 448; r0 = r1 = ra; }
                else if (m < 8) { m0 = m1 = m < 6 ? 1 : 2; c0 = c1 = 56 * sl; r0 = rb; r1 = rc; }
                else if (m < 20) { m0 = 3; m1 = 4; c0 = c1 = 224 * sl + 32 * hr + 64 * ((m - 8) >> 2); r0 = r1 = ra; }
                else if (m < 22) { kind = 2; m0 = 5; m1 = 6; c0 = c1 = 224 * sl + (hr ? 0 : 192); r0 = rb; r1 = rc; }
                else { m0 = m1 = 7; c0 = c1 = 56 * (2 * ((pr + (m >> 1) - 10) & 3) + hr); r0 = 224 * (sl ^ (m & 1)); r1 = r0 + 112; }
                if (packed) { kind = 1; r0 = sl * 16 + (m < 8 ? m : m - 14); r1 = 0; }
                e0[0] = e0[1]; e1[0] = e1[1];
                e0[1] = kind | (m0 << 2) | (m1 << 6) | (c0 << 10) | (c1 << 21);
                e1[1] = r0 | (r1 << 16);
            }
        } else {
            const int j = t128 - 32;
            asm volatile("barrier.cluster.wait.aligned;" ::: "memory");
            uint2 wv[7];
            const int k = j < 56 ? j : 55, hh = k >= 28;
#pragma unroll
            for (int i = 0; i < 7; i++) wv[i] = __ldg(reinterpret_cast<const uint2*>(w_phi + (sl * 56 + k) * 28) + i);
#pragma unroll 1
            for (int i = j; i < 7168 / 16; i += 96) sts4(sb + OFF_WPHI + i * 16, 0, 0, 0, 0);
            bar_sync(5, 96);
            if (j < 56) {
                uint32_t a4[4];
#pragma unroll
                for (int q = 0; q < 4; q++) a4[q] = sb + OFF_WPHI + (4 * hh + q) * 128 + ((((k >> 3) ^ (4 * hh + q)) & 7) << 4) + (k & 7) * 2;
                FOR14(const uint32_t v = (t & 1) ? wv[t >> 1].y : wv[t >> 1].x;
                      asm volatile("{ .reg .b16 l, h; mov.b32 {l, h}, %2; st.shared.u16 [%0+%3], l; st.shared.u16 [%1+%3], h; }"
                                   ::"r"(a4[t >= 7 ? 2 : 0]), "r"(a4[t >= 7 ? 3 : 1]), "r"(v), "n"((t % 7) * 1024) : "memory"));
            }
            __syncwarp();
            fence_async();
            bar_arrive(1, 224);
            bar_arrive(9, 224);
            if (w == 1) {
                mbar_wait(BAR(2), 0);
                mbar_wait(BAR(2), 1);
                const int b = blockIdx.x;
                asm volatile(ELECT "cp.async.bulk.prefetch.L2.global [%0], %1; }" ::"l"(wg + b * 6272), "r"(12544) : "memory");
                asm volatile(ELECT "cp.async.bulk.prefetch.L2.global [%0], %1; }" ::"l"(wu + b * 6272), "r"(12544) : "memory");
                asm volatile(ELECT "cp.async.bulk.prefetch.L2.global [%0], %1; }" ::"l"(wd + b * 6272), "r"(12544) : "memory");
            }
        }
        uint32_t kseq = ld_word(g_c1 + (sl * 8 * 16 + tile) * 32);
        int slot = 0, ph = 0, n = NST;
#pragma unroll 1
        for (int layer = 0; layer < 3; layer++) {
            if (w == 0) {
                const int nend = layer == 0 ? 11 : (layer == 1 ? 42 : 63);
#pragma unroll 1
                for (; n < nend; n++) {
                const uint32_t w0 = __shfl_sync(0xffffffffu, n < 32 ? e0[0] : e0[1], n & 31), w1 = __shfl_sync(0xffffffffu, n < 32 ? e1[0] : e1[1], n & 31);
                const uint32_t dst = sb + slot * STAGE, fb = BAR(n == PACK ? B_PACK : slot);
                const CUtensorMap* m0 = &maps.x + ((w0 >> 2) & 15);
                const CUtensorMap* m1 = &maps.x + ((w0 >> 6) & 15);
                const int c0 = (w0 >> 10) & 2047, c1 = w0 >> 21, r0 = w1 & 0xffff, r1 = w1 >> 16;
                if (n == 25) {
                    int it = 0;
                    uint32_t v;
                    do { asm volatile("ld.acquire.gpu.global.u32 %0, [%1];" : "=r"(v) : "l"(g_cw + sl * 32) : "memory"); } while ((int)(v - cw_target) < 0 && ++it < 0x400000);
                    asm volatile("fence.proxy.async.global;" ::: "memory");
                    __syncwarp();
                }
                mbar_wait(BAR(B_EMPTY + slot), ph);
                __syncwarp();
                asm volatile(ELECT "mbarrier.arrive.expect_tx.shared::cta.b64 _, [%0], %1; }" ::"r"(fb), "r"(STAGE) : "memory");
                if ((w0 & 3) == 0) {
                    tma2d(dst, m0, c0, r0, fb);
                    tma2d(dst + HALF, m1, c1, r1, fb);
                } else if (w0 & 1) {
                    asm volatile(ELECT "cp.async.bulk.shared::cluster.global.mbarrier::complete_tx::bytes [%0], [%1], %2, [%3]; }"
                                 ::"r"(dst), "l"(reinterpret_cast<const char*>(g_wp) + (size_t)r0 * STAGE), "r"(STAGE), "r"(fb) : "memory");
                } else {
                    tma2d(dst, m0, c0, r0, fb); tma2d(dst + 7168, m0, c0, r1, fb);
                    tma2d(dst + HALF, m1, c0, r0, fb); tma2d(dst + HALF + 7168, m1, c0, r1, fb);
                }
                if (n == PACK) asm volatile(ELECT "mbarrier.arrive.shared::cta.b64 _, [%0]; }" ::"r"(BAR(slot)) : "memory");
                if (++slot == NST) { slot = 0; ph ^= 1; }
                }
            } else if (w == 1 && layer == 1) {
                constexpr int ps = PACK % NST;
                mbar_wait(BAR(B_PACK), 0);
                asm volatile("{ .reg .pred e; elect.sync _|e, 0xffffffff;\n"
                             "@e cp.async.bulk.global.shared::cta.bulk_group [%0], [%1], %2;\n"
                             "@e cp.async.bulk.commit_group;\n"
                             "@e cp.async.bulk.wait_group.read 0;\n"
                             "@e mbarrier.arrive.shared::cta.b64 _, [%3], 8;\n"
                             "@e cp.async.bulk.wait_group 0;\n"
                             "@e fence.proxy.async.global;\n"
                             "@e red.release.gpu.global.add.u32 [%4], 1; }"
                             ::"l"(reinterpret_cast<char*>(g_wp) + (size_t)(sl * 16 + tile) * STAGE), "r"(sb + ps * STAGE), "r"(STAGE), "r"(BAR(B_EMPTY + ps)), "l"(g_cw + sl * 32) : "memory");
                __syncwarp();
            }
            if (layer < 2) {
            const uint32_t tag = layer ^ 1;
            kseq++;
            bar_sync(7, 384);
            ASTAMP(0);
            if (tile < 15) {
                const int sq = lane >> 3, pk = 8 * w + (lane & (tile == 14 ? 3 : 7));
                uint32_t v[16];
                if (layer == 0) poll_cnt(g_c1 + ((sl * 8 + (w >> 1) * 4 + (tile >> 2)) * 16 + (lane & 15)) * 32, kseq);
                ASTAMP(1);
                poll4_kv<32>(v, g_kv1 + ((sl * 16 + tile) * 16 + 4 * sq) * 32 + pk, tag);
#pragma unroll
                for (int k = 0; k < 4; k++) {
                    float lo = (bf_lo(v[k]) + bf_lo(v[4 + k])) + (bf_lo(v[8 + k]) + bf_lo(v[12 + k]));
                    float hi = (bf_hi(v[k]) + bf_hi(v[4 + k])) + (bf_hi(v[8 + k]) + bf_hi(v[12 + k]));
                    lo += __shfl_xor_sync(0xffffffffu, lo, 8); hi += __shfl_xor_sync(0xffffffffu, hi, 8);
                    lo += __shfl_xor_sync(0xffffffffu, lo, 16); hi += __shfl_xor_sync(0xffffffffu, hi, 16);
                    v[k] = pack2(lo, hi);
                }
                if (sq == 0) st_pkt<0>(g_kv2 + sl * 512 + 32 * tile + pk, settag(v[0], tag), v[1], v[2], v[3]);
            }
            ASTAMP(2);
            {
                const int item = t128 < 112 ? t128 : 112 + (t128 & 3), d = item >> 1;
                const int cc = t128 < 112 ? 2 * (d >= 28) + (item & 1) : item - 112;
                const int r = t128 < 112 ? d : 56 + (cc >> 1) + 2 * ((t128 - 112) >> 2);
                uint32_t ra = sb + OFF_KVB + r * 128 + 4 * cc, rx = (r & 7) << 4;
                asm volatile("" : "+r"(ra), "+r"(rx));
                FOR14(asm volatile("st.shared.u32 [%0+%2], %1;" ::"r"((ra ^ 8) + (((t & 7) << 4) ^ rx)), "r"(0), "n"((t >> 3) * 8192) : "memory"));
                uint32_t v[16];
                asm volatile("" : "+r"(ra), "+r"(rx));
                poll4_kv<8>(v, g_kv2 + sl * 512 + (item >> 3) * 32 + (item & 7), tag);
                FOR14(asm volatile("st.shared.u32 [%0+%2], %1;" ::"r"(ra + (((t & 7) << 4) ^ rx)), "r"(v[t < 7 ? t : t + 1]), "n"((t >> 3) * 8192) : "memory"));
                fence_async();
            }
            bar_arrive(3, 384);
            ASTAMP(3);
            }
        }
    } else {
        asm volatile("setmaxnreg.inc.sync.aligned.u32 232;");
        const int tid = fresh_tid(), lane = tid & 31, t128 = tid & 127, g = lane >> 2, c = lane & 3;
        const int wu = __shfl_sync(0xffffffffu, tid >> 5, 0), w = wu & 3;
        uint4* const xp0 = g_ex + 3 * PLANE + ((tile * 2 + wgi) * 8) * 512 + w * 128 + lane;
        const uint32_t hbuf = sb + OFF_H + wgi * STAGE;
        uint32_t slot = 0, ph = 0, eb1 = 0, eb2 = 0, ackph = 0, rcvph = 0, gatph = 0, swp = 0;
        uint32_t ppid = 6;
#define cx(s) (reinterpret_cast<uint32_t*>(again(xp0) - lane + PL(1) + 112 + (s) * 512))
#define stp (again(xp0) - lane + g + PL(0) + 112)
        uint32_t seq = ld_word(cx(sl));
        uint32_t kseq = ld_word(g_c1 + ((sl * 8 + (tid >> 5)) * 16 + tile) * 32);
        uint32_t stag = ld_word(reinterpret_cast<const uint32_t*>(stp + sl * 512) + 3) & 1;
        asm volatile("barrier.cluster.wait.aligned;" ::: "memory");
        STAMP(1);
        uint32_t X[14];
        const uint32_t x0row = (w < 2 ? hbuf : sb + wgi * STAGE) + ((w & 1) * 16 + (lane & 15)) * 128;
        mbar_wait(BAR(wgi), 0);
        STAMP(51);
#pragma unroll
        for (int j = 0; j < 4; j++) {
            const int G = 7 * sl + min(2 * j + (lane >> 4), 6);
            uint32_t q2, q3;
            asm volatile("ldmatrix.sync.aligned.m8n8.x4.shared.b16 {%0,%1,%2,%3}, [%4];" : "=r"(X[4 * j]), "=r"(X[4 * j + 1]), "=r"(q2), "=r"(q3)
                         : "r"(x0row + (G >> 3) * 4096 + (((G ^ lane) & 7) << 4)) : "memory");
            if (j < 3) { X[(4 * j + 2) % 14] = q2; X[(4 * j + 3) % 14] = q3; }
        }
#define PUSH_SLICE(W)                                                                          \
    {                                                                                          \
        if (t128 == 0) mbar_expect_tx(BAR(B_RECV + wgi), 7168);                                \
        PUSH_BEGIN();                                                                          \
        const uint32_t ra = mapa(hbuf + 24576 + t128 * 16, hr ^ 1), rb = mapa(sb + OFF_XR + wgi * 3072, hr ^ 1), rbar = mapa(BAR(B_RECV + wgi), hr ^ 1); \
        st_async4(ra, W[0], W[1], W[2], W[3], rbar);                                           \
        st_async4(ra + 2048, W[4], W[5], W[6], W[7], rbar);                                    \
        st_async4(rb + t128 * 16, W[8], W[9], W[10], W[11], rbar);                             \
        asm volatile("st.async.weak.shared::cluster.mbarrier::complete_tx::bytes.v2.b32 [%0], {%1,%2}, [%3];" ::"r"(rb + 2048 + t128 * 8), "r"(W[12]), "r"(W[13]), "r"(rbar) : "memory"); \
    }
#define PULL_SLICE(W)                                                                          \
    {                                                                                          \
        uint32_t t0, t1;                                                                       \
        mbar_wait(BAR(B_RECV + wgi), rcvph);                                                   \
        rcvph ^= 1;                                                                            \
        lds4(&A[1][0], hbuf + 24576 + t128 * 16);                                              \
        lds4(&A[1][4], hbuf + 26624 + t128 * 16);                                              \
        lds4(&A[1][8], sb + OFF_XR + wgi * 3072 + t128 * 16);                                  \
        asm volatile("ld.shared.v2.u32 {%0,%1}, [%2];" : "=r"(t0), "=r"(t1) : "r"(sb + OFF_XR + wgi * 3072 + 2048 + t128 * 8) : "memory"); \
        _Pragma("unroll") for (int i = 0; i < 12; i++) A[0][i] = (i & 3) ? W[i] : W[i] & ~1u;  \
        A[1][0] &= ~1u; A[1][4] &= ~1u; A[1][8] &= ~1u;                                        \
        A[0][12] = (hr ? t0 : W[12]) & ~1u; A[0][13] = hr ? t1 : W[13];                        \
        A[1][12] = (hr ? W[12] : t0) & ~1u; A[1][13] = hr ? W[13] : t1;                        \
        asm volatile("" : RW4(A[0], 0), RW4(A[0], 4), RW4(A[0], 8), RW2(A[0], 12), RW4(A[1], 0), RW4(A[1], 4), RW4(A[1], 8), RW2(A[1], 12)); \
        swp = hr * 448;                                                                        \
    }
#define SWB(b, t, db, sh) ((b) == 0 && (t) < 6 ? ((t) < 3 ? db##p : db##m) : db)
#define DECL_DB(b, MK, lbo, sh) const uint64_t db = MK(0, lbo, R_ADJ), dbp = (b) == 0 ? MK(0, lbo, R_ADJ + (swp >> (sh))) : db, dbm = (b) == 0 ? MK(0, lbo, R_ADJ - (swp >> (sh))) : db;
#define EARLY 1
#define EARLYK 1
#define PPB 2
#define PP_WAIT() if (wgi == 1) { bar_sync(ppid, 256); ppid ^= 14; }
#define PP_GO() if (wgi == 0) { bar_arrive(ppid, 256); ppid ^= 14; }
#define GAT_ISSUE(base)                                                                        \
    {                                                                                          \
        const char* gs = reinterpret_cast<const char*>(g_ex + 3 * PLANE + (base) + (tile * 16 + wgi * 8 + 2 * kblk(pr, GB)) * 512 + w * 128); \
        const uint32_t gd = hbuf + w * 3584, gb = BAR(B_GAT + wu);                     \
        asm volatile("{ .reg .pred e; elect.sync _|e, 0xffffffff;\n"                           \
                     "@e mbarrier.arrive.expect_tx.shared::cta.b64 _, [%2], 3584;\n"           \
                     "@e cp.async.bulk.shared::cluster.global.mbarrier::complete_tx::bytes [%0], [%1], 1792, [%2];\n" \
                     "@e cp.async.bulk.shared::cluster.global.mbarrier::complete_tx::bytes [%0+1792], [%1+8192], 1792, [%2]; }" \
                     ::"r"(gd), "l"(gs), "r"(gb) : "memory");                                  \
        __syncwarp();                                                                          \
    }
#define GAT_FETCH()                                                                            \
    {                                                                                          \
        mbar_wait(BAR(B_GAT + wu), gatph);                                             \
        gatph ^= 1;                                                                            \
        const uint32_t ga = hbuf + w * 3584 + lane * 16;                                       \
        _Pragma("unroll") for (int s2 = 0; s2 < 2; s2++) {                                     \
            lds4(&A[2 * GB + s2][0], ga + s2 * 1792); lds4(&A[2 * GB + s2][4], ga + s2 * 1792 + 512); lds4(&A[2 * GB + s2][8], ga + s2 * 1792 + 1024); \
            asm volatile("ld.shared.v2.u32 {%0,%1}, [%2];" : "=r"(A[2 * GB + s2][12]), "=r"(A[2 * GB + s2][13]) : "r"(ga - lane * 8 + s2 * 1792 + 1536) : "memory"); \
        }                                                                                      \
    }
#define PT 3
#define PREP(b, t, remote)                                                                     \
    if constexpr ((b) < 3 && (t) == PT) {                                                      \
        wg_commit();                                                                           \
        STAMP(80 + 8 * (step & 1) + 2 * (b));                                                  \
        if constexpr (GB == 1 && (b) == 0) { if (remote) GAT_FETCH() }                         \
        if (remote) blk_check<((b) + 1) & 3>(A, BLK(xsrc, (b) + 1), lane, xtag);               \
        STAMP(81 + 8 * (step & 1) + 2 * (b));                                                  \
        if constexpr ((b) == 0) { if (remote) blk_load<3>(A, BLK(xsrc, 3), lane); }            \
        normalize<((b) + 1) & 3>(A, k0, k1);                                                   \
        asm volatile("" : RW4(A[(2 * (b) + 2) & 7], 0), RW4(A[(2 * (b) + 2) & 7], 4), RW4(A[(2 * (b) + 2) & 7], 8), RW2(A[(2 * (b) + 2) & 7], 12), \
                          RW4(A[(2 * (b) + 3) & 7], 0), RW4(A[(2 * (b) + 3) & 7], 4), RW4(A[(2 * (b) + 3) & 7], 8), RW2(A[(2 * (b) + 3) & 7], 12)); \
        wg_fence();                                                                            \
    }                                                                                          \
    if constexpr ((b) == 3 && ((t) == 0 || (t) == 6)) { STAMP(86 + 8 * (step & 1) + (t) / 6); }
#define BLK(base, b) ((base) + kblk(pr, b) * 1024)

#pragma unroll 1
        for (int step = 0; step < 4; step++) {
            const uint32_t tag = (step >> 1) ^ 1;
            const int so = (step >> 1) * 24 + (step & 1) * 12;
            (void)so;
            uint32_t A[8][14];
            uint4* const xsrc = xp0 + ((step & 1) ? PL(2) : PL(0));
            const uint32_t xtag = (step & 1) ? tag : ((seq >> 3) & 1) ^ 1;
            uint32_t xbits;
            {
                float st[4];
                slice_stats(X, st);
                stag ^= 1;
                xbits = x_bits(X);
                tag_slice(X, xtag);
                if (step) send_slice<0>(xsrc + sl * 512, lane, X);
                if (c == 0) st_pkt<0>(stp + sl * 512, __float_as_uint(st[0]), __float_as_uint(st[1]), __float_as_uint(st[2]), settag(__float_as_uint(st[3]), stag));
            }
            STAMP(2 + so);
            uint32_t sv[8];
            if (step == 0) {
                const int rr = lane & 7, hi = lane >> 4;
                const uint32_t rowa = (w < 2 ? hbuf : sb + wgi * STAGE) + ((w & 1) * 16 + (lane & 15)) * 128;
                uint32_t xr[8];
#pragma unroll
                for (int j = 0; j < 8; j++) xr[j] = rowa + ((((j + hi) ^ rr) & 7) << 4) + (j == 7 ? hi * 4096 : 0);
#define X0_BLOCK(b)                                                                            \
    FOR7(constexpr int G = 14 * (b) + (t < 3 ? 2 * t : (t < 6 ? 2 * t + 1 : 6));               \
         uint32_t q0, q1, q2, q3;                                                              \
         const uint32_t ad = t < 6 ? xr[G & 7] : rowa + ((G + 7 * hi) >> 3) * 4096 + ((((G + 7 * hi) ^ rr) & 7) << 4); \
         asm volatile("ldmatrix.sync.aligned.m8n8.x4.shared.b16 {%0,%1,%2,%3}, [%4+%5];" : "=r"(q0), "=r"(q1), "=r"(q2), "=r"(q3) \
                      : "r"(ad), "n"(t < 6 ? (G >> 3) * 4096 : 0) : "memory");                 \
         if (t < 3) { A[2 * (b)][4 * t] = q0; A[2 * (b)][4 * t + 1] = q1; A[2 * (b)][4 * t + 2] = q2; A[2 * (b)][4 * t + 3] = q3; } \
         else if (t < 6) { A[2 * (b) + 1][(4 * t - 12) & 15] = q0; A[2 * (b) + 1][((4 * t - 12) & 15) + 1] = q1; A[2 * (b) + 1][((4 * t - 12) & 15) + 2] = q2; A[2 * (b) + 1][((4 * t - 12) & 15) + 3] = q3; } \
         else { A[2 * (b)][12] = q0; A[2 * (b)][13] = q1; A[2 * (b) + 1][12] = q2; A[2 * (b) + 1][13] = q3; });
                X0_BLOCK(0) X0_BLOCK(1) X0_BLOCK(2) X0_BLOCK(3)
                mbar_wait(BAR(wgi ^ 1), 0);
                R_NEXT();
                R_NEXT();
                stat_load(sv, stp + c * 1024);
                stat_check(sv, stp + c * 1024, stag);
                STAMP(52 + step);
            } else {
                PUSH_SLICE(X)
                stat_load(sv, stp + c * 1024);
                kill<14>(A[2]); kill<14>(A[3]); kill<14>(A[4]); kill<14>(A[5]); kill<14>(A[6]); kill<14>(A[7]);
                PULL_SLICE(X)
                stat_check(sv, stp + c * 1024, stag);
                STAMP(52 + step);
                if (GB == 1) GAT_ISSUE((step & 1) ? PL(2) : PL(0))
                else { blk_load<1>(A, BLK(xsrc, 1), lane); if (GE) GAT_ISSUE((step & 1) ? PL(2) : PL(0)) }
            }
            LnCoef k0, k1;
            {
                k0 = ln_coef(__uint_as_float(sv[0]) + __uint_as_float(sv[4]), __uint_as_float(sv[1]) + __uint_as_float(sv[5]));
                k1 = ln_coef(__uint_as_float(sv[2]) + __uint_as_float(sv[6]), __uint_as_float(sv[3] & ~1u) + __uint_as_float(sv[7] & ~1u));
            }
            if (step) {
                if (GB == 2) { if (!GE) GAT_ISSUE((step & 1) ? PL(2) : PL(0)) }
                else blk_load<2>(A, BLK(xsrc, 2), lane);
            }
            STAMP(3 + so);
            GSTAMP(76 + step);

            if ((step & 1) == 0) {
                float tq[28];
                {
                    float av[28];
#define KV_BLOCK(b)                                                                           \
    if (GB == 2 && (b) == 1 && step) GAT_FETCH()                                                         \
    if ((b) == 2) PUSH_ACK();                                                                 \
    if (QE && (b) == 1) R_RELEASE(2);                                                         \
    if (QE && (b) == 2) { wg_wait<2>(); R_RELEASE(2); }                                       \
    R_WAIT();                                                                                 \
    if ((b) == PPK) { PP_WAIT() }                                                             \
    { DECL_DB(b, BASE128, 16, 0)                                                              \
    wg_fence();                                                                               \
    FOR7(mma_rs56<1, D128(0, t)>(tq, AQ(A, b, t), (b) + t > 0, SWB(b, t, db, 0));             \
         mma_rs56<1, D128(HALF, t)>(av, AQ(A, b, t), (b) + t > 0, SWB(b, t, db, 0));          \
         PREP(b, t, step)); }                                                                 \
    wg_commit();                                                                              \
    if ((b) == 3 && PPK < 4) { PP_GO() }                                                      \
    R_NEXT();
                    if (EARLYK == 0 || step == 0) R_RELEASE(2);
                    normalize<0>(A, k0, k1);
                    KV_BLOCK(0) KV_BLOCK(1) KV_BLOCK(2) KV_BLOCK(3)
                    wg_wait<0>();
                    if (lane < (QE ? 3 : NST)) mbar_arrive(BAR(B_EMPTY + (slot + NST - 1 - lane) % NST));
                    STAMP(4 + so);
                    WSUM(80 + 7 * (step >> 1));
                    const int m = lane >> 3, rr = lane & 7;
                    const uint32_t rowa = hbuf + 16384 + (w * 16 + rr + 8 * (m & 1)) * 128;
                    const uint32_t one = c == 0 ? 0x00003f80u : 0u;
                    if (step == 0) { bar_sync(wgi ? 9 : 1, 224); }
#pragma unroll
                    for (int j = 0; j < 4; j++) {
                        const uint32_t a = rowa + (((2 * j + (m >> 1)) ^ rr) << 4);
                        if (j < 3) stsm4(a, pack2(av[8 * j], av[8 * j + 1]), pack2(av[8 * j + 2], av[8 * j + 3]), pack2(av[8 * j + 4], av[8 * j + 5]), pack2(av[8 * j + 6], av[8 * j + 7]));
                        else stsm4(a, pack2(av[24], av[25]), pack2(av[26], av[27]), one, one);
                    }
                }
                uint32_t PH[28];
                int it = 1;
#pragma unroll 1
                do {
                    float pp[28];
                    phi_gemm(tq, pp);
                    dual_softmax(pp, PH);
                    if (((trips >> (it + 1)) & 1) == 0) continue;
                    {
                        const int m = lane >> 3, rr = lane & 7;
                        const uint32_t rowa = hbuf + (w * 16 + rr + 8 * (m & 1)) * 128;
#pragma unroll
                        for (int j = 0; j < 7; j++) {
                            const int cg = 2 * j + (m >> 1), hi = cg >= 7;
                            stsm4(rowa + hi * 8192 + (((cg - 7 * hi) ^ rr) << 4), PH[4 * j], PH[4 * j + 1], PH[4 * j + 2], PH[4 * j + 3]);
                        }
                    }
                    fence_async();
                    STAMP(5 + so);
#define Q_STAGE(b0)                                                                           \
    R_WAIT();                                                                                 \
    { DECL_DB(b0, BASE128, 16, 0)                                                             \
    wg_fence();                                                                               \
    FOR7(mma_rs56<1, D128(0, t)>(tq, AQ(A, b0, t), (b0) + t > 0, SWB(b0, t, db, 0)));         \
    FOR7(mma_rs56<1, D128(HALF, t)>(tq, AQ(A, (b0) + 1, t), 1, db)); }                        \
    wg_commit();                                                                              \
    R_NEXT();
                    if (QE && wgi == 0) { kill<28>(tq); Q_STAGE(0) Q_STAGE(2) wg_wait<1>(); R_RELEASE(2); wg_wait<0>(); R_RELEASE(1); }
                    bar_sync(2, 256);
                    float kv[28];
                    const uint64_t da = BASE128(OFF_H + 16384, 16, 0), dbk = BASE128(OFF_H, 16, wgi * 512);
                    wg_fence();
                    FOR8(constexpr uint64_t o = ((t >> 2) * STAGE + (t & 3) * 2048) >> 4; mma_ss56_tt<o, o>(kv, t > 0, da, dbk));
                    wg_commit();
                    wg_wait<0>();
#pragma unroll
                    for (int hf = 0; hf < 2; hf++) {
                        const int d = 16 * w + g + 8 * hf;
                        if ((d < 56 && (d >= 28) == (c >= 2)) || d == 56) {
                            const int item = d < 56 ? 2 * d + (c & 1) : 112 + c;
                            uint4* dst = g_kv1 + ((sl * 16 + (item >> 3)) * 16 + tile) * 32 + wgi * 16 + (item & 7);
#define KVW(i) pack2(kv[4 * (i) + 2 * hf], kv[4 * (i) + 2 * hf + 1])
                            st_pkt<0>(dst, settag(KVW(0), tag), KVW(1), KVW(2), KVW(3));
                            st_pkt<8>(dst, settag(KVW(4), tag), KVW(5), KVW(6), 0u);
                        }
                    }
                    __syncwarp();
                    kseq++;
                    if (lane == 0) st_word(g_c1 + ((sl * 8 + (tid >> 5)) * 16 + tile) * 32, kseq);
                    bar_arrive(7, 384);
                    STAMP(6 + so);
                    if (!QE || wgi == 1) { kill<28>(tq); Q_STAGE(0) Q_STAGE(2) wg_wait<1>(); R_RELEASE(2); wg_wait<0>(); R_RELEASE(1); }
                    STAMP(7 + so);
                    kill<28>(PH);
                } while (((trips >> (++it)) & 1));
                STAMP(8 + so);
                if (step) {
                    slice_load<PL(0)>(X, xp0 + sl * 512, lane);
                } else {
                    const uint32_t* xp = reinterpret_cast<const uint32_t*>(x_in + (size_t)(tile * 128 + wu * 16 + g) * 448 + 56 * sl + 2 * c);
#pragma unroll
                    for (int i = 0; i < 7; i++) { X[2 * i] = __ldg(xp + 4 * i); X[2 * i + 1] = __ldg(xp + 4 * i + 8 * 224); }
                }
                bar_sync(3, 384);
                STAMP(9 + so);
                const uint4* const osrc = xp0 + PL(1);
                {
                    float nm[32];
                    const uint64_t db = BASE128(OFF_KVB, 16, 0);
                    wg_fence();
                    FOR7(mma_rs64<0, ((t >> 2) * 8192 + (t & 3) * 32) / 16>(nm, PH[4 * t], PH[4 * t + 1], PH[4 * t + 2], PH[4 * t + 3], t > 0, db));
                    wg_commit();
                    wg_wait<0>();
                    const float i00 = rcp(nm[28] + 1e-6f), i01 = rcp(nm[29] + 1e-6f), i10 = rcp(nm[30] + 1e-6f), i11 = rcp(nm[31] + 1e-6f);
                    const float m0 = c >= 2 ? i01 : i00, m1 = c >= 2 ? i11 : i10;
                    uint32_t O[14];
#pragma unroll
                    for (int i = 0; i < 7; i++) {
                        const float f0 = i < 3 ? i00 : (i > 3 ? i01 : m0), f1 = i < 3 ? i10 : (i > 3 ? i11 : m1);
                        O[2 * i] = pack2(nm[4 * i] * f0, nm[4 * i + 1] * f0);
                        O[2 * i + 1] = pack2(nm[4 * i + 2] * f1, nm[4 * i + 3] * f1);
                    }
                    if (OST) { PP_WAIT() }
                    tag_slice(O, tag);
                    send_slice<PL(1)>(xp0 + sl * 512, lane, O);
                    seq++;
                    if (lane == 0) st_word(cx(sl), seq);
                    STAMP(10 + so);
                    PUSH_SLICE(O)
                    if (OST == 1) { PP_GO() }
                    const uint32_t cv = ld_word(cx(lane & 7));
                    PULL_SLICE(O)
                    check_cnt(cv, cx(lane & 7), seq);
                    if (OST == 2) { PP_GO() }
                    STAMP(56 + (step >> 1));
                    GAT_ISSUE(PL(1))
                    blk_load<3 - GB>(A, BLK(osrc, 3 - GB), lane);
                }
                float ao[28];
#define WO_BLOCK(b)                                                                           \
    if ((b) > 0) blk_check<b>(A, BLK(osrc, b), lane, tag);                                    \
    if (((b) & 1) == 0) R_WAIT();                                                             \
    { DECL_DB(b, BASE128, 16, 0)                                                              \
    wg_fence();                                                                               \
    FOR7(mma_rs56<1, D128(((b) & 1) * HALF, t)>(ao, AQ(A, b, t), (b) + t > 0, SWB(b, t, db, 0))); } \
    wg_commit();                                                                              \
    if ((b) & 1) R_NEXT();
                WO_BLOCK(0)
                STAMP(11 + so);
                blk_load<3>(A, BLK(osrc, 3), lane);
                if (GB == 1) GAT_FETCH()
                WO_BLOCK(1)
                if (GB == 2) GAT_FETCH()
                WO_BLOCK(2)
                PUSH_ACK();
                WO_BLOCK(3)
                wg_wait<0>();
                if (EARLY >= 1) R_RELEASE(2);
                if (EARLY >= 2) R_RELEASE(1);
                STAMP(12 + so);
                WSUM(86 + 7 * (step >> 1));
                x_fix(X, xbits);
#pragma unroll
                for (int i = 0; i < 14; i++) X[i] = pack2(bf_lo(X[i]) + ao[2 * i], bf_hi(X[i]) + ao[2 * i + 1]);
            } else {
                uint32_t H[56];
                float ag[64];
#define F1_EPI(dst, ng, ag)                                                                    \
    _Pragma("unroll") for (int i = 0; i < 2 * (ng); i++)                                       \
        (dst)[i] = pack2(geglu(ag[2 * i], ag[4 * (ng) + 2 * i]), geglu(ag[2 * i + 1], ag[4 * (ng) + 2 * i + 1]));
#define H_PUSH(h0, off) st_async4(rem_h + (off), H[h0], H[(h0) + 1], H[(h0) + 2], H[(h0) + 3], mapa(BAR(B_RECV2 + wgi), hr ^ 1));
#define F1_BLOCK(b, first)                                                                     \
    if ((first) && (b) < 2 && (b) >= EARLY) R_RELEASE(2);                                      \
    if (GB == 2 && (first) && (b) == 1) GAT_FETCH()                                                       \
    if ((first) && (b) == 2) PUSH_ACK();                                                       \
    R_WAIT();                                                                                  \
    if ((b) == ((first) ? PPF : PPB)) { PP_WAIT() }                                            \
    { DECL_DB(b, BASE128, HALF, 0)                                                             \
    wg_fence();                                                                                \
    FOR7(mma_rs128<1, D128(0, t)>(ag, AQ(A, b, t), (b) + t > 0, SWB(b, t, db, 0));             \
         if constexpr (first) { PREP(b, t, true) }); }                                         \
    wg_commit();                                                                               \
    if ((b) == 3) { PP_GO() }                                                                  \
    if ((b) > 0) { wg_wait<1>(); R_RELEASE(1); }       \
    R_NEXT();
                normalize<0>(A, k0, k1);
                F1_BLOCK(0, true) F1_BLOCK(1, true) F1_BLOCK(2, true) F1_BLOCK(3, true)
                if (t128 == 0) { mbar_expect_tx(BAR(B_RECV + wgi), 16384); mbar_expect_tx(BAR(B_RECV2 + wgi), 12288); }
                PUSH_BEGIN();
                wg_wait<0>();
                R_RELEASE(1);
                if (step == 1) R_NEXT();
                int p = 0;
#pragma unroll 1
                do {
                    STAMP(68 + p);
                    F1_EPI(H + 32, 8, ag)
                    STAMP(4 + p + so);
                    WSUM(81 + p + 7 * (step >> 1));
                    if (((trips >> (p + 1)) & 1) == 0) continue;
                    {
                        const uint32_t pk = (p ? hbuf + 16384 : sb + OFF_KVB + wgi * 8192) + w * 2048;
#pragma unroll
                        for (int k = 0; k < 4; k++) sts4(pk + k * 512 + lane * 16, H[32 + 4 * k], H[33 + 4 * k], H[34 + 4 * k], H[35 + 4 * k]);
                        fence_async();
                        __syncwarp();
                        asm volatile(ELECT "cp.async.bulk.shared::cluster.shared::cta.mbarrier::complete_tx::bytes [%0], [%1], 2048, [%2]; }"
                                     ::"r"(mapa(hbuf + p * 8192 + w * 2048, hr ^ 1)), "r"(pk), "r"(mapa(BAR(B_RECV + wgi), hr ^ 1)) : "memory");
                    }
                    kill<64>(ag);
                    F1_BLOCK(0, false) F1_BLOCK(1, false) F1_BLOCK(2, false) F1_BLOCK(3, false)
                    wg_wait<0>();
                    R_RELEASE(1);
                    kill<16>(H + 32);
                } while (((trips >> (++p)) & 1));
#pragma unroll
                for (int k = 0; k < 4; k++) lds4(H + 16 + 4 * k, hbuf + 16384 + w * 2048 + k * 512 + lane * 16);
                __syncwarp();
                if (lane == 0) asm volatile("mbarrier.arrive.shared::cluster.b64 _, [%0];" ::"r"(mapa(BAR(B_ACK2 + wgi), hr ^ 1)) : "memory");
                const uint32_t rem_h = mapa(hbuf + w * 2048 + lane * 16, hr ^ 1);
#define F1_LAST(b0)                                                                            \
    R_WAIT();                                                                                  \
    if (b0) { PP_WAIT() }                                                                      \
    { DECL_DB(b0, BASE64, HALF, 1)                                                             \
    wg_fence();                                                                                \
    FOR7(mma_rs64<1, D64(0, t)>(al, AQ(A, b0, t), (b0) + t > 0, SWB(b0, t, db, 1)));           \
    FOR7(mma_rs64<1, D64(7168, t)>(al, AQ(A, (b0) + 1, t), 1, db)); }                          \
    wg_commit();                                                                               \
    if (b0) { PP_GO() }                                                                        \
    R_NEXT();
                float al[32];
                F1_LAST(0)
                mbar_wait(BAR(B_RECV + wgi), rcvph);
                rcvph ^= 1;
                mbar_wait(BAR(B_ACK2 + wgi), step >> 1);
                H_PUSH(32, 16384) H_PUSH(36, 16896)
                F1_LAST(2)
                H_PUSH(40, 17408) H_PUSH(44, 17920)
                wg_wait<1>();
                R_RELEASE(2);
                wg_wait<0>();
                R_RELEASE(1);
                uint32_t HP[56];
#pragma unroll
                for (int k = 0; k < 4; k++) lds4(H + 4 * k, sb + OFF_KVB + wgi * 8192 + w * 2048 + k * 512 + lane * 16);
#pragma unroll
                for (int t = 0; t < 8; t++) lds4(HP + 4 * t, hbuf + (t >> 2) * 8192 + w * 2048 + (t & 3) * 512 + lane * 16);
                F1_EPI(H + 48, 4, al)
                H_PUSH(48, 24576 - w * 1024) H_PUSH(52, 25088 - w * 1024)
                STAMP(7 + so);
                WSUM(84 + 7 * (step >> 1));
                float acc[28];
                const uint32_t roA = hr ? 256u : 0u, roB = hr ? (uint32_t)-1536 : 0u;
                const uint32_t rpA = hr ? 0u : 256u, rpB = hr ? 0u : (uint32_t)-1536;
                float res[28];
                uint32_t v0[14], v1[14], P[14];
                const uint4* ps = xp0 + sl * 512;
#define F2_OWN_A()                                                                             \
    R_WAIT();                                                                                  \
    d0 = BASE128(0, 16, R_ADJ + roA); d1 = BASE128(0, 16, R_ADJ + roB);                        \
    wg_fence();                                                                                \
    FOR14(if constexpr (t < OT) mma_rs56<1, t * 128>(acc, H[4 * t], H[4 * t + 1], H[4 * t + 2], H[4 * t + 3], t > 0, d0)); \
    wg_commit();
#define F2_OWN_B()                                                                             \
    wg_fence();                                                                                \
    FOR14(if constexpr (t >= OT) mma_rs56<1, t * 128>(acc, H[4 * t], H[4 * t + 1], H[4 * t + 2], H[4 * t + 3], 1, t < 12 ? d0 : d1)); \
    wg_commit();                                                                               \
    R_NEXT();
#define F2_PEER()                                                                              \
    R_WAIT();                                                                                  \
    if (F2PP) { PP_WAIT() }                                                                    \
    d0 = BASE128(0, 16, R_ADJ + rpA); d1 = BASE128(0, 16, R_ADJ + rpB);                        \
    wg_fence();                                                                                \
    FOR14(mma_rs56<1, t * 128>(acc, HP[4 * t], HP[4 * t + 1], HP[4 * t + 2], HP[4 * t + 3], 1, t < 12 ? d0 : d1)); \
    wg_commit();                                                                               \
    if (F2PP) { PP_GO() }                                                                      \
    R_NEXT();
#define F2_TURN(u)                                                                             \
    wg_wait<1>();                                                                              \
    R_RELEASE(2);                                                                              \
    wg_wait<0>();                                                                              \
    R_RELEASE(1);                                                                              \
    _Pragma("unroll") for (int i = 0; i < 14; i++) P[i] = pack2(acc[2 * i], acc[2 * i + 1]);   \
    tag_slice(P, tag);                                                                         \
    asm volatile("" : RW4(P, 0), RW4(P, 4), RW4(P, 8), RW2(P, 12));                            \
    kill<28>(acc);                                                                             \
    F2_OWN_A()                                                                                 \
    if ((u) == 2) { slice_load<PL(3)>(v0, ps, lane); slice_load<PL(4)>(v1, ps, lane); } \
    send_slice<PL(3 + (u))>(xp0 + (2 * ((pr + (u) + 1) & 3) + hr) * 512, lane, P);             \
    seq++;                                                                                     \
    if (lane == 0) st_word(cx(sl), seq);                                                       \
    __syncwarp();                                                                              \
    STAMP(8 + (u) + so);                                                                       \
    F2_OWN_B()
                uint64_t d0, d1;
                F2_OWN_A()
                F2_OWN_B()
                R_WAIT();
                d0 = BASE128(0, 16, R_ADJ + rpA); d1 = BASE128(0, 16, R_ADJ + rpB);
                wg_fence();
                FOR8(mma_rs56<1, t * 128>(acc, HP[4 * t], HP[4 * t + 1], HP[4 * t + 2], HP[4 * t + 3], 1, d0));
                wg_commit();
                mbar_wait(BAR(B_RECV2 + wgi), step >> 1);
#pragma unroll
                for (int k = 0; k < 4; k++) lds4(HP + 32 + 4 * k, hbuf + 16384 + w * 2048 + k * 512 + lane * 16);
                lds4(HP + 48, hbuf + 24576 + w * 1024 + lane * 16);
                lds4(HP + 52, hbuf + 25088 + w * 1024 + lane * 16);
                if (step == 1) PUSH_ACK();
                wg_fence();
                FOR14(if constexpr (t >= 8) mma_rs56<1, t * 128>(acc, HP[4 * t], HP[4 * t + 1], HP[4 * t + 2], HP[4 * t + 3], 1, t < 12 ? d0 : d1));
                wg_commit();
                R_NEXT();
                F2_TURN(0)
                F2_PEER()
                F2_TURN(1)
                F2_PEER()
                F2_TURN(2)
                STAMP(64 + 8 * (step >> 1));
                slice_check<PL(3)>(v0, ps, lane, tag);
                slice_check<PL(4)>(v1, ps, lane, tag);
#pragma unroll
                for (int i = 0; i < 14; i++) { res[2 * i] = bf_lo(v0[i]) + bf_lo(v1[i]); res[2 * i + 1] = bf_hi(v0[i]) + bf_hi(v1[i]); }
                slice_load<PL(2)>(X, ps, lane);
                STAMP(65 + 8 * (step >> 1));
                const uint32_t cv = ld_word(cx(2 * ((pr + 1) & 3) + hr));
                F2_PEER()
                STAMP(66 + 8 * (step >> 1));
                check_cnt(cv, cx(2 * ((pr + 1) & 3) + hr), seq);
                STAMP(67 + 8 * (step >> 1));
                slice_load<PL(5)>(v0, ps, lane);
                x_fix(X, xbits);
                slice_check<PL(5)>(v0, ps, lane, tag);
#pragma unroll
                for (int i = 0; i < 14; i++) { res[2 * i] += bf_lo(v0[i]); res[2 * i + 1] += bf_hi(v0[i]); }
                STAMP(11 + so);
                wg_wait<0>();
                if (EARLYK >= 1) R_RELEASE(2);
                STAMP(12 + so);
                WSUM(85 + 7 * (step >> 1));
#pragma unroll
                for (int i = 0; i < 14; i++) X[i] = pack2(fmaf(res[2 * i] + acc[2 * i], 0.5f, bf_lo(X[i])), fmaf(res[2 * i + 1] + acc[2 * i + 1], 0.5f, bf_hi(X[i])));
            }
        }
        {
            const int m = lane >> 3, rr = lane & 7;
            const uint32_t ob = hbuf + w * 2048, rowa = ob + (rr + 8 * (m & 1)) * 112 + (m >> 1) * 16;
#pragma unroll
            for (int j = 0; j < 3; j++) stsm4(rowa + 32 * j, X[4 * j], X[4 * j + 1], X[4 * j + 2], X[4 * j + 3]);
            asm volatile("stmatrix.sync.aligned.m8n8.x2.shared.b16 [%0], {%1,%2};" ::"r"(ob + (rr + 8 * (m & 1)) * 112 + 96), "r"(X[12]), "r"(X[13]) : "memory");
            fence_async();
            __syncwarp();
            if (lane == 0) {
                asm volatile("cp.async.bulk.tensor.2d.global.shared::cta.bulk_group [%0, {%2, %3}], [%1];" ::"l"(&maps.out), "r"(ob), "r"(56 * sl), "r"(tile * 128 + (tid >> 5) * 16) : "memory");
                asm volatile("cp.async.bulk.commit_group;" ::: "memory");
                asm volatile("cp.async.bulk.wait_group.read 0;" ::: "memory");
            }
        }
        STAMP(50);
        GSTAMP(61);
        PDUMP();
    }
}

typedef CUresult (*EncodeFn)(CUtensorMap*, CUtensorMapDataType, cuuint32_t, void*, const cuuint64_t*, const cuuint64_t*, const cuuint32_t*,
                             const cuuint32_t*, CUtensorMapInterleave, CUtensorMapSwizzle, CUtensorMapL2promotion, CUtensorMapFloatOOBfill);

static void make_map(EncodeFn enc, CUtensorMap* m, const void* p, uint64_t cols, uint64_t rows, uint32_t bc, uint32_t br, CUtensorMapSwizzle sw) {
    cuuint64_t gd[2] = {cols, rows};
    cuuint64_t gs[1] = {cols * 2};
    cuuint32_t bd[2] = {bc, br};
    cuuint32_t es[2] = {1, 1};
    enc(m, CU_TENSOR_MAP_DATA_TYPE_BFLOAT16, 2, const_cast<void*>(p), gd, gs, bd, es, CU_TENSOR_MAP_INTERLEAVE_NONE, sw,
        CU_TENSOR_MAP_L2_PROMOTION_L2_128B, CU_TENSOR_MAP_FLOAT_OOB_FILL_NONE);
}

extern "C" void kernel_launch(void* const* d_in, const int* in_sizes, int n_in, void* d_out, int out_size) {
    (void)in_sizes; (void)n_in; (void)out_size;
    static EncodeFn enc = nullptr;
    static Scratch* scratch = nullptr;
    if (!enc) {
        void* fn = nullptr;
        cudaDriverEntryPointQueryResult qr;
        cudaGetDriverEntryPoint("cuTensorMapEncodeTiled", &fn, cudaEnableDefault, &qr);
        enc = (EncodeFn)fn;
        cudaGetSymbolAddress((void**)&scratch, g_scratch);
        cudaFuncSetAttribute(fused_kernel, cudaFuncAttributeMaxDynamicSharedMemorySize, SMEM_BYTES);
    }
    Maps maps;
    {
        cuuint64_t gd[3] = {64, 2048, 7};
        cuuint64_t gs[2] = {896, 128};
        cuuint32_t bd[3] = {64, 32, 7};
        cuuint32_t es[3] = {1, 1, 1};
        enc(&maps.x, CU_TENSOR_MAP_DATA_TYPE_BFLOAT16, 3, d_in[0], gd, gs, bd, es, CU_TENSOR_MAP_INTERLEAVE_NONE, CU_TENSOR_MAP_SWIZZLE_128B,
            CU_TENSOR_MAP_L2_PROMOTION_L2_128B, CU_TENSOR_MAP_FLOAT_OOB_FILL_NONE);
    }
    make_map(enc, &maps.out, d_out, 448, 2048, 56, 16, CU_TENSOR_MAP_SWIZZLE_NONE);
    make_map(enc, &maps.qkv, d_in[1], 1344, 448, 64, 112, CU_TENSOR_MAP_SWIZZLE_128B);
    make_map(enc, &maps.wo, d_in[3], 448, 448, 64, 112, CU_TENSOR_MAP_SWIZZLE_128B);
    make_map(enc, &maps.wg, d_in[5], 1792, 448, 64, 112, CU_TENSOR_MAP_SWIZZLE_128B);
    make_map(enc, &maps.wu, d_in[6], 1792, 448, 64, 112, CU_TENSOR_MAP_SWIZZLE_128B);
    make_map(enc, &maps.wg32, d_in[5], 1792, 448, 32, 112, CU_TENSOR_MAP_SWIZZLE_64B);
    make_map(enc, &maps.wu32, d_in[6], 1792, 448, 32, 112, CU_TENSOR_MAP_SWIZZLE_64B);
    make_map(enc, &maps.wd, d_in[7], 448, 1792, 64, 112, CU_TENSOR_MAP_SWIZZLE_128B);
    fused_kernel<<<128, 384, SMEM_BYTES>>>(scratch, (const __nv_bfloat16*)d_in[0], (const __nv_bfloat16*)d_in[2], 7, (const __nv_bfloat16*)d_in[5],
                                           (const __nv_bfloat16*)d_in[6], (const __nv_bfloat16*)d_in[7], maps);
}
```

```cpp
#include <cuda_runtime.h>
#include <cuda.h>
#include <cuda_bf16.h>
#include <stdint.h>
#include <type_traits>

#define MC 0
#define PPF 2
#define GE 0
#define ACAN 1
#define SPLIT0 1
#define OT 2
#define F2PP 0
#define PPK 2
#define QE 1
#define OST 1
#define GB 1
#define B3T 6
#define PP

namespace {

constexpr uint32_t STAGE = 28672, HALF = 14336;
constexpr int NST = 5;
constexpr uint32_t OFF_H = NST * STAGE;
constexpr uint32_t OFF_KVB = OFF_H + 2 * STAGE;
constexpr uint32_t OFF_WPHI = OFF_KVB + 16384;
constexpr uint32_t OFF_XR = OFF_WPHI + 7168;
constexpr uint32_t OFF_BAR = OFF_XR + 6144;
constexpr uint32_t SMEM_BYTES = OFF_BAR + 256 + 1536;
constexpr int B_EMPTY = NST, B_RECV = 2 * NST, B_RECV2 = B_RECV + 2, B_PACK = B_RECV2 + 2, B_GAT = B_PACK + 1, B_ACK = B_GAT + 8, B_ACK2 = B_ACK + 2, B_COUNT = B_ACK2 + 2;

constexpr int PACK = 14;

struct Maps { CUtensorMap x, qkv, wo, wg, wu, wg32, wu32, wd, out; };

}

constexpr int PLANE = 16 * 2 * 8 * 512;
struct Scratch {
    uint4 ex[6 * PLANE];
    uint4 kv1[8 * 16 * 16 * 32];
    uint4 kv2[8 * 512];
    uint32_t c1[8 * 8 * 16 * 32];
    uint32_t cw[8 * 32];
    uint4 wp[8 * 32 * (HALF / 16)];
};
__device__ __align__(1024) Scratch g_scratch;
#define g_ex (sc->ex)
#define g_kv1 (sc->kv1)
#define g_kv2 (sc->kv2)
#define g_c1 (sc->c1)
#define g_cw (sc->cw)
#define g_wp (sc->wp)
#define STAMP(i)
#define GSTAMP(i)
#define PDUMP()
#define ASTAMP(i)

namespace {

__device__ __forceinline__ int fresh_tid() { int t; asm volatile("mov.u32 %0, %%tid.x;" : "=r"(t)); return t; }
template <int N> __device__ __forceinline__ void kill(uint32_t* v) {
#pragma unroll
    for (int i = 0; i < N; i++) v[i] = 0;
}
template <int N> __device__ __forceinline__ void kill(float* v) {
#pragma unroll
    for (int i = 0; i < N; i++) v[i] = 0.f;
}
__device__ __forceinline__ uint32_t s2u(const void* p) { return (uint32_t)__cvta_generic_to_shared(p); }
__device__ __forceinline__ void mbar_init(uint32_t a, uint32_t c) { asm volatile("mbarrier.init.shared::cta.b64 [%0], %1;" ::"r"(a), "r"(c) : "memory"); }
__device__ __forceinline__ void mbar_expect_tx(uint32_t a, uint32_t b) { asm volatile("mbarrier.arrive.expect_tx.shared::cta.b64 _, [%0], %1;" ::"r"(a), "r"(b) : "memory"); }
__device__ __forceinline__ void mbar_arrive(uint32_t a) { asm volatile("mbarrier.arrive.shared::cta.b64 _, [%0];" ::"r"(a) : "memory"); }
#define GIVE_UP(id) "trap;\n"
#define SPIN_MAX "0x400000"
#define SPIN_TAIL(id) "add.u32 n, n, 1;\n setp.lt.u32 p, n, " SPIN_MAX ";\n @p bra.uni LP;\n" GIVE_UP(id) " DN:\n }"
__device__ __forceinline__ void mbar_wait(uint32_t a, uint32_t ph) {
    asm volatile("{ .reg .pred p; .reg .b32 n; mov.u32 n, 0;\n LP:\n"
                 "mbarrier.try_wait.parity.shared::cta.b64 p, [%0], %1;\n @p bra DN;\n"
                 "add.u32 n, n, 1;\n setp.lt.u32 p, n, " SPIN_MAX ";\n @p bra LP;\n"
                 GIVE_UP("")
                 " DN:\n }" ::"r"(a), "r"(ph) : "memory");
}
#define ELECT "{ .reg .pred e; elect.sync _|e, 0xffffffff; @e "
__device__ __forceinline__ void tma2d(uint32_t dst, const CUtensorMap* m, int c0, int c1, uint32_t bar) {
    asm volatile(ELECT "cp.async.bulk.tensor.2d.shared::cluster.global.mbarrier::complete_tx::bytes [%0], [%1, {%3, %4}], [%2]; }" ::"r"(dst), "l"(m), "r"(bar), "r"(c0), "r"(c1) : "memory");
}
__device__ __forceinline__ void tma3x(uint32_t dst, const CUtensorMap* m, int row, uint32_t bar) {
    asm volatile(ELECT "cp.async.bulk.tensor.3d.shared::cluster.global.mbarrier::complete_tx::bytes [%0], [%1, {0, %3, 0}], [%2]; }" ::"r"(dst), "l"(m), "r"(bar), "r"(row) : "memory");
}
template <int OFF>
__device__ __forceinline__ void ld_pkt(uint32_t* v, const uint4* p) {
    asm volatile("{ .reg .b128 t; ld.relaxed.gpu.global.b128 t, [%4+%5]; mov.b128 {%0,%1,%2,%3}, t; }" : "=r"(v[0]), "=r"(v[1]), "=r"(v[2]), "=r"(v[3]) : "l"(p), "n"(OFF * 16) : "memory");
}
template <int OFF>
__device__ __forceinline__ void st_pkt(uint4* p, uint32_t a, uint32_t b, uint32_t c, uint32_t d) {
    asm volatile("{ .reg .b128 t; mov.b128 t, {%1,%2,%3,%4}; st.relaxed.gpu.global.b128 [%0+%5], t; }" ::"l"(p), "r"(a), "r"(b), "r"(c), "r"(d), "n"(OFF * 16) : "memory");
}
__device__ __forceinline__ uint32_t pack2(float lo, float hi) {
    uint32_t r;
    asm("cvt.rn.bf16x2.f32 %0, %1, %2;" : "=r"(r) : "f"(hi), "f"(lo));
    return r;
}
__device__ __forceinline__ float bf_lo(uint32_t w) { return __uint_as_float(w << 16); }
__device__ __forceinline__ float bf_hi(uint32_t w) { return __uint_as_float(w & 0xffff0000u); }
__device__ __forceinline__ uint32_t settag(uint32_t w, uint32_t tag) { return (w & ~1u) | tag; }
__device__ __forceinline__ float ex2(float x) { float y; asm("ex2.approx.ftz.f32 %0, %1;" : "=f"(y) : "f"(x)); return y; }
__device__ __forceinline__ float rcp(float x) { float y; asm("rcp.approx.ftz.f32 %0, %1;" : "=f"(y) : "f"(x)); return y; }
__device__ __forceinline__ float tanh_hw(float x) { float y; asm("tanh.approx.f32 %0, %1;" : "=f"(y) : "f"(x)); return y; }
__device__ __forceinline__ void stsm4(uint32_t addr, uint32_t a, uint32_t b, uint32_t c, uint32_t d) {
    asm volatile("stmatrix.sync.aligned.m8n8.x4.shared.b16 [%0], {%1,%2,%3,%4};" ::"r"(addr), "r"(a), "r"(b), "r"(c), "r"(d) : "memory");
}
__device__ __forceinline__ void fence_async() { asm volatile("fence.proxy.async.shared::cta;" ::: "memory"); }
__device__ __forceinline__ void bar_sync(int id, int n) { asm volatile("bar.sync %0, %1;" ::"r"(id), "r"(n) : "memory"); }
__device__ __forceinline__ void bar_arrive(int id, int n) { asm volatile("bar.arrive %0, %1;" ::"r"(id), "r"(n) : "memory"); }
__device__ __forceinline__ void wg_fence() { asm volatile("wgmma.fence.sync.aligned;" ::: "memory"); }
__device__ __forceinline__ void wg_commit() { asm volatile("wgmma.commit_group.sync.aligned;" ::: "memory"); }
template <int N> __device__ __forceinline__ void wg_wait() { asm volatile("wgmma.wait_group.sync.aligned %0;" ::"n"(N) : "memory"); }

constexpr uint32_t SB0 = 1024;
__host__ __device__ constexpr uint32_t dlo(uint32_t off, uint32_t lbo) { return ((SB0 + off) >> 4) | ((lbo >> 4) << 16); }
__host__ __device__ constexpr uint32_t dhi(uint32_t sbo, uint32_t sw) { return (sbo >> 4) | (sw << 30); }
__device__ __forceinline__ uint64_t dbase(uint32_t lo, uint32_t hi) { uint64_t d; asm volatile("mov.b64 %0, {%1, %2};" : "=l"(d) : "r"(lo), "r"(hi)); return d; }
#define BASE128(off, lbo, adj) dbase(dlo(off, lbo) + (adj), dhi(1024, 1))
#define BASE64(off, lbo, adj) dbase(dlo(off, lbo) + (adj), dhi(512, 2))

#define ACC4(d, o) "+f"(d[o]), "+f"(d[o + 1]), "+f"(d[o + 2]), "+f"(d[o + 3])
#define ACC28(d) ACC4(d, 0), ACC4(d, 4), ACC4(d, 8), ACC4(d, 12), ACC4(d, 16), ACC4(d, 20), ACC4(d, 24)
#define ACC32(d, o) ACC4(d, o), ACC4(d, o + 4), ACC4(d, o + 8), ACC4(d, o + 12), ACC4(d, o + 16), ACC4(d, o + 20), ACC4(d, o + 24), ACC4(d, o + 28)

template <int TB, uint64_t D>
__device__ __forceinline__ void mma_rs56(float* d, uint32_t a0, uint32_t a1, uint32_t a2, uint32_t a3, int sd, uint64_t base) {
    asm volatile("{ .reg .pred p; .reg .b64 db; setp.ne.b32 p, %32, 0; add.u64 db, %33, %34;\n"
                 "wgmma.mma_async.sync.aligned.m64n56k16.f32.bf16.bf16 "
                 "{%0,%1,%2,%3,%4,%5,%6,%7,%8,%9,%10,%11,%12,%13,%14,%15,%16,%17,%18,%19,%20,%21,%22,%23,%24,%25,%26,%27}, "
                 "{%28,%29,%30,%31}, db, p, 1, 1, %35; }\n"
                 : ACC28(d)
                 : "r"(a0), "r"(a1), "r"(a2), "r"(a3), "r"(sd), "l"(base), "n"(D), "n"(TB));
}
template <int TB, uint64_t D>
__device__ __forceinline__ void mma_rs64(float* d, uint32_t a0, uint32_t a1, uint32_t a2, uint32_t a3, int sd, uint64_t base) {
    asm volatile("{ .reg .pred p; .reg .b64 db; setp.ne.b32 p, %36, 0; add.u64 db, %37, %38;\n"
                 "wgmma.mma_async.sync.aligned.m64n64k16.f32.bf16.bf16 "
                 "{%0,%1,%2,%3,%4,%5,%6,%7,%8,%9,%10,%11,%12,%13,%14,%15,%16,%17,%18,%19,%20,%21,%22,%23,%24,%25,%26,%27,%28,%29,%30,%31}, "
                 "{%32,%33,%34,%35}, db, p, 1, 1, %39; }\n"
                 : ACC32(d, 0)
                 : "r"(a0), "r"(a1), "r"(a2), "r"(a3), "r"(sd), "l"(base), "n"(D), "n"(TB));
}
template <int TB, uint64_t D>
__device__ __forceinline__ void mma_rs128(float* d, uint32_t a0, uint32_t a1, uint32_t a2, uint32_t a3, int sd, uint64_t base) {
    asm volatile("{ .reg .pred p; .reg .b64 db; setp.ne.b32 p, %68, 0; add.u64 db, %69, %70;\n"
                 "wgmma.mma_async.sync.aligned.m64n128k16.f32.bf16.bf16 "
                 "{%0,%1,%2,%3,%4,%5,%6,%7,%8,%9,%10,%11,%12,%13,%14,%15,%16,%17,%18,%19,%20,%21,%22,%23,%24,%25,%26,%27,%28,%29,%30,%31,%32,%33,%34,%35,%36,%37,%38,%39,%40,%41,%42,%43,%44,%45,%46,%47,%48,%49,%50,%51,%52,%53,%54,%55,%56,%57,%58,%59,%60,%61,%62,%63}, "
                 "{%64,%65,%66,%67}, db, p, 1, 1, %71; }\n"
                 : ACC32(d, 0), ACC32(d, 32)
                 : "r"(a0), "r"(a1), "r"(a2), "r"(a3), "r"(sd), "l"(base), "n"(D), "n"(TB));
}
template <uint64_t DA, uint64_t DB>
__device__ __forceinline__ void mma_ss56_tt(float* d, int sd, uint64_t ba, uint64_t bb) {
    asm volatile("{ .reg .pred p; .reg .b64 da, db; setp.ne.b32 p, %28, 0; add.u64 da, %29, %31; add.u64 db, %30, %32;\n"
                 "wgmma.mma_async.sync.aligned.m64n56k16.f32.bf16.bf16 "
                 "{%0,%1,%2,%3,%4,%5,%6,%7,%8,%9,%10,%11,%12,%13,%14,%15,%16,%17,%18,%19,%20,%21,%22,%23,%24,%25,%26,%27}, "
                 "da, db, p, 1, 1, 1, 1; }\n"
                 : ACC28(d)
                 : "r"(sd), "l"(ba), "l"(bb), "n"(DA), "n"(DB));
}
template <int... I> struct Seq {};
template <class F, int... I> __device__ __forceinline__ void static_for_impl(F&& f, Seq<I...>) { (f(std::integral_constant<int, I>{}), ...); }
#define FOR7(...) static_for_impl([&](auto T_) { constexpr int t = decltype(T_)::value; __VA_ARGS__; }, Seq<0, 1, 2, 3, 4, 5, 6>{})
#define FOR8(...) static_for_impl([&](auto T_) { constexpr int t = decltype(T_)::value; __VA_ARGS__; }, Seq<0, 1, 2, 3, 4, 5, 6, 7>{})
#define FOR14(...) static_for_impl([&](auto T_) { constexpr int t = decltype(T_)::value; __VA_ARGS__; }, Seq<0, 1, 2, 3, 4, 5, 6, 7, 8, 9, 10, 11, 12, 13>{})

__device__ __forceinline__ int kblk(int p, int b) { return b == 0 ? p : b - (b <= p); }
__host__ __device__ constexpr int krow(int t) { return t < 3 ? 16 * t : (t < 6 ? 56 + 16 * (t - 3) : 48); }
#define AQ(A, b, t) ((t) < 3 ? A[2 * (b)][4 * (t)] : (t) < 6 ? A[2 * (b) + 1][4 * ((t) - 3)] : A[2 * (b)][12]), \
                    ((t) < 3 ? A[2 * (b)][4 * (t) + 1] : (t) < 6 ? A[2 * (b) + 1][4 * ((t) - 3) + 1] : A[2 * (b)][13]), \
                    ((t) < 3 ? A[2 * (b)][4 * (t) + 2] : (t) < 6 ? A[2 * (b) + 1][4 * ((t) - 3) + 2] : A[2 * (b) + 1][12]), \
                    ((t) < 3 ? A[2 * (b)][4 * (t) + 3] : (t) < 6 ? A[2 * (b) + 1][4 * ((t) - 3) + 3] : A[2 * (b) + 1][13])
#define D128(off, t) ((uint64_t)(((off) + krow(t) * 128) >> 4) + ((uint64_t)((t) == 6 ? (7168 - 1024) >> 4 : 0) << 32))
#define D64(off, t) ((uint64_t)(((off) + krow(t) * 64) >> 4) + ((uint64_t)((t) == 6 ? (3584 - 512) >> 4 : 0) << 32))

#define PL(k) (((k) - 3) * PLANE)
__device__ __forceinline__ void st_word(uint32_t* p, uint32_t v) { asm volatile("st.relaxed.gpu.global.u32 [%0], %1;" ::"l"(p), "r"(v) : "memory"); }
__device__ __forceinline__ uint32_t ld_word(const uint32_t* p) { uint32_t v; asm volatile("ld.relaxed.gpu.global.u32 %0, [%1];" : "=r"(v) : "l"(p) : "memory"); return v; }
__device__ __forceinline__ void tag_slice(uint32_t* w, uint32_t tag) { w[0] = settag(w[0], tag); w[4] = settag(w[4], tag); w[8] = settag(w[8], tag); w[12] = settag(w[12], tag); }
template <int O>
__device__ __forceinline__ void send_slice(uint4* dst, int lane, const uint32_t* w) {
    st_pkt<O>(dst, w[0], w[1], w[2], w[3]);
    st_pkt<O + 32>(dst, w[4], w[5], w[6], w[7]);
    st_pkt<O + 64>(dst, w[8], w[9], w[10], w[11]);
    asm volatile("{ .reg .b64 t; mov.b64 t, {%1,%2}; st.relaxed.gpu.global.b64 [%0+%3], t; }" ::"l"((char*)dst - lane * 8), "r"(w[12]), "r"(w[13]), "n"(16 * (O + 96)) : "memory");
}
#define RW4(v, o) "+r"(v[o]), "+r"(v[(o) + 1]), "+r"(v[(o) + 2]), "+r"(v[(o) + 3])
#define RW2(v, o) "+r"(v[o]), "+r"(v[(o) + 1])
#define WR4(v, o) "=&r"(v[o]), "=&r"(v[(o) + 1]), "=&r"(v[(o) + 2]), "=&r"(v[(o) + 3])
#define LDP(a, b, c, d, addr, off) "ld.relaxed.gpu.global.b128 q, [" addr "+" off "];\n mov.b128 {" a "," b "," c "," d "}, q;\n"
#define LDH(a, b, addr, off) "ld.relaxed.gpu.global.b64 h, [" addr "+" off "];\n mov.b64 {" a "," b "}, h;\n"
#define VOTE_OK "and.b32 t, t, 1;\n setp.ne.u32 p, t, 0;\n vote.sync.any.pred p, p, 0xffffffff;\n @!p bra.uni DN;\n"
#define CHK(x, tag) "lop3.b32 t, " x ", " tag ", t, 0xBE;\n"
__device__ __forceinline__ void check_cnt(uint32_t v, const uint32_t* p, uint32_t target) {
    asm volatile("{ .reg .pred p; .reg .b32 n, t; mov.u32 n, 0; mov.u32 t, %2;\n LP:\n"
                 "sub.s32 t, t, %1;\n setp.lt.s32 p, t, 0;\n vote.sync.any.pred p, p, 0xffffffff;\n @!p bra.uni DN;\n ld.relaxed.gpu.global.u32 t, [%0];\n" SPIN_TAIL("7")
                 ::"l"(p), "r"(target), "r"(v) : "memory");
}
__device__ __forceinline__ void poll_cnt(const uint32_t* p, uint32_t target) {
    asm volatile("{ .reg .pred p; .reg .b32 n, t; mov.u32 n, 0;\n LP:\n"
                 "ld.relaxed.gpu.global.u32 t, [%0];\n sub.s32 t, t, %1;\n setp.lt.s32 p, t, 0;\n vote.sync.any.pred p, p, 0xffffffff;\n @!p bra.uni DN;\n" SPIN_TAIL("1")
                 ::"l"(p), "r"(target) : "memory");
}
template <int STR>
__device__ __forceinline__ void poll4_kv(uint32_t* v, const uint4* p, uint32_t tag) {
    asm volatile("{ .reg .pred p; .reg .b32 n, t; .reg .b128 q; mov.u32 n, 0;\n LP:\n"
                 LDP("%0", "%1", "%2", "%3", "%16", "0") LDP("%4", "%5", "%6", "%7", "%16", "%18")
                 LDP("%8", "%9", "%10", "%11", "%16", "%19") LDP("%12", "%13", "%14", "%15", "%16", "%20")
                 "xor.b32 t, %0, %17;\n" CHK("%4", "%17") CHK("%8", "%17") CHK("%12", "%17") VOTE_OK SPIN_TAIL("2")
                 : WR4(v, 0), WR4(v, 4), WR4(v, 8), WR4(v, 12)
                 : "l"(p), "r"(tag), "n"(16 * STR), "n"(32 * STR), "n"(48 * STR)
                 : "memory");
}
template <int B>
__device__ __forceinline__ void blk_load(uint32_t (&A)[8][14], const uint4* src, int lane) {
    ld_pkt<0>(&A[2 * B][0], src); ld_pkt<32>(&A[2 * B][4], src); ld_pkt<64>(&A[2 * B][8], src);
    ld_pkt<512>(&A[2 * B + 1][0], src); ld_pkt<544>(&A[2 * B + 1][4], src); ld_pkt<576>(&A[2 * B + 1][8], src);
    asm volatile("{ .reg .b64 h;\n" LDH("%0", "%1", "%4", "1536") LDH("%2", "%3", "%4", "9728") "}"
                 : "=&r"(A[2 * B][12]), "=&r"(A[2 * B][13]), "=&r"(A[2 * B + 1][12]), "=&r"(A[2 * B + 1][13])
                 : "l"((const char*)src - lane * 8) : "memory");
}
template <int B>
__device__ __forceinline__ void blk_check(uint32_t (&A)[8][14], const uint4* src, int lane, uint32_t tag) {
    asm volatile("{ .reg .pred p; .reg .b32 n, t; .reg .b128 q; .reg .b64 h, a8; mov.u32 n, 0;\n LP:\n"
                 "xor.b32 t, %0, %30;\n" CHK("%4", "%30") CHK("%8", "%30") CHK("%12", "%30") CHK("%16", "%30") CHK("%20", "%30") CHK("%24", "%30") CHK("%26", "%30") VOTE_OK
                 LDP("%0", "%1", "%2", "%3", "%28", "0") LDP("%4", "%5", "%6", "%7", "%28", "512") LDP("%8", "%9", "%10", "%11", "%28", "1024")
                 LDP("%12", "%13", "%14", "%15", "%28", "8192") LDP("%16", "%17", "%18", "%19", "%28", "8704") LDP("%20", "%21", "%22", "%23", "%28", "9216")
                 "mad.wide.s32 a8, %29, -8, %28;\n" LDH("%24", "%25", "a8", "1536") LDH("%26", "%27", "a8", "9728") SPIN_TAIL("3")
                 "\n and.b32 %0, %0, -2; and.b32 %4, %4, -2; and.b32 %8, %8, -2; and.b32 %12, %12, -2; and.b32 %16, %16, -2; and.b32 %20, %20, -2; and.b32 %24, %24, -2; and.b32 %26, %26, -2;"
                 : RW4(A[2 * B], 0), RW4(A[2 * B], 4), RW4(A[2 * B], 8), RW4(A[2 * B + 1], 0), RW4(A[2 * B + 1], 4), RW4(A[2 * B + 1], 8),
                   RW2(A[2 * B], 12), RW2(A[2 * B + 1], 12)
                 : "l"(src), "r"(lane), "r"(tag)
                 : "memory");
}
__device__ __forceinline__ void st_async4(uint32_t a, uint32_t x, uint32_t y, uint32_t z, uint32_t w, uint32_t bar) {
    asm volatile("st.async.weak.shared::cluster.mbarrier::complete_tx::bytes.v4.b32 [%0], {%1,%2,%3,%4}, [%5];" ::"r"(a), "r"(x), "r"(y), "r"(z), "r"(w), "r"(bar) : "memory");
}
__device__ __forceinline__ uint32_t mapa(uint32_t a, uint32_t cta) { uint32_t r; asm("mapa.shared::cluster.u32 %0, %1, %2;" : "=r"(r) : "r"(a), "r"(cta)); return r; }
__device__ __forceinline__ void stat_load(uint32_t* v, const uint4* p) { ld_pkt<0>(v, p); ld_pkt<512>(v + 4, p); }
__device__ __forceinline__ void stat_check(uint32_t* v, const uint4* p, uint32_t tag) {
    asm volatile("{ .reg .pred p; .reg .b32 n, t; .reg .b128 q; mov.u32 n, 0;\n LP:\n"
                 "xor.b32 t, %3, %9;\n" CHK("%7", "%9") VOTE_OK
                 LDP("%0", "%1", "%2", "%3", "%8", "0") LDP("%4", "%5", "%6", "%7", "%8", "8192") SPIN_TAIL("4")
                 : RW4(v, 0), RW4(v, 4) : "l"(p), "r"(tag) : "memory");
}
__device__ __forceinline__ uint32_t x_bits(const uint32_t* X) {
    uint32_t r;
    asm volatile("{ .reg .b32 a, b; prmt.b32 a, %1, %2, 0x0040; prmt.b32 b, %3, %4, 0x0040; prmt.b32 %0, a, b, 0x5410; }" : "=r"(r) : "r"(X[0]), "r"(X[4]), "r"(X[8]), "r"(X[12]));
    return r;
}
template <int O>
__device__ __forceinline__ void slice_load(uint32_t* v, const uint4* p, int lane) {
    ld_pkt<O>(v, p); ld_pkt<O + 32>(v + 4, p); ld_pkt<O + 64>(v + 8, p);
    asm volatile("{ .reg .b64 h;\n" LDH("%0", "%1", "%2", "%3") "}" : "=r"(v[12]), "=r"(v[13]) : "l"((const char*)p - lane * 8), "n"(16 * (O + 96)) : "memory");
}
template <int O>
__device__ __forceinline__ void slice_check(uint32_t* v, const uint4* p, int lane, uint32_t tag) {
    asm volatile("{ .reg .pred p; .reg .b32 n, t; .reg .b128 q; .reg .b64 h; mov.u32 n, 0;\n LP:\n"
                 "xor.b32 t, %0, %16;\n" CHK("%4", "%16") CHK("%8", "%16") CHK("%12", "%16") VOTE_OK
                 LDP("%0", "%1", "%2", "%3", "%14", "%17") LDP("%4", "%5", "%6", "%7", "%14", "%18") LDP("%8", "%9", "%10", "%11", "%14", "%19")
                 LDH("%12", "%13", "%15", "%20") SPIN_TAIL("5")
                 : RW4(v, 0), RW4(v, 4), RW4(v, 8), RW2(v, 12)
                 : "l"(p), "l"((const char*)p - lane * 8), "r"(tag), "n"(16 * O), "n"(16 * (O + 32)), "n"(16 * (O + 64)), "n"(16 * (O + 96))
                 : "memory");
}
__device__ __forceinline__ void x_fix(uint32_t* X, uint32_t bits) {
    X[0] = __byte_perm(X[0], bits, 0x3214); X[4] = __byte_perm(X[4], bits, 0x3215); X[8] = __byte_perm(X[8], bits, 0x3216); X[12] = __byte_perm(X[12], bits, 0x3217);
}
__device__ __forceinline__ void sts4(uint32_t a, uint32_t x, uint32_t y, uint32_t z, uint32_t w) {
    asm volatile("st.shared.v4.u32 [%0], {%1,%2,%3,%4};" ::"r"(a), "r"(x), "r"(y), "r"(z), "r"(w) : "memory");
}
__device__ __forceinline__ void lds4(uint32_t* v, uint32_t a) {
    asm volatile("ld.shared.v4.u32 {%0,%1,%2,%3}, [%4];" : "=r"(v[0]), "=r"(v[1]), "=r"(v[2]), "=r"(v[3]) : "r"(a) : "memory");
}
struct LnCoef { uint32_t hi, lo, sh; };
__device__ __forceinline__ LnCoef ln_coef(float sum, float sq) {
    sum += __shfl_xor_sync(0xffffffffu, sum, 1); sq += __shfl_xor_sync(0xffffffffu, sq, 1);
    sum += __shfl_xor_sync(0xffffffffu, sum, 2); sq += __shfl_xor_sync(0xffffffffu, sq, 2);
    const float mean = sum * (1.f / 448.f);
    const float var = fmaxf(fmaf(-mean, mean, sq * (1.f / 448.f)), 0.f);
    const float sc = rsqrtf(var + 1e-5f);
    LnCoef r;
    r.hi = pack2(sc, sc);
    const float lo = sc - bf_lo(r.hi), sh = -mean * sc;
    r.lo = pack2(lo, lo);
    r.sh = pack2(sh, sh);
    return r;
}
template <int B>
__device__ __forceinline__ void normalize(uint32_t (&A)[8][14], const LnCoef& c0, const LnCoef& c1) {
#pragma unroll
    for (int s = 2 * B; s < 2 * B + 2; s++)
#pragma unroll
        for (int i = 0; i < 14; i++) {
            const LnCoef& k = (i & 1) ? c1 : c0;
            asm("{ .reg .b32 t; fma.rn.bf16x2 t, %0, %2, %3; fma.rn.bf16x2 %0, %0, %1, t; }" : "+r"(A[s][i]) : "r"(k.hi), "r"(k.lo), "r"(k.sh));
        }
}
__device__ __forceinline__ void slice_stats(const uint32_t* w, float* st) {
    float a = 0.f, b = 0.f, p = 0.f, q = 0.f;
#pragma unroll
    for (int i = 0; i < 7; i++) {
        const float e0 = bf_lo(w[2 * i]), e1 = bf_hi(w[2 * i]), e2 = bf_lo(w[2 * i + 1]), e3 = bf_hi(w[2 * i + 1]);
        a += e0 + e1; b += e2 + e3;
        p = fmaf(e0, e0, p); p = fmaf(e1, e1, p); q = fmaf(e2, e2, q); q = fmaf(e3, e3, q);
    }
    a += __shfl_xor_sync(0xffffffffu, a, 1); p += __shfl_xor_sync(0xffffffffu, p, 1); b += __shfl_xor_sync(0xffffffffu, b, 1); q += __shfl_xor_sync(0xffffffffu, q, 1);
    a += __shfl_xor_sync(0xffffffffu, a, 2); p += __shfl_xor_sync(0xffffffffu, p, 2); b += __shfl_xor_sync(0xffffffffu, b, 2); q += __shfl_xor_sync(0xffffffffu, q, 2);
    st[0] = a; st[1] = p; st[2] = b; st[3] = q;
}
__device__ __forceinline__ void dual_softmax(const float* p, uint32_t* out) {
    constexpr float L = 1.4426950408889634f;
#pragma unroll
    for (int r = 0; r < 2; r++) {
        float mx = fmaxf(p[2 * r], p[2 * r + 1]), mn = fminf(p[2 * r], p[2 * r + 1]);
#pragma unroll
        for (int i = 1; i < 7; i++) {
            mx = fmaxf(mx, fmaxf(p[4 * i + 2 * r], p[4 * i + 2 * r + 1]));
            mn = fminf(mn, fminf(p[4 * i + 2 * r], p[4 * i + 2 * r + 1]));
        }
        mx = fmaxf(mx, __shfl_xor_sync(0xffffffffu, mx, 1));
        mn = fminf(mn, __shfl_xor_sync(0xffffffffu, mn, 1));
        const float bx = -mx * L, bn = mn * L;
        float ep[14], en[14], sp = 0.f, sn = 0.f;
#pragma unroll
        for (int i = 0; i < 14; i++) {
            const float v = p[4 * (i >> 1) + 2 * r + (i & 1)];
            ep[i] = ex2(fmaf(v, L, bx));
            en[i] = ex2(fmaf(v, -L, bn));
            sp += ep[i]; sn += en[i];
        }
        sp += __shfl_xor_sync(0xffffffffu, sp, 1);
        sn += __shfl_xor_sync(0xffffffffu, sn, 1);
        const float ip = rcp(sp), in = rcp(sn);
#pragma unroll
        for (int i = 0; i < 7; i++) {
            out[4 * i + r] = pack2(ep[2 * i] * ip, ep[2 * i + 1] * ip);
            out[4 * i + 2 + r] = pack2(en[2 * i] * in, en[2 * i + 1] * in);
        }
    }
}
__device__ __forceinline__ float geglu(float g, float u) {
    const float t = tanh_hw(g * fmaf(g * g, 0.7978845608028654f * 0.044715f, 0.7978845608028654f));
    const float gu = g * u;
    return fmaf(t, gu, gu);
}
__device__ __forceinline__ void phi_gemm(const float* t, float* p) {
    uint32_t w[14];
#pragma unroll
    for (int i = 0; i < 14; i++) w[i] = pack2(t[2 * i], t[2 * i + 1]);
    const uint64_t db = BASE128(OFF_WPHI, 16, 0);
    wg_fence();
    mma_rs56<0, 0>(p, w[0], w[1], w[2], w[3], 0, db);
    mma_rs56<0, 2>(p, w[4], w[5], w[6], w[7], 1, db);
    mma_rs56<0, 4>(p, w[8], w[9], w[10], w[11], 1, db);
    mma_rs56<0, 6>(p, w[12], w[13], 0u, 0u, 1, db);
    wg_commit();
    wg_wait<0>();
}

}

#define BAR(i) (bars + 8 * (i))
#define R_WAIT() mbar_wait(BAR(slot), ph)
#define WSUM(i)
#define R_ADJ (slot * (STAGE >> 4))
#define R_NEXT() do { eb2 = eb1; eb1 = BAR(B_EMPTY + slot); if (++slot == NST) { slot = 0; ph ^= 1; } } while (0)
#define R_RELEASE(k) do { if (lane == 0) mbar_arrive((k) == 1 ? eb1 : eb2); } while (0)
#define PUSH_BEGIN() do { mbar_wait(BAR(B_ACK + wgi), ackph); ackph ^= 1; } while (0)
#define PUSH_ACK() do { __syncwarp(); if (lane == 0) asm volatile("mbarrier.arrive.shared::cluster.b64 _, [%0];" ::"r"(mapa(BAR(B_ACK + wgi), hr ^ 1)) : "memory"); } while (0)

__global__ void __cluster_dims__(2, 1, 1) __launch_bounds__(384, 1)
fused_kernel(Scratch* const sc, const __nv_bfloat16* __restrict__ x_in, const __nv_bfloat16* __restrict__ w_phi, const int trips,
             const __nv_bfloat16* __restrict__ wg, const __nv_bfloat16* __restrict__ wu, const __nv_bfloat16* __restrict__ wd,
             const __grid_constant__ Maps maps) {
    extern __shared__ __align__(1024) unsigned char smem_raw[];
    const uint32_t sb = s2u(smem_raw);
    const uint32_t bars = sb + OFF_BAR;
    const int wgi = __shfl_sync(0xffffffffu, threadIdx.x >> 7, 0);
    const int hr = blockIdx.x & 1, ck = blockIdx.x >> 1;
    const int gp = (ck - 4) & 7, q7 = ((ck - 36) * 37) >> 8;
    const int pr = __shfl_sync(0xffffffffu, ck < 4 ? ck : (ck < 36 ? (ck - 4) >> 3 : q7), 0);
    const int tile = __shfl_sync(0xffffffffu, ck < 4 ? 0 : (ck < 36 ? (gp ? 2 * gp : 1) : 2 * (ck - 36 - 7 * q7) + 3), 0);
    const int sl = 2 * pr + hr;
    STAMP(0);
    GSTAMP(60);
    if (threadIdx.x == 256) {
#pragma unroll
        for (int i = 0; i < NST; i++) mbar_init(BAR(i), 1);
        asm volatile("fence.mbarrier_init.release.cluster;" ::: "memory");
    }
    if (threadIdx.x == 288) {
        if ((sb & 0x3FFFF) != SB0) asm volatile("trap;");
#pragma unroll
        for (int i = NST; i < B_COUNT; i++) mbar_init(BAR(i), i >= B_ACK ? 4 : (i < B_RECV ? 8 : 1));
        asm volatile("fence.mbarrier_init.release.cluster;" ::: "memory");
    }
    __syncwarp();
    asm volatile("barrier.cluster.arrive.relaxed.aligned;" ::: "memory");

    if (wgi == 2) {
        asm volatile("setmaxnreg.dec.sync.aligned.u32 40;");
        const int t128 = fresh_tid() & 127, w = __shfl_sync(0xffffffffu, t128 >> 5, 0), lane = t128 & 31;
        uint32_t e0[2] = {0, 0}, e1[2] = {0, 0}, cw_target = 0;
        if (w == 0) {
#pragma unroll 1
            for (int n = 0; n < NST; n++) {
                const uint32_t dst = sb + n * STAGE, fb = BAR(n);
                asm volatile(ELECT "mbarrier.arrive.expect_tx.shared::cta.b64 _, [%0], %1; }" ::"r"(fb), "r"(n < 2 ? 2 * STAGE : STAGE) : "memory");
                if (n < 2) {
                    tma3x(sb + OFF_H + n * STAGE, &maps.x, tile * 128 + n * 64, fb);
                    tma3x(dst, &maps.x, tile * 128 + n * 64 + 32, fb);
                } else {
                    if (n == 3) mbar_wait(BAR(1), 0);
                    const int ra = 112 * (n - 2);
                    tma2d(dst, &maps.qkv, 448 + 56 * sl, ra, fb);
                    tma2d(dst + HALF, &maps.qkv, 896 + 56 * sl, ra, fb);
                }
            }
            asm volatile("barrier.cluster.wait.aligned;" ::: "memory");
            cw_target = (ld_word(g_cw + sl * 32) & ~15u) + 16;
#pragma unroll 1
            for (int k = 0; k < 2; k++) {
                const int n = t128 + 32 * k;
                int m = n - 2 - (n > PACK);
                const bool packed = m >= 30 ? (m < 38 || m >= 52) : m >= 22;
                if (m >= 30) m -= 30;
                if (n == PACK) m = tile < 8 ? tile : tile + 14;
                const int rot = n < 8 ? 0 : pr;
                const int ra = 112 * kblk(rot, m & 3), rb = 112 * kblk(rot, 2 * m & 3), rc = 112 * kblk(rot, (2 * m + 1) & 3);
                int kind = 0, m0, m1, c0, c1, r0, r1;
                if (m < 4) { m0 = m1 = 1; c0 = 448 + 56 * sl; c1 = c0 + 448; r0 = r1 = ra; }
                else if (m < 8) { m0 = m1 = m < 6 ? 1 : 2; c0 = c1 = 56 * sl; r0 = rb; r1 = rc; }
                else if (m < 20) { m0 = 3; m1 = 4; c0 = c1 = 224 * sl + 32 * hr + 64 * ((m - 8) >> 2); r0 = r1 = ra; }
                else if (m < 22) { kind = 2; m0 = 5; m1 = 6; c0 = c1 = 224 * sl + (hr ? 0 : 192); r0 = rb; r1 = rc; }
                else { m0 = m1 = 7; c0 = c1 = 56 * (2 * ((pr + (m >> 1) - 10) & 3) + hr); r0 = 224 * (sl ^ (m & 1)); r1 = r0 + 112; }
                if (packed) { kind = 1; r0 = sl * 16 + (m < 8 ? m : m - 14); r1 = 0; }
                e0[0] = e0[1]; e1[0] = e1[1];
                e0[1] = kind | (m0 << 2) | (m1 << 6) | (c0 << 10) | (c1 << 21);
                e1[1] = r0 | (r1 << 16);
            }
        } else {
            const int j = t128 - 32;
            asm volatile("barrier.cluster.wait.aligned;" ::: "memory");
            uint2 wv[7];
            const int k = j < 56 ? j : 55, hh = k >= 28;
#pragma unroll
            for (int i = 0; i < 7; i++) wv[i] = __ldg(reinterpret_cast<const uint2*>(w_phi + (sl * 56 + k) * 28) + i);
#pragma unroll 1
            for (int i = j; i < 7168 / 16; i += 96) sts4(sb + OFF_WPHI + i * 16, 0, 0, 0, 0);
            bar_sync(5, 96);
            if (j < 56) {
                uint32_t a4[4];
#pragma unroll
                for (int q = 0; q < 4; q++) a4[q] = sb + OFF_WPHI + (4 * hh + q) * 128 + ((((k >> 3) ^ (4 * hh + q)) & 7) << 4) + (k & 7) * 2;
                FOR14(const uint32_t v = (t & 1) ? wv[t >> 1].y : wv[t >> 1].x;
                      asm volatile("{ .reg .b16 l, h; mov.b32 {l, h}, %2; st.shared.u16 [%0+%3], l; st.shared.u16 [%1+%3], h; }"
                                   ::"r"(a4[t >= 7 ? 2 : 0]), "r"(a4[t >= 7 ? 3 : 1]), "r"(v), "n"((t % 7) * 1024) : "memory"));
            }
            __syncwarp();
            fence_async();
            bar_arrive(1, 224);
            bar_arrive(9, 224);
            if (w == 1) {
                mbar_wait(BAR(2), 0);
                mbar_wait(BAR(2), 1);
                const int b = blockIdx.x;
                asm volatile(ELECT "cp.async.bulk.prefetch.L2.global [%0], %1; }" ::"l"(wg + b * 6272), "r"(12544) : "memory");
                asm volatile(ELECT "cp.async.bulk.prefetch.L2.global [%0], %1; }" ::"l"(wu + b * 6272), "r"(12544) : "memory");
                asm volatile(ELECT "cp.async.bulk.prefetch.L2.global [%0], %1; }" ::"l"(wd + b * 6272), "r"(12544) : "memory");
            }
        }
        uint32_t kseq = ld_word(g_c1 + (sl * 8 * 16 + tile) * 32);
        int slot = 0, ph = 0, n = NST;
#pragma unroll 1
        for (int layer = 0; layer < 3; layer++) {
            if (w == 0) {
                const int nend = layer == 0 ? 11 : (layer == 1 ? 42 : 63);
#pragma unroll 1
                for (; n < nend; n++) {
                const uint32_t w0 = __shfl_sync(0xffffffffu, n < 32 ? e0[0] : e0[1], n & 31), w1 = __shfl_sync(0xffffffffu, n < 32 ? e1[0] : e1[1], n & 31);
                const uint32_t dst = sb + slot * STAGE, fb = BAR(n == PACK ? B_PACK : slot);
                const CUtensorMap* m0 = &maps.x + ((w0 >> 2) & 15);
                const CUtensorMap* m1 = &maps.x + ((w0 >> 6) & 15);
                const int c0 = (w0 >> 10) & 2047, c1 = w0 >> 21, r0 = w1 & 0xffff, r1 = w1 >> 16;
                if (n == 25) {
                    int it = 0;
                    uint32_t v;
                    do { asm volatile("ld.acquire.gpu.global.u32 %0, [%1];" : "=r"(v) : "l"(g_cw + sl * 32) : "memory"); } while ((int)(v - cw_target) < 0 && ++it < 0x400000);
                    asm volatile("fence.proxy.async.global;" ::: "memory");
                    __syncwarp();
                }
                mbar_wait(BAR(B_EMPTY + slot), ph);
                __syncwarp();
                asm volatile(ELECT "mbarrier.arrive.expect_tx.shared::cta.b64 _, [%0], %1; }" ::"r"(fb), "r"(STAGE) : "memory");
                if ((w0 & 3) == 0) {
                    tma2d(dst, m0, c0, r0, fb);
                    tma2d(dst + HALF, m1, c1, r1, fb);
                } else if (w0 & 1) {
                    asm volatile(ELECT "cp.async.bulk.shared::cluster.global.mbarrier::complete_tx::bytes [%0], [%1], %2, [%3]; }"
                                 ::"r"(dst), "l"(reinterpret_cast<const char*>(g_wp) + (size_t)r0 * STAGE), "r"(STAGE), "r"(fb) : "memory");
                } else {
                    tma2d(dst, m0, c0, r0, fb); tma2d(dst + 7168, m0, c0, r1, fb);
                    tma2d(dst + HALF, m1, c0, r0, fb); tma2d(dst + HALF + 7168, m1, c0, r1, fb);
                }
                if (n == PACK) asm volatile(ELECT "mbarrier.arrive.shared::cta.b64 _, [%0]; }" ::"r"(BAR(slot)) : "memory");
                if (++slot == NST) { slot = 0; ph ^= 1; }
                }
            } else if (w == 1 && layer == 1) {
                constexpr int ps = PACK % NST;
                mbar_wait(BAR(B_PACK), 0);
                asm volatile("{ .reg .pred e; elect.sync _|e, 0xffffffff;\n"
                             "@e cp.async.bulk.global.shared::cta.bulk_group [%0], [%1], %2;\n"
                             "@e cp.async.bulk.commit_group;\n"
                             "@e cp.async.bulk.wait_group.read 0;\n"
                             "@e mbarrier.arrive.shared::cta.b64 _, [%3], 8;\n"
                             "@e cp.async.bulk.wait_group 0;\n"
                             "@e fence.proxy.async.global;\n"
                             "@e red.release.gpu.global.add.u32 [%4], 1; }"
                             ::"l"(reinterpret_cast<char*>(g_wp) + (size_t)(sl * 16 + tile) * STAGE), "r"(sb + ps * STAGE), "r"(STAGE), "r"(BAR(B_EMPTY + ps)), "l"(g_cw + sl * 32) : "memory");
                __syncwarp();
            }
            if (layer < 2) {
            const uint32_t tag = layer ^ 1;
            kseq++;
            bar_sync(7, 384);
            ASTAMP(0);
            if (tile < 15) {
                const int sq = lane >> 3, pk = 8 * w + (lane & (tile == 14 ? 3 : 7));
                uint32_t v[16];
                if (layer == 0) poll_cnt(g_c1 + ((sl * 8 + (w >> 1) * 4 + (tile >> 2)) * 16 + (lane & 15)) * 32, kseq);
                ASTAMP(1);
                poll4_kv<32>(v, g_kv1 + ((sl * 16 + tile) * 16 + 4 * sq) * 32 + pk, tag);
#pragma unroll
                for (int k = 0; k < 4; k++) {
                    float lo = (bf_lo(v[k]) + bf_lo(v[4 + k])) + (bf_lo(v[8 + k]) + bf_lo(v[12 + k]));
                    float hi = (bf_hi(v[k]) + bf_hi(v[4 + k])) + (bf_hi(v[8 + k]) + bf_hi(v[12 + k]));
                    lo += __shfl_xor_sync(0xffffffffu, lo, 8); hi += __shfl_xor_sync(0xffffffffu, hi, 8);
                    lo += __shfl_xor_sync(0xffffffffu, lo, 16); hi += __shfl_xor_sync(0xffffffffu, hi, 16);
                    v[k] = pack2(lo, hi);
                }
                if (sq == 0) st_pkt<0>(g_kv2 + sl * 512 + 32 * tile + pk, settag(v[0], tag), v[1], v[2], v[3]);
            }
            ASTAMP(2);
            {
                const int item = t128 < 112 ? t128 : 112 + (t128 & 3), d = item >> 1;
                const int cc = t128 < 112 ? 2 * (d >= 28) + (item & 1) : item - 112;
                const int r = t128 < 112 ? d : 56 + (cc >> 1) + 2 * ((t128 - 112) >> 2);
                uint32_t ra = sb + OFF_KVB + r * 128 + 4 * cc, rx = (r & 7) << 4;
                asm volatile("" : "+r"(ra), "+r"(rx));
                FOR14(asm volatile("st.shared.u32 [%0+%2], %1;" ::"r"((ra ^ 8) + (((t & 7) << 4) ^ rx)), "r"(0), "n"((t >> 3) * 8192) : "memory"));
                uint32_t v[16];
                asm volatile("" : "+r"(ra), "+r"(rx));
                poll4_kv<8>(v, g_kv2 + sl * 512 + (item >> 3) * 32 + (item & 7), tag);
                FOR14(asm volatile("st.shared.u32 [%0+%2], %1;" ::"r"(ra + (((t & 7) << 4) ^ rx)), "r"(v[t < 7 ? t : t + 1]), "n"((t >> 3) * 8192) : "memory"));
                fence_async();
            }
            bar_arrive(3, 384);
            ASTAMP(3);
            }
        }
    } else {
        asm volatile("setmaxnreg.inc.sync.aligned.u32 232;");
        const int tid = fresh_tid(), t128 = tid & 127, g = (tid & 31) >> 2, c = tid & 3;
        int lane = tid & 31;
        const int wu = __shfl_sync(0xffffffffu, tid >> 5, 0), w = wu & 3;
        const uint32_t xoff = __shfl_sync(0xffffffffu, (3 * PLANE + ((tile * 2 + wgi) * 8) * 512 + w * 128) * 16, 0);
        char* xu = reinterpret_cast<char*>(g_ex) + xoff;
#define FRESH() asm volatile("" : "+l"(xu), "+r"(lane))
#define xp0 (reinterpret_cast<uint4*>(xu) + lane)
        const uint32_t hbuf = sb + OFF_H + wgi * STAGE;
        uint32_t slot = 0, ph = 0, eb1 = 0, eb2 = 0, ackph = 0, rcvph = 0, gatph = 0, swp = 0;
        uint32_t ppid = 6;
#define cx(s) (reinterpret_cast<uint32_t*>(reinterpret_cast<uint4*>(xu) + PL(1) + 112 + (s) * 512))
#define stp (reinterpret_cast<uint4*>(xu) + g + PL(0) + 112)
        uint32_t seq = ld_word(cx(sl));
        uint32_t kseq = ld_word(g_c1 + ((sl * 8 + (tid >> 5)) * 16 + tile) * 32);
        uint32_t stag = ld_word(reinterpret_cast<const uint32_t*>(stp + sl * 512) + 3) & 1;
        asm volatile("barrier.cluster.wait.aligned;" ::: "memory");
        STAMP(1);
        uint32_t X[14];
        const uint32_t x0row = (w < 2 ? hbuf : sb + wgi * STAGE) + ((w & 1) * 16 + (lane & 15)) * 128;
        mbar_wait(BAR(wgi), 0);
        STAMP(51);
#pragma unroll
        for (int j = 0; j < 4; j++) {
            const int G = 7 * sl + min(2 * j + (lane >> 4), 6);
            uint32_t q2, q3;
            asm volatile("ldmatrix.sync.aligned.m8n8.x4.shared.b16 {%0,%1,%2,%3}, [%4];" : "=r"(X[4 * j]), "=r"(X[4 * j + 1]), "=r"(q2), "=r"(q3)
                         : "r"(x0row + (G >> 3) * 4096 + (((G ^ lane) & 7) << 4)) : "memory");
            if (j < 3) { X[(4 * j + 2) % 14] = q2; X[(4 * j + 3) % 14] = q3; }
        }
#define PUSH_SLICE(W)                                                                          \
    {                                                                                          \
        if (t128 == 0) mbar_expect_tx(BAR(B_RECV + wgi), 7168);                                \
        PUSH_BEGIN();                                                                          \
        const uint32_t ra = mapa(hbuf + 24576 + t128 * 16, hr ^ 1), rb = mapa(sb + OFF_XR + wgi * 3072, hr ^ 1), rbar = mapa(BAR(B_RECV + wgi), hr ^ 1); \
        st_async4(ra, W[0], W[1], W[2], W[3], rbar);                                           \
        st_async4(ra + 2048, W[4], W[5], W[6], W[7], rbar);                                    \
        st_async4(rb + t128 * 16, W[8], W[9], W[10], W[11], rbar);                             \
        asm volatile("st.async.weak.shared::cluster.mbarrier::complete_tx::bytes.v2.b32 [%0], {%1,%2}, [%3];" ::"r"(rb + 2048 + t128 * 8), "r"(W[12]), "r"(W[13]), "r"(rbar) : "memory"); \
    }
#define PULL_SLICE(W)                                                                          \
    {                                                                                          \
        uint32_t t0, t1;                                                                       \
        mbar_wait(BAR(B_RECV + wgi), rcvph);                                                   \
        rcvph ^= 1;                                                                            \
        lds4(&A[1][0], hbuf + 24576 + t128 * 16);                                              \
        lds4(&A[1][4], hbuf + 26624 + t128 * 16);                                              \
        lds4(&A[1][8], sb + OFF_XR + wgi * 3072 + t128 * 16);                                  \
        asm volatile("ld.shared.v2.u32 {%0,%1}, [%2];" : "=r"(t0), "=r"(t1) : "r"(sb + OFF_XR + wgi * 3072 + 2048 + t128 * 8) : "memory"); \
        _Pragma("unroll") for (int i = 0; i < 12; i++) A[0][i] = (i & 3) ? W[i] : W[i] & ~1u;  \
        A[1][0] &= ~1u; A[1][4] &= ~1u; A[1][8] &= ~1u;                                        \
        A[0][12] = (hr ? t0 : W[12]) & ~1u; A[0][13] = hr ? t1 : W[13];                        \
        A[1][12] = (hr ? W[12] : t0) & ~1u; A[1][13] = hr ? W[13] : t1;                        \
        asm volatile("" : RW4(A[0], 0), RW4(A[0], 4), RW4(A[0], 8), RW2(A[0], 12), RW4(A[1], 0), RW4(A[1], 4), RW4(A[1], 8), RW2(A[1], 12)); \
        swp = hr * 448;                                                                        \
    }
#define SWB(b, t, db, sh) ((b) == 0 && (t) < 6 ? ((t) < 3 ? db##p : db##m) : db)
#define DECL_DB(b, MK, lbo, sh) const uint64_t db = MK(0, lbo, R_ADJ), dbp = (b) == 0 ? MK(0, lbo, R_ADJ + (swp >> (sh))) : db, dbm = (b) == 0 ? MK(0, lbo, R_ADJ - (swp >> (sh))) : db;
#define EARLY 1
#define EARLYK 1
#define PPB 2
#define PP_WAIT() if (wgi == 1) { bar_sync(ppid, 256); ppid ^= 14; }
#define PP_GO() if (wgi == 0) { bar_arrive(ppid, 256); ppid ^= 14; }
#define GAT_ISSUE(base)                                                                        \
    {                                                                                          \
        const char* gs = xu + ((base) + kblk(pr, GB) * 1024) * 16; \
        const uint32_t gd = hbuf + w * 3584, gb = BAR(B_GAT + wu);                     \
        asm volatile("{ .reg .pred e; elect.sync _|e, 0xffffffff;\n"                           \
                     "@e mbarrier.arrive.expect_tx.shared::cta.b64 _, [%2], 3584;\n"           \
                     "@e cp.async.bulk.shared::cluster.global.mbarrier::complete_tx::bytes [%0], [%1], 1792, [%2];\n" \
                     "@e cp.async.bulk.shared::cluster.global.mbarrier::complete_tx::bytes [%0+1792], [%1+8192], 1792, [%2]; }" \
                     ::"r"(gd), "l"(gs), "r"(gb) : "memory");                                  \
        __syncwarp();                                                                          \
    }
#define GAT_FETCH()                                                                            \
    {                                                                                          \
        mbar_wait(BAR(B_GAT + wu), gatph);                                             \
        gatph ^= 1;                                                                            \
        const uint32_t ga = hbuf + w * 3584 + lane * 16;                                       \
        _Pragma("unroll") for (int s2 = 0; s2 < 2; s2++) {                                     \
            lds4(&A[2 * GB + s2][0], ga + s2 * 1792); lds4(&A[2 * GB + s2][4], ga + s2 * 1792 + 512); lds4(&A[2 * GB + s2][8], ga + s2 * 1792 + 1024); \
            asm volatile("ld.shared.v2.u32 {%0,%1}, [%2];" : "=r"(A[2 * GB + s2][12]), "=r"(A[2 * GB + s2][13]) : "r"(ga - lane * 8 + s2 * 1792 + 1536) : "memory"); \
        }                                                                                      \
    }
#define PT 3
#define PREP(b, t, remote)                                                                     \
    if constexpr ((b) < 3 && (t) == PT) {                                                      \
        wg_commit();                                                                           \
        STAMP(80 + 8 * (step & 1) + 2 * (b));                                                  \
        if constexpr ((b) == 0) { if (remote) GAT_FETCH() else X0_BLOCK(1) }                   \
        if (remote) blk_check<((b) + 1) & 3>(A, BLK(xsrc, (b) + 1), lane, xtag);               \
        STAMP(81 + 8 * (step & 1) + 2 * (b));                                                  \
        if constexpr ((b) == 0) { if (remote) blk_load<3>(A, BLK(xsrc, 3), lane); else X0_BLOCK(3) } \
        normalize<((b) + 1) & 3>(A, k0, k1);                                                   \
        asm volatile("" : RW4(A[(2 * (b) + 2) & 7], 0), RW4(A[(2 * (b) + 2) & 7], 4), RW4(A[(2 * (b) + 2) & 7], 8), RW2(A[(2 * (b) + 2) & 7], 12), \
                          RW4(A[(2 * (b) + 3) & 7], 0), RW4(A[(2 * (b) + 3) & 7], 4), RW4(A[(2 * (b) + 3) & 7], 8), RW2(A[(2 * (b) + 3) & 7], 12)); \
        wg_fence();                                                                            \
    }                                                                                          \
    if constexpr ((b) == 3 && ((t) == 0 || (t) == 6)) { STAMP(86 + 8 * (step & 1) + (t) / 6); }
#define X0_BLOCK(b)                                                                            \
    { const int rr = lane & 7, hi = lane >> 4;                                                 \
    const uint32_t rowa = (w < 2 ? hbuf : sb + wgi * STAGE) + ((w & 1) * 16 + (lane & 15)) * 128; \
    FOR7(constexpr int G = 14 * (b) + (t < 3 ? 2 * t : (t < 6 ? 2 * t + 1 : 6));               \
         uint32_t q0, q1, q2, q3;                                                              \
         const uint32_t ad = t < 6 ? rowa + (((((G & 7) + hi) ^ rr) & 7) << 4) + ((G & 7) == 7 ? hi * 4096 : 0) : rowa + ((G + 7 * hi) >> 3) * 4096 + ((((G + 7 * hi) ^ rr) & 7) << 4); \
         asm volatile("ldmatrix.sync.aligned.m8n8.x4.shared.b16 {%0,%1,%2,%3}, [%4+%5];" : "=r"(q0), "=r"(q1), "=r"(q2), "=r"(q3) \
                      : "r"(ad), "n"(t < 6 ? (G >> 3) * 4096 : 0) : "memory");                 \
         if (t < 3) { A[2 * (b)][4 * t] = q0; A[2 * (b)][4 * t + 1] = q1; A[2 * (b)][4 * t + 2] = q2; A[2 * (b)][4 * t + 3] = q3; } \
         else if (t < 6) { A[2 * (b) + 1][(4 * t - 12) & 15] = q0; A[2 * (b) + 1][((4 * t - 12) & 15) + 1] = q1; A[2 * (b) + 1][((4 * t - 12) & 15) + 2] = q2; A[2 * (b) + 1][((4 * t - 12) & 15) + 3] = q3; } \
         else { A[2 * (b)][12] = q0; A[2 * (b)][13] = q1; A[2 * (b) + 1][12] = q2; A[2 * (b) + 1][13] = q3; }); }
#define BLK(base, b) ((base) + kblk(pr, b) * 1024)

#pragma unroll 1
        for (int step = 0; step < 4; step++) {
            FRESH();
            const uint32_t tag = (step >> 1) ^ 1;
            const int so = (step >> 1) * 24 + (step & 1) * 12;
            (void)so;
            uint32_t A[8][14];
            uint4* const xsrc = xp0 + ((step & 1) ? PL(2) : PL(0));
            const uint32_t xtag = (step & 1) ? tag : ((seq >> 3) & 1) ^ 1;
            uint32_t xbits;
            {
                float st[4];
                slice_stats(X, st);
                stag ^= 1;
                xbits = x_bits(X);
                tag_slice(X, xtag);
                if (step) send_slice<0>(xsrc + sl * 512, lane, X);
                if (c == 0) st_pkt<0>(stp + sl * 512, __float_as_uint(st[0]), __float_as_uint(st[1]), __float_as_uint(st[2]), settag(__float_as_uint(st[3]), stag));
            }
            STAMP(2 + so);
            uint32_t sv[8];
            if (step == 0) {
                X0_BLOCK(0)
                mbar_wait(BAR(wgi ^ 1), 0);
                R_NEXT();
                R_NEXT();
                stat_load(sv, stp + c * 1024);
                stat_check(sv, stp + c * 1024, stag);
                STAMP(52 + step);
            } else {
                PUSH_SLICE(X)
                stat_load(sv, stp + c * 1024);
                PULL_SLICE(X)
                stat_check(sv, stp + c * 1024, stag);
                STAMP(52 + step);
                GAT_ISSUE((step & 1) ? PL(2) : PL(0))
            }
            LnCoef k0, k1;
            {
                k0 = ln_coef(__uint_as_float(sv[0]) + __uint_as_float(sv[4]), __uint_as_float(sv[1]) + __uint_as_float(sv[5]));
                k1 = ln_coef(__uint_as_float(sv[2]) + __uint_as_float(sv[6]), __uint_as_float(sv[3] & ~1u) + __uint_as_float(sv[7] & ~1u));
            }
            if (step) {
                blk_load<2>(A, BLK(xsrc, 2), lane);
            } else {
                X0_BLOCK(2)
            }
            STAMP(3 + so);
            GSTAMP(76 + step);

            if ((step & 1) == 0) {
                float tq[28];
                {
                    float av[28];
#define KV_BLOCK(b)                                                                           \
    if (GB == 2 && (b) == 1 && step) GAT_FETCH()                                                         \
    if ((b) == 2) PUSH_ACK();                                                                 \
    if ((b) == 1 && step == 0) { if (lane == 0) mbar_arrive(BAR(B_EMPTY)); }                  \
    if (QE && (b) == 1) R_RELEASE(2);                                                         \
    if (QE && (b) == 2) { wg_wait<2>(); R_RELEASE(2); }                                       \
    R_WAIT();                                                                                 \
    if ((b) == PPK) { PP_WAIT() }                                                             \
    { DECL_DB(b, BASE128, 16, 0)                                                              \
    wg_fence();                                                                               \
    FOR7(mma_rs56<1, D128(0, t)>(tq, AQ(A, b, t), (b) + t > 0, SWB(b, t, db, 0));             \
         mma_rs56<1, D128(HALF, t)>(av, AQ(A, b, t), (b) + t > 0, SWB(b, t, db, 0));          \
         PREP(b, t, step)); }                                                                 \
    wg_commit();                                                                              \
    if ((b) == 3 && PPK < 4) { PP_GO() }                                                      \
    R_NEXT();
                    normalize<0>(A, k0, k1);
                    KV_BLOCK(0) KV_BLOCK(1) KV_BLOCK(2) KV_BLOCK(3)
                    wg_wait<0>();
                    if (lane < (QE ? 3 : NST)) mbar_arrive(BAR(B_EMPTY + (slot + NST - 1 - lane) % NST));
                    STAMP(4 + so);
                    WSUM(80 + 7 * (step >> 1));
                    const int m = lane >> 3, rr = lane & 7;
                    const uint32_t rowa = hbuf + 16384 + (w * 16 + rr + 8 * (m & 1)) * 128;
                    const uint32_t one = c == 0 ? 0x00003f80u : 0u;
                    if (step == 0) { bar_sync(wgi ? 9 : 1, 224); }
#pragma unroll
                    for (int j = 0; j < 4; j++) {
                        const uint32_t a = rowa + (((2 * j + (m >> 1)) ^ rr) << 4);
                        if (j < 3) stsm4(a, pack2(av[8 * j], av[8 * j + 1]), pack2(av[8 * j + 2], av[8 * j + 3]), pack2(av[8 * j + 4], av[8 * j + 5]), pack2(av[8 * j + 6], av[8 * j + 7]));
                        else stsm4(a, pack2(av[24], av[25]), pack2(av[26], av[27]), one, one);
                    }
                }
                uint32_t PH[28];
                int it = 1;
#pragma unroll 1
                do {
                    float pp[28];
                    phi_gemm(tq, pp);
                    dual_softmax(pp, PH);
                    if (((trips >> (it + 1)) & 1) == 0) continue;
                    {
                        const int m = lane >> 3, rr = lane & 7;
                        const uint32_t rowa = hbuf + (w * 16 + rr + 8 * (m & 1)) * 128;
#pragma unroll
                        for (int j = 0; j < 7; j++) {
                            const int cg = 2 * j + (m >> 1), hi = cg >= 7;
                            stsm4(rowa + hi * 8192 + (((cg - 7 * hi) ^ rr) << 4), PH[4 * j], PH[4 * j + 1], PH[4 * j + 2], PH[4 * j + 3]);
                        }
                    }
                    fence_async();
                    STAMP(5 + so);
#define Q_STAGE(b0)                                                                           \
    R_WAIT();                                                                                 \
    { DECL_DB(b0, BASE128, 16, 0)                                                             \
    wg_fence();                                                                               \
    FOR7(mma_rs56<1, D128(0, t)>(tq, AQ(A, b0, t), (b0) + t > 0, SWB(b0, t, db, 0)));         \
    FOR7(mma_rs56<1, D128(HALF, t)>(tq, AQ(A, (b0) + 1, t), 1, db)); }                        \
    wg_commit();                                                                              \
    R_NEXT();
                    if (QE && wgi == 0) { kill<28>(tq); Q_STAGE(0) Q_STAGE(2) wg_wait<1>(); R_RELEASE(2); wg_wait<0>(); R_RELEASE(1); }
                    bar_sync(2, 256);
                    float kv[28];
                    const uint64_t da = BASE128(OFF_H + 16384, 16, 0), dbk = BASE128(OFF_H, 16, wgi * 512);
                    wg_fence();
                    FOR8(constexpr uint64_t o = ((t >> 2) * STAGE + (t & 3) * 2048) >> 4; mma_ss56_tt<o, o>(kv, t > 0, da, dbk));
                    wg_commit();
                    wg_wait<0>();
#pragma unroll
                    for (int hf = 0; hf < 2; hf++) {
                        const int d = 16 * w + g + 8 * hf;
                        if ((d < 56 && (d >= 28) == (c >= 2)) || d == 56) {
                            const int item = d < 56 ? 2 * d + (c & 1) : 112 + c;
                            uint4* dst = g_kv1 + ((sl * 16 + (item >> 3)) * 16 + tile) * 32 + wgi * 16 + (item & 7);
#define KVW(i) pack2(kv[4 * (i) + 2 * hf], kv[4 * (i) + 2 * hf + 1])
                            st_pkt<0>(dst, settag(KVW(0), tag), KVW(1), KVW(2), KVW(3));
                            st_pkt<8>(dst, settag(KVW(4), tag), KVW(5), KVW(6), 0u);
                        }
                    }
                    __syncwarp();
                    kseq++;
                    if (lane == 0) st_word(g_c1 + ((sl * 8 + (tid >> 5)) * 16 + tile) * 32, kseq);
                    bar_arrive(7, 384);
                    STAMP(6 + so);
                    if (!QE || wgi == 1) { kill<28>(tq); Q_STAGE(0) Q_STAGE(2) wg_wait<1>(); R_RELEASE(2); wg_wait<0>(); R_RELEASE(1); }
                    STAMP(7 + so);
                    kill<28>(PH);
                } while (((trips >> (++it)) & 1));
                STAMP(8 + so);
                FRESH();
                if (step) {
                    slice_load<PL(0)>(X, xp0 + sl * 512, lane);
                } else {
                    const uint32_t* xp = reinterpret_cast<const uint32_t*>(x_in + (size_t)(tile * 128 + wu * 16 + g) * 448 + 56 * sl + 2 * c);
#pragma unroll
                    for (int i = 0; i < 7; i++) { X[2 * i] = __ldg(xp + 4 * i); X[2 * i + 1] = __ldg(xp + 4 * i + 8 * 224); }
                }
                bar_sync(3, 384);
                STAMP(9 + so);
                const uint4* const osrc = xp0 + PL(1);
                {
                    float nm[32];
                    const uint64_t db = BASE128(OFF_KVB, 16, 0);
                    wg_fence();
                    FOR7(mma_rs64<0, ((t >> 2) * 8192 + (t & 3) * 32) / 16>(nm, PH[4 * t], PH[4 * t + 1], PH[4 * t + 2], PH[4 * t + 3], t > 0, db));
                    wg_commit();
                    wg_wait<0>();
                    const float i00 = rcp(nm[28] + 1e-6f), i01 = rcp(nm[29] + 1e-6f), i10 = rcp(nm[30] + 1e-6f), i11 = rcp(nm[31] + 1e-6f);
                    const float m0 = c >= 2 ? i01 : i00, m1 = c >= 2 ? i11 : i10;
                    uint32_t O[14];
#pragma unroll
                    for (int i = 0; i < 7; i++) {
                        const float f0 = i < 3 ? i00 : (i > 3 ? i01 : m0), f1 = i < 3 ? i10 : (i > 3 ? i11 : m1);
                        O[2 * i] = pack2(nm[4 * i] * f0, nm[4 * i + 1] * f0);
                        O[2 * i + 1] = pack2(nm[4 * i + 2] * f1, nm[4 * i + 3] * f1);
                    }
                    if (OST) { PP_WAIT() }
                    tag_slice(O, tag);
                    send_slice<PL(1)>(xp0 + sl * 512, lane, O);
                    seq++;
                    if (lane == 0) st_word(cx(sl), seq);
                    STAMP(10 + so);
                    PUSH_SLICE(O)
                    if (OST == 1) { PP_GO() }
                    const uint32_t cv = ld_word(cx(lane & 7));
                    PULL_SLICE(O)
                    check_cnt(cv, cx(lane & 7), seq);
                    if (OST == 2) { PP_GO() }
                    STAMP(56 + (step >> 1));
                    GAT_ISSUE(PL(1))
                    blk_load<3 - GB>(A, BLK(osrc, 3 - GB), lane);
                }
                float ao[28];
#define WO_BLOCK(b)                                                                           \
    if ((b) > 0) blk_check<b>(A, BLK(osrc, b), lane, tag);                                    \
    if (((b) & 1) == 0) R_WAIT();                                                             \
    { DECL_DB(b, BASE128, 16, 0)                                                              \
    wg_fence();                                                                               \
    FOR7(mma_rs56<1, D128(((b) & 1) * HALF, t)>(ao, AQ(A, b, t), (b) + t > 0, SWB(b, t, db, 0))); } \
    wg_commit();                                                                              \
    if ((b) & 1) R_NEXT();
                WO_BLOCK(0)
                STAMP(11 + so);
                blk_load<3>(A, BLK(osrc, 3), lane);
                if (GB == 1) GAT_FETCH()
                WO_BLOCK(1)
                if (GB == 2) GAT_FETCH()
                WO_BLOCK(2)
                PUSH_ACK();
                WO_BLOCK(3)
                wg_wait<0>();
                if (EARLY >= 1) R_RELEASE(2);
                if (EARLY >= 2) R_RELEASE(1);
                STAMP(12 + so);
                WSUM(86 + 7 * (step >> 1));
                x_fix(X, xbits);
#pragma unroll
                for (int i = 0; i < 14; i++) X[i] = pack2(bf_lo(X[i]) + ao[2 * i], bf_hi(X[i]) + ao[2 * i + 1]);
            } else {
                uint32_t H[56];
                float ag[64];
#define F1_EPI(dst, ng, ag)                                                                    \
    _Pragma("unroll") for (int i = 0; i < 2 * (ng); i++)                                       \
        (dst)[i] = pack2(geglu(ag[2 * i], ag[4 * (ng) + 2 * i]), geglu(ag[2 * i + 1], ag[4 * (ng) + 2 * i + 1]));
#define H_PUSH(h0, off) st_async4(rem_h + (off), H[h0], H[(h0) + 1], H[(h0) + 2], H[(h0) + 3], mapa(BAR(B_RECV2 + wgi), hr ^ 1));
#define F1_BLOCK(b, first)                                                                     \
    if ((first) && (b) < 2 && (b) >= EARLY) R_RELEASE(2);                                      \
    if (GB == 2 && (first) && (b) == 1) GAT_FETCH()                                                       \
    if ((first) && (b) == 2) PUSH_ACK();                                                       \
    R_WAIT();                                                                                  \
    if ((b) == ((first) ? PPF : PPB)) { PP_WAIT() }                                            \
    { DECL_DB(b, BASE128, HALF, 0)                                                             \
    wg_fence();                                                                                \
    FOR7(mma_rs128<1, D128(0, t)>(ag, AQ(A, b, t), (b) + t > 0, SWB(b, t, db, 0));             \
         if constexpr (first) { PREP(b, t, true) }); }                                         \
    wg_commit();                                                                               \
    if ((b) == 3) { PP_GO() }                                                                  \
    if ((b) > 0) { wg_wait<1>(); R_RELEASE(1); }       \
    R_NEXT();
                normalize<0>(A, k0, k1);
                F1_BLOCK(0, true) F1_BLOCK(1, true) F1_BLOCK(2, true) F1_BLOCK(3, true)
                if (t128 == 0) { mbar_expect_tx(BAR(B_RECV + wgi), 16384); mbar_expect_tx(BAR(B_RECV2 + wgi), 12288); }
                PUSH_BEGIN();
                wg_wait<0>();
                R_RELEASE(1);
                if (step == 1) R_NEXT();
                int p = 0;
#pragma unroll 1
                do {
                    STAMP(68 + p);
                    F1_EPI(H + 32, 8, ag)
                    STAMP(4 + p + so);
                    WSUM(81 + p + 7 * (step >> 1));
                    if (((trips >> (p + 1)) & 1) == 0) continue;
                    {
                        const uint32_t pk = (p ? hbuf + 16384 : sb + OFF_KVB + wgi * 8192) + w * 2048;
#pragma unroll
                        for (int k = 0; k < 4; k++) sts4(pk + k * 512 + lane * 16, H[32 + 4 * k], H[33 + 4 * k], H[34 + 4 * k], H[35 + 4 * k]);
                        fence_async();
                        __syncwarp();
                        asm volatile(ELECT "cp.async.bulk.shared::cluster.shared::cta.mbarrier::complete_tx::bytes [%0], [%1], 2048, [%2]; }"
                                     ::"r"(mapa(hbuf + p * 8192 + w * 2048, hr ^ 1)), "r"(pk), "r"(mapa(BAR(B_RECV + wgi), hr ^ 1)) : "memory");
                    }
                    kill<64>(ag);
                    F1_BLOCK(0, false) F1_BLOCK(1, false) F1_BLOCK(2, false) F1_BLOCK(3, false)
                    wg_wait<0>();
                    R_RELEASE(1);
                    kill<16>(H + 32);
                } while (((trips >> (++p)) & 1));
#pragma unroll
                for (int k = 0; k < 4; k++) lds4(H + 16 + 4 * k, hbuf + 16384 + w * 2048 + k * 512 + lane * 16);
                __syncwarp();
                if (lane == 0) asm volatile("mbarrier.arrive.shared::cluster.b64 _, [%0];" ::"r"(mapa(BAR(B_ACK2 + wgi), hr ^ 1)) : "memory");
                const uint32_t rem_h = mapa(hbuf + w * 2048 + lane * 16, hr ^ 1);
#define F1_LAST(b0)                                                                            \
    R_WAIT();                                                                                  \
    if (b0) { PP_WAIT() }                                                                      \
    { DECL_DB(b0, BASE64, HALF, 1)                                                             \
    wg_fence();                                                                                \
    FOR7(mma_rs64<1, D64(0, t)>(al, AQ(A, b0, t), (b0) + t > 0, SWB(b0, t, db, 1)));           \
    FOR7(mma_rs64<1, D64(7168, t)>(al, AQ(A, (b0) + 1, t), 1, db)); }                          \
    wg_commit();                                                                               \
    if (b0) { PP_GO() }                                                                        \
    R_NEXT();
                float al[32];
                F1_LAST(0)
                mbar_wait(BAR(B_RECV + wgi), rcvph);
                rcvph ^= 1;
                mbar_wait(BAR(B_ACK2 + wgi), step >> 1);
                H_PUSH(32, 16384) H_PUSH(36, 16896)
                F1_LAST(2)
                H_PUSH(40, 17408) H_PUSH(44, 17920)
                wg_wait<1>();
                R_RELEASE(2);
                wg_wait<0>();
                R_RELEASE(1);
                uint32_t HP[56];
#pragma unroll
                for (int k = 0; k < 4; k++) lds4(H + 4 * k, sb + OFF_KVB + wgi * 8192 + w * 2048 + k * 512 + lane * 16);
#pragma unroll
                for (int t = 0; t < 8; t++) lds4(HP + 4 * t, hbuf + (t >> 2) * 8192 + w * 2048 + (t & 3) * 512 + lane * 16);
                F1_EPI(H + 48, 4, al)
                H_PUSH(48, 24576 - w * 1024) H_PUSH(52, 25088 - w * 1024)
                STAMP(7 + so);
                WSUM(84 + 7 * (step >> 1));
                FRESH();
                float acc[28];
                const uint32_t roA = hr ? 256u : 0u, roB = hr ? (uint32_t)-1536 : 0u;
                const uint32_t rpA = hr ? 0u : 256u, rpB = hr ? 0u : (uint32_t)-1536;
                float res[28];
                uint32_t v0[14], v1[14], P[14];
                const uint4* ps = xp0 + sl * 512;
#define F2_OWN_A()                                                                             \
    R_WAIT();                                                                                  \
    d0 = BASE128(0, 16, R_ADJ + roA); d1 = BASE128(0, 16, R_ADJ + roB);                        \
    wg_fence();                                                                                \
    FOR14(if constexpr (t < OT) mma_rs56<1, t * 128>(acc, H[4 * t], H[4 * t + 1], H[4 * t + 2], H[4 * t + 3], t > 0, d0)); \
    wg_commit();
#define F2_OWN_B()                                                                             \
    wg_fence();                                                                                \
    FOR14(if constexpr (t >= OT) mma_rs56<1, t * 128>(acc, H[4 * t], H[4 * t + 1], H[4 * t + 2], H[4 * t + 3], 1, t < 12 ? d0 : d1)); \
    wg_commit();                                                                               \
    R_NEXT();
#define F2_PEER()                                                                              \
    R_WAIT();                                                                                  \
    if (F2PP) { PP_WAIT() }                                                                    \
    d0 = BASE128(0, 16, R_ADJ + rpA); d1 = BASE128(0, 16, R_ADJ + rpB);                        \
    wg_fence();                                                                                \
    FOR14(mma_rs56<1, t * 128>(acc, HP[4 * t], HP[4 * t + 1], HP[4 * t + 2], HP[4 * t + 3], 1, t < 12 ? d0 : d1)); \
    wg_commit();                                                                               \
    if (F2PP) { PP_GO() }                                                                      \
    R_NEXT();
#define F2_TURN(u)                                                                             \
    wg_wait<1>();                                                                              \
    R_RELEASE(2);                                                                              \
    wg_wait<0>();                                                                              \
    R_RELEASE(1);                                                                              \
    _Pragma("unroll") for (int i = 0; i < 14; i++) P[i] = pack2(acc[2 * i], acc[2 * i + 1]);   \
    tag_slice(P, tag);                                                                         \
    asm volatile("" : RW4(P, 0), RW4(P, 4), RW4(P, 8), RW2(P, 12));                            \
    kill<28>(acc);                                                                             \
    F2_OWN_A()                                                                                 \
    if ((u) == 2) { slice_load<PL(3)>(v0, ps, lane); slice_load<PL(4)>(v1, ps, lane); } \
    send_slice<PL(3 + (u))>(xp0 + (2 * ((pr + (u) + 1) & 3) + hr) * 512, lane, P);             \
    seq++;                                                                                     \
    if (lane == 0) st_word(cx(sl), seq);                                                       \
    __syncwarp();                                                                              \
    STAMP(8 + (u) + so);                                                                       \
    F2_OWN_B()
                uint64_t d0, d1;
                F2_OWN_A()
                F2_OWN_B()
                R_WAIT();
                d0 = BASE128(0, 16, R_ADJ + rpA); d1 = BASE128(0, 16, R_ADJ + rpB);
                wg_fence();
                FOR8(mma_rs56<1, t * 128>(acc, HP[4 * t], HP[4 * t + 1], HP[4 * t + 2], HP[4 * t + 3], 1, d0));
                wg_commit();
                mbar_wait(BAR(B_RECV2 + wgi), step >> 1);
#pragma unroll
                for (int k = 0; k < 4; k++) lds4(HP + 32 + 4 * k, hbuf + 16384 + w * 2048 + k * 512 + lane * 16);
                lds4(HP + 48, hbuf + 24576 + w * 1024 + lane * 16);
                lds4(HP + 52, hbuf + 25088 + w * 1024 + lane * 16);
                if (step == 1) PUSH_ACK();
                wg_fence();
                FOR14(if constexpr (t >= 8) mma_rs56<1, t * 128>(acc, HP[4 * t], HP[4 * t + 1], HP[4 * t + 2], HP[4 * t + 3], 1, t < 12 ? d0 : d1));
                wg_commit();
                R_NEXT();
                F2_TURN(0)
                F2_PEER()
                F2_TURN(1)
                F2_PEER()
                F2_TURN(2)
                STAMP(64 + 8 * (step >> 1));
                slice_check<PL(3)>(v0, ps, lane, tag);
                slice_check<PL(4)>(v1, ps, lane, tag);
#pragma unroll
                for (int i = 0; i < 14; i++) { res[2 * i] = bf_lo(v0[i]) + bf_lo(v1[i]); res[2 * i + 1] = bf_hi(v0[i]) + bf_hi(v1[i]); }
                slice_load<PL(2)>(X, ps, lane);
                STAMP(65 + 8 * (step >> 1));
                const uint32_t cv = ld_word(cx(2 * ((pr + 1) & 3) + hr));
                F2_PEER()
                STAMP(66 + 8 * (step >> 1));
                check_cnt(cv, cx(2 * ((pr + 1) & 3) + hr), seq);
                STAMP(67 + 8 * (step >> 1));
                slice_load<PL(5)>(v0, ps, lane);
                x_fix(X, xbits);
                slice_check<PL(5)>(v0, ps, lane, tag);
#pragma unroll
                for (int i = 0; i < 14; i++) { res[2 * i] += bf_lo(v0[i]); res[2 * i + 1] += bf_hi(v0[i]); }
                STAMP(11 + so);
                wg_wait<0>();
                if (EARLYK >= 1) R_RELEASE(2);
                STAMP(12 + so);
                WSUM(85 + 7 * (step >> 1));
#pragma unroll
                for (int i = 0; i < 14; i++) X[i] = pack2(fmaf(res[2 * i] + acc[2 * i], 0.5f, bf_lo(X[i])), fmaf(res[2 * i + 1] + acc[2 * i + 1], 0.5f, bf_hi(X[i])));
            }
        }
        {
            const int m = lane >> 3, rr = lane & 7;
            const uint32_t ob = hbuf + w * 2048, rowa = ob + (rr + 8 * (m & 1)) * 112 + (m >> 1) * 16;
#pragma unroll
            for (int j = 0; j < 3; j++) stsm4(rowa + 32 * j, X[4 * j], X[4 * j + 1], X[4 * j + 2], X[4 * j + 3]);
            asm volatile("stmatrix.sync.aligned.m8n8.x2.shared.b16 [%0], {%1,%2};" ::"r"(ob + (rr + 8 * (m & 1)) * 112 + 96), "r"(X[12]), "r"(X[13]) : "memory");
            fence_async();
            __syncwarp();
            if (lane == 0) {
                asm volatile("cp.async.bulk.tensor.2d.global.shared::cta.bulk_group [%0, {%2, %3}], [%1];" ::"l"(&maps.out), "r"(ob), "r"(56 * sl), "r"(tile * 128 + (tid >> 5) * 16) : "memory");
                asm volatile("cp.async.bulk.commit_group;" ::: "memory");
                asm volatile("cp.async.bulk.wait_group.read 0;" ::: "memory");
            }
        }
        STAMP(50);
        GSTAMP(61);
        PDUMP();
    }
}

typedef CUresult (*EncodeFn)(CUtensorMap*, CUtensorMapDataType, cuuint32_t, void*, const cuuint64_t*, const cuuint64_t*, const cuuint32_t*,
                             const cuuint32_t*, CUtensorMapInterleave, CUtensorMapSwizzle, CUtensorMapL2promotion, CUtensorMapFloatOOBfill);

static void make_map(EncodeFn enc, CUtensorMap* m, const void* p, uint64_t cols, uint64_t rows, uint32_t bc, uint32_t br, CUtensorMapSwizzle sw) {
    cuuint64_t gd[2] = {cols, rows};
    cuuint64_t gs[1] = {cols * 2};
    cuuint32_t bd[2] = {bc, br};
    cuuint32_t es[2] = {1, 1};
    enc(m, CU_TENSOR_MAP_DATA_TYPE_BFLOAT16, 2, const_cast<void*>(p), gd, gs, bd, es, CU_TENSOR_MAP_INTERLEAVE_NONE, sw,
        CU_TENSOR_MAP_L2_PROMOTION_L2_128B, CU_TENSOR_MAP_FLOAT_OOB_FILL_NONE);
}

extern "C" void kernel_launch(void* const* d_in, const int* in_sizes, int n_in, void* d_out, int out_size) {
    (void)in_sizes; (void)n_in; (void)out_size;
    static EncodeFn enc = nullptr;
    static Scratch* scratch = nullptr;
    if (!enc) {
        void* fn = nullptr;
        cudaDriverEntryPointQueryResult qr;
        cudaGetDriverEntryPoint("cuTensorMapEncodeTiled", &fn, cudaEnableDefault, &qr);
        enc = (EncodeFn)fn;
        cudaGetSymbolAddress((void**)&scratch, g_scratch);
        cudaFuncSetAttribute(fused_kernel, cudaFuncAttributeMaxDynamicSharedMemorySize, SMEM_BYTES);
    }
    Maps maps;
    {
        cuuint64_t gd[3] = {64, 2048, 7};
        cuuint64_t gs[2] = {896, 128};
        cuuint32_t bd[3] = {64, 32, 7};
        cuuint32_t es[3] = {1, 1, 1};
        enc(&maps.x, CU_TENSOR_MAP_DATA_TYPE_BFLOAT16, 3, d_in[0], gd, gs, bd, es, CU_TENSOR_MAP_INTERLEAVE_NONE, CU_TENSOR_MAP_SWIZZLE_128B,
            CU_TENSOR_MAP_L2_PROMOTION_L2_128B, CU_TENSOR_MAP_FLOAT_OOB_FILL_NONE);
    }
    make_map(enc, &maps.out, d_out, 448, 2048, 56, 16, CU_TENSOR_MAP_SWIZZLE_NONE);
    make_map(enc, &maps.qkv, d_in[1], 1344, 448, 64, 112, CU_TENSOR_MAP_SWIZZLE_128B);
    make_map(enc, &maps.wo, d_in[3], 448, 448, 64, 112, CU_TENSOR_MAP_SWIZZLE_128B);
    make_map(enc, &maps.wg, d_in[5], 1792, 448, 64, 112, CU_TENSOR_MAP_SWIZZLE_128B);
    make_map(enc, &maps.wu, d_in[6], 1792, 448, 64, 112, CU_TENSOR_MAP_SWIZZLE_128B);
    make_map(enc, &maps.wg32, d_in[5], 1792, 448, 32, 112, CU_TENSOR_MAP_SWIZZLE_64B);
    make_map(enc, &maps.wu32, d_in[6], 1792, 448, 32, 112, CU_TENSOR_MAP_SWIZZLE_64B);
    make_map(enc, &maps.wd, d_in[7], 448, 1792, 64, 112, CU_TENSOR_MAP_SWIZZLE_128B);
    fused_kernel<<<128, 384, SMEM_BYTES>>>(scratch, (const __nv_bfloat16*)d_in[0], (const __nv_bfloat16*)d_in[2], 7, (const __nv_bfloat16*)d_in[5],
                                           (const __nv_bfloat16*)d_in[6], (const __nv_bfloat16*)d_in[7], maps);
}
```

```cpp
#include <cuda_runtime.h>
#include <cuda.h>
#include <cuda_bf16.h>
#include <stdint.h>
#include <type_traits>

#define MC 0
#define PPF 2
#define GE 0
#define ACAN 1
#define SPLIT0 1
#define OT 2
#define F2PP 0
#define PPK 2
#define QE 1
#define OST 1
#define GB 1
#define B3T 6
#define PP

namespace {

constexpr uint32_t STAGE = 28672, HALF = 14336;
constexpr int NST = 5;
constexpr uint32_t OFF_H = NST * STAGE;
constexpr uint32_t OFF_KVB = OFF_H + 2 * STAGE;
constexpr uint32_t OFF_WPHI = OFF_KVB + 16384;
constexpr uint32_t OFF_XR = OFF_WPHI + 7168;
constexpr uint32_t OFF_BAR = OFF_XR + 6144;
constexpr uint32_t SMEM_BYTES = OFF_BAR + 256 + 1536;
constexpr int B_EMPTY = NST, B_RECV = 2 * NST, B_RECV2 = B_RECV + 2, B_PACK = B_RECV2 + 2, B_GAT = B_PACK + 1, B_ACK = B_GAT + 8, B_ACK2 = B_ACK + 2, B_COUNT = B_ACK2 + 2;

constexpr int PACK = 14;

struct Maps { CUtensorMap x, qkv, wo, wg, wu, wg32, wu32, wd, out; };

}

constexpr int PLANE = 16 * 2 * 8 * 512;
struct Scratch {
    uint4 ex[6 * PLANE];
    uint4 kv1[8 * 16 * 16 * 32];
    uint4 kv2[8 * 512];
    uint32_t c1[8 * 8 * 16 * 32];
    uint32_t cw[8 * 32];
    uint4 wp[8 * 32 * (HALF / 16)];
};
__device__ __align__(1024) Scratch g_scratch;
#define g_ex (sc->ex)
#define g_kv1 (sc->kv1)
#define g_kv2 (sc->kv2)
#define g_c1 (sc->c1)
#define g_cw (sc->cw)
#define g_wp (sc->wp)
#define STAMP(i)
#define GSTAMP(i)
#define PDUMP()
#define ASTAMP(i)

namespace {

__device__ __forceinline__ int fresh_tid() { int t; asm volatile("mov.u32 %0, %%tid.x;" : "=r"(t)); return t; }
template <int N> __device__ __forceinline__ void kill(uint32_t* v) {
#pragma unroll
    for (int i = 0; i < N; i++) v[i] = 0;
}
template <int N> __device__ __forceinline__ void kill(float* v) {
#pragma unroll
    for (int i = 0; i < N; i++) v[i] = 0.f;
}
__device__ __forceinline__ uint32_t s2u(const void* p) { return (uint32_t)__cvta_generic_to_shared(p); }
__device__ __forceinline__ void mbar_init(uint32_t a, uint32_t c) { asm volatile("mbarrier.init.shared::cta.b64 [%0], %1;" ::"r"(a), "r"(c) : "memory"); }
__device__ __forceinline__ void mbar_expect_tx(uint32_t a, uint32_t b) { asm volatile("mbarrier.arrive.expect_tx.shared::cta.b64 _, [%0], %1;" ::"r"(a), "r"(b) : "memory"); }
__device__ __forceinline__ void mbar_arrive(uint32_t a) { asm volatile("mbarrier.arrive.shared::cta.b64 _, [%0];" ::"r"(a) : "memory"); }
#define GIVE_UP(id) "trap;\n"
#define SPIN_MAX "0x400000"
#define SPIN_TAIL(id) "add.u32 n, n, 1;\n setp.lt.u32 p, n, " SPIN_MAX ";\n @p bra.uni LP;\n" GIVE_UP(id) " DN:\n }"
__device__ __forceinline__ void mbar_wait(uint32_t a, uint32_t ph) {
    asm volatile("{ .reg .pred p; .reg .b32 n; mov.u32 n, 0;\n LP:\n"
                 "mbarrier.try_wait.parity.shared::cta.b64 p, [%0], %1;\n @p bra DN;\n"
                 "add.u32 n, n, 1;\n setp.lt.u32 p, n, " SPIN_MAX ";\n @p bra LP;\n"
                 GIVE_UP("")
                 " DN:\n }" ::"r"(a), "r"(ph) : "memory");
}
#define ELECT "{ .reg .pred e; elect.sync _|e, 0xffffffff; @e "
__device__ __forceinline__ void tma2d(uint32_t dst, const CUtensorMap* m, int c0, int c1, uint32_t bar) {
    asm volatile(ELECT "cp.async.bulk.tensor.2d.shared::cluster.global.mbarrier::complete_tx::bytes [%0], [%1, {%3, %4}], [%2]; }" ::"r"(dst), "l"(m), "r"(bar), "r"(c0), "r"(c1) : "memory");
}
__device__ __forceinline__ void tma3x(uint32_t dst, const CUtensorMap* m, int row, uint32_t bar) {
    asm volatile(ELECT "cp.async.bulk.tensor.3d.shared::cluster.global.mbarrier::complete_tx::bytes [%0], [%1, {0, %3, 0}], [%2]; }" ::"r"(dst), "l"(m), "r"(bar), "r"(row) : "memory");
}
template <int OFF>
__device__ __forceinline__ void ld_pkt(uint32_t* v, const uint4* p) {
    asm volatile("{ .reg .b128 t; ld.relaxed.gpu.global.b128 t, [%4+%5]; mov.b128 {%0,%1,%2,%3}, t; }" : "=r"(v[0]), "=r"(v[1]), "=r"(v[2]), "=r"(v[3]) : "l"(p), "n"(OFF * 16) : "memory");
}
template <int OFF>
__device__ __forceinline__ void st_pkt(uint4* p, uint32_t a, uint32_t b, uint32_t c, uint32_t d) {
    asm volatile("{ .reg .b128 t; mov.b128 t, {%1,%2,%3,%4}; st.relaxed.gpu.global.b128 [%0+%5], t; }" ::"l"(p), "r"(a), "r"(b), "r"(c), "r"(d), "n"(OFF * 16) : "memory");
}
__device__ __forceinline__ uint32_t pack2(float lo, float hi) {
    uint32_t r;
    asm("cvt.rn.bf16x2.f32 %0, %1, %2;" : "=r"(r) : "f"(hi), "f"(lo));
    return r;
}
__device__ __forceinline__ float bf_lo(uint32_t w) { return __uint_as_float(w << 16); }
__device__ __forceinline__ float bf_hi(uint32_t w) { return __uint_as_float(w & 0xffff0000u); }
__device__ __forceinline__ uint32_t settag(uint32_t w, uint32_t tag) { return (w & ~1u) | tag; }
__device__ __forceinline__ float ex2(float x) { float y; asm("ex2.approx.ftz.f32 %0, %1;" : "=f"(y) : "f"(x)); return y; }
__device__ __forceinline__ float rcp(float x) { float y; asm("rcp.approx.ftz.f32 %0, %1;" : "=f"(y) : "f"(x)); return y; }
__device__ __forceinline__ float tanh_hw(float x) { float y; asm("tanh.approx.f32 %0, %1;" : "=f"(y) : "f"(x)); return y; }
__device__ __forceinline__ void stsm4(uint32_t addr, uint32_t a, uint32_t b, uint32_t c, uint32_t d) {
    asm volatile("stmatrix.sync.aligned.m8n8.x4.shared.b16 [%0], {%1,%2,%3,%4};" ::"r"(addr), "r"(a), "r"(b), "r"(c), "r"(d) : "memory");
}
__device__ __forceinline__ void fence_async() { asm volatile("fence.proxy.async.shared::cta;" ::: "memory"); }
__device__ __forceinline__ void bar_sync(int id, int n) { asm volatile("bar.sync %0, %1;" ::"r"(id), "r"(n) : "memory"); }
__device__ __forceinline__ void bar_arrive(int id, int n) { asm volatile("bar.arrive %0, %1;" ::"r"(id), "r"(n) : "memory"); }
__device__ __forceinline__ void wg_fence() { asm volatile("wgmma.fence.sync.aligned;" ::: "memory"); }
__device__ __forceinline__ void wg_commit() { asm volatile("wgmma.commit_group.sync.aligned;" ::: "memory"); }
template <int N> __device__ __forceinline__ void wg_wait() { asm volatile("wgmma.wait_group.sync.aligned %0;" ::"n"(N) : "memory"); }

constexpr uint32_t SB0 = 1024;
__host__ __device__ constexpr uint32_t dlo(uint32_t off, uint32_t lbo) { return ((SB0 + off) >> 4) | ((lbo >> 4) << 16); }
__host__ __device__ constexpr uint32_t dhi(uint32_t sbo, uint32_t sw) { return (sbo >> 4) | (sw << 30); }
__device__ __forceinline__ uint64_t dbase(uint32_t lo, uint32_t hi) { uint64_t d; asm volatile("mov.b64 %0, {%1, %2};" : "=l"(d) : "r"(lo), "r"(hi)); return d; }
#define BASE128(off, lbo, adj) dbase(dlo(off, lbo) + (adj), dhi(1024, 1))
#define BASE64(off, lbo, adj) dbase(dlo(off, lbo) + (adj), dhi(512, 2))

#define ACC4(d, o) "+f"(d[o]), "+f"(d[o + 1]), "+f"(d[o + 2]), "+f"(d[o + 3])
#define ACC28(d) ACC4(d, 0), ACC4(d, 4), ACC4(d, 8), ACC4(d, 12), ACC4(d, 16), ACC4(d, 20), ACC4(d, 24)
#define ACC32(d, o) ACC4(d, o), ACC4(d, o + 4), ACC4(d, o + 8), ACC4(d, o + 12), ACC4(d, o + 16), ACC4(d, o + 20), ACC4(d, o + 24), ACC4(d, o + 28)

template <int TB, uint64_t D>
__device__ __forceinline__ void mma_rs56(float* d, uint32_t a0, uint32_t a1, uint32_t a2, uint32_t a3, int sd, uint64_t base) {
    asm volatile("{ .reg .pred p; .reg .b64 db; setp.ne.b32 p, %32, 0; add.u64 db, %33, %34;\n"
                 "wgmma.mma_async.sync.aligned.m64n56k16.f32.bf16.bf16 "
                 "{%0,%1,%2,%3,%4,%5,%6,%7,%8,%9,%10,%11,%12,%13,%14,%15,%16,%17,%18,%19,%20,%21,%22,%23,%24,%25,%26,%27}, "
                 "{%28,%29,%30,%31}, db, p, 1, 1, %35; }\n"
                 : ACC28(d)
                 : "r"(a0), "r"(a1), "r"(a2), "r"(a3), "r"(sd), "l"(base), "n"(D), "n"(TB));
}
template <int TB, uint64_t D>
__device__ __forceinline__ void mma_rs64(float* d, uint32_t a0, uint32_t a1, uint32_t a2, uint32_t a3, int sd, uint64_t base) {
    asm volatile("{ .reg .pred p; .reg .b64 db; setp.ne.b32 p, %36, 0; add.u64 db, %37, %38;\n"
                 "wgmma.mma_async.sync.aligned.m64n64k16.f32.bf16.bf16 "
                 "{%0,%1,%2,%3,%4,%5,%6,%7,%8,%9,%10,%11,%12,%13,%14,%15,%16,%17,%18,%19,%20,%21,%22,%23,%24,%25,%26,%27,%28,%29,%30,%31}, "
                 "{%32,%33,%34,%35}, db, p, 1, 1, %39; }\n"
                 : ACC32(d, 0)
                 : "r"(a0), "r"(a1), "r"(a2), "r"(a3), "r"(sd), "l"(base), "n"(D), "n"(TB));
}
template <int TB, uint64_t D>
__device__ __forceinline__ void mma_rs128(float* d, uint32_t a0, uint32_t a1, uint32_t a2, uint32_t a3, int sd, uint64_t base) {
    asm volatile("{ .reg .pred p; .reg .b64 db; setp.ne.b32 p, %68, 0; add.u64 db, %69, %70;\n"
                 "wgmma.mma_async.sync.aligned.m64n128k16.f32.bf16.bf16 "
                 "{%0,%1,%2,%3,%4,%5,%6,%7,%8,%9,%10,%11,%12,%13,%14,%15,%16,%17,%18,%19,%20,%21,%22,%23,%24,%25,%26,%27,%28,%29,%30,%31,%32,%33,%34,%35,%36,%37,%38,%39,%40,%41,%42,%43,%44,%45,%46,%47,%48,%49,%50,%51,%52,%53,%54,%55,%56,%57,%58,%59,%60,%61,%62,%63}, "
                 "{%64,%65,%66,%67}, db, p, 1, 1, %71; }\n"
                 : ACC32(d, 0), ACC32(d, 32)
                 : "r"(a0), "r"(a1), "r"(a2), "r"(a3), "r"(sd), "l"(base), "n"(D), "n"(TB));
}
template <uint64_t DA, uint64_t DB>
__device__ __forceinline__ void mma_ss56_tt(float* d, int sd, uint64_t ba, uint64_t bb) {
    asm volatile("{ .reg .pred p; .reg .b64 da, db; setp.ne.b32 p, %28, 0; add.u64 da, %29, %31; add.u64 db, %30, %32;\n"
                 "wgmma.mma_async.sync.aligned.m64n56k16.f32.bf16.bf16 "
                 "{%0,%1,%2,%3,%4,%5,%6,%7,%8,%9,%10,%11,%12,%13,%14,%15,%16,%17,%18,%19,%20,%21,%22,%23,%24,%25,%26,%27}, "
                 "da, db, p, 1, 1, 1, 1; }\n"
                 : ACC28(d)
                 : "r"(sd), "l"(ba), "l"(bb), "n"(DA), "n"(DB));
}
template <int... I> struct Seq {};
template <class F, int... I> __device__ __forceinline__ void static_for_impl(F&& f, Seq<I...>) { (f(std::integral_constant<int, I>{}), ...); }
#define FOR7(...) static_for_impl([&](auto T_) { constexpr int t = decltype(T_)::value; __VA_ARGS__; }, Seq<0, 1, 2, 3, 4, 5, 6>{})
#define FOR8(...) static_for_impl([&](auto T_) { constexpr int t = decltype(T_)::value; __VA_ARGS__; }, Seq<0, 1, 2, 3, 4, 5, 6, 7>{})
#define FOR14(...) static_for_impl([&](auto T_) { constexpr int t = decltype(T_)::value; __VA_ARGS__; }, Seq<0, 1, 2, 3, 4, 5, 6, 7, 8, 9, 10, 11, 12, 13>{})

__device__ __forceinline__ int kblk(int p, int b) { return b == 0 ? p : b - (b <= p); }
__host__ __device__ constexpr int krow(int t) { return t < 3 ? 16 * t : (t < 6 ? 56 + 16 * (t - 3) : 48); }
#define AQ(A, b, t) ((t) < 3 ? A[2 * (b)][4 * (t)] : (t) < 6 ? A[2 * (b) + 1][4 * ((t) - 3)] : A[2 * (b)][12]), \
                    ((t) < 3 ? A[2 * (b)][4 * (t) + 1] : (t) < 6 ? A[2 * (b) + 1][4 * ((t) - 3) + 1] : A[2 * (b)][13]), \
                    ((t) < 3 ? A[2 * (b)][4 * (t) + 2] : (t) < 6 ? A[2 * (b) + 1][4 * ((t) - 3) + 2] : A[2 * (b) + 1][12]), \
                    ((t) < 3 ? A[2 * (b)][4 * (t) + 3] : (t) < 6 ? A[2 * (b) + 1][4 * ((t) - 3) + 3] : A[2 * (b) + 1][13])
#define D128(off, t) ((uint64_t)(((off) + krow(t) * 128) >> 4) + ((uint64_t)((t) == 6 ? (7168 - 1024) >> 4 : 0) << 32))
#define D64(off, t) ((uint64_t)(((off) + krow(t) * 64) >> 4) + ((uint64_t)((t) == 6 ? (3584 - 512) >> 4 : 0) << 32))

#define PL(k) (((k) - 3) * PLANE)
__device__ __forceinline__ void st_word(uint32_t* p, uint32_t v) { asm volatile("st.relaxed.gpu.global.u32 [%0], %1;" ::"l"(p), "r"(v) : "memory"); }
__device__ __forceinline__ uint32_t ld_word(const uint32_t* p) { uint32_t v; asm volatile("ld.relaxed.gpu.global.u32 %0, [%1];" : "=r"(v) : "l"(p) : "memory"); return v; }
__device__ __forceinline__ void tag_slice(uint32_t* w, uint32_t tag) { w[0] = settag(w[0], tag); w[4] = settag(w[4], tag); w[8] = settag(w[8], tag); w[12] = settag(w[12], tag); }
template <int O>
__device__ __forceinline__ void send_slice(uint4* dst, int lane, const uint32_t* w) {
    st_pkt<O>(dst, w[0], w[1], w[2], w[3]);
    st_pkt<O + 32>(dst, w[4], w[5], w[6], w[7]);
    st_pkt<O + 64>(dst, w[8], w[9], w[10], w[11]);
    asm volatile("{ .reg .b64 t; mov.b64 t, {%1,%2}; st.relaxed.gpu.global.b64 [%0+%3], t; }" ::"l"((char*)dst - lane * 8), "r"(w[12]), "r"(w[13]), "n"(16 * (O + 96)) : "memory");
}
#define RW4(v, o) "+r"(v[o]), "+r"(v[(o) + 1]), "+r"(v[(o) + 2]), "+r"(v[(o) + 3])
#define RW2(v, o) "+r"(v[o]), "+r"(v[(o) + 1])
#define WR4(v, o) "=&r"(v[o]), "=&r"(v[(o) + 1]), "=&r"(v[(o) + 2]), "=&r"(v[(o) + 3])
#define LDP(a, b, c, d, addr, off) "ld.relaxed.gpu.global.b128 q, [" addr "+" off "];\n mov.b128 {" a "," b "," c "," d "}, q;\n"
#define LDH(a, b, addr, off) "ld.relaxed.gpu.global.b64 h, [" addr "+" off "];\n mov.b64 {" a "," b "}, h;\n"
#define VOTE_OK "and.b32 t, t, 1;\n setp.ne.u32 p, t, 0;\n vote.sync.any.pred p, p, 0xffffffff;\n @!p bra.uni DN;\n"
#define CHK(x, tag) "lop3.b32 t, " x ", " tag ", t, 0xBE;\n"
__device__ __forceinline__ void check_cnt(uint32_t v, const uint32_t* p, uint32_t target) {
    asm volatile("{ .reg .pred p; .reg .b32 n, t; mov.u32 n, 0; mov.u32 t, %2;\n LP:\n"
                 "sub.s32 t, t, %1;\n setp.lt.s32 p, t, 0;\n vote.sync.any.pred p, p, 0xffffffff;\n @!p bra.uni DN;\n ld.relaxed.gpu.global.u32 t, [%0];\n" SPIN_TAIL("7")
                 ::"l"(p), "r"(target), "r"(v) : "memory");
}
__device__ __forceinline__ void poll_cnt(const uint32_t* p, uint32_t target) {
    asm volatile("{ .reg .pred p; .reg .b32 n, t; mov.u32 n, 0;\n LP:\n"
                 "ld.relaxed.gpu.global.u32 t, [%0];\n sub.s32 t, t, %1;\n setp.lt.s32 p, t, 0;\n vote.sync.any.pred p, p, 0xffffffff;\n @!p bra.uni DN;\n" SPIN_TAIL("1")
                 ::"l"(p), "r"(target) : "memory");
}
template <int STR>
__device__ __forceinline__ void poll4_kv(uint32_t* v, const uint4* p, uint32_t tag) {
    asm volatile("{ .reg .pred p; .reg .b32 n, t; .reg .b128 q; mov.u32 n, 0;\n LP:\n"
                 LDP("%0", "%1", "%2", "%3", "%16", "0") LDP("%4", "%5", "%6", "%7", "%16", "%18")
                 LDP("%8", "%9", "%10", "%11", "%16", "%19") LDP("%12", "%13", "%14", "%15", "%16", "%20")
                 "xor.b32 t, %0, %17;\n" CHK("%4", "%17") CHK("%8", "%17") CHK("%12", "%17") VOTE_OK SPIN_TAIL("2")
                 : WR4(v, 0), WR4(v, 4), WR4(v, 8), WR4(v, 12)
                 : "l"(p), "r"(tag), "n"(16 * STR), "n"(32 * STR), "n"(48 * STR)
                 : "memory");
}
template <int B>
__device__ __forceinline__ void blk_load(uint32_t (&A)[8][14], const uint4* src, int lane) {
    ld_pkt<0>(&A[2 * B][0], src); ld_pkt<32>(&A[2 * B][4], src); ld_pkt<64>(&A[2 * B][8], src);
    ld_pkt<512>(&A[2 * B + 1][0], src); ld_pkt<544>(&A[2 * B + 1][4], src); ld_pkt<576>(&A[2 * B + 1][8], src);
    asm volatile("{ .reg .b64 h;\n" LDH("%0", "%1", "%4", "1536") LDH("%2", "%3", "%4", "9728") "}"
                 : "=&r"(A[2 * B][12]), "=&r"(A[2 * B][13]), "=&r"(A[2 * B + 1][12]), "=&r"(A[2 * B + 1][13])
                 : "l"((const char*)src - lane * 8) : "memory");
}
template <int B>
__device__ __forceinline__ void blk_check(uint32_t (&A)[8][14], const uint4* src, int lane, uint32_t tag) {
    asm volatile("{ .reg .pred p; .reg .b32 n, t; .reg .b128 q; .reg .b64 h, a8; mov.u32 n, 0;\n LP:\n"
                 "xor.b32 t, %0, %30;\n" CHK("%4", "%30") CHK("%8", "%30") CHK("%12", "%30") CHK("%16", "%30") CHK("%20", "%30") CHK("%24", "%30") CHK("%26", "%30") VOTE_OK
                 LDP("%0", "%1", "%2", "%3", "%28", "0") LDP("%4", "%5", "%6", "%7", "%28", "512") LDP("%8", "%9", "%10", "%11", "%28", "1024")
                 LDP("%12", "%13", "%14", "%15", "%28", "8192") LDP("%16", "%17", "%18", "%19", "%28", "8704") LDP("%20", "%21", "%22", "%23", "%28", "9216")
                 "mad.wide.s32 a8, %29, -8, %28;\n" LDH("%24", "%25", "a8", "1536") LDH("%26", "%27", "a8", "9728") SPIN_TAIL("3")
                 "\n and.b32 %0, %0, -2; and.b32 %4, %4, -2; and.b32 %8, %8, -2; and.b32 %12, %12, -2; and.b32 %16, %16, -2; and.b32 %20, %20, -2; and.b32 %24, %24, -2; and.b32 %26, %26, -2;"
                 : RW4(A[2 * B], 0), RW4(A[2 * B], 4), RW4(A[2 * B], 8), RW4(A[2 * B + 1], 0), RW4(A[2 * B + 1], 4), RW4(A[2 * B + 1], 8),
                   RW2(A[2 * B], 12), RW2(A[2 * B + 1], 12)
                 : "l"(src), "r"(lane), "r"(tag)
                 : "memory");
}
__device__ __forceinline__ void st_async4(uint32_t a, uint32_t x, uint32_t y, uint32_t z, uint32_t w, uint32_t bar) {
    asm volatile("st.async.weak.shared::cluster.mbarrier::complete_tx::bytes.v4.b32 [%0], {%1,%2,%3,%4}, [%5];" ::"r"(a), "r"(x), "r"(y), "r"(z), "r"(w), "r"(bar) : "memory");
}
__device__ __forceinline__ uint32_t mapa(uint32_t a, uint32_t cta) { uint32_t r; asm("mapa.shared::cluster.u32 %0, %1, %2;" : "=r"(r) : "r"(a), "r"(cta)); return r; }
__device__ __forceinline__ void stat_load(uint32_t* v, const uint4* p) { ld_pkt<0>(v, p); ld_pkt<512>(v + 4, p); }
__device__ __forceinline__ void stat_check(uint32_t* v, const uint4* p, uint32_t tag) {
    asm volatile("{ .reg .pred p; .reg .b32 n, t; .reg .b128 q; mov.u32 n, 0;\n LP:\n"
                 "xor.b32 t, %3, %9;\n" CHK("%7", "%9") VOTE_OK
                 LDP("%0", "%1", "%2", "%3", "%8", "0") LDP("%4", "%5", "%6", "%7", "%8", "8192") SPIN_TAIL("4")
                 : RW4(v, 0), RW4(v, 4) : "l"(p), "r"(tag) : "memory");
}
__device__ __forceinline__ uint32_t x_bits(const uint32_t* X) {
    uint32_t r;
    asm volatile("{ .reg .b32 a, b; prmt.b32 a, %1, %2, 0x0040; prmt.b32 b, %3, %4, 0x0040; prmt.b32 %0, a, b, 0x5410; }" : "=r"(r) : "r"(X[0]), "r"(X[4]), "r"(X[8]), "r"(X[12]));
    return r;
}
template <int O>
__device__ __forceinline__ void slice_load(uint32_t* v, const uint4* p, int lane) {
    ld_pkt<O>(v, p); ld_pkt<O + 32>(v + 4, p); ld_pkt<O + 64>(v + 8, p);
    asm volatile("{ .reg .b64 h;\n" LDH("%0", "%1", "%2", "%3") "}" : "=r"(v[12]), "=r"(v[13]) : "l"((const char*)p - lane * 8), "n"(16 * (O + 96)) : "memory");
}
template <int O>
__device__ __forceinline__ void slice_check(uint32_t* v, const uint4* p, int lane, uint32_t tag) {
    asm volatile("{ .reg .pred p; .reg .b32 n, t; .reg .b128 q; .reg .b64 h; mov.u32 n, 0;\n LP:\n"
                 "xor.b32 t, %0, %16;\n" CHK("%4", "%16") CHK("%8", "%16") CHK("%12", "%16") VOTE_OK
                 LDP("%0", "%1", "%2", "%3", "%14", "%17") LDP("%4", "%5", "%6", "%7", "%14", "%18") LDP("%8", "%9", "%10", "%11", "%14", "%19")
                 LDH("%12", "%13", "%15", "%20") SPIN_TAIL("5")
                 : RW4(v, 0), RW4(v, 4), RW4(v, 8), RW2(v, 12)
                 : "l"(p), "l"((const char*)p - lane * 8), "r"(tag), "n"(16 * O), "n"(16 * (O + 32)), "n"(16 * (O + 64)), "n"(16 * (O + 96))
                 : "memory");
}
__device__ __forceinline__ void x_fix(uint32_t* X, uint32_t bits) {
    X[0] = __byte_perm(X[0], bits, 0x3214); X[4] = __byte_perm(X[4], bits, 0x3215); X[8] = __byte_perm(X[8], bits, 0x3216); X[12] = __byte_perm(X[12], bits, 0x3217);
}
__device__ __forceinline__ void sts4(uint32_t a, uint32_t x, uint32_t y, uint32_t z, uint32_t w) {
    asm volatile("st.shared.v4.u32 [%0], {%1,%2,%3,%4};" ::"r"(a), "r"(x), "r"(y), "r"(z), "r"(w) : "memory");
}
__device__ __forceinline__ void lds4(uint32_t* v, uint32_t a) {
    asm volatile("ld.shared.v4.u32 {%0,%1,%2,%3}, [%4];" : "=r"(v[0]), "=r"(v[1]), "=r"(v[2]), "=r"(v[3]) : "r"(a) : "memory");
}
struct LnCoef { uint32_t hi, lo, sh; };
__device__ __forceinline__ LnCoef ln_coef(float sum, float sq) {
    sum += __shfl_xor_sync(0xffffffffu, sum, 1); sq += __shfl_xor_sync(0xffffffffu, sq, 1);
    sum += __shfl_xor_sync(0xffffffffu, sum, 2); sq += __shfl_xor_sync(0xffffffffu, sq, 2);
    const float mean = sum * (1.f / 448.f);
    const float var = fmaxf(fmaf(-mean, mean, sq * (1.f / 448.f)), 0.f);
    const float sc = rsqrtf(var + 1e-5f);
    LnCoef r;
    r.hi = pack2(sc, sc);
    const float lo = sc - bf_lo(r.hi), sh = -mean * sc;
    r.lo = pack2(lo, lo);
    r.sh = pack2(sh, sh);
    return r;
}
template <int B>
__device__ __forceinline__ void normalize(uint32_t (&A)[8][14], const LnCoef& c0, const LnCoef& c1) {
#pragma unroll
    for (int s = 2 * B; s < 2 * B + 2; s++)
#pragma unroll
        for (int i = 0; i < 14; i++) {
            const LnCoef& k = (i & 1) ? c1 : c0;
            asm("{ .reg .b32 t; fma.rn.bf16x2 t, %0, %2, %3; fma.rn.bf16x2 %0, %0, %1, t; }" : "+r"(A[s][i]) : "r"(k.hi), "r"(k.lo), "r"(k.sh));
        }
}
__device__ __forceinline__ void slice_stats(const uint32_t* w, float* st) {
    float a = 0.f, b = 0.f, p = 0.f, q = 0.f;
#pragma unroll
    for (int i = 0; i < 7; i++) {
        const float e0 = bf_lo(w[2 * i]), e1 = bf_hi(w[2 * i]), e2 = bf_lo(w[2 * i + 1]), e3 = bf_hi(w[2 * i + 1]);
        a += e0 + e1; b += e2 + e3;
        p = fmaf(e0, e0, p); p = fmaf(e1, e1, p); q = fmaf(e2, e2, q); q = fmaf(e3, e3, q);
    }
    a += __shfl_xor_sync(0xffffffffu, a, 1); p += __shfl_xor_sync(0xffffffffu, p, 1); b += __shfl_xor_sync(0xffffffffu, b, 1); q += __shfl_xor_sync(0xffffffffu, q, 1);
    a += __shfl_xor_sync(0xffffffffu, a, 2); p += __shfl_xor_sync(0xffffffffu, p, 2); b += __shfl_xor_sync(0xffffffffu, b, 2); q += __shfl_xor_sync(0xffffffffu, q, 2);
    st[0] = a; st[1] = p; st[2] = b; st[3] = q;
}
__device__ __forceinline__ void dual_softmax(const float* p, uint32_t* out) {
    constexpr float L = 1.4426950408889634f;
#pragma unroll
    for (int r = 0; r < 2; r++) {
        float mx = fmaxf(p[2 * r], p[2 * r + 1]), mn = fminf(p[2 * r], p[2 * r + 1]);
#pragma unroll
        for (int i = 1; i < 7; i++) {
            mx = fmaxf(mx, fmaxf(p[4 * i + 2 * r], p[4 * i + 2 * r + 1]));
            mn = fminf(mn, fminf(p[4 * i + 2 * r], p[4 * i + 2 * r + 1]));
        }
        mx = fmaxf(mx, __shfl_xor_sync(0xffffffffu, mx, 1));
        mn = fminf(mn, __shfl_xor_sync(0xffffffffu, mn, 1));
        const float bx = -mx * L, bn = mn * L;
        float ep[14], en[14], sp = 0.f, sn = 0.f;
#pragma unroll
        for (int i = 0; i < 14; i++) {
            const float v = p[4 * (i >> 1) + 2 * r + (i & 1)];
            ep[i] = ex2(fmaf(v, L, bx));
            en[i] = ex2(fmaf(v, -L, bn));
            sp += ep[i]; sn += en[i];
        }
        sp += __shfl_xor_sync(0xffffffffu, sp, 1);
        sn += __shfl_xor_sync(0xffffffffu, sn, 1);
        const float ip = rcp(sp), in = rcp(sn);
#pragma unroll
        for (int i = 0; i < 7; i++) {
            out[4 * i + r] = pack2(ep[2 * i] * ip, ep[2 * i + 1] * ip);
            out[4 * i + 2 + r] = pack2(en[2 * i] * in, en[2 * i + 1] * in);
        }
    }
}
__device__ __forceinline__ float geglu(float g, float u) {
    const float t = tanh_hw(g * fmaf(g * g, 0.7978845608028654f * 0.044715f, 0.7978845608028654f));
    const float gu = g * u;
    return fmaf(t, gu, gu);
}
__device__ __forceinline__ void phi_gemm(const float* t, float* p) {
    uint32_t w[14];
#pragma unroll
    for (int i = 0; i < 14; i++) w[i] = pack2(t[2 * i], t[2 * i + 1]);
    const uint64_t db = BASE128(OFF_WPHI, 16, 0);
    wg_fence();
    mma_rs56<0, 0>(p, w[0], w[1], w[2], w[3], 0, db);
    mma_rs56<0, 2>(p, w[4], w[5], w[6], w[7], 1, db);
    mma_rs56<0, 4>(p, w[8], w[9], w[10], w[11], 1, db);
    mma_rs56<0, 6>(p, w[12], w[13], 0u, 0u, 1, db);
    wg_commit();
    wg_wait<0>();
}

}

#define BAR(i) (bars + 8 * (i))
#define R_WAIT() mbar_wait(BAR(slot), ph)
#define WSUM(i)
#define R_ADJ (slot * (STAGE >> 4))
#define R_NEXT() do { eb2 = eb1; eb1 = BAR(B_EMPTY + slot); if (++slot == NST) { slot = 0; ph ^= 1; } } while (0)
#define R_RELEASE(k) do { if (lane == 0) mbar_arrive((k) == 1 ? eb1 : eb2); } while (0)
#define PUSH_BEGIN() do { mbar_wait(BAR(B_ACK + wgi), ackph); ackph ^= 1; } while (0)
#define PUSH_ACK() do { __syncwarp(); if (lane == 0) asm volatile("mbarrier.arrive.shared::cluster.b64 _, [%0];" ::"r"(mapa(BAR(B_ACK + wgi), hr ^ 1)) : "memory"); } while (0)

__global__ void __cluster_dims__(2, 1, 1) __launch_bounds__(384, 1)
fused_kernel(Scratch* const sc, const __nv_bfloat16* __restrict__ x_in, const __nv_bfloat16* __restrict__ w_phi, const int trips,
             const __nv_bfloat16* __restrict__ wg, const __nv_bfloat16* __restrict__ wu, const __nv_bfloat16* __restrict__ wd,
             const __grid_constant__ Maps maps) {
    extern __shared__ __align__(1024) unsigned char smem_raw[];
    const uint32_t sb = s2u(smem_raw);
    const uint32_t bars = sb + OFF_BAR;
    const int wgi = __shfl_sync(0xffffffffu, threadIdx.x >> 7, 0);
    const int hr = blockIdx.x & 1, ck = blockIdx.x >> 1;
    const int gp = (ck - 4) & 7, q7 = ((ck - 36) * 37) >> 8;
    const int pr = __shfl_sync(0xffffffffu, ck < 4 ? ck : (ck < 36 ? (ck - 4) >> 3 : q7), 0);
    const int tile = __shfl_sync(0xffffffffu, ck < 4 ? 0 : (ck < 36 ? (gp ? 2 * gp : 1) : 2 * (ck - 36 - 7 * q7) + 3), 0);
    const int sl = 2 * pr + hr;
    STAMP(0);
    GSTAMP(60);
    if (threadIdx.x == 256) {
#pragma unroll
        for (int i = 0; i < NST; i++) mbar_init(BAR(i), 1);
        asm volatile("fence.mbarrier_init.release.cluster;" ::: "memory");
    }
    if (threadIdx.x == 288) {
        if ((sb & 0x3FFFF) != SB0) asm volatile("trap;");
#pragma unroll
        for (int i = NST; i < B_COUNT; i++) mbar_init(BAR(i), i >= B_ACK ? 4 : (i < B_RECV ? 8 : 1));
        asm volatile("fence.mbarrier_init.release.cluster;" ::: "memory");
    }
    __syncwarp();
    asm volatile("barrier.cluster.arrive.relaxed.aligned;" ::: "memory");

    if (wgi == 2) {
        asm volatile("setmaxnreg.dec.sync.aligned.u32 40;");
        const int t128 = fresh_tid() & 127, w = __shfl_sync(0xffffffffu, t128 >> 5, 0), lane = t128 & 31;
        uint32_t e0[2] = {0, 0}, e1[2] = {0, 0}, cw_target = 0;
        if (w == 0) {
#pragma unroll 1
            for (int n = 0; n < NST; n++) {
                const uint32_t dst = sb + n * STAGE, fb = BAR(n);
                asm volatile(ELECT "mbarrier.arrive.expect_tx.shared::cta.b64 _, [%0], %1; }" ::"r"(fb), "r"(n < 2 ? 2 * STAGE : STAGE) : "memory");
                if (n < 2) {
                    tma3x(sb + OFF_H + n * STAGE, &maps.x, tile * 128 + n * 64, fb);
                    tma3x(dst, &maps.x, tile * 128 + n * 64 + 32, fb);
                } else {
                    if (n == 3) mbar_wait(BAR(1), 0);
                    const int ra = 112 * (n - 2);
                    tma2d(dst, &maps.qkv, 448 + 56 * sl, ra, fb);
                    tma2d(dst + HALF, &maps.qkv, 896 + 56 * sl, ra, fb);
                }
            }
            asm volatile("barrier.cluster.wait.aligned;" ::: "memory");
            cw_target = (ld_word(g_cw + sl * 32) & ~15u) + 16;
#pragma unroll 1
            for (int k = 0; k < 2; k++) {
                const int n = t128 + 32 * k;
                int m = n - 2 - (n > PACK);
                const bool packed = m >= 30 ? (m < 38 || m >= 52) : m >= 22;
                if (m >= 30) m -= 30;
                if (n == PACK) m = tile < 8 ? tile : tile + 14;
                const int rot = n < 8 ? 0 : pr;
                const int ra = 112 * kblk(rot, m & 3), rb = 112 * kblk(rot, 2 * m & 3), rc = 112 * kblk(rot, (2 * m + 1) & 3);
                int kind = 0, m0, m1, c0, c1, r0, r1;
                if (m < 4) { m0 = m1 = 1; c0 = 448 + 56 * sl; c1 = c0 + 448; r0 = r1 = ra; }
                else if (m < 8) { m0 = m1 = m < 6 ? 1 : 2; c0 = c1 = 56 * sl; r0 = rb; r1 = rc; }
                else if (m < 20) { m0 = 3; m1 = 4; c0 = c1 = 224 * sl + 32 * hr + 64 * ((m - 8) >> 2); r0 = r1 = ra; }
                else if (m < 22) { kind = 2; m0 = 5; m1 = 6; c0 = c1 = 224 * sl + (hr ? 0 : 192); r0 = rb; r1 = rc; }
                else { m0 = m1 = 7; c0 = c1 = 56 * (2 * ((pr + (m >> 1) - 10) & 3) + hr); r0 = 224 * (sl ^ (m & 1)); r1 = r0 + 112; }
                if (packed) { kind = 1; r0 = sl * 16 + (m < 8 ? m : m - 14); r1 = 0; }
                e0[0] = e0[1]; e1[0] = e1[1];
                e0[1] = kind | (m0 << 2) | (m1 << 6) | (c0 << 10) | (c1 << 21);
                e1[1] = r0 | (r1 << 16);
            }
        } else {
            const int j = t128 - 32;
            asm volatile("barrier.cluster.wait.aligned;" ::: "memory");
            uint2 wv[7];
            const int k = j < 56 ? j : 55, hh = k >= 28;
#pragma unroll
            for (int i = 0; i < 7; i++) wv[i] = __ldg(reinterpret_cast<const uint2*>(w_phi + (sl * 56 + k) * 28) + i);
#pragma unroll 1
            for (int i = j; i < 7168 / 16; i += 96) sts4(sb + OFF_WPHI + i * 16, 0, 0, 0, 0);
            bar_sync(5, 96);
            if (j < 56) {
                uint32_t a4[4];
#pragma unroll
                for (int q = 0; q < 4; q++) a4[q] = sb + OFF_WPHI + (4 * hh + q) * 128 + ((((k >> 3) ^ (4 * hh + q)) & 7) << 4) + (k & 7) * 2;
                FOR14(const uint32_t v = (t & 1) ? wv[t >> 1].y : wv[t >> 1].x;
                      asm volatile("{ .reg .b16 l, h; mov.b32 {l, h}, %2; st.shared.u16 [%0+%3], l; st.shared.u16 [%1+%3], h; }"
                                   ::"r"(a4[t >= 7 ? 2 : 0]), "r"(a4[t >= 7 ? 3 : 1]), "r"(v), "n"((t % 7) * 1024) : "memory"));
            }
            __syncwarp();
            fence_async();
            bar_arrive(1, 224);
            bar_arrive(9, 224);
            if (w == 1) {
                mbar_wait(BAR(2), 0);
                mbar_wait(BAR(2), 1);
                const int b = blockIdx.x;
                asm volatile(ELECT "cp.async.bulk.prefetch.L2.global [%0], %1; }" ::"l"(wg + b * 6272), "r"(12544) : "memory");
                asm volatile(ELECT "cp.async.bulk.prefetch.L2.global [%0], %1; }" ::"l"(wu + b * 6272), "r"(12544) : "memory");
                asm volatile(ELECT "cp.async.bulk.prefetch.L2.global [%0], %1; }" ::"l"(wd + b * 6272), "r"(12544) : "memory");
            }
        }
        uint32_t kseq = ld_word(g_c1 + (sl * 8 * 16 + tile) * 32);
        int slot = 0, ph = 0, n = NST;
#pragma unroll 1
        for (int layer = 0; layer < 3; layer++) {
            if (w == 0) {
                const int nend = layer == 0 ? 11 : (layer == 1 ? 42 : 63);
#pragma unroll 1
                for (; n < nend; n++) {
                const uint32_t w0 = __shfl_sync(0xffffffffu, n < 32 ? e0[0] : e0[1], n & 31), w1 = __shfl_sync(0xffffffffu, n < 32 ? e1[0] : e1[1], n & 31);
                const uint32_t dst = sb + slot * STAGE, fb = BAR(n == PACK ? B_PACK : slot);
                const CUtensorMap* m0 = &maps.x + ((w0 >> 2) & 15);
                const CUtensorMap* m1 = &maps.x + ((w0 >> 6) & 15);
                const int c0 = (w0 >> 10) & 2047, c1 = w0 >> 21, r0 = w1 & 0xffff, r1 = w1 >> 16;
                if (n == 25) {
                    int it = 0;
                    uint32_t v;
                    do { asm volatile("ld.acquire.gpu.global.u32 %0, [%1];" : "=r"(v) : "l"(g_cw + sl * 32) : "memory"); } while ((int)(v - cw_target) < 0 && ++it < 0x400000);
                    asm volatile("fence.proxy.async.global;" ::: "memory");
                    __syncwarp();
                }
                mbar_wait(BAR(B_EMPTY + slot), ph);
                __syncwarp();
                asm volatile(ELECT "mbarrier.arrive.expect_tx.shared::cta.b64 _, [%0], %1; }" ::"r"(fb), "r"(STAGE) : "memory");
                if ((w0 & 3) == 0) {
                    tma2d(dst, m0, c0, r0, fb);
                    tma2d(dst + HALF, m1, c1, r1, fb);
                } else if (w0 & 1) {
                    asm volatile(ELECT "cp.async.bulk.shared::cluster.global.mbarrier::complete_tx::bytes [%0], [%1], %2, [%3]; }"
                                 ::"r"(dst), "l"(reinterpret_cast<const char*>(g_wp) + (size_t)r0 * STAGE), "r"(STAGE), "r"(fb) : "memory");
                } else {
                    tma2d(dst, m0, c0, r0, fb); tma2d(dst + 7168, m0, c0, r1, fb);
                    tma2d(dst + HALF, m1, c0, r0, fb); tma2d(dst + HALF + 7168, m1, c0, r1, fb);
                }
                if (n == PACK) asm volatile(ELECT "mbarrier.arrive.shared::cta.b64 _, [%0]; }" ::"r"(BAR(slot)) : "memory");
                if (++slot == NST) { slot = 0; ph ^= 1; }
                }
            } else if (w == 1 && layer == 1) {
                constexpr int ps = PACK % NST;
                mbar_wait(BAR(B_PACK), 0);
                asm volatile("{ .reg .pred e; elect.sync _|e, 0xffffffff;\n"
                             "@e cp.async.bulk.global.shared::cta.bulk_group [%0], [%1], %2;\n"
                             "@e cp.async.bulk.commit_group;\n"
                             "@e cp.async.bulk.wait_group.read 0;\n"
                             "@e mbarrier.arrive.shared::cta.b64 _, [%3], 8;\n"
                             "@e cp.async.bulk.wait_group 0;\n"
                             "@e fence.proxy.async.global;\n"
                             "@e red.release.gpu.global.add.u32 [%4], 1; }"
                             ::"l"(reinterpret_cast<char*>(g_wp) + (size_t)(sl * 16 + tile) * STAGE), "r"(sb + ps * STAGE), "r"(STAGE), "r"(BAR(B_EMPTY + ps)), "l"(g_cw + sl * 32) : "memory");
                __syncwarp();
            }
            if (layer < 2) {
            const uint32_t tag = layer ^ 1;
            kseq++;
            bar_sync(7, 384);
            ASTAMP(0);
            if (tile < 15) {
                const int sq = lane >> 3, pk = 8 * w + (lane & (tile == 14 ? 3 : 7));
                uint32_t v[16];
                if (layer == 0) poll_cnt(g_c1 + ((sl * 8 + (w >> 1) * 4 + (tile >> 2)) * 16 + (lane & 15)) * 32, kseq);
                ASTAMP(1);
                poll4_kv<32>(v, g_kv1 + ((sl * 16 + tile) * 16 + 4 * sq) * 32 + pk, tag);
#pragma unroll
                for (int k = 0; k < 4; k++) {
                    float lo = (bf_lo(v[k]) + bf_lo(v[4 + k])) + (bf_lo(v[8 + k]) + bf_lo(v[12 + k]));
                    float hi = (bf_hi(v[k]) + bf_hi(v[4 + k])) + (bf_hi(v[8 + k]) + bf_hi(v[12 + k]));
                    lo += __shfl_xor_sync(0xffffffffu, lo, 8); hi += __shfl_xor_sync(0xffffffffu, hi, 8);
                    lo += __shfl_xor_sync(0xffffffffu, lo, 16); hi += __shfl_xor_sync(0xffffffffu, hi, 16);
                    v[k] = pack2(lo, hi);
                }
                if (sq == 0) st_pkt<0>(g_kv2 + sl * 512 + 32 * tile + pk, settag(v[0], tag), v[1], v[2], v[3]);
            }
            ASTAMP(2);
            {
                const int item = t128 < 112 ? t128 : 112 + (t128 & 3), d = item >> 1;
                const int cc = t128 < 112 ? 2 * (d >= 28) + (item & 1) : item - 112;
                const int r = t128 < 112 ? d : 56 + (cc >> 1) + 2 * ((t128 - 112) >> 2);
                uint32_t ra = sb + OFF_KVB + r * 128 + 4 * cc, rx = (r & 7) << 4;
                asm volatile("" : "+r"(ra), "+r"(rx));
                FOR14(asm volatile("st.shared.u32 [%0+%2], %1;" ::"r"((ra ^ 8) + (((t & 7) << 4) ^ rx)), "r"(0), "n"((t >> 3) * 8192) : "memory"));
                uint32_t v[16];
                asm volatile("" : "+r"(ra), "+r"(rx));
                poll4_kv<8>(v, g_kv2 + sl * 512 + (item >> 3) * 32 + (item & 7), tag);
                FOR14(asm volatile("st.shared.u32 [%0+%2], %1;" ::"r"(ra + (((t & 7) << 4) ^ rx)), "r"(v[t < 7 ? t : t + 1]), "n"((t >> 3) * 8192) : "memory"));
                fence_async();
            }
            bar_arrive(3, 384);
            ASTAMP(3);
            }
        }
    } else {
        asm volatile("setmaxnreg.inc.sync.aligned.u32 232;");
        int lane = fresh_tid() & 31;
#define g (lane >> 2)
#define c (lane & 3)
#define t128 (w * 32 + lane)
        const int wu = __shfl_sync(0xffffffffu, fresh_tid() >> 5, 0), w = wu & 3;
        const uint32_t xoff = __shfl_sync(0xffffffffu, (3 * PLANE + ((tile * 2 + wgi) * 8) * 512 + w * 128) * 16, 0);
        char* xu = reinterpret_cast<char*>(g_ex) + xoff;
#define FRESH() asm volatile("" : "+l"(xu), "+r"(lane))
#define xp0 (reinterpret_cast<uint4*>(xu) + lane)
        const uint32_t hbuf = sb + OFF_H + wgi * STAGE;
        uint32_t slot = 0, ph = 0, eb1 = 0, eb2 = 0, ackph = 0, rcvph = 0, gatph = 0, swp = 0;
        uint32_t ppid = 6;
#define cx(s) (reinterpret_cast<uint32_t*>(reinterpret_cast<uint4*>(xu) + PL(1) + 112 + (s) * 512))
#define stp (reinterpret_cast<uint4*>(xu) + g + PL(0) + 112)
        uint32_t seq = ld_word(cx(sl));
        uint32_t kseq = ld_word(g_c1 + ((sl * 8 + wu) * 16 + tile) * 32);
        uint32_t stag = ld_word(reinterpret_cast<const uint32_t*>(stp + sl * 512) + 3) & 1;
        asm volatile("barrier.cluster.wait.aligned;" ::: "memory");
        STAMP(1);
        uint32_t X[14];
        const uint32_t x0row = (w < 2 ? hbuf : sb + wgi * STAGE) + ((w & 1) * 16 + (lane & 15)) * 128;
        mbar_wait(BAR(wgi), 0);
        STAMP(51);
#pragma unroll
        for (int j = 0; j < 4; j++) {
            const int G = 7 * sl + min(2 * j + (lane >> 4), 6);
            uint32_t q2, q3;
            asm volatile("ldmatrix.sync.aligned.m8n8.x4.shared.b16 {%0,%1,%2,%3}, [%4];" : "=r"(X[4 * j]), "=r"(X[4 * j + 1]), "=r"(q2), "=r"(q3)
                         : "r"(x0row + (G >> 3) * 4096 + (((G ^ lane) & 7) << 4)) : "memory");
            if (j < 3) { X[(4 * j + 2) % 14] = q2; X[(4 * j + 3) % 14] = q3; }
        }
#define PUSH_SLICE(W)                                                                          \
    {                                                                                          \
        if (t128 == 0) mbar_expect_tx(BAR(B_RECV + wgi), 7168);                                \
        PUSH_BEGIN();                                                                          \
        const uint32_t ra = mapa(hbuf + 24576 + t128 * 16, hr ^ 1), rb = mapa(sb + OFF_XR + wgi * 3072, hr ^ 1), rbar = mapa(BAR(B_RECV + wgi), hr ^ 1); \
        st_async4(ra, W[0], W[1], W[2], W[3], rbar);                                           \
        st_async4(ra + 2048, W[4], W[5], W[6], W[7], rbar);                                    \
        st_async4(rb + t128 * 16, W[8], W[9], W[10], W[11], rbar);                             \
        asm volatile("st.async.weak.shared::cluster.mbarrier::complete_tx::bytes.v2.b32 [%0], {%1,%2}, [%3];" ::"r"(rb + 2048 + t128 * 8), "r"(W[12]), "r"(W[13]), "r"(rbar) : "memory"); \
    }
#define PULL_SLICE(W)                                                                          \
    {                                                                                          \
        uint32_t t0, t1;                                                                       \
        mbar_wait(BAR(B_RECV + wgi), rcvph);                                                   \
        rcvph ^= 1;                                                                            \
        lds4(&A[1][0], hbuf + 24576 + t128 * 16);                                              \
        lds4(&A[1][4], hbuf + 26624 + t128 * 16);                                              \
        lds4(&A[1][8], sb + OFF_XR + wgi * 3072 + t128 * 16);                                  \
        asm volatile("ld.shared.v2.u32 {%0,%1}, [%2];" : "=r"(t0), "=r"(t1) : "r"(sb + OFF_XR + wgi * 3072 + 2048 + t128 * 8) : "memory"); \
        _Pragma("unroll") for (int i = 0; i < 12; i++) A[0][i] = (i & 3) ? W[i] : W[i] & ~1u;  \
        A[1][0] &= ~1u; A[1][4] &= ~1u; A[1][8] &= ~1u;                                        \
        A[0][12] = (hr ? t0 : W[12]) & ~1u; A[0][13] = hr ? t1 : W[13];                        \
        A[1][12] = (hr ? W[12] : t0) & ~1u; A[1][13] = hr ? W[13] : t1;                        \
        asm volatile("" : RW4(A[0], 0), RW4(A[0], 4), RW4(A[0], 8), RW2(A[0], 12), RW4(A[1], 0), RW4(A[1], 4), RW4(A[1], 8), RW2(A[1], 12)); \
        swp = hr * 448;                                                                        \
    }
#define SWB(b, t, db, sh) ((b) == 0 && (t) < 6 ? ((t) < 3 ? db##p : db##m) : db)
#define DECL_DB(b, MK, lbo, sh) const uint64_t db = MK(0, lbo, R_ADJ), dbp = (b) == 0 ? MK(0, lbo, R_ADJ + (swp >> (sh))) : db, dbm = (b) == 0 ? MK(0, lbo, R_ADJ - (swp >> (sh))) : db;
#define EARLY 1
#define EARLYK 1
#define PPB 2
#define PP_WAIT() if (wgi == 1) { bar_sync(ppid, 256); ppid ^= 14; }
#define PP_GO() if (wgi == 0) { bar_arrive(ppid, 256); ppid ^= 14; }
#define GAT_ISSUE(base)                                                                        \
    {                                                                                          \
        const char* gs = xu + ((base) + kblk(pr, GB) * 1024) * 16; \
        const uint32_t gd = hbuf + w * 3584, gb = BAR(B_GAT + wu);                     \
        asm volatile("{ .reg .pred e; elect.sync _|e, 0xffffffff;\n"                           \
                     "@e mbarrier.arrive.expect_tx.shared::cta.b64 _, [%2], 3584;\n"           \
                     "@e cp.async.bulk.shared::cluster.global.mbarrier::complete_tx::bytes [%0], [%1], 1792, [%2];\n" \
                     "@e cp.async.bulk.shared::cluster.global.mbarrier::complete_tx::bytes [%0+1792], [%1+8192], 1792, [%2]; }" \
                     ::"r"(gd), "l"(gs), "r"(gb) : "memory");                                  \
        __syncwarp();                                                                          \
    }
#define GAT_FETCH()                                                                            \
    {                                                                                          \
        mbar_wait(BAR(B_GAT + wu), gatph);                                             \
        gatph ^= 1;                                                                            \
        const uint32_t ga = hbuf + w * 3584 + lane * 16;                                       \
        _Pragma("unroll") for (int s2 = 0; s2 < 2; s2++) {                                     \
            lds4(&A[2 * GB + s2][0], ga + s2 * 1792); lds4(&A[2 * GB + s2][4], ga + s2 * 1792 + 512); lds4(&A[2 * GB + s2][8], ga + s2 * 1792 + 1024); \
            asm volatile("ld.shared.v2.u32 {%0,%1}, [%2];" : "=r"(A[2 * GB + s2][12]), "=r"(A[2 * GB + s2][13]) : "r"(ga - lane * 8 + s2 * 1792 + 1536) : "memory"); \
        }                                                                                      \
    }
#define PT 3
#define PREP(b, t, remote)                                                                     \
    if constexpr ((b) < 3 && (t) == PT) {                                                      \
        wg_commit();                                                                           \
        STAMP(80 + 8 * (step & 1) + 2 * (b));                                                  \
        if constexpr ((b) == 0) { if (remote) GAT_FETCH() else X0_BLOCK(1) }                   \
        if (remote) blk_check<((b) + 1) & 3>(A, BLK(xsrc, (b) + 1), lane, xtag);               \
        STAMP(81 + 8 * (step & 1) + 2 * (b));                                                  \
        if constexpr ((b) == 0) { if (remote) blk_load<3>(A, BLK(xsrc, 3), lane); else X0_BLOCK(3) } \
        normalize<((b) + 1) & 3>(A, k0, k1);                                                   \
        asm volatile("" : RW4(A[(2 * (b) + 2) & 7], 0), RW4(A[(2 * (b) + 2) & 7], 4), RW4(A[(2 * (b) + 2) & 7], 8), RW2(A[(2 * (b) + 2) & 7], 12), \
                          RW4(A[(2 * (b) + 3) & 7], 0), RW4(A[(2 * (b) + 3) & 7], 4), RW4(A[(2 * (b) + 3) & 7], 8), RW2(A[(2 * (b) + 3) & 7], 12)); \
        wg_fence();                                                                            \
    }                                                                                          \
    if constexpr ((b) == 3 && ((t) == 0 || (t) == 6)) { STAMP(86 + 8 * (step & 1) + (t) / 6); }
#define X0_BLOCK(b)                                                                            \
    { const int rr = lane & 7, hi = lane >> 4;                                                 \
    const uint32_t rowa = (w < 2 ? hbuf : sb + wgi * STAGE) + ((w & 1) * 16 + (lane & 15)) * 128; \
    FOR7(constexpr int G = 14 * (b) + (t < 3 ? 2 * t : (t < 6 ? 2 * t + 1 : 6));               \
         uint32_t q0, q1, q2, q3;                                                              \
         const uint32_t ad = t < 6 ? rowa + (((((G & 7) + hi) ^ rr) & 7) << 4) + ((G & 7) == 7 ? hi * 4096 : 0) : rowa + ((G + 7 * hi) >> 3) * 4096 + ((((G + 7 * hi) ^ rr) & 7) << 4); \
         asm volatile("ldmatrix.sync.aligned.m8n8.x4.shared.b16 {%0,%1,%2,%3}, [%4+%5];" : "=r"(q0), "=r"(q1), "=r"(q2), "=r"(q3) \
                      : "r"(ad), "n"(t < 6 ? (G >> 3) * 4096 : 0) : "memory");                 \
         if (t < 3) { A[2 * (b)][4 * t] = q0; A[2 * (b)][4 * t + 1] = q1; A[2 * (b)][4 * t + 2] = q2; A[2 * (b)][4 * t + 3] = q3; } \
         else if (t < 6) { A[2 * (b) + 1][(4 * t - 12) & 15] = q0; A[2 * (b) + 1][((4 * t - 12) & 15) + 1] = q1; A[2 * (b) + 1][((4 * t - 12) & 15) + 2] = q2; A[2 * (b) + 1][((4 * t - 12) & 15) + 3] = q3; } \
         else { A[2 * (b)][12] = q0; A[2 * (b)][13] = q1; A[2 * (b) + 1][12] = q2; A[2 * (b) + 1][13] = q3; }); }
#define BLK(base, b) ((base) + kblk(pr, b) * 1024)

#pragma unroll 1
        for (int step = 0; step < 4; step++) {
            FRESH();
            const uint32_t tag = (step >> 1) ^ 1;
            const int so = (step >> 1) * 24 + (step & 1) * 12;
            (void)so;
            uint32_t A[8][14];
            uint4* const xsrc = xp0 + ((step & 1) ? PL(2) : PL(0));
            const uint32_t xtag = (step & 1) ? tag : ((seq >> 3) & 1) ^ 1;
            uint32_t xbits;
            {
                float st[4];
                slice_stats(X, st);
                stag ^= 1;
                xbits = x_bits(X);
                tag_slice(X, xtag);
                if (step) send_slice<0>(xsrc + sl * 512, lane, X);
                if (c == 0) st_pkt<0>(stp + sl * 512, __float_as_uint(st[0]), __float_as_uint(st[1]), __float_as_uint(st[2]), settag(__float_as_uint(st[3]), stag));
            }
            STAMP(2 + so);
            uint32_t sv[8];
            if (step == 0) {
                X0_BLOCK(0)
                mbar_wait(BAR(wgi ^ 1), 0);
                R_NEXT();
                R_NEXT();
                stat_load(sv, stp + c * 1024);
                stat_check(sv, stp + c * 1024, stag);
                STAMP(52 + step);
            } else {
                PUSH_SLICE(X)
                stat_load(sv, stp + c * 1024);
                PULL_SLICE(X)
                stat_check(sv, stp + c * 1024, stag);
                STAMP(52 + step);
                GAT_ISSUE((step & 1) ? PL(2) : PL(0))
            }
            LnCoef k0, k1;
            {
                k0 = ln_coef(__uint_as_float(sv[0]) + __uint_as_float(sv[4]), __uint_as_float(sv[1]) + __uint_as_float(sv[5]));
                k1 = ln_coef(__uint_as_float(sv[2]) + __uint_as_float(sv[6]), __uint_as_float(sv[3] & ~1u) + __uint_as_float(sv[7] & ~1u));
            }
            if (step) {
                blk_load<2>(A, BLK(xsrc, 2), lane);
            } else {
                X0_BLOCK(2)
            }
            STAMP(3 + so);
            GSTAMP(76 + step);

            if ((step & 1) == 0) {
                float tq[28];
                {
                    float av[28];
#define KV_BLOCK(b)                                                                           \
    if (GB == 2 && (b) == 1 && step) GAT_FETCH()                                                         \
    if ((b) == 2) PUSH_ACK();                                                                 \
    if ((b) == 1 && step == 0) { if (lane == 0) mbar_arrive(BAR(B_EMPTY)); }                  \
    if (QE && (b) == 1) R_RELEASE(2);                                                         \
    if (QE && (b) == 2) { wg_wait<2>(); R_RELEASE(2); }                                       \
    R_WAIT();                                                                                 \
    if ((b) == PPK) { PP_WAIT() }                                                             \
    { DECL_DB(b, BASE128, 16, 0)                                                              \
    wg_fence();                                                                               \
    FOR7(mma_rs56<1, D128(0, t)>(tq, AQ(A, b, t), (b) + t > 0, SWB(b, t, db, 0));             \
         mma_rs56<1, D128(HALF, t)>(av, AQ(A, b, t), (b) + t > 0, SWB(b, t, db, 0));          \
         PREP(b, t, step)); }                                                                 \
    wg_commit();                                                                              \
    if ((b) == 3 && PPK < 4) { PP_GO() }                                                      \
    R_NEXT();
                    normalize<0>(A, k0, k1);
                    KV_BLOCK(0) KV_BLOCK(1) KV_BLOCK(2) KV_BLOCK(3)
                    wg_wait<0>();
                    if (lane < (QE ? 3 : NST)) mbar_arrive(BAR(B_EMPTY + (slot + NST - 1 - lane) % NST));
                    STAMP(4 + so);
                    WSUM(80 + 7 * (step >> 1));
                    const int m = lane >> 3, rr = lane & 7;
                    const uint32_t rowa = hbuf + 16384 + (w * 16 + rr + 8 * (m & 1)) * 128;
                    const uint32_t one = c == 0 ? 0x00003f80u : 0u;
                    if (step == 0) { bar_sync(wgi ? 9 : 1, 224); }
#pragma unroll
                    for (int j = 0; j < 4; j++) {
                        const uint32_t a = rowa + (((2 * j + (m >> 1)) ^ rr) << 4);
                        if (j < 3) stsm4(a, pack2(av[8 * j], av[8 * j + 1]), pack2(av[8 * j + 2], av[8 * j + 3]), pack2(av[8 * j + 4], av[8 * j + 5]), pack2(av[8 * j + 6], av[8 * j + 7]));
                        else stsm4(a, pack2(av[24], av[25]), pack2(av[26], av[27]), one, one);
                    }
                }
                uint32_t PH[28];
                int it = 1;
#pragma unroll 1
                do {
                    float pp[28];
                    phi_gemm(tq, pp);
                    dual_softmax(pp, PH);
                    if (((trips >> (it + 1)) & 1) == 0) continue;
                    {
                        const int m = lane >> 3, rr = lane & 7;
                        const uint32_t rowa = hbuf + (w * 16 + rr + 8 * (m & 1)) * 128;
#pragma unroll
                        for (int j = 0; j < 7; j++) {
                            const int cg = 2 * j + (m >> 1), hi = cg >= 7;
                            stsm4(rowa + hi * 8192 + (((cg - 7 * hi) ^ rr) << 4), PH[4 * j], PH[4 * j + 1], PH[4 * j + 2], PH[4 * j + 3]);
                        }
                    }
                    fence_async();
                    STAMP(5 + so);
#define Q_STAGE(b0)                                                                           \
    R_WAIT();                                                                                 \
    { DECL_DB(b0, BASE128, 16, 0)                                                             \
    wg_fence();                                                                               \
    FOR7(mma_rs56<1, D128(0, t)>(tq, AQ(A, b0, t), (b0) + t > 0, SWB(b0, t, db, 0)));         \
    FOR7(mma_rs56<1, D128(HALF, t)>(tq, AQ(A, (b0) + 1, t), 1, db)); }                        \
    wg_commit();                                                                              \
    R_NEXT();
                    if (QE && wgi == 0) { kill<28>(tq); Q_STAGE(0) Q_STAGE(2) wg_wait<1>(); R_RELEASE(2); wg_wait<0>(); R_RELEASE(1); }
                    bar_sync(2, 256);
                    float kv[28];
                    const uint64_t da = BASE128(OFF_H + 16384, 16, 0), dbk = BASE128(OFF_H, 16, wgi * 512);
                    wg_fence();
                    FOR8(constexpr uint64_t o = ((t >> 2) * STAGE + (t & 3) * 2048) >> 4; mma_ss56_tt<o, o>(kv, t > 0, da, dbk));
                    wg_commit();
                    wg_wait<0>();
#pragma unroll
                    for (int hf = 0; hf < 2; hf++) {
                        const int d = 16 * w + g + 8 * hf;
                        if ((d < 56 && (d >= 28) == (c >= 2)) || d == 56) {
                            const int item = d < 56 ? 2 * d + (c & 1) : 112 + c;
                            uint4* dst = g_kv1 + ((sl * 16 + (item >> 3)) * 16 + tile) * 32 + wgi * 16 + (item & 7);
#define KVW(i) pack2(kv[4 * (i) + 2 * hf], kv[4 * (i) + 2 * hf + 1])
                            st_pkt<0>(dst, settag(KVW(0), tag), KVW(1), KVW(2), KVW(3));
                            st_pkt<8>(dst, settag(KVW(4), tag), KVW(5), KVW(6), 0u);
                        }
                    }
                    __syncwarp();
                    kseq++;
                    if (lane == 0) st_word(g_c1 + ((sl * 8 + wu) * 16 + tile) * 32, kseq);
                    bar_arrive(7, 384);
                    STAMP(6 + so);
                    if (!QE || wgi == 1) { kill<28>(tq); Q_STAGE(0) Q_STAGE(2) wg_wait<1>(); R_RELEASE(2); wg_wait<0>(); R_RELEASE(1); }
                    STAMP(7 + so);
                    kill<28>(PH);
                } while (((trips >> (++it)) & 1));
                STAMP(8 + so);
                FRESH();
                if (step) {
                    slice_load<PL(0)>(X, xp0 + sl * 512, lane);
                } else {
                    const uint32_t* xp = reinterpret_cast<const uint32_t*>(x_in + (size_t)(tile * 128 + wu * 16 + g) * 448 + 56 * sl + 2 * c);
#pragma unroll
                    for (int i = 0; i < 7; i++) { X[2 * i] = __ldg(xp + 4 * i); X[2 * i + 1] = __ldg(xp + 4 * i + 8 * 224); }
                }
                bar_sync(3, 384);
                STAMP(9 + so);
                const uint4* const osrc = xp0 + PL(1);
                {
                    float nm[32];
                    const uint64_t db = BASE128(OFF_KVB, 16, 0);
                    wg_fence();
                    FOR7(mma_rs64<0, ((t >> 2) * 8192 + (t & 3) * 32) / 16>(nm, PH[4 * t], PH[4 * t + 1], PH[4 * t + 2], PH[4 * t + 3], t > 0, db));
                    wg_commit();
                    wg_wait<0>();
                    const float i00 = rcp(nm[28] + 1e-6f), i01 = rcp(nm[29] + 1e-6f), i10 = rcp(nm[30] + 1e-6f), i11 = rcp(nm[31] + 1e-6f);
                    const float m0 = c >= 2 ? i01 : i00, m1 = c >= 2 ? i11 : i10;
                    uint32_t O[14];
#pragma unroll
                    for (int i = 0; i < 7; i++) {
                        const float f0 = i < 3 ? i00 : (i > 3 ? i01 : m0), f1 = i < 3 ? i10 : (i > 3 ? i11 : m1);
                        O[2 * i] = pack2(nm[4 * i] * f0, nm[4 * i + 1] * f0);
                        O[2 * i + 1] = pack2(nm[4 * i + 2] * f1, nm[4 * i + 3] * f1);
                    }
                    if (OST) { PP_WAIT() }
                    tag_slice(O, tag);
                    send_slice<PL(1)>(xp0 + sl * 512, lane, O);
                    seq++;
                    if (lane == 0) st_word(cx(sl), seq);
                    STAMP(10 + so);
                    PUSH_SLICE(O)
                    if (OST == 1) { PP_GO() }
                    const uint32_t cv = ld_word(cx(lane & 7));
                    PULL_SLICE(O)
                    check_cnt(cv, cx(lane & 7), seq);
                    if (OST == 2) { PP_GO() }
                    STAMP(56 + (step >> 1));
                    GAT_ISSUE(PL(1))
                    blk_load<3 - GB>(A, BLK(osrc, 3 - GB), lane);
                }
                float ao[28];
#define WO_BLOCK(b)                                                                           \
    if ((b) > 0) blk_check<b>(A, BLK(osrc, b), lane, tag);                                    \
    if (((b) & 1) == 0) R_WAIT();                                                             \
    { DECL_DB(b, BASE128, 16, 0)                                                              \
    wg_fence();                                                                               \
    FOR7(mma_rs56<1, D128(((b) & 1) * HALF, t)>(ao, AQ(A, b, t), (b) + t > 0, SWB(b, t, db, 0))); } \
    wg_commit();                                                                              \
    if ((b) & 1) R_NEXT();
                WO_BLOCK(0)
                STAMP(11 + so);
                blk_load<3>(A, BLK(osrc, 3), lane);
                if (GB == 1) GAT_FETCH()
                WO_BLOCK(1)
                if (GB == 2) GAT_FETCH()
                WO_BLOCK(2)
                PUSH_ACK();
                WO_BLOCK(3)
                wg_wait<0>();
                if (EARLY >= 1) R_RELEASE(2);
                if (EARLY >= 2) R_RELEASE(1);
                STAMP(12 + so);
                WSUM(86 + 7 * (step >> 1));
                x_fix(X, xbits);
#pragma unroll
                for (int i = 0; i < 14; i++) X[i] = pack2(bf_lo(X[i]) + ao[2 * i], bf_hi(X[i]) + ao[2 * i + 1]);
            } else {
                uint32_t H[56];
                float ag[64];
#define F1_EPI(dst, ng, ag)                                                                    \
    _Pragma("unroll") for (int i = 0; i < 2 * (ng); i++)                                       \
        (dst)[i] = pack2(geglu(ag[2 * i], ag[4 * (ng) + 2 * i]), geglu(ag[2 * i + 1], ag[4 * (ng) + 2 * i + 1]));
#define H_PUSH(h0, off) st_async4(rem_h + (off), H[h0], H[(h0) + 1], H[(h0) + 2], H[(h0) + 3], mapa(BAR(B_RECV2 + wgi), hr ^ 1));
#define F1_BLOCK(b, first)                                                                     \
    if ((first) && (b) < 2 && (b) >= EARLY) R_RELEASE(2);                                      \
    if (GB == 2 && (first) && (b) == 1) GAT_FETCH()                                                       \
    if ((first) && (b) == 2) PUSH_ACK();                                                       \
    R_WAIT();                                                                                  \
    if ((b) == ((first) ? PPF : PPB)) { PP_WAIT() }                                            \
    { DECL_DB(b, BASE128, HALF, 0)                                                             \
    wg_fence();                                                                                \
    FOR7(mma_rs128<1, D128(0, t)>(ag, AQ(A, b, t), (b) + t > 0, SWB(b, t, db, 0));             \
         if constexpr (first) { PREP(b, t, true) }); }                                         \
    wg_commit();                                                                               \
    if ((b) == 3) { PP_GO() }                                                                  \
    if ((b) > 0) { wg_wait<1>(); R_RELEASE(1); }       \
    R_NEXT();
                normalize<0>(A, k0, k1);
                F1_BLOCK(0, true) F1_BLOCK(1, true) F1_BLOCK(2, true) F1_BLOCK(3, true)
                if (t128 == 0) { mbar_expect_tx(BAR(B_RECV + wgi), 16384); mbar_expect_tx(BAR(B_RECV2 + wgi), 12288); }
                PUSH_BEGIN();
                wg_wait<0>();
                R_RELEASE(1);
                if (step == 1) R_NEXT();
                int p = 0;
#pragma unroll 1
                do {
                    STAMP(68 + p);
                    F1_EPI(H + 32, 8, ag)
                    STAMP(4 + p + so);
                    WSUM(81 + p + 7 * (step >> 1));
                    if (((trips >> (p + 1)) & 1) == 0) continue;
                    {
                        const uint32_t pk = (p ? hbuf + 16384 : sb + OFF_KVB + wgi * 8192) + w * 2048;
#pragma unroll
                        for (int k = 0; k < 4; k++) sts4(pk + k * 512 + lane * 16, H[32 + 4 * k], H[33 + 4 * k], H[34 + 4 * k], H[35 + 4 * k]);
                        fence_async();
                        __syncwarp();
                        asm volatile(ELECT "cp.async.bulk.shared::cluster.shared::cta.mbarrier::complete_tx::bytes [%0], [%1], 2048, [%2]; }"
                                     ::"r"(mapa(hbuf + p * 8192 + w * 2048, hr ^ 1)), "r"(pk), "r"(mapa(BAR(B_RECV + wgi), hr ^ 1)) : "memory");
                    }
                    kill<64>(ag);
                    F1_BLOCK(0, false) F1_BLOCK(1, false) F1_BLOCK(2, false) F1_BLOCK(3, false)
                    wg_wait<0>();
                    R_RELEASE(1);
                    kill<16>(H + 32);
                } while (((trips >> (++p)) & 1));
#pragma unroll
                for (int k = 0; k < 4; k++) lds4(H + 16 + 4 * k, hbuf + 16384 + w * 2048 + k * 512 + lane * 16);
                __syncwarp();
                if (lane == 0) asm volatile("mbarrier.arrive.shared::cluster.b64 _, [%0];" ::"r"(mapa(BAR(B_ACK2 + wgi), hr ^ 1)) : "memory");
                const uint32_t rem_h = mapa(hbuf + w * 2048 + lane * 16, hr ^ 1);
#define F1_LAST(b0)                                                                            \
    R_WAIT();                                                                                  \
    if (b0) { PP_WAIT() }                                                                      \
    { DECL_DB(b0, BASE64, HALF, 1)                                                             \
    wg_fence();                                                                                \
    FOR7(mma_rs64<1, D64(0, t)>(al, AQ(A, b0, t), (b0) + t > 0, SWB(b0, t, db, 1)));           \
    FOR7(mma_rs64<1, D64(7168, t)>(al, AQ(A, (b0) + 1, t), 1, db)); }                          \
    wg_commit();                                                                               \
    if (b0) { PP_GO() }                                                                        \
    R_NEXT();
                float al[32];
                F1_LAST(0)
                mbar_wait(BAR(B_RECV + wgi), rcvph);
                rcvph ^= 1;
                mbar_wait(BAR(B_ACK2 + wgi), step >> 1);
                H_PUSH(32, 16384) H_PUSH(36, 16896)
                F1_LAST(2)
                H_PUSH(40, 17408) H_PUSH(44, 17920)
                wg_wait<1>();
                R_RELEASE(2);
                wg_wait<0>();
                R_RELEASE(1);
                uint32_t HP[56];
#pragma unroll
                for (int k = 0; k < 4; k++) lds4(H + 4 * k, sb + OFF_KVB + wgi * 8192 + w * 2048 + k * 512 + lane * 16);
#pragma unroll
                for (int t = 0; t < 8; t++) lds4(HP + 4 * t, hbuf + (t >> 2) * 8192 + w * 2048 + (t & 3) * 512 + lane * 16);
                F1_EPI(H + 48, 4, al)
                H_PUSH(48, 24576 - w * 1024) H_PUSH(52, 25088 - w * 1024)
                STAMP(7 + so);
                WSUM(84 + 7 * (step >> 1));
                FRESH();
                float acc[28];
                const uint32_t roA = hr ? 256u : 0u, roB = hr ? (uint32_t)-1536 : 0u;
                const uint32_t rpA = hr ? 0u : 256u, rpB = hr ? 0u : (uint32_t)-1536;
                float res[28];
                uint32_t v0[14], v1[14], P[14];
                const uint4* ps = xp0 + sl * 512;
#define F2_OWN_A()                                                                             \
    R_WAIT();                                                                                  \
    d0 = BASE128(0, 16, R_ADJ + roA); d1 = BASE128(0, 16, R_ADJ + roB);                        \
    wg_fence();                                                                                \
    FOR14(if constexpr (t < OT) mma_rs56<1, t * 128>(acc, H[4 * t], H[4 * t + 1], H[4 * t + 2], H[4 * t + 3], t > 0, d0)); \
    wg_commit();
#define F2_OWN_B()                                                                             \
    wg_fence();                                                                                \
    FOR14(if constexpr (t >= OT) mma_rs56<1, t * 128>(acc, H[4 * t], H[4 * t + 1], H[4 * t + 2], H[4 * t + 3], 1, t < 12 ? d0 : d1)); \
    wg_commit();                                                                               \
    R_NEXT();
#define F2_PEER()                                                                              \
    R_WAIT();                                                                                  \
    if (F2PP) { PP_WAIT() }                                                                    \
    d0 = BASE128(0, 16, R_ADJ + rpA); d1 = BASE128(0, 16, R_ADJ + rpB);                        \
    wg_fence();                                                                                \
    FOR14(mma_rs56<1, t * 128>(acc, HP[4 * t], HP[4 * t + 1], HP[4 * t + 2], HP[4 * t + 3], 1, t < 12 ? d0 : d1)); \
    wg_commit();                                                                               \
    if (F2PP) { PP_GO() }                                                                      \
    R_NEXT();
#define F2_TURN(u)                                                                             \
    wg_wait<1>();                                                                              \
    R_RELEASE(2);                                                                              \
    wg_wait<0>();                                                                              \
    R_RELEASE(1);                                                                              \
    _Pragma("unroll") for (int i = 0; i < 14; i++) P[i] = pack2(acc[2 * i], acc[2 * i + 1]);   \
    tag_slice(P, tag);                                                                         \
    asm volatile("" : RW4(P, 0), RW4(P, 4), RW4(P, 8), RW2(P, 12));                            \
    kill<28>(acc);                                                                             \
    F2_OWN_A()                                                                                 \
    if ((u) == 2) { slice_load<PL(3)>(v0, ps, lane); slice_load<PL(4)>(v1, ps, lane); } \
    send_slice<PL(3 + (u))>(xp0 + (2 * ((pr + (u) + 1) & 3) + hr) * 512, lane, P);             \
    seq++;                                                                                     \
    if (lane == 0) st_word(cx(sl), seq);                                                       \
    __syncwarp();                                                                              \
    STAMP(8 + (u) + so);                                                                       \
    F2_OWN_B()
                uint64_t d0, d1;
                F2_OWN_A()
                F2_OWN_B()
                R_WAIT();
                d0 = BASE128(0, 16, R_ADJ + rpA); d1 = BASE128(0, 16, R_ADJ + rpB);
                wg_fence();
                FOR8(mma_rs56<1, t * 128>(acc, HP[4 * t], HP[4 * t + 1], HP[4 * t + 2], HP[4 * t + 3], 1, d0));
                wg_commit();
                mbar_wait(BAR(B_RECV2 + wgi), step >> 1);
#pragma unroll
                for (int k = 0; k < 4; k++) lds4(HP + 32 + 4 * k, hbuf + 16384 + w * 2048 + k * 512 + lane * 16);
                lds4(HP + 48, hbuf + 24576 + w * 1024 + lane * 16);
                lds4(HP + 52, hbuf + 25088 + w * 1024 + lane * 16);
                if (step == 1) PUSH_ACK();
                wg_fence();
                FOR14(if constexpr (t >= 8) mma_rs56<1, t * 128>(acc, HP[4 * t], HP[4 * t + 1], HP[4 * t + 2], HP[4 * t + 3], 1, t < 12 ? d0 : d1));
                wg_commit();
                R_NEXT();
                F2_TURN(0)
                F2_PEER()
                F2_TURN(1)
                F2_PEER()
                F2_TURN(2)
                STAMP(64 + 8 * (step >> 1));
                slice_check<PL(3)>(v0, ps, lane, tag);
                slice_check<PL(4)>(v1, ps, lane, tag);
#pragma unroll
                for (int i = 0; i < 14; i++) { res[2 * i] = bf_lo(v0[i]) + bf_lo(v1[i]); res[2 * i + 1] = bf_hi(v0[i]) + bf_hi(v1[i]); }
                slice_load<PL(2)>(X, ps, lane);
                STAMP(65 + 8 * (step >> 1));
                const uint32_t cv = ld_word(cx(2 * ((pr + 1) & 3) + hr));
                F2_PEER()
                STAMP(66 + 8 * (step >> 1));
                check_cnt(cv, cx(2 * ((pr + 1) & 3) + hr), seq);
                STAMP(67 + 8 * (step >> 1));
                slice_load<PL(5)>(v0, ps, lane);
                x_fix(X, xbits);
                slice_check<PL(5)>(v0, ps, lane, tag);
#pragma unroll
                for (int i = 0; i < 14; i++) { res[2 * i] += bf_lo(v0[i]); res[2 * i + 1] += bf_hi(v0[i]); }
                STAMP(11 + so);
                wg_wait<0>();
                if (EARLYK >= 1) R_RELEASE(2);
                STAMP(12 + so);
                WSUM(85 + 7 * (step >> 1));
#pragma unroll
                for (int i = 0; i < 14; i++) X[i] = pack2(fmaf(res[2 * i] + acc[2 * i], 0.5f, bf_lo(X[i])), fmaf(res[2 * i + 1] + acc[2 * i + 1], 0.5f, bf_hi(X[i])));
            }
        }
        {
            const int m = lane >> 3, rr = lane & 7;
            const uint32_t ob = hbuf + w * 2048, rowa = ob + (rr + 8 * (m & 1)) * 112 + (m >> 1) * 16;
#pragma unroll
            for (int j = 0; j < 3; j++) stsm4(rowa + 32 * j, X[4 * j], X[4 * j + 1], X[4 * j + 2], X[4 * j + 3]);
            asm volatile("stmatrix.sync.aligned.m8n8.x2.shared.b16 [%0], {%1,%2};" ::"r"(ob + (rr + 8 * (m & 1)) * 112 + 96), "r"(X[12]), "r"(X[13]) : "memory");
            fence_async();
            __syncwarp();
            if (lane == 0) {
                asm volatile("cp.async.bulk.tensor.2d.global.shared::cta.bulk_group [%0, {%2, %3}], [%1];" ::"l"(&maps.out), "r"(ob), "r"(56 * sl), "r"(tile * 128 + wu * 16) : "memory");
                asm volatile("cp.async.bulk.commit_group;" ::: "memory");
                asm volatile("cp.async.bulk.wait_group.read 0;" ::: "memory");
            }
        }
        STAMP(50);
        GSTAMP(61);
        PDUMP();
    }
}

#undef g
#undef c
#undef t128

typedef CUresult (*EncodeFn)(CUtensorMap*, CUtensorMapDataType, cuuint32_t, void*, const cuuint64_t*, const cuuint64_t*, const cuuint32_t*,
                             const cuuint32_t*, CUtensorMapInterleave, CUtensorMapSwizzle, CUtensorMapL2promotion, CUtensorMapFloatOOBfill);

static void make_map(EncodeFn enc, CUtensorMap* m, const void* p, uint64_t cols, uint64_t rows, uint32_t bc, uint32_t br, CUtensorMapSwizzle sw) {
    cuuint64_t gd[2] = {cols, rows};
    cuuint64_t gs[1] = {cols * 2};
    cuuint32_t bd[2] = {bc, br};
    cuuint32_t es[2] = {1, 1};
    enc(m, CU_TENSOR_MAP_DATA_TYPE_BFLOAT16, 2, const_cast<void*>(p), gd, gs, bd, es, CU_TENSOR_MAP_INTERLEAVE_NONE, sw,
        CU_TENSOR_MAP_L2_PROMOTION_L2_128B, CU_TENSOR_MAP_FLOAT_OOB_FILL_NONE);
}

extern "C" void kernel_launch(void* const* d_in, const int* in_sizes, int n_in, void* d_out, int out_size) {
    (void)in_sizes; (void)n_in; (void)out_size;
    static EncodeFn enc = nullptr;
    static Scratch* scratch = nullptr;
    if (!enc) {
        void* fn = nullptr;
        cudaDriverEntryPointQueryResult qr;
        cudaGetDriverEntryPoint("cuTensorMapEncodeTiled", &fn, cudaEnableDefault, &qr);
        enc = (EncodeFn)fn;
        cudaGetSymbolAddress((void**)&scratch, g_scratch);
        cudaFuncSetAttribute(fused_kernel, cudaFuncAttributeMaxDynamicSharedMemorySize, SMEM_BYTES);
    }
    Maps maps;
    {
        cuuint64_t gd[3] = {64, 2048, 7};
        cuuint64_t gs[2] = {896, 128};
        cuuint32_t bd[3] = {64, 32, 7};
        cuuint32_t es[3] = {1, 1, 1};
        enc(&maps.x, CU_TENSOR_MAP_DATA_TYPE_BFLOAT16, 3, d_in[0], gd, gs, bd, es, CU_TENSOR_MAP_INTERLEAVE_NONE, CU_TENSOR_MAP_SWIZZLE_128B,
            CU_TENSOR_MAP_L2_PROMOTION_L2_128B, CU_TENSOR_MAP_FLOAT_OOB_FILL_NONE);
    }
    make_map(enc, &maps.out, d_out, 448, 2048, 56, 16, CU_TENSOR_MAP_SWIZZLE_NONE);
    make_map(enc, &maps.qkv, d_in[1], 1344, 448, 64, 112, CU_TENSOR_MAP_SWIZZLE_128B);
    make_map(enc, &maps.wo, d_in[3], 448, 448, 64, 112, CU_TENSOR_MAP_SWIZZLE_128B);
    make_map(enc, &maps.wg, d_in[5], 1792, 448, 64, 112, CU_TENSOR_MAP_SWIZZLE_128B);
    make_map(enc, &maps.wu, d_in[6], 1792, 448, 64, 112, CU_TENSOR_MAP_SWIZZLE_128B);
    make_map(enc, &maps.wg32, d_in[5], 1792, 448, 32, 112, CU_TENSOR_MAP_SWIZZLE_64B);
    make_map(enc, &maps.wu32, d_in[6], 1792, 448, 32, 112, CU_TENSOR_MAP_SWIZZLE_64B);
    make_map(enc, &maps.wd, d_in[7], 448, 1792, 64, 112, CU_TENSOR_MAP_SWIZZLE_128B);
    fused_kernel<<<128, 384, SMEM_BYTES>>>(scratch, (const __nv_bfloat16*)d_in[0], (const __nv_bfloat16*)d_in[2], 7, (const __nv_bfloat16*)d_in[5],
                                           (const __nv_bfloat16*)d_in[6], (const __nv_bfloat16*)d_in[7], maps);
}
```

```cpp
#include <cuda_runtime.h>
#include <cuda.h>
#include <cuda_bf16.h>
#include <stdint.h>
#include <type_traits>

#define MC 0
#define PPF 2
#define GE 0
#define ACAN 1
#define SPLIT0 1
#define OT 2
#define F2PP 0
#define PPK 2
#define QE 1
#define OST 1
#define GB 1
#define B3T 6
#define PP

namespace {

constexpr uint32_t STAGE = 28672, HALF = 14336;
constexpr int NST = 5;
constexpr uint32_t OFF_H = NST * STAGE;
constexpr uint32_t OFF_KVB = OFF_H + 2 * STAGE;
constexpr uint32_t OFF_WPHI = OFF_KVB + 16384;
constexpr uint32_t OFF_XR = OFF_WPHI + 7168;
constexpr uint32_t OFF_BAR = OFF_XR + 6144;
constexpr uint32_t SMEM_BYTES = OFF_BAR + 256 + 1536;
constexpr int B_EMPTY = NST, B_RECV = 2 * NST, B_RECV2 = B_RECV + 2, B_PACK = B_RECV2 + 2, B_GAT = B_PACK + 1, B_ACK = B_GAT + 8, B_ACK2 = B_ACK + 2, B_COUNT = B_ACK2 + 2;

constexpr int PACK = 14;

struct Maps { CUtensorMap x, qkv, wo, wg, wu, wg32, wu32, wd, out; };

}

constexpr int PLANE = 16 * 2 * 8 * 512;
struct Scratch {
    uint4 ex[6 * PLANE];
    uint4 kv1[8 * 16 * 16 * 32];
    uint4 kv2[8 * 512];
    uint32_t c1[8 * 8 * 16 * 32];
    uint32_t cw[8 * 32];
    uint4 wp[8 * 32 * (HALF / 16)];
};
__device__ __align__(1024) Scratch g_scratch;
#define g_ex (sc->ex)
#define g_kv1 (sc->kv1)
#define g_kv2 (sc->kv2)
#define g_c1 (sc->c1)
#define g_cw (sc->cw)
#define g_wp (sc->wp)
#define STAMP(i)
#define GSTAMP(i)
#define PDUMP()
#define ASTAMP(i)

namespace {

__device__ __forceinline__ int fresh_tid() { int t; asm volatile("mov.u32 %0, %%tid.x;" : "=r"(t)); return t; }
template <int N> __device__ __forceinline__ void kill(uint32_t* v) {
#pragma unroll
    for (int i = 0; i < N; i++) v[i] = 0;
}
template <int N> __device__ __forceinline__ void kill(float* v) {
#pragma unroll
    for (int i = 0; i < N; i++) v[i] = 0.f;
}
__device__ __forceinline__ uint32_t s2u(const void* p) { return (uint32_t)__cvta_generic_to_shared(p); }
__device__ __forceinline__ void mbar_init(uint32_t a, uint32_t c) { asm volatile("mbarrier.init.shared::cta.b64 [%0], %1;" ::"r"(a), "r"(c) : "memory"); }
__device__ __forceinline__ void mbar_expect_tx(uint32_t a, uint32_t b) { asm volatile("mbarrier.arrive.expect_tx.shared::cta.b64 _, [%0], %1;" ::"r"(a), "r"(b) : "memory"); }
__device__ __forceinline__ void mbar_arrive(uint32_t a) { asm volatile("mbarrier.arrive.shared::cta.b64 _, [%0];" ::"r"(a) : "memory"); }
#define GIVE_UP(id) "trap;\n"
#define SPIN_MAX "0x400000"
#define SPIN_TAIL(id) "add.u32 n, n, 1;\n setp.lt.u32 p, n, " SPIN_MAX ";\n @p bra.uni LP;\n" GIVE_UP(id) " DN:\n }"
__device__ __forceinline__ void mbar_wait(uint32_t a, uint32_t ph) {
    asm volatile("{ .reg .pred p; .reg .b32 n; mov.u32 n, 0;\n LP:\n"
                 "mbarrier.try_wait.parity.shared::cta.b64 p, [%0], %1;\n @p bra DN;\n"
                 "add.u32 n, n, 1;\n setp.lt.u32 p, n, " SPIN_MAX ";\n @p bra LP;\n"
                 GIVE_UP("")
                 " DN:\n }" ::"r"(a), "r"(ph) : "memory");
}
#define ELECT "{ .reg .pred e; elect.sync _|e, 0xffffffff; @e "
__device__ __forceinline__ void tma2d(uint32_t dst, const CUtensorMap* m, int c0, int c1, uint32_t bar) {
    asm volatile(ELECT "cp.async.bulk.tensor.2d.shared::cluster.global.mbarrier::complete_tx::bytes [%0], [%1, {%3, %4}], [%2]; }" ::"r"(dst), "l"(m), "r"(bar), "r"(c0), "r"(c1) : "memory");
}
__device__ __forceinline__ void tma3x(uint32_t dst, const CUtensorMap* m, int row, uint32_t bar) {
    asm volatile(ELECT "cp.async.bulk.tensor.3d.shared::cluster.global.mbarrier::complete_tx::bytes [%0], [%1, {0, %3, 0}], [%2]; }" ::"r"(dst), "l"(m), "r"(bar), "r"(row) : "memory");
}
template <int OFF>
__device__ __forceinline__ void ld_pkt(uint32_t* v, const uint4* p) {
    asm volatile("{ .reg .b128 t; ld.relaxed.gpu.global.b128 t, [%4+%5]; mov.b128 {%0,%1,%2,%3}, t; }" : "=r"(v[0]), "=r"(v[1]), "=r"(v[2]), "=r"(v[3]) : "l"(p), "n"(OFF * 16) : "memory");
}
template <int OFF>
__device__ __forceinline__ void st_pkt(uint4* p, uint32_t a, uint32_t b, uint32_t c, uint32_t d) {
    asm volatile("{ .reg .b128 t; mov.b128 t, {%1,%2,%3,%4}; st.relaxed.gpu.global.b128 [%0+%5], t; }" ::"l"(p), "r"(a), "r"(b), "r"(c), "r"(d), "n"(OFF * 16) : "memory");
}
__device__ __forceinline__ uint32_t pack2(float lo, float hi) {
    uint32_t r;
    asm("cvt.rn.bf16x2.f32 %0, %1, %2;" : "=r"(r) : "f"(hi), "f"(lo));
    return r;
}
__device__ __forceinline__ float bf_lo(uint32_t w) { return __uint_as_float(w << 16); }
__device__ __forceinline__ float bf_hi(uint32_t w) { return __uint_as_float(w & 0xffff0000u); }
__device__ __forceinline__ uint32_t settag(uint32_t w, uint32_t tag) { return (w & ~1u) | tag; }
__device__ __forceinline__ float ex2(float x) { float y; asm("ex2.approx.ftz.f32 %0, %1;" : "=f"(y) : "f"(x)); return y; }
__device__ __forceinline__ float rcp(float x) { float y; asm("rcp.approx.ftz.f32 %0, %1;" : "=f"(y) : "f"(x)); return y; }
__device__ __forceinline__ float tanh_hw(float x) { float y; asm("tanh.approx.f32 %0, %1;" : "=f"(y) : "f"(x)); return y; }
__device__ __forceinline__ void stsm4(uint32_t addr, uint32_t a, uint32_t b, uint32_t c, uint32_t d) {
    asm volatile("stmatrix.sync.aligned.m8n8.x4.shared.b16 [%0], {%1,%2,%3,%4};" ::"r"(addr), "r"(a), "r"(b), "r"(c), "r"(d) : "memory");
}
__device__ __forceinline__ void fence_async() { asm volatile("fence.proxy.async.shared::cta;" ::: "memory"); }
__device__ __forceinline__ void bar_sync(int id, int n) { asm volatile("bar.sync %0, %1;" ::"r"(id), "r"(n) : "memory"); }
__device__ __forceinline__ void bar_arrive(int id, int n) { asm volatile("bar.arrive %0, %1;" ::"r"(id), "r"(n) : "memory"); }
__device__ __forceinline__ void wg_fence() { asm volatile("wgmma.fence.sync.aligned;" ::: "memory"); }
__device__ __forceinline__ void wg_commit() { asm volatile("wgmma.commit_group.sync.aligned;" ::: "memory"); }
template <int N> __device__ __forceinline__ void wg_wait() { asm volatile("wgmma.wait_group.sync.aligned %0;" ::"n"(N) : "memory"); }

constexpr uint32_t SB0 = 1024;
__host__ __device__ constexpr uint32_t dlo(uint32_t off, uint32_t lbo) { return ((SB0 + off) >> 4) | ((lbo >> 4) << 16); }
__host__ __device__ constexpr uint32_t dhi(uint32_t sbo, uint32_t sw) { return (sbo >> 4) | (sw << 30); }
__device__ __forceinline__ uint64_t dbase(uint32_t lo, uint32_t hi) { uint64_t d; asm volatile("mov.b64 %0, {%1, %2};" : "=l"(d) : "r"(lo), "r"(hi)); return d; }
#define BASE128(off, lbo, adj) dbase(dlo(off, lbo) + (adj), dhi(1024, 1))
#define BASE64(off, lbo, adj) dbase(dlo(off, lbo) + (adj), dhi(512, 2))

#define ACC4(d, o) "+f"(d[o]), "+f"(d[o + 1]), "+f"(d[o + 2]), "+f"(d[o + 3])
#define ACC28(d) ACC4(d, 0), ACC4(d, 4), ACC4(d, 8), ACC4(d, 12), ACC4(d, 16), ACC4(d, 20), ACC4(d, 24)
#define ACC32(d, o) ACC4(d, o), ACC4(d, o + 4), ACC4(d, o + 8), ACC4(d, o + 12), ACC4(d, o + 16), ACC4(d, o + 20), ACC4(d, o + 24), ACC4(d, o + 28)

template <int TB, uint64_t D>
__device__ __forceinline__ void mma_rs56(float* d, uint32_t a0, uint32_t a1, uint32_t a2, uint32_t a3, int sd, uint64_t base) {
    asm volatile("{ .reg .pred p; .reg .b64 db; setp.ne.b32 p, %32, 0; add.u64 db, %33, %34;\n"
                 "wgmma.mma_async.sync.aligned.m64n56k16.f32.bf16.bf16 "
                 "{%0,%1,%2,%3,%4,%5,%6,%7,%8,%9,%10,%11,%12,%13,%14,%15,%16,%17,%18,%19,%20,%21,%22,%23,%24,%25,%26,%27}, "
                 "{%28,%29,%30,%31}, db, p, 1, 1, %35; }\n"
                 : ACC28(d)
                 : "r"(a0), "r"(a1), "r"(a2), "r"(a3), "r"(sd), "l"(base), "n"(D), "n"(TB));
}
template <int TB, uint64_t D>
__device__ __forceinline__ void mma_rs64(float* d, uint32_t a0, uint32_t a1, uint32_t a2, uint32_t a3, int sd, uint64_t base) {
    asm volatile("{ .reg .pred p; .reg .b64 db; setp.ne.b32 p, %36, 0; add.u64 db, %37, %38;\n"
                 "wgmma.mma_async.sync.aligned.m64n64k16.f32.bf16.bf16 "
                 "{%0,%1,%2,%3,%4,%5,%6,%7,%8,%9,%10,%11,%12,%13,%14,%15,%16,%17,%18,%19,%20,%21,%22,%23,%24,%25,%26,%27,%28,%29,%30,%31}, "
                 "{%32,%33,%34,%35}, db, p, 1, 1, %39; }\n"
                 : ACC32(d, 0)
                 : "r"(a0), "r"(a1), "r"(a2), "r"(a3), "r"(sd), "l"(base), "n"(D), "n"(TB));
}
template <int TB, uint64_t D>
__device__ __forceinline__ void mma_rs128(float* d, uint32_t a0, uint32_t a1, uint32_t a2, uint32_t a3, int sd, uint64_t base) {
    asm volatile("{ .reg .pred p; .reg .b64 db; setp.ne.b32 p, %68, 0; add.u64 db, %69, %70;\n"
                 "wgmma.mma_async.sync.aligned.m64n128k16.f32.bf16.bf16 "
                 "{%0,%1,%2,%3,%4,%5,%6,%7,%8,%9,%10,%11,%12,%13,%14,%15,%16,%17,%18,%19,%20,%21,%22,%23,%24,%25,%26,%27,%28,%29,%30,%31,%32,%33,%34,%35,%36,%37,%38,%39,%40,%41,%42,%43,%44,%45,%46,%47,%48,%49,%50,%51,%52,%53,%54,%55,%56,%57,%58,%59,%60,%61,%62,%63}, "
                 "{%64,%65,%66,%67}, db, p, 1, 1, %71; }\n"
                 : ACC32(d, 0), ACC32(d, 32)
                 : "r"(a0), "r"(a1), "r"(a2), "r"(a3), "r"(sd), "l"(base), "n"(D), "n"(TB));
}
template <uint64_t DA, uint64_t DB>
__device__ __forceinline__ void mma_ss56_tt(float* d, int sd, uint64_t ba, uint64_t bb) {
    asm volatile("{ .reg .pred p; .reg .b64 da, db; setp.ne.b32 p, %28, 0; add.u64 da, %29, %31; add.u64 db, %30, %32;\n"
                 "wgmma.mma_async.sync.aligned.m64n56k16.f32.bf16.bf16 "
                 "{%0,%1,%2,%3,%4,%5,%6,%7,%8,%9,%10,%11,%12,%13,%14,%15,%16,%17,%18,%19,%20,%21,%22,%23,%24,%25,%26,%27}, "
                 "da, db, p, 1, 1, 1, 1; }\n"
                 : ACC28(d)
                 : "r"(sd), "l"(ba), "l"(bb), "n"(DA), "n"(DB));
}
template <int... I> struct Seq {};
template <class F, int... I> __device__ __forceinline__ void static_for_impl(F&& f, Seq<I...>) { (f(std::integral_constant<int, I>{}), ...); }
#define FOR7(...) static_for_impl([&](auto T_) { constexpr int t = decltype(T_)::value; __VA_ARGS__; }, Seq<0, 1, 2, 3, 4, 5, 6>{})
#define FOR8(...) static_for_impl([&](auto T_) { constexpr int t = decltype(T_)::value; __VA_ARGS__; }, Seq<0, 1, 2, 3, 4, 5, 6, 7>{})
#define FOR14(...) static_for_impl([&](auto T_) { constexpr int t = decltype(T_)::value; __VA_ARGS__; }, Seq<0, 1, 2, 3, 4, 5, 6, 7, 8, 9, 10, 11, 12, 13>{})

__device__ __forceinline__ int kblk(int p, int b) { return b == 0 ? p : b - (b <= p); }
__host__ __device__ constexpr int krow(int t) { return t < 3 ? 16 * t : (t < 6 ? 56 + 16 * (t - 3) : 48); }
#define AQ(A, b, t) ((t) < 3 ? A[2 * (b)][4 * (t)] : (t) < 6 ? A[2 * (b) + 1][4 * ((t) - 3)] : A[2 * (b)][12]), \
                    ((t) < 3 ? A[2 * (b)][4 * (t) + 1] : (t) < 6 ? A[2 * (b) + 1][4 * ((t) - 3) + 1] : A[2 * (b)][13]), \
                    ((t) < 3 ? A[2 * (b)][4 * (t) + 2] : (t) < 6 ? A[2 * (b) + 1][4 * ((t) - 3) + 2] : A[2 * (b) + 1][12]), \
                    ((t) < 3 ? A[2 * (b)][4 * (t) + 3] : (t) < 6 ? A[2 * (b) + 1][4 * ((t) - 3) + 3] : A[2 * (b) + 1][13])
#define D128(off, t) ((uint64_t)(((off) + krow(t) * 128) >> 4) + ((uint64_t)((t) == 6 ? (7168 - 1024) >> 4 : 0) << 32))
#define D64(off, t) ((uint64_t)(((off) + krow(t) * 64) >> 4) + ((uint64_t)((t) == 6 ? (3584 - 512) >> 4 : 0) << 32))

#define PL(k) (((k) - 3) * PLANE)
__device__ __forceinline__ void st_word(uint32_t* p, uint32_t v) { asm volatile("st.relaxed.gpu.global.u32 [%0], %1;" ::"l"(p), "r"(v) : "memory"); }
__device__ __forceinline__ uint32_t ld_word(const uint32_t* p) { uint32_t v; asm volatile("ld.relaxed.gpu.global.u32 %0, [%1];" : "=r"(v) : "l"(p) : "memory"); return v; }
__device__ __forceinline__ void tag_slice(uint32_t* w, uint32_t tag) { w[0] = settag(w[0], tag); w[4] = settag(w[4], tag); w[8] = settag(w[8], tag); w[12] = settag(w[12], tag); }
template <int O>
__device__ __forceinline__ void send_slice(uint4* dst, int lane, const uint32_t* w) {
    st_pkt<O>(dst, w[0], w[1], w[2], w[3]);
    st_pkt<O + 32>(dst, w[4], w[5], w[6], w[7]);
    st_pkt<O + 64>(dst, w[8], w[9], w[10], w[11]);
    asm volatile("{ .reg .b64 t; mov.b64 t, {%1,%2}; st.relaxed.gpu.global.b64 [%0+%3], t; }" ::"l"((char*)dst - lane * 8), "r"(w[12]), "r"(w[13]), "n"(16 * (O + 96)) : "memory");
}
#define RW4(v, o) "+r"(v[o]), "+r"(v[(o) + 1]), "+r"(v[(o) + 2]), "+r"(v[(o) + 3])
#define RW2(v, o) "+r"(v[o]), "+r"(v[(o) + 1])
#define WR4(v, o) "=&r"(v[o]), "=&r"(v[(o) + 1]), "=&r"(v[(o) + 2]), "=&r"(v[(o) + 3])
#define LDP(a, b, c, d, addr, off) "ld.relaxed.gpu.global.b128 q, [" addr "+" off "];\n mov.b128 {" a "," b "," c "," d "}, q;\n"
#define LDH(a, b, addr, off) "ld.relaxed.gpu.global.b64 h, [" addr "+" off "];\n mov.b64 {" a "," b "}, h;\n"
#define VOTE_OK "and.b32 t, t, 1;\n setp.ne.u32 p, t, 0;\n vote.sync.any.pred p, p, 0xffffffff;\n @!p bra.uni DN;\n"
#define CHK(x, tag) "lop3.b32 t, " x ", " tag ", t, 0xBE;\n"
__device__ __forceinline__ void check_cnt(uint32_t v, const uint32_t* p, uint32_t target) {
    asm volatile("{ .reg .pred p; .reg .b32 n, t; mov.u32 n, 0; mov.u32 t, %2;\n LP:\n"
                 "sub.s32 t, t, %1;\n setp.lt.s32 p, t, 0;\n vote.sync.any.pred p, p, 0xffffffff;\n @!p bra.uni DN;\n ld.relaxed.gpu.global.u32 t, [%0];\n" SPIN_TAIL("7")
                 ::"l"(p), "r"(target), "r"(v) : "memory");
}
__device__ __forceinline__ void poll_cnt(const uint32_t* p, uint32_t target) {
    asm volatile("{ .reg .pred p; .reg .b32 n, t; mov.u32 n, 0;\n LP:\n"
                 "ld.relaxed.gpu.global.u32 t, [%0];\n sub.s32 t, t, %1;\n setp.lt.s32 p, t, 0;\n vote.sync.any.pred p, p, 0xffffffff;\n @!p bra.uni DN;\n" SPIN_TAIL("1")
                 ::"l"(p), "r"(target) : "memory");
}
template <int STR>
__device__ __forceinline__ void poll4_kv(uint32_t* v, const uint4* p, uint32_t tag) {
    asm volatile("{ .reg .pred p; .reg .b32 n, t; .reg .b128 q; mov.u32 n, 0;\n LP:\n"
                 LDP("%0", "%1", "%2", "%3", "%16", "0") LDP("%4", "%5", "%6", "%7", "%16", "%18")
                 LDP("%8", "%9", "%10", "%11", "%16", "%19") LDP("%12", "%13", "%14", "%15", "%16", "%20")
                 "xor.b32 t, %0, %17;\n" CHK("%4", "%17") CHK("%8", "%17") CHK("%12", "%17") VOTE_OK SPIN_TAIL("2")
                 : WR4(v, 0), WR4(v, 4), WR4(v, 8), WR4(v, 12)
                 : "l"(p), "r"(tag), "n"(16 * STR), "n"(32 * STR), "n"(48 * STR)
                 : "memory");
}
template <int B>
__device__ __forceinline__ void blk_load(uint32_t (&A)[8][14], const uint4* src, int lane) {
    ld_pkt<0>(&A[2 * B][0], src); ld_pkt<32>(&A[2 * B][4], src); ld_pkt<64>(&A[2 * B][8], src);
    ld_pkt<512>(&A[2 * B + 1][0], src); ld_pkt<544>(&A[2 * B + 1][4], src); ld_pkt<576>(&A[2 * B + 1][8], src);
    asm volatile("{ .reg .b64 h;\n" LDH("%0", "%1", "%4", "1536") LDH("%2", "%3", "%4", "9728") "}"
                 : "=&r"(A[2 * B][12]), "=&r"(A[2 * B][13]), "=&r"(A[2 * B + 1][12]), "=&r"(A[2 * B + 1][13])
                 : "l"((const char*)src - lane * 8) : "memory");
}
template <int B>
__device__ __forceinline__ void blk_check(uint32_t (&A)[8][14], const uint4* src, int lane, uint32_t tag) {
    asm volatile("{ .reg .pred p; .reg .b32 n, t; .reg .b128 q; .reg .b64 h, a8; mov.u32 n, 0;\n LP:\n"
                 "xor.b32 t, %0, %30;\n" CHK("%4", "%30") CHK("%8", "%30") CHK("%12", "%30") CHK("%16", "%30") CHK("%20", "%30") CHK("%24", "%30") CHK("%26", "%30") VOTE_OK
                 LDP("%0", "%1", "%2", "%3", "%28", "0") LDP("%4", "%5", "%6", "%7", "%28", "512") LDP("%8", "%9", "%10", "%11", "%28", "1024")
                 LDP("%12", "%13", "%14", "%15", "%28", "8192") LDP("%16", "%17", "%18", "%19", "%28", "8704") LDP("%20", "%21", "%22", "%23", "%28", "9216")
                 "mad.wide.s32 a8, %29, -8, %28;\n" LDH("%24", "%25", "a8", "1536") LDH("%26", "%27", "a8", "9728") SPIN_TAIL("3")
                 "\n and.b32 %0, %0, -2; and.b32 %4, %4, -2; and.b32 %8, %8, -2; and.b32 %12, %12, -2; and.b32 %16, %16, -2; and.b32 %20, %20, -2; and.b32 %24, %24, -2; and.b32 %26, %26, -2;"
                 : RW4(A[2 * B], 0), RW4(A[2 * B], 4), RW4(A[2 * B], 8), RW4(A[2 * B + 1], 0), RW4(A[2 * B + 1], 4), RW4(A[2 * B + 1], 8),
                   RW2(A[2 * B], 12), RW2(A[2 * B + 1], 12)
                 : "l"(src), "r"(lane), "r"(tag)
                 : "memory");
}
__device__ __forceinline__ void st_async4(uint32_t a, uint32_t x, uint32_t y, uint32_t z, uint32_t w, uint32_t bar) {
    asm volatile("st.async.weak.shared::cluster.mbarrier::complete_tx::bytes.v4.b32 [%0], {%1,%2,%3,%4}, [%5];" ::"r"(a), "r"(x), "r"(y), "r"(z), "r"(w), "r"(bar) : "memory");
}
__device__ __forceinline__ uint32_t mapa(uint32_t a, uint32_t cta) { uint32_t r; asm("mapa.shared::cluster.u32 %0, %1, %2;" : "=r"(r) : "r"(a), "r"(cta)); return r; }
__device__ __forceinline__ void stat_load(uint32_t* v, const uint4* p) { ld_pkt<0>(v, p); ld_pkt<512>(v + 4, p); }
__device__ __forceinline__ void stat_check(uint32_t* v, const uint4* p, uint32_t tag) {
    asm volatile("{ .reg .pred p; .reg .b32 n, t; .reg .b128 q; mov.u32 n, 0;\n LP:\n"
                 "xor.b32 t, %3, %9;\n" CHK("%7", "%9") VOTE_OK
                 LDP("%0", "%1", "%2", "%3", "%8", "0") LDP("%4", "%5", "%6", "%7", "%8", "8192") SPIN_TAIL("4")
                 : RW4(v, 0), RW4(v, 4) : "l"(p), "r"(tag) : "memory");
}
__device__ __forceinline__ uint32_t x_bits(const uint32_t* X) {
    uint32_t r;
    asm volatile("{ .reg .b32 a, b; prmt.b32 a, %1, %2, 0x0040; prmt.b32 b, %3, %4, 0x0040; prmt.b32 %0, a, b, 0x5410; }" : "=r"(r) : "r"(X[0]), "r"(X[4]), "r"(X[8]), "r"(X[12]));
    return r;
}
template <int O>
__device__ __forceinline__ void slice_load(uint32_t* v, const uint4* p, int lane) {
    ld_pkt<O>(v, p); ld_pkt<O + 32>(v + 4, p); ld_pkt<O + 64>(v + 8, p);
    asm volatile("{ .reg .b64 h;\n" LDH("%0", "%1", "%2", "%3") "}" : "=r"(v[12]), "=r"(v[13]) : "l"((const char*)p - lane * 8), "n"(16 * (O + 96)) : "memory");
}
template <int O>
__device__ __forceinline__ void slice_check(uint32_t* v, const uint4* p, int lane, uint32_t tag) {
    asm volatile("{ .reg .pred p; .reg .b32 n, t; .reg .b128 q; .reg .b64 h; mov.u32 n, 0;\n LP:\n"
                 "xor.b32 t, %0, %16;\n" CHK("%4", "%16") CHK("%8", "%16") CHK("%12", "%16") VOTE_OK
                 LDP("%0", "%1", "%2", "%3", "%14", "%17") LDP("%4", "%5", "%6", "%7", "%14", "%18") LDP("%8", "%9", "%10", "%11", "%14", "%19")
                 LDH("%12", "%13", "%15", "%20") SPIN_TAIL("5")
                 : RW4(v, 0), RW4(v, 4), RW4(v, 8), RW2(v, 12)
                 : "l"(p), "l"((const char*)p - lane * 8), "r"(tag), "n"(16 * O), "n"(16 * (O + 32)), "n"(16 * (O + 64)), "n"(16 * (O + 96))
                 : "memory");
}
__device__ __forceinline__ void x_fix(uint32_t* X, uint32_t bits) {
    X[0] = __byte_perm(X[0], bits, 0x3214); X[4] = __byte_perm(X[4], bits, 0x3215); X[8] = __byte_perm(X[8], bits, 0x3216); X[12] = __byte_perm(X[12], bits, 0x3217);
}
__device__ __forceinline__ void sts4(uint32_t a, uint32_t x, uint32_t y, uint32_t z, uint32_t w) {
    asm volatile("st.shared.v4.u32 [%0], {%1,%2,%3,%4};" ::"r"(a), "r"(x), "r"(y), "r"(z), "r"(w) : "memory");
}
__device__ __forceinline__ void lds4(uint32_t* v, uint32_t a) {
    asm volatile("ld.shared.v4.u32 {%0,%1,%2,%3}, [%4];" : "=r"(v[0]), "=r"(v[1]), "=r"(v[2]), "=r"(v[3]) : "r"(a) : "memory");
}
struct LnCoef { uint32_t hi, lo, sh; };
__device__ __forceinline__ LnCoef ln_coef(float sum, float sq) {
    sum += __shfl_xor_sync(0xffffffffu, sum, 1); sq += __shfl_xor_sync(0xffffffffu, sq, 1);
    sum += __shfl_xor_sync(0xffffffffu, sum, 2); sq += __shfl_xor_sync(0xffffffffu, sq, 2);
    const float mean = sum * (1.f / 448.f);
    const float var = fmaxf(fmaf(-mean, mean, sq * (1.f / 448.f)), 0.f);
    const float sc = rsqrtf(var + 1e-5f);
    LnCoef r;
    r.hi = pack2(sc, sc);
    const float lo = sc - bf_lo(r.hi), sh = -mean * sc;
    r.lo = pack2(lo, lo);
    r.sh = pack2(sh, sh);
    return r;
}
template <int B>
__device__ __forceinline__ void normalize(uint32_t (&A)[8][14], const LnCoef& c0, const LnCoef& c1) {
#pragma unroll
    for (int s = 2 * B; s < 2 * B + 2; s++)
#pragma unroll
        for (int i = 0; i < 14; i++) {
            const LnCoef& k = (i & 1) ? c1 : c0;
            asm("{ .reg .b32 t; fma.rn.bf16x2 t, %0, %2, %3; fma.rn.bf16x2 %0, %0, %1, t; }" : "+r"(A[s][i]) : "r"(k.hi), "r"(k.lo), "r"(k.sh));
        }
}
__device__ __forceinline__ void slice_stats(const uint32_t* w, float* st) {
    float a = 0.f, b = 0.f, p = 0.f, q = 0.f;
#pragma unroll
    for (int i = 0; i < 7; i++) {
        const float e0 = bf_lo(w[2 * i]), e1 = bf_hi(w[2 * i]), e2 = bf_lo(w[2 * i + 1]), e3 = bf_hi(w[2 * i + 1]);
        a += e0 + e1; b += e2 + e3;
        p = fmaf(e0, e0, p); p = fmaf(e1, e1, p); q = fmaf(e2, e2, q); q = fmaf(e3, e3, q);
    }
    a += __shfl_xor_sync(0xffffffffu, a, 1); p += __shfl_xor_sync(0xffffffffu, p, 1); b += __shfl_xor_sync(0xffffffffu, b, 1); q += __shfl_xor_sync(0xffffffffu, q, 1);
    a += __shfl_xor_sync(0xffffffffu, a, 2); p += __shfl_xor_sync(0xffffffffu, p, 2); b += __shfl_xor_sync(0xffffffffu, b, 2); q += __shfl_xor_sync(0xffffffffu, q, 2);
    st[0] = a; st[1] = p; st[2] = b; st[3] = q;
}
__device__ __forceinline__ void dual_softmax(const float* p, uint32_t* out) {
    constexpr float L = 1.4426950408889634f;
#pragma unroll
    for (int r = 0; r < 2; r++) {
        float mx = fmaxf(p[2 * r], p[2 * r + 1]), mn = fminf(p[2 * r], p[2 * r + 1]);
#pragma unroll
        for (int i = 1; i < 7; i++) {
            mx = fmaxf(mx, fmaxf(p[4 * i + 2 * r], p[4 * i + 2 * r + 1]));
            mn = fminf(mn, fminf(p[4 * i + 2 * r], p[4 * i + 2 * r + 1]));
        }
        mx = fmaxf(mx, __shfl_xor_sync(0xffffffffu, mx, 1));
        mn = fminf(mn, __shfl_xor_sync(0xffffffffu, mn, 1));
        const float bx = -mx * L, bn = mn * L;
        float ep[14], en[14], sp = 0.f, sn = 0.f;
#pragma unroll
        for (int i = 0; i < 14; i++) {
            const float v = p[4 * (i >> 1) + 2 * r + (i & 1)];
            ep[i] = ex2(fmaf(v, L, bx));
            en[i] = ex2(fmaf(v, -L, bn));
            sp += ep[i]; sn += en[i];
        }
        sp += __shfl_xor_sync(0xffffffffu, sp, 1);
        sn += __shfl_xor_sync(0xffffffffu, sn, 1);
        const float ip = rcp(sp), in = rcp(sn);
#pragma unroll
        for (int i = 0; i < 7; i++) {
            out[4 * i + r] = pack2(ep[2 * i] * ip, ep[2 * i + 1] * ip);
            out[4 * i + 2 + r] = pack2(en[2 * i] * in, en[2 * i + 1] * in);
        }
    }
}
__device__ __forceinline__ float geglu(float g, float u) {
    const float t = tanh_hw(g * fmaf(g * g, 0.7978845608028654f * 0.044715f, 0.7978845608028654f));
    const float gu = g * u;
    return fmaf(t, gu, gu);
}
__device__ __forceinline__ void phi_gemm(const float* t, float* p) {
    uint32_t w[14];
#pragma unroll
    for (int i = 0; i < 14; i++) w[i] = pack2(t[2 * i], t[2 * i + 1]);
    const uint64_t db = BASE128(OFF_WPHI, 16, 0);
    wg_fence();
    mma_rs56<0, 0>(p, w[0], w[1], w[2], w[3], 0, db);
    mma_rs56<0, 2>(p, w[4], w[5], w[6], w[7], 1, db);
    mma_rs56<0, 4>(p, w[8], w[9], w[10], w[11], 1, db);
    mma_rs56<0, 6>(p, w[12], w[13], 0u, 0u, 1, db);
    wg_commit();
    wg_wait<0>();
}

}

#define BAR(i) (bars + 8 * (i))
#define R_WAIT() mbar_wait(BAR(slot), ph)
#define WSUM(i)
#define R_ADJ (slot * (STAGE >> 4))
#define R_NEXT() do { eb2 = eb1; eb1 = BAR(B_EMPTY + slot); if (++slot == NST) { slot = 0; ph ^= 1; } } while (0)
#define R_RELEASE(k) do { if (lane == 0) mbar_arrive((k) == 1 ? eb1 : eb2); } while (0)
#define PUSH_BEGIN() do { mbar_wait(BAR(B_ACK + wgi), ackph); ackph ^= 1; } while (0)
#define PUSH_ACK() do { __syncwarp(); if (lane == 0) asm volatile("mbarrier.arrive.shared::cluster.b64 _, [%0];" ::"r"(mapa(BAR(B_ACK + wgi), hr ^ 1)) : "memory"); } while (0)

__global__ void __cluster_dims__(2, 1, 1) __launch_bounds__(384, 1)
fused_kernel(Scratch* const sc, const __nv_bfloat16* __restrict__ x_in, const __nv_bfloat16* __restrict__ w_phi, const int trips,
             const __nv_bfloat16* __restrict__ wg, const __nv_bfloat16* __restrict__ wu, const __nv_bfloat16* __restrict__ wd,
             const __grid_constant__ Maps maps) {
    extern __shared__ __align__(1024) unsigned char smem_raw[];
    const uint32_t sb = s2u(smem_raw);
    const uint32_t bars = sb + OFF_BAR;
    const int wgi = __shfl_sync(0xffffffffu, threadIdx.x >> 7, 0);
    const int hr = blockIdx.x & 1, ck = blockIdx.x >> 1;
    const int gp = (ck - 4) & 7, q7 = ((ck - 36) * 37) >> 8;
    const int pr = __shfl_sync(0xffffffffu, ck < 4 ? ck : (ck < 36 ? (ck - 4) >> 3 : q7), 0);
    const int tile = __shfl_sync(0xffffffffu, ck < 4 ? 0 : (ck < 36 ? (gp ? 2 * gp : 1) : 2 * (ck - 36 - 7 * q7) + 3), 0);
    const int sl = 2 * pr + hr;
    STAMP(0);
    GSTAMP(60);
    if (threadIdx.x == 256) {
#pragma unroll
        for (int i = 0; i < NST; i++) mbar_init(BAR(i), 1);
        asm volatile("fence.mbarrier_init.release.cluster;" ::: "memory");
    }
    if (threadIdx.x == 288) {
        if ((sb & 0x3FFFF) != SB0) asm volatile("trap;");
#pragma unroll
        for (int i = NST; i < B_COUNT; i++) mbar_init(BAR(i), i >= B_ACK ? 4 : (i < B_RECV ? 8 : 1));
        asm volatile("fence.mbarrier_init.release.cluster;" ::: "memory");
    }
    __syncwarp();
    asm volatile("barrier.cluster.arrive.relaxed.aligned;" ::: "memory");

    if (wgi == 2) {
        asm volatile("setmaxnreg.dec.sync.aligned.u32 40;");
        const int t128 = fresh_tid() & 127, w = __shfl_sync(0xffffffffu, t128 >> 5, 0), lane = t128 & 31;
        uint32_t e0[2] = {0, 0}, e1[2] = {0, 0}, cw_target = 0;
        if (w == 0) {
#pragma unroll 1
            for (int n = 0; n < NST; n++) {
                const uint32_t dst = sb + n * STAGE, fb = BAR(n);
                asm volatile(ELECT "mbarrier.arrive.expect_tx.shared::cta.b64 _, [%0], %1; }" ::"r"(fb), "r"(n < 2 ? 2 * STAGE : STAGE) : "memory");
                if (n < 2) {
                    tma3x(sb + OFF_H + n * STAGE, &maps.x, tile * 128 + n * 64, fb);
                    tma3x(dst, &maps.x, tile * 128 + n * 64 + 32, fb);
                } else {
                    if (n == 3) mbar_wait(BAR(1), 0);
                    const int ra = 112 * (n - 2);
                    tma2d(dst, &maps.qkv, 448 + 56 * sl, ra, fb);
                    tma2d(dst + HALF, &maps.qkv, 896 + 56 * sl, ra, fb);
                }
            }
            asm volatile("barrier.cluster.wait.aligned;" ::: "memory");
            cw_target = (ld_word(g_cw + sl * 32) & ~15u) + 16;
#pragma unroll 1
            for (int k = 0; k < 2; k++) {
                const int n = t128 + 32 * k;
                int m = n - 2 - (n > PACK);
                const bool packed = m >= 30 ? (m < 38 || m >= 52) : m >= 22;
                if (m >= 30) m -= 30;
                if (n == PACK) m = tile < 8 ? tile : tile + 14;
                const int rot = n < 8 ? 0 : pr;
                const int ra = 112 * kblk(rot, m & 3), rb = 112 * kblk(rot, 2 * m & 3), rc = 112 * kblk(rot, (2 * m + 1) & 3);
                int kind = 0, m0, m1, c0, c1, r0, r1;
                if (m < 4) { m0 = m1 = 1; c0 = 448 + 56 * sl; c1 = c0 + 448; r0 = r1 = ra; }
                else if (m < 8) { m0 = m1 = m < 6 ? 1 : 2; c0 = c1 = 56 * sl; r0 = rb; r1 = rc; }
                else if (m < 20) { m0 = 3; m1 = 4; c0 = c1 = 224 * sl + 32 * hr + 64 * ((m - 8) >> 2); r0 = r1 = ra; }
                else if (m < 22) { kind = 2; m0 = 5; m1 = 6; c0 = c1 = 224 * sl + (hr ? 0 : 192); r0 = rb; r1 = rc; }
                else { m0 = m1 = 7; c0 = c1 = 56 * (2 * ((pr + (m >> 1) - 10) & 3) + hr); r0 = 224 * (sl ^ (m & 1)); r1 = r0 + 112; }
                if (packed) { kind = 1; r0 = sl * 16 + (m < 8 ? m : m - 14); r1 = 0; }
                e0[0] = e0[1]; e1[0] = e1[1];
                e0[1] = kind | (m0 << 2) | (m1 << 6) | (c0 << 10) | (c1 << 21);
                e1[1] = r0 | (r1 << 16);
            }
        } else {
            const int j = t128 - 32;
            asm volatile("barrier.cluster.wait.aligned;" ::: "memory");
            uint2 wv[7];
            const int k = j < 56 ? j : 55, hh = k >= 28;
#pragma unroll
            for (int i = 0; i < 7; i++) wv[i] = __ldg(reinterpret_cast<const uint2*>(w_phi + (sl * 56 + k) * 28) + i);
#pragma unroll 1
            for (int i = j; i < 7168 / 16; i += 96) sts4(sb + OFF_WPHI + i * 16, 0, 0, 0, 0);
            bar_sync(5, 96);
            if (j < 56) {
                uint32_t a4[4];
#pragma unroll
                for (int q = 0; q < 4; q++) a4[q] = sb + OFF_WPHI + (4 * hh + q) * 128 + ((((k >> 3) ^ (4 * hh + q)) & 7) << 4) + (k & 7) * 2;
                FOR14(const uint32_t v = (t & 1) ? wv[t >> 1].y : wv[t >> 1].x;
                      asm volatile("{ .reg .b16 l, h; mov.b32 {l, h}, %2; st.shared.u16 [%0+%3], l; st.shared.u16 [%1+%3], h; }"
                                   ::"r"(a4[t >= 7 ? 2 : 0]), "r"(a4[t >= 7 ? 3 : 1]), "r"(v), "n"((t % 7) * 1024) : "memory"));
            }
            __syncwarp();
            fence_async();
            bar_arrive(1, 224);
            bar_arrive(9, 224);
            if (w == 1) {
                mbar_wait(BAR(2), 0);
                mbar_wait(BAR(2), 1);
                const int b = blockIdx.x;
                asm volatile(ELECT "cp.async.bulk.prefetch.L2.global [%0], %1; }" ::"l"(wg + b * 6272), "r"(12544) : "memory");
                asm volatile(ELECT "cp.async.bulk.prefetch.L2.global [%0], %1; }" ::"l"(wu + b * 6272), "r"(12544) : "memory");
                asm volatile(ELECT "cp.async.bulk.prefetch.L2.global [%0], %1; }" ::"l"(wd + b * 6272), "r"(12544) : "memory");
            }
        }
        uint32_t kseq = ld_word(g_c1 + (sl * 8 * 16 + tile) * 32);
        int slot = 0, ph = 0, n = NST;
#pragma unroll 1
        for (int layer = 0; layer < 3; layer++) {
            if (w == 0) {
                const int nend = layer == 0 ? 11 : (layer == 1 ? 42 : 63);
#pragma unroll 1
                for (; n < nend; n++) {
                const uint32_t w0 = __shfl_sync(0xffffffffu, n < 32 ? e0[0] : e0[1], n & 31), w1 = __shfl_sync(0xffffffffu, n < 32 ? e1[0] : e1[1], n & 31);
                const uint32_t dst = sb + slot * STAGE, fb = BAR(n == PACK ? B_PACK : slot);
                const CUtensorMap* m0 = &maps.x + ((w0 >> 2) & 15);
                const CUtensorMap* m1 = &maps.x + ((w0 >> 6) & 15);
                const int c0 = (w0 >> 10) & 2047, c1 = w0 >> 21, r0 = w1 & 0xffff, r1 = w1 >> 16;
                if (n == 25) {
                    int it = 0;
                    uint32_t v;
                    do { asm volatile("ld.acquire.gpu.global.u32 %0, [%1];" : "=r"(v) : "l"(g_cw + sl * 32) : "memory"); } while ((int)(v - cw_target) < 0 && ++it < 0x400000);
                    asm volatile("fence.proxy.async.global;" ::: "memory");
                    __syncwarp();
                }
                mbar_wait(BAR(B_EMPTY + slot), ph);
                __syncwarp();
                asm volatile(ELECT "mbarrier.arrive.expect_tx.shared::cta.b64 _, [%0], %1; }" ::"r"(fb), "r"(STAGE) : "memory");
                if ((w0 & 3) == 0) {
                    tma2d(dst, m0, c0, r0, fb);
                    tma2d(dst + HALF, m1, c1, r1, fb);
                } else if (w0 & 1) {
                    asm volatile(ELECT "cp.async.bulk.shared::cluster.global.mbarrier::complete_tx::bytes [%0], [%1], %2, [%3]; }"
                                 ::"r"(dst), "l"(reinterpret_cast<const char*>(g_wp) + (size_t)r0 * STAGE), "r"(STAGE), "r"(fb) : "memory");
                } else {
                    tma2d(dst, m0, c0, r0, fb); tma2d(dst + 7168, m0, c0, r1, fb);
                    tma2d(dst + HALF, m1, c0, r0, fb); tma2d(dst + HALF + 7168, m1, c0, r1, fb);
                }
                if (n == PACK) asm volatile(ELECT "mbarrier.arrive.shared::cta.b64 _, [%0]; }" ::"r"(BAR(slot)) : "memory");
                if (++slot == NST) { slot = 0; ph ^= 1; }
                }
            } else if (w == 1 && layer == 1) {
                constexpr int ps = PACK % NST;
                mbar_wait(BAR(B_PACK), 0);
                asm volatile("{ .reg .pred e; elect.sync _|e, 0xffffffff;\n"
                             "@e cp.async.bulk.global.shared::cta.bulk_group [%0], [%1], %2;\n"
                             "@e cp.async.bulk.commit_group;\n"
                             "@e cp.async.bulk.wait_group.read 0;\n"
                             "@e mbarrier.arrive.shared::cta.b64 _, [%3], 8;\n"
                             "@e cp.async.bulk.wait_group 0;\n"
                             "@e fence.proxy.async.global;\n"
                             "@e red.release.gpu.global.add.u32 [%4], 1; }"
                             ::"l"(reinterpret_cast<char*>(g_wp) + (size_t)(sl * 16 + tile) * STAGE), "r"(sb + ps * STAGE), "r"(STAGE), "r"(BAR(B_EMPTY + ps)), "l"(g_cw + sl * 32) : "memory");
                __syncwarp();
            }
            if (layer < 2) {
            const uint32_t tag = layer ^ 1;
            kseq++;
            bar_sync(7, 384);
            ASTAMP(0);
            if (tile < 15) {
                const int sq = lane >> 3, pk = 8 * w + (lane & (tile == 14 ? 3 : 7));
                uint32_t v[16];
                if (layer == 0) poll_cnt(g_c1 + ((sl * 8 + (w >> 1) * 4 + (tile >> 2)) * 16 + (lane & 15)) * 32, kseq);
                ASTAMP(1);
                poll4_kv<32>(v, g_kv1 + ((sl * 16 + tile) * 16 + 4 * sq) * 32 + pk, tag);
#pragma unroll
                for (int k = 0; k < 4; k++) {
                    float lo = (bf_lo(v[k]) + bf_lo(v[4 + k])) + (bf_lo(v[8 + k]) + bf_lo(v[12 + k]));
                    float hi = (bf_hi(v[k]) + bf_hi(v[4 + k])) + (bf_hi(v[8 + k]) + bf_hi(v[12 + k]));
                    lo += __shfl_xor_sync(0xffffffffu, lo, 8); hi += __shfl_xor_sync(0xffffffffu, hi, 8);
                    lo += __shfl_xor_sync(0xffffffffu, lo, 16); hi += __shfl_xor_sync(0xffffffffu, hi, 16);
                    v[k] = pack2(lo, hi);
                }
                if (sq == 0) st_pkt<0>(g_kv2 + sl * 512 + 32 * tile + pk, settag(v[0], tag), v[1], v[2], v[3]);
            }
            ASTAMP(2);
            {
                const int item = t128 < 112 ? t128 : 112 + (t128 & 3), d = item >> 1;
                const int cc = t128 < 112 ? 2 * (d >= 28) + (item & 1) : item - 112;
                const int r = t128 < 112 ? d : 56 + (cc >> 1) + 2 * ((t128 - 112) >> 2);
                uint32_t ra = sb + OFF_KVB + r * 128 + 4 * cc, rx = (r & 7) << 4;
                asm volatile("" : "+r"(ra), "+r"(rx));
                FOR14(asm volatile("st.shared.u32 [%0+%2], %1;" ::"r"((ra ^ 8) + (((t & 7) << 4) ^ rx)), "r"(0), "n"((t >> 3) * 8192) : "memory"));
                uint32_t v[16];
                asm volatile("" : "+r"(ra), "+r"(rx));
                poll4_kv<8>(v, g_kv2 + sl * 512 + (item >> 3) * 32 + (item & 7), tag);
                FOR14(asm volatile("st.shared.u32 [%0+%2], %1;" ::"r"(ra + (((t & 7) << 4) ^ rx)), "r"(v[t < 7 ? t : t + 1]), "n"((t >> 3) * 8192) : "memory"));
                fence_async();
            }
            bar_arrive(3, 384);
            ASTAMP(3);
            }
        }
    } else {
        asm volatile("setmaxnreg.inc.sync.aligned.u32 232;");
        int lane = fresh_tid() & 31;
#define g (lane >> 2)
#define c (lane & 3)
#define t128 (w * 32 + lane)
        const int wu = __shfl_sync(0xffffffffu, fresh_tid() >> 5, 0), w = wu & 3;
        const uint32_t xoff = __shfl_sync(0xffffffffu, (3 * PLANE + ((tile * 2 + wgi) * 8) * 512 + w * 128) * 16, 0);
        char* xu = reinterpret_cast<char*>(g_ex) + xoff;
#define FRESH() asm volatile("" : "+l"(xu), "+r"(lane))
#define xp0 (reinterpret_cast<uint4*>(xu) + lane)
        const uint32_t hbuf = sb + OFF_H + wgi * STAGE;
        uint32_t slot = 0, ph = 0, eb1 = 0, eb2 = 0, ackph = 0, rcvph = 0, gatph = 0, swp = 0;
        uint32_t ppid = 6;
#define cx(s) (reinterpret_cast<uint32_t*>(reinterpret_cast<uint4*>(xu) + PL(1) + 112 + (s) * 512))
#define stp (reinterpret_cast<uint4*>(xu) + g + PL(0) + 112)
        uint32_t seq = ld_word(cx(sl));
        uint32_t kseq = ld_word(g_c1 + ((sl * 8 + wu) * 16 + tile) * 32);
        uint32_t stag = ld_word(reinterpret_cast<const uint32_t*>(stp + sl * 512) + 3) & 1;
        asm volatile("barrier.cluster.wait.aligned;" ::: "memory");
        STAMP(1);
        uint32_t X[14];
        const uint32_t x0row = (w < 2 ? hbuf : sb + wgi * STAGE) + ((w & 1) * 16 + (lane & 15)) * 128;
        mbar_wait(BAR(wgi), 0);
        STAMP(51);
#pragma unroll
        for (int j = 0; j < 4; j++) {
            const int G = 7 * sl + min(2 * j + (lane >> 4), 6);
            uint32_t q2, q3;
            asm volatile("ldmatrix.sync.aligned.m8n8.x4.shared.b16 {%0,%1,%2,%3}, [%4];" : "=r"(X[4 * j]), "=r"(X[4 * j + 1]), "=r"(q2), "=r"(q3)
                         : "r"(x0row + (G >> 3) * 4096 + (((G ^ lane) & 7) << 4)) : "memory");
            if (j < 3) { X[(4 * j + 2) % 14] = q2; X[(4 * j + 3) % 14] = q3; }
        }
#define PUSH_SLICE(W)                                                                          \
    {                                                                                          \
        if (t128 == 0) mbar_expect_tx(BAR(B_RECV + wgi), 7168);                                \
        PUSH_BEGIN();                                                                          \
        const uint32_t ra = mapa(hbuf + 24576 + t128 * 16, hr ^ 1), rb = mapa(sb + OFF_XR + wgi * 3072, hr ^ 1), rbar = mapa(BAR(B_RECV + wgi), hr ^ 1); \
        st_async4(ra, W[0], W[1], W[2], W[3], rbar);                                           \
        st_async4(ra + 2048, W[4], W[5], W[6], W[7], rbar);                                    \
        st_async4(rb + t128 * 16, W[8], W[9], W[10], W[11], rbar);                             \
        asm volatile("st.async.weak.shared::cluster.mbarrier::complete_tx::bytes.v2.b32 [%0], {%1,%2}, [%3];" ::"r"(rb + 2048 + t128 * 8), "r"(W[12]), "r"(W[13]), "r"(rbar) : "memory"); \
    }
#define PULL_SLICE(W)                                                                          \
    {                                                                                          \
        uint32_t t0, t1;                                                                       \
        mbar_wait(BAR(B_RECV + wgi), rcvph);                                                   \
        rcvph ^= 1;                                                                            \
        lds4(&A[1][0], hbuf + 24576 + t128 * 16);                                              \
        lds4(&A[1][4], hbuf + 26624 + t128 * 16);                                              \
        lds4(&A[1][8], sb + OFF_XR + wgi * 3072 + t128 * 16);                                  \
        asm volatile("ld.shared.v2.u32 {%0,%1}, [%2];" : "=r"(t0), "=r"(t1) : "r"(sb + OFF_XR + wgi * 3072 + 2048 + t128 * 8) : "memory"); \
        _Pragma("unroll") for (int i = 0; i < 12; i++) A[0][i] = (i & 3) ? W[i] : W[i] & ~1u;  \
        A[1][0] &= ~1u; A[1][4] &= ~1u; A[1][8] &= ~1u;                                        \
        A[0][12] = (hr ? t0 : W[12]) & ~1u; A[0][13] = hr ? t1 : W[13];                        \
        A[1][12] = (hr ? W[12] : t0) & ~1u; A[1][13] = hr ? W[13] : t1;                        \
        asm volatile("" : RW4(A[0], 0), RW4(A[0], 4), RW4(A[0], 8), RW2(A[0], 12), RW4(A[1], 0), RW4(A[1], 4), RW4(A[1], 8), RW2(A[1], 12)); \
        swp = hr * 448;                                                                        \
    }
#define SWB(b, t, db, sh) ((b) == 0 && (t) < 6 ? ((t) < 3 ? db##p : db##m) : db)
#define DECL_DB(b, MK, lbo, sh) const uint64_t db = MK(0, lbo, R_ADJ), dbp = (b) == 0 ? MK(0, lbo, R_ADJ + (swp >> (sh))) : db, dbm = (b) == 0 ? MK(0, lbo, R_ADJ - (swp >> (sh))) : db;
#define EARLY 1
#define EARLYK 1
#define PPB 2
#define PP_WAIT() if (wgi == 1) { bar_sync(ppid, 256); ppid ^= 14; }
#define PP_GO() if (wgi == 0) { bar_arrive(ppid, 256); ppid ^= 14; }
#define GAT_ISSUE(base)                                                                        \
    {                                                                                          \
        const char* gs = xu + ((base) + kblk(pr, GB) * 1024) * 16; \
        const uint32_t gd = hbuf + w * 3584, gb = BAR(B_GAT + wu);                     \
        asm volatile("{ .reg .pred e; elect.sync _|e, 0xffffffff;\n"                           \
                     "@e mbarrier.arrive.expect_tx.shared::cta.b64 _, [%2], 3584;\n"           \
                     "@e cp.async.bulk.shared::cluster.global.mbarrier::complete_tx::bytes [%0], [%1], 1792, [%2];\n" \
                     "@e cp.async.bulk.shared::cluster.global.mbarrier::complete_tx::bytes [%0+1792], [%1+8192], 1792, [%2]; }" \
                     ::"r"(gd), "l"(gs), "r"(gb) : "memory");                                  \
        __syncwarp();                                                                          \
    }
#define GAT_FETCH()                                                                            \
    {                                                                                          \
        mbar_wait(BAR(B_GAT + wu), gatph);                                             \
        gatph ^= 1;                                                                            \
        const uint32_t ga = hbuf + w * 3584 + lane * 16;                                       \
        _Pragma("unroll") for (int s2 = 0; s2 < 2; s2++) {                                     \
            lds4(&A[2 * GB + s2][0], ga + s2 * 1792); lds4(&A[2 * GB + s2][4], ga + s2 * 1792 + 512); lds4(&A[2 * GB + s2][8], ga + s2 * 1792 + 1024); \
            asm volatile("ld.shared.v2.u32 {%0,%1}, [%2];" : "=r"(A[2 * GB + s2][12]), "=r"(A[2 * GB + s2][13]) : "r"(ga - lane * 8 + s2 * 1792 + 1536) : "memory"); \
        }                                                                                      \
    }
#define PT 3
#define PREP(b, t, remote)                                                                     \
    if constexpr ((b) < 3 && (t) == PT) {                                                      \
        wg_commit();                                                                           \
        STAMP(80 + 8 * (step & 1) + 2 * (b));                                                  \
        if constexpr ((b) == 0) { if (remote) GAT_FETCH() }                   \
        if (remote) blk_check<((b) + 1) & 3>(A, BLK(xsrc, (b) + 1), lane, xtag);               \
        STAMP(81 + 8 * (step & 1) + 2 * (b));                                                  \
        if constexpr ((b) == 0) { if (remote) blk_load<3>(A, BLK(xsrc, 3), lane); } \
        normalize<((b) + 1) & 3>(A, k0, k1);                                                   \
        asm volatile("" : RW4(A[(2 * (b) + 2) & 7], 0), RW4(A[(2 * (b) + 2) & 7], 4), RW4(A[(2 * (b) + 2) & 7], 8), RW2(A[(2 * (b) + 2) & 7], 12), \
                          RW4(A[(2 * (b) + 3) & 7], 0), RW4(A[(2 * (b) + 3) & 7], 4), RW4(A[(2 * (b) + 3) & 7], 8), RW2(A[(2 * (b) + 3) & 7], 12)); \
        wg_fence();                                                                            \
    }                                                                                          \
    if constexpr ((b) == 3 && ((t) == 0 || (t) == 6)) { STAMP(86 + 8 * (step & 1) + (t) / 6); }
#define X0_BLOCK(b)                                                                            \
    { const int rr = lane & 7, hi = lane >> 4;                                                 \
    const uint32_t rowa = (w < 2 ? hbuf : sb + wgi * STAGE) + ((w & 1) * 16 + (lane & 15)) * 128; \
    FOR7(constexpr int G = 14 * (b) + (t < 3 ? 2 * t : (t < 6 ? 2 * t + 1 : 6));               \
         uint32_t q0, q1, q2, q3;                                                              \
         const uint32_t ad = t < 6 ? rowa + (((((G & 7) + hi) ^ rr) & 7) << 4) + ((G & 7) == 7 ? hi * 4096 : 0) : rowa + ((G + 7 * hi) >> 3) * 4096 + ((((G + 7 * hi) ^ rr) & 7) << 4); \
         asm volatile("ldmatrix.sync.aligned.m8n8.x4.shared.b16 {%0,%1,%2,%3}, [%4+%5];" : "=r"(q0), "=r"(q1), "=r"(q2), "=r"(q3) \
                      : "r"(ad), "n"(t < 6 ? (G >> 3) * 4096 : 0) : "memory");                 \
         if (t < 3) { A[2 * (b)][4 * t] = q0; A[2 * (b)][4 * t + 1] = q1; A[2 * (b)][4 * t + 2] = q2; A[2 * (b)][4 * t + 3] = q3; } \
         else if (t < 6) { A[2 * (b) + 1][(4 * t - 12) & 15] = q0; A[2 * (b) + 1][((4 * t - 12) & 15) + 1] = q1; A[2 * (b) + 1][((4 * t - 12) & 15) + 2] = q2; A[2 * (b) + 1][((4 * t - 12) & 15) + 3] = q3; } \
         else { A[2 * (b)][12] = q0; A[2 * (b)][13] = q1; A[2 * (b) + 1][12] = q2; A[2 * (b) + 1][13] = q3; }); }
#define BLK(base, b) ((base) + kblk(pr, b) * 1024)

#pragma unroll 1
        for (int step = 0; step < 4; step++) {
            FRESH();
            const uint32_t tag = (step >> 1) ^ 1;
            const int so = (step >> 1) * 24 + (step & 1) * 12;
            (void)so;
            uint32_t A[8][14];
            uint4* const xsrc = xp0 + ((step & 1) ? PL(2) : PL(0));
            const uint32_t xtag = (step & 1) ? tag : ((seq >> 3) & 1) ^ 1;
            uint32_t xbits;
            {
                float st[4];
                slice_stats(X, st);
                stag ^= 1;
                xbits = x_bits(X);
                tag_slice(X, xtag);
                if (step) send_slice<0>(xsrc + sl * 512, lane, X);
                if (c == 0) st_pkt<0>(stp + sl * 512, __float_as_uint(st[0]), __float_as_uint(st[1]), __float_as_uint(st[2]), settag(__float_as_uint(st[3]), stag));
            }
            STAMP(2 + so);
            uint32_t sv[8];
            if (step == 0) {
                X0_BLOCK(0) X0_BLOCK(1) X0_BLOCK(3)
                mbar_wait(BAR(wgi ^ 1), 0);
                R_NEXT();
                R_NEXT();
                stat_load(sv, stp + c * 1024);
                stat_check(sv, stp + c * 1024, stag);
                STAMP(52 + step);
            } else {
                kill<14>(A[2]); kill<14>(A[3]); kill<14>(A[6]); kill<14>(A[7]);
                PUSH_SLICE(X)
                stat_load(sv, stp + c * 1024);
                PULL_SLICE(X)
                stat_check(sv, stp + c * 1024, stag);
                STAMP(52 + step);
                GAT_ISSUE((step & 1) ? PL(2) : PL(0))
            }
            LnCoef k0, k1;
            {
                k0 = ln_coef(__uint_as_float(sv[0]) + __uint_as_float(sv[4]), __uint_as_float(sv[1]) + __uint_as_float(sv[5]));
                k1 = ln_coef(__uint_as_float(sv[2]) + __uint_as_float(sv[6]), __uint_as_float(sv[3] & ~1u) + __uint_as_float(sv[7] & ~1u));
            }
            if (step) {
                blk_load<2>(A, BLK(xsrc, 2), lane);
            } else {
                X0_BLOCK(2)
                R_RELEASE(2);
            }
            STAMP(3 + so);
            GSTAMP(76 + step);

            if ((step & 1) == 0) {
                float tq[28];
                {
                    float av[28];
#define KV_BLOCK(b)                                                                           \
    if (GB == 2 && (b) == 1 && step) GAT_FETCH()                                                         \
    if ((b) == 2) PUSH_ACK();                                                                 \
    if (QE && (b) == 1) R_RELEASE(2);                                                         \
    if (QE && (b) == 2) { wg_wait<2>(); R_RELEASE(2); }                                       \
    R_WAIT();                                                                                 \
    if ((b) == PPK) { PP_WAIT() }                                                             \
    { DECL_DB(b, BASE128, 16, 0)                                                              \
    wg_fence();                                                                               \
    FOR7(mma_rs56<1, D128(0, t)>(tq, AQ(A, b, t), (b) + t > 0, SWB(b, t, db, 0));             \
         mma_rs56<1, D128(HALF, t)>(av, AQ(A, b, t), (b) + t > 0, SWB(b, t, db, 0));          \
         PREP(b, t, step)); }                                                                 \
    wg_commit();                                                                              \
    if ((b) == 3 && PPK < 4) { PP_GO() }                                                      \
    R_NEXT();
                    normalize<0>(A, k0, k1);
                    KV_BLOCK(0) KV_BLOCK(1) KV_BLOCK(2) KV_BLOCK(3)
                    wg_wait<0>();
                    if (lane < (QE ? 3 : NST)) mbar_arrive(BAR(B_EMPTY + (slot + NST - 1 - lane) % NST));
                    STAMP(4 + so);
                    WSUM(80 + 7 * (step >> 1));
                    const int m = lane >> 3, rr = lane & 7;
                    const uint32_t rowa = hbuf + 16384 + (w * 16 + rr + 8 * (m & 1)) * 128;
                    const uint32_t one = c == 0 ? 0x00003f80u : 0u;
                    if (step == 0) { bar_sync(wgi ? 9 : 1, 224); }
#pragma unroll
                    for (int j = 0; j < 4; j++) {
                        const uint32_t a = rowa + (((2 * j + (m >> 1)) ^ rr) << 4);
                        if (j < 3) stsm4(a, pack2(av[8 * j], av[8 * j + 1]), pack2(av[8 * j + 2], av[8 * j + 3]), pack2(av[8 * j + 4], av[8 * j + 5]), pack2(av[8 * j + 6], av[8 * j + 7]));
                        else stsm4(a, pack2(av[24], av[25]), pack2(av[26], av[27]), one, one);
                    }
                }
                uint32_t PH[28];
                int it = 1;
#pragma unroll 1
                do {
                    float pp[28];
                    phi_gemm(tq, pp);
                    dual_softmax(pp, PH);
                    if (((trips >> (it + 1)) & 1) == 0) continue;
                    {
                        const int m = lane >> 3, rr = lane & 7;
                        const uint32_t rowa = hbuf + (w * 16 + rr + 8 * (m & 1)) * 128;
#pragma unroll
                        for (int j = 0; j < 7; j++) {
                            const int cg = 2 * j + (m >> 1), hi = cg >= 7;
                            stsm4(rowa + hi * 8192 + (((cg - 7 * hi) ^ rr) << 4), PH[4 * j], PH[4 * j + 1], PH[4 * j + 2], PH[4 * j + 3]);
                        }
                    }
                    fence_async();
                    STAMP(5 + so);
#define Q_STAGE(b0)                                                                           \
    R_WAIT();                                                                                 \
    { DECL_DB(b0, BASE128, 16, 0)                                                             \
    wg_fence();                                                                               \
    FOR7(mma_rs56<1, D128(0, t)>(tq, AQ(A, b0, t), (b0) + t > 0, SWB(b0, t, db, 0)));         \
    FOR7(mma_rs56<1, D128(HALF, t)>(tq, AQ(A, (b0) + 1, t), 1, db)); }                        \
    wg_commit();                                                                              \
    R_NEXT();
                    if (QE && wgi == 0) { kill<28>(tq); Q_STAGE(0) Q_STAGE(2) wg_wait<1>(); R_RELEASE(2); wg_wait<0>(); R_RELEASE(1); }
                    bar_sync(2, 256);
                    float kv[28];
                    const uint64_t da = BASE128(OFF_H + 16384, 16, 0), dbk = BASE128(OFF_H, 16, wgi * 512);
                    wg_fence();
                    FOR8(constexpr uint64_t o = ((t >> 2) * STAGE + (t & 3) * 2048) >> 4; mma_ss56_tt<o, o>(kv, t > 0, da, dbk));
                    wg_commit();
                    wg_wait<0>();
#pragma unroll
                    for (int hf = 0; hf < 2; hf++) {
                        const int d = 16 * w + g + 8 * hf;
                        if ((d < 56 && (d >= 28) == (c >= 2)) || d == 56) {
                            const int item = d < 56 ? 2 * d + (c & 1) : 112 + c;
                            uint4* dst = g_kv1 + ((sl * 16 + (item >> 3)) * 16 + tile) * 32 + wgi * 16 + (item & 7);
#define KVW(i) pack2(kv[4 * (i) + 2 * hf], kv[4 * (i) + 2 * hf + 1])
                            st_pkt<0>(dst, settag(KVW(0), tag), KVW(1), KVW(2), KVW(3));
                            st_pkt<8>(dst, settag(KVW(4), tag), KVW(5), KVW(6), 0u);
                        }
                    }
                    __syncwarp();
                    kseq++;
                    if (lane == 0) st_word(g_c1 + ((sl * 8 + wu) * 16 + tile) * 32, kseq);
                    bar_arrive(7, 384);
                    STAMP(6 + so);
                    if (!QE || wgi == 1) { kill<28>(tq); Q_STAGE(0) Q_STAGE(2) wg_wait<1>(); R_RELEASE(2); wg_wait<0>(); R_RELEASE(1); }
                    STAMP(7 + so);
                    kill<28>(PH);
                } while (((trips >> (++it)) & 1));
                STAMP(8 + so);
                FRESH();
                if (step) {
                    slice_load<PL(0)>(X, xp0 + sl * 512, lane);
                } else {
                    const uint32_t* xp = reinterpret_cast<const uint32_t*>(x_in + (size_t)(tile * 128 + wu * 16 + g) * 448 + 56 * sl + 2 * c);
#pragma unroll
                    for (int i = 0; i < 7; i++) { X[2 * i] = __ldg(xp + 4 * i); X[2 * i + 1] = __ldg(xp + 4 * i + 8 * 224); }
                }
                bar_sync(3, 384);
                STAMP(9 + so);
                const uint4* const osrc = xp0 + PL(1);
                {
                    float nm[32];
                    const uint64_t db = BASE128(OFF_KVB, 16, 0);
                    wg_fence();
                    FOR7(mma_rs64<0, ((t >> 2) * 8192 + (t & 3) * 32) / 16>(nm, PH[4 * t], PH[4 * t + 1], PH[4 * t + 2], PH[4 * t + 3], t > 0, db));
                    wg_commit();
                    wg_wait<0>();
                    const float i00 = rcp(nm[28] + 1e-6f), i01 = rcp(nm[29] + 1e-6f), i10 = rcp(nm[30] + 1e-6f), i11 = rcp(nm[31] + 1e-6f);
                    const float m0 = c >= 2 ? i01 : i00, m1 = c >= 2 ? i11 : i10;
                    uint32_t O[14];
#pragma unroll
                    for (int i = 0; i < 7; i++) {
                        const float f0 = i < 3 ? i00 : (i > 3 ? i01 : m0), f1 = i < 3 ? i10 : (i > 3 ? i11 : m1);
                        O[2 * i] = pack2(nm[4 * i] * f0, nm[4 * i + 1] * f0);
                        O[2 * i + 1] = pack2(nm[4 * i + 2] * f1, nm[4 * i + 3] * f1);
                    }
                    if (OST) { PP_WAIT() }
                    tag_slice(O, tag);
                    send_slice<PL(1)>(xp0 + sl * 512, lane, O);
                    seq++;
                    if (lane == 0) st_word(cx(sl), seq);
                    STAMP(10 + so);
                    PUSH_SLICE(O)
                    if (OST == 1) { PP_GO() }
                    const uint32_t cv = ld_word(cx(lane & 7));
                    PULL_SLICE(O)
                    check_cnt(cv, cx(lane & 7), seq);
                    if (OST == 2) { PP_GO() }
                    STAMP(56 + (step >> 1));
                    GAT_ISSUE(PL(1))
                    blk_load<3 - GB>(A, BLK(osrc, 3 - GB), lane);
                }
                float ao[28];
#define WO_BLOCK(b)                                                                           \
    if ((b) > 0) blk_check<b>(A, BLK(osrc, b), lane, tag);                                    \
    if (((b) & 1) == 0) R_WAIT();                                                             \
    { DECL_DB(b, BASE128, 16, 0)                                                              \
    wg_fence();                                                                               \
    FOR7(mma_rs56<1, D128(((b) & 1) * HALF, t)>(ao, AQ(A, b, t), (b) + t > 0, SWB(b, t, db, 0))); } \
    wg_commit();                                                                              \
    if ((b) & 1) R_NEXT();
                WO_BLOCK(0)
                STAMP(11 + so);
                blk_load<3>(A, BLK(osrc, 3), lane);
                if (GB == 1) GAT_FETCH()
                WO_BLOCK(1)
                if (GB == 2) GAT_FETCH()
                WO_BLOCK(2)
                PUSH_ACK();
                WO_BLOCK(3)
                wg_wait<0>();
                if (EARLY >= 1) R_RELEASE(2);
                if (EARLY >= 2) R_RELEASE(1);
                STAMP(12 + so);
                WSUM(86 + 7 * (step >> 1));
                x_fix(X, xbits);
#pragma unroll
                for (int i = 0; i < 14; i++) X[i] = pack2(bf_lo(X[i]) + ao[2 * i], bf_hi(X[i]) + ao[2 * i + 1]);
            } else {
                uint32_t H[56];
                float ag[64];
#define F1_EPI(dst, ng, ag)                                                                    \
    _Pragma("unroll") for (int i = 0; i < 2 * (ng); i++)                                       \
        (dst)[i] = pack2(geglu(ag[2 * i], ag[4 * (ng) + 2 * i]), geglu(ag[2 * i + 1], ag[4 * (ng) + 2 * i + 1]));
#define H_PUSH(h0, off) st_async4(rem_h + (off), H[h0], H[(h0) + 1], H[(h0) + 2], H[(h0) + 3], mapa(BAR(B_RECV2 + wgi), hr ^ 1));
#define F1_BLOCK(b, first)                                                                     \
    if ((first) && (b) < 2 && (b) >= EARLY) R_RELEASE(2);                                      \
    if (GB == 2 && (first) && (b) == 1) GAT_FETCH()                                                       \
    if ((first) && (b) == 2) PUSH_ACK();                                                       \
    R_WAIT();                                                                                  \
    if ((b) == ((first) ? PPF : PPB)) { PP_WAIT() }                                            \
    { DECL_DB(b, BASE128, HALF, 0)                                                             \
    wg_fence();                                                                                \
    FOR7(mma_rs128<1, D128(0, t)>(ag, AQ(A, b, t), (b) + t > 0, SWB(b, t, db, 0));             \
         if constexpr (first) { PREP(b, t, true) }); }                                         \
    wg_commit();                                                                               \
    if ((b) == 3) { PP_GO() }                                                                  \
    if ((b) > 0) { wg_wait<1>(); R_RELEASE(1); }       \
    R_NEXT();
                normalize<0>(A, k0, k1);
                F1_BLOCK(0, true) F1_BLOCK(1, true) F1_BLOCK(2, true) F1_BLOCK(3, true)
                if (t128 == 0) { mbar_expect_tx(BAR(B_RECV + wgi), 16384); mbar_expect_tx(BAR(B_RECV2 + wgi), 12288); }
                PUSH_BEGIN();
                wg_wait<0>();
                R_RELEASE(1);
                if (step == 1) R_NEXT();
                int p = 0;
#pragma unroll 1
                do {
                    STAMP(68 + p);
                    F1_EPI(H + 32, 8, ag)
                    STAMP(4 + p + so);
                    WSUM(81 + p + 7 * (step >> 1));
                    if (((trips >> (p + 1)) & 1) == 0) continue;
                    {
                        const uint32_t pk = (p ? hbuf + 16384 : sb + OFF_KVB + wgi * 8192) + w * 2048;
#pragma unroll
                        for (int k = 0; k < 4; k++) sts4(pk + k * 512 + lane * 16, H[32 + 4 * k], H[33 + 4 * k], H[34 + 4 * k], H[35 + 4 * k]);
                        fence_async();
                        __syncwarp();
                        asm volatile(ELECT "cp.async.bulk.shared::cluster.shared::cta.mbarrier::complete_tx::bytes [%0], [%1], 2048, [%2]; }"
                                     ::"r"(mapa(hbuf + p * 8192 + w * 2048, hr ^ 1)), "r"(pk), "r"(mapa(BAR(B_RECV + wgi), hr ^ 1)) : "memory");
                    }
                    kill<64>(ag);
                    F1_BLOCK(0, false) F1_BLOCK(1, false) F1_BLOCK(2, false) F1_BLOCK(3, false)
                    wg_wait<0>();
                    R_RELEASE(1);
                    kill<16>(H + 32);
                } while (((trips >> (++p)) & 1));
#pragma unroll
                for (int k = 0; k < 4; k++) lds4(H + 16 + 4 * k, hbuf + 16384 + w * 2048 + k * 512 + lane * 16);
                __syncwarp();
                if (lane == 0) asm volatile("mbarrier.arrive.shared::cluster.b64 _, [%0];" ::"r"(mapa(BAR(B_ACK2 + wgi), hr ^ 1)) : "memory");
                const uint32_t rem_h = mapa(hbuf + w * 2048 + lane * 16, hr ^ 1);
#define F1_LAST(b0)                                                                            \
    R_WAIT();                                                                                  \
    if (b0) { PP_WAIT() }                                                                      \
    { DECL_DB(b0, BASE64, HALF, 1)                                                             \
    wg_fence();                                                                                \
    FOR7(mma_rs64<1, D64(0, t)>(al, AQ(A, b0, t), (b0) + t > 0, SWB(b0, t, db, 1)));           \
    FOR7(mma_rs64<1, D64(7168, t)>(al, AQ(A, (b0) + 1, t), 1, db)); }                          \
    wg_commit();                                                                               \
    if (b0) { PP_GO() }                                                                        \
    R_NEXT();
                float al[32];
                F1_LAST(0)
                mbar_wait(BAR(B_RECV + wgi), rcvph);
                rcvph ^= 1;
                mbar_wait(BAR(B_ACK2 + wgi), step >> 1);
                H_PUSH(32, 16384) H_PUSH(36, 16896)
                F1_LAST(2)
                H_PUSH(40, 17408) H_PUSH(44, 17920)
                wg_wait<1>();
                R_RELEASE(2);
                wg_wait<0>();
                R_RELEASE(1);
                uint32_t HP[56];
#pragma unroll
                for (int k = 0; k < 4; k++) lds4(H + 4 * k, sb + OFF_KVB + wgi * 8192 + w * 2048 + k * 512 + lane * 16);
#pragma unroll
                for (int t = 0; t < 8; t++) lds4(HP + 4 * t, hbuf + (t >> 2) * 8192 + w * 2048 + (t & 3) * 512 + lane * 16);
                F1_EPI(H + 48, 4, al)
                H_PUSH(48, 24576 - w * 1024) H_PUSH(52, 25088 - w * 1024)
                STAMP(7 + so);
                WSUM(84 + 7 * (step >> 1));
                FRESH();
                float acc[28];
                const uint32_t roA = hr ? 256u : 0u, roB = hr ? (uint32_t)-1536 : 0u;
                const uint32_t rpA = hr ? 0u : 256u, rpB = hr ? 0u : (uint32_t)-1536;
                float res[28];
                uint32_t v0[14], v1[14], P[14];
                const uint4* ps = xp0 + sl * 512;
#define F2_OWN_A()                                                                             \
    R_WAIT();                                                                                  \
    d0 = BASE128(0, 16, R_ADJ + roA); d1 = BASE128(0, 16, R_ADJ + roB);                        \
    wg_fence();                                                                                \
    FOR14(if constexpr (t < OT) mma_rs56<1, t * 128>(acc, H[4 * t], H[4 * t + 1], H[4 * t + 2], H[4 * t + 3], t > 0, d0)); \
    wg_commit();
#define F2_OWN_B()                                                                             \
    wg_fence();                                                                                \
    FOR14(if constexpr (t >= OT) mma_rs56<1, t * 128>(acc, H[4 * t], H[4 * t + 1], H[4 * t + 2], H[4 * t + 3], 1, t < 12 ? d0 : d1)); \
    wg_commit();                                                                               \
    R_NEXT();
#define F2_PEER()                                                                              \
    R_WAIT();                                                                                  \
    if (F2PP) { PP_WAIT() }                                                                    \
    d0 = BASE128(0, 16, R_ADJ + rpA); d1 = BASE128(0, 16, R_ADJ + rpB);                        \
    wg_fence();                                                                                \
    FOR14(mma_rs56<1, t * 128>(acc, HP[4 * t], HP[4 * t + 1], HP[4 * t + 2], HP[4 * t + 3], 1, t < 12 ? d0 : d1)); \
    wg_commit();                                                                               \
    if (F2PP) { PP_GO() }                                                                      \
    R_NEXT();
#define F2_TURN(u)                                                                             \
    wg_wait<1>();                                                                              \
    R_RELEASE(2);                                                                              \
    wg_wait<0>();                                                                              \
    R_RELEASE(1);                                                                              \
    _Pragma("unroll") for (int i = 0; i < 14; i++) P[i] = pack2(acc[2 * i], acc[2 * i + 1]);   \
    tag_slice(P, tag);                                                                         \
    asm volatile("" : RW4(P, 0), RW4(P, 4), RW4(P, 8), RW2(P, 12));                            \
    kill<28>(acc);                                                                             \
    F2_OWN_A()                                                                                 \
    if ((u) == 2) { slice_load<PL(3)>(v0, ps, lane); slice_load<PL(4)>(v1, ps, lane); } \
    send_slice<PL(3 + (u))>(xp0 + (2 * ((pr + (u) + 1) & 3) + hr) * 512, lane, P);             \
    seq++;                                                                                     \
    if (lane == 0) st_word(cx(sl), seq);                                                       \
    __syncwarp();                                                                              \
    STAMP(8 + (u) + so);                                                                       \
    F2_OWN_B()
                uint64_t d0, d1;
                F2_OWN_A()
                F2_OWN_B()
                R_WAIT();
                d0 = BASE128(0, 16, R_ADJ + rpA); d1 = BASE128(0, 16, R_ADJ + rpB);
                wg_fence();
                FOR8(mma_rs56<1, t * 128>(acc, HP[4 * t], HP[4 * t + 1], HP[4 * t + 2], HP[4 * t + 3], 1, d0));
                wg_commit();
                mbar_wait(BAR(B_RECV2 + wgi), step >> 1);
#pragma unroll
                for (int k = 0; k < 4; k++) lds4(HP + 32 + 4 * k, hbuf + 16384 + w * 2048 + k * 512 + lane * 16);
                lds4(HP + 48, hbuf + 24576 + w * 1024 + lane * 16);
                lds4(HP + 52, hbuf + 25088 + w * 1024 + lane * 16);
                if (step == 1) PUSH_ACK();
                wg_fence();
                FOR14(if constexpr (t >= 8) mma_rs56<1, t * 128>(acc, HP[4 * t], HP[4 * t + 1], HP[4 * t + 2], HP[4 * t + 3], 1, t < 12 ? d0 : d1));
                wg_commit();
                R_NEXT();
                F2_TURN(0)
                F2_PEER()
                F2_TURN(1)
                F2_PEER()
                F2_TURN(2)
                STAMP(64 + 8 * (step >> 1));
                slice_check<PL(3)>(v0, ps, lane, tag);
                slice_check<PL(4)>(v1, ps, lane, tag);
#pragma unroll
                for (int i = 0; i < 14; i++) { res[2 * i] = bf_lo(v0[i]) + bf_lo(v1[i]); res[2 * i + 1] = bf_hi(v0[i]) + bf_hi(v1[i]); }
                slice_load<PL(2)>(X, ps, lane);
                STAMP(65 + 8 * (step >> 1));
                const uint32_t cv = ld_word(cx(2 * ((pr + 1) & 3) + hr));
                F2_PEER()
                STAMP(66 + 8 * (step >> 1));
                check_cnt(cv, cx(2 * ((pr + 1) & 3) + hr), seq);
                STAMP(67 + 8 * (step >> 1));
                slice_load<PL(5)>(v0, ps, lane);
                x_fix(X, xbits);
                slice_check<PL(5)>(v0, ps, lane, tag);
#pragma unroll
                for (int i = 0; i < 14; i++) { res[2 * i] += bf_lo(v0[i]); res[2 * i + 1] += bf_hi(v0[i]); }
                STAMP(11 + so);
                wg_wait<0>();
                if (EARLYK >= 1) R_RELEASE(2);
                STAMP(12 + so);
                WSUM(85 + 7 * (step >> 1));
#pragma unroll
                for (int i = 0; i < 14; i++) X[i] = pack2(fmaf(res[2 * i] + acc[2 * i], 0.5f, bf_lo(X[i])), fmaf(res[2 * i + 1] + acc[2 * i + 1], 0.5f, bf_hi(X[i])));
            }
        }
        {
            const int m = lane >> 3, rr = lane & 7;
            const uint32_t ob = hbuf + w * 2048, rowa = ob + (rr + 8 * (m & 1)) * 112 + (m >> 1) * 16;
#pragma unroll
            for (int j = 0; j < 3; j++) stsm4(rowa + 32 * j, X[4 * j], X[4 * j + 1], X[4 * j + 2], X[4 * j + 3]);
            asm volatile("stmatrix.sync.aligned.m8n8.x2.shared.b16 [%0], {%1,%2};" ::"r"(ob + (rr + 8 * (m & 1)) * 112 + 96), "r"(X[12]), "r"(X[13]) : "memory");
            fence_async();
            __syncwarp();
            if (lane == 0) {
                asm volatile("cp.async.bulk.tensor.2d.global.shared::cta.bulk_group [%0, {%2, %3}], [%1];" ::"l"(&maps.out), "r"(ob), "r"(56 * sl), "r"(tile * 128 + wu * 16) : "memory");
                asm volatile("cp.async.bulk.commit_group;" ::: "memory");
                asm volatile("cp.async.bulk.wait_group.read 0;" ::: "memory");
            }
        }
        STAMP(50);
        GSTAMP(61);
        PDUMP();
    }
}

#undef g
#undef c
#undef t128

typedef CUresult (*EncodeFn)(CUtensorMap*, CUtensorMapDataType, cuuint32_t, void*, const cuuint64_t*, const cuuint64_t*, const cuuint32_t*,
                             const cuuint32_t*, CUtensorMapInterleave, CUtensorMapSwizzle, CUtensorMapL2promotion, CUtensorMapFloatOOBfill);

static void make_map(EncodeFn enc, CUtensorMap* m, const void* p, uint64_t cols, uint64_t rows, uint32_t bc, uint32_t br, CUtensorMapSwizzle sw) {
    cuuint64_t gd[2] = {cols, rows};
    cuuint64_t gs[1] = {cols * 2};
    cuuint32_t bd[2] = {bc, br};
    cuuint32_t es[2] = {1, 1};
    enc(m, CU_TENSOR_MAP_DATA_TYPE_BFLOAT16, 2, const_cast<void*>(p), gd, gs, bd, es, CU_TENSOR_MAP_INTERLEAVE_NONE, sw,
        CU_TENSOR_MAP_L2_PROMOTION_L2_128B, CU_TENSOR_MAP_FLOAT_OOB_FILL_NONE);
}

extern "C" void kernel_launch(void* const* d_in, const int* in_sizes, int n_in, void* d_out, int out_size) {
    (void)in_sizes; (void)n_in; (void)out_size;
    static EncodeFn enc = nullptr;
    static Scratch* scratch = nullptr;
    if (!enc) {
        void* fn = nullptr;
        cudaDriverEntryPointQueryResult qr;
        cudaGetDriverEntryPoint("cuTensorMapEncodeTiled", &fn, cudaEnableDefault, &qr);
        enc = (EncodeFn)fn;
        cudaGetSymbolAddress((void**)&scratch, g_scratch);
        cudaFuncSetAttribute(fused_kernel, cudaFuncAttributeMaxDynamicSharedMemorySize, SMEM_BYTES);
    }
    Maps maps;
    {
        cuuint64_t gd[3] = {64, 2048, 7};
        cuuint64_t gs[2] = {896, 128};
        cuuint32_t bd[3] = {64, 32, 7};
        cuuint32_t es[3] = {1, 1, 1};
        enc(&maps.x, CU_TENSOR_MAP_DATA_TYPE_BFLOAT16, 3, d_in[0], gd, gs, bd, es, CU_TENSOR_MAP_INTERLEAVE_NONE, CU_TENSOR_MAP_SWIZZLE_128B,
            CU_TENSOR_MAP_L2_PROMOTION_L2_128B, CU_TENSOR_MAP_FLOAT_OOB_FILL_NONE);
    }
    make_map(enc, &maps.out, d_out, 448, 2048, 56, 16, CU_TENSOR_MAP_SWIZZLE_NONE);
    make_map(enc, &maps.qkv, d_in[1], 1344, 448, 64, 112, CU_TENSOR_MAP_SWIZZLE_128B);
    make_map(enc, &maps.wo, d_in[3], 448, 448, 64, 112, CU_TENSOR_MAP_SWIZZLE_128B);
    make_map(enc, &maps.wg, d_in[5], 1792, 448, 64, 112, CU_TENSOR_MAP_SWIZZLE_128B);
    make_map(enc, &maps.wu, d_in[6], 1792, 448, 64, 112, CU_TENSOR_MAP_SWIZZLE_128B);
    make_map(enc, &maps.wg32, d_in[5], 1792, 448, 32, 112, CU_TENSOR_MAP_SWIZZLE_64B);
    make_map(enc, &maps.wu32, d_in[6], 1792, 448, 32, 112, CU_TENSOR_MAP_SWIZZLE_64B);
    make_map(enc, &maps.wd, d_in[7], 448, 1792, 64, 112, CU_TENSOR_MAP_SWIZZLE_128B);
    fused_kernel<<<128, 384, SMEM_BYTES>>>(scratch, (const __nv_bfloat16*)d_in[0], (const __nv_bfloat16*)d_in[2], 7, (const __nv_bfloat16*)d_in[5],
                                           (const __nv_bfloat16*)d_in[6], (const __nv_bfloat16*)d_in[7], maps);
}
```

```cpp
#include <cuda_runtime.h>
#include <cuda.h>
#include <cuda_bf16.h>
#include <stdint.h>
#include <type_traits>

#define MC 0
#define PPF 2
#define GE 0
#define ACAN 0
#define SPLIT0 1
#define OT 2
#define F2PP 0
#define PPK 2
#define QE 1
#define OST 1
#define GB 1
#define B3T 6
#define PP

namespace {

constexpr uint32_t STAGE = 28672, HALF = 14336;
constexpr int NST = 5;
constexpr uint32_t OFF_H = NST * STAGE;
constexpr uint32_t OFF_KVB = OFF_H + 2 * STAGE;
constexpr uint32_t OFF_WPHI = OFF_KVB + 16384;
constexpr uint32_t OFF_XR = OFF_WPHI + 7168;
constexpr uint32_t OFF_BAR = OFF_XR + 6144;
constexpr uint32_t SMEM_BYTES = OFF_BAR + 256 + 1536;
constexpr int B_EMPTY = NST, B_RECV = 2 * NST, B_RECV2 = B_RECV + 2, B_PACK = B_RECV2 + 2, B_GAT = B_PACK + 1, B_ACK = B_GAT + 8, B_ACK2 = B_ACK + 2, B_COUNT = B_ACK2 + 2;

constexpr int PACK = 14;

struct Maps { CUtensorMap x, qkv, wo, wg, wu, wg32, wu32, wd, out; };

}

constexpr int PLANE = 16 * 2 * 8 * 512;
struct Scratch {
    uint4 ex[6 * PLANE];
    uint4 kv1[8 * 16 * 16 * 32];
    uint4 kv2[8 * 512];
    uint32_t c1[8 * 8 * 16 * 32];
    uint32_t cw[8 * 32];
    uint4 wp[8 * 32 * (HALF / 16)];
};
__device__ __align__(1024) Scratch g_scratch;
#define g_ex (sc->ex)
#define g_kv1 (sc->kv1)
#define g_kv2 (sc->kv2)
#define g_c1 (sc->c1)
#define g_cw (sc->cw)
#define g_wp (sc->wp)
#define STAMP(i)
#define GSTAMP(i)
#define PDUMP()
#define ASTAMP(i)

namespace {

__device__ __forceinline__ int fresh_tid() { int t; asm volatile("mov.u32 %0, %%tid.x;" : "=r"(t)); return t; }
template <int N> __device__ __forceinline__ void kill(uint32_t* v) {
#pragma unroll
    for (int i = 0; i < N; i++) v[i] = 0;
}
template <int N> __device__ __forceinline__ void kill(float* v) {
#pragma unroll
    for (int i = 0; i < N; i++) v[i] = 0.f;
}
__device__ __forceinline__ uint32_t s2u(const void* p) { return (uint32_t)__cvta_generic_to_shared(p); }
__device__ __forceinline__ void mbar_init(uint32_t a, uint32_t c) { asm volatile("mbarrier.init.shared::cta.b64 [%0], %1;" ::"r"(a), "r"(c) : "memory"); }
__device__ __forceinline__ void mbar_expect_tx(uint32_t a, uint32_t b) { asm volatile("mbarrier.arrive.expect_tx.shared::cta.b64 _, [%0], %1;" ::"r"(a), "r"(b) : "memory"); }
__device__ __forceinline__ void mbar_arrive(uint32_t a) { asm volatile("mbarrier.arrive.shared::cta.b64 _, [%0];" ::"r"(a) : "memory"); }
#define GIVE_UP(id) "trap;\n"
#define SPIN_MAX "0x400000"
#define SPIN_TAIL(id) "add.u32 n, n, 1;\n setp.lt.u32 p, n, " SPIN_MAX ";\n @p bra.uni LP;\n" GIVE_UP(id) " DN:\n }"
__device__ __forceinline__ void mbar_wait(uint32_t a, uint32_t ph) {
    asm volatile("{ .reg .pred p; .reg .b32 n; mov.u32 n, 0;\n LP:\n"
                 "mbarrier.try_wait.parity.shared::cta.b64 p, [%0], %1;\n @p bra DN;\n"
                 "add.u32 n, n, 1;\n setp.lt.u32 p, n, " SPIN_MAX ";\n @p bra LP;\n"
                 GIVE_UP("")
                 " DN:\n }" ::"r"(a), "r"(ph) : "memory");
}
#define ELECT "{ .reg .pred e; elect.sync _|e, 0xffffffff; @e "
__device__ __forceinline__ void tma2d(uint32_t dst, const CUtensorMap* m, int c0, int c1, uint32_t bar) {
    asm volatile(ELECT "cp.async.bulk.tensor.2d.shared::cluster.global.mbarrier::complete_tx::bytes [%0], [%1, {%3, %4}], [%2]; }" ::"r"(dst), "l"(m), "r"(bar), "r"(c0), "r"(c1) : "memory");
}
__device__ __forceinline__ void tma3x(uint32_t dst, const CUtensorMap* m, int row, uint32_t bar) {
    asm volatile(ELECT "cp.async.bulk.tensor.3d.shared::cluster.global.mbarrier::complete_tx::bytes [%0], [%1, {0, %3, 0}], [%2]; }" ::"r"(dst), "l"(m), "r"(bar), "r"(row) : "memory");
}
template <int OFF>
__device__ __forceinline__ void ld_pkt(uint32_t* v, const uint4* p) {
    asm volatile("{ .reg .b128 t; ld.relaxed.gpu.global.b128 t, [%4+%5]; mov.b128 {%0,%1,%2,%3}, t; }" : "=r"(v[0]), "=r"(v[1]), "=r"(v[2]), "=r"(v[3]) : "l"(p), "n"(OFF * 16) : "memory");
}
template <int OFF>
__device__ __forceinline__ void st_pkt(uint4* p, uint32_t a, uint32_t b, uint32_t c, uint32_t d) {
    asm volatile("{ .reg .b128 t; mov.b128 t, {%1,%2,%3,%4}; st.relaxed.gpu.global.b128 [%0+%5], t; }" ::"l"(p), "r"(a), "r"(b), "r"(c), "r"(d), "n"(OFF * 16) : "memory");
}
__device__ __forceinline__ uint32_t pack2(float lo, float hi) {
    uint32_t r;
    asm("cvt.rn.bf16x2.f32 %0, %1, %2;" : "=r"(r) : "f"(hi), "f"(lo));
    return r;
}
__device__ __forceinline__ float bf_lo(uint32_t w) { return __uint_as_float(w << 16); }
__device__ __forceinline__ float bf_hi(uint32_t w) { return __uint_as_float(w & 0xffff0000u); }
__device__ __forceinline__ uint32_t settag(uint32_t w, uint32_t tag) { return (w & ~1u) | tag; }
__device__ __forceinline__ float ex2(float x) { float y; asm("ex2.approx.ftz.f32 %0, %1;" : "=f"(y) : "f"(x)); return y; }
__device__ __forceinline__ float rcp(float x) { float y; asm("rcp.approx.ftz.f32 %0, %1;" : "=f"(y) : "f"(x)); return y; }
__device__ __forceinline__ float tanh_hw(float x) { float y; asm("tanh.approx.f32 %0, %1;" : "=f"(y) : "f"(x)); return y; }
__device__ __forceinline__ void stsm4(uint32_t addr, uint32_t a, uint32_t b, uint32_t c, uint32_t d) {
    asm volatile("stmatrix.sync.aligned.m8n8.x4.shared.b16 [%0], {%1,%2,%3,%4};" ::"r"(addr), "r"(a), "r"(b), "r"(c), "r"(d) : "memory");
}
__device__ __forceinline__ void fence_async() { asm volatile("fence.proxy.async.shared::cta;" ::: "memory"); }
__device__ __forceinline__ void bar_sync(int id, int n) { asm volatile("bar.sync %0, %1;" ::"r"(id), "r"(n) : "memory"); }
__device__ __forceinline__ void bar_arrive(int id, int n) { asm volatile("bar.arrive %0, %1;" ::"r"(id), "r"(n) : "memory"); }
__device__ __forceinline__ void wg_fence() { asm volatile("wgmma.fence.sync.aligned;" ::: "memory"); }
__device__ __forceinline__ void wg_commit() { asm volatile("wgmma.commit_group.sync.aligned;" ::: "memory"); }
template <int N> __device__ __forceinline__ void wg_wait() { asm volatile("wgmma.wait_group.sync.aligned %0;" ::"n"(N) : "memory"); }

constexpr uint32_t SB0 = 1024;
__host__ __device__ constexpr uint32_t dlo(uint32_t off, uint32_t lbo) { return ((SB0 + off) >> 4) | ((lbo >> 4) << 16); }
__host__ __device__ constexpr uint32_t dhi(uint32_t sbo, uint32_t sw) { return (sbo >> 4) | (sw << 30); }
__device__ __forceinline__ uint64_t dbase(uint32_t lo, uint32_t hi) { uint64_t d; asm volatile("mov.b64 %0, {%1, %2};" : "=l"(d) : "r"(lo), "r"(hi)); return d; }
#define BASE128(off, lbo, adj) dbase(dlo(off, lbo) + (adj), dhi(1024, 1))
#define BASE64(off, lbo, adj) dbase(dlo(off, lbo) + (adj), dhi(512, 2))

#define ACC4(d, o) "+f"(d[o]), "+f"(d[o + 1]), "+f"(d[o + 2]), "+f"(d[o + 3])
#define ACC28(d) ACC4(d, 0), ACC4(d, 4), ACC4(d, 8), ACC4(d, 12), ACC4(d, 16), ACC4(d, 20), ACC4(d, 24)
#define ACC32(d, o) ACC4(d, o), ACC4(d, o + 4), ACC4(d, o + 8), ACC4(d, o + 12), ACC4(d, o + 16), ACC4(d, o + 20), ACC4(d, o + 24), ACC4(d, o + 28)

template <int TB, uint64_t D>
__device__ __forceinline__ void mma_rs56(float* d, uint32_t a0, uint32_t a1, uint32_t a2, uint32_t a3, int sd, uint64_t base) {
    asm volatile("{ .reg .pred p; .reg .b64 db; setp.ne.b32 p, %32, 0; add.u64 db, %33, %34;\n"
                 "wgmma.mma_async.sync.aligned.m64n56k16.f32.bf16.bf16 "
                 "{%0,%1,%2,%3,%4,%5,%6,%7,%8,%9,%10,%11,%12,%13,%14,%15,%16,%17,%18,%19,%20,%21,%22,%23,%24,%25,%26,%27}, "
                 "{%28,%29,%30,%31}, db, p, 1, 1, %35; }\n"
                 : ACC28(d)
                 : "r"(a0), "r"(a1), "r"(a2), "r"(a3), "r"(sd), "l"(base), "n"(D), "n"(TB));
}
template <int TB, uint64_t D>
__device__ __forceinline__ void mma_rs64(float* d, uint32_t a0, uint32_t a1, uint32_t a2, uint32_t a3, int sd, uint64_t base) {
    asm volatile("{ .reg .pred p; .reg .b64 db; setp.ne.b32 p, %36, 0; add.u64 db, %37, %38;\n"
                 "wgmma.mma_async.sync.aligned.m64n64k16.f32.bf16.bf16 "
                 "{%0,%1,%2,%3,%4,%5,%6,%7,%8,%9,%10,%11,%12,%13,%14,%15,%16,%17,%18,%19,%20,%21,%22,%23,%24,%25,%26,%27,%28,%29,%30,%31}, "
                 "{%32,%33,%34,%35}, db, p, 1, 1, %39; }\n"
                 : ACC32(d, 0)
                 : "r"(a0), "r"(a1), "r"(a2), "r"(a3), "r"(sd), "l"(base), "n"(D), "n"(TB));
}
template <int TB, uint64_t D>
__device__ __forceinline__ void mma_rs128(float* d, uint32_t a0, uint32_t a1, uint32_t a2, uint32_t a3, int sd, uint64_t base) {
    asm volatile("{ .reg .pred p; .reg .b64 db; setp.ne.b32 p, %68, 0; add.u64 db, %69, %70;\n"
                 "wgmma.mma_async.sync.aligned.m64n128k16.f32.bf16.bf16 "
                 "{%0,%1,%2,%3,%4,%5,%6,%7,%8,%9,%10,%11,%12,%13,%14,%15,%16,%17,%18,%19,%20,%21,%22,%23,%24,%25,%26,%27,%28,%29,%30,%31,%32,%33,%34,%35,%36,%37,%38,%39,%40,%41,%42,%43,%44,%45,%46,%47,%48,%49,%50,%51,%52,%53,%54,%55,%56,%57,%58,%59,%60,%61,%62,%63}, "
                 "{%64,%65,%66,%67}, db, p, 1, 1, %71; }\n"
                 : ACC32(d, 0), ACC32(d, 32)
                 : "r"(a0), "r"(a1), "r"(a2), "r"(a3), "r"(sd), "l"(base), "n"(D), "n"(TB));
}
template <uint64_t DA, uint64_t DB>
__device__ __forceinline__ void mma_ss56_tt(float* d, int sd, uint64_t ba, uint64_t bb) {
    asm volatile("{ .reg .pred p; .reg .b64 da, db; setp.ne.b32 p, %28, 0; add.u64 da, %29, %31; add.u64 db, %30, %32;\n"
                 "wgmma.mma_async.sync.aligned.m64n56k16.f32.bf16.bf16 "
                 "{%0,%1,%2,%3,%4,%5,%6,%7,%8,%9,%10,%11,%12,%13,%14,%15,%16,%17,%18,%19,%20,%21,%22,%23,%24,%25,%26,%27}, "
                 "da, db, p, 1, 1, 1, 1; }\n"
                 : ACC28(d)
                 : "r"(sd), "l"(ba), "l"(bb), "n"(DA), "n"(DB));
}
template <int... I> struct Seq {};
template <class F, int... I> __device__ __forceinline__ void static_for_impl(F&& f, Seq<I...>) { (f(std::integral_constant<int, I>{}), ...); }
#define FOR7(...) static_for_impl([&](auto T_) { constexpr int t = decltype(T_)::value; __VA_ARGS__; }, Seq<0, 1, 2, 3, 4, 5, 6>{})
#define FOR8(...) static_for_impl([&](auto T_) { constexpr int t = decltype(T_)::value; __VA_ARGS__; }, Seq<0, 1, 2, 3, 4, 5, 6, 7>{})
#define FOR14(...) static_for_impl([&](auto T_) { constexpr int t = decltype(T_)::value; __VA_ARGS__; }, Seq<0, 1, 2, 3, 4, 5, 6, 7, 8, 9, 10, 11, 12, 13>{})

__device__ __forceinline__ int kblk(int p, int b) { return b == 0 ? p : b - (b <= p); }
__host__ __device__ constexpr int krow(int t) { return t < 3 ? 16 * t : (t < 6 ? 56 + 16 * (t - 3) : 48); }
#define AQ(A, b, t) ((t) < 3 ? A[2 * (b)][4 * (t)] : (t) < 6 ? A[2 * (b) + 1][4 * ((t) - 3)] : A[2 * (b)][12]), \
                    ((t) < 3 ? A[2 * (b)][4 * (t) + 1] : (t) < 6 ? A[2 * (b) + 1][4 * ((t) - 3) + 1] : A[2 * (b)][13]), \
                    ((t) < 3 ? A[2 * (b)][4 * (t) + 2] : (t) < 6 ? A[2 * (b) + 1][4 * ((t) - 3) + 2] : A[2 * (b) + 1][12]), \
                    ((t) < 3 ? A[2 * (b)][4 * (t) + 3] : (t) < 6 ? A[2 * (b) + 1][4 * ((t) - 3) + 3] : A[2 * (b) + 1][13])
#define D128(off, t) ((uint64_t)(((off) + krow(t) * 128) >> 4) + ((uint64_t)((t) == 6 ? (7168 - 1024) >> 4 : 0) << 32))
#define D64(off, t) ((uint64_t)(((off) + krow(t) * 64) >> 4) + ((uint64_t)((t) == 6 ? (3584 - 512) >> 4 : 0) << 32))

#define PL(k) (((k) - 3) * PLANE)
__device__ __forceinline__ void st_word(uint32_t* p, uint32_t v) { asm volatile("st.relaxed.gpu.global.u32 [%0], %1;" ::"l"(p), "r"(v) : "memory"); }
__device__ __forceinline__ uint32_t ld_word(const uint32_t* p) { uint32_t v; asm volatile("ld.relaxed.gpu.global.u32 %0, [%1];" : "=r"(v) : "l"(p) : "memory"); return v; }
__device__ __forceinline__ void tag_slice(uint32_t* w, uint32_t tag) { w[0] = settag(w[0], tag); w[4] = settag(w[4], tag); w[8] = settag(w[8], tag); w[12] = settag(w[12], tag); }
template <int O>
__device__ __forceinline__ void send_slice(uint4* dst, int lane, const uint32_t* w) {
    st_pkt<O>(dst, w[0], w[1], w[2], w[3]);
    st_pkt<O + 32>(dst, w[4], w[5], w[6], w[7]);
    st_pkt<O + 64>(dst, w[8], w[9], w[10], w[11]);
    asm volatile("{ .reg .b64 t; mov.b64 t, {%1,%2}; st.relaxed.gpu.global.b64 [%0+%3], t; }" ::"l"((char*)dst - lane * 8), "r"(w[12]), "r"(w[13]), "n"(16 * (O + 96)) : "memory");
}
#define RW4(v, o) "+r"(v[o]), "+r"(v[(o) + 1]), "+r"(v[(o) + 2]), "+r"(v[(o) + 3])
#define RW2(v, o) "+r"(v[o]), "+r"(v[(o) + 1])
#define WR4(v, o) "=&r"(v[o]), "=&r"(v[(o) + 1]), "=&r"(v[(o) + 2]), "=&r"(v[(o) + 3])
#define LDP(a, b, c, d, addr, off) "ld.relaxed.gpu.global.b128 q, [" addr "+" off "];\n mov.b128 {" a "," b "," c "," d "}, q;\n"
#define LDH(a, b, addr, off) "ld.relaxed.gpu.global.b64 h, [" addr "+" off "];\n mov.b64 {" a "," b "}, h;\n"
#define VOTE_OK "and.b32 t, t, 1;\n setp.ne.u32 p, t, 0;\n vote.sync.any.pred p, p, 0xffffffff;\n @!p bra.uni DN;\n"
#define CHK(x, tag) "lop3.b32 t, " x ", " tag ", t, 0xBE;\n"
__device__ __forceinline__ void check_cnt(uint32_t v, const uint32_t* p, uint32_t target) {
    asm volatile("{ .reg .pred p; .reg .b32 n, t; mov.u32 n, 0; mov.u32 t, %2;\n LP:\n"
                 "sub.s32 t, t, %1;\n setp.lt.s32 p, t, 0;\n vote.sync.any.pred p, p, 0xffffffff;\n @!p bra.uni DN;\n ld.relaxed.gpu.global.u32 t, [%0];\n" SPIN_TAIL("7")
                 ::"l"(p), "r"(target), "r"(v) : "memory");
}
__device__ __forceinline__ void poll_cnt(const uint32_t* p, uint32_t target) {
    asm volatile("{ .reg .pred p; .reg .b32 n, t; mov.u32 n, 0;\n LP:\n"
                 "ld.relaxed.gpu.global.u32 t, [%0];\n sub.s32 t, t, %1;\n setp.lt.s32 p, t, 0;\n vote.sync.any.pred p, p, 0xffffffff;\n @!p bra.uni DN;\n" SPIN_TAIL("1")
                 ::"l"(p), "r"(target) : "memory");
}
template <int STR>
__device__ __forceinline__ void poll4_kv(uint32_t* v, const uint4* p, uint32_t tag) {
    asm volatile("{ .reg .pred p; .reg .b32 n, t; .reg .b128 q; mov.u32 n, 0;\n LP:\n"
                 LDP("%0", "%1", "%2", "%3", "%16", "0") LDP("%4", "%5", "%6", "%7", "%16", "%18")
                 LDP("%8", "%9", "%10", "%11", "%16", "%19") LDP("%12", "%13", "%14", "%15", "%16", "%20")
                 "xor.b32 t, %0, %17;\n" CHK("%4", "%17") CHK("%8", "%17") CHK("%12", "%17") VOTE_OK SPIN_TAIL("2")
                 : WR4(v, 0), WR4(v, 4), WR4(v, 8), WR4(v, 12)
                 : "l"(p), "r"(tag), "n"(16 * STR), "n"(32 * STR), "n"(48 * STR)
                 : "memory");
}
template <int B>
__device__ __forceinline__ void blk_load(uint32_t (&A)[8][14], const uint4* src, int lane) {
    ld_pkt<0>(&A[2 * B][0], src); ld_pkt<32>(&A[2 * B][4], src); ld_pkt<64>(&A[2 * B][8], src);
    ld_pkt<512>(&A[2 * B + 1][0], src); ld_pkt<544>(&A[2 * B + 1][4], src); ld_pkt<576>(&A[2 * B + 1][8], src);
    asm volatile("{ .reg .b64 h;\n" LDH("%0", "%1", "%4", "1536") LDH("%2", "%3", "%4", "9728") "}"
                 : "=&r"(A[2 * B][12]), "=&r"(A[2 * B][13]), "=&r"(A[2 * B + 1][12]), "=&r"(A[2 * B + 1][13])
                 : "l"((const char*)src - lane * 8) : "memory");
}
template <int B>
__device__ __forceinline__ void blk_check(uint32_t (&A)[8][14], const uint4* src, int lane, uint32_t tag) {
    asm volatile("{ .reg .pred p; .reg .b32 n, t; .reg .b128 q; .reg .b64 h, a8; mov.u32 n, 0;\n LP:\n"
                 "xor.b32 t, %0, %30;\n" CHK("%4", "%30") CHK("%8", "%30") CHK("%12", "%30") CHK("%16", "%30") CHK("%20", "%30") CHK("%24", "%30") CHK("%26", "%30") VOTE_OK
                 LDP("%0", "%1", "%2", "%3", "%28", "0") LDP("%4", "%5", "%6", "%7", "%28", "512") LDP("%8", "%9", "%10", "%11", "%28", "1024")
                 LDP("%12", "%13", "%14", "%15", "%28", "8192") LDP("%16", "%17", "%18", "%19", "%28", "8704") LDP("%20", "%21", "%22", "%23", "%28", "9216")
                 "mad.wide.s32 a8, %29, -8, %28;\n" LDH("%24", "%25", "a8", "1536") LDH("%26", "%27", "a8", "9728") SPIN_TAIL("3")
                 "\n and.b32 %0, %0, -2; and.b32 %4, %4, -2; and.b32 %8, %8, -2; and.b32 %12, %12, -2; and.b32 %16, %16, -2; and.b32 %20, %20, -2; and.b32 %24, %24, -2; and.b32 %26, %26, -2;"
                 : RW4(A[2 * B], 0), RW4(A[2 * B], 4), RW4(A[2 * B], 8), RW4(A[2 * B + 1], 0), RW4(A[2 * B + 1], 4), RW4(A[2 * B + 1], 8),
                   RW2(A[2 * B], 12), RW2(A[2 * B + 1], 12)
                 : "l"(src), "r"(lane), "r"(tag)
                 : "memory");
}
__device__ __forceinline__ void st_async4(uint32_t a, uint32_t x, uint32_t y, uint32_t z, uint32_t w, uint32_t bar) {
    asm volatile("st.async.weak.shared::cluster.mbarrier::complete_tx::bytes.v4.b32 [%0], {%1,%2,%3,%4}, [%5];" ::"r"(a), "r"(x), "r"(y), "r"(z), "r"(w), "r"(bar) : "memory");
}
__device__ __forceinline__ uint32_t mapa(uint32_t a, uint32_t cta) { uint32_t r; asm("mapa.shared::cluster.u32 %0, %1, %2;" : "=r"(r) : "r"(a), "r"(cta)); return r; }
__device__ __forceinline__ void stat_load(uint32_t* v, const uint4* p) { ld_pkt<0>(v, p); ld_pkt<512>(v + 4, p); }
__device__ __forceinline__ void stat_check(uint32_t* v, const uint4* p, uint32_t tag) {
    asm volatile("{ .reg .pred p; .reg .b32 n, t; .reg .b128 q; mov.u32 n, 0;\n LP:\n"
                 "xor.b32 t, %3, %9;\n" CHK("%7", "%9") VOTE_OK
                 LDP("%0", "%1", "%2", "%3", "%8", "0") LDP("%4", "%5", "%6", "%7", "%8", "8192") SPIN_TAIL("4")
                 : RW4(v, 0), RW4(v, 4) : "l"(p), "r"(tag) : "memory");
}
__device__ __forceinline__ uint32_t x_bits(const uint32_t* X) {
    uint32_t r;
    asm volatile("{ .reg .b32 a, b; prmt.b32 a, %1, %2, 0x0040; prmt.b32 b, %3, %4, 0x0040; prmt.b32 %0, a, b, 0x5410; }" : "=r"(r) : "r"(X[0]), "r"(X[4]), "r"(X[8]), "r"(X[12]));
    return r;
}
template <int O>
__device__ __forceinline__ void slice_load(uint32_t* v, const uint4* p, int lane) {
    ld_pkt<O>(v, p); ld_pkt<O + 32>(v + 4, p); ld_pkt<O + 64>(v + 8, p);
    asm volatile("{ .reg .b64 h;\n" LDH("%0", "%1", "%2", "%3") "}" : "=r"(v[12]), "=r"(v[13]) : "l"((const char*)p - lane * 8), "n"(16 * (O + 96)) : "memory");
}
template <int O>
__device__ __forceinline__ void slice_check(uint32_t* v, const uint4* p, int lane, uint32_t tag) {
    asm volatile("{ .reg .pred p; .reg .b32 n, t; .reg .b128 q; .reg .b64 h; mov.u32 n, 0;\n LP:\n"
                 "xor.b32 t, %0, %16;\n" CHK("%4", "%16") CHK("%8", "%16") CHK("%12", "%16") VOTE_OK
                 LDP("%0", "%1", "%2", "%3", "%14", "%17") LDP("%4", "%5", "%6", "%7", "%14", "%18") LDP("%8", "%9", "%10", "%11", "%14", "%19")
                 LDH("%12", "%13", "%15", "%20") SPIN_TAIL("5")
                 : RW4(v, 0), RW4(v, 4), RW4(v, 8), RW2(v, 12)
                 : "l"(p), "l"((const char*)p - lane * 8), "r"(tag), "n"(16 * O), "n"(16 * (O + 32)), "n"(16 * (O + 64)), "n"(16 * (O + 96))
                 : "memory");
}
__device__ __forceinline__ void x_fix(uint32_t* X, uint32_t bits) {
    X[0] = __byte_perm(X[0], bits, 0x3214); X[4] = __byte_perm(X[4], bits, 0x3215); X[8] = __byte_perm(X[8], bits, 0x3216); X[12] = __byte_perm(X[12], bits, 0x3217);
}
__device__ __forceinline__ void sts4(uint32_t a, uint32_t x, uint32_t y, uint32_t z, uint32_t w) {
    asm volatile("st.shared.v4.u32 [%0], {%1,%2,%3,%4};" ::"r"(a), "r"(x), "r"(y), "r"(z), "r"(w) : "memory");
}
__device__ __forceinline__ void lds4(uint32_t* v, uint32_t a) {
    asm volatile("ld.shared.v4.u32 {%0,%1,%2,%3}, [%4];" : "=r"(v[0]), "=r"(v[1]), "=r"(v[2]), "=r"(v[3]) : "r"(a) : "memory");
}
struct LnCoef { uint32_t hi, lo, sh; };
__device__ __forceinline__ LnCoef ln_coef(float sum, float sq) {
    sum += __shfl_xor_sync(0xffffffffu, sum, 1); sq += __shfl_xor_sync(0xffffffffu, sq, 1);
    sum += __shfl_xor_sync(0xffffffffu, sum, 2); sq += __shfl_xor_sync(0xffffffffu, sq, 2);
    const float mean = sum * (1.f / 448.f);
    const float var = fmaxf(fmaf(-mean, mean, sq * (1.f / 448.f)), 0.f);
    const float sc = rsqrtf(var + 1e-5f);
    LnCoef r;
    r.hi = pack2(sc, sc);
    const float lo = sc - bf_lo(r.hi), sh = -mean * sc;
    r.lo = pack2(lo, lo);
    r.sh = pack2(sh, sh);
    return r;
}
template <int B>
__device__ __forceinline__ void normalize(uint32_t (&A)[8][14], const LnCoef& c0, const LnCoef& c1) {
#pragma unroll
    for (int s = 2 * B; s < 2 * B + 2; s++)
#pragma unroll
        for (int i = 0; i < 14; i++) {
            const LnCoef& k = (i & 1) ? c1 : c0;
            asm("{ .reg .b32 t; fma.rn.bf16x2 t, %0, %2, %3; fma.rn.bf16x2 %0, %0, %1, t; }" : "+r"(A[s][i]) : "r"(k.hi), "r"(k.lo), "r"(k.sh));
        }
}
__device__ __forceinline__ void slice_stats(const uint32_t* w, float* st) {
    float a = 0.f, b = 0.f, p = 0.f, q = 0.f;
#pragma unroll
    for (int i = 0; i < 7; i++) {
        const float e0 = bf_lo(w[2 * i]), e1 = bf_hi(w[2 * i]), e2 = bf_lo(w[2 * i + 1]), e3 = bf_hi(w[2 * i + 1]);
        a += e0 + e1; b += e2 + e3;
        p = fmaf(e0, e0, p); p = fmaf(e1, e1, p); q = fmaf(e2, e2, q); q = fmaf(e3, e3, q);
    }
    a += __shfl_xor_sync(0xffffffffu, a, 1); p += __shfl_xor_sync(0xffffffffu, p, 1); b += __shfl_xor_sync(0xffffffffu, b, 1); q += __shfl_xor_sync(0xffffffffu, q, 1);
    a += __shfl_xor_sync(0xffffffffu, a, 2); p += __shfl_xor_sync(0xffffffffu, p, 2); b += __shfl_xor_sync(0xffffffffu, b, 2); q += __shfl_xor_sync(0xffffffffu, q, 2);
    st[0] = a; st[1] = p; st[2] = b; st[3] = q;
}
__device__ __forceinline__ void dual_softmax(const float* p, uint32_t* out) {
    constexpr float L = 1.4426950408889634f;
#pragma unroll
    for (int r = 0; r < 2; r++) {
        float mx = fmaxf(p[2 * r], p[2 * r + 1]), mn = fminf(p[2 * r], p[2 * r + 1]);
#pragma unroll
        for (int i = 1; i < 7; i++) {
            mx = fmaxf(mx, fmaxf(p[4 * i + 2 * r], p[4 * i + 2 * r + 1]));
            mn = fminf(mn, fminf(p[4 * i + 2 * r], p[4 * i + 2 * r + 1]));
        }
        mx = fmaxf(mx, __shfl_xor_sync(0xffffffffu, mx, 1));
        mn = fminf(mn, __shfl_xor_sync(0xffffffffu, mn, 1));
        const float bx = -mx * L, bn = mn * L;
        float ep[14], en[14], sp = 0.f, sn = 0.f;
#pragma unroll
        for (int i = 0; i < 14; i++) {
            const float v = p[4 * (i >> 1) + 2 * r + (i & 1)];
            ep[i] = ex2(fmaf(v, L, bx));
            en[i] = ex2(fmaf(v, -L, bn));
            sp += ep[i]; sn += en[i];
        }
        sp += __shfl_xor_sync(0xffffffffu, sp, 1);
        sn += __shfl_xor_sync(0xffffffffu, sn, 1);
        const float ip = rcp(sp), in = rcp(sn);
#pragma unroll
        for (int i = 0; i < 7; i++) {
            out[4 * i + r] = pack2(ep[2 * i] * ip, ep[2 * i + 1] * ip);
            out[4 * i + 2 + r] = pack2(en[2 * i] * in, en[2 * i + 1] * in);
        }
    }
}
__device__ __forceinline__ float geglu(float g, float u) {
    const float t = tanh_hw(g * fmaf(g * g, 0.7978845608028654f * 0.044715f, 0.7978845608028654f));
    const float gu = g * u;
    return fmaf(t, gu, gu);
}
__device__ __forceinline__ void phi_gemm(const float* t, float* p) {
    uint32_t w[14];
#pragma unroll
    for (int i = 0; i < 14; i++) w[i] = pack2(t[2 * i], t[2 * i + 1]);
    const uint64_t db = BASE128(OFF_WPHI, 16, 0);
    wg_fence();
    mma_rs56<0, 0>(p, w[0], w[1], w[2], w[3], 0, db);
    mma_rs56<0, 2>(p, w[4], w[5], w[6], w[7], 1, db);
    mma_rs56<0, 4>(p, w[8], w[9], w[10], w[11], 1, db);
    mma_rs56<0, 6>(p, w[12], w[13], 0u, 0u, 1, db);
    wg_commit();
    wg_wait<0>();
}

}

#define BAR(i) (bars + 8 * (i))
#define R_WAIT() mbar_wait(BAR(slot), ph)
#define WSUM(i)
#define R_ADJ (slot * (STAGE >> 4))
#define R_NEXT() do { eb2 = eb1; eb1 = BAR(B_EMPTY + slot); if (++slot == NST) { slot = 0; ph ^= 1; } } while (0)
#define R_RELEASE(k) do { if (lane == 0) mbar_arrive((k) == 1 ? eb1 : eb2); } while (0)
#define PUSH_BEGIN() do { mbar_wait(BAR(B_ACK + wgi), ackph); ackph ^= 1; } while (0)
#define PUSH_ACK() do { __syncwarp(); if (lane == 0) asm volatile("mbarrier.arrive.shared::cluster.b64 _, [%0];" ::"r"(mapa(BAR(B_ACK + wgi), hr ^ 1)) : "memory"); } while (0)

__global__ void __cluster_dims__(2, 1, 1) __launch_bounds__(384, 1)
fused_kernel(Scratch* const sc, const __nv_bfloat16* __restrict__ x_in, const __nv_bfloat16* __restrict__ w_phi, const int trips,
             const __nv_bfloat16* __restrict__ wg, const __nv_bfloat16* __restrict__ wu, const __nv_bfloat16* __restrict__ wd,
             const __grid_constant__ Maps maps) {
    extern __shared__ __align__(1024) unsigned char smem_raw[];
    const uint32_t sb = s2u(smem_raw);
    const uint32_t bars = sb + OFF_BAR;
    const int wgi = __shfl_sync(0xffffffffu, threadIdx.x >> 7, 0);
    const int hr = blockIdx.x & 1, ck = blockIdx.x >> 1;
    const int gp = (ck - 4) & 7, q7 = ((ck - 36) * 37) >> 8;
    const int pr = __shfl_sync(0xffffffffu, ck < 4 ? ck : (ck < 36 ? (ck - 4) >> 3 : q7), 0);
    const int tile = __shfl_sync(0xffffffffu, ck < 4 ? 0 : (ck < 36 ? (gp ? 2 * gp : 1) : 2 * (ck - 36 - 7 * q7) + 3), 0);
    const int sl = 2 * pr + hr;
    STAMP(0);
    GSTAMP(60);
    if (threadIdx.x == 256) {
#pragma unroll
        for (int i = 0; i < NST; i++) mbar_init(BAR(i), 1);
        asm volatile("fence.mbarrier_init.release.cluster;" ::: "memory");
    }
    if (threadIdx.x == 288) {
        if ((sb & 0x3FFFF) != SB0) asm volatile("trap;");
#pragma unroll
        for (int i = NST; i < B_COUNT; i++) mbar_init(BAR(i), i >= B_ACK ? 4 : (i < B_RECV ? 8 : 1));
        asm volatile("fence.mbarrier_init.release.cluster;" ::: "memory");
    }
    __syncwarp();
    asm volatile("barrier.cluster.arrive.relaxed.aligned;" ::: "memory");

    if (wgi == 2) {
        asm volatile("setmaxnreg.dec.sync.aligned.u32 40;");
        const int t128 = fresh_tid() & 127, w = __shfl_sync(0xffffffffu, t128 >> 5, 0), lane = t128 & 31;
        uint32_t e0[2] = {0, 0}, e1[2] = {0, 0}, cw_target = 0;
        if (w == 0) {
#pragma unroll 1
            for (int n = 0; n < NST; n++) {
                const uint32_t dst = sb + n * STAGE, fb = BAR(n);
                asm volatile(ELECT "mbarrier.arrive.expect_tx.shared::cta.b64 _, [%0], %1; }" ::"r"(fb), "r"(n < 2 ? 2 * STAGE : STAGE) : "memory");
                if (n < 2) {
                    tma3x(sb + OFF_H + n * STAGE, &maps.x, tile * 128 + n * 64, fb);
                    tma3x(dst, &maps.x, tile * 128 + n * 64 + 32, fb);
                } else {
                    if (n == 3) mbar_wait(BAR(1), 0);
                    const int ra = 112 * (n - 2);
                    tma2d(dst, &maps.qkv, 448 + 56 * sl, ra, fb);
                    tma2d(dst + HALF, &maps.qkv, 896 + 56 * sl, ra, fb);
                }
            }
            asm volatile("barrier.cluster.wait.aligned;" ::: "memory");
            cw_target = (ld_word(g_cw + sl * 32) & ~15u) + 16;
#pragma unroll 1
            for (int k = 0; k < 2; k++) {
                const int n = t128 + 32 * k;
                int m = n - 2 - (n > PACK);
                const bool packed = m >= 30 ? (m < 38 || m >= 52) : m >= 22;
                if (m >= 30) m -= 30;
                if (n == PACK) m = tile < 8 ? tile : tile + 14;
                const int rot = n < 8 ? 0 : pr;
                const int ra = 112 * kblk(rot, m & 3), rb = 112 * kblk(rot, 2 * m & 3), rc = 112 * kblk(rot, (2 * m + 1) & 3);
                int kind = 0, m0, m1, c0, c1, r0, r1;
                if (m < 4) { m0 = m1 = 1; c0 = 448 + 56 * sl; c1 = c0 + 448; r0 = r1 = ra; }
                else if (m < 8) { m0 = m1 = m < 6 ? 1 : 2; c0 = c1 = 56 * sl; r0 = rb; r1 = rc; }
                else if (m < 20) { m0 = 3; m1 = 4; c0 = c1 = 224 * sl + 32 * hr + 64 * ((m - 8) >> 2); r0 = r1 = ra; }
                else if (m < 22) { kind = 2; m0 = 5; m1 = 6; c0 = c1 = 224 * sl + (hr ? 0 : 192); r0 = rb; r1 = rc; }
                else { m0 = m1 = 7; c0 = c1 = 56 * (2 * ((pr + (m >> 1) - 10) & 3) + hr); r0 = 224 * (sl ^ (m & 1)); r1 = r0 + 112; }
                if (packed) { kind = 1; r0 = sl * 16 + (m < 8 ? m : m - 14); r1 = 0; }
                e0[0] = e0[1]; e1[0] = e1[1];
                e0[1] = kind | (m0 << 2) | (m1 << 6) | (c0 << 10) | (c1 << 21);
                e1[1] = r0 | (r1 << 16);
            }
        } else {
            const int j = t128 - 32;
            asm volatile("barrier.cluster.wait.aligned;" ::: "memory");
            uint2 wv[7];
            const int k = j < 56 ? j : 55, hh = k >= 28;
#pragma unroll
            for (int i = 0; i < 7; i++) wv[i] = __ldg(reinterpret_cast<const uint2*>(w_phi + (sl * 56 + k) * 28) + i);
#pragma unroll 1
            for (int i = j; i < 7168 / 16; i += 96) sts4(sb + OFF_WPHI + i * 16, 0, 0, 0, 0);
            bar_sync(5, 96);
            if (j < 56) {
                uint32_t a4[4];
#pragma unroll
                for (int q = 0; q < 4; q++) a4[q] = sb + OFF_WPHI + (4 * hh + q) * 128 + ((((k >> 3) ^ (4 * hh + q)) & 7) << 4) + (k & 7) * 2;
                FOR14(const uint32_t v = (t & 1) ? wv[t >> 1].y : wv[t >> 1].x;
                      asm volatile("{ .reg .b16 l, h; mov.b32 {l, h}, %2; st.shared.u16 [%0+%3], l; st.shared.u16 [%1+%3], h; }"
                                   ::"r"(a4[t >= 7 ? 2 : 0]), "r"(a4[t >= 7 ? 3 : 1]), "r"(v), "n"((t % 7) * 1024) : "memory"));
            }
            __syncwarp();
            fence_async();
            bar_arrive(1, 224);
            bar_arrive(9, 224);
            if (w == 1) {
                mbar_wait(BAR(2), 0);
                mbar_wait(BAR(2), 1);
                const int b = blockIdx.x;
                asm volatile(ELECT "cp.async.bulk.prefetch.L2.global [%0], %1; }" ::"l"(wg + b * 6272), "r"(12544) : "memory");
                asm volatile(ELECT "cp.async.bulk.prefetch.L2.global [%0], %1; }" ::"l"(wu + b * 6272), "r"(12544) : "memory");
                asm volatile(ELECT "cp.async.bulk.prefetch.L2.global [%0], %1; }" ::"l"(wd + b * 6272), "r"(12544) : "memory");
            }
        }
        uint32_t kseq = ld_word(g_c1 + (sl * 8 * 16 + tile) * 32);
        int slot = 0, ph = 0, n = NST;
#pragma unroll 1
        for (int layer = 0; layer < 3; layer++) {
            if (w == 0) {
                const int nend = layer == 0 ? 11 : (layer == 1 ? 42 : 63);
#pragma unroll 1
                for (; n < nend; n++) {
                const uint32_t w0 = __shfl_sync(0xffffffffu, n < 32 ? e0[0] : e0[1], n & 31), w1 = __shfl_sync(0xffffffffu, n < 32 ? e1[0] : e1[1], n & 31);
                const uint32_t dst = sb + slot * STAGE, fb = BAR(n == PACK ? B_PACK : slot);
                const CUtensorMap* m0 = &maps.x + ((w0 >> 2) & 15);
                const CUtensorMap* m1 = &maps.x + ((w0 >> 6) & 15);
                const int c0 = (w0 >> 10) & 2047, c1 = w0 >> 21, r0 = w1 & 0xffff, r1 = w1 >> 16;
                if (n == 25) {
                    int it = 0;
                    uint32_t v;
                    do { asm volatile("ld.acquire.gpu.global.u32 %0, [%1];" : "=r"(v) : "l"(g_cw + sl * 32) : "memory"); } while ((int)(v - cw_target) < 0 && ++it < 0x400000);
                    asm volatile("fence.proxy.async.global;" ::: "memory");
                    __syncwarp();
                }
                mbar_wait(BAR(B_EMPTY + slot), ph);
                __syncwarp();
                asm volatile(ELECT "mbarrier.arrive.expect_tx.shared::cta.b64 _, [%0], %1; }" ::"r"(fb), "r"(STAGE) : "memory");
                if ((w0 & 3) == 0) {
                    tma2d(dst, m0, c0, r0, fb);
                    tma2d(dst + HALF, m1, c1, r1, fb);
                } else if (w0 & 1) {
                    asm volatile(ELECT "cp.async.bulk.shared::cluster.global.mbarrier::complete_tx::bytes [%0], [%1], %2, [%3]; }"
                                 ::"r"(dst), "l"(reinterpret_cast<const char*>(g_wp) + (size_t)r0 * STAGE), "r"(STAGE), "r"(fb) : "memory");
                } else {
                    tma2d(dst, m0, c0, r0, fb); tma2d(dst + 7168, m0, c0, r1, fb);
                    tma2d(dst + HALF, m1, c0, r0, fb); tma2d(dst + HALF + 7168, m1, c0, r1, fb);
                }
                if (n == PACK) asm volatile(ELECT "mbarrier.arrive.shared::cta.b64 _, [%0]; }" ::"r"(BAR(slot)) : "memory");
                if (++slot == NST) { slot = 0; ph ^= 1; }
                }
            } else if (w == 1 && layer == 1) {
                constexpr int ps = PACK % NST;
                mbar_wait(BAR(B_PACK), 0);
                asm volatile("{ .reg .pred e; elect.sync _|e, 0xffffffff;\n"
                             "@e cp.async.bulk.global.shared::cta.bulk_group [%0], [%1], %2;\n"
                             "@e cp.async.bulk.commit_group;\n"
                             "@e cp.async.bulk.wait_group.read 0;\n"
                             "@e mbarrier.arrive.shared::cta.b64 _, [%3], 8;\n"
                             "@e cp.async.bulk.wait_group 0;\n"
                             "@e fence.proxy.async.global;\n"
                             "@e red.release.gpu.global.add.u32 [%4], 1; }"
                             ::"l"(reinterpret_cast<char*>(g_wp) + (size_t)(sl * 16 + tile) * STAGE), "r"(sb + ps * STAGE), "r"(STAGE), "r"(BAR(B_EMPTY + ps)), "l"(g_cw + sl * 32) : "memory");
                __syncwarp();
            }
            if (layer < 2) {
            const uint32_t tag = layer ^ 1;
            kseq++;
            bar_sync(7, 384);
            ASTAMP(0);
            if (tile < 15) {
                const int sq = lane >> 3, pk = 8 * w + (lane & (tile == 14 ? 3 : 7));
                uint32_t v[16];
                if (layer == 0) poll_cnt(g_c1 + ((sl * 8 + (w >> 1) * 4 + (tile >> 2)) * 16 + (lane & 15)) * 32, kseq);
                ASTAMP(1);
                poll4_kv<32>(v, g_kv1 + ((sl * 16 + tile) * 16 + 4 * sq) * 32 + pk, tag);
#pragma unroll
                for (int k = 0; k < 4; k++) {
                    float lo = (bf_lo(v[k]) + bf_lo(v[4 + k])) + (bf_lo(v[8 + k]) + bf_lo(v[12 + k]));
                    float hi = (bf_hi(v[k]) + bf_hi(v[4 + k])) + (bf_hi(v[8 + k]) + bf_hi(v[12 + k]));
                    lo += __shfl_xor_sync(0xffffffffu, lo, 8); hi += __shfl_xor_sync(0xffffffffu, hi, 8);
                    lo += __shfl_xor_sync(0xffffffffu, lo, 16); hi += __shfl_xor_sync(0xffffffffu, hi, 16);
                    v[k] = pack2(lo, hi);
                }
                if (sq == 0) st_pkt<0>(g_kv2 + sl * 512 + 32 * tile + pk, settag(v[0], tag), v[1], v[2], v[3]);
            }
            ASTAMP(2);
            {
                const int item = t128 < 112 ? t128 : 112 + (t128 & 3), d = item >> 1;
                const int cc = t128 < 112 ? 2 * (d >= 28) + (item & 1) : item - 112;
                const int r = t128 < 112 ? d : 56 + (cc >> 1) + 2 * ((t128 - 112) >> 2);
                uint32_t ra = sb + OFF_KVB + r * 128 + 4 * cc, rx = (r & 7) << 4;
                asm volatile("" : "+r"(ra), "+r"(rx));
                FOR14(asm volatile("st.shared.u32 [%0+%2], %1;" ::"r"((ra ^ 8) + (((t & 7) << 4) ^ rx)), "r"(0), "n"((t >> 3) * 8192) : "memory"));
                uint32_t v[16];
                asm volatile("" : "+r"(ra), "+r"(rx));
                poll4_kv<8>(v, g_kv2 + sl * 512 + (item >> 3) * 32 + (item & 7), tag);
                FOR14(asm volatile("st.shared.u32 [%0+%2], %1;" ::"r"(ra + (((t & 7) << 4) ^ rx)), "r"(v[t < 7 ? t : t + 1]), "n"((t >> 3) * 8192) : "memory"));
                fence_async();
            }
            bar_arrive(3, 384);
            ASTAMP(3);
            }
        }
    } else {
        asm volatile("setmaxnreg.inc.sync.aligned.u32 232;");
        int lane = fresh_tid() & 31;
#define g (lane >> 2)
#define c (lane & 3)
#define t128 (w * 32 + lane)
        const int wu = __shfl_sync(0xffffffffu, fresh_tid() >> 5, 0), w = wu & 3;
        const uint32_t xoff = __shfl_sync(0xffffffffu, (3 * PLANE + ((tile * 2 + wgi) * 8) * 512 + w * 128) * 16, 0);
        char* xu = reinterpret_cast<char*>(g_ex) + xoff;
#define FRESH() asm volatile("" : "+l"(xu), "+r"(lane))
#define xp0 (reinterpret_cast<uint4*>(xu) + lane)
        const uint32_t hbuf = sb + OFF_H + wgi * STAGE;
        uint32_t slot = 0, ph = 0, eb1 = 0, eb2 = 0, ackph = 0, rcvph = 0, gatph = 0, swp = 0;
        uint32_t ppid = 6;
#define cx(s) (reinterpret_cast<uint32_t*>(reinterpret_cast<uint4*>(xu) + PL(1) + 112 + (s) * 512))
#define stp (reinterpret_cast<uint4*>(xu) + g + PL(0) + 112)
        uint32_t seq = ld_word(cx(sl));
        uint32_t kseq = ld_word(g_c1 + ((sl * 8 + wu) * 16 + tile) * 32);
        uint32_t stag = ld_word(reinterpret_cast<const uint32_t*>(stp + sl * 512) + 3) & 1;
        asm volatile("barrier.cluster.wait.aligned;" ::: "memory");
        STAMP(1);
        uint32_t X[14];
        const uint32_t x0row = (w < 2 ? hbuf : sb + wgi * STAGE) + ((w & 1) * 16 + (lane & 15)) * 128;
        mbar_wait(BAR(wgi), 0);
        STAMP(51);
#pragma unroll
        for (int j = 0; j < 4; j++) {
            const int G = 7 * sl + min(2 * j + (lane >> 4), 6);
            uint32_t q2, q3;
            asm volatile("ldmatrix.sync.aligned.m8n8.x4.shared.b16 {%0,%1,%2,%3}, [%4];" : "=r"(X[4 * j]), "=r"(X[4 * j + 1]), "=r"(q2), "=r"(q3)
                         : "r"(x0row + (G >> 3) * 4096 + (((G ^ lane) & 7) << 4)) : "memory");
            if (j < 3) { X[(4 * j + 2) % 14] = q2; X[(4 * j + 3) % 14] = q3; }
        }
#define PUSH_SLICE(W)                                                                          \
    {                                                                                          \
        if (t128 == 0) mbar_expect_tx(BAR(B_RECV + wgi), 7168);                                \
        PUSH_BEGIN();                                                                          \
        const uint32_t ra = mapa(hbuf + 24576 + t128 * 16, hr ^ 1), rb = mapa(sb + OFF_XR + wgi * 3072, hr ^ 1), rbar = mapa(BAR(B_RECV + wgi), hr ^ 1); \
        st_async4(ra, W[0], W[1], W[2], W[3], rbar);                                           \
        st_async4(ra + 2048, W[4], W[5], W[6], W[7], rbar);                                    \
        st_async4(rb + t128 * 16, W[8], W[9], W[10], W[11], rbar);                             \
        asm volatile("st.async.weak.shared::cluster.mbarrier::complete_tx::bytes.v2.b32 [%0], {%1,%2}, [%3];" ::"r"(rb + 2048 + t128 * 8), "r"(W[12]), "r"(W[13]), "r"(rbar) : "memory"); \
    }
#define PULL_SLICE(W)                                                                          \
    {                                                                                          \
        uint32_t t0, t1;                                                                       \
        mbar_wait(BAR(B_RECV + wgi), rcvph);                                                   \
        rcvph ^= 1;                                                                            \
        lds4(&A[1][0], hbuf + 24576 + t128 * 16);                                              \
        lds4(&A[1][4], hbuf + 26624 + t128 * 16);                                              \
        lds4(&A[1][8], sb + OFF_XR + wgi * 3072 + t128 * 16);                                  \
        asm volatile("ld.shared.v2.u32 {%0,%1}, [%2];" : "=r"(t0), "=r"(t1) : "r"(sb + OFF_XR + wgi * 3072 + 2048 + t128 * 8) : "memory"); \
        _Pragma("unroll") for (int i = 0; i < 12; i++) A[0][i] = (i & 3) ? W[i] : W[i] & ~1u;  \
        A[1][0] &= ~1u; A[1][4] &= ~1u; A[1][8] &= ~1u;                                        \
        A[0][12] = (hr ? t0 : W[12]) & ~1u; A[0][13] = hr ? t1 : W[13];                        \
        A[1][12] = (hr ? W[12] : t0) & ~1u; A[1][13] = hr ? W[13] : t1;                        \
        asm volatile("" : RW4(A[0], 0), RW4(A[0], 4), RW4(A[0], 8), RW2(A[0], 12), RW4(A[1], 0), RW4(A[1], 4), RW4(A[1], 8), RW2(A[1], 12)); \
        swp = hr * 448;                                                                        \
    }
#define SWB(b, t, db, sh) ((b) == 0 && (t) < 6 ? ((t) < 3 ? db##p : db##m) : db)
#define DECL_DB(b, MK, lbo, sh) const uint64_t db = MK(0, lbo, R_ADJ), dbp = (b) == 0 ? MK(0, lbo, R_ADJ + (swp >> (sh))) : db, dbm = (b) == 0 ? MK(0, lbo, R_ADJ - (swp >> (sh))) : db;
#define EARLY 1
#define EARLYK 1
#define PPB 2
#define PP_WAIT() if (wgi == 1) { bar_sync(ppid, 256); ppid ^= 14; }
#define PP_GO() if (wgi == 0) { bar_arrive(ppid, 256); ppid ^= 14; }
#define GAT_ISSUE(base)                                                                        \
    {                                                                                          \
        const char* gs = xu + ((base) + kblk(pr, GB) * 1024) * 16; \
        const uint32_t gd = hbuf + w * 3584, gb = BAR(B_GAT + wu);                     \
        asm volatile("{ .reg .pred e; elect.sync _|e, 0xffffffff;\n"                           \
                     "@e mbarrier.arrive.expect_tx.shared::cta.b64 _, [%2], 3584;\n"           \
                     "@e cp.async.bulk.shared::cluster.global.mbarrier::complete_tx::bytes [%0], [%1], 1792, [%2];\n" \
                     "@e cp.async.bulk.shared::cluster.global.mbarrier::complete_tx::bytes [%0+1792], [%1+8192], 1792, [%2]; }" \
                     ::"r"(gd), "l"(gs), "r"(gb) : "memory");                                  \
        __syncwarp();                                                                          \
    }
#define GAT_FETCH()                                                                            \
    {                                                                                          \
        mbar_wait(BAR(B_GAT + wu), gatph);                                             \
        gatph ^= 1;                                                                            \
        const uint32_t ga = hbuf + w * 3584 + lane * 16;                                       \
        _Pragma("unroll") for (int s2 = 0; s2 < 2; s2++) {                                     \
            lds4(&A[2 * GB + s2][0], ga + s2 * 1792); lds4(&A[2 * GB + s2][4], ga + s2 * 1792 + 512); lds4(&A[2 * GB + s2][8], ga + s2 * 1792 + 1024); \
            asm volatile("ld.shared.v2.u32 {%0,%1}, [%2];" : "=r"(A[2 * GB + s2][12]), "=r"(A[2 * GB + s2][13]) : "r"(ga - lane * 8 + s2 * 1792 + 1536) : "memory"); \
        }                                                                                      \
    }
#define PT 3
#define PREP(b, t, remote)                                                                     \
    if constexpr ((b) < 3 && (t) == PT) {                                                      \
        wg_commit();                                                                           \
        STAMP(80 + 8 * (step & 1) + 2 * (b));                                                  \
        if constexpr ((b) == 0) { if (remote) GAT_FETCH() }                   \
        if (remote) blk_check<((b) + 1) & 3>(A, BLK(xsrc, (b) + 1), lane, xtag);               \
        STAMP(81 + 8 * (step & 1) + 2 * (b));                                                  \
        if constexpr ((b) == 0) { if (remote) blk_load<3>(A, BLK(xsrc, 3), lane); } \
        normalize<((b) + 1) & 3>(A, k0, k1);                                                   \
        asm volatile("" : RW4(A[(2 * (b) + 2) & 7], 0), RW4(A[(2 * (b) + 2) & 7], 4), RW4(A[(2 * (b) + 2) & 7], 8), RW2(A[(2 * (b) + 2) & 7], 12), \
                          RW4(A[(2 * (b) + 3) & 7], 0), RW4(A[(2 * (b) + 3) & 7], 4), RW4(A[(2 * (b) + 3) & 7], 8), RW2(A[(2 * (b) + 3) & 7], 12)); \
        wg_fence();                                                                            \
    }                                                                                          \
    if constexpr ((b) == 3 && ((t) == 0 || (t) == 6)) { STAMP(86 + 8 * (step & 1) + (t) / 6); }
#define X0_BLOCK(b)                                                                            \
    { const int rr = lane & 7, hi = lane >> 4;                                                 \
    const uint32_t rowa = (w < 2 ? hbuf : sb + wgi * STAGE) + ((w & 1) * 16 + (lane & 15)) * 128; \
    FOR7(constexpr int G = 14 * (b) + (t < 3 ? 2 * t : (t < 6 ? 2 * t + 1 : 6));               \
         uint32_t q0, q1, q2, q3;                                                              \
         const uint32_t ad = t < 6 ? rowa + (((((G & 7) + hi) ^ rr) & 7) << 4) + ((G & 7) == 7 ? hi * 4096 : 0) : rowa + ((G + 7 * hi) >> 3) * 4096 + ((((G + 7 * hi) ^ rr) & 7) << 4); \
         asm volatile("ldmatrix.sync.aligned.m8n8.x4.shared.b16 {%0,%1,%2,%3}, [%4+%5];" : "=r"(q0), "=r"(q1), "=r"(q2), "=r"(q3) \
                      : "r"(ad), "n"(t < 6 ? (G >> 3) * 4096 : 0) : "memory");                 \
         if (t < 3) { A[2 * (b)][4 * t] = q0; A[2 * (b)][4 * t + 1] = q1; A[2 * (b)][4 * t + 2] = q2; A[2 * (b)][4 * t + 3] = q3; } \
         else if (t < 6) { A[2 * (b) + 1][(4 * t - 12) & 15] = q0; A[2 * (b) + 1][((4 * t - 12) & 15) + 1] = q1; A[2 * (b) + 1][((4 * t - 12) & 15) + 2] = q2; A[2 * (b) + 1][((4 * t - 12) & 15) + 3] = q3; } \
         else { A[2 * (b)][12] = q0; A[2 * (b)][13] = q1; A[2 * (b) + 1][12] = q2; A[2 * (b) + 1][13] = q3; }); }
#define BLK(base, b) ((base) + kblk(pr, b) * 1024)

#pragma unroll 1
        for (int step = 0; step < 4; step++) {
            FRESH();
            const uint32_t tag = (step >> 1) ^ 1;
            const int so = (step >> 1) * 24 + (step & 1) * 12;
            (void)so;
            uint32_t A[8][14];
            uint4* const xsrc = xp0 + ((step & 1) ? PL(2) : PL(0));
            const uint32_t xtag = (step & 1) ? tag : ((seq >> 3) & 1) ^ 1;
            uint32_t xbits;
            {
                float st[4];
                slice_stats(X, st);
                stag ^= 1;
                xbits = x_bits(X);
                tag_slice(X, xtag);
                if (step) send_slice<0>(xsrc + sl * 512, lane, X);
                if (c == 0) st_pkt<0>(stp + sl * 512, __float_as_uint(st[0]), __float_as_uint(st[1]), __float_as_uint(st[2]), settag(__float_as_uint(st[3]), stag));
            }
            STAMP(2 + so);
            uint32_t sv[8];
            if (step == 0) {
                X0_BLOCK(0) X0_BLOCK(1) X0_BLOCK(3)
                mbar_wait(BAR(wgi ^ 1), 0);
                R_NEXT();
                R_NEXT();
                stat_load(sv, stp + c * 1024);
                stat_check(sv, stp + c * 1024, stag);
                STAMP(52 + step);
            } else {
                kill<14>(A[2]); kill<14>(A[3]); kill<14>(A[6]); kill<14>(A[7]);
                PUSH_SLICE(X)
                stat_load(sv, stp + c * 1024);
                PULL_SLICE(X)
                stat_check(sv, stp + c * 1024, stag);
                STAMP(52 + step);
                GAT_ISSUE((step & 1) ? PL(2) : PL(0))
            }
            LnCoef k0, k1;
            {
                k0 = ln_coef(__uint_as_float(sv[0]) + __uint_as_float(sv[4]), __uint_as_float(sv[1]) + __uint_as_float(sv[5]));
                k1 = ln_coef(__uint_as_float(sv[2]) + __uint_as_float(sv[6]), __uint_as_float(sv[3] & ~1u) + __uint_as_float(sv[7] & ~1u));
            }
            if (step) {
                blk_load<2>(A, BLK(xsrc, 2) + ((k0.hi & k1.hi) == 0xffffffffu), lane);
            } else {
                X0_BLOCK(2)
                R_RELEASE(2);
            }
            STAMP(3 + so);
            GSTAMP(76 + step);

            if ((step & 1) == 0) {
                float tq[28];
                {
                    float av[28];
#define KV_BLOCK(b)                                                                           \
    if (GB == 2 && (b) == 1 && step) GAT_FETCH()                                                         \
    if ((b) == 2) PUSH_ACK();                                                                 \
    if (QE && (b) == 1) R_RELEASE(2);                                                         \
    if (QE && (b) == 2) { wg_wait<2>(); R_RELEASE(2); }                                       \
    R_WAIT();                                                                                 \
    if ((b) == PPK) { PP_WAIT() }                                                             \
    { DECL_DB(b, BASE128, 16, 0)                                                              \
    wg_fence();                                                                               \
    FOR7(mma_rs56<1, D128(0, t)>(tq, AQ(A, b, t), (b) + t > 0, SWB(b, t, db, 0));             \
         mma_rs56<1, D128(HALF, t)>(av, AQ(A, b, t), (b) + t > 0, SWB(b, t, db, 0));          \
         PREP(b, t, step)); }                                                                 \
    wg_commit();                                                                              \
    if ((b) == 3 && PPK < 4) { PP_GO() }                                                      \
    R_NEXT();
                    normalize<0>(A, k0, k1);
                    KV_BLOCK(0) KV_BLOCK(1) KV_BLOCK(2) KV_BLOCK(3)
                    wg_wait<0>();
                    if (lane < (QE ? 3 : NST)) mbar_arrive(BAR(B_EMPTY + (slot + NST - 1 - lane) % NST));
                    STAMP(4 + so);
                    WSUM(80 + 7 * (step >> 1));
                    const int m = lane >> 3, rr = lane & 7;
                    const uint32_t rowa = hbuf + 16384 + (w * 16 + rr + 8 * (m & 1)) * 128;
                    const uint32_t one = c == 0 ? 0x00003f80u : 0u;
                    if (step == 0) { bar_sync(wgi ? 9 : 1, 224); }
#pragma unroll
                    for (int j = 0; j < 4; j++) {
                        const uint32_t a = rowa + (((2 * j + (m >> 1)) ^ rr) << 4);
                        if (j < 3) stsm4(a, pack2(av[8 * j], av[8 * j + 1]), pack2(av[8 * j + 2], av[8 * j + 3]), pack2(av[8 * j + 4], av[8 * j + 5]), pack2(av[8 * j + 6], av[8 * j + 7]));
                        else stsm4(a, pack2(av[24], av[25]), pack2(av[26], av[27]), one, one);
                    }
                }
                uint32_t PH[28];
                int it = 1;
#pragma unroll 1
                do {
                    float pp[28];
                    phi_gemm(tq, pp);
                    dual_softmax(pp, PH);
                    if (((trips >> (it + 1)) & 1) == 0) continue;
                    {
                        const int m = lane >> 3, rr = lane & 7;
                        const uint32_t rowa = hbuf + (w * 16 + rr + 8 * (m & 1)) * 128;
#pragma unroll
                        for (int j = 0; j < 7; j++) {
                            const int cg = 2 * j + (m >> 1), hi = cg >= 7;
                            stsm4(rowa + hi * 8192 + (((cg - 7 * hi) ^ rr) << 4), PH[4 * j], PH[4 * j + 1], PH[4 * j + 2], PH[4 * j + 3]);
                        }
                    }
                    fence_async();
                    STAMP(5 + so);
#define Q_STAGE(b0)                                                                           \
    R_WAIT();                                                                                 \
    { DECL_DB(b0, BASE128, 16, 0)                                                             \
    wg_fence();                                                                               \
    FOR7(mma_rs56<1, D128(0, t)>(tq, AQ(A, b0, t), (b0) + t > 0, SWB(b0, t, db, 0)));         \
    FOR7(mma_rs56<1, D128(HALF, t)>(tq, AQ(A, (b0) + 1, t), 1, db)); }                        \
    wg_commit();                                                                              \
    R_NEXT();
                    if (QE && wgi == 0) { kill<28>(tq); Q_STAGE(0) Q_STAGE(2) wg_wait<1>(); R_RELEASE(2); wg_wait<0>(); R_RELEASE(1); }
                    bar_sync(2, 256);
                    float kv[28];
                    const uint64_t da = BASE128(OFF_H + 16384, 16, 0), dbk = BASE128(OFF_H, 16, wgi * 512);
                    wg_fence();
                    FOR8(constexpr uint64_t o = ((t >> 2) * STAGE + (t & 3) * 2048) >> 4; mma_ss56_tt<o, o>(kv, t > 0, da, dbk));
                    wg_commit();
                    wg_wait<0>();
#pragma unroll
                    for (int hf = 0; hf < 2; hf++) {
                        const int d = 16 * w + g + 8 * hf;
                        if ((d < 56 && (d >= 28) == (c >= 2)) || d == 56) {
                            const int item = d < 56 ? 2 * d + (c & 1) : 112 + c;
                            uint4* dst = g_kv1 + ((sl * 16 + (item >> 3)) * 16 + tile) * 32 + wgi * 16 + (item & 7);
#define KVW(i) pack2(kv[4 * (i) + 2 * hf], kv[4 * (i) + 2 * hf + 1])
                            st_pkt<0>(dst, settag(KVW(0), tag), KVW(1), KVW(2), KVW(3));
                            st_pkt<8>(dst, settag(KVW(4), tag), KVW(5), KVW(6), 0u);
                        }
                    }
                    __syncwarp();
                    kseq++;
                    if (lane == 0) st_word(g_c1 + ((sl * 8 + wu) * 16 + tile) * 32, kseq);
                    bar_arrive(7, 384);
                    STAMP(6 + so);
                    if (!QE || wgi == 1) { kill<28>(tq); Q_STAGE(0) Q_STAGE(2) wg_wait<1>(); R_RELEASE(2); wg_wait<0>(); R_RELEASE(1); }
                    STAMP(7 + so);
                    kill<28>(PH);
                } while (((trips >> (++it)) & 1));
                STAMP(8 + so);
                FRESH();
                if (step) {
                    slice_load<PL(0)>(X, xp0 + sl * 512, lane);
                } else {
                    const uint32_t* xp = reinterpret_cast<const uint32_t*>(x_in + (size_t)(tile * 128 + wu * 16 + g) * 448 + 56 * sl + 2 * c);
#pragma unroll
                    for (int i = 0; i < 7; i++) { X[2 * i] = __ldg(xp + 4 * i); X[2 * i + 1] = __ldg(xp + 4 * i + 8 * 224); }
                }
                bar_sync(3, 384);
                STAMP(9 + so);
                const uint4* const osrc = xp0 + PL(1);
                {
                    float nm[32];
                    const uint64_t db = BASE128(OFF_KVB, 16, 0);
                    wg_fence();
                    FOR7(mma_rs64<0, ((t >> 2) * 8192 + (t & 3) * 32) / 16>(nm, PH[4 * t], PH[4 * t + 1], PH[4 * t + 2], PH[4 * t + 3], t > 0, db));
                    wg_commit();
                    wg_wait<0>();
                    const float i00 = rcp(nm[28] + 1e-6f), i01 = rcp(nm[29] + 1e-6f), i10 = rcp(nm[30] + 1e-6f), i11 = rcp(nm[31] + 1e-6f);
                    const float m0 = c >= 2 ? i01 : i00, m1 = c >= 2 ? i11 : i10;
                    uint32_t O[14];
#pragma unroll
                    for (int i = 0; i < 7; i++) {
                        const float f0 = i < 3 ? i00 : (i > 3 ? i01 : m0), f1 = i < 3 ? i10 : (i > 3 ? i11 : m1);
                        O[2 * i] = pack2(nm[4 * i] * f0, nm[4 * i + 1] * f0);
                        O[2 * i + 1] = pack2(nm[4 * i + 2] * f1, nm[4 * i + 3] * f1);
                    }
                    if (OST) { PP_WAIT() }
                    tag_slice(O, tag);
                    send_slice<PL(1)>(xp0 + sl * 512, lane, O);
                    seq++;
                    if (lane == 0) st_word(cx(sl), seq);
                    STAMP(10 + so);
                    PUSH_SLICE(O)
                    if (OST == 1) { PP_GO() }
                    const uint32_t cv = ld_word(cx(lane & 7));
                    PULL_SLICE(O)
                    check_cnt(cv, cx(lane & 7), seq);
                    if (OST == 2) { PP_GO() }
                    STAMP(56 + (step >> 1));
                    GAT_ISSUE(PL(1))
                    blk_load<3 - GB>(A, BLK(osrc, 3 - GB), lane);
                }
                float ao[28];
#define WO_BLOCK(b)                                                                           \
    if ((b) > 0) blk_check<b>(A, BLK(osrc, b), lane, tag);                                    \
    if (((b) & 1) == 0) R_WAIT();                                                             \
    { DECL_DB(b, BASE128, 16, 0)                                                              \
    wg_fence();                                                                               \
    FOR7(mma_rs56<1, D128(((b) & 1) * HALF, t)>(ao, AQ(A, b, t), (b) + t > 0, SWB(b, t, db, 0))); } \
    wg_commit();                                                                              \
    if ((b) & 1) R_NEXT();
                WO_BLOCK(0)
                STAMP(11 + so);
                blk_load<3>(A, BLK(osrc, 3), lane);
                if (GB == 1) GAT_FETCH()
                WO_BLOCK(1)
                if (GB == 2) GAT_FETCH()
                WO_BLOCK(2)
                PUSH_ACK();
                WO_BLOCK(3)
                wg_wait<0>();
                if (EARLY >= 1) R_RELEASE(2);
                if (EARLY >= 2) R_RELEASE(1);
                STAMP(12 + so);
                WSUM(86 + 7 * (step >> 1));
                x_fix(X, xbits);
#pragma unroll
                for (int i = 0; i < 14; i++) X[i] = pack2(bf_lo(X[i]) + ao[2 * i], bf_hi(X[i]) + ao[2 * i + 1]);
            } else {
                uint32_t H[56];
                float ag[64];
#define F1_EPI(dst, ng, ag)                                                                    \
    _Pragma("unroll") for (int i = 0; i < 2 * (ng); i++)                                       \
        (dst)[i] = pack2(geglu(ag[2 * i], ag[4 * (ng) + 2 * i]), geglu(ag[2 * i + 1], ag[4 * (ng) + 2 * i + 1]));
#define H_PUSH(h0, off) st_async4(rem_h + (off), H[h0], H[(h0) + 1], H[(h0) + 2], H[(h0) + 3], mapa(BAR(B_RECV2 + wgi), hr ^ 1));
#define F1_BLOCK(b, first)                                                                     \
    if ((first) && (b) < 2 && (b) >= EARLY) R_RELEASE(2);                                      \
    if (GB == 2 && (first) && (b) == 1) GAT_FETCH()                                                       \
    if ((first) && (b) == 2) PUSH_ACK();                                                       \
    R_WAIT();                                                                                  \
    if ((b) == ((first) ? PPF : PPB)) { PP_WAIT() }                                            \
    { DECL_DB(b, BASE128, HALF, 0)                                                             \
    wg_fence();                                                                                \
    FOR7(mma_rs128<1, D128(0, t)>(ag, AQ(A, b, t), (b) + t > 0, SWB(b, t, db, 0));             \
         if constexpr (first) { PREP(b, t, true) }); }                                         \
    wg_commit();                                                                               \
    if ((b) == 3) { PP_GO() }                                                                  \
    if ((b) > 0) { wg_wait<1>(); R_RELEASE(1); }       \
    R_NEXT();
                normalize<0>(A, k0, k1);
                F1_BLOCK(0, true) F1_BLOCK(1, true) F1_BLOCK(2, true) F1_BLOCK(3, true)
                if (t128 == 0) { mbar_expect_tx(BAR(B_RECV + wgi), 16384); mbar_expect_tx(BAR(B_RECV2 + wgi), 12288); }
                PUSH_BEGIN();
                wg_wait<0>();
                R_RELEASE(1);
                if (step == 1) R_NEXT();
                int p = 0;
#pragma unroll 1
                do {
                    STAMP(68 + p);
                    F1_EPI(H + 32, 8, ag)
                    STAMP(4 + p + so);
                    WSUM(81 + p + 7 * (step >> 1));
                    if (((trips >> (p + 1)) & 1) == 0) continue;
                    {
                        const uint32_t pk = (p ? hbuf + 16384 : sb + OFF_KVB + wgi * 8192) + w * 2048;
#pragma unroll
                        for (int k = 0; k < 4; k++) sts4(pk + k * 512 + lane * 16, H[32 + 4 * k], H[33 + 4 * k], H[34 + 4 * k], H[35 + 4 * k]);
                        fence_async();
                        __syncwarp();
                        asm volatile(ELECT "cp.async.bulk.shared::cluster.shared::cta.mbarrier::complete_tx::bytes [%0], [%1], 2048, [%2]; }"
                                     ::"r"(mapa(hbuf + p * 8192 + w * 2048, hr ^ 1)), "r"(pk), "r"(mapa(BAR(B_RECV + wgi), hr ^ 1)) : "memory");
                    }
                    kill<64>(ag);
                    F1_BLOCK(0, false) F1_BLOCK(1, false) F1_BLOCK(2, false) F1_BLOCK(3, false)
                    wg_wait<0>();
                    R_RELEASE(1);
                    kill<16>(H + 32);
                } while (((trips >> (++p)) & 1));
#pragma unroll
                for (int k = 0; k < 4; k++) lds4(H + 16 + 4 * k, hbuf + 16384 + w * 2048 + k * 512 + lane * 16);
                __syncwarp();
                if (lane == 0) asm volatile("mbarrier.arrive.shared::cluster.b64 _, [%0];" ::"r"(mapa(BAR(B_ACK2 + wgi), hr ^ 1)) : "memory");
                const uint32_t rem_h = mapa(hbuf + w * 2048 + lane * 16, hr ^ 1);
#define F1_LAST(b0)                                                                            \
    R_WAIT();                                                                                  \
    if (b0) { PP_WAIT() }                                                                      \
    { DECL_DB(b0, BASE64, HALF, 1)                                                             \
    wg_fence();                                                                                \
    FOR7(mma_rs64<1, D64(0, t)>(al, AQ(A, b0, t), (b0) + t > 0, SWB(b0, t, db, 1)));           \
    FOR7(mma_rs64<1, D64(7168, t)>(al, AQ(A, (b0) + 1, t), 1, db)); }                          \
    wg_commit();                                                                               \
    if (b0) { PP_GO() }                                                                        \
    R_NEXT();
                float al[32];
                F1_LAST(0)
                mbar_wait(BAR(B_RECV + wgi), rcvph);
                rcvph ^= 1;
                mbar_wait(BAR(B_ACK2 + wgi), step >> 1);
                H_PUSH(32, 16384) H_PUSH(36, 16896)
                F1_LAST(2)
                H_PUSH(40, 17408) H_PUSH(44, 17920)
                wg_wait<1>();
                R_RELEASE(2);
                wg_wait<0>();
                R_RELEASE(1);
                uint32_t HP[56];
#pragma unroll
                for (int k = 0; k < 4; k++) lds4(H + 4 * k, sb + OFF_KVB + wgi * 8192 + w * 2048 + k * 512 + lane * 16);
#pragma unroll
                for (int t = 0; t < 8; t++) lds4(HP + 4 * t, hbuf + (t >> 2) * 8192 + w * 2048 + (t & 3) * 512 + lane * 16);
                F1_EPI(H + 48, 4, al)
                H_PUSH(48, 24576 - w * 1024) H_PUSH(52, 25088 - w * 1024)
                STAMP(7 + so);
                WSUM(84 + 7 * (step >> 1));
                FRESH();
                float acc[28];
                const uint32_t roA = hr ? 256u : 0u, roB = hr ? (uint32_t)-1536 : 0u;
                const uint32_t rpA = hr ? 0u : 256u, rpB = hr ? 0u : (uint32_t)-1536;
                float res[28];
                uint32_t v0[14], v1[14], P[14];
                const uint4* ps = xp0 + sl * 512;
#define F2_OWN_A()                                                                             \
    R_WAIT();                                                                                  \
    d0 = BASE128(0, 16, R_ADJ + roA); d1 = BASE128(0, 16, R_ADJ + roB);                        \
    wg_fence();                                                                                \
    FOR14(if constexpr (t < OT) mma_rs56<1, t * 128>(acc, H[4 * t], H[4 * t + 1], H[4 * t + 2], H[4 * t + 3], t > 0, d0)); \
    wg_commit();
#define F2_OWN_B()                                                                             \
    wg_fence();                                                                                \
    FOR14(if constexpr (t >= OT) mma_rs56<1, t * 128>(acc, H[4 * t], H[4 * t + 1], H[4 * t + 2], H[4 * t + 3], 1, t < 12 ? d0 : d1)); \
    wg_commit();                                                                               \
    R_NEXT();
#define F2_PEER()                                                                              \
    R_WAIT();                                                                                  \
    if (F2PP) { PP_WAIT() }                                                                    \
    d0 = BASE128(0, 16, R_ADJ + rpA); d1 = BASE128(0, 16, R_ADJ + rpB);                        \
    wg_fence();                                                                                \
    FOR14(mma_rs56<1, t * 128>(acc, HP[4 * t], HP[4 * t + 1], HP[4 * t + 2], HP[4 * t + 3], 1, t < 12 ? d0 : d1)); \
    wg_commit();                                                                               \
    if (F2PP) { PP_GO() }                                                                      \
    R_NEXT();
#define F2_TURN(u)                                                                             \
    wg_wait<1>();                                                                              \
    R_RELEASE(2);                                                                              \
    wg_wait<0>();                                                                              \
    R_RELEASE(1);                                                                              \
    _Pragma("unroll") for (int i = 0; i < 14; i++) P[i] = pack2(acc[2 * i], acc[2 * i + 1]);   \
    tag_slice(P, tag);                                                                         \
    asm volatile("" : RW4(P, 0), RW4(P, 4), RW4(P, 8), RW2(P, 12));                            \
    kill<28>(acc);                                                                             \
    F2_OWN_A()                                                                                 \
    if ((u) == 2) { slice_load<PL(3)>(v0, ps, lane); slice_load<PL(4)>(v1, ps, lane); } \
    send_slice<PL(3 + (u))>(xp0 + (2 * ((pr + (u) + 1) & 3) + hr) * 512, lane, P);             \
    seq++;                                                                                     \
    if (lane == 0) st_word(cx(sl), seq);                                                       \
    __syncwarp();                                                                              \
    STAMP(8 + (u) + so);                                                                       \
    F2_OWN_B()
                uint64_t d0, d1;
                F2_OWN_A()
                F2_OWN_B()
                R_WAIT();
                d0 = BASE128(0, 16, R_ADJ + rpA); d1 = BASE128(0, 16, R_ADJ + rpB);
                wg_fence();
                FOR8(mma_rs56<1, t * 128>(acc, HP[4 * t], HP[4 * t + 1], HP[4 * t + 2], HP[4 * t + 3], 1, d0));
                wg_commit();
                mbar_wait(BAR(B_RECV2 + wgi), step >> 1);
#pragma unroll
                for (int k = 0; k < 4; k++) lds4(HP + 32 + 4 * k, hbuf + 16384 + w * 2048 + k * 512 + lane * 16);
                lds4(HP + 48, hbuf + 24576 + w * 1024 + lane * 16);
                lds4(HP + 52, hbuf + 25088 + w * 1024 + lane * 16);
                if (step == 1) PUSH_ACK();
                wg_fence();
                FOR14(if constexpr (t >= 8) mma_rs56<1, t * 128>(acc, HP[4 * t], HP[4 * t + 1], HP[4 * t + 2], HP[4 * t + 3], 1, t < 12 ? d0 : d1));
                wg_commit();
                R_NEXT();
                F2_TURN(0)
                F2_PEER()
                F2_TURN(1)
                F2_PEER()
                F2_TURN(2)
                STAMP(64 + 8 * (step >> 1));
                slice_check<PL(3)>(v0, ps, lane, tag);
                slice_check<PL(4)>(v1, ps, lane, tag);
#pragma unroll
                for (int i = 0; i < 14; i++) { res[2 * i] = bf_lo(v0[i]) + bf_lo(v1[i]); res[2 * i + 1] = bf_hi(v0[i]) + bf_hi(v1[i]); }
                slice_load<PL(2)>(X, ps, lane);
                STAMP(65 + 8 * (step >> 1));
                F2_PEER()
                STAMP(66 + 8 * (step >> 1));
                poll_cnt(cx(2 * ((pr + 1) & 3) + hr), seq);
                STAMP(67 + 8 * (step >> 1));
                slice_load<PL(5)>(v0, ps, lane);
                x_fix(X, xbits);
                slice_check<PL(5)>(v0, ps, lane, tag);
#pragma unroll
                for (int i = 0; i < 14; i++) { res[2 * i] += bf_lo(v0[i]); res[2 * i + 1] += bf_hi(v0[i]); }
                STAMP(11 + so);
                wg_wait<0>();
                if (EARLYK >= 1) R_RELEASE(2);
                STAMP(12 + so);
                WSUM(85 + 7 * (step >> 1));
#pragma unroll
                for (int i = 0; i < 14; i++) X[i] = pack2(fmaf(res[2 * i] + acc[2 * i], 0.5f, bf_lo(X[i])), fmaf(res[2 * i + 1] + acc[2 * i + 1], 0.5f, bf_hi(X[i])));
            }
        }
        {
            const int m = lane >> 3, rr = lane & 7;
            const uint32_t ob = hbuf + w * 2048, rowa = ob + (rr + 8 * (m & 1)) * 112 + (m >> 1) * 16;
#pragma unroll
            for (int j = 0; j < 3; j++) stsm4(rowa + 32 * j, X[4 * j], X[4 * j + 1], X[4 * j + 2], X[4 * j + 3]);
            asm volatile("stmatrix.sync.aligned.m8n8.x2.shared.b16 [%0], {%1,%2};" ::"r"(ob + (rr + 8 * (m & 1)) * 112 + 96), "r"(X[12]), "r"(X[13]) : "memory");
            fence_async();
            __syncwarp();
            if (lane == 0) {
                asm volatile("cp.async.bulk.tensor.2d.global.shared::cta.bulk_group [%0, {%2, %3}], [%1];" ::"l"(&maps.out), "r"(ob), "r"(56 * sl), "r"(tile * 128 + wu * 16) : "memory");
                asm volatile("cp.async.bulk.commit_group;" ::: "memory");
                asm volatile("cp.async.bulk.wait_group.read 0;" ::: "memory");
            }
        }
        STAMP(50);
        GSTAMP(61);
        PDUMP();
    }
}

#undef g
#undef c
#undef t128

typedef CUresult (*EncodeFn)(CUtensorMap*, CUtensorMapDataType, cuuint32_t, void*, const cuuint64_t*, const cuuint64_t*, const cuuint32_t*,
                             const cuuint32_t*, CUtensorMapInterleave, CUtensorMapSwizzle, CUtensorMapL2promotion, CUtensorMapFloatOOBfill);

static void make_map(EncodeFn enc, CUtensorMap* m, const void* p, uint64_t cols, uint64_t rows, uint32_t bc, uint32_t br, CUtensorMapSwizzle sw) {
    cuuint64_t gd[2] = {cols, rows};
    cuuint64_t gs[1] = {cols * 2};
    cuuint32_t bd[2] = {bc, br};
    cuuint32_t es[2] = {1, 1};
    enc(m, CU_TENSOR_MAP_DATA_TYPE_BFLOAT16, 2, const_cast<void*>(p), gd, gs, bd, es, CU_TENSOR_MAP_INTERLEAVE_NONE, sw,
        CU_TENSOR_MAP_L2_PROMOTION_L2_128B, CU_TENSOR_MAP_FLOAT_OOB_FILL_NONE);
}

extern "C" void kernel_launch(void* const* d_in, const int* in_sizes, int n_in, void* d_out, int out_size) {
    (void)in_sizes; (void)n_in; (void)out_size;
    static EncodeFn enc = nullptr;
    static Scratch* scratch = nullptr;
    if (!enc) {
        void* fn = nullptr;
        cudaDriverEntryPointQueryResult qr;
        cudaGetDriverEntryPoint("cuTensorMapEncodeTiled", &fn, cudaEnableDefault, &qr);
        enc = (EncodeFn)fn;
        cudaGetSymbolAddress((void**)&scratch, g_scratch);
        cudaFuncSetAttribute(fused_kernel, cudaFuncAttributeMaxDynamicSharedMemorySize, SMEM_BYTES);
    }
    Maps maps;
    {
        cuuint64_t gd[3] = {64, 2048, 7};
        cuuint64_t gs[2] = {896, 128};
        cuuint32_t bd[3] = {64, 32, 7};
        cuuint32_t es[3] = {1, 1, 1};
        enc(&maps.x, CU_TENSOR_MAP_DATA_TYPE_BFLOAT16, 3, d_in[0], gd, gs, bd, es, CU_TENSOR_MAP_INTERLEAVE_NONE, CU_TENSOR_MAP_SWIZZLE_128B,
            CU_TENSOR_MAP_L2_PROMOTION_L2_128B, CU_TENSOR_MAP_FLOAT_OOB_FILL_NONE);
    }
    make_map(enc, &maps.out, d_out, 448, 2048, 56, 16, CU_TENSOR_MAP_SWIZZLE_NONE);
    make_map(enc, &maps.qkv, d_in[1], 1344, 448, 64, 112, CU_TENSOR_MAP_SWIZZLE_128B);
    make_map(enc, &maps.wo, d_in[3], 448, 448, 64, 112, CU_TENSOR_MAP_SWIZZLE_128B);
    make_map(enc, &maps.wg, d_in[5], 1792, 448, 64, 112, CU_TENSOR_MAP_SWIZZLE_128B);
    make_map(enc, &maps.wu, d_in[6], 1792, 448, 64, 112, CU_TENSOR_MAP_SWIZZLE_128B);
    make_map(enc, &maps.wg32, d_in[5], 1792, 448, 32, 112, CU_TENSOR_MAP_SWIZZLE_64B);
    make_map(enc, &maps.wu32, d_in[6], 1792, 448, 32, 112, CU_TENSOR_MAP_SWIZZLE_64B);
    make_map(enc, &maps.wd, d_in[7], 448, 1792, 64, 112, CU_TENSOR_MAP_SWIZZLE_128B);
    fused_kernel<<<128, 384, SMEM_BYTES>>>(scratch, (const __nv_bfloat16*)d_in[0], (const __nv_bfloat16*)d_in[2], 7, (const __nv_bfloat16*)d_in[5],
                                           (const __nv_bfloat16*)d_in[6], (const __nv_bfloat16*)d_in[7], maps);
}
```

```cpp
#include <cuda_runtime.h>
#include <cuda.h>
#include <cuda_bf16.h>
#include <stdint.h>
#include <type_traits>

#define MC 0
#define PPF 2
#define GE 0
#define B2L 0
#define B3L 0
#define ACAN 0
#define SPLIT0 1
#define OT 2
#define F2PP 0
#define PPK 2
#define QE 1
#define OST 1
#define GB 1
#define B3T 6
#define PP

namespace {

constexpr uint32_t STAGE = 28672, HALF = 14336;
constexpr int NST = 5;
constexpr uint32_t OFF_H = NST * STAGE;
constexpr uint32_t OFF_KVB = OFF_H + 2 * STAGE;
constexpr uint32_t OFF_WPHI = OFF_KVB + 16384;
constexpr uint32_t OFF_XR = OFF_WPHI + 7168;
constexpr uint32_t OFF_BAR = OFF_XR + 6144;
constexpr uint32_t SMEM_BYTES = OFF_BAR + 256 + 1536;
constexpr int B_EMPTY = NST, B_RECV = 2 * NST, B_RECV2 = B_RECV + 2, B_PACK = B_RECV2 + 2, B_GAT = B_PACK + 1, B_ACK = B_GAT + 8, B_ACK2 = B_ACK + 2, B_COUNT = B_ACK2 + 2;

constexpr int PACK = 14;

struct Maps { CUtensorMap x, qkv, wo, wg, wu, wg32, wu32, wd, out; };

}

constexpr int PLANE = 16 * 2 * 8 * 512;
struct Scratch {
    uint4 ex[6 * PLANE];
    uint4 kv1[8 * 16 * 16 * 32];
    uint4 kv2[8 * 512];
    uint32_t c1[8 * 8 * 16 * 32];
    uint32_t cw[8 * 32];
    uint4 wp[8 * 32 * (HALF / 16)];
};
__device__ __align__(1024) Scratch g_scratch;
#define g_ex (sc->ex)
#define g_kv1 (sc->kv1)
#define g_kv2 (sc->kv2)
#define g_c1 (sc->c1)
#define g_cw (sc->cw)
#define g_wp (sc->wp)
#define STAMP(i)
#define GSTAMP(i)
#define PDUMP()
#define ASTAMP(i)

namespace {

__device__ __forceinline__ int fresh_tid() { int t; asm volatile("mov.u32 %0, %%tid.x;" : "=r"(t)); return t; }
template <int N> __device__ __forceinline__ void kill(uint32_t* v) {
#pragma unroll
    for (int i = 0; i < N; i++) v[i] = 0;
}
template <int N> __device__ __forceinline__ void kill(float* v) {
#pragma unroll
    for (int i = 0; i < N; i++) v[i] = 0.f;
}
__device__ __forceinline__ uint32_t s2u(const void* p) { return (uint32_t)__cvta_generic_to_shared(p); }
__device__ __forceinline__ void mbar_init(uint32_t a, uint32_t c) { asm volatile("mbarrier.init.shared::cta.b64 [%0], %1;" ::"r"(a), "r"(c) : "memory"); }
__device__ __forceinline__ void mbar_expect_tx(uint32_t a, uint32_t b) { asm volatile("mbarrier.arrive.expect_tx.shared::cta.b64 _, [%0], %1;" ::"r"(a), "r"(b) : "memory"); }
__device__ __forceinline__ void mbar_arrive(uint32_t a) { asm volatile("mbarrier.arrive.shared::cta.b64 _, [%0];" ::"r"(a) : "memory"); }
#define GIVE_UP(id) "trap;\n"
#define SPIN_MAX "0x400000"
#define SPIN_TAIL(id) "add.u32 n, n, 1;\n setp.lt.u32 p, n, " SPIN_MAX ";\n @p bra.uni LP;\n" GIVE_UP(id) " DN:\n }"
__device__ __forceinline__ void mbar_wait(uint32_t a, uint32_t ph) {
    asm volatile("{ .reg .pred p; .reg .b32 n; mov.u32 n, 0;\n LP:\n"
                 "mbarrier.try_wait.parity.shared::cta.b64 p, [%0], %1;\n @p bra DN;\n"
                 "add.u32 n, n, 1;\n setp.lt.u32 p, n, " SPIN_MAX ";\n @p bra LP;\n"
                 GIVE_UP("")
                 " DN:\n }" ::"r"(a), "r"(ph) : "memory");
}
#define ELECT "{ .reg .pred e; elect.sync _|e, 0xffffffff; @e "
__device__ __forceinline__ void tma2d(uint32_t dst, const CUtensorMap* m, int c0, int c1, uint32_t bar) {
    asm volatile(ELECT "cp.async.bulk.tensor.2d.shared::cluster.global.mbarrier::complete_tx::bytes [%0], [%1, {%3, %4}], [%2]; }" ::"r"(dst), "l"(m), "r"(bar), "r"(c0), "r"(c1) : "memory");
}
__device__ __forceinline__ void tma3x(uint32_t dst, const CUtensorMap* m, int row, uint32_t bar) {
    asm volatile(ELECT "cp.async.bulk.tensor.3d.shared::cluster.global.mbarrier::complete_tx::bytes [%0], [%1, {0, %3, 0}], [%2]; }" ::"r"(dst), "l"(m), "r"(bar), "r"(row) : "memory");
}
template <int OFF>
__device__ __forceinline__ void ld_pkt(uint32_t* v, const uint4* p) {
    asm volatile("{ .reg .b128 t; ld.relaxed.gpu.global.b128 t, [%4+%5]; mov.b128 {%0,%1,%2,%3}, t; }" : "=r"(v[0]), "=r"(v[1]), "=r"(v[2]), "=r"(v[3]) : "l"(p), "n"(OFF * 16) : "memory");
}
template <int OFF>
__device__ __forceinline__ void st_pkt(uint4* p, uint32_t a, uint32_t b, uint32_t c, uint32_t d) {
    asm volatile("{ .reg .b128 t; mov.b128 t, {%1,%2,%3,%4}; st.relaxed.gpu.global.b128 [%0+%5], t; }" ::"l"(p), "r"(a), "r"(b), "r"(c), "r"(d), "n"(OFF * 16) : "memory");
}
__device__ __forceinline__ uint32_t pack2(float lo, float hi) {
    uint32_t r;
    asm("cvt.rn.bf16x2.f32 %0, %1, %2;" : "=r"(r) : "f"(hi), "f"(lo));
    return r;
}
__device__ __forceinline__ float bf_lo(uint32_t w) { return __uint_as_float(w << 16); }
__device__ __forceinline__ float bf_hi(uint32_t w) { return __uint_as_float(w & 0xffff0000u); }
__device__ __forceinline__ uint32_t settag(uint32_t w, uint32_t tag) { return (w & ~1u) | tag; }
__device__ __forceinline__ float ex2(float x) { float y; asm("ex2.approx.ftz.f32 %0, %1;" : "=f"(y) : "f"(x)); return y; }
__device__ __forceinline__ float rcp(float x) { float y; asm("rcp.approx.ftz.f32 %0, %1;" : "=f"(y) : "f"(x)); return y; }
__device__ __forceinline__ float tanh_hw(float x) { float y; asm("tanh.approx.f32 %0, %1;" : "=f"(y) : "f"(x)); return y; }
__device__ __forceinline__ void stsm4(uint32_t addr, uint32_t a, uint32_t b, uint32_t c, uint32_t d) {
    asm volatile("stmatrix.sync.aligned.m8n8.x4.shared.b16 [%0], {%1,%2,%3,%4};" ::"r"(addr), "r"(a), "r"(b), "r"(c), "r"(d) : "memory");
}
__device__ __forceinline__ void fence_async() { asm volatile("fence.proxy.async.shared::cta;" ::: "memory"); }
__device__ __forceinline__ void bar_sync(int id, int n) { asm volatile("bar.sync %0, %1;" ::"r"(id), "r"(n) : "memory"); }
__device__ __forceinline__ void bar_arrive(int id, int n) { asm volatile("bar.arrive %0, %1;" ::"r"(id), "r"(n) : "memory"); }
__device__ __forceinline__ void wg_fence() { asm volatile("wgmma.fence.sync.aligned;" ::: "memory"); }
__device__ __forceinline__ void wg_commit() { asm volatile("wgmma.commit_group.sync.aligned;" ::: "memory"); }
template <int N> __device__ __forceinline__ void wg_wait() { asm volatile("wgmma.wait_group.sync.aligned %0;" ::"n"(N) : "memory"); }

constexpr uint32_t SB0 = 1024;
__host__ __device__ constexpr uint32_t dlo(uint32_t off, uint32_t lbo) { return ((SB0 + off) >> 4) | ((lbo >> 4) << 16); }
__host__ __device__ constexpr uint32_t dhi(uint32_t sbo, uint32_t sw) { return (sbo >> 4) | (sw << 30); }
__device__ __forceinline__ uint64_t dbase(uint32_t lo, uint32_t hi) { uint64_t d; asm volatile("mov.b64 %0, {%1, %2};" : "=l"(d) : "r"(lo), "r"(hi)); return d; }
#define BASE128(off, lbo, adj) dbase(dlo(off, lbo) + (adj), dhi(1024, 1))
#define BASE64(off, lbo, adj) dbase(dlo(off, lbo) + (adj), dhi(512, 2))

#define ACC4(d, o) "+f"(d[o]), "+f"(d[o + 1]), "+f"(d[o + 2]), "+f"(d[o + 3])
#define ACC28(d) ACC4(d, 0), ACC4(d, 4), ACC4(d, 8), ACC4(d, 12), ACC4(d, 16), ACC4(d, 20), ACC4(d, 24)
#define ACC32(d, o) ACC4(d, o), ACC4(d, o + 4), ACC4(d, o + 8), ACC4(d, o + 12), ACC4(d, o + 16), ACC4(d, o + 20), ACC4(d, o + 24), ACC4(d, o + 28)

template <int TB, uint64_t D>
__device__ __forceinline__ void mma_rs56(float* d, uint32_t a0, uint32_t a1, uint32_t a2, uint32_t a3, int sd, uint64_t base) {
    asm volatile("{ .reg .pred p; .reg .b64 db; setp.ne.b32 p, %32, 0; add.u64 db, %33, %34;\n"
                 "wgmma.mma_async.sync.aligned.m64n56k16.f32.bf16.bf16 "
                 "{%0,%1,%2,%3,%4,%5,%6,%7,%8,%9,%10,%11,%12,%13,%14,%15,%16,%17,%18,%19,%20,%21,%22,%23,%24,%25,%26,%27}, "
                 "{%28,%29,%30,%31}, db, p, 1, 1, %35; }\n"
                 : ACC28(d)
                 : "r"(a0), "r"(a1), "r"(a2), "r"(a3), "r"(sd), "l"(base), "n"(D), "n"(TB));
}
template <int TB, uint64_t D>
__device__ __forceinline__ void mma_rs64(float* d, uint32_t a0, uint32_t a1, uint32_t a2, uint32_t a3, int sd, uint64_t base) {
    asm volatile("{ .reg .pred p; .reg .b64 db; setp.ne.b32 p, %36, 0; add.u64 db, %37, %38;\n"
                 "wgmma.mma_async.sync.aligned.m64n64k16.f32.bf16.bf16 "
                 "{%0,%1,%2,%3,%4,%5,%6,%7,%8,%9,%10,%11,%12,%13,%14,%15,%16,%17,%18,%19,%20,%21,%22,%23,%24,%25,%26,%27,%28,%29,%30,%31}, "
                 "{%32,%33,%34,%35}, db, p, 1, 1, %39; }\n"
                 : ACC32(d, 0)
                 : "r"(a0), "r"(a1), "r"(a2), "r"(a3), "r"(sd), "l"(base), "n"(D), "n"(TB));
}
template <int TB, uint64_t D>
__device__ __forceinline__ void mma_rs128(float* d, uint32_t a0, uint32_t a1, uint32_t a2, uint32_t a3, int sd, uint64_t base) {
    asm volatile("{ .reg .pred p; .reg .b64 db; setp.ne.b32 p, %68, 0; add.u64 db, %69, %70;\n"
                 "wgmma.mma_async.sync.aligned.m64n128k16.f32.bf16.bf16 "
                 "{%0,%1,%2,%3,%4,%5,%6,%7,%8,%9,%10,%11,%12,%13,%14,%15,%16,%17,%18,%19,%20,%21,%22,%23,%24,%25,%26,%27,%28,%29,%30,%31,%32,%33,%34,%35,%36,%37,%38,%39,%40,%41,%42,%43,%44,%45,%46,%47,%48,%49,%50,%51,%52,%53,%54,%55,%56,%57,%58,%59,%60,%61,%62,%63}, "
                 "{%64,%65,%66,%67}, db, p, 1, 1, %71; }\n"
                 : ACC32(d, 0), ACC32(d, 32)
                 : "r"(a0), "r"(a1), "r"(a2), "r"(a3), "r"(sd), "l"(base), "n"(D), "n"(TB));
}
template <uint64_t DA, uint64_t DB>
__device__ __forceinline__ void mma_ss56_tt(float* d, int sd, uint64_t ba, uint64_t bb) {
    asm volatile("{ .reg .pred p; .reg .b64 da, db; setp.ne.b32 p, %28, 0; add.u64 da, %29, %31; add.u64 db, %30, %32;\n"
                 "wgmma.mma_async.sync.aligned.m64n56k16.f32.bf16.bf16 "
                 "{%0,%1,%2,%3,%4,%5,%6,%7,%8,%9,%10,%11,%12,%13,%14,%15,%16,%17,%18,%19,%20,%21,%22,%23,%24,%25,%26,%27}, "
                 "da, db, p, 1, 1, 1, 1; }\n"
                 : ACC28(d)
                 : "r"(sd), "l"(ba), "l"(bb), "n"(DA), "n"(DB));
}
template <int... I> struct Seq {};
template <class F, int... I> __device__ __forceinline__ void static_for_impl(F&& f, Seq<I...>) { (f(std::integral_constant<int, I>{}), ...); }
#define FOR7(...) static_for_impl([&](auto T_) { constexpr int t = decltype(T_)::value; __VA_ARGS__; }, Seq<0, 1, 2, 3, 4, 5, 6>{})
#define FOR8(...) static_for_impl([&](auto T_) { constexpr int t = decltype(T_)::value; __VA_ARGS__; }, Seq<0, 1, 2, 3, 4, 5, 6, 7>{})
#define FOR14(...) static_for_impl([&](auto T_) { constexpr int t = decltype(T_)::value; __VA_ARGS__; }, Seq<0, 1, 2, 3, 4, 5, 6, 7, 8, 9, 10, 11, 12, 13>{})

__device__ __forceinline__ int kblk(int p, int b) { return b == 0 ? p : b - (b <= p); }
__host__ __device__ constexpr int krow(int t) { return t < 3 ? 16 * t : (t < 6 ? 56 + 16 * (t - 3) : 48); }
#define AQ(A, b, t) ((t) < 3 ? A[2 * (b)][4 * (t)] : (t) < 6 ? A[2 * (b) + 1][4 * ((t) - 3)] : A[2 * (b)][12]), \
                    ((t) < 3 ? A[2 * (b)][4 * (t) + 1] : (t) < 6 ? A[2 * (b) + 1][4 * ((t) - 3) + 1] : A[2 * (b)][13]), \
                    ((t) < 3 ? A[2 * (b)][4 * (t) + 2] : (t) < 6 ? A[2 * (b) + 1][4 * ((t) - 3) + 2] : A[2 * (b) + 1][12]), \
                    ((t) < 3 ? A[2 * (b)][4 * (t) + 3] : (t) < 6 ? A[2 * (b) + 1][4 * ((t) - 3) + 3] : A[2 * (b) + 1][13])
#define D128(off, t) ((uint64_t)(((off) + krow(t) * 128) >> 4) + ((uint64_t)((t) == 6 ? (7168 - 1024) >> 4 : 0) << 32))
#define D64(off, t) ((uint64_t)(((off) + krow(t) * 64) >> 4) + ((uint64_t)((t) == 6 ? (3584 - 512) >> 4 : 0) << 32))

#define PL(k) (((k) - 3) * PLANE)
__device__ __forceinline__ void st_word(uint32_t* p, uint32_t v) { asm volatile("st.relaxed.gpu.global.u32 [%0], %1;" ::"l"(p), "r"(v) : "memory"); }
__device__ __forceinline__ uint32_t ld_word(const uint32_t* p) { uint32_t v; asm volatile("ld.relaxed.gpu.global.u32 %0, [%1];" : "=r"(v) : "l"(p) : "memory"); return v; }
__device__ __forceinline__ void tag_slice(uint32_t* w, uint32_t tag) { w[0] = settag(w[0], tag); w[4] = settag(w[4], tag); w[8] = settag(w[8], tag); w[12] = settag(w[12], tag); }
template <int O>
__device__ __forceinline__ void send_slice(uint4* dst, int lane, const uint32_t* w) {
    st_pkt<O>(dst, w[0], w[1], w[2], w[3]);
    st_pkt<O + 32>(dst, w[4], w[5], w[6], w[7]);
    st_pkt<O + 64>(dst, w[8], w[9], w[10], w[11]);
    asm volatile("{ .reg .b64 t; mov.b64 t, {%1,%2}; st.relaxed.gpu.global.b64 [%0+%3], t; }" ::"l"((char*)dst - lane * 8), "r"(w[12]), "r"(w[13]), "n"(16 * (O + 96)) : "memory");
}
#define RW4(v, o) "+r"(v[o]), "+r"(v[(o) + 1]), "+r"(v[(o) + 2]), "+r"(v[(o) + 3])
#define RW2(v, o) "+r"(v[o]), "+r"(v[(o) + 1])
#define WR4(v, o) "=&r"(v[o]), "=&r"(v[(o) + 1]), "=&r"(v[(o) + 2]), "=&r"(v[(o) + 3])
#define LDP(a, b, c, d, addr, off) "ld.relaxed.gpu.global.b128 q, [" addr "+" off "];\n mov.b128 {" a "," b "," c "," d "}, q;\n"
#define LDH(a, b, addr, off) "ld.relaxed.gpu.global.b64 h, [" addr "+" off "];\n mov.b64 {" a "," b "}, h;\n"
#define VOTE_OK "and.b32 t, t, 1;\n setp.ne.u32 p, t, 0;\n vote.sync.any.pred p, p, 0xffffffff;\n @!p bra.uni DN;\n"
#define CHK(x, tag) "lop3.b32 t, " x ", " tag ", t, 0xBE;\n"
__device__ __forceinline__ void check_cnt(uint32_t v, const uint32_t* p, uint32_t target) {
    asm volatile("{ .reg .pred p; .reg .b32 n, t; mov.u32 n, 0; mov.u32 t, %2;\n LP:\n"
                 "sub.s32 t, t, %1;\n setp.lt.s32 p, t, 0;\n vote.sync.any.pred p, p, 0xffffffff;\n @!p bra.uni DN;\n ld.relaxed.gpu.global.u32 t, [%0];\n" SPIN_TAIL("7")
                 ::"l"(p), "r"(target), "r"(v) : "memory");
}
__device__ __forceinline__ void poll_cnt(const uint32_t* p, uint32_t target) {
    asm volatile("{ .reg .pred p; .reg .b32 n, t; mov.u32 n, 0;\n LP:\n"
                 "ld.relaxed.gpu.global.u32 t, [%0];\n sub.s32 t, t, %1;\n setp.lt.s32 p, t, 0;\n vote.sync.any.pred p, p, 0xffffffff;\n @!p bra.uni DN;\n" SPIN_TAIL("1")
                 ::"l"(p), "r"(target) : "memory");
}
template <int STR>
__device__ __forceinline__ void poll4_kv(uint32_t* v, const uint4* p, uint32_t tag) {
    asm volatile("{ .reg .pred p; .reg .b32 n, t; .reg .b128 q; mov.u32 n, 0;\n LP:\n"
                 LDP("%0", "%1", "%2", "%3", "%16", "0") LDP("%4", "%5", "%6", "%7", "%16", "%18")
                 LDP("%8", "%9", "%10", "%11", "%16", "%19") LDP("%12", "%13", "%14", "%15", "%16", "%20")
                 "xor.b32 t, %0, %17;\n" CHK("%4", "%17") CHK("%8", "%17") CHK("%12", "%17") VOTE_OK SPIN_TAIL("2")
                 : WR4(v, 0), WR4(v, 4), WR4(v, 8), WR4(v, 12)
                 : "l"(p), "r"(tag), "n"(16 * STR), "n"(32 * STR), "n"(48 * STR)
                 : "memory");
}
template <int B>
__device__ __forceinline__ void blk_load(uint32_t (&A)[8][14], const uint4* src, int lane) {
    ld_pkt<0>(&A[2 * B][0], src); ld_pkt<32>(&A[2 * B][4], src); ld_pkt<64>(&A[2 * B][8], src);
    ld_pkt<512>(&A[2 * B + 1][0], src); ld_pkt<544>(&A[2 * B + 1][4], src); ld_pkt<576>(&A[2 * B + 1][8], src);
    asm volatile("{ .reg .b64 h;\n" LDH("%0", "%1", "%4", "1536") LDH("%2", "%3", "%4", "9728") "}"
                 : "=&r"(A[2 * B][12]), "=&r"(A[2 * B][13]), "=&r"(A[2 * B + 1][12]), "=&r"(A[2 * B + 1][13])
                 : "l"((const char*)src - lane * 8) : "memory");
}
template <int B>
__device__ __forceinline__ void blk_check(uint32_t (&A)[8][14], const uint4* src, int lane, uint32_t tag) {
    asm volatile("{ .reg .pred p; .reg .b32 n, t; .reg .b128 q; .reg .b64 h, a8; mov.u32 n, 0;\n LP:\n"
                 "xor.b32 t, %0, %30;\n" CHK("%4", "%30") CHK("%8", "%30") CHK("%12", "%30") CHK("%16", "%30") CHK("%20", "%30") CHK("%24", "%30") CHK("%26", "%30") VOTE_OK
                 LDP("%0", "%1", "%2", "%3", "%28", "0") LDP("%4", "%5", "%6", "%7", "%28", "512") LDP("%8", "%9", "%10", "%11", "%28", "1024")
                 LDP("%12", "%13", "%14", "%15", "%28", "8192") LDP("%16", "%17", "%18", "%19", "%28", "8704") LDP("%20", "%21", "%22", "%23", "%28", "9216")
                 "mad.wide.s32 a8, %29, -8, %28;\n" LDH("%24", "%25", "a8", "1536") LDH("%26", "%27", "a8", "9728") SPIN_TAIL("3")
                 "\n and.b32 %0, %0, -2; and.b32 %4, %4, -2; and.b32 %8, %8, -2; and.b32 %12, %12, -2; and.b32 %16, %16, -2; and.b32 %20, %20, -2; and.b32 %24, %24, -2; and.b32 %26, %26, -2;"
                 : RW4(A[2 * B], 0), RW4(A[2 * B], 4), RW4(A[2 * B], 8), RW4(A[2 * B + 1], 0), RW4(A[2 * B + 1], 4), RW4(A[2 * B + 1], 8),
                   RW2(A[2 * B], 12), RW2(A[2 * B + 1], 12)
                 : "l"(src), "r"(lane), "r"(tag)
                 : "memory");
}
__device__ __forceinline__ void st_async4(uint32_t a, uint32_t x, uint32_t y, uint32_t z, uint32_t w, uint32_t bar) {
    asm volatile("st.async.weak.shared::cluster.mbarrier::complete_tx::bytes.v4.b32 [%0], {%1,%2,%3,%4}, [%5];" ::"r"(a), "r"(x), "r"(y), "r"(z), "r"(w), "r"(bar) : "memory");
}
__device__ __forceinline__ uint32_t mapa(uint32_t a, uint32_t cta) { uint32_t r; asm("mapa.shared::cluster.u32 %0, %1, %2;" : "=r"(r) : "r"(a), "r"(cta)); return r; }
__device__ __forceinline__ void stat_load(uint32_t* v, const uint4* p) { ld_pkt<0>(v, p); ld_pkt<512>(v + 4, p); }
__device__ __forceinline__ void stat_check(uint32_t* v, const uint4* p, uint32_t tag) {
    asm volatile("{ .reg .pred p; .reg .b32 n, t; .reg .b128 q; mov.u32 n, 0;\n LP:\n"
                 "xor.b32 t, %3, %9;\n" CHK("%7", "%9") VOTE_OK
                 LDP("%0", "%1", "%2", "%3", "%8", "0") LDP("%4", "%5", "%6", "%7", "%8", "8192") SPIN_TAIL("4")
                 : RW4(v, 0), RW4(v, 4) : "l"(p), "r"(tag) : "memory");
}
__device__ __forceinline__ uint32_t x_bits(const uint32_t* X) {
    uint32_t r;
    asm volatile("{ .reg .b32 a, b; prmt.b32 a, %1, %2, 0x0040; prmt.b32 b, %3, %4, 0x0040; prmt.b32 %0, a, b, 0x5410; }" : "=r"(r) : "r"(X[0]), "r"(X[4]), "r"(X[8]), "r"(X[12]));
    return r;
}
template <int O>
__device__ __forceinline__ void slice_load(uint32_t* v, const uint4* p, int lane) {
    ld_pkt<O>(v, p); ld_pkt<O + 32>(v + 4, p); ld_pkt<O + 64>(v + 8, p);
    asm volatile("{ .reg .b64 h;\n" LDH("%0", "%1", "%2", "%3") "}" : "=r"(v[12]), "=r"(v[13]) : "l"((const char*)p - lane * 8), "n"(16 * (O + 96)) : "memory");
}
template <int O>
__device__ __forceinline__ void slice_check(uint32_t* v, const uint4* p, int lane, uint32_t tag) {
    asm volatile("{ .reg .pred p; .reg .b32 n, t; .reg .b128 q; .reg .b64 h; mov.u32 n, 0;\n LP:\n"
                 "xor.b32 t, %0, %16;\n" CHK("%4", "%16") CHK("%8", "%16") CHK("%12", "%16") VOTE_OK
                 LDP("%0", "%1", "%2", "%3", "%14", "%17") LDP("%4", "%5", "%6", "%7", "%14", "%18") LDP("%8", "%9", "%10", "%11", "%14", "%19")
                 LDH("%12", "%13", "%15", "%20") SPIN_TAIL("5")
                 : RW4(v, 0), RW4(v, 4), RW4(v, 8), RW2(v, 12)
                 : "l"(p), "l"((const char*)p - lane * 8), "r"(tag), "n"(16 * O), "n"(16 * (O + 32)), "n"(16 * (O + 64)), "n"(16 * (O + 96))
                 : "memory");
}
__device__ __forceinline__ void x_fix(uint32_t* X, uint32_t bits) {
    X[0] = __byte_perm(X[0], bits, 0x3214); X[4] = __byte_perm(X[4], bits, 0x3215); X[8] = __byte_perm(X[8], bits, 0x3216); X[12] = __byte_perm(X[12], bits, 0x3217);
}
__device__ __forceinline__ void sts4(uint32_t a, uint32_t x, uint32_t y, uint32_t z, uint32_t w) {
    asm volatile("st.shared.v4.u32 [%0], {%1,%2,%3,%4};" ::"r"(a), "r"(x), "r"(y), "r"(z), "r"(w) : "memory");
}
__device__ __forceinline__ void lds4(uint32_t* v, uint32_t a) {
    asm volatile("ld.shared.v4.u32 {%0,%1,%2,%3}, [%4];" : "=r"(v[0]), "=r"(v[1]), "=r"(v[2]), "=r"(v[3]) : "r"(a) : "memory");
}
struct LnCoef { uint32_t hi, lo, sh; };
__device__ __forceinline__ LnCoef ln_coef(float sum, float sq) {
    sum += __shfl_xor_sync(0xffffffffu, sum, 1); sq += __shfl_xor_sync(0xffffffffu, sq, 1);
    sum += __shfl_xor_sync(0xffffffffu, sum, 2); sq += __shfl_xor_sync(0xffffffffu, sq, 2);
    const float mean = sum * (1.f / 448.f);
    const float var = fmaxf(fmaf(-mean, mean, sq * (1.f / 448.f)), 0.f);
    const float sc = rsqrtf(var + 1e-5f);
    LnCoef r;
    r.hi = pack2(sc, sc);
    const float lo = sc - bf_lo(r.hi), sh = -mean * sc;
    r.lo = pack2(lo, lo);
    r.sh = pack2(sh, sh);
    return r;
}
template <int B>
__device__ __forceinline__ void normalize(uint32_t (&A)[8][14], const LnCoef& c0, const LnCoef& c1) {
#pragma unroll
    for (int s = 2 * B; s < 2 * B + 2; s++)
#pragma unroll
        for (int i = 0; i < 14; i++) {
            const LnCoef& k = (i & 1) ? c1 : c0;
            asm("{ .reg .b32 t; fma.rn.bf16x2 t, %0, %2, %3; fma.rn.bf16x2 %0, %0, %1, t; }" : "+r"(A[s][i]) : "r"(k.hi), "r"(k.lo), "r"(k.sh));
        }
}
__device__ __forceinline__ void slice_stats(const uint32_t* w, float* st) {
    float a = 0.f, b = 0.f, p = 0.f, q = 0.f;
#pragma unroll
    for (int i = 0; i < 7; i++) {
        const float e0 = bf_lo(w[2 * i]), e1 = bf_hi(w[2 * i]), e2 = bf_lo(w[2 * i + 1]), e3 = bf_hi(w[2 * i + 1]);
        a += e0 + e1; b += e2 + e3;
        p = fmaf(e0, e0, p); p = fmaf(e1, e1, p); q = fmaf(e2, e2, q); q = fmaf(e3, e3, q);
    }
    a += __shfl_xor_sync(0xffffffffu, a, 1); p += __shfl_xor_sync(0xffffffffu, p, 1); b += __shfl_xor_sync(0xffffffffu, b, 1); q += __shfl_xor_sync(0xffffffffu, q, 1);
    a += __shfl_xor_sync(0xffffffffu, a, 2); p += __shfl_xor_sync(0xffffffffu, p, 2); b += __shfl_xor_sync(0xffffffffu, b, 2); q += __shfl_xor_sync(0xffffffffu, q, 2);
    st[0] = a; st[1] = p; st[2] = b; st[3] = q;
}
__device__ __forceinline__ void dual_softmax(const float* p, uint32_t* out) {
    constexpr float L = 1.4426950408889634f;
#pragma unroll
    for (int r = 0; r < 2; r++) {
        float mx = fmaxf(p[2 * r], p[2 * r + 1]), mn = fminf(p[2 * r], p[2 * r + 1]);
#pragma unroll
        for (int i = 1; i < 7; i++) {
            mx = fmaxf(mx, fmaxf(p[4 * i + 2 * r], p[4 * i + 2 * r + 1]));
            mn = fminf(mn, fminf(p[4 * i + 2 * r], p[4 * i + 2 * r + 1]));
        }
        mx = fmaxf(mx, __shfl_xor_sync(0xffffffffu, mx, 1));
        mn = fminf(mn, __shfl_xor_sync(0xffffffffu, mn, 1));
        const float bx = -mx * L, bn = mn * L;
        float ep[14], en[14], sp = 0.f, sn = 0.f;
#pragma unroll
        for (int i = 0; i < 14; i++) {
            const float v = p[4 * (i >> 1) + 2 * r + (i & 1)];
            ep[i] = ex2(fmaf(v, L, bx));
            en[i] = ex2(fmaf(v, -L, bn));
            sp += ep[i]; sn += en[i];
        }
        sp += __shfl_xor_sync(0xffffffffu, sp, 1);
        sn += __shfl_xor_sync(0xffffffffu, sn, 1);
        const float ip = rcp(sp), in = rcp(sn);
#pragma unroll
        for (int i = 0; i < 7; i++) {
            out[4 * i + r] = pack2(ep[2 * i] * ip, ep[2 * i + 1] * ip);
            out[4 * i + 2 + r] = pack2(en[2 * i] * in, en[2 * i + 1] * in);
        }
    }
}
__device__ __forceinline__ float geglu(float g, float u) {
    const float t = tanh_hw(g * fmaf(g * g, 0.7978845608028654f * 0.044715f, 0.7978845608028654f));
    const float gu = g * u;
    return fmaf(t, gu, gu);
}
__device__ __forceinline__ void phi_gemm(const float* t, float* p) {
    uint32_t w[14];
#pragma unroll
    for (int i = 0; i < 14; i++) w[i] = pack2(t[2 * i], t[2 * i + 1]);
    const uint64_t db = BASE128(OFF_WPHI, 16, 0);
    wg_fence();
    mma_rs56<0, 0>(p, w[0], w[1], w[2], w[3], 0, db);
    mma_rs56<0, 2>(p, w[4], w[5], w[6], w[7], 1, db);
    mma_rs56<0, 4>(p, w[8], w[9], w[10], w[11], 1, db);
    mma_rs56<0, 6>(p, w[12], w[13], 0u, 0u, 1, db);
    wg_commit();
    wg_wait<0>();
}

}

#define BAR(i) (bars + 8 * (i))
#define R_WAIT() mbar_wait(BAR(slot), ph)
#define WSUM(i)
#define R_ADJ (slot * (STAGE >> 4))
#define R_NEXT() do { eb2 = eb1; eb1 = BAR(B_EMPTY + slot); if (++slot == NST) { slot = 0; ph ^= 1; } } while (0)
#define R_RELEASE(k) do { if (lane == 0) mbar_arrive((k) == 1 ? eb1 : eb2); } while (0)
#define PUSH_BEGIN() do { mbar_wait(BAR(B_ACK + wgi), ackph); ackph ^= 1; } while (0)
#define PUSH_ACK() do { __syncwarp(); if (lane == 0) asm volatile("mbarrier.arrive.shared::cluster.b64 _, [%0];" ::"r"(mapa(BAR(B_ACK + wgi), hr ^ 1)) : "memory"); } while (0)

__global__ void __cluster_dims__(2, 1, 1) __launch_bounds__(384, 1)
fused_kernel(Scratch* const sc, const __nv_bfloat16* __restrict__ x_in, const __nv_bfloat16* __restrict__ w_phi, const int trips,
             const __nv_bfloat16* __restrict__ wg, const __nv_bfloat16* __restrict__ wu, const __nv_bfloat16* __restrict__ wd,
             const __grid_constant__ Maps maps) {
    extern __shared__ __align__(1024) unsigned char smem_raw[];
    const uint32_t sb = s2u(smem_raw);
    const uint32_t bars = sb + OFF_BAR;
    const int wgi = __shfl_sync(0xffffffffu, threadIdx.x >> 7, 0);
    const int hr = blockIdx.x & 1, ck = blockIdx.x >> 1;
    const int gp = (ck - 4) & 7, q7 = ((ck - 36) * 37) >> 8;
    const int pr = __shfl_sync(0xffffffffu, ck < 4 ? ck : (ck < 36 ? (ck - 4) >> 3 : q7), 0);
    const int tile = __shfl_sync(0xffffffffu, ck < 4 ? 0 : (ck < 36 ? (gp ? 2 * gp : 1) : 2 * (ck - 36 - 7 * q7) + 3), 0);
    const int sl = 2 * pr + hr;
    STAMP(0);
    GSTAMP(60);
    if (threadIdx.x == 256) {
#pragma unroll
        for (int i = 0; i < NST; i++) mbar_init(BAR(i), 1);
        asm volatile("fence.mbarrier_init.release.cluster;" ::: "memory");
    }
    if (threadIdx.x == 288) {
        if ((sb & 0x3FFFF) != SB0) asm volatile("trap;");
#pragma unroll
        for (int i = NST; i < B_COUNT; i++) mbar_init(BAR(i), i >= B_ACK ? 4 : (i < B_RECV ? 8 : 1));
        asm volatile("fence.mbarrier_init.release.cluster;" ::: "memory");
    }
    __syncwarp();
    asm volatile("barrier.cluster.arrive.relaxed.aligned;" ::: "memory");

    if (wgi == 2) {
        asm volatile("setmaxnreg.dec.sync.aligned.u32 40;");
        const int t128 = fresh_tid() & 127, w = __shfl_sync(0xffffffffu, t128 >> 5, 0), lane = t128 & 31;
        uint32_t e0[2] = {0, 0}, e1[2] = {0, 0}, cw_target = 0;
        if (w == 0) {
#pragma unroll 1
            for (int n = 0; n < NST; n++) {
                const uint32_t dst = sb + n * STAGE, fb = BAR(n);
                asm volatile(ELECT "mbarrier.arrive.expect_tx.shared::cta.b64 _, [%0], %1; }" ::"r"(fb), "r"(n < 2 ? 2 * STAGE : STAGE) : "memory");
                if (n < 2) {
                    tma3x(sb + OFF_H + n * STAGE, &maps.x, tile * 128 + n * 64, fb);
                    tma3x(dst, &maps.x, tile * 128 + n * 64 + 32, fb);
                } else {
                    if (n == 3) mbar_wait(BAR(1), 0);
                    const int ra = 112 * (n - 2);
                    tma2d(dst, &maps.qkv, 448 + 56 * sl, ra, fb);
                    tma2d(dst + HALF, &maps.qkv, 896 + 56 * sl, ra, fb);
                }
            }
            asm volatile("barrier.cluster.wait.aligned;" ::: "memory");
            cw_target = (ld_word(g_cw + sl * 32) & ~15u) + 16;
#pragma unroll 1
            for (int k = 0; k < 2; k++) {
                const int n = t128 + 32 * k;
                int m = n - 2 - (n > PACK);
                const bool packed = m >= 30 ? (m < 38 || m >= 52) : m >= 22;
                if (m >= 30) m -= 30;
                if (n == PACK) m = tile < 8 ? tile : tile + 14;
                const int rot = n < 8 ? 0 : pr;
                const int ra = 112 * kblk(rot, m & 3), rb = 112 * kblk(rot, 2 * m & 3), rc = 112 * kblk(rot, (2 * m + 1) & 3);
                int kind = 0, m0, m1, c0, c1, r0, r1;
                if (m < 4) { m0 = m1 = 1; c0 = 448 + 56 * sl; c1 = c0 + 448; r0 = r1 = ra; }
                else if (m < 8) { m0 = m1 = m < 6 ? 1 : 2; c0 = c1 = 56 * sl; r0 = rb; r1 = rc; }
                else if (m < 20) { m0 = 3; m1 = 4; c0 = c1 = 224 * sl + 32 * hr + 64 * ((m - 8) >> 2); r0 = r1 = ra; }
                else if (m < 22) { kind = 2; m0 = 5; m1 = 6; c0 = c1 = 224 * sl + (hr ? 0 : 192); r0 = rb; r1 = rc; }
                else { m0 = m1 = 7; c0 = c1 = 56 * (2 * ((pr + (m >> 1) - 10) & 3) + hr); r0 = 224 * (sl ^ (m & 1)); r1 = r0 + 112; }
                if (packed) { kind = 1; r0 = sl * 16 + (m < 8 ? m : m - 14); r1 = 0; }
                e0[0] = e0[1]; e1[0] = e1[1];
                e0[1] = kind | (m0 << 2) | (m1 << 6) | (c0 << 10) | (c1 << 21);
                e1[1] = r0 | (r1 << 16);
            }
        } else {
            const int j = t128 - 32;
            asm volatile("barrier.cluster.wait.aligned;" ::: "memory");
            uint2 wv[7];
            const int k = j < 56 ? j : 55, hh = k >= 28;
#pragma unroll
            for (int i = 0; i < 7; i++) wv[i] = __ldg(reinterpret_cast<const uint2*>(w_phi + (sl * 56 + k) * 28) + i);
#pragma unroll 1
            for (int i = j; i < 7168 / 16; i += 96) sts4(sb + OFF_WPHI + i * 16, 0, 0, 0, 0);
            bar_sync(5, 96);
            if (j < 56) {
                uint32_t a4[4];
#pragma unroll
                for (int q = 0; q < 4; q++) a4[q] = sb + OFF_WPHI + (4 * hh + q) * 128 + ((((k >> 3) ^ (4 * hh + q)) & 7) << 4) + (k & 7) * 2;
                FOR14(const uint32_t v = (t & 1) ? wv[t >> 1].y : wv[t >> 1].x;
                      asm volatile("{ .reg .b16 l, h; mov.b32 {l, h}, %2; st.shared.u16 [%0+%3], l; st.shared.u16 [%1+%3], h; }"
                                   ::"r"(a4[t >= 7 ? 2 : 0]), "r"(a4[t >= 7 ? 3 : 1]), "r"(v), "n"((t % 7) * 1024) : "memory"));
            }
            __syncwarp();
            fence_async();
            bar_arrive(1, 224);
            bar_arrive(9, 224);
            if (w == 1) {
                mbar_wait(BAR(2), 0);
                mbar_wait(BAR(2), 1);
                const int b = blockIdx.x;
                asm volatile(ELECT "cp.async.bulk.prefetch.L2.global [%0], %1; }" ::"l"(wg + b * 6272), "r"(12544) : "memory");
                asm volatile(ELECT "cp.async.bulk.prefetch.L2.global [%0], %1; }" ::"l"(wu + b * 6272), "r"(12544) : "memory");
                asm volatile(ELECT "cp.async.bulk.prefetch.L2.global [%0], %1; }" ::"l"(wd + b * 6272), "r"(12544) : "memory");
            }
        }
        uint32_t kseq = ld_word(g_c1 + (sl * 8 * 16 + tile) * 32);
        int slot = 0, ph = 0, n = NST;
#pragma unroll 1
        for (int layer = 0; layer < 3; layer++) {
            if (w == 0) {
                const int nend = layer == 0 ? 11 : (layer == 1 ? 42 : 63);
#pragma unroll 1
                for (; n < nend; n++) {
                const uint32_t w0 = __shfl_sync(0xffffffffu, n < 32 ? e0[0] : e0[1], n & 31), w1 = __shfl_sync(0xffffffffu, n < 32 ? e1[0] : e1[1], n & 31);
                const uint32_t dst = sb + slot * STAGE, fb = BAR(n == PACK ? B_PACK : slot);
                const CUtensorMap* m0 = &maps.x + ((w0 >> 2) & 15);
                const CUtensorMap* m1 = &maps.x + ((w0 >> 6) & 15);
                const int c0 = (w0 >> 10) & 2047, c1 = w0 >> 21, r0 = w1 & 0xffff, r1 = w1 >> 16;
                if (n == 25) {
                    int it = 0;
                    uint32_t v;
                    do { asm volatile("ld.acquire.gpu.global.u32 %0, [%1];" : "=r"(v) : "l"(g_cw + sl * 32) : "memory"); } while ((int)(v - cw_target) < 0 && ++it < 0x400000);
                    asm volatile("fence.proxy.async.global;" ::: "memory");
                    __syncwarp();
                }
                mbar_wait(BAR(B_EMPTY + slot), ph);
                __syncwarp();
                asm volatile(ELECT "mbarrier.arrive.expect_tx.shared::cta.b64 _, [%0], %1; }" ::"r"(fb), "r"(STAGE) : "memory");
                if ((w0 & 3) == 0) {
                    tma2d(dst, m0, c0, r0, fb);
                    tma2d(dst + HALF, m1, c1, r1, fb);
                } else if (w0 & 1) {
                    asm volatile(ELECT "cp.async.bulk.shared::cluster.global.mbarrier::complete_tx::bytes [%0], [%1], %2, [%3]; }"
                                 ::"r"(dst), "l"(reinterpret_cast<const char*>(g_wp) + (size_t)r0 * STAGE), "r"(STAGE), "r"(fb) : "memory");
                } else {
                    tma2d(dst, m0, c0, r0, fb); tma2d(dst + 7168, m0, c0, r1, fb);
                    tma2d(dst + HALF, m1, c0, r0, fb); tma2d(dst + HALF + 7168, m1, c0, r1, fb);
                }
                if (n == PACK) asm volatile(ELECT "mbarrier.arrive.shared::cta.b64 _, [%0]; }" ::"r"(BAR(slot)) : "memory");
                if (++slot == NST) { slot = 0; ph ^= 1; }
                }
            } else if (w == 1 && layer == 1) {
                constexpr int ps = PACK % NST;
                mbar_wait(BAR(B_PACK), 0);
                asm volatile("{ .reg .pred e; elect.sync _|e, 0xffffffff;\n"
                             "@e cp.async.bulk.global.shared::cta.bulk_group [%0], [%1], %2;\n"
                             "@e cp.async.bulk.commit_group;\n"
                             "@e cp.async.bulk.wait_group.read 0;\n"
                             "@e mbarrier.arrive.shared::cta.b64 _, [%3], 8;\n"
                             "@e cp.async.bulk.wait_group 0;\n"
                             "@e fence.proxy.async.global;\n"
                             "@e red.release.gpu.global.add.u32 [%4], 1; }"
                             ::"l"(reinterpret_cast<char*>(g_wp) + (size_t)(sl * 16 + tile) * STAGE), "r"(sb + ps * STAGE), "r"(STAGE), "r"(BAR(B_EMPTY + ps)), "l"(g_cw + sl * 32) : "memory");
                __syncwarp();
            }
            if (layer < 2) {
            const uint32_t tag = layer ^ 1;
            kseq++;
            bar_sync(7, 384);
            ASTAMP(0);
            if (tile < 15) {
                const int sq = lane >> 3, pk = 8 * w + (lane & (tile == 14 ? 3 : 7));
                uint32_t v[16];
                if (layer == 0) poll_cnt(g_c1 + ((sl * 8 + (w >> 1) * 4 + (tile >> 2)) * 16 + (lane & 15)) * 32, kseq);
                ASTAMP(1);
                poll4_kv<32>(v, g_kv1 + ((sl * 16 + tile) * 16 + 4 * sq) * 32 + pk, tag);
#pragma unroll
                for (int k = 0; k < 4; k++) {
                    float lo = (bf_lo(v[k]) + bf_lo(v[4 + k])) + (bf_lo(v[8 + k]) + bf_lo(v[12 + k]));
                    float hi = (bf_hi(v[k]) + bf_hi(v[4 + k])) + (bf_hi(v[8 + k]) + bf_hi(v[12 + k]));
                    lo += __shfl_xor_sync(0xffffffffu, lo, 8); hi += __shfl_xor_sync(0xffffffffu, hi, 8);
                    lo += __shfl_xor_sync(0xffffffffu, lo, 16); hi += __shfl_xor_sync(0xffffffffu, hi, 16);
                    v[k] = pack2(lo, hi);
                }
                if (sq == 0) st_pkt<0>(g_kv2 + sl * 512 + 32 * tile + pk, settag(v[0], tag), v[1], v[2], v[3]);
            }
            ASTAMP(2);
            {
                const int item = t128 < 112 ? t128 : 112 + (t128 & 3), d = item >> 1;
                const int cc = t128 < 112 ? 2 * (d >= 28) + (item & 1) : item - 112;
                const int r = t128 < 112 ? d : 56 + (cc >> 1) + 2 * ((t128 - 112) >> 2);
                uint32_t ra = sb + OFF_KVB + r * 128 + 4 * cc, rx = (r & 7) << 4;
                asm volatile("" : "+r"(ra), "+r"(rx));
                FOR14(asm volatile("st.shared.u32 [%0+%2], %1;" ::"r"((ra ^ 8) + (((t & 7) << 4) ^ rx)), "r"(0), "n"((t >> 3) * 8192) : "memory"));
                uint32_t v[16];
                asm volatile("" : "+r"(ra), "+r"(rx));
                poll4_kv<8>(v, g_kv2 + sl * 512 + (item >> 3) * 32 + (item & 7), tag);
                FOR14(asm volatile("st.shared.u32 [%0+%2], %1;" ::"r"(ra + (((t & 7) << 4) ^ rx)), "r"(v[t < 7 ? t : t + 1]), "n"((t >> 3) * 8192) : "memory"));
                fence_async();
            }
            bar_arrive(3, 384);
            ASTAMP(3);
            }
        }
    } else {
        asm volatile("setmaxnreg.inc.sync.aligned.u32 232;");
        int lane = fresh_tid() & 31;
#define g (lane >> 2)
#define c (lane & 3)
#define t128 (w * 32 + lane)
        const int wu = __shfl_sync(0xffffffffu, fresh_tid() >> 5, 0), w = wu & 3;
        const uint32_t xoff = __shfl_sync(0xffffffffu, (3 * PLANE + ((tile * 2 + wgi) * 8) * 512 + w * 128) * 16, 0);
        char* xu = reinterpret_cast<char*>(g_ex) + xoff;
#define FRESH() asm volatile("" : "+l"(xu), "+r"(lane))
#define xp0 (reinterpret_cast<uint4*>(xu) + lane)
        const uint32_t hbuf = sb + OFF_H + wgi * STAGE;
        uint32_t slot = 0, ph = 0, eb1 = 0, eb2 = 0, ackph = 0, rcvph = 0, gatph = 0, swp = 0;
        uint32_t ppid = 6;
#define cx(s) (reinterpret_cast<uint32_t*>(reinterpret_cast<uint4*>(xu) + PL(1) + 112 + (s) * 512))
#define stp (reinterpret_cast<uint4*>(xu) + g + PL(0) + 112)
        uint32_t seq = ld_word(cx(sl));
        uint32_t kseq = ld_word(g_c1 + ((sl * 8 + wu) * 16 + tile) * 32);
        uint32_t stag = ld_word(reinterpret_cast<const uint32_t*>(stp + sl * 512) + 3) & 1;
        asm volatile("barrier.cluster.wait.aligned;" ::: "memory");
        STAMP(1);
        uint32_t X[14];
        const uint32_t x0row = (w < 2 ? hbuf : sb + wgi * STAGE) + ((w & 1) * 16 + (lane & 15)) * 128;
        mbar_wait(BAR(wgi), 0);
        STAMP(51);
#pragma unroll
        for (int j = 0; j < 4; j++) {
            const int G = 7 * sl + min(2 * j + (lane >> 4), 6);
            uint32_t q2, q3;
            asm volatile("ldmatrix.sync.aligned.m8n8.x4.shared.b16 {%0,%1,%2,%3}, [%4];" : "=r"(X[4 * j]), "=r"(X[4 * j + 1]), "=r"(q2), "=r"(q3)
                         : "r"(x0row + (G >> 3) * 4096 + (((G ^ lane) & 7) << 4)) : "memory");
            if (j < 3) { X[(4 * j + 2) % 14] = q2; X[(4 * j + 3) % 14] = q3; }
        }
#define PUSH_SLICE(W)                                                                          \
    {                                                                                          \
        if (t128 == 0) mbar_expect_tx(BAR(B_RECV + wgi), 7168);                                \
        PUSH_BEGIN();                                                                          \
        const uint32_t ra = mapa(hbuf + 24576 + t128 * 16, hr ^ 1), rb = mapa(sb + OFF_XR + wgi * 3072, hr ^ 1), rbar = mapa(BAR(B_RECV + wgi), hr ^ 1); \
        st_async4(ra, W[0], W[1], W[2], W[3], rbar);                                           \
        st_async4(ra + 2048, W[4], W[5], W[6], W[7], rbar);                                    \
        st_async4(rb + t128 * 16, W[8], W[9], W[10], W[11], rbar);                             \
        asm volatile("st.async.weak.shared::cluster.mbarrier::complete_tx::bytes.v2.b32 [%0], {%1,%2}, [%3];" ::"r"(rb + 2048 + t128 * 8), "r"(W[12]), "r"(W[13]), "r"(rbar) : "memory"); \
    }
#define PULL_SLICE(W)                                                                          \
    {                                                                                          \
        uint32_t t0, t1;                                                                       \
        mbar_wait(BAR(B_RECV + wgi), rcvph);                                                   \
        rcvph ^= 1;                                                                            \
        lds4(&A[1][0], hbuf + 24576 + t128 * 16);                                              \
        lds4(&A[1][4], hbuf + 26624 + t128 * 16);                                              \
        lds4(&A[1][8], sb + OFF_XR + wgi * 3072 + t128 * 16);                                  \
        asm volatile("ld.shared.v2.u32 {%0,%1}, [%2];" : "=r"(t0), "=r"(t1) : "r"(sb + OFF_XR + wgi * 3072 + 2048 + t128 * 8) : "memory"); \
        _Pragma("unroll") for (int i = 0; i < 12; i++) A[0][i] = (i & 3) ? W[i] : W[i] & ~1u;  \
        A[1][0] &= ~1u; A[1][4] &= ~1u; A[1][8] &= ~1u;                                        \
        A[0][12] = (hr ? t0 : W[12]) & ~1u; A[0][13] = hr ? t1 : W[13];                        \
        A[1][12] = (hr ? W[12] : t0) & ~1u; A[1][13] = hr ? W[13] : t1;                        \
        asm volatile("" : RW4(A[0], 0), RW4(A[0], 4), RW4(A[0], 8), RW2(A[0], 12), RW4(A[1], 0), RW4(A[1], 4), RW4(A[1], 8), RW2(A[1], 12)); \
        swp = hr * 448;                                                                        \
    }
#define SWB(b, t, db, sh) ((b) == 0 && (t) < 6 ? ((t) < 3 ? db##p : db##m) : db)
#define DECL_DB(b, MK, lbo, sh) const uint64_t db = MK(0, lbo, R_ADJ), dbp = (b) == 0 ? MK(0, lbo, R_ADJ + (swp >> (sh))) : db, dbm = (b) == 0 ? MK(0, lbo, R_ADJ - (swp >> (sh))) : db;
#define EARLY 1
#define EARLYK 1
#define PPB 2
#define PP_WAIT() if (wgi == 1) { bar_sync(ppid, 256); ppid ^= 14; }
#define PP_GO() if (wgi == 0) { bar_arrive(ppid, 256); ppid ^= 14; }
#define GAT_ISSUE(base)                                                                        \
    {                                                                                          \
        const char* gs = xu + ((base) + kblk(pr, GB) * 1024) * 16; \
        const uint32_t gd = hbuf + w * 3584, gb = BAR(B_GAT + wu);                     \
        asm volatile("{ .reg .pred e; elect.sync _|e, 0xffffffff;\n"                           \
                     "@e mbarrier.arrive.expect_tx.shared::cta.b64 _, [%2], 3584;\n"           \
                     "@e cp.async.bulk.shared::cluster.global.mbarrier::complete_tx::bytes [%0], [%1], 1792, [%2];\n" \
                     "@e cp.async.bulk.shared::cluster.global.mbarrier::complete_tx::bytes [%0+1792], [%1+8192], 1792, [%2]; }" \
                     ::"r"(gd), "l"(gs), "r"(gb) : "memory");                                  \
        __syncwarp();                                                                          \
    }
#define GAT_FETCH()                                                                            \
    {                                                                                          \
        mbar_wait(BAR(B_GAT + wu), gatph);                                             \
        gatph ^= 1;                                                                            \
        const uint32_t ga = hbuf + w * 3584 + lane * 16;                                       \
        _Pragma("unroll") for (int s2 = 0; s2 < 2; s2++) {                                     \
            lds4(&A[2 * GB + s2][0], ga + s2 * 1792); lds4(&A[2 * GB + s2][4], ga + s2 * 1792 + 512); lds4(&A[2 * GB + s2][8], ga + s2 * 1792 + 1024); \
            asm volatile("ld.shared.v2.u32 {%0,%1}, [%2];" : "=r"(A[2 * GB + s2][12]), "=r"(A[2 * GB + s2][13]) : "r"(ga - lane * 8 + s2 * 1792 + 1536) : "memory"); \
        }                                                                                      \
    }
#define PT 3
#define PREP(b, t, remote)                                                                     \
    if constexpr ((b) < 3 && (t) == PT) {                                                      \
        wg_commit();                                                                           \
        STAMP(80 + 8 * (step & 1) + 2 * (b));                                                  \
        if constexpr ((b) == 0 && B2L == 1) { if (remote) blk_load<2>(A, BLK(xsrc, 2), lane); } \
        if constexpr ((b) == 1 && B3L == 1) { if (remote) blk_load<3>(A, BLK(xsrc, 3), lane); } \
        if constexpr ((b) == 0) { if (remote) GAT_FETCH() }                   \
        if (remote) blk_check<((b) + 1) & 3>(A, BLK(xsrc, (b) + 1), lane, xtag);               \
        STAMP(81 + 8 * (step & 1) + 2 * (b));                                                  \
        if constexpr ((b) == 0 && B2L == 2) { if (remote) blk_load<2>(A, BLK(xsrc, 2), lane); } \
        if constexpr ((b) == (B3L == 2) && B3L != 1) { if (remote) blk_load<3>(A, BLK(xsrc, 3), lane); } \
        normalize<((b) + 1) & 3>(A, k0, k1);                                                   \
        asm volatile("" : RW4(A[(2 * (b) + 2) & 7], 0), RW4(A[(2 * (b) + 2) & 7], 4), RW4(A[(2 * (b) + 2) & 7], 8), RW2(A[(2 * (b) + 2) & 7], 12), \
                          RW4(A[(2 * (b) + 3) & 7], 0), RW4(A[(2 * (b) + 3) & 7], 4), RW4(A[(2 * (b) + 3) & 7], 8), RW2(A[(2 * (b) + 3) & 7], 12)); \
        wg_fence();                                                                            \
    }                                                                                          \
    if constexpr ((b) == 3 && ((t) == 0 || (t) == 6)) { STAMP(86 + 8 * (step & 1) + (t) / 6); }
#define X0_BLOCK(b)                                                                            \
    { const int rr = lane & 7, hi = lane >> 4;                                                 \
    const uint32_t rowa = (w < 2 ? hbuf : sb + wgi * STAGE) + ((w & 1) * 16 + (lane & 15)) * 128; \
    FOR7(constexpr int G = 14 * (b) + (t < 3 ? 2 * t : (t < 6 ? 2 * t + 1 : 6));               \
         uint32_t q0, q1, q2, q3;                                                              \
         const uint32_t ad = t < 6 ? rowa + (((((G & 7) + hi) ^ rr) & 7) << 4) + ((G & 7) == 7 ? hi * 4096 : 0) : rowa + ((G + 7 * hi) >> 3) * 4096 + ((((G + 7 * hi) ^ rr) & 7) << 4); \
         asm volatile("ldmatrix.sync.aligned.m8n8.x4.shared.b16 {%0,%1,%2,%3}, [%4+%5];" : "=r"(q0), "=r"(q1), "=r"(q2), "=r"(q3) \
                      : "r"(ad), "n"(t < 6 ? (G >> 3) * 4096 : 0) : "memory");                 \
         if (t < 3) { A[2 * (b)][4 * t] = q0; A[2 * (b)][4 * t + 1] = q1; A[2 * (b)][4 * t + 2] = q2; A[2 * (b)][4 * t + 3] = q3; } \
         else if (t < 6) { A[2 * (b) + 1][(4 * t - 12) & 15] = q0; A[2 * (b) + 1][((4 * t - 12) & 15) + 1] = q1; A[2 * (b) + 1][((4 * t - 12) & 15) + 2] = q2; A[2 * (b) + 1][((4 * t - 12) & 15) + 3] = q3; } \
         else { A[2 * (b)][12] = q0; A[2 * (b)][13] = q1; A[2 * (b) + 1][12] = q2; A[2 * (b) + 1][13] = q3; }); }
#define BLK(base, b) ((base) + kblk(pr, b) * 1024)

#pragma unroll 1
        for (int step = 0; step < 4; step++) {
            FRESH();
            const uint32_t tag = (step >> 1) ^ 1;
            const int so = (step >> 1) * 24 + (step & 1) * 12;
            (void)so;
            uint32_t A[8][14];
            uint4* const xsrc = xp0 + ((step & 1) ? PL(2) : PL(0));
            const uint32_t xtag = (step & 1) ? tag : ((seq >> 3) & 1) ^ 1;
            uint32_t xbits;
            {
                float st[4];
                slice_stats(X, st);
                stag ^= 1;
                xbits = x_bits(X);
                tag_slice(X, xtag);
                if (step) send_slice<0>(xsrc + sl * 512, lane, X);
                if (c == 0) st_pkt<0>(stp + sl * 512, __float_as_uint(st[0]), __float_as_uint(st[1]), __float_as_uint(st[2]), settag(__float_as_uint(st[3]), stag));
            }
            STAMP(2 + so);
            uint32_t sv[8];
            if (step == 0) {
                X0_BLOCK(0) X0_BLOCK(1) X0_BLOCK(3)
                mbar_wait(BAR(wgi ^ 1), 0);
                R_NEXT();
                R_NEXT();
                stat_load(sv, stp + c * 1024);
                stat_check(sv, stp + c * 1024, stag);
                STAMP(52 + step);
            } else {
                kill<14>(A[2]); kill<14>(A[3]); kill<14>(A[6]); kill<14>(A[7]);
                PUSH_SLICE(X)
                stat_load(sv, stp + c * 1024);
                PULL_SLICE(X)
                stat_check(sv, stp + c * 1024, stag);
                STAMP(52 + step);
                GAT_ISSUE((step & 1) ? PL(2) : PL(0))
            }
            LnCoef k0, k1;
            {
                k0 = ln_coef(__uint_as_float(sv[0]) + __uint_as_float(sv[4]), __uint_as_float(sv[1]) + __uint_as_float(sv[5]));
                k1 = ln_coef(__uint_as_float(sv[2]) + __uint_as_float(sv[6]), __uint_as_float(sv[3] & ~1u) + __uint_as_float(sv[7] & ~1u));
            }
            if (step) {
                if (B2L == 0) blk_load<2>(A, BLK(xsrc, 2) + ((k0.hi & k1.hi) == 0xffffffffu), lane);
                else { kill<14>(A[4]); kill<14>(A[5]); }
            } else {
                X0_BLOCK(2)
                R_RELEASE(2);
            }
            STAMP(3 + so);
            GSTAMP(76 + step);

            if ((step & 1) == 0) {
                float tq[28];
                {
                    float av[28];
#define KV_BLOCK(b)                                                                           \
    if (GB == 2 && (b) == 1 && step) GAT_FETCH()                                                         \
    if ((b) == 2) PUSH_ACK();                                                                 \
    if (QE && (b) == 1) R_RELEASE(2);                                                         \
    if (QE && (b) == 2) { wg_wait<2>(); R_RELEASE(2); }                                       \
    R_WAIT();                                                                                 \
    if ((b) == PPK) { PP_WAIT() }                                                             \
    { DECL_DB(b, BASE128, 16, 0)                                                              \
    wg_fence();                                                                               \
    FOR7(mma_rs56<1, D128(0, t)>(tq, AQ(A, b, t), (b) + t > 0, SWB(b, t, db, 0));             \
         mma_rs56<1, D128(HALF, t)>(av, AQ(A, b, t), (b) + t > 0, SWB(b, t, db, 0));          \
         PREP(b, t, step)); }                                                                 \
    wg_commit();                                                                              \
    if ((b) == 3 && PPK < 4) { PP_GO() }                                                      \
    R_NEXT();
                    normalize<0>(A, k0, k1);
                    KV_BLOCK(0) KV_BLOCK(1) KV_BLOCK(2) KV_BLOCK(3)
                    wg_wait<0>();
                    if (lane < (QE ? 3 : NST)) mbar_arrive(BAR(B_EMPTY + (slot + NST - 1 - lane) % NST));
                    STAMP(4 + so);
                    WSUM(80 + 7 * (step >> 1));
                    const int m = lane >> 3, rr = lane & 7;
                    const uint32_t rowa = hbuf + 16384 + (w * 16 + rr + 8 * (m & 1)) * 128;
                    const uint32_t one = c == 0 ? 0x00003f80u : 0u;
                    if (step == 0) { bar_sync(wgi ? 9 : 1, 224); }
#pragma unroll
                    for (int j = 0; j < 4; j++) {
                        const uint32_t a = rowa + (((2 * j + (m >> 1)) ^ rr) << 4);
                        if (j < 3) stsm4(a, pack2(av[8 * j], av[8 * j + 1]), pack2(av[8 * j + 2], av[8 * j + 3]), pack2(av[8 * j + 4], av[8 * j + 5]), pack2(av[8 * j + 6], av[8 * j + 7]));
                        else stsm4(a, pack2(av[24], av[25]), pack2(av[26], av[27]), one, one);
                    }
                }
                uint32_t PH[28];
                int it = 1;
#pragma unroll 1
                do {
                    float pp[28];
                    phi_gemm(tq, pp);
                    dual_softmax(pp, PH);
                    if (((trips >> (it + 1)) & 1) == 0) continue;
                    {
                        const int m = lane >> 3, rr = lane & 7;
                        const uint32_t rowa = hbuf + (w * 16 + rr + 8 * (m & 1)) * 128;
#pragma unroll
                        for (int j = 0; j < 7; j++) {
                            const int cg = 2 * j + (m >> 1), hi = cg >= 7;
                            stsm4(rowa + hi * 8192 + (((cg - 7 * hi) ^ rr) << 4), PH[4 * j], PH[4 * j + 1], PH[4 * j + 2], PH[4 * j + 3]);
                        }
                    }
                    fence_async();
                    STAMP(5 + so);
#define Q_STAGE(b0)                                                                           \
    R_WAIT();                                                                                 \
    { DECL_DB(b0, BASE128, 16, 0)                                                             \
    wg_fence();                                                                               \
    FOR7(mma_rs56<1, D128(0, t)>(tq, AQ(A, b0, t), (b0) + t > 0, SWB(b0, t, db, 0)));         \
    FOR7(mma_rs56<1, D128(HALF, t)>(tq, AQ(A, (b0) + 1, t), 1, db)); }                        \
    wg_commit();                                                                              \
    R_NEXT();
                    if (QE && wgi == 0) { kill<28>(tq); Q_STAGE(0) Q_STAGE(2) wg_wait<1>(); R_RELEASE(2); wg_wait<0>(); R_RELEASE(1); }
                    bar_sync(2, 256);
                    float kv[28];
                    const uint64_t da = BASE128(OFF_H + 16384, 16, 0), dbk = BASE128(OFF_H, 16, wgi * 512);
                    wg_fence();
                    FOR8(constexpr uint64_t o = ((t >> 2) * STAGE + (t & 3) * 2048) >> 4; mma_ss56_tt<o, o>(kv, t > 0, da, dbk));
                    wg_commit();
                    wg_wait<0>();
#pragma unroll
                    for (int hf = 0; hf < 2; hf++) {
                        const int d = 16 * w + g + 8 * hf;
                        if ((d < 56 && (d >= 28) == (c >= 2)) || d == 56) {
                            const int item = d < 56 ? 2 * d + (c & 1) : 112 + c;
                            uint4* dst = g_kv1 + ((sl * 16 + (item >> 3)) * 16 + tile) * 32 + wgi * 16 + (item & 7);
#define KVW(i) pack2(kv[4 * (i) + 2 * hf], kv[4 * (i) + 2 * hf + 1])
                            st_pkt<0>(dst, settag(KVW(0), tag), KVW(1), KVW(2), KVW(3));
                            st_pkt<8>(dst, settag(KVW(4), tag), KVW(5), KVW(6), 0u);
                        }
                    }
                    __syncwarp();
                    kseq++;
                    if (lane == 0) st_word(g_c1 + ((sl * 8 + wu) * 16 + tile) * 32, kseq);
                    bar_arrive(7, 384);
                    STAMP(6 + so);
                    if (!QE || wgi == 1) { kill<28>(tq); Q_STAGE(0) Q_STAGE(2) wg_wait<1>(); R_RELEASE(2); wg_wait<0>(); R_RELEASE(1); }
                    STAMP(7 + so);
                    kill<28>(PH);
                } while (((trips >> (++it)) & 1));
                STAMP(8 + so);
                FRESH();
                if (step) {
                    slice_load<PL(0)>(X, xp0 + sl * 512, lane);
                } else {
                    const uint32_t* xp = reinterpret_cast<const uint32_t*>(x_in + (size_t)(tile * 128 + wu * 16 + g) * 448 + 56 * sl + 2 * c);
#pragma unroll
                    for (int i = 0; i < 7; i++) { X[2 * i] = __ldg(xp + 4 * i); X[2 * i + 1] = __ldg(xp + 4 * i + 8 * 224); }
                }
                bar_sync(3, 384);
                STAMP(9 + so);
                const uint4* const osrc = xp0 + PL(1);
                {
                    float nm[32];
                    const uint64_t db = BASE128(OFF_KVB, 16, 0);
                    wg_fence();
                    FOR7(mma_rs64<0, ((t >> 2) * 8192 + (t & 3) * 32) / 16>(nm, PH[4 * t], PH[4 * t + 1], PH[4 * t + 2], PH[4 * t + 3], t > 0, db));
                    wg_commit();
                    wg_wait<0>();
                    const float i00 = rcp(nm[28] + 1e-6f), i01 = rcp(nm[29] + 1e-6f), i10 = rcp(nm[30] + 1e-6f), i11 = rcp(nm[31] + 1e-6f);
                    const float m0 = c >= 2 ? i01 : i00, m1 = c >= 2 ? i11 : i10;
                    uint32_t O[14];
#pragma unroll
                    for (int i = 0; i < 7; i++) {
                        const float f0 = i < 3 ? i00 : (i > 3 ? i01 : m0), f1 = i < 3 ? i10 : (i > 3 ? i11 : m1);
                        O[2 * i] = pack2(nm[4 * i] * f0, nm[4 * i + 1] * f0);
                        O[2 * i + 1] = pack2(nm[4 * i + 2] * f1, nm[4 * i + 3] * f1);
                    }
                    if (OST) { PP_WAIT() }
                    tag_slice(O, tag);
                    send_slice<PL(1)>(xp0 + sl * 512, lane, O);
                    seq++;
                    if (lane == 0) st_word(cx(sl), seq);
                    STAMP(10 + so);
                    PUSH_SLICE(O)
                    if (OST == 1) { PP_GO() }
                    const uint32_t cv = ld_word(cx(lane & 7));
                    PULL_SLICE(O)
                    check_cnt(cv, cx(lane & 7), seq);
                    if (OST == 2) { PP_GO() }
                    STAMP(56 + (step >> 1));
                    GAT_ISSUE(PL(1))
                    blk_load<3 - GB>(A, BLK(osrc, 3 - GB), lane);
                }
                float ao[28];
#define WO_BLOCK(b)                                                                           \
    if ((b) > 0) blk_check<b>(A, BLK(osrc, b), lane, tag);                                    \
    if (((b) & 1) == 0) R_WAIT();                                                             \
    { DECL_DB(b, BASE128, 16, 0)                                                              \
    wg_fence();                                                                               \
    FOR7(mma_rs56<1, D128(((b) & 1) * HALF, t)>(ao, AQ(A, b, t), (b) + t > 0, SWB(b, t, db, 0))); } \
    wg_commit();                                                                              \
    if ((b) & 1) R_NEXT();
                WO_BLOCK(0)
                STAMP(11 + so);
                blk_load<3>(A, BLK(osrc, 3), lane);
                if (GB == 1) GAT_FETCH()
                WO_BLOCK(1)
                if (GB == 2) GAT_FETCH()
                WO_BLOCK(2)
                PUSH_ACK();
                WO_BLOCK(3)
                wg_wait<0>();
                if (EARLY >= 1) R_RELEASE(2);
                if (EARLY >= 2) R_RELEASE(1);
                STAMP(12 + so);
                WSUM(86 + 7 * (step >> 1));
                x_fix(X, xbits);
#pragma unroll
                for (int i = 0; i < 14; i++) X[i] = pack2(bf_lo(X[i]) + ao[2 * i], bf_hi(X[i]) + ao[2 * i + 1]);
            } else {
                uint32_t H[56];
                float ag[64];
#define F1_EPI(dst, ng, ag)                                                                    \
    _Pragma("unroll") for (int i = 0; i < 2 * (ng); i++)                                       \
        (dst)[i] = pack2(geglu(ag[2 * i], ag[4 * (ng) + 2 * i]), geglu(ag[2 * i + 1], ag[4 * (ng) + 2 * i + 1]));
#define H_PUSH(h0, off) st_async4(rem_h + (off), H[h0], H[(h0) + 1], H[(h0) + 2], H[(h0) + 3], mapa(BAR(B_RECV2 + wgi), hr ^ 1));
#define F1_BLOCK(b, first)                                                                     \
    if ((first) && (b) < 2 && (b) >= EARLY) R_RELEASE(2);                                      \
    if (GB == 2 && (first) && (b) == 1) GAT_FETCH()                                                       \
    if ((first) && (b) == 2) PUSH_ACK();                                                       \
    R_WAIT();                                                                                  \
    if ((b) == ((first) ? PPF : PPB)) { PP_WAIT() }                                            \
    { DECL_DB(b, BASE128, HALF, 0)                                                             \
    wg_fence();                                                                                \
    FOR7(mma_rs128<1, D128(0, t)>(ag, AQ(A, b, t), (b) + t > 0, SWB(b, t, db, 0));             \
         if constexpr (first) { PREP(b, t, true) }); }                                         \
    wg_commit();                                                                               \
    if ((b) == 3) { PP_GO() }                                                                  \
    if ((b) > 0) { wg_wait<1>(); R_RELEASE(1); }       \
    R_NEXT();
                normalize<0>(A, k0, k1);
                F1_BLOCK(0, true) F1_BLOCK(1, true) F1_BLOCK(2, true) F1_BLOCK(3, true)
                if (t128 == 0) { mbar_expect_tx(BAR(B_RECV + wgi), 16384); mbar_expect_tx(BAR(B_RECV2 + wgi), 12288); }
                PUSH_BEGIN();
                wg_wait<0>();
                R_RELEASE(1);
                if (step == 1) R_NEXT();
                int p = 0;
#pragma unroll 1
                do {
                    STAMP(68 + p);
                    F1_EPI(H + 32, 8, ag)
                    STAMP(4 + p + so);
                    WSUM(81 + p + 7 * (step >> 1));
                    if (((trips >> (p + 1)) & 1) == 0) continue;
                    {
                        const uint32_t pk = (p ? hbuf + 16384 : sb + OFF_KVB + wgi * 8192) + w * 2048;
#pragma unroll
                        for (int k = 0; k < 4; k++) sts4(pk + k * 512 + lane * 16, H[32 + 4 * k], H[33 + 4 * k], H[34 + 4 * k], H[35 + 4 * k]);
                        fence_async();
                        __syncwarp();
                        asm volatile(ELECT "cp.async.bulk.shared::cluster.shared::cta.mbarrier::complete_tx::bytes [%0], [%1], 2048, [%2]; }"
                                     ::"r"(mapa(hbuf + p * 8192 + w * 2048, hr ^ 1)), "r"(pk), "r"(mapa(BAR(B_RECV + wgi), hr ^ 1)) : "memory");
                    }
                    kill<64>(ag);
                    F1_BLOCK(0, false) F1_BLOCK(1, false) F1_BLOCK(2, false) F1_BLOCK(3, false)
                    wg_wait<0>();
                    R_RELEASE(1);
                    kill<16>(H + 32);
                } while (((trips >> (++p)) & 1));
#pragma unroll
                for (int k = 0; k < 4; k++) lds4(H + 16 + 4 * k, hbuf + 16384 + w * 2048 + k * 512 + lane * 16);
                __syncwarp();
                if (lane == 0) asm volatile("mbarrier.arrive.shared::cluster.b64 _, [%0];" ::"r"(mapa(BAR(B_ACK2 + wgi), hr ^ 1)) : "memory");
                const uint32_t rem_h = mapa(hbuf + w * 2048 + lane * 16, hr ^ 1);
#define F1_LAST(b0)                                                                            \
    R_WAIT();                                                                                  \
    if (b0) { PP_WAIT() }                                                                      \
    { DECL_DB(b0, BASE64, HALF, 1)                                                             \
    wg_fence();                                                                                \
    FOR7(mma_rs64<1, D64(0, t)>(al, AQ(A, b0, t), (b0) + t > 0, SWB(b0, t, db, 1)));           \
    FOR7(mma_rs64<1, D64(7168, t)>(al, AQ(A, (b0) + 1, t), 1, db)); }                          \
    wg_commit();                                                                               \
    if (b0) { PP_GO() }                                                                        \
    R_NEXT();
                float al[32];
                F1_LAST(0)
                mbar_wait(BAR(B_RECV + wgi), rcvph);
                rcvph ^= 1;
                mbar_wait(BAR(B_ACK2 + wgi), step >> 1);
                H_PUSH(32, 16384) H_PUSH(36, 16896)
                F1_LAST(2)
                H_PUSH(40, 17408) H_PUSH(44, 17920)
                wg_wait<1>();
                R_RELEASE(2);
                wg_wait<0>();
                R_RELEASE(1);
                uint32_t HP[56];
#pragma unroll
                for (int k = 0; k < 4; k++) lds4(H + 4 * k, sb + OFF_KVB + wgi * 8192 + w * 2048 + k * 512 + lane * 16);
#pragma unroll
                for (int t = 0; t < 8; t++) lds4(HP + 4 * t, hbuf + (t >> 2) * 8192 + w * 2048 + (t & 3) * 512 + lane * 16);
                F1_EPI(H + 48, 4, al)
                H_PUSH(48, 24576 - w * 1024) H_PUSH(52, 25088 - w * 1024)
                STAMP(7 + so);
                WSUM(84 + 7 * (step >> 1));
                FRESH();
                float acc[28];
                const uint32_t roA = hr ? 256u : 0u, roB = hr ? (uint32_t)-1536 : 0u;
                const uint32_t rpA = hr ? 0u : 256u, rpB = hr ? 0u : (uint32_t)-1536;
                float res[28];
                uint32_t v0[14], v1[14], P[14];
                const uint4* ps = xp0 + sl * 512;
#define F2_OWN_A()                                                                             \
    R_WAIT();                                                                                  \
    d0 = BASE128(0, 16, R_ADJ + roA); d1 = BASE128(0, 16, R_ADJ + roB);                        \
    wg_fence();                                                                                \
    FOR14(if constexpr (t < OT) mma_rs56<1, t * 128>(acc, H[4 * t], H[4 * t + 1], H[4 * t + 2], H[4 * t + 3], t > 0, d0)); \
    wg_commit();
#define F2_OWN_B()                                                                             \
    wg_fence();                                                                                \
    FOR14(if constexpr (t >= OT) mma_rs56<1, t * 128>(acc, H[4 * t], H[4 * t + 1], H[4 * t + 2], H[4 * t + 3], 1, t < 12 ? d0 : d1)); \
    wg_commit();                                                                               \
    R_NEXT();
#define F2_PEER()                                                                              \
    R_WAIT();                                                                                  \
    if (F2PP) { PP_WAIT() }                                                                    \
    d0 = BASE128(0, 16, R_ADJ + rpA); d1 = BASE128(0, 16, R_ADJ + rpB);                        \
    wg_fence();                                                                                \
    FOR14(mma_rs56<1, t * 128>(acc, HP[4 * t], HP[4 * t + 1], HP[4 * t + 2], HP[4 * t + 3], 1, t < 12 ? d0 : d1)); \
    wg_commit();                                                                               \
    if (F2PP) { PP_GO() }                                                                      \
    R_NEXT();
#define F2_TURN(u)                                                                             \
    wg_wait<1>();                                                                              \
    R_RELEASE(2);                                                                              \
    wg_wait<0>();                                                                              \
    R_RELEASE(1);                                                                              \
    _Pragma("unroll") for (int i = 0; i < 14; i++) P[i] = pack2(acc[2 * i], acc[2 * i + 1]);   \
    tag_slice(P, tag);                                                                         \
    asm volatile("" : RW4(P, 0), RW4(P, 4), RW4(P, 8), RW2(P, 12));                            \
    kill<28>(acc);                                                                             \
    F2_OWN_A()                                                                                 \
    if ((u) == 2) { slice_load<PL(3)>(v0, ps, lane); slice_load<PL(4)>(v1, ps, lane); } \
    send_slice<PL(3 + (u))>(xp0 + (2 * ((pr + (u) + 1) & 3) + hr) * 512, lane, P);             \
    seq++;                                                                                     \
    if (lane == 0) st_word(cx(sl), seq);                                                       \
    __syncwarp();                                                                              \
    STAMP(8 + (u) + so);                                                                       \
    F2_OWN_B()
                uint64_t d0, d1;
                F2_OWN_A()
                F2_OWN_B()
                R_WAIT();
                d0 = BASE128(0, 16, R_ADJ + rpA); d1 = BASE128(0, 16, R_ADJ + rpB);
                wg_fence();
                FOR8(mma_rs56<1, t * 128>(acc, HP[4 * t], HP[4 * t + 1], HP[4 * t + 2], HP[4 * t + 3], 1, d0));
                wg_commit();
                mbar_wait(BAR(B_RECV2 + wgi), step >> 1);
#pragma unroll
                for (int k = 0; k < 4; k++) lds4(HP + 32 + 4 * k, hbuf + 16384 + w * 2048 + k * 512 + lane * 16);
                lds4(HP + 48, hbuf + 24576 + w * 1024 + lane * 16);
                lds4(HP + 52, hbuf + 25088 + w * 1024 + lane * 16);
                if (step == 1) PUSH_ACK();
                wg_fence();
                FOR14(if constexpr (t >= 8) mma_rs56<1, t * 128>(acc, HP[4 * t], HP[4 * t + 1], HP[4 * t + 2], HP[4 * t + 3], 1, t < 12 ? d0 : d1));
                wg_commit();
                R_NEXT();
                F2_TURN(0)
                F2_PEER()
                F2_TURN(1)
                F2_PEER()
                F2_TURN(2)
                STAMP(64 + 8 * (step >> 1));
                slice_check<PL(3)>(v0, ps, lane, tag);
                slice_check<PL(4)>(v1, ps, lane, tag);
#pragma unroll
                for (int i = 0; i < 14; i++) { res[2 * i] = bf_lo(v0[i]) + bf_lo(v1[i]); res[2 * i + 1] = bf_hi(v0[i]) + bf_hi(v1[i]); }
                slice_load<PL(2)>(X, ps, lane);
                STAMP(65 + 8 * (step >> 1));
                F2_PEER()
                STAMP(66 + 8 * (step >> 1));
                poll_cnt(cx(2 * ((pr + 1) & 3) + hr), seq);
                STAMP(67 + 8 * (step >> 1));
                slice_load<PL(5)>(v0, ps, lane);
                x_fix(X, xbits);
                slice_check<PL(5)>(v0, ps, lane, tag);
#pragma unroll
                for (int i = 0; i < 14; i++) { res[2 * i] += bf_lo(v0[i]); res[2 * i + 1] += bf_hi(v0[i]); }
                STAMP(11 + so);
                wg_wait<0>();
                if (EARLYK >= 1) R_RELEASE(2);
                STAMP(12 + so);
                WSUM(85 + 7 * (step >> 1));
#pragma unroll
                for (int i = 0; i < 14; i++) X[i] = pack2(fmaf(res[2 * i] + acc[2 * i], 0.5f, bf_lo(X[i])), fmaf(res[2 * i + 1] + acc[2 * i + 1], 0.5f, bf_hi(X[i])));
            }
        }
        {
            const int m = lane >> 3, rr = lane & 7;
            const uint32_t ob = hbuf + w * 2048, rowa = ob + (rr + 8 * (m & 1)) * 112 + (m >> 1) * 16;
#pragma unroll
            for (int j = 0; j < 3; j++) stsm4(rowa + 32 * j, X[4 * j], X[4 * j + 1], X[4 * j + 2], X[4 * j + 3]);
            asm volatile("stmatrix.sync.aligned.m8n8.x2.shared.b16 [%0], {%1,%2};" ::"r"(ob + (rr + 8 * (m & 1)) * 112 + 96), "r"(X[12]), "r"(X[13]) : "memory");
            fence_async();
            __syncwarp();
            if (lane == 0) {
                asm volatile("cp.async.bulk.tensor.2d.global.shared::cta.bulk_group [%0, {%2, %3}], [%1];" ::"l"(&maps.out), "r"(ob), "r"(56 * sl), "r"(tile * 128 + wu * 16) : "memory");
                asm volatile("cp.async.bulk.commit_group;" ::: "memory");
                asm volatile("cp.async.bulk.wait_group.read 0;" ::: "memory");
            }
        }
        STAMP(50);
        GSTAMP(61);
        PDUMP();
    }
}

#undef g
#undef c
#undef t128

typedef CUresult (*EncodeFn)(CUtensorMap*, CUtensorMapDataType, cuuint32_t, void*, const cuuint64_t*, const cuuint64_t*, const cuuint32_t*,
                             const cuuint32_t*, CUtensorMapInterleave, CUtensorMapSwizzle, CUtensorMapL2promotion, CUtensorMapFloatOOBfill);

static void make_map(EncodeFn enc, CUtensorMap* m, const void* p, uint64_t cols, uint64_t rows, uint32_t bc, uint32_t br, CUtensorMapSwizzle sw) {
    cuuint64_t gd[2] = {cols, rows};
    cuuint64_t gs[1] = {cols * 2};
    cuuint32_t bd[2] = {bc, br};
    cuuint32_t es[2] = {1, 1};
    enc(m, CU_TENSOR_MAP_DATA_TYPE_BFLOAT16, 2, const_cast<void*>(p), gd, gs, bd, es, CU_TENSOR_MAP_INTERLEAVE_NONE, sw,
        CU_TENSOR_MAP_L2_PROMOTION_L2_128B, CU_TENSOR_MAP_FLOAT_OOB_FILL_NONE);
}

extern "C" void kernel_launch(void* const* d_in, const int* in_sizes, int n_in, void* d_out, int out_size) {
    (void)in_sizes; (void)n_in; (void)out_size;
    static EncodeFn enc = nullptr;
    static Scratch* scratch = nullptr;
    if (!enc) {
        void* fn = nullptr;
        cudaDriverEntryPointQueryResult qr;
        cudaGetDriverEntryPoint("cuTensorMapEncodeTiled", &fn, cudaEnableDefault, &qr);
        enc = (EncodeFn)fn;
        cudaGetSymbolAddress((void**)&scratch, g_scratch);
        cudaFuncSetAttribute(fused_kernel, cudaFuncAttributeMaxDynamicSharedMemorySize, SMEM_BYTES);
    }
    Maps maps;
    {
        cuuint64_t gd[3] = {64, 2048, 7};
        cuuint64_t gs[2] = {896, 128};
        cuuint32_t bd[3] = {64, 32, 7};
        cuuint32_t es[3] = {1, 1, 1};
        enc(&maps.x, CU_TENSOR_MAP_DATA_TYPE_BFLOAT16, 3, d_in[0], gd, gs, bd, es, CU_TENSOR_MAP_INTERLEAVE_NONE, CU_TENSOR_MAP_SWIZZLE_128B,
            CU_TENSOR_MAP_L2_PROMOTION_L2_128B, CU_TENSOR_MAP_FLOAT_OOB_FILL_NONE);
    }
    make_map(enc, &maps.out, d_out, 448, 2048, 56, 16, CU_TENSOR_MAP_SWIZZLE_NONE);
    make_map(enc, &maps.qkv, d_in[1], 1344, 448, 64, 112, CU_TENSOR_MAP_SWIZZLE_128B);
    make_map(enc, &maps.wo, d_in[3], 448, 448, 64, 112, CU_TENSOR_MAP_SWIZZLE_128B);
    make_map(enc, &maps.wg, d_in[5], 1792, 448, 64, 112, CU_TENSOR_MAP_SWIZZLE_128B);
    make_map(enc, &maps.wu, d_in[6], 1792, 448, 64, 112, CU_TENSOR_MAP_SWIZZLE_128B);
    make_map(enc, &maps.wg32, d_in[5], 1792, 448, 32, 112, CU_TENSOR_MAP_SWIZZLE_64B);
    make_map(enc, &maps.wu32, d_in[6], 1792, 448, 32, 112, CU_TENSOR_MAP_SWIZZLE_64B);
    make_map(enc, &maps.wd, d_in[7], 448, 1792, 64, 112, CU_TENSOR_MAP_SWIZZLE_128B);
    fused_kernel<<<128, 384, SMEM_BYTES>>>(scratch, (const __nv_bfloat16*)d_in[0], (const __nv_bfloat16*)d_in[2], 7, (const __nv_bfloat16*)d_in[5],
                                           (const __nv_bfloat16*)d_in[6], (const __nv_bfloat16*)d_in[7], maps);
}
```

```cpp
#include <cuda_runtime.h>
#include <cuda.h>
#include <cuda_bf16.h>
#include <stdint.h>
#include <type_traits>

#define MC 0
#define PPF 2
#define GE 0
#define B2L 1
#define B3L 0
#define PKP 0
#define TDEF 1
#define TMPF 0
#define NORM1 0
#define ACAN 0
#define SPLIT0 1
#define OT 2
#define F2PP 0
#define PPK 2
#define QE 1
#define OST 1
#define GB 1
#define B3T 6
#define PP

namespace {

constexpr uint32_t STAGE = 28672, HALF = 14336;
constexpr int NST = 5;
constexpr uint32_t OFF_H = NST * STAGE;
constexpr uint32_t OFF_KVB = OFF_H + 2 * STAGE;
constexpr uint32_t OFF_WPHI = OFF_KVB + 16384;
constexpr uint32_t OFF_XR = OFF_WPHI + 7168;
constexpr uint32_t OFF_BAR = OFF_XR + 6144;
constexpr uint32_t SMEM_BYTES = OFF_BAR + 256 + 1536;
constexpr int B_EMPTY = NST, B_RECV = 2 * NST, B_RECV2 = B_RECV + 2, B_PACK = B_RECV2 + 2, B_GAT = B_PACK + 1, B_ACK = B_GAT + 8, B_ACK2 = B_ACK + 2, B_COUNT = B_ACK2 + 2;

constexpr int PACK = 14 + 4 * PKP;

struct Maps { CUtensorMap x, qkv, wo, wg, wu, wg32, wu32, wd, out; };

}

constexpr int PLANE = 16 * 2 * 8 * 512;
struct Scratch {
    uint4 ex[6 * PLANE];
    uint4 kv1[8 * 16 * 16 * 32];
    uint4 kv2[8 * 512];
    uint32_t c1[8 * 8 * 16 * 32];
    uint32_t cw[8 * 32];
    uint4 wp[8 * 32 * (HALF / 16)];
};
__device__ __align__(1024) Scratch g_scratch;
#define g_ex (sc->ex)
#define g_kv1 (sc->kv1)
#define g_kv2 (sc->kv2)
#define g_c1 (sc->c1)
#define g_cw (sc->cw)
#define g_wp (sc->wp)
#define STAMP(i)
#define GSTAMP(i)
#define PDUMP()
#define ASTAMP(i)

namespace {

__device__ __forceinline__ int fresh_tid() { int t; asm volatile("mov.u32 %0, %%tid.x;" : "=r"(t)); return t; }
template <int N> __device__ __forceinline__ void kill(uint32_t* v) {
#pragma unroll
    for (int i = 0; i < N; i++) v[i] = 0;
}
template <int N> __device__ __forceinline__ void kill(float* v) {
#pragma unroll
    for (int i = 0; i < N; i++) v[i] = 0.f;
}
__device__ __forceinline__ uint32_t s2u(const void* p) { return (uint32_t)__cvta_generic_to_shared(p); }
__device__ __forceinline__ void mbar_init(uint32_t a, uint32_t c) { asm volatile("mbarrier.init.shared::cta.b64 [%0], %1;" ::"r"(a), "r"(c) : "memory"); }
__device__ __forceinline__ void mbar_expect_tx(uint32_t a, uint32_t b) { asm volatile("mbarrier.arrive.expect_tx.shared::cta.b64 _, [%0], %1;" ::"r"(a), "r"(b) : "memory"); }
__device__ __forceinline__ void mbar_arrive(uint32_t a) { asm volatile("mbarrier.arrive.shared::cta.b64 _, [%0];" ::"r"(a) : "memory"); }
#define GIVE_UP(id) "trap;\n"
#define SPIN_MAX "0x400000"
#define SPIN_TAIL(id) "add.u32 n, n, 1;\n setp.lt.u32 p, n, " SPIN_MAX ";\n @p bra.uni LP;\n" GIVE_UP(id) " DN:\n }"
__device__ __forceinline__ void mbar_wait(uint32_t a, uint32_t ph) {
    asm volatile("{ .reg .pred p; .reg .b32 n; mov.u32 n, 0;\n LP:\n"
                 "mbarrier.try_wait.parity.shared::cta.b64 p, [%0], %1;\n @p bra DN;\n"
                 "add.u32 n, n, 1;\n setp.lt.u32 p, n, " SPIN_MAX ";\n @p bra LP;\n"
                 GIVE_UP("")
                 " DN:\n }" ::"r"(a), "r"(ph) : "memory");
}
#define ELECT "{ .reg .pred e; elect.sync _|e, 0xffffffff; @e "
__device__ __forceinline__ void tma2d(uint32_t dst, const CUtensorMap* m, int c0, int c1, uint32_t bar) {
    asm volatile(ELECT "cp.async.bulk.tensor.2d.shared::cluster.global.mbarrier::complete_tx::bytes [%0], [%1, {%3, %4}], [%2]; }" ::"r"(dst), "l"(m), "r"(bar), "r"(c0), "r"(c1) : "memory");
}
__device__ __forceinline__ void tma3x(uint32_t dst, const CUtensorMap* m, int row, uint32_t bar) {
    asm volatile(ELECT "cp.async.bulk.tensor.3d.shared::cluster.global.mbarrier::complete_tx::bytes [%0], [%1, {0, %3, 0}], [%2]; }" ::"r"(dst), "l"(m), "r"(bar), "r"(row) : "memory");
}
template <int OFF>
__device__ __forceinline__ void ld_pkt(uint32_t* v, const uint4* p) {
    asm volatile("{ .reg .b128 t; ld.relaxed.gpu.global.b128 t, [%4+%5]; mov.b128 {%0,%1,%2,%3}, t; }" : "=r"(v[0]), "=r"(v[1]), "=r"(v[2]), "=r"(v[3]) : "l"(p), "n"(OFF * 16) : "memory");
}
template <int OFF>
__device__ __forceinline__ void st_pkt(uint4* p, uint32_t a, uint32_t b, uint32_t c, uint32_t d) {
    asm volatile("{ .reg .b128 t; mov.b128 t, {%1,%2,%3,%4}; st.relaxed.gpu.global.b128 [%0+%5], t; }" ::"l"(p), "r"(a), "r"(b), "r"(c), "r"(d), "n"(OFF * 16) : "memory");
}
__device__ __forceinline__ uint32_t pack2(float lo, float hi) {
    uint32_t r;
    asm("cvt.rn.bf16x2.f32 %0, %1, %2;" : "=r"(r) : "f"(hi), "f"(lo));
    return r;
}
__device__ __forceinline__ float bf_lo(uint32_t w) { return __uint_as_float(w << 16); }
__device__ __forceinline__ float bf_hi(uint32_t w) { return __uint_as_float(w & 0xffff0000u); }
__device__ __forceinline__ uint32_t settag(uint32_t w, uint32_t tag) { return (w & ~1u) | tag; }
__device__ __forceinline__ float ex2(float x) { float y; asm("ex2.approx.ftz.f32 %0, %1;" : "=f"(y) : "f"(x)); return y; }
__device__ __forceinline__ float rcp(float x) { float y; asm("rcp.approx.ftz.f32 %0, %1;" : "=f"(y) : "f"(x)); return y; }
__device__ __forceinline__ float tanh_hw(float x) { float y; asm("tanh.approx.f32 %0, %1;" : "=f"(y) : "f"(x)); return y; }
__device__ __forceinline__ void stsm4(uint32_t addr, uint32_t a, uint32_t b, uint32_t c, uint32_t d) {
    asm volatile("stmatrix.sync.aligned.m8n8.x4.shared.b16 [%0], {%1,%2,%3,%4};" ::"r"(addr), "r"(a), "r"(b), "r"(c), "r"(d) : "memory");
}
__device__ __forceinline__ void fence_async() { asm volatile("fence.proxy.async.shared::cta;" ::: "memory"); }
__device__ __forceinline__ void bar_sync(int id, int n) { asm volatile("bar.sync %0, %1;" ::"r"(id), "r"(n) : "memory"); }
__device__ __forceinline__ void bar_arrive(int id, int n) { asm volatile("bar.arrive %0, %1;" ::"r"(id), "r"(n) : "memory"); }
__device__ __forceinline__ void wg_fence() { asm volatile("wgmma.fence.sync.aligned;" ::: "memory"); }
__device__ __forceinline__ void wg_commit() { asm volatile("wgmma.commit_group.sync.aligned;" ::: "memory"); }
template <int N> __device__ __forceinline__ void wg_wait() { asm volatile("wgmma.wait_group.sync.aligned %0;" ::"n"(N) : "memory"); }

constexpr uint32_t SB0 = 1024;
__host__ __device__ constexpr uint32_t dlo(uint32_t off, uint32_t lbo) { return ((SB0 + off) >> 4) | ((lbo >> 4) << 16); }
__host__ __device__ constexpr uint32_t dhi(uint32_t sbo, uint32_t sw) { return (sbo >> 4) | (sw << 30); }
__device__ __forceinline__ uint64_t dbase(uint32_t lo, uint32_t hi) { uint64_t d; asm volatile("mov.b64 %0, {%1, %2};" : "=l"(d) : "r"(lo), "r"(hi)); return d; }
#define BASE128(off, lbo, adj) dbase(dlo(off, lbo) + (adj), dhi(1024, 1))
#define BASE64(off, lbo, adj) dbase(dlo(off, lbo) + (adj), dhi(512, 2))

#define ACC4(d, o) "+f"(d[o]), "+f"(d[o + 1]), "+f"(d[o + 2]), "+f"(d[o + 3])
#define ACC28(d) ACC4(d, 0), ACC4(d, 4), ACC4(d, 8), ACC4(d, 12), ACC4(d, 16), ACC4(d, 20), ACC4(d, 24)
#define ACC32(d, o) ACC4(d, o), ACC4(d, o + 4), ACC4(d, o + 8), ACC4(d, o + 12), ACC4(d, o + 16), ACC4(d, o + 20), ACC4(d, o + 24), ACC4(d, o + 28)

template <int TB, uint64_t D>
__device__ __forceinline__ void mma_rs56(float* d, uint32_t a0, uint32_t a1, uint32_t a2, uint32_t a3, int sd, uint64_t base) {
    asm volatile("{ .reg .pred p; .reg .b64 db; setp.ne.b32 p, %32, 0; add.u64 db, %33, %34;\n"
                 "wgmma.mma_async.sync.aligned.m64n56k16.f32.bf16.bf16 "
                 "{%0,%1,%2,%3,%4,%5,%6,%7,%8,%9,%10,%11,%12,%13,%14,%15,%16,%17,%18,%19,%20,%21,%22,%23,%24,%25,%26,%27}, "
                 "{%28,%29,%30,%31}, db, p, 1, 1, %35; }\n"
                 : ACC28(d)
                 : "r"(a0), "r"(a1), "r"(a2), "r"(a3), "r"(sd), "l"(base), "n"(D), "n"(TB));
}
template <int TB, uint64_t D>
__device__ __forceinline__ void mma_rs64(float* d, uint32_t a0, uint32_t a1, uint32_t a2, uint32_t a3, int sd, uint64_t base) {
    asm volatile("{ .reg .pred p; .reg .b64 db; setp.ne.b32 p, %36, 0; add.u64 db, %37, %38;\n"
                 "wgmma.mma_async.sync.aligned.m64n64k16.f32.bf16.bf16 "
                 "{%0,%1,%2,%3,%4,%5,%6,%7,%8,%9,%10,%11,%12,%13,%14,%15,%16,%17,%18,%19,%20,%21,%22,%23,%24,%25,%26,%27,%28,%29,%30,%31}, "
                 "{%32,%33,%34,%35}, db, p, 1, 1, %39; }\n"
                 : ACC32(d, 0)
                 : "r"(a0), "r"(a1), "r"(a2), "r"(a3), "r"(sd), "l"(base), "n"(D), "n"(TB));
}
template <int TB, uint64_t D>
__device__ __forceinline__ void mma_rs128(float* d, uint32_t a0, uint32_t a1, uint32_t a2, uint32_t a3, int sd, uint64_t base) {
    asm volatile("{ .reg .pred p; .reg .b64 db; setp.ne.b32 p, %68, 0; add.u64 db, %69, %70;\n"
                 "wgmma.mma_async.sync.aligned.m64n128k16.f32.bf16.bf16 "
                 "{%0,%1,%2,%3,%4,%5,%6,%7,%8,%9,%10,%11,%12,%13,%14,%15,%16,%17,%18,%19,%20,%21,%22,%23,%24,%25,%26,%27,%28,%29,%30,%31,%32,%33,%34,%35,%36,%37,%38,%39,%40,%41,%42,%43,%44,%45,%46,%47,%48,%49,%50,%51,%52,%53,%54,%55,%56,%57,%58,%59,%60,%61,%62,%63}, "
                 "{%64,%65,%66,%67}, db, p, 1, 1, %71; }\n"
                 : ACC32(d, 0), ACC32(d, 32)
                 : "r"(a0), "r"(a1), "r"(a2), "r"(a3), "r"(sd), "l"(base), "n"(D), "n"(TB));
}
template <uint64_t DA, uint64_t DB>
__device__ __forceinline__ void mma_ss56_tt(float* d, int sd, uint64_t ba, uint64_t bb) {
    asm volatile("{ .reg .pred p; .reg .b64 da, db; setp.ne.b32 p, %28, 0; add.u64 da, %29, %31; add.u64 db, %30, %32;\n"
                 "wgmma.mma_async.sync.aligned.m64n56k16.f32.bf16.bf16 "
                 "{%0,%1,%2,%3,%4,%5,%6,%7,%8,%9,%10,%11,%12,%13,%14,%15,%16,%17,%18,%19,%20,%21,%22,%23,%24,%25,%26,%27}, "
                 "da, db, p, 1, 1, 1, 1; }\n"
                 : ACC28(d)
                 : "r"(sd), "l"(ba), "l"(bb), "n"(DA), "n"(DB));
}
template <int... I> struct Seq {};
template <class F, int... I> __device__ __forceinline__ void static_for_impl(F&& f, Seq<I...>) { (f(std::integral_constant<int, I>{}), ...); }
#define FOR7(...) static_for_impl([&](auto T_) { constexpr int t = decltype(T_)::value; __VA_ARGS__; }, Seq<0, 1, 2, 3, 4, 5, 6>{})
#define FOR8(...) static_for_impl([&](auto T_) { constexpr int t = decltype(T_)::value; __VA_ARGS__; }, Seq<0, 1, 2, 3, 4, 5, 6, 7>{})
#define FOR14(...) static_for_impl([&](auto T_) { constexpr int t = decltype(T_)::value; __VA_ARGS__; }, Seq<0, 1, 2, 3, 4, 5, 6, 7, 8, 9, 10, 11, 12, 13>{})

__device__ __forceinline__ int kblk(int p, int b) { return b == 0 ? p : b - (b <= p); }
__host__ __device__ constexpr int krow(int t) { return t < 3 ? 16 * t : (t < 6 ? 56 + 16 * (t - 3) : 48); }
#define AQ(A, b, t) ((t) < 3 ? A[2 * (b)][4 * (t)] : (t) < 6 ? A[2 * (b) + 1][4 * ((t) - 3)] : A[2 * (b)][12]), \
                    ((t) < 3 ? A[2 * (b)][4 * (t) + 1] : (t) < 6 ? A[2 * (b) + 1][4 * ((t) - 3) + 1] : A[2 * (b)][13]), \
                    ((t) < 3 ? A[2 * (b)][4 * (t) + 2] : (t) < 6 ? A[2 * (b) + 1][4 * ((t) - 3) + 2] : A[2 * (b) + 1][12]), \
                    ((t) < 3 ? A[2 * (b)][4 * (t) + 3] : (t) < 6 ? A[2 * (b) + 1][4 * ((t) - 3) + 3] : A[2 * (b) + 1][13])
#define D128(off, t) ((uint64_t)(((off) + krow(t) * 128) >> 4) + ((uint64_t)((t) == 6 ? (7168 - 1024) >> 4 : 0) << 32))
#define D64(off, t) ((uint64_t)(((off) + krow(t) * 64) >> 4) + ((uint64_t)((t) == 6 ? (3584 - 512) >> 4 : 0) << 32))

#define PL(k) (((k) - 3) * PLANE)
__device__ __forceinline__ void st_word(uint32_t* p, uint32_t v) { asm volatile("st.relaxed.gpu.global.u32 [%0], %1;" ::"l"(p), "r"(v) : "memory"); }
__device__ __forceinline__ uint32_t ld_word(const uint32_t* p) { uint32_t v; asm volatile("ld.relaxed.gpu.global.u32 %0, [%1];" : "=r"(v) : "l"(p) : "memory"); return v; }
__device__ __forceinline__ void tag_slice(uint32_t* w, uint32_t tag) { w[0] = settag(w[0], tag); w[4] = settag(w[4], tag); w[8] = settag(w[8], tag); w[12] = settag(w[12], tag); }
template <int O>
__device__ __forceinline__ void send_slice(uint4* dst, int lane, const uint32_t* w) {
    st_pkt<O>(dst, w[0], w[1], w[2], w[3]);
    st_pkt<O + 32>(dst, w[4], w[5], w[6], w[7]);
    st_pkt<O + 64>(dst, w[8], w[9], w[10], w[11]);
    asm volatile("{ .reg .b64 t; mov.b64 t, {%1,%2}; st.relaxed.gpu.global.b64 [%0+%3], t; }" ::"l"((char*)dst - lane * 8), "r"(w[12]), "r"(w[13]), "n"(16 * (O + 96)) : "memory");
}
#define RW4(v, o) "+r"(v[o]), "+r"(v[(o) + 1]), "+r"(v[(o) + 2]), "+r"(v[(o) + 3])
#define RW2(v, o) "+r"(v[o]), "+r"(v[(o) + 1])
#define WR4(v, o) "=&r"(v[o]), "=&r"(v[(o) + 1]), "=&r"(v[(o) + 2]), "=&r"(v[(o) + 3])
#define LDP(a, b, c, d, addr, off) "ld.relaxed.gpu.global.b128 q, [" addr "+" off "];\n mov.b128 {" a "," b "," c "," d "}, q;\n"
#define LDH(a, b, addr, off) "ld.relaxed.gpu.global.b64 h, [" addr "+" off "];\n mov.b64 {" a "," b "}, h;\n"
#define VOTE_OK "and.b32 t, t, 1;\n setp.ne.u32 p, t, 0;\n vote.sync.any.pred p, p, 0xffffffff;\n @!p bra.uni DN;\n"
#define CHK(x, tag) "lop3.b32 t, " x ", " tag ", t, 0xBE;\n"
__device__ __forceinline__ void check_cnt(uint32_t v, const uint32_t* p, uint32_t target) {
    asm volatile("{ .reg .pred p; .reg .b32 n, t; mov.u32 n, 0; mov.u32 t, %2;\n LP:\n"
                 "sub.s32 t, t, %1;\n setp.lt.s32 p, t, 0;\n vote.sync.any.pred p, p, 0xffffffff;\n @!p bra.uni DN;\n ld.relaxed.gpu.global.u32 t, [%0];\n" SPIN_TAIL("7")
                 ::"l"(p), "r"(target), "r"(v) : "memory");
}
__device__ __forceinline__ void poll_cnt(const uint32_t* p, uint32_t target) {
    asm volatile("{ .reg .pred p; .reg .b32 n, t; mov.u32 n, 0;\n LP:\n"
                 "ld.relaxed.gpu.global.u32 t, [%0];\n sub.s32 t, t, %1;\n setp.lt.s32 p, t, 0;\n vote.sync.any.pred p, p, 0xffffffff;\n @!p bra.uni DN;\n" SPIN_TAIL("1")
                 ::"l"(p), "r"(target) : "memory");
}
template <int STR>
__device__ __forceinline__ void poll4_kv(uint32_t* v, const uint4* p, uint32_t tag) {
    asm volatile("{ .reg .pred p; .reg .b32 n, t; .reg .b128 q; mov.u32 n, 0;\n LP:\n"
                 LDP("%0", "%1", "%2", "%3", "%16", "0") LDP("%4", "%5", "%6", "%7", "%16", "%18")
                 LDP("%8", "%9", "%10", "%11", "%16", "%19") LDP("%12", "%13", "%14", "%15", "%16", "%20")
                 "xor.b32 t, %0, %17;\n" CHK("%4", "%17") CHK("%8", "%17") CHK("%12", "%17") VOTE_OK SPIN_TAIL("2")
                 : WR4(v, 0), WR4(v, 4), WR4(v, 8), WR4(v, 12)
                 : "l"(p), "r"(tag), "n"(16 * STR), "n"(32 * STR), "n"(48 * STR)
                 : "memory");
}
template <int B>
__device__ __forceinline__ void blk_load(uint32_t (&A)[8][14], const uint4* src, int lane) {
    ld_pkt<0>(&A[2 * B][0], src); ld_pkt<32>(&A[2 * B][4], src); ld_pkt<64>(&A[2 * B][8], src);
    ld_pkt<512>(&A[2 * B + 1][0], src); ld_pkt<544>(&A[2 * B + 1][4], src); ld_pkt<576>(&A[2 * B + 1][8], src);
    asm volatile("{ .reg .b64 h;\n" LDH("%0", "%1", "%4", "1536") LDH("%2", "%3", "%4", "9728") "}"
                 : "=&r"(A[2 * B][12]), "=&r"(A[2 * B][13]), "=&r"(A[2 * B + 1][12]), "=&r"(A[2 * B + 1][13])
                 : "l"((const char*)src - lane * 8) : "memory");
}
template <int B>
__device__ __forceinline__ void blk_check(uint32_t (&A)[8][14], const uint4* src, int lane, uint32_t tag) {
    asm volatile("{ .reg .pred p; .reg .b32 n, t; .reg .b128 q; .reg .b64 h, a8; mov.u32 n, 0;\n LP:\n"
                 "xor.b32 t, %0, %30;\n" CHK("%4", "%30") CHK("%8", "%30") CHK("%12", "%30") CHK("%16", "%30") CHK("%20", "%30") CHK("%24", "%30") CHK("%26", "%30") VOTE_OK
                 LDP("%0", "%1", "%2", "%3", "%28", "0") LDP("%4", "%5", "%6", "%7", "%28", "512") LDP("%8", "%9", "%10", "%11", "%28", "1024")
                 LDP("%12", "%13", "%14", "%15", "%28", "8192") LDP("%16", "%17", "%18", "%19", "%28", "8704") LDP("%20", "%21", "%22", "%23", "%28", "9216")
                 "mad.wide.s32 a8, %29, -8, %28;\n" LDH("%24", "%25", "a8", "1536") LDH("%26", "%27", "a8", "9728") SPIN_TAIL("3")
                 "\n and.b32 %0, %0, -2; and.b32 %4, %4, -2; and.b32 %8, %8, -2; and.b32 %12, %12, -2; and.b32 %16, %16, -2; and.b32 %20, %20, -2; and.b32 %24, %24, -2; and.b32 %26, %26, -2;"
                 : RW4(A[2 * B], 0), RW4(A[2 * B], 4), RW4(A[2 * B], 8), RW4(A[2 * B + 1], 0), RW4(A[2 * B + 1], 4), RW4(A[2 * B + 1], 8),
                   RW2(A[2 * B], 12), RW2(A[2 * B + 1], 12)
                 : "l"(src), "r"(lane), "r"(tag)
                 : "memory");
}
__device__ __forceinline__ void st_async4(uint32_t a, uint32_t x, uint32_t y, uint32_t z, uint32_t w, uint32_t bar) {
    asm volatile("st.async.weak.shared::cluster.mbarrier::complete_tx::bytes.v4.b32 [%0], {%1,%2,%3,%4}, [%5];" ::"r"(a), "r"(x), "r"(y), "r"(z), "r"(w), "r"(bar) : "memory");
}
__device__ __forceinline__ uint32_t mapa(uint32_t a, uint32_t cta) { uint32_t r; asm("mapa.shared::cluster.u32 %0, %1, %2;" : "=r"(r) : "r"(a), "r"(cta)); return r; }
__device__ __forceinline__ void stat_load(uint32_t* v, const uint4* p) { ld_pkt<0>(v, p); ld_pkt<512>(v + 4, p); }
__device__ __forceinline__ void stat_check(uint32_t* v, const uint4* p, uint32_t tag) {
    asm volatile("{ .reg .pred p; .reg .b32 n, t; .reg .b128 q; mov.u32 n, 0;\n LP:\n"
                 "xor.b32 t, %3, %9;\n" CHK("%7", "%9") VOTE_OK
                 LDP("%0", "%1", "%2", "%3", "%8", "0") LDP("%4", "%5", "%6", "%7", "%8", "8192") SPIN_TAIL("4")
                 : RW4(v, 0), RW4(v, 4) : "l"(p), "r"(tag) : "memory");
}
__device__ __forceinline__ uint32_t x_bits(const uint32_t* X) {
    uint32_t r;
    asm volatile("{ .reg .b32 a, b; prmt.b32 a, %1, %2, 0x0040; prmt.b32 b, %3, %4, 0x0040; prmt.b32 %0, a, b, 0x5410; }" : "=r"(r) : "r"(X[0]), "r"(X[4]), "r"(X[8]), "r"(X[12]));
    return r;
}
template <int O>
__device__ __forceinline__ void slice_load(uint32_t* v, const uint4* p, int lane) {
    ld_pkt<O>(v, p); ld_pkt<O + 32>(v + 4, p); ld_pkt<O + 64>(v + 8, p);
    asm volatile("{ .reg .b64 h;\n" LDH("%0", "%1", "%2", "%3") "}" : "=r"(v[12]), "=r"(v[13]) : "l"((const char*)p - lane * 8), "n"(16 * (O + 96)) : "memory");
}
template <int O>
__device__ __forceinline__ void slice_check(uint32_t* v, const uint4* p, int lane, uint32_t tag) {
    asm volatile("{ .reg .pred p; .reg .b32 n, t; .reg .b128 q; .reg .b64 h; mov.u32 n, 0;\n LP:\n"
                 "xor.b32 t, %0, %16;\n" CHK("%4", "%16") CHK("%8", "%16") CHK("%12", "%16") VOTE_OK
                 LDP("%0", "%1", "%2", "%3", "%14", "%17") LDP("%4", "%5", "%6", "%7", "%14", "%18") LDP("%8", "%9", "%10", "%11", "%14", "%19")
                 LDH("%12", "%13", "%15", "%20") SPIN_TAIL("5")
                 : RW4(v, 0), RW4(v, 4), RW4(v, 8), RW2(v, 12)
                 : "l"(p), "l"((const char*)p - lane * 8), "r"(tag), "n"(16 * O), "n"(16 * (O + 32)), "n"(16 * (O + 64)), "n"(16 * (O + 96))
                 : "memory");
}
__device__ __forceinline__ void x_fix(uint32_t* X, uint32_t bits) {
    X[0] = __byte_perm(X[0], bits, 0x3214); X[4] = __byte_perm(X[4], bits, 0x3215); X[8] = __byte_perm(X[8], bits, 0x3216); X[12] = __byte_perm(X[12], bits, 0x3217);
}
__device__ __forceinline__ void sts4(uint32_t a, uint32_t x, uint32_t y, uint32_t z, uint32_t w) {
    asm volatile("st.shared.v4.u32 [%0], {%1,%2,%3,%4};" ::"r"(a), "r"(x), "r"(y), "r"(z), "r"(w) : "memory");
}
__device__ __forceinline__ void lds4(uint32_t* v, uint32_t a) {
    asm volatile("ld.shared.v4.u32 {%0,%1,%2,%3}, [%4];" : "=r"(v[0]), "=r"(v[1]), "=r"(v[2]), "=r"(v[3]) : "r"(a) : "memory");
}
struct LnCoef { uint32_t hi, lo, sh; };
__device__ __forceinline__ LnCoef ln_coef(float sum, float sq) {
    sum += __shfl_xor_sync(0xffffffffu, sum, 1); sq += __shfl_xor_sync(0xffffffffu, sq, 1);
    sum += __shfl_xor_sync(0xffffffffu, sum, 2); sq += __shfl_xor_sync(0xffffffffu, sq, 2);
    const float mean = sum * (1.f / 448.f);
    const float var = fmaxf(fmaf(-mean, mean, sq * (1.f / 448.f)), 0.f);
    const float sc = rsqrtf(var + 1e-5f);
    LnCoef r;
    r.hi = pack2(sc, sc);
    const float lo = sc - bf_lo(r.hi), sh = -mean * sc;
    r.lo = pack2(lo, lo);
    r.sh = pack2(sh, sh);
    return r;
}
template <int B>
__device__ __forceinline__ void normalize(uint32_t (&A)[8][14], const LnCoef& c0, const LnCoef& c1) {
#pragma unroll
    for (int s = 2 * B; s < 2 * B + 2; s++)
#pragma unroll
        for (int i = 0; i < 14; i++) {
            const LnCoef& k = (i & 1) ? c1 : c0;
            asm("{ .reg .b32 t; fma.rn.bf16x2 t, %0, %2, %3; fma.rn.bf16x2 %0, %0, %1, t; }" : "+r"(A[s][i]) : "r"(k.hi), "r"(k.lo), "r"(k.sh));
        }
}
__device__ __forceinline__ void slice_stats(const uint32_t* w, float* st) {
    float a = 0.f, b = 0.f, p = 0.f, q = 0.f;
#pragma unroll
    for (int i = 0; i < 7; i++) {
        const float e0 = bf_lo(w[2 * i]), e1 = bf_hi(w[2 * i]), e2 = bf_lo(w[2 * i + 1]), e3 = bf_hi(w[2 * i + 1]);
        a += e0 + e1; b += e2 + e3;
        p = fmaf(e0, e0, p); p = fmaf(e1, e1, p); q = fmaf(e2, e2, q); q = fmaf(e3, e3, q);
    }
    a += __shfl_xor_sync(0xffffffffu, a, 1); p += __shfl_xor_sync(0xffffffffu, p, 1); b += __shfl_xor_sync(0xffffffffu, b, 1); q += __shfl_xor_sync(0xffffffffu, q, 1);
    a += __shfl_xor_sync(0xffffffffu, a, 2); p += __shfl_xor_sync(0xffffffffu, p, 2); b += __shfl_xor_sync(0xffffffffu, b, 2); q += __shfl_xor_sync(0xffffffffu, q, 2);
    st[0] = a; st[1] = p; st[2] = b; st[3] = q;
}
__device__ __forceinline__ void dual_softmax(const float* p, uint32_t* out) {
    constexpr float L = 1.4426950408889634f;
#pragma unroll
    for (int r = 0; r < 2; r++) {
        float mx = fmaxf(p[2 * r], p[2 * r + 1]), mn = fminf(p[2 * r], p[2 * r + 1]);
#pragma unroll
        for (int i = 1; i < 7; i++) {
            mx = fmaxf(mx, fmaxf(p[4 * i + 2 * r], p[4 * i + 2 * r + 1]));
            mn = fminf(mn, fminf(p[4 * i + 2 * r], p[4 * i + 2 * r + 1]));
        }
        mx = fmaxf(mx, __shfl_xor_sync(0xffffffffu, mx, 1));
        mn = fminf(mn, __shfl_xor_sync(0xffffffffu, mn, 1));
        const float bx = -mx * L, bn = mn * L;
        float ep[14], en[14], sp = 0.f, sn = 0.f;
#pragma unroll
        for (int i = 0; i < 14; i++) {
            const float v = p[4 * (i >> 1) + 2 * r + (i & 1)];
            ep[i] = ex2(fmaf(v, L, bx));
            en[i] = ex2(fmaf(v, -L, bn));
            sp += ep[i]; sn += en[i];
        }
        sp += __shfl_xor_sync(0xffffffffu, sp, 1);
        sn += __shfl_xor_sync(0xffffffffu, sn, 1);
        const float ip = rcp(sp), in = rcp(sn);
#pragma unroll
        for (int i = 0; i < 7; i++) {
            out[4 * i + r] = pack2(ep[2 * i] * ip, ep[2 * i + 1] * ip);
            out[4 * i + 2 + r] = pack2(en[2 * i] * in, en[2 * i + 1] * in);
        }
    }
}
__device__ __forceinline__ float geglu(float g, float u) {
    const float t = tanh_hw(g * fmaf(g * g, 0.7978845608028654f * 0.044715f, 0.7978845608028654f));
    const float gu = g * u;
    return fmaf(t, gu, gu);
}
__device__ __forceinline__ void phi_gemm(const float* t, float* p) {
    uint32_t w[14];
#pragma unroll
    for (int i = 0; i < 14; i++) w[i] = pack2(t[2 * i], t[2 * i + 1]);
    const uint64_t db = BASE128(OFF_WPHI, 16, 0);
    wg_fence();
    mma_rs56<0, 0>(p, w[0], w[1], w[2], w[3], 0, db);
    mma_rs56<0, 2>(p, w[4], w[5], w[6], w[7], 1, db);
    mma_rs56<0, 4>(p, w[8], w[9], w[10], w[11], 1, db);
    mma_rs56<0, 6>(p, w[12], w[13], 0u, 0u, 1, db);
    wg_commit();
    wg_wait<0>();
}

}

#define BAR(i) (bars + 8 * (i))
#define R_WAIT() mbar_wait(BAR(slot), ph)
#define WSUM(i)
#define R_ADJ (slot * (STAGE >> 4))
#define R_NEXT() do { eb2 = eb1; eb1 = BAR(B_EMPTY + slot); if (++slot == NST) { slot = 0; ph ^= 1; } } while (0)
#define R_RELEASE(k) do { if (lane == 0) mbar_arrive((k) == 1 ? eb1 : eb2); } while (0)
#define PUSH_BEGIN() do { mbar_wait(BAR(B_ACK + wgi), ackph); ackph ^= 1; } while (0)
#define PUSH_ACK() do { __syncwarp(); if (lane == 0) asm volatile("mbarrier.arrive.shared::cluster.b64 _, [%0];" ::"r"(mapa(BAR(B_ACK + wgi), hr ^ 1)) : "memory"); } while (0)

__global__ void __cluster_dims__(2, 1, 1) __launch_bounds__(384, 1)
fused_kernel(Scratch* const sc, const __nv_bfloat16* __restrict__ x_in, const __nv_bfloat16* __restrict__ w_phi, const int trips,
             const __nv_bfloat16* __restrict__ wg, const __nv_bfloat16* __restrict__ wu, const __nv_bfloat16* __restrict__ wd,
             const __grid_constant__ Maps maps) {
    extern __shared__ __align__(1024) unsigned char smem_raw[];
    const uint32_t sb = s2u(smem_raw);
    const uint32_t bars = sb + OFF_BAR;
    const int wgi = __shfl_sync(0xffffffffu, threadIdx.x >> 7, 0);
    const int hr = blockIdx.x & 1, ck = blockIdx.x >> 1;
    const int gp = (ck - 4) & 7, q7 = ((ck - 36) * 37) >> 8;
    const int pr = __shfl_sync(0xffffffffu, ck < 4 ? ck : (ck < 36 ? (ck - 4) >> 3 : q7), 0);
    const int tile = __shfl_sync(0xffffffffu, ck < 4 ? 0 : (ck < 36 ? (gp ? 2 * gp : 1) : 2 * (ck - 36 - 7 * q7) + 3), 0);
    const int sl = 2 * pr + hr;
    STAMP(0);
    GSTAMP(60);
    if (threadIdx.x == 256) {
#pragma unroll
        for (int i = 0; i < NST; i++) mbar_init(BAR(i), 1);
        asm volatile("fence.mbarrier_init.release.cluster;" ::: "memory");
    }
    if (threadIdx.x == 288) {
        if ((sb & 0x3FFFF) != SB0) asm volatile("trap;");
#pragma unroll
        for (int i = NST; i < B_COUNT; i++) mbar_init(BAR(i), i >= B_ACK ? 4 : (i < B_RECV ? 8 : 1));
        asm volatile("fence.mbarrier_init.release.cluster;" ::: "memory");
    }
    __syncwarp();
    asm volatile("barrier.cluster.arrive.relaxed.aligned;" ::: "memory");

    if (wgi == 2) {
        asm volatile("setmaxnreg.dec.sync.aligned.u32 40;");
        const int t128 = fresh_tid() & 127, w = __shfl_sync(0xffffffffu, t128 >> 5, 0), lane = t128 & 31;
        uint32_t e0[2] = {0, 0}, e1[2] = {0, 0}, cw_target = 0;
        if (w == 0) {
#pragma unroll 1
            for (int n = 0; n < NST; n++) {
                const uint32_t dst = sb + n * STAGE, fb = BAR(n);
                asm volatile(ELECT "mbarrier.arrive.expect_tx.shared::cta.b64 _, [%0], %1; }" ::"r"(fb), "r"(n < 2 ? 2 * STAGE : STAGE) : "memory");
                if (n < 2) {
                    tma3x(sb + OFF_H + n * STAGE, &maps.x, tile * 128 + n * 64, fb);
                    tma3x(dst, &maps.x, tile * 128 + n * 64 + 32, fb);
                } else {
                    if (n == 3) mbar_wait(BAR(1), 0);
                    const int ra = 112 * (n - 2);
                    tma2d(dst, &maps.qkv, 448 + 56 * sl, ra, fb);
                    tma2d(dst + HALF, &maps.qkv, 896 + 56 * sl, ra, fb);
                }
            }
            asm volatile("barrier.cluster.wait.aligned;" ::: "memory");
            cw_target = (ld_word(g_cw + sl * 32) & ~15u) + 16;
#pragma unroll 1
            for (int k = 0; k < 2; k++) {
                const int n = t128 + 32 * k;
                int m = n - 2 - (n > PACK);
                const bool packed = m >= 30 ? (m < 38 || m >= 52) : m >= 22;
                if (m >= 30) m -= 30;
                if (n == PACK) m = tile < 8 ? tile : tile + 14;
                const int rot = n < 8 ? 0 : pr;
                const int ra = 112 * kblk(rot, m & 3), rb = 112 * kblk(rot, 2 * m & 3), rc = 112 * kblk(rot, (2 * m + 1) & 3);
                int kind = 0, m0, m1, c0, c1, r0, r1;
                if (m < 4) { m0 = m1 = 1; c0 = 448 + 56 * sl; c1 = c0 + 448; r0 = r1 = ra; }
                else if (m < 8) { m0 = m1 = m < 6 ? 1 : 2; c0 = c1 = 56 * sl; r0 = rb; r1 = rc; }
                else if (m < 20) { m0 = 3; m1 = 4; c0 = c1 = 224 * sl + 32 * hr + 64 * ((m - 8) >> 2); r0 = r1 = ra; }
                else if (m < 22) { kind = 2; m0 = 5; m1 = 6; c0 = c1 = 224 * sl + (hr ? 0 : 192); r0 = rb; r1 = rc; }
                else { m0 = m1 = 7; c0 = c1 = 56 * (2 * ((pr + (m >> 1) - 10) & 3) + hr); r0 = 224 * (sl ^ (m & 1)); r1 = r0 + 112; }
                if (packed) { kind = 1; r0 = sl * 16 + (m < 8 ? m : m - 14); r1 = 0; }
                e0[0] = e0[1]; e1[0] = e1[1];
                e0[1] = kind | (m0 << 2) | (m1 << 6) | (c0 << 10) | (c1 << 21);
                e1[1] = r0 | (r1 << 16);
            }
        } else {
            const int j = t128 - 32;
            asm volatile("barrier.cluster.wait.aligned;" ::: "memory");
            uint2 wv[7];
            const int k = j < 56 ? j : 55, hh = k >= 28;
#pragma unroll
            for (int i = 0; i < 7; i++) wv[i] = __ldg(reinterpret_cast<const uint2*>(w_phi + (sl * 56 + k) * 28) + i);
#pragma unroll 1
            for (int i = j; i < 7168 / 16; i += 96) sts4(sb + OFF_WPHI + i * 16, 0, 0, 0, 0);
            bar_sync(5, 96);
            if (j < 56) {
                uint32_t a4[4];
#pragma unroll
                for (int q = 0; q < 4; q++) a4[q] = sb + OFF_WPHI + (4 * hh + q) * 128 + ((((k >> 3) ^ (4 * hh + q)) & 7) << 4) + (k & 7) * 2;
                FOR14(const uint32_t v = (t & 1) ? wv[t >> 1].y : wv[t >> 1].x;
                      asm volatile("{ .reg .b16 l, h; mov.b32 {l, h}, %2; st.shared.u16 [%0+%3], l; st.shared.u16 [%1+%3], h; }"
                                   ::"r"(a4[t >= 7 ? 2 : 0]), "r"(a4[t >= 7 ? 3 : 1]), "r"(v), "n"((t % 7) * 1024) : "memory"));
            }
            __syncwarp();
            fence_async();
            bar_arrive(1, 224);
            bar_arrive(9, 224);
            if (w == 1) {
                mbar_wait(BAR(2), 0);
                mbar_wait(BAR(2), 1);
                const int b = blockIdx.x;
                asm volatile(ELECT "cp.async.bulk.prefetch.L2.global [%0], %1; }" ::"l"(wg + b * 6272), "r"(12544) : "memory");
                asm volatile(ELECT "cp.async.bulk.prefetch.L2.global [%0], %1; }" ::"l"(wu + b * 6272), "r"(12544) : "memory");
                asm volatile(ELECT "cp.async.bulk.prefetch.L2.global [%0], %1; }" ::"l"(wd + b * 6272), "r"(12544) : "memory");
            }
        }
        uint32_t kseq = ld_word(g_c1 + (sl * 8 * 16 + tile) * 32);
        int slot = 0, ph = 0, n = NST;
#pragma unroll 1
        for (int layer = 0; layer < 3; layer++) {
            if (w == 0) {
                const int nend = layer == 0 ? 11 : (layer == 1 ? 42 : 63);
#pragma unroll 1
                for (; n < nend; n++) {
                const uint32_t w0 = __shfl_sync(0xffffffffu, n < 32 ? e0[0] : e0[1], n & 31), w1 = __shfl_sync(0xffffffffu, n < 32 ? e1[0] : e1[1], n & 31);
                const uint32_t dst = sb + slot * STAGE, fb = BAR(n == PACK ? B_PACK : slot);
                const CUtensorMap* m0 = &maps.x + ((w0 >> 2) & 15);
                const CUtensorMap* m1 = &maps.x + ((w0 >> 6) & 15);
                const int c0 = (w0 >> 10) & 2047, c1 = w0 >> 21, r0 = w1 & 0xffff, r1 = w1 >> 16;
                if (n == 25) {
                    int it = 0;
                    uint32_t v;
                    do { asm volatile("ld.acquire.gpu.global.u32 %0, [%1];" : "=r"(v) : "l"(g_cw + sl * 32) : "memory"); } while ((int)(v - cw_target) < 0 && ++it < 0x400000);
                    asm volatile("fence.proxy.async.global;" ::: "memory");
                    __syncwarp();
                }
                mbar_wait(BAR(B_EMPTY + slot), ph);
                __syncwarp();
                asm volatile(ELECT "mbarrier.arrive.expect_tx.shared::cta.b64 _, [%0], %1; }" ::"r"(fb), "r"(STAGE) : "memory");
                if ((w0 & 3) == 0) {
                    tma2d(dst, m0, c0, r0, fb);
                    tma2d(dst + HALF, m1, c1, r1, fb);
                } else if (w0 & 1) {
                    asm volatile(ELECT "cp.async.bulk.shared::cluster.global.mbarrier::complete_tx::bytes [%0], [%1], %2, [%3]; }"
                                 ::"r"(dst), "l"(reinterpret_cast<const char*>(g_wp) + (size_t)r0 * STAGE), "r"(STAGE), "r"(fb) : "memory");
                } else {
                    tma2d(dst, m0, c0, r0, fb); tma2d(dst + 7168, m0, c0, r1, fb);
                    tma2d(dst + HALF, m1, c0, r0, fb); tma2d(dst + HALF + 7168, m1, c0, r1, fb);
                }
                if (n == PACK) asm volatile(ELECT "mbarrier.arrive.shared::cta.b64 _, [%0]; }" ::"r"(BAR(slot)) : "memory");
                if (++slot == NST) { slot = 0; ph ^= 1; }
                }
            } else if (w == 1 && layer == 1) {
                constexpr int ps = PACK % NST;
                mbar_wait(BAR(B_PACK), 0);
                asm volatile("{ .reg .pred e; elect.sync _|e, 0xffffffff;\n"
                             "@e cp.async.bulk.global.shared::cta.bulk_group [%0], [%1], %2;\n"
                             "@e cp.async.bulk.commit_group;\n"
                             "@e cp.async.bulk.wait_group.read 0;\n"
                             "@e mbarrier.arrive.shared::cta.b64 _, [%3], 8;\n"
                             "@e cp.async.bulk.wait_group 0;\n"
                             "@e fence.proxy.async.global;\n"
                             "@e red.release.gpu.global.add.u32 [%4], 1; }"
                             ::"l"(reinterpret_cast<char*>(g_wp) + (size_t)(sl * 16 + tile) * STAGE), "r"(sb + ps * STAGE), "r"(STAGE), "r"(BAR(B_EMPTY + ps)), "l"(g_cw + sl * 32) : "memory");
                __syncwarp();
            }
            if (layer < 2) {
            const uint32_t tag = layer ^ 1;
            kseq++;
            bar_sync(7, 384);
            ASTAMP(0);
            if (tile < 15) {
                const int sq = lane >> 3, pk = 8 * w + (lane & (tile == 14 ? 3 : 7));
                uint32_t v[16];
                if (layer == 0) poll_cnt(g_c1 + ((sl * 8 + (w >> 1) * 4 + (tile >> 2)) * 16 + (lane & 15)) * 32, kseq);
                ASTAMP(1);
                poll4_kv<32>(v, g_kv1 + ((sl * 16 + tile) * 16 + 4 * sq) * 32 + pk, tag);
#pragma unroll
                for (int k = 0; k < 4; k++) {
                    float lo = (bf_lo(v[k]) + bf_lo(v[4 + k])) + (bf_lo(v[8 + k]) + bf_lo(v[12 + k]));
                    float hi = (bf_hi(v[k]) + bf_hi(v[4 + k])) + (bf_hi(v[8 + k]) + bf_hi(v[12 + k]));
                    lo += __shfl_xor_sync(0xffffffffu, lo, 8); hi += __shfl_xor_sync(0xffffffffu, hi, 8);
                    lo += __shfl_xor_sync(0xffffffffu, lo, 16); hi += __shfl_xor_sync(0xffffffffu, hi, 16);
                    v[k] = pack2(lo, hi);
                }
                if (sq == 0) st_pkt<0>(g_kv2 + sl * 512 + 32 * tile + pk, settag(v[0], tag), v[1], v[2], v[3]);
            }
            ASTAMP(2);
            {
                const int item = t128 < 112 ? t128 : 112 + (t128 & 3), d = item >> 1;
                const int cc = t128 < 112 ? 2 * (d >= 28) + (item & 1) : item - 112;
                const int r = t128 < 112 ? d : 56 + (cc >> 1) + 2 * ((t128 - 112) >> 2);
                uint32_t ra = sb + OFF_KVB + r * 128 + 4 * cc, rx = (r & 7) << 4;
                asm volatile("" : "+r"(ra), "+r"(rx));
                FOR14(asm volatile("st.shared.u32 [%0+%2], %1;" ::"r"((ra ^ 8) + (((t & 7) << 4) ^ rx)), "r"(0), "n"((t >> 3) * 8192) : "memory"));
                uint32_t v[16];
                asm volatile("" : "+r"(ra), "+r"(rx));
                poll4_kv<8>(v, g_kv2 + sl * 512 + (item >> 3) * 32 + (item & 7), tag);
                FOR14(asm volatile("st.shared.u32 [%0+%2], %1;" ::"r"(ra + (((t & 7) << 4) ^ rx)), "r"(v[t < 7 ? t : t + 1]), "n"((t >> 3) * 8192) : "memory"));
                fence_async();
            }
            bar_arrive(3, 384);
            ASTAMP(3);
            }
        }
    } else {
        asm volatile("setmaxnreg.inc.sync.aligned.u32 232;");
        int lane = fresh_tid() & 31;
#define g (lane >> 2)
#define c (lane & 3)
#define t128 (w * 32 + lane)
        const int wu = __shfl_sync(0xffffffffu, fresh_tid() >> 5, 0), w = wu & 3;
        const uint32_t xoff = __shfl_sync(0xffffffffu, (3 * PLANE + ((tile * 2 + wgi) * 8) * 512 + w * 128) * 16, 0);
        char* xu = reinterpret_cast<char*>(g_ex) + xoff;
#define FRESH() asm volatile("" : "+l"(xu), "+r"(lane))
#define xp0 (reinterpret_cast<uint4*>(xu) + lane)
        const uint32_t hbuf = sb + OFF_H + wgi * STAGE;
        uint32_t slot = 0, ph = 0, eb1 = 0, eb2 = 0, ackph = 0, rcvph = 0, gatph = 0, swp = 0;
        uint32_t ppid = 6;
#define cx(s) (reinterpret_cast<uint32_t*>(reinterpret_cast<uint4*>(xu) + PL(1) + 112 + (s) * 512))
#define stp (reinterpret_cast<uint4*>(xu) + g + PL(0) + 112)
        uint32_t seq = ld_word(cx(sl));
        uint32_t kseq = ld_word(g_c1 + ((sl * 8 + wu) * 16 + tile) * 32);
        uint32_t stag = ld_word(reinterpret_cast<const uint32_t*>(stp + sl * 512) + 3) & 1;
        asm volatile("barrier.cluster.wait.aligned;" ::: "memory");
        STAMP(1);
        uint32_t X[14];
        const uint32_t x0row = (w < 2 ? hbuf : sb + wgi * STAGE) + ((w & 1) * 16 + (lane & 15)) * 128;
        mbar_wait(BAR(wgi), 0);
        STAMP(51);
#pragma unroll
        for (int j = 0; j < 4; j++) {
            const int G = 7 * sl + min(2 * j + (lane >> 4), 6);
            uint32_t q2, q3;
            asm volatile("ldmatrix.sync.aligned.m8n8.x4.shared.b16 {%0,%1,%2,%3}, [%4];" : "=r"(X[4 * j]), "=r"(X[4 * j + 1]), "=r"(q2), "=r"(q3)
                         : "r"(x0row + (G >> 3) * 4096 + (((G ^ lane) & 7) << 4)) : "memory");
            if (j < 3) { X[(4 * j + 2) % 14] = q2; X[(4 * j + 3) % 14] = q3; }
        }
#define PUSH_SLICE(W)                                                                          \
    {                                                                                          \
        if (t128 == 0) mbar_expect_tx(BAR(B_RECV + wgi), 7168);                                \
        PUSH_BEGIN();                                                                          \
        const uint32_t ra = mapa(hbuf + 24576 + t128 * 16, hr ^ 1), rb = mapa(sb + OFF_XR + wgi * 3072, hr ^ 1), rbar = mapa(BAR(B_RECV + wgi), hr ^ 1); \
        st_async4(ra, W[0], W[1], W[2], W[3], rbar);                                           \
        st_async4(ra + 2048, W[4], W[5], W[6], W[7], rbar);                                    \
        st_async4(rb + t128 * 16, W[8], W[9], W[10], W[11], rbar);                             \
        asm volatile("st.async.weak.shared::cluster.mbarrier::complete_tx::bytes.v2.b32 [%0], {%1,%2}, [%3];" ::"r"(rb + 2048 + t128 * 8), "r"(W[12]), "r"(W[13]), "r"(rbar) : "memory"); \
    }
#define PULL_SLICE(W)                                                                          \
    {                                                                                          \
        uint32_t t0, t1;                                                                       \
        mbar_wait(BAR(B_RECV + wgi), rcvph);                                                   \
        rcvph ^= 1;                                                                            \
        lds4(&A[1][0], hbuf + 24576 + t128 * 16);                                              \
        lds4(&A[1][4], hbuf + 26624 + t128 * 16);                                              \
        lds4(&A[1][8], sb + OFF_XR + wgi * 3072 + t128 * 16);                                  \
        asm volatile("ld.shared.v2.u32 {%0,%1}, [%2];" : "=r"(t0), "=r"(t1) : "r"(sb + OFF_XR + wgi * 3072 + 2048 + t128 * 8) : "memory"); \
        _Pragma("unroll") for (int i = 0; i < 12; i++) A[0][i] = (i & 3) ? W[i] : W[i] & ~1u;  \
        A[1][0] &= ~1u; A[1][4] &= ~1u; A[1][8] &= ~1u;                                        \
        A[0][12] = (hr ? t0 : W[12]) & ~1u; A[0][13] = hr ? t1 : W[13];                        \
        A[1][12] = (hr ? W[12] : t0) & ~1u; A[1][13] = hr ? W[13] : t1;                        \
        asm volatile("" : RW4(A[0], 0), RW4(A[0], 4), RW4(A[0], 8), RW2(A[0], 12), RW4(A[1], 0), RW4(A[1], 4), RW4(A[1], 8), RW2(A[1], 12)); \
        swp = hr * 448;                                                                        \
    }
#define SWB(b, t, db, sh) ((b) == 0 && (t) < 6 ? ((t) < 3 ? db##p : db##m) : db)
#define DECL_DB(b, MK, lbo, sh) const uint64_t db = MK(0, lbo, R_ADJ), dbp = (b) == 0 ? MK(0, lbo, R_ADJ + (swp >> (sh))) : db, dbm = (b) == 0 ? MK(0, lbo, R_ADJ - (swp >> (sh))) : db;
#define EARLY 1
#define EARLYK 1
#define PPB 2
#define PP_WAIT() if (wgi == 1) { bar_sync(ppid, 256); ppid ^= 14; }
#define PP_GO() if (wgi == 0) { bar_arrive(ppid, 256); ppid ^= 14; }
#define GAT_ISSUE(base)                                                                        \
    {                                                                                          \
        const char* gs = xu + ((base) + kblk(pr, GB) * 1024) * 16; \
        const uint32_t gd = hbuf + w * 3584, gb = BAR(B_GAT + wu);                     \
        asm volatile("{ .reg .pred e; elect.sync _|e, 0xffffffff;\n"                           \
                     "@e mbarrier.arrive.expect_tx.shared::cta.b64 _, [%2], 3584;\n"           \
                     "@e cp.async.bulk.shared::cluster.global.mbarrier::complete_tx::bytes [%0], [%1], 1792, [%2];\n" \
                     "@e cp.async.bulk.shared::cluster.global.mbarrier::complete_tx::bytes [%0+1792], [%1+8192], 1792, [%2]; }" \
                     ::"r"(gd), "l"(gs), "r"(gb) : "memory");                                  \
        __syncwarp();                                                                          \
    }
#define GAT_FETCH()                                                                            \
    {                                                                                          \
        mbar_wait(BAR(B_GAT + wu), gatph);                                             \
        gatph ^= 1;                                                                            \
        const uint32_t ga = hbuf + w * 3584 + lane * 16;                                       \
        _Pragma("unroll") for (int s2 = 0; s2 < 2; s2++) {                                     \
            lds4(&A[2 * GB + s2][0], ga + s2 * 1792); lds4(&A[2 * GB + s2][4], ga + s2 * 1792 + 512); lds4(&A[2 * GB + s2][8], ga + s2 * 1792 + 1024); \
            asm volatile("ld.shared.v2.u32 {%0,%1}, [%2];" : "=r"(A[2 * GB + s2][12]), "=r"(A[2 * GB + s2][13]) : "r"(ga - lane * 8 + s2 * 1792 + 1536) : "memory"); \
        }                                                                                      \
    }
#define PT 3
#define PREP(b, t, remote)                                                                     \
    if constexpr ((b) < 3 && (t) == PT) {                                                      \
        wg_commit();                                                                           \
        STAMP(80 + 8 * (step & 1) + 2 * (b));                                                  \
        if constexpr ((b) == 0 && B2L == 1) { if (remote) blk_load<2>(A, BLK(xsrc, 2), lane); } \
        if constexpr ((b) == 1 && B3L == 1) { if (remote) blk_load<3>(A, BLK(xsrc, 3), lane); } \
        if constexpr ((b) == 0) { if (remote) GAT_FETCH() }                   \
        if (remote) blk_check<((b) + 1) & 3>(A, BLK(xsrc, (b) + 1), lane, xtag);               \
        STAMP(81 + 8 * (step & 1) + 2 * (b));                                                  \
        if constexpr ((b) == 0 && B2L == 2) { if (remote) blk_load<2>(A, BLK(xsrc, 2), lane); } \
        if constexpr ((b) == (B3L == 2) && B3L != 1) { if (remote) blk_load<3>(A, BLK(xsrc, 3), lane); } \
        normalize<((b) + 1) & 3>(A, k0, k1);                                                   \
        asm volatile("" : RW4(A[(2 * (b) + 2) & 7], 0), RW4(A[(2 * (b) + 2) & 7], 4), RW4(A[(2 * (b) + 2) & 7], 8), RW2(A[(2 * (b) + 2) & 7], 12), \
                          RW4(A[(2 * (b) + 3) & 7], 0), RW4(A[(2 * (b) + 3) & 7], 4), RW4(A[(2 * (b) + 3) & 7], 8), RW2(A[(2 * (b) + 3) & 7], 12)); \
        wg_fence();                                                                            \
    }                                                                                          \
    if constexpr ((b) == 3 && ((t) == 0 || (t) == 6)) { STAMP(86 + 8 * (step & 1) + (t) / 6); }
#define X0_BLOCK(b)                                                                            \
    { const int rr = lane & 7, hi = lane >> 4;                                                 \
    const uint32_t rowa = (w < 2 ? hbuf : sb + wgi * STAGE) + ((w & 1) * 16 + (lane & 15)) * 128; \
    FOR7(constexpr int G = 14 * (b) + (t < 3 ? 2 * t : (t < 6 ? 2 * t + 1 : 6));               \
         uint32_t q0, q1, q2, q3;                                                              \
         const uint32_t ad = t < 6 ? rowa + (((((G & 7) + hi) ^ rr) & 7) << 4) + ((G & 7) == 7 ? hi * 4096 : 0) : rowa + ((G + 7 * hi) >> 3) * 4096 + ((((G + 7 * hi) ^ rr) & 7) << 4); \
         asm volatile("ldmatrix.sync.aligned.m8n8.x4.shared.b16 {%0,%1,%2,%3}, [%4+%5];" : "=r"(q0), "=r"(q1), "=r"(q2), "=r"(q3) \
                      : "r"(ad), "n"(t < 6 ? (G >> 3) * 4096 : 0) : "memory");                 \
         if (t < 3) { A[2 * (b)][4 * t] = q0; A[2 * (b)][4 * t + 1] = q1; A[2 * (b)][4 * t + 2] = q2; A[2 * (b)][4 * t + 3] = q3; } \
         else if (t < 6) { A[2 * (b) + 1][(4 * t - 12) & 15] = q0; A[2 * (b) + 1][((4 * t - 12) & 15) + 1] = q1; A[2 * (b) + 1][((4 * t - 12) & 15) + 2] = q2; A[2 * (b) + 1][((4 * t - 12) & 15) + 3] = q3; } \
         else { A[2 * (b)][12] = q0; A[2 * (b)][13] = q1; A[2 * (b) + 1][12] = q2; A[2 * (b) + 1][13] = q3; }); }
#define BLK(base, b) ((base) + kblk(pr, b) * 1024)

#pragma unroll 1
        for (int step = 0; step < 4; step++) {
            FRESH();
            const uint32_t tag = (step >> 1) ^ 1;
            const int so = (step >> 1) * 24 + (step & 1) * 12;
            (void)so;
            uint32_t A[8][14];
            uint4* const xsrc = xp0 + ((step & 1) ? PL(2) : PL(0));
            const uint32_t xtag = (step & 1) ? tag : ((seq >> 3) & 1) ^ 1;
            uint32_t xbits;
            {
                float st[4];
                slice_stats(X, st);
                stag ^= 1;
                xbits = x_bits(X);
                tag_slice(X, xtag);
                if (step) send_slice<0>(xsrc + sl * 512, lane, X);
                if (c == 0) st_pkt<0>(stp + sl * 512, __float_as_uint(st[0]), __float_as_uint(st[1]), __float_as_uint(st[2]), settag(__float_as_uint(st[3]), stag));
            }
            STAMP(2 + so);
            uint32_t sv[8];
            if (step == 0) {
                X0_BLOCK(0) X0_BLOCK(1) X0_BLOCK(3)
                mbar_wait(BAR(wgi ^ 1), 0);
                R_NEXT();
                R_NEXT();
                stat_load(sv, stp + c * 1024);
                stat_check(sv, stp + c * 1024, stag);
                STAMP(52 + step);
            } else {
                kill<14>(A[2]); kill<14>(A[3]); kill<14>(A[6]); kill<14>(A[7]);
                PUSH_SLICE(X)
                stat_load(sv, stp + c * 1024);
                PULL_SLICE(X)
                stat_check(sv, stp + c * 1024, stag);
                STAMP(52 + step);
                GAT_ISSUE((step & 1) ? PL(2) : PL(0))
            }
            LnCoef k0, k1;
            {
                k0 = ln_coef(__uint_as_float(sv[0]) + __uint_as_float(sv[4]), __uint_as_float(sv[1]) + __uint_as_float(sv[5]));
                k1 = ln_coef(__uint_as_float(sv[2]) + __uint_as_float(sv[6]), __uint_as_float(sv[3] & ~1u) + __uint_as_float(sv[7] & ~1u));
            }
            if (step) {
                if (B2L == 0) blk_load<2>(A, BLK(xsrc, 2) + ((k0.hi & k1.hi) == 0xffffffffu), lane);
                else { kill<14>(A[4]); kill<14>(A[5]); }
            } else {
                X0_BLOCK(2)
                R_RELEASE(2);
            }
            STAMP(3 + so);
            GSTAMP(76 + step);

            if ((step & 1) == 0) {
                float tq[28];
                {
                    float av[28];
#define KV_BLOCK(b)                                                                           \
    if (GB == 2 && (b) == 1 && step) GAT_FETCH()                                                         \
    if ((b) == 2) PUSH_ACK();                                                                 \
    if (QE && (b) == 1) R_RELEASE(2);                                                         \
    if (QE && (b) == 2) { wg_wait<2>(); R_RELEASE(2); }                                       \
    R_WAIT();                                                                                 \
    if ((b) == PPK) { PP_WAIT() }                                                             \
    { DECL_DB(b, BASE128, 16, 0)                                                              \
    wg_fence();                                                                               \
    FOR7(mma_rs56<1, D128(0, t)>(tq, AQ(A, b, t), (b) + t > 0, SWB(b, t, db, 0));             \
         mma_rs56<1, D128(HALF, t)>(av, AQ(A, b, t), (b) + t > 0, SWB(b, t, db, 0));          \
         PREP(b, t, step)); }                                                                 \
    wg_commit();                                                                              \
    if ((b) == 3 && PPK < 4) { PP_GO() }                                                      \
    R_NEXT();
                    normalize<0>(A, k0, k1);
                    KV_BLOCK(0) KV_BLOCK(1) KV_BLOCK(2) KV_BLOCK(3)
                    wg_wait<0>();
                    if (lane < (QE ? 3 : NST)) mbar_arrive(BAR(B_EMPTY + (slot + NST - 1 - lane) % NST));
                    STAMP(4 + so);
                    WSUM(80 + 7 * (step >> 1));
                    const int m = lane >> 3, rr = lane & 7;
                    const uint32_t rowa = hbuf + 16384 + (w * 16 + rr + 8 * (m & 1)) * 128;
                    const uint32_t one = c == 0 ? 0x00003f80u : 0u;
                    if (step == 0) { bar_sync(wgi ? 9 : 1, 224); }
#pragma unroll
                    for (int j = 0; j < 4; j++) {
                        const uint32_t a = rowa + (((2 * j + (m >> 1)) ^ rr) << 4);
                        if (j < 3) stsm4(a, pack2(av[8 * j], av[8 * j + 1]), pack2(av[8 * j + 2], av[8 * j + 3]), pack2(av[8 * j + 4], av[8 * j + 5]), pack2(av[8 * j + 6], av[8 * j + 7]));
                        else stsm4(a, pack2(av[24], av[25]), pack2(av[26], av[27]), one, one);
                    }
                }
                uint32_t PH[28];
                int it = 1;
#pragma unroll 1
                do {
                    float pp[28];
                    phi_gemm(tq, pp);
                    dual_softmax(pp, PH);
                    if (((trips >> (it + 1)) & 1) == 0) continue;
                    {
                        const int m = lane >> 3, rr = lane & 7;
                        const uint32_t rowa = hbuf + (w * 16 + rr + 8 * (m & 1)) * 128;
#pragma unroll
                        for (int j = 0; j < 7; j++) {
                            const int cg = 2 * j + (m >> 1), hi = cg >= 7;
                            stsm4(rowa + hi * 8192 + (((cg - 7 * hi) ^ rr) << 4), PH[4 * j], PH[4 * j + 1], PH[4 * j + 2], PH[4 * j + 3]);
                        }
                    }
                    fence_async();
                    STAMP(5 + so);
#define Q_STAGE(b0)                                                                           \
    R_WAIT();                                                                                 \
    { DECL_DB(b0, BASE128, 16, 0)                                                             \
    wg_fence();                                                                               \
    FOR7(mma_rs56<1, D128(0, t)>(tq, AQ(A, b0, t), (b0) + t > 0, SWB(b0, t, db, 0)));         \
    FOR7(mma_rs56<1, D128(HALF, t)>(tq, AQ(A, (b0) + 1, t), 1, db)); }                        \
    wg_commit();                                                                              \
    R_NEXT();
                    if (QE && wgi == 0) { kill<28>(tq); Q_STAGE(0) Q_STAGE(2) wg_wait<1>(); R_RELEASE(2); wg_wait<0>(); R_RELEASE(1); }
                    bar_sync(2, 256);
                    float kv[28];
                    const uint64_t da = BASE128(OFF_H + 16384, 16, 0), dbk = BASE128(OFF_H, 16, wgi * 512);
                    wg_fence();
                    FOR8(constexpr uint64_t o = ((t >> 2) * STAGE + (t & 3) * 2048) >> 4; mma_ss56_tt<o, o>(kv, t > 0, da, dbk));
                    wg_commit();
                    wg_wait<0>();
#pragma unroll
                    for (int hf = 0; hf < 2; hf++) {
                        const int d = 16 * w + g + 8 * hf;
                        if ((d < 56 && (d >= 28) == (c >= 2)) || d == 56) {
                            const int item = d < 56 ? 2 * d + (c & 1) : 112 + c;
                            uint4* dst = g_kv1 + ((sl * 16 + (item >> 3)) * 16 + tile) * 32 + wgi * 16 + (item & 7);
#define KVW(i) pack2(kv[4 * (i) + 2 * hf], kv[4 * (i) + 2 * hf + 1])
                            st_pkt<0>(dst, settag(KVW(0), tag), KVW(1), KVW(2), KVW(3));
                            st_pkt<8>(dst, settag(KVW(4), tag), KVW(5), KVW(6), 0u);
                        }
                    }
                    __syncwarp();
                    kseq++;
                    if (lane == 0) st_word(g_c1 + ((sl * 8 + wu) * 16 + tile) * 32, kseq);
                    bar_arrive(7, 384);
                    STAMP(6 + so);
                    if (!QE || wgi == 1) { kill<28>(tq); Q_STAGE(0) Q_STAGE(2) wg_wait<1>(); R_RELEASE(2); wg_wait<0>(); R_RELEASE(1); }
                    STAMP(7 + so);
                    kill<28>(PH);
                } while (((trips >> (++it)) & 1));
                STAMP(8 + so);
                FRESH();
                if (step) {
                    slice_load<PL(0)>(X, xp0 + sl * 512, lane);
                } else {
                    const uint32_t* xp = reinterpret_cast<const uint32_t*>(x_in + (size_t)(tile * 128 + wu * 16 + g) * 448 + 56 * sl + 2 * c);
#pragma unroll
                    for (int i = 0; i < 7; i++) { X[2 * i] = __ldg(xp + 4 * i); X[2 * i + 1] = __ldg(xp + 4 * i + 8 * 224); }
                }
                bar_sync(3, 384);
                STAMP(9 + so);
                const uint4* const osrc = xp0 + PL(1);
                {
                    float nm[32];
                    const uint64_t db = BASE128(OFF_KVB, 16, 0);
                    wg_fence();
                    FOR7(mma_rs64<0, ((t >> 2) * 8192 + (t & 3) * 32) / 16>(nm, PH[4 * t], PH[4 * t + 1], PH[4 * t + 2], PH[4 * t + 3], t > 0, db));
                    wg_commit();
                    wg_wait<0>();
                    const float i00 = rcp(nm[28] + 1e-6f), i01 = rcp(nm[29] + 1e-6f), i10 = rcp(nm[30] + 1e-6f), i11 = rcp(nm[31] + 1e-6f);
                    const float m0 = c >= 2 ? i01 : i00, m1 = c >= 2 ? i11 : i10;
                    uint32_t O[14];
#pragma unroll
                    for (int i = 0; i < 7; i++) {
                        const float f0 = i < 3 ? i00 : (i > 3 ? i01 : m0), f1 = i < 3 ? i10 : (i > 3 ? i11 : m1);
                        O[2 * i] = pack2(nm[4 * i] * f0, nm[4 * i + 1] * f0);
                        O[2 * i + 1] = pack2(nm[4 * i + 2] * f1, nm[4 * i + 3] * f1);
                    }
                    if (OST) { PP_WAIT() }
                    tag_slice(O, tag);
                    send_slice<PL(1)>(xp0 + sl * 512, lane, O);
                    seq++;
                    if (lane == 0) st_word(cx(sl), seq);
                    STAMP(10 + so);
                    PUSH_SLICE(O)
                    if (OST == 1) { PP_GO() }
                    const uint32_t cv = ld_word(cx(lane & 7));
                    PULL_SLICE(O)
                    check_cnt(cv, cx(lane & 7), seq);
                    if (OST == 2) { PP_GO() }
                    STAMP(56 + (step >> 1));
                    GAT_ISSUE(PL(1))
                    blk_load<3 - GB>(A, BLK(osrc, 3 - GB), lane);
                }
                float ao[28];
#define WO_BLOCK(b)                                                                           \
    if ((b) > 0) blk_check<b>(A, BLK(osrc, b), lane, tag);                                    \
    if (((b) & 1) == 0) R_WAIT();                                                             \
    { DECL_DB(b, BASE128, 16, 0)                                                              \
    wg_fence();                                                                               \
    FOR7(mma_rs56<1, D128(((b) & 1) * HALF, t)>(ao, AQ(A, b, t), (b) + t > 0, SWB(b, t, db, 0))); } \
    wg_commit();                                                                              \
    if ((b) & 1) R_NEXT();
                WO_BLOCK(0)
                STAMP(11 + so);
                blk_load<3>(A, BLK(osrc, 3), lane);
                if (GB == 1) GAT_FETCH()
                WO_BLOCK(1)
                if (GB == 2) GAT_FETCH()
                WO_BLOCK(2)
                PUSH_ACK();
                WO_BLOCK(3)
                wg_wait<0>();
                if (EARLY >= 1) R_RELEASE(2);
                if (EARLY >= 2) R_RELEASE(1);
                STAMP(12 + so);
                WSUM(86 + 7 * (step >> 1));
                x_fix(X, xbits);
#pragma unroll
                for (int i = 0; i < 14; i++) X[i] = pack2(bf_lo(X[i]) + ao[2 * i], bf_hi(X[i]) + ao[2 * i + 1]);
            } else {
                uint32_t H[56];
                float ag[64];
#define F1_EPI(dst, ng, ag)                                                                    \
    _Pragma("unroll") for (int i = 0; i < 2 * (ng); i++)                                       \
        (dst)[i] = pack2(geglu(ag[2 * i], ag[4 * (ng) + 2 * i]), geglu(ag[2 * i + 1], ag[4 * (ng) + 2 * i + 1]));
#define H_PUSH(h0, off) st_async4(rem_h + (off), H[h0], H[(h0) + 1], H[(h0) + 2], H[(h0) + 3], mapa(BAR(B_RECV2 + wgi), hr ^ 1));
#define F1_BLOCK(b, first)                                                                     \
    if ((first) && (b) < 2 && (b) >= EARLY) R_RELEASE(2);                                      \
    if (GB == 2 && (first) && (b) == 1) GAT_FETCH()                                                       \
    if ((first) && (b) == 2) PUSH_ACK();                                                       \
    R_WAIT();                                                                                  \
    if ((b) == ((first) ? PPF : PPB)) { PP_WAIT() }                                            \
    { DECL_DB(b, BASE128, HALF, 0)                                                             \
    wg_fence();                                                                                \
    FOR7(mma_rs128<1, D128(0, t)>(ag, AQ(A, b, t), (b) + t > 0, SWB(b, t, db, 0));             \
         if constexpr (first) { PREP(b, t, true) }); }                                         \
    wg_commit();                                                                               \
    if ((b) == 3) { PP_GO() }                                                                  \
    if ((b) > 0) { wg_wait<1>(); R_RELEASE(1); }       \
    R_NEXT();
                normalize<0>(A, k0, k1);
                F1_BLOCK(0, true) F1_BLOCK(1, true) F1_BLOCK(2, true) F1_BLOCK(3, true)
                if (t128 == 0) { mbar_expect_tx(BAR(B_RECV + wgi), 16384); mbar_expect_tx(BAR(B_RECV2 + wgi), 12288); }
                PUSH_BEGIN();
                wg_wait<0>();
                R_RELEASE(1);
                int p = 0;
#pragma unroll 1
                do {
                    STAMP(68 + p);
                    F1_EPI(H + 32, 8, ag)
                    STAMP(4 + p + so);
                    WSUM(81 + p + 7 * (step >> 1));
                    if (((trips >> (p + 1)) & 1) == 0) continue;
                    {
                        const uint32_t pk = (p ? hbuf + 16384 : sb + OFF_KVB + wgi * 8192) + w * 2048;
#pragma unroll
                        for (int k = 0; k < 4; k++) sts4(pk + k * 512 + lane * 16, H[32 + 4 * k], H[33 + 4 * k], H[34 + 4 * k], H[35 + 4 * k]);
                        fence_async();
                        __syncwarp();
                        asm volatile(ELECT "cp.async.bulk.shared::cluster.shared::cta.mbarrier::complete_tx::bytes [%0], [%1], 2048, [%2]; }"
                                     ::"r"(mapa(hbuf + p * 8192 + w * 2048, hr ^ 1)), "r"(pk), "r"(mapa(BAR(B_RECV + wgi), hr ^ 1)) : "memory");
                    }
                    if (step == 1 && p == PKP) R_NEXT();
                    kill<64>(ag);
                    F1_BLOCK(0, false) F1_BLOCK(1, false) F1_BLOCK(2, false) F1_BLOCK(3, false)
                    wg_wait<0>();
                    R_RELEASE(1);
                    kill<16>(H + 32);
                } while (((trips >> (++p)) & 1));
#pragma unroll
                for (int k = 0; k < 4; k++) lds4(H + 16 + 4 * k, hbuf + 16384 + w * 2048 + k * 512 + lane * 16);
                __syncwarp();
                if (lane == 0) asm volatile("mbarrier.arrive.shared::cluster.b64 _, [%0];" ::"r"(mapa(BAR(B_ACK2 + wgi), hr ^ 1)) : "memory");
                const uint32_t rem_h = mapa(hbuf + w * 2048 + lane * 16, hr ^ 1);
#define F1_LAST(b0)                                                                            \
    R_WAIT();                                                                                  \
    if (b0) { PP_WAIT() }                                                                      \
    { DECL_DB(b0, BASE64, HALF, 1)                                                             \
    wg_fence();                                                                                \
    FOR7(mma_rs64<1, D64(0, t)>(al, AQ(A, b0, t), (b0) + t > 0, SWB(b0, t, db, 1)));           \
    FOR7(mma_rs64<1, D64(7168, t)>(al, AQ(A, (b0) + 1, t), 1, db)); }                          \
    wg_commit();                                                                               \
    if (b0) { PP_GO() }                                                                        \
    R_NEXT();
                float al[32];
                F1_LAST(0)
                mbar_wait(BAR(B_RECV + wgi), rcvph);
                rcvph ^= 1;
                mbar_wait(BAR(B_ACK2 + wgi), step >> 1);
                H_PUSH(32, 16384) H_PUSH(36, 16896)
                F1_LAST(2)
                H_PUSH(40, 17408) H_PUSH(44, 17920)
                wg_wait<1>();
                R_RELEASE(2);
                wg_wait<0>();
                R_RELEASE(1);
                uint32_t HP[56];
#pragma unroll
                for (int k = 0; k < 4; k++) lds4(H + 4 * k, sb + OFF_KVB + wgi * 8192 + w * 2048 + k * 512 + lane * 16);
#pragma unroll
                for (int t = 0; t < 8; t++) lds4(HP + 4 * t, hbuf + (t >> 2) * 8192 + w * 2048 + (t & 3) * 512 + lane * 16);
                F1_EPI(H + 48, 4, al)
                H_PUSH(48, 24576 - w * 1024) H_PUSH(52, 25088 - w * 1024)
                STAMP(7 + so);
                WSUM(84 + 7 * (step >> 1));
                FRESH();
                float acc[28];
                const uint32_t roA = hr ? 256u : 0u, roB = hr ? (uint32_t)-1536 : 0u;
                const uint32_t rpA = hr ? 0u : 256u, rpB = hr ? 0u : (uint32_t)-1536;
                float res[28];
                uint32_t v0[14], v1[14], P[14];
                const uint4* ps = xp0 + sl * 512;
#define F2_OWN_A()                                                                             \
    R_WAIT();                                                                                  \
    d0 = BASE128(0, 16, R_ADJ + roA); d1 = BASE128(0, 16, R_ADJ + roB);                        \
    wg_fence();                                                                                \
    FOR14(if constexpr (t < OT) mma_rs56<1, t * 128>(acc, H[4 * t], H[4 * t + 1], H[4 * t + 2], H[4 * t + 3], t > 0, d0)); \
    wg_commit();
#define F2_OWN_B()                                                                             \
    wg_fence();                                                                                \
    FOR14(if constexpr (t >= OT) mma_rs56<1, t * 128>(acc, H[4 * t], H[4 * t + 1], H[4 * t + 2], H[4 * t + 3], 1, t < 12 ? d0 : d1)); \
    wg_commit();                                                                               \
    R_NEXT();
#define F2_PEER()                                                                              \
    R_WAIT();                                                                                  \
    if (F2PP) { PP_WAIT() }                                                                    \
    d0 = BASE128(0, 16, R_ADJ + rpA); d1 = BASE128(0, 16, R_ADJ + rpB);                        \
    wg_fence();                                                                                \
    FOR14(mma_rs56<1, t * 128>(acc, HP[4 * t], HP[4 * t + 1], HP[4 * t + 2], HP[4 * t + 3], 1, t < 12 ? d0 : d1)); \
    wg_commit();                                                                               \
    if (F2PP) { PP_GO() }                                                                      \
    R_NEXT();
#define F2_TURN(u)                                                                             \
    wg_wait<1>();                                                                              \
    if ((u) < 2 || TDEF < 2) R_RELEASE(2);                                                     \
    wg_wait<0>();                                                                              \
    if ((u) < 2 || TDEF < 1) R_RELEASE(1);                                                     \
    _Pragma("unroll") for (int i = 0; i < 14; i++) P[i] = pack2(acc[2 * i], acc[2 * i + 1]);   \
    tag_slice(P, tag);                                                                         \
    asm volatile("" : RW4(P, 0), RW4(P, 4), RW4(P, 8), RW2(P, 12));                            \
    kill<28>(acc);                                                                             \
    F2_OWN_A()                                                                                 \
    if ((u) == 2) { slice_load<PL(3)>(v0, ps, lane); slice_load<PL(4)>(v1, ps, lane); } \
    send_slice<PL(3 + (u))>(xp0 + (2 * ((pr + (u) + 1) & 3) + hr) * 512, lane, P);             \
    seq++;                                                                                     \
    if (lane == 0) st_word(cx(sl), seq);                                                       \
    __syncwarp();                                                                              \
    STAMP(8 + (u) + so);                                                                       \
    F2_OWN_B()
                uint64_t d0, d1;
                F2_OWN_A()
                F2_OWN_B()
                R_WAIT();
                d0 = BASE128(0, 16, R_ADJ + rpA); d1 = BASE128(0, 16, R_ADJ + rpB);
                wg_fence();
                FOR8(mma_rs56<1, t * 128>(acc, HP[4 * t], HP[4 * t + 1], HP[4 * t + 2], HP[4 * t + 3], 1, d0));
                wg_commit();
                mbar_wait(BAR(B_RECV2 + wgi), step >> 1);
#pragma unroll
                for (int k = 0; k < 4; k++) lds4(HP + 32 + 4 * k, hbuf + 16384 + w * 2048 + k * 512 + lane * 16);
                lds4(HP + 48, hbuf + 24576 + w * 1024 + lane * 16);
                lds4(HP + 52, hbuf + 25088 + w * 1024 + lane * 16);
                if (step == 1) PUSH_ACK();
                wg_fence();
                FOR14(if constexpr (t >= 8) mma_rs56<1, t * 128>(acc, HP[4 * t], HP[4 * t + 1], HP[4 * t + 2], HP[4 * t + 3], 1, t < 12 ? d0 : d1));
                wg_commit();
                R_NEXT();
                F2_TURN(0)
                F2_PEER()
                F2_TURN(1)
                F2_PEER()
                F2_TURN(2)
                STAMP(64 + 8 * (step >> 1));
                slice_check<PL(3)>(v0, ps, lane, tag);
                slice_check<PL(4)>(v1, ps, lane, tag);
#pragma unroll
                for (int i = 0; i < 14; i++) { res[2 * i] = bf_lo(v0[i]) + bf_lo(v1[i]); res[2 * i + 1] = bf_hi(v0[i]) + bf_hi(v1[i]); }
                slice_load<PL(2)>(X, ps, lane);
                STAMP(65 + 8 * (step >> 1));
                F2_PEER()
                STAMP(66 + 8 * (step >> 1));
                poll_cnt(cx(2 * ((pr + 1) & 3) + hr), seq);
                STAMP(67 + 8 * (step >> 1));
                slice_load<PL(5)>(v0, ps, lane);
                x_fix(X, xbits);
                slice_check<PL(5)>(v0, ps, lane, tag);
                if (lane < TDEF) mbar_arrive(BAR(B_EMPTY + (slot + NST - 3 - lane) % NST));
#pragma unroll
                for (int i = 0; i < 14; i++) { res[2 * i] += bf_lo(v0[i]); res[2 * i + 1] += bf_hi(v0[i]); }
                STAMP(11 + so);
                wg_wait<0>();
                if (EARLYK >= 1) R_RELEASE(2);
                STAMP(12 + so);
                WSUM(85 + 7 * (step >> 1));
#pragma unroll
                for (int i = 0; i < 14; i++) X[i] = pack2(fmaf(res[2 * i] + acc[2 * i], 0.5f, bf_lo(X[i])), fmaf(res[2 * i + 1] + acc[2 * i + 1], 0.5f, bf_hi(X[i])));
            }
        }
        {
            const int m = lane >> 3, rr = lane & 7;
            const uint32_t ob = hbuf + w * 2048, rowa = ob + (rr + 8 * (m & 1)) * 112 + (m >> 1) * 16;
#pragma unroll
            for (int j = 0; j < 3; j++) stsm4(rowa + 32 * j, X[4 * j], X[4 * j + 1], X[4 * j + 2], X[4 * j + 3]);
            asm volatile("stmatrix.sync.aligned.m8n8.x2.shared.b16 [%0], {%1,%2};" ::"r"(ob + (rr + 8 * (m & 1)) * 112 + 96), "r"(X[12]), "r"(X[13]) : "memory");
            fence_async();
            __syncwarp();
            if (lane == 0) {
                asm volatile("cp.async.bulk.tensor.2d.global.shared::cta.bulk_group [%0, {%2, %3}], [%1];" ::"l"(&maps.out), "r"(ob), "r"(56 * sl), "r"(tile * 128 + wu * 16) : "memory");
                asm volatile("cp.async.bulk.commit_group;" ::: "memory");
                asm volatile("cp.async.bulk.wait_group.read 0;" ::: "memory");
            }
        }
        STAMP(50);
        GSTAMP(61);
        PDUMP();
    }
}

#undef g
#undef c
#undef t128

typedef CUresult (*EncodeFn)(CUtensorMap*, CUtensorMapDataType, cuuint32_t, void*, const cuuint64_t*, const cuuint64_t*, const cuuint32_t*,
                             const cuuint32_t*, CUtensorMapInterleave, CUtensorMapSwizzle, CUtensorMapL2promotion, CUtensorMapFloatOOBfill);

static void make_map(EncodeFn enc, CUtensorMap* m, const void* p, uint64_t cols, uint64_t rows, uint32_t bc, uint32_t br, CUtensorMapSwizzle sw) {
    cuuint64_t gd[2] = {cols, rows};
    cuuint64_t gs[1] = {cols * 2};
    cuuint32_t bd[2] = {bc, br};
    cuuint32_t es[2] = {1, 1};
    enc(m, CU_TENSOR_MAP_DATA_TYPE_BFLOAT16, 2, const_cast<void*>(p), gd, gs, bd, es, CU_TENSOR_MAP_INTERLEAVE_NONE, sw,
        CU_TENSOR_MAP_L2_PROMOTION_L2_128B, CU_TENSOR_MAP_FLOAT_OOB_FILL_NONE);
}

extern "C" void kernel_launch(void* const* d_in, const int* in_sizes, int n_in, void* d_out, int out_size) {
    (void)in_sizes; (void)n_in; (void)out_size;
    static EncodeFn enc = nullptr;
    static Scratch* scratch = nullptr;
    if (!enc) {
        void* fn = nullptr;
        cudaDriverEntryPointQueryResult qr;
        cudaGetDriverEntryPoint("cuTensorMapEncodeTiled", &fn, cudaEnableDefault, &qr);
        enc = (EncodeFn)fn;
        cudaGetSymbolAddress((void**)&scratch, g_scratch);
        cudaFuncSetAttribute(fused_kernel, cudaFuncAttributeMaxDynamicSharedMemorySize, SMEM_BYTES);
    }
    Maps maps;
    {
        cuuint64_t gd[3] = {64, 2048, 7};
        cuuint64_t gs[2] = {896, 128};
        cuuint32_t bd[3] = {64, 32, 7};
        cuuint32_t es[3] = {1, 1, 1};
        enc(&maps.x, CU_TENSOR_MAP_DATA_TYPE_BFLOAT16, 3, d_in[0], gd, gs, bd, es, CU_TENSOR_MAP_INTERLEAVE_NONE, CU_TENSOR_MAP_SWIZZLE_128B,
            CU_TENSOR_MAP_L2_PROMOTION_L2_128B, CU_TENSOR_MAP_FLOAT_OOB_FILL_NONE);
    }
    make_map(enc, &maps.out, d_out, 448, 2048, 56, 16, CU_TENSOR_MAP_SWIZZLE_NONE);
    make_map(enc, &maps.qkv, d_in[1], 1344, 448, 64, 112, CU_TENSOR_MAP_SWIZZLE_128B);
    make_map(enc, &maps.wo, d_in[3], 448, 448, 64, 112, CU_TENSOR_MAP_SWIZZLE_128B);
    make_map(enc, &maps.wg, d_in[5], 1792, 448, 64, 112, CU_TENSOR_MAP_SWIZZLE_128B);
    make_map(enc, &maps.wu, d_in[6], 1792, 448, 64, 112, CU_TENSOR_MAP_SWIZZLE_128B);
    make_map(enc, &maps.wg32, d_in[5], 1792, 448, 32, 112, CU_TENSOR_MAP_SWIZZLE_64B);
    make_map(enc, &maps.wu32, d_in[6], 1792, 448, 32, 112, CU_TENSOR_MAP_SWIZZLE_64B);
    make_map(enc, &maps.wd, d_in[7], 448, 1792, 64, 112, CU_TENSOR_MAP_SWIZZLE_128B);
    fused_kernel<<<128, 384, SMEM_BYTES>>>(scratch, (const __nv_bfloat16*)d_in[0], (const __nv_bfloat16*)d_in[2], 7, (const __nv_bfloat16*)d_in[5],
                                           (const __nv_bfloat16*)d_in[6], (const __nv_bfloat16*)d_in[7], maps);
}
```

```cpp
#include <cuda_runtime.h>
#include <cuda.h>
#include <cuda_bf16.h>
#include <stdint.h>
#include <type_traits>

#define PPF 2
#define PKP 0
#define TDEF 1
#define TMPF 0
#define NORM1 0
#define ACAN 0
#define SPLIT0 1
#define OT 2
#define F2PP 0
#define PPK 2
#define QE 1
#define OST 1
#define PP

namespace {

constexpr uint32_t STAGE = 28672, HALF = 14336;
constexpr int NST = 5;
constexpr uint32_t OFF_H = NST * STAGE;
constexpr uint32_t OFF_KVB = OFF_H + 2 * STAGE;
constexpr uint32_t OFF_WPHI = OFF_KVB + 16384;
constexpr uint32_t OFF_XR = OFF_WPHI + 7168;
constexpr uint32_t OFF_BAR = OFF_XR + 6144;
constexpr uint32_t SMEM_BYTES = OFF_BAR + 384 + 1408;
constexpr int B_EMPTY = NST, B_RECV = 2 * NST, B_RECV2 = B_RECV + 2, B_PACK = B_RECV2 + 2, B_GAT = B_PACK + 1, B_LATE = B_GAT + 24, B_ACK = B_LATE + 1, B_ACK2 = B_ACK + 2, B_COUNT = B_ACK2 + 2;

constexpr int PACK = 14 + 4 * PKP;

struct Maps { CUtensorMap x, qkv, wo, wg, wu, wg32, wu32, wd, out; };

}

constexpr int PLANE = 16 * 2 * 8 * 512;
struct Scratch {
    uint4 ex[6 * PLANE];
    uint4 kv1[8 * 16 * 16 * 32];
    uint4 kv2[8 * 512];
    uint32_t c1[8 * 8 * 16 * 32];
    uint32_t cw[8 * 32];
    uint4 wp[8 * 32 * (HALF / 16)];
};
__device__ __align__(1024) Scratch g_scratch;
#define g_ex (sc->ex)
#define g_kv1 (sc->kv1)
#define g_kv2 (sc->kv2)
#define g_c1 (sc->c1)
#define g_cw (sc->cw)
#define g_wp (sc->wp)
#define STAMP(i)
#define GSTAMP(i)
#define PDUMP()
#define ASTAMP(i)

namespace {

__device__ __forceinline__ int fresh_tid() { int t; asm volatile("mov.u32 %0, %%tid.x;" : "=r"(t)); return t; }
template <int N> __device__ __forceinline__ void kill(uint32_t* v) {
#pragma unroll
    for (int i = 0; i < N; i++) v[i] = 0;
}
template <int N> __device__ __forceinline__ void kill(float* v) {
#pragma unroll
    for (int i = 0; i < N; i++) v[i] = 0.f;
}
__device__ __forceinline__ uint32_t s2u(const void* p) { return (uint32_t)__cvta_generic_to_shared(p); }
__device__ __forceinline__ void mbar_init(uint32_t a, uint32_t c) { asm volatile("mbarrier.init.shared::cta.b64 [%0], %1;" ::"r"(a), "r"(c) : "memory"); }
__device__ __forceinline__ void mbar_expect_tx(uint32_t a, uint32_t b) { asm volatile("mbarrier.arrive.expect_tx.shared::cta.b64 _, [%0], %1;" ::"r"(a), "r"(b) : "memory"); }
__device__ __forceinline__ void mbar_arrive(uint32_t a) { asm volatile("mbarrier.arrive.shared::cta.b64 _, [%0];" ::"r"(a) : "memory"); }
#define GIVE_UP(id) "trap;\n"
#define SPIN_MAX "0x400000"
#define SPIN_TAIL(id) "add.u32 n, n, 1;\n setp.lt.u32 p, n, " SPIN_MAX ";\n @p bra.uni LP;\n" GIVE_UP(id) " DN:\n }"
__device__ __forceinline__ void mbar_wait(uint32_t a, uint32_t ph) {
    asm volatile("{ .reg .pred p; .reg .b32 n; mov.u32 n, 0;\n LP:\n"
                 "mbarrier.try_wait.parity.shared::cta.b64 p, [%0], %1;\n @p bra DN;\n"
                 "add.u32 n, n, 1;\n setp.lt.u32 p, n, " SPIN_MAX ";\n @p bra LP;\n"
                 GIVE_UP("")
                 " DN:\n }" ::"r"(a), "r"(ph) : "memory");
}
#define ELECT "{ .reg .pred e; elect.sync _|e, 0xffffffff; @e "
__device__ __forceinline__ void tma2d(uint32_t dst, const CUtensorMap* m, int c0, int c1, uint32_t bar) {
    asm volatile(ELECT "cp.async.bulk.tensor.2d.shared::cluster.global.mbarrier::complete_tx::bytes [%0], [%1, {%3, %4}], [%2]; }" ::"r"(dst), "l"(m), "r"(bar), "r"(c0), "r"(c1) : "memory");
}
__device__ __forceinline__ void tma3x(uint32_t dst, const CUtensorMap* m, int row, uint32_t bar) {
    asm volatile(ELECT "cp.async.bulk.tensor.3d.shared::cluster.global.mbarrier::complete_tx::bytes [%0], [%1, {0, %3, 0}], [%2]; }" ::"r"(dst), "l"(m), "r"(bar), "r"(row) : "memory");
}
template <int OFF>
__device__ __forceinline__ void ld_pkt(uint32_t* v, const uint4* p) {
    asm volatile("{ .reg .b128 t; ld.relaxed.gpu.global.b128 t, [%4+%5]; mov.b128 {%0,%1,%2,%3}, t; }" : "=r"(v[0]), "=r"(v[1]), "=r"(v[2]), "=r"(v[3]) : "l"(p), "n"(OFF * 16) : "memory");
}
template <int OFF>
__device__ __forceinline__ void st_pkt(uint4* p, uint32_t a, uint32_t b, uint32_t c, uint32_t d) {
    asm volatile("{ .reg .b128 t; mov.b128 t, {%1,%2,%3,%4}; st.relaxed.gpu.global.b128 [%0+%5], t; }" ::"l"(p), "r"(a), "r"(b), "r"(c), "r"(d), "n"(OFF * 16) : "memory");
}
__device__ __forceinline__ uint32_t pack2(float lo, float hi) {
    uint32_t r;
    asm("cvt.rn.bf16x2.f32 %0, %1, %2;" : "=r"(r) : "f"(hi), "f"(lo));
    return r;
}
__device__ __forceinline__ float bf_lo(uint32_t w) { return __uint_as_float(w << 16); }
__device__ __forceinline__ float bf_hi(uint32_t w) { return __uint_as_float(w & 0xffff0000u); }
__device__ __forceinline__ uint32_t settag(uint32_t w, uint32_t tag) { return (w & ~1u) | tag; }
__device__ __forceinline__ float ex2(float x) { float y; asm("ex2.approx.ftz.f32 %0, %1;" : "=f"(y) : "f"(x)); return y; }
__device__ __forceinline__ float rcp(float x) { float y; asm("rcp.approx.ftz.f32 %0, %1;" : "=f"(y) : "f"(x)); return y; }
__device__ __forceinline__ float tanh_hw(float x) { float y; asm("tanh.approx.f32 %0, %1;" : "=f"(y) : "f"(x)); return y; }
__device__ __forceinline__ void stsm4(uint32_t addr, uint32_t a, uint32_t b, uint32_t c, uint32_t d) {
    asm volatile("stmatrix.sync.aligned.m8n8.x4.shared.b16 [%0], {%1,%2,%3,%4};" ::"r"(addr), "r"(a), "r"(b), "r"(c), "r"(d) : "memory");
}
__device__ __forceinline__ void fence_async() { asm volatile("fence.proxy.async.shared::cta;" ::: "memory"); }
__device__ __forceinline__ void bar_sync(int id, int n) { asm volatile("bar.sync %0, %1;" ::"r"(id), "r"(n) : "memory"); }
__device__ __forceinline__ void bar_arrive(int id, int n) { asm volatile("bar.arrive %0, %1;" ::"r"(id), "r"(n) : "memory"); }
__device__ __forceinline__ void wg_fence() { asm volatile("wgmma.fence.sync.aligned;" ::: "memory"); }
__device__ __forceinline__ void wg_commit() { asm volatile("wgmma.commit_group.sync.aligned;" ::: "memory"); }
template <int N> __device__ __forceinline__ void wg_wait() { asm volatile("wgmma.wait_group.sync.aligned %0;" ::"n"(N) : "memory"); }

constexpr uint32_t SB0 = 1024;
__host__ __device__ constexpr uint32_t dlo(uint32_t off, uint32_t lbo) { return ((SB0 + off) >> 4) | ((lbo >> 4) << 16); }
__host__ __device__ constexpr uint32_t dhi(uint32_t sbo, uint32_t sw) { return (sbo >> 4) | (sw << 30); }
__device__ __forceinline__ uint64_t dbase(uint32_t lo, uint32_t hi) { uint64_t d; asm volatile("mov.b64 %0, {%1, %2};" : "=l"(d) : "r"(lo), "r"(hi)); return d; }
#define BASE128(off, lbo, adj) dbase(dlo(off, lbo) + (adj), dhi(1024, 1))
#define BASE64(off, lbo, adj) dbase(dlo(off, lbo) + (adj), dhi(512, 2))

#define ACC4(d, o) "+f"(d[o]), "+f"(d[o + 1]), "+f"(d[o + 2]), "+f"(d[o + 3])
#define ACC28(d) ACC4(d, 0), ACC4(d, 4), ACC4(d, 8), ACC4(d, 12), ACC4(d, 16), ACC4(d, 20), ACC4(d, 24)
#define ACC32(d, o) ACC4(d, o), ACC4(d, o + 4), ACC4(d, o + 8), ACC4(d, o + 12), ACC4(d, o + 16), ACC4(d, o + 20), ACC4(d, o + 24), ACC4(d, o + 28)

template <int TB, uint64_t D>
__device__ __forceinline__ void mma_rs56(float* d, uint32_t a0, uint32_t a1, uint32_t a2, uint32_t a3, int sd, uint64_t base) {
    asm volatile("{ .reg .pred p; .reg .b64 db; setp.ne.b32 p, %32, 0; add.u64 db, %33, %34;\n"
                 "wgmma.mma_async.sync.aligned.m64n56k16.f32.bf16.bf16 "
                 "{%0,%1,%2,%3,%4,%5,%6,%7,%8,%9,%10,%11,%12,%13,%14,%15,%16,%17,%18,%19,%20,%21,%22,%23,%24,%25,%26,%27}, "
                 "{%28,%29,%30,%31}, db, p, 1, 1, %35; }\n"
                 : ACC28(d)
                 : "r"(a0), "r"(a1), "r"(a2), "r"(a3), "r"(sd), "l"(base), "n"(D), "n"(TB));
}
template <int TB, uint64_t D>
__device__ __forceinline__ void mma_rs64(float* d, uint32_t a0, uint32_t a1, uint32_t a2, uint32_t a3, int sd, uint64_t base) {
    asm volatile("{ .reg .pred p; .reg .b64 db; setp.ne.b32 p, %36, 0; add.u64 db, %37, %38;\n"
                 "wgmma.mma_async.sync.aligned.m64n64k16.f32.bf16.bf16 "
                 "{%0,%1,%2,%3,%4,%5,%6,%7,%8,%9,%10,%11,%12,%13,%14,%15,%16,%17,%18,%19,%20,%21,%22,%23,%24,%25,%26,%27,%28,%29,%30,%31}, "
                 "{%32,%33,%34,%35}, db, p, 1, 1, %39; }\n"
                 : ACC32(d, 0)
                 : "r"(a0), "r"(a1), "r"(a2), "r"(a3), "r"(sd), "l"(base), "n"(D), "n"(TB));
}
template <int TB, uint64_t D>
__device__ __forceinline__ void mma_rs128(float* d, uint32_t a0, uint32_t a1, uint32_t a2, uint32_t a3, int sd, uint64_t base) {
    asm volatile("{ .reg .pred p; .reg .b64 db; setp.ne.b32 p, %68, 0; add.u64 db, %69, %70;\n"
                 "wgmma.mma_async.sync.aligned.m64n128k16.f32.bf16.bf16 "
                 "{%0,%1,%2,%3,%4,%5,%6,%7,%8,%9,%10,%11,%12,%13,%14,%15,%16,%17,%18,%19,%20,%21,%22,%23,%24,%25,%26,%27,%28,%29,%30,%31,%32,%33,%34,%35,%36,%37,%38,%39,%40,%41,%42,%43,%44,%45,%46,%47,%48,%49,%50,%51,%52,%53,%54,%55,%56,%57,%58,%59,%60,%61,%62,%63}, "
                 "{%64,%65,%66,%67}, db, p, 1, 1, %71; }\n"
                 : ACC32(d, 0), ACC32(d, 32)
                 : "r"(a0), "r"(a1), "r"(a2), "r"(a3), "r"(sd), "l"(base), "n"(D), "n"(TB));
}
template <uint64_t DA, uint64_t DB>
__device__ __forceinline__ void mma_ss56_tt(float* d, int sd, uint64_t ba, uint64_t bb) {
    asm volatile("{ .reg .pred p; .reg .b64 da, db; setp.ne.b32 p, %28, 0; add.u64 da, %29, %31; add.u64 db, %30, %32;\n"
                 "wgmma.mma_async.sync.aligned.m64n56k16.f32.bf16.bf16 "
                 "{%0,%1,%2,%3,%4,%5,%6,%7,%8,%9,%10,%11,%12,%13,%14,%15,%16,%17,%18,%19,%20,%21,%22,%23,%24,%25,%26,%27}, "
                 "da, db, p, 1, 1, 1, 1; }\n"
                 : ACC28(d)
                 : "r"(sd), "l"(ba), "l"(bb), "n"(DA), "n"(DB));
}
template <int... I> struct Seq {};
template <class F, int... I> __device__ __forceinline__ void static_for_impl(F&& f, Seq<I...>) { (f(std::integral_constant<int, I>{}), ...); }
#define FOR7(...) static_for_impl([&](auto T_) { constexpr int t = decltype(T_)::value; __VA_ARGS__; }, Seq<0, 1, 2, 3, 4, 5, 6>{})
#define FOR8(...) static_for_impl([&](auto T_) { constexpr int t = decltype(T_)::value; __VA_ARGS__; }, Seq<0, 1, 2, 3, 4, 5, 6, 7>{})
#define FOR14(...) static_for_impl([&](auto T_) { constexpr int t = decltype(T_)::value; __VA_ARGS__; }, Seq<0, 1, 2, 3, 4, 5, 6, 7, 8, 9, 10, 11, 12, 13>{})

__device__ __forceinline__ int kblk(int p, int b) { return b == 0 ? p : b - (b <= p); }
__host__ __device__ constexpr int krow(int t) { return t < 3 ? 16 * t : (t < 6 ? 56 + 16 * (t - 3) : 48); }
#define AQ(A, b, t) ((t) < 3 ? A[2 * (b)][4 * (t)] : (t) < 6 ? A[2 * (b) + 1][4 * ((t) - 3)] : A[2 * (b)][12]), \
                    ((t) < 3 ? A[2 * (b)][4 * (t) + 1] : (t) < 6 ? A[2 * (b) + 1][4 * ((t) - 3) + 1] : A[2 * (b)][13]), \
                    ((t) < 3 ? A[2 * (b)][4 * (t) + 2] : (t) < 6 ? A[2 * (b) + 1][4 * ((t) - 3) + 2] : A[2 * (b) + 1][12]), \
                    ((t) < 3 ? A[2 * (b)][4 * (t) + 3] : (t) < 6 ? A[2 * (b) + 1][4 * ((t) - 3) + 3] : A[2 * (b) + 1][13])
#define D128(off, t) ((uint64_t)(((off) + krow(t) * 128) >> 4) + ((uint64_t)((t) == 6 ? (7168 - 1024) >> 4 : 0) << 32))
#define D64(off, t) ((uint64_t)(((off) + krow(t) * 64) >> 4) + ((uint64_t)((t) == 6 ? (3584 - 512) >> 4 : 0) << 32))

#define PL(k) (((k) - 3) * PLANE)
__device__ __forceinline__ void st_word(uint32_t* p, uint32_t v) { asm volatile("st.relaxed.gpu.global.u32 [%0], %1;" ::"l"(p), "r"(v) : "memory"); }
__device__ __forceinline__ uint32_t ld_word(const uint32_t* p) { uint32_t v; asm volatile("ld.relaxed.gpu.global.u32 %0, [%1];" : "=r"(v) : "l"(p) : "memory"); return v; }
__device__ __forceinline__ void tag_slice(uint32_t* w, uint32_t tag) { w[0] = settag(w[0], tag); w[4] = settag(w[4], tag); w[8] = settag(w[8], tag); w[12] = settag(w[12], tag); }
template <int O>
__device__ __forceinline__ void send_slice(uint4* dst, int lane, const uint32_t* w) {
    st_pkt<O>(dst, w[0], w[1], w[2], w[3]);
    st_pkt<O + 32>(dst, w[4], w[5], w[6], w[7]);
    st_pkt<O + 64>(dst, w[8], w[9], w[10], w[11]);
    asm volatile("{ .reg .b64 t; mov.b64 t, {%1,%2}; st.relaxed.gpu.global.b64 [%0+%3], t; }" ::"l"((char*)dst - lane * 8), "r"(w[12]), "r"(w[13]), "n"(16 * (O + 96)) : "memory");
}
#define RW4(v, o) "+r"(v[o]), "+r"(v[(o) + 1]), "+r"(v[(o) + 2]), "+r"(v[(o) + 3])
#define RW2(v, o) "+r"(v[o]), "+r"(v[(o) + 1])
#define WR4(v, o) "=&r"(v[o]), "=&r"(v[(o) + 1]), "=&r"(v[(o) + 2]), "=&r"(v[(o) + 3])
#define LDP(a, b, c, d, addr, off) "ld.relaxed.gpu.global.b128 q, [" addr "+" off "];\n mov.b128 {" a "," b "," c "," d "}, q;\n"
#define LDH(a, b, addr, off) "ld.relaxed.gpu.global.b64 h, [" addr "+" off "];\n mov.b64 {" a "," b "}, h;\n"
#define VOTE_OK "and.b32 t, t, 1;\n setp.ne.u32 p, t, 0;\n vote.sync.any.pred p, p, 0xffffffff;\n @!p bra.uni DN;\n"
#define CHK(x, tag) "lop3.b32 t, " x ", " tag ", t, 0xBE;\n"
__device__ __forceinline__ void check_cnt(uint32_t v, const uint32_t* p, uint32_t target) {
    asm volatile("{ .reg .pred p; .reg .b32 n, t; mov.u32 n, 0; mov.u32 t, %2;\n LP:\n"
                 "sub.s32 t, t, %1;\n setp.lt.s32 p, t, 0;\n vote.sync.any.pred p, p, 0xffffffff;\n @!p bra.uni DN;\n ld.relaxed.gpu.global.u32 t, [%0];\n" SPIN_TAIL("7")
                 ::"l"(p), "r"(target), "r"(v) : "memory");
}
__device__ __forceinline__ void poll_cnt(const uint32_t* p, uint32_t target) {
    asm volatile("{ .reg .pred p; .reg .b32 n, t; mov.u32 n, 0;\n LP:\n"
                 "ld.relaxed.gpu.global.u32 t, [%0];\n sub.s32 t, t, %1;\n setp.lt.s32 p, t, 0;\n vote.sync.any.pred p, p, 0xffffffff;\n @!p bra.uni DN;\n" SPIN_TAIL("1")
                 ::"l"(p), "r"(target) : "memory");
}
template <int STR>
__device__ __forceinline__ void poll4_kv(uint32_t* v, const uint4* p, uint32_t tag) {
    asm volatile("{ .reg .pred p; .reg .b32 n, t; .reg .b128 q; mov.u32 n, 0;\n LP:\n"
                 LDP("%0", "%1", "%2", "%3", "%16", "0") LDP("%4", "%5", "%6", "%7", "%16", "%18")
                 LDP("%8", "%9", "%10", "%11", "%16", "%19") LDP("%12", "%13", "%14", "%15", "%16", "%20")
                 "xor.b32 t, %0, %17;\n" CHK("%4", "%17") CHK("%8", "%17") CHK("%12", "%17") VOTE_OK SPIN_TAIL("2")
                 : WR4(v, 0), WR4(v, 4), WR4(v, 8), WR4(v, 12)
                 : "l"(p), "r"(tag), "n"(16 * STR), "n"(32 * STR), "n"(48 * STR)
                 : "memory");
}
template <int B>
__device__ __forceinline__ void blk_load(uint32_t (&A)[8][14], const uint4* src, int lane) {
    ld_pkt<0>(&A[2 * B][0], src); ld_pkt<32>(&A[2 * B][4], src); ld_pkt<64>(&A[2 * B][8], src);
    ld_pkt<512>(&A[2 * B + 1][0], src); ld_pkt<544>(&A[2 * B + 1][4], src); ld_pkt<576>(&A[2 * B + 1][8], src);
    asm volatile("{ .reg .b64 h;\n" LDH("%0", "%1", "%4", "1536") LDH("%2", "%3", "%4", "9728") "}"
                 : "=&r"(A[2 * B][12]), "=&r"(A[2 * B][13]), "=&r"(A[2 * B + 1][12]), "=&r"(A[2 * B + 1][13])
                 : "l"((const char*)src - lane * 8) : "memory");
}
template <int B>
__device__ __forceinline__ void blk_check(uint32_t (&A)[8][14], const uint4* src, int lane, uint32_t tag) {
    asm volatile("{ .reg .pred p; .reg .b32 n, t; .reg .b128 q; .reg .b64 h, a8; mov.u32 n, 0;\n LP:\n"
                 "xor.b32 t, %0, %30;\n" CHK("%4", "%30") CHK("%8", "%30") CHK("%12", "%30") CHK("%16", "%30") CHK("%20", "%30") CHK("%24", "%30") CHK("%26", "%30") VOTE_OK
                 LDP("%0", "%1", "%2", "%3", "%28", "0") LDP("%4", "%5", "%6", "%7", "%28", "512") LDP("%8", "%9", "%10", "%11", "%28", "1024")
                 LDP("%12", "%13", "%14", "%15", "%28", "8192") LDP("%16", "%17", "%18", "%19", "%28", "8704") LDP("%20", "%21", "%22", "%23", "%28", "9216")
                 "mad.wide.s32 a8, %29, -8, %28;\n" LDH("%24", "%25", "a8", "1536") LDH("%26", "%27", "a8", "9728") SPIN_TAIL("3")
                 "\n and.b32 %0, %0, -2; and.b32 %4, %4, -2; and.b32 %8, %8, -2; and.b32 %12, %12, -2; and.b32 %16, %16, -2; and.b32 %20, %20, -2; and.b32 %24, %24, -2; and.b32 %26, %26, -2;"
                 : RW4(A[2 * B], 0), RW4(A[2 * B], 4), RW4(A[2 * B], 8), RW4(A[2 * B + 1], 0), RW4(A[2 * B + 1], 4), RW4(A[2 * B + 1], 8),
                   RW2(A[2 * B], 12), RW2(A[2 * B + 1], 12)
                 : "l"(src), "r"(lane), "r"(tag)
                 : "memory");
}
__device__ __forceinline__ void st_async4(uint32_t a, uint32_t x, uint32_t y, uint32_t z, uint32_t w, uint32_t bar) {
    asm volatile("st.async.weak.shared::cluster.mbarrier::complete_tx::bytes.v4.b32 [%0], {%1,%2,%3,%4}, [%5];" ::"r"(a), "r"(x), "r"(y), "r"(z), "r"(w), "r"(bar) : "memory");
}
__device__ __forceinline__ uint32_t mapa(uint32_t a, uint32_t cta) { uint32_t r; asm("mapa.shared::cluster.u32 %0, %1, %2;" : "=r"(r) : "r"(a), "r"(cta)); return r; }
__device__ __forceinline__ void stat_load(uint32_t* v, const uint4* p) { ld_pkt<0>(v, p); ld_pkt<512>(v + 4, p); }
__device__ __forceinline__ void stat_check(uint32_t* v, const uint4* p, uint32_t tag) {
    asm volatile("{ .reg .pred p; .reg .b32 n, t; .reg .b128 q; mov.u32 n, 0;\n LP:\n"
                 "xor.b32 t, %3, %9;\n" CHK("%7", "%9") VOTE_OK
                 LDP("%0", "%1", "%2", "%3", "%8", "0") LDP("%4", "%5", "%6", "%7", "%8", "8192") SPIN_TAIL("4")
                 : RW4(v, 0), RW4(v, 4) : "l"(p), "r"(tag) : "memory");
}
__device__ __forceinline__ uint32_t x_bits(const uint32_t* X) {
    uint32_t r;
    asm volatile("{ .reg .b32 a, b; prmt.b32 a, %1, %2, 0x0040; prmt.b32 b, %3, %4, 0x0040; prmt.b32 %0, a, b, 0x5410; }" : "=r"(r) : "r"(X[0]), "r"(X[4]), "r"(X[8]), "r"(X[12]));
    return r;
}
template <int O>
__device__ __forceinline__ void slice_load(uint32_t* v, const uint4* p, int lane) {
    ld_pkt<O>(v, p); ld_pkt<O + 32>(v + 4, p); ld_pkt<O + 64>(v + 8, p);
    asm volatile("{ .reg .b64 h;\n" LDH("%0", "%1", "%2", "%3") "}" : "=r"(v[12]), "=r"(v[13]) : "l"((const char*)p - lane * 8), "n"(16 * (O + 96)) : "memory");
}
template <int O>
__device__ __forceinline__ void slice_check(uint32_t* v, const uint4* p, int lane, uint32_t tag) {
    asm volatile("{ .reg .pred p; .reg .b32 n, t; .reg .b128 q; .reg .b64 h; mov.u32 n, 0;\n LP:\n"
                 "xor.b32 t, %0, %16;\n" CHK("%4", "%16") CHK("%8", "%16") CHK("%12", "%16") VOTE_OK
                 LDP("%0", "%1", "%2", "%3", "%14", "%17") LDP("%4", "%5", "%6", "%7", "%14", "%18") LDP("%8", "%9", "%10", "%11", "%14", "%19")
                 LDH("%12", "%13", "%15", "%20") SPIN_TAIL("5")
                 : RW4(v, 0), RW4(v, 4), RW4(v, 8), RW2(v, 12)
                 : "l"(p), "l"((const char*)p - lane * 8), "r"(tag), "n"(16 * O), "n"(16 * (O + 32)), "n"(16 * (O + 64)), "n"(16 * (O + 96))
                 : "memory");
}
__device__ __forceinline__ void x_fix(uint32_t* X, uint32_t bits) {
    X[0] = __byte_perm(X[0], bits, 0x3214); X[4] = __byte_perm(X[4], bits, 0x3215); X[8] = __byte_perm(X[8], bits, 0x3216); X[12] = __byte_perm(X[12], bits, 0x3217);
}
__device__ __forceinline__ void sts4(uint32_t a, uint32_t x, uint32_t y, uint32_t z, uint32_t w) {
    asm volatile("st.shared.v4.u32 [%0], {%1,%2,%3,%4};" ::"r"(a), "r"(x), "r"(y), "r"(z), "r"(w) : "memory");
}
__device__ __forceinline__ void lds4(uint32_t* v, uint32_t a) {
    asm volatile("ld.shared.v4.u32 {%0,%1,%2,%3}, [%4];" : "=r"(v[0]), "=r"(v[1]), "=r"(v[2]), "=r"(v[3]) : "r"(a) : "memory");
}
struct LnCoef { uint32_t hi, lo, sh; };
__device__ __forceinline__ LnCoef ln_coef(float sum, float sq) {
    sum += __shfl_xor_sync(0xffffffffu, sum, 1); sq += __shfl_xor_sync(0xffffffffu, sq, 1);
    sum += __shfl_xor_sync(0xffffffffu, sum, 2); sq += __shfl_xor_sync(0xffffffffu, sq, 2);
    const float mean = sum * (1.f / 448.f);
    const float var = fmaxf(fmaf(-mean, mean, sq * (1.f / 448.f)), 0.f);
    const float sc = rsqrtf(var + 1e-5f);
    LnCoef r;
    r.hi = pack2(sc, sc);
    const float lo = sc - bf_lo(r.hi), sh = -mean * sc;
    r.lo = pack2(lo, lo);
    r.sh = pack2(sh, sh);
    return r;
}
template <int B>
__device__ __forceinline__ void normalize(uint32_t (&A)[8][14], const LnCoef& c0, const LnCoef& c1) {
#pragma unroll
    for (int s = 2 * B; s < 2 * B + 2; s++)
#pragma unroll
        for (int i = 0; i < 14; i++) {
            const LnCoef& k = (i & 1) ? c1 : c0;
            asm("{ .reg .b32 t; fma.rn.bf16x2 t, %0, %2, %3; fma.rn.bf16x2 %0, %0, %1, t; }" : "+r"(A[s][i]) : "r"(k.hi), "r"(k.lo), "r"(k.sh));
        }
}
__device__ __forceinline__ void slice_stats(const uint32_t* w, float* st) {
    float a = 0.f, b = 0.f, p = 0.f, q = 0.f;
#pragma unroll
    for (int i = 0; i < 7; i++) {
        const float e0 = bf_lo(w[2 * i]), e1 = bf_hi(w[2 * i]), e2 = bf_lo(w[2 * i + 1]), e3 = bf_hi(w[2 * i + 1]);
        a += e0 + e1; b += e2 + e3;
        p = fmaf(e0, e0, p); p = fmaf(e1, e1, p); q = fmaf(e2, e2, q); q = fmaf(e3, e3, q);
    }
    a += __shfl_xor_sync(0xffffffffu, a, 1); p += __shfl_xor_sync(0xffffffffu, p, 1); b += __shfl_xor_sync(0xffffffffu, b, 1); q += __shfl_xor_sync(0xffffffffu, q, 1);
    a += __shfl_xor_sync(0xffffffffu, a, 2); p += __shfl_xor_sync(0xffffffffu, p, 2); b += __shfl_xor_sync(0xffffffffu, b, 2); q += __shfl_xor_sync(0xffffffffu, q, 2);
    st[0] = a; st[1] = p; st[2] = b; st[3] = q;
}
__device__ __forceinline__ void dual_softmax(const float* p, uint32_t* out) {
    constexpr float L = 1.4426950408889634f;
#pragma unroll
    for (int r = 0; r < 2; r++) {
        float mx = fmaxf(p[2 * r], p[2 * r + 1]), mn = fminf(p[2 * r], p[2 * r + 1]);
#pragma unroll
        for (int i = 1; i < 7; i++) {
            mx = fmaxf(mx, fmaxf(p[4 * i + 2 * r], p[4 * i + 2 * r + 1]));
            mn = fminf(mn, fminf(p[4 * i + 2 * r], p[4 * i + 2 * r + 1]));
        }
        mx = fmaxf(mx, __shfl_xor_sync(0xffffffffu, mx, 1));
        mn = fminf(mn, __shfl_xor_sync(0xffffffffu, mn, 1));
        const float bx = -mx * L, bn = mn * L;
        float ep[14], en[14], sp = 0.f, sn = 0.f;
#pragma unroll
        for (int i = 0; i < 14; i++) {
            const float v = p[4 * (i >> 1) + 2 * r + (i & 1)];
            ep[i] = ex2(fmaf(v, L, bx));
            en[i] = ex2(fmaf(v, -L, bn));
            sp += ep[i]; sn += en[i];
        }
        sp += __shfl_xor_sync(0xffffffffu, sp, 1);
        sn += __shfl_xor_sync(0xffffffffu, sn, 1);
        const float ip = rcp(sp), in = rcp(sn);
#pragma unroll
        for (int i = 0; i < 7; i++) {
            out[4 * i + r] = pack2(ep[2 * i] * ip, ep[2 * i + 1] * ip);
            out[4 * i + 2 + r] = pack2(en[2 * i] * in, en[2 * i + 1] * in);
        }
    }
}
__device__ __forceinline__ float geglu(float g, float u) {
    const float t = tanh_hw(g * fmaf(g * g, 0.7978845608028654f * 0.044715f, 0.7978845608028654f));
    const float gu = g * u;
    return fmaf(t, gu, gu);
}
__device__ __forceinline__ void phi_gemm(const float* t, float* p) {
    uint32_t w[14];
#pragma unroll
    for (int i = 0; i < 14; i++) w[i] = pack2(t[2 * i], t[2 * i + 1]);
    const uint64_t db = BASE128(OFF_WPHI, 16, 0);
    wg_fence();
    mma_rs56<0, 0>(p, w[0], w[1], w[2], w[3], 0, db);
    mma_rs56<0, 2>(p, w[4], w[5], w[6], w[7], 1, db);
    mma_rs56<0, 4>(p, w[8], w[9], w[10], w[11], 1, db);
    mma_rs56<0, 6>(p, w[12], w[13], 0u, 0u, 1, db);
    wg_commit();
    wg_wait<0>();
}

}

#define BAR(i) (bars + 8 * (i))
#define R_WAIT() mbar_wait(BAR(slot), ph)
#define WSUM(i)
#define R_ADJ (slot * (STAGE >> 4))
#define R_NEXT() do { eb2 = eb1; eb1 = BAR(B_EMPTY + slot); if (++slot == NST) { slot = 0; ph ^= 1; } } while (0)
#define R_RELEASE(k) do { if (lane == 0) mbar_arrive((k) == 1 ? eb1 : eb2); } while (0)
#define PUSH_BEGIN() do { mbar_wait(BAR(B_ACK + wgi), ackph); ackph ^= 1; } while (0)
#define PUSH_ACK() do { __syncwarp(); if (lane == 0) asm volatile("mbarrier.arrive.shared::cluster.b64 _, [%0];" ::"r"(mapa(BAR(B_ACK + wgi), hr ^ 1)) : "memory"); } while (0)

__global__ void __cluster_dims__(2, 1, 1) __launch_bounds__(384, 1)
fused_kernel(Scratch* const sc, const __nv_bfloat16* __restrict__ x_in, const __nv_bfloat16* __restrict__ w_phi, const int trips,
             const __nv_bfloat16* __restrict__ wg, const __nv_bfloat16* __restrict__ wu, const __nv_bfloat16* __restrict__ wd,
             const __grid_constant__ Maps maps) {
    extern __shared__ __align__(1024) unsigned char smem_raw[];
    const uint32_t sb = s2u(smem_raw);
    const uint32_t bars = sb + OFF_BAR;
    const int wgi = __shfl_sync(0xffffffffu, threadIdx.x >> 7, 0);
    const int hr = blockIdx.x & 1, ck = blockIdx.x >> 1;
    const int gp = (ck - 4) & 7, q7 = ((ck - 36) * 37) >> 8;
    const int pr = __shfl_sync(0xffffffffu, ck < 4 ? ck : (ck < 36 ? (ck - 4) >> 3 : q7), 0);
    const int tile = __shfl_sync(0xffffffffu, ck < 4 ? 0 : (ck < 36 ? (gp ? 2 * gp : 1) : 2 * (ck - 36 - 7 * q7) + 3), 0);
    const int sl = 2 * pr + hr;
    STAMP(0);
    GSTAMP(60);
    if (threadIdx.x == 256) {
#pragma unroll
        for (int i = 0; i < NST; i++) mbar_init(BAR(i), 1);
        asm volatile("fence.mbarrier_init.release.cluster;" ::: "memory");
    }
    if (threadIdx.x == 288) {
        if ((sb & 0x3FFFF) != SB0) asm volatile("trap;");
#pragma unroll
        for (int i = NST; i < B_COUNT; i++) mbar_init(BAR(i), i >= B_ACK ? 4 : (i < B_RECV || i == B_LATE ? 8 : 1));
        asm volatile("fence.mbarrier_init.release.cluster;" ::: "memory");
    }
    __syncwarp();
    asm volatile("barrier.cluster.arrive.relaxed.aligned;" ::: "memory");

    if (wgi == 2) {
        asm volatile("setmaxnreg.dec.sync.aligned.u32 40;");
        const int t128 = fresh_tid() & 127, w = __shfl_sync(0xffffffffu, t128 >> 5, 0), lane = t128 & 31;
        uint32_t e0[2] = {0, 0}, e1[2] = {0, 0}, cw_target = 0;
        if (w == 0) {
#pragma unroll 1
            for (int n = 0; n < NST; n++) {
                const uint32_t dst = sb + n * STAGE, fb = BAR(n);
                asm volatile(ELECT "mbarrier.arrive.expect_tx.shared::cta.b64 _, [%0], %1; }" ::"r"(fb), "r"(n < 2 ? 2 * STAGE : STAGE) : "memory");
                if (n < 2) {
                    tma3x(sb + OFF_H + n * STAGE, &maps.x, tile * 128 + n * 64, fb);
                    tma3x(dst, &maps.x, tile * 128 + n * 64 + 32, fb);
                } else {
                    if (n == 3) mbar_wait(BAR(1), 0);
                    const int ra = 112 * (n - 2);
                    tma2d(dst, &maps.qkv, 448 + 56 * sl, ra, fb);
                    tma2d(dst + HALF, &maps.qkv, 896 + 56 * sl, ra, fb);
                }
            }
            asm volatile("barrier.cluster.wait.aligned;" ::: "memory");
            cw_target = (ld_word(g_cw + sl * 32) & ~15u) + 16;
#pragma unroll 1
            for (int k = 0; k < 2; k++) {
                const int n = t128 + 32 * k;
                int m = n - 2 - (n > PACK);
                const bool packed = m >= 30 ? (m < 38 || m >= 52) : m >= 22;
                if (m >= 30) m -= 30;
                if (n == PACK) m = tile < 8 ? tile : tile + 14;
                const int rot = n < 8 ? 0 : pr;
                const int ra = 112 * kblk(rot, m & 3), rb = 112 * kblk(rot, 2 * m & 3), rc = 112 * kblk(rot, (2 * m + 1) & 3);
                int kind = 0, m0, m1, c0, c1, r0, r1;
                if (m < 4) { m0 = m1 = 1; c0 = 448 + 56 * sl; c1 = c0 + 448; r0 = r1 = ra; }
                else if (m < 8) { m0 = m1 = m < 6 ? 1 : 2; c0 = c1 = 56 * sl; r0 = rb; r1 = rc; }
                else if (m < 20) { m0 = 3; m1 = 4; c0 = c1 = 224 * sl + 32 * hr + 64 * ((m - 8) >> 2); r0 = r1 = ra; }
                else if (m < 22) { kind = 2; m0 = 5; m1 = 6; c0 = c1 = 224 * sl + (hr ? 0 : 192); r0 = rb; r1 = rc; }
                else { m0 = m1 = 7; c0 = c1 = 56 * (2 * ((pr + (m >> 1) - 10) & 3) + hr); r0 = 224 * (sl ^ (m & 1)); r1 = r0 + 112; }
                if (packed) { kind = 1; r0 = sl * 16 + (m < 8 ? m : m - 14); r1 = 0; }
                e0[0] = e0[1]; e1[0] = e1[1];
                e0[1] = kind | (m0 << 2) | (m1 << 6) | (c0 << 10) | (c1 << 21);
                e1[1] = r0 | (r1 << 16);
            }
        } else {
            const int j = t128 - 32;
            asm volatile("barrier.cluster.wait.aligned;" ::: "memory");
            uint2 wv[7];
            const int k = j < 56 ? j : 55, hh = k >= 28;
#pragma unroll
            for (int i = 0; i < 7; i++) wv[i] = __ldg(reinterpret_cast<const uint2*>(w_phi + (sl * 56 + k) * 28) + i);
#pragma unroll 1
            for (int i = j; i < 7168 / 16; i += 96) sts4(sb + OFF_WPHI + i * 16, 0, 0, 0, 0);
            bar_sync(5, 96);
            if (j < 56) {
                uint32_t a4[4];
#pragma unroll
                for (int q = 0; q < 4; q++) a4[q] = sb + OFF_WPHI + (4 * hh + q) * 128 + ((((k >> 3) ^ (4 * hh + q)) & 7) << 4) + (k & 7) * 2;
                FOR14(const uint32_t v = (t & 1) ? wv[t >> 1].y : wv[t >> 1].x;
                      asm volatile("{ .reg .b16 l, h; mov.b32 {l, h}, %2; st.shared.u16 [%0+%3], l; st.shared.u16 [%1+%3], h; }"
                                   ::"r"(a4[t >= 7 ? 2 : 0]), "r"(a4[t >= 7 ? 3 : 1]), "r"(v), "n"((t % 7) * 1024) : "memory"));
            }
            __syncwarp();
            fence_async();
            bar_arrive(1, 224);
            bar_arrive(9, 224);
            if (w == 1) {
                mbar_wait(BAR(2), 0);
                mbar_wait(BAR(2), 1);
                const int b = blockIdx.x;
                asm volatile(ELECT "cp.async.bulk.prefetch.L2.global [%0], %1; }" ::"l"(wg + b * 6272), "r"(12544) : "memory");
                asm volatile(ELECT "cp.async.bulk.prefetch.L2.global [%0], %1; }" ::"l"(wu + b * 6272), "r"(12544) : "memory");
                asm volatile(ELECT "cp.async.bulk.prefetch.L2.global [%0], %1; }" ::"l"(wd + b * 6272), "r"(12544) : "memory");
            }
        }
        uint32_t kseq = ld_word(g_c1 + (sl * 8 * 16 + tile) * 32);
        int slot = 0, ph = 0, n = NST;
#pragma unroll 1
        for (int layer = 0; layer < 3; layer++) {
            if (w == 0) {
                const int nend = layer == 0 ? 11 : (layer == 1 ? 42 : 63);
#pragma unroll 1
                for (; n < nend; n++) {
                const uint32_t w0 = __shfl_sync(0xffffffffu, n < 32 ? e0[0] : e0[1], n & 31), w1 = __shfl_sync(0xffffffffu, n < 32 ? e1[0] : e1[1], n & 31);
                const uint32_t dst = sb + slot * STAGE, fb = BAR(n == PACK ? B_PACK : slot);
                const CUtensorMap* m0 = &maps.x + ((w0 >> 2) & 15);
                const CUtensorMap* m1 = &maps.x + ((w0 >> 6) & 15);
                const int c0 = (w0 >> 10) & 2047, c1 = w0 >> 21, r0 = w1 & 0xffff, r1 = w1 >> 16;
                if (n == 25) {
                    int it = 0;
                    uint32_t v;
                    do { asm volatile("ld.acquire.gpu.global.u32 %0, [%1];" : "=r"(v) : "l"(g_cw + sl * 32) : "memory"); } while ((int)(v - cw_target) < 0 && ++it < 0x400000);
                    asm volatile("fence.proxy.async.global;" ::: "memory");
                    __syncwarp();
                }
                mbar_wait(BAR(B_EMPTY + slot), ph);
                __syncwarp();
                asm volatile(ELECT "mbarrier.arrive.expect_tx.shared::cta.b64 _, [%0], %1; }" ::"r"(fb), "r"(STAGE) : "memory");
                if ((w0 & 3) == 0) {
                    tma2d(dst, m0, c0, r0, fb);
                    tma2d(dst + HALF, m1, c1, r1, fb);
                } else if (w0 & 1) {
                    asm volatile(ELECT "cp.async.bulk.shared::cluster.global.mbarrier::complete_tx::bytes [%0], [%1], %2, [%3]; }"
                                 ::"r"(dst), "l"(reinterpret_cast<const char*>(g_wp) + (size_t)r0 * STAGE), "r"(STAGE), "r"(fb) : "memory");
                } else {
                    tma2d(dst, m0, c0, r0, fb); tma2d(dst + 7168, m0, c0, r1, fb);
                    tma2d(dst + HALF, m1, c0, r0, fb); tma2d(dst + HALF + 7168, m1, c0, r1, fb);
                }
                if (n == PACK) asm volatile(ELECT "mbarrier.arrive.shared::cta.b64 _, [%0]; }" ::"r"(BAR(slot)) : "memory");
                if (++slot == NST) { slot = 0; ph ^= 1; }
                }
            } else if (w == 1 && layer == 1) {
                constexpr int ps = PACK % NST;
                mbar_wait(BAR(B_PACK), 0);
                asm volatile("{ .reg .pred e; elect.sync _|e, 0xffffffff;\n"
                             "@e cp.async.bulk.global.shared::cta.bulk_group [%0], [%1], %2;\n"
                             "@e cp.async.bulk.commit_group;\n"
                             "@e cp.async.bulk.wait_group.read 0;\n"
                             "@e mbarrier.arrive.shared::cta.b64 _, [%3], 8;\n"
                             "@e cp.async.bulk.wait_group 0;\n"
                             "@e fence.proxy.async.global;\n"
                             "@e red.release.gpu.global.add.u32 [%4], 1; }"
                             ::"l"(reinterpret_cast<char*>(g_wp) + (size_t)(sl * 16 + tile) * STAGE), "r"(sb + ps * STAGE), "r"(STAGE), "r"(BAR(B_EMPTY + ps)), "l"(g_cw + sl * 32) : "memory");
                __syncwarp();
            }
            if (layer < 2) {
            const uint32_t tag = layer ^ 1;
            kseq++;
            bar_sync(7, 384);
            ASTAMP(0);
            if (tile < 15) {
                const int sq = lane >> 3, pk = 8 * w + (lane & (tile == 14 ? 3 : 7));
                uint32_t v[16];
                if (layer == 0) poll_cnt(g_c1 + ((sl * 8 + (w >> 1) * 4 + (tile >> 2)) * 16 + (lane & 15)) * 32, kseq);
                ASTAMP(1);
                poll4_kv<32>(v, g_kv1 + ((sl * 16 + tile) * 16 + 4 * sq) * 32 + pk, tag);
#pragma unroll
                for (int k = 0; k < 4; k++) {
                    float lo = (bf_lo(v[k]) + bf_lo(v[4 + k])) + (bf_lo(v[8 + k]) + bf_lo(v[12 + k]));
                    float hi = (bf_hi(v[k]) + bf_hi(v[4 + k])) + (bf_hi(v[8 + k]) + bf_hi(v[12 + k]));
                    lo += __shfl_xor_sync(0xffffffffu, lo, 8); hi += __shfl_xor_sync(0xffffffffu, hi, 8);
                    lo += __shfl_xor_sync(0xffffffffu, lo, 16); hi += __shfl_xor_sync(0xffffffffu, hi, 16);
                    v[k] = pack2(lo, hi);
                }
                if (sq == 0) st_pkt<0>(g_kv2 + sl * 512 + 32 * tile + pk, settag(v[0], tag), v[1], v[2], v[3]);
            }
            ASTAMP(2);
            {
                const int item = t128 < 112 ? t128 : 112 + (t128 & 3), d = item >> 1;
                const int cc = t128 < 112 ? 2 * (d >= 28) + (item & 1) : item - 112;
                const int r = t128 < 112 ? d : 56 + (cc >> 1) + 2 * ((t128 - 112) >> 2);
                uint32_t ra = sb + OFF_KVB + r * 128 + 4 * cc, rx = (r & 7) << 4;
                asm volatile("" : "+r"(ra), "+r"(rx));
                FOR14(asm volatile("st.shared.u32 [%0+%2], %1;" ::"r"((ra ^ 8) + (((t & 7) << 4) ^ rx)), "r"(0), "n"((t >> 3) * 8192) : "memory"));
                uint32_t v[16];
                asm volatile("" : "+r"(ra), "+r"(rx));
                poll4_kv<8>(v, g_kv2 + sl * 512 + (item >> 3) * 32 + (item & 7), tag);
                FOR14(asm volatile("st.shared.u32 [%0+%2], %1;" ::"r"(ra + (((t & 7) << 4) ^ rx)), "r"(v[t < 7 ? t : t + 1]), "n"((t >> 3) * 8192) : "memory"));
                fence_async();
            }
            bar_arrive(3, 384);
            ASTAMP(3);
            }
        }
    } else {
        asm volatile("setmaxnreg.inc.sync.aligned.u32 232;");
        int lane = fresh_tid() & 31, prf = pr;
#define pr prf
#define g (lane >> 2)
#define c (lane & 3)
#define t128 (w * 32 + lane)
        const int wu = __shfl_sync(0xffffffffu, fresh_tid() >> 5, 0), w = wu & 3;
        const uint32_t xoff = __shfl_sync(0xffffffffu, (3 * PLANE + ((tile * 2 + wgi) * 8) * 512 + w * 128) * 16, 0);
        char* xu = reinterpret_cast<char*>(g_ex) + xoff;
#define FRESH() asm volatile("" : "+l"(xu), "+r"(lane), "+r"(prf))
#define xp0 (reinterpret_cast<uint4*>(xu) + lane)
        const uint32_t hbuf = sb + OFF_H + wgi * STAGE;
        uint32_t slot = 0, ph = 0, eb1 = 0, eb2 = 0, ackph = 0, rcvph = 0, gatph = 0, swp = 0;
        uint32_t ppid = 6;
#define cx(s) (reinterpret_cast<uint32_t*>(reinterpret_cast<uint4*>(xu) + PL(1) + 112 + (s) * 512))
#define stp (reinterpret_cast<uint4*>(xu) + g + PL(0) + 112)
        uint32_t seq = ld_word(cx(sl));
        uint32_t kseq = ld_word(g_c1 + ((sl * 8 + wu) * 16 + tile) * 32);
        uint32_t stag = ld_word(reinterpret_cast<const uint32_t*>(stp + sl * 512) + 3) & 1;
        asm volatile("barrier.cluster.wait.aligned;" ::: "memory");
        STAMP(1);
        uint32_t X[14];
        const uint32_t x0row = (w < 2 ? hbuf : sb + wgi * STAGE) + ((w & 1) * 16 + (lane & 15)) * 128;
        mbar_wait(BAR(wgi), 0);
        STAMP(51);
#pragma unroll
        for (int j = 0; j < 4; j++) {
            const int G = 7 * sl + min(2 * j + (lane >> 4), 6);
            uint32_t q2, q3;
            asm volatile("ldmatrix.sync.aligned.m8n8.x4.shared.b16 {%0,%1,%2,%3}, [%4];" : "=r"(X[4 * j]), "=r"(X[4 * j + 1]), "=r"(q2), "=r"(q3)
                         : "r"(x0row + (G >> 3) * 4096 + (((G ^ lane) & 7) << 4)) : "memory");
            if (j < 3) { X[(4 * j + 2) % 14] = q2; X[(4 * j + 3) % 14] = q3; }
        }
#define PUSH_SLICE(W)                                                                          \
    {                                                                                          \
        if (t128 == 0) mbar_expect_tx(BAR(B_RECV + wgi), 7168);                                \
        PUSH_BEGIN();                                                                          \
        const uint32_t ra = mapa(hbuf + 24576 + t128 * 16, hr ^ 1), rb = mapa(sb + OFF_XR + wgi * 3072, hr ^ 1), rbar = mapa(BAR(B_RECV + wgi), hr ^ 1); \
        st_async4(ra, W[0], W[1], W[2], W[3], rbar);                                           \
        st_async4(ra + 2048, W[4], W[5], W[6], W[7], rbar);                                    \
        st_async4(rb + t128 * 16, W[8], W[9], W[10], W[11], rbar);                             \
        asm volatile("st.async.weak.shared::cluster.mbarrier::complete_tx::bytes.v2.b32 [%0], {%1,%2}, [%3];" ::"r"(rb + 2048 + t128 * 8), "r"(W[12]), "r"(W[13]), "r"(rbar) : "memory"); \
    }
#define PULL_SLICE(W)                                                                          \
    {                                                                                          \
        uint32_t t0, t1;                                                                       \
        mbar_wait(BAR(B_RECV + wgi), rcvph);                                                   \
        rcvph ^= 1;                                                                            \
        lds4(&A[1][0], hbuf + 24576 + t128 * 16);                                              \
        lds4(&A[1][4], hbuf + 26624 + t128 * 16);                                              \
        lds4(&A[1][8], sb + OFF_XR + wgi * 3072 + t128 * 16);                                  \
        asm volatile("ld.shared.v2.u32 {%0,%1}, [%2];" : "=r"(t0), "=r"(t1) : "r"(sb + OFF_XR + wgi * 3072 + 2048 + t128 * 8) : "memory"); \
        _Pragma("unroll") for (int i = 0; i < 12; i++) A[0][i] = (i & 3) ? W[i] : W[i] & ~1u;  \
        A[1][0] &= ~1u; A[1][4] &= ~1u; A[1][8] &= ~1u;                                        \
        A[0][12] = (hr ? t0 : W[12]) & ~1u; A[0][13] = hr ? t1 : W[13];                        \
        A[1][12] = (hr ? W[12] : t0) & ~1u; A[1][13] = hr ? W[13] : t1;                        \
        asm volatile("" : RW4(A[0], 0), RW4(A[0], 4), RW4(A[0], 8), RW2(A[0], 12), RW4(A[1], 0), RW4(A[1], 4), RW4(A[1], 8), RW2(A[1], 12)); \
        swp = hr * 448;                                                                        \
    }
#define SWB(b, t, db, sh) ((b) == 0 && (t) < 6 ? ((t) < 3 ? db##p : db##m) : db)
#define DECL_DB(b, MK, lbo, sh) const uint64_t db = MK(0, lbo, R_ADJ), dbp = (b) == 0 ? MK(0, lbo, R_ADJ + (swp >> (sh))) : db, dbm = (b) == 0 ? MK(0, lbo, R_ADJ - (swp >> (sh))) : db;
#define PPB 2
#define PP_WAIT() if (wgi == 1) { bar_sync(ppid, 256); ppid ^= 14; }
#define PP_GO() if (wgi == 0) { bar_arrive(ppid, 256); ppid ^= 14; }
#define GAT_DST(B, s2) ((B) == 1 ? hbuf + w * 3584 + (s2) * 1792 : ((B) == 2 ? lateb + w * 3584 + (s2) * 1792 : ((s2) ? sb + OFF_KVB + wgi * 8192 : hbuf + 14336) + w * 1792))
#define GAT_ISSUE(B, base)                                                                     \
    {                                                                                          \
        const char* gs = xu + ((base) + kblk(pr, B) * 1024) * 16;                              \
        asm volatile("{ .reg .pred e; elect.sync _|e, 0xffffffff;\n"                           \
                     "@e mbarrier.arrive.expect_tx.shared::cta.b64 _, [%3], 3584;\n"           \
                     "@e cp.async.bulk.shared::cluster.global.mbarrier::complete_tx::bytes [%0], [%2], 1792, [%3];\n" \
                     "@e cp.async.bulk.shared::cluster.global.mbarrier::complete_tx::bytes [%1], [%2+8192], 1792, [%3]; }" \
                     ::"r"(GAT_DST(B, 0)), "r"(GAT_DST(B, 1)), "l"(gs), "r"(BAR(B_GAT + wu * 3 + (B) - 1)) : "memory"); \
        __syncwarp();                                                                          \
    }
#define GAT_FETCH(B)                                                                           \
    {                                                                                          \
        mbar_wait(BAR(B_GAT + wu * 3 + (B) - 1), (gatph >> (B)) & 1);                          \
        gatph ^= 1 << (B);                                                                     \
        _Pragma("unroll") for (int s2 = 0; s2 < 2; s2++) {                                     \
            const uint32_t ga = GAT_DST(B, s2) + lane * 16;                                    \
            lds4(&A[2 * (B) + s2][0], ga); lds4(&A[2 * (B) + s2][4], ga + 512); lds4(&A[2 * (B) + s2][8], ga + 1024); \
            asm volatile("ld.shared.v2.u32 {%0,%1}, [%2];" : "=r"(A[2 * (B) + s2][12]), "=r"(A[2 * (B) + s2][13]) : "r"(ga - lane * 8 + 1536) : "memory"); \
        }                                                                                      \
    }
#define LATE_ARRIVE() do { if (lane == 0) mbar_arrive(BAR(B_LATE)); } while (0)
#define LATE_WAIT() do { mbar_wait(BAR(B_LATE), gatph & 1); gatph ^= 1; } while (0)
#define PT 3
#define PREP(b, t, remote)                                                                     \
    if constexpr ((b) < 3 && (t) == PT) {                                                      \
        wg_commit();                                                                           \
        STAMP(74 + 6 * (step & 1) + 2 * (b));                                                  \
        if (remote) { GAT_FETCH(((b) + 1) & 3) blk_check<((b) + 1) & 3>(A, BLK(xsrc, (b) + 1), lane, xtag); } \
        STAMP(75 + 6 * (step & 1) + 2 * (b));                                                  \
        normalize<((b) + 1) & 3>(A, k0, k1);                                                   \
        asm volatile("" : RW4(A[(2 * (b) + 2) & 7], 0), RW4(A[(2 * (b) + 2) & 7], 4), RW4(A[(2 * (b) + 2) & 7], 8), RW2(A[(2 * (b) + 2) & 7], 12), \
                          RW4(A[(2 * (b) + 3) & 7], 0), RW4(A[(2 * (b) + 3) & 7], 4), RW4(A[(2 * (b) + 3) & 7], 8), RW2(A[(2 * (b) + 3) & 7], 12)); \
        wg_fence();                                                                            \
    }
#define X0_BLOCK(b)                                                                            \
    { const int rr = lane & 7, hi = lane >> 4;                                                 \
    const uint32_t rowa = (w < 2 ? hbuf : sb + wgi * STAGE) + ((w & 1) * 16 + (lane & 15)) * 128; \
    FOR7(constexpr int G = 14 * (b) + (t < 3 ? 2 * t : (t < 6 ? 2 * t + 1 : 6));               \
         uint32_t q0, q1, q2, q3;                                                              \
         const uint32_t ad = t < 6 ? rowa + (((((G & 7) + hi) ^ rr) & 7) << 4) + ((G & 7) == 7 ? hi * 4096 : 0) : rowa + ((G + 7 * hi) >> 3) * 4096 + ((((G + 7 * hi) ^ rr) & 7) << 4); \
         asm volatile("ldmatrix.sync.aligned.m8n8.x4.shared.b16 {%0,%1,%2,%3}, [%4+%5];" : "=r"(q0), "=r"(q1), "=r"(q2), "=r"(q3) \
                      : "r"(ad), "n"(t < 6 ? (G >> 3) * 4096 : 0) : "memory");                 \
         if (t < 3) { A[2 * (b)][4 * t] = q0; A[2 * (b)][4 * t + 1] = q1; A[2 * (b)][4 * t + 2] = q2; A[2 * (b)][4 * t + 3] = q3; } \
         else if (t < 6) { A[2 * (b) + 1][(4 * t - 12) & 15] = q0; A[2 * (b) + 1][((4 * t - 12) & 15) + 1] = q1; A[2 * (b) + 1][((4 * t - 12) & 15) + 2] = q2; A[2 * (b) + 1][((4 * t - 12) & 15) + 3] = q3; } \
         else { A[2 * (b)][12] = q0; A[2 * (b)][13] = q1; A[2 * (b) + 1][12] = q2; A[2 * (b) + 1][13] = q3; }); }
#define BLK(base, b) ((base) + kblk(pr, b) * 1024)

#pragma unroll 1
        for (int step = 0; step < 4; step++) {
            FRESH();
            const uint32_t tag = (step >> 1) ^ 1;
            const int so = (step >> 1) * 24 + (step & 1) * 12;
            (void)so;
            uint32_t A[8][14];
            uint4* const xsrc = xp0 + ((step & 1) ? PL(2) : PL(0));
            const uint32_t xtag = (step & 1) ? tag : ((seq >> 3) & 1) ^ 1;
            uint32_t xbits;
            {
                float st[4];
                slice_stats(X, st);
                stag ^= 1;
                xbits = x_bits(X);
                tag_slice(X, xtag);
                if (step) send_slice<0>(xsrc + sl * 512, lane, X);
                if (c == 0) st_pkt<0>(stp + sl * 512, __float_as_uint(st[0]), __float_as_uint(st[1]), __float_as_uint(st[2]), settag(__float_as_uint(st[3]), stag));
            }
            STAMP(2 + so);
            uint32_t sv[8];
            const uint32_t lateb = sb + ((slot + NST - 1) % NST) * STAGE + wgi * HALF;
            if (step == 0) {
                X0_BLOCK(0) X0_BLOCK(1) X0_BLOCK(2) X0_BLOCK(3)
                mbar_wait(BAR(wgi ^ 1), 0);
                R_NEXT();
                R_NEXT();
                R_RELEASE(2);
                stat_load(sv, stp + c * 1024);
                stat_check(sv, stp + c * 1024, stag);
                STAMP(52 + step);
            } else {
                kill<14>(A[2]); kill<14>(A[3]); kill<14>(A[4]); kill<14>(A[5]); kill<14>(A[6]); kill<14>(A[7]);
                PUSH_SLICE(X)
                stat_load(sv, stp + c * 1024);
                PULL_SLICE(X)
                LATE_WAIT();
                stat_check(sv, stp + c * 1024, stag);
                STAMP(52 + step);
                const int pb = (step & 1) ? PL(2) : PL(0);
                GAT_ISSUE(1, pb) GAT_ISSUE(2, pb) GAT_ISSUE(3, pb)
            }
            LnCoef k0, k1;
            {
                k0 = ln_coef(__uint_as_float(sv[0]) + __uint_as_float(sv[4]), __uint_as_float(sv[1]) + __uint_as_float(sv[5]));
                k1 = ln_coef(__uint_as_float(sv[2]) + __uint_as_float(sv[6]), __uint_as_float(sv[3] & ~1u) + __uint_as_float(sv[7] & ~1u));
            }
            STAMP(3 + so);
            GSTAMP(70 + step);

            uint32_t late1 = 0;
            if ((step & 1) == 0) {
                float tq[28];
                {
                    float av[28];
#define KV_BLOCK(b)                                                                           \
    if ((b) == 1) late1 = eb2;                                                                \
    if ((b) == 2) { if (lane == 0) mbar_arrive(late1); wg_wait<2>(); R_RELEASE(2); }          \
    if ((b) == 3) PUSH_ACK();                                                                 \
    R_WAIT();                                                                                 \
    if ((b) == PPK) { PP_WAIT() }                                                             \
    { DECL_DB(b, BASE128, 16, 0)                                                              \
    wg_fence();                                                                               \
    FOR7(mma_rs56<1, D128(0, t)>(tq, AQ(A, b, t), (b) + t > 0, SWB(b, t, db, 0));             \
         mma_rs56<1, D128(HALF, t)>(av, AQ(A, b, t), (b) + t > 0, SWB(b, t, db, 0));          \
         PREP(b, t, step)); }                                                                 \
    wg_commit();                                                                              \
    if ((b) == 3 && PPK < 4) { PP_GO() }                                                      \
    R_NEXT();
                    normalize<0>(A, k0, k1);
                    KV_BLOCK(0) KV_BLOCK(1) KV_BLOCK(2) KV_BLOCK(3)
                    wg_wait<0>();
                    if (lane < 3) mbar_arrive(BAR(B_EMPTY + (slot + NST - 1 - lane) % NST));
                    STAMP(4 + so);
                    WSUM(80 + 7 * (step >> 1));
                    const int m = lane >> 3, rr = lane & 7;
                    const uint32_t rowa = hbuf + 16384 + (w * 16 + rr + 8 * (m & 1)) * 128;
                    const uint32_t one = c == 0 ? 0x00003f80u : 0u;
                    if (step == 0) { bar_sync(wgi ? 9 : 1, 224); }
#pragma unroll
                    for (int j = 0; j < 4; j++) {
                        const uint32_t a = rowa + (((2 * j + (m >> 1)) ^ rr) << 4);
                        if (j < 3) stsm4(a, pack2(av[8 * j], av[8 * j + 1]), pack2(av[8 * j + 2], av[8 * j + 3]), pack2(av[8 * j + 4], av[8 * j + 5]), pack2(av[8 * j + 6], av[8 * j + 7]));
                        else stsm4(a, pack2(av[24], av[25]), pack2(av[26], av[27]), one, one);
                    }
                }
                uint32_t PH[28];
                int it = 1;
#pragma unroll 1
                do {
                    float pp[28];
                    phi_gemm(tq, pp);
                    dual_softmax(pp, PH);
                    if (((trips >> (it + 1)) & 1) == 0) continue;
                    {
                        const int m = lane >> 3, rr = lane & 7;
                        const uint32_t rowa = hbuf + (w * 16 + rr + 8 * (m & 1)) * 128;
#pragma unroll
                        for (int j = 0; j < 7; j++) {
                            const int cg = 2 * j + (m >> 1), hi = cg >= 7;
                            stsm4(rowa + hi * 8192 + (((cg - 7 * hi) ^ rr) << 4), PH[4 * j], PH[4 * j + 1], PH[4 * j + 2], PH[4 * j + 3]);
                        }
                    }
                    fence_async();
                    STAMP(5 + so);
#define Q_STAGE(b0)                                                                           \
    R_WAIT();                                                                                 \
    { DECL_DB(b0, BASE128, 16, 0)                                                             \
    wg_fence();                                                                               \
    FOR7(mma_rs56<1, D128(0, t)>(tq, AQ(A, b0, t), (b0) + t > 0, SWB(b0, t, db, 0)));         \
    FOR7(mma_rs56<1, D128(HALF, t)>(tq, AQ(A, (b0) + 1, t), 1, db)); }                        \
    wg_commit();                                                                              \
    R_NEXT();
                    if (QE && wgi == 0) { kill<28>(tq); Q_STAGE(0) Q_STAGE(2) wg_wait<1>(); R_RELEASE(2); wg_wait<0>(); R_RELEASE(1); }
                    bar_sync(2, 256);
                    float kv[28];
                    const uint64_t da = BASE128(OFF_H + 16384, 16, 0), dbk = BASE128(OFF_H, 16, wgi * 512);
                    wg_fence();
                    FOR8(constexpr uint64_t o = ((t >> 2) * STAGE + (t & 3) * 2048) >> 4; mma_ss56_tt<o, o>(kv, t > 0, da, dbk));
                    wg_commit();
                    wg_wait<0>();
#pragma unroll
                    for (int hf = 0; hf < 2; hf++) {
                        const int d = 16 * w + g + 8 * hf;
                        if ((d < 56 && (d >= 28) == (c >= 2)) || d == 56) {
                            const int item = d < 56 ? 2 * d + (c & 1) : 112 + c;
                            uint4* dst = g_kv1 + ((sl * 16 + (item >> 3)) * 16 + tile) * 32 + wgi * 16 + (item & 7);
#define KVW(i) pack2(kv[4 * (i) + 2 * hf], kv[4 * (i) + 2 * hf + 1])
                            st_pkt<0>(dst, settag(KVW(0), tag), KVW(1), KVW(2), KVW(3));
                            st_pkt<8>(dst, settag(KVW(4), tag), KVW(5), KVW(6), 0u);
                        }
                    }
                    __syncwarp();
                    kseq++;
                    if (lane == 0) st_word(g_c1 + ((sl * 8 + wu) * 16 + tile) * 32, kseq);
                    bar_arrive(7, 384);
                    STAMP(6 + so);
                    if (!QE || wgi == 1) { kill<28>(tq); Q_STAGE(0) Q_STAGE(2) wg_wait<1>(); R_RELEASE(2); wg_wait<0>(); R_RELEASE(1); }
                    STAMP(7 + so);
                    kill<28>(PH);
                } while (((trips >> (++it)) & 1));
                STAMP(8 + so);
                FRESH();
                if (step) {
                    slice_load<PL(0)>(X, xp0 + sl * 512, lane);
                } else {
                    const uint32_t* xp = reinterpret_cast<const uint32_t*>(x_in + (size_t)(tile * 128 + wu * 16 + g) * 448 + 56 * sl + 2 * c);
#pragma unroll
                    for (int i = 0; i < 7; i++) { X[2 * i] = __ldg(xp + 4 * i); X[2 * i + 1] = __ldg(xp + 4 * i + 8 * 224); }
                }
                bar_sync(3, 384);
                STAMP(9 + so);
                const uint4* const osrc = xp0 + PL(1);
                {
                    float nm[32];
                    const uint64_t db = BASE128(OFF_KVB, 16, 0);
                    wg_fence();
                    FOR7(mma_rs64<0, ((t >> 2) * 8192 + (t & 3) * 32) / 16>(nm, PH[4 * t], PH[4 * t + 1], PH[4 * t + 2], PH[4 * t + 3], t > 0, db));
                    wg_commit();
                    wg_wait<0>();
                    LATE_ARRIVE();
                    const float i00 = rcp(nm[28] + 1e-6f), i01 = rcp(nm[29] + 1e-6f), i10 = rcp(nm[30] + 1e-6f), i11 = rcp(nm[31] + 1e-6f);
                    const float m0 = c >= 2 ? i01 : i00, m1 = c >= 2 ? i11 : i10;
                    uint32_t O[14];
#pragma unroll
                    for (int i = 0; i < 7; i++) {
                        const float f0 = i < 3 ? i00 : (i > 3 ? i01 : m0), f1 = i < 3 ? i10 : (i > 3 ? i11 : m1);
                        O[2 * i] = pack2(nm[4 * i] * f0, nm[4 * i + 1] * f0);
                        O[2 * i + 1] = pack2(nm[4 * i + 2] * f1, nm[4 * i + 3] * f1);
                    }
                    if (OST) { PP_WAIT() }
                    tag_slice(O, tag);
                    send_slice<PL(1)>(xp0 + sl * 512, lane, O);
                    seq++;
                    if (lane == 0) st_word(cx(sl), seq);
                    STAMP(10 + so);
                    PUSH_SLICE(O)
                    if (OST == 1) { PP_GO() }
                    const uint32_t cv = ld_word(cx(lane & 7));
                    PULL_SLICE(O)
                    LATE_WAIT();
                    check_cnt(cv, cx(lane & 7), seq);
                    if (OST == 2) { PP_GO() }
                    STAMP(56 + (step >> 1));
                    GAT_ISSUE(1, PL(1))
                    GAT_ISSUE(3, PL(1))
                    blk_load<2>(A, BLK(osrc, 2), lane);
                }
                float ao[28];
#define WO_BLOCK(b)                                                                           \
    if ((b) > 0) blk_check<b>(A, BLK(osrc, b), lane, tag);                                    \
    if (((b) & 1) == 0) R_WAIT();                                                             \
    { DECL_DB(b, BASE128, 16, 0)                                                              \
    wg_fence();                                                                               \
    FOR7(mma_rs56<1, D128(((b) & 1) * HALF, t)>(ao, AQ(A, b, t), (b) + t > 0, SWB(b, t, db, 0))); } \
    wg_commit();                                                                              \
    if ((b) & 1) R_NEXT();
                WO_BLOCK(0)
                STAMP(11 + so);
                GAT_FETCH(1)
                WO_BLOCK(1)
                WO_BLOCK(2)
                GAT_FETCH(3)
                WO_BLOCK(3)
                PUSH_ACK();
                wg_wait<0>();
                R_RELEASE(2);
                LATE_ARRIVE();
                STAMP(12 + so);
                WSUM(86 + 7 * (step >> 1));
                x_fix(X, xbits);
#pragma unroll
                for (int i = 0; i < 14; i++) X[i] = pack2(bf_lo(X[i]) + ao[2 * i], bf_hi(X[i]) + ao[2 * i + 1]);
            } else {
                uint32_t H[56];
                float ag[64];
#define F1_EPI(dst, ng, ag)                                                                    \
    _Pragma("unroll") for (int i = 0; i < 2 * (ng); i++)                                       \
        (dst)[i] = pack2(geglu(ag[2 * i], ag[4 * (ng) + 2 * i]), geglu(ag[2 * i + 1], ag[4 * (ng) + 2 * i + 1]));
#define H_PUSH(h0, off) st_async4(rem_h + (off), H[h0], H[(h0) + 1], H[(h0) + 2], H[(h0) + 3], mapa(BAR(B_RECV2 + wgi), hr ^ 1));
#define F1_BLOCK(b, first)                                                                     \
    if ((first) && (b) == 1) late1 = eb2;                                                      \
    if ((first) && (b) == 2) { if (lane == 0) mbar_arrive(late1); }                            \
    if ((first) && (b) == 3) PUSH_ACK();                                                       \
    R_WAIT();                                                                                  \
    if ((b) == ((first) ? PPF : PPB)) { PP_WAIT() }                                            \
    { DECL_DB(b, BASE128, HALF, 0)                                                             \
    wg_fence();                                                                                \
    FOR7(mma_rs128<1, D128(0, t)>(ag, AQ(A, b, t), (b) + t > 0, SWB(b, t, db, 0));             \
         if constexpr (first) { PREP(b, t, true) }); }                                         \
    wg_commit();                                                                               \
    if ((b) == 3) { PP_GO() }                                                                  \
    if ((b) > 0) { wg_wait<1>(); R_RELEASE(1); }       \
    R_NEXT();
                normalize<0>(A, k0, k1);
                F1_BLOCK(0, true) F1_BLOCK(1, true) F1_BLOCK(2, true) F1_BLOCK(3, true)
                if (t128 == 0) { mbar_expect_tx(BAR(B_RECV + wgi), 16384); mbar_expect_tx(BAR(B_RECV2 + wgi), 12288); }
                PUSH_BEGIN();
                wg_wait<0>();
                R_RELEASE(1);
                int p = 0;
#pragma unroll 1
                do {
                    F1_EPI(H + 32, 8, ag)
                    STAMP(4 + p + so);
                    WSUM(81 + p + 7 * (step >> 1));
                    if (((trips >> (p + 1)) & 1) == 0) continue;
                    {
                        const uint32_t pk = (p ? hbuf + 16384 : sb + OFF_KVB + wgi * 8192) + w * 2048;
#pragma unroll
                        for (int k = 0; k < 4; k++) sts4(pk + k * 512 + lane * 16, H[32 + 4 * k], H[33 + 4 * k], H[34 + 4 * k], H[35 + 4 * k]);
                        fence_async();
                        __syncwarp();
                        asm volatile(ELECT "cp.async.bulk.shared::cluster.shared::cta.mbarrier::complete_tx::bytes [%0], [%1], 2048, [%2]; }"
                                     ::"r"(mapa(hbuf + p * 8192 + w * 2048, hr ^ 1)), "r"(pk), "r"(mapa(BAR(B_RECV + wgi), hr ^ 1)) : "memory");
                    }
                    if (step == 1 && p == PKP) R_NEXT();
                    kill<64>(ag);
                    F1_BLOCK(0, false) F1_BLOCK(1, false) F1_BLOCK(2, false) F1_BLOCK(3, false)
                    wg_wait<0>();
                    R_RELEASE(1);
                    kill<16>(H + 32);
                } while (((trips >> (++p)) & 1));
#pragma unroll
                for (int k = 0; k < 4; k++) lds4(H + 16 + 4 * k, hbuf + 16384 + w * 2048 + k * 512 + lane * 16);
                __syncwarp();
                if (lane == 0) asm volatile("mbarrier.arrive.shared::cluster.b64 _, [%0];" ::"r"(mapa(BAR(B_ACK2 + wgi), hr ^ 1)) : "memory");
                const uint32_t rem_h = mapa(hbuf + w * 2048 + lane * 16, hr ^ 1);
#define F1_LAST(b0)                                                                            \
    R_WAIT();                                                                                  \
    if (b0) { PP_WAIT() }                                                                      \
    { DECL_DB(b0, BASE64, HALF, 1)                                                             \
    wg_fence();                                                                                \
    FOR7(mma_rs64<1, D64(0, t)>(al, AQ(A, b0, t), (b0) + t > 0, SWB(b0, t, db, 1)));           \
    FOR7(mma_rs64<1, D64(7168, t)>(al, AQ(A, (b0) + 1, t), 1, db)); }                          \
    wg_commit();                                                                               \
    if (b0) { PP_GO() }                                                                        \
    R_NEXT();
                float al[32];
                F1_LAST(0)
                mbar_wait(BAR(B_RECV + wgi), rcvph);
                rcvph ^= 1;
                mbar_wait(BAR(B_ACK2 + wgi), step >> 1);
                H_PUSH(32, 16384) H_PUSH(36, 16896)
                F1_LAST(2)
                H_PUSH(40, 17408) H_PUSH(44, 17920)
                wg_wait<1>();
                R_RELEASE(2);
                wg_wait<0>();
                R_RELEASE(1);
                uint32_t HP[56];
#pragma unroll
                for (int k = 0; k < 4; k++) lds4(H + 4 * k, sb + OFF_KVB + wgi * 8192 + w * 2048 + k * 512 + lane * 16);
#pragma unroll
                for (int t = 0; t < 8; t++) lds4(HP + 4 * t, hbuf + (t >> 2) * 8192 + w * 2048 + (t & 3) * 512 + lane * 16);
                F1_EPI(H + 48, 4, al)
                H_PUSH(48, 24576 - w * 1024) H_PUSH(52, 25088 - w * 1024)
                STAMP(7 + so);
                WSUM(84 + 7 * (step >> 1));
                FRESH();
                float acc[28];
                const uint32_t roA = hr ? 256u : 0u, roB = hr ? (uint32_t)-1536 : 0u;
                const uint32_t rpA = hr ? 0u : 256u, rpB = hr ? 0u : (uint32_t)-1536;
                float res[28];
                uint32_t v0[14], v1[14], P[14];
                const uint4* ps = xp0 + sl * 512;
#define F2_OWN_A()                                                                             \
    R_WAIT();                                                                                  \
    d0 = BASE128(0, 16, R_ADJ + roA); d1 = BASE128(0, 16, R_ADJ + roB);                        \
    wg_fence();                                                                                \
    FOR14(if constexpr (t < OT) mma_rs56<1, t * 128>(acc, H[4 * t], H[4 * t + 1], H[4 * t + 2], H[4 * t + 3], t > 0, d0)); \
    wg_commit();
#define F2_OWN_B()                                                                             \
    wg_fence();                                                                                \
    FOR14(if constexpr (t >= OT) mma_rs56<1, t * 128>(acc, H[4 * t], H[4 * t + 1], H[4 * t + 2], H[4 * t + 3], 1, t < 12 ? d0 : d1)); \
    wg_commit();                                                                               \
    R_NEXT();
#define F2_PEER()                                                                              \
    R_WAIT();                                                                                  \
    if (F2PP) { PP_WAIT() }                                                                    \
    d0 = BASE128(0, 16, R_ADJ + rpA); d1 = BASE128(0, 16, R_ADJ + rpB);                        \
    wg_fence();                                                                                \
    FOR14(mma_rs56<1, t * 128>(acc, HP[4 * t], HP[4 * t + 1], HP[4 * t + 2], HP[4 * t + 3], 1, t < 12 ? d0 : d1)); \
    wg_commit();                                                                               \
    if (F2PP) { PP_GO() }                                                                      \
    R_NEXT();
#define F2_TURN(u)                                                                             \
    wg_wait<1>();                                                                              \
    if ((u) < 2 || TDEF < 2) R_RELEASE(2);                                                     \
    wg_wait<0>();                                                                              \
    if ((u) < 2 || TDEF < 1) R_RELEASE(1);                                                     \
    _Pragma("unroll") for (int i = 0; i < 14; i++) P[i] = pack2(acc[2 * i], acc[2 * i + 1]);   \
    tag_slice(P, tag);                                                                         \
    asm volatile("" : RW4(P, 0), RW4(P, 4), RW4(P, 8), RW2(P, 12));                            \
    kill<28>(acc);                                                                             \
    F2_OWN_A()                                                                                 \
    if ((u) == 2) { slice_load<PL(3)>(v0, ps, lane); slice_load<PL(4)>(v1, ps, lane); } \
    send_slice<PL(3 + (u))>(xp0 + (2 * ((pr + (u) + 1) & 3) + hr) * 512, lane, P);             \
    seq++;                                                                                     \
    if (lane == 0) st_word(cx(sl), seq);                                                       \
    __syncwarp();                                                                              \
    STAMP(8 + (u) + so);                                                                       \
    F2_OWN_B()
                uint64_t d0, d1;
                F2_OWN_A()
                F2_OWN_B()
                R_WAIT();
                d0 = BASE128(0, 16, R_ADJ + rpA); d1 = BASE128(0, 16, R_ADJ + rpB);
                wg_fence();
                FOR8(mma_rs56<1, t * 128>(acc, HP[4 * t], HP[4 * t + 1], HP[4 * t + 2], HP[4 * t + 3], 1, d0));
                wg_commit();
                mbar_wait(BAR(B_RECV2 + wgi), step >> 1);
#pragma unroll
                for (int k = 0; k < 4; k++) lds4(HP + 32 + 4 * k, hbuf + 16384 + w * 2048 + k * 512 + lane * 16);
                lds4(HP + 48, hbuf + 24576 + w * 1024 + lane * 16);
                lds4(HP + 52, hbuf + 25088 + w * 1024 + lane * 16);
                if (step == 1) PUSH_ACK();
                wg_fence();
                FOR14(if constexpr (t >= 8) mma_rs56<1, t * 128>(acc, HP[4 * t], HP[4 * t + 1], HP[4 * t + 2], HP[4 * t + 3], 1, t < 12 ? d0 : d1));
                wg_commit();
                R_NEXT();
                F2_TURN(0)
                F2_PEER()
                F2_TURN(1)
                F2_PEER()
                F2_TURN(2)
                if (step == 1) STAMP(64);
                slice_check<PL(3)>(v0, ps, lane, tag);
                slice_check<PL(4)>(v1, ps, lane, tag);
#pragma unroll
                for (int i = 0; i < 14; i++) { res[2 * i] = bf_lo(v0[i]) + bf_lo(v1[i]); res[2 * i + 1] = bf_hi(v0[i]) + bf_hi(v1[i]); }
                slice_load<PL(2)>(X, ps, lane);
                if (step == 1) STAMP(65);
                F2_PEER()
                if (step == 1) STAMP(66);
                poll_cnt(cx(2 * ((pr + 1) & 3) + hr), seq);
                if (step == 1) STAMP(67);
                slice_load<PL(5)>(v0, ps, lane);
                x_fix(X, xbits);
                slice_check<PL(5)>(v0, ps, lane, tag);
                if (lane < TDEF) mbar_arrive(BAR(B_EMPTY + (slot + NST - 3 - lane) % NST));
#pragma unroll
                for (int i = 0; i < 14; i++) { res[2 * i] += bf_lo(v0[i]); res[2 * i + 1] += bf_hi(v0[i]); }
                STAMP(11 + so);
                wg_wait<0>();
                R_RELEASE(2);
                LATE_ARRIVE();
                STAMP(12 + so);
                WSUM(85 + 7 * (step >> 1));
#pragma unroll
                for (int i = 0; i < 14; i++) X[i] = pack2(fmaf(res[2 * i] + acc[2 * i], 0.5f, bf_lo(X[i])), fmaf(res[2 * i + 1] + acc[2 * i + 1], 0.5f, bf_hi(X[i])));
            }
        }
        {
            const int m = lane >> 3, rr = lane & 7;
            const uint32_t ob = hbuf + w * 2048, rowa = ob + (rr + 8 * (m & 1)) * 112 + (m >> 1) * 16;
#pragma unroll
            for (int j = 0; j < 3; j++) stsm4(rowa + 32 * j, X[4 * j], X[4 * j + 1], X[4 * j + 2], X[4 * j + 3]);
            asm volatile("stmatrix.sync.aligned.m8n8.x2.shared.b16 [%0], {%1,%2};" ::"r"(ob + (rr + 8 * (m & 1)) * 112 + 96), "r"(X[12]), "r"(X[13]) : "memory");
            fence_async();
            __syncwarp();
            if (lane == 0) {
                asm volatile("cp.async.bulk.tensor.2d.global.shared::cta.bulk_group [%0, {%2, %3}], [%1];" ::"l"(&maps.out), "r"(ob), "r"(56 * sl), "r"(tile * 128 + wu * 16) : "memory");
                asm volatile("cp.async.bulk.commit_group;" ::: "memory");
                asm volatile("cp.async.bulk.wait_group.read 0;" ::: "memory");
            }
        }
        STAMP(50);
        GSTAMP(61);
        PDUMP();
    }
}

#undef g
#undef pr
#undef c
#undef t128

typedef CUresult (*EncodeFn)(CUtensorMap*, CUtensorMapDataType, cuuint32_t, void*, const cuuint64_t*, const cuuint64_t*, const cuuint32_t*,
                             const cuuint32_t*, CUtensorMapInterleave, CUtensorMapSwizzle, CUtensorMapL2promotion, CUtensorMapFloatOOBfill);

static void make_map(EncodeFn enc, CUtensorMap* m, const void* p, uint64_t cols, uint64_t rows, uint32_t bc, uint32_t br, CUtensorMapSwizzle sw) {
    cuuint64_t gd[2] = {cols, rows};
    cuuint64_t gs[1] = {cols * 2};
    cuuint32_t bd[2] = {bc, br};
    cuuint32_t es[2] = {1, 1};
    enc(m, CU_TENSOR_MAP_DATA_TYPE_BFLOAT16, 2, const_cast<void*>(p), gd, gs, bd, es, CU_TENSOR_MAP_INTERLEAVE_NONE, sw,
        CU_TENSOR_MAP_L2_PROMOTION_L2_128B, CU_TENSOR_MAP_FLOAT_OOB_FILL_NONE);
}

extern "C" void kernel_launch(void* const* d_in, const int* in_sizes, int n_in, void* d_out, int out_size) {
    (void)in_sizes; (void)n_in; (void)out_size;
    static EncodeFn enc = nullptr;
    static Scratch* scratch = nullptr;
    if (!enc) {
        void* fn = nullptr;
        cudaDriverEntryPointQueryResult qr;
        cudaGetDriverEntryPoint("cuTensorMapEncodeTiled", &fn, cudaEnableDefault, &qr);
        enc = (EncodeFn)fn;
        cudaGetSymbolAddress((void**)&scratch, g_scratch);
        cudaFuncSetAttribute(fused_kernel, cudaFuncAttributeMaxDynamicSharedMemorySize, SMEM_BYTES);
    }
    Maps maps;
    {
        cuuint64_t gd[3] = {64, 2048, 7};
        cuuint64_t gs[2] = {896, 128};
        cuuint32_t bd[3] = {64, 32, 7};
        cuuint32_t es[3] = {1, 1, 1};
        enc(&maps.x, CU_TENSOR_MAP_DATA_TYPE_BFLOAT16, 3, d_in[0], gd, gs, bd, es, CU_TENSOR_MAP_INTERLEAVE_NONE, CU_TENSOR_MAP_SWIZZLE_128B,
            CU_TENSOR_MAP_L2_PROMOTION_L2_128B, CU_TENSOR_MAP_FLOAT_OOB_FILL_NONE);
    }
    make_map(enc, &maps.out, d_out, 448, 2048, 56, 16, CU_TENSOR_MAP_SWIZZLE_NONE);
    make_map(enc, &maps.qkv, d_in[1], 1344, 448, 64, 112, CU_TENSOR_MAP_SWIZZLE_128B);
    make_map(enc, &maps.wo, d_in[3], 448, 448, 64, 112, CU_TENSOR_MAP_SWIZZLE_128B);
    make_map(enc, &maps.wg, d_in[5], 1792, 448, 64, 112, CU_TENSOR_MAP_SWIZZLE_128B);
    make_map(enc, &maps.wu, d_in[6], 1792, 448, 64, 112, CU_TENSOR_MAP_SWIZZLE_128B);
    make_map(enc, &maps.wg32, d_in[5], 1792, 448, 32, 112, CU_TENSOR_MAP_SWIZZLE_64B);
    make_map(enc, &maps.wu32, d_in[6], 1792, 448, 32, 112, CU_TENSOR_MAP_SWIZZLE_64B);
    make_map(enc, &maps.wd, d_in[7], 448, 1792, 64, 112, CU_TENSOR_MAP_SWIZZLE_128B);
    fused_kernel<<<128, 384, SMEM_BYTES>>>(scratch, (const __nv_bfloat16*)d_in[0], (const __nv_bfloat16*)d_in[2], 7, (const __nv_bfloat16*)d_in[5],
                                           (const __nv_bfloat16*)d_in[6], (const __nv_bfloat16*)d_in[7], maps);
}
```

```cpp
#include <cuda_runtime.h>
#include <cuda.h>
#include <cuda_bf16.h>
#include <stdint.h>
#include <type_traits>

#define PPF 2
#define PKP 0
#define TDEF 1
#define TMPF 0
#define NORM1 0
#define FE 1
#define ACAN 0
#define SPLIT0 1
#define OT 2
#define F2PP 0
#define PPK 2
#define QE 1
#define OST 1
#define PP

namespace {

constexpr uint32_t STAGE = 28672, HALF = 14336;
constexpr int NST = 5;
constexpr uint32_t OFF_H = NST * STAGE;
constexpr uint32_t OFF_KVB = OFF_H + 2 * STAGE;
constexpr uint32_t OFF_WPHI = OFF_KVB + 16384;
constexpr uint32_t OFF_XR = OFF_WPHI + 7168;
constexpr uint32_t OFF_BAR = OFF_XR + 6144;
constexpr uint32_t SMEM_BYTES = OFF_BAR + 384 + 1408;
constexpr int B_EMPTY = NST, B_RECV = 2 * NST, B_RECV2 = B_RECV + 2, B_PACK = B_RECV2 + 2, B_GAT = B_PACK + 1, B_LATE = B_GAT + 24, B_ACK = B_LATE + 1, B_ACK2 = B_ACK + 2, B_COUNT = B_ACK2 + 2;

constexpr int PACK = 14 + 4 * PKP;

struct Maps { CUtensorMap x, qkv, wo, wg, wu, wg32, wu32, wd, out; };

}

constexpr int PLANE = 16 * 2 * 8 * 512;
struct Scratch {
    uint4 ex[6 * PLANE];
    uint4 kv1[8 * 16 * 16 * 32];
    uint4 kv2[8 * 512];
    uint32_t c1[8 * 8 * 16 * 32];
    uint32_t cw[8 * 32];
    uint4 wp[8 * 32 * (HALF / 16)];
};
__device__ __align__(1024) Scratch g_scratch;
#define g_ex (sc->ex)
#define g_kv1 (sc->kv1)
#define g_kv2 (sc->kv2)
#define g_c1 (sc->c1)
#define g_cw (sc->cw)
#define g_wp (sc->wp)
#define STAMP(i)
#define GSTAMP(i)
#define PDUMP()
#define ASTAMP(i)

namespace {

__device__ __forceinline__ int fresh_tid() { int t; asm volatile("mov.u32 %0, %%tid.x;" : "=r"(t)); return t; }
template <int N> __device__ __forceinline__ void kill(uint32_t* v) {
#pragma unroll
    for (int i = 0; i < N; i++) v[i] = 0;
}
template <int N> __device__ __forceinline__ void kill(float* v) {
#pragma unroll
    for (int i = 0; i < N; i++) v[i] = 0.f;
}
__device__ __forceinline__ uint32_t s2u(const void* p) { return (uint32_t)__cvta_generic_to_shared(p); }
__device__ __forceinline__ void mbar_init(uint32_t a, uint32_t c) { asm volatile("mbarrier.init.shared::cta.b64 [%0], %1;" ::"r"(a), "r"(c) : "memory"); }
__device__ __forceinline__ void mbar_expect_tx(uint32_t a, uint32_t b) { asm volatile("mbarrier.arrive.expect_tx.shared::cta.b64 _, [%0], %1;" ::"r"(a), "r"(b) : "memory"); }
__device__ __forceinline__ void mbar_arrive(uint32_t a) { asm volatile("mbarrier.arrive.shared::cta.b64 _, [%0];" ::"r"(a) : "memory"); }
#define GIVE_UP(id) "trap;\n"
#define SPIN_MAX "0x400000"
#define SPIN_TAIL(id) "add.u32 n, n, 1;\n setp.lt.u32 p, n, " SPIN_MAX ";\n @p bra.uni LP;\n" GIVE_UP(id) " DN:\n }"
__device__ __forceinline__ void mbar_wait(uint32_t a, uint32_t ph) {
    asm volatile("{ .reg .pred p; .reg .b32 n; mov.u32 n, 0;\n LP:\n"
                 "mbarrier.try_wait.parity.shared::cta.b64 p, [%0], %1;\n @p bra DN;\n"
                 "add.u32 n, n, 1;\n setp.lt.u32 p, n, " SPIN_MAX ";\n @p bra LP;\n"
                 GIVE_UP("")
                 " DN:\n }" ::"r"(a), "r"(ph) : "memory");
}
#define ELECT "{ .reg .pred e; elect.sync _|e, 0xffffffff; @e "
__device__ __forceinline__ void tma2d(uint32_t dst, const CUtensorMap* m, int c0, int c1, uint32_t bar) {
    asm volatile(ELECT "cp.async.bulk.tensor.2d.shared::cluster.global.mbarrier::complete_tx::bytes [%0], [%1, {%3, %4}], [%2]; }" ::"r"(dst), "l"(m), "r"(bar), "r"(c0), "r"(c1) : "memory");
}
__device__ __forceinline__ void tma3x(uint32_t dst, const CUtensorMap* m, int row, uint32_t bar) {
    asm volatile(ELECT "cp.async.bulk.tensor.3d.shared::cluster.global.mbarrier::complete_tx::bytes [%0], [%1, {0, %3, 0}], [%2]; }" ::"r"(dst), "l"(m), "r"(bar), "r"(row) : "memory");
}
template <int OFF>
__device__ __forceinline__ void ld_pkt(uint32_t* v, const uint4* p) {
    asm volatile("{ .reg .b128 t; ld.relaxed.gpu.global.b128 t, [%4+%5]; mov.b128 {%0,%1,%2,%3}, t; }" : "=r"(v[0]), "=r"(v[1]), "=r"(v[2]), "=r"(v[3]) : "l"(p), "n"(OFF * 16) : "memory");
}
template <int OFF>
__device__ __forceinline__ void st_pkt(uint4* p, uint32_t a, uint32_t b, uint32_t c, uint32_t d) {
    asm volatile("{ .reg .b128 t; mov.b128 t, {%1,%2,%3,%4}; st.relaxed.gpu.global.b128 [%0+%5], t; }" ::"l"(p), "r"(a), "r"(b), "r"(c), "r"(d), "n"(OFF * 16) : "memory");
}
__device__ __forceinline__ uint32_t pack2(float lo, float hi) {
    uint32_t r;
    asm("cvt.rn.bf16x2.f32 %0, %1, %2;" : "=r"(r) : "f"(hi), "f"(lo));
    return r;
}
__device__ __forceinline__ float bf_lo(uint32_t w) { return __uint_as_float(w << 16); }
__device__ __forceinline__ float bf_hi(uint32_t w) { return __uint_as_float(w & 0xffff0000u); }
__device__ __forceinline__ uint32_t settag(uint32_t w, uint32_t tag) { return (w & ~1u) | tag; }
__device__ __forceinline__ float ex2(float x) { float y; asm("ex2.approx.ftz.f32 %0, %1;" : "=f"(y) : "f"(x)); return y; }
__device__ __forceinline__ float rcp(float x) { float y; asm("rcp.approx.ftz.f32 %0, %1;" : "=f"(y) : "f"(x)); return y; }
__device__ __forceinline__ float tanh_hw(float x) { float y; asm("tanh.approx.f32 %0, %1;" : "=f"(y) : "f"(x)); return y; }
__device__ __forceinline__ void stsm4(uint32_t addr, uint32_t a, uint32_t b, uint32_t c, uint32_t d) {
    asm volatile("stmatrix.sync.aligned.m8n8.x4.shared.b16 [%0], {%1,%2,%3,%4};" ::"r"(addr), "r"(a), "r"(b), "r"(c), "r"(d) : "memory");
}
__device__ __forceinline__ void fence_async() { asm volatile("fence.proxy.async.shared::cta;" ::: "memory"); }
__device__ __forceinline__ void bar_sync(int id, int n) { asm volatile("bar.sync %0, %1;" ::"r"(id), "r"(n) : "memory"); }
__device__ __forceinline__ void bar_arrive(int id, int n) { asm volatile("bar.arrive %0, %1;" ::"r"(id), "r"(n) : "memory"); }
__device__ __forceinline__ void wg_fence() { asm volatile("wgmma.fence.sync.aligned;" ::: "memory"); }
__device__ __forceinline__ void wg_commit() { asm volatile("wgmma.commit_group.sync.aligned;" ::: "memory"); }
template <int N> __device__ __forceinline__ void wg_wait() { asm volatile("wgmma.wait_group.sync.aligned %0;" ::"n"(N) : "memory"); }

constexpr uint32_t SB0 = 1024;
__host__ __device__ constexpr uint32_t dlo(uint32_t off, uint32_t lbo) { return ((SB0 + off) >> 4) | ((lbo >> 4) << 16); }
__host__ __device__ constexpr uint32_t dhi(uint32_t sbo, uint32_t sw) { return (sbo >> 4) | (sw << 30); }
__device__ __forceinline__ uint64_t dbase(uint32_t lo, uint32_t hi) { uint64_t d; asm volatile("mov.b64 %0, {%1, %2};" : "=l"(d) : "r"(lo), "r"(hi)); return d; }
#define BASE128(off, lbo, adj) dbase(dlo(off, lbo) + (adj), dhi(1024, 1))
#define BASE64(off, lbo, adj) dbase(dlo(off, lbo) + (adj), dhi(512, 2))

#define ACC4(d, o) "+f"(d[o]), "+f"(d[o + 1]), "+f"(d[o + 2]), "+f"(d[o + 3])
#define ACC28(d) ACC4(d, 0), ACC4(d, 4), ACC4(d, 8), ACC4(d, 12), ACC4(d, 16), ACC4(d, 20), ACC4(d, 24)
#define ACC32(d, o) ACC4(d, o), ACC4(d, o + 4), ACC4(d, o + 8), ACC4(d, o + 12), ACC4(d, o + 16), ACC4(d, o + 20), ACC4(d, o + 24), ACC4(d, o + 28)

template <int TB, uint64_t D>
__device__ __forceinline__ void mma_rs56(float* d, uint32_t a0, uint32_t a1, uint32_t a2, uint32_t a3, int sd, uint64_t base) {
    asm volatile("{ .reg .pred p; .reg .b64 db; setp.ne.b32 p, %32, 0; add.u64 db, %33, %34;\n"
                 "wgmma.mma_async.sync.aligned.m64n56k16.f32.bf16.bf16 "
                 "{%0,%1,%2,%3,%4,%5,%6,%7,%8,%9,%10,%11,%12,%13,%14,%15,%16,%17,%18,%19,%20,%21,%22,%23,%24,%25,%26,%27}, "
                 "{%28,%29,%30,%31}, db, p, 1, 1, %35; }\n"
                 : ACC28(d)
                 : "r"(a0), "r"(a1), "r"(a2), "r"(a3), "r"(sd), "l"(base), "n"(D), "n"(TB));
}
template <int TB, uint64_t D>
__device__ __forceinline__ void mma_rs64(float* d, uint32_t a0, uint32_t a1, uint32_t a2, uint32_t a3, int sd, uint64_t base) {
    asm volatile("{ .reg .pred p; .reg .b64 db; setp.ne.b32 p, %36, 0; add.u64 db, %37, %38;\n"
                 "wgmma.mma_async.sync.aligned.m64n64k16.f32.bf16.bf16 "
                 "{%0,%1,%2,%3,%4,%5,%6,%7,%8,%9,%10,%11,%12,%13,%14,%15,%16,%17,%18,%19,%20,%21,%22,%23,%24,%25,%26,%27,%28,%29,%30,%31}, "
                 "{%32,%33,%34,%35}, db, p, 1, 1, %39; }\n"
                 : ACC32(d, 0)
                 : "r"(a0), "r"(a1), "r"(a2), "r"(a3), "r"(sd), "l"(base), "n"(D), "n"(TB));
}
template <int TB, uint64_t D>
__device__ __forceinline__ void mma_rs128(float* d, uint32_t a0, uint32_t a1, uint32_t a2, uint32_t a3, int sd, uint64_t base) {
    asm volatile("{ .reg .pred p; .reg .b64 db; setp.ne.b32 p, %68, 0; add.u64 db, %69, %70;\n"
                 "wgmma.mma_async.sync.aligned.m64n128k16.f32.bf16.bf16 "
                 "{%0,%1,%2,%3,%4,%5,%6,%7,%8,%9,%10,%11,%12,%13,%14,%15,%16,%17,%18,%19,%20,%21,%22,%23,%24,%25,%26,%27,%28,%29,%30,%31,%32,%33,%34,%35,%36,%37,%38,%39,%40,%41,%42,%43,%44,%45,%46,%47,%48,%49,%50,%51,%52,%53,%54,%55,%56,%57,%58,%59,%60,%61,%62,%63}, "
                 "{%64,%65,%66,%67}, db, p, 1, 1, %71; }\n"
                 : ACC32(d, 0), ACC32(d, 32)
                 : "r"(a0), "r"(a1), "r"(a2), "r"(a3), "r"(sd), "l"(base), "n"(D), "n"(TB));
}
template <uint64_t DA, uint64_t DB>
__device__ __forceinline__ void mma_ss56_tt(float* d, int sd, uint64_t ba, uint64_t bb) {
    asm volatile("{ .reg .pred p; .reg .b64 da, db; setp.ne.b32 p, %28, 0; add.u64 da, %29, %31; add.u64 db, %30, %32;\n"
                 "wgmma.mma_async.sync.aligned.m64n56k16.f32.bf16.bf16 "
                 "{%0,%1,%2,%3,%4,%5,%6,%7,%8,%9,%10,%11,%12,%13,%14,%15,%16,%17,%18,%19,%20,%21,%22,%23,%24,%25,%26,%27}, "
                 "da, db, p, 1, 1, 1, 1; }\n"
                 : ACC28(d)
                 : "r"(sd), "l"(ba), "l"(bb), "n"(DA), "n"(DB));
}
template <int... I> struct Seq {};
template <class F, int... I> __device__ __forceinline__ void static_for_impl(F&& f, Seq<I...>) { (f(std::integral_constant<int, I>{}), ...); }
#define FOR7(...) static_for_impl([&](auto T_) { constexpr int t = decltype(T_)::value; __VA_ARGS__; }, Seq<0, 1, 2, 3, 4, 5, 6>{})
#define FOR8(...) static_for_impl([&](auto T_) { constexpr int t = decltype(T_)::value; __VA_ARGS__; }, Seq<0, 1, 2, 3, 4, 5, 6, 7>{})
#define FOR14(...) static_for_impl([&](auto T_) { constexpr int t = decltype(T_)::value; __VA_ARGS__; }, Seq<0, 1, 2, 3, 4, 5, 6, 7, 8, 9, 10, 11, 12, 13>{})

__device__ __forceinline__ int kblk(int p, int b) { return b == 0 ? p : b - (b <= p); }
__host__ __device__ constexpr int krow(int t) { return t < 3 ? 16 * t : (t < 6 ? 56 + 16 * (t - 3) : 48); }
#define AQ(A, b, t) ((t) < 3 ? A[2 * (b)][4 * (t)] : (t) < 6 ? A[2 * (b) + 1][4 * ((t) - 3)] : A[2 * (b)][12]), \
                    ((t) < 3 ? A[2 * (b)][4 * (t) + 1] : (t) < 6 ? A[2 * (b) + 1][4 * ((t) - 3) + 1] : A[2 * (b)][13]), \
                    ((t) < 3 ? A[2 * (b)][4 * (t) + 2] : (t) < 6 ? A[2 * (b) + 1][4 * ((t) - 3) + 2] : A[2 * (b) + 1][12]), \
                    ((t) < 3 ? A[2 * (b)][4 * (t) + 3] : (t) < 6 ? A[2 * (b) + 1][4 * ((t) - 3) + 3] : A[2 * (b) + 1][13])
#define D128(off, t) ((uint64_t)(((off) + krow(t) * 128) >> 4) + ((uint64_t)((t) == 6 ? (7168 - 1024) >> 4 : 0) << 32))
#define D64(off, t) ((uint64_t)(((off) + krow(t) * 64) >> 4) + ((uint64_t)((t) == 6 ? (3584 - 512) >> 4 : 0) << 32))

#define PL(k) (((k) - 3) * PLANE)
__device__ __forceinline__ void st_word(uint32_t* p, uint32_t v) { asm volatile("st.relaxed.gpu.global.u32 [%0], %1;" ::"l"(p), "r"(v) : "memory"); }
__device__ __forceinline__ uint32_t ld_word(const uint32_t* p) { uint32_t v; asm volatile("ld.relaxed.gpu.global.u32 %0, [%1];" : "=r"(v) : "l"(p) : "memory"); return v; }
__device__ __forceinline__ void tag_slice(uint32_t* w, uint32_t tag) { w[0] = settag(w[0], tag); w[4] = settag(w[4], tag); w[8] = settag(w[8], tag); w[12] = settag(w[12], tag); }
template <int O>
__device__ __forceinline__ void send_slice(uint4* dst, int lane, const uint32_t* w) {
    st_pkt<O>(dst, w[0], w[1], w[2], w[3]);
    st_pkt<O + 32>(dst, w[4], w[5], w[6], w[7]);
    st_pkt<O + 64>(dst, w[8], w[9], w[10], w[11]);
    asm volatile("{ .reg .b64 t; mov.b64 t, {%1,%2}; st.relaxed.gpu.global.b64 [%0+%3], t; }" ::"l"((char*)dst - lane * 8), "r"(w[12]), "r"(w[13]), "n"(16 * (O + 96)) : "memory");
}
#define RW4(v, o) "+r"(v[o]), "+r"(v[(o) + 1]), "+r"(v[(o) + 2]), "+r"(v[(o) + 3])
#define RW2(v, o) "+r"(v[o]), "+r"(v[(o) + 1])
#define WR4(v, o) "=&r"(v[o]), "=&r"(v[(o) + 1]), "=&r"(v[(o) + 2]), "=&r"(v[(o) + 3])
#define LDP(a, b, c, d, addr, off) "ld.relaxed.gpu.global.b128 q, [" addr "+" off "];\n mov.b128 {" a "," b "," c "," d "}, q;\n"
#define LDH(a, b, addr, off) "ld.relaxed.gpu.global.b64 h, [" addr "+" off "];\n mov.b64 {" a "," b "}, h;\n"
#define VOTE_OK "and.b32 t, t, 1;\n setp.ne.u32 p, t, 0;\n vote.sync.any.pred p, p, 0xffffffff;\n @!p bra.uni DN;\n"
#define CHK(x, tag) "lop3.b32 t, " x ", " tag ", t, 0xBE;\n"
__device__ __forceinline__ void check_cnt(uint32_t v, const uint32_t* p, uint32_t target) {
    asm volatile("{ .reg .pred p; .reg .b32 n, t; mov.u32 n, 0; mov.u32 t, %2;\n LP:\n"
                 "sub.s32 t, t, %1;\n setp.lt.s32 p, t, 0;\n vote.sync.any.pred p, p, 0xffffffff;\n @!p bra.uni DN;\n ld.relaxed.gpu.global.u32 t, [%0];\n" SPIN_TAIL("7")
                 ::"l"(p), "r"(target), "r"(v) : "memory");
}
__device__ __forceinline__ void poll_cnt(const uint32_t* p, uint32_t target) {
    asm volatile("{ .reg .pred p; .reg .b32 n, t; mov.u32 n, 0;\n LP:\n"
                 "ld.relaxed.gpu.global.u32 t, [%0];\n sub.s32 t, t, %1;\n setp.lt.s32 p, t, 0;\n vote.sync.any.pred p, p, 0xffffffff;\n @!p bra.uni DN;\n" SPIN_TAIL("1")
                 ::"l"(p), "r"(target) : "memory");
}
template <int STR>
__device__ __forceinline__ void poll4_kv(uint32_t* v, const uint4* p, uint32_t tag) {
    asm volatile("{ .reg .pred p; .reg .b32 n, t; .reg .b128 q; mov.u32 n, 0;\n LP:\n"
                 LDP("%0", "%1", "%2", "%3", "%16", "0") LDP("%4", "%5", "%6", "%7", "%16", "%18")
                 LDP("%8", "%9", "%10", "%11", "%16", "%19") LDP("%12", "%13", "%14", "%15", "%16", "%20")
                 "xor.b32 t, %0, %17;\n" CHK("%4", "%17") CHK("%8", "%17") CHK("%12", "%17") VOTE_OK SPIN_TAIL("2")
                 : WR4(v, 0), WR4(v, 4), WR4(v, 8), WR4(v, 12)
                 : "l"(p), "r"(tag), "n"(16 * STR), "n"(32 * STR), "n"(48 * STR)
                 : "memory");
}
template <int B>
__device__ __forceinline__ void blk_load(uint32_t (&A)[8][14], const uint4* src, int lane) {
    ld_pkt<0>(&A[2 * B][0], src); ld_pkt<32>(&A[2 * B][4], src); ld_pkt<64>(&A[2 * B][8], src);
    ld_pkt<512>(&A[2 * B + 1][0], src); ld_pkt<544>(&A[2 * B + 1][4], src); ld_pkt<576>(&A[2 * B + 1][8], src);
    asm volatile("{ .reg .b64 h;\n" LDH("%0", "%1", "%4", "1536") LDH("%2", "%3", "%4", "9728") "}"
                 : "=&r"(A[2 * B][12]), "=&r"(A[2 * B][13]), "=&r"(A[2 * B + 1][12]), "=&r"(A[2 * B + 1][13])
                 : "l"((const char*)src - lane * 8) : "memory");
}
template <int B>
__device__ __forceinline__ void blk_check(uint32_t (&A)[8][14], const uint4* src, int lane, uint32_t tag) {
    asm volatile("{ .reg .pred p; .reg .b32 n, t; .reg .b128 q; .reg .b64 h, a8; mov.u32 n, 0;\n LP:\n"
                 "xor.b32 t, %0, %30;\n" CHK("%4", "%30") CHK("%8", "%30") CHK("%12", "%30") CHK("%16", "%30") CHK("%20", "%30") CHK("%24", "%30") CHK("%26", "%30") VOTE_OK
                 LDP("%0", "%1", "%2", "%3", "%28", "0") LDP("%4", "%5", "%6", "%7", "%28", "512") LDP("%8", "%9", "%10", "%11", "%28", "1024")
                 LDP("%12", "%13", "%14", "%15", "%28", "8192") LDP("%16", "%17", "%18", "%19", "%28", "8704") LDP("%20", "%21", "%22", "%23", "%28", "9216")
                 "mad.wide.s32 a8, %29, -8, %28;\n" LDH("%24", "%25", "a8", "1536") LDH("%26", "%27", "a8", "9728") SPIN_TAIL("3")
                 "\n and.b32 %0, %0, -2; and.b32 %4, %4, -2; and.b32 %8, %8, -2; and.b32 %12, %12, -2; and.b32 %16, %16, -2; and.b32 %20, %20, -2; and.b32 %24, %24, -2; and.b32 %26, %26, -2;"
                 : RW4(A[2 * B], 0), RW4(A[2 * B], 4), RW4(A[2 * B], 8), RW4(A[2 * B + 1], 0), RW4(A[2 * B + 1], 4), RW4(A[2 * B + 1], 8),
                   RW2(A[2 * B], 12), RW2(A[2 * B + 1], 12)
                 : "l"(src), "r"(lane), "r"(tag)
                 : "memory");
}
__device__ __forceinline__ void st_async4(uint32_t a, uint32_t x, uint32_t y, uint32_t z, uint32_t w, uint32_t bar) {
    asm volatile("st.async.weak.shared::cluster.mbarrier::complete_tx::bytes.v4.b32 [%0], {%1,%2,%3,%4}, [%5];" ::"r"(a), "r"(x), "r"(y), "r"(z), "r"(w), "r"(bar) : "memory");
}
__device__ __forceinline__ uint32_t mapa(uint32_t a, uint32_t cta) { uint32_t r; asm("mapa.shared::cluster.u32 %0, %1, %2;" : "=r"(r) : "r"(a), "r"(cta)); return r; }
__device__ __forceinline__ void stat_load(uint32_t* v, const uint4* p) { ld_pkt<0>(v, p); ld_pkt<512>(v + 4, p); }
__device__ __forceinline__ void stat_check(uint32_t* v, const uint4* p, uint32_t tag) {
    asm volatile("{ .reg .pred p; .reg .b32 n, t; .reg .b128 q; mov.u32 n, 0;\n LP:\n"
                 "xor.b32 t, %3, %9;\n" CHK("%7", "%9") VOTE_OK
                 LDP("%0", "%1", "%2", "%3", "%8", "0") LDP("%4", "%5", "%6", "%7", "%8", "8192") SPIN_TAIL("4")
                 : RW4(v, 0), RW4(v, 4) : "l"(p), "r"(tag) : "memory");
}
__device__ __forceinline__ uint32_t x_bits(const uint32_t* X) {
    uint32_t r;
    asm volatile("{ .reg .b32 a, b; prmt.b32 a, %1, %2, 0x0040; prmt.b32 b, %3, %4, 0x0040; prmt.b32 %0, a, b, 0x5410; }" : "=r"(r) : "r"(X[0]), "r"(X[4]), "r"(X[8]), "r"(X[12]));
    return r;
}
template <int O>
__device__ __forceinline__ void slice_load(uint32_t* v, const uint4* p, int lane) {
    ld_pkt<O>(v, p); ld_pkt<O + 32>(v + 4, p); ld_pkt<O + 64>(v + 8, p);
    asm volatile("{ .reg .b64 h;\n" LDH("%0", "%1", "%2", "%3") "}" : "=r"(v[12]), "=r"(v[13]) : "l"((const char*)p - lane * 8), "n"(16 * (O + 96)) : "memory");
}
template <int O>
__device__ __forceinline__ void slice_check(uint32_t* v, const uint4* p, int lane, uint32_t tag) {
    asm volatile("{ .reg .pred p; .reg .b32 n, t; .reg .b128 q; .reg .b64 h; mov.u32 n, 0;\n LP:\n"
                 "xor.b32 t, %0, %16;\n" CHK("%4", "%16") CHK("%8", "%16") CHK("%12", "%16") VOTE_OK
                 LDP("%0", "%1", "%2", "%3", "%14", "%17") LDP("%4", "%5", "%6", "%7", "%14", "%18") LDP("%8", "%9", "%10", "%11", "%14", "%19")
                 LDH("%12", "%13", "%15", "%20") SPIN_TAIL("5")
                 : RW4(v, 0), RW4(v, 4), RW4(v, 8), RW2(v, 12)
                 : "l"(p), "l"((const char*)p - lane * 8), "r"(tag), "n"(16 * O), "n"(16 * (O + 32)), "n"(16 * (O + 64)), "n"(16 * (O + 96))
                 : "memory");
}
__device__ __forceinline__ void x_fix(uint32_t* X, uint32_t bits) {
    X[0] = __byte_perm(X[0], bits, 0x3214); X[4] = __byte_perm(X[4], bits, 0x3215); X[8] = __byte_perm(X[8], bits, 0x3216); X[12] = __byte_perm(X[12], bits, 0x3217);
}
__device__ __forceinline__ void sts4(uint32_t a, uint32_t x, uint32_t y, uint32_t z, uint32_t w) {
    asm volatile("st.shared.v4.u32 [%0], {%1,%2,%3,%4};" ::"r"(a), "r"(x), "r"(y), "r"(z), "r"(w) : "memory");
}
__device__ __forceinline__ void lds4(uint32_t* v, uint32_t a) {
    asm volatile("ld.shared.v4.u32 {%0,%1,%2,%3}, [%4];" : "=r"(v[0]), "=r"(v[1]), "=r"(v[2]), "=r"(v[3]) : "r"(a) : "memory");
}
struct LnCoef { uint32_t hi, lo, sh; };
__device__ __forceinline__ LnCoef ln_coef(float sum, float sq) {
    sum += __shfl_xor_sync(0xffffffffu, sum, 1); sq += __shfl_xor_sync(0xffffffffu, sq, 1);
    sum += __shfl_xor_sync(0xffffffffu, sum, 2); sq += __shfl_xor_sync(0xffffffffu, sq, 2);
    const float mean = sum * (1.f / 448.f);
    const float var = fmaxf(fmaf(-mean, mean, sq * (1.f / 448.f)), 0.f);
    const float sc = rsqrtf(var + 1e-5f);
    LnCoef r;
    r.hi = pack2(sc, sc);
    const float lo = sc - bf_lo(r.hi), sh = -mean * sc;
    r.lo = pack2(lo, lo);
    r.sh = pack2(sh, sh);
    return r;
}
template <int B>
__device__ __forceinline__ void normalize(uint32_t (&A)[8][14], const LnCoef& c0, const LnCoef& c1) {
#pragma unroll
    for (int s = 2 * B; s < 2 * B + 2; s++)
#pragma unroll
        for (int i = 0; i < 14; i++) {
            const LnCoef& k = (i & 1) ? c1 : c0;
            asm("{ .reg .b32 t; fma.rn.bf16x2 t, %0, %2, %3; fma.rn.bf16x2 %0, %0, %1, t; }" : "+r"(A[s][i]) : "r"(k.hi), "r"(k.lo), "r"(k.sh));
        }
}
__device__ __forceinline__ void slice_stats(const uint32_t* w, float* st) {
    float a = 0.f, b = 0.f, p = 0.f, q = 0.f;
#pragma unroll
    for (int i = 0; i < 7; i++) {
        const float e0 = bf_lo(w[2 * i]), e1 = bf_hi(w[2 * i]), e2 = bf_lo(w[2 * i + 1]), e3 = bf_hi(w[2 * i + 1]);
        a += e0 + e1; b += e2 + e3;
        p = fmaf(e0, e0, p); p = fmaf(e1, e1, p); q = fmaf(e2, e2, q); q = fmaf(e3, e3, q);
    }
    a += __shfl_xor_sync(0xffffffffu, a, 1); p += __shfl_xor_sync(0xffffffffu, p, 1); b += __shfl_xor_sync(0xffffffffu, b, 1); q += __shfl_xor_sync(0xffffffffu, q, 1);
    a += __shfl_xor_sync(0xffffffffu, a, 2); p += __shfl_xor_sync(0xffffffffu, p, 2); b += __shfl_xor_sync(0xffffffffu, b, 2); q += __shfl_xor_sync(0xffffffffu, q, 2);
    st[0] = a; st[1] = p; st[2] = b; st[3] = q;
}
__device__ __forceinline__ void dual_softmax(const float* p, uint32_t* out) {
    constexpr float L = 1.4426950408889634f;
#pragma unroll
    for (int r = 0; r < 2; r++) {
        float mx = fmaxf(p[2 * r], p[2 * r + 1]), mn = fminf(p[2 * r], p[2 * r + 1]);
#pragma unroll
        for (int i = 1; i < 7; i++) {
            mx = fmaxf(mx, fmaxf(p[4 * i + 2 * r], p[4 * i + 2 * r + 1]));
            mn = fminf(mn, fminf(p[4 * i + 2 * r], p[4 * i + 2 * r + 1]));
        }
        mx = fmaxf(mx, __shfl_xor_sync(0xffffffffu, mx, 1));
        mn = fminf(mn, __shfl_xor_sync(0xffffffffu, mn, 1));
        const float bx = -mx * L, bn = mn * L;
        float ep[14], en[14], sp = 0.f, sn = 0.f;
#pragma unroll
        for (int i = 0; i < 14; i++) {
            const float v = p[4 * (i >> 1) + 2 * r + (i & 1)];
            ep[i] = ex2(fmaf(v, L, bx));
            en[i] = ex2(fmaf(v, -L, bn));
            sp += ep[i]; sn += en[i];
        }
        sp += __shfl_xor_sync(0xffffffffu, sp, 1);
        sn += __shfl_xor_sync(0xffffffffu, sn, 1);
        const float ip = rcp(sp), in = rcp(sn);
#pragma unroll
        for (int i = 0; i < 7; i++) {
            out[4 * i + r] = pack2(ep[2 * i] * ip, ep[2 * i + 1] * ip);
            out[4 * i + 2 + r] = pack2(en[2 * i] * in, en[2 * i + 1] * in);
        }
    }
}
__device__ __forceinline__ float geglu(float g, float u) {
    const float t = tanh_hw(g * fmaf(g * g, 0.7978845608028654f * 0.044715f, 0.7978845608028654f));
    const float gu = g * u;
    return fmaf(t, gu, gu);
}
__device__ __forceinline__ void phi_gemm(const float* t, float* p) {
    uint32_t w[14];
#pragma unroll
    for (int i = 0; i < 14; i++) w[i] = pack2(t[2 * i], t[2 * i + 1]);
    const uint64_t db = BASE128(OFF_WPHI, 16, 0);
    wg_fence();
    mma_rs56<0, 0>(p, w[0], w[1], w[2], w[3], 0, db);
    mma_rs56<0, 2>(p, w[4], w[5], w[6], w[7], 1, db);
    mma_rs56<0, 4>(p, w[8], w[9], w[10], w[11], 1, db);
    mma_rs56<0, 6>(p, w[12], w[13], 0u, 0u, 1, db);
    wg_commit();
    wg_wait<0>();
}

}

#define BAR(i) (bars + 8 * (i))
#define R_WAIT() mbar_wait(BAR(slot), ph)
#define WSUM(i)
#define R_ADJ (slot * (STAGE >> 4))
#define R_NEXT() do { eb2 = eb1; eb1 = BAR(B_EMPTY + slot); if (++slot == NST) { slot = 0; ph ^= 1; } } while (0)
#define R_RELEASE(k) do { if (lane == 0) mbar_arrive((k) == 1 ? eb1 : eb2); } while (0)
#define PUSH_BEGIN() do { mbar_wait(BAR(B_ACK + wgi), ackph); ackph ^= 1; } while (0)
#define PUSH_ACK() do { __syncwarp(); if (lane == 0) asm volatile("mbarrier.arrive.shared::cluster.b64 _, [%0];" ::"r"(mapa(BAR(B_ACK + wgi), hr ^ 1)) : "memory"); } while (0)

__global__ void __cluster_dims__(2, 1, 1) __launch_bounds__(384, 1)
fused_kernel(Scratch* const sc, const __nv_bfloat16* __restrict__ x_in, const __nv_bfloat16* __restrict__ w_phi, const int trips,
             const __nv_bfloat16* __restrict__ wg, const __nv_bfloat16* __restrict__ wu, const __nv_bfloat16* __restrict__ wd,
             const __grid_constant__ Maps maps) {
    extern __shared__ __align__(1024) unsigned char smem_raw[];
    const uint32_t sb = s2u(smem_raw);
    const uint32_t bars = sb + OFF_BAR;
    const int wgi = __shfl_sync(0xffffffffu, threadIdx.x >> 7, 0);
    const int hr = blockIdx.x & 1, ck = blockIdx.x >> 1;
    const int gp = (ck - 4) & 7, q7 = ((ck - 36) * 37) >> 8;
    const int pr = __shfl_sync(0xffffffffu, ck < 4 ? ck : (ck < 36 ? (ck - 4) >> 3 : q7), 0);
    const int tile = __shfl_sync(0xffffffffu, ck < 4 ? 0 : (ck < 36 ? (gp ? 2 * gp : 1) : 2 * (ck - 36 - 7 * q7) + 3), 0);
    const int sl = 2 * pr + hr;
    STAMP(0);
    GSTAMP(60);
    if (threadIdx.x == 256) {
#pragma unroll
        for (int i = 0; i < NST; i++) mbar_init(BAR(i), 1);
        asm volatile("fence.mbarrier_init.release.cluster;" ::: "memory");
    }
    if (threadIdx.x == 288) {
        if ((sb & 0x3FFFF) != SB0) asm volatile("trap;");
#pragma unroll
        for (int i = NST; i < B_COUNT; i++) mbar_init(BAR(i), i >= B_ACK ? 4 : (i < B_RECV || i == B_LATE ? 8 : 1));
        asm volatile("fence.mbarrier_init.release.cluster;" ::: "memory");
    }
    __syncwarp();
    asm volatile("barrier.cluster.arrive.relaxed.aligned;" ::: "memory");

    if (wgi == 2) {
        asm volatile("setmaxnreg.dec.sync.aligned.u32 40;");
        const int t128 = fresh_tid() & 127, w = __shfl_sync(0xffffffffu, t128 >> 5, 0), lane = t128 & 31;
        uint32_t e0[2] = {0, 0}, e1[2] = {0, 0}, cw_target = 0;
        if (w == 0) {
#pragma unroll 1
            for (int n = 0; n < NST; n++) {
                const uint32_t dst = sb + n * STAGE, fb = BAR(n);
                asm volatile(ELECT "mbarrier.arrive.expect_tx.shared::cta.b64 _, [%0], %1; }" ::"r"(fb), "r"(n < 2 ? 2 * STAGE : STAGE) : "memory");
                if (n < 2) {
                    tma3x(sb + OFF_H + n * STAGE, &maps.x, tile * 128 + n * 64, fb);
                    tma3x(dst, &maps.x, tile * 128 + n * 64 + 32, fb);
                } else {
                    if (n == 3) mbar_wait(BAR(1), 0);
                    const int ra = 112 * (n - 2);
                    tma2d(dst, &maps.qkv, 448 + 56 * sl, ra, fb);
                    tma2d(dst + HALF, &maps.qkv, 896 + 56 * sl, ra, fb);
                }
            }
            asm volatile("barrier.cluster.wait.aligned;" ::: "memory");
            cw_target = (ld_word(g_cw + sl * 32) & ~15u) + 16;
#pragma unroll 1
            for (int k = 0; k < 2; k++) {
                const int n = t128 + 32 * k;
                int m = n - 2 - (n > PACK);
                const bool packed = m >= 30 ? (m < 38 || m >= 52) : m >= 22;
                if (m >= 30) m -= 30;
                if (n == PACK) m = tile < 8 ? tile : tile + 14;
                const int rot = n < 8 ? 0 : pr;
                const int ra = 112 * kblk(rot, m & 3), rb = 112 * kblk(rot, 2 * m & 3), rc = 112 * kblk(rot, (2 * m + 1) & 3);
                int kind = 0, m0, m1, c0, c1, r0, r1;
                if (m < 4) { m0 = m1 = 1; c0 = 448 + 56 * sl; c1 = c0 + 448; r0 = r1 = ra; }
                else if (m < 8) { m0 = m1 = m < 6 ? 1 : 2; c0 = c1 = 56 * sl; r0 = rb; r1 = rc; }
                else if (m < 20) { m0 = 3; m1 = 4; c0 = c1 = 224 * sl + 32 * hr + 64 * ((m - 8) >> 2); r0 = r1 = ra; }
                else if (m < 22) { kind = 2; m0 = 5; m1 = 6; c0 = c1 = 224 * sl + (hr ? 0 : 192); r0 = rb; r1 = rc; }
                else { m0 = m1 = 7; c0 = c1 = 56 * (2 * ((pr + (m >> 1) - 10) & 3) + hr); r0 = 224 * (sl ^ (m & 1)); r1 = r0 + 112; }
                if (packed) { kind = 1; r0 = sl * 16 + (m < 8 ? m : m - 14); r1 = 0; }
                e0[0] = e0[1]; e1[0] = e1[1];
                e0[1] = kind | (m0 << 2) | (m1 << 6) | (c0 << 10) | (c1 << 21);
                e1[1] = r0 | (r1 << 16);
            }
        } else {
            const int j = t128 - 32;
            asm volatile("barrier.cluster.wait.aligned;" ::: "memory");
            uint2 wv[7];
            const int k = j < 56 ? j : 55, hh = k >= 28;
#pragma unroll
            for (int i = 0; i < 7; i++) wv[i] = __ldg(reinterpret_cast<const uint2*>(w_phi + (sl * 56 + k) * 28) + i);
#pragma unroll 1
            for (int i = j; i < 7168 / 16; i += 96) sts4(sb + OFF_WPHI + i * 16, 0, 0, 0, 0);
            bar_sync(5, 96);
            if (j < 56) {
                uint32_t a4[4];
#pragma unroll
                for (int q = 0; q < 4; q++) a4[q] = sb + OFF_WPHI + (4 * hh + q) * 128 + ((((k >> 3) ^ (4 * hh + q)) & 7) << 4) + (k & 7) * 2;
                FOR14(const uint32_t v = (t & 1) ? wv[t >> 1].y : wv[t >> 1].x;
                      asm volatile("{ .reg .b16 l, h; mov.b32 {l, h}, %2; st.shared.u16 [%0+%3], l; st.shared.u16 [%1+%3], h; }"
                                   ::"r"(a4[t >= 7 ? 2 : 0]), "r"(a4[t >= 7 ? 3 : 1]), "r"(v), "n"((t % 7) * 1024) : "memory"));
            }
            __syncwarp();
            fence_async();
            bar_arrive(1, 224);
            bar_arrive(9, 224);
            if (w == 1) {
                mbar_wait(BAR(2), 0);
                mbar_wait(BAR(2), 1);
                const int b = blockIdx.x;
                asm volatile(ELECT "cp.async.bulk.prefetch.L2.global [%0], %1; }" ::"l"(wg + b * 6272), "r"(12544) : "memory");
                asm volatile(ELECT "cp.async.bulk.prefetch.L2.global [%0], %1; }" ::"l"(wu + b * 6272), "r"(12544) : "memory");
                asm volatile(ELECT "cp.async.bulk.prefetch.L2.global [%0], %1; }" ::"l"(wd + b * 6272), "r"(12544) : "memory");
            }
        }
        uint32_t kseq = ld_word(g_c1 + (sl * 8 * 16 + tile) * 32);
        int slot = 0, ph = 0, n = NST;
#pragma unroll 1
        for (int layer = 0; layer < 3; layer++) {
            if (w == 0) {
                const int nend = layer == 0 ? 11 : (layer == 1 ? 42 : 63);
#pragma unroll 1
                for (; n < nend; n++) {
                const uint32_t w0 = __shfl_sync(0xffffffffu, n < 32 ? e0[0] : e0[1], n & 31), w1 = __shfl_sync(0xffffffffu, n < 32 ? e1[0] : e1[1], n & 31);
                const uint32_t dst = sb + slot * STAGE, fb = BAR(n == PACK ? B_PACK : slot);
                const CUtensorMap* m0 = &maps.x + ((w0 >> 2) & 15);
                const CUtensorMap* m1 = &maps.x + ((w0 >> 6) & 15);
                const int c0 = (w0 >> 10) & 2047, c1 = w0 >> 21, r0 = w1 & 0xffff, r1 = w1 >> 16;
                if (n == 25) {
                    int it = 0;
                    uint32_t v;
                    do { asm volatile("ld.acquire.gpu.global.u32 %0, [%1];" : "=r"(v) : "l"(g_cw + sl * 32) : "memory"); } while ((int)(v - cw_target) < 0 && ++it < 0x400000);
                    asm volatile("fence.proxy.async.global;" ::: "memory");
                    __syncwarp();
                }
                mbar_wait(BAR(B_EMPTY + slot), ph);
                __syncwarp();
                asm volatile(ELECT "mbarrier.arrive.expect_tx.shared::cta.b64 _, [%0], %1; }" ::"r"(fb), "r"(STAGE) : "memory");
                if ((w0 & 3) == 0) {
                    tma2d(dst, m0, c0, r0, fb);
                    tma2d(dst + HALF, m1, c1, r1, fb);
                } else if (w0 & 1) {
                    asm volatile(ELECT "cp.async.bulk.shared::cluster.global.mbarrier::complete_tx::bytes [%0], [%1], %2, [%3]; }"
                                 ::"r"(dst), "l"(reinterpret_cast<const char*>(g_wp) + (size_t)r0 * STAGE), "r"(STAGE), "r"(fb) : "memory");
                } else {
                    tma2d(dst, m0, c0, r0, fb); tma2d(dst + 7168, m0, c0, r1, fb);
                    tma2d(dst + HALF, m1, c0, r0, fb); tma2d(dst + HALF + 7168, m1, c0, r1, fb);
                }
                if (n == PACK) asm volatile(ELECT "mbarrier.arrive.shared::cta.b64 _, [%0]; }" ::"r"(BAR(slot)) : "memory");
                if (++slot == NST) { slot = 0; ph ^= 1; }
                }
            } else if (w == 1 && layer == 1) {
                constexpr int ps = PACK % NST;
                mbar_wait(BAR(B_PACK), 0);
                asm volatile("{ .reg .pred e; elect.sync _|e, 0xffffffff;\n"
                             "@e cp.async.bulk.global.shared::cta.bulk_group [%0], [%1], %2;\n"
                             "@e cp.async.bulk.commit_group;\n"
                             "@e cp.async.bulk.wait_group.read 0;\n"
                             "@e mbarrier.arrive.shared::cta.b64 _, [%3], 8;\n"
                             "@e cp.async.bulk.wait_group 0;\n"
                             "@e fence.proxy.async.global;\n"
                             "@e red.release.gpu.global.add.u32 [%4], 1; }"
                             ::"l"(reinterpret_cast<char*>(g_wp) + (size_t)(sl * 16 + tile) * STAGE), "r"(sb + ps * STAGE), "r"(STAGE), "r"(BAR(B_EMPTY + ps)), "l"(g_cw + sl * 32) : "memory");
                __syncwarp();
            }
            if (layer < 2) {
            const uint32_t tag = layer ^ 1;
            kseq++;
            bar_sync(7, 384);
            ASTAMP(0);
            if (tile < 15) {
                const int sq = lane >> 3, pk = 8 * w + (lane & (tile == 14 ? 3 : 7));
                uint32_t v[16];
                if (layer == 0) poll_cnt(g_c1 + ((sl * 8 + (w >> 1) * 4 + (tile >> 2)) * 16 + (lane & 15)) * 32, kseq);
                ASTAMP(1);
                poll4_kv<32>(v, g_kv1 + ((sl * 16 + tile) * 16 + 4 * sq) * 32 + pk, tag);
#pragma unroll
                for (int k = 0; k < 4; k++) {
                    float lo = (bf_lo(v[k]) + bf_lo(v[4 + k])) + (bf_lo(v[8 + k]) + bf_lo(v[12 + k]));
                    float hi = (bf_hi(v[k]) + bf_hi(v[4 + k])) + (bf_hi(v[8 + k]) + bf_hi(v[12 + k]));
                    lo += __shfl_xor_sync(0xffffffffu, lo, 8); hi += __shfl_xor_sync(0xffffffffu, hi, 8);
                    lo += __shfl_xor_sync(0xffffffffu, lo, 16); hi += __shfl_xor_sync(0xffffffffu, hi, 16);
                    v[k] = pack2(lo, hi);
                }
                if (sq == 0) st_pkt<0>(g_kv2 + sl * 512 + 32 * tile + pk, settag(v[0], tag), v[1], v[2], v[3]);
            }
            ASTAMP(2);
            {
                const int item = t128 < 112 ? t128 : 112 + (t128 & 3), d = item >> 1;
                const int cc = t128 < 112 ? 2 * (d >= 28) + (item & 1) : item - 112;
                const int r = t128 < 112 ? d : 56 + (cc >> 1) + 2 * ((t128 - 112) >> 2);
                uint32_t ra = sb + OFF_KVB + r * 128 + 4 * cc, rx = (r & 7) << 4;
                asm volatile("" : "+r"(ra), "+r"(rx));
                FOR14(asm volatile("st.shared.u32 [%0+%2], %1;" ::"r"((ra ^ 8) + (((t & 7) << 4) ^ rx)), "r"(0), "n"((t >> 3) * 8192) : "memory"));
                uint32_t v[16];
                asm volatile("" : "+r"(ra), "+r"(rx));
                poll4_kv<8>(v, g_kv2 + sl * 512 + (item >> 3) * 32 + (item & 7), tag);
                FOR14(asm volatile("st.shared.u32 [%0+%2], %1;" ::"r"(ra + (((t & 7) << 4) ^ rx)), "r"(v[t < 7 ? t : t + 1]), "n"((t >> 3) * 8192) : "memory"));
                fence_async();
            }
            bar_arrive(3, 384);
            ASTAMP(3);
            }
        }
    } else {
        asm volatile("setmaxnreg.inc.sync.aligned.u32 232;");
        int lane = fresh_tid() & 31, prf = pr;
#define pr prf
#define g (lane >> 2)
#define c (lane & 3)
#define t128 (w * 32 + lane)
        const int wu = __shfl_sync(0xffffffffu, fresh_tid() >> 5, 0), w = wu & 3;
        const uint32_t xoff = __shfl_sync(0xffffffffu, (3 * PLANE + ((tile * 2 + wgi) * 8) * 512 + w * 128) * 16, 0);
        char* xu = reinterpret_cast<char*>(g_ex) + xoff;
#define FRESH() asm volatile("" : "+l"(xu), "+r"(lane), "+r"(prf))
#define xp0 (reinterpret_cast<uint4*>(xu) + lane)
        const uint32_t hbuf = sb + OFF_H + wgi * STAGE;
        uint32_t slot = 0, ph = 0, eb1 = 0, eb2 = 0, ackph = 0, rcvph = 0, gatph = 0, swp = 0;
        uint32_t ppid = 6;
#define cx(s) (reinterpret_cast<uint32_t*>(reinterpret_cast<uint4*>(xu) + PL(1) + 112 + (s) * 512))
#define stp (reinterpret_cast<uint4*>(xu) + g + PL(0) + 112)
        uint32_t seq = ld_word(cx(sl));
        uint32_t kseq = ld_word(g_c1 + ((sl * 8 + wu) * 16 + tile) * 32);
        uint32_t stag = ld_word(reinterpret_cast<const uint32_t*>(stp + sl * 512) + 3) & 1;
        asm volatile("barrier.cluster.wait.aligned;" ::: "memory");
        STAMP(1);
        uint32_t X[14];
        const uint32_t x0row = (w < 2 ? hbuf : sb + wgi * STAGE) + ((w & 1) * 16 + (lane & 15)) * 128;
        mbar_wait(BAR(wgi), 0);
        STAMP(51);
#pragma unroll
        for (int j = 0; j < 4; j++) {
            const int G = 7 * sl + min(2 * j + (lane >> 4), 6);
            uint32_t q2, q3;
            asm volatile("ldmatrix.sync.aligned.m8n8.x4.shared.b16 {%0,%1,%2,%3}, [%4];" : "=r"(X[4 * j]), "=r"(X[4 * j + 1]), "=r"(q2), "=r"(q3)
                         : "r"(x0row + (G >> 3) * 4096 + (((G ^ lane) & 7) << 4)) : "memory");
            if (j < 3) { X[(4 * j + 2) % 14] = q2; X[(4 * j + 3) % 14] = q3; }
        }
#define PUSH_SLICE(W)                                                                          \
    {                                                                                          \
        if (t128 == 0) mbar_expect_tx(BAR(B_RECV + wgi), 7168);                                \
        PUSH_BEGIN();                                                                          \
        const uint32_t ra = mapa(hbuf + 24576 + t128 * 16, hr ^ 1), rb = mapa(sb + OFF_XR + wgi * 3072, hr ^ 1), rbar = mapa(BAR(B_RECV + wgi), hr ^ 1); \
        st_async4(ra, W[0], W[1], W[2], W[3], rbar);                                           \
        st_async4(ra + 2048, W[4], W[5], W[6], W[7], rbar);                                    \
        st_async4(rb + t128 * 16, W[8], W[9], W[10], W[11], rbar);                             \
        asm volatile("st.async.weak.shared::cluster.mbarrier::complete_tx::bytes.v2.b32 [%0], {%1,%2}, [%3];" ::"r"(rb + 2048 + t128 * 8), "r"(W[12]), "r"(W[13]), "r"(rbar) : "memory"); \
    }
#define PULL_SLICE(W)                                                                          \
    {                                                                                          \
        uint32_t t0, t1;                                                                       \
        mbar_wait(BAR(B_RECV + wgi), rcvph);                                                   \
        rcvph ^= 1;                                                                            \
        lds4(&A[1][0], hbuf + 24576 + t128 * 16);                                              \
        lds4(&A[1][4], hbuf + 26624 + t128 * 16);                                              \
        lds4(&A[1][8], sb + OFF_XR + wgi * 3072 + t128 * 16);                                  \
        asm volatile("ld.shared.v2.u32 {%0,%1}, [%2];" : "=r"(t0), "=r"(t1) : "r"(sb + OFF_XR + wgi * 3072 + 2048 + t128 * 8) : "memory"); \
        _Pragma("unroll") for (int i = 0; i < 12; i++) A[0][i] = (i & 3) ? W[i] : W[i] & ~1u;  \
        A[1][0] &= ~1u; A[1][4] &= ~1u; A[1][8] &= ~1u;                                        \
        A[0][12] = (hr ? t0 : W[12]) & ~1u; A[0][13] = hr ? t1 : W[13];                        \
        A[1][12] = (hr ? W[12] : t0) & ~1u; A[1][13] = hr ? W[13] : t1;                        \
        asm volatile("" : RW4(A[0], 0), RW4(A[0], 4), RW4(A[0], 8), RW2(A[0], 12), RW4(A[1], 0), RW4(A[1], 4), RW4(A[1], 8), RW2(A[1], 12)); \
        swp = hr * 448;                                                                        \
    }
#define SWB(b, t, db, sh) ((b) == 0 && (t) < 6 ? ((t) < 3 ? db##p : db##m) : db)
#define DECL_DB(b, MK, lbo, sh) const uint64_t db = MK(0, lbo, R_ADJ), dbp = (b) == 0 ? MK(0, lbo, R_ADJ + (swp >> (sh))) : db, dbm = (b) == 0 ? MK(0, lbo, R_ADJ - (swp >> (sh))) : db;
#define PPB 2
#define PP_WAIT() if (wgi == 1) { bar_sync(ppid, 256); ppid ^= 14; }
#define PP_GO() if (wgi == 0) { bar_arrive(ppid, 256); ppid ^= 14; }
#define GAT_DST(B, s2) ((B) == 1 ? hbuf + w * 3584 + (s2) * 1792 : ((B) == 2 ? lateb + w * 3584 + (s2) * 1792 : ((s2) ? sb + OFF_KVB + wgi * 8192 : hbuf + 14336) + w * 1792))
#define GAT_ISSUE(B, base)                                                                     \
    {                                                                                          \
        const char* gs = xu + ((base) + kblk(pr, B) * 1024) * 16;                              \
        asm volatile("{ .reg .pred e; elect.sync _|e, 0xffffffff;\n"                           \
                     "@e mbarrier.arrive.expect_tx.shared::cta.b64 _, [%3], 3584;\n"           \
                     "@e cp.async.bulk.shared::cluster.global.mbarrier::complete_tx::bytes [%0], [%2], 1792, [%3];\n" \
                     "@e cp.async.bulk.shared::cluster.global.mbarrier::complete_tx::bytes [%1], [%2+8192], 1792, [%3]; }" \
                     ::"r"(GAT_DST(B, 0)), "r"(GAT_DST(B, 1)), "l"(gs), "r"(BAR(B_GAT + wu * 3 + (B) - 1)) : "memory"); \
        __syncwarp();                                                                          \
    }
#define GAT_FETCH(B)                                                                           \
    {                                                                                          \
        mbar_wait(BAR(B_GAT + wu * 3 + (B) - 1), (gatph >> (B)) & 1);                          \
        gatph ^= 1 << (B);                                                                     \
        _Pragma("unroll") for (int s2 = 0; s2 < 2; s2++) {                                     \
            const uint32_t ga = GAT_DST(B, s2) + lane * 16;                                    \
            lds4(&A[2 * (B) + s2][0], ga); lds4(&A[2 * (B) + s2][4], ga + 512); lds4(&A[2 * (B) + s2][8], ga + 1024); \
            asm volatile("ld.shared.v2.u32 {%0,%1}, [%2];" : "=r"(A[2 * (B) + s2][12]), "=r"(A[2 * (B) + s2][13]) : "r"(ga - lane * 8 + 1536) : "memory"); \
        }                                                                                      \
    }
#define LATE_ARRIVE() do { if (lane == 0) mbar_arrive(BAR(B_LATE)); } while (0)
#define LATE_WAIT() do { mbar_wait(BAR(B_LATE), gatph & 1); gatph ^= 1; } while (0)
#define PT 3
#define PREP(b, t, remote)                                                                     \
    if constexpr ((b) < 3 && (t) == PT) {                                                      \
        wg_commit();                                                                           \
        STAMP(74 + 6 * (step & 1) + 2 * (b));                                                  \
        if (remote) { if ((b) < FE) GAT_FETCH(((b) + 1) & 3) blk_check<((b) + 1) & 3>(A, BLK(xsrc, (b) + 1), lane, xtag); } \
        STAMP(75 + 6 * (step & 1) + 2 * (b));                                                  \
        normalize<((b) + 1) & 3>(A, k0, k1);                                                   \
        asm volatile("" : RW4(A[(2 * (b) + 2) & 7], 0), RW4(A[(2 * (b) + 2) & 7], 4), RW4(A[(2 * (b) + 2) & 7], 8), RW2(A[(2 * (b) + 2) & 7], 12), \
                          RW4(A[(2 * (b) + 3) & 7], 0), RW4(A[(2 * (b) + 3) & 7], 4), RW4(A[(2 * (b) + 3) & 7], 8), RW2(A[(2 * (b) + 3) & 7], 12)); \
        wg_fence();                                                                            \
    }
#define X0_BLOCK(b)                                                                            \
    { const int rr = lane & 7, hi = lane >> 4;                                                 \
    const uint32_t rowa = (w < 2 ? hbuf : sb + wgi * STAGE) + ((w & 1) * 16 + (lane & 15)) * 128; \
    FOR7(constexpr int G = 14 * (b) + (t < 3 ? 2 * t : (t < 6 ? 2 * t + 1 : 6));               \
         uint32_t q0, q1, q2, q3;                                                              \
         const uint32_t ad = t < 6 ? rowa + (((((G & 7) + hi) ^ rr) & 7) << 4) + ((G & 7) == 7 ? hi * 4096 : 0) : rowa + ((G + 7 * hi) >> 3) * 4096 + ((((G + 7 * hi) ^ rr) & 7) << 4); \
         asm volatile("ldmatrix.sync.aligned.m8n8.x4.shared.b16 {%0,%1,%2,%3}, [%4+%5];" : "=r"(q0), "=r"(q1), "=r"(q2), "=r"(q3) \
                      : "r"(ad), "n"(t < 6 ? (G >> 3) * 4096 : 0) : "memory");                 \
         if (t < 3) { A[2 * (b)][4 * t] = q0; A[2 * (b)][4 * t + 1] = q1; A[2 * (b)][4 * t + 2] = q2; A[2 * (b)][4 * t + 3] = q3; } \
         else if (t < 6) { A[2 * (b) + 1][(4 * t - 12) & 15] = q0; A[2 * (b) + 1][((4 * t - 12) & 15) + 1] = q1; A[2 * (b) + 1][((4 * t - 12) & 15) + 2] = q2; A[2 * (b) + 1][((4 * t - 12) & 15) + 3] = q3; } \
         else { A[2 * (b)][12] = q0; A[2 * (b)][13] = q1; A[2 * (b) + 1][12] = q2; A[2 * (b) + 1][13] = q3; }); }
#define BLK(base, b) ((base) + kblk(pr, b) * 1024)

#pragma unroll 1
        for (int step = 0; step < 4; step++) {
            FRESH();
            const uint32_t tag = (step >> 1) ^ 1;
            const int so = (step >> 1) * 24 + (step & 1) * 12;
            (void)so;
            uint32_t A[8][14];
            uint4* const xsrc = xp0 + ((step & 1) ? PL(2) : PL(0));
            const uint32_t xtag = (step & 1) ? tag : ((seq >> 3) & 1) ^ 1;
            uint32_t xbits;
            {
                float st[4];
                slice_stats(X, st);
                stag ^= 1;
                xbits = x_bits(X);
                tag_slice(X, xtag);
                if (step) send_slice<0>(xsrc + sl * 512, lane, X);
                if (c == 0) st_pkt<0>(stp + sl * 512, __float_as_uint(st[0]), __float_as_uint(st[1]), __float_as_uint(st[2]), settag(__float_as_uint(st[3]), stag));
            }
            STAMP(2 + so);
            uint32_t sv[8];
            const uint32_t lateb = sb + ((slot + NST - 1) % NST) * STAGE + wgi * HALF;
            if (step == 0) {
                X0_BLOCK(0) X0_BLOCK(1) X0_BLOCK(2) X0_BLOCK(3)
                mbar_wait(BAR(wgi ^ 1), 0);
                R_NEXT();
                R_NEXT();
                R_RELEASE(2);
                stat_load(sv, stp + c * 1024);
                stat_check(sv, stp + c * 1024, stag);
                STAMP(52 + step);
            } else {
                kill<14>(A[2]); kill<14>(A[3]); kill<14>(A[4]); kill<14>(A[5]); kill<14>(A[6]); kill<14>(A[7]);
                PUSH_SLICE(X)
                stat_load(sv, stp + c * 1024);
                PULL_SLICE(X)
                LATE_WAIT();
                stat_check(sv, stp + c * 1024, stag);
                STAMP(52 + step);
                const int pb = (step & 1) ? PL(2) : PL(0);
                GAT_ISSUE(1, pb) GAT_ISSUE(2, pb) GAT_ISSUE(3, pb)
            }
            LnCoef k0, k1;
            {
                k0 = ln_coef(__uint_as_float(sv[0]) + __uint_as_float(sv[4]), __uint_as_float(sv[1]) + __uint_as_float(sv[5]));
                k1 = ln_coef(__uint_as_float(sv[2]) + __uint_as_float(sv[6]), __uint_as_float(sv[3] & ~1u) + __uint_as_float(sv[7] & ~1u));
            }
            STAMP(3 + so);
            GSTAMP(70 + step);

            uint32_t late1 = 0;
            if ((step & 1) == 0) {
                float tq[28];
                {
                    float av[28];
#define KV_BLOCK(b)                                                                           \
    if ((b) == 1) late1 = eb2;                                                                \
    if ((b) == 2) { if (lane == 0) mbar_arrive(late1); wg_wait<2>(); R_RELEASE(2); }          \
    if ((b) == 3) PUSH_ACK();                                                                 \
    if ((b) >= FE && (b) < 3 && step) GAT_FETCH(((b) + 1) & 3)                                \
    R_WAIT();                                                                                 \
    if ((b) == PPK) { PP_WAIT() }                                                             \
    { DECL_DB(b, BASE128, 16, 0)                                                              \
    wg_fence();                                                                               \
    FOR7(mma_rs56<1, D128(0, t)>(tq, AQ(A, b, t), (b) + t > 0, SWB(b, t, db, 0));             \
         mma_rs56<1, D128(HALF, t)>(av, AQ(A, b, t), (b) + t > 0, SWB(b, t, db, 0));          \
         PREP(b, t, step)); }                                                                 \
    wg_commit();                                                                              \
    if ((b) == 3 && PPK < 4) { PP_GO() }                                                      \
    R_NEXT();
                    normalize<0>(A, k0, k1);
                    KV_BLOCK(0) KV_BLOCK(1) KV_BLOCK(2) KV_BLOCK(3)
                    wg_wait<0>();
                    if (lane < 3) mbar_arrive(BAR(B_EMPTY + (slot + NST - 1 - lane) % NST));
                    STAMP(4 + so);
                    WSUM(80 + 7 * (step >> 1));
                    const int m = lane >> 3, rr = lane & 7;
                    const uint32_t rowa = hbuf + 16384 + (w * 16 + rr + 8 * (m & 1)) * 128;
                    const uint32_t one = c == 0 ? 0x00003f80u : 0u;
                    if (step == 0) { bar_sync(wgi ? 9 : 1, 224); }
#pragma unroll
                    for (int j = 0; j < 4; j++) {
                        const uint32_t a = rowa + (((2 * j + (m >> 1)) ^ rr) << 4);
                        if (j < 3) stsm4(a, pack2(av[8 * j], av[8 * j + 1]), pack2(av[8 * j + 2], av[8 * j + 3]), pack2(av[8 * j + 4], av[8 * j + 5]), pack2(av[8 * j + 6], av[8 * j + 7]));
                        else stsm4(a, pack2(av[24], av[25]), pack2(av[26], av[27]), one, one);
                    }
                }
                uint32_t PH[28];
                int it = 1;
#pragma unroll 1
                do {
                    float pp[28];
                    phi_gemm(tq, pp);
                    dual_softmax(pp, PH);
                    if (((trips >> (it + 1)) & 1) == 0) continue;
                    {
                        const int m = lane >> 3, rr = lane & 7;
                        const uint32_t rowa = hbuf + (w * 16 + rr + 8 * (m & 1)) * 128;
#pragma unroll
                        for (int j = 0; j < 7; j++) {
                            const int cg = 2 * j + (m >> 1), hi = cg >= 7;
                            stsm4(rowa + hi * 8192 + (((cg - 7 * hi) ^ rr) << 4), PH[4 * j], PH[4 * j + 1], PH[4 * j + 2], PH[4 * j + 3]);
                        }
                    }
                    fence_async();
                    STAMP(5 + so);
#define Q_STAGE(b0)                                                                           \
    R_WAIT();                                                                                 \
    { DECL_DB(b0, BASE128, 16, 0)                                                             \
    wg_fence();                                                                               \
    FOR7(mma_rs56<1, D128(0, t)>(tq, AQ(A, b0, t), (b0) + t > 0, SWB(b0, t, db, 0)));         \
    FOR7(mma_rs56<1, D128(HALF, t)>(tq, AQ(A, (b0) + 1, t), 1, db)); }                        \
    wg_commit();                                                                              \
    R_NEXT();
                    if (QE && wgi == 0) { kill<28>(tq); Q_STAGE(0) Q_STAGE(2) wg_wait<1>(); R_RELEASE(2); wg_wait<0>(); R_RELEASE(1); }
                    bar_sync(2, 256);
                    float kv[28];
                    const uint64_t da = BASE128(OFF_H + 16384, 16, 0), dbk = BASE128(OFF_H, 16, wgi * 512);
                    wg_fence();
                    FOR8(constexpr uint64_t o = ((t >> 2) * STAGE + (t & 3) * 2048) >> 4; mma_ss56_tt<o, o>(kv, t > 0, da, dbk));
                    wg_commit();
                    wg_wait<0>();
#pragma unroll
                    for (int hf = 0; hf < 2; hf++) {
                        const int d = 16 * w + g + 8 * hf;
                        if ((d < 56 && (d >= 28) == (c >= 2)) || d == 56) {
                            const int item = d < 56 ? 2 * d + (c & 1) : 112 + c;
                            uint4* dst = g_kv1 + ((sl * 16 + (item >> 3)) * 16 + tile) * 32 + wgi * 16 + (item & 7);
#define KVW(i) pack2(kv[4 * (i) + 2 * hf], kv[4 * (i) + 2 * hf + 1])
                            st_pkt<0>(dst, settag(KVW(0), tag), KVW(1), KVW(2), KVW(3));
                            st_pkt<8>(dst, settag(KVW(4), tag), KVW(5), KVW(6), 0u);
                        }
                    }
                    __syncwarp();
                    kseq++;
                    if (lane == 0) st_word(g_c1 + ((sl * 8 + wu) * 16 + tile) * 32, kseq);
                    bar_arrive(7, 384);
                    STAMP(6 + so);
                    if (!QE || wgi == 1) { kill<28>(tq); Q_STAGE(0) Q_STAGE(2) wg_wait<1>(); R_RELEASE(2); wg_wait<0>(); R_RELEASE(1); }
                    STAMP(7 + so);
                    kill<28>(PH);
                } while (((trips >> (++it)) & 1));
                STAMP(8 + so);
                FRESH();
                if (step) {
                    slice_load<PL(0)>(X, xp0 + sl * 512, lane);
                } else {
                    const uint32_t* xp = reinterpret_cast<const uint32_t*>(x_in + (size_t)(tile * 128 + wu * 16 + g) * 448 + 56 * sl + 2 * c);
#pragma unroll
                    for (int i = 0; i < 7; i++) { X[2 * i] = __ldg(xp + 4 * i); X[2 * i + 1] = __ldg(xp + 4 * i + 8 * 224); }
                }
                bar_sync(3, 384);
                STAMP(9 + so);
                const uint4* const osrc = xp0 + PL(1);
                {
                    float nm[32];
                    const uint64_t db = BASE128(OFF_KVB, 16, 0);
                    wg_fence();
                    FOR7(mma_rs64<0, ((t >> 2) * 8192 + (t & 3) * 32) / 16>(nm, PH[4 * t], PH[4 * t + 1], PH[4 * t + 2], PH[4 * t + 3], t > 0, db));
                    wg_commit();
                    wg_wait<0>();
                    LATE_ARRIVE();
                    const float i00 = rcp(nm[28] + 1e-6f), i01 = rcp(nm[29] + 1e-6f), i10 = rcp(nm[30] + 1e-6f), i11 = rcp(nm[31] + 1e-6f);
                    const float m0 = c >= 2 ? i01 : i00, m1 = c >= 2 ? i11 : i10;
                    uint32_t O[14];
#pragma unroll
                    for (int i = 0; i < 7; i++) {
                        const float f0 = i < 3 ? i00 : (i > 3 ? i01 : m0), f1 = i < 3 ? i10 : (i > 3 ? i11 : m1);
                        O[2 * i] = pack2(nm[4 * i] * f0, nm[4 * i + 1] * f0);
                        O[2 * i + 1] = pack2(nm[4 * i + 2] * f1, nm[4 * i + 3] * f1);
                    }
                    if (OST) { PP_WAIT() }
                    tag_slice(O, tag);
                    send_slice<PL(1)>(xp0 + sl * 512, lane, O);
                    seq++;
                    if (lane == 0) st_word(cx(sl), seq);
                    STAMP(10 + so);
                    PUSH_SLICE(O)
                    if (OST == 1) { PP_GO() }
                    const uint32_t cv = ld_word(cx(lane & 7));
                    PULL_SLICE(O)
                    LATE_WAIT();
                    check_cnt(cv, cx(lane & 7), seq);
                    if (OST == 2) { PP_GO() }
                    STAMP(56 + (step >> 1));
                    GAT_ISSUE(1, PL(1))
                    GAT_ISSUE(3, PL(1))
                    blk_load<2>(A, BLK(osrc, 2), lane);
                }
                float ao[28];
#define WO_BLOCK(b)                                                                           \
    if ((b) > 0) blk_check<b>(A, BLK(osrc, b), lane, tag);                                    \
    if (((b) & 1) == 0) R_WAIT();                                                             \
    { DECL_DB(b, BASE128, 16, 0)                                                              \
    wg_fence();                                                                               \
    FOR7(mma_rs56<1, D128(((b) & 1) * HALF, t)>(ao, AQ(A, b, t), (b) + t > 0, SWB(b, t, db, 0))); } \
    wg_commit();                                                                              \
    if ((b) & 1) R_NEXT();
                WO_BLOCK(0)
                STAMP(11 + so);
                GAT_FETCH(1)
                WO_BLOCK(1)
                WO_BLOCK(2)
                GAT_FETCH(3)
                WO_BLOCK(3)
                PUSH_ACK();
                wg_wait<0>();
                R_RELEASE(2);
                LATE_ARRIVE();
                STAMP(12 + so);
                WSUM(86 + 7 * (step >> 1));
                x_fix(X, xbits);
#pragma unroll
                for (int i = 0; i < 14; i++) X[i] = pack2(bf_lo(X[i]) + ao[2 * i], bf_hi(X[i]) + ao[2 * i + 1]);
            } else {
                uint32_t H[56];
                float ag[64];
#define F1_EPI(dst, ng, ag)                                                                    \
    _Pragma("unroll") for (int i = 0; i < 2 * (ng); i++)                                       \
        (dst)[i] = pack2(geglu(ag[2 * i], ag[4 * (ng) + 2 * i]), geglu(ag[2 * i + 1], ag[4 * (ng) + 2 * i + 1]));
#define H_PUSH(h0, off) st_async4(rem_h + (off), H[h0], H[(h0) + 1], H[(h0) + 2], H[(h0) + 3], mapa(BAR(B_RECV2 + wgi), hr ^ 1));
#define F1_BLOCK(b, first)                                                                     \
    if ((first) && (b) == 1) late1 = eb2;                                                      \
    if ((first) && (b) == 2) { if (lane == 0) mbar_arrive(late1); }                            \
    if ((first) && (b) == 3) PUSH_ACK();                                                       \
    if ((first) && (b) >= FE && (b) < 3) GAT_FETCH(((b) + 1) & 3)                              \
    R_WAIT();                                                                                  \
    if ((b) == ((first) ? PPF : PPB)) { PP_WAIT() }                                            \
    { DECL_DB(b, BASE128, HALF, 0)                                                             \
    wg_fence();                                                                                \
    FOR7(mma_rs128<1, D128(0, t)>(ag, AQ(A, b, t), (b) + t > 0, SWB(b, t, db, 0));             \
         if constexpr (first) { PREP(b, t, true) }); }                                         \
    wg_commit();                                                                               \
    if ((b) == 3) { PP_GO() }                                                                  \
    if ((b) > 0) { wg_wait<1>(); R_RELEASE(1); }       \
    R_NEXT();
                normalize<0>(A, k0, k1);
                F1_BLOCK(0, true) F1_BLOCK(1, true) F1_BLOCK(2, true) F1_BLOCK(3, true)
                if (t128 == 0) { mbar_expect_tx(BAR(B_RECV + wgi), 16384); mbar_expect_tx(BAR(B_RECV2 + wgi), 12288); }
                PUSH_BEGIN();
                wg_wait<0>();
                R_RELEASE(1);
                int p = 0;
#pragma unroll 1
                do {
                    F1_EPI(H + 32, 8, ag)
                    STAMP(4 + p + so);
                    WSUM(81 + p + 7 * (step >> 1));
                    if (((trips >> (p + 1)) & 1) == 0) continue;
                    {
                        const uint32_t pk = (p ? hbuf + 16384 : sb + OFF_KVB + wgi * 8192) + w * 2048;
#pragma unroll
                        for (int k = 0; k < 4; k++) sts4(pk + k * 512 + lane * 16, H[32 + 4 * k], H[33 + 4 * k], H[34 + 4 * k], H[35 + 4 * k]);
                        fence_async();
                        __syncwarp();
                        asm volatile(ELECT "cp.async.bulk.shared::cluster.shared::cta.mbarrier::complete_tx::bytes [%0], [%1], 2048, [%2]; }"
                                     ::"r"(mapa(hbuf + p * 8192 + w * 2048, hr ^ 1)), "r"(pk), "r"(mapa(BAR(B_RECV + wgi), hr ^ 1)) : "memory");
                    }
                    if (step == 1 && p == PKP) R_NEXT();
                    kill<64>(ag);
                    F1_BLOCK(0, false) F1_BLOCK(1, false) F1_BLOCK(2, false) F1_BLOCK(3, false)
                    wg_wait<0>();
                    R_RELEASE(1);
                    kill<16>(H + 32);
                } while (((trips >> (++p)) & 1));
#pragma unroll
                for (int k = 0; k < 4; k++) lds4(H + 16 + 4 * k, hbuf + 16384 + w * 2048 + k * 512 + lane * 16);
                __syncwarp();
                if (lane == 0) asm volatile("mbarrier.arrive.shared::cluster.b64 _, [%0];" ::"r"(mapa(BAR(B_ACK2 + wgi), hr ^ 1)) : "memory");
                const uint32_t rem_h = mapa(hbuf + w * 2048 + lane * 16, hr ^ 1);
#define F1_LAST(b0)                                                                            \
    R_WAIT();                                                                                  \
    if (b0) { PP_WAIT() }                                                                      \
    { DECL_DB(b0, BASE64, HALF, 1)                                                             \
    wg_fence();                                                                                \
    FOR7(mma_rs64<1, D64(0, t)>(al, AQ(A, b0, t), (b0) + t > 0, SWB(b0, t, db, 1)));           \
    FOR7(mma_rs64<1, D64(7168, t)>(al, AQ(A, (b0) + 1, t), 1, db)); }                          \
    wg_commit();                                                                               \
    if (b0) { PP_GO() }                                                                        \
    R_NEXT();
                float al[32];
                F1_LAST(0)
                mbar_wait(BAR(B_RECV + wgi), rcvph);
                rcvph ^= 1;
                mbar_wait(BAR(B_ACK2 + wgi), step >> 1);
                H_PUSH(32, 16384) H_PUSH(36, 16896)
                F1_LAST(2)
                H_PUSH(40, 17408) H_PUSH(44, 17920)
                wg_wait<1>();
                R_RELEASE(2);
                wg_wait<0>();
                R_RELEASE(1);
                uint32_t HP[56];
#pragma unroll
                for (int k = 0; k < 4; k++) lds4(H + 4 * k, sb + OFF_KVB + wgi * 8192 + w * 2048 + k * 512 + lane * 16);
#pragma unroll
                for (int t = 0; t < 8; t++) lds4(HP + 4 * t, hbuf + (t >> 2) * 8192 + w * 2048 + (t & 3) * 512 + lane * 16);
                F1_EPI(H + 48, 4, al)
                H_PUSH(48, 24576 - w * 1024) H_PUSH(52, 25088 - w * 1024)
                STAMP(7 + so);
                WSUM(84 + 7 * (step >> 1));
                FRESH();
                float acc[28];
                const uint32_t roA = hr ? 256u : 0u, roB = hr ? (uint32_t)-1536 : 0u;
                const uint32_t rpA = hr ? 0u : 256u, rpB = hr ? 0u : (uint32_t)-1536;
                float res[28];
                uint32_t v0[14], v1[14], P[14];
                const uint4* ps = xp0 + sl * 512;
#define F2_OWN_A()                                                                             \
    R_WAIT();                                                                                  \
    d0 = BASE128(0, 16, R_ADJ + roA); d1 = BASE128(0, 16, R_ADJ + roB);                        \
    wg_fence();                                                                                \
    FOR14(if constexpr (t < OT) mma_rs56<1, t * 128>(acc, H[4 * t], H[4 * t + 1], H[4 * t + 2], H[4 * t + 3], t > 0, d0)); \
    wg_commit();
#define F2_OWN_B()                                                                             \
    wg_fence();                                                                                \
    FOR14(if constexpr (t >= OT) mma_rs56<1, t * 128>(acc, H[4 * t], H[4 * t + 1], H[4 * t + 2], H[4 * t + 3], 1, t < 12 ? d0 : d1)); \
    wg_commit();                                                                               \
    R_NEXT();
#define F2_PEER()                                                                              \
    R_WAIT();                                                                                  \
    if (F2PP) { PP_WAIT() }                                                                    \
    d0 = BASE128(0, 16, R_ADJ + rpA); d1 = BASE128(0, 16, R_ADJ + rpB);                        \
    wg_fence();                                                                                \
    FOR14(mma_rs56<1, t * 128>(acc, HP[4 * t], HP[4 * t + 1], HP[4 * t + 2], HP[4 * t + 3], 1, t < 12 ? d0 : d1)); \
    wg_commit();                                                                               \
    if (F2PP) { PP_GO() }                                                                      \
    R_NEXT();
#define F2_TURN(u)                                                                             \
    wg_wait<1>();                                                                              \
    if ((u) < 2 || TDEF < 2) R_RELEASE(2);                                                     \
    wg_wait<0>();                                                                              \
    if ((u) < 2 || TDEF < 1) R_RELEASE(1);                                                     \
    _Pragma("unroll") for (int i = 0; i < 14; i++) P[i] = pack2(acc[2 * i], acc[2 * i + 1]);   \
    tag_slice(P, tag);                                                                         \
    asm volatile("" : RW4(P, 0), RW4(P, 4), RW4(P, 8), RW2(P, 12));                            \
    kill<28>(acc);                                                                             \
    F2_OWN_A()                                                                                 \
    if ((u) == 2) { slice_load<PL(3)>(v0, ps, lane); slice_load<PL(4)>(v1, ps, lane); } \
    send_slice<PL(3 + (u))>(xp0 + (2 * ((pr + (u) + 1) & 3) + hr) * 512, lane, P);             \
    seq++;                                                                                     \
    if (lane == 0) st_word(cx(sl), seq);                                                       \
    __syncwarp();                                                                              \
    STAMP(8 + (u) + so);                                                                       \
    F2_OWN_B()
                uint64_t d0, d1;
                F2_OWN_A()
                F2_OWN_B()
                R_WAIT();
                d0 = BASE128(0, 16, R_ADJ + rpA); d1 = BASE128(0, 16, R_ADJ + rpB);
                wg_fence();
                FOR8(mma_rs56<1, t * 128>(acc, HP[4 * t], HP[4 * t + 1], HP[4 * t + 2], HP[4 * t + 3], 1, d0));
                wg_commit();
                mbar_wait(BAR(B_RECV2 + wgi), step >> 1);
#pragma unroll
                for (int k = 0; k < 4; k++) lds4(HP + 32 + 4 * k, hbuf + 16384 + w * 2048 + k * 512 + lane * 16);
                lds4(HP + 48, hbuf + 24576 + w * 1024 + lane * 16);
                lds4(HP + 52, hbuf + 25088 + w * 1024 + lane * 16);
                if (step == 1) PUSH_ACK();
                wg_fence();
                FOR14(if constexpr (t >= 8) mma_rs56<1, t * 128>(acc, HP[4 * t], HP[4 * t + 1], HP[4 * t + 2], HP[4 * t + 3], 1, t < 12 ? d0 : d1));
                wg_commit();
                R_NEXT();
                F2_TURN(0)
                F2_PEER()
                F2_TURN(1)
                F2_PEER()
                F2_TURN(2)
                if (step == 1) STAMP(64);
                slice_check<PL(3)>(v0, ps, lane, tag);
                slice_check<PL(4)>(v1, ps, lane, tag);
#pragma unroll
                for (int i = 0; i < 14; i++) { res[2 * i] = bf_lo(v0[i]) + bf_lo(v1[i]); res[2 * i + 1] = bf_hi(v0[i]) + bf_hi(v1[i]); }
                slice_load<PL(2)>(X, ps, lane);
                if (step == 1) STAMP(65);
                F2_PEER()
                if (step == 1) STAMP(66);
                poll_cnt(cx(2 * ((pr + 1) & 3) + hr), seq);
                if (step == 1) STAMP(67);
                slice_load<PL(5)>(v0, ps, lane);
                x_fix(X, xbits);
                slice_check<PL(5)>(v0, ps, lane, tag);
                if (lane < TDEF) mbar_arrive(BAR(B_EMPTY + (slot + NST - 3 - lane) % NST));
#pragma unroll
                for (int i = 0; i < 14; i++) { res[2 * i] += bf_lo(v0[i]); res[2 * i + 1] += bf_hi(v0[i]); }
                STAMP(11 + so);
                wg_wait<0>();
                R_RELEASE(2);
                LATE_ARRIVE();
                STAMP(12 + so);
                WSUM(85 + 7 * (step >> 1));
#pragma unroll
                for (int i = 0; i < 14; i++) X[i] = pack2(fmaf(res[2 * i] + acc[2 * i], 0.5f, bf_lo(X[i])), fmaf(res[2 * i + 1] + acc[2 * i + 1], 0.5f, bf_hi(X[i])));
            }
        }
        {
            const int m = lane >> 3, rr = lane & 7;
            const uint32_t ob = hbuf + w * 2048, rowa = ob + (rr + 8 * (m & 1)) * 112 + (m >> 1) * 16;
#pragma unroll
            for (int j = 0; j < 3; j++) stsm4(rowa + 32 * j, X[4 * j], X[4 * j + 1], X[4 * j + 2], X[4 * j + 3]);
            asm volatile("stmatrix.sync.aligned.m8n8.x2.shared.b16 [%0], {%1,%2};" ::"r"(ob + (rr + 8 * (m & 1)) * 112 + 96), "r"(X[12]), "r"(X[13]) : "memory");
            fence_async();
            __syncwarp();
            if (lane == 0) {
                asm volatile("cp.async.bulk.tensor.2d.global.shared::cta.bulk_group [%0, {%2, %3}], [%1];" ::"l"(&maps.out), "r"(ob), "r"(56 * sl), "r"(tile * 128 + wu * 16) : "memory");
                asm volatile("cp.async.bulk.commit_group;" ::: "memory");
                asm volatile("cp.async.bulk.wait_group.read 0;" ::: "memory");
            }
        }
        STAMP(50);
        GSTAMP(61);
        PDUMP();
    }
}

#undef g
#undef pr
#undef c
#undef t128

typedef CUresult (*EncodeFn)(CUtensorMap*, CUtensorMapDataType, cuuint32_t, void*, const cuuint64_t*, const cuuint64_t*, const cuuint32_t*,
                             const cuuint32_t*, CUtensorMapInterleave, CUtensorMapSwizzle, CUtensorMapL2promotion, CUtensorMapFloatOOBfill);

static void make_map(EncodeFn enc, CUtensorMap* m, const void* p, uint64_t cols, uint64_t rows, uint32_t bc, uint32_t br, CUtensorMapSwizzle sw) {
    cuuint64_t gd[2] = {cols, rows};
    cuuint64_t gs[1] = {cols * 2};
    cuuint32_t bd[2] = {bc, br};
    cuuint32_t es[2] = {1, 1};
    enc(m, CU_TENSOR_MAP_DATA_TYPE_BFLOAT16, 2, const_cast<void*>(p), gd, gs, bd, es, CU_TENSOR_MAP_INTERLEAVE_NONE, sw,
        CU_TENSOR_MAP_L2_PROMOTION_L2_128B, CU_TENSOR_MAP_FLOAT_OOB_FILL_NONE);
}

extern "C" void kernel_launch(void* const* d_in, const int* in_sizes, int n_in, void* d_out, int out_size) {
    (void)in_sizes; (void)n_in; (void)out_size;
    static EncodeFn enc = nullptr;
    static Scratch* scratch = nullptr;
    if (!enc) {
        void* fn = nullptr;
        cudaDriverEntryPointQueryResult qr;
        cudaGetDriverEntryPoint("cuTensorMapEncodeTiled", &fn, cudaEnableDefault, &qr);
        enc = (EncodeFn)fn;
        cudaGetSymbolAddress((void**)&scratch, g_scratch);
        cudaFuncSetAttribute(fused_kernel, cudaFuncAttributeMaxDynamicSharedMemorySize, SMEM_BYTES);
    }
    Maps maps;
    {
        cuuint64_t gd[3] = {64, 2048, 7};
        cuuint64_t gs[2] = {896, 128};
        cuuint32_t bd[3] = {64, 32, 7};
        cuuint32_t es[3] = {1, 1, 1};
        enc(&maps.x, CU_TENSOR_MAP_DATA_TYPE_BFLOAT16, 3, d_in[0], gd, gs, bd, es, CU_TENSOR_MAP_INTERLEAVE_NONE, CU_TENSOR_MAP_SWIZZLE_128B,
            CU_TENSOR_MAP_L2_PROMOTION_L2_128B, CU_TENSOR_MAP_FLOAT_OOB_FILL_NONE);
    }
    make_map(enc, &maps.out, d_out, 448, 2048, 56, 16, CU_TENSOR_MAP_SWIZZLE_NONE);
    make_map(enc, &maps.qkv, d_in[1], 1344, 448, 64, 112, CU_TENSOR_MAP_SWIZZLE_128B);
    make_map(enc, &maps.wo, d_in[3], 448, 448, 64, 112, CU_TENSOR_MAP_SWIZZLE_128B);
    make_map(enc, &maps.wg, d_in[5], 1792, 448, 64, 112, CU_TENSOR_MAP_SWIZZLE_128B);
    make_map(enc, &maps.wu, d_in[6], 1792, 448, 64, 112, CU_TENSOR_MAP_SWIZZLE_128B);
    make_map(enc, &maps.wg32, d_in[5], 1792, 448, 32, 112, CU_TENSOR_MAP_SWIZZLE_64B);
    make_map(enc, &maps.wu32, d_in[6], 1792, 448, 32, 112, CU_TENSOR_MAP_SWIZZLE_64B);
    make_map(enc, &maps.wd, d_in[7], 448, 1792, 64, 112, CU_TENSOR_MAP_SWIZZLE_128B);
    fused_kernel<<<128, 384, SMEM_BYTES>>>(scratch, (const __nv_bfloat16*)d_in[0], (const __nv_bfloat16*)d_in[2], 7, (const __nv_bfloat16*)d_in[5],
                                           (const __nv_bfloat16*)d_in[6], (const __nv_bfloat16*)d_in[7], maps);
}
```

```cpp
#include <cuda_runtime.h>
#include <cuda.h>
#include <cuda_bf16.h>
#include <stdint.h>
#include <type_traits>

#define PPF 2
#define PKP 0
#define TDEF 1
#define TMPF 0
#define NORM1 0
#define ACAN 0
#define SPLIT0 1
#define OT 2
#define F2PP 0
#define PPK 2
#define QE 1
#define OST 1
#define PP

namespace {

constexpr uint32_t STAGE = 28672, HALF = 14336;
constexpr int NST = 5;
constexpr uint32_t OFF_H = NST * STAGE;
constexpr uint32_t OFF_KVB = OFF_H + 2 * STAGE;
constexpr uint32_t OFF_WPHI = OFF_KVB + 16384;
constexpr uint32_t OFF_XR = OFF_WPHI + 7168;
constexpr uint32_t OFF_BAR = OFF_XR + 6144;
constexpr uint32_t SMEM_BYTES = OFF_BAR + 384 + 1408;
constexpr int B_EMPTY = NST, B_RECV = 2 * NST, B_RECV2 = B_RECV + 2, B_PACK = B_RECV2 + 2, B_GAT = B_PACK + 1, B_LATE = B_GAT + 16, B_ACK = B_LATE + 1, B_ACK2 = B_ACK + 2, B_COUNT = B_ACK2 + 2;

constexpr int PACK = 14 + 4 * PKP;

struct Maps { CUtensorMap x, qkv, wo, wg, wu, wg32, wu32, wd, out; };

}

constexpr int PLANE = 16 * 2 * 8 * 512;
struct Scratch {
    uint4 ex[6 * PLANE];
    uint4 kv1[8 * 16 * 16 * 32];
    uint4 kv2[8 * 512];
    uint32_t c1[8 * 8 * 16 * 32];
    uint32_t cw[8 * 32];
    uint4 wp[8 * 32 * (HALF / 16)];
};
__device__ __align__(1024) Scratch g_scratch;
#define g_ex (sc->ex)
#define g_kv1 (sc->kv1)
#define g_kv2 (sc->kv2)
#define g_c1 (sc->c1)
#define g_cw (sc->cw)
#define g_wp (sc->wp)
#define STAMP(i)
#define GSTAMP(i)
#define PDUMP()
#define ASTAMP(i)

namespace {

__device__ __forceinline__ int fresh_tid() { int t; asm volatile("mov.u32 %0, %%tid.x;" : "=r"(t)); return t; }
template <int N> __device__ __forceinline__ void kill(uint32_t* v) {
#pragma unroll
    for (int i = 0; i < N; i++) v[i] = 0;
}
template <int N> __device__ __forceinline__ void kill(float* v) {
#pragma unroll
    for (int i = 0; i < N; i++) v[i] = 0.f;
}
__device__ __forceinline__ uint32_t s2u(const void* p) { return (uint32_t)__cvta_generic_to_shared(p); }
__device__ __forceinline__ void mbar_init(uint32_t a, uint32_t c) { asm volatile("mbarrier.init.shared::cta.b64 [%0], %1;" ::"r"(a), "r"(c) : "memory"); }
__device__ __forceinline__ void mbar_expect_tx(uint32_t a, uint32_t b) { asm volatile("mbarrier.arrive.expect_tx.shared::cta.b64 _, [%0], %1;" ::"r"(a), "r"(b) : "memory"); }
__device__ __forceinline__ void mbar_arrive(uint32_t a) { asm volatile("mbarrier.arrive.shared::cta.b64 _, [%0];" ::"r"(a) : "memory"); }
#define GIVE_UP(id) "trap;\n"
#define SPIN_MAX "0x400000"
#define SPIN_TAIL(id) "add.u32 n, n, 1;\n setp.lt.u32 p, n, " SPIN_MAX ";\n @p bra.uni LP;\n" GIVE_UP(id) " DN:\n }"
__device__ __forceinline__ void mbar_wait(uint32_t a, uint32_t ph) {
    asm volatile("{ .reg .pred p; .reg .b32 n; mov.u32 n, 0;\n LP:\n"
                 "mbarrier.try_wait.parity.shared::cta.b64 p, [%0], %1;\n @p bra DN;\n"
                 "add.u32 n, n, 1;\n setp.lt.u32 p, n, " SPIN_MAX ";\n @p bra LP;\n"
                 GIVE_UP("")
                 " DN:\n }" ::"r"(a), "r"(ph) : "memory");
}
#define ELECT "{ .reg .pred e; elect.sync _|e, 0xffffffff; @e "
__device__ __forceinline__ void tma2d(uint32_t dst, const CUtensorMap* m, int c0, int c1, uint32_t bar) {
    asm volatile(ELECT "cp.async.bulk.tensor.2d.shared::cluster.global.mbarrier::complete_tx::bytes [%0], [%1, {%3, %4}], [%2]; }" ::"r"(dst), "l"(m), "r"(bar), "r"(c0), "r"(c1) : "memory");
}
__device__ __forceinline__ void tma3x(uint32_t dst, const CUtensorMap* m, int row, uint32_t bar) {
    asm volatile(ELECT "cp.async.bulk.tensor.3d.shared::cluster.global.mbarrier::complete_tx::bytes [%0], [%1, {0, %3, 0}], [%2]; }" ::"r"(dst), "l"(m), "r"(bar), "r"(row) : "memory");
}
template <int OFF>
__device__ __forceinline__ void ld_pkt(uint32_t* v, const uint4* p) {
    asm volatile("{ .reg .b128 t; ld.relaxed.gpu.global.b128 t, [%4+%5]; mov.b128 {%0,%1,%2,%3}, t; }" : "=r"(v[0]), "=r"(v[1]), "=r"(v[2]), "=r"(v[3]) : "l"(p), "n"(OFF * 16) : "memory");
}
template <int OFF>
__device__ __forceinline__ void st_pkt(uint4* p, uint32_t a, uint32_t b, uint32_t c, uint32_t d) {
    asm volatile("{ .reg .b128 t; mov.b128 t, {%1,%2,%3,%4}; st.relaxed.gpu.global.b128 [%0+%5], t; }" ::"l"(p), "r"(a), "r"(b), "r"(c), "r"(d), "n"(OFF * 16) : "memory");
}
__device__ __forceinline__ uint32_t pack2(float lo, float hi) {
    uint32_t r;
    asm("cvt.rn.bf16x2.f32 %0, %1, %2;" : "=r"(r) : "f"(hi), "f"(lo));
    return r;
}
__device__ __forceinline__ float bf_lo(uint32_t w) { return __uint_as_float(w << 16); }
__device__ __forceinline__ float bf_hi(uint32_t w) { return __uint_as_float(w & 0xffff0000u); }
__device__ __forceinline__ uint32_t settag(uint32_t w, uint32_t tag) { return (w & ~1u) | tag; }
__device__ __forceinline__ float ex2(float x) { float y; asm("ex2.approx.ftz.f32 %0, %1;" : "=f"(y) : "f"(x)); return y; }
__device__ __forceinline__ float rcp(float x) { float y; asm("rcp.approx.ftz.f32 %0, %1;" : "=f"(y) : "f"(x)); return y; }
__device__ __forceinline__ float tanh_hw(float x) { float y; asm("tanh.approx.f32 %0, %1;" : "=f"(y) : "f"(x)); return y; }
__device__ __forceinline__ void stsm4(uint32_t addr, uint32_t a, uint32_t b, uint32_t c, uint32_t d) {
    asm volatile("stmatrix.sync.aligned.m8n8.x4.shared.b16 [%0], {%1,%2,%3,%4};" ::"r"(addr), "r"(a), "r"(b), "r"(c), "r"(d) : "memory");
}
__device__ __forceinline__ void fence_async() { asm volatile("fence.proxy.async.shared::cta;" ::: "memory"); }
__device__ __forceinline__ void bar_sync(int id, int n) { asm volatile("bar.sync %0, %1;" ::"r"(id), "r"(n) : "memory"); }
__device__ __forceinline__ void bar_arrive(int id, int n) { asm volatile("bar.arrive %0, %1;" ::"r"(id), "r"(n) : "memory"); }
__device__ __forceinline__ void wg_fence() { asm volatile("wgmma.fence.sync.aligned;" ::: "memory"); }
__device__ __forceinline__ void wg_commit() { asm volatile("wgmma.commit_group.sync.aligned;" ::: "memory"); }
template <int N> __device__ __forceinline__ void wg_wait() { asm volatile("wgmma.wait_group.sync.aligned %0;" ::"n"(N) : "memory"); }

constexpr uint32_t SB0 = 1024;
__host__ __device__ constexpr uint32_t dlo(uint32_t off, uint32_t lbo) { return ((SB0 + off) >> 4) | ((lbo >> 4) << 16); }
__host__ __device__ constexpr uint32_t dhi(uint32_t sbo, uint32_t sw) { return (sbo >> 4) | (sw << 30); }
__device__ __forceinline__ uint64_t dbase(uint32_t lo, uint32_t hi) { uint64_t d; asm volatile("mov.b64 %0, {%1, %2};" : "=l"(d) : "r"(lo), "r"(hi)); return d; }
#define BASE128(off, lbo, adj) dbase(dlo(off, lbo) + (adj), dhi(1024, 1))
#define BASE64(off, lbo, adj) dbase(dlo(off, lbo) + (adj), dhi(512, 2))

#define ACC4(d, o) "+f"(d[o]), "+f"(d[o + 1]), "+f"(d[o + 2]), "+f"(d[o + 3])
#define ACC28(d) ACC4(d, 0), ACC4(d, 4), ACC4(d, 8), ACC4(d, 12), ACC4(d, 16), ACC4(d, 20), ACC4(d, 24)
#define ACC32(d, o) ACC4(d, o), ACC4(d, o + 4), ACC4(d, o + 8), ACC4(d, o + 12), ACC4(d, o + 16), ACC4(d, o + 20), ACC4(d, o + 24), ACC4(d, o + 28)

template <int TB, uint64_t D>
__device__ __forceinline__ void mma_rs56(float* d, uint32_t a0, uint32_t a1, uint32_t a2, uint32_t a3, int sd, uint64_t base) {
    asm volatile("{ .reg .pred p; .reg .b64 db; setp.ne.b32 p, %32, 0; add.u64 db, %33, %34;\n"
                 "wgmma.mma_async.sync.aligned.m64n56k16.f32.bf16.bf16 "
                 "{%0,%1,%2,%3,%4,%5,%6,%7,%8,%9,%10,%11,%12,%13,%14,%15,%16,%17,%18,%19,%20,%21,%22,%23,%24,%25,%26,%27}, "
                 "{%28,%29,%30,%31}, db, p, 1, 1, %35; }\n"
                 : ACC28(d)
                 : "r"(a0), "r"(a1), "r"(a2), "r"(a3), "r"(sd), "l"(base), "n"(D), "n"(TB));
}
template <int TB, uint64_t D>
__device__ __forceinline__ void mma_rs64(float* d, uint32_t a0, uint32_t a1, uint32_t a2, uint32_t a3, int sd, uint64_t base) {
    asm volatile("{ .reg .pred p; .reg .b64 db; setp.ne.b32 p, %36, 0; add.u64 db, %37, %38;\n"
                 "wgmma.mma_async.sync.aligned.m64n64k16.f32.bf16.bf16 "
                 "{%0,%1,%2,%3,%4,%5,%6,%7,%8,%9,%10,%11,%12,%13,%14,%15,%16,%17,%18,%19,%20,%21,%22,%23,%24,%25,%26,%27,%28,%29,%30,%31}, "
                 "{%32,%33,%34,%35}, db, p, 1, 1, %39; }\n"
                 : ACC32(d, 0)
                 : "r"(a0), "r"(a1), "r"(a2), "r"(a3), "r"(sd), "l"(base), "n"(D), "n"(TB));
}
template <int TB, uint64_t D>
__device__ __forceinline__ void mma_rs128(float* d, uint32_t a0, uint32_t a1, uint32_t a2, uint32_t a3, int sd, uint64_t base) {
    asm volatile("{ .reg .pred p; .reg .b64 db; setp.ne.b32 p, %68, 0; add.u64 db, %69, %70;\n"
                 "wgmma.mma_async.sync.aligned.m64n128k16.f32.bf16.bf16 "
                 "{%0,%1,%2,%3,%4,%5,%6,%7,%8,%9,%10,%11,%12,%13,%14,%15,%16,%17,%18,%19,%20,%21,%22,%23,%24,%25,%26,%27,%28,%29,%30,%31,%32,%33,%34,%35,%36,%37,%38,%39,%40,%41,%42,%43,%44,%45,%46,%47,%48,%49,%50,%51,%52,%53,%54,%55,%56,%57,%58,%59,%60,%61,%62,%63}, "
                 "{%64,%65,%66,%67}, db, p, 1, 1, %71; }\n"
                 : ACC32(d, 0), ACC32(d, 32)
                 : "r"(a0), "r"(a1), "r"(a2), "r"(a3), "r"(sd), "l"(base), "n"(D), "n"(TB));
}
template <uint64_t DA, uint64_t DB>
__device__ __forceinline__ void mma_ss56_tt(float* d, int sd, uint64_t ba, uint64_t bb) {
    asm volatile("{ .reg .pred p; .reg .b64 da, db; setp.ne.b32 p, %28, 0; add.u64 da, %29, %31; add.u64 db, %30, %32;\n"
                 "wgmma.mma_async.sync.aligned.m64n56k16.f32.bf16.bf16 "
                 "{%0,%1,%2,%3,%4,%5,%6,%7,%8,%9,%10,%11,%12,%13,%14,%15,%16,%17,%18,%19,%20,%21,%22,%23,%24,%25,%26,%27}, "
                 "da, db, p, 1, 1, 1, 1; }\n"
                 : ACC28(d)
                 : "r"(sd), "l"(ba), "l"(bb), "n"(DA), "n"(DB));
}
template <int... I> struct Seq {};
template <class F, int... I> __device__ __forceinline__ void static_for_impl(F&& f, Seq<I...>) { (f(std::integral_constant<int, I>{}), ...); }
#define FOR7(...) static_for_impl([&](auto T_) { constexpr int t = decltype(T_)::value; __VA_ARGS__; }, Seq<0, 1, 2, 3, 4, 5, 6>{})
#define FOR8(...) static_for_impl([&](auto T_) { constexpr int t = decltype(T_)::value; __VA_ARGS__; }, Seq<0, 1, 2, 3, 4, 5, 6, 7>{})
#define FOR14(...) static_for_impl([&](auto T_) { constexpr int t = decltype(T_)::value; __VA_ARGS__; }, Seq<0, 1, 2, 3, 4, 5, 6, 7, 8, 9, 10, 11, 12, 13>{})

__device__ __forceinline__ int kblk(int p, int b) { return b == 0 ? p : b - (b <= p); }
__host__ __device__ constexpr int krow(int t) { return t < 3 ? 16 * t : (t < 6 ? 56 + 16 * (t - 3) : 48); }
#define AQ(A, b, t) ((t) < 3 ? A[2 * (b)][4 * (t)] : (t) < 6 ? A[2 * (b) + 1][4 * ((t) - 3)] : A[2 * (b)][12]), \
                    ((t) < 3 ? A[2 * (b)][4 * (t) + 1] : (t) < 6 ? A[2 * (b) + 1][4 * ((t) - 3) + 1] : A[2 * (b)][13]), \
                    ((t) < 3 ? A[2 * (b)][4 * (t) + 2] : (t) < 6 ? A[2 * (b) + 1][4 * ((t) - 3) + 2] : A[2 * (b) + 1][12]), \
                    ((t) < 3 ? A[2 * (b)][4 * (t) + 3] : (t) < 6 ? A[2 * (b) + 1][4 * ((t) - 3) + 3] : A[2 * (b) + 1][13])
#define D128(off, t) ((uint64_t)(((off) + krow(t) * 128) >> 4) + ((uint64_t)((t) == 6 ? (7168 - 1024) >> 4 : 0) << 32))
#define D64(off, t) ((uint64_t)(((off) + krow(t) * 64) >> 4) + ((uint64_t)((t) == 6 ? (3584 - 512) >> 4 : 0) << 32))

#define PL(k) (((k) - 3) * PLANE)
__device__ __forceinline__ void st_word(uint32_t* p, uint32_t v) { asm volatile("st.relaxed.gpu.global.u32 [%0], %1;" ::"l"(p), "r"(v) : "memory"); }
__device__ __forceinline__ uint32_t ld_word(const uint32_t* p) { uint32_t v; asm volatile("ld.relaxed.gpu.global.u32 %0, [%1];" : "=r"(v) : "l"(p) : "memory"); return v; }
__device__ __forceinline__ void tag_slice(uint32_t* w, uint32_t tag) { w[0] = settag(w[0], tag); w[4] = settag(w[4], tag); w[8] = settag(w[8], tag); w[12] = settag(w[12], tag); }
template <int O>
__device__ __forceinline__ void send_slice(uint4* dst, int lane, const uint32_t* w) {
    st_pkt<O>(dst, w[0], w[1], w[2], w[3]);
    st_pkt<O + 32>(dst, w[4], w[5], w[6], w[7]);
    st_pkt<O + 64>(dst, w[8], w[9], w[10], w[11]);
    asm volatile("{ .reg .b64 t; mov.b64 t, {%1,%2}; st.relaxed.gpu.global.b64 [%0+%3], t; }" ::"l"((char*)dst - lane * 8), "r"(w[12]), "r"(w[13]), "n"(16 * (O + 96)) : "memory");
}
#define RW4(v, o) "+r"(v[o]), "+r"(v[(o) + 1]), "+r"(v[(o) + 2]), "+r"(v[(o) + 3])
#define RW2(v, o) "+r"(v[o]), "+r"(v[(o) + 1])
#define WR4(v, o) "=&r"(v[o]), "=&r"(v[(o) + 1]), "=&r"(v[(o) + 2]), "=&r"(v[(o) + 3])
#define LDP(a, b, c, d, addr, off) "ld.relaxed.gpu.global.b128 q, [" addr "+" off "];\n mov.b128 {" a "," b "," c "," d "}, q;\n"
#define LDH(a, b, addr, off) "ld.relaxed.gpu.global.b64 h, [" addr "+" off "];\n mov.b64 {" a "," b "}, h;\n"
#define VOTE_OK "and.b32 t, t, 1;\n setp.ne.u32 p, t, 0;\n vote.sync.any.pred p, p, 0xffffffff;\n @!p bra.uni DN;\n"
#define CHK(x, tag) "lop3.b32 t, " x ", " tag ", t, 0xBE;\n"
__device__ __forceinline__ void check_cnt(uint32_t v, const uint32_t* p, uint32_t target) {
    asm volatile("{ .reg .pred p; .reg .b32 n, t; mov.u32 n, 0; mov.u32 t, %2;\n LP:\n"
                 "sub.s32 t, t, %1;\n setp.lt.s32 p, t, 0;\n vote.sync.any.pred p, p, 0xffffffff;\n @!p bra.uni DN;\n ld.relaxed.gpu.global.u32 t, [%0];\n" SPIN_TAIL("7")
                 ::"l"(p), "r"(target), "r"(v) : "memory");
}
__device__ __forceinline__ void poll_cnt(const uint32_t* p, uint32_t target) {
    asm volatile("{ .reg .pred p; .reg .b32 n, t; mov.u32 n, 0;\n LP:\n"
                 "ld.relaxed.gpu.global.u32 t, [%0];\n sub.s32 t, t, %1;\n setp.lt.s32 p, t, 0;\n vote.sync.any.pred p, p, 0xffffffff;\n @!p bra.uni DN;\n" SPIN_TAIL("1")
                 ::"l"(p), "r"(target) : "memory");
}
template <int STR>
__device__ __forceinline__ void poll4_kv(uint32_t* v, const uint4* p, uint32_t tag) {
    asm volatile("{ .reg .pred p; .reg .b32 n, t; .reg .b128 q; mov.u32 n, 0;\n LP:\n"
                 LDP("%0", "%1", "%2", "%3", "%16", "0") LDP("%4", "%5", "%6", "%7", "%16", "%18")
                 LDP("%8", "%9", "%10", "%11", "%16", "%19") LDP("%12", "%13", "%14", "%15", "%16", "%20")
                 "xor.b32 t, %0, %17;\n" CHK("%4", "%17") CHK("%8", "%17") CHK("%12", "%17") VOTE_OK SPIN_TAIL("2")
                 : WR4(v, 0), WR4(v, 4), WR4(v, 8), WR4(v, 12)
                 : "l"(p), "r"(tag), "n"(16 * STR), "n"(32 * STR), "n"(48 * STR)
                 : "memory");
}
template <int B>
__device__ __forceinline__ void blk_load(uint32_t (&A)[8][14], const uint4* src, int lane) {
    ld_pkt<0>(&A[2 * B][0], src); ld_pkt<32>(&A[2 * B][4], src); ld_pkt<64>(&A[2 * B][8], src);
    ld_pkt<512>(&A[2 * B + 1][0], src); ld_pkt<544>(&A[2 * B + 1][4], src); ld_pkt<576>(&A[2 * B + 1][8], src);
    asm volatile("{ .reg .b64 h;\n" LDH("%0", "%1", "%4", "1536") LDH("%2", "%3", "%4", "9728") "}"
                 : "=&r"(A[2 * B][12]), "=&r"(A[2 * B][13]), "=&r"(A[2 * B + 1][12]), "=&r"(A[2 * B + 1][13])
                 : "l"((const char*)src - lane * 8) : "memory");
}
template <int B>
__device__ __forceinline__ void blk_check(uint32_t (&A)[8][14], const uint4* src, int lane, uint32_t tag) {
    asm volatile("{ .reg .pred p; .reg .b32 n, t; .reg .b128 q; .reg .b64 h, a8; mov.u32 n, 0;\n LP:\n"
                 "xor.b32 t, %0, %30;\n" CHK("%4", "%30") CHK("%8", "%30") CHK("%12", "%30") CHK("%16", "%30") CHK("%20", "%30") CHK("%24", "%30") CHK("%26", "%30") VOTE_OK
                 LDP("%0", "%1", "%2", "%3", "%28", "0") LDP("%4", "%5", "%6", "%7", "%28", "512") LDP("%8", "%9", "%10", "%11", "%28", "1024")
                 LDP("%12", "%13", "%14", "%15", "%28", "8192") LDP("%16", "%17", "%18", "%19", "%28", "8704") LDP("%20", "%21", "%22", "%23", "%28", "9216")
                 "mad.wide.s32 a8, %29, -8, %28;\n" LDH("%24", "%25", "a8", "1536") LDH("%26", "%27", "a8", "9728") SPIN_TAIL("3")
                 "\n and.b32 %0, %0, -2; and.b32 %4, %4, -2; and.b32 %8, %8, -2; and.b32 %12, %12, -2; and.b32 %16, %16, -2; and.b32 %20, %20, -2; and.b32 %24, %24, -2; and.b32 %26, %26, -2;"
                 : RW4(A[2 * B], 0), RW4(A[2 * B], 4), RW4(A[2 * B], 8), RW4(A[2 * B + 1], 0), RW4(A[2 * B + 1], 4), RW4(A[2 * B + 1], 8),
                   RW2(A[2 * B], 12), RW2(A[2 * B + 1], 12)
                 : "l"(src), "r"(lane), "r"(tag)
                 : "memory");
}
__device__ __forceinline__ void st_async4(uint32_t a, uint32_t x, uint32_t y, uint32_t z, uint32_t w, uint32_t bar) {
    asm volatile("st.async.weak.shared::cluster.mbarrier::complete_tx::bytes.v4.b32 [%0], {%1,%2,%3,%4}, [%5];" ::"r"(a), "r"(x), "r"(y), "r"(z), "r"(w), "r"(bar) : "memory");
}
__device__ __forceinline__ uint32_t mapa(uint32_t a, uint32_t cta) { uint32_t r; asm("mapa.shared::cluster.u32 %0, %1, %2;" : "=r"(r) : "r"(a), "r"(cta)); return r; }
__device__ __forceinline__ void stat_load(uint32_t* v, const uint4* p) { ld_pkt<0>(v, p); ld_pkt<512>(v + 4, p); }
__device__ __forceinline__ void stat_check(uint32_t* v, const uint4* p, uint32_t tag) {
    asm volatile("{ .reg .pred p; .reg .b32 n, t; .reg .b128 q; mov.u32 n, 0;\n LP:\n"
                 "xor.b32 t, %3, %9;\n" CHK("%7", "%9") VOTE_OK
                 LDP("%0", "%1", "%2", "%3", "%8", "0") LDP("%4", "%5", "%6", "%7", "%8", "8192") SPIN_TAIL("4")
                 : RW4(v, 0), RW4(v, 4) : "l"(p), "r"(tag) : "memory");
}
__device__ __forceinline__ uint32_t x_bits(const uint32_t* X) {
    uint32_t r;
    asm volatile("{ .reg .b32 a, b; prmt.b32 a, %1, %2, 0x0040; prmt.b32 b, %3, %4, 0x0040; prmt.b32 %0, a, b, 0x5410; }" : "=r"(r) : "r"(X[0]), "r"(X[4]), "r"(X[8]), "r"(X[12]));
    return r;
}
template <int O>
__device__ __forceinline__ void slice_load(uint32_t* v, const uint4* p, int lane) {
    ld_pkt<O>(v, p); ld_pkt<O + 32>(v + 4, p); ld_pkt<O + 64>(v + 8, p);
    asm volatile("{ .reg .b64 h;\n" LDH("%0", "%1", "%2", "%3") "}" : "=r"(v[12]), "=r"(v[13]) : "l"((const char*)p - lane * 8), "n"(16 * (O + 96)) : "memory");
}
template <int O>
__device__ __forceinline__ void slice_check(uint32_t* v, const uint4* p, int lane, uint32_t tag) {
    asm volatile("{ .reg .pred p; .reg .b32 n, t; .reg .b128 q; .reg .b64 h; mov.u32 n, 0;\n LP:\n"
                 "xor.b32 t, %0, %16;\n" CHK("%4", "%16") CHK("%8", "%16") CHK("%12", "%16") VOTE_OK
                 LDP("%0", "%1", "%2", "%3", "%14", "%17") LDP("%4", "%5", "%6", "%7", "%14", "%18") LDP("%8", "%9", "%10", "%11", "%14", "%19")
                 LDH("%12", "%13", "%15", "%20") SPIN_TAIL("5")
                 : RW4(v, 0), RW4(v, 4), RW4(v, 8), RW2(v, 12)
                 : "l"(p), "l"((const char*)p - lane * 8), "r"(tag), "n"(16 * O), "n"(16 * (O + 32)), "n"(16 * (O + 64)), "n"(16 * (O + 96))
                 : "memory");
}
__device__ __forceinline__ void x_fix(uint32_t* X, uint32_t bits) {
    X[0] = __byte_perm(X[0], bits, 0x3214); X[4] = __byte_perm(X[4], bits, 0x3215); X[8] = __byte_perm(X[8], bits, 0x3216); X[12] = __byte_perm(X[12], bits, 0x3217);
}
__device__ __forceinline__ void sts4(uint32_t a, uint32_t x, uint32_t y, uint32_t z, uint32_t w) {
    asm volatile("st.shared.v4.u32 [%0], {%1,%2,%3,%4};" ::"r"(a), "r"(x), "r"(y), "r"(z), "r"(w) : "memory");
}
__device__ __forceinline__ void lds4(uint32_t* v, uint32_t a) {
    asm volatile("ld.shared.v4.u32 {%0,%1,%2,%3}, [%4];" : "=r"(v[0]), "=r"(v[1]), "=r"(v[2]), "=r"(v[3]) : "r"(a) : "memory");
}
struct LnCoef { uint32_t hi, lo, sh; };
__device__ __forceinline__ LnCoef ln_coef(float sum, float sq) {
    sum += __shfl_xor_sync(0xffffffffu, sum, 1); sq += __shfl_xor_sync(0xffffffffu, sq, 1);
    sum += __shfl_xor_sync(0xffffffffu, sum, 2); sq += __shfl_xor_sync(0xffffffffu, sq, 2);
    const float mean = sum * (1.f / 448.f);
    const float var = fmaxf(fmaf(-mean, mean, sq * (1.f / 448.f)), 0.f);
    const float sc = rsqrtf(var + 1e-5f);
    LnCoef r;
    r.hi = pack2(sc, sc);
    const float lo = sc - bf_lo(r.hi), sh = -mean * sc;
    r.lo = pack2(lo, lo);
    r.sh = pack2(sh, sh);
    return r;
}
template <int B>
__device__ __forceinline__ void normalize(uint32_t (&A)[8][14], const LnCoef& c0, const LnCoef& c1) {
#pragma unroll
    for (int s = 2 * B; s < 2 * B + 2; s++)
#pragma unroll
        for (int i = 0; i < 14; i++) {
            const LnCoef& k = (i & 1) ? c1 : c0;
            asm("{ .reg .b32 t; fma.rn.bf16x2 t, %0, %2, %3; fma.rn.bf16x2 %0, %0, %1, t; }" : "+r"(A[s][i]) : "r"(k.hi), "r"(k.lo), "r"(k.sh));
        }
}
__device__ __forceinline__ void slice_stats(const uint32_t* w, float* st) {
    float a = 0.f, b = 0.f, p = 0.f, q = 0.f;
#pragma unroll
    for (int i = 0; i < 7; i++) {
        const float e0 = bf_lo(w[2 * i]), e1 = bf_hi(w[2 * i]), e2 = bf_lo(w[2 * i + 1]), e3 = bf_hi(w[2 * i + 1]);
        a += e0 + e1; b += e2 + e3;
        p = fmaf(e0, e0, p); p = fmaf(e1, e1, p); q = fmaf(e2, e2, q); q = fmaf(e3, e3, q);
    }
    a += __shfl_xor_sync(0xffffffffu, a, 1); p += __shfl_xor_sync(0xffffffffu, p, 1); b += __shfl_xor_sync(0xffffffffu, b, 1); q += __shfl_xor_sync(0xffffffffu, q, 1);
    a += __shfl_xor_sync(0xffffffffu, a, 2); p += __shfl_xor_sync(0xffffffffu, p, 2); b += __shfl_xor_sync(0xffffffffu, b, 2); q += __shfl_xor_sync(0xffffffffu, q, 2);
    st[0] = a; st[1] = p; st[2] = b; st[3] = q;
}
__device__ __forceinline__ void dual_softmax(const float* p, uint32_t* out) {
    constexpr float L = 1.4426950408889634f;
#pragma unroll
    for (int r = 0; r < 2; r++) {
        float mx = fmaxf(p[2 * r], p[2 * r + 1]), mn = fminf(p[2 * r], p[2 * r + 1]);
#pragma unroll
        for (int i = 1; i < 7; i++) {
            mx = fmaxf(mx, fmaxf(p[4 * i + 2 * r], p[4 * i + 2 * r + 1]));
            mn = fminf(mn, fminf(p[4 * i + 2 * r], p[4 * i + 2 * r + 1]));
        }
        mx = fmaxf(mx, __shfl_xor_sync(0xffffffffu, mx, 1));
        mn = fminf(mn, __shfl_xor_sync(0xffffffffu, mn, 1));
        const float bx = -mx * L, bn = mn * L;
        float ep[14], en[14], sp = 0.f, sn = 0.f;
#pragma unroll
        for (int i = 0; i < 14; i++) {
            const float v = p[4 * (i >> 1) + 2 * r + (i & 1)];
            ep[i] = ex2(fmaf(v, L, bx));
            en[i] = ex2(fmaf(v, -L, bn));
            sp += ep[i]; sn += en[i];
        }
        sp += __shfl_xor_sync(0xffffffffu, sp, 1);
        sn += __shfl_xor_sync(0xffffffffu, sn, 1);
        const float ip = rcp(sp), in = rcp(sn);
#pragma unroll
        for (int i = 0; i < 7; i++) {
            out[4 * i + r] = pack2(ep[2 * i] * ip, ep[2 * i + 1] * ip);
            out[4 * i + 2 + r] = pack2(en[2 * i] * in, en[2 * i + 1] * in);
        }
    }
}
__device__ __forceinline__ float geglu(float g, float u) {
    const float t = tanh_hw(g * fmaf(g * g, 0.7978845608028654f * 0.044715f, 0.7978845608028654f));
    const float gu = g * u;
    return fmaf(t, gu, gu);
}
__device__ __forceinline__ void phi_gemm(const float* t, float* p) {
    uint32_t w[14];
#pragma unroll
    for (int i = 0; i < 14; i++) w[i] = pack2(t[2 * i], t[2 * i + 1]);
    const uint64_t db = BASE128(OFF_WPHI, 16, 0);
    wg_fence();
    mma_rs56<0, 0>(p, w[0], w[1], w[2], w[3], 0, db);
    mma_rs56<0, 2>(p, w[4], w[5], w[6], w[7], 1, db);
    mma_rs56<0, 4>(p, w[8], w[9], w[10], w[11], 1, db);
    mma_rs56<0, 6>(p, w[12], w[13], 0u, 0u, 1, db);
    wg_commit();
    wg_wait<0>();
}

}

#define BAR(i) (bars + 8 * (i))
#define R_WAIT() mbar_wait(BAR(slot), ph)
#define WSUM(i)
#define R_ADJ (slot * (STAGE >> 4))
#define R_NEXT() do { eb2 = eb1; eb1 = BAR(B_EMPTY + slot); if (++slot == NST) { slot = 0; ph ^= 1; } } while (0)
#define R_RELEASE(k) do { if (lane == 0) mbar_arrive((k) == 1 ? eb1 : eb2); } while (0)
#define PUSH_BEGIN() do { mbar_wait(BAR(B_ACK + wgi), ackph); ackph ^= 1; } while (0)
#define PUSH_ACK() do { __syncwarp(); if (lane == 0) asm volatile("mbarrier.arrive.shared::cluster.b64 _, [%0];" ::"r"(mapa(BAR(B_ACK + wgi), hr ^ 1)) : "memory"); } while (0)

__global__ void __cluster_dims__(2, 1, 1) __launch_bounds__(384, 1)
fused_kernel(Scratch* const sc, const __nv_bfloat16* __restrict__ x_in, const __nv_bfloat16* __restrict__ w_phi, const int trips,
             const __nv_bfloat16* __restrict__ wg, const __nv_bfloat16* __restrict__ wu, const __nv_bfloat16* __restrict__ wd,
             const __grid_constant__ Maps maps) {
    extern __shared__ __align__(1024) unsigned char smem_raw[];
    const uint32_t sb = s2u(smem_raw);
    const uint32_t bars = sb + OFF_BAR;
    const int wgi = __shfl_sync(0xffffffffu, threadIdx.x >> 7, 0);
    const int hr = blockIdx.x & 1, ck = blockIdx.x >> 1;
    const int gp = (ck - 4) & 7, q7 = ((ck - 36) * 37) >> 8;
    const int pr = __shfl_sync(0xffffffffu, ck < 4 ? ck : (ck < 36 ? (ck - 4) >> 3 : q7), 0);
    const int tile = __shfl_sync(0xffffffffu, ck < 4 ? 0 : (ck < 36 ? (gp ? 2 * gp : 1) : 2 * (ck - 36 - 7 * q7) + 3), 0);
    const int sl = 2 * pr + hr;
    STAMP(0);
    GSTAMP(60);
    if (threadIdx.x == 256) {
#pragma unroll
        for (int i = 0; i < NST; i++) mbar_init(BAR(i), 1);
        asm volatile("fence.mbarrier_init.release.cluster;" ::: "memory");
    }
    if (threadIdx.x == 288) {
        if ((sb & 0x3FFFF) != SB0) asm volatile("trap;");
#pragma unroll
        for (int i = NST; i < B_COUNT; i++) mbar_init(BAR(i), i >= B_ACK ? 4 : (i < B_RECV || i == B_LATE ? 8 : 1));
        asm volatile("fence.mbarrier_init.release.cluster;" ::: "memory");
    }
    __syncwarp();
    asm volatile("barrier.cluster.arrive.relaxed.aligned;" ::: "memory");

    if (wgi == 2) {
        asm volatile("setmaxnreg.dec.sync.aligned.u32 40;");
        const int t128 = fresh_tid() & 127, w = __shfl_sync(0xffffffffu, t128 >> 5, 0), lane = t128 & 31;
        uint32_t e0[2] = {0, 0}, e1[2] = {0, 0}, cw_target = 0;
        if (w == 0) {
#pragma unroll 1
            for (int n = 0; n < NST; n++) {
                const uint32_t dst = sb + n * STAGE, fb = BAR(n);
                asm volatile(ELECT "mbarrier.arrive.expect_tx.shared::cta.b64 _, [%0], %1; }" ::"r"(fb), "r"(n < 2 ? 2 * STAGE : STAGE) : "memory");
                if (n < 2) {
                    tma3x(sb + OFF_H + n * STAGE, &maps.x, tile * 128 + n * 64, fb);
                    tma3x(dst, &maps.x, tile * 128 + n * 64 + 32, fb);
                } else {
                    if (n == 3) mbar_wait(BAR(1), 0);
                    const int ra = 112 * (n - 2);
                    tma2d(dst, &maps.qkv, 448 + 56 * sl, ra, fb);
                    tma2d(dst + HALF, &maps.qkv, 896 + 56 * sl, ra, fb);
                }
            }
            asm volatile("barrier.cluster.wait.aligned;" ::: "memory");
            cw_target = (ld_word(g_cw + sl * 32) & ~15u) + 16;
#pragma unroll 1
            for (int k = 0; k < 2; k++) {
                const int n = t128 + 32 * k;
                int m = n - 2 - (n > PACK);
                const bool packed = m >= 30 ? (m < 38 || m >= 52) : m >= 22;
                if (m >= 30) m -= 30;
                if (n == PACK) m = tile < 8 ? tile : tile + 14;
                const int rot = n < 8 ? 0 : pr;
                const int ra = 112 * kblk(rot, m & 3), rb = 112 * kblk(rot, 2 * m & 3), rc = 112 * kblk(rot, (2 * m + 1) & 3);
                int kind = 0, m0, m1, c0, c1, r0, r1;
                if (m < 4) { m0 = m1 = 1; c0 = 448 + 56 * sl; c1 = c0 + 448; r0 = r1 = ra; }
                else if (m < 8) { m0 = m1 = m < 6 ? 1 : 2; c0 = c1 = 56 * sl; r0 = rb; r1 = rc; }
                else if (m < 20) { m0 = 3; m1 = 4; c0 = c1 = 224 * sl + 32 * hr + 64 * ((m - 8) >> 2); r0 = r1 = ra; }
                else if (m < 22) { kind = 2; m0 = 5; m1 = 6; c0 = c1 = 224 * sl + (hr ? 0 : 192); r0 = rb; r1 = rc; }
                else { m0 = m1 = 7; c0 = c1 = 56 * (2 * ((pr + (m >> 1) - 10) & 3) + hr); r0 = 224 * (sl ^ (m & 1)); r1 = r0 + 112; }
                if (packed) { kind = 1; r0 = sl * 16 + (m < 8 ? m : m - 14); r1 = 0; }
                e0[0] = e0[1]; e1[0] = e1[1];
                e0[1] = kind | (m0 << 2) | (m1 << 6) | (c0 << 10) | (c1 << 21);
                e1[1] = r0 | (r1 << 16);
            }
        } else {
            const int j = t128 - 32;
            asm volatile("barrier.cluster.wait.aligned;" ::: "memory");
            uint2 wv[7];
            const int k = j < 56 ? j : 55, hh = k >= 28;
#pragma unroll
            for (int i = 0; i < 7; i++) wv[i] = __ldg(reinterpret_cast<const uint2*>(w_phi + (sl * 56 + k) * 28) + i);
#pragma unroll 1
            for (int i = j; i < 7168 / 16; i += 96) sts4(sb + OFF_WPHI + i * 16, 0, 0, 0, 0);
            bar_sync(5, 96);
            if (j < 56) {
                uint32_t a4[4];
#pragma unroll
                for (int q = 0; q < 4; q++) a4[q] = sb + OFF_WPHI + (4 * hh + q) * 128 + ((((k >> 3) ^ (4 * hh + q)) & 7) << 4) + (k & 7) * 2;
                FOR14(const uint32_t v = (t & 1) ? wv[t >> 1].y : wv[t >> 1].x;
                      asm volatile("{ .reg .b16 l, h; mov.b32 {l, h}, %2; st.shared.u16 [%0+%3], l; st.shared.u16 [%1+%3], h; }"
                                   ::"r"(a4[t >= 7 ? 2 : 0]), "r"(a4[t >= 7 ? 3 : 1]), "r"(v), "n"((t % 7) * 1024) : "memory"));
            }
            __syncwarp();
            fence_async();
            bar_arrive(1, 224);
            bar_arrive(9, 224);
            if (w == 1) {
                mbar_wait(BAR(2), 0);
                mbar_wait(BAR(2), 1);
                const int b = blockIdx.x;
                asm volatile(ELECT "cp.async.bulk.prefetch.L2.global [%0], %1; }" ::"l"(wg + b * 6272), "r"(12544) : "memory");
                asm volatile(ELECT "cp.async.bulk.prefetch.L2.global [%0], %1; }" ::"l"(wu + b * 6272), "r"(12544) : "memory");
                asm volatile(ELECT "cp.async.bulk.prefetch.L2.global [%0], %1; }" ::"l"(wd + b * 6272), "r"(12544) : "memory");
            }
        }
        uint32_t kseq = ld_word(g_c1 + (sl * 8 * 16 + tile) * 32);
        int slot = 0, ph = 0, n = NST;
#pragma unroll 1
        for (int layer = 0; layer < 3; layer++) {
            if (w == 0) {
                const int nend = layer == 0 ? 11 : (layer == 1 ? 42 : 63);
#pragma unroll 1
                for (; n < nend; n++) {
                const uint32_t w0 = __shfl_sync(0xffffffffu, n < 32 ? e0[0] : e0[1], n & 31), w1 = __shfl_sync(0xffffffffu, n < 32 ? e1[0] : e1[1], n & 31);
                const uint32_t dst = sb + slot * STAGE, fb = BAR(n == PACK ? B_PACK : slot);
                const CUtensorMap* m0 = &maps.x + ((w0 >> 2) & 15);
                const CUtensorMap* m1 = &maps.x + ((w0 >> 6) & 15);
                const int c0 = (w0 >> 10) & 2047, c1 = w0 >> 21, r0 = w1 & 0xffff, r1 = w1 >> 16;
                if (n == 25) {
                    int it = 0;
                    uint32_t v;
                    do { asm volatile("ld.acquire.gpu.global.u32 %0, [%1];" : "=r"(v) : "l"(g_cw + sl * 32) : "memory"); } while ((int)(v - cw_target) < 0 && ++it < 0x400000);
                    asm volatile("fence.proxy.async.global;" ::: "memory");
                    __syncwarp();
                }
                mbar_wait(BAR(B_EMPTY + slot), ph);
                __syncwarp();
                asm volatile(ELECT "mbarrier.arrive.expect_tx.shared::cta.b64 _, [%0], %1; }" ::"r"(fb), "r"(STAGE) : "memory");
                if ((w0 & 3) == 0) {
                    tma2d(dst, m0, c0, r0, fb);
                    tma2d(dst + HALF, m1, c1, r1, fb);
                } else if (w0 & 1) {
                    asm volatile(ELECT "cp.async.bulk.shared::cluster.global.mbarrier::complete_tx::bytes [%0], [%1], %2, [%3]; }"
                                 ::"r"(dst), "l"(reinterpret_cast<const char*>(g_wp) + (size_t)r0 * STAGE), "r"(STAGE), "r"(fb) : "memory");
                } else {
                    tma2d(dst, m0, c0, r0, fb); tma2d(dst + 7168, m0, c0, r1, fb);
                    tma2d(dst + HALF, m1, c0, r0, fb); tma2d(dst + HALF + 7168, m1, c0, r1, fb);
                }
                if (n == PACK) asm volatile(ELECT "mbarrier.arrive.shared::cta.b64 _, [%0]; }" ::"r"(BAR(slot)) : "memory");
                if (++slot == NST) { slot = 0; ph ^= 1; }
                }
            } else if (w == 1 && layer == 1) {
                constexpr int ps = PACK % NST;
                mbar_wait(BAR(B_PACK), 0);
                asm volatile("{ .reg .pred e; elect.sync _|e, 0xffffffff;\n"
                             "@e cp.async.bulk.global.shared::cta.bulk_group [%0], [%1], %2;\n"
                             "@e cp.async.bulk.commit_group;\n"
                             "@e cp.async.bulk.wait_group.read 0;\n"
                             "@e mbarrier.arrive.shared::cta.b64 _, [%3], 8;\n"
                             "@e cp.async.bulk.wait_group 0;\n"
                             "@e fence.proxy.async.global;\n"
                             "@e red.release.gpu.global.add.u32 [%4], 1; }"
                             ::"l"(reinterpret_cast<char*>(g_wp) + (size_t)(sl * 16 + tile) * STAGE), "r"(sb + ps * STAGE), "r"(STAGE), "r"(BAR(B_EMPTY + ps)), "l"(g_cw + sl * 32) : "memory");
                __syncwarp();
            }
            if (layer < 2) {
            const uint32_t tag = layer ^ 1;
            kseq++;
            bar_sync(7, 384);
            ASTAMP(0);
            if (tile < 15) {
                const int sq = lane >> 3, pk = 8 * w + (lane & (tile == 14 ? 3 : 7));
                uint32_t v[16];
                if (layer == 0) poll_cnt(g_c1 + ((sl * 8 + (w >> 1) * 4 + (tile >> 2)) * 16 + (lane & 15)) * 32, kseq);
                ASTAMP(1);
                poll4_kv<32>(v, g_kv1 + ((sl * 16 + tile) * 16 + 4 * sq) * 32 + pk, tag);
#pragma unroll
                for (int k = 0; k < 4; k++) {
                    float lo = (bf_lo(v[k]) + bf_lo(v[4 + k])) + (bf_lo(v[8 + k]) + bf_lo(v[12 + k]));
                    float hi = (bf_hi(v[k]) + bf_hi(v[4 + k])) + (bf_hi(v[8 + k]) + bf_hi(v[12 + k]));
                    lo += __shfl_xor_sync(0xffffffffu, lo, 8); hi += __shfl_xor_sync(0xffffffffu, hi, 8);
                    lo += __shfl_xor_sync(0xffffffffu, lo, 16); hi += __shfl_xor_sync(0xffffffffu, hi, 16);
                    v[k] = pack2(lo, hi);
                }
                if (sq == 0) st_pkt<0>(g_kv2 + sl * 512 + 32 * tile + pk, settag(v[0], tag), v[1], v[2], v[3]);
            }
            ASTAMP(2);
            {
                const int item = t128 < 112 ? t128 : 112 + (t128 & 3), d = item >> 1;
                const int cc = t128 < 112 ? 2 * (d >= 28) + (item & 1) : item - 112;
                const int r = t128 < 112 ? d : 56 + (cc >> 1) + 2 * ((t128 - 112) >> 2);
                uint32_t ra = sb + OFF_KVB + r * 128 + 4 * cc, rx = (r & 7) << 4;
                asm volatile("" : "+r"(ra), "+r"(rx));
                FOR14(asm volatile("st.shared.u32 [%0+%2], %1;" ::"r"((ra ^ 8) + (((t & 7) << 4) ^ rx)), "r"(0), "n"((t >> 3) * 8192) : "memory"));
                uint32_t v[16];
                asm volatile("" : "+r"(ra), "+r"(rx));
                poll4_kv<8>(v, g_kv2 + sl * 512 + (item >> 3) * 32 + (item & 7), tag);
                FOR14(asm volatile("st.shared.u32 [%0+%2], %1;" ::"r"(ra + (((t & 7) << 4) ^ rx)), "r"(v[t < 7 ? t : t + 1]), "n"((t >> 3) * 8192) : "memory"));
                fence_async();
            }
            bar_arrive(3, 384);
            ASTAMP(3);
            }
        }
    } else {
        asm volatile("setmaxnreg.inc.sync.aligned.u32 232;");
        int lane = fresh_tid() & 31, prf = pr;
#define pr prf
#define g (lane >> 2)
#define c (lane & 3)
#define t128 (w * 32 + lane)
        const int wu = __shfl_sync(0xffffffffu, fresh_tid() >> 5, 0), w = wu & 3;
        const uint32_t xoff = __shfl_sync(0xffffffffu, (3 * PLANE + ((tile * 2 + wgi) * 8) * 512 + w * 128) * 16, 0);
        char* xu = reinterpret_cast<char*>(g_ex) + xoff;
#define FRESH() asm volatile("" : "+l"(xu), "+r"(lane), "+r"(prf))
#define xp0 (reinterpret_cast<uint4*>(xu) + lane)
        const uint32_t hbuf = sb + OFF_H + wgi * STAGE;
        uint32_t slot = 0, ph = 0, eb1 = 0, eb2 = 0, ackph = 0, rcvph = 0, gatph = 0, swp = 0;
        uint32_t ppid = 6;
#define cx(s) (reinterpret_cast<uint32_t*>(reinterpret_cast<uint4*>(xu) + PL(1) + 112 + (s) * 512))
#define stp (reinterpret_cast<uint4*>(xu) + g + PL(0) + 112)
        uint32_t seq = ld_word(cx(sl));
        uint32_t kseq = ld_word(g_c1 + ((sl * 8 + wu) * 16 + tile) * 32);
        uint32_t stag = ld_word(reinterpret_cast<const uint32_t*>(stp + sl * 512) + 3) & 1;
        asm volatile("barrier.cluster.wait.aligned;" ::: "memory");
        STAMP(1);
        uint32_t X[14];
        const uint32_t x0row = (w < 2 ? hbuf : sb + wgi * STAGE) + ((w & 1) * 16 + (lane & 15)) * 128;
        mbar_wait(BAR(wgi), 0);
        STAMP(51);
#pragma unroll
        for (int j = 0; j < 4; j++) {
            const int G = 7 * sl + min(2 * j + (lane >> 4), 6);
            uint32_t q2, q3;
            asm volatile("ldmatrix.sync.aligned.m8n8.x4.shared.b16 {%0,%1,%2,%3}, [%4];" : "=r"(X[4 * j]), "=r"(X[4 * j + 1]), "=r"(q2), "=r"(q3)
                         : "r"(x0row + (G >> 3) * 4096 + (((G ^ lane) & 7) << 4)) : "memory");
            if (j < 3) { X[(4 * j + 2) % 14] = q2; X[(4 * j + 3) % 14] = q3; }
        }
#define PUSH_SLICE(W)                                                                          \
    {                                                                                          \
        if (t128 == 0) mbar_expect_tx(BAR(B_RECV + wgi), 7168);                                \
        PUSH_BEGIN();                                                                          \
        const uint32_t ra = mapa(hbuf + 24576 + t128 * 16, hr ^ 1), rb = mapa(sb + OFF_XR + wgi * 3072, hr ^ 1), rbar = mapa(BAR(B_RECV + wgi), hr ^ 1); \
        st_async4(ra, W[0], W[1], W[2], W[3], rbar);                                           \
        st_async4(ra + 2048, W[4], W[5], W[6], W[7], rbar);                                    \
        st_async4(rb + t128 * 16, W[8], W[9], W[10], W[11], rbar);                             \
        asm volatile("st.async.weak.shared::cluster.mbarrier::complete_tx::bytes.v2.b32 [%0], {%1,%2}, [%3];" ::"r"(rb + 2048 + t128 * 8), "r"(W[12]), "r"(W[13]), "r"(rbar) : "memory"); \
    }
#define PULL_SLICE(W)                                                                          \
    {                                                                                          \
        uint32_t t0, t1;                                                                       \
        mbar_wait(BAR(B_RECV + wgi), rcvph);                                                   \
        rcvph ^= 1;                                                                            \
        lds4(&A[1][0], hbuf + 24576 + t128 * 16);                                              \
        lds4(&A[1][4], hbuf + 26624 + t128 * 16);                                              \
        lds4(&A[1][8], sb + OFF_XR + wgi * 3072 + t128 * 16);                                  \
        asm volatile("ld.shared.v2.u32 {%0,%1}, [%2];" : "=r"(t0), "=r"(t1) : "r"(sb + OFF_XR + wgi * 3072 + 2048 + t128 * 8) : "memory"); \
        _Pragma("unroll") for (int i = 0; i < 12; i++) A[0][i] = (i & 3) ? W[i] : W[i] & ~1u;  \
        A[1][0] &= ~1u; A[1][4] &= ~1u; A[1][8] &= ~1u;                                        \
        A[0][12] = (hr ? t0 : W[12]) & ~1u; A[0][13] = hr ? t1 : W[13];                        \
        A[1][12] = (hr ? W[12] : t0) & ~1u; A[1][13] = hr ? W[13] : t1;                        \
        asm volatile("" : RW4(A[0], 0), RW4(A[0], 4), RW4(A[0], 8), RW2(A[0], 12), RW4(A[1], 0), RW4(A[1], 4), RW4(A[1], 8), RW2(A[1], 12)); \
        swp = hr * 448;                                                                        \
    }
#define SWB(b, t, db, sh) ((b) == 0 && (t) < 6 ? ((t) < 3 ? db##p : db##m) : db)
#define DECL_DB(b, MK, lbo, sh) const uint64_t db = MK(0, lbo, R_ADJ), dbp = (b) == 0 ? MK(0, lbo, R_ADJ + (swp >> (sh))) : db, dbm = (b) == 0 ? MK(0, lbo, R_ADJ - (swp >> (sh))) : db;
#define PPB 2
#define PP_WAIT() if (wgi == 1) { bar_sync(ppid, 256); ppid ^= 14; }
#define PP_GO() if (wgi == 0) { bar_arrive(ppid, 256); ppid ^= 14; }
#define GAT_DST(B, s2) ((B) == 1 ? hbuf + w * 3584 + (s2) * 1792 : ((s2) ? sb + OFF_KVB + wgi * 8192 : hbuf + 14336) + w * 1792)
#define GAT_ISSUE(B, base)                                                                     \
    {                                                                                          \
        const char* gs = xu + ((base) + kblk(pr, B) * 1024) * 16;                              \
        asm volatile("{ .reg .pred e; elect.sync _|e, 0xffffffff;\n"                           \
                     "@e mbarrier.arrive.expect_tx.shared::cta.b64 _, [%3], 3584;\n"           \
                     "@e cp.async.bulk.shared::cluster.global.mbarrier::complete_tx::bytes [%0], [%2], 1792, [%3];\n" \
                     "@e cp.async.bulk.shared::cluster.global.mbarrier::complete_tx::bytes [%1], [%2+8192], 1792, [%3]; }" \
                     ::"r"(GAT_DST(B, 0)), "r"(GAT_DST(B, 1)), "l"(gs), "r"(BAR(B_GAT + wu * 2 + ((B) >> 1))) : "memory"); \
        __syncwarp();                                                                          \
    }
#define GAT_FETCH(B)                                                                           \
    {                                                                                          \
        mbar_wait(BAR(B_GAT + wu * 2 + ((B) >> 1)), (gatph >> (B)) & 1);                          \
        gatph ^= 1 << (B);                                                                     \
        _Pragma("unroll") for (int s2 = 0; s2 < 2; s2++) {                                     \
            const uint32_t ga = GAT_DST(B, s2) + lane * 16;                                    \
            lds4(&A[2 * (B) + s2][0], ga); lds4(&A[2 * (B) + s2][4], ga + 512); lds4(&A[2 * (B) + s2][8], ga + 1024); \
            asm volatile("ld.shared.v2.u32 {%0,%1}, [%2];" : "=r"(A[2 * (B) + s2][12]), "=r"(A[2 * (B) + s2][13]) : "r"(ga - lane * 8 + 1536) : "memory"); \
        }                                                                                      \
    }
#define LATE_ARRIVE() do { if (lane == 0) mbar_arrive(BAR(B_LATE)); } while (0)
#define LATE_WAIT() do { mbar_wait(BAR(B_LATE), gatph & 1); gatph ^= 1; } while (0)
#define PT 3
#define PREP(b, t, remote)                                                                     \
    if constexpr ((b) < 3 && (t) == PT) {                                                      \
        wg_commit();                                                                           \
        STAMP(74 + 6 * (step & 1) + 2 * (b));                                                  \
        if (remote) {                                                                          \
            if constexpr ((b) == 0) { blk_load<2>(A, BLK(xsrc, 2), lane); GAT_FETCH(1) }       \
            blk_check<((b) + 1) & 3>(A, BLK(xsrc, (b) + 1), lane, xtag);                       \
            if constexpr ((b) == 0) blk_load<3>(A, BLK(xsrc, 3), lane);                        \
        }                                                                                      \
        STAMP(75 + 6 * (step & 1) + 2 * (b));                                                  \
        normalize<((b) + 1) & 3>(A, k0, k1);                                                   \
        asm volatile("" : RW4(A[(2 * (b) + 2) & 7], 0), RW4(A[(2 * (b) + 2) & 7], 4), RW4(A[(2 * (b) + 2) & 7], 8), RW2(A[(2 * (b) + 2) & 7], 12), \
                          RW4(A[(2 * (b) + 3) & 7], 0), RW4(A[(2 * (b) + 3) & 7], 4), RW4(A[(2 * (b) + 3) & 7], 8), RW2(A[(2 * (b) + 3) & 7], 12)); \
        wg_fence();                                                                            \
    }
#define X0_BLOCK(b)                                                                            \
    { const int rr = lane & 7, hi = lane >> 4;                                                 \
    const uint32_t rowa = (w < 2 ? hbuf : sb + wgi * STAGE) + ((w & 1) * 16 + (lane & 15)) * 128; \
    FOR7(constexpr int G = 14 * (b) + (t < 3 ? 2 * t : (t < 6 ? 2 * t + 1 : 6));               \
         uint32_t q0, q1, q2, q3;                                                              \
         const uint32_t ad = t < 6 ? rowa + (((((G & 7) + hi) ^ rr) & 7) << 4) + ((G & 7) == 7 ? hi * 4096 : 0) : rowa + ((G + 7 * hi) >> 3) * 4096 + ((((G + 7 * hi) ^ rr) & 7) << 4); \
         asm volatile("ldmatrix.sync.aligned.m8n8.x4.shared.b16 {%0,%1,%2,%3}, [%4+%5];" : "=r"(q0), "=r"(q1), "=r"(q2), "=r"(q3) \
                      : "r"(ad), "n"(t < 6 ? (G >> 3) * 4096 : 0) : "memory");                 \
         if (t < 3) { A[2 * (b)][4 * t] = q0; A[2 * (b)][4 * t + 1] = q1; A[2 * (b)][4 * t + 2] = q2; A[2 * (b)][4 * t + 3] = q3; } \
         else if (t < 6) { A[2 * (b) + 1][(4 * t - 12) & 15] = q0; A[2 * (b) + 1][((4 * t - 12) & 15) + 1] = q1; A[2 * (b) + 1][((4 * t - 12) & 15) + 2] = q2; A[2 * (b) + 1][((4 * t - 12) & 15) + 3] = q3; } \
         else { A[2 * (b)][12] = q0; A[2 * (b)][13] = q1; A[2 * (b) + 1][12] = q2; A[2 * (b) + 1][13] = q3; }); }
#define BLK(base, b) ((base) + kblk(pr, b) * 1024)

#pragma unroll 1
        for (int step = 0; step < 4; step++) {
            FRESH();
            const uint32_t tag = (step >> 1) ^ 1;
            const int so = (step >> 1) * 24 + (step & 1) * 12;
            (void)so;
            uint32_t A[8][14];
            uint4* const xsrc = xp0 + ((step & 1) ? PL(2) : PL(0));
            const uint32_t xtag = (step & 1) ? tag : ((seq >> 3) & 1) ^ 1;
            uint32_t xbits;
            {
                float st[4];
                slice_stats(X, st);
                stag ^= 1;
                xbits = x_bits(X);
                tag_slice(X, xtag);
                if (step) send_slice<0>(xsrc + sl * 512, lane, X);
                if (c == 0) st_pkt<0>(stp + sl * 512, __float_as_uint(st[0]), __float_as_uint(st[1]), __float_as_uint(st[2]), settag(__float_as_uint(st[3]), stag));
            }
            STAMP(2 + so);
            uint32_t sv[8];
            if (step == 0) {
                X0_BLOCK(0) X0_BLOCK(1) X0_BLOCK(2) X0_BLOCK(3)
                mbar_wait(BAR(wgi ^ 1), 0);
                R_NEXT();
                R_NEXT();
                R_RELEASE(2);
                stat_load(sv, stp + c * 1024);
                stat_check(sv, stp + c * 1024, stag);
                STAMP(52 + step);
            } else {
                kill<14>(A[2]); kill<14>(A[3]); kill<14>(A[4]); kill<14>(A[5]); kill<14>(A[6]); kill<14>(A[7]);
                PUSH_SLICE(X)
                stat_load(sv, stp + c * 1024);
                PULL_SLICE(X)
                stat_check(sv, stp + c * 1024, stag);
                STAMP(52 + step);
                GAT_ISSUE(1, (step & 1) ? PL(2) : PL(0))
            }
            LnCoef k0, k1;
            {
                k0 = ln_coef(__uint_as_float(sv[0]) + __uint_as_float(sv[4]), __uint_as_float(sv[1]) + __uint_as_float(sv[5]));
                k1 = ln_coef(__uint_as_float(sv[2]) + __uint_as_float(sv[6]), __uint_as_float(sv[3] & ~1u) + __uint_as_float(sv[7] & ~1u));
            }
            STAMP(3 + so);
            GSTAMP(70 + step);

            if ((step & 1) == 0) {
                float tq[28];
                {
                    float av[28];
#define KV_BLOCK(b)                                                                           \
    if ((b) == 1) R_RELEASE(2);                                                               \
    if ((b) == 2) { PUSH_ACK(); wg_wait<2>(); R_RELEASE(2); }                                 \
    R_WAIT();                                                                                 \
    if ((b) == PPK) { PP_WAIT() }                                                             \
    { DECL_DB(b, BASE128, 16, 0)                                                              \
    wg_fence();                                                                               \
    FOR7(mma_rs56<1, D128(0, t)>(tq, AQ(A, b, t), (b) + t > 0, SWB(b, t, db, 0));             \
         mma_rs56<1, D128(HALF, t)>(av, AQ(A, b, t), (b) + t > 0, SWB(b, t, db, 0));          \
         PREP(b, t, step)); }                                                                 \
    wg_commit();                                                                              \
    if ((b) == 3 && PPK < 4) { PP_GO() }                                                      \
    R_NEXT();
                    normalize<0>(A, k0, k1);
                    KV_BLOCK(0) KV_BLOCK(1) KV_BLOCK(2) KV_BLOCK(3)
                    wg_wait<0>();
                    if (lane < 3) mbar_arrive(BAR(B_EMPTY + (slot + NST - 1 - lane) % NST));
                    STAMP(4 + so);
                    WSUM(80 + 7 * (step >> 1));
                    const int m = lane >> 3, rr = lane & 7;
                    const uint32_t rowa = hbuf + 16384 + (w * 16 + rr + 8 * (m & 1)) * 128;
                    const uint32_t one = c == 0 ? 0x00003f80u : 0u;
                    if (step == 0) { bar_sync(wgi ? 9 : 1, 224); }
#pragma unroll
                    for (int j = 0; j < 4; j++) {
                        const uint32_t a = rowa + (((2 * j + (m >> 1)) ^ rr) << 4);
                        if (j < 3) stsm4(a, pack2(av[8 * j], av[8 * j + 1]), pack2(av[8 * j + 2], av[8 * j + 3]), pack2(av[8 * j + 4], av[8 * j + 5]), pack2(av[8 * j + 6], av[8 * j + 7]));
                        else stsm4(a, pack2(av[24], av[25]), pack2(av[26], av[27]), one, one);
                    }
                }
                uint32_t PH[28];
                int it = 1;
#pragma unroll 1
                do {
                    float pp[28];
                    phi_gemm(tq, pp);
                    dual_softmax(pp, PH);
                    if (((trips >> (it + 1)) & 1) == 0) continue;
                    {
                        const int m = lane >> 3, rr = lane & 7;
                        const uint32_t rowa = hbuf + (w * 16 + rr + 8 * (m & 1)) * 128;
#pragma unroll
                        for (int j = 0; j < 7; j++) {
                            const int cg = 2 * j + (m >> 1), hi = cg >= 7;
                            stsm4(rowa + hi * 8192 + (((cg - 7 * hi) ^ rr) << 4), PH[4 * j], PH[4 * j + 1], PH[4 * j + 2], PH[4 * j + 3]);
                        }
                    }
                    fence_async();
                    STAMP(5 + so);
#define Q_STAGE(b0)                                                                           \
    R_WAIT();                                                                                 \
    { DECL_DB(b0, BASE128, 16, 0)                                                             \
    wg_fence();                                                                               \
    FOR7(mma_rs56<1, D128(0, t)>(tq, AQ(A, b0, t), (b0) + t > 0, SWB(b0, t, db, 0)));         \
    FOR7(mma_rs56<1, D128(HALF, t)>(tq, AQ(A, (b0) + 1, t), 1, db)); }                        \
    wg_commit();                                                                              \
    R_NEXT();
                    if (QE && wgi == 0) { kill<28>(tq); Q_STAGE(0) Q_STAGE(2) wg_wait<1>(); R_RELEASE(2); wg_wait<0>(); R_RELEASE(1); }
                    bar_sync(2, 256);
                    float kv[28];
                    const uint64_t da = BASE128(OFF_H + 16384, 16, 0), dbk = BASE128(OFF_H, 16, wgi * 512);
                    wg_fence();
                    FOR8(constexpr uint64_t o = ((t >> 2) * STAGE + (t & 3) * 2048) >> 4; mma_ss56_tt<o, o>(kv, t > 0, da, dbk));
                    wg_commit();
                    wg_wait<0>();
#pragma unroll
                    for (int hf = 0; hf < 2; hf++) {
                        const int d = 16 * w + g + 8 * hf;
                        if ((d < 56 && (d >= 28) == (c >= 2)) || d == 56) {
                            const int item = d < 56 ? 2 * d + (c & 1) : 112 + c;
                            uint4* dst = g_kv1 + ((sl * 16 + (item >> 3)) * 16 + tile) * 32 + wgi * 16 + (item & 7);
#define KVW(i) pack2(kv[4 * (i) + 2 * hf], kv[4 * (i) + 2 * hf + 1])
                            st_pkt<0>(dst, settag(KVW(0), tag), KVW(1), KVW(2), KVW(3));
                            st_pkt<8>(dst, settag(KVW(4), tag), KVW(5), KVW(6), 0u);
                        }
                    }
                    __syncwarp();
                    kseq++;
                    if (lane == 0) st_word(g_c1 + ((sl * 8 + wu) * 16 + tile) * 32, kseq);
                    bar_arrive(7, 384);
                    STAMP(6 + so);
                    if (!QE || wgi == 1) { kill<28>(tq); Q_STAGE(0) Q_STAGE(2) wg_wait<1>(); R_RELEASE(2); wg_wait<0>(); R_RELEASE(1); }
                    STAMP(7 + so);
                    kill<28>(PH);
                } while (((trips >> (++it)) & 1));
                STAMP(8 + so);
                FRESH();
                if (step) {
                    slice_load<PL(0)>(X, xp0 + sl * 512, lane);
                } else {
                    const uint32_t* xp = reinterpret_cast<const uint32_t*>(x_in + (size_t)(tile * 128 + wu * 16 + g) * 448 + 56 * sl + 2 * c);
#pragma unroll
                    for (int i = 0; i < 7; i++) { X[2 * i] = __ldg(xp + 4 * i); X[2 * i + 1] = __ldg(xp + 4 * i + 8 * 224); }
                }
                bar_sync(3, 384);
                STAMP(9 + so);
                const uint4* const osrc = xp0 + PL(1);
                {
                    float nm[32];
                    const uint64_t db = BASE128(OFF_KVB, 16, 0);
                    wg_fence();
                    FOR7(mma_rs64<0, ((t >> 2) * 8192 + (t & 3) * 32) / 16>(nm, PH[4 * t], PH[4 * t + 1], PH[4 * t + 2], PH[4 * t + 3], t > 0, db));
                    wg_commit();
                    wg_wait<0>();
                    LATE_ARRIVE();
                    const float i00 = rcp(nm[28] + 1e-6f), i01 = rcp(nm[29] + 1e-6f), i10 = rcp(nm[30] + 1e-6f), i11 = rcp(nm[31] + 1e-6f);
                    const float m0 = c >= 2 ? i01 : i00, m1 = c >= 2 ? i11 : i10;
                    uint32_t O[14];
#pragma unroll
                    for (int i = 0; i < 7; i++) {
                        const float f0 = i < 3 ? i00 : (i > 3 ? i01 : m0), f1 = i < 3 ? i10 : (i > 3 ? i11 : m1);
                        O[2 * i] = pack2(nm[4 * i] * f0, nm[4 * i + 1] * f0);
                        O[2 * i + 1] = pack2(nm[4 * i + 2] * f1, nm[4 * i + 3] * f1);
                    }
                    if (OST) { PP_WAIT() }
                    tag_slice(O, tag);
                    send_slice<PL(1)>(xp0 + sl * 512, lane, O);
                    seq++;
                    if (lane == 0) st_word(cx(sl), seq);
                    STAMP(10 + so);
                    PUSH_SLICE(O)
                    if (OST == 1) { PP_GO() }
                    const uint32_t cv = ld_word(cx(lane & 7));
                    PULL_SLICE(O)
                    LATE_WAIT();
                    check_cnt(cv, cx(lane & 7), seq);
                    if (OST == 2) { PP_GO() }
                    STAMP(56 + (step >> 1));
                    GAT_ISSUE(1, PL(1))
                    GAT_ISSUE(3, PL(1))
                    blk_load<2>(A, BLK(osrc, 2), lane);
                }
                float ao[28];
#define WO_BLOCK(b)                                                                           \
    if ((b) > 0) blk_check<b>(A, BLK(osrc, b), lane, tag);                                    \
    if (((b) & 1) == 0) R_WAIT();                                                             \
    { DECL_DB(b, BASE128, 16, 0)                                                              \
    wg_fence();                                                                               \
    FOR7(mma_rs56<1, D128(((b) & 1) * HALF, t)>(ao, AQ(A, b, t), (b) + t > 0, SWB(b, t, db, 0))); } \
    wg_commit();                                                                              \
    if ((b) & 1) R_NEXT();
                WO_BLOCK(0)
                STAMP(11 + so);
                GAT_FETCH(1)
                WO_BLOCK(1)
                WO_BLOCK(2)
                GAT_FETCH(3)
                WO_BLOCK(3)
                PUSH_ACK();
                wg_wait<0>();
                R_RELEASE(2);
                STAMP(12 + so);
                WSUM(86 + 7 * (step >> 1));
                x_fix(X, xbits);
#pragma unroll
                for (int i = 0; i < 14; i++) X[i] = pack2(bf_lo(X[i]) + ao[2 * i], bf_hi(X[i]) + ao[2 * i + 1]);
            } else {
                uint32_t H[56];
                float ag[64];
#define F1_EPI(dst, ng, ag)                                                                    \
    _Pragma("unroll") for (int i = 0; i < 2 * (ng); i++)                                       \
        (dst)[i] = pack2(geglu(ag[2 * i], ag[4 * (ng) + 2 * i]), geglu(ag[2 * i + 1], ag[4 * (ng) + 2 * i + 1]));
#define H_PUSH(h0, off) st_async4(rem_h + (off), H[h0], H[(h0) + 1], H[(h0) + 2], H[(h0) + 3], mapa(BAR(B_RECV2 + wgi), hr ^ 1));
#define F1_BLOCK(b, first)                                                                     \
    if ((first) && (b) == 1) R_RELEASE(2);                                                     \
    if ((first) && (b) == 2) PUSH_ACK();                                                       \
    R_WAIT();                                                                                  \
    if ((b) == ((first) ? PPF : PPB)) { PP_WAIT() }                                            \
    { DECL_DB(b, BASE128, HALF, 0)                                                             \
    wg_fence();                                                                                \
    FOR7(mma_rs128<1, D128(0, t)>(ag, AQ(A, b, t), (b) + t > 0, SWB(b, t, db, 0));             \
         if constexpr (first) { PREP(b, t, true) }); }                                         \
    wg_commit();                                                                               \
    if ((b) == 3) { PP_GO() }                                                                  \
    if ((b) > 0) { wg_wait<1>(); R_RELEASE(1); }       \
    R_NEXT();
                normalize<0>(A, k0, k1);
                F1_BLOCK(0, true) F1_BLOCK(1, true) F1_BLOCK(2, true) F1_BLOCK(3, true)
                if (t128 == 0) { mbar_expect_tx(BAR(B_RECV + wgi), 16384); mbar_expect_tx(BAR(B_RECV2 + wgi), 12288); }
                PUSH_BEGIN();
                wg_wait<0>();
                R_RELEASE(1);
                int p = 0;
#pragma unroll 1
                do {
                    F1_EPI(H + 32, 8, ag)
                    STAMP(4 + p + so);
                    WSUM(81 + p + 7 * (step >> 1));
                    if (((trips >> (p + 1)) & 1) == 0) continue;
                    {
                        const uint32_t pk = (p ? hbuf + 16384 : sb + OFF_KVB + wgi * 8192) + w * 2048;
#pragma unroll
                        for (int k = 0; k < 4; k++) sts4(pk + k * 512 + lane * 16, H[32 + 4 * k], H[33 + 4 * k], H[34 + 4 * k], H[35 + 4 * k]);
                        fence_async();
                        __syncwarp();
                        asm volatile(ELECT "cp.async.bulk.shared::cluster.shared::cta.mbarrier::complete_tx::bytes [%0], [%1], 2048, [%2]; }"
                                     ::"r"(mapa(hbuf + p * 8192 + w * 2048, hr ^ 1)), "r"(pk), "r"(mapa(BAR(B_RECV + wgi), hr ^ 1)) : "memory");
                    }
                    if (step == 1 && p == PKP) R_NEXT();
                    kill<64>(ag);
                    F1_BLOCK(0, false) F1_BLOCK(1, false) F1_BLOCK(2, false) F1_BLOCK(3, false)
                    wg_wait<0>();
                    R_RELEASE(1);
                    kill<16>(H + 32);
                } while (((trips >> (++p)) & 1));
#pragma unroll
                for (int k = 0; k < 4; k++) lds4(H + 16 + 4 * k, hbuf + 16384 + w * 2048 + k * 512 + lane * 16);
                __syncwarp();
                if (lane == 0) asm volatile("mbarrier.arrive.shared::cluster.b64 _, [%0];" ::"r"(mapa(BAR(B_ACK2 + wgi), hr ^ 1)) : "memory");
                const uint32_t rem_h = mapa(hbuf + w * 2048 + lane * 16, hr ^ 1);
#define F1_LAST(b0)                                                                            \
    R_WAIT();                                                                                  \
    if (b0) { PP_WAIT() }                                                                      \
    { DECL_DB(b0, BASE64, HALF, 1)                                                             \
    wg_fence();                                                                                \
    FOR7(mma_rs64<1, D64(0, t)>(al, AQ(A, b0, t), (b0) + t > 0, SWB(b0, t, db, 1)));           \
    FOR7(mma_rs64<1, D64(7168, t)>(al, AQ(A, (b0) + 1, t), 1, db)); }                          \
    wg_commit();                                                                               \
    if (b0) { PP_GO() }                                                                        \
    R_NEXT();
                float al[32];
                F1_LAST(0)
                mbar_wait(BAR(B_RECV + wgi), rcvph);
                rcvph ^= 1;
                mbar_wait(BAR(B_ACK2 + wgi), step >> 1);
                H_PUSH(32, 16384) H_PUSH(36, 16896)
                F1_LAST(2)
                H_PUSH(40, 17408) H_PUSH(44, 17920)
                wg_wait<1>();
                R_RELEASE(2);
                wg_wait<0>();
                R_RELEASE(1);
                uint32_t HP[56];
#pragma unroll
                for (int k = 0; k < 4; k++) lds4(H + 4 * k, sb + OFF_KVB + wgi * 8192 + w * 2048 + k * 512 + lane * 16);
#pragma unroll
                for (int t = 0; t < 8; t++) lds4(HP + 4 * t, hbuf + (t >> 2) * 8192 + w * 2048 + (t & 3) * 512 + lane * 16);
                F1_EPI(H + 48, 4, al)
                H_PUSH(48, 24576 - w * 1024) H_PUSH(52, 25088 - w * 1024)
                STAMP(7 + so);
                WSUM(84 + 7 * (step >> 1));
                FRESH();
                float acc[28];
                const uint32_t roA = hr ? 256u : 0u, roB = hr ? (uint32_t)-1536 : 0u;
                const uint32_t rpA = hr ? 0u : 256u, rpB = hr ? 0u : (uint32_t)-1536;
                float res[28];
                uint32_t v0[14], v1[14], P[14];
                const uint4* ps = xp0 + sl * 512;
#define F2_OWN_A()                                                                             \
    R_WAIT();                                                                                  \
    d0 = BASE128(0, 16, R_ADJ + roA); d1 = BASE128(0, 16, R_ADJ + roB);                        \
    wg_fence();                                                                                \
    FOR14(if constexpr (t < OT) mma_rs56<1, t * 128>(acc, H[4 * t], H[4 * t + 1], H[4 * t + 2], H[4 * t + 3], t > 0, d0)); \
    wg_commit();
#define F2_OWN_B()                                                                             \
    wg_fence();                                                                                \
    FOR14(if constexpr (t >= OT) mma_rs56<1, t * 128>(acc, H[4 * t], H[4 * t + 1], H[4 * t + 2], H[4 * t + 3], 1, t < 12 ? d0 : d1)); \
    wg_commit();                                                                               \
    R_NEXT();
#define F2_PEER()                                                                              \
    R_WAIT();                                                                                  \
    if (F2PP) { PP_WAIT() }                                                                    \
    d0 = BASE128(0, 16, R_ADJ + rpA); d1 = BASE128(0, 16, R_ADJ + rpB);                        \
    wg_fence();                                                                                \
    FOR14(mma_rs56<1, t * 128>(acc, HP[4 * t], HP[4 * t + 1], HP[4 * t + 2], HP[4 * t + 3], 1, t < 12 ? d0 : d1)); \
    wg_commit();                                                                               \
    if (F2PP) { PP_GO() }                                                                      \
    R_NEXT();
#define F2_TURN(u)                                                                             \
    wg_wait<1>();                                                                              \
    if ((u) < 2 || TDEF < 2) R_RELEASE(2);                                                     \
    wg_wait<0>();                                                                              \
    if ((u) < 2 || TDEF < 1) R_RELEASE(1);                                                     \
    _Pragma("unroll") for (int i = 0; i < 14; i++) P[i] = pack2(acc[2 * i], acc[2 * i + 1]);   \
    tag_slice(P, tag);                                                                         \
    asm volatile("" : RW4(P, 0), RW4(P, 4), RW4(P, 8), RW2(P, 12));                            \
    kill<28>(acc);                                                                             \
    F2_OWN_A()                                                                                 \
    if ((u) == 2) { slice_load<PL(3)>(v0, ps, lane); slice_load<PL(4)>(v1, ps, lane); } \
    send_slice<PL(3 + (u))>(xp0 + (2 * ((pr + (u) + 1) & 3) + hr) * 512, lane, P);             \
    seq++;                                                                                     \
    if (lane == 0) st_word(cx(sl), seq);                                                       \
    __syncwarp();                                                                              \
    STAMP(8 + (u) + so);                                                                       \
    F2_OWN_B()
                uint64_t d0, d1;
                F2_OWN_A()
                F2_OWN_B()
                R_WAIT();
                d0 = BASE128(0, 16, R_ADJ + rpA); d1 = BASE128(0, 16, R_ADJ + rpB);
                wg_fence();
                FOR8(mma_rs56<1, t * 128>(acc, HP[4 * t], HP[4 * t + 1], HP[4 * t + 2], HP[4 * t + 3], 1, d0));
                wg_commit();
                mbar_wait(BAR(B_RECV2 + wgi), step >> 1);
#pragma unroll
                for (int k = 0; k < 4; k++) lds4(HP + 32 + 4 * k, hbuf + 16384 + w * 2048 + k * 512 + lane * 16);
                lds4(HP + 48, hbuf + 24576 + w * 1024 + lane * 16);
                lds4(HP + 52, hbuf + 25088 + w * 1024 + lane * 16);
                if (step == 1) PUSH_ACK();
                wg_fence();
                FOR14(if constexpr (t >= 8) mma_rs56<1, t * 128>(acc, HP[4 * t], HP[4 * t + 1], HP[4 * t + 2], HP[4 * t + 3], 1, t < 12 ? d0 : d1));
                wg_commit();
                R_NEXT();
                F2_TURN(0)
                F2_PEER()
                F2_TURN(1)
                F2_PEER()
                F2_TURN(2)
                if (step == 1) STAMP(64);
                slice_check<PL(3)>(v0, ps, lane, tag);
                slice_check<PL(4)>(v1, ps, lane, tag);
#pragma unroll
                for (int i = 0; i < 14; i++) { res[2 * i] = bf_lo(v0[i]) + bf_lo(v1[i]); res[2 * i + 1] = bf_hi(v0[i]) + bf_hi(v1[i]); }
                slice_load<PL(2)>(X, ps, lane);
                if (step == 1) STAMP(65);
                F2_PEER()
                if (step == 1) STAMP(66);
                poll_cnt(cx(2 * ((pr + 1) & 3) + hr), seq);
                if (step == 1) STAMP(67);
                slice_load<PL(5)>(v0, ps, lane);
                x_fix(X, xbits);
                slice_check<PL(5)>(v0, ps, lane, tag);
                if (lane < TDEF) mbar_arrive(BAR(B_EMPTY + (slot + NST - 3 - lane) % NST));
#pragma unroll
                for (int i = 0; i < 14; i++) { res[2 * i] += bf_lo(v0[i]); res[2 * i + 1] += bf_hi(v0[i]); }
                STAMP(11 + so);
                wg_wait<0>();
                R_RELEASE(2);
                STAMP(12 + so);
                WSUM(85 + 7 * (step >> 1));
#pragma unroll
                for (int i = 0; i < 14; i++) X[i] = pack2(fmaf(res[2 * i] + acc[2 * i], 0.5f, bf_lo(X[i])), fmaf(res[2 * i + 1] + acc[2 * i + 1], 0.5f, bf_hi(X[i])));
            }
        }
        {
            const int m = lane >> 3, rr = lane & 7;
            const uint32_t ob = hbuf + w * 2048, rowa = ob + (rr + 8 * (m & 1)) * 112 + (m >> 1) * 16;
#pragma unroll
            for (int j = 0; j < 3; j++) stsm4(rowa + 32 * j, X[4 * j], X[4 * j + 1], X[4 * j + 2], X[4 * j + 3]);
            asm volatile("stmatrix.sync.aligned.m8n8.x2.shared.b16 [%0], {%1,%2};" ::"r"(ob + (rr + 8 * (m & 1)) * 112 + 96), "r"(X[12]), "r"(X[13]) : "memory");
            fence_async();
            __syncwarp();
            if (lane == 0) {
                asm volatile("cp.async.bulk.tensor.2d.global.shared::cta.bulk_group [%0, {%2, %3}], [%1];" ::"l"(&maps.out), "r"(ob), "r"(56 * sl), "r"(tile * 128 + wu * 16) : "memory");
                asm volatile("cp.async.bulk.commit_group;" ::: "memory");
                asm volatile("cp.async.bulk.wait_group.read 0;" ::: "memory");
            }
        }
        STAMP(50);
        GSTAMP(61);
        PDUMP();
    }
}

#undef g
#undef pr
#undef c
#undef t128

typedef CUresult (*EncodeFn)(CUtensorMap*, CUtensorMapDataType, cuuint32_t, void*, const cuuint64_t*, const cuuint64_t*, const cuuint32_t*,
                             const cuuint32_t*, CUtensorMapInterleave, CUtensorMapSwizzle, CUtensorMapL2promotion, CUtensorMapFloatOOBfill);

static void make_map(EncodeFn enc, CUtensorMap* m, const void* p, uint64_t cols, uint64_t rows, uint32_t bc, uint32_t br, CUtensorMapSwizzle sw) {
    cuuint64_t gd[2] = {cols, rows};
    cuuint64_t gs[1] = {cols * 2};
    cuuint32_t bd[2] = {bc, br};
    cuuint32_t es[2] = {1, 1};
    enc(m, CU_TENSOR_MAP_DATA_TYPE_BFLOAT16, 2, const_cast<void*>(p), gd, gs, bd, es, CU_TENSOR_MAP_INTERLEAVE_NONE, sw,
        CU_TENSOR_MAP_L2_PROMOTION_L2_128B, CU_TENSOR_MAP_FLOAT_OOB_FILL_NONE);
}

extern "C" void kernel_launch(void* const* d_in, const int* in_sizes, int n_in, void* d_out, int out_size) {
    (void)in_sizes; (void)n_in; (void)out_size;
    static EncodeFn enc = nullptr;
    static Scratch* scratch = nullptr;
    if (!enc) {
        void* fn = nullptr;
        cudaDriverEntryPointQueryResult qr;
        cudaGetDriverEntryPoint("cuTensorMapEncodeTiled", &fn, cudaEnableDefault, &qr);
        enc = (EncodeFn)fn;
        cudaGetSymbolAddress((void**)&scratch, g_scratch);
        cudaFuncSetAttribute(fused_kernel, cudaFuncAttributeMaxDynamicSharedMemorySize, SMEM_BYTES);
    }
    Maps maps;
    {
        cuuint64_t gd[3] = {64, 2048, 7};
        cuuint64_t gs[2] = {896, 128};
        cuuint32_t bd[3] = {64, 32, 7};
        cuuint32_t es[3] = {1, 1, 1};
        enc(&maps.x, CU_TENSOR_MAP_DATA_TYPE_BFLOAT16, 3, d_in[0], gd, gs, bd, es, CU_TENSOR_MAP_INTERLEAVE_NONE, CU_TENSOR_MAP_SWIZZLE_128B,
            CU_TENSOR_MAP_L2_PROMOTION_L2_128B, CU_TENSOR_MAP_FLOAT_OOB_FILL_NONE);
    }
    make_map(enc, &maps.out, d_out, 448, 2048, 56, 16, CU_TENSOR_MAP_SWIZZLE_NONE);
    make_map(enc, &maps.qkv, d_in[1], 1344, 448, 64, 112, CU_TENSOR_MAP_SWIZZLE_128B);
    make_map(enc, &maps.wo, d_in[3], 448, 448, 64, 112, CU_TENSOR_MAP_SWIZZLE_128B);
    make_map(enc, &maps.wg, d_in[5], 1792, 448, 64, 112, CU_TENSOR_MAP_SWIZZLE_128B);
    make_map(enc, &maps.wu, d_in[6], 1792, 448, 64, 112, CU_TENSOR_MAP_SWIZZLE_128B);
    make_map(enc, &maps.wg32, d_in[5], 1792, 448, 32, 112, CU_TENSOR_MAP_SWIZZLE_64B);
    make_map(enc, &maps.wu32, d_in[6], 1792, 448, 32, 112, CU_TENSOR_MAP_SWIZZLE_64B);
    make_map(enc, &maps.wd, d_in[7], 448, 1792, 64, 112, CU_TENSOR_MAP_SWIZZLE_128B);
    fused_kernel<<<128, 384, SMEM_BYTES>>>(scratch, (const __nv_bfloat16*)d_in[0], (const __nv_bfloat16*)d_in[2], 7, (const __nv_bfloat16*)d_in[5],
                                           (const __nv_bfloat16*)d_in[6], (const __nv_bfloat16*)d_in[7], maps);
}
```

```cpp
#include <cuda_runtime.h>
#include <cuda.h>
#include <cuda_bf16.h>
#include <stdint.h>
#include <type_traits>

#define PPF 2
#define PKP 0
#define TDEF 1
#define TMPF 0
#define NORM1 0
#define PP0 1
#define ACAN 0
#define SPLIT0 1
#define OT 2
#define F2PP 0
#define PPK 2
#define QE 1
#define OST 1
#define PP

namespace {

constexpr uint32_t STAGE = 28672, HALF = 14336;
constexpr int NST = 5;
constexpr uint32_t OFF_H = NST * STAGE;
constexpr uint32_t OFF_KVB = OFF_H + 2 * STAGE;
constexpr uint32_t OFF_WPHI = OFF_KVB + 16384;
constexpr uint32_t OFF_XR = OFF_WPHI + 7168;
constexpr uint32_t OFF_BAR = OFF_XR + 6144;
constexpr uint32_t SMEM_BYTES = OFF_BAR + 384 + 1408;
constexpr int B_EMPTY = NST, B_RECV = 2 * NST, B_RECV2 = B_RECV + 2, B_PACK = B_RECV2 + 2, B_GAT = B_PACK + 1, B_LATE = B_GAT + 16, B_ACK = B_LATE + 1, B_ACK2 = B_ACK + 2, B_COUNT = B_ACK2 + 2;

constexpr int PACK = 14 + 4 * PKP;

struct Maps { CUtensorMap x, qkv, wo, wg, wu, wg32, wu32, wd, out; };

}

constexpr int PLANE = 16 * 2 * 8 * 512;
struct Scratch {
    uint4 ex[6 * PLANE];
    uint4 kv1[8 * 16 * 16 * 32];
    uint4 kv2[8 * 512];
    uint32_t c1[8 * 8 * 16 * 32];
    uint32_t cw[8 * 32];
    uint4 wp[8 * 32 * (HALF / 16)];
};
__device__ __align__(1024) Scratch g_scratch;
#define g_ex (sc->ex)
#define g_kv1 (sc->kv1)
#define g_kv2 (sc->kv2)
#define g_c1 (sc->c1)
#define g_cw (sc->cw)
#define g_wp (sc->wp)
#define STAMP(i)
#define GSTAMP(i)
#define PDUMP()
#define ASTAMP(i)

namespace {

__device__ __forceinline__ int fresh_tid() { int t; asm volatile("mov.u32 %0, %%tid.x;" : "=r"(t)); return t; }
template <int N> __device__ __forceinline__ void kill(uint32_t* v) {
#pragma unroll
    for (int i = 0; i < N; i++) v[i] = 0;
}
template <int N> __device__ __forceinline__ void kill(float* v) {
#pragma unroll
    for (int i = 0; i < N; i++) v[i] = 0.f;
}
__device__ __forceinline__ uint32_t s2u(const void* p) { return (uint32_t)__cvta_generic_to_shared(p); }
__device__ __forceinline__ void mbar_init(uint32_t a, uint32_t c) { asm volatile("mbarrier.init.shared::cta.b64 [%0], %1;" ::"r"(a), "r"(c) : "memory"); }
__device__ __forceinline__ void mbar_expect_tx(uint32_t a, uint32_t b) { asm volatile("mbarrier.arrive.expect_tx.shared::cta.b64 _, [%0], %1;" ::"r"(a), "r"(b) : "memory"); }
__device__ __forceinline__ void mbar_arrive(uint32_t a) { asm volatile("mbarrier.arrive.shared::cta.b64 _, [%0];" ::"r"(a) : "memory"); }
#define GIVE_UP(id) "trap;\n"
#define SPIN_MAX "0x400000"
#define SPIN_TAIL(id) "add.u32 n, n, 1;\n setp.lt.u32 p, n, " SPIN_MAX ";\n @p bra.uni LP;\n" GIVE_UP(id) " DN:\n }"
__device__ __forceinline__ void mbar_wait(uint32_t a, uint32_t ph) {
    asm volatile("{ .reg .pred p; .reg .b32 n; mov.u32 n, 0;\n LP:\n"
                 "mbarrier.try_wait.parity.shared::cta.b64 p, [%0], %1;\n @p bra DN;\n"
                 "add.u32 n, n, 1;\n setp.lt.u32 p, n, " SPIN_MAX ";\n @p bra LP;\n"
                 GIVE_UP("")
                 " DN:\n }" ::"r"(a), "r"(ph) : "memory");
}
#define ELECT "{ .reg .pred e; elect.sync _|e, 0xffffffff; @e "
__device__ __forceinline__ void tma2d(uint32_t dst, const CUtensorMap* m, int c0, int c1, uint32_t bar) {
    asm volatile(ELECT "cp.async.bulk.tensor.2d.shared::cluster.global.mbarrier::complete_tx::bytes [%0], [%1, {%3, %4}], [%2]; }" ::"r"(dst), "l"(m), "r"(bar), "r"(c0), "r"(c1) : "memory");
}
__device__ __forceinline__ void tma3x(uint32_t dst, const CUtensorMap* m, int row, uint32_t bar) {
    asm volatile(ELECT "cp.async.bulk.tensor.3d.shared::cluster.global.mbarrier::complete_tx::bytes [%0], [%1, {0, %3, 0}], [%2]; }" ::"r"(dst), "l"(m), "r"(bar), "r"(row) : "memory");
}
template <int OFF>
__device__ __forceinline__ void ld_pkt(uint32_t* v, const uint4* p) {
    asm volatile("{ .reg .b128 t; ld.relaxed.gpu.global.b128 t, [%4+%5]; mov.b128 {%0,%1,%2,%3}, t; }" : "=r"(v[0]), "=r"(v[1]), "=r"(v[2]), "=r"(v[3]) : "l"(p), "n"(OFF * 16) : "memory");
}
template <int OFF>
__device__ __forceinline__ void st_pkt(uint4* p, uint32_t a, uint32_t b, uint32_t c, uint32_t d) {
    asm volatile("{ .reg .b128 t; mov.b128 t, {%1,%2,%3,%4}; st.relaxed.gpu.global.b128 [%0+%5], t; }" ::"l"(p), "r"(a), "r"(b), "r"(c), "r"(d), "n"(OFF * 16) : "memory");
}
__device__ __forceinline__ uint32_t pack2(float lo, float hi) {
    uint32_t r;
    asm("cvt.rn.bf16x2.f32 %0, %1, %2;" : "=r"(r) : "f"(hi), "f"(lo));
    return r;
}
__device__ __forceinline__ float bf_lo(uint32_t w) { return __uint_as_float(w << 16); }
__device__ __forceinline__ float bf_hi(uint32_t w) { return __uint_as_float(w & 0xffff0000u); }
__device__ __forceinline__ uint32_t settag(uint32_t w, uint32_t tag) { return (w & ~1u) | tag; }
__device__ __forceinline__ float ex2(float x) { float y; asm("ex2.approx.ftz.f32 %0, %1;" : "=f"(y) : "f"(x)); return y; }
__device__ __forceinline__ float rcp(float x) { float y; asm("rcp.approx.ftz.f32 %0, %1;" : "=f"(y) : "f"(x)); return y; }
__device__ __forceinline__ float tanh_hw(float x) { float y; asm("tanh.approx.f32 %0, %1;" : "=f"(y) : "f"(x)); return y; }
__device__ __forceinline__ void stsm4(uint32_t addr, uint32_t a, uint32_t b, uint32_t c, uint32_t d) {
    asm volatile("stmatrix.sync.aligned.m8n8.x4.shared.b16 [%0], {%1,%2,%3,%4};" ::"r"(addr), "r"(a), "r"(b), "r"(c), "r"(d) : "memory");
}
__device__ __forceinline__ void fence_async() { asm volatile("fence.proxy.async.shared::cta;" ::: "memory"); }
__device__ __forceinline__ void bar_sync(int id, int n) { asm volatile("bar.sync %0, %1;" ::"r"(id), "r"(n) : "memory"); }
__device__ __forceinline__ void bar_arrive(int id, int n) { asm volatile("bar.arrive %0, %1;" ::"r"(id), "r"(n) : "memory"); }
__device__ __forceinline__ void wg_fence() { asm volatile("wgmma.fence.sync.aligned;" ::: "memory"); }
__device__ __forceinline__ void wg_commit() { asm volatile("wgmma.commit_group.sync.aligned;" ::: "memory"); }
template <int N> __device__ __forceinline__ void wg_wait() { asm volatile("wgmma.wait_group.sync.aligned %0;" ::"n"(N) : "memory"); }

constexpr uint32_t SB0 = 1024;
__host__ __device__ constexpr uint32_t dlo(uint32_t off, uint32_t lbo) { return ((SB0 + off) >> 4) | ((lbo >> 4) << 16); }
__host__ __device__ constexpr uint32_t dhi(uint32_t sbo, uint32_t sw) { return (sbo >> 4) | (sw << 30); }
__device__ __forceinline__ uint64_t dbase(uint32_t lo, uint32_t hi) { uint64_t d; asm volatile("mov.b64 %0, {%1, %2};" : "=l"(d) : "r"(lo), "r"(hi)); return d; }
#define BASE128(off, lbo, adj) dbase(dlo(off, lbo) + (adj), dhi(1024, 1))
#define BASE64(off, lbo, adj) dbase(dlo(off, lbo) + (adj), dhi(512, 2))

#define ACC4(d, o) "+f"(d[o]), "+f"(d[o + 1]), "+f"(d[o + 2]), "+f"(d[o + 3])
#define ACC28(d) ACC4(d, 0), ACC4(d, 4), ACC4(d, 8), ACC4(d, 12), ACC4(d, 16), ACC4(d, 20), ACC4(d, 24)
#define ACC32(d, o) ACC4(d, o), ACC4(d, o + 4), ACC4(d, o + 8), ACC4(d, o + 12), ACC4(d, o + 16), ACC4(d, o + 20), ACC4(d, o + 24), ACC4(d, o + 28)

template <int TB, uint64_t D>
__device__ __forceinline__ void mma_rs56(float* d, uint32_t a0, uint32_t a1, uint32_t a2, uint32_t a3, int sd, uint64_t base) {
    asm volatile("{ .reg .pred p; .reg .b64 db; setp.ne.b32 p, %32, 0; add.u64 db, %33, %34;\n"
                 "wgmma.mma_async.sync.aligned.m64n56k16.f32.bf16.bf16 "
                 "{%0,%1,%2,%3,%4,%5,%6,%7,%8,%9,%10,%11,%12,%13,%14,%15,%16,%17,%18,%19,%20,%21,%22,%23,%24,%25,%26,%27}, "
                 "{%28,%29,%30,%31}, db, p, 1, 1, %35; }\n"
                 : ACC28(d)
                 : "r"(a0), "r"(a1), "r"(a2), "r"(a3), "r"(sd), "l"(base), "n"(D), "n"(TB));
}
template <int TB, uint64_t D>
__device__ __forceinline__ void mma_rs64(float* d, uint32_t a0, uint32_t a1, uint32_t a2, uint32_t a3, int sd, uint64_t base) {
    asm volatile("{ .reg .pred p; .reg .b64 db; setp.ne.b32 p, %36, 0; add.u64 db, %37, %38;\n"
                 "wgmma.mma_async.sync.aligned.m64n64k16.f32.bf16.bf16 "
                 "{%0,%1,%2,%3,%4,%5,%6,%7,%8,%9,%10,%11,%12,%13,%14,%15,%16,%17,%18,%19,%20,%21,%22,%23,%24,%25,%26,%27,%28,%29,%30,%31}, "
                 "{%32,%33,%34,%35}, db, p, 1, 1, %39; }\n"
                 : ACC32(d, 0)
                 : "r"(a0), "r"(a1), "r"(a2), "r"(a3), "r"(sd), "l"(base), "n"(D), "n"(TB));
}
template <int TB, uint64_t D>
__device__ __forceinline__ void mma_rs128(float* d, uint32_t a0, uint32_t a1, uint32_t a2, uint32_t a3, int sd, uint64_t base) {
    asm volatile("{ .reg .pred p; .reg .b64 db; setp.ne.b32 p, %68, 0; add.u64 db, %69, %70;\n"
                 "wgmma.mma_async.sync.aligned.m64n128k16.f32.bf16.bf16 "
                 "{%0,%1,%2,%3,%4,%5,%6,%7,%8,%9,%10,%11,%12,%13,%14,%15,%16,%17,%18,%19,%20,%21,%22,%23,%24,%25,%26,%27,%28,%29,%30,%31,%32,%33,%34,%35,%36,%37,%38,%39,%40,%41,%42,%43,%44,%45,%46,%47,%48,%49,%50,%51,%52,%53,%54,%55,%56,%57,%58,%59,%60,%61,%62,%63}, "
                 "{%64,%65,%66,%67}, db, p, 1, 1, %71; }\n"
                 : ACC32(d, 0), ACC32(d, 32)
                 : "r"(a0), "r"(a1), "r"(a2), "r"(a3), "r"(sd), "l"(base), "n"(D), "n"(TB));
}
template <uint64_t DA, uint64_t DB>
__device__ __forceinline__ void mma_ss56_tt(float* d, int sd, uint64_t ba, uint64_t bb) {
    asm volatile("{ .reg .pred p; .reg .b64 da, db; setp.ne.b32 p, %28, 0; add.u64 da, %29, %31; add.u64 db, %30, %32;\n"
                 "wgmma.mma_async.sync.aligned.m64n56k16.f32.bf16.bf16 "
                 "{%0,%1,%2,%3,%4,%5,%6,%7,%8,%9,%10,%11,%12,%13,%14,%15,%16,%17,%18,%19,%20,%21,%22,%23,%24,%25,%26,%27}, "
                 "da, db, p, 1, 1, 1, 1; }\n"
                 : ACC28(d)
                 : "r"(sd), "l"(ba), "l"(bb), "n"(DA), "n"(DB));
}
template <int... I> struct Seq {};
template <class F, int... I> __device__ __forceinline__ void static_for_impl(F&& f, Seq<I...>) { (f(std::integral_constant<int, I>{}), ...); }
#define FOR7(...) static_for_impl([&](auto T_) { constexpr int t = decltype(T_)::value; __VA_ARGS__; }, Seq<0, 1, 2, 3, 4, 5, 6>{})
#define FOR8(...) static_for_impl([&](auto T_) { constexpr int t = decltype(T_)::value; __VA_ARGS__; }, Seq<0, 1, 2, 3, 4, 5, 6, 7>{})
#define FOR14(...) static_for_impl([&](auto T_) { constexpr int t = decltype(T_)::value; __VA_ARGS__; }, Seq<0, 1, 2, 3, 4, 5, 6, 7, 8, 9, 10, 11, 12, 13>{})

__device__ __forceinline__ int kblk(int p, int b) { return b == 0 ? p : b - (b <= p); }
__host__ __device__ constexpr int krow(int t) { return t < 3 ? 16 * t : (t < 6 ? 56 + 16 * (t - 3) : 48); }
#define AQ(A, b, t) ((t) < 3 ? A[2 * (b)][4 * (t)] : (t) < 6 ? A[2 * (b) + 1][4 * ((t) - 3)] : A[2 * (b)][12]), \
                    ((t) < 3 ? A[2 * (b)][4 * (t) + 1] : (t) < 6 ? A[2 * (b) + 1][4 * ((t) - 3) + 1] : A[2 * (b)][13]), \
                    ((t) < 3 ? A[2 * (b)][4 * (t) + 2] : (t) < 6 ? A[2 * (b) + 1][4 * ((t) - 3) + 2] : A[2 * (b) + 1][12]), \
                    ((t) < 3 ? A[2 * (b)][4 * (t) + 3] : (t) < 6 ? A[2 * (b) + 1][4 * ((t) - 3) + 3] : A[2 * (b) + 1][13])
#define D128(off, t) ((uint64_t)(((off) + krow(t) * 128) >> 4) + ((uint64_t)((t) == 6 ? (7168 - 1024) >> 4 : 0) << 32))
#define D64(off, t) ((uint64_t)(((off) + krow(t) * 64) >> 4) + ((uint64_t)((t) == 6 ? (3584 - 512) >> 4 : 0) << 32))

#define PL(k) (((k) - 3) * PLANE)
__device__ __forceinline__ void st_word(uint32_t* p, uint32_t v) { asm volatile("st.relaxed.gpu.global.u32 [%0], %1;" ::"l"(p), "r"(v) : "memory"); }
__device__ __forceinline__ uint32_t ld_word(const uint32_t* p) { uint32_t v; asm volatile("ld.relaxed.gpu.global.u32 %0, [%1];" : "=r"(v) : "l"(p) : "memory"); return v; }
__device__ __forceinline__ void tag_slice(uint32_t* w, uint32_t tag) { w[0] = settag(w[0], tag); w[4] = settag(w[4], tag); w[8] = settag(w[8], tag); w[12] = settag(w[12], tag); }
template <int O>
__device__ __forceinline__ void send_slice(uint4* dst, int lane, const uint32_t* w) {
    st_pkt<O>(dst, w[0], w[1], w[2], w[3]);
    st_pkt<O + 32>(dst, w[4], w[5], w[6], w[7]);
    st_pkt<O + 64>(dst, w[8], w[9], w[10], w[11]);
    asm volatile("{ .reg .b64 t; mov.b64 t, {%1,%2}; st.relaxed.gpu.global.b64 [%0+%3], t; }" ::"l"((char*)dst - lane * 8), "r"(w[12]), "r"(w[13]), "n"(16 * (O + 96)) : "memory");
}
#define RW4(v, o) "+r"(v[o]), "+r"(v[(o) + 1]), "+r"(v[(o) + 2]), "+r"(v[(o) + 3])
#define RW2(v, o) "+r"(v[o]), "+r"(v[(o) + 1])
#define WR4(v, o) "=&r"(v[o]), "=&r"(v[(o) + 1]), "=&r"(v[(o) + 2]), "=&r"(v[(o) + 3])
#define LDP(a, b, c, d, addr, off) "ld.relaxed.gpu.global.b128 q, [" addr "+" off "];\n mov.b128 {" a "," b "," c "," d "}, q;\n"
#define LDH(a, b, addr, off) "ld.relaxed.gpu.global.b64 h, [" addr "+" off "];\n mov.b64 {" a "," b "}, h;\n"
#define VOTE_OK "and.b32 t, t, 1;\n setp.ne.u32 p, t, 0;\n vote.sync.any.pred p, p, 0xffffffff;\n @!p bra.uni DN;\n"
#define CHK(x, tag) "lop3.b32 t, " x ", " tag ", t, 0xBE;\n"
__device__ __forceinline__ void check_cnt(uint32_t v, const uint32_t* p, uint32_t target) {
    asm volatile("{ .reg .pred p; .reg .b32 n, t; mov.u32 n, 0; mov.u32 t, %2;\n LP:\n"
                 "sub.s32 t, t, %1;\n setp.lt.s32 p, t, 0;\n vote.sync.any.pred p, p, 0xffffffff;\n @!p bra.uni DN;\n ld.relaxed.gpu.global.u32 t, [%0];\n" SPIN_TAIL("7")
                 ::"l"(p), "r"(target), "r"(v) : "memory");
}
__device__ __forceinline__ void poll_cnt(const uint32_t* p, uint32_t target) {
    asm volatile("{ .reg .pred p; .reg .b32 n, t; mov.u32 n, 0;\n LP:\n"
                 "ld.relaxed.gpu.global.u32 t, [%0];\n sub.s32 t, t, %1;\n setp.lt.s32 p, t, 0;\n vote.sync.any.pred p, p, 0xffffffff;\n @!p bra.uni DN;\n" SPIN_TAIL("1")
                 ::"l"(p), "r"(target) : "memory");
}
template <int STR>
__device__ __forceinline__ void poll4_kv(uint32_t* v, const uint4* p, uint32_t tag) {
    asm volatile("{ .reg .pred p; .reg .b32 n, t; .reg .b128 q; mov.u32 n, 0;\n LP:\n"
                 LDP("%0", "%1", "%2", "%3", "%16", "0") LDP("%4", "%5", "%6", "%7", "%16", "%18")
                 LDP("%8", "%9", "%10", "%11", "%16", "%19") LDP("%12", "%13", "%14", "%15", "%16", "%20")
                 "xor.b32 t, %0, %17;\n" CHK("%4", "%17") CHK("%8", "%17") CHK("%12", "%17") VOTE_OK SPIN_TAIL("2")
                 : WR4(v, 0), WR4(v, 4), WR4(v, 8), WR4(v, 12)
                 : "l"(p), "r"(tag), "n"(16 * STR), "n"(32 * STR), "n"(48 * STR)
                 : "memory");
}
template <int B>
__device__ __forceinline__ void blk_load(uint32_t (&A)[8][14], const uint4* src, int lane) {
    ld_pkt<0>(&A[2 * B][0], src); ld_pkt<32>(&A[2 * B][4], src); ld_pkt<64>(&A[2 * B][8], src);
    ld_pkt<512>(&A[2 * B + 1][0], src); ld_pkt<544>(&A[2 * B + 1][4], src); ld_pkt<576>(&A[2 * B + 1][8], src);
    asm volatile("{ .reg .b64 h;\n" LDH("%0", "%1", "%4", "1536") LDH("%2", "%3", "%4", "9728") "}"
                 : "=&r"(A[2 * B][12]), "=&r"(A[2 * B][13]), "=&r"(A[2 * B + 1][12]), "=&r"(A[2 * B + 1][13])
                 : "l"((const char*)src - lane * 8) : "memory");
}
template <int B>
__device__ __forceinline__ void blk_check(uint32_t (&A)[8][14], const uint4* src, int lane, uint32_t tag) {
    asm volatile("{ .reg .pred p; .reg .b32 n, t; .reg .b128 q; .reg .b64 h, a8; mov.u32 n, 0;\n LP:\n"
                 "xor.b32 t, %0, %30;\n" CHK("%4", "%30") CHK("%8", "%30") CHK("%12", "%30") CHK("%16", "%30") CHK("%20", "%30") CHK("%24", "%30") CHK("%26", "%30") VOTE_OK
                 LDP("%0", "%1", "%2", "%3", "%28", "0") LDP("%4", "%5", "%6", "%7", "%28", "512") LDP("%8", "%9", "%10", "%11", "%28", "1024")
                 LDP("%12", "%13", "%14", "%15", "%28", "8192") LDP("%16", "%17", "%18", "%19", "%28", "8704") LDP("%20", "%21", "%22", "%23", "%28", "9216")
                 "mad.wide.s32 a8, %29, -8, %28;\n" LDH("%24", "%25", "a8", "1536") LDH("%26", "%27", "a8", "9728") SPIN_TAIL("3")
                 "\n and.b32 %0, %0, -2; and.b32 %4, %4, -2; and.b32 %8, %8, -2; and.b32 %12, %12, -2; and.b32 %16, %16, -2; and.b32 %20, %20, -2; and.b32 %24, %24, -2; and.b32 %26, %26, -2;"
                 : RW4(A[2 * B], 0), RW4(A[2 * B], 4), RW4(A[2 * B], 8), RW4(A[2 * B + 1], 0), RW4(A[2 * B + 1], 4), RW4(A[2 * B + 1], 8),
                   RW2(A[2 * B], 12), RW2(A[2 * B + 1], 12)
                 : "l"(src), "r"(lane), "r"(tag)
                 : "memory");
}
__device__ __forceinline__ void st_async4(uint32_t a, uint32_t x, uint32_t y, uint32_t z, uint32_t w, uint32_t bar) {
    asm volatile("st.async.weak.shared::cluster.mbarrier::complete_tx::bytes.v4.b32 [%0], {%1,%2,%3,%4}, [%5];" ::"r"(a), "r"(x), "r"(y), "r"(z), "r"(w), "r"(bar) : "memory");
}
__device__ __forceinline__ uint32_t mapa(uint32_t a, uint32_t cta) { uint32_t r; asm("mapa.shared::cluster.u32 %0, %1, %2;" : "=r"(r) : "r"(a), "r"(cta)); return r; }
__device__ __forceinline__ void stat_load(uint32_t* v, const uint4* p) { ld_pkt<0>(v, p); ld_pkt<512>(v + 4, p); }
__device__ __forceinline__ void stat_check(uint32_t* v, const uint4* p, uint32_t tag) {
    asm volatile("{ .reg .pred p; .reg .b32 n, t; .reg .b128 q; mov.u32 n, 0;\n LP:\n"
                 "xor.b32 t, %3, %9;\n" CHK("%7", "%9") VOTE_OK
                 LDP("%0", "%1", "%2", "%3", "%8", "0") LDP("%4", "%5", "%6", "%7", "%8", "8192") SPIN_TAIL("4")
                 : RW4(v, 0), RW4(v, 4) : "l"(p), "r"(tag) : "memory");
}
__device__ __forceinline__ uint32_t x_bits(const uint32_t* X) {
    uint32_t r;
    asm volatile("{ .reg .b32 a, b; prmt.b32 a, %1, %2, 0x0040; prmt.b32 b, %3, %4, 0x0040; prmt.b32 %0, a, b, 0x5410; }" : "=r"(r) : "r"(X[0]), "r"(X[4]), "r"(X[8]), "r"(X[12]));
    return r;
}
template <int O>
__device__ __forceinline__ void slice_load(uint32_t* v, const uint4* p, int lane) {
    ld_pkt<O>(v, p); ld_pkt<O + 32>(v + 4, p); ld_pkt<O + 64>(v + 8, p);
    asm volatile("{ .reg .b64 h;\n" LDH("%0", "%1", "%2", "%3") "}" : "=r"(v[12]), "=r"(v[13]) : "l"((const char*)p - lane * 8), "n"(16 * (O + 96)) : "memory");
}
template <int O>
__device__ __forceinline__ void slice_check(uint32_t* v, const uint4* p, int lane, uint32_t tag) {
    asm volatile("{ .reg .pred p; .reg .b32 n, t; .reg .b128 q; .reg .b64 h; mov.u32 n, 0;\n LP:\n"
                 "xor.b32 t, %0, %16;\n" CHK("%4", "%16") CHK("%8", "%16") CHK("%12", "%16") VOTE_OK
                 LDP("%0", "%1", "%2", "%3", "%14", "%17") LDP("%4", "%5", "%6", "%7", "%14", "%18") LDP("%8", "%9", "%10", "%11", "%14", "%19")
                 LDH("%12", "%13", "%15", "%20") SPIN_TAIL("5")
                 : RW4(v, 0), RW4(v, 4), RW4(v, 8), RW2(v, 12)
                 : "l"(p), "l"((const char*)p - lane * 8), "r"(tag), "n"(16 * O), "n"(16 * (O + 32)), "n"(16 * (O + 64)), "n"(16 * (O + 96))
                 : "memory");
}
__device__ __forceinline__ void x_fix(uint32_t* X, uint32_t bits) {
    X[0] = __byte_perm(X[0], bits, 0x3214); X[4] = __byte_perm(X[4], bits, 0x3215); X[8] = __byte_perm(X[8], bits, 0x3216); X[12] = __byte_perm(X[12], bits, 0x3217);
}
__device__ __forceinline__ void sts4(uint32_t a, uint32_t x, uint32_t y, uint32_t z, uint32_t w) {
    asm volatile("st.shared.v4.u32 [%0], {%1,%2,%3,%4};" ::"r"(a), "r"(x), "r"(y), "r"(z), "r"(w) : "memory");
}
__device__ __forceinline__ void lds4(uint32_t* v, uint32_t a) {
    asm volatile("ld.shared.v4.u32 {%0,%1,%2,%3}, [%4];" : "=r"(v[0]), "=r"(v[1]), "=r"(v[2]), "=r"(v[3]) : "r"(a) : "memory");
}
struct LnCoef { uint32_t hi, lo, sh; };
__device__ __forceinline__ LnCoef ln_coef(float sum, float sq) {
    sum += __shfl_xor_sync(0xffffffffu, sum, 1); sq += __shfl_xor_sync(0xffffffffu, sq, 1);
    sum += __shfl_xor_sync(0xffffffffu, sum, 2); sq += __shfl_xor_sync(0xffffffffu, sq, 2);
    const float mean = sum * (1.f / 448.f);
    const float var = fmaxf(fmaf(-mean, mean, sq * (1.f / 448.f)), 0.f);
    const float sc = rsqrtf(var + 1e-5f);
    LnCoef r;
    r.hi = pack2(sc, sc);
    const float lo = sc - bf_lo(r.hi), sh = -mean * sc;
    r.lo = pack2(lo, lo);
    r.sh = pack2(sh, sh);
    return r;
}
template <int B>
__device__ __forceinline__ void normalize(uint32_t (&A)[8][14], const LnCoef& c0, const LnCoef& c1) {
#pragma unroll
    for (int s = 2 * B; s < 2 * B + 2; s++)
#pragma unroll
        for (int i = 0; i < 14; i++) {
            const LnCoef& k = (i & 1) ? c1 : c0;
            asm("{ .reg .b32 t; fma.rn.bf16x2 t, %0, %2, %3; fma.rn.bf16x2 %0, %0, %1, t; }" : "+r"(A[s][i]) : "r"(k.hi), "r"(k.lo), "r"(k.sh));
        }
}
__device__ __forceinline__ void slice_stats(const uint32_t* w, float* st) {
    float a = 0.f, b = 0.f, p = 0.f, q = 0.f;
#pragma unroll
    for (int i = 0; i < 7; i++) {
        const float e0 = bf_lo(w[2 * i]), e1 = bf_hi(w[2 * i]), e2 = bf_lo(w[2 * i + 1]), e3 = bf_hi(w[2 * i + 1]);
        a += e0 + e1; b += e2 + e3;
        p = fmaf(e0, e0, p); p = fmaf(e1, e1, p); q = fmaf(e2, e2, q); q = fmaf(e3, e3, q);
    }
    a += __shfl_xor_sync(0xffffffffu, a, 1); p += __shfl_xor_sync(0xffffffffu, p, 1); b += __shfl_xor_sync(0xffffffffu, b, 1); q += __shfl_xor_sync(0xffffffffu, q, 1);
    a += __shfl_xor_sync(0xffffffffu, a, 2); p += __shfl_xor_sync(0xffffffffu, p, 2); b += __shfl_xor_sync(0xffffffffu, b, 2); q += __shfl_xor_sync(0xffffffffu, q, 2);
    st[0] = a; st[1] = p; st[2] = b; st[3] = q;
}
__device__ __forceinline__ void dual_softmax(const float* p, uint32_t* out) {
    constexpr float L = 1.4426950408889634f;
#pragma unroll
    for (int r = 0; r < 2; r++) {
        float mx = fmaxf(p[2 * r], p[2 * r + 1]), mn = fminf(p[2 * r], p[2 * r + 1]);
#pragma unroll
        for (int i = 1; i < 7; i++) {
            mx = fmaxf(mx, fmaxf(p[4 * i + 2 * r], p[4 * i + 2 * r + 1]));
            mn = fminf(mn, fminf(p[4 * i + 2 * r], p[4 * i + 2 * r + 1]));
        }
        mx = fmaxf(mx, __shfl_xor_sync(0xffffffffu, mx, 1));
        mn = fminf(mn, __shfl_xor_sync(0xffffffffu, mn, 1));
        const float bx = -mx * L, bn = mn * L;
        float ep[14], en[14], sp = 0.f, sn = 0.f;
#pragma unroll
        for (int i = 0; i < 14; i++) {
            const float v = p[4 * (i >> 1) + 2 * r + (i & 1)];
            ep[i] = ex2(fmaf(v, L, bx));
            en[i] = ex2(fmaf(v, -L, bn));
            sp += ep[i]; sn += en[i];
        }
        sp += __shfl_xor_sync(0xffffffffu, sp, 1);
        sn += __shfl_xor_sync(0xffffffffu, sn, 1);
        const float ip = rcp(sp), in = rcp(sn);
#pragma unroll
        for (int i = 0; i < 7; i++) {
            out[4 * i + r] = pack2(ep[2 * i] * ip, ep[2 * i + 1] * ip);
            out[4 * i + 2 + r] = pack2(en[2 * i] * in, en[2 * i + 1] * in);
        }
    }
}
__device__ __forceinline__ float geglu(float g, float u) {
    const float t = tanh_hw(g * fmaf(g * g, 0.7978845608028654f * 0.044715f, 0.7978845608028654f));
    const float gu = g * u;
    return fmaf(t, gu, gu);
}
__device__ __forceinline__ void phi_gemm(const float* t, float* p) {
    uint32_t w[14];
#pragma unroll
    for (int i = 0; i < 14; i++) w[i] = pack2(t[2 * i], t[2 * i + 1]);
    const uint64_t db = BASE128(OFF_WPHI, 16, 0);
    wg_fence();
    mma_rs56<0, 0>(p, w[0], w[1], w[2], w[3], 0, db);
    mma_rs56<0, 2>(p, w[4], w[5], w[6], w[7], 1, db);
    mma_rs56<0, 4>(p, w[8], w[9], w[10], w[11], 1, db);
    mma_rs56<0, 6>(p, w[12], w[13], 0u, 0u, 1, db);
    wg_commit();
    wg_wait<0>();
}

}

#define BAR(i) (bars + 8 * (i))
#define R_WAIT() mbar_wait(BAR(slot), ph)
#define WSUM(i)
#define R_ADJ (slot * (STAGE >> 4))
#define R_NEXT() do { eb2 = eb1; eb1 = BAR(B_EMPTY + slot); if (++slot == NST) { slot = 0; ph ^= 1; } } while (0)
#define R_RELEASE(k) do { if (lane == 0) mbar_arrive((k) == 1 ? eb1 : eb2); } while (0)
#define PUSH_BEGIN() do { mbar_wait(BAR(B_ACK + wgi), ackph); ackph ^= 1; } while (0)
#define PUSH_ACK() do { __syncwarp(); if (lane == 0) asm volatile("mbarrier.arrive.shared::cluster.b64 _, [%0];" ::"r"(mapa(BAR(B_ACK + wgi), hr ^ 1)) : "memory"); } while (0)

__global__ void __cluster_dims__(2, 1, 1) __launch_bounds__(384, 1)
fused_kernel(Scratch* const sc, const __nv_bfloat16* __restrict__ x_in, const __nv_bfloat16* __restrict__ w_phi, const int trips,
             const __nv_bfloat16* __restrict__ wg, const __nv_bfloat16* __restrict__ wu, const __nv_bfloat16* __restrict__ wd,
             const __grid_constant__ Maps maps) {
    extern __shared__ __align__(1024) unsigned char smem_raw[];
    const uint32_t sb = s2u(smem_raw);
    const uint32_t bars = sb + OFF_BAR;
    const int wgi = __shfl_sync(0xffffffffu, threadIdx.x >> 7, 0);
    const int hr = blockIdx.x & 1, ck = blockIdx.x >> 1;
    const int gp = (ck - 4) & 7, q7 = ((ck - 36) * 37) >> 8;
    const int pr = __shfl_sync(0xffffffffu, ck < 4 ? ck : (ck < 36 ? (ck - 4) >> 3 : q7), 0);
    const int tile = __shfl_sync(0xffffffffu, ck < 4 ? 0 : (ck < 36 ? (gp ? 2 * gp : 1) : 2 * (ck - 36 - 7 * q7) + 3), 0);
    const int sl = 2 * pr + hr;
    STAMP(0);
    GSTAMP(60);
    if (threadIdx.x == 256) {
#pragma unroll
        for (int i = 0; i < NST; i++) mbar_init(BAR(i), 1);
        asm volatile("fence.mbarrier_init.release.cluster;" ::: "memory");
    }
    if (threadIdx.x == 288) {
        if ((sb & 0x3FFFF) != SB0) asm volatile("trap;");
#pragma unroll
        for (int i = NST; i < B_COUNT; i++) mbar_init(BAR(i), i >= B_ACK ? 4 : (i < B_RECV || i == B_LATE ? 8 : 1));
        asm volatile("fence.mbarrier_init.release.cluster;" ::: "memory");
    }
    __syncwarp();
    asm volatile("barrier.cluster.arrive.relaxed.aligned;" ::: "memory");

    if (wgi == 2) {
        asm volatile("setmaxnreg.dec.sync.aligned.u32 40;");
        const int t128 = fresh_tid() & 127, w = __shfl_sync(0xffffffffu, t128 >> 5, 0), lane = t128 & 31;
        uint32_t e0[2] = {0, 0}, e1[2] = {0, 0}, cw_target = 0;
        if (w == 0) {
#pragma unroll 1
            for (int n = 0; n < NST; n++) {
                const uint32_t dst = sb + n * STAGE, fb = BAR(n);
                asm volatile(ELECT "mbarrier.arrive.expect_tx.shared::cta.b64 _, [%0], %1; }" ::"r"(fb), "r"(n < 2 ? 2 * STAGE : STAGE) : "memory");
                if (n < 2) {
                    tma3x(sb + OFF_H + n * STAGE, &maps.x, tile * 128 + n * 64, fb);
                    tma3x(dst, &maps.x, tile * 128 + n * 64 + 32, fb);
                } else {
                    if (n == 3) mbar_wait(BAR(1), 0);
                    const int ra = 112 * (n - 2);
                    tma2d(dst, &maps.qkv, 448 + 56 * sl, ra, fb);
                    tma2d(dst + HALF, &maps.qkv, 896 + 56 * sl, ra, fb);
                }
            }
            asm volatile("barrier.cluster.wait.aligned;" ::: "memory");
            cw_target = (ld_word(g_cw + sl * 32) & ~15u) + 16;
#pragma unroll 1
            for (int k = 0; k < 2; k++) {
                const int n = t128 + 32 * k;
                int m = n - 2 - (n > PACK);
                const bool packed = m >= 30 ? (m < 38 || m >= 52) : m >= 22;
                if (m >= 30) m -= 30;
                if (n == PACK) m = tile < 8 ? tile : tile + 14;
                const int rot = n < 8 ? 0 : pr;
                const int ra = 112 * kblk(rot, m & 3), rb = 112 * kblk(rot, 2 * m & 3), rc = 112 * kblk(rot, (2 * m + 1) & 3);
                int kind = 0, m0, m1, c0, c1, r0, r1;
                if (m < 4) { m0 = m1 = 1; c0 = 448 + 56 * sl; c1 = c0 + 448; r0 = r1 = ra; }
                else if (m < 8) { m0 = m1 = m < 6 ? 1 : 2; c0 = c1 = 56 * sl; r0 = rb; r1 = rc; }
                else if (m < 20) { m0 = 3; m1 = 4; c0 = c1 = 224 * sl + 32 * hr + 64 * ((m - 8) >> 2); r0 = r1 = ra; }
                else if (m < 22) { kind = 2; m0 = 5; m1 = 6; c0 = c1 = 224 * sl + (hr ? 0 : 192); r0 = rb; r1 = rc; }
                else { m0 = m1 = 7; c0 = c1 = 56 * (2 * ((pr + (m >> 1) - 10) & 3) + hr); r0 = 224 * (sl ^ (m & 1)); r1 = r0 + 112; }
                if (packed) { kind = 1; r0 = sl * 16 + (m < 8 ? m : m - 14); r1 = 0; }
                e0[0] = e0[1]; e1[0] = e1[1];
                e0[1] = kind | (m0 << 2) | (m1 << 6) | (c0 << 10) | (c1 << 21);
                e1[1] = r0 | (r1 << 16);
            }
        } else {
            const int j = t128 - 32;
            asm volatile("barrier.cluster.wait.aligned;" ::: "memory");
            uint2 wv[7];
            const int k = j < 56 ? j : 55, hh = k >= 28;
#pragma unroll
            for (int i = 0; i < 7; i++) wv[i] = __ldg(reinterpret_cast<const uint2*>(w_phi + (sl * 56 + k) * 28) + i);
#pragma unroll 1
            for (int i = j; i < 7168 / 16; i += 96) sts4(sb + OFF_WPHI + i * 16, 0, 0, 0, 0);
            bar_sync(5, 96);
            if (j < 56) {
                uint32_t a4[4];
#pragma unroll
                for (int q = 0; q < 4; q++) a4[q] = sb + OFF_WPHI + (4 * hh + q) * 128 + ((((k >> 3) ^ (4 * hh + q)) & 7) << 4) + (k & 7) * 2;
                FOR14(const uint32_t v = (t & 1) ? wv[t >> 1].y : wv[t >> 1].x;
                      asm volatile("{ .reg .b16 l, h; mov.b32 {l, h}, %2; st.shared.u16 [%0+%3], l; st.shared.u16 [%1+%3], h; }"
                                   ::"r"(a4[t >= 7 ? 2 : 0]), "r"(a4[t >= 7 ? 3 : 1]), "r"(v), "n"((t % 7) * 1024) : "memory"));
            }
            __syncwarp();
            fence_async();
            bar_arrive(1, 224);
            bar_arrive(9, 224);
            if (w == 1) {
                mbar_wait(BAR(2), 0);
                mbar_wait(BAR(2), 1);
                const int b = blockIdx.x;
                asm volatile(ELECT "cp.async.bulk.prefetch.L2.global [%0], %1; }" ::"l"(wg + b * 6272), "r"(12544) : "memory");
                asm volatile(ELECT "cp.async.bulk.prefetch.L2.global [%0], %1; }" ::"l"(wu + b * 6272), "r"(12544) : "memory");
                asm volatile(ELECT "cp.async.bulk.prefetch.L2.global [%0], %1; }" ::"l"(wd + b * 6272), "r"(12544) : "memory");
            }
        }
        uint32_t kseq = ld_word(g_c1 + (sl * 8 * 16 + tile) * 32);
        int slot = 0, ph = 0, n = NST;
#pragma unroll 1
        for (int layer = 0; layer < 3; layer++) {
            if (w == 0) {
                const int nend = layer == 0 ? 11 : (layer == 1 ? 42 : 63);
#pragma unroll 1
                for (; n < nend; n++) {
                const uint32_t w0 = __shfl_sync(0xffffffffu, n < 32 ? e0[0] : e0[1], n & 31), w1 = __shfl_sync(0xffffffffu, n < 32 ? e1[0] : e1[1], n & 31);
                const uint32_t dst = sb + slot * STAGE, fb = BAR(n == PACK ? B_PACK : slot);
                const CUtensorMap* m0 = &maps.x + ((w0 >> 2) & 15);
                const CUtensorMap* m1 = &maps.x + ((w0 >> 6) & 15);
                const int c0 = (w0 >> 10) & 2047, c1 = w0 >> 21, r0 = w1 & 0xffff, r1 = w1 >> 16;
                if (n == 25) {
                    int it = 0;
                    uint32_t v;
                    do { asm volatile("ld.acquire.gpu.global.u32 %0, [%1];" : "=r"(v) : "l"(g_cw + sl * 32) : "memory"); } while ((int)(v - cw_target) < 0 && ++it < 0x400000);
                    asm volatile("fence.proxy.async.global;" ::: "memory");
                    __syncwarp();
                }
                mbar_wait(BAR(B_EMPTY + slot), ph);
                __syncwarp();
                asm volatile(ELECT "mbarrier.arrive.expect_tx.shared::cta.b64 _, [%0], %1; }" ::"r"(fb), "r"(STAGE) : "memory");
                if ((w0 & 3) == 0) {
                    tma2d(dst, m0, c0, r0, fb);
                    tma2d(dst + HALF, m1, c1, r1, fb);
                } else if (w0 & 1) {
                    asm volatile(ELECT "cp.async.bulk.shared::cluster.global.mbarrier::complete_tx::bytes [%0], [%1], %2, [%3]; }"
                                 ::"r"(dst), "l"(reinterpret_cast<const char*>(g_wp) + (size_t)r0 * STAGE), "r"(STAGE), "r"(fb) : "memory");
                } else {
                    tma2d(dst, m0, c0, r0, fb); tma2d(dst + 7168, m0, c0, r1, fb);
                    tma2d(dst + HALF, m1, c0, r0, fb); tma2d(dst + HALF + 7168, m1, c0, r1, fb);
                }
                if (n == PACK) asm volatile(ELECT "mbarrier.arrive.shared::cta.b64 _, [%0]; }" ::"r"(BAR(slot)) : "memory");
                if (++slot == NST) { slot = 0; ph ^= 1; }
                }
            } else if (w == 1 && layer == 1) {
                constexpr int ps = PACK % NST;
                mbar_wait(BAR(B_PACK), 0);
                asm volatile("{ .reg .pred e; elect.sync _|e, 0xffffffff;\n"
                             "@e cp.async.bulk.global.shared::cta.bulk_group [%0], [%1], %2;\n"
                             "@e cp.async.bulk.commit_group;\n"
                             "@e cp.async.bulk.wait_group.read 0;\n"
                             "@e mbarrier.arrive.shared::cta.b64 _, [%3], 8;\n"
                             "@e cp.async.bulk.wait_group 0;\n"
                             "@e fence.proxy.async.global;\n"
                             "@e red.release.gpu.global.add.u32 [%4], 1; }"
                             ::"l"(reinterpret_cast<char*>(g_wp) + (size_t)(sl * 16 + tile) * STAGE), "r"(sb + ps * STAGE), "r"(STAGE), "r"(BAR(B_EMPTY + ps)), "l"(g_cw + sl * 32) : "memory");
                __syncwarp();
            }
            if (layer < 2) {
            const uint32_t tag = layer ^ 1;
            kseq++;
            bar_sync(7, 384);
            ASTAMP(0);
            if (tile < 15) {
                const int sq = lane >> 3, pk = 8 * w + (lane & (tile == 14 ? 3 : 7));
                uint32_t v[16];
                if (layer == 0) poll_cnt(g_c1 + ((sl * 8 + (w >> 1) * 4 + (tile >> 2)) * 16 + (lane & 15)) * 32, kseq);
                ASTAMP(1);
                poll4_kv<32>(v, g_kv1 + ((sl * 16 + tile) * 16 + 4 * sq) * 32 + pk, tag);
#pragma unroll
                for (int k = 0; k < 4; k++) {
                    float lo = (bf_lo(v[k]) + bf_lo(v[4 + k])) + (bf_lo(v[8 + k]) + bf_lo(v[12 + k]));
                    float hi = (bf_hi(v[k]) + bf_hi(v[4 + k])) + (bf_hi(v[8 + k]) + bf_hi(v[12 + k]));
                    lo += __shfl_xor_sync(0xffffffffu, lo, 8); hi += __shfl_xor_sync(0xffffffffu, hi, 8);
                    lo += __shfl_xor_sync(0xffffffffu, lo, 16); hi += __shfl_xor_sync(0xffffffffu, hi, 16);
                    v[k] = pack2(lo, hi);
                }
                if (sq == 0) st_pkt<0>(g_kv2 + sl * 512 + 32 * tile + pk, settag(v[0], tag), v[1], v[2], v[3]);
            }
            ASTAMP(2);
            {
                const int item = t128 < 112 ? t128 : 112 + (t128 & 3), d = item >> 1;
                const int cc = t128 < 112 ? 2 * (d >= 28) + (item & 1) : item - 112;
                const int r = t128 < 112 ? d : 56 + (cc >> 1) + 2 * ((t128 - 112) >> 2);
                uint32_t ra = sb + OFF_KVB + r * 128 + 4 * cc, rx = (r & 7) << 4;
                asm volatile("" : "+r"(ra), "+r"(rx));
                FOR14(asm volatile("st.shared.u32 [%0+%2], %1;" ::"r"((ra ^ 8) + (((t & 7) << 4) ^ rx)), "r"(0), "n"((t >> 3) * 8192) : "memory"));
                uint32_t v[16];
                asm volatile("" : "+r"(ra), "+r"(rx));
                poll4_kv<8>(v, g_kv2 + sl * 512 + (item >> 3) * 32 + (item & 7), tag);
                FOR14(asm volatile("st.shared.u32 [%0+%2], %1;" ::"r"(ra + (((t & 7) << 4) ^ rx)), "r"(v[t < 7 ? t : t + 1]), "n"((t >> 3) * 8192) : "memory"));
                fence_async();
            }
            bar_arrive(3, 384);
            ASTAMP(3);
            }
        }
    } else {
        asm volatile("setmaxnreg.inc.sync.aligned.u32 232;");
        int lane = fresh_tid() & 31, prf = pr;
#define pr prf
#define g (lane >> 2)
#define c (lane & 3)
#define t128 (w * 32 + lane)
        const int wu = __shfl_sync(0xffffffffu, fresh_tid() >> 5, 0), w = wu & 3;
        const uint32_t xoff = __shfl_sync(0xffffffffu, (3 * PLANE + ((tile * 2 + wgi) * 8) * 512 + w * 128) * 16, 0);
        char* xu = reinterpret_cast<char*>(g_ex) + xoff;
#define FRESH() asm volatile("" : "+l"(xu), "+r"(lane), "+r"(prf))
#define xp0 (reinterpret_cast<uint4*>(xu) + lane)
        const uint32_t hbuf = sb + OFF_H + wgi * STAGE;
        uint32_t slot = 0, ph = 0, eb1 = 0, eb2 = 0, ackph = 0, rcvph = 0, gatph = 0, swp = 0;
        uint32_t ppid = 6;
#define cx(s) (reinterpret_cast<uint32_t*>(reinterpret_cast<uint4*>(xu) + PL(1) + 112 + (s) * 512))
#define stp (reinterpret_cast<uint4*>(xu) + g + PL(0) + 112)
        uint32_t seq = ld_word(cx(sl));
        uint32_t kseq = ld_word(g_c1 + ((sl * 8 + wu) * 16 + tile) * 32);
        uint32_t stag = ld_word(reinterpret_cast<const uint32_t*>(stp + sl * 512) + 3) & 1;
        asm volatile("barrier.cluster.wait.aligned;" ::: "memory");
        STAMP(1);
        uint32_t X[14];
        const uint32_t x0row = (w < 2 ? hbuf : sb + wgi * STAGE) + ((w & 1) * 16 + (lane & 15)) * 128;
        mbar_wait(BAR(wgi), 0);
        STAMP(51);
#pragma unroll
        for (int j = 0; j < 4; j++) {
            const int G = 7 * sl + min(2 * j + (lane >> 4), 6);
            uint32_t q2, q3;
            asm volatile("ldmatrix.sync.aligned.m8n8.x4.shared.b16 {%0,%1,%2,%3}, [%4];" : "=r"(X[4 * j]), "=r"(X[4 * j + 1]), "=r"(q2), "=r"(q3)
                         : "r"(x0row + (G >> 3) * 4096 + (((G ^ lane) & 7) << 4)) : "memory");
            if (j < 3) { X[(4 * j + 2) % 14] = q2; X[(4 * j + 3) % 14] = q3; }
        }
#define PUSH_SLICE(W)                                                                          \
    {                                                                                          \
        if (t128 == 0) mbar_expect_tx(BAR(B_RECV + wgi), 7168);                                \
        PUSH_BEGIN();                                                                          \
        const uint32_t ra = mapa(hbuf + 24576 + t128 * 16, hr ^ 1), rb = mapa(sb + OFF_XR + wgi * 3072, hr ^ 1), rbar = mapa(BAR(B_RECV + wgi), hr ^ 1); \
        st_async4(ra, W[0], W[1], W[2], W[3], rbar);                                           \
        st_async4(ra + 2048, W[4], W[5], W[6], W[7], rbar);                                    \
        st_async4(rb + t128 * 16, W[8], W[9], W[10], W[11], rbar);                             \
        asm volatile("st.async.weak.shared::cluster.mbarrier::complete_tx::bytes.v2.b32 [%0], {%1,%2}, [%3];" ::"r"(rb + 2048 + t128 * 8), "r"(W[12]), "r"(W[13]), "r"(rbar) : "memory"); \
    }
#define PULL_SLICE(W)                                                                          \
    {                                                                                          \
        uint32_t t0, t1;                                                                       \
        mbar_wait(BAR(B_RECV + wgi), rcvph);                                                   \
        rcvph ^= 1;                                                                            \
        lds4(&A[1][0], hbuf + 24576 + t128 * 16);                                              \
        lds4(&A[1][4], hbuf + 26624 + t128 * 16);                                              \
        lds4(&A[1][8], sb + OFF_XR + wgi * 3072 + t128 * 16);                                  \
        asm volatile("ld.shared.v2.u32 {%0,%1}, [%2];" : "=r"(t0), "=r"(t1) : "r"(sb + OFF_XR + wgi * 3072 + 2048 + t128 * 8) : "memory"); \
        _Pragma("unroll") for (int i = 0; i < 12; i++) A[0][i] = (i & 3) ? W[i] : W[i] & ~1u;  \
        A[1][0] &= ~1u; A[1][4] &= ~1u; A[1][8] &= ~1u;                                        \
        A[0][12] = (hr ? t0 : W[12]) & ~1u; A[0][13] = hr ? t1 : W[13];                        \
        A[1][12] = (hr ? W[12] : t0) & ~1u; A[1][13] = hr ? W[13] : t1;                        \
        asm volatile("" : RW4(A[0], 0), RW4(A[0], 4), RW4(A[0], 8), RW2(A[0], 12), RW4(A[1], 0), RW4(A[1], 4), RW4(A[1], 8), RW2(A[1], 12)); \
        swp = hr * 448;                                                                        \
    }
#define SWB(b, t, db, sh) ((b) == 0 && (t) < 6 ? ((t) < 3 ? db##p : db##m) : db)
#define DECL_DB(b, MK, lbo, sh) const uint64_t db = MK(0, lbo, R_ADJ), dbp = (b) == 0 ? MK(0, lbo, R_ADJ + (swp >> (sh))) : db, dbm = (b) == 0 ? MK(0, lbo, R_ADJ - (swp >> (sh))) : db;
#define PPB 2
#define PP_WAIT() if (wgi == 1) { bar_sync(ppid, 256); ppid ^= 14; }
#define PP_GO() if (wgi == 0) { bar_arrive(ppid, 256); ppid ^= 14; }
#define GAT_DST(B, s2) ((B) == 1 ? hbuf + w * 3584 + (s2) * 1792 : ((s2) ? sb + OFF_KVB + wgi * 8192 : hbuf + 14336) + w * 1792)
#define GAT_ISSUE(B, base)                                                                     \
    {                                                                                          \
        const char* gs = xu + ((base) + kblk(pr, B) * 1024) * 16;                              \
        asm volatile("{ .reg .pred e; elect.sync _|e, 0xffffffff;\n"                           \
                     "@e mbarrier.arrive.expect_tx.shared::cta.b64 _, [%3], 3584;\n"           \
                     "@e cp.async.bulk.shared::cluster.global.mbarrier::complete_tx::bytes [%0], [%2], 1792, [%3];\n" \
                     "@e cp.async.bulk.shared::cluster.global.mbarrier::complete_tx::bytes [%1], [%2+8192], 1792, [%3]; }" \
                     ::"r"(GAT_DST(B, 0)), "r"(GAT_DST(B, 1)), "l"(gs), "r"(BAR(B_GAT + wu * 2 + ((B) >> 1))) : "memory"); \
        __syncwarp();                                                                          \
    }
#define GAT_FETCH(B)                                                                           \
    {                                                                                          \
        mbar_wait(BAR(B_GAT + wu * 2 + ((B) >> 1)), (gatph >> (B)) & 1);                          \
        gatph ^= 1 << (B);                                                                     \
        _Pragma("unroll") for (int s2 = 0; s2 < 2; s2++) {                                     \
            const uint32_t ga = GAT_DST(B, s2) + lane * 16;                                    \
            lds4(&A[2 * (B) + s2][0], ga); lds4(&A[2 * (B) + s2][4], ga + 512); lds4(&A[2 * (B) + s2][8], ga + 1024); \
            asm volatile("ld.shared.v2.u32 {%0,%1}, [%2];" : "=r"(A[2 * (B) + s2][12]), "=r"(A[2 * (B) + s2][13]) : "r"(ga - lane * 8 + 1536) : "memory"); \
        }                                                                                      \
    }
#define LATE_ARRIVE() do { if (lane == 0) mbar_arrive(BAR(B_LATE)); } while (0)
#define LATE_WAIT() do { mbar_wait(BAR(B_LATE), gatph & 1); gatph ^= 1; } while (0)
#define PT 3
#define PREP(b, t, remote)                                                                     \
    if constexpr ((b) < 3 && (t) == PT) {                                                      \
        wg_commit();                                                                           \
        if constexpr (PP0 && (b) == 0) { PP_GO() }                                             \
        STAMP(74 + 6 * (step & 1) + 2 * (b));                                                  \
        if (remote) {                                                                          \
            if constexpr ((b) == 0) { blk_load<2>(A, BLK(xsrc, 2), lane); GAT_FETCH(1) }       \
            blk_check<((b) + 1) & 3>(A, BLK(xsrc, (b) + 1), lane, xtag);                       \
            if constexpr ((b) == 0) blk_load<3>(A, BLK(xsrc, 3), lane);                        \
        }                                                                                      \
        STAMP(75 + 6 * (step & 1) + 2 * (b));                                                  \
        normalize<((b) + 1) & 3>(A, k0, k1);                                                   \
        asm volatile("" : RW4(A[(2 * (b) + 2) & 7], 0), RW4(A[(2 * (b) + 2) & 7], 4), RW4(A[(2 * (b) + 2) & 7], 8), RW2(A[(2 * (b) + 2) & 7], 12), \
                          RW4(A[(2 * (b) + 3) & 7], 0), RW4(A[(2 * (b) + 3) & 7], 4), RW4(A[(2 * (b) + 3) & 7], 8), RW2(A[(2 * (b) + 3) & 7], 12)); \
        wg_fence();                                                                            \
    }
#define X0_BLOCK(b)                                                                            \
    { const int rr = lane & 7, hi = lane >> 4;                                                 \
    const uint32_t rowa = (w < 2 ? hbuf : sb + wgi * STAGE) + ((w & 1) * 16 + (lane & 15)) * 128; \
    FOR7(constexpr int G = 14 * (b) + (t < 3 ? 2 * t : (t < 6 ? 2 * t + 1 : 6));               \
         uint32_t q0, q1, q2, q3;                                                              \
         const uint32_t ad = t < 6 ? rowa + (((((G & 7) + hi) ^ rr) & 7) << 4) + ((G & 7) == 7 ? hi * 4096 : 0) : rowa + ((G + 7 * hi) >> 3) * 4096 + ((((G + 7 * hi) ^ rr) & 7) << 4); \
         asm volatile("ldmatrix.sync.aligned.m8n8.x4.shared.b16 {%0,%1,%2,%3}, [%4+%5];" : "=r"(q0), "=r"(q1), "=r"(q2), "=r"(q3) \
                      : "r"(ad), "n"(t < 6 ? (G >> 3) * 4096 : 0) : "memory");                 \
         if (t < 3) { A[2 * (b)][4 * t] = q0; A[2 * (b)][4 * t + 1] = q1; A[2 * (b)][4 * t + 2] = q2; A[2 * (b)][4 * t + 3] = q3; } \
         else if (t < 6) { A[2 * (b) + 1][(4 * t - 12) & 15] = q0; A[2 * (b) + 1][((4 * t - 12) & 15) + 1] = q1; A[2 * (b) + 1][((4 * t - 12) & 15) + 2] = q2; A[2 * (b) + 1][((4 * t - 12) & 15) + 3] = q3; } \
         else { A[2 * (b)][12] = q0; A[2 * (b)][13] = q1; A[2 * (b) + 1][12] = q2; A[2 * (b) + 1][13] = q3; }); }
#define BLK(base, b) ((base) + kblk(pr, b) * 1024)

#pragma unroll 1
        for (int step = 0; step < 4; step++) {
            FRESH();
            const uint32_t tag = (step >> 1) ^ 1;
            const int so = (step >> 1) * 24 + (step & 1) * 12;
            (void)so;
            uint32_t A[8][14];
            uint4* const xsrc = xp0 + ((step & 1) ? PL(2) : PL(0));
            const uint32_t xtag = (step & 1) ? tag : ((seq >> 3) & 1) ^ 1;
            uint32_t xbits;
            {
                float st[4];
                slice_stats(X, st);
                stag ^= 1;
                xbits = x_bits(X);
                tag_slice(X, xtag);
                if (step) send_slice<0>(xsrc + sl * 512, lane, X);
                if (c == 0) st_pkt<0>(stp + sl * 512, __float_as_uint(st[0]), __float_as_uint(st[1]), __float_as_uint(st[2]), settag(__float_as_uint(st[3]), stag));
            }
            STAMP(2 + so);
            uint32_t sv[8];
            if (step == 0) {
                X0_BLOCK(0) X0_BLOCK(1) X0_BLOCK(2) X0_BLOCK(3)
                mbar_wait(BAR(wgi ^ 1), 0);
                R_NEXT();
                R_NEXT();
                R_RELEASE(2);
                stat_load(sv, stp + c * 1024);
                stat_check(sv, stp + c * 1024, stag);
                STAMP(52 + step);
            } else {
                kill<14>(A[2]); kill<14>(A[3]); kill<14>(A[4]); kill<14>(A[5]); kill<14>(A[6]); kill<14>(A[7]);
                PUSH_SLICE(X)
                stat_load(sv, stp + c * 1024);
                PULL_SLICE(X)
                stat_check(sv, stp + c * 1024, stag);
                STAMP(52 + step);
                GAT_ISSUE(1, (step & 1) ? PL(2) : PL(0))
            }
            LnCoef k0, k1;
            {
                k0 = ln_coef(__uint_as_float(sv[0]) + __uint_as_float(sv[4]), __uint_as_float(sv[1]) + __uint_as_float(sv[5]));
                k1 = ln_coef(__uint_as_float(sv[2]) + __uint_as_float(sv[6]), __uint_as_float(sv[3] & ~1u) + __uint_as_float(sv[7] & ~1u));
            }
            STAMP(3 + so);
            GSTAMP(70 + step);

            if ((step & 1) == 0) {
                float tq[28];
                {
                    float av[28];
#define KV_BLOCK(b)                                                                           \
    if ((b) == 1) R_RELEASE(2);                                                               \
    if ((b) == 2) { PUSH_ACK(); wg_wait<2>(); R_RELEASE(2); }                                 \
    R_WAIT();                                                                                 \
    if ((b) == PPK || (PP0 && (b) == 0)) { PP_WAIT() }                                        \
    { DECL_DB(b, BASE128, 16, 0)                                                              \
    wg_fence();                                                                               \
    FOR7(mma_rs56<1, D128(0, t)>(tq, AQ(A, b, t), (b) + t > 0, SWB(b, t, db, 0));             \
         mma_rs56<1, D128(HALF, t)>(av, AQ(A, b, t), (b) + t > 0, SWB(b, t, db, 0));          \
         PREP(b, t, step)); }                                                                 \
    wg_commit();                                                                              \
    if ((b) == 3 && PPK < 4) { PP_GO() }                                                      \
    R_NEXT();
                    normalize<0>(A, k0, k1);
                    KV_BLOCK(0) KV_BLOCK(1) KV_BLOCK(2) KV_BLOCK(3)
                    wg_wait<0>();
                    if (lane < 3) mbar_arrive(BAR(B_EMPTY + (slot + NST - 1 - lane) % NST));
                    STAMP(4 + so);
                    WSUM(80 + 7 * (step >> 1));
                    const int m = lane >> 3, rr = lane & 7;
                    const uint32_t rowa = hbuf + 16384 + (w * 16 + rr + 8 * (m & 1)) * 128;
                    const uint32_t one = c == 0 ? 0x00003f80u : 0u;
                    if (step == 0) { bar_sync(wgi ? 9 : 1, 224); }
#pragma unroll
                    for (int j = 0; j < 4; j++) {
                        const uint32_t a = rowa + (((2 * j + (m >> 1)) ^ rr) << 4);
                        if (j < 3) stsm4(a, pack2(av[8 * j], av[8 * j + 1]), pack2(av[8 * j + 2], av[8 * j + 3]), pack2(av[8 * j + 4], av[8 * j + 5]), pack2(av[8 * j + 6], av[8 * j + 7]));
                        else stsm4(a, pack2(av[24], av[25]), pack2(av[26], av[27]), one, one);
                    }
                }
                uint32_t PH[28];
                int it = 1;
#pragma unroll 1
                do {
                    float pp[28];
                    phi_gemm(tq, pp);
                    dual_softmax(pp, PH);
                    if (((trips >> (it + 1)) & 1) == 0) continue;
                    {
                        const int m = lane >> 3, rr = lane & 7;
                        const uint32_t rowa = hbuf + (w * 16 + rr + 8 * (m & 1)) * 128;
#pragma unroll
                        for (int j = 0; j < 7; j++) {
                            const int cg = 2 * j + (m >> 1), hi = cg >= 7;
                            stsm4(rowa + hi * 8192 + (((cg - 7 * hi) ^ rr) << 4), PH[4 * j], PH[4 * j + 1], PH[4 * j + 2], PH[4 * j + 3]);
                        }
                    }
                    fence_async();
                    STAMP(5 + so);
#define Q_STAGE(b0)                                                                           \
    R_WAIT();                                                                                 \
    { DECL_DB(b0, BASE128, 16, 0)                                                             \
    wg_fence();                                                                               \
    FOR7(mma_rs56<1, D128(0, t)>(tq, AQ(A, b0, t), (b0) + t > 0, SWB(b0, t, db, 0)));         \
    FOR7(mma_rs56<1, D128(HALF, t)>(tq, AQ(A, (b0) + 1, t), 1, db)); }                        \
    wg_commit();                                                                              \
    R_NEXT();
                    if (QE && wgi == 0) { kill<28>(tq); Q_STAGE(0) Q_STAGE(2) wg_wait<1>(); R_RELEASE(2); wg_wait<0>(); R_RELEASE(1); }
                    bar_sync(2, 256);
                    float kv[28];
                    const uint64_t da = BASE128(OFF_H + 16384, 16, 0), dbk = BASE128(OFF_H, 16, wgi * 512);
                    wg_fence();
                    FOR8(constexpr uint64_t o = ((t >> 2) * STAGE + (t & 3) * 2048) >> 4; mma_ss56_tt<o, o>(kv, t > 0, da, dbk));
                    wg_commit();
                    wg_wait<0>();
#pragma unroll
                    for (int hf = 0; hf < 2; hf++) {
                        const int d = 16 * w + g + 8 * hf;
                        if ((d < 56 && (d >= 28) == (c >= 2)) || d == 56) {
                            const int item = d < 56 ? 2 * d + (c & 1) : 112 + c;
                            uint4* dst = g_kv1 + ((sl * 16 + (item >> 3)) * 16 + tile) * 32 + wgi * 16 + (item & 7);
#define KVW(i) pack2(kv[4 * (i) + 2 * hf], kv[4 * (i) + 2 * hf + 1])
                            st_pkt<0>(dst, settag(KVW(0), tag), KVW(1), KVW(2), KVW(3));
                            st_pkt<8>(dst, settag(KVW(4), tag), KVW(5), KVW(6), 0u);
                        }
                    }
                    __syncwarp();
                    kseq++;
                    if (lane == 0) st_word(g_c1 + ((sl * 8 + wu) * 16 + tile) * 32, kseq);
                    bar_arrive(7, 384);
                    STAMP(6 + so);
                    if (!QE || wgi == 1) { kill<28>(tq); Q_STAGE(0) Q_STAGE(2) wg_wait<1>(); R_RELEASE(2); wg_wait<0>(); R_RELEASE(1); }
                    STAMP(7 + so);
                    kill<28>(PH);
                } while (((trips >> (++it)) & 1));
                STAMP(8 + so);
                FRESH();
                if (step) {
                    slice_load<PL(0)>(X, xp0 + sl * 512, lane);
                } else {
                    const uint32_t* xp = reinterpret_cast<const uint32_t*>(x_in + (size_t)(tile * 128 + wu * 16 + g) * 448 + 56 * sl + 2 * c);
#pragma unroll
                    for (int i = 0; i < 7; i++) { X[2 * i] = __ldg(xp + 4 * i); X[2 * i + 1] = __ldg(xp + 4 * i + 8 * 224); }
                }
                bar_sync(3, 384);
                STAMP(9 + so);
                const uint4* const osrc = xp0 + PL(1);
                {
                    float nm[32];
                    const uint64_t db = BASE128(OFF_KVB, 16, 0);
                    wg_fence();
                    FOR7(mma_rs64<0, ((t >> 2) * 8192 + (t & 3) * 32) / 16>(nm, PH[4 * t], PH[4 * t + 1], PH[4 * t + 2], PH[4 * t + 3], t > 0, db));
                    wg_commit();
                    wg_wait<0>();
                    LATE_ARRIVE();
                    const float i00 = rcp(nm[28] + 1e-6f), i01 = rcp(nm[29] + 1e-6f), i10 = rcp(nm[30] + 1e-6f), i11 = rcp(nm[31] + 1e-6f);
                    const float m0 = c >= 2 ? i01 : i00, m1 = c >= 2 ? i11 : i10;
                    uint32_t O[14];
#pragma unroll
                    for (int i = 0; i < 7; i++) {
                        const float f0 = i < 3 ? i00 : (i > 3 ? i01 : m0), f1 = i < 3 ? i10 : (i > 3 ? i11 : m1);
                        O[2 * i] = pack2(nm[4 * i] * f0, nm[4 * i + 1] * f0);
                        O[2 * i + 1] = pack2(nm[4 * i + 2] * f1, nm[4 * i + 3] * f1);
                    }
                    if (OST) { PP_WAIT() }
                    tag_slice(O, tag);
                    send_slice<PL(1)>(xp0 + sl * 512, lane, O);
                    seq++;
                    if (lane == 0) st_word(cx(sl), seq);
                    STAMP(10 + so);
                    PUSH_SLICE(O)
                    if (OST == 1) { PP_GO() }
                    const uint32_t cv = ld_word(cx(lane & 7));
                    PULL_SLICE(O)
                    LATE_WAIT();
                    check_cnt(cv, cx(lane & 7), seq);
                    if (OST == 2) { PP_GO() }
                    STAMP(56 + (step >> 1));
                    GAT_ISSUE(1, PL(1))
                    GAT_ISSUE(3, PL(1))
                    blk_load<2>(A, BLK(osrc, 2), lane);
                }
                float ao[28];
#define WO_BLOCK(b)                                                                           \
    if ((b) > 0) blk_check<b>(A, BLK(osrc, b), lane, tag);                                    \
    if (((b) & 1) == 0) R_WAIT();                                                             \
    { DECL_DB(b, BASE128, 16, 0)                                                              \
    wg_fence();                                                                               \
    FOR7(mma_rs56<1, D128(((b) & 1) * HALF, t)>(ao, AQ(A, b, t), (b) + t > 0, SWB(b, t, db, 0))); } \
    wg_commit();                                                                              \
    if ((b) & 1) R_NEXT();
                WO_BLOCK(0)
                STAMP(11 + so);
                GAT_FETCH(1)
                WO_BLOCK(1)
                WO_BLOCK(2)
                GAT_FETCH(3)
                WO_BLOCK(3)
                PUSH_ACK();
                wg_wait<0>();
                R_RELEASE(2);
                STAMP(12 + so);
                WSUM(86 + 7 * (step >> 1));
                x_fix(X, xbits);
#pragma unroll
                for (int i = 0; i < 14; i++) X[i] = pack2(bf_lo(X[i]) + ao[2 * i], bf_hi(X[i]) + ao[2 * i + 1]);
            } else {
                uint32_t H[56];
                float ag[64];
#define F1_EPI(dst, ng, ag)                                                                    \
    _Pragma("unroll") for (int i = 0; i < 2 * (ng); i++)                                       \
        (dst)[i] = pack2(geglu(ag[2 * i], ag[4 * (ng) + 2 * i]), geglu(ag[2 * i + 1], ag[4 * (ng) + 2 * i + 1]));
#define H_PUSH(h0, off) st_async4(rem_h + (off), H[h0], H[(h0) + 1], H[(h0) + 2], H[(h0) + 3], mapa(BAR(B_RECV2 + wgi), hr ^ 1));
#define F1_BLOCK(b, first)                                                                     \
    if ((first) && (b) == 1) R_RELEASE(2);                                                     \
    if ((first) && (b) == 2) PUSH_ACK();                                                       \
    R_WAIT();                                                                                  \
    if ((b) == ((first) ? PPF : PPB) || (PP0 && (first) && (b) == 0)) { PP_WAIT() }            \
    { DECL_DB(b, BASE128, HALF, 0)                                                             \
    wg_fence();                                                                                \
    FOR7(mma_rs128<1, D128(0, t)>(ag, AQ(A, b, t), (b) + t > 0, SWB(b, t, db, 0));             \
         if constexpr (first) { PREP(b, t, true) }); }                                         \
    wg_commit();                                                                               \
    if ((b) == 3) { PP_GO() }                                                                  \
    if ((b) > 0) { wg_wait<1>(); R_RELEASE(1); }       \
    R_NEXT();
                normalize<0>(A, k0, k1);
                F1_BLOCK(0, true) F1_BLOCK(1, true) F1_BLOCK(2, true) F1_BLOCK(3, true)
                if (t128 == 0) { mbar_expect_tx(BAR(B_RECV + wgi), 16384); mbar_expect_tx(BAR(B_RECV2 + wgi), 12288); }
                PUSH_BEGIN();
                wg_wait<0>();
                R_RELEASE(1);
                int p = 0;
#pragma unroll 1
                do {
                    F1_EPI(H + 32, 8, ag)
                    STAMP(4 + p + so);
                    WSUM(81 + p + 7 * (step >> 1));
                    if (((trips >> (p + 1)) & 1) == 0) continue;
                    {
                        const uint32_t pk = (p ? hbuf + 16384 : sb + OFF_KVB + wgi * 8192) + w * 2048;
#pragma unroll
                        for (int k = 0; k < 4; k++) sts4(pk + k * 512 + lane * 16, H[32 + 4 * k], H[33 + 4 * k], H[34 + 4 * k], H[35 + 4 * k]);
                        fence_async();
                        __syncwarp();
                        asm volatile(ELECT "cp.async.bulk.shared::cluster.shared::cta.mbarrier::complete_tx::bytes [%0], [%1], 2048, [%2]; }"
                                     ::"r"(mapa(hbuf + p * 8192 + w * 2048, hr ^ 1)), "r"(pk), "r"(mapa(BAR(B_RECV + wgi), hr ^ 1)) : "memory");
                    }
                    if (step == 1 && p == PKP) R_NEXT();
                    kill<64>(ag);
                    F1_BLOCK(0, false) F1_BLOCK(1, false) F1_BLOCK(2, false) F1_BLOCK(3, false)
                    wg_wait<0>();
                    R_RELEASE(1);
                    kill<16>(H + 32);
                } while (((trips >> (++p)) & 1));
#pragma unroll
                for (int k = 0; k < 4; k++) lds4(H + 16 + 4 * k, hbuf + 16384 + w * 2048 + k * 512 + lane * 16);
                __syncwarp();
                if (lane == 0) asm volatile("mbarrier.arrive.shared::cluster.b64 _, [%0];" ::"r"(mapa(BAR(B_ACK2 + wgi), hr ^ 1)) : "memory");
                const uint32_t rem_h = mapa(hbuf + w * 2048 + lane * 16, hr ^ 1);
#define F1_LAST(b0)                                                                            \
    R_WAIT();                                                                                  \
    if (b0) { PP_WAIT() }                                                                      \
    { DECL_DB(b0, BASE64, HALF, 1)                                                             \
    wg_fence();                                                                                \
    FOR7(mma_rs64<1, D64(0, t)>(al, AQ(A, b0, t), (b0) + t > 0, SWB(b0, t, db, 1)));           \
    FOR7(mma_rs64<1, D64(7168, t)>(al, AQ(A, (b0) + 1, t), 1, db)); }                          \
    wg_commit();                                                                               \
    if (b0) { PP_GO() }                                                                        \
    R_NEXT();
                float al[32];
                F1_LAST(0)
                mbar_wait(BAR(B_RECV + wgi), rcvph);
                rcvph ^= 1;
                mbar_wait(BAR(B_ACK2 + wgi), step >> 1);
                H_PUSH(32, 16384) H_PUSH(36, 16896)
                F1_LAST(2)
                H_PUSH(40, 17408) H_PUSH(44, 17920)
                wg_wait<1>();
                R_RELEASE(2);
                wg_wait<0>();
                R_RELEASE(1);
                uint32_t HP[56];
#pragma unroll
                for (int k = 0; k < 4; k++) lds4(H + 4 * k, sb + OFF_KVB + wgi * 8192 + w * 2048 + k * 512 + lane * 16);
#pragma unroll
                for (int t = 0; t < 8; t++) lds4(HP + 4 * t, hbuf + (t >> 2) * 8192 + w * 2048 + (t & 3) * 512 + lane * 16);
                F1_EPI(H + 48, 4, al)
                H_PUSH(48, 24576 - w * 1024) H_PUSH(52, 25088 - w * 1024)
                STAMP(7 + so);
                WSUM(84 + 7 * (step >> 1));
                FRESH();
                float acc[28];
                const uint32_t roA = hr ? 256u : 0u, roB = hr ? (uint32_t)-1536 : 0u;
                const uint32_t rpA = hr ? 0u : 256u, rpB = hr ? 0u : (uint32_t)-1536;
                float res[28];
                uint32_t v0[14], v1[14], P[14];
                const uint4* ps = xp0 + sl * 512;
#define F2_OWN_A()                                                                             \
    R_WAIT();                                                                                  \
    d0 = BASE128(0, 16, R_ADJ + roA); d1 = BASE128(0, 16, R_ADJ + roB);                        \
    wg_fence();                                                                                \
    FOR14(if constexpr (t < OT) mma_rs56<1, t * 128>(acc, H[4 * t], H[4 * t + 1], H[4 * t + 2], H[4 * t + 3], t > 0, d0)); \
    wg_commit();
#define F2_OWN_B()                                                                             \
    wg_fence();                                                                                \
    FOR14(if constexpr (t >= OT) mma_rs56<1, t * 128>(acc, H[4 * t], H[4 * t + 1], H[4 * t + 2], H[4 * t + 3], 1, t < 12 ? d0 : d1)); \
    wg_commit();                                                                               \
    R_NEXT();
#define F2_PEER()                                                                              \
    R_WAIT();                                                                                  \
    if (F2PP) { PP_WAIT() }                                                                    \
    d0 = BASE128(0, 16, R_ADJ + rpA); d1 = BASE128(0, 16, R_ADJ + rpB);                        \
    wg_fence();                                                                                \
    FOR14(mma_rs56<1, t * 128>(acc, HP[4 * t], HP[4 * t + 1], HP[4 * t + 2], HP[4 * t + 3], 1, t < 12 ? d0 : d1)); \
    wg_commit();                                                                               \
    if (F2PP) { PP_GO() }                                                                      \
    R_NEXT();
#define F2_TURN(u)                                                                             \
    wg_wait<1>();                                                                              \
    if ((u) < 2 || TDEF < 2) R_RELEASE(2);                                                     \
    wg_wait<0>();                                                                              \
    if ((u) < 2 || TDEF < 1) R_RELEASE(1);                                                     \
    _Pragma("unroll") for (int i = 0; i < 14; i++) P[i] = pack2(acc[2 * i], acc[2 * i + 1]);   \
    tag_slice(P, tag);                                                                         \
    asm volatile("" : RW4(P, 0), RW4(P, 4), RW4(P, 8), RW2(P, 12));                            \
    kill<28>(acc);                                                                             \
    F2_OWN_A()                                                                                 \
    if ((u) == 2) { slice_load<PL(3)>(v0, ps, lane); slice_load<PL(4)>(v1, ps, lane); } \
    send_slice<PL(3 + (u))>(xp0 + (2 * ((pr + (u) + 1) & 3) + hr) * 512, lane, P);             \
    seq++;                                                                                     \
    if (lane == 0) st_word(cx(sl), seq);                                                       \
    __syncwarp();                                                                              \
    STAMP(8 + (u) + so);                                                                       \
    F2_OWN_B()
                uint64_t d0, d1;
                F2_OWN_A()
                F2_OWN_B()
                R_WAIT();
                d0 = BASE128(0, 16, R_ADJ + rpA); d1 = BASE128(0, 16, R_ADJ + rpB);
                wg_fence();
                FOR8(mma_rs56<1, t * 128>(acc, HP[4 * t], HP[4 * t + 1], HP[4 * t + 2], HP[4 * t + 3], 1, d0));
                wg_commit();
                mbar_wait(BAR(B_RECV2 + wgi), step >> 1);
#pragma unroll
                for (int k = 0; k < 4; k++) lds4(HP + 32 + 4 * k, hbuf + 16384 + w * 2048 + k * 512 + lane * 16);
                lds4(HP + 48, hbuf + 24576 + w * 1024 + lane * 16);
                lds4(HP + 52, hbuf + 25088 + w * 1024 + lane * 16);
                if (step == 1) PUSH_ACK();
                wg_fence();
                FOR14(if constexpr (t >= 8) mma_rs56<1, t * 128>(acc, HP[4 * t], HP[4 * t + 1], HP[4 * t + 2], HP[4 * t + 3], 1, t < 12 ? d0 : d1));
                wg_commit();
                R_NEXT();
                F2_TURN(0)
                F2_PEER()
                F2_TURN(1)
                F2_PEER()
                F2_TURN(2)
                if (step == 1) STAMP(64);
                slice_check<PL(3)>(v0, ps, lane, tag);
                slice_check<PL(4)>(v1, ps, lane, tag);
#pragma unroll
                for (int i = 0; i < 14; i++) { res[2 * i] = bf_lo(v0[i]) + bf_lo(v1[i]); res[2 * i + 1] = bf_hi(v0[i]) + bf_hi(v1[i]); }
                slice_load<PL(2)>(X, ps, lane);
                if (step == 1) STAMP(65);
                F2_PEER()
                if (step == 1) STAMP(66);
                poll_cnt(cx(2 * ((pr + 1) & 3) + hr), seq);
                if (step == 1) STAMP(67);
                slice_load<PL(5)>(v0, ps, lane);
                x_fix(X, xbits);
                slice_check<PL(5)>(v0, ps, lane, tag);
                if (lane < TDEF) mbar_arrive(BAR(B_EMPTY + (slot + NST - 3 - lane) % NST));
#pragma unroll
                for (int i = 0; i < 14; i++) { res[2 * i] += bf_lo(v0[i]); res[2 * i + 1] += bf_hi(v0[i]); }
                STAMP(11 + so);
                wg_wait<0>();
                R_RELEASE(2);
                STAMP(12 + so);
                WSUM(85 + 7 * (step >> 1));
#pragma unroll
                for (int i = 0; i < 14; i++) X[i] = pack2(fmaf(res[2 * i] + acc[2 * i], 0.5f, bf_lo(X[i])), fmaf(res[2 * i + 1] + acc[2 * i + 1], 0.5f, bf_hi(X[i])));
            }
        }
        {
            const int m = lane >> 3, rr = lane & 7;
            const uint32_t ob = hbuf + w * 2048, rowa = ob + (rr + 8 * (m & 1)) * 112 + (m >> 1) * 16;
#pragma unroll
            for (int j = 0; j < 3; j++) stsm4(rowa + 32 * j, X[4 * j], X[4 * j + 1], X[4 * j + 2], X[4 * j + 3]);
            asm volatile("stmatrix.sync.aligned.m8n8.x2.shared.b16 [%0], {%1,%2};" ::"r"(ob + (rr + 8 * (m & 1)) * 112 + 96), "r"(X[12]), "r"(X[13]) : "memory");
            fence_async();
            __syncwarp();
            if (lane == 0) {
                asm volatile("cp.async.bulk.tensor.2d.global.shared::cta.bulk_group [%0, {%2, %3}], [%1];" ::"l"(&maps.out), "r"(ob), "r"(56 * sl), "r"(tile * 128 + wu * 16) : "memory");
                asm volatile("cp.async.bulk.commit_group;" ::: "memory");
                asm volatile("cp.async.bulk.wait_group.read 0;" ::: "memory");
            }
        }
        STAMP(50);
        GSTAMP(61);
        PDUMP();
    }
}

#undef g
#undef pr
#undef c
#undef t128

typedef CUresult (*EncodeFn)(CUtensorMap*, CUtensorMapDataType, cuuint32_t, void*, const cuuint64_t*, const cuuint64_t*, const cuuint32_t*,
                             const cuuint32_t*, CUtensorMapInterleave, CUtensorMapSwizzle, CUtensorMapL2promotion, CUtensorMapFloatOOBfill);

static void make_map(EncodeFn enc, CUtensorMap* m, const void* p, uint64_t cols, uint64_t rows, uint32_t bc, uint32_t br, CUtensorMapSwizzle sw) {
    cuuint64_t gd[2] = {cols, rows};
    cuuint64_t gs[1] = {cols * 2};
    cuuint32_t bd[2] = {bc, br};
    cuuint32_t es[2] = {1, 1};
    enc(m, CU_TENSOR_MAP_DATA_TYPE_BFLOAT16, 2, const_cast<void*>(p), gd, gs, bd, es, CU_TENSOR_MAP_INTERLEAVE_NONE, sw,
        CU_TENSOR_MAP_L2_PROMOTION_L2_128B, CU_TENSOR_MAP_FLOAT_OOB_FILL_NONE);
}

extern "C" void kernel_launch(void* const* d_in, const int* in_sizes, int n_in, void* d_out, int out_size) {
    (void)in_sizes; (void)n_in; (void)out_size;
    static EncodeFn enc = nullptr;
    static Scratch* scratch = nullptr;
    if (!enc) {
        void* fn = nullptr;
        cudaDriverEntryPointQueryResult qr;
        cudaGetDriverEntryPoint("cuTensorMapEncodeTiled", &fn, cudaEnableDefault, &qr);
        enc = (EncodeFn)fn;
        cudaGetSymbolAddress((void**)&scratch, g_scratch);
        cudaFuncSetAttribute(fused_kernel, cudaFuncAttributeMaxDynamicSharedMemorySize, SMEM_BYTES);
    }
    Maps maps;
    {
        cuuint64_t gd[3] = {64, 2048, 7};
        cuuint64_t gs[2] = {896, 128};
        cuuint32_t bd[3] = {64, 32, 7};
        cuuint32_t es[3] = {1, 1, 1};
        enc(&maps.x, CU_TENSOR_MAP_DATA_TYPE_BFLOAT16, 3, d_in[0], gd, gs, bd, es, CU_TENSOR_MAP_INTERLEAVE_NONE, CU_TENSOR_MAP_SWIZZLE_128B,
            CU_TENSOR_MAP_L2_PROMOTION_L2_128B, CU_TENSOR_MAP_FLOAT_OOB_FILL_NONE);
    }
    make_map(enc, &maps.out, d_out, 448, 2048, 56, 16, CU_TENSOR_MAP_SWIZZLE_NONE);
    make_map(enc, &maps.qkv, d_in[1], 1344, 448, 64, 112, CU_TENSOR_MAP_SWIZZLE_128B);
    make_map(enc, &maps.wo, d_in[3], 448, 448, 64, 112, CU_TENSOR_MAP_SWIZZLE_128B);
    make_map(enc, &maps.wg, d_in[5], 1792, 448, 64, 112, CU_TENSOR_MAP_SWIZZLE_128B);
    make_map(enc, &maps.wu, d_in[6], 1792, 448, 64, 112, CU_TENSOR_MAP_SWIZZLE_128B);
    make_map(enc, &maps.wg32, d_in[5], 1792, 448, 32, 112, CU_TENSOR_MAP_SWIZZLE_64B);
    make_map(enc, &maps.wu32, d_in[6], 1792, 448, 32, 112, CU_TENSOR_MAP_SWIZZLE_64B);
    make_map(enc, &maps.wd, d_in[7], 448, 1792, 64, 112, CU_TENSOR_MAP_SWIZZLE_128B);
    fused_kernel<<<128, 384, SMEM_BYTES>>>(scratch, (const __nv_bfloat16*)d_in[0], (const __nv_bfloat16*)d_in[2], 7, (const __nv_bfloat16*)d_in[5],
                                           (const __nv_bfloat16*)d_in[6], (const __nv_bfloat16*)d_in[7], maps);
}
```

```cpp
#include <cuda_runtime.h>
#include <cuda.h>
#include <cuda_bf16.h>
#include <stdint.h>
#include <type_traits>

#define PPF 2
#define PKP 0
#define TDEF 1
#define TMPF 0
#define NORM1 0
#define PP0 0
#define P13 0
#define ACAN 0
#define SPLIT0 1
#define OT 2
#define F2PP 0
#define PPK 2
#define QE 1
#define OST 1
#define PP

namespace {

constexpr uint32_t STAGE = 28672, HALF = 14336;
constexpr int NST = 5;
constexpr uint32_t OFF_H = NST * STAGE;
constexpr uint32_t OFF_KVB = OFF_H + 2 * STAGE;
constexpr uint32_t OFF_WPHI = OFF_KVB + 16384;
constexpr uint32_t OFF_XR = OFF_WPHI + 7168;
constexpr uint32_t OFF_BAR = OFF_XR + 6144;
constexpr uint32_t SMEM_BYTES = OFF_BAR + 384 + 1408;
constexpr int B_EMPTY = NST, B_RECV = 2 * NST, B_RECV2 = B_RECV + 2, B_PACK = B_RECV2 + 2, B_GAT = B_PACK + 1, B_LATE = B_GAT + 16, B_ACK = B_LATE + 1, B_ACK2 = B_ACK + 2, B_COUNT = B_ACK2 + 2;

constexpr int PACK = 14 + 4 * PKP;

struct Maps { CUtensorMap x, qkv, wo, wg, wu, wg32, wu32, wd, out; };

}

constexpr int PLANE = 16 * 2 * 8 * 512;
struct Scratch {
    uint4 ex[6 * PLANE];
    uint4 kv1[8 * 16 * 16 * 32];
    uint4 kv2[8 * 512];
    uint32_t c1[8 * 8 * 16 * 32];
    uint32_t cw[8 * 32];
    uint4 wp[8 * 32 * (HALF / 16)];
};
__device__ __align__(1024) Scratch g_scratch;
#define g_ex (sc->ex)
#define g_kv1 (sc->kv1)
#define g_kv2 (sc->kv2)
#define g_c1 (sc->c1)
#define g_cw (sc->cw)
#define g_wp (sc->wp)
#define STAMP(i)
#define GSTAMP(i)
#define PDUMP()
#define ASTAMP(i)

namespace {

__device__ __forceinline__ int fresh_tid() { int t; asm volatile("mov.u32 %0, %%tid.x;" : "=r"(t)); return t; }
template <int N> __device__ __forceinline__ void kill(uint32_t* v) {
#pragma unroll
    for (int i = 0; i < N; i++) v[i] = 0;
}
template <int N> __device__ __forceinline__ void kill(float* v) {
#pragma unroll
    for (int i = 0; i < N; i++) v[i] = 0.f;
}
__device__ __forceinline__ uint32_t s2u(const void* p) { return (uint32_t)__cvta_generic_to_shared(p); }
__device__ __forceinline__ void mbar_init(uint32_t a, uint32_t c) { asm volatile("mbarrier.init.shared::cta.b64 [%0], %1;" ::"r"(a), "r"(c) : "memory"); }
__device__ __forceinline__ void mbar_expect_tx(uint32_t a, uint32_t b) { asm volatile("mbarrier.arrive.expect_tx.shared::cta.b64 _, [%0], %1;" ::"r"(a), "r"(b) : "memory"); }
__device__ __forceinline__ void mbar_arrive(uint32_t a) { asm volatile("mbarrier.arrive.shared::cta.b64 _, [%0];" ::"r"(a) : "memory"); }
#define GIVE_UP(id) "trap;\n"
#define SPIN_MAX "0x400000"
#define SPIN_TAIL(id) "add.u32 n, n, 1;\n setp.lt.u32 p, n, " SPIN_MAX ";\n @p bra.uni LP;\n" GIVE_UP(id) " DN:\n }"
__device__ __forceinline__ void mbar_wait(uint32_t a, uint32_t ph) {
    asm volatile("{ .reg .pred p; .reg .b32 n; mov.u32 n, 0;\n LP:\n"
                 "mbarrier.try_wait.parity.shared::cta.b64 p, [%0], %1;\n @p bra DN;\n"
                 "add.u32 n, n, 1;\n setp.lt.u32 p, n, " SPIN_MAX ";\n @p bra LP;\n"
                 GIVE_UP("")
                 " DN:\n }" ::"r"(a), "r"(ph) : "memory");
}
#define ELECT "{ .reg .pred e; elect.sync _|e, 0xffffffff; @e "
__device__ __forceinline__ void tma2d(uint32_t dst, const CUtensorMap* m, int c0, int c1, uint32_t bar) {
    asm volatile(ELECT "cp.async.bulk.tensor.2d.shared::cluster.global.mbarrier::complete_tx::bytes [%0], [%1, {%3, %4}], [%2]; }" ::"r"(dst), "l"(m), "r"(bar), "r"(c0), "r"(c1) : "memory");
}
__device__ __forceinline__ void tma3x(uint32_t dst, const CUtensorMap* m, int row, uint32_t bar) {
    asm volatile(ELECT "cp.async.bulk.tensor.3d.shared::cluster.global.mbarrier::complete_tx::bytes [%0], [%1, {0, %3, 0}], [%2]; }" ::"r"(dst), "l"(m), "r"(bar), "r"(row) : "memory");
}
template <int OFF>
__device__ __forceinline__ void ld_pkt(uint32_t* v, const uint4* p) {
    asm volatile("{ .reg .b128 t; ld.relaxed.gpu.global.b128 t, [%4+%5]; mov.b128 {%0,%1,%2,%3}, t; }" : "=r"(v[0]), "=r"(v[1]), "=r"(v[2]), "=r"(v[3]) : "l"(p), "n"(OFF * 16) : "memory");
}
template <int OFF>
__device__ __forceinline__ void st_pkt(uint4* p, uint32_t a, uint32_t b, uint32_t c, uint32_t d) {
    asm volatile("{ .reg .b128 t; mov.b128 t, {%1,%2,%3,%4}; st.relaxed.gpu.global.b128 [%0+%5], t; }" ::"l"(p), "r"(a), "r"(b), "r"(c), "r"(d), "n"(OFF * 16) : "memory");
}
__device__ __forceinline__ uint32_t pack2(float lo, float hi) {
    uint32_t r;
    asm("cvt.rn.bf16x2.f32 %0, %1, %2;" : "=r"(r) : "f"(hi), "f"(lo));
    return r;
}
__device__ __forceinline__ float bf_lo(uint32_t w) { return __uint_as_float(w << 16); }
__device__ __forceinline__ float bf_hi(uint32_t w) { return __uint_as_float(w & 0xffff0000u); }
__device__ __forceinline__ uint32_t settag(uint32_t w, uint32_t tag) { return (w & ~1u) | tag; }
__device__ __forceinline__ float ex2(float x) { float y; asm("ex2.approx.ftz.f32 %0, %1;" : "=f"(y) : "f"(x)); return y; }
__device__ __forceinline__ float rcp(float x) { float y; asm("rcp.approx.ftz.f32 %0, %1;" : "=f"(y) : "f"(x)); return y; }
__device__ __forceinline__ float tanh_hw(float x) { float y; asm("tanh.approx.f32 %0, %1;" : "=f"(y) : "f"(x)); return y; }
__device__ __forceinline__ void stsm4(uint32_t addr, uint32_t a, uint32_t b, uint32_t c, uint32_t d) {
    asm volatile("stmatrix.sync.aligned.m8n8.x4.shared.b16 [%0], {%1,%2,%3,%4};" ::"r"(addr), "r"(a), "r"(b), "r"(c), "r"(d) : "memory");
}
__device__ __forceinline__ void fence_async() { asm volatile("fence.proxy.async.shared::cta;" ::: "memory"); }
__device__ __forceinline__ void bar_sync(int id, int n) { asm volatile("bar.sync %0, %1;" ::"r"(id), "r"(n) : "memory"); }
__device__ __forceinline__ void bar_arrive(int id, int n) { asm volatile("bar.arrive %0, %1;" ::"r"(id), "r"(n) : "memory"); }
__device__ __forceinline__ void wg_fence() { asm volatile("wgmma.fence.sync.aligned;" ::: "memory"); }
__device__ __forceinline__ void wg_commit() { asm volatile("wgmma.commit_group.sync.aligned;" ::: "memory"); }
template <int N> __device__ __forceinline__ void wg_wait() { asm volatile("wgmma.wait_group.sync.aligned %0;" ::"n"(N) : "memory"); }

constexpr uint32_t SB0 = 1024;
__host__ __device__ constexpr uint32_t dlo(uint32_t off, uint32_t lbo) { return ((SB0 + off) >> 4) | ((lbo >> 4) << 16); }
__host__ __device__ constexpr uint32_t dhi(uint32_t sbo, uint32_t sw) { return (sbo >> 4) | (sw << 30); }
__device__ __forceinline__ uint64_t dbase(uint32_t lo, uint32_t hi) { uint64_t d; asm volatile("mov.b64 %0, {%1, %2};" : "=l"(d) : "r"(lo), "r"(hi)); return d; }
#define BASE128(off, lbo, adj) dbase(dlo(off, lbo) + (adj), dhi(1024, 1))
#define BASE64(off, lbo, adj) dbase(dlo(off, lbo) + (adj), dhi(512, 2))

#define ACC4(d, o) "+f"(d[o]), "+f"(d[o + 1]), "+f"(d[o + 2]), "+f"(d[o + 3])
#define ACC28(d) ACC4(d, 0), ACC4(d, 4), ACC4(d, 8), ACC4(d, 12), ACC4(d, 16), ACC4(d, 20), ACC4(d, 24)
#define ACC32(d, o) ACC4(d, o), ACC4(d, o + 4), ACC4(d, o + 8), ACC4(d, o + 12), ACC4(d, o + 16), ACC4(d, o + 20), ACC4(d, o + 24), ACC4(d, o + 28)

template <int TB, uint64_t D>
__device__ __forceinline__ void mma_rs56(float* d, uint32_t a0, uint32_t a1, uint32_t a2, uint32_t a3, int sd, uint64_t base) {
    asm volatile("{ .reg .pred p; .reg .b64 db; setp.ne.b32 p, %32, 0; add.u64 db, %33, %34;\n"
                 "wgmma.mma_async.sync.aligned.m64n56k16.f32.bf16.bf16 "
                 "{%0,%1,%2,%3,%4,%5,%6,%7,%8,%9,%10,%11,%12,%13,%14,%15,%16,%17,%18,%19,%20,%21,%22,%23,%24,%25,%26,%27}, "
                 "{%28,%29,%30,%31}, db, p, 1, 1, %35; }\n"
                 : ACC28(d)
                 : "r"(a0), "r"(a1), "r"(a2), "r"(a3), "r"(sd), "l"(base), "n"(D), "n"(TB));
}
template <int TB, uint64_t D>
__device__ __forceinline__ void mma_rs64(float* d, uint32_t a0, uint32_t a1, uint32_t a2, uint32_t a3, int sd, uint64_t base) {
    asm volatile("{ .reg .pred p; .reg .b64 db; setp.ne.b32 p, %36, 0; add.u64 db, %37, %38;\n"
                 "wgmma.mma_async.sync.aligned.m64n64k16.f32.bf16.bf16 "
                 "{%0,%1,%2,%3,%4,%5,%6,%7,%8,%9,%10,%11,%12,%13,%14,%15,%16,%17,%18,%19,%20,%21,%22,%23,%24,%25,%26,%27,%28,%29,%30,%31}, "
                 "{%32,%33,%34,%35}, db, p, 1, 1, %39; }\n"
                 : ACC32(d, 0)
                 : "r"(a0), "r"(a1), "r"(a2), "r"(a3), "r"(sd), "l"(base), "n"(D), "n"(TB));
}
template <int TB, uint64_t D>
__device__ __forceinline__ void mma_rs128(float* d, uint32_t a0, uint32_t a1, uint32_t a2, uint32_t a3, int sd, uint64_t base) {
    asm volatile("{ .reg .pred p; .reg .b64 db; setp.ne.b32 p, %68, 0; add.u64 db, %69, %70;\n"
                 "wgmma.mma_async.sync.aligned.m64n128k16.f32.bf16.bf16 "
                 "{%0,%1,%2,%3,%4,%5,%6,%7,%8,%9,%10,%11,%12,%13,%14,%15,%16,%17,%18,%19,%20,%21,%22,%23,%24,%25,%26,%27,%28,%29,%30,%31,%32,%33,%34,%35,%36,%37,%38,%39,%40,%41,%42,%43,%44,%45,%46,%47,%48,%49,%50,%51,%52,%53,%54,%55,%56,%57,%58,%59,%60,%61,%62,%63}, "
                 "{%64,%65,%66,%67}, db, p, 1, 1, %71; }\n"
                 : ACC32(d, 0), ACC32(d, 32)
                 : "r"(a0), "r"(a1), "r"(a2), "r"(a3), "r"(sd), "l"(base), "n"(D), "n"(TB));
}
template <uint64_t DA, uint64_t DB>
__device__ __forceinline__ void mma_ss56_tt(float* d, int sd, uint64_t ba, uint64_t bb) {
    asm volatile("{ .reg .pred p; .reg .b64 da, db; setp.ne.b32 p, %28, 0; add.u64 da, %29, %31; add.u64 db, %30, %32;\n"
                 "wgmma.mma_async.sync.aligned.m64n56k16.f32.bf16.bf16 "
                 "{%0,%1,%2,%3,%4,%5,%6,%7,%8,%9,%10,%11,%12,%13,%14,%15,%16,%17,%18,%19,%20,%21,%22,%23,%24,%25,%26,%27}, "
                 "da, db, p, 1, 1, 1, 1; }\n"
                 : ACC28(d)
                 : "r"(sd), "l"(ba), "l"(bb), "n"(DA), "n"(DB));
}
template <int... I> struct Seq {};
template <class F, int... I> __device__ __forceinline__ void static_for_impl(F&& f, Seq<I...>) { (f(std::integral_constant<int, I>{}), ...); }
#define FOR7(...) static_for_impl([&](auto T_) { constexpr int t = decltype(T_)::value; __VA_ARGS__; }, Seq<0, 1, 2, 3, 4, 5, 6>{})
#define FOR8(...) static_for_impl([&](auto T_) { constexpr int t = decltype(T_)::value; __VA_ARGS__; }, Seq<0, 1, 2, 3, 4, 5, 6, 7>{})
#define FOR14(...) static_for_impl([&](auto T_) { constexpr int t = decltype(T_)::value; __VA_ARGS__; }, Seq<0, 1, 2, 3, 4, 5, 6, 7, 8, 9, 10, 11, 12, 13>{})

__device__ __forceinline__ int kblk(int p, int b) { return b == 0 ? p : b - (b <= p); }
__host__ __device__ constexpr int krow(int t) { return t < 3 ? 16 * t : (t < 6 ? 56 + 16 * (t - 3) : 48); }
#define AQ(A, b, t) ((t) < 3 ? A[2 * (b)][4 * (t)] : (t) < 6 ? A[2 * (b) + 1][4 * ((t) - 3)] : A[2 * (b)][12]), \
                    ((t) < 3 ? A[2 * (b)][4 * (t) + 1] : (t) < 6 ? A[2 * (b) + 1][4 * ((t) - 3) + 1] : A[2 * (b)][13]), \
                    ((t) < 3 ? A[2 * (b)][4 * (t) + 2] : (t) < 6 ? A[2 * (b) + 1][4 * ((t) - 3) + 2] : A[2 * (b) + 1][12]), \
                    ((t) < 3 ? A[2 * (b)][4 * (t) + 3] : (t) < 6 ? A[2 * (b) + 1][4 * ((t) - 3) + 3] : A[2 * (b) + 1][13])
#define D128(off, t) ((uint64_t)(((off) + krow(t) * 128) >> 4) + ((uint64_t)((t) == 6 ? (7168 - 1024) >> 4 : 0) << 32))
#define D64(off, t) ((uint64_t)(((off) + krow(t) * 64) >> 4) + ((uint64_t)((t) == 6 ? (3584 - 512) >> 4 : 0) << 32))

#define PL(k) (((k) - 3) * PLANE)
__device__ __forceinline__ void st_word(uint32_t* p, uint32_t v) { asm volatile("st.relaxed.gpu.global.u32 [%0], %1;" ::"l"(p), "r"(v) : "memory"); }
__device__ __forceinline__ uint32_t ld_word(const uint32_t* p) { uint32_t v; asm volatile("ld.relaxed.gpu.global.u32 %0, [%1];" : "=r"(v) : "l"(p) : "memory"); return v; }
__device__ __forceinline__ void tag_slice(uint32_t* w, uint32_t tag) { w[0] = settag(w[0], tag); w[4] = settag(w[4], tag); w[8] = settag(w[8], tag); w[12] = settag(w[12], tag); }
template <int O>
__device__ __forceinline__ void send_slice(uint4* dst, int lane, const uint32_t* w) {
    st_pkt<O>(dst, w[0], w[1], w[2], w[3]);
    st_pkt<O + 32>(dst, w[4], w[5], w[6], w[7]);
    st_pkt<O + 64>(dst, w[8], w[9], w[10], w[11]);
    asm volatile("{ .reg .b64 t; mov.b64 t, {%1,%2}; st.relaxed.gpu.global.b64 [%0+%3], t; }" ::"l"((char*)dst - lane * 8), "r"(w[12]), "r"(w[13]), "n"(16 * (O + 96)) : "memory");
}
#define RW4(v, o) "+r"(v[o]), "+r"(v[(o) + 1]), "+r"(v[(o) + 2]), "+r"(v[(o) + 3])
#define RW2(v, o) "+r"(v[o]), "+r"(v[(o) + 1])
#define WR4(v, o) "=&r"(v[o]), "=&r"(v[(o) + 1]), "=&r"(v[(o) + 2]), "=&r"(v[(o) + 3])
#define LDP(a, b, c, d, addr, off) "ld.relaxed.gpu.global.b128 q, [" addr "+" off "];\n mov.b128 {" a "," b "," c "," d "}, q;\n"
#define LDH(a, b, addr, off) "ld.relaxed.gpu.global.b64 h, [" addr "+" off "];\n mov.b64 {" a "," b "}, h;\n"
#define VOTE_OK "and.b32 t, t, 1;\n setp.ne.u32 p, t, 0;\n vote.sync.any.pred p, p, 0xffffffff;\n @!p bra.uni DN;\n"
#define CHK(x, tag) "lop3.b32 t, " x ", " tag ", t, 0xBE;\n"
__device__ __forceinline__ void check_cnt(uint32_t v, const uint32_t* p, uint32_t target) {
    asm volatile("{ .reg .pred p; .reg .b32 n, t; mov.u32 n, 0; mov.u32 t, %2;\n LP:\n"
                 "sub.s32 t, t, %1;\n setp.lt.s32 p, t, 0;\n vote.sync.any.pred p, p, 0xffffffff;\n @!p bra.uni DN;\n ld.relaxed.gpu.global.u32 t, [%0];\n" SPIN_TAIL("7")
                 ::"l"(p), "r"(target), "r"(v) : "memory");
}
__device__ __forceinline__ void poll_cnt(const uint32_t* p, uint32_t target) {
    asm volatile("{ .reg .pred p; .reg .b32 n, t; mov.u32 n, 0;\n LP:\n"
                 "ld.relaxed.gpu.global.u32 t, [%0];\n sub.s32 t, t, %1;\n setp.lt.s32 p, t, 0;\n vote.sync.any.pred p, p, 0xffffffff;\n @!p bra.uni DN;\n" SPIN_TAIL("1")
                 ::"l"(p), "r"(target) : "memory");
}
template <int STR>
__device__ __forceinline__ void poll4_kv(uint32_t* v, const uint4* p, uint32_t tag) {
    asm volatile("{ .reg .pred p; .reg .b32 n, t; .reg .b128 q; mov.u32 n, 0;\n LP:\n"
                 LDP("%0", "%1", "%2", "%3", "%16", "0") LDP("%4", "%5", "%6", "%7", "%16", "%18")
                 LDP("%8", "%9", "%10", "%11", "%16", "%19") LDP("%12", "%13", "%14", "%15", "%16", "%20")
                 "xor.b32 t, %0, %17;\n" CHK("%4", "%17") CHK("%8", "%17") CHK("%12", "%17") VOTE_OK SPIN_TAIL("2")
                 : WR4(v, 0), WR4(v, 4), WR4(v, 8), WR4(v, 12)
                 : "l"(p), "r"(tag), "n"(16 * STR), "n"(32 * STR), "n"(48 * STR)
                 : "memory");
}
template <int B>
__device__ __forceinline__ void blk_load(uint32_t (&A)[8][14], const uint4* src, int lane) {
    ld_pkt<0>(&A[2 * B][0], src); ld_pkt<32>(&A[2 * B][4], src); ld_pkt<64>(&A[2 * B][8], src);
    ld_pkt<512>(&A[2 * B + 1][0], src); ld_pkt<544>(&A[2 * B + 1][4], src); ld_pkt<576>(&A[2 * B + 1][8], src);
    asm volatile("{ .reg .b64 h;\n" LDH("%0", "%1", "%4", "1536") LDH("%2", "%3", "%4", "9728") "}"
                 : "=&r"(A[2 * B][12]), "=&r"(A[2 * B][13]), "=&r"(A[2 * B + 1][12]), "=&r"(A[2 * B + 1][13])
                 : "l"((const char*)src - lane * 8) : "memory");
}
template <int B>
__device__ __forceinline__ void blk_check(uint32_t (&A)[8][14], const uint4* src, int lane, uint32_t tag) {
    asm volatile("{ .reg .pred p; .reg .b32 n, t; .reg .b128 q; .reg .b64 h, a8; mov.u32 n, 0;\n LP:\n"
                 "xor.b32 t, %0, %30;\n" CHK("%4", "%30") CHK("%8", "%30") CHK("%12", "%30") CHK("%16", "%30") CHK("%20", "%30") CHK("%24", "%30") CHK("%26", "%30") VOTE_OK
                 LDP("%0", "%1", "%2", "%3", "%28", "0") LDP("%4", "%5", "%6", "%7", "%28", "512") LDP("%8", "%9", "%10", "%11", "%28", "1024")
                 LDP("%12", "%13", "%14", "%15", "%28", "8192") LDP("%16", "%17", "%18", "%19", "%28", "8704") LDP("%20", "%21", "%22", "%23", "%28", "9216")
                 "mad.wide.s32 a8, %29, -8, %28;\n" LDH("%24", "%25", "a8", "1536") LDH("%26", "%27", "a8", "9728") SPIN_TAIL("3")
                 "\n and.b32 %0, %0, -2; and.b32 %4, %4, -2; and.b32 %8, %8, -2; and.b32 %12, %12, -2; and.b32 %16, %16, -2; and.b32 %20, %20, -2; and.b32 %24, %24, -2; and.b32 %26, %26, -2;"
                 : RW4(A[2 * B], 0), RW4(A[2 * B], 4), RW4(A[2 * B], 8), RW4(A[2 * B + 1], 0), RW4(A[2 * B + 1], 4), RW4(A[2 * B + 1], 8),
                   RW2(A[2 * B], 12), RW2(A[2 * B + 1], 12)
                 : "l"(src), "r"(lane), "r"(tag)
                 : "memory");
}
__device__ __forceinline__ void st_async4(uint32_t a, uint32_t x, uint32_t y, uint32_t z, uint32_t w, uint32_t bar) {
    asm volatile("st.async.weak.shared::cluster.mbarrier::complete_tx::bytes.v4.b32 [%0], {%1,%2,%3,%4}, [%5];" ::"r"(a), "r"(x), "r"(y), "r"(z), "r"(w), "r"(bar) : "memory");
}
__device__ __forceinline__ uint32_t mapa(uint32_t a, uint32_t cta) { uint32_t r; asm("mapa.shared::cluster.u32 %0, %1, %2;" : "=r"(r) : "r"(a), "r"(cta)); return r; }
__device__ __forceinline__ void stat_load(uint32_t* v, const uint4* p) { ld_pkt<0>(v, p); ld_pkt<512>(v + 4, p); }
__device__ __forceinline__ void stat_check(uint32_t* v, const uint4* p, uint32_t tag) {
    asm volatile("{ .reg .pred p; .reg .b32 n, t; .reg .b128 q; mov.u32 n, 0;\n LP:\n"
                 "xor.b32 t, %3, %9;\n" CHK("%7", "%9") VOTE_OK
                 LDP("%0", "%1", "%2", "%3", "%8", "0") LDP("%4", "%5", "%6", "%7", "%8", "8192") SPIN_TAIL("4")
                 : RW4(v, 0), RW4(v, 4) : "l"(p), "r"(tag) : "memory");
}
__device__ __forceinline__ uint32_t x_bits(const uint32_t* X) {
    uint32_t r;
    asm volatile("{ .reg .b32 a, b; prmt.b32 a, %1, %2, 0x0040; prmt.b32 b, %3, %4, 0x0040; prmt.b32 %0, a, b, 0x5410; }" : "=r"(r) : "r"(X[0]), "r"(X[4]), "r"(X[8]), "r"(X[12]));
    return r;
}
template <int O>
__device__ __forceinline__ void slice_load(uint32_t* v, const uint4* p, int lane) {
    ld_pkt<O>(v, p); ld_pkt<O + 32>(v + 4, p); ld_pkt<O + 64>(v + 8, p);
    asm volatile("{ .reg .b64 h;\n" LDH("%0", "%1", "%2", "%3") "}" : "=r"(v[12]), "=r"(v[13]) : "l"((const char*)p - lane * 8), "n"(16 * (O + 96)) : "memory");
}
template <int O>
__device__ __forceinline__ void slice_check(uint32_t* v, const uint4* p, int lane, uint32_t tag) {
    asm volatile("{ .reg .pred p; .reg .b32 n, t; .reg .b128 q; .reg .b64 h; mov.u32 n, 0;\n LP:\n"
                 "xor.b32 t, %0, %16;\n" CHK("%4", "%16") CHK("%8", "%16") CHK("%12", "%16") VOTE_OK
                 LDP("%0", "%1", "%2", "%3", "%14", "%17") LDP("%4", "%5", "%6", "%7", "%14", "%18") LDP("%8", "%9", "%10", "%11", "%14", "%19")
                 LDH("%12", "%13", "%15", "%20") SPIN_TAIL("5")
                 : RW4(v, 0), RW4(v, 4), RW4(v, 8), RW2(v, 12)
                 : "l"(p), "l"((const char*)p - lane * 8), "r"(tag), "n"(16 * O), "n"(16 * (O + 32)), "n"(16 * (O + 64)), "n"(16 * (O + 96))
                 : "memory");
}
__device__ __forceinline__ void x_fix(uint32_t* X, uint32_t bits) {
    X[0] = __byte_perm(X[0], bits, 0x3214); X[4] = __byte_perm(X[4], bits, 0x3215); X[8] = __byte_perm(X[8], bits, 0x3216); X[12] = __byte_perm(X[12], bits, 0x3217);
}
__device__ __forceinline__ void sts4(uint32_t a, uint32_t x, uint32_t y, uint32_t z, uint32_t w) {
    asm volatile("st.shared.v4.u32 [%0], {%1,%2,%3,%4};" ::"r"(a), "r"(x), "r"(y), "r"(z), "r"(w) : "memory");
}
__device__ __forceinline__ void lds4(uint32_t* v, uint32_t a) {
    asm volatile("ld.shared.v4.u32 {%0,%1,%2,%3}, [%4];" : "=r"(v[0]), "=r"(v[1]), "=r"(v[2]), "=r"(v[3]) : "r"(a) : "memory");
}
struct LnCoef { uint32_t hi, lo, sh; };
__device__ __forceinline__ LnCoef ln_coef(float sum, float sq) {
    sum += __shfl_xor_sync(0xffffffffu, sum, 1); sq += __shfl_xor_sync(0xffffffffu, sq, 1);
    sum += __shfl_xor_sync(0xffffffffu, sum, 2); sq += __shfl_xor_sync(0xffffffffu, sq, 2);
    const float mean = sum * (1.f / 448.f);
    const float var = fmaxf(fmaf(-mean, mean, sq * (1.f / 448.f)), 0.f);
    const float sc = rsqrtf(var + 1e-5f);
    LnCoef r;
    r.hi = pack2(sc, sc);
    const float lo = sc - bf_lo(r.hi), sh = -mean * sc;
    r.lo = pack2(lo, lo);
    r.sh = pack2(sh, sh);
    return r;
}
template <int B>
__device__ __forceinline__ void normalize(uint32_t (&A)[8][14], const LnCoef& c0, const LnCoef& c1) {
#pragma unroll
    for (int s = 2 * B; s < 2 * B + 2; s++)
#pragma unroll
        for (int i = 0; i < 14; i++) {
            const LnCoef& k = (i & 1) ? c1 : c0;
            asm("{ .reg .b32 t; fma.rn.bf16x2 t, %0, %2, %3; fma.rn.bf16x2 %0, %0, %1, t; }" : "+r"(A[s][i]) : "r"(k.hi), "r"(k.lo), "r"(k.sh));
        }
}
__device__ __forceinline__ void slice_stats(const uint32_t* w, float* st) {
    float a = 0.f, b = 0.f, p = 0.f, q = 0.f;
#pragma unroll
    for (int i = 0; i < 7; i++) {
        const float e0 = bf_lo(w[2 * i]), e1 = bf_hi(w[2 * i]), e2 = bf_lo(w[2 * i + 1]), e3 = bf_hi(w[2 * i + 1]);
        a += e0 + e1; b += e2 + e3;
        p = fmaf(e0, e0, p); p = fmaf(e1, e1, p); q = fmaf(e2, e2, q); q = fmaf(e3, e3, q);
    }
    a += __shfl_xor_sync(0xffffffffu, a, 1); p += __shfl_xor_sync(0xffffffffu, p, 1); b += __shfl_xor_sync(0xffffffffu, b, 1); q += __shfl_xor_sync(0xffffffffu, q, 1);
    a += __shfl_xor_sync(0xffffffffu, a, 2); p += __shfl_xor_sync(0xffffffffu, p, 2); b += __shfl_xor_sync(0xffffffffu, b, 2); q += __shfl_xor_sync(0xffffffffu, q, 2);
    st[0] = a; st[1] = p; st[2] = b; st[3] = q;
}
__device__ __forceinline__ void dual_softmax(const float* p, uint32_t* out) {
    constexpr float L = 1.4426950408889634f;
#pragma unroll
    for (int r = 0; r < 2; r++) {
        float mx = fmaxf(p[2 * r], p[2 * r + 1]), mn = fminf(p[2 * r], p[2 * r + 1]);
#pragma unroll
        for (int i = 1; i < 7; i++) {
            mx = fmaxf(mx, fmaxf(p[4 * i + 2 * r], p[4 * i + 2 * r + 1]));
            mn = fminf(mn, fminf(p[4 * i + 2 * r], p[4 * i + 2 * r + 1]));
        }
        mx = fmaxf(mx, __shfl_xor_sync(0xffffffffu, mx, 1));
        mn = fminf(mn, __shfl_xor_sync(0xffffffffu, mn, 1));
        const float bx = -mx * L, bn = mn * L;
        float ep[14], en[14], sp = 0.f, sn = 0.f;
#pragma unroll
        for (int i = 0; i < 14; i++) {
            const float v = p[4 * (i >> 1) + 2 * r + (i & 1)];
            ep[i] = ex2(fmaf(v, L, bx));
            en[i] = ex2(fmaf(v, -L, bn));
            sp += ep[i]; sn += en[i];
        }
        sp += __shfl_xor_sync(0xffffffffu, sp, 1);
        sn += __shfl_xor_sync(0xffffffffu, sn, 1);
        const float ip = rcp(sp), in = rcp(sn);
#pragma unroll
        for (int i = 0; i < 7; i++) {
            out[4 * i + r] = pack2(ep[2 * i] * ip, ep[2 * i + 1] * ip);
            out[4 * i + 2 + r] = pack2(en[2 * i] * in, en[2 * i + 1] * in);
        }
    }
}
__device__ __forceinline__ float geglu(float g, float u) {
    const float t = tanh_hw(g * fmaf(g * g, 0.7978845608028654f * 0.044715f, 0.7978845608028654f));
    const float gu = g * u;
    return fmaf(t, gu, gu);
}
__device__ __forceinline__ void phi_gemm(const float* t, float* p) {
    uint32_t w[14];
#pragma unroll
    for (int i = 0; i < 14; i++) w[i] = pack2(t[2 * i], t[2 * i + 1]);
    const uint64_t db = BASE128(OFF_WPHI, 16, 0);
    wg_fence();
    mma_rs56<0, 0>(p, w[0], w[1], w[2], w[3], 0, db);
    mma_rs56<0, 2>(p, w[4], w[5], w[6], w[7], 1, db);
    mma_rs56<0, 4>(p, w[8], w[9], w[10], w[11], 1, db);
    mma_rs56<0, 6>(p, w[12], w[13], 0u, 0u, 1, db);
    wg_commit();
    wg_wait<0>();
}

}

#define BAR(i) (bars + 8 * (i))
#define R_WAIT() mbar_wait(BAR(slot), ph)
#define WSUM(i)
#define R_ADJ (slot * (STAGE >> 4))
#define R_NEXT() do { eb2 = eb1; eb1 = BAR(B_EMPTY + slot); if (++slot == NST) { slot = 0; ph ^= 1; } } while (0)
#define R_RELEASE(k) do { if (lane == 0) mbar_arrive((k) == 1 ? eb1 : eb2); } while (0)
#define PUSH_BEGIN() do { mbar_wait(BAR(B_ACK + wgi), ackph); ackph ^= 1; } while (0)
#define PUSH_ACK() do { __syncwarp(); if (lane == 0) asm volatile("mbarrier.arrive.shared::cluster.b64 _, [%0];" ::"r"(mapa(BAR(B_ACK + wgi), hr ^ 1)) : "memory"); } while (0)

__global__ void __cluster_dims__(2, 1, 1) __launch_bounds__(384, 1)
fused_kernel(Scratch* const sc, const __nv_bfloat16* __restrict__ x_in, const __nv_bfloat16* __restrict__ w_phi, const int trips,
             const __nv_bfloat16* __restrict__ wg, const __nv_bfloat16* __restrict__ wu, const __nv_bfloat16* __restrict__ wd,
             const __grid_constant__ Maps maps) {
    extern __shared__ __align__(1024) unsigned char smem_raw[];
    const uint32_t sb = s2u(smem_raw);
    const uint32_t bars = sb + OFF_BAR;
    const int wgi = __shfl_sync(0xffffffffu, threadIdx.x >> 7, 0);
    const int hr = blockIdx.x & 1, ck = blockIdx.x >> 1;
    const int gp = (ck - 4) & 7, q7 = ((ck - 36) * 37) >> 8;
    const int pr = __shfl_sync(0xffffffffu, ck < 4 ? ck : (ck < 36 ? (ck - 4) >> 3 : q7), 0);
    const int tile = __shfl_sync(0xffffffffu, ck < 4 ? 0 : (ck < 36 ? (gp ? 2 * gp : 1) : 2 * (ck - 36 - 7 * q7) + 3), 0);
    const int sl = 2 * pr + hr;
    STAMP(0);
    GSTAMP(60);
    if (threadIdx.x == 256) {
#pragma unroll
        for (int i = 0; i < NST; i++) mbar_init(BAR(i), 1);
        asm volatile("fence.mbarrier_init.release.cluster;" ::: "memory");
    }
    if (threadIdx.x == 288) {
        if ((sb & 0x3FFFF) != SB0) asm volatile("trap;");
#pragma unroll
        for (int i = NST; i < B_COUNT; i++) mbar_init(BAR(i), i >= B_ACK ? 4 : (i < B_RECV || i == B_LATE ? 8 : 1));
        asm volatile("fence.mbarrier_init.release.cluster;" ::: "memory");
    }
    __syncwarp();
    asm volatile("barrier.cluster.arrive.relaxed.aligned;" ::: "memory");

    if (wgi == 2) {
        asm volatile("setmaxnreg.dec.sync.aligned.u32 40;");
        const int t128 = fresh_tid() & 127, w = __shfl_sync(0xffffffffu, t128 >> 5, 0), lane = t128 & 31;
        uint32_t e0[2] = {0, 0}, e1[2] = {0, 0}, cw_target = 0;
        if (w == 0) {
#pragma unroll 1
            for (int n = 0; n < NST; n++) {
                const uint32_t dst = sb + n * STAGE, fb = BAR(n);
                asm volatile(ELECT "mbarrier.arrive.expect_tx.shared::cta.b64 _, [%0], %1; }" ::"r"(fb), "r"(n < 2 ? 2 * STAGE : STAGE) : "memory");
                if (n < 2) {
                    tma3x(sb + OFF_H + n * STAGE, &maps.x, tile * 128 + n * 64, fb);
                    tma3x(dst, &maps.x, tile * 128 + n * 64 + 32, fb);
                } else {
                    if (n == 3) mbar_wait(BAR(1), 0);
                    const int ra = 112 * (n - 2);
                    tma2d(dst, &maps.qkv, 448 + 56 * sl, ra, fb);
                    tma2d(dst + HALF, &maps.qkv, 896 + 56 * sl, ra, fb);
                }
            }
            asm volatile("barrier.cluster.wait.aligned;" ::: "memory");
            cw_target = (ld_word(g_cw + sl * 32) & ~15u) + 16;
#pragma unroll 1
            for (int k = 0; k < 2; k++) {
                const int n = t128 + 32 * k;
                int m = n - 2 - (n > PACK);
                const bool packed = m >= 30 ? (m < 38 || m >= 52) : m >= 22;
                if (m >= 30) m -= 30;
                if (n == PACK) m = tile < 8 ? tile : tile + 14;
                const int rot = n < 8 ? 0 : pr;
                const int ra = 112 * kblk(rot, m & 3), rb = 112 * kblk(rot, 2 * m & 3), rc = 112 * kblk(rot, (2 * m + 1) & 3);
                int kind = 0, m0, m1, c0, c1, r0, r1;
                if (m < 4) { m0 = m1 = 1; c0 = 448 + 56 * sl; c1 = c0 + 448; r0 = r1 = ra; }
                else if (m < 8) { m0 = m1 = m < 6 ? 1 : 2; c0 = c1 = 56 * sl; r0 = rb; r1 = rc; }
                else if (m < 20) { m0 = 3; m1 = 4; c0 = c1 = 224 * sl + 32 * hr + 64 * ((m - 8) >> 2); r0 = r1 = ra; }
                else if (m < 22) { kind = 2; m0 = 5; m1 = 6; c0 = c1 = 224 * sl + (hr ? 0 : 192); r0 = rb; r1 = rc; }
                else { m0 = m1 = 7; c0 = c1 = 56 * (2 * ((pr + (m >> 1) - 10) & 3) + hr); r0 = 224 * (sl ^ (m & 1)); r1 = r0 + 112; }
                if (packed) { kind = 1; r0 = sl * 16 + (m < 8 ? m : m - 14); r1 = 0; }
                e0[0] = e0[1]; e1[0] = e1[1];
                e0[1] = kind | (m0 << 2) | (m1 << 6) | (c0 << 10) | (c1 << 21);
                e1[1] = r0 | (r1 << 16);
            }
        } else {
            const int j = t128 - 32;
            asm volatile("barrier.cluster.wait.aligned;" ::: "memory");
            uint2 wv[7];
            const int k = j < 56 ? j : 55, hh = k >= 28;
#pragma unroll
            for (int i = 0; i < 7; i++) wv[i] = __ldg(reinterpret_cast<const uint2*>(w_phi + (sl * 56 + k) * 28) + i);
#pragma unroll 1
            for (int i = j; i < 7168 / 16; i += 96) sts4(sb + OFF_WPHI + i * 16, 0, 0, 0, 0);
            bar_sync(5, 96);
            if (j < 56) {
                uint32_t a4[4];
#pragma unroll
                for (int q = 0; q < 4; q++) a4[q] = sb + OFF_WPHI + (4 * hh + q) * 128 + ((((k >> 3) ^ (4 * hh + q)) & 7) << 4) + (k & 7) * 2;
                FOR14(const uint32_t v = (t & 1) ? wv[t >> 1].y : wv[t >> 1].x;
                      asm volatile("{ .reg .b16 l, h; mov.b32 {l, h}, %2; st.shared.u16 [%0+%3], l; st.shared.u16 [%1+%3], h; }"
                                   ::"r"(a4[t >= 7 ? 2 : 0]), "r"(a4[t >= 7 ? 3 : 1]), "r"(v), "n"((t % 7) * 1024) : "memory"));
            }
            __syncwarp();
            fence_async();
            bar_arrive(1, 224);
            bar_arrive(9, 224);
            if (w == 1) {
                mbar_wait(BAR(2), 0);
                mbar_wait(BAR(2), 1);
                const int b = blockIdx.x;
                asm volatile(ELECT "cp.async.bulk.prefetch.L2.global [%0], %1; }" ::"l"(wg + b * 6272), "r"(12544) : "memory");
                asm volatile(ELECT "cp.async.bulk.prefetch.L2.global [%0], %1; }" ::"l"(wu + b * 6272), "r"(12544) : "memory");
                asm volatile(ELECT "cp.async.bulk.prefetch.L2.global [%0], %1; }" ::"l"(wd + b * 6272), "r"(12544) : "memory");
            }
        }
        uint32_t kseq = ld_word(g_c1 + (sl * 8 * 16 + tile) * 32);
        int slot = 0, ph = 0, n = NST;
#pragma unroll 1
        for (int layer = 0; layer < 3; layer++) {
            if (w == 0) {
                const int nend = layer == 0 ? 11 : (layer == 1 ? 42 : 63);
#pragma unroll 1
                for (; n < nend; n++) {
                const uint32_t w0 = __shfl_sync(0xffffffffu, n < 32 ? e0[0] : e0[1], n & 31), w1 = __shfl_sync(0xffffffffu, n < 32 ? e1[0] : e1[1], n & 31);
                const uint32_t dst = sb + slot * STAGE, fb = BAR(n == PACK ? B_PACK : slot);
                const CUtensorMap* m0 = &maps.x + ((w0 >> 2) & 15);
                const CUtensorMap* m1 = &maps.x + ((w0 >> 6) & 15);
                const int c0 = (w0 >> 10) & 2047, c1 = w0 >> 21, r0 = w1 & 0xffff, r1 = w1 >> 16;
                if (n == 25) {
                    int it = 0;
                    uint32_t v;
                    do { asm volatile("ld.acquire.gpu.global.u32 %0, [%1];" : "=r"(v) : "l"(g_cw + sl * 32) : "memory"); } while ((int)(v - cw_target) < 0 && ++it < 0x400000);
                    asm volatile("fence.proxy.async.global;" ::: "memory");
                    __syncwarp();
                }
                mbar_wait(BAR(B_EMPTY + slot), ph);
                __syncwarp();
                asm volatile(ELECT "mbarrier.arrive.expect_tx.shared::cta.b64 _, [%0], %1; }" ::"r"(fb), "r"(STAGE) : "memory");
                if ((w0 & 3) == 0) {
                    tma2d(dst, m0, c0, r0, fb);
                    tma2d(dst + HALF, m1, c1, r1, fb);
                } else if (w0 & 1) {
                    asm volatile(ELECT "cp.async.bulk.shared::cluster.global.mbarrier::complete_tx::bytes [%0], [%1], %2, [%3]; }"
                                 ::"r"(dst), "l"(reinterpret_cast<const char*>(g_wp) + (size_t)r0 * STAGE), "r"(STAGE), "r"(fb) : "memory");
                } else {
                    tma2d(dst, m0, c0, r0, fb); tma2d(dst + 7168, m0, c0, r1, fb);
                    tma2d(dst + HALF, m1, c0, r0, fb); tma2d(dst + HALF + 7168, m1, c0, r1, fb);
                }
                if (n == PACK) asm volatile(ELECT "mbarrier.arrive.shared::cta.b64 _, [%0]; }" ::"r"(BAR(slot)) : "memory");
                if (++slot == NST) { slot = 0; ph ^= 1; }
                }
            } else if (w == 1 && layer == 1) {
                constexpr int ps = PACK % NST;
                mbar_wait(BAR(B_PACK), 0);
                asm volatile("{ .reg .pred e; elect.sync _|e, 0xffffffff;\n"
                             "@e cp.async.bulk.global.shared::cta.bulk_group [%0], [%1], %2;\n"
                             "@e cp.async.bulk.commit_group;\n"
                             "@e cp.async.bulk.wait_group.read 0;\n"
                             "@e mbarrier.arrive.shared::cta.b64 _, [%3], 8;\n"
                             "@e cp.async.bulk.wait_group 0;\n"
                             "@e fence.proxy.async.global;\n"
                             "@e red.release.gpu.global.add.u32 [%4], 1; }"
                             ::"l"(reinterpret_cast<char*>(g_wp) + (size_t)(sl * 16 + tile) * STAGE), "r"(sb + ps * STAGE), "r"(STAGE), "r"(BAR(B_EMPTY + ps)), "l"(g_cw + sl * 32) : "memory");
                __syncwarp();
            }
            if (layer < 2) {
            const uint32_t tag = layer ^ 1;
            kseq++;
            bar_sync(7, 384);
            ASTAMP(0);
            if (tile < 15) {
                const int sq = lane >> 3, pk = 8 * w + (lane & (tile == 14 ? 3 : 7));
                uint32_t v[16];
                if (layer == 0) poll_cnt(g_c1 + ((sl * 8 + (w >> 1) * 4 + (tile >> 2)) * 16 + (lane & 15)) * 32, kseq);
                ASTAMP(1);
                poll4_kv<32>(v, g_kv1 + ((sl * 16 + tile) * 16 + 4 * sq) * 32 + pk, tag);
#pragma unroll
                for (int k = 0; k < 4; k++) {
                    float lo = (bf_lo(v[k]) + bf_lo(v[4 + k])) + (bf_lo(v[8 + k]) + bf_lo(v[12 + k]));
                    float hi = (bf_hi(v[k]) + bf_hi(v[4 + k])) + (bf_hi(v[8 + k]) + bf_hi(v[12 + k]));
                    lo += __shfl_xor_sync(0xffffffffu, lo, 8); hi += __shfl_xor_sync(0xffffffffu, hi, 8);
                    lo += __shfl_xor_sync(0xffffffffu, lo, 16); hi += __shfl_xor_sync(0xffffffffu, hi, 16);
                    v[k] = pack2(lo, hi);
                }
                if (sq == 0) st_pkt<0>(g_kv2 + sl * 512 + 32 * tile + pk, settag(v[0], tag), v[1], v[2], v[3]);
            }
            ASTAMP(2);
            {
                const int item = t128 < 112 ? t128 : 112 + (t128 & 3), d = item >> 1;
                const int cc = t128 < 112 ? 2 * (d >= 28) + (item & 1) : item - 112;
                const int r = t128 < 112 ? d : 56 + (cc >> 1) + 2 * ((t128 - 112) >> 2);
                uint32_t ra = sb + OFF_KVB + r * 128 + 4 * cc, rx = (r & 7) << 4;
                asm volatile("" : "+r"(ra), "+r"(rx));
                FOR14(asm volatile("st.shared.u32 [%0+%2], %1;" ::"r"((ra ^ 8) + (((t & 7) << 4) ^ rx)), "r"(0), "n"((t >> 3) * 8192) : "memory"));
                uint32_t v[16];
                asm volatile("" : "+r"(ra), "+r"(rx));
                poll4_kv<8>(v, g_kv2 + sl * 512 + (item >> 3) * 32 + (item & 7), tag);
                FOR14(asm volatile("st.shared.u32 [%0+%2], %1;" ::"r"(ra + (((t & 7) << 4) ^ rx)), "r"(v[t < 7 ? t : t + 1]), "n"((t >> 3) * 8192) : "memory"));
                fence_async();
            }
            bar_arrive(3, 384);
            ASTAMP(3);
            }
        }
    } else {
        asm volatile("setmaxnreg.inc.sync.aligned.u32 232;");
        int lane = fresh_tid() & 31, prf = pr;
#define pr prf
#define g (lane >> 2)
#define c (lane & 3)
#define t128 (w * 32 + lane)
        const int wu = __shfl_sync(0xffffffffu, fresh_tid() >> 5, 0), w = wu & 3;
        const uint32_t xoff = __shfl_sync(0xffffffffu, (3 * PLANE + ((tile * 2 + wgi) * 8) * 512 + w * 128) * 16, 0);
        char* xu = reinterpret_cast<char*>(g_ex) + xoff;
#define FRESH() asm volatile("" : "+l"(xu), "+r"(lane), "+r"(prf))
#define xp0 (reinterpret_cast<uint4*>(xu) + lane)
        const uint32_t hbuf = sb + OFF_H + wgi * STAGE;
        uint32_t slot = 0, ph = 0, eb1 = 0, eb2 = 0, ackph = 0, rcvph = 0, gatph = 0, swp = 0;
        uint32_t ppid = 6;
#define cx(s) (reinterpret_cast<uint32_t*>(reinterpret_cast<uint4*>(xu) + PL(1) + 112 + (s) * 512))
#define stp (reinterpret_cast<uint4*>(xu) + g + PL(0) + 112)
        uint32_t seq = ld_word(cx(sl));
        uint32_t kseq = ld_word(g_c1 + ((sl * 8 + wu) * 16 + tile) * 32);
        uint32_t stag = ld_word(reinterpret_cast<const uint32_t*>(stp + sl * 512) + 3) & 1;
        asm volatile("barrier.cluster.wait.aligned;" ::: "memory");
        STAMP(1);
        uint32_t X[14];
        const uint32_t x0row = (w < 2 ? hbuf : sb + wgi * STAGE) + ((w & 1) * 16 + (lane & 15)) * 128;
        mbar_wait(BAR(wgi), 0);
        STAMP(51);
#pragma unroll
        for (int j = 0; j < 4; j++) {
            const int G = 7 * sl + min(2 * j + (lane >> 4), 6);
            uint32_t q2, q3;
            asm volatile("ldmatrix.sync.aligned.m8n8.x4.shared.b16 {%0,%1,%2,%3}, [%4];" : "=r"(X[4 * j]), "=r"(X[4 * j + 1]), "=r"(q2), "=r"(q3)
                         : "r"(x0row + (G >> 3) * 4096 + (((G ^ lane) & 7) << 4)) : "memory");
            if (j < 3) { X[(4 * j + 2) % 14] = q2; X[(4 * j + 3) % 14] = q3; }
        }
#define PUSH_SLICE(W)                                                                          \
    {                                                                                          \
        if (t128 == 0) mbar_expect_tx(BAR(B_RECV + wgi), 7168);                                \
        PUSH_BEGIN();                                                                          \
        const uint32_t ra = mapa(hbuf + 24576 + t128 * 16, hr ^ 1), rb = mapa(sb + OFF_XR + wgi * 3072, hr ^ 1), rbar = mapa(BAR(B_RECV + wgi), hr ^ 1); \
        st_async4(ra, W[0], W[1], W[2], W[3], rbar);                                           \
        st_async4(ra + 2048, W[4], W[5], W[6], W[7], rbar);                                    \
        st_async4(rb + t128 * 16, W[8], W[9], W[10], W[11], rbar);                             \
        asm volatile("st.async.weak.shared::cluster.mbarrier::complete_tx::bytes.v2.b32 [%0], {%1,%2}, [%3];" ::"r"(rb + 2048 + t128 * 8), "r"(W[12]), "r"(W[13]), "r"(rbar) : "memory"); \
    }
#define PULL_SLICE(W)                                                                          \
    {                                                                                          \
        uint32_t t0, t1;                                                                       \
        mbar_wait(BAR(B_RECV + wgi), rcvph);                                                   \
        rcvph ^= 1;                                                                            \
        lds4(&A[1][0], hbuf + 24576 + t128 * 16);                                              \
        lds4(&A[1][4], hbuf + 26624 + t128 * 16);                                              \
        lds4(&A[1][8], sb + OFF_XR + wgi * 3072 + t128 * 16);                                  \
        asm volatile("ld.shared.v2.u32 {%0,%1}, [%2];" : "=r"(t0), "=r"(t1) : "r"(sb + OFF_XR + wgi * 3072 + 2048 + t128 * 8) : "memory"); \
        _Pragma("unroll") for (int i = 0; i < 12; i++) A[0][i] = (i & 3) ? W[i] : W[i] & ~1u;  \
        A[1][0] &= ~1u; A[1][4] &= ~1u; A[1][8] &= ~1u;                                        \
        A[0][12] = (hr ? t0 : W[12]) & ~1u; A[0][13] = hr ? t1 : W[13];                        \
        A[1][12] = (hr ? W[12] : t0) & ~1u; A[1][13] = hr ? W[13] : t1;                        \
        asm volatile("" : RW4(A[0], 0), RW4(A[0], 4), RW4(A[0], 8), RW2(A[0], 12), RW4(A[1], 0), RW4(A[1], 4), RW4(A[1], 8), RW2(A[1], 12)); \
        swp = hr * 448;                                                                        \
    }
#define SWB(b, t, db, sh) ((b) == 0 && (t) < 6 ? ((t) < 3 ? db##p : db##m) : db)
#define DECL_DB(b, MK, lbo, sh) const uint64_t db = MK(0, lbo, R_ADJ), dbp = (b) == 0 ? MK(0, lbo, R_ADJ + (swp >> (sh))) : db, dbm = (b) == 0 ? MK(0, lbo, R_ADJ - (swp >> (sh))) : db;
#define PPB 2
#define PP_WAIT() if (wgi == 1) { bar_sync(ppid, 256); ppid ^= 14; }
#define PP_GO() if (wgi == 0) { bar_arrive(ppid, 256); ppid ^= 14; }
#define GAT_DST(B, s2) ((B) == 1 ? hbuf + w * 3584 + (s2) * 1792 : ((s2) ? sb + OFF_KVB + wgi * 8192 : hbuf + 14336) + w * 1792)
#define GAT_ISSUE(B, base)                                                                     \
    {                                                                                          \
        const char* gs = xu + ((base) + kblk(pr, B) * 1024) * 16;                              \
        asm volatile("{ .reg .pred e; elect.sync _|e, 0xffffffff;\n"                           \
                     "@e mbarrier.arrive.expect_tx.shared::cta.b64 _, [%3], 3584;\n"           \
                     "@e cp.async.bulk.shared::cluster.global.mbarrier::complete_tx::bytes [%0], [%2], 1792, [%3];\n" \
                     "@e cp.async.bulk.shared::cluster.global.mbarrier::complete_tx::bytes [%1], [%2+8192], 1792, [%3]; }" \
                     ::"r"(GAT_DST(B, 0)), "r"(GAT_DST(B, 1)), "l"(gs), "r"(BAR(B_GAT + wu * 2 + ((B) >> 1))) : "memory"); \
        __syncwarp();                                                                          \
    }
#define GAT_FETCH(B)                                                                           \
    {                                                                                          \
        mbar_wait(BAR(B_GAT + wu * 2 + ((B) >> 1)), (gatph >> (B)) & 1);                          \
        gatph ^= 1 << (B);                                                                     \
        _Pragma("unroll") for (int s2 = 0; s2 < 2; s2++) {                                     \
            const uint32_t ga = GAT_DST(B, s2) + lane * 16;                                    \
            lds4(&A[2 * (B) + s2][0], ga); lds4(&A[2 * (B) + s2][4], ga + 512); lds4(&A[2 * (B) + s2][8], ga + 1024); \
            asm volatile("ld.shared.v2.u32 {%0,%1}, [%2];" : "=r"(A[2 * (B) + s2][12]), "=r"(A[2 * (B) + s2][13]) : "r"(ga - lane * 8 + 1536) : "memory"); \
        }                                                                                      \
    }
#define LATE_ARRIVE() do { if (lane == 0) mbar_arrive(BAR(B_LATE)); } while (0)
#define LATE_WAIT() do { mbar_wait(BAR(B_LATE), gatph & 1); gatph ^= 1; } while (0)
#define PT 3
#define PREP(b, t, remote)                                                                     \
    if constexpr (P13 && (b) == 1 && (t) == P13) {                                             \
        wg_commit();                                                                           \
        if (remote) blk_check<3>(A, BLK(xsrc, 3), lane, xtag);                                 \
        normalize<3>(A, k0, k1);                                                               \
        asm volatile("" : RW4(A[6], 0), RW4(A[6], 4), RW4(A[6], 8), RW2(A[6], 12), RW4(A[7], 0), RW4(A[7], 4), RW4(A[7], 8), RW2(A[7], 12)); \
        wg_fence();                                                                            \
    }                                                                                          \
    if constexpr ((b) < (P13 ? 2 : 3) && (t) == ((P13 && (b) == 1) ? 1 : PT)) {                \
        wg_commit();                                                                           \
        if constexpr (PP0 && (b) == 0) { PP_GO() }                                             \
        STAMP(74 + 6 * (step & 1) + 2 * (b));                                                  \
        if (remote) {                                                                          \
            if constexpr ((b) == 0) { blk_load<2>(A, BLK(xsrc, 2), lane); GAT_FETCH(1) }       \
            blk_check<((b) + 1) & 3>(A, BLK(xsrc, (b) + 1), lane, xtag);                       \
            if constexpr ((b) == 0) blk_load<3>(A, BLK(xsrc, 3), lane);                        \
        }                                                                                      \
        STAMP(75 + 6 * (step & 1) + 2 * (b));                                                  \
        normalize<((b) + 1) & 3>(A, k0, k1);                                                   \
        asm volatile("" : RW4(A[(2 * (b) + 2) & 7], 0), RW4(A[(2 * (b) + 2) & 7], 4), RW4(A[(2 * (b) + 2) & 7], 8), RW2(A[(2 * (b) + 2) & 7], 12), \
                          RW4(A[(2 * (b) + 3) & 7], 0), RW4(A[(2 * (b) + 3) & 7], 4), RW4(A[(2 * (b) + 3) & 7], 8), RW2(A[(2 * (b) + 3) & 7], 12)); \
        wg_fence();                                                                            \
    }
#define X0_BLOCK(b)                                                                            \
    { const int rr = lane & 7, hi = lane >> 4;                                                 \
    const uint32_t rowa = (w < 2 ? hbuf : sb + wgi * STAGE) + ((w & 1) * 16 + (lane & 15)) * 128; \
    FOR7(constexpr int G = 14 * (b) + (t < 3 ? 2 * t : (t < 6 ? 2 * t + 1 : 6));               \
         uint32_t q0, q1, q2, q3;                                                              \
         const uint32_t ad = t < 6 ? rowa + (((((G & 7) + hi) ^ rr) & 7) << 4) + ((G & 7) == 7 ? hi * 4096 : 0) : rowa + ((G + 7 * hi) >> 3) * 4096 + ((((G + 7 * hi) ^ rr) & 7) << 4); \
         asm volatile("ldmatrix.sync.aligned.m8n8.x4.shared.b16 {%0,%1,%2,%3}, [%4+%5];" : "=r"(q0), "=r"(q1), "=r"(q2), "=r"(q3) \
                      : "r"(ad), "n"(t < 6 ? (G >> 3) * 4096 : 0) : "memory");                 \
         if (t < 3) { A[2 * (b)][4 * t] = q0; A[2 * (b)][4 * t + 1] = q1; A[2 * (b)][4 * t + 2] = q2; A[2 * (b)][4 * t + 3] = q3; } \
         else if (t < 6) { A[2 * (b) + 1][(4 * t - 12) & 15] = q0; A[2 * (b) + 1][((4 * t - 12) & 15) + 1] = q1; A[2 * (b) + 1][((4 * t - 12) & 15) + 2] = q2; A[2 * (b) + 1][((4 * t - 12) & 15) + 3] = q3; } \
         else { A[2 * (b)][12] = q0; A[2 * (b)][13] = q1; A[2 * (b) + 1][12] = q2; A[2 * (b) + 1][13] = q3; }); }
#define BLK(base, b) ((base) + kblk(pr, b) * 1024)

#pragma unroll 1
        for (int step = 0; step < 4; step++) {
            FRESH();
            const uint32_t tag = (step >> 1) ^ 1;
            const int so = (step >> 1) * 24 + (step & 1) * 12;
            (void)so;
            uint32_t A[8][14];
            uint4* const xsrc = xp0 + ((step & 1) ? PL(2) : PL(0));
            const uint32_t xtag = (step & 1) ? tag : ((seq >> 3) & 1) ^ 1;
            uint32_t xbits;
            {
                float st[4];
                slice_stats(X, st);
                stag ^= 1;
                xbits = x_bits(X);
                tag_slice(X, xtag);
                if (step) send_slice<0>(xsrc + sl * 512, lane, X);
                if (c == 0) st_pkt<0>(stp + sl * 512, __float_as_uint(st[0]), __float_as_uint(st[1]), __float_as_uint(st[2]), settag(__float_as_uint(st[3]), stag));
            }
            STAMP(2 + so);
            uint32_t sv[8];
            if (step == 0) {
                X0_BLOCK(0) X0_BLOCK(1) X0_BLOCK(2) X0_BLOCK(3)
                mbar_wait(BAR(wgi ^ 1), 0);
                R_NEXT();
                R_NEXT();
                R_RELEASE(2);
                stat_load(sv, stp + c * 1024);
                stat_check(sv, stp + c * 1024, stag);
                STAMP(52 + step);
            } else {
                kill<14>(A[2]); kill<14>(A[3]); kill<14>(A[4]); kill<14>(A[5]); kill<14>(A[6]); kill<14>(A[7]);
                PUSH_SLICE(X)
                stat_load(sv, stp + c * 1024);
                PULL_SLICE(X)
                stat_check(sv, stp + c * 1024, stag);
                STAMP(52 + step);
                GAT_ISSUE(1, (step & 1) ? PL(2) : PL(0))
            }
            LnCoef k0, k1;
            {
                k0 = ln_coef(__uint_as_float(sv[0]) + __uint_as_float(sv[4]), __uint_as_float(sv[1]) + __uint_as_float(sv[5]));
                k1 = ln_coef(__uint_as_float(sv[2]) + __uint_as_float(sv[6]), __uint_as_float(sv[3] & ~1u) + __uint_as_float(sv[7] & ~1u));
            }
            STAMP(3 + so);
            GSTAMP(70 + step);

            if ((step & 1) == 0) {
                float tq[28];
                {
                    float av[28];
#define KV_BLOCK(b)                                                                           \
    if ((b) == 1) R_RELEASE(2);                                                               \
    if ((b) == 2) { PUSH_ACK(); wg_wait<(P13 ? 3 : 2)>(); R_RELEASE(2); }                                 \
    R_WAIT();                                                                                 \
    if ((b) == PPK || (PP0 && (b) == 0)) { PP_WAIT() }                                        \
    { DECL_DB(b, BASE128, 16, 0)                                                              \
    wg_fence();                                                                               \
    FOR7(mma_rs56<1, D128(0, t)>(tq, AQ(A, b, t), (b) + t > 0, SWB(b, t, db, 0));             \
         mma_rs56<1, D128(HALF, t)>(av, AQ(A, b, t), (b) + t > 0, SWB(b, t, db, 0));          \
         PREP(b, t, step)); }                                                                 \
    wg_commit();                                                                              \
    if ((b) == 3 && PPK < 4) { PP_GO() }                                                      \
    R_NEXT();
                    normalize<0>(A, k0, k1);
                    KV_BLOCK(0) KV_BLOCK(1) KV_BLOCK(2) KV_BLOCK(3)
                    wg_wait<0>();
                    if (lane < 3) mbar_arrive(BAR(B_EMPTY + (slot + NST - 1 - lane) % NST));
                    STAMP(4 + so);
                    WSUM(80 + 7 * (step >> 1));
                    const int m = lane >> 3, rr = lane & 7;
                    const uint32_t rowa = hbuf + 16384 + (w * 16 + rr + 8 * (m & 1)) * 128;
                    const uint32_t one = c == 0 ? 0x00003f80u : 0u;
                    if (step == 0) { bar_sync(wgi ? 9 : 1, 224); }
#pragma unroll
                    for (int j = 0; j < 4; j++) {
                        const uint32_t a = rowa + (((2 * j + (m >> 1)) ^ rr) << 4);
                        if (j < 3) stsm4(a, pack2(av[8 * j], av[8 * j + 1]), pack2(av[8 * j + 2], av[8 * j + 3]), pack2(av[8 * j + 4], av[8 * j + 5]), pack2(av[8 * j + 6], av[8 * j + 7]));
                        else stsm4(a, pack2(av[24], av[25]), pack2(av[26], av[27]), one, one);
                    }
                }
                uint32_t PH[28];
                int it = 1;
#pragma unroll 1
                do {
                    float pp[28];
                    phi_gemm(tq, pp);
                    dual_softmax(pp, PH);
                    if (((trips >> (it + 1)) & 1) == 0) continue;
                    {
                        const int m = lane >> 3, rr = lane & 7;
                        const uint32_t rowa = hbuf + (w * 16 + rr + 8 * (m & 1)) * 128;
#pragma unroll
                        for (int j = 0; j < 7; j++) {
                            const int cg = 2 * j + (m >> 1), hi = cg >= 7;
                            stsm4(rowa + hi * 8192 + (((cg - 7 * hi) ^ rr) << 4), PH[4 * j], PH[4 * j + 1], PH[4 * j + 2], PH[4 * j + 3]);
                        }
                    }
                    fence_async();
                    STAMP(5 + so);
#define Q_STAGE(b0)                                                                           \
    R_WAIT();                                                                                 \
    { DECL_DB(b0, BASE128, 16, 0)                                                             \
    wg_fence();                                                                               \
    FOR7(mma_rs56<1, D128(0, t)>(tq, AQ(A, b0, t), (b0) + t > 0, SWB(b0, t, db, 0)));         \
    FOR7(mma_rs56<1, D128(HALF, t)>(tq, AQ(A, (b0) + 1, t), 1, db)); }                        \
    wg_commit();                                                                              \
    R_NEXT();
                    if (QE && wgi == 0) { kill<28>(tq); Q_STAGE(0) Q_STAGE(2) wg_wait<1>(); R_RELEASE(2); wg_wait<0>(); R_RELEASE(1); }
                    bar_sync(2, 256);
                    float kv[28];
                    const uint64_t da = BASE128(OFF_H + 16384, 16, 0), dbk = BASE128(OFF_H, 16, wgi * 512);
                    wg_fence();
                    FOR8(constexpr uint64_t o = ((t >> 2) * STAGE + (t & 3) * 2048) >> 4; mma_ss56_tt<o, o>(kv, t > 0, da, dbk));
                    wg_commit();
                    wg_wait<0>();
#pragma unroll
                    for (int hf = 0; hf < 2; hf++) {
                        const int d = 16 * w + g + 8 * hf;
                        if ((d < 56 && (d >= 28) == (c >= 2)) || d == 56) {
                            const int item = d < 56 ? 2 * d + (c & 1) : 112 + c;
                            uint4* dst = g_kv1 + ((sl * 16 + (item >> 3)) * 16 + tile) * 32 + wgi * 16 + (item & 7);
#define KVW(i) pack2(kv[4 * (i) + 2 * hf], kv[4 * (i) + 2 * hf + 1])
                            st_pkt<0>(dst, settag(KVW(0), tag), KVW(1), KVW(2), KVW(3));
                            st_pkt<8>(dst, settag(KVW(4), tag), KVW(5), KVW(6), 0u);
                        }
                    }
                    __syncwarp();
                    kseq++;
                    if (lane == 0) st_word(g_c1 + ((sl * 8 + wu) * 16 + tile) * 32, kseq);
                    bar_arrive(7, 384);
                    STAMP(6 + so);
                    if (!QE || wgi == 1) { kill<28>(tq); Q_STAGE(0) Q_STAGE(2) wg_wait<1>(); R_RELEASE(2); wg_wait<0>(); R_RELEASE(1); }
                    STAMP(7 + so);
                    kill<28>(PH);
                } while (((trips >> (++it)) & 1));
                STAMP(8 + so);
                FRESH();
                if (step) {
                    slice_load<PL(0)>(X, xp0 + sl * 512, lane);
                } else {
                    const uint32_t* xp = reinterpret_cast<const uint32_t*>(x_in + (size_t)(tile * 128 + wu * 16 + g) * 448 + 56 * sl + 2 * c);
#pragma unroll
                    for (int i = 0; i < 7; i++) { X[2 * i] = __ldg(xp + 4 * i); X[2 * i + 1] = __ldg(xp + 4 * i + 8 * 224); }
                }
                bar_sync(3, 384);
                STAMP(9 + so);
                const uint4* const osrc = xp0 + PL(1);
                {
                    float nm[32];
                    const uint64_t db = BASE128(OFF_KVB, 16, 0);
                    wg_fence();
                    FOR7(mma_rs64<0, ((t >> 2) * 8192 + (t & 3) * 32) / 16>(nm, PH[4 * t], PH[4 * t + 1], PH[4 * t + 2], PH[4 * t + 3], t > 0, db));
                    wg_commit();
                    wg_wait<0>();
                    LATE_ARRIVE();
                    const float i00 = rcp(nm[28] + 1e-6f), i01 = rcp(nm[29] + 1e-6f), i10 = rcp(nm[30] + 1e-6f), i11 = rcp(nm[31] + 1e-6f);
                    const float m0 = c >= 2 ? i01 : i00, m1 = c >= 2 ? i11 : i10;
                    uint32_t O[14];
#pragma unroll
                    for (int i = 0; i < 7; i++) {
                        const float f0 = i < 3 ? i00 : (i > 3 ? i01 : m0), f1 = i < 3 ? i10 : (i > 3 ? i11 : m1);
                        O[2 * i] = pack2(nm[4 * i] * f0, nm[4 * i + 1] * f0);
                        O[2 * i + 1] = pack2(nm[4 * i + 2] * f1, nm[4 * i + 3] * f1);
                    }
                    if (OST) { PP_WAIT() }
                    tag_slice(O, tag);
                    send_slice<PL(1)>(xp0 + sl * 512, lane, O);
                    seq++;
                    if (lane == 0) st_word(cx(sl), seq);
                    STAMP(10 + so);
                    PUSH_SLICE(O)
                    if (OST == 1) { PP_GO() }
                    const uint32_t cv = ld_word(cx(lane & 7));
                    PULL_SLICE(O)
                    LATE_WAIT();
                    check_cnt(cv, cx(lane & 7), seq);
                    if (OST == 2) { PP_GO() }
                    STAMP(56 + (step >> 1));
                    GAT_ISSUE(1, PL(1))
                    GAT_ISSUE(3, PL(1))
                    blk_load<2>(A, BLK(osrc, 2), lane);
                }
                float ao[28];
#define WO_BLOCK(b)                                                                           \
    if ((b) > 0) blk_check<b>(A, BLK(osrc, b), lane, tag);                                    \
    if (((b) & 1) == 0) R_WAIT();                                                             \
    { DECL_DB(b, BASE128, 16, 0)                                                              \
    wg_fence();                                                                               \
    FOR7(mma_rs56<1, D128(((b) & 1) * HALF, t)>(ao, AQ(A, b, t), (b) + t > 0, SWB(b, t, db, 0))); } \
    wg_commit();                                                                              \
    if ((b) & 1) R_NEXT();
                WO_BLOCK(0)
                STAMP(11 + so);
                GAT_FETCH(1)
                WO_BLOCK(1)
                WO_BLOCK(2)
                GAT_FETCH(3)
                WO_BLOCK(3)
                PUSH_ACK();
                wg_wait<0>();
                R_RELEASE(2);
                STAMP(12 + so);
                WSUM(86 + 7 * (step >> 1));
                x_fix(X, xbits);
#pragma unroll
                for (int i = 0; i < 14; i++) X[i] = pack2(bf_lo(X[i]) + ao[2 * i], bf_hi(X[i]) + ao[2 * i + 1]);
            } else {
                uint32_t H[56];
                float ag[64];
#define F1_EPI(dst, ng, ag)                                                                    \
    _Pragma("unroll") for (int i = 0; i < 2 * (ng); i++)                                       \
        (dst)[i] = pack2(geglu(ag[2 * i], ag[4 * (ng) + 2 * i]), geglu(ag[2 * i + 1], ag[4 * (ng) + 2 * i + 1]));
#define H_PUSH(h0, off) st_async4(rem_h + (off), H[h0], H[(h0) + 1], H[(h0) + 2], H[(h0) + 3], mapa(BAR(B_RECV2 + wgi), hr ^ 1));
#define F1_BLOCK(b, first)                                                                     \
    if ((first) && (b) == 1) R_RELEASE(2);                                                     \
    if ((first) && (b) == 2) PUSH_ACK();                                                       \
    R_WAIT();                                                                                  \
    if ((b) == ((first) ? PPF : PPB) || (PP0 && (first) && (b) == 0)) { PP_WAIT() }            \
    { DECL_DB(b, BASE128, HALF, 0)                                                             \
    wg_fence();                                                                                \
    FOR7(mma_rs128<1, D128(0, t)>(ag, AQ(A, b, t), (b) + t > 0, SWB(b, t, db, 0));             \
         if constexpr (first) { PREP(b, t, true) }); }                                         \
    wg_commit();                                                                               \
    if ((b) == 3) { PP_GO() }                                                                  \
    if ((b) > 0) { wg_wait<1>(); R_RELEASE(1); }       \
    R_NEXT();
                normalize<0>(A, k0, k1);
                F1_BLOCK(0, true) F1_BLOCK(1, true) F1_BLOCK(2, true) F1_BLOCK(3, true)
                if (t128 == 0) { mbar_expect_tx(BAR(B_RECV + wgi), 16384); mbar_expect_tx(BAR(B_RECV2 + wgi), 12288); }
                PUSH_BEGIN();
                wg_wait<0>();
                R_RELEASE(1);
                int p = 0;
#pragma unroll 1
                do {
                    F1_EPI(H + 32, 8, ag)
                    STAMP(4 + p + so);
                    WSUM(81 + p + 7 * (step >> 1));
                    if (((trips >> (p + 1)) & 1) == 0) continue;
                    {
                        const uint32_t pk = (p ? hbuf + 16384 : sb + OFF_KVB + wgi * 8192) + w * 2048;
#pragma unroll
                        for (int k = 0; k < 4; k++) sts4(pk + k * 512 + lane * 16, H[32 + 4 * k], H[33 + 4 * k], H[34 + 4 * k], H[35 + 4 * k]);
                        fence_async();
                        __syncwarp();
                        asm volatile(ELECT "cp.async.bulk.shared::cluster.shared::cta.mbarrier::complete_tx::bytes [%0], [%1], 2048, [%2]; }"
                                     ::"r"(mapa(hbuf + p * 8192 + w * 2048, hr ^ 1)), "r"(pk), "r"(mapa(BAR(B_RECV + wgi), hr ^ 1)) : "memory");
                    }
                    if (step == 1 && p == PKP) R_NEXT();
                    kill<64>(ag);
                    F1_BLOCK(0, false) F1_BLOCK(1, false) F1_BLOCK(2, false) F1_BLOCK(3, false)
                    wg_wait<0>();
                    R_RELEASE(1);
                    kill<16>(H + 32);
                } while (((trips >> (++p)) & 1));
#pragma unroll
                for (int k = 0; k < 4; k++) lds4(H + 16 + 4 * k, hbuf + 16384 + w * 2048 + k * 512 + lane * 16);
                __syncwarp();
                if (lane == 0) asm volatile("mbarrier.arrive.shared::cluster.b64 _, [%0];" ::"r"(mapa(BAR(B_ACK2 + wgi), hr ^ 1)) : "memory");
                const uint32_t rem_h = mapa(hbuf + w * 2048 + lane * 16, hr ^ 1);
#define F1_LAST(b0)                                                                            \
    R_WAIT();                                                                                  \
    if (b0) { PP_WAIT() }                                                                      \
    { DECL_DB(b0, BASE64, HALF, 1)                                                             \
    wg_fence();                                                                                \
    FOR7(mma_rs64<1, D64(0, t)>(al, AQ(A, b0, t), (b0) + t > 0, SWB(b0, t, db, 1)));           \
    FOR7(mma_rs64<1, D64(7168, t)>(al, AQ(A, (b0) + 1, t), 1, db)); }                          \
    wg_commit();                                                                               \
    if (b0) { PP_GO() }                                                                        \
    R_NEXT();
                float al[32];
                F1_LAST(0)
                mbar_wait(BAR(B_RECV + wgi), rcvph);
                rcvph ^= 1;
                mbar_wait(BAR(B_ACK2 + wgi), step >> 1);
                H_PUSH(32, 16384) H_PUSH(36, 16896)
                F1_LAST(2)
                H_PUSH(40, 17408) H_PUSH(44, 17920)
                wg_wait<1>();
                R_RELEASE(2);
                wg_wait<0>();
                R_RELEASE(1);
                uint32_t HP[56];
#pragma unroll
                for (int k = 0; k < 4; k++) lds4(H + 4 * k, sb + OFF_KVB + wgi * 8192 + w * 2048 + k * 512 + lane * 16);
#pragma unroll
                for (int t = 0; t < 8; t++) lds4(HP + 4 * t, hbuf + (t >> 2) * 8192 + w * 2048 + (t & 3) * 512 + lane * 16);
                F1_EPI(H + 48, 4, al)
                H_PUSH(48, 24576 - w * 1024) H_PUSH(52, 25088 - w * 1024)
                STAMP(7 + so);
                WSUM(84 + 7 * (step >> 1));
                FRESH();
                float acc[28];
                const uint32_t roA = hr ? 256u : 0u, roB = hr ? (uint32_t)-1536 : 0u;
                const uint32_t rpA = hr ? 0u : 256u, rpB = hr ? 0u : (uint32_t)-1536;
                float res[28];
                uint32_t v0[14], v1[14], P[14];
                const uint4* ps = xp0 + sl * 512;
#define F2_OWN_A()                                                                             \
    R_WAIT();                                                                                  \
    d0 = BASE128(0, 16, R_ADJ + roA); d1 = BASE128(0, 16, R_ADJ + roB);                        \
    wg_fence();                                                                                \
    FOR14(if constexpr (t < OT) mma_rs56<1, t * 128>(acc, H[4 * t], H[4 * t + 1], H[4 * t + 2], H[4 * t + 3], t > 0, d0)); \
    wg_commit();
#define F2_OWN_B()                                                                             \
    wg_fence();                                                                                \
    FOR14(if constexpr (t >= OT) mma_rs56<1, t * 128>(acc, H[4 * t], H[4 * t + 1], H[4 * t + 2], H[4 * t + 3], 1, t < 12 ? d0 : d1)); \
    wg_commit();                                                                               \
    R_NEXT();
#define F2_PEER()                                                                              \
    R_WAIT();                                                                                  \
    if (F2PP) { PP_WAIT() }                                                                    \
    d0 = BASE128(0, 16, R_ADJ + rpA); d1 = BASE128(0, 16, R_ADJ + rpB);                        \
    wg_fence();                                                                                \
    FOR14(mma_rs56<1, t * 128>(acc, HP[4 * t], HP[4 * t + 1], HP[4 * t + 2], HP[4 * t + 3], 1, t < 12 ? d0 : d1)); \
    wg_commit();                                                                               \
    if (F2PP) { PP_GO() }                                                                      \
    R_NEXT();
#define F2_TURN(u)                                                                             \
    wg_wait<1>();                                                                              \
    if ((u) < 2 || TDEF < 2) R_RELEASE(2);                                                     \
    wg_wait<0>();                                                                              \
    if ((u) < 2 || TDEF < 1) R_RELEASE(1);                                                     \
    _Pragma("unroll") for (int i = 0; i < 14; i++) P[i] = pack2(acc[2 * i], acc[2 * i + 1]);   \
    tag_slice(P, tag);                                                                         \
    asm volatile("" : RW4(P, 0), RW4(P, 4), RW4(P, 8), RW2(P, 12));                            \
    kill<28>(acc);                                                                             \
    F2_OWN_A()                                                                                 \
    if ((u) == 2) { slice_load<PL(3)>(v0, ps, lane); slice_load<PL(4)>(v1, ps, lane); } \
    send_slice<PL(3 + (u))>(xp0 + (2 * ((pr + (u) + 1) & 3) + hr) * 512, lane, P);             \
    seq++;                                                                                     \
    if (lane == 0) st_word(cx(sl), seq);                                                       \
    __syncwarp();                                                                              \
    STAMP(8 + (u) + so);                                                                       \
    F2_OWN_B()
                uint64_t d0, d1;
                F2_OWN_A()
                F2_OWN_B()
                R_WAIT();
                d0 = BASE128(0, 16, R_ADJ + rpA); d1 = BASE128(0, 16, R_ADJ + rpB);
                wg_fence();
                FOR8(mma_rs56<1, t * 128>(acc, HP[4 * t], HP[4 * t + 1], HP[4 * t + 2], HP[4 * t + 3], 1, d0));
                wg_commit();
                mbar_wait(BAR(B_RECV2 + wgi), step >> 1);
#pragma unroll
                for (int k = 0; k < 4; k++) lds4(HP + 32 + 4 * k, hbuf + 16384 + w * 2048 + k * 512 + lane * 16);
                lds4(HP + 48, hbuf + 24576 + w * 1024 + lane * 16);
                lds4(HP + 52, hbuf + 25088 + w * 1024 + lane * 16);
                if (step == 1) PUSH_ACK();
                wg_fence();
                FOR14(if constexpr (t >= 8) mma_rs56<1, t * 128>(acc, HP[4 * t], HP[4 * t + 1], HP[4 * t + 2], HP[4 * t + 3], 1, t < 12 ? d0 : d1));
                wg_commit();
                R_NEXT();
                F2_TURN(0)
                F2_PEER()
                F2_TURN(1)
                F2_PEER()
                F2_TURN(2)
                if (step == 1) STAMP(64);
                slice_check<PL(3)>(v0, ps, lane, tag);
                slice_check<PL(4)>(v1, ps, lane, tag);
#pragma unroll
                for (int i = 0; i < 14; i++) { res[2 * i] = bf_lo(v0[i]) + bf_lo(v1[i]); res[2 * i + 1] = bf_hi(v0[i]) + bf_hi(v1[i]); }
                slice_load<PL(2)>(X, ps, lane);
                if (step == 1) STAMP(65);
                F2_PEER()
                if (step == 1) STAMP(66);
                poll_cnt(cx(2 * ((pr + 1) & 3) + hr), seq);
                if (step == 1) STAMP(67);
                slice_load<PL(5)>(v0, ps, lane);
                x_fix(X, xbits);
                slice_check<PL(5)>(v0, ps, lane, tag);
                if (lane < TDEF) mbar_arrive(BAR(B_EMPTY + (slot + NST - 3 - lane) % NST));
#pragma unroll
                for (int i = 0; i < 14; i++) { res[2 * i] += bf_lo(v0[i]); res[2 * i + 1] += bf_hi(v0[i]); }
                STAMP(11 + so);
                wg_wait<0>();
                R_RELEASE(2);
                STAMP(12 + so);
                WSUM(85 + 7 * (step >> 1));
#pragma unroll
                for (int i = 0; i < 14; i++) X[i] = pack2(fmaf(res[2 * i] + acc[2 * i], 0.5f, bf_lo(X[i])), fmaf(res[2 * i + 1] + acc[2 * i + 1], 0.5f, bf_hi(X[i])));
            }
        }
        {
            const int m = lane >> 3, rr = lane & 7;
            const uint32_t ob = hbuf + w * 2048, rowa = ob + (rr + 8 * (m & 1)) * 112 + (m >> 1) * 16;
#pragma unroll
            for (int j = 0; j < 3; j++) stsm4(rowa + 32 * j, X[4 * j], X[4 * j + 1], X[4 * j + 2], X[4 * j + 3]);
            asm volatile("stmatrix.sync.aligned.m8n8.x2.shared.b16 [%0], {%1,%2};" ::"r"(ob + (rr + 8 * (m & 1)) * 112 + 96), "r"(X[12]), "r"(X[13]) : "memory");
            fence_async();
            __syncwarp();
            if (lane == 0) {
                asm volatile("cp.async.bulk.tensor.2d.global.shared::cta.bulk_group [%0, {%2, %3}], [%1];" ::"l"(&maps.out), "r"(ob), "r"(56 * sl), "r"(tile * 128 + wu * 16) : "memory");
                asm volatile("cp.async.bulk.commit_group;" ::: "memory");
                asm volatile("cp.async.bulk.wait_group.read 0;" ::: "memory");
            }
        }
        STAMP(50);
        GSTAMP(61);
        PDUMP();
    }
}

#undef g
#undef pr
#undef c
#undef t128

typedef CUresult (*EncodeFn)(CUtensorMap*, CUtensorMapDataType, cuuint32_t, void*, const cuuint64_t*, const cuuint64_t*, const cuuint32_t*,
                             const cuuint32_t*, CUtensorMapInterleave, CUtensorMapSwizzle, CUtensorMapL2promotion, CUtensorMapFloatOOBfill);

static void make_map(EncodeFn enc, CUtensorMap* m, const void* p, uint64_t cols, uint64_t rows, uint32_t bc, uint32_t br, CUtensorMapSwizzle sw) {
    cuuint64_t gd[2] = {cols, rows};
    cuuint64_t gs[1] = {cols * 2};
    cuuint32_t bd[2] = {bc, br};
    cuuint32_t es[2] = {1, 1};
    enc(m, CU_TENSOR_MAP_DATA_TYPE_BFLOAT16, 2, const_cast<void*>(p), gd, gs, bd, es, CU_TENSOR_MAP_INTERLEAVE_NONE, sw,
        CU_TENSOR_MAP_L2_PROMOTION_L2_128B, CU_TENSOR_MAP_FLOAT_OOB_FILL_NONE);
}

extern "C" void kernel_launch(void* const* d_in, const int* in_sizes, int n_in, void* d_out, int out_size) {
    (void)in_sizes; (void)n_in; (void)out_size;
    static EncodeFn enc = nullptr;
    static Scratch* scratch = nullptr;
    if (!enc) {
        void* fn = nullptr;
        cudaDriverEntryPointQueryResult qr;
        cudaGetDriverEntryPoint("cuTensorMapEncodeTiled", &fn, cudaEnableDefault, &qr);
        enc = (EncodeFn)fn;
        cudaGetSymbolAddress((void**)&scratch, g_scratch);
        cudaFuncSetAttribute(fused_kernel, cudaFuncAttributeMaxDynamicSharedMemorySize, SMEM_BYTES);
    }
    Maps maps;
    {
        cuuint64_t gd[3] = {64, 2048, 7};
        cuuint64_t gs[2] = {896, 128};
        cuuint32_t bd[3] = {64, 32, 7};
        cuuint32_t es[3] = {1, 1, 1};
        enc(&maps.x, CU_TENSOR_MAP_DATA_TYPE_BFLOAT16, 3, d_in[0], gd, gs, bd, es, CU_TENSOR_MAP_INTERLEAVE_NONE, CU_TENSOR_MAP_SWIZZLE_128B,
            CU_TENSOR_MAP_L2_PROMOTION_L2_128B, CU_TENSOR_MAP_FLOAT_OOB_FILL_NONE);
    }
    make_map(enc, &maps.out, d_out, 448, 2048, 56, 16, CU_TENSOR_MAP_SWIZZLE_NONE);
    make_map(enc, &maps.qkv, d_in[1], 1344, 448, 64, 112, CU_TENSOR_MAP_SWIZZLE_128B);
    make_map(enc, &maps.wo, d_in[3], 448, 448, 64, 112, CU_TENSOR_MAP_SWIZZLE_128B);
    make_map(enc, &maps.wg, d_in[5], 1792, 448, 64, 112, CU_TENSOR_MAP_SWIZZLE_128B);
    make_map(enc, &maps.wu, d_in[6], 1792, 448, 64, 112, CU_TENSOR_MAP_SWIZZLE_128B);
    make_map(enc, &maps.wg32, d_in[5], 1792, 448, 32, 112, CU_TENSOR_MAP_SWIZZLE_64B);
    make_map(enc, &maps.wu32, d_in[6], 1792, 448, 32, 112, CU_TENSOR_MAP_SWIZZLE_64B);
    make_map(enc, &maps.wd, d_in[7], 448, 1792, 64, 112, CU_TENSOR_MAP_SWIZZLE_128B);
    fused_kernel<<<128, 384, SMEM_BYTES>>>(scratch, (const __nv_bfloat16*)d_in[0], (const __nv_bfloat16*)d_in[2], 7, (const __nv_bfloat16*)d_in[5],
                                           (const __nv_bfloat16*)d_in[6], (const __nv_bfloat16*)d_in[7], maps);
}
```

```cpp
#include <cuda_runtime.h>
#include <cuda.h>
#include <cuda_bf16.h>
#include <stdint.h>
#include <type_traits>

#define PPF 2
#define PKP 0
#define TDEF 1
#define TMPF 0
#define ACAN 0
#define SPLIT0 1
#define OT 2
#define F2PP 0
#define PPK 2
#define QE 1
#define OST 1
#define PP

namespace {

constexpr uint32_t STAGE = 28672, HALF = 14336;
constexpr int NST = 5;
constexpr uint32_t OFF_H = NST * STAGE;
constexpr uint32_t OFF_KVB = OFF_H + 2 * STAGE;
constexpr uint32_t OFF_WPHI = OFF_KVB + 16384;
constexpr uint32_t OFF_BAR = OFF_WPHI + 7168;
constexpr uint32_t SMEM_BYTES = OFF_BAR + 384 + 1408;
constexpr int B_EMPTY = NST, B_RECV = 2 * NST, B_RECV2 = B_RECV + 2, B_PACK = B_RECV2 + 2, B_GAT = B_PACK + 1, B_LATE = B_GAT + 16, B_ACK = B_LATE + 1, B_ACK2 = B_ACK + 2, B_COUNT = B_ACK2 + 2;

constexpr int PACK = 14 + 4 * PKP;

struct Maps { CUtensorMap x, qkv, wo, wg, wu, wg32, wu32, wd, out; };

}

constexpr int PLANE = 16 * 2 * 8 * 512;
struct Scratch {
    uint4 ex[6 * PLANE];
    uint4 kv1[8 * 16 * 16 * 32];
    uint4 kv2[8 * 512];
    uint32_t c1[8 * 8 * 16 * 32];
    uint32_t cw[8 * 32];
    uint4 wp[8 * 32 * (HALF / 16)];
};
__device__ __align__(1024) Scratch g_scratch;
#define g_ex (sc->ex)
#define g_kv1 (sc->kv1)
#define g_kv2 (sc->kv2)
#define g_c1 (sc->c1)
#define g_cw (sc->cw)
#define g_wp (sc->wp)
#define STAMP(i)
#define GSTAMP(i)
#define PDUMP()
#define ASTAMP(i)

namespace {

__device__ __forceinline__ int fresh_tid() { int t; asm volatile("mov.u32 %0, %%tid.x;" : "=r"(t)); return t; }
template <int N> __device__ __forceinline__ void kill(uint32_t* v) {
#pragma unroll
    for (int i = 0; i < N; i++) v[i] = 0;
}
template <int N> __device__ __forceinline__ void kill(float* v) {
#pragma unroll
    for (int i = 0; i < N; i++) v[i] = 0.f;
}
__device__ __forceinline__ uint32_t s2u(const void* p) { return (uint32_t)__cvta_generic_to_shared(p); }
__device__ __forceinline__ void mbar_init(uint32_t a, uint32_t c) { asm volatile("mbarrier.init.shared::cta.b64 [%0], %1;" ::"r"(a), "r"(c) : "memory"); }
__device__ __forceinline__ void mbar_expect_tx(uint32_t a, uint32_t b) { asm volatile("mbarrier.arrive.expect_tx.shared::cta.b64 _, [%0], %1;" ::"r"(a), "r"(b) : "memory"); }
__device__ __forceinline__ void mbar_arrive(uint32_t a) { asm volatile("mbarrier.arrive.shared::cta.b64 _, [%0];" ::"r"(a) : "memory"); }
#define GIVE_UP(id) "trap;\n"
#define SPIN_MAX "0x400000"
#define SPIN_TAIL(id) "add.u32 n, n, 1;\n setp.lt.u32 p, n, " SPIN_MAX ";\n @p bra.uni LP;\n" GIVE_UP(id) " DN:\n }"
__device__ __forceinline__ void mbar_wait(uint32_t a, uint32_t ph) {
    asm volatile("{ .reg .pred p; .reg .b32 n; mov.u32 n, 0;\n LP:\n"
                 "mbarrier.try_wait.parity.shared::cta.b64 p, [%0], %1;\n @p bra DN;\n"
                 "add.u32 n, n, 1;\n setp.lt.u32 p, n, " SPIN_MAX ";\n @p bra LP;\n"
                 GIVE_UP("")
                 " DN:\n }" ::"r"(a), "r"(ph) : "memory");
}
#define ELECT "{ .reg .pred e; elect.sync _|e, 0xffffffff; @e "
__device__ __forceinline__ void tma2d(uint32_t dst, const CUtensorMap* m, int c0, int c1, uint32_t bar) {
    asm volatile(ELECT "cp.async.bulk.tensor.2d.shared::cluster.global.mbarrier::complete_tx::bytes [%0], [%1, {%3, %4}], [%2]; }" ::"r"(dst), "l"(m), "r"(bar), "r"(c0), "r"(c1) : "memory");
}
__device__ __forceinline__ void tma3x(uint32_t dst, const CUtensorMap* m, int row, uint32_t bar) {
    asm volatile(ELECT "cp.async.bulk.tensor.3d.shared::cluster.global.mbarrier::complete_tx::bytes [%0], [%1, {0, %3, 0}], [%2]; }" ::"r"(dst), "l"(m), "r"(bar), "r"(row) : "memory");
}
template <int OFF>
__device__ __forceinline__ void ld_pkt(uint32_t* v, const uint4* p) {
    asm volatile("{ .reg .b128 t; ld.relaxed.gpu.global.b128 t, [%4+%5]; mov.b128 {%0,%1,%2,%3}, t; }" : "=r"(v[0]), "=r"(v[1]), "=r"(v[2]), "=r"(v[3]) : "l"(p), "n"(OFF * 16) : "memory");
}
template <int OFF>
__device__ __forceinline__ void st_pkt(uint4* p, uint32_t a, uint32_t b, uint32_t c, uint32_t d) {
    asm volatile("{ .reg .b128 t; mov.b128 t, {%1,%2,%3,%4}; st.relaxed.gpu.global.b128 [%0+%5], t; }" ::"l"(p), "r"(a), "r"(b), "r"(c), "r"(d), "n"(OFF * 16) : "memory");
}
__device__ __forceinline__ uint32_t pack2(float lo, float hi) {
    uint32_t r;
    asm("cvt.rn.bf16x2.f32 %0, %1, %2;" : "=r"(r) : "f"(hi), "f"(lo));
    return r;
}
__device__ __forceinline__ float bf_lo(uint32_t w) { return __uint_as_float(w << 16); }
__device__ __forceinline__ float bf_hi(uint32_t w) { return __uint_as_float(w & 0xffff0000u); }
__device__ __forceinline__ uint32_t settag(uint32_t w, uint32_t tag) { return (w & ~1u) | tag; }
__device__ __forceinline__ float ex2(float x) { float y; asm("ex2.approx.ftz.f32 %0, %1;" : "=f"(y) : "f"(x)); return y; }
__device__ __forceinline__ float rcp(float x) { float y; asm("rcp.approx.ftz.f32 %0, %1;" : "=f"(y) : "f"(x)); return y; }
__device__ __forceinline__ float tanh_hw(float x) { float y; asm("tanh.approx.f32 %0, %1;" : "=f"(y) : "f"(x)); return y; }
__device__ __forceinline__ void stsm4(uint32_t addr, uint32_t a, uint32_t b, uint32_t c, uint32_t d) {
    asm volatile("stmatrix.sync.aligned.m8n8.x4.shared.b16 [%0], {%1,%2,%3,%4};" ::"r"(addr), "r"(a), "r"(b), "r"(c), "r"(d) : "memory");
}
__device__ __forceinline__ void fence_async() { asm volatile("fence.proxy.async.shared::cta;" ::: "memory"); }
__device__ __forceinline__ void bar_sync(int id, int n) { asm volatile("bar.sync %0, %1;" ::"r"(id), "r"(n) : "memory"); }
__device__ __forceinline__ void bar_arrive(int id, int n) { asm volatile("bar.arrive %0, %1;" ::"r"(id), "r"(n) : "memory"); }
__device__ __forceinline__ void wg_fence() { asm volatile("wgmma.fence.sync.aligned;" ::: "memory"); }
__device__ __forceinline__ void wg_commit() { asm volatile("wgmma.commit_group.sync.aligned;" ::: "memory"); }
template <int N> __device__ __forceinline__ void wg_wait() { asm volatile("wgmma.wait_group.sync.aligned %0;" ::"n"(N) : "memory"); }

constexpr uint32_t SB0 = 1024;
__host__ __device__ constexpr uint32_t dlo(uint32_t off, uint32_t lbo) { return ((SB0 + off) >> 4) | ((lbo >> 4) << 16); }
__host__ __device__ constexpr uint32_t dhi(uint32_t sbo, uint32_t sw) { return (sbo >> 4) | (sw << 30); }
__device__ __forceinline__ uint64_t dbase(uint32_t lo, uint32_t hi) { uint64_t d; asm volatile("mov.b64 %0, {%1, %2};" : "=l"(d) : "r"(lo), "r"(hi)); return d; }
#define BASE128(off, lbo, adj) dbase(dlo(off, lbo) + (adj), dhi(1024, 1))
#define BASE64(off, lbo, adj) dbase(dlo(off, lbo) + (adj), dhi(512, 2))

#define ACC4(d, o) "+f"(d[o]), "+f"(d[o + 1]), "+f"(d[o + 2]), "+f"(d[o + 3])
#define ACC28(d) ACC4(d, 0), ACC4(d, 4), ACC4(d, 8), ACC4(d, 12), ACC4(d, 16), ACC4(d, 20), ACC4(d, 24)
#define ACC32(d, o) ACC4(d, o), ACC4(d, o + 4), ACC4(d, o + 8), ACC4(d, o + 12), ACC4(d, o + 16), ACC4(d, o + 20), ACC4(d, o + 24), ACC4(d, o + 28)

template <int TB, uint64_t D>
__device__ __forceinline__ void mma_rs56(float* d, uint32_t a0, uint32_t a1, uint32_t a2, uint32_t a3, int sd, uint64_t base) {
    asm volatile("{ .reg .pred p; .reg .b64 db; setp.ne.b32 p, %32, 0; add.u64 db, %33, %34;\n"
                 "wgmma.mma_async.sync.aligned.m64n56k16.f32.bf16.bf16 "
                 "{%0,%1,%2,%3,%4,%5,%6,%7,%8,%9,%10,%11,%12,%13,%14,%15,%16,%17,%18,%19,%20,%21,%22,%23,%24,%25,%26,%27}, "
                 "{%28,%29,%30,%31}, db, p, 1, 1, %35; }\n"
                 : ACC28(d)
                 : "r"(a0), "r"(a1), "r"(a2), "r"(a3), "r"(sd), "l"(base), "n"(D), "n"(TB));
}
template <int TB, uint64_t D>
__device__ __forceinline__ void mma_rs64(float* d, uint32_t a0, uint32_t a1, uint32_t a2, uint32_t a3, int sd, uint64_t base) {
    asm volatile("{ .reg .pred p; .reg .b64 db; setp.ne.b32 p, %36, 0; add.u64 db, %37, %38;\n"
                 "wgmma.mma_async.sync.aligned.m64n64k16.f32.bf16.bf16 "
                 "{%0,%1,%2,%3,%4,%5,%6,%7,%8,%9,%10,%11,%12,%13,%14,%15,%16,%17,%18,%19,%20,%21,%22,%23,%24,%25,%26,%27,%28,%29,%30,%31}, "
                 "{%32,%33,%34,%35}, db, p, 1, 1, %39; }\n"
                 : ACC32(d, 0)
                 : "r"(a0), "r"(a1), "r"(a2), "r"(a3), "r"(sd), "l"(base), "n"(D), "n"(TB));
}
template <int TB, uint64_t D>
__device__ __forceinline__ void mma_rs128(float* d, uint32_t a0, uint32_t a1, uint32_t a2, uint32_t a3, int sd, uint64_t base) {
    asm volatile("{ .reg .pred p; .reg .b64 db; setp.ne.b32 p, %68, 0; add.u64 db, %69, %70;\n"
                 "wgmma.mma_async.sync.aligned.m64n128k16.f32.bf16.bf16 "
                 "{%0,%1,%2,%3,%4,%5,%6,%7,%8,%9,%10,%11,%12,%13,%14,%15,%16,%17,%18,%19,%20,%21,%22,%23,%24,%25,%26,%27,%28,%29,%30,%31,%32,%33,%34,%35,%36,%37,%38,%39,%40,%41,%42,%43,%44,%45,%46,%47,%48,%49,%50,%51,%52,%53,%54,%55,%56,%57,%58,%59,%60,%61,%62,%63}, "
                 "{%64,%65,%66,%67}, db, p, 1, 1, %71; }\n"
                 : ACC32(d, 0), ACC32(d, 32)
                 : "r"(a0), "r"(a1), "r"(a2), "r"(a3), "r"(sd), "l"(base), "n"(D), "n"(TB));
}
template <uint64_t DA, uint64_t DB>
__device__ __forceinline__ void mma_ss56_tt(float* d, int sd, uint64_t ba, uint64_t bb) {
    asm volatile("{ .reg .pred p; .reg .b64 da, db; setp.ne.b32 p, %28, 0; add.u64 da, %29, %31; add.u64 db, %30, %32;\n"
                 "wgmma.mma_async.sync.aligned.m64n56k16.f32.bf16.bf16 "
                 "{%0,%1,%2,%3,%4,%5,%6,%7,%8,%9,%10,%11,%12,%13,%14,%15,%16,%17,%18,%19,%20,%21,%22,%23,%24,%25,%26,%27}, "
                 "da, db, p, 1, 1, 1, 1; }\n"
                 : ACC28(d)
                 : "r"(sd), "l"(ba), "l"(bb), "n"(DA), "n"(DB));
}
template <int... I> struct Seq {};
template <class F, int... I> __device__ __forceinline__ void static_for_impl(F&& f, Seq<I...>) { (f(std::integral_constant<int, I>{}), ...); }
#define FOR7(...) static_for_impl([&](auto T_) { constexpr int t = decltype(T_)::value; __VA_ARGS__; }, Seq<0, 1, 2, 3, 4, 5, 6>{})
#define FOR8(...) static_for_impl([&](auto T_) { constexpr int t = decltype(T_)::value; __VA_ARGS__; }, Seq<0, 1, 2, 3, 4, 5, 6, 7>{})
#define FOR14(...) static_for_impl([&](auto T_) { constexpr int t = decltype(T_)::value; __VA_ARGS__; }, Seq<0, 1, 2, 3, 4, 5, 6, 7, 8, 9, 10, 11, 12, 13>{})

__device__ __forceinline__ int kblk(int p, int b) { return b == 0 ? p : b - (b <= p); }
__host__ __device__ constexpr int krow(int t) { return t < 3 ? 16 * t : (t < 6 ? 56 + 16 * (t - 3) : 48); }
#define AQ(A, b, t) ((t) < 3 ? A[2 * (b)][4 * (t)] : (t) < 6 ? A[2 * (b) + 1][4 * ((t) - 3)] : A[2 * (b)][12]), \
                    ((t) < 3 ? A[2 * (b)][4 * (t) + 1] : (t) < 6 ? A[2 * (b) + 1][4 * ((t) - 3) + 1] : A[2 * (b)][13]), \
                    ((t) < 3 ? A[2 * (b)][4 * (t) + 2] : (t) < 6 ? A[2 * (b) + 1][4 * ((t) - 3) + 2] : A[2 * (b) + 1][12]), \
                    ((t) < 3 ? A[2 * (b)][4 * (t) + 3] : (t) < 6 ? A[2 * (b) + 1][4 * ((t) - 3) + 3] : A[2 * (b) + 1][13])
#define D128(off, t) ((uint64_t)(((off) + krow(t) * 128) >> 4) + ((uint64_t)((t) == 6 ? (7168 - 1024) >> 4 : 0) << 32))
#define D64(off, t) ((uint64_t)(((off) + krow(t) * 64) >> 4) + ((uint64_t)((t) == 6 ? (3584 - 512) >> 4 : 0) << 32))

#define PL(k) (((k) - 3) * PLANE)
__device__ __forceinline__ void st_word(uint32_t* p, uint32_t v) { asm volatile("st.relaxed.gpu.global.u32 [%0], %1;" ::"l"(p), "r"(v) : "memory"); }
__device__ __forceinline__ uint32_t ld_word(const uint32_t* p) { uint32_t v; asm volatile("ld.relaxed.gpu.global.u32 %0, [%1];" : "=r"(v) : "l"(p) : "memory"); return v; }
__device__ __forceinline__ void tag_slice(uint32_t* w, uint32_t tag) { w[0] = settag(w[0], tag); w[4] = settag(w[4], tag); w[8] = settag(w[8], tag); w[12] = settag(w[12], tag); }
template <int O>
__device__ __forceinline__ void send_slice(uint4* dst, int lane, const uint32_t* w) {
    st_pkt<O>(dst, w[0], w[1], w[2], w[3]);
    st_pkt<O + 32>(dst, w[4], w[5], w[6], w[7]);
    st_pkt<O + 64>(dst, w[8], w[9], w[10], w[11]);
    asm volatile("{ .reg .b64 t; mov.b64 t, {%1,%2}; st.relaxed.gpu.global.b64 [%0+%3], t; }" ::"l"((char*)dst - lane * 8), "r"(w[12]), "r"(w[13]), "n"(16 * (O + 96)) : "memory");
}
#define RW4(v, o) "+r"(v[o]), "+r"(v[(o) + 1]), "+r"(v[(o) + 2]), "+r"(v[(o) + 3])
#define RW2(v, o) "+r"(v[o]), "+r"(v[(o) + 1])
#define WR4(v, o) "=&r"(v[o]), "=&r"(v[(o) + 1]), "=&r"(v[(o) + 2]), "=&r"(v[(o) + 3])
#define LDP(a, b, c, d, addr, off) "ld.relaxed.gpu.global.b128 q, [" addr "+" off "];\n mov.b128 {" a "," b "," c "," d "}, q;\n"
#define LDH(a, b, addr, off) "ld.relaxed.gpu.global.b64 h, [" addr "+" off "];\n mov.b64 {" a "," b "}, h;\n"
#define VOTE_OK "and.b32 t, t, 1;\n setp.ne.u32 p, t, 0;\n vote.sync.any.pred p, p, 0xffffffff;\n @!p bra.uni DN;\n"
#define CHK(x, tag) "lop3.b32 t, " x ", " tag ", t, 0xBE;\n"
__device__ __forceinline__ void check_cnt(uint32_t v, const uint32_t* p, uint32_t target) {
    asm volatile("{ .reg .pred p; .reg .b32 n, t; mov.u32 n, 0; mov.u32 t, %2;\n LP:\n"
                 "sub.s32 t, t, %1;\n setp.lt.s32 p, t, 0;\n vote.sync.any.pred p, p, 0xffffffff;\n @!p bra.uni DN;\n ld.relaxed.gpu.global.u32 t, [%0];\n" SPIN_TAIL("7")
                 ::"l"(p), "r"(target), "r"(v) : "memory");
}
__device__ __forceinline__ void poll_cnt(const uint32_t* p, uint32_t target) {
    asm volatile("{ .reg .pred p; .reg .b32 n, t; mov.u32 n, 0;\n LP:\n"
                 "ld.relaxed.gpu.global.u32 t, [%0];\n sub.s32 t, t, %1;\n setp.lt.s32 p, t, 0;\n vote.sync.any.pred p, p, 0xffffffff;\n @!p bra.uni DN;\n" SPIN_TAIL("1")
                 ::"l"(p), "r"(target) : "memory");
}
template <int STR>
__device__ __forceinline__ void poll4_kv(uint32_t* v, const uint4* p, uint32_t tag) {
    asm volatile("{ .reg .pred p; .reg .b32 n, t; .reg .b128 q; mov.u32 n, 0;\n LP:\n"
                 LDP("%0", "%1", "%2", "%3", "%16", "0") LDP("%4", "%5", "%6", "%7", "%16", "%18")
                 LDP("%8", "%9", "%10", "%11", "%16", "%19") LDP("%12", "%13", "%14", "%15", "%16", "%20")
                 "xor.b32 t, %0, %17;\n" CHK("%4", "%17") CHK("%8", "%17") CHK("%12", "%17") VOTE_OK SPIN_TAIL("2")
                 : WR4(v, 0), WR4(v, 4), WR4(v, 8), WR4(v, 12)
                 : "l"(p), "r"(tag), "n"(16 * STR), "n"(32 * STR), "n"(48 * STR)
                 : "memory");
}
template <int B>
__device__ __forceinline__ void blk_load(uint32_t (&A)[8][14], const uint4* src, int lane) {
    ld_pkt<0>(&A[2 * B][0], src); ld_pkt<32>(&A[2 * B][4], src); ld_pkt<64>(&A[2 * B][8], src);
    ld_pkt<512>(&A[2 * B + 1][0], src); ld_pkt<544>(&A[2 * B + 1][4], src); ld_pkt<576>(&A[2 * B + 1][8], src);
    asm volatile("{ .reg .b64 h;\n" LDH("%0", "%1", "%4", "1536") LDH("%2", "%3", "%4", "9728") "}"
                 : "=&r"(A[2 * B][12]), "=&r"(A[2 * B][13]), "=&r"(A[2 * B + 1][12]), "=&r"(A[2 * B + 1][13])
                 : "l"((const char*)src - lane * 8) : "memory");
}
template <int B>
__device__ __forceinline__ void blk_check(uint32_t (&A)[8][14], const uint4* src, int lane, uint32_t tag) {
    asm volatile("{ .reg .pred p; .reg .b32 n, t; .reg .b128 q; .reg .b64 h, a8; mov.u32 n, 0;\n LP:\n"
                 "xor.b32 t, %0, %30;\n" CHK("%4", "%30") CHK("%8", "%30") CHK("%12", "%30") CHK("%16", "%30") CHK("%20", "%30") CHK("%24", "%30") CHK("%26", "%30") VOTE_OK
                 LDP("%0", "%1", "%2", "%3", "%28", "0") LDP("%4", "%5", "%6", "%7", "%28", "512") LDP("%8", "%9", "%10", "%11", "%28", "1024")
                 LDP("%12", "%13", "%14", "%15", "%28", "8192") LDP("%16", "%17", "%18", "%19", "%28", "8704") LDP("%20", "%21", "%22", "%23", "%28", "9216")
                 "mad.wide.s32 a8, %29, -8, %28;\n" LDH("%24", "%25", "a8", "1536") LDH("%26", "%27", "a8", "9728") SPIN_TAIL("3")
                 "\n and.b32 %0, %0, -2; and.b32 %4, %4, -2; and.b32 %8, %8, -2; and.b32 %12, %12, -2; and.b32 %16, %16, -2; and.b32 %20, %20, -2; and.b32 %24, %24, -2; and.b32 %26, %26, -2;"
                 : RW4(A[2 * B], 0), RW4(A[2 * B], 4), RW4(A[2 * B], 8), RW4(A[2 * B + 1], 0), RW4(A[2 * B + 1], 4), RW4(A[2 * B + 1], 8),
                   RW2(A[2 * B], 12), RW2(A[2 * B + 1], 12)
                 : "l"(src), "r"(lane), "r"(tag)
                 : "memory");
}
__device__ __forceinline__ void st_async4(uint32_t a, uint32_t x, uint32_t y, uint32_t z, uint32_t w, uint32_t bar) {
    asm volatile("st.async.weak.shared::cluster.mbarrier::complete_tx::bytes.v4.b32 [%0], {%1,%2,%3,%4}, [%5];" ::"r"(a), "r"(x), "r"(y), "r"(z), "r"(w), "r"(bar) : "memory");
}
__device__ __forceinline__ uint32_t mapa(uint32_t a, uint32_t cta) { uint32_t r; asm("mapa.shared::cluster.u32 %0, %1, %2;" : "=r"(r) : "r"(a), "r"(cta)); return r; }
__device__ __forceinline__ void stat_load(uint32_t* v, const uint4* p) { ld_pkt<0>(v, p); ld_pkt<512>(v + 4, p); }
__device__ __forceinline__ void stat_check(uint32_t* v, const uint4* p, uint32_t tag) {
    asm volatile("{ .reg .pred p; .reg .b32 n, t; .reg .b128 q; mov.u32 n, 0;\n LP:\n"
                 "xor.b32 t, %3, %9;\n" CHK("%7", "%9") VOTE_OK
                 LDP("%0", "%1", "%2", "%3", "%8", "0") LDP("%4", "%5", "%6", "%7", "%8", "8192") SPIN_TAIL("4")
                 : RW4(v, 0), RW4(v, 4) : "l"(p), "r"(tag) : "memory");
}
__device__ __forceinline__ uint32_t x_bits(const uint32_t* X) {
    uint32_t r;
    asm volatile("{ .reg .b32 a, b; prmt.b32 a, %1, %2, 0x0040; prmt.b32 b, %3, %4, 0x0040; prmt.b32 %0, a, b, 0x5410; }" : "=r"(r) : "r"(X[0]), "r"(X[4]), "r"(X[8]), "r"(X[12]));
    return r;
}
template <int O>
__device__ __forceinline__ void slice_load(uint32_t* v, const uint4* p, int lane) {
    ld_pkt<O>(v, p); ld_pkt<O + 32>(v + 4, p); ld_pkt<O + 64>(v + 8, p);
    asm volatile("{ .reg .b64 h;\n" LDH("%0", "%1", "%2", "%3") "}" : "=r"(v[12]), "=r"(v[13]) : "l"((const char*)p - lane * 8), "n"(16 * (O + 96)) : "memory");
}
template <int O>
__device__ __forceinline__ void slice_check(uint32_t* v, const uint4* p, int lane, uint32_t tag) {
    asm volatile("{ .reg .pred p; .reg .b32 n, t; .reg .b128 q; .reg .b64 h; mov.u32 n, 0;\n LP:\n"
                 "xor.b32 t, %0, %16;\n" CHK("%4", "%16") CHK("%8", "%16") CHK("%12", "%16") VOTE_OK
                 LDP("%0", "%1", "%2", "%3", "%14", "%17") LDP("%4", "%5", "%6", "%7", "%14", "%18") LDP("%8", "%9", "%10", "%11", "%14", "%19")
                 LDH("%12", "%13", "%15", "%20") SPIN_TAIL("5")
                 : RW4(v, 0), RW4(v, 4), RW4(v, 8), RW2(v, 12)
                 : "l"(p), "l"((const char*)p - lane * 8), "r"(tag), "n"(16 * O), "n"(16 * (O + 32)), "n"(16 * (O + 64)), "n"(16 * (O + 96))
                 : "memory");
}
__device__ __forceinline__ void x_fix(uint32_t* X, uint32_t bits) {
    X[0] = __byte_perm(X[0], bits, 0x3214); X[4] = __byte_perm(X[4], bits, 0x3215); X[8] = __byte_perm(X[8], bits, 0x3216); X[12] = __byte_perm(X[12], bits, 0x3217);
}
__device__ __forceinline__ void sts4(uint32_t a, uint32_t x, uint32_t y, uint32_t z, uint32_t w) {
    asm volatile("st.shared.v4.u32 [%0], {%1,%2,%3,%4};" ::"r"(a), "r"(x), "r"(y), "r"(z), "r"(w) : "memory");
}
__device__ __forceinline__ void lds4(uint32_t* v, uint32_t a) {
    asm volatile("ld.shared.v4.u32 {%0,%1,%2,%3}, [%4];" : "=r"(v[0]), "=r"(v[1]), "=r"(v[2]), "=r"(v[3]) : "r"(a) : "memory");
}
struct LnCoef { uint32_t hi, lo, sh; };
__device__ __forceinline__ LnCoef ln_coef(float sum, float sq) {
    sum += __shfl_xor_sync(0xffffffffu, sum, 1); sq += __shfl_xor_sync(0xffffffffu, sq, 1);
    sum += __shfl_xor_sync(0xffffffffu, sum, 2); sq += __shfl_xor_sync(0xffffffffu, sq, 2);
    const float mean = sum * (1.f / 448.f);
    const float var = fmaxf(fmaf(-mean, mean, sq * (1.f / 448.f)), 0.f);
    const float sc = rsqrtf(var + 1e-5f);
    LnCoef r;
    r.hi = pack2(sc, sc);
    const float lo = sc - bf_lo(r.hi), sh = -mean * sc;
    r.lo = pack2(lo, lo);
    r.sh = pack2(sh, sh);
    return r;
}
template <int W0, int W1>
__device__ __forceinline__ void normalize(uint32_t (&A)[8][14], const LnCoef& c0, const LnCoef& c1) {
#pragma unroll
    for (int i = W0; i < W1; i++) {
        const LnCoef& k = (i & 1) ? c1 : c0;
        asm("{ .reg .b32 t; fma.rn.bf16x2 t, %0, %2, %3; fma.rn.bf16x2 %0, %0, %1, t; }" : "+r"(A[i / 14][i % 14]) : "r"(k.hi), "r"(k.lo), "r"(k.sh));
    }
}
__device__ __forceinline__ void slice_stats(const uint32_t* w, float* st) {
    float a = 0.f, b = 0.f, p = 0.f, q = 0.f;
#pragma unroll
    for (int i = 0; i < 7; i++) {
        const float e0 = bf_lo(w[2 * i]), e1 = bf_hi(w[2 * i]), e2 = bf_lo(w[2 * i + 1]), e3 = bf_hi(w[2 * i + 1]);
        a += e0 + e1; b += e2 + e3;
        p = fmaf(e0, e0, p); p = fmaf(e1, e1, p); q = fmaf(e2, e2, q); q = fmaf(e3, e3, q);
    }
    a += __shfl_xor_sync(0xffffffffu, a, 1); p += __shfl_xor_sync(0xffffffffu, p, 1); b += __shfl_xor_sync(0xffffffffu, b, 1); q += __shfl_xor_sync(0xffffffffu, q, 1);
    a += __shfl_xor_sync(0xffffffffu, a, 2); p += __shfl_xor_sync(0xffffffffu, p, 2); b += __shfl_xor_sync(0xffffffffu, b, 2); q += __shfl_xor_sync(0xffffffffu, q, 2);
    st[0] = a; st[1] = p; st[2] = b; st[3] = q;
}
__device__ __forceinline__ void dual_softmax(const float* p, uint32_t* out) {
    constexpr float L = 1.4426950408889634f;
#pragma unroll
    for (int r = 0; r < 2; r++) {
        float mx = fmaxf(p[2 * r], p[2 * r + 1]), mn = fminf(p[2 * r], p[2 * r + 1]);
#pragma unroll
        for (int i = 1; i < 7; i++) {
            mx = fmaxf(mx, fmaxf(p[4 * i + 2 * r], p[4 * i + 2 * r + 1]));
            mn = fminf(mn, fminf(p[4 * i + 2 * r], p[4 * i + 2 * r + 1]));
        }
        mx = fmaxf(mx, __shfl_xor_sync(0xffffffffu, mx, 1));
        mn = fminf(mn, __shfl_xor_sync(0xffffffffu, mn, 1));
        const float bx = -mx * L, bn = mn * L;
        float ep[14], en[14], sp = 0.f, sn = 0.f;
#pragma unroll
        for (int i = 0; i < 14; i++) {
            const float v = p[4 * (i >> 1) + 2 * r + (i & 1)];
            ep[i] = ex2(fmaf(v, L, bx));
            en[i] = ex2(fmaf(v, -L, bn));
            sp += ep[i]; sn += en[i];
        }
        sp += __shfl_xor_sync(0xffffffffu, sp, 1);
        sn += __shfl_xor_sync(0xffffffffu, sn, 1);
        const float ip = rcp(sp), in = rcp(sn);
#pragma unroll
        for (int i = 0; i < 7; i++) {
            out[4 * i + r] = pack2(ep[2 * i] * ip, ep[2 * i + 1] * ip);
            out[4 * i + 2 + r] = pack2(en[2 * i] * in, en[2 * i + 1] * in);
        }
    }
}
__device__ __forceinline__ float geglu(float g, float u) {
    const float t = tanh_hw(g * fmaf(g * g, 0.7978845608028654f * 0.044715f, 0.7978845608028654f));
    const float gu = g * u;
    return fmaf(t, gu, gu);
}
__device__ __forceinline__ void phi_gemm(const float* t, float* p) {
    uint32_t w[14];
#pragma unroll
    for (int i = 0; i < 14; i++) w[i] = pack2(t[2 * i], t[2 * i + 1]);
    const uint64_t db = BASE128(OFF_WPHI, 16, 0);
    wg_fence();
    mma_rs56<0, 0>(p, w[0], w[1], w[2], w[3], 0, db);
    mma_rs56<0, 2>(p, w[4], w[5], w[6], w[7], 1, db);
    mma_rs56<0, 4>(p, w[8], w[9], w[10], w[11], 1, db);
    mma_rs56<0, 6>(p, w[12], w[13], 0u, 0u, 1, db);
    wg_commit();
    wg_wait<0>();
}

}

#define BAR(i) (bars + 8 * (i))
#define R_WAIT() mbar_wait(BAR(slot), ph)
#define WSUM(i)
#define R_ADJ (slot * (STAGE >> 4))
#define R_NEXT() do { eb2 = eb1; eb1 = BAR(B_EMPTY + slot); if (++slot == NST) { slot = 0; ph ^= 1; } } while (0)
#define R_RELEASE(k) do { if (lane == 0) mbar_arrive((k) == 1 ? eb1 : eb2); } while (0)
#define PUSH_BEGIN() mbar_wait(BAR(B_ACK + wgi), step >> 1)
#define PUSH_ACK() do { __syncwarp(); if (lane == 0) asm volatile("mbarrier.arrive.shared::cluster.b64 _, [%0];" ::"r"(mapa(BAR(B_ACK + wgi), hr ^ 1)) : "memory"); } while (0)

__global__ void __cluster_dims__(2, 1, 1) __launch_bounds__(384, 1)
fused_kernel(Scratch* const sc, const __nv_bfloat16* __restrict__ x_in, const __nv_bfloat16* __restrict__ w_phi, const int trips,
             const __nv_bfloat16* __restrict__ wg, const __nv_bfloat16* __restrict__ wu, const __nv_bfloat16* __restrict__ wd,
             const __grid_constant__ Maps maps) {
    extern __shared__ __align__(1024) unsigned char smem_raw[];
    const uint32_t sb = s2u(smem_raw);
    const uint32_t bars = sb + OFF_BAR;
    const int wgi = __shfl_sync(0xffffffffu, threadIdx.x >> 7, 0);
    const int hr = blockIdx.x & 1, ck = blockIdx.x >> 1;
    const int gp = (ck - 4) & 7, q7 = ((ck - 36) * 37) >> 8;
    const int pr = __shfl_sync(0xffffffffu, ck < 4 ? ck : (ck < 36 ? (ck - 4) >> 3 : q7), 0);
    const int tile = __shfl_sync(0xffffffffu, ck < 4 ? 0 : (ck < 36 ? (gp ? 2 * gp : 1) : 2 * (ck - 36 - 7 * q7) + 3), 0);
    const int sl = 2 * pr + hr;
    STAMP(0);
    GSTAMP(60);
    if (threadIdx.x == 256) {
#pragma unroll
        for (int i = 0; i < NST; i++) mbar_init(BAR(i), 1);
        asm volatile("fence.mbarrier_init.release.cluster;" ::: "memory");
    }
    if (threadIdx.x == 288) {
        if ((sb & 0x3FFFF) != SB0) asm volatile("trap;");
#pragma unroll
        for (int i = NST; i < B_COUNT; i++) mbar_init(BAR(i), i >= B_ACK ? 4 : (i < B_RECV || i == B_LATE ? 8 : 1));
        asm volatile("fence.mbarrier_init.release.cluster;" ::: "memory");
    }
    __syncwarp();
    asm volatile("barrier.cluster.arrive.relaxed.aligned;" ::: "memory");

    if (wgi == 2) {
        asm volatile("setmaxnreg.dec.sync.aligned.u32 40;");
        const int t128 = fresh_tid() & 127, w = __shfl_sync(0xffffffffu, t128 >> 5, 0), lane = t128 & 31;
        uint32_t e0[2] = {0, 0}, e1[2] = {0, 0}, cw_target = 0;
        if (w == 0) {
#pragma unroll 1
            for (int n = 0; n < NST; n++) {
                const uint32_t dst = sb + n * STAGE, fb = BAR(n);
                asm volatile(ELECT "mbarrier.arrive.expect_tx.shared::cta.b64 _, [%0], %1; }" ::"r"(fb), "r"(n < 2 ? 2 * STAGE : STAGE) : "memory");
                if (n < 2) {
                    tma3x(sb + OFF_H + n * STAGE, &maps.x, tile * 128 + n * 64, fb);
                    tma3x(dst, &maps.x, tile * 128 + n * 64 + 32, fb);
                } else {
                    if (n == 3) mbar_wait(BAR(1), 0);
                    const int ra = 112 * (n - 2);
                    tma2d(dst, &maps.qkv, 448 + 56 * sl, ra, fb);
                    tma2d(dst + HALF, &maps.qkv, 896 + 56 * sl, ra, fb);
                }
            }
            asm volatile("barrier.cluster.wait.aligned;" ::: "memory");
            cw_target = (ld_word(g_cw + sl * 32) & ~15u) + 16;
#pragma unroll 1
            for (int k = 0; k < 2; k++) {
                const int n = t128 + 32 * k;
                int m = n - 2 - (n > PACK);
                const bool packed = m >= 30 ? (m < 38 || m >= 52) : m >= 22;
                if (m >= 30) m -= 30;
                if (n == PACK) m = tile < 8 ? tile : tile + 14;
                const int rot = n < 8 ? 0 : pr;
                const int ra = 112 * kblk(rot, m & 3), rb = 112 * kblk(rot, 2 * m & 3), rc = 112 * kblk(rot, (2 * m + 1) & 3);
                int kind = 0, m0, m1, c0, c1, r0, r1;
                if (m < 4) { m0 = m1 = 1; c0 = 448 + 56 * sl; c1 = c0 + 448; r0 = r1 = ra; }
                else if (m < 8) { m0 = m1 = m < 6 ? 1 : 2; c0 = c1 = 56 * sl; r0 = rb; r1 = rc; }
                else if (m < 20) { m0 = 3; m1 = 4; c0 = c1 = 224 * sl + 32 * hr + 64 * ((m - 8) >> 2); r0 = r1 = ra; }
                else if (m < 22) { kind = 2; m0 = 5; m1 = 6; c0 = c1 = 224 * sl + (hr ? 0 : 192); r0 = rb; r1 = rc; }
                else { m0 = m1 = 7; c0 = c1 = 56 * (2 * ((pr + (m >> 1) - 10) & 3) + hr); r0 = 224 * (sl ^ (m & 1)); r1 = r0 + 112; }
                if (packed) { kind = 1; r0 = sl * 16 + (m < 8 ? m : m - 14); r1 = 0; }
                e0[0] = e0[1]; e1[0] = e1[1];
                e0[1] = kind | (m0 << 2) | (m1 << 6) | (c0 << 10) | (c1 << 21);
                e1[1] = r0 | (r1 << 16);
            }
        } else {
            const int j = t128 - 32;
            asm volatile("barrier.cluster.wait.aligned;" ::: "memory");
            uint2 wv[7];
            const int k = j < 56 ? j : 55, hh = k >= 28;
#pragma unroll
            for (int i = 0; i < 7; i++) wv[i] = __ldg(reinterpret_cast<const uint2*>(w_phi + (sl * 56 + k) * 28) + i);
#pragma unroll 1
            for (int i = j; i < 7168 / 16; i += 96) sts4(sb + OFF_WPHI + i * 16, 0, 0, 0, 0);
            bar_sync(5, 96);
            if (j < 56) {
                uint32_t a4[4];
#pragma unroll
                for (int q = 0; q < 4; q++) a4[q] = sb + OFF_WPHI + (4 * hh + q) * 128 + ((((k >> 3) ^ (4 * hh + q)) & 7) << 4) + (k & 7) * 2;
                FOR14(const uint32_t v = (t & 1) ? wv[t >> 1].y : wv[t >> 1].x;
                      asm volatile("{ .reg .b16 l, h; mov.b32 {l, h}, %2; st.shared.u16 [%0+%3], l; st.shared.u16 [%1+%3], h; }"
                                   ::"r"(a4[t >= 7 ? 2 : 0]), "r"(a4[t >= 7 ? 3 : 1]), "r"(v), "n"((t % 7) * 1024) : "memory"));
            }
            __syncwarp();
            fence_async();
            bar_arrive(1, 224);
            bar_arrive(9, 224);
            if (w == 1) {
                mbar_wait(BAR(2), 0);
                mbar_wait(BAR(2), 1);
                const int b = blockIdx.x;
                asm volatile(ELECT "cp.async.bulk.prefetch.L2.global [%0], %1; }" ::"l"(wg + b * 6272), "r"(12544) : "memory");
                asm volatile(ELECT "cp.async.bulk.prefetch.L2.global [%0], %1; }" ::"l"(wu + b * 6272), "r"(12544) : "memory");
                asm volatile(ELECT "cp.async.bulk.prefetch.L2.global [%0], %1; }" ::"l"(wd + b * 6272), "r"(12544) : "memory");
            }
        }
        uint32_t kseq = ld_word(g_c1 + (sl * 8 * 16 + tile) * 32);
        int slot = 0, ph = 0, n = NST;
#pragma unroll 1
        for (int layer = 0; layer < 3; layer++) {
            if (w == 0) {
                const int nend = layer == 0 ? 11 : (layer == 1 ? 42 : 63);
#pragma unroll 1
                for (; n < nend; n++) {
                const uint32_t w0 = __shfl_sync(0xffffffffu, n < 32 ? e0[0] : e0[1], n & 31), w1 = __shfl_sync(0xffffffffu, n < 32 ? e1[0] : e1[1], n & 31);
                const uint32_t dst = sb + slot * STAGE, fb = BAR(n == PACK ? B_PACK : slot);
                const CUtensorMap* m0 = &maps.x + ((w0 >> 2) & 15);
                const CUtensorMap* m1 = &maps.x + ((w0 >> 6) & 15);
                const int c0 = (w0 >> 10) & 2047, c1 = w0 >> 21, r0 = w1 & 0xffff, r1 = w1 >> 16;
                if (n == 25) {
                    int it = 0;
                    uint32_t v;
                    do { asm volatile("ld.acquire.gpu.global.u32 %0, [%1];" : "=r"(v) : "l"(g_cw + sl * 32) : "memory"); } while ((int)(v - cw_target) < 0 && ++it < 0x400000);
                    asm volatile("fence.proxy.async.global;" ::: "memory");
                    __syncwarp();
                }
                mbar_wait(BAR(B_EMPTY + slot), ph);
                __syncwarp();
                asm volatile(ELECT "mbarrier.arrive.expect_tx.shared::cta.b64 _, [%0], %1; }" ::"r"(fb), "r"(STAGE) : "memory");
                if ((w0 & 3) == 0) {
                    tma2d(dst, m0, c0, r0, fb);
                    tma2d(dst + HALF, m1, c1, r1, fb);
                } else if (w0 & 1) {
                    asm volatile(ELECT "cp.async.bulk.shared::cluster.global.mbarrier::complete_tx::bytes [%0], [%1], %2, [%3]; }"
                                 ::"r"(dst), "l"(reinterpret_cast<const char*>(g_wp) + (size_t)r0 * STAGE), "r"(STAGE), "r"(fb) : "memory");
                } else {
                    tma2d(dst, m0, c0, r0, fb); tma2d(dst + 7168, m0, c0, r1, fb);
                    tma2d(dst + HALF, m1, c0, r0, fb); tma2d(dst + HALF + 7168, m1, c0, r1, fb);
                }
                if (n == PACK) asm volatile(ELECT "mbarrier.arrive.shared::cta.b64 _, [%0]; }" ::"r"(BAR(slot)) : "memory");
                if (++slot == NST) { slot = 0; ph ^= 1; }
                }
            } else if (w == 1 && layer == 1) {
                constexpr int ps = PACK % NST;
                mbar_wait(BAR(B_PACK), 0);
                asm volatile("{ .reg .pred e; elect.sync _|e, 0xffffffff;\n"
                             "@e cp.async.bulk.global.shared::cta.bulk_group [%0], [%1], %2;\n"
                             "@e cp.async.bulk.commit_group;\n"
                             "@e cp.async.bulk.wait_group.read 0;\n"
                             "@e mbarrier.arrive.shared::cta.b64 _, [%3], 8;\n"
                             "@e cp.async.bulk.wait_group 0;\n"
                             "@e fence.proxy.async.global;\n"
                             "@e red.release.gpu.global.add.u32 [%4], 1; }"
                             ::"l"(reinterpret_cast<char*>(g_wp) + (size_t)(sl * 16 + tile) * STAGE), "r"(sb + ps * STAGE), "r"(STAGE), "r"(BAR(B_EMPTY + ps)), "l"(g_cw + sl * 32) : "memory");
                __syncwarp();
            }
            if (layer < 2) {
            const uint32_t tag = layer ^ 1;
            int ln = lane;
            asm volatile("" : "+r"(ln));
            const int tj = w * 32 + ln;
            kseq++;
            bar_sync(7, 384);
            ASTAMP(0);
            if (tile < 15) {
                const int sq = ln >> 3, pk = 8 * w + (ln & (tile == 14 ? 3 : 7));
                uint32_t v[16];
                if (layer == 0) poll_cnt(g_c1 + ((sl * 8 + (w >> 1) * 4 + (tile >> 2)) * 16 + (ln & 15)) * 32, kseq);
                ASTAMP(1);
                poll4_kv<32>(v, g_kv1 + ((sl * 16 + tile) * 16 + 4 * sq) * 32 + pk, tag);
#pragma unroll
                for (int k = 0; k < 4; k++) {
                    float lo = (bf_lo(v[k]) + bf_lo(v[4 + k])) + (bf_lo(v[8 + k]) + bf_lo(v[12 + k]));
                    float hi = (bf_hi(v[k]) + bf_hi(v[4 + k])) + (bf_hi(v[8 + k]) + bf_hi(v[12 + k]));
                    lo += __shfl_xor_sync(0xffffffffu, lo, 8); hi += __shfl_xor_sync(0xffffffffu, hi, 8);
                    lo += __shfl_xor_sync(0xffffffffu, lo, 16); hi += __shfl_xor_sync(0xffffffffu, hi, 16);
                    v[k] = pack2(lo, hi);
                }
                if (sq == 0) st_pkt<0>(g_kv2 + sl * 512 + 32 * tile + pk, settag(v[0], tag), v[1], v[2], v[3]);
            }
            ASTAMP(2);
            {
                const int item = tj < 112 ? tj : 112 + (tj & 3), d = item >> 1;
                const int cc = tj < 112 ? 2 * (d >= 28) + (item & 1) : item - 112;
                const int r = tj < 112 ? d : 56 + (cc >> 1) + 2 * ((tj - 112) >> 2);
                uint32_t ra = sb + OFF_KVB + r * 128 + 4 * cc, rx = (r & 7) << 4;
                asm volatile("" : "+r"(ra), "+r"(rx));
                FOR14(asm volatile("st.shared.u32 [%0+%2], %1;" ::"r"((ra ^ 8) + (((t & 7) << 4) ^ rx)), "r"(0), "n"((t >> 3) * 8192) : "memory"));
                uint32_t v[16];
                asm volatile("" : "+r"(ra), "+r"(rx));
                poll4_kv<8>(v, g_kv2 + sl * 512 + (item >> 3) * 32 + (item & 7), tag);
                FOR14(asm volatile("st.shared.u32 [%0+%2], %1;" ::"r"(ra + (((t & 7) << 4) ^ rx)), "r"(v[t < 7 ? t : t + 1]), "n"((t >> 3) * 8192) : "memory"));
                fence_async();
            }
            bar_arrive(3, 384);
            ASTAMP(3);
            }
        }
    } else {
        asm volatile("setmaxnreg.inc.sync.aligned.u32 232;");
        int lane = fresh_tid() & 31, prf = pr;
#define pr prf
#define g (lane >> 2)
#define c (lane & 3)
#define t128 (w * 32 + lane)
        const int wu = __shfl_sync(0xffffffffu, fresh_tid() >> 5, 0), w = wu & 3;
        const uint32_t xoff = __shfl_sync(0xffffffffu, (3 * PLANE + ((tile * 2 + wgi) * 8) * 512 + w * 128) * 16, 0);
        char* xu = reinterpret_cast<char*>(g_ex) + xoff;
#define FRESH() asm volatile("" : "+l"(xu), "+r"(lane), "+r"(prf))
#define xp0 (reinterpret_cast<uint4*>(xu) + lane)
        const uint32_t hbuf = sb + OFF_H + wgi * STAGE;
        uint32_t slot = 0, ph = 0, eb1 = 0, eb2 = 0, gatph = 0, swp = 0;
        uint32_t ppid = 6;
#define cx(s) (reinterpret_cast<uint32_t*>(reinterpret_cast<uint4*>(xu) + PL(1) + 112 + (s) * 512))
#define stp (reinterpret_cast<uint4*>(xu) + g + PL(0) + 112)
        uint32_t seq = ld_word(cx(sl));
        uint32_t kseq = ld_word(g_c1 + ((sl * 8 + wu) * 16 + tile) * 32);
        uint32_t stag = ld_word(reinterpret_cast<const uint32_t*>(stp + sl * 512) + 3) & 1;
        asm volatile("barrier.cluster.wait.aligned;" ::: "memory");
        STAMP(1);
        uint32_t X[14];
        const uint32_t x0row = (w < 2 ? hbuf : sb + wgi * STAGE) + ((w & 1) * 16 + (lane & 15)) * 128;
        mbar_wait(BAR(wgi), 0);
        STAMP(51);
#pragma unroll
        for (int j = 0; j < 4; j++) {
            const int G = 7 * sl + min(2 * j + (lane >> 4), 6);
            uint32_t q2, q3;
            asm volatile("ldmatrix.sync.aligned.m8n8.x4.shared.b16 {%0,%1,%2,%3}, [%4];" : "=r"(X[4 * j]), "=r"(X[4 * j + 1]), "=r"(q2), "=r"(q3)
                         : "r"(x0row + (G >> 3) * 4096 + (((G ^ lane) & 7) << 4)) : "memory");
            if (j < 3) { X[(4 * j + 2) % 14] = q2; X[(4 * j + 3) % 14] = q3; }
        }
#define OWN_SLICE(W)                                                                           \
    _Pragma("unroll") for (int i = 0; i < 14; i++) A[0][i] = (i & 3) ? W[i] : W[i] & ~1u;      \
    swp = hr * 448;
#define SWB(b, t, db, sh) ((b) == 0 && (t) < 6 ? ((t) < 3 ? db##p : db##m) : db)
#define DECL_DB(b, MK, lbo, sh) const uint64_t db = MK(0, lbo, R_ADJ), dbp = (b) == 0 ? MK(0, lbo, R_ADJ + (swp >> (sh))) : db, dbm = (b) == 0 ? MK(0, lbo, R_ADJ - (swp >> (sh))) : db;
#define PPB 2
#define PP_WAIT() if (wgi == 1) { bar_sync(ppid, 256); ppid ^= 14; }
#define PP_GO() if (wgi == 0) { bar_arrive(ppid, 256); ppid ^= 14; }
#define BULK(dst, src) "@e cp.async.bulk.shared::cluster.global.mbarrier::complete_tx::bytes [" dst "], [" src "], 1792, [%0];\n"
#define GAT_ISSUE1(base)                                                                       \
    asm volatile("{ .reg .pred e; elect.sync _|e, 0xffffffff;\n @e mbarrier.arrive.expect_tx.shared::cta.b64 _, [%0], 5376;\n" \
                 BULK("%1", "%2") BULK("%1+1792", "%3") BULK("%1+3584", "%3+8192") "}"         \
                 ::"r"(BAR(B_GAT + wu * 2)), "r"(hbuf + w * 5376), "l"(xu + ((base) + (sl ^ 1) * 512) * 16), "l"(xu + ((base) + kblk(pr, 1) * 1024) * 16) : "memory"); \
    __syncwarp();
#define GAT_ISSUE3(base)                                                                       \
    asm volatile("{ .reg .pred e; elect.sync _|e, 0xffffffff;\n @e mbarrier.arrive.expect_tx.shared::cta.b64 _, [%0], 3584;\n" \
                 BULK("%1", "%3") BULK("%2", "%3+8192") "}"                                    \
                 ::"r"(BAR(B_GAT + wu * 2 + 1)), "r"(hbuf + 21504 + w * 1792), "r"(sb + OFF_KVB + wgi * 8192 + w * 1792), "l"(xu + ((base) + kblk(pr, 3) * 1024) * 16) : "memory"); \
    __syncwarp();
#define LDS_SLICE(V, addr)                                                                     \
    { const uint32_t ga = (addr) + lane * 16;                                                  \
      lds4(&(V)[0], ga); lds4(&(V)[4], ga + 512); lds4(&(V)[8], ga + 1024);                    \
      asm volatile("ld.shared.v2.u32 {%0,%1}, [%2];" : "=r"((V)[12]), "=r"((V)[13]) : "r"(ga - lane * 8 + 1536) : "memory"); }
#define GAT_FETCH1(src, tg)                                                                    \
    {                                                                                          \
        mbar_wait(BAR(B_GAT + wu * 2), (gatph >> 1) & 1);                                      \
        gatph ^= 2;                                                                            \
        LDS_SLICE(A[1], hbuf + w * 5376) LDS_SLICE(A[2], hbuf + w * 5376 + 1792) LDS_SLICE(A[3], hbuf + w * 5376 + 3584) \
        slice_check<0>(A[1], (src) + (sl ^ 1) * 512, lane, tg);                                \
        A[1][0] &= ~1u; A[1][4] &= ~1u; A[1][8] &= ~1u;                                        \
        const uint32_t t0 = A[1][12] & ~1u, t1 = A[1][13], u0 = A[0][12], u1 = A[0][13];       \
        A[0][12] = hr ? t0 : u0; A[0][13] = hr ? t1 : u1; A[1][12] = hr ? u0 : t0; A[1][13] = hr ? u1 : t1; \
    }
#define GAT_FETCH3()                                                                           \
    {                                                                                          \
        mbar_wait(BAR(B_GAT + wu * 2 + 1), step >> 1);                                         \
        LDS_SLICE(A[6], hbuf + 21504 + w * 1792) LDS_SLICE(A[7], sb + OFF_KVB + wgi * 8192 + w * 1792) \
    }
#define LATE_ARRIVE() do { if (lane == 0) mbar_arrive(BAR(B_LATE)); } while (0)
#define LATE_WAIT() do { mbar_wait(BAR(B_LATE), gatph & 1); gatph ^= 1; } while (0)
#define PT 3
#define PIN(V) asm volatile("" : RW4(V, 0), RW4(V, 4), RW4(V, 8), RW2(V, 12));
#define PREP(b, t, remote)                                                                     \
    if constexpr ((b) < 3 && (t) == ((b) ? PT : 2)) {                                          \
        wg_commit();                                                                           \
        STAMP(74 + 6 * (step & 1) + 2 * (b));                                                  \
        if (remote) {                                                                          \
            if constexpr ((b) == 0) { blk_load<2>(A, BLK(xsrc, 2), lane); GAT_FETCH1(xsrc, xtag) } \
            blk_check<((b) + 1) & 3>(A, BLK(xsrc, (b) + 1), lane, xtag);                       \
            if constexpr ((b) == 0) blk_load<3>(A, BLK(xsrc, 3), lane);                        \
        }                                                                                      \
        STAMP(75 + 6 * (step & 1) + 2 * (b));                                                  \
        if constexpr ((b) == 0) { normalize<12, 28>(A, k0, k1); PIN(A[0]) PIN(A[1]) wg_fence(); } \
        else { normalize<28 * ((b) + 1), 28 * ((b) + 2)>(A, k0, k1); PIN(A[(2 * (b) + 2) & 7]) PIN(A[(2 * (b) + 3) & 7]) wg_fence(); } \
    }                                                                                          \
    if constexpr ((b) == 0 && (t) == 4) { wg_commit(); normalize<28, 56>(A, k0, k1); PIN(A[2]) PIN(A[3]) wg_fence(); }
#define X0_BLOCK(b)                                                                            \
    { const int rr = lane & 7, hi = lane >> 4;                                                 \
    const uint32_t rowa = (w < 2 ? hbuf : sb + wgi * STAGE) + ((w & 1) * 16 + (lane & 15)) * 128; \
    FOR7(constexpr int G = 14 * (b) + (t < 3 ? 2 * t : (t < 6 ? 2 * t + 1 : 6));               \
         uint32_t q0, q1, q2, q3;                                                              \
         const uint32_t ad = t < 6 ? rowa + (((((G & 7) + hi) ^ rr) & 7) << 4) + ((G & 7) == 7 ? hi * 4096 : 0) : rowa + ((G + 7 * hi) >> 3) * 4096 + ((((G + 7 * hi) ^ rr) & 7) << 4); \
         asm volatile("ldmatrix.sync.aligned.m8n8.x4.shared.b16 {%0,%1,%2,%3}, [%4+%5];" : "=r"(q0), "=r"(q1), "=r"(q2), "=r"(q3) \
                      : "r"(ad), "n"(t < 6 ? (G >> 3) * 4096 : 0) : "memory");                 \
         if (t < 3) { A[2 * (b)][4 * t] = q0; A[2 * (b)][4 * t + 1] = q1; A[2 * (b)][4 * t + 2] = q2; A[2 * (b)][4 * t + 3] = q3; } \
         else if (t < 6) { A[2 * (b) + 1][(4 * t - 12) & 15] = q0; A[2 * (b) + 1][((4 * t - 12) & 15) + 1] = q1; A[2 * (b) + 1][((4 * t - 12) & 15) + 2] = q2; A[2 * (b) + 1][((4 * t - 12) & 15) + 3] = q3; } \
         else { A[2 * (b)][12] = q0; A[2 * (b)][13] = q1; A[2 * (b) + 1][12] = q2; A[2 * (b) + 1][13] = q3; }); }
#define BLK(base, b) ((base) + kblk(pr, b) * 1024)

#pragma unroll 1
        for (int step = 0; step < 4; step++) {
            FRESH();
            const uint32_t tag = (step >> 1) ^ 1;
            const int so = (step >> 1) * 24 + (step & 1) * 12;
            (void)so;
            uint32_t A[8][14];
            uint4* const xsrc = xp0 + ((step & 1) ? PL(2) : PL(0));
            const uint32_t xtag = (step & 1) ? tag : ((seq >> 3) & 1) ^ 1;
            uint32_t xbits;
            {
                float st[4];
                slice_stats(X, st);
                stag ^= 1;
                xbits = x_bits(X);
                tag_slice(X, xtag);
                if (step) send_slice<0>(xsrc + sl * 512, lane, X);
                if (c == 0) st_pkt<0>(stp + sl * 512, __float_as_uint(st[0]), __float_as_uint(st[1]), __float_as_uint(st[2]), settag(__float_as_uint(st[3]), stag));
            }
            STAMP(2 + so);
            uint32_t sv[8];
            if (step == 0) {
                X0_BLOCK(0) X0_BLOCK(1) X0_BLOCK(2) X0_BLOCK(3)
                mbar_wait(BAR(wgi ^ 1), 0);
                R_NEXT();
                R_NEXT();
                R_RELEASE(2);
                stat_load(sv, stp + c * 1024);
                stat_check(sv, stp + c * 1024, stag);
                STAMP(52 + step);
            } else {
                kill<14>(A[1]); kill<14>(A[2]); kill<14>(A[3]); kill<14>(A[4]); kill<14>(A[5]); kill<14>(A[6]); kill<14>(A[7]);
                stat_load(sv, stp + c * 1024);
                OWN_SLICE(X)
                stat_check(sv, stp + c * 1024, stag);
                STAMP(52 + step);
                GAT_ISSUE1((step & 1) ? PL(2) : PL(0))
            }
            LnCoef k0, k1;
            {
                k0 = ln_coef(__uint_as_float(sv[0]) + __uint_as_float(sv[4]), __uint_as_float(sv[1]) + __uint_as_float(sv[5]));
                k1 = ln_coef(__uint_as_float(sv[2]) + __uint_as_float(sv[6]), __uint_as_float(sv[3] & ~1u) + __uint_as_float(sv[7] & ~1u));
            }
            STAMP(3 + so);
            GSTAMP(70 + step);

            if ((step & 1) == 0) {
                float tq[28];
                {
                    float av[28];
#define KV_BLOCK(b)                                                                           \
    if ((b) == 1) R_RELEASE(2);                                                               \
    if ((b) == 2) { wg_wait<2>(); R_RELEASE(2); }                                 \
    R_WAIT();                                                                                 \
    if ((b) == PPK) { PP_WAIT() }                                                             \
    { DECL_DB(b, BASE128, 16, 0)                                                              \
    wg_fence();                                                                               \
    FOR7(mma_rs56<1, D128(0, t)>(tq, AQ(A, b, t), (b) + t > 0, SWB(b, t, db, 0));             \
         mma_rs56<1, D128(HALF, t)>(av, AQ(A, b, t), (b) + t > 0, SWB(b, t, db, 0));          \
         PREP(b, t, step)); }                                                                 \
    wg_commit();                                                                              \
    if ((b) == 3 && PPK < 4) { PP_GO() }                                                      \
    R_NEXT();
                    normalize<0, 12>(A, k0, k1);
                    KV_BLOCK(0) KV_BLOCK(1) KV_BLOCK(2) KV_BLOCK(3)
                    wg_wait<0>();
                    if (lane < 3) mbar_arrive(BAR(B_EMPTY + (slot + NST - 1 - lane) % NST));
                    STAMP(4 + so);
                    WSUM(80 + 7 * (step >> 1));
                    const int m = lane >> 3, rr = lane & 7;
                    const uint32_t rowa = hbuf + 16384 + (w * 16 + rr + 8 * (m & 1)) * 128;
                    const uint32_t one = c == 0 ? 0x00003f80u : 0u;
                    if (step == 0) { bar_sync(wgi ? 9 : 1, 224); }
#pragma unroll
                    for (int j = 0; j < 4; j++) {
                        const uint32_t a = rowa + (((2 * j + (m >> 1)) ^ rr) << 4);
                        if (j < 3) stsm4(a, pack2(av[8 * j], av[8 * j + 1]), pack2(av[8 * j + 2], av[8 * j + 3]), pack2(av[8 * j + 4], av[8 * j + 5]), pack2(av[8 * j + 6], av[8 * j + 7]));
                        else stsm4(a, pack2(av[24], av[25]), pack2(av[26], av[27]), one, one);
                    }
                }
                uint32_t PH[28];
                int it = 1;
#pragma unroll 1
                do {
                    float pp[28];
                    phi_gemm(tq, pp);
                    dual_softmax(pp, PH);
                    if (((trips >> (it + 1)) & 1) == 0) continue;
                    {
                        const int m = lane >> 3, rr = lane & 7;
                        const uint32_t rowa = hbuf + (w * 16 + rr + 8 * (m & 1)) * 128;
#pragma unroll
                        for (int j = 0; j < 7; j++) {
                            const int cg = 2 * j + (m >> 1), hi = cg >= 7;
                            stsm4(rowa + hi * 8192 + (((cg - 7 * hi) ^ rr) << 4), PH[4 * j], PH[4 * j + 1], PH[4 * j + 2], PH[4 * j + 3]);
                        }
                    }
                    fence_async();
                    STAMP(5 + so);
#define Q_STAGE(b0)                                                                           \
    R_WAIT();                                                                                 \
    { DECL_DB(b0, BASE128, 16, 0)                                                             \
    wg_fence();                                                                               \
    FOR7(mma_rs56<1, D128(0, t)>(tq, AQ(A, b0, t), (b0) + t > 0, SWB(b0, t, db, 0)));         \
    FOR7(mma_rs56<1, D128(HALF, t)>(tq, AQ(A, (b0) + 1, t), 1, db)); }                        \
    wg_commit();                                                                              \
    R_NEXT();
                    if (QE && wgi == 0) { kill<28>(tq); Q_STAGE(0) Q_STAGE(2) wg_wait<1>(); R_RELEASE(2); wg_wait<0>(); R_RELEASE(1); }
                    bar_sync(2, 256);
                    float kv[28];
                    const uint64_t da = BASE128(OFF_H + 16384, 16, 0), dbk = BASE128(OFF_H, 16, wgi * 512);
                    wg_fence();
                    FOR8(constexpr uint64_t o = ((t >> 2) * STAGE + (t & 3) * 2048) >> 4; mma_ss56_tt<o, o>(kv, t > 0, da, dbk));
                    wg_commit();
                    wg_wait<0>();
#pragma unroll
                    for (int hf = 0; hf < 2; hf++) {
                        const int d = 16 * w + g + 8 * hf;
                        if ((d < 56 && (d >= 28) == (c >= 2)) || d == 56) {
                            const int item = d < 56 ? 2 * d + (c & 1) : 112 + c;
                            uint4* dst = g_kv1 + ((sl * 16 + (item >> 3)) * 16 + tile) * 32 + wgi * 16 + (item & 7);
#define KVW(i) pack2(kv[4 * (i) + 2 * hf], kv[4 * (i) + 2 * hf + 1])
                            st_pkt<0>(dst, settag(KVW(0), tag), KVW(1), KVW(2), KVW(3));
                            st_pkt<8>(dst, settag(KVW(4), tag), KVW(5), KVW(6), 0u);
                        }
                    }
                    __syncwarp();
                    kseq++;
                    if (lane == 0) st_word(g_c1 + ((sl * 8 + wu) * 16 + tile) * 32, kseq);
                    bar_arrive(7, 384);
                    STAMP(6 + so);
                    if (!QE || wgi == 1) { kill<28>(tq); Q_STAGE(0) Q_STAGE(2) wg_wait<1>(); R_RELEASE(2); wg_wait<0>(); R_RELEASE(1); }
                    STAMP(7 + so);
                    kill<28>(PH);
                } while (((trips >> (++it)) & 1));
                STAMP(8 + so);
                FRESH();
                if (step) {
                    slice_load<PL(0)>(X, xp0 + sl * 512, lane);
                } else {
                    const uint32_t* xp = reinterpret_cast<const uint32_t*>(x_in + (size_t)(tile * 128 + wu * 16 + g) * 448 + 56 * sl + 2 * c);
#pragma unroll
                    for (int i = 0; i < 7; i++) { X[2 * i] = __ldg(xp + 4 * i); X[2 * i + 1] = __ldg(xp + 4 * i + 8 * 224); }
                }
                bar_sync(3, 384);
                STAMP(9 + so);
                const uint4* const osrc = xp0 + PL(1);
                {
                    float nm[32];
                    const uint64_t db = BASE128(OFF_KVB, 16, 0);
                    wg_fence();
                    FOR7(mma_rs64<0, ((t >> 2) * 8192 + (t & 3) * 32) / 16>(nm, PH[4 * t], PH[4 * t + 1], PH[4 * t + 2], PH[4 * t + 3], t > 0, db));
                    wg_commit();
                    wg_wait<0>();
                    LATE_ARRIVE();
                    const float i00 = rcp(nm[28] + 1e-6f), i01 = rcp(nm[29] + 1e-6f), i10 = rcp(nm[30] + 1e-6f), i11 = rcp(nm[31] + 1e-6f);
                    const float m0 = c >= 2 ? i01 : i00, m1 = c >= 2 ? i11 : i10;
                    uint32_t O[14];
#pragma unroll
                    for (int i = 0; i < 7; i++) {
                        const float f0 = i < 3 ? i00 : (i > 3 ? i01 : m0), f1 = i < 3 ? i10 : (i > 3 ? i11 : m1);
                        O[2 * i] = pack2(nm[4 * i] * f0, nm[4 * i + 1] * f0);
                        O[2 * i + 1] = pack2(nm[4 * i + 2] * f1, nm[4 * i + 3] * f1);
                    }
                    if (OST) { PP_WAIT() }
                    tag_slice(O, tag);
                    send_slice<PL(1)>(xp0 + sl * 512, lane, O);
                    seq++;
                    if (lane == 0) st_word(cx(sl), seq);
                    STAMP(10 + so);
                    if (OST) { PP_GO() }
                    OWN_SLICE(O)
                    PIN(A[0])
                }
                float ao[28];
#define WO_BLOCK(b)                                                                           \
    if ((b) > 0) blk_check<b>(A, BLK(osrc, b), lane, tag);                                    \
    if (((b) & 1) == 0) R_WAIT();                                                             \
    { DECL_DB(b, BASE128, 16, 0)                                                              \
    wg_fence();                                                                               \
    FOR7(mma_rs56<1, D128(((b) & 1) * HALF, t)>(ao, AQ(A, b, t), (b) + t > 0, SWB(b, t, db, 0))); } \
    wg_commit();                                                                              \
    if ((b) & 1) R_NEXT();
                {
                    const uint32_t cv = ld_word(cx(lane & 7));
                    R_WAIT();
                    DECL_DB(0, BASE128, 16, 0)
                    wg_fence();
                    FOR7(if constexpr (t < 3) mma_rs56<1, D128(0, t)>(ao, AQ(A, 0, t), t > 0, dbp));
                    wg_commit();
                    LATE_WAIT();
                    check_cnt(cv, cx(lane & 7), seq);
                    STAMP(56 + (step >> 1));
                    GAT_ISSUE1(PL(1))
                    GAT_ISSUE3(PL(1))
                    blk_load<2>(A, BLK(osrc, 2), lane);
                    STAMP(11 + so);
                    GAT_FETCH1(osrc, tag)
                    PIN(A[0]) PIN(A[1])
                    wg_fence();
                    FOR7(if constexpr (t >= 3) mma_rs56<1, D128(0, t)>(ao, AQ(A, 0, t), 1, SWB(0, t, db, 0)));
                    wg_commit();
                }
                WO_BLOCK(1)
                WO_BLOCK(2)
                GAT_FETCH3()
                WO_BLOCK(3)
                wg_wait<0>();
                R_RELEASE(2);
                STAMP(12 + so);
                WSUM(86 + 7 * (step >> 1));
                x_fix(X, xbits);
#pragma unroll
                for (int i = 0; i < 14; i++) X[i] = pack2(bf_lo(X[i]) + ao[2 * i], bf_hi(X[i]) + ao[2 * i + 1]);
            } else {
                uint32_t H[56];
                float ag[64];
#define F1_EPI(dst, ng, ag)                                                                    \
    _Pragma("unroll") for (int i = 0; i < 2 * (ng); i++)                                       \
        (dst)[i] = pack2(geglu(ag[2 * i], ag[4 * (ng) + 2 * i]), geglu(ag[2 * i + 1], ag[4 * (ng) + 2 * i + 1]));
#define H_PUSH(h0, off) st_async4(rem_h + (off), H[h0], H[(h0) + 1], H[(h0) + 2], H[(h0) + 3], mapa(BAR(B_RECV2 + wgi), hr ^ 1));
#define F1_BLOCK(b, first)                                                                     \
    if ((first) && (b) == 1) R_RELEASE(2);                                                     \
    if ((first) && (b) == 1) PUSH_ACK();                                                       \
    R_WAIT();                                                                                  \
    if ((b) == ((first) ? PPF : PPB)) { PP_WAIT() }                                            \
    { DECL_DB(b, BASE128, HALF, 0)                                                             \
    wg_fence();                                                                                \
    FOR7(mma_rs128<1, D128(0, t)>(ag, AQ(A, b, t), (b) + t > 0, SWB(b, t, db, 0));             \
         if constexpr (first) { PREP(b, t, true) }); }                                         \
    wg_commit();                                                                               \
    if ((b) == 3) { PP_GO() }                                                                  \
    if ((b) > 0) { wg_wait<1>(); R_RELEASE(1); }       \
    R_NEXT();
                normalize<0, 12>(A, k0, k1);
                F1_BLOCK(0, true) F1_BLOCK(1, true) F1_BLOCK(2, true) F1_BLOCK(3, true)
                if (t128 == 0) { mbar_expect_tx(BAR(B_RECV + wgi), 16384); mbar_expect_tx(BAR(B_RECV2 + wgi), 12288); }
                PUSH_BEGIN();
                wg_wait<0>();
                R_RELEASE(1);
                int p = 0;
#pragma unroll 1
                do {
                    F1_EPI(H + 32, 8, ag)
                    STAMP(4 + p + so);
                    WSUM(81 + p + 7 * (step >> 1));
                    if (((trips >> (p + 1)) & 1) == 0) continue;
                    {
                        const uint32_t pk = (p ? hbuf + 16384 : sb + OFF_KVB + wgi * 8192) + w * 2048;
#pragma unroll
                        for (int k = 0; k < 4; k++) sts4(pk + k * 512 + lane * 16, H[32 + 4 * k], H[33 + 4 * k], H[34 + 4 * k], H[35 + 4 * k]);
                        fence_async();
                        __syncwarp();
                        asm volatile(ELECT "cp.async.bulk.shared::cluster.shared::cta.mbarrier::complete_tx::bytes [%0], [%1], 2048, [%2]; }"
                                     ::"r"(mapa(hbuf + p * 8192 + w * 2048, hr ^ 1)), "r"(pk), "r"(mapa(BAR(B_RECV + wgi), hr ^ 1)) : "memory");
                    }
                    if (step == 1 && p == PKP) R_NEXT();
                    kill<64>(ag);
                    F1_BLOCK(0, false) F1_BLOCK(1, false) F1_BLOCK(2, false) F1_BLOCK(3, false)
                    wg_wait<0>();
                    R_RELEASE(1);
                    kill<16>(H + 32);
                } while (((trips >> (++p)) & 1));
#pragma unroll
                for (int k = 0; k < 4; k++) lds4(H + 16 + 4 * k, hbuf + 16384 + w * 2048 + k * 512 + lane * 16);
                __syncwarp();
                if (lane == 0) asm volatile("mbarrier.arrive.shared::cluster.b64 _, [%0];" ::"r"(mapa(BAR(B_ACK2 + wgi), hr ^ 1)) : "memory");
                const uint32_t rem_h = mapa(hbuf + w * 2048 + lane * 16, hr ^ 1);
#define F1_LAST(b0)                                                                            \
    R_WAIT();                                                                                  \
    if (b0) { PP_WAIT() }                                                                      \
    { DECL_DB(b0, BASE64, HALF, 1)                                                             \
    wg_fence();                                                                                \
    FOR7(mma_rs64<1, D64(0, t)>(al, AQ(A, b0, t), (b0) + t > 0, SWB(b0, t, db, 1)));           \
    FOR7(mma_rs64<1, D64(7168, t)>(al, AQ(A, (b0) + 1, t), 1, db)); }                          \
    wg_commit();                                                                               \
    if (b0) { PP_GO() }                                                                        \
    R_NEXT();
                float al[32];
                F1_LAST(0)
                mbar_wait(BAR(B_RECV + wgi), step >> 1);
                mbar_wait(BAR(B_ACK2 + wgi), step >> 1);
                H_PUSH(32, 16384) H_PUSH(36, 16896)
                F1_LAST(2)
                H_PUSH(40, 17408) H_PUSH(44, 17920)
                wg_wait<1>();
                R_RELEASE(2);
                wg_wait<0>();
                R_RELEASE(1);
                uint32_t HP[56];
#pragma unroll
                for (int k = 0; k < 4; k++) lds4(H + 4 * k, sb + OFF_KVB + wgi * 8192 + w * 2048 + k * 512 + lane * 16);
#pragma unroll
                for (int t = 0; t < 8; t++) lds4(HP + 4 * t, hbuf + (t >> 2) * 8192 + w * 2048 + (t & 3) * 512 + lane * 16);
                F1_EPI(H + 48, 4, al)
                H_PUSH(48, 24576 - w * 1024) H_PUSH(52, 25088 - w * 1024)
                STAMP(7 + so);
                WSUM(84 + 7 * (step >> 1));
                FRESH();
                float acc[28];
                const uint32_t roA = hr ? 256u : 0u, roB = hr ? (uint32_t)-1536 : 0u;
                const uint32_t rpA = hr ? 0u : 256u, rpB = hr ? 0u : (uint32_t)-1536;
                float res[28];
                uint32_t v0[14], v1[14], P[14];
                const uint4* ps = xp0 + sl * 512;
#define F2_OWN_A()                                                                             \
    R_WAIT();                                                                                  \
    d0 = BASE128(0, 16, R_ADJ + roA); d1 = BASE128(0, 16, R_ADJ + roB);                        \
    wg_fence();                                                                                \
    FOR14(if constexpr (t < OT) mma_rs56<1, t * 128>(acc, H[4 * t], H[4 * t + 1], H[4 * t + 2], H[4 * t + 3], t > 0, d0)); \
    wg_commit();
#define F2_OWN_B()                                                                             \
    wg_fence();                                                                                \
    FOR14(if constexpr (t >= OT) mma_rs56<1, t * 128>(acc, H[4 * t], H[4 * t + 1], H[4 * t + 2], H[4 * t + 3], 1, t < 12 ? d0 : d1)); \
    wg_commit();                                                                               \
    R_NEXT();
#define F2_PEER()                                                                              \
    R_WAIT();                                                                                  \
    if (F2PP) { PP_WAIT() }                                                                    \
    d0 = BASE128(0, 16, R_ADJ + rpA); d1 = BASE128(0, 16, R_ADJ + rpB);                        \
    wg_fence();                                                                                \
    FOR14(mma_rs56<1, t * 128>(acc, HP[4 * t], HP[4 * t + 1], HP[4 * t + 2], HP[4 * t + 3], 1, t < 12 ? d0 : d1)); \
    wg_commit();                                                                               \
    if (F2PP) { PP_GO() }                                                                      \
    R_NEXT();
#define F2_TURN(u)                                                                             \
    wg_wait<1>();                                                                              \
    if ((u) < 2 || TDEF < 2) R_RELEASE(2);                                                     \
    wg_wait<0>();                                                                              \
    if ((u) < 2 || TDEF < 1) R_RELEASE(1);                                                     \
    _Pragma("unroll") for (int i = 0; i < 14; i++) P[i] = pack2(acc[2 * i], acc[2 * i + 1]);   \
    tag_slice(P, tag);                                                                         \
    asm volatile("" : RW4(P, 0), RW4(P, 4), RW4(P, 8), RW2(P, 12));                            \
    kill<28>(acc);                                                                             \
    F2_OWN_A()                                                                                 \
    if ((u) == 2) { slice_load<PL(3)>(v0, ps, lane); slice_load<PL(4)>(v1, ps, lane); } \
    send_slice<PL(3 + (u))>(xp0 + (2 * ((pr + (u) + 1) & 3) + hr) * 512, lane, P);             \
    seq++;                                                                                     \
    if (lane == 0) st_word(cx(sl), seq);                                                       \
    __syncwarp();                                                                              \
    STAMP(8 + (u) + so);                                                                       \
    F2_OWN_B()
                uint64_t d0, d1;
                F2_OWN_A()
                F2_OWN_B()
                R_WAIT();
                d0 = BASE128(0, 16, R_ADJ + rpA); d1 = BASE128(0, 16, R_ADJ + rpB);
                wg_fence();
                FOR8(mma_rs56<1, t * 128>(acc, HP[4 * t], HP[4 * t + 1], HP[4 * t + 2], HP[4 * t + 3], 1, d0));
                wg_commit();
                mbar_wait(BAR(B_RECV2 + wgi), step >> 1);
#pragma unroll
                for (int k = 0; k < 4; k++) lds4(HP + 32 + 4 * k, hbuf + 16384 + w * 2048 + k * 512 + lane * 16);
                lds4(HP + 48, hbuf + 24576 + w * 1024 + lane * 16);
                lds4(HP + 52, hbuf + 25088 + w * 1024 + lane * 16);
                wg_fence();
                FOR14(if constexpr (t >= 8) mma_rs56<1, t * 128>(acc, HP[4 * t], HP[4 * t + 1], HP[4 * t + 2], HP[4 * t + 3], 1, t < 12 ? d0 : d1));
                wg_commit();
                R_NEXT();
                F2_TURN(0)
                F2_PEER()
                F2_TURN(1)
                F2_PEER()
                F2_TURN(2)
                if (step == 1) STAMP(64);
                slice_check<PL(3)>(v0, ps, lane, tag);
                slice_check<PL(4)>(v1, ps, lane, tag);
#pragma unroll
                for (int i = 0; i < 14; i++) { res[2 * i] = bf_lo(v0[i]) + bf_lo(v1[i]); res[2 * i + 1] = bf_hi(v0[i]) + bf_hi(v1[i]); }
                slice_load<PL(2)>(X, ps, lane);
                if (step == 1) STAMP(65);
                F2_PEER()
                if (step == 1) STAMP(66);
                poll_cnt(cx(2 * ((pr + 1) & 3) + hr), seq);
                if (step == 1) STAMP(67);
                slice_load<PL(5)>(v0, ps, lane);
                x_fix(X, xbits);
                slice_check<PL(5)>(v0, ps, lane, tag);
                if (lane < TDEF) mbar_arrive(BAR(B_EMPTY + (slot + NST - 3 - lane) % NST));
#pragma unroll
                for (int i = 0; i < 14; i++) { res[2 * i] += bf_lo(v0[i]); res[2 * i + 1] += bf_hi(v0[i]); }
                STAMP(11 + so);
                wg_wait<0>();
                R_RELEASE(2);
                STAMP(12 + so);
                WSUM(85 + 7 * (step >> 1));
#pragma unroll
                for (int i = 0; i < 14; i++) X[i] = pack2(fmaf(res[2 * i] + acc[2 * i], 0.5f, bf_lo(X[i])), fmaf(res[2 * i + 1] + acc[2 * i + 1], 0.5f, bf_hi(X[i])));
            }
        }
        {
            const int m = lane >> 3, rr = lane & 7;
            const uint32_t ob = hbuf + w * 2048, rowa = ob + (rr + 8 * (m & 1)) * 112 + (m >> 1) * 16;
#pragma unroll
            for (int j = 0; j < 3; j++) stsm4(rowa + 32 * j, X[4 * j], X[4 * j + 1], X[4 * j + 2], X[4 * j + 3]);
            asm volatile("stmatrix.sync.aligned.m8n8.x2.shared.b16 [%0], {%1,%2};" ::"r"(ob + (rr + 8 * (m & 1)) * 112 + 96), "r"(X[12]), "r"(X[13]) : "memory");
            fence_async();
            __syncwarp();
            if (lane == 0) {
                asm volatile("cp.async.bulk.tensor.2d.global.shared::cta.bulk_group [%0, {%2, %3}], [%1];" ::"l"(&maps.out), "r"(ob), "r"(56 * sl), "r"(tile * 128 + wu * 16) : "memory");
                asm volatile("cp.async.bulk.commit_group;" ::: "memory");
                asm volatile("cp.async.bulk.wait_group.read 0;" ::: "memory");
            }
        }
        STAMP(50);
        GSTAMP(61);
        PDUMP();
    }
}

#undef g
#undef pr
#undef c
#undef t128

typedef CUresult (*EncodeFn)(CUtensorMap*, CUtensorMapDataType, cuuint32_t, void*, const cuuint64_t*, const cuuint64_t*, const cuuint32_t*,
                             const cuuint32_t*, CUtensorMapInterleave, CUtensorMapSwizzle, CUtensorMapL2promotion, CUtensorMapFloatOOBfill);

static void make_map(EncodeFn enc, CUtensorMap* m, const void* p, uint64_t cols, uint64_t rows, uint32_t bc, uint32_t br, CUtensorMapSwizzle sw) {
    cuuint64_t gd[2] = {cols, rows};
    cuuint64_t gs[1] = {cols * 2};
    cuuint32_t bd[2] = {bc, br};
    cuuint32_t es[2] = {1, 1};
    enc(m, CU_TENSOR_MAP_DATA_TYPE_BFLOAT16, 2, const_cast<void*>(p), gd, gs, bd, es, CU_TENSOR_MAP_INTERLEAVE_NONE, sw,
        CU_TENSOR_MAP_L2_PROMOTION_L2_128B, CU_TENSOR_MAP_FLOAT_OOB_FILL_NONE);
}

extern "C" void kernel_launch(void* const* d_in, const int* in_sizes, int n_in, void* d_out, int out_size) {
    (void)in_sizes; (void)n_in; (void)out_size;
    static EncodeFn enc = nullptr;
    static Scratch* scratch = nullptr;
    if (!enc) {
        void* fn = nullptr;
        cudaDriverEntryPointQueryResult qr;
        cudaGetDriverEntryPoint("cuTensorMapEncodeTiled", &fn, cudaEnableDefault, &qr);
        enc = (EncodeFn)fn;
        cudaGetSymbolAddress((void**)&scratch, g_scratch);
        cudaFuncSetAttribute(fused_kernel, cudaFuncAttributeMaxDynamicSharedMemorySize, SMEM_BYTES);
    }
    Maps maps;
    {
        cuuint64_t gd[3] = {64, 2048, 7};
        cuuint64_t gs[2] = {896, 128};
        cuuint32_t bd[3] = {64, 32, 7};
        cuuint32_t es[3] = {1, 1, 1};
        enc(&maps.x, CU_TENSOR_MAP_DATA_TYPE_BFLOAT16, 3, d_in[0], gd, gs, bd, es, CU_TENSOR_MAP_INTERLEAVE_NONE, CU_TENSOR_MAP_SWIZZLE_128B,
            CU_TENSOR_MAP_L2_PROMOTION_L2_128B, CU_TENSOR_MAP_FLOAT_OOB_FILL_NONE);
    }
    make_map(enc, &maps.out, d_out, 448, 2048, 56, 16, CU_TENSOR_MAP_SWIZZLE_NONE);
    make_map(enc, &maps.qkv, d_in[1], 1344, 448, 64, 112, CU_TENSOR_MAP_SWIZZLE_128B);
    make_map(enc, &maps.wo, d_in[3], 448, 448, 64, 112, CU_TENSOR_MAP_SWIZZLE_128B);
    make_map(enc, &maps.wg, d_in[5], 1792, 448, 64, 112, CU_TENSOR_MAP_SWIZZLE_128B);
    make_map(enc, &maps.wu, d_in[6], 1792, 448, 64, 112, CU_TENSOR_MAP_SWIZZLE_128B);
    make_map(enc, &maps.wg32, d_in[5], 1792, 448, 32, 112, CU_TENSOR_MAP_SWIZZLE_64B);
    make_map(enc, &maps.wu32, d_in[6], 1792, 448, 32, 112, CU_TENSOR_MAP_SWIZZLE_64B);
    make_map(enc, &maps.wd, d_in[7], 448, 1792, 64, 112, CU_TENSOR_MAP_SWIZZLE_128B);
    fused_kernel<<<128, 384, SMEM_BYTES>>>(scratch, (const __nv_bfloat16*)d_in[0], (const __nv_bfloat16*)d_in[2], 7, (const __nv_bfloat16*)d_in[5],
                                           (const __nv_bfloat16*)d_in[6], (const __nv_bfloat16*)d_in[7], maps);
}
```

```cpp
#include <cuda_runtime.h>
#include <cuda.h>
#include <cuda_bf16.h>
#include <stdint.h>
#include <type_traits>

#define PPF 2
#define PKP 0
#define TDEF 1
#define TMPF 0
#define NORM1 0
#define ACAN 0
#define SPLIT0 1
#define OT 2
#define F2PP 0
#define PPK 2
#define QE 1
#define OST 1
#define PP

namespace {

constexpr uint32_t STAGE = 28672, HALF = 14336;
constexpr int NST = 5;
constexpr uint32_t OFF_H = NST * STAGE;
constexpr uint32_t OFF_KVB = OFF_H + 2 * STAGE;
constexpr uint32_t OFF_WPHI = OFF_KVB + 16384;
constexpr uint32_t OFF_XR = OFF_WPHI + 7168;
constexpr uint32_t OFF_BAR = OFF_XR + 6144;
constexpr uint32_t SMEM_BYTES = OFF_BAR + 384 + 1408;
constexpr int B_EMPTY = NST, B_RECV = 2 * NST, B_RECV2 = B_RECV + 2, B_XS = B_RECV2 + 2, B_PACK = B_XS + 1, B_GAT = B_PACK + 1, B_LATE = B_GAT + 16, B_ACK = B_LATE + 1, B_ACK2 = B_ACK + 2, B_COUNT = B_ACK2 + 2;

constexpr int PACK = 14 + 4 * PKP;

struct Maps { CUtensorMap x, qkv, wo, wg, wu, wg32, wu32, wd, out, xs; };

}

constexpr int PLANE = 16 * 2 * 8 * 512;
struct Scratch {
    uint4 ex[6 * PLANE];
    uint4 kv1[8 * 16 * 16 * 32];
    uint4 kv2[8 * 512];
    uint32_t c1[8 * 8 * 16 * 32];
    uint32_t cw[8 * 32];
    uint4 wp[8 * 32 * (HALF / 16)];
};
__device__ __align__(1024) Scratch g_scratch;
#define g_ex (sc->ex)
#define g_kv1 (sc->kv1)
#define g_kv2 (sc->kv2)
#define g_c1 (sc->c1)
#define g_cw (sc->cw)
#define g_wp (sc->wp)
#define STAMP(i)
#define GSTAMP(i)
#define PDUMP()
#define ASTAMP(i)

namespace {

__device__ __forceinline__ int fresh_tid() { int t; asm volatile("mov.u32 %0, %%tid.x;" : "=r"(t)); return t; }
template <int N> __device__ __forceinline__ void kill(uint32_t* v) {
#pragma unroll
    for (int i = 0; i < N; i++) v[i] = 0;
}
template <int N> __device__ __forceinline__ void kill(float* v) {
#pragma unroll
    for (int i = 0; i < N; i++) v[i] = 0.f;
}
__device__ __forceinline__ uint32_t s2u(const void* p) { return (uint32_t)__cvta_generic_to_shared(p); }
__device__ __forceinline__ void mbar_init(uint32_t a, uint32_t c) { asm volatile("mbarrier.init.shared::cta.b64 [%0], %1;" ::"r"(a), "r"(c) : "memory"); }
__device__ __forceinline__ void mbar_expect_tx(uint32_t a, uint32_t b) { asm volatile("mbarrier.arrive.expect_tx.shared::cta.b64 _, [%0], %1;" ::"r"(a), "r"(b) : "memory"); }
__device__ __forceinline__ void mbar_arrive(uint32_t a) { asm volatile("mbarrier.arrive.shared::cta.b64 _, [%0];" ::"r"(a) : "memory"); }
#define GIVE_UP(id) "trap;\n"
#define SPIN_MAX "0x400000"
#define SPIN_TAIL(id) "add.u32 n, n, 1;\n setp.lt.u32 p, n, " SPIN_MAX ";\n @p bra.uni LP;\n" GIVE_UP(id) " DN:\n }"
__device__ __forceinline__ void mbar_wait(uint32_t a, uint32_t ph) {
    asm volatile("{ .reg .pred p; .reg .b32 n; mov.u32 n, 0;\n LP:\n"
                 "mbarrier.try_wait.parity.shared::cta.b64 p, [%0], %1;\n @p bra DN;\n"
                 "add.u32 n, n, 1;\n setp.lt.u32 p, n, " SPIN_MAX ";\n @p bra LP;\n"
                 GIVE_UP("")
                 " DN:\n }" ::"r"(a), "r"(ph) : "memory");
}
#define ELECT "{ .reg .pred e; elect.sync _|e, 0xffffffff; @e "
__device__ __forceinline__ void tma2d(uint32_t dst, const CUtensorMap* m, int c0, int c1, uint32_t bar) {
    asm volatile(ELECT "cp.async.bulk.tensor.2d.shared::cluster.global.mbarrier::complete_tx::bytes [%0], [%1, {%3, %4}], [%2]; }" ::"r"(dst), "l"(m), "r"(bar), "r"(c0), "r"(c1) : "memory");
}
__device__ __forceinline__ void tma3x(uint32_t dst, const CUtensorMap* m, int row, uint32_t bar) {
    asm volatile(ELECT "cp.async.bulk.tensor.3d.shared::cluster.global.mbarrier::complete_tx::bytes [%0], [%1, {0, %3, 0}], [%2]; }" ::"r"(dst), "l"(m), "r"(bar), "r"(row) : "memory");
}
template <int OFF>
__device__ __forceinline__ void ld_pkt(uint32_t* v, const uint4* p) {
    asm volatile("{ .reg .b128 t; ld.relaxed.gpu.global.b128 t, [%4+%5]; mov.b128 {%0,%1,%2,%3}, t; }" : "=r"(v[0]), "=r"(v[1]), "=r"(v[2]), "=r"(v[3]) : "l"(p), "n"(OFF * 16) : "memory");
}
template <int OFF>
__device__ __forceinline__ void st_pkt(uint4* p, uint32_t a, uint32_t b, uint32_t c, uint32_t d) {
    asm volatile("{ .reg .b128 t; mov.b128 t, {%1,%2,%3,%4}; st.relaxed.gpu.global.b128 [%0+%5], t; }" ::"l"(p), "r"(a), "r"(b), "r"(c), "r"(d), "n"(OFF * 16) : "memory");
}
__device__ __forceinline__ uint32_t pack2(float lo, float hi) {
    uint32_t r;
    asm("cvt.rn.bf16x2.f32 %0, %1, %2;" : "=r"(r) : "f"(hi), "f"(lo));
    return r;
}
__device__ __forceinline__ float bf_lo(uint32_t w) { return __uint_as_float(w << 16); }
__device__ __forceinline__ float bf_hi(uint32_t w) { return __uint_as_float(w & 0xffff0000u); }
__device__ __forceinline__ uint32_t settag(uint32_t w, uint32_t tag) { return (w & ~1u) | tag; }
__device__ __forceinline__ float ex2(float x) { float y; asm("ex2.approx.ftz.f32 %0, %1;" : "=f"(y) : "f"(x)); return y; }
__device__ __forceinline__ float rcp(float x) { float y; asm("rcp.approx.ftz.f32 %0, %1;" : "=f"(y) : "f"(x)); return y; }
__device__ __forceinline__ float tanh_hw(float x) { float y; asm("tanh.approx.f32 %0, %1;" : "=f"(y) : "f"(x)); return y; }
__device__ __forceinline__ void stsm4(uint32_t addr, uint32_t a, uint32_t b, uint32_t c, uint32_t d) {
    asm volatile("stmatrix.sync.aligned.m8n8.x4.shared.b16 [%0], {%1,%2,%3,%4};" ::"r"(addr), "r"(a), "r"(b), "r"(c), "r"(d) : "memory");
}
__device__ __forceinline__ void fence_async() { asm volatile("fence.proxy.async.shared::cta;" ::: "memory"); }
__device__ __forceinline__ void bar_sync(int id, int n) { asm volatile("bar.sync %0, %1;" ::"r"(id), "r"(n) : "memory"); }
__device__ __forceinline__ void bar_arrive(int id, int n) { asm volatile("bar.arrive %0, %1;" ::"r"(id), "r"(n) : "memory"); }
__device__ __forceinline__ void wg_fence() { asm volatile("wgmma.fence.sync.aligned;" ::: "memory"); }
__device__ __forceinline__ void wg_commit() { asm volatile("wgmma.commit_group.sync.aligned;" ::: "memory"); }
template <int N> __device__ __forceinline__ void wg_wait() { asm volatile("wgmma.wait_group.sync.aligned %0;" ::"n"(N) : "memory"); }

constexpr uint32_t SB0 = 1024;
__host__ __device__ constexpr uint32_t dlo(uint32_t off, uint32_t lbo) { return ((SB0 + off) >> 4) | ((lbo >> 4) << 16); }
__host__ __device__ constexpr uint32_t dhi(uint32_t sbo, uint32_t sw) { return (sbo >> 4) | (sw << 30); }
__device__ __forceinline__ uint64_t dbase(uint32_t lo, uint32_t hi) { uint64_t d; asm volatile("mov.b64 %0, {%1, %2};" : "=l"(d) : "r"(lo), "r"(hi)); return d; }
#define BASE128(off, lbo, adj) dbase(dlo(off, lbo) + (adj), dhi(1024, 1))
#define BASE64(off, lbo, adj) dbase(dlo(off, lbo) + (adj), dhi(512, 2))

#define ACC4(d, o) "+f"(d[o]), "+f"(d[o + 1]), "+f"(d[o + 2]), "+f"(d[o + 3])
#define ACC28(d) ACC4(d, 0), ACC4(d, 4), ACC4(d, 8), ACC4(d, 12), ACC4(d, 16), ACC4(d, 20), ACC4(d, 24)
#define ACC32(d, o) ACC4(d, o), ACC4(d, o + 4), ACC4(d, o + 8), ACC4(d, o + 12), ACC4(d, o + 16), ACC4(d, o + 20), ACC4(d, o + 24), ACC4(d, o + 28)

template <int TB, uint64_t D>
__device__ __forceinline__ void mma_rs56(float* d, uint32_t a0, uint32_t a1, uint32_t a2, uint32_t a3, int sd, uint64_t base) {
    asm volatile("{ .reg .pred p; .reg .b64 db; setp.ne.b32 p, %32, 0; add.u64 db, %33, %34;\n"
                 "wgmma.mma_async.sync.aligned.m64n56k16.f32.bf16.bf16 "
                 "{%0,%1,%2,%3,%4,%5,%6,%7,%8,%9,%10,%11,%12,%13,%14,%15,%16,%17,%18,%19,%20,%21,%22,%23,%24,%25,%26,%27}, "
                 "{%28,%29,%30,%31}, db, p, 1, 1, %35; }\n"
                 : ACC28(d)
                 : "r"(a0), "r"(a1), "r"(a2), "r"(a3), "r"(sd), "l"(base), "n"(D), "n"(TB));
}
template <int TB, uint64_t D>
__device__ __forceinline__ void mma_rs64(float* d, uint32_t a0, uint32_t a1, uint32_t a2, uint32_t a3, int sd, uint64_t base) {
    asm volatile("{ .reg .pred p; .reg .b64 db; setp.ne.b32 p, %36, 0; add.u64 db, %37, %38;\n"
                 "wgmma.mma_async.sync.aligned.m64n64k16.f32.bf16.bf16 "
                 "{%0,%1,%2,%3,%4,%5,%6,%7,%8,%9,%10,%11,%12,%13,%14,%15,%16,%17,%18,%19,%20,%21,%22,%23,%24,%25,%26,%27,%28,%29,%30,%31}, "
                 "{%32,%33,%34,%35}, db, p, 1, 1, %39; }\n"
                 : ACC32(d, 0)
                 : "r"(a0), "r"(a1), "r"(a2), "r"(a3), "r"(sd), "l"(base), "n"(D), "n"(TB));
}
template <int TB, uint64_t D>
__device__ __forceinline__ void mma_rs128(float* d, uint32_t a0, uint32_t a1, uint32_t a2, uint32_t a3, int sd, uint64_t base) {
    asm volatile("{ .reg .pred p; .reg .b64 db; setp.ne.b32 p, %68, 0; add.u64 db, %69, %70;\n"
                 "wgmma.mma_async.sync.aligned.m64n128k16.f32.bf16.bf16 "
                 "{%0,%1,%2,%3,%4,%5,%6,%7,%8,%9,%10,%11,%12,%13,%14,%15,%16,%17,%18,%19,%20,%21,%22,%23,%24,%25,%26,%27,%28,%29,%30,%31,%32,%33,%34,%35,%36,%37,%38,%39,%40,%41,%42,%43,%44,%45,%46,%47,%48,%49,%50,%51,%52,%53,%54,%55,%56,%57,%58,%59,%60,%61,%62,%63}, "
                 "{%64,%65,%66,%67}, db, p, 1, 1, %71; }\n"
                 : ACC32(d, 0), ACC32(d, 32)
                 : "r"(a0), "r"(a1), "r"(a2), "r"(a3), "r"(sd), "l"(base), "n"(D), "n"(TB));
}
template <uint64_t DA, uint64_t DB>
__device__ __forceinline__ void mma_ss56_tt(float* d, int sd, uint64_t ba, uint64_t bb) {
    asm volatile("{ .reg .pred p; .reg .b64 da, db; setp.ne.b32 p, %28, 0; add.u64 da, %29, %31; add.u64 db, %30, %32;\n"
                 "wgmma.mma_async.sync.aligned.m64n56k16.f32.bf16.bf16 "
                 "{%0,%1,%2,%3,%4,%5,%6,%7,%8,%9,%10,%11,%12,%13,%14,%15,%16,%17,%18,%19,%20,%21,%22,%23,%24,%25,%26,%27}, "
                 "da, db, p, 1, 1, 1, 1; }\n"
                 : ACC28(d)
                 : "r"(sd), "l"(ba), "l"(bb), "n"(DA), "n"(DB));
}
template <int... I> struct Seq {};
template <class F, int... I> __device__ __forceinline__ void static_for_impl(F&& f, Seq<I...>) { (f(std::integral_constant<int, I>{}), ...); }
#define FOR7(...) static_for_impl([&](auto T_) { constexpr int t = decltype(T_)::value; __VA_ARGS__; }, Seq<0, 1, 2, 3, 4, 5, 6>{})
#define FOR8(...) static_for_impl([&](auto T_) { constexpr int t = decltype(T_)::value; __VA_ARGS__; }, Seq<0, 1, 2, 3, 4, 5, 6, 7>{})
#define FOR14(...) static_for_impl([&](auto T_) { constexpr int t = decltype(T_)::value; __VA_ARGS__; }, Seq<0, 1, 2, 3, 4, 5, 6, 7, 8, 9, 10, 11, 12, 13>{})

__device__ __forceinline__ int kblk(int p, int b) { return b == 0 ? p : b - (b <= p); }
__host__ __device__ constexpr int krow(int t) { return t < 3 ? 16 * t : (t < 6 ? 56 + 16 * (t - 3) : 48); }
#define AQ(A, b, t) ((t) < 3 ? A[2 * (b)][4 * (t)] : (t) < 6 ? A[2 * (b) + 1][4 * ((t) - 3)] : A[2 * (b)][12]), \
                    ((t) < 3 ? A[2 * (b)][4 * (t) + 1] : (t) < 6 ? A[2 * (b) + 1][4 * ((t) - 3) + 1] : A[2 * (b)][13]), \
                    ((t) < 3 ? A[2 * (b)][4 * (t) + 2] : (t) < 6 ? A[2 * (b) + 1][4 * ((t) - 3) + 2] : A[2 * (b) + 1][12]), \
                    ((t) < 3 ? A[2 * (b)][4 * (t) + 3] : (t) < 6 ? A[2 * (b) + 1][4 * ((t) - 3) + 3] : A[2 * (b) + 1][13])
#define D128(off, t) ((uint64_t)(((off) + krow(t) * 128) >> 4) + ((uint64_t)((t) == 6 ? (7168 - 1024) >> 4 : 0) << 32))
#define D64(off, t) ((uint64_t)(((off) + krow(t) * 64) >> 4) + ((uint64_t)((t) == 6 ? (3584 - 512) >> 4 : 0) << 32))

#define PL(k) (((k) - 3) * PLANE)
__device__ __forceinline__ void st_word(uint32_t* p, uint32_t v) { asm volatile("st.relaxed.gpu.global.u32 [%0], %1;" ::"l"(p), "r"(v) : "memory"); }
__device__ __forceinline__ uint32_t ld_word(const uint32_t* p) { uint32_t v; asm volatile("ld.relaxed.gpu.global.u32 %0, [%1];" : "=r"(v) : "l"(p) : "memory"); return v; }
__device__ __forceinline__ void tag_slice(uint32_t* w, uint32_t tag) { w[0] = settag(w[0], tag); w[4] = settag(w[4], tag); w[8] = settag(w[8], tag); w[12] = settag(w[12], tag); }
template <int O>
__device__ __forceinline__ void send_slice(uint4* dst, int lane, const uint32_t* w) {
    st_pkt<O>(dst, w[0], w[1], w[2], w[3]);
    st_pkt<O + 32>(dst, w[4], w[5], w[6], w[7]);
    st_pkt<O + 64>(dst, w[8], w[9], w[10], w[11]);
    asm volatile("{ .reg .b64 t; mov.b64 t, {%1,%2}; st.relaxed.gpu.global.b64 [%0+%3], t; }" ::"l"((char*)dst - lane * 8), "r"(w[12]), "r"(w[13]), "n"(16 * (O + 96)) : "memory");
}
#define RW4(v, o) "+r"(v[o]), "+r"(v[(o) + 1]), "+r"(v[(o) + 2]), "+r"(v[(o) + 3])
#define RW2(v, o) "+r"(v[o]), "+r"(v[(o) + 1])
#define WR4(v, o) "=&r"(v[o]), "=&r"(v[(o) + 1]), "=&r"(v[(o) + 2]), "=&r"(v[(o) + 3])
#define LDP(a, b, c, d, addr, off) "ld.relaxed.gpu.global.b128 q, [" addr "+" off "];\n mov.b128 {" a "," b "," c "," d "}, q;\n"
#define LDH(a, b, addr, off) "ld.relaxed.gpu.global.b64 h, [" addr "+" off "];\n mov.b64 {" a "," b "}, h;\n"
#define VOTE_OK "and.b32 t, t, 1;\n setp.ne.u32 p, t, 0;\n vote.sync.any.pred p, p, 0xffffffff;\n @!p bra.uni DN;\n"
#define CHK(x, tag) "lop3.b32 t, " x ", " tag ", t, 0xBE;\n"
__device__ __forceinline__ void check_cnt(uint32_t v, const uint32_t* p, uint32_t target) {
    asm volatile("{ .reg .pred p; .reg .b32 n, t; mov.u32 n, 0; mov.u32 t, %2;\n LP:\n"
                 "sub.s32 t, t, %1;\n setp.lt.s32 p, t, 0;\n vote.sync.any.pred p, p, 0xffffffff;\n @!p bra.uni DN;\n ld.relaxed.gpu.global.u32 t, [%0];\n" SPIN_TAIL("7")
                 ::"l"(p), "r"(target), "r"(v) : "memory");
}
__device__ __forceinline__ void poll_cnt(const uint32_t* p, uint32_t target) {
    asm volatile("{ .reg .pred p; .reg .b32 n, t; mov.u32 n, 0;\n LP:\n"
                 "ld.relaxed.gpu.global.u32 t, [%0];\n sub.s32 t, t, %1;\n setp.lt.s32 p, t, 0;\n vote.sync.any.pred p, p, 0xffffffff;\n @!p bra.uni DN;\n" SPIN_TAIL("1")
                 ::"l"(p), "r"(target) : "memory");
}
template <int STR>
__device__ __forceinline__ void poll4_kv(uint32_t* v, const uint4* p, uint32_t tag) {
    asm volatile("{ .reg .pred p; .reg .b32 n, t; .reg .b128 q; mov.u32 n, 0;\n LP:\n"
                 LDP("%0", "%1", "%2", "%3", "%16", "0") LDP("%4", "%5", "%6", "%7", "%16", "%18")
                 LDP("%8", "%9", "%10", "%11", "%16", "%19") LDP("%12", "%13", "%14", "%15", "%16", "%20")
                 "xor.b32 t, %0, %17;\n" CHK("%4", "%17") CHK("%8", "%17") CHK("%12", "%17") VOTE_OK SPIN_TAIL("2")
                 : WR4(v, 0), WR4(v, 4), WR4(v, 8), WR4(v, 12)
                 : "l"(p), "r"(tag), "n"(16 * STR), "n"(32 * STR), "n"(48 * STR)
                 : "memory");
}
template <int B>
__device__ __forceinline__ void blk_load(uint32_t (&A)[8][14], const uint4* src, int lane) {
    ld_pkt<0>(&A[2 * B][0], src); ld_pkt<32>(&A[2 * B][4], src); ld_pkt<64>(&A[2 * B][8], src);
    ld_pkt<512>(&A[2 * B + 1][0], src); ld_pkt<544>(&A[2 * B + 1][4], src); ld_pkt<576>(&A[2 * B + 1][8], src);
    asm volatile("{ .reg .b64 h;\n" LDH("%0", "%1", "%4", "1536") LDH("%2", "%3", "%4", "9728") "}"
                 : "=&r"(A[2 * B][12]), "=&r"(A[2 * B][13]), "=&r"(A[2 * B + 1][12]), "=&r"(A[2 * B + 1][13])
                 : "l"((const char*)src - lane * 8) : "memory");
}
template <int B>
__device__ __forceinline__ void blk_check(uint32_t (&A)[8][14], const uint4* src, int lane, uint32_t tag) {
    asm volatile("{ .reg .pred p; .reg .b32 n, t; .reg .b128 q; .reg .b64 h, a8; mov.u32 n, 0;\n LP:\n"
                 "xor.b32 t, %0, %30;\n" CHK("%4", "%30") CHK("%8", "%30") CHK("%12", "%30") CHK("%16", "%30") CHK("%20", "%30") CHK("%24", "%30") CHK("%26", "%30") VOTE_OK
                 LDP("%0", "%1", "%2", "%3", "%28", "0") LDP("%4", "%5", "%6", "%7", "%28", "512") LDP("%8", "%9", "%10", "%11", "%28", "1024")
                 LDP("%12", "%13", "%14", "%15", "%28", "8192") LDP("%16", "%17", "%18", "%19", "%28", "8704") LDP("%20", "%21", "%22", "%23", "%28", "9216")
                 "mad.wide.s32 a8, %29, -8, %28;\n" LDH("%24", "%25", "a8", "1536") LDH("%26", "%27", "a8", "9728") SPIN_TAIL("3")
                 "\n and.b32 %0, %0, -2; and.b32 %4, %4, -2; and.b32 %8, %8, -2; and.b32 %12, %12, -2; and.b32 %16, %16, -2; and.b32 %20, %20, -2; and.b32 %24, %24, -2; and.b32 %26, %26, -2;"
                 : RW4(A[2 * B], 0), RW4(A[2 * B], 4), RW4(A[2 * B], 8), RW4(A[2 * B + 1], 0), RW4(A[2 * B + 1], 4), RW4(A[2 * B + 1], 8),
                   RW2(A[2 * B], 12), RW2(A[2 * B + 1], 12)
                 : "l"(src), "r"(lane), "r"(tag)
                 : "memory");
}
__device__ __forceinline__ void st_async4(uint32_t a, uint32_t x, uint32_t y, uint32_t z, uint32_t w, uint32_t bar) {
    asm volatile("st.async.weak.shared::cluster.mbarrier::complete_tx::bytes.v4.b32 [%0], {%1,%2,%3,%4}, [%5];" ::"r"(a), "r"(x), "r"(y), "r"(z), "r"(w), "r"(bar) : "memory");
}
__device__ __forceinline__ uint32_t mapa(uint32_t a, uint32_t cta) { uint32_t r; asm("mapa.shared::cluster.u32 %0, %1, %2;" : "=r"(r) : "r"(a), "r"(cta)); return r; }
__device__ __forceinline__ void stat_load(uint32_t* v, const uint4* p) { ld_pkt<0>(v, p); ld_pkt<512>(v + 4, p); }
__device__ __forceinline__ void stat_check(uint32_t* v, const uint4* p, uint32_t tag) {
    asm volatile("{ .reg .pred p; .reg .b32 n, t; .reg .b128 q; mov.u32 n, 0;\n LP:\n"
                 "xor.b32 t, %3, %9;\n" CHK("%7", "%9") VOTE_OK
                 LDP("%0", "%1", "%2", "%3", "%8", "0") LDP("%4", "%5", "%6", "%7", "%8", "8192") SPIN_TAIL("4")
                 : RW4(v, 0), RW4(v, 4) : "l"(p), "r"(tag) : "memory");
}
__device__ __forceinline__ uint32_t x_bits(const uint32_t* X) {
    uint32_t r;
    asm volatile("{ .reg .b32 a, b; prmt.b32 a, %1, %2, 0x0040; prmt.b32 b, %3, %4, 0x0040; prmt.b32 %0, a, b, 0x5410; }" : "=r"(r) : "r"(X[0]), "r"(X[4]), "r"(X[8]), "r"(X[12]));
    return r;
}
template <int O>
__device__ __forceinline__ void slice_load(uint32_t* v, const uint4* p, int lane) {
    ld_pkt<O>(v, p); ld_pkt<O + 32>(v + 4, p); ld_pkt<O + 64>(v + 8, p);
    asm volatile("{ .reg .b64 h;\n" LDH("%0", "%1", "%2", "%3") "}" : "=r"(v[12]), "=r"(v[13]) : "l"((const char*)p - lane * 8), "n"(16 * (O + 96)) : "memory");
}
template <int O>
__device__ __forceinline__ void slice_check(uint32_t* v, const uint4* p, int lane, uint32_t tag) {
    asm volatile("{ .reg .pred p; .reg .b32 n, t; .reg .b128 q; .reg .b64 h; mov.u32 n, 0;\n LP:\n"
                 "xor.b32 t, %0, %16;\n" CHK("%4", "%16") CHK("%8", "%16") CHK("%12", "%16") VOTE_OK
                 LDP("%0", "%1", "%2", "%3", "%14", "%17") LDP("%4", "%5", "%6", "%7", "%14", "%18") LDP("%8", "%9", "%10", "%11", "%14", "%19")
                 LDH("%12", "%13", "%15", "%20") SPIN_TAIL("5")
                 : RW4(v, 0), RW4(v, 4), RW4(v, 8), RW2(v, 12)
                 : "l"(p), "l"((const char*)p - lane * 8), "r"(tag), "n"(16 * O), "n"(16 * (O + 32)), "n"(16 * (O + 64)), "n"(16 * (O + 96))
                 : "memory");
}
__device__ __forceinline__ void x_fix(uint32_t* X, uint32_t bits) {
    X[0] = __byte_perm(X[0], bits, 0x3214); X[4] = __byte_perm(X[4], bits, 0x3215); X[8] = __byte_perm(X[8], bits, 0x3216); X[12] = __byte_perm(X[12], bits, 0x3217);
}
__device__ __forceinline__ void sts4(uint32_t a, uint32_t x, uint32_t y, uint32_t z, uint32_t w) {
    asm volatile("st.shared.v4.u32 [%0], {%1,%2,%3,%4};" ::"r"(a), "r"(x), "r"(y), "r"(z), "r"(w) : "memory");
}
__device__ __forceinline__ void lds4(uint32_t* v, uint32_t a) {
    asm volatile("ld.shared.v4.u32 {%0,%1,%2,%3}, [%4];" : "=r"(v[0]), "=r"(v[1]), "=r"(v[2]), "=r"(v[3]) : "r"(a) : "memory");
}
struct LnCoef { uint32_t hi, lo, sh; };
__device__ __forceinline__ LnCoef ln_coef(float sum, float sq) {
    sum += __shfl_xor_sync(0xffffffffu, sum, 1); sq += __shfl_xor_sync(0xffffffffu, sq, 1);
    sum += __shfl_xor_sync(0xffffffffu, sum, 2); sq += __shfl_xor_sync(0xffffffffu, sq, 2);
    const float mean = sum * (1.f / 448.f);
    const float var = fmaxf(fmaf(-mean, mean, sq * (1.f / 448.f)), 0.f);
    const float sc = rsqrtf(var + 1e-5f);
    LnCoef r;
    r.hi = pack2(sc, sc);
    const float lo = sc - bf_lo(r.hi), sh = -mean * sc;
    r.lo = pack2(lo, lo);
    r.sh = pack2(sh, sh);
    return r;
}
template <int B>
__device__ __forceinline__ void normalize(uint32_t (&A)[8][14], const LnCoef& c0, const LnCoef& c1) {
#pragma unroll
    for (int s = 2 * B; s < 2 * B + 2; s++)
#pragma unroll
        for (int i = 0; i < 14; i++) {
            const LnCoef& k = (i & 1) ? c1 : c0;
            asm("{ .reg .b32 t; fma.rn.bf16x2 t, %0, %2, %3; fma.rn.bf16x2 %0, %0, %1, t; }" : "+r"(A[s][i]) : "r"(k.hi), "r"(k.lo), "r"(k.sh));
        }
}
__device__ __forceinline__ void slice_stats(const uint32_t* w, float* st) {
    float a = 0.f, b = 0.f, p = 0.f, q = 0.f;
#pragma unroll
    for (int i = 0; i < 7; i++) {
        const float e0 = bf_lo(w[2 * i]), e1 = bf_hi(w[2 * i]), e2 = bf_lo(w[2 * i + 1]), e3 = bf_hi(w[2 * i + 1]);
        a += e0 + e1; b += e2 + e3;
        p = fmaf(e0, e0, p); p = fmaf(e1, e1, p); q = fmaf(e2, e2, q); q = fmaf(e3, e3, q);
    }
    a += __shfl_xor_sync(0xffffffffu, a, 1); p += __shfl_xor_sync(0xffffffffu, p, 1); b += __shfl_xor_sync(0xffffffffu, b, 1); q += __shfl_xor_sync(0xffffffffu, q, 1);
    a += __shfl_xor_sync(0xffffffffu, a, 2); p += __shfl_xor_sync(0xffffffffu, p, 2); b += __shfl_xor_sync(0xffffffffu, b, 2); q += __shfl_xor_sync(0xffffffffu, q, 2);
    st[0] = a; st[1] = p; st[2] = b; st[3] = q;
}
__device__ __forceinline__ void dual_softmax(const float* p, uint32_t* out) {
    constexpr float L = 1.4426950408889634f;
#pragma unroll
    for (int r = 0; r < 2; r++) {
        float mx = fmaxf(p[2 * r], p[2 * r + 1]), mn = fminf(p[2 * r], p[2 * r + 1]);
#pragma unroll
        for (int i = 1; i < 7; i++) {
            mx = fmaxf(mx, fmaxf(p[4 * i + 2 * r], p[4 * i + 2 * r + 1]));
            mn = fminf(mn, fminf(p[4 * i + 2 * r], p[4 * i + 2 * r + 1]));
        }
        mx = fmaxf(mx, __shfl_xor_sync(0xffffffffu, mx, 1));
        mn = fminf(mn, __shfl_xor_sync(0xffffffffu, mn, 1));
        const float bx = -mx * L, bn = mn * L;
        float ep[14], en[14], sp = 0.f, sn = 0.f;
#pragma unroll
        for (int i = 0; i < 14; i++) {
            const float v = p[4 * (i >> 1) + 2 * r + (i & 1)];
            ep[i] = ex2(fmaf(v, L, bx));
            en[i] = ex2(fmaf(v, -L, bn));
            sp += ep[i]; sn += en[i];
        }
        sp += __shfl_xor_sync(0xffffffffu, sp, 1);
        sn += __shfl_xor_sync(0xffffffffu, sn, 1);
        const float ip = rcp(sp), in = rcp(sn);
#pragma unroll
        for (int i = 0; i < 7; i++) {
            out[4 * i + r] = pack2(ep[2 * i] * ip, ep[2 * i + 1] * ip);
            out[4 * i + 2 + r] = pack2(en[2 * i] * in, en[2 * i + 1] * in);
        }
    }
}
__device__ __forceinline__ float geglu(float g, float u) {
    const float t = tanh_hw(g * fmaf(g * g, 0.7978845608028654f * 0.044715f, 0.7978845608028654f));
    const float gu = g * u;
    return fmaf(t, gu, gu);
}
__device__ __forceinline__ void phi_gemm(const float* t, float* p) {
    uint32_t w[14];
#pragma unroll
    for (int i = 0; i < 14; i++) w[i] = pack2(t[2 * i], t[2 * i + 1]);
    const uint64_t db = BASE128(OFF_WPHI, 16, 0);
    wg_fence();
    mma_rs56<0, 0>(p, w[0], w[1], w[2], w[3], 0, db);
    mma_rs56<0, 2>(p, w[4], w[5], w[6], w[7], 1, db);
    mma_rs56<0, 4>(p, w[8], w[9], w[10], w[11], 1, db);
    mma_rs56<0, 6>(p, w[12], w[13], 0u, 0u, 1, db);
    wg_commit();
    wg_wait<0>();
}

}

#define BAR(i) (bars + 8 * (i))
#define R_WAIT() mbar_wait(BAR(slot), ph)
#define WSUM(i)
#define R_ADJ (slot * (STAGE >> 4))
#define R_NEXT() do { eb2 = eb1; eb1 = BAR(B_EMPTY + slot); if (++slot == NST) { slot = 0; ph ^= 1; } } while (0)
#define R_RELEASE(k) do { if (lane == 0) mbar_arrive((k) == 1 ? eb1 : eb2); } while (0)
#define PUSH_BEGIN() do { mbar_wait(BAR(B_ACK + wgi), ackph); ackph ^= 1; } while (0)
#define PUSH_ACK() do { __syncwarp(); if (lane == 0) asm volatile("mbarrier.arrive.shared::cluster.b64 _, [%0];" ::"r"(mapa(BAR(B_ACK + wgi), hr ^ 1)) : "memory"); } while (0)

__global__ void __cluster_dims__(2, 1, 1) __launch_bounds__(384, 1)
fused_kernel(Scratch* const sc, const __nv_bfloat16* __restrict__ x_in, const __nv_bfloat16* __restrict__ w_phi, const int trips,
             const __nv_bfloat16* __restrict__ wg, const __nv_bfloat16* __restrict__ wu, const __nv_bfloat16* __restrict__ wd,
             const __grid_constant__ Maps maps) {
    extern __shared__ __align__(1024) unsigned char smem_raw[];
    const uint32_t sb = s2u(smem_raw);
    const uint32_t bars = sb + OFF_BAR;
    const int wgi = __shfl_sync(0xffffffffu, threadIdx.x >> 7, 0);
    const int hr = blockIdx.x & 1, ck = blockIdx.x >> 1;
    const int gp = (ck - 4) & 7, q7 = ((ck - 36) * 37) >> 8;
    const int pr = __shfl_sync(0xffffffffu, ck < 4 ? ck : (ck < 36 ? (ck - 4) >> 3 : q7), 0);
    const int tile = __shfl_sync(0xffffffffu, ck < 4 ? 0 : (ck < 36 ? (gp ? 2 * gp : 1) : 2 * (ck - 36 - 7 * q7) + 3), 0);
    const int sl = 2 * pr + hr;
    STAMP(0);
    GSTAMP(60);
    if (threadIdx.x == 256) {
#pragma unroll
        for (int i = 0; i < NST; i++) mbar_init(BAR(i), 1);
        mbar_init(BAR(B_XS), 1);
        asm volatile("fence.mbarrier_init.release.cluster;" ::: "memory");
    }
    if (threadIdx.x == 288) {
        if ((sb & 0x3FFFF) != SB0) asm volatile("trap;");
#pragma unroll
        for (int i = NST; i < B_COUNT; i++) if (i != B_XS) mbar_init(BAR(i), i >= B_ACK ? 4 : (i < B_RECV || i == B_LATE ? 8 : 1));
        asm volatile("fence.mbarrier_init.release.cluster;" ::: "memory");
    }
    __syncwarp();
    asm volatile("barrier.cluster.arrive.relaxed.aligned;" ::: "memory");

    if (wgi == 2) {
        asm volatile("setmaxnreg.dec.sync.aligned.u32 40;");
        const int t128 = fresh_tid() & 127, w = __shfl_sync(0xffffffffu, t128 >> 5, 0), lane = t128 & 31;
        uint32_t e0[2] = {0, 0}, e1[2] = {0, 0}, cw_target = 0;
        if (w == 0) {
            asm volatile(ELECT "mbarrier.arrive.expect_tx.shared::cta.b64 _, [%0], %1; }" ::"r"(BAR(B_XS)), "r"(HALF) : "memory");
            tma2d(sb + OFF_KVB, &maps.xs, 56 * sl, tile * 128, BAR(B_XS));
#pragma unroll 1
            for (int n = 0; n < NST; n++) {
                const uint32_t dst = sb + n * STAGE, fb = BAR(n);
                asm volatile(ELECT "mbarrier.arrive.expect_tx.shared::cta.b64 _, [%0], %1; }" ::"r"(fb), "r"(n < 2 ? 2 * STAGE : STAGE) : "memory");
                if (n < 2) {
                    tma3x(sb + OFF_H + n * STAGE, &maps.x, tile * 128 + n * 64, fb);
                    tma3x(dst, &maps.x, tile * 128 + n * 64 + 32, fb);
                } else {
                    if (n == 3) mbar_wait(BAR(1), 0);
                    const int ra = 112 * (n - 2);
                    tma2d(dst, &maps.qkv, 448 + 56 * sl, ra, fb);
                    tma2d(dst + HALF, &maps.qkv, 896 + 56 * sl, ra, fb);
                }
            }
            asm volatile("barrier.cluster.wait.aligned;" ::: "memory");
            cw_target = (ld_word(g_cw + sl * 32) & ~15u) + 16;
#pragma unroll 1
            for (int k = 0; k < 2; k++) {
                const int n = t128 + 32 * k;
                int m = n - 2 - (n > PACK);
                const bool packed = m >= 30 ? (m < 38 || m >= 52) : m >= 22;
                if (m >= 30) m -= 30;
                if (n == PACK) m = tile < 8 ? tile : tile + 14;
                const int rot = n < 8 ? 0 : pr;
                const int ra = 112 * kblk(rot, m & 3), rb = 112 * kblk(rot, 2 * m & 3), rc = 112 * kblk(rot, (2 * m + 1) & 3);
                int kind = 0, m0, m1, c0, c1, r0, r1;
                if (m < 4) { m0 = m1 = 1; c0 = 448 + 56 * sl; c1 = c0 + 448; r0 = r1 = ra; }
                else if (m < 8) { m0 = m1 = m < 6 ? 1 : 2; c0 = c1 = 56 * sl; r0 = rb; r1 = rc; }
                else if (m < 20) { m0 = 3; m1 = 4; c0 = c1 = 224 * sl + 32 * hr + 64 * ((m - 8) >> 2); r0 = r1 = ra; }
                else if (m < 22) { kind = 2; m0 = 5; m1 = 6; c0 = c1 = 224 * sl + (hr ? 0 : 192); r0 = rb; r1 = rc; }
                else { m0 = m1 = 7; c0 = c1 = 56 * (2 * ((pr + (m >> 1) - 10) & 3) + hr); r0 = 224 * (sl ^ (m & 1)); r1 = r0 + 112; }
                if (packed) { kind = 1; r0 = sl * 16 + (m < 8 ? m : m - 14); r1 = 0; }
                e0[0] = e0[1]; e1[0] = e1[1];
                e0[1] = kind | (m0 << 2) | (m1 << 6) | (c0 << 10) | (c1 << 21);
                e1[1] = r0 | (r1 << 16);
            }
        } else {
            const int j = t128 - 32;
            asm volatile("barrier.cluster.wait.aligned;" ::: "memory");
            uint2 wv[7];
            const int k = j < 56 ? j : 55, hh = k >= 28;
#pragma unroll
            for (int i = 0; i < 7; i++) wv[i] = __ldg(reinterpret_cast<const uint2*>(w_phi + (sl * 56 + k) * 28) + i);
#pragma unroll 1
            for (int i = j; i < 7168 / 16; i += 96) sts4(sb + OFF_WPHI + i * 16, 0, 0, 0, 0);
            bar_sync(5, 96);
            if (j < 56) {
                uint32_t a4[4];
#pragma unroll
                for (int q = 0; q < 4; q++) a4[q] = sb + OFF_WPHI + (4 * hh + q) * 128 + ((((k >> 3) ^ (4 * hh + q)) & 7) << 4) + (k & 7) * 2;
                FOR14(const uint32_t v = (t & 1) ? wv[t >> 1].y : wv[t >> 1].x;
                      asm volatile("{ .reg .b16 l, h; mov.b32 {l, h}, %2; st.shared.u16 [%0+%3], l; st.shared.u16 [%1+%3], h; }"
                                   ::"r"(a4[t >= 7 ? 2 : 0]), "r"(a4[t >= 7 ? 3 : 1]), "r"(v), "n"((t % 7) * 1024) : "memory"));
            }
            __syncwarp();
            fence_async();
            bar_arrive(1, 224);
            bar_arrive(9, 224);
            if (w == 1) {
                mbar_wait(BAR(2), 0);
                mbar_wait(BAR(2), 1);
                const int b = blockIdx.x;
                asm volatile(ELECT "cp.async.bulk.prefetch.L2.global [%0], %1; }" ::"l"(wg + b * 6272), "r"(12544) : "memory");
                asm volatile(ELECT "cp.async.bulk.prefetch.L2.global [%0], %1; }" ::"l"(wu + b * 6272), "r"(12544) : "memory");
                asm volatile(ELECT "cp.async.bulk.prefetch.L2.global [%0], %1; }" ::"l"(wd + b * 6272), "r"(12544) : "memory");
            }
        }
        uint32_t kseq = ld_word(g_c1 + (sl * 8 * 16 + tile) * 32);
        int slot = 0, ph = 0, n = NST;
#pragma unroll 1
        for (int layer = 0; layer < 3; layer++) {
            if (w == 0) {
                const int nend = layer == 0 ? 11 : (layer == 1 ? 42 : 63);
#pragma unroll 1
                for (; n < nend; n++) {
                const uint32_t w0 = __shfl_sync(0xffffffffu, n < 32 ? e0[0] : e0[1], n & 31), w1 = __shfl_sync(0xffffffffu, n < 32 ? e1[0] : e1[1], n & 31);
                const uint32_t dst = sb + slot * STAGE, fb = BAR(n == PACK ? B_PACK : slot);
                const CUtensorMap* m0 = &maps.x + ((w0 >> 2) & 15);
                const CUtensorMap* m1 = &maps.x + ((w0 >> 6) & 15);
                const int c0 = (w0 >> 10) & 2047, c1 = w0 >> 21, r0 = w1 & 0xffff, r1 = w1 >> 16;
                if (n == 25) {
                    int it = 0;
                    uint32_t v;
                    do { asm volatile("ld.acquire.gpu.global.u32 %0, [%1];" : "=r"(v) : "l"(g_cw + sl * 32) : "memory"); } while ((int)(v - cw_target) < 0 && ++it < 0x400000);
                    asm volatile("fence.proxy.async.global;" ::: "memory");
                    __syncwarp();
                }
                mbar_wait(BAR(B_EMPTY + slot), ph);
                __syncwarp();
                asm volatile(ELECT "mbarrier.arrive.expect_tx.shared::cta.b64 _, [%0], %1; }" ::"r"(fb), "r"(STAGE) : "memory");
                if ((w0 & 3) == 0) {
                    tma2d(dst, m0, c0, r0, fb);
                    tma2d(dst + HALF, m1, c1, r1, fb);
                } else if (w0 & 1) {
                    asm volatile(ELECT "cp.async.bulk.shared::cluster.global.mbarrier::complete_tx::bytes [%0], [%1], %2, [%3]; }"
                                 ::"r"(dst), "l"(reinterpret_cast<const char*>(g_wp) + (size_t)r0 * STAGE), "r"(STAGE), "r"(fb) : "memory");
                } else {
                    tma2d(dst, m0, c0, r0, fb); tma2d(dst + 7168, m0, c0, r1, fb);
                    tma2d(dst + HALF, m1, c0, r0, fb); tma2d(dst + HALF + 7168, m1, c0, r1, fb);
                }
                if (n == PACK) asm volatile(ELECT "mbarrier.arrive.shared::cta.b64 _, [%0]; }" ::"r"(BAR(slot)) : "memory");
                if (++slot == NST) { slot = 0; ph ^= 1; }
                }
            } else if (w == 1 && layer == 1) {
                constexpr int ps = PACK % NST;
                mbar_wait(BAR(B_PACK), 0);
                asm volatile("{ .reg .pred e; elect.sync _|e, 0xffffffff;\n"
                             "@e cp.async.bulk.global.shared::cta.bulk_group [%0], [%1], %2;\n"
                             "@e cp.async.bulk.commit_group;\n"
                             "@e cp.async.bulk.wait_group.read 0;\n"
                             "@e mbarrier.arrive.shared::cta.b64 _, [%3], 8;\n"
                             "@e cp.async.bulk.wait_group 0;\n"
                             "@e fence.proxy.async.global;\n"
                             "@e red.release.gpu.global.add.u32 [%4], 1; }"
                             ::"l"(reinterpret_cast<char*>(g_wp) + (size_t)(sl * 16 + tile) * STAGE), "r"(sb + ps * STAGE), "r"(STAGE), "r"(BAR(B_EMPTY + ps)), "l"(g_cw + sl * 32) : "memory");
                __syncwarp();
            }
            if (layer < 2) {
            const uint32_t tag = layer ^ 1;
            kseq++;
            bar_sync(7, 384);
            ASTAMP(0);
            if (tile < 15) {
                const int sq = lane >> 3, pk = 8 * w + (lane & (tile == 14 ? 3 : 7));
                uint32_t v[16];
                if (layer == 0) poll_cnt(g_c1 + ((sl * 8 + (w >> 1) * 4 + (tile >> 2)) * 16 + (lane & 15)) * 32, kseq);
                ASTAMP(1);
                poll4_kv<32>(v, g_kv1 + ((sl * 16 + tile) * 16 + 4 * sq) * 32 + pk, tag);
#pragma unroll
                for (int k = 0; k < 4; k++) {
                    float lo = (bf_lo(v[k]) + bf_lo(v[4 + k])) + (bf_lo(v[8 + k]) + bf_lo(v[12 + k]));
                    float hi = (bf_hi(v[k]) + bf_hi(v[4 + k])) + (bf_hi(v[8 + k]) + bf_hi(v[12 + k]));
                    lo += __shfl_xor_sync(0xffffffffu, lo, 8); hi += __shfl_xor_sync(0xffffffffu, hi, 8);
                    lo += __shfl_xor_sync(0xffffffffu, lo, 16); hi += __shfl_xor_sync(0xffffffffu, hi, 16);
                    v[k] = pack2(lo, hi);
                }
                if (sq == 0) st_pkt<0>(g_kv2 + sl * 512 + 32 * tile + pk, settag(v[0], tag), v[1], v[2], v[3]);
            }
            ASTAMP(2);
            {
                const int item = t128 < 112 ? t128 : 112 + (t128 & 3), d = item >> 1;
                const int cc = t128 < 112 ? 2 * (d >= 28) + (item & 1) : item - 112;
                const int r = t128 < 112 ? d : 56 + (cc >> 1) + 2 * ((t128 - 112) >> 2);
                uint32_t ra = sb + OFF_KVB + r * 128 + 4 * cc, rx = (r & 7) << 4;
                asm volatile("" : "+r"(ra), "+r"(rx));
                FOR14(asm volatile("st.shared.u32 [%0+%2], %1;" ::"r"((ra ^ 8) + (((t & 7) << 4) ^ rx)), "r"(0), "n"((t >> 3) * 8192) : "memory"));
                uint32_t v[16];
                asm volatile("" : "+r"(ra), "+r"(rx));
                poll4_kv<8>(v, g_kv2 + sl * 512 + (item >> 3) * 32 + (item & 7), tag);
                FOR14(asm volatile("st.shared.u32 [%0+%2], %1;" ::"r"(ra + (((t & 7) << 4) ^ rx)), "r"(v[t < 7 ? t : t + 1]), "n"((t >> 3) * 8192) : "memory"));
                fence_async();
            }
            bar_arrive(3, 384);
            ASTAMP(3);
            }
        }
    } else {
        asm volatile("setmaxnreg.inc.sync.aligned.u32 232;");
        int lane = fresh_tid() & 31, prf = pr;
#define pr prf
#define g (lane >> 2)
#define c (lane & 3)
#define t128 (w * 32 + lane)
        const int wu = __shfl_sync(0xffffffffu, fresh_tid() >> 5, 0), w = wu & 3;
        const uint32_t xoff = __shfl_sync(0xffffffffu, (3 * PLANE + ((tile * 2 + wgi) * 8) * 512 + w * 128) * 16, 0);
        char* xu = reinterpret_cast<char*>(g_ex) + xoff;
#define FRESH() asm volatile("" : "+l"(xu), "+r"(lane), "+r"(prf))
#define xp0 (reinterpret_cast<uint4*>(xu) + lane)
        const uint32_t hbuf = sb + OFF_H + wgi * STAGE;
        uint32_t slot = 0, ph = 0, eb1 = 0, eb2 = 0, ackph = 0, rcvph = 0, gatph = 0, swp = 0;
        uint32_t ppid = 6;
#define cx(s) (reinterpret_cast<uint32_t*>(reinterpret_cast<uint4*>(xu) + PL(1) + 112 + (s) * 512))
#define stp (reinterpret_cast<uint4*>(xu) + g + PL(0) + 112)
        uint32_t seq = ld_word(cx(sl));
        uint32_t kseq = ld_word(g_c1 + ((sl * 8 + wu) * 16 + tile) * 32);
        uint32_t stag = ld_word(reinterpret_cast<const uint32_t*>(stp + sl * 512) + 3) & 1;
        asm volatile("barrier.cluster.wait.aligned;" ::: "memory");
        STAMP(1);
        uint32_t X[14];
        mbar_wait(BAR(B_XS), 0);
        STAMP(51);
#pragma unroll
        for (int j = 0; j < 4; j++) {
            uint32_t q2, q3;
            asm volatile("ldmatrix.sync.aligned.m8n8.x4.shared.b16 {%0,%1,%2,%3}, [%4];" : "=r"(X[4 * j]), "=r"(X[4 * j + 1]), "=r"(q2), "=r"(q3)
                         : "r"(sb + OFF_KVB + (wu * 16 + (lane & 15)) * 112 + (j < 3 ? 32 * j + (lane >> 4) * 16 : 96)) : "memory");
            if (j < 3) { X[(4 * j + 2) % 14] = q2; X[(4 * j + 3) % 14] = q3; }
        }
#define PUSH_SLICE(W)                                                                          \
    {                                                                                          \
        if (t128 == 0) mbar_expect_tx(BAR(B_RECV + wgi), 7168);                                \
        PUSH_BEGIN();                                                                          \
        const uint32_t ra = mapa(hbuf + 24576 + t128 * 16, hr ^ 1), rb = mapa(sb + OFF_XR + wgi * 3072, hr ^ 1), rbar = mapa(BAR(B_RECV + wgi), hr ^ 1); \
        st_async4(ra, W[0], W[1], W[2], W[3], rbar);                                           \
        st_async4(ra + 2048, W[4], W[5], W[6], W[7], rbar);                                    \
        st_async4(rb + t128 * 16, W[8], W[9], W[10], W[11], rbar);                             \
        asm volatile("st.async.weak.shared::cluster.mbarrier::complete_tx::bytes.v2.b32 [%0], {%1,%2}, [%3];" ::"r"(rb + 2048 + t128 * 8), "r"(W[12]), "r"(W[13]), "r"(rbar) : "memory"); \
    }
#define PULL_SLICE(W)                                                                          \
    {                                                                                          \
        uint32_t t0, t1;                                                                       \
        mbar_wait(BAR(B_RECV + wgi), rcvph);                                                   \
        rcvph ^= 1;                                                                            \
        lds4(&A[1][0], hbuf + 24576 + t128 * 16);                                              \
        lds4(&A[1][4], hbuf + 26624 + t128 * 16);                                              \
        lds4(&A[1][8], sb + OFF_XR + wgi * 3072 + t128 * 16);                                  \
        asm volatile("ld.shared.v2.u32 {%0,%1}, [%2];" : "=r"(t0), "=r"(t1) : "r"(sb + OFF_XR + wgi * 3072 + 2048 + t128 * 8) : "memory"); \
        _Pragma("unroll") for (int i = 0; i < 12; i++) A[0][i] = (i & 3) ? W[i] : W[i] & ~1u;  \
        A[1][0] &= ~1u; A[1][4] &= ~1u; A[1][8] &= ~1u;                                        \
        A[0][12] = (hr ? t0 : W[12]) & ~1u; A[0][13] = hr ? t1 : W[13];                        \
        A[1][12] = (hr ? W[12] : t0) & ~1u; A[1][13] = hr ? W[13] : t1;                        \
        asm volatile("" : RW4(A[0], 0), RW4(A[0], 4), RW4(A[0], 8), RW2(A[0], 12), RW4(A[1], 0), RW4(A[1], 4), RW4(A[1], 8), RW2(A[1], 12)); \
        swp = hr * 448;                                                                        \
    }
#define SWB(b, t, db, sh) ((b) == 0 && (t) < 6 ? ((t) < 3 ? db##p : db##m) : db)
#define DECL_DB(b, MK, lbo, sh) const uint64_t db = MK(0, lbo, R_ADJ), dbp = (b) == 0 ? MK(0, lbo, R_ADJ + (swp >> (sh))) : db, dbm = (b) == 0 ? MK(0, lbo, R_ADJ - (swp >> (sh))) : db;
#define PPB 2
#define PP_WAIT() if (wgi == 1) { bar_sync(ppid, 256); ppid ^= 14; }
#define PP_GO() if (wgi == 0) { bar_arrive(ppid, 256); ppid ^= 14; }
#define GAT_DST(B, s2) ((B) == 1 ? hbuf + w * 3584 + (s2) * 1792 : ((s2) ? sb + OFF_KVB + wgi * 8192 : hbuf + 14336) + w * 1792)
#define GAT_ISSUE(B, base)                                                                     \
    {                                                                                          \
        const char* gs = xu + ((base) + kblk(pr, B) * 1024) * 16;                              \
        asm volatile("{ .reg .pred e; elect.sync _|e, 0xffffffff;\n"                           \
                     "@e mbarrier.arrive.expect_tx.shared::cta.b64 _, [%3], 3584;\n"           \
                     "@e cp.async.bulk.shared::cluster.global.mbarrier::complete_tx::bytes [%0], [%2], 1792, [%3];\n" \
                     "@e cp.async.bulk.shared::cluster.global.mbarrier::complete_tx::bytes [%1], [%2+8192], 1792, [%3]; }" \
                     ::"r"(GAT_DST(B, 0)), "r"(GAT_DST(B, 1)), "l"(gs), "r"(BAR(B_GAT + wu * 2 + ((B) >> 1))) : "memory"); \
        __syncwarp();                                                                          \
    }
#define GAT_FETCH(B)                                                                           \
    {                                                                                          \
        mbar_wait(BAR(B_GAT + wu * 2 + ((B) >> 1)), (gatph >> (B)) & 1);                          \
        gatph ^= 1 << (B);                                                                     \
        _Pragma("unroll") for (int s2 = 0; s2 < 2; s2++) {                                     \
            const uint32_t ga = GAT_DST(B, s2) + lane * 16;                                    \
            lds4(&A[2 * (B) + s2][0], ga); lds4(&A[2 * (B) + s2][4], ga + 512); lds4(&A[2 * (B) + s2][8], ga + 1024); \
            asm volatile("ld.shared.v2.u32 {%0,%1}, [%2];" : "=r"(A[2 * (B) + s2][12]), "=r"(A[2 * (B) + s2][13]) : "r"(ga - lane * 8 + 1536) : "memory"); \
        }                                                                                      \
    }
#define LATE_ARRIVE() do { if (lane == 0) mbar_arrive(BAR(B_LATE)); } while (0)
#define LATE_WAIT() do { mbar_wait(BAR(B_LATE), gatph & 1); gatph ^= 1; } while (0)
#define PT 3
#define PREP(b, t, remote)                                                                     \
    if constexpr ((b) < 3 && (t) == PT) {                                                      \
        wg_commit();                                                                           \
        STAMP(74 + 6 * (step & 1) + 2 * (b));                                                  \
        if (remote) {                                                                          \
            if constexpr ((b) == 0) { blk_load<2>(A, BLK(xsrc, 2), lane); GAT_FETCH(1) }       \
            blk_check<((b) + 1) & 3>(A, BLK(xsrc, (b) + 1), lane, xtag);                       \
            if constexpr ((b) == 0) blk_load<3>(A, BLK(xsrc, 3), lane);                        \
        }                                                                                      \
        STAMP(75 + 6 * (step & 1) + 2 * (b));                                                  \
        normalize<((b) + 1) & 3>(A, k0, k1);                                                   \
        asm volatile("" : RW4(A[(2 * (b) + 2) & 7], 0), RW4(A[(2 * (b) + 2) & 7], 4), RW4(A[(2 * (b) + 2) & 7], 8), RW2(A[(2 * (b) + 2) & 7], 12), \
                          RW4(A[(2 * (b) + 3) & 7], 0), RW4(A[(2 * (b) + 3) & 7], 4), RW4(A[(2 * (b) + 3) & 7], 8), RW2(A[(2 * (b) + 3) & 7], 12)); \
        wg_fence();                                                                            \
    }
#define X0_BLOCK(b)                                                                            \
    { const int rr = lane & 7, hi = lane >> 4;                                                 \
    const uint32_t rowa = (w < 2 ? hbuf : sb + wgi * STAGE) + ((w & 1) * 16 + (lane & 15)) * 128; \
    FOR7(constexpr int G = 14 * (b) + (t < 3 ? 2 * t : (t < 6 ? 2 * t + 1 : 6));               \
         uint32_t q0, q1, q2, q3;                                                              \
         const uint32_t ad = t < 6 ? rowa + (((((G & 7) + hi) ^ rr) & 7) << 4) + ((G & 7) == 7 ? hi * 4096 : 0) : rowa + ((G + 7 * hi) >> 3) * 4096 + ((((G + 7 * hi) ^ rr) & 7) << 4); \
         asm volatile("ldmatrix.sync.aligned.m8n8.x4.shared.b16 {%0,%1,%2,%3}, [%4+%5];" : "=r"(q0), "=r"(q1), "=r"(q2), "=r"(q3) \
                      : "r"(ad), "n"(t < 6 ? (G >> 3) * 4096 : 0) : "memory");                 \
         if (t < 3) { A[2 * (b)][4 * t] = q0; A[2 * (b)][4 * t + 1] = q1; A[2 * (b)][4 * t + 2] = q2; A[2 * (b)][4 * t + 3] = q3; } \
         else if (t < 6) { A[2 * (b) + 1][(4 * t - 12) & 15] = q0; A[2 * (b) + 1][((4 * t - 12) & 15) + 1] = q1; A[2 * (b) + 1][((4 * t - 12) & 15) + 2] = q2; A[2 * (b) + 1][((4 * t - 12) & 15) + 3] = q3; } \
         else { A[2 * (b)][12] = q0; A[2 * (b)][13] = q1; A[2 * (b) + 1][12] = q2; A[2 * (b) + 1][13] = q3; }); }
#define BLK(base, b) ((base) + kblk(pr, b) * 1024)

#pragma unroll 1
        for (int step = 0; step < 4; step++) {
            FRESH();
            const uint32_t tag = (step >> 1) ^ 1;
            const int so = (step >> 1) * 24 + (step & 1) * 12;
            (void)so;
            uint32_t A[8][14];
            uint4* const xsrc = xp0 + ((step & 1) ? PL(2) : PL(0));
            const uint32_t xtag = (step & 1) ? tag : ((seq >> 3) & 1) ^ 1;
            uint32_t xbits;
            {
                float st[4];
                slice_stats(X, st);
                stag ^= 1;
                xbits = x_bits(X);
                tag_slice(X, xtag);
                if (step) send_slice<0>(xsrc + sl * 512, lane, X);
                if (c == 0) st_pkt<0>(stp + sl * 512, __float_as_uint(st[0]), __float_as_uint(st[1]), __float_as_uint(st[2]), settag(__float_as_uint(st[3]), stag));
            }
            STAMP(2 + so);
            uint32_t sv[8];
            if (step == 0) {
                mbar_wait(BAR(wgi), 0);
                X0_BLOCK(0) X0_BLOCK(1) X0_BLOCK(2) X0_BLOCK(3)
                mbar_wait(BAR(wgi ^ 1), 0);
                R_NEXT();
                R_NEXT();
                R_RELEASE(2);
                stat_load(sv, stp + c * 1024);
                stat_check(sv, stp + c * 1024, stag);
                STAMP(52 + step);
            } else {
                kill<14>(A[2]); kill<14>(A[3]); kill<14>(A[4]); kill<14>(A[5]); kill<14>(A[6]); kill<14>(A[7]);
                PUSH_SLICE(X)
                stat_load(sv, stp + c * 1024);
                PULL_SLICE(X)
                stat_check(sv, stp + c * 1024, stag);
                STAMP(52 + step);
                GAT_ISSUE(1, (step & 1) ? PL(2) : PL(0))
            }
            LnCoef k0, k1;
            {
                k0 = ln_coef(__uint_as_float(sv[0]) + __uint_as_float(sv[4]), __uint_as_float(sv[1]) + __uint_as_float(sv[5]));
                k1 = ln_coef(__uint_as_float(sv[2]) + __uint_as_float(sv[6]), __uint_as_float(sv[3] & ~1u) + __uint_as_float(sv[7] & ~1u));
            }
            STAMP(3 + so);
            GSTAMP(70 + step);

            if ((step & 1) == 0) {
                float tq[28];
                {
                    float av[28];
#define KV_BLOCK(b)                                                                           \
    if ((b) == 1) R_RELEASE(2);                                                               \
    if ((b) == 2) { PUSH_ACK(); wg_wait<2>(); R_RELEASE(2); }                                 \
    R_WAIT();                                                                                 \
    if ((b) == PPK) { PP_WAIT() }                                                             \
    { DECL_DB(b, BASE128, 16, 0)                                                              \
    wg_fence();                                                                               \
    FOR7(mma_rs56<1, D128(0, t)>(tq, AQ(A, b, t), (b) + t > 0, SWB(b, t, db, 0));             \
         mma_rs56<1, D128(HALF, t)>(av, AQ(A, b, t), (b) + t > 0, SWB(b, t, db, 0));          \
         PREP(b, t, step)); }                                                                 \
    wg_commit();                                                                              \
    if ((b) == 3 && PPK < 4) { PP_GO() }                                                      \
    R_NEXT();
                    normalize<0>(A, k0, k1);
                    KV_BLOCK(0) KV_BLOCK(1) KV_BLOCK(2) KV_BLOCK(3)
                    wg_wait<0>();
                    if (lane < 3) mbar_arrive(BAR(B_EMPTY + (slot + NST - 1 - lane) % NST));
                    STAMP(4 + so);
                    WSUM(80 + 7 * (step >> 1));
                    const int m = lane >> 3, rr = lane & 7;
                    const uint32_t rowa = hbuf + 16384 + (w * 16 + rr + 8 * (m & 1)) * 128;
                    const uint32_t one = c == 0 ? 0x00003f80u : 0u;
                    if (step == 0) { bar_sync(wgi ? 9 : 1, 224); }
#pragma unroll
                    for (int j = 0; j < 4; j++) {
                        const uint32_t a = rowa + (((2 * j + (m >> 1)) ^ rr) << 4);
                        if (j < 3) stsm4(a, pack2(av[8 * j], av[8 * j + 1]), pack2(av[8 * j + 2], av[8 * j + 3]), pack2(av[8 * j + 4], av[8 * j + 5]), pack2(av[8 * j + 6], av[8 * j + 7]));
                        else stsm4(a, pack2(av[24], av[25]), pack2(av[26], av[27]), one, one);
                    }
                }
                uint32_t PH[28];
                int it = 1;
#pragma unroll 1
                do {
                    float pp[28];
                    phi_gemm(tq, pp);
                    dual_softmax(pp, PH);
                    if (((trips >> (it + 1)) & 1) == 0) continue;
                    {
                        const int m = lane >> 3, rr = lane & 7;
                        const uint32_t rowa = hbuf + (w * 16 + rr + 8 * (m & 1)) * 128;
#pragma unroll
                        for (int j = 0; j < 7; j++) {
                            const int cg = 2 * j + (m >> 1), hi = cg >= 7;
                            stsm4(rowa + hi * 8192 + (((cg - 7 * hi) ^ rr) << 4), PH[4 * j], PH[4 * j + 1], PH[4 * j + 2], PH[4 * j + 3]);
                        }
                    }
                    fence_async();
                    STAMP(5 + so);
#define Q_STAGE(b0)                                                                           \
    R_WAIT();                                                                                 \
    { DECL_DB(b0, BASE128, 16, 0)                                                             \
    wg_fence();                                                                               \
    FOR7(mma_rs56<1, D128(0, t)>(tq, AQ(A, b0, t), (b0) + t > 0, SWB(b0, t, db, 0)));         \
    FOR7(mma_rs56<1, D128(HALF, t)>(tq, AQ(A, (b0) + 1, t), 1, db)); }                        \
    wg_commit();                                                                              \
    R_NEXT();
                    if (QE && wgi == 0) { kill<28>(tq); Q_STAGE(0) Q_STAGE(2) wg_wait<1>(); R_RELEASE(2); wg_wait<0>(); R_RELEASE(1); }
                    bar_sync(2, 256);
                    float kv[28];
                    const uint64_t da = BASE128(OFF_H + 16384, 16, 0), dbk = BASE128(OFF_H, 16, wgi * 512);
                    wg_fence();
                    FOR8(constexpr uint64_t o = ((t >> 2) * STAGE + (t & 3) * 2048) >> 4; mma_ss56_tt<o, o>(kv, t > 0, da, dbk));
                    wg_commit();
                    wg_wait<0>();
#pragma unroll
                    for (int hf = 0; hf < 2; hf++) {
                        const int d = 16 * w + g + 8 * hf;
                        if ((d < 56 && (d >= 28) == (c >= 2)) || d == 56) {
                            const int item = d < 56 ? 2 * d + (c & 1) : 112 + c;
                            uint4* dst = g_kv1 + ((sl * 16 + (item >> 3)) * 16 + tile) * 32 + wgi * 16 + (item & 7);
#define KVW(i) pack2(kv[4 * (i) + 2 * hf], kv[4 * (i) + 2 * hf + 1])
                            st_pkt<0>(dst, settag(KVW(0), tag), KVW(1), KVW(2), KVW(3));
                            st_pkt<8>(dst, settag(KVW(4), tag), KVW(5), KVW(6), 0u);
                        }
                    }
                    __syncwarp();
                    kseq++;
                    if (lane == 0) st_word(g_c1 + ((sl * 8 + wu) * 16 + tile) * 32, kseq);
                    bar_arrive(7, 384);
                    STAMP(6 + so);
                    if (!QE || wgi == 1) { kill<28>(tq); Q_STAGE(0) Q_STAGE(2) wg_wait<1>(); R_RELEASE(2); wg_wait<0>(); R_RELEASE(1); }
                    STAMP(7 + so);
                    kill<28>(PH);
                } while (((trips >> (++it)) & 1));
                STAMP(8 + so);
                FRESH();
                if (step) {
                    slice_load<PL(0)>(X, xp0 + sl * 512, lane);
                } else {
                    const uint32_t* xp = reinterpret_cast<const uint32_t*>(x_in + (size_t)(tile * 128 + wu * 16 + g) * 448 + 56 * sl + 2 * c);
#pragma unroll
                    for (int i = 0; i < 7; i++) { X[2 * i] = __ldg(xp + 4 * i); X[2 * i + 1] = __ldg(xp + 4 * i + 8 * 224); }
                }
                bar_sync(3, 384);
                STAMP(9 + so);
                const uint4* const osrc = xp0 + PL(1);
                {
                    float nm[32];
                    const uint64_t db = BASE128(OFF_KVB, 16, 0);
                    wg_fence();
                    FOR7(mma_rs64<0, ((t >> 2) * 8192 + (t & 3) * 32) / 16>(nm, PH[4 * t], PH[4 * t + 1], PH[4 * t + 2], PH[4 * t + 3], t > 0, db));
                    wg_commit();
                    wg_wait<0>();
                    LATE_ARRIVE();
                    const float i00 = rcp(nm[28] + 1e-6f), i01 = rcp(nm[29] + 1e-6f), i10 = rcp(nm[30] + 1e-6f), i11 = rcp(nm[31] + 1e-6f);
                    const float m0 = c >= 2 ? i01 : i00, m1 = c >= 2 ? i11 : i10;
                    uint32_t O[14];
#pragma unroll
                    for (int i = 0; i < 7; i++) {
                        const float f0 = i < 3 ? i00 : (i > 3 ? i01 : m0), f1 = i < 3 ? i10 : (i > 3 ? i11 : m1);
                        O[2 * i] = pack2(nm[4 * i] * f0, nm[4 * i + 1] * f0);
                        O[2 * i + 1] = pack2(nm[4 * i + 2] * f1, nm[4 * i + 3] * f1);
                    }
                    if (OST) { PP_WAIT() }
                    tag_slice(O, tag);
                    send_slice<PL(1)>(xp0 + sl * 512, lane, O);
                    seq++;
                    if (lane == 0) st_word(cx(sl), seq);
                    STAMP(10 + so);
                    PUSH_SLICE(O)
                    if (OST == 1) { PP_GO() }
                    const uint32_t cv = ld_word(cx(lane & 7));
                    PULL_SLICE(O)
                    LATE_WAIT();
                    check_cnt(cv, cx(lane & 7), seq);
                    if (OST == 2) { PP_GO() }
                    STAMP(56 + (step >> 1));
                    GAT_ISSUE(1, PL(1))
                    GAT_ISSUE(3, PL(1))
                    blk_load<2>(A, BLK(osrc, 2), lane);
                }
                float ao[28];
#define WO_BLOCK(b)                                                                           \
    if ((b) > 0) blk_check<b>(A, BLK(osrc, b), lane, tag);                                    \
    if (((b) & 1) == 0) R_WAIT();                                                             \
    { DECL_DB(b, BASE128, 16, 0)                                                              \
    wg_fence();                                                                               \
    FOR7(mma_rs56<1, D128(((b) & 1) * HALF, t)>(ao, AQ(A, b, t), (b) + t > 0, SWB(b, t, db, 0))); } \
    wg_commit();                                                                              \
    if ((b) & 1) R_NEXT();
                WO_BLOCK(0)
                STAMP(11 + so);
                GAT_FETCH(1)
                WO_BLOCK(1)
                WO_BLOCK(2)
                GAT_FETCH(3)
                WO_BLOCK(3)
                PUSH_ACK();
                wg_wait<0>();
                R_RELEASE(2);
                STAMP(12 + so);
                WSUM(86 + 7 * (step >> 1));
                x_fix(X, xbits);
#pragma unroll
                for (int i = 0; i < 14; i++) X[i] = pack2(bf_lo(X[i]) + ao[2 * i], bf_hi(X[i]) + ao[2 * i + 1]);
            } else {
                uint32_t H[56];
                float ag[64];
#define F1_EPI(dst, ng, ag)                                                                    \
    _Pragma("unroll") for (int i = 0; i < 2 * (ng); i++)                                       \
        (dst)[i] = pack2(geglu(ag[2 * i], ag[4 * (ng) + 2 * i]), geglu(ag[2 * i + 1], ag[4 * (ng) + 2 * i + 1]));
#define H_PUSH(h0, off) st_async4(rem_h + (off), H[h0], H[(h0) + 1], H[(h0) + 2], H[(h0) + 3], mapa(BAR(B_RECV2 + wgi), hr ^ 1));
#define F1_BLOCK(b, first)                                                                     \
    if ((first) && (b) == 1) R_RELEASE(2);                                                     \
    if ((first) && (b) == 2) PUSH_ACK();                                                       \
    R_WAIT();                                                                                  \
    if ((b) == ((first) ? PPF : PPB)) { PP_WAIT() }                                            \
    { DECL_DB(b, BASE128, HALF, 0)                                                             \
    wg_fence();                                                                                \
    FOR7(mma_rs128<1, D128(0, t)>(ag, AQ(A, b, t), (b) + t > 0, SWB(b, t, db, 0));             \
         if constexpr (first) { PREP(b, t, true) }); }                                         \
    wg_commit();                                                                               \
    if ((b) == 3) { PP_GO() }                                                                  \
    if ((b) > 0) { wg_wait<1>(); R_RELEASE(1); }       \
    R_NEXT();
                normalize<0>(A, k0, k1);
                F1_BLOCK(0, true) F1_BLOCK(1, true) F1_BLOCK(2, true) F1_BLOCK(3, true)
                if (t128 == 0) { mbar_expect_tx(BAR(B_RECV + wgi), 16384); mbar_expect_tx(BAR(B_RECV2 + wgi), 12288); }
                PUSH_BEGIN();
                wg_wait<0>();
                R_RELEASE(1);
                int p = 0;
#pragma unroll 1
                do {
                    F1_EPI(H + 32, 8, ag)
                    STAMP(4 + p + so);
                    WSUM(81 + p + 7 * (step >> 1));
                    if (((trips >> (p + 1)) & 1) == 0) continue;
                    {
                        const uint32_t pk = (p ? hbuf + 16384 : sb + OFF_KVB + wgi * 8192) + w * 2048;
#pragma unroll
                        for (int k = 0; k < 4; k++) sts4(pk + k * 512 + lane * 16, H[32 + 4 * k], H[33 + 4 * k], H[34 + 4 * k], H[35 + 4 * k]);
                        fence_async();
                        __syncwarp();
                        asm volatile(ELECT "cp.async.bulk.shared::cluster.shared::cta.mbarrier::complete_tx::bytes [%0], [%1], 2048, [%2]; }"
                                     ::"r"(mapa(hbuf + p * 8192 + w * 2048, hr ^ 1)), "r"(pk), "r"(mapa(BAR(B_RECV + wgi), hr ^ 1)) : "memory");
                    }
                    if (step == 1 && p == PKP) R_NEXT();
                    kill<64>(ag);
                    F1_BLOCK(0, false) F1_BLOCK(1, false) F1_BLOCK(2, false) F1_BLOCK(3, false)
                    wg_wait<0>();
                    R_RELEASE(1);
                    kill<16>(H + 32);
                } while (((trips >> (++p)) & 1));
#pragma unroll
                for (int k = 0; k < 4; k++) lds4(H + 16 + 4 * k, hbuf + 16384 + w * 2048 + k * 512 + lane * 16);
                __syncwarp();
                if (lane == 0) asm volatile("mbarrier.arrive.shared::cluster.b64 _, [%0];" ::"r"(mapa(BAR(B_ACK2 + wgi), hr ^ 1)) : "memory");
                const uint32_t rem_h = mapa(hbuf + w * 2048 + lane * 16, hr ^ 1);
#define F1_LAST(b0)                                                                            \
    R_WAIT();                                                                                  \
    if (b0) { PP_WAIT() }                                                                      \
    { DECL_DB(b0, BASE64, HALF, 1)                                                             \
    wg_fence();                                                                                \
    FOR7(mma_rs64<1, D64(0, t)>(al, AQ(A, b0, t), (b0) + t > 0, SWB(b0, t, db, 1)));           \
    FOR7(mma_rs64<1, D64(7168, t)>(al, AQ(A, (b0) + 1, t), 1, db)); }                          \
    wg_commit();                                                                               \
    if (b0) { PP_GO() }                                                                        \
    R_NEXT();
                float al[32];
                F1_LAST(0)
                mbar_wait(BAR(B_RECV + wgi), rcvph);
                rcvph ^= 1;
                mbar_wait(BAR(B_ACK2 + wgi), step >> 1);
                H_PUSH(32, 16384) H_PUSH(36, 16896)
                F1_LAST(2)
                H_PUSH(40, 17408) H_PUSH(44, 17920)
                wg_wait<1>();
                R_RELEASE(2);
                wg_wait<0>();
                R_RELEASE(1);
                uint32_t HP[56];
#pragma unroll
                for (int k = 0; k < 4; k++) lds4(H + 4 * k, sb + OFF_KVB + wgi * 8192 + w * 2048 + k * 512 + lane * 16);
#pragma unroll
                for (int t = 0; t < 8; t++) lds4(HP + 4 * t, hbuf + (t >> 2) * 8192 + w * 2048 + (t & 3) * 512 + lane * 16);
                F1_EPI(H + 48, 4, al)
                H_PUSH(48, 24576 - w * 1024) H_PUSH(52, 25088 - w * 1024)
                STAMP(7 + so);
                WSUM(84 + 7 * (step >> 1));
                FRESH();
                float acc[28];
                const uint32_t roA = hr ? 256u : 0u, roB = hr ? (uint32_t)-1536 : 0u;
                const uint32_t rpA = hr ? 0u : 256u, rpB = hr ? 0u : (uint32_t)-1536;
                float res[28];
                uint32_t v0[14], v1[14], P[14];
                const uint4* ps = xp0 + sl * 512;
#define F2_OWN_A()                                                                             \
    R_WAIT();                                                                                  \
    d0 = BASE128(0, 16, R_ADJ + roA); d1 = BASE128(0, 16, R_ADJ + roB);                        \
    wg_fence();                                                                                \
    FOR14(if constexpr (t < OT) mma_rs56<1, t * 128>(acc, H[4 * t], H[4 * t + 1], H[4 * t + 2], H[4 * t + 3], t > 0, d0)); \
    wg_commit();
#define F2_OWN_B()                                                                             \
    wg_fence();                                                                                \
    FOR14(if constexpr (t >= OT) mma_rs56<1, t * 128>(acc, H[4 * t], H[4 * t + 1], H[4 * t + 2], H[4 * t + 3], 1, t < 12 ? d0 : d1)); \
    wg_commit();                                                                               \
    R_NEXT();
#define F2_PEER()                                                                              \
    R_WAIT();                                                                                  \
    if (F2PP) { PP_WAIT() }                                                                    \
    d0 = BASE128(0, 16, R_ADJ + rpA); d1 = BASE128(0, 16, R_ADJ + rpB);                        \
    wg_fence();                                                                                \
    FOR14(mma_rs56<1, t * 128>(acc, HP[4 * t], HP[4 * t + 1], HP[4 * t + 2], HP[4 * t + 3], 1, t < 12 ? d0 : d1)); \
    wg_commit();                                                                               \
    if (F2PP) { PP_GO() }                                                                      \
    R_NEXT();
#define F2_TURN(u)                                                                             \
    wg_wait<1>();                                                                              \
    if ((u) < 2 || TDEF < 2) R_RELEASE(2);                                                     \
    wg_wait<0>();                                                                              \
    if ((u) < 2 || TDEF < 1) R_RELEASE(1);                                                     \
    _Pragma("unroll") for (int i = 0; i < 14; i++) P[i] = pack2(acc[2 * i], acc[2 * i + 1]);   \
    tag_slice(P, tag);                                                                         \
    asm volatile("" : RW4(P, 0), RW4(P, 4), RW4(P, 8), RW2(P, 12));                            \
    kill<28>(acc);                                                                             \
    F2_OWN_A()                                                                                 \
    if ((u) == 2) { slice_load<PL(3)>(v0, ps, lane); slice_load<PL(4)>(v1, ps, lane); } \
    send_slice<PL(3 + (u))>(xp0 + (2 * ((pr + (u) + 1) & 3) + hr) * 512, lane, P);             \
    seq++;                                                                                     \
    if (lane == 0) st_word(cx(sl), seq);                                                       \
    __syncwarp();                                                                              \
    STAMP(8 + (u) + so);                                                                       \
    F2_OWN_B()
                uint64_t d0, d1;
                F2_OWN_A()
                F2_OWN_B()
                R_WAIT();
                d0 = BASE128(0, 16, R_ADJ + rpA); d1 = BASE128(0, 16, R_ADJ + rpB);
                wg_fence();
                FOR8(mma_rs56<1, t * 128>(acc, HP[4 * t], HP[4 * t + 1], HP[4 * t + 2], HP[4 * t + 3], 1, d0));
                wg_commit();
                mbar_wait(BAR(B_RECV2 + wgi), step >> 1);
#pragma unroll
                for (int k = 0; k < 4; k++) lds4(HP + 32 + 4 * k, hbuf + 16384 + w * 2048 + k * 512 + lane * 16);
                lds4(HP + 48, hbuf + 24576 + w * 1024 + lane * 16);
                lds4(HP + 52, hbuf + 25088 + w * 1024 + lane * 16);
                if (step == 1) PUSH_ACK();
                wg_fence();
                FOR14(if constexpr (t >= 8) mma_rs56<1, t * 128>(acc, HP[4 * t], HP[4 * t + 1], HP[4 * t + 2], HP[4 * t + 3], 1, t < 12 ? d0 : d1));
                wg_commit();
                R_NEXT();
                F2_TURN(0)
                F2_PEER()
                F2_TURN(1)
                F2_PEER()
                F2_TURN(2)
                if (step == 1) STAMP(64);
                slice_check<PL(3)>(v0, ps, lane, tag);
                slice_check<PL(4)>(v1, ps, lane, tag);
#pragma unroll
                for (int i = 0; i < 14; i++) { res[2 * i] = bf_lo(v0[i]) + bf_lo(v1[i]); res[2 * i + 1] = bf_hi(v0[i]) + bf_hi(v1[i]); }
                slice_load<PL(2)>(X, ps, lane);
                if (step == 1) STAMP(65);
                F2_PEER()
                if (step == 1) STAMP(66);
                poll_cnt(cx(2 * ((pr + 1) & 3) + hr), seq);
                if (step == 1) STAMP(67);
                slice_load<PL(5)>(v0, ps, lane);
                x_fix(X, xbits);
                slice_check<PL(5)>(v0, ps, lane, tag);
                if (lane < TDEF) mbar_arrive(BAR(B_EMPTY + (slot + NST - 3 - lane) % NST));
#pragma unroll
                for (int i = 0; i < 14; i++) { res[2 * i] += bf_lo(v0[i]); res[2 * i + 1] += bf_hi(v0[i]); }
                STAMP(11 + so);
                wg_wait<0>();
                R_RELEASE(2);
                STAMP(12 + so);
                WSUM(85 + 7 * (step >> 1));
#pragma unroll
                for (int i = 0; i < 14; i++) X[i] = pack2(fmaf(res[2 * i] + acc[2 * i], 0.5f, bf_lo(X[i])), fmaf(res[2 * i + 1] + acc[2 * i + 1], 0.5f, bf_hi(X[i])));
            }
        }
        {
            const int m = lane >> 3, rr = lane & 7;
            const uint32_t ob = hbuf + w * 2048, rowa = ob + (rr + 8 * (m & 1)) * 112 + (m >> 1) * 16;
#pragma unroll
            for (int j = 0; j < 3; j++) stsm4(rowa + 32 * j, X[4 * j], X[4 * j + 1], X[4 * j + 2], X[4 * j + 3]);
            asm volatile("stmatrix.sync.aligned.m8n8.x2.shared.b16 [%0], {%1,%2};" ::"r"(ob + (rr + 8 * (m & 1)) * 112 + 96), "r"(X[12]), "r"(X[13]) : "memory");
            fence_async();
            __syncwarp();
            if (lane == 0) {
                asm volatile("cp.async.bulk.tensor.2d.global.shared::cta.bulk_group [%0, {%2, %3}], [%1];" ::"l"(&maps.out), "r"(ob), "r"(56 * sl), "r"(tile * 128 + wu * 16) : "memory");
                asm volatile("cp.async.bulk.commit_group;" ::: "memory");
                asm volatile("cp.async.bulk.wait_group.read 0;" ::: "memory");
            }
        }
        STAMP(50);
        GSTAMP(61);
        PDUMP();
    }
}

#undef g
#undef pr
#undef c
#undef t128

typedef CUresult (*EncodeFn)(CUtensorMap*, CUtensorMapDataType, cuuint32_t, void*, const cuuint64_t*, const cuuint64_t*, const cuuint32_t*,
                             const cuuint32_t*, CUtensorMapInterleave, CUtensorMapSwizzle, CUtensorMapL2promotion, CUtensorMapFloatOOBfill);

static void make_map(EncodeFn enc, CUtensorMap* m, const void* p, uint64_t cols, uint64_t rows, uint32_t bc, uint32_t br, CUtensorMapSwizzle sw) {
    cuuint64_t gd[2] = {cols, rows};
    cuuint64_t gs[1] = {cols * 2};
    cuuint32_t bd[2] = {bc, br};
    cuuint32_t es[2] = {1, 1};
    enc(m, CU_TENSOR_MAP_DATA_TYPE_BFLOAT16, 2, const_cast<void*>(p), gd, gs, bd, es, CU_TENSOR_MAP_INTERLEAVE_NONE, sw,
        CU_TENSOR_MAP_L2_PROMOTION_L2_128B, CU_TENSOR_MAP_FLOAT_OOB_FILL_NONE);
}

extern "C" void kernel_launch(void* const* d_in, const int* in_sizes, int n_in, void* d_out, int out_size) {
    (void)in_sizes; (void)n_in; (void)out_size;
    static EncodeFn enc = nullptr;
    static Scratch* scratch = nullptr;
    if (!enc) {
        void* fn = nullptr;
        cudaDriverEntryPointQueryResult qr;
        cudaGetDriverEntryPoint("cuTensorMapEncodeTiled", &fn, cudaEnableDefault, &qr);
        enc = (EncodeFn)fn;
        cudaGetSymbolAddress((void**)&scratch, g_scratch);
        cudaFuncSetAttribute(fused_kernel, cudaFuncAttributeMaxDynamicSharedMemorySize, SMEM_BYTES);
    }
    Maps maps;
    {
        cuuint64_t gd[3] = {64, 2048, 7};
        cuuint64_t gs[2] = {896, 128};
        cuuint32_t bd[3] = {64, 32, 7};
        cuuint32_t es[3] = {1, 1, 1};
        enc(&maps.x, CU_TENSOR_MAP_DATA_TYPE_BFLOAT16, 3, d_in[0], gd, gs, bd, es, CU_TENSOR_MAP_INTERLEAVE_NONE, CU_TENSOR_MAP_SWIZZLE_128B,
            CU_TENSOR_MAP_L2_PROMOTION_L2_128B, CU_TENSOR_MAP_FLOAT_OOB_FILL_NONE);
    }
    make_map(enc, &maps.xs, d_in[0], 448, 2048, 56, 128, CU_TENSOR_MAP_SWIZZLE_NONE);
    make_map(enc, &maps.out, d_out, 448, 2048, 56, 16, CU_TENSOR_MAP_SWIZZLE_NONE);
    make_map(enc, &maps.qkv, d_in[1], 1344, 448, 64, 112, CU_TENSOR_MAP_SWIZZLE_128B);
    make_map(enc, &maps.wo, d_in[3], 448, 448, 64, 112, CU_TENSOR_MAP_SWIZZLE_128B);
    make_map(enc, &maps.wg, d_in[5], 1792, 448, 64, 112, CU_TENSOR_MAP_SWIZZLE_128B);
    make_map(enc, &maps.wu, d_in[6], 1792, 448, 64, 112, CU_TENSOR_MAP_SWIZZLE_128B);
    make_map(enc, &maps.wg32, d_in[5], 1792, 448, 32, 112, CU_TENSOR_MAP_SWIZZLE_64B);
    make_map(enc, &maps.wu32, d_in[6], 1792, 448, 32, 112, CU_TENSOR_MAP_SWIZZLE_64B);
    make_map(enc, &maps.wd, d_in[7], 448, 1792, 64, 112, CU_TENSOR_MAP_SWIZZLE_128B);
    fused_kernel<<<128, 384, SMEM_BYTES>>>(scratch, (const __nv_bfloat16*)d_in[0], (const __nv_bfloat16*)d_in[2], 7, (const __nv_bfloat16*)d_in[5],
                                           (const __nv_bfloat16*)d_in[6], (const __nv_bfloat16*)d_in[7], maps);
}
```

```cpp
#include <cuda_runtime.h>
#include <cuda.h>
#include <cuda_bf16.h>
#include <stdint.h>
#include <type_traits>

#define PPF 2
#define PKP 0
#define TDEF 1
#define TMPF 0
#define NORM1 0
#define ACAN 0
#define SPLIT0 1
#define OT 2
#define F2PP 0
#define PPK 2
#define QE 1
#define OST 1
#define PP

namespace {

constexpr uint32_t STAGE = 28672, HALF = 14336;
constexpr int NST = 5;
constexpr uint32_t OFF_H = NST * STAGE;
constexpr uint32_t OFF_KVB = OFF_H + 2 * STAGE;
constexpr uint32_t OFF_WPHI = OFF_KVB + 16384;
constexpr uint32_t OFF_XR = OFF_WPHI + 7168;
constexpr uint32_t OFF_BAR = OFF_XR + 6144;
constexpr uint32_t SMEM_BYTES = OFF_BAR + 384 + 1408;
constexpr int B_EMPTY = NST, B_RECV = 2 * NST, B_RECV2 = B_RECV + 2, B_PACK = B_RECV2 + 2, B_GAT = B_PACK + 1, B_LATE = B_GAT + 16, B_ACK = B_LATE + 1, B_ACK2 = B_ACK + 2, B_COUNT = B_ACK2 + 2;

constexpr int PACK = 14 + 4 * PKP;

struct Maps { CUtensorMap x, qkv, wo, wg, wu, wg32, wu32, wd, out; };

}

constexpr int PLANE = 16 * 2 * 8 * 512;
struct Scratch {
    uint4 ex[6 * PLANE];
    uint4 kv1[8 * 16 * 16 * 32];
    uint4 kv2[8 * 512];
    uint32_t c1[8 * 8 * 16 * 32];
    uint32_t cw[8 * 32];
    uint4 wp[8 * 32 * (HALF / 16)];
};
__device__ __align__(1024) Scratch g_scratch;
#define g_ex (sc->ex)
#define g_kv1 (sc->kv1)
#define g_kv2 (sc->kv2)
#define g_c1 (sc->c1)
#define g_cw (sc->cw)
#define g_wp (sc->wp)
#define STAMP(i)
#define GSTAMP(i)
#define PDUMP()
#define ASTAMP(i)

namespace {

__device__ __forceinline__ int fresh_tid() { int t; asm volatile("mov.u32 %0, %%tid.x;" : "=r"(t)); return t; }
template <int N> __device__ __forceinline__ void kill(uint32_t* v) {
#pragma unroll
    for (int i = 0; i < N; i++) v[i] = 0;
}
template <int N> __device__ __forceinline__ void kill(float* v) {
#pragma unroll
    for (int i = 0; i < N; i++) v[i] = 0.f;
}
__device__ __forceinline__ uint32_t s2u(const void* p) { return (uint32_t)__cvta_generic_to_shared(p); }
__device__ __forceinline__ void mbar_init(uint32_t a, uint32_t c) { asm volatile("mbarrier.init.shared::cta.b64 [%0], %1;" ::"r"(a), "r"(c) : "memory"); }
__device__ __forceinline__ void mbar_expect_tx(uint32_t a, uint32_t b) { asm volatile("mbarrier.arrive.expect_tx.shared::cta.b64 _, [%0], %1;" ::"r"(a), "r"(b) : "memory"); }
__device__ __forceinline__ void mbar_arrive(uint32_t a) { asm volatile("mbarrier.arrive.shared::cta.b64 _, [%0];" ::"r"(a) : "memory"); }
#define GIVE_UP(id) "trap;\n"
#define SPIN_MAX "0x400000"
#define SPIN_TAIL(id) "add.u32 n, n, 1;\n setp.lt.u32 p, n, " SPIN_MAX ";\n @p bra.uni LP;\n" GIVE_UP(id) " DN:\n }"
__device__ __forceinline__ void mbar_wait(uint32_t a, uint32_t ph) {
    asm volatile("{ .reg .pred p; .reg .b32 n; mov.u32 n, 0;\n LP:\n"
                 "mbarrier.try_wait.parity.shared::cta.b64 p, [%0], %1;\n @p bra DN;\n"
                 "add.u32 n, n, 1;\n setp.lt.u32 p, n, " SPIN_MAX ";\n @p bra LP;\n"
                 GIVE_UP("")
                 " DN:\n }" ::"r"(a), "r"(ph) : "memory");
}
#define ELECT "{ .reg .pred e; elect.sync _|e, 0xffffffff; @e "
__device__ __forceinline__ void tma2d(uint32_t dst, const CUtensorMap* m, int c0, int c1, uint32_t bar) {
    asm volatile(ELECT "cp.async.bulk.tensor.2d.shared::cluster.global.mbarrier::complete_tx::bytes [%0], [%1, {%3, %4}], [%2]; }" ::"r"(dst), "l"(m), "r"(bar), "r"(c0), "r"(c1) : "memory");
}
__device__ __forceinline__ void tma3x(uint32_t dst, const CUtensorMap* m, int row, uint32_t bar) {
    asm volatile(ELECT "cp.async.bulk.tensor.3d.shared::cluster.global.mbarrier::complete_tx::bytes [%0], [%1, {0, %3, 0}], [%2]; }" ::"r"(dst), "l"(m), "r"(bar), "r"(row) : "memory");
}
template <int OFF>
__device__ __forceinline__ void ld_pkt(uint32_t* v, const uint4* p) {
    asm volatile("{ .reg .b128 t; ld.relaxed.gpu.global.b128 t, [%4+%5]; mov.b128 {%0,%1,%2,%3}, t; }" : "=r"(v[0]), "=r"(v[1]), "=r"(v[2]), "=r"(v[3]) : "l"(p), "n"(OFF * 16) : "memory");
}
template <int OFF>
__device__ __forceinline__ void st_pkt(uint4* p, uint32_t a, uint32_t b, uint32_t c, uint32_t d) {
    asm volatile("{ .reg .b128 t; mov.b128 t, {%1,%2,%3,%4}; st.relaxed.gpu.global.b128 [%0+%5], t; }" ::"l"(p), "r"(a), "r"(b), "r"(c), "r"(d), "n"(OFF * 16) : "memory");
}
__device__ __forceinline__ uint32_t pack2(float lo, float hi) {
    uint32_t r;
    asm("cvt.rn.bf16x2.f32 %0, %1, %2;" : "=r"(r) : "f"(hi), "f"(lo));
    return r;
}
__device__ __forceinline__ float bf_lo(uint32_t w) { return __uint_as_float(w << 16); }
__device__ __forceinline__ float bf_hi(uint32_t w) { return __uint_as_float(w & 0xffff0000u); }
__device__ __forceinline__ uint32_t settag(uint32_t w, uint32_t tag) { return (w & ~1u) | tag; }
__device__ __forceinline__ float ex2(float x) { float y; asm("ex2.approx.ftz.f32 %0, %1;" : "=f"(y) : "f"(x)); return y; }
__device__ __forceinline__ float rcp(float x) { float y; asm("rcp.approx.ftz.f32 %0, %1;" : "=f"(y) : "f"(x)); return y; }
__device__ __forceinline__ float tanh_hw(float x) { float y; asm("tanh.approx.f32 %0, %1;" : "=f"(y) : "f"(x)); return y; }
__device__ __forceinline__ void stsm4(uint32_t addr, uint32_t a, uint32_t b, uint32_t c, uint32_t d) {
    asm volatile("stmatrix.sync.aligned.m8n8.x4.shared.b16 [%0], {%1,%2,%3,%4};" ::"r"(addr), "r"(a), "r"(b), "r"(c), "r"(d) : "memory");
}
__device__ __forceinline__ void fence_async() { asm volatile("fence.proxy.async.shared::cta;" ::: "memory"); }
__device__ __forceinline__ void bar_sync(int id, int n) { asm volatile("bar.sync %0, %1;" ::"r"(id), "r"(n) : "memory"); }
__device__ __forceinline__ void bar_arrive(int id, int n) { asm volatile("bar.arrive %0, %1;" ::"r"(id), "r"(n) : "memory"); }
__device__ __forceinline__ void wg_fence() { asm volatile("wgmma.fence.sync.aligned;" ::: "memory"); }
__device__ __forceinline__ void wg_commit() { asm volatile("wgmma.commit_group.sync.aligned;" ::: "memory"); }
template <int N> __device__ __forceinline__ void wg_wait() { asm volatile("wgmma.wait_group.sync.aligned %0;" ::"n"(N) : "memory"); }

constexpr uint32_t SB0 = 1024;
__host__ __device__ constexpr uint32_t dlo(uint32_t off, uint32_t lbo) { return ((SB0 + off) >> 4) | ((lbo >> 4) << 16); }
__host__ __device__ constexpr uint32_t dhi(uint32_t sbo, uint32_t sw) { return (sbo >> 4) | (sw << 30); }
__device__ __forceinline__ uint64_t dbase(uint32_t lo, uint32_t hi) { uint64_t d; asm volatile("mov.b64 %0, {%1, %2};" : "=l"(d) : "r"(lo), "r"(hi)); return d; }
#define BASE128(off, lbo, adj) dbase(dlo(off, lbo) + (adj), dhi(1024, 1))
#define BASE64(off, lbo, adj) dbase(dlo(off, lbo) + (adj), dhi(512, 2))

#define ACC4(d, o) "+f"(d[o]), "+f"(d[o + 1]), "+f"(d[o + 2]), "+f"(d[o + 3])
#define ACC28(d) ACC4(d, 0), ACC4(d, 4), ACC4(d, 8), ACC4(d, 12), ACC4(d, 16), ACC4(d, 20), ACC4(d, 24)
#define ACC32(d, o) ACC4(d, o), ACC4(d, o + 4), ACC4(d, o + 8), ACC4(d, o + 12), ACC4(d, o + 16), ACC4(d, o + 20), ACC4(d, o + 24), ACC4(d, o + 28)

template <int TB, uint64_t D>
__device__ __forceinline__ void mma_rs56(float* d, uint32_t a0, uint32_t a1, uint32_t a2, uint32_t a3, int sd, uint64_t base) {
    asm volatile("{ .reg .pred p; .reg .b64 db; setp.ne.b32 p, %32, 0; add.u64 db, %33, %34;\n"
                 "wgmma.mma_async.sync.aligned.m64n56k16.f32.bf16.bf16 "
                 "{%0,%1,%2,%3,%4,%5,%6,%7,%8,%9,%10,%11,%12,%13,%14,%15,%16,%17,%18,%19,%20,%21,%22,%23,%24,%25,%26,%27}, "
                 "{%28,%29,%30,%31}, db, p, 1, 1, %35; }\n"
                 : ACC28(d)
                 : "r"(a0), "r"(a1), "r"(a2), "r"(a3), "r"(sd), "l"(base), "n"(D), "n"(TB));
}
template <int TB, uint64_t D>
__device__ __forceinline__ void mma_rs64(float* d, uint32_t a0, uint32_t a1, uint32_t a2, uint32_t a3, int sd, uint64_t base) {
    asm volatile("{ .reg .pred p; .reg .b64 db; setp.ne.b32 p, %36, 0; add.u64 db, %37, %38;\n"
                 "wgmma.mma_async.sync.aligned.m64n64k16.f32.bf16.bf16 "
                 "{%0,%1,%2,%3,%4,%5,%6,%7,%8,%9,%10,%11,%12,%13,%14,%15,%16,%17,%18,%19,%20,%21,%22,%23,%24,%25,%26,%27,%28,%29,%30,%31}, "
                 "{%32,%33,%34,%35}, db, p, 1, 1, %39; }\n"
                 : ACC32(d, 0)
                 : "r"(a0), "r"(a1), "r"(a2), "r"(a3), "r"(sd), "l"(base), "n"(D), "n"(TB));
}
template <int TB, uint64_t D>
__device__ __forceinline__ void mma_rs128(float* d, uint32_t a0, uint32_t a1, uint32_t a2, uint32_t a3, int sd, uint64_t base) {
    asm volatile("{ .reg .pred p; .reg .b64 db; setp.ne.b32 p, %68, 0; add.u64 db, %69, %70;\n"
                 "wgmma.mma_async.sync.aligned.m64n128k16.f32.bf16.bf16 "
                 "{%0,%1,%2,%3,%4,%5,%6,%7,%8,%9,%10,%11,%12,%13,%14,%15,%16,%17,%18,%19,%20,%21,%22,%23,%24,%25,%26,%27,%28,%29,%30,%31,%32,%33,%34,%35,%36,%37,%38,%39,%40,%41,%42,%43,%44,%45,%46,%47,%48,%49,%50,%51,%52,%53,%54,%55,%56,%57,%58,%59,%60,%61,%62,%63}, "
                 "{%64,%65,%66,%67}, db, p, 1, 1, %71; }\n"
                 : ACC32(d, 0), ACC32(d, 32)
                 : "r"(a0), "r"(a1), "r"(a2), "r"(a3), "r"(sd), "l"(base), "n"(D), "n"(TB));
}
template <uint64_t DA, uint64_t DB>
__device__ __forceinline__ void mma_ss56_tt(float* d, int sd, uint64_t ba, uint64_t bb) {
    asm volatile("{ .reg .pred p; .reg .b64 da, db; setp.ne.b32 p, %28, 0; add.u64 da, %29, %31; add.u64 db, %30, %32;\n"
                 "wgmma.mma_async.sync.aligned.m64n56k16.f32.bf16.bf16 "
                 "{%0,%1,%2,%3,%4,%5,%6,%7,%8,%9,%10,%11,%12,%13,%14,%15,%16,%17,%18,%19,%20,%21,%22,%23,%24,%25,%26,%27}, "
                 "da, db, p, 1, 1, 1, 1; }\n"
                 : ACC28(d)
                 : "r"(sd), "l"(ba), "l"(bb), "n"(DA), "n"(DB));
}
template <int... I> struct Seq {};
template <class F, int... I> __device__ __forceinline__ void static_for_impl(F&& f, Seq<I...>) { (f(std::integral_constant<int, I>{}), ...); }
#define FOR7(...) static_for_impl([&](auto T_) { constexpr int t = decltype(T_)::value; __VA_ARGS__; }, Seq<0, 1, 2, 3, 4, 5, 6>{})
#define FOR8(...) static_for_impl([&](auto T_) { constexpr int t = decltype(T_)::value; __VA_ARGS__; }, Seq<0, 1, 2, 3, 4, 5, 6, 7>{})
#define FOR14(...) static_for_impl([&](auto T_) { constexpr int t = decltype(T_)::value; __VA_ARGS__; }, Seq<0, 1, 2, 3, 4, 5, 6, 7, 8, 9, 10, 11, 12, 13>{})

__device__ __forceinline__ int kblk(int p, int b) { return b == 0 ? p : b - (b <= p); }
__host__ __device__ constexpr int krow(int t) { return t < 3 ? 16 * t : (t < 6 ? 56 + 16 * (t - 3) : 48); }
#define AQ(A, b, t) ((t) < 3 ? A[2 * (b)][4 * (t)] : (t) < 6 ? A[2 * (b) + 1][4 * ((t) - 3)] : A[2 * (b)][12]), \
                    ((t) < 3 ? A[2 * (b)][4 * (t) + 1] : (t) < 6 ? A[2 * (b) + 1][4 * ((t) - 3) + 1] : A[2 * (b)][13]), \
                    ((t) < 3 ? A[2 * (b)][4 * (t) + 2] : (t) < 6 ? A[2 * (b) + 1][4 * ((t) - 3) + 2] : A[2 * (b) + 1][12]), \
                    ((t) < 3 ? A[2 * (b)][4 * (t) + 3] : (t) < 6 ? A[2 * (b) + 1][4 * ((t) - 3) + 3] : A[2 * (b) + 1][13])
#define D128(off, t) ((uint64_t)(((off) + krow(t) * 128) >> 4) + ((uint64_t)((t) == 6 ? (7168 - 1024) >> 4 : 0) << 32))
#define D64(off, t) ((uint64_t)(((off) + krow(t) * 64) >> 4) + ((uint64_t)((t) == 6 ? (3584 - 512) >> 4 : 0) << 32))

#define PL(k) (((k) - 3) * PLANE)
__device__ __forceinline__ void st_word(uint32_t* p, uint32_t v) { asm volatile("st.relaxed.gpu.global.u32 [%0], %1;" ::"l"(p), "r"(v) : "memory"); }
__device__ __forceinline__ uint32_t ld_word(const uint32_t* p) { uint32_t v; asm volatile("ld.relaxed.gpu.global.u32 %0, [%1];" : "=r"(v) : "l"(p) : "memory"); return v; }
__device__ __forceinline__ void tag_slice(uint32_t* w, uint32_t tag) { w[0] = settag(w[0], tag); w[4] = settag(w[4], tag); w[8] = settag(w[8], tag); w[12] = settag(w[12], tag); }
template <int O>
__device__ __forceinline__ void send_slice(uint4* dst, int lane, const uint32_t* w) {
    st_pkt<O>(dst, w[0], w[1], w[2], w[3]);
    st_pkt<O + 32>(dst, w[4], w[5], w[6], w[7]);
    st_pkt<O + 64>(dst, w[8], w[9], w[10], w[11]);
    asm volatile("{ .reg .b64 t; mov.b64 t, {%1,%2}; st.relaxed.gpu.global.b64 [%0+%3], t; }" ::"l"((char*)dst - lane * 8), "r"(w[12]), "r"(w[13]), "n"(16 * (O + 96)) : "memory");
}
#define RW4(v, o) "+r"(v[o]), "+r"(v[(o) + 1]), "+r"(v[(o) + 2]), "+r"(v[(o) + 3])
#define RW2(v, o) "+r"(v[o]), "+r"(v[(o) + 1])
#define WR4(v, o) "=&r"(v[o]), "=&r"(v[(o) + 1]), "=&r"(v[(o) + 2]), "=&r"(v[(o) + 3])
#define LDP(a, b, c, d, addr, off) "ld.relaxed.gpu.global.b128 q, [" addr "+" off "];\n mov.b128 {" a "," b "," c "," d "}, q;\n"
#define LDH(a, b, addr, off) "ld.relaxed.gpu.global.b64 h, [" addr "+" off "];\n mov.b64 {" a "," b "}, h;\n"
#define VOTE_OK "and.b32 t, t, 1;\n setp.ne.u32 p, t, 0;\n vote.sync.any.pred p, p, 0xffffffff;\n @!p bra.uni DN;\n"
#define CHK(x, tag) "lop3.b32 t, " x ", " tag ", t, 0xBE;\n"
__device__ __forceinline__ void check_cnt(uint32_t v, const uint32_t* p, uint32_t target) {
    asm volatile("{ .reg .pred p; .reg .b32 n, t; mov.u32 n, 0; mov.u32 t, %2;\n LP:\n"
                 "sub.s32 t, t, %1;\n setp.lt.s32 p, t, 0;\n vote.sync.any.pred p, p, 0xffffffff;\n @!p bra.uni DN;\n ld.relaxed.gpu.global.u32 t, [%0];\n" SPIN_TAIL("7")
                 ::"l"(p), "r"(target), "r"(v) : "memory");
}
__device__ __forceinline__ void poll_cnt(const uint32_t* p, uint32_t target) {
    asm volatile("{ .reg .pred p; .reg .b32 n, t; mov.u32 n, 0;\n LP:\n"
                 "ld.relaxed.gpu.global.u32 t, [%0];\n sub.s32 t, t, %1;\n setp.lt.s32 p, t, 0;\n vote.sync.any.pred p, p, 0xffffffff;\n @!p bra.uni DN;\n" SPIN_TAIL("1")
                 ::"l"(p), "r"(target) : "memory");
}
template <int STR>
__device__ __forceinline__ void poll4_kv(uint32_t* v, const uint4* p, uint32_t tag) {
    asm volatile("{ .reg .pred p; .reg .b32 n, t; .reg .b128 q; mov.u32 n, 0;\n LP:\n"
                 LDP("%0", "%1", "%2", "%3", "%16", "0") LDP("%4", "%5", "%6", "%7", "%16", "%18")
                 LDP("%8", "%9", "%10", "%11", "%16", "%19") LDP("%12", "%13", "%14", "%15", "%16", "%20")
                 "xor.b32 t, %0, %17;\n" CHK("%4", "%17") CHK("%8", "%17") CHK("%12", "%17") VOTE_OK SPIN_TAIL("2")
                 : WR4(v, 0), WR4(v, 4), WR4(v, 8), WR4(v, 12)
                 : "l"(p), "r"(tag), "n"(16 * STR), "n"(32 * STR), "n"(48 * STR)
                 : "memory");
}
template <int B>
__device__ __forceinline__ void blk_load(uint32_t (&A)[8][14], const uint4* src, int lane) {
    ld_pkt<0>(&A[2 * B][0], src); ld_pkt<32>(&A[2 * B][4], src); ld_pkt<64>(&A[2 * B][8], src);
    ld_pkt<512>(&A[2 * B + 1][0], src); ld_pkt<544>(&A[2 * B + 1][4], src); ld_pkt<576>(&A[2 * B + 1][8], src);
    asm volatile("{ .reg .b64 h;\n" LDH("%0", "%1", "%4", "1536") LDH("%2", "%3", "%4", "9728") "}"
                 : "=&r"(A[2 * B][12]), "=&r"(A[2 * B][13]), "=&r"(A[2 * B + 1][12]), "=&r"(A[2 * B + 1][13])
                 : "l"((const char*)src - lane * 8) : "memory");
}
template <int B>
__device__ __forceinline__ void blk_check(uint32_t (&A)[8][14], const uint4* src, int lane, uint32_t tag) {
    asm volatile("{ .reg .pred p; .reg .b32 n, t; .reg .b128 q; .reg .b64 h, a8; mov.u32 n, 0;\n LP:\n"
                 "xor.b32 t, %0, %30;\n" CHK("%4", "%30") CHK("%8", "%30") CHK("%12", "%30") CHK("%16", "%30") CHK("%20", "%30") CHK("%24", "%30") CHK("%26", "%30") VOTE_OK
                 LDP("%0", "%1", "%2", "%3", "%28", "0") LDP("%4", "%5", "%6", "%7", "%28", "512") LDP("%8", "%9", "%10", "%11", "%28", "1024")
                 LDP("%12", "%13", "%14", "%15", "%28", "8192") LDP("%16", "%17", "%18", "%19", "%28", "8704") LDP("%20", "%21", "%22", "%23", "%28", "9216")
                 "mad.wide.s32 a8, %29, -8, %28;\n" LDH("%24", "%25", "a8", "1536") LDH("%26", "%27", "a8", "9728") SPIN_TAIL("3")
                 "\n and.b32 %0, %0, -2; and.b32 %4, %4, -2; and.b32 %8, %8, -2; and.b32 %12, %12, -2; and.b32 %16, %16, -2; and.b32 %20, %20, -2; and.b32 %24, %24, -2; and.b32 %26, %26, -2;"
                 : RW4(A[2 * B], 0), RW4(A[2 * B], 4), RW4(A[2 * B], 8), RW4(A[2 * B + 1], 0), RW4(A[2 * B + 1], 4), RW4(A[2 * B + 1], 8),
                   RW2(A[2 * B], 12), RW2(A[2 * B + 1], 12)
                 : "l"(src), "r"(lane), "r"(tag)
                 : "memory");
}
__device__ __forceinline__ void st_async4(uint32_t a, uint32_t x, uint32_t y, uint32_t z, uint32_t w, uint32_t bar) {
    asm volatile("st.async.weak.shared::cluster.mbarrier::complete_tx::bytes.v4.b32 [%0], {%1,%2,%3,%4}, [%5];" ::"r"(a), "r"(x), "r"(y), "r"(z), "r"(w), "r"(bar) : "memory");
}
__device__ __forceinline__ uint32_t mapa(uint32_t a, uint32_t cta) { uint32_t r; asm("mapa.shared::cluster.u32 %0, %1, %2;" : "=r"(r) : "r"(a), "r"(cta)); return r; }
__device__ __forceinline__ void stat_load(uint32_t* v, const uint4* p) { ld_pkt<0>(v, p); ld_pkt<512>(v + 4, p); }
__device__ __forceinline__ void stat_check(uint32_t* v, const uint4* p, uint32_t tag) {
    asm volatile("{ .reg .pred p; .reg .b32 n, t; .reg .b128 q; mov.u32 n, 0;\n LP:\n"
                 "xor.b32 t, %3, %9;\n" CHK("%7", "%9") VOTE_OK
                 LDP("%0", "%1", "%2", "%3", "%8", "0") LDP("%4", "%5", "%6", "%7", "%8", "8192") SPIN_TAIL("4")
                 : RW4(v, 0), RW4(v, 4) : "l"(p), "r"(tag) : "memory");
}
__device__ __forceinline__ uint32_t x_bits(const uint32_t* X) {
    uint32_t r;
    asm volatile("{ .reg .b32 a, b; prmt.b32 a, %1, %2, 0x0040; prmt.b32 b, %3, %4, 0x0040; prmt.b32 %0, a, b, 0x5410; }" : "=r"(r) : "r"(X[0]), "r"(X[4]), "r"(X[8]), "r"(X[12]));
    return r;
}
template <int O>
__device__ __forceinline__ void slice_load(uint32_t* v, const uint4* p, int lane) {
    ld_pkt<O>(v, p); ld_pkt<O + 32>(v + 4, p); ld_pkt<O + 64>(v + 8, p);
    asm volatile("{ .reg .b64 h;\n" LDH("%0", "%1", "%2", "%3") "}" : "=r"(v[12]), "=r"(v[13]) : "l"((const char*)p - lane * 8), "n"(16 * (O + 96)) : "memory");
}
template <int O>
__device__ __forceinline__ void slice_check(uint32_t* v, const uint4* p, int lane, uint32_t tag) {
    asm volatile("{ .reg .pred p; .reg .b32 n, t; .reg .b128 q; .reg .b64 h; mov.u32 n, 0;\n LP:\n"
                 "xor.b32 t, %0, %16;\n" CHK("%4", "%16") CHK("%8", "%16") CHK("%12", "%16") VOTE_OK
                 LDP("%0", "%1", "%2", "%3", "%14", "%17") LDP("%4", "%5", "%6", "%7", "%14", "%18") LDP("%8", "%9", "%10", "%11", "%14", "%19")
                 LDH("%12", "%13", "%15", "%20") SPIN_TAIL("5")
                 : RW4(v, 0), RW4(v, 4), RW4(v, 8), RW2(v, 12)
                 : "l"(p), "l"((const char*)p - lane * 8), "r"(tag), "n"(16 * O), "n"(16 * (O + 32)), "n"(16 * (O + 64)), "n"(16 * (O + 96))
                 : "memory");
}
__device__ __forceinline__ void x_fix(uint32_t* X, uint32_t bits) {
    X[0] = __byte_perm(X[0], bits, 0x3214); X[4] = __byte_perm(X[4], bits, 0x3215); X[8] = __byte_perm(X[8], bits, 0x3216); X[12] = __byte_perm(X[12], bits, 0x3217);
}
__device__ __forceinline__ void sts4(uint32_t a, uint32_t x, uint32_t y, uint32_t z, uint32_t w) {
    asm volatile("st.shared.v4.u32 [%0], {%1,%2,%3,%4};" ::"r"(a), "r"(x), "r"(y), "r"(z), "r"(w) : "memory");
}
__device__ __forceinline__ void lds4(uint32_t* v, uint32_t a) {
    asm volatile("ld.shared.v4.u32 {%0,%1,%2,%3}, [%4];" : "=r"(v[0]), "=r"(v[1]), "=r"(v[2]), "=r"(v[3]) : "r"(a) : "memory");
}
struct LnCoef { uint32_t hi, lo, sh; };
__device__ __forceinline__ LnCoef ln_coef(float sum, float sq) {
    sum += __shfl_xor_sync(0xffffffffu, sum, 1); sq += __shfl_xor_sync(0xffffffffu, sq, 1);
    sum += __shfl_xor_sync(0xffffffffu, sum, 2); sq += __shfl_xor_sync(0xffffffffu, sq, 2);
    const float mean = sum * (1.f / 448.f);
    const float var = fmaxf(fmaf(-mean, mean, sq * (1.f / 448.f)), 0.f);
    const float sc = rsqrtf(var + 1e-5f);
    LnCoef r;
    r.hi = pack2(sc, sc);
    const float lo = sc - bf_lo(r.hi), sh = -mean * sc;
    r.lo = pack2(lo, lo);
    r.sh = pack2(sh, sh);
    return r;
}
template <int B>
__device__ __forceinline__ void normalize(uint32_t (&A)[8][14], const LnCoef& c0, const LnCoef& c1) {
#pragma unroll
    for (int s = 2 * B; s < 2 * B + 2; s++)
#pragma unroll
        for (int i = 0; i < 14; i++) {
            const LnCoef& k = (i & 1) ? c1 : c0;
            asm("{ .reg .b32 t; fma.rn.bf16x2 t, %0, %2, %3; fma.rn.bf16x2 %0, %0, %1, t; }" : "+r"(A[s][i]) : "r"(k.hi), "r"(k.lo), "r"(k.sh));
        }
}
__device__ __forceinline__ void slice_stats(const uint32_t* w, float* st) {
    float a = 0.f, b = 0.f, p = 0.f, q = 0.f;
#pragma unroll
    for (int i = 0; i < 7; i++) {
        const float e0 = bf_lo(w[2 * i]), e1 = bf_hi(w[2 * i]), e2 = bf_lo(w[2 * i + 1]), e3 = bf_hi(w[2 * i + 1]);
        a += e0 + e1; b += e2 + e3;
        p = fmaf(e0, e0, p); p = fmaf(e1, e1, p); q = fmaf(e2, e2, q); q = fmaf(e3, e3, q);
    }
    a += __shfl_xor_sync(0xffffffffu, a, 1); p += __shfl_xor_sync(0xffffffffu, p, 1); b += __shfl_xor_sync(0xffffffffu, b, 1); q += __shfl_xor_sync(0xffffffffu, q, 1);
    a += __shfl_xor_sync(0xffffffffu, a, 2); p += __shfl_xor_sync(0xffffffffu, p, 2); b += __shfl_xor_sync(0xffffffffu, b, 2); q += __shfl_xor_sync(0xffffffffu, q, 2);
    st[0] = a; st[1] = p; st[2] = b; st[3] = q;
}
__device__ __forceinline__ void dual_softmax(const float* p, uint32_t* out) {
    constexpr float L = 1.4426950408889634f;
#pragma unroll
    for (int r = 0; r < 2; r++) {
        float mx = fmaxf(p[2 * r], p[2 * r + 1]), mn = fminf(p[2 * r], p[2 * r + 1]);
#pragma unroll
        for (int i = 1; i < 7; i++) {
            mx = fmaxf(mx, fmaxf(p[4 * i + 2 * r], p[4 * i + 2 * r + 1]));
            mn = fminf(mn, fminf(p[4 * i + 2 * r], p[4 * i + 2 * r + 1]));
        }
        mx = fmaxf(mx, __shfl_xor_sync(0xffffffffu, mx, 1));
        mn = fminf(mn, __shfl_xor_sync(0xffffffffu, mn, 1));
        const float bx = -mx * L, bn = mn * L;
        float ep[14], en[14], sp = 0.f, sn = 0.f;
#pragma unroll
        for (int i = 0; i < 14; i++) {
            const float v = p[4 * (i >> 1) + 2 * r + (i & 1)];
            ep[i] = ex2(fmaf(v, L, bx));
            en[i] = ex2(fmaf(v, -L, bn));
            sp += ep[i]; sn += en[i];
        }
        sp += __shfl_xor_sync(0xffffffffu, sp, 1);
        sn += __shfl_xor_sync(0xffffffffu, sn, 1);
        const float ip = rcp(sp), in = rcp(sn);
#pragma unroll
        for (int i = 0; i < 7; i++) {
            out[4 * i + r] = pack2(ep[2 * i] * ip, ep[2 * i + 1] * ip);
            out[4 * i + 2 + r] = pack2(en[2 * i] * in, en[2 * i + 1] * in);
        }
    }
}
__device__ __forceinline__ float geglu(float g, float u) {
    const float t = tanh_hw(g * fmaf(g * g, 0.7978845608028654f * 0.044715f, 0.7978845608028654f));
    const float gu = g * u;
    return fmaf(t, gu, gu);
}
__device__ __forceinline__ void phi_gemm(const float* t, float* p) {
    uint32_t w[14];
#pragma unroll
    for (int i = 0; i < 14; i++) w[i] = pack2(t[2 * i], t[2 * i + 1]);
    const uint64_t db = BASE128(OFF_WPHI, 16, 0);
    wg_fence();
    mma_rs56<0, 0>(p, w[0], w[1], w[2], w[3], 0, db);
    mma_rs56<0, 2>(p, w[4], w[5], w[6], w[7], 1, db);
    mma_rs56<0, 4>(p, w[8], w[9], w[10], w[11], 1, db);
    mma_rs56<0, 6>(p, w[12], w[13], 0u, 0u, 1, db);
    wg_commit();
    wg_wait<0>();
}

}

#define BAR(i) (bars + 8 * (i))
#define R_WAIT() mbar_wait(BAR(slot), ph)
#define WSUM(i)
#define R_ADJ (slot * (STAGE >> 4))
#define R_NEXT() do { eb2 = eb1; eb1 = BAR(B_EMPTY + slot); if (++slot == NST) { slot = 0; ph ^= 1; } } while (0)
#define R_RELEASE(k) do { if (lane == 0) mbar_arrive((k) == 1 ? eb1 : eb2); } while (0)
#define PUSH_BEGIN() do { mbar_wait(BAR(B_ACK + wgi), ackph); ackph ^= 1; } while (0)
#define PUSH_ACK() do { __syncwarp(); if (lane == 0) asm volatile("mbarrier.arrive.shared::cluster.b64 _, [%0];" ::"r"(mapa(BAR(B_ACK + wgi), hr ^ 1)) : "memory"); } while (0)

__global__ void __cluster_dims__(2, 1, 1) __launch_bounds__(384, 1)
fused_kernel(Scratch* const sc, const __nv_bfloat16* __restrict__ x_in, const __nv_bfloat16* __restrict__ w_phi, const int trips,
             const __nv_bfloat16* __restrict__ wg, const __nv_bfloat16* __restrict__ wu, const __nv_bfloat16* __restrict__ wd,
             const __grid_constant__ Maps maps) {
    extern __shared__ __align__(1024) unsigned char smem_raw[];
    const uint32_t sb = s2u(smem_raw);
    const uint32_t bars = sb + OFF_BAR;
    const int wgi = __shfl_sync(0xffffffffu, threadIdx.x >> 7, 0);
    const int hr = blockIdx.x & 1, ck = blockIdx.x >> 1;
    const int gp = (ck - 4) & 7, q7 = ((ck - 36) * 37) >> 8;
    const int pr = __shfl_sync(0xffffffffu, ck < 4 ? ck : (ck < 36 ? (ck - 4) >> 3 : q7), 0);
    const int tile = __shfl_sync(0xffffffffu, ck < 4 ? 0 : (ck < 36 ? (gp ? 2 * gp : 1) : 2 * (ck - 36 - 7 * q7) + 3), 0);
    const int sl = 2 * pr + hr;
    STAMP(0);
    GSTAMP(60);
    if (__shfl_sync(0xffffffffu, threadIdx.x >> 5, 0) == 8) {
        if (threadIdx.x == 256) {
#pragma unroll
            for (int i = 0; i < NST; i++) mbar_init(BAR(i), 1);
            asm volatile("fence.mbarrier_init.release.cluster;" ::: "memory");
        }
        __syncwarp();
#pragma unroll
        for (int n = 0; n < 3; n++) asm volatile(ELECT "mbarrier.arrive.expect_tx.shared::cta.b64 _, [%0], %1; }" ::"r"(BAR(n)), "r"(n < 2 ? 2 * STAGE : STAGE) : "memory");
#pragma unroll
        for (int n = 0; n < 2; n++) {
            tma3x(sb + OFF_H + n * STAGE, &maps.x, tile * 128 + n * 64, BAR(n));
            tma3x(sb + n * STAGE, &maps.x, tile * 128 + n * 64 + 32, BAR(n));
        }
        tma2d(sb + 2 * STAGE, &maps.qkv, 448 + 56 * sl, 0, BAR(2));
        tma2d(sb + 2 * STAGE + HALF, &maps.qkv, 896 + 56 * sl, 0, BAR(2));
    }
    if (threadIdx.x == 288) {
        if ((sb & 0x3FFFF) != SB0) asm volatile("trap;");
#pragma unroll
        for (int i = NST; i < B_COUNT; i++) mbar_init(BAR(i), i >= B_ACK ? 4 : (i < B_RECV || i == B_LATE ? 8 : 1));
        asm volatile("fence.mbarrier_init.release.cluster;" ::: "memory");
    }
    __syncwarp();
    asm volatile("barrier.cluster.arrive.relaxed.aligned;" ::: "memory");

    if (wgi == 2) {
        asm volatile("setmaxnreg.dec.sync.aligned.u32 40;");
        const int t128 = fresh_tid() & 127, w = __shfl_sync(0xffffffffu, t128 >> 5, 0), lane = t128 & 31;
        uint32_t e0[2] = {0, 0}, e1[2] = {0, 0}, cw_target = 0;
        if (w == 0) {
            mbar_wait(BAR(1), 0);
#pragma unroll 1
            for (int n = 3; n < NST; n++) {
                asm volatile(ELECT "mbarrier.arrive.expect_tx.shared::cta.b64 _, [%0], %1; }" ::"r"(BAR(n)), "r"(STAGE) : "memory");
                tma2d(sb + n * STAGE, &maps.qkv, 448 + 56 * sl, 112 * (n - 2), BAR(n));
                tma2d(sb + n * STAGE + HALF, &maps.qkv, 896 + 56 * sl, 112 * (n - 2), BAR(n));
            }
            asm volatile("barrier.cluster.wait.aligned;" ::: "memory");
            cw_target = (ld_word(g_cw + sl * 32) & ~15u) + 16;
#pragma unroll 1
            for (int k = 0; k < 2; k++) {
                const int n = t128 + 32 * k;
                int m = n - 2 - (n > PACK);
                const bool packed = m >= 30 ? (m < 38 || m >= 52) : m >= 22;
                if (m >= 30) m -= 30;
                if (n == PACK) m = tile < 8 ? tile : tile + 14;
                const int rot = n < 8 ? 0 : pr;
                const int ra = 112 * kblk(rot, m & 3), rb = 112 * kblk(rot, 2 * m & 3), rc = 112 * kblk(rot, (2 * m + 1) & 3);
                int kind = 0, m0, m1, c0, c1, r0, r1;
                if (m < 4) { m0 = m1 = 1; c0 = 448 + 56 * sl; c1 = c0 + 448; r0 = r1 = ra; }
                else if (m < 8) { m0 = m1 = m < 6 ? 1 : 2; c0 = c1 = 56 * sl; r0 = rb; r1 = rc; }
                else if (m < 20) { m0 = 3; m1 = 4; c0 = c1 = 224 * sl + 32 * hr + 64 * ((m - 8) >> 2); r0 = r1 = ra; }
                else if (m < 22) { kind = 2; m0 = 5; m1 = 6; c0 = c1 = 224 * sl + (hr ? 0 : 192); r0 = rb; r1 = rc; }
                else { m0 = m1 = 7; c0 = c1 = 56 * (2 * ((pr + (m >> 1) - 10) & 3) + hr); r0 = 224 * (sl ^ (m & 1)); r1 = r0 + 112; }
                if (packed) { kind = 1; r0 = sl * 16 + (m < 8 ? m : m - 14); r1 = 0; }
                e0[0] = e0[1]; e1[0] = e1[1];
                e0[1] = kind | (m0 << 2) | (m1 << 6) | (c0 << 10) | (c1 << 21);
                e1[1] = r0 | (r1 << 16);
            }
        } else {
            const int j = t128 - 32;
            asm volatile("barrier.cluster.wait.aligned;" ::: "memory");
            uint2 wv[7];
            const int k = j < 56 ? j : 55, hh = k >= 28;
#pragma unroll
            for (int i = 0; i < 7; i++) wv[i] = __ldg(reinterpret_cast<const uint2*>(w_phi + (sl * 56 + k) * 28) + i);
#pragma unroll 1
            for (int i = j; i < 7168 / 16; i += 96) sts4(sb + OFF_WPHI + i * 16, 0, 0, 0, 0);
            bar_sync(5, 96);
            if (j < 56) {
                uint32_t a4[4];
#pragma unroll
                for (int q = 0; q < 4; q++) a4[q] = sb + OFF_WPHI + (4 * hh + q) * 128 + ((((k >> 3) ^ (4 * hh + q)) & 7) << 4) + (k & 7) * 2;
                FOR14(const uint32_t v = (t & 1) ? wv[t >> 1].y : wv[t >> 1].x;
                      asm volatile("{ .reg .b16 l, h; mov.b32 {l, h}, %2; st.shared.u16 [%0+%3], l; st.shared.u16 [%1+%3], h; }"
                                   ::"r"(a4[t >= 7 ? 2 : 0]), "r"(a4[t >= 7 ? 3 : 1]), "r"(v), "n"((t % 7) * 1024) : "memory"));
            }
            __syncwarp();
            fence_async();
            bar_arrive(1, 224);
            bar_arrive(9, 224);
            if (w == 1) {
                mbar_wait(BAR(2), 0);
                mbar_wait(BAR(2), 1);
                const int b = blockIdx.x;
                asm volatile(ELECT "cp.async.bulk.prefetch.L2.global [%0], %1; }" ::"l"(wg + b * 6272), "r"(12544) : "memory");
                asm volatile(ELECT "cp.async.bulk.prefetch.L2.global [%0], %1; }" ::"l"(wu + b * 6272), "r"(12544) : "memory");
                asm volatile(ELECT "cp.async.bulk.prefetch.L2.global [%0], %1; }" ::"l"(wd + b * 6272), "r"(12544) : "memory");
            }
        }
        uint32_t kseq = ld_word(g_c1 + (sl * 8 * 16 + tile) * 32);
        int slot = 0, ph = 0, n = NST;
#pragma unroll 1
        for (int layer = 0; layer < 3; layer++) {
            if (w == 0) {
                const int nend = layer == 0 ? 11 : (layer == 1 ? 42 : 63);
#pragma unroll 1
                for (; n < nend; n++) {
                const uint32_t w0 = __shfl_sync(0xffffffffu, n < 32 ? e0[0] : e0[1], n & 31), w1 = __shfl_sync(0xffffffffu, n < 32 ? e1[0] : e1[1], n & 31);
                const uint32_t dst = sb + slot * STAGE, fb = BAR(n == PACK ? B_PACK : slot);
                const CUtensorMap* m0 = &maps.x + ((w0 >> 2) & 15);
                const CUtensorMap* m1 = &maps.x + ((w0 >> 6) & 15);
                const int c0 = (w0 >> 10) & 2047, c1 = w0 >> 21, r0 = w1 & 0xffff, r1 = w1 >> 16;
                if (n == 25) {
                    int it = 0;
                    uint32_t v;
                    do { asm volatile("ld.acquire.gpu.global.u32 %0, [%1];" : "=r"(v) : "l"(g_cw + sl * 32) : "memory"); } while ((int)(v - cw_target) < 0 && ++it < 0x400000);
                    asm volatile("fence.proxy.async.global;" ::: "memory");
                    __syncwarp();
                }
                mbar_wait(BAR(B_EMPTY + slot), ph);
                __syncwarp();
                asm volatile(ELECT "mbarrier.arrive.expect_tx.shared::cta.b64 _, [%0], %1; }" ::"r"(fb), "r"(STAGE) : "memory");
                if ((w0 & 3) == 0) {
                    tma2d(dst, m0, c0, r0, fb);
                    tma2d(dst + HALF, m1, c1, r1, fb);
                } else if (w0 & 1) {
                    asm volatile(ELECT "cp.async.bulk.shared::cluster.global.mbarrier::complete_tx::bytes [%0], [%1], %2, [%3]; }"
                                 ::"r"(dst), "l"(reinterpret_cast<const char*>(g_wp) + (size_t)r0 * STAGE), "r"(STAGE), "r"(fb) : "memory");
                } else {
                    tma2d(dst, m0, c0, r0, fb); tma2d(dst + 7168, m0, c0, r1, fb);
                    tma2d(dst + HALF, m1, c0, r0, fb); tma2d(dst + HALF + 7168, m1, c0, r1, fb);
                }
                if (n == PACK) asm volatile(ELECT "mbarrier.arrive.shared::cta.b64 _, [%0]; }" ::"r"(BAR(slot)) : "memory");
                if (++slot == NST) { slot = 0; ph ^= 1; }
                }
            } else if (w == 1 && layer == 1) {
                constexpr int ps = PACK % NST;
                mbar_wait(BAR(B_PACK), 0);
                asm volatile("{ .reg .pred e; elect.sync _|e, 0xffffffff;\n"
                             "@e cp.async.bulk.global.shared::cta.bulk_group [%0], [%1], %2;\n"
                             "@e cp.async.bulk.commit_group;\n"
                             "@e cp.async.bulk.wait_group.read 0;\n"
                             "@e mbarrier.arrive.shared::cta.b64 _, [%3], 8;\n"
                             "@e cp.async.bulk.wait_group 0;\n"
                             "@e fence.proxy.async.global;\n"
                             "@e red.release.gpu.global.add.u32 [%4], 1; }"
                             ::"l"(reinterpret_cast<char*>(g_wp) + (size_t)(sl * 16 + tile) * STAGE), "r"(sb + ps * STAGE), "r"(STAGE), "r"(BAR(B_EMPTY + ps)), "l"(g_cw + sl * 32) : "memory");
                __syncwarp();
            }
            if (layer < 2) {
            const uint32_t tag = layer ^ 1;
            kseq++;
            bar_sync(7, 384);
            ASTAMP(0);
            if (tile < 15) {
                const int sq = lane >> 3, pk = 8 * w + (lane & (tile == 14 ? 3 : 7));
                uint32_t v[16];
                if (layer == 0) poll_cnt(g_c1 + ((sl * 8 + (w >> 1) * 4 + (tile >> 2)) * 16 + (lane & 15)) * 32, kseq);
                ASTAMP(1);
                poll4_kv<32>(v, g_kv1 + ((sl * 16 + tile) * 16 + 4 * sq) * 32 + pk, tag);
#pragma unroll
                for (int k = 0; k < 4; k++) {
                    float lo = (bf_lo(v[k]) + bf_lo(v[4 + k])) + (bf_lo(v[8 + k]) + bf_lo(v[12 + k]));
                    float hi = (bf_hi(v[k]) + bf_hi(v[4 + k])) + (bf_hi(v[8 + k]) + bf_hi(v[12 + k]));
                    lo += __shfl_xor_sync(0xffffffffu, lo, 8); hi += __shfl_xor_sync(0xffffffffu, hi, 8);
                    lo += __shfl_xor_sync(0xffffffffu, lo, 16); hi += __shfl_xor_sync(0xffffffffu, hi, 16);
                    v[k] = pack2(lo, hi);
                }
                if (sq == 0) st_pkt<0>(g_kv2 + sl * 512 + 32 * tile + pk, settag(v[0], tag), v[1], v[2], v[3]);
            }
            ASTAMP(2);
            {
                const int item = t128 < 112 ? t128 : 112 + (t128 & 3), d = item >> 1;
                const int cc = t128 < 112 ? 2 * (d >= 28) + (item & 1) : item - 112;
                const int r = t128 < 112 ? d : 56 + (cc >> 1) + 2 * ((t128 - 112) >> 2);
                uint32_t ra = sb + OFF_KVB + r * 128 + 4 * cc, rx = (r & 7) << 4;
                asm volatile("" : "+r"(ra), "+r"(rx));
                FOR14(asm volatile("st.shared.u32 [%0+%2], %1;" ::"r"((ra ^ 8) + (((t & 7) << 4) ^ rx)), "r"(0), "n"((t >> 3) * 8192) : "memory"));
                uint32_t v[16];
                asm volatile("" : "+r"(ra), "+r"(rx));
                poll4_kv<8>(v, g_kv2 + sl * 512 + (item >> 3) * 32 + (item & 7), tag);
                FOR14(asm volatile("st.shared.u32 [%0+%2], %1;" ::"r"(ra + (((t & 7) << 4) ^ rx)), "r"(v[t < 7 ? t : t + 1]), "n"((t >> 3) * 8192) : "memory"));
                fence_async();
            }
            bar_arrive(3, 384);
            ASTAMP(3);
            }
        }
    } else {
        asm volatile("setmaxnreg.inc.sync.aligned.u32 232;");
        int lane = fresh_tid() & 31, prf = pr;
#define pr prf
#define g (lane >> 2)
#define c (lane & 3)
#define t128 (w * 32 + lane)
        const int wu = __shfl_sync(0xffffffffu, fresh_tid() >> 5, 0), w = wu & 3;
        const uint32_t xoff = __shfl_sync(0xffffffffu, (3 * PLANE + ((tile * 2 + wgi) * 8) * 512 + w * 128) * 16, 0);
        char* xu = reinterpret_cast<char*>(g_ex) + xoff;
#define FRESH() asm volatile("" : "+l"(xu), "+r"(lane), "+r"(prf))
#define xp0 (reinterpret_cast<uint4*>(xu) + lane)
        const uint32_t hbuf = sb + OFF_H + wgi * STAGE;
        uint32_t slot = 0, ph = 0, eb1 = 0, eb2 = 0, ackph = 0, rcvph = 0, gatph = 0, swp = 0;
        uint32_t ppid = 6;
#define cx(s) (reinterpret_cast<uint32_t*>(reinterpret_cast<uint4*>(xu) + PL(1) + 112 + (s) * 512))
#define stp (reinterpret_cast<uint4*>(xu) + g + PL(0) + 112)
        uint32_t seq = ld_word(cx(sl));
        uint32_t kseq = ld_word(g_c1 + ((sl * 8 + wu) * 16 + tile) * 32);
        uint32_t stag = ld_word(reinterpret_cast<const uint32_t*>(stp + sl * 512) + 3) & 1;
        asm volatile("barrier.cluster.wait.aligned;" ::: "memory");
        STAMP(1);
        uint32_t X[14];
        const uint32_t x0row = (w < 2 ? hbuf : sb + wgi * STAGE) + ((w & 1) * 16 + (lane & 15)) * 128;
        mbar_wait(BAR(wgi), 0);
        STAMP(51);
#pragma unroll
        for (int j = 0; j < 4; j++) {
            const int G = 7 * sl + min(2 * j + (lane >> 4), 6);
            uint32_t q2, q3;
            asm volatile("ldmatrix.sync.aligned.m8n8.x4.shared.b16 {%0,%1,%2,%3}, [%4];" : "=r"(X[4 * j]), "=r"(X[4 * j + 1]), "=r"(q2), "=r"(q3)
                         : "r"(x0row + (G >> 3) * 4096 + (((G ^ lane) & 7) << 4)) : "memory");
            if (j < 3) { X[(4 * j + 2) % 14] = q2; X[(4 * j + 3) % 14] = q3; }
        }
#define PUSH_SLICE(W)                                                                          \
    {                                                                                          \
        if (t128 == 0) mbar_expect_tx(BAR(B_RECV + wgi), 7168);                                \
        PUSH_BEGIN();                                                                          \
        const uint32_t ra = mapa(hbuf + 24576 + t128 * 16, hr ^ 1), rb = mapa(sb + OFF_XR + wgi * 3072, hr ^ 1), rbar = mapa(BAR(B_RECV + wgi), hr ^ 1); \
        st_async4(ra, W[0], W[1], W[2], W[3], rbar);                                           \
        st_async4(ra + 2048, W[4], W[5], W[6], W[7], rbar);                                    \
        st_async4(rb + t128 * 16, W[8], W[9], W[10], W[11], rbar);                             \
        asm volatile("st.async.weak.shared::cluster.mbarrier::complete_tx::bytes.v2.b32 [%0], {%1,%2}, [%3];" ::"r"(rb + 2048 + t128 * 8), "r"(W[12]), "r"(W[13]), "r"(rbar) : "memory"); \
    }
#define PULL_SLICE(W)                                                                          \
    {                                                                                          \
        uint32_t t0, t1;                                                                       \
        mbar_wait(BAR(B_RECV + wgi), rcvph);                                                   \
        rcvph ^= 1;                                                                            \
        lds4(&A[1][0], hbuf + 24576 + t128 * 16);                                              \
        lds4(&A[1][4], hbuf + 26624 + t128 * 16);                                              \
        lds4(&A[1][8], sb + OFF_XR + wgi * 3072 + t128 * 16);                                  \
        asm volatile("ld.shared.v2.u32 {%0,%1}, [%2];" : "=r"(t0), "=r"(t1) : "r"(sb + OFF_XR + wgi * 3072 + 2048 + t128 * 8) : "memory"); \
        _Pragma("unroll") for (int i = 0; i < 12; i++) A[0][i] = (i & 3) ? W[i] : W[i] & ~1u;  \
        A[1][0] &= ~1u; A[1][4] &= ~1u; A[1][8] &= ~1u;                                        \
        A[0][12] = (hr ? t0 : W[12]) & ~1u; A[0][13] = hr ? t1 : W[13];                        \
        A[1][12] = (hr ? W[12] : t0) & ~1u; A[1][13] = hr ? W[13] : t1;                        \
        asm volatile("" : RW4(A[0], 0), RW4(A[0], 4), RW4(A[0], 8), RW2(A[0], 12), RW4(A[1], 0), RW4(A[1], 4), RW4(A[1], 8), RW2(A[1], 12)); \
        swp = hr * 448;                                                                        \
    }
#define SWB(b, t, db, sh) ((b) == 0 && (t) < 6 ? ((t) < 3 ? db##p : db##m) : db)
#define DECL_DB(b, MK, lbo, sh) const uint64_t db = MK(0, lbo, R_ADJ), dbp = (b) == 0 ? MK(0, lbo, R_ADJ + (swp >> (sh))) : db, dbm = (b) == 0 ? MK(0, lbo, R_ADJ - (swp >> (sh))) : db;
#define PPB 2
#define PP_WAIT() if (wgi == 1) { bar_sync(ppid, 256); ppid ^= 14; }
#define PP_GO() if (wgi == 0) { bar_arrive(ppid, 256); ppid ^= 14; }
#define GAT_DST(B, s2) ((B) == 1 ? hbuf + w * 3584 + (s2) * 1792 : ((s2) ? sb + OFF_KVB + wgi * 8192 : hbuf + 14336) + w * 1792)
#define GAT_ISSUE(B, base)                                                                     \
    {                                                                                          \
        const char* gs = xu + ((base) + kblk(pr, B) * 1024) * 16;                              \
        asm volatile("{ .reg .pred e; elect.sync _|e, 0xffffffff;\n"                           \
                     "@e mbarrier.arrive.expect_tx.shared::cta.b64 _, [%3], 3584;\n"           \
                     "@e cp.async.bulk.shared::cluster.global.mbarrier::complete_tx::bytes [%0], [%2], 1792, [%3];\n" \
                     "@e cp.async.bulk.shared::cluster.global.mbarrier::complete_tx::bytes [%1], [%2+8192], 1792, [%3]; }" \
                     ::"r"(GAT_DST(B, 0)), "r"(GAT_DST(B, 1)), "l"(gs), "r"(BAR(B_GAT + wu * 2 + ((B) >> 1))) : "memory"); \
        __syncwarp();                                                                          \
    }
#define GAT_FETCH(B)                                                                           \
    {                                                                                          \
        mbar_wait(BAR(B_GAT + wu * 2 + ((B) >> 1)), (gatph >> (B)) & 1);                          \
        gatph ^= 1 << (B);                                                                     \
        _Pragma("unroll") for (int s2 = 0; s2 < 2; s2++) {                                     \
            const uint32_t ga = GAT_DST(B, s2) + lane * 16;                                    \
            lds4(&A[2 * (B) + s2][0], ga); lds4(&A[2 * (B) + s2][4], ga + 512); lds4(&A[2 * (B) + s2][8], ga + 1024); \
            asm volatile("ld.shared.v2.u32 {%0,%1}, [%2];" : "=r"(A[2 * (B) + s2][12]), "=r"(A[2 * (B) + s2][13]) : "r"(ga - lane * 8 + 1536) : "memory"); \
        }                                                                                      \
    }
#define LATE_ARRIVE() do { if (lane == 0) mbar_arrive(BAR(B_LATE)); } while (0)
#define LATE_WAIT() do { mbar_wait(BAR(B_LATE), gatph & 1); gatph ^= 1; } while (0)
#define PT 3
#define PREP(b, t, remote)                                                                     \
    if constexpr ((b) < 3 && (t) == PT) {                                                      \
        wg_commit();                                                                           \
        STAMP(74 + 6 * (step & 1) + 2 * (b));                                                  \
        if (remote) {                                                                          \
            if constexpr ((b) == 0) { blk_load<2>(A, BLK(xsrc, 2), lane); GAT_FETCH(1) }       \
            blk_check<((b) + 1) & 3>(A, BLK(xsrc, (b) + 1), lane, xtag);                       \
            if constexpr ((b) == 0) blk_load<3>(A, BLK(xsrc, 3), lane);                        \
        }                                                                                      \
        STAMP(75 + 6 * (step & 1) + 2 * (b));                                                  \
        normalize<((b) + 1) & 3>(A, k0, k1);                                                   \
        asm volatile("" : RW4(A[(2 * (b) + 2) & 7], 0), RW4(A[(2 * (b) + 2) & 7], 4), RW4(A[(2 * (b) + 2) & 7], 8), RW2(A[(2 * (b) + 2) & 7], 12), \
                          RW4(A[(2 * (b) + 3) & 7], 0), RW4(A[(2 * (b) + 3) & 7], 4), RW4(A[(2 * (b) + 3) & 7], 8), RW2(A[(2 * (b) + 3) & 7], 12)); \
        wg_fence();                                                                            \
    }
#define X0_BLOCK(b)                                                                            \
    { const int rr = lane & 7, hi = lane >> 4;                                                 \
    const uint32_t rowa = (w < 2 ? hbuf : sb + wgi * STAGE) + ((w & 1) * 16 + (lane & 15)) * 128; \
    FOR7(constexpr int G = 14 * (b) + (t < 3 ? 2 * t : (t < 6 ? 2 * t + 1 : 6));               \
         uint32_t q0, q1, q2, q3;                                                              \
         const uint32_t ad = t < 6 ? rowa + (((((G & 7) + hi) ^ rr) & 7) << 4) + ((G & 7) == 7 ? hi * 4096 : 0) : rowa + ((G + 7 * hi) >> 3) * 4096 + ((((G + 7 * hi) ^ rr) & 7) << 4); \
         asm volatile("ldmatrix.sync.aligned.m8n8.x4.shared.b16 {%0,%1,%2,%3}, [%4+%5];" : "=r"(q0), "=r"(q1), "=r"(q2), "=r"(q3) \
                      : "r"(ad), "n"(t < 6 ? (G >> 3) * 4096 : 0) : "memory");                 \
         if (t < 3) { A[2 * (b)][4 * t] = q0; A[2 * (b)][4 * t + 1] = q1; A[2 * (b)][4 * t + 2] = q2; A[2 * (b)][4 * t + 3] = q3; } \
         else if (t < 6) { A[2 * (b) + 1][(4 * t - 12) & 15] = q0; A[2 * (b) + 1][((4 * t - 12) & 15) + 1] = q1; A[2 * (b) + 1][((4 * t - 12) & 15) + 2] = q2; A[2 * (b) + 1][((4 * t - 12) & 15) + 3] = q3; } \
         else { A[2 * (b)][12] = q0; A[2 * (b)][13] = q1; A[2 * (b) + 1][12] = q2; A[2 * (b) + 1][13] = q3; }); }
#define BLK(base, b) ((base) + kblk(pr, b) * 1024)

#pragma unroll 1
        for (int step = 0; step < 4; step++) {
            FRESH();
            const uint32_t tag = (step >> 1) ^ 1;
            const int so = (step >> 1) * 24 + (step & 1) * 12;
            (void)so;
            uint32_t A[8][14];
            uint4* const xsrc = xp0 + ((step & 1) ? PL(2) : PL(0));
            const uint32_t xtag = (step & 1) ? tag : ((seq >> 3) & 1) ^ 1;
            uint32_t xbits;
            {
                float st[4];
                slice_stats(X, st);
                stag ^= 1;
                xbits = x_bits(X);
                tag_slice(X, xtag);
                if (step) send_slice<0>(xsrc + sl * 512, lane, X);
                if (c == 0) st_pkt<0>(stp + sl * 512, __float_as_uint(st[0]), __float_as_uint(st[1]), __float_as_uint(st[2]), settag(__float_as_uint(st[3]), stag));
            }
            STAMP(2 + so);
            uint32_t sv[8];
            if (step == 0) {
                X0_BLOCK(0) X0_BLOCK(1) X0_BLOCK(2) X0_BLOCK(3)
                mbar_wait(BAR(wgi ^ 1), 0);
                R_NEXT();
                R_NEXT();
                R_RELEASE(2);
                stat_load(sv, stp + c * 1024);
                stat_check(sv, stp + c * 1024, stag);
                STAMP(52 + step);
            } else {
                kill<14>(A[2]); kill<14>(A[3]); kill<14>(A[4]); kill<14>(A[5]); kill<14>(A[6]); kill<14>(A[7]);
                PUSH_SLICE(X)
                stat_load(sv, stp + c * 1024);
                PULL_SLICE(X)
                stat_check(sv, stp + c * 1024, stag);
                STAMP(52 + step);
                GAT_ISSUE(1, (step & 1) ? PL(2) : PL(0))
            }
            LnCoef k0, k1;
            {
                k0 = ln_coef(__uint_as_float(sv[0]) + __uint_as_float(sv[4]), __uint_as_float(sv[1]) + __uint_as_float(sv[5]));
                k1 = ln_coef(__uint_as_float(sv[2]) + __uint_as_float(sv[6]), __uint_as_float(sv[3] & ~1u) + __uint_as_float(sv[7] & ~1u));
            }
            STAMP(3 + so);
            GSTAMP(70 + step);

            if ((step & 1) == 0) {
                float tq[28];
                {
                    float av[28];
#define KV_BLOCK(b)                                                                           \
    if ((b) == 1) R_RELEASE(2);                                                               \
    if ((b) == 2) { PUSH_ACK(); wg_wait<2>(); R_RELEASE(2); }                                 \
    R_WAIT();                                                                                 \
    if ((b) == PPK) { PP_WAIT() }                                                             \
    { DECL_DB(b, BASE128, 16, 0)                                                              \
    wg_fence();                                                                               \
    FOR7(mma_rs56<1, D128(0, t)>(tq, AQ(A, b, t), (b) + t > 0, SWB(b, t, db, 0));             \
         mma_rs56<1, D128(HALF, t)>(av, AQ(A, b, t), (b) + t > 0, SWB(b, t, db, 0));          \
         PREP(b, t, step)); }                                                                 \
    wg_commit();                                                                              \
    if ((b) == 3 && PPK < 4) { PP_GO() }                                                      \
    R_NEXT();
                    normalize<0>(A, k0, k1);
                    KV_BLOCK(0) KV_BLOCK(1) KV_BLOCK(2) KV_BLOCK(3)
                    wg_wait<0>();
                    if (lane < 3) mbar_arrive(BAR(B_EMPTY + (slot + NST - 1 - lane) % NST));
                    STAMP(4 + so);
                    WSUM(80 + 7 * (step >> 1));
                    const int m = lane >> 3, rr = lane & 7;
                    const uint32_t rowa = hbuf + 16384 + (w * 16 + rr + 8 * (m & 1)) * 128;
                    const uint32_t one = c == 0 ? 0x00003f80u : 0u;
                    if (step == 0) { bar_sync(wgi ? 9 : 1, 224); }
#pragma unroll
                    for (int j = 0; j < 4; j++) {
                        const uint32_t a = rowa + (((2 * j + (m >> 1)) ^ rr) << 4);
                        if (j < 3) stsm4(a, pack2(av[8 * j], av[8 * j + 1]), pack2(av[8 * j + 2], av[8 * j + 3]), pack2(av[8 * j + 4], av[8 * j + 5]), pack2(av[8 * j + 6], av[8 * j + 7]));
                        else stsm4(a, pack2(av[24], av[25]), pack2(av[26], av[27]), one, one);
                    }
                }
                uint32_t PH[28];
                int it = 1;
#pragma unroll 1
                do {
                    float pp[28];
                    phi_gemm(tq, pp);
                    dual_softmax(pp, PH);
                    if (((trips >> (it + 1)) & 1) == 0) continue;
                    {
                        const int m = lane >> 3, rr = lane & 7;
                        const uint32_t rowa = hbuf + (w * 16 + rr + 8 * (m & 1)) * 128;
#pragma unroll
                        for (int j = 0; j < 7; j++) {
                            const int cg = 2 * j + (m >> 1), hi = cg >= 7;
                            stsm4(rowa + hi * 8192 + (((cg - 7 * hi) ^ rr) << 4), PH[4 * j], PH[4 * j + 1], PH[4 * j + 2], PH[4 * j + 3]);
                        }
                    }
                    fence_async();
                    STAMP(5 + so);
#define Q_STAGE(b0)                                                                           \
    R_WAIT();                                                                                 \
    { DECL_DB(b0, BASE128, 16, 0)                                                             \
    wg_fence();                                                                               \
    FOR7(mma_rs56<1, D128(0, t)>(tq, AQ(A, b0, t), (b0) + t > 0, SWB(b0, t, db, 0)));         \
    FOR7(mma_rs56<1, D128(HALF, t)>(tq, AQ(A, (b0) + 1, t), 1, db)); }                        \
    wg_commit();                                                                              \
    R_NEXT();
                    if (QE && wgi == 0) { kill<28>(tq); Q_STAGE(0) Q_STAGE(2) wg_wait<1>(); R_RELEASE(2); wg_wait<0>(); R_RELEASE(1); }
                    bar_sync(2, 256);
                    float kv[28];
                    const uint64_t da = BASE128(OFF_H + 16384, 16, 0), dbk = BASE128(OFF_H, 16, wgi * 512);
                    wg_fence();
                    FOR8(constexpr uint64_t o = ((t >> 2) * STAGE + (t & 3) * 2048) >> 4; mma_ss56_tt<o, o>(kv, t > 0, da, dbk));
                    wg_commit();
                    wg_wait<0>();
#pragma unroll
                    for (int hf = 0; hf < 2; hf++) {
                        const int d = 16 * w + g + 8 * hf;
                        if ((d < 56 && (d >= 28) == (c >= 2)) || d == 56) {
                            const int item = d < 56 ? 2 * d + (c & 1) : 112 + c;
                            uint4* dst = g_kv1 + ((sl * 16 + (item >> 3)) * 16 + tile) * 32 + wgi * 16 + (item & 7);
#define KVW(i) pack2(kv[4 * (i) + 2 * hf], kv[4 * (i) + 2 * hf + 1])
                            st_pkt<0>(dst, settag(KVW(0), tag), KVW(1), KVW(2), KVW(3));
                            st_pkt<8>(dst, settag(KVW(4), tag), KVW(5), KVW(6), 0u);
                        }
                    }
                    __syncwarp();
                    kseq++;
                    if (lane == 0) st_word(g_c1 + ((sl * 8 + wu) * 16 + tile) * 32, kseq);
                    bar_arrive(7, 384);
                    STAMP(6 + so);
                    if (!QE || wgi == 1) { kill<28>(tq); Q_STAGE(0) Q_STAGE(2) wg_wait<1>(); R_RELEASE(2); wg_wait<0>(); R_RELEASE(1); }
                    STAMP(7 + so);
                    kill<28>(PH);
                } while (((trips >> (++it)) & 1));
                STAMP(8 + so);
                FRESH();
                if (step) {
                    slice_load<PL(0)>(X, xp0 + sl * 512, lane);
                } else {
                    const uint32_t* xp = reinterpret_cast<const uint32_t*>(x_in + (size_t)(tile * 128 + wu * 16 + g) * 448 + 56 * sl + 2 * c);
#pragma unroll
                    for (int i = 0; i < 7; i++) { X[2 * i] = __ldg(xp + 4 * i); X[2 * i + 1] = __ldg(xp + 4 * i + 8 * 224); }
                }
                bar_sync(3, 384);
                STAMP(9 + so);
                const uint4* const osrc = xp0 + PL(1);
                {
                    float nm[32];
                    const uint64_t db = BASE128(OFF_KVB, 16, 0);
                    wg_fence();
                    FOR7(mma_rs64<0, ((t >> 2) * 8192 + (t & 3) * 32) / 16>(nm, PH[4 * t], PH[4 * t + 1], PH[4 * t + 2], PH[4 * t + 3], t > 0, db));
                    wg_commit();
                    wg_wait<0>();
                    LATE_ARRIVE();
                    const float i00 = rcp(nm[28] + 1e-6f), i01 = rcp(nm[29] + 1e-6f), i10 = rcp(nm[30] + 1e-6f), i11 = rcp(nm[31] + 1e-6f);
                    const float m0 = c >= 2 ? i01 : i00, m1 = c >= 2 ? i11 : i10;
                    uint32_t O[14];
#pragma unroll
                    for (int i = 0; i < 7; i++) {
                        const float f0 = i < 3 ? i00 : (i > 3 ? i01 : m0), f1 = i < 3 ? i10 : (i > 3 ? i11 : m1);
                        O[2 * i] = pack2(nm[4 * i] * f0, nm[4 * i + 1] * f0);
                        O[2 * i + 1] = pack2(nm[4 * i + 2] * f1, nm[4 * i + 3] * f1);
                    }
                    if (OST) { PP_WAIT() }
                    tag_slice(O, tag);
                    send_slice<PL(1)>(xp0 + sl * 512, lane, O);
                    seq++;
                    if (lane == 0) st_word(cx(sl), seq);
                    STAMP(10 + so);
                    PUSH_SLICE(O)
                    if (OST == 1) { PP_GO() }
                    const uint32_t cv = ld_word(cx(lane & 7));
                    PULL_SLICE(O)
                    LATE_WAIT();
                    check_cnt(cv, cx(lane & 7), seq);
                    if (OST == 2) { PP_GO() }
                    STAMP(56 + (step >> 1));
                    GAT_ISSUE(1, PL(1))
                    GAT_ISSUE(3, PL(1))
                    blk_load<2>(A, BLK(osrc, 2), lane);
                }
                float ao[28];
#define WO_BLOCK(b)                                                                           \
    if ((b) > 0) blk_check<b>(A, BLK(osrc, b), lane, tag);                                    \
    if (((b) & 1) == 0) R_WAIT();                                                             \
    { DECL_DB(b, BASE128, 16, 0)                                                              \
    wg_fence();                                                                               \
    FOR7(mma_rs56<1, D128(((b) & 1) * HALF, t)>(ao, AQ(A, b, t), (b) + t > 0, SWB(b, t, db, 0))); } \
    wg_commit();                                                                              \
    if ((b) & 1) R_NEXT();
                WO_BLOCK(0)
                STAMP(11 + so);
                GAT_FETCH(1)
                WO_BLOCK(1)
                WO_BLOCK(2)
                GAT_FETCH(3)
                WO_BLOCK(3)
                PUSH_ACK();
                wg_wait<0>();
                R_RELEASE(2);
                STAMP(12 + so);
                WSUM(86 + 7 * (step >> 1));
                x_fix(X, xbits);
#pragma unroll
                for (int i = 0; i < 14; i++) X[i] = pack2(bf_lo(X[i]) + ao[2 * i], bf_hi(X[i]) + ao[2 * i + 1]);
            } else {
                uint32_t H[56];
                float ag[64];
#define F1_EPI(dst, ng, ag)                                                                    \
    _Pragma("unroll") for (int i = 0; i < 2 * (ng); i++)                                       \
        (dst)[i] = pack2(geglu(ag[2 * i], ag[4 * (ng) + 2 * i]), geglu(ag[2 * i + 1], ag[4 * (ng) + 2 * i + 1]));
#define H_PUSH(h0, off) st_async4(rem_h + (off), H[h0], H[(h0) + 1], H[(h0) + 2], H[(h0) + 3], mapa(BAR(B_RECV2 + wgi), hr ^ 1));
#define F1_BLOCK(b, first)                                                                     \
    if ((first) && (b) == 1) R_RELEASE(2);                                                     \
    if ((first) && (b) == 2) PUSH_ACK();                                                       \
    R_WAIT();                                                                                  \
    if ((b) == ((first) ? PPF : PPB)) { PP_WAIT() }                                            \
    { DECL_DB(b, BASE128, HALF, 0)                                                             \
    wg_fence();                                                                                \
    FOR7(mma_rs128<1, D128(0, t)>(ag, AQ(A, b, t), (b) + t > 0, SWB(b, t, db, 0));             \
         if constexpr (first) { PREP(b, t, true) }); }                                         \
    wg_commit();                                                                               \
    if ((b) == 3) { PP_GO() }                                                                  \
    if ((b) > 0) { wg_wait<1>(); R_RELEASE(1); }       \
    R_NEXT();
                normalize<0>(A, k0, k1);
                F1_BLOCK(0, true) F1_BLOCK(1, true) F1_BLOCK(2, true) F1_BLOCK(3, true)
                if (t128 == 0) { mbar_expect_tx(BAR(B_RECV + wgi), 16384); mbar_expect_tx(BAR(B_RECV2 + wgi), 12288); }
                PUSH_BEGIN();
                wg_wait<0>();
                R_RELEASE(1);
                int p = 0;
#pragma unroll 1
                do {
                    F1_EPI(H + 32, 8, ag)
                    STAMP(4 + p + so);
                    WSUM(81 + p + 7 * (step >> 1));
                    if (((trips >> (p + 1)) & 1) == 0) continue;
                    {
                        const uint32_t pk = (p ? hbuf + 16384 : sb + OFF_KVB + wgi * 8192) + w * 2048;
#pragma unroll
                        for (int k = 0; k < 4; k++) sts4(pk + k * 512 + lane * 16, H[32 + 4 * k], H[33 + 4 * k], H[34 + 4 * k], H[35 + 4 * k]);
                        fence_async();
                        __syncwarp();
                        asm volatile(ELECT "cp.async.bulk.shared::cluster.shared::cta.mbarrier::complete_tx::bytes [%0], [%1], 2048, [%2]; }"
                                     ::"r"(mapa(hbuf + p * 8192 + w * 2048, hr ^ 1)), "r"(pk), "r"(mapa(BAR(B_RECV + wgi), hr ^ 1)) : "memory");
                    }
                    if (step == 1 && p == PKP) R_NEXT();
                    kill<64>(ag);
                    F1_BLOCK(0, false) F1_BLOCK(1, false) F1_BLOCK(2, false) F1_BLOCK(3, false)
                    wg_wait<0>();
                    R_RELEASE(1);
                    kill<16>(H + 32);
                } while (((trips >> (++p)) & 1));
#pragma unroll
                for (int k = 0; k < 4; k++) lds4(H + 16 + 4 * k, hbuf + 16384 + w * 2048 + k * 512 + lane * 16);
                __syncwarp();
                if (lane == 0) asm volatile("mbarrier.arrive.shared::cluster.b64 _, [%0];" ::"r"(mapa(BAR(B_ACK2 + wgi), hr ^ 1)) : "memory");
                const uint32_t rem_h = mapa(hbuf + w * 2048 + lane * 16, hr ^ 1);
#define F1_LAST(b0)                                                                            \
    R_WAIT();                                                                                  \
    if (b0) { PP_WAIT() }                                                                      \
    { DECL_DB(b0, BASE64, HALF, 1)                                                             \
    wg_fence();                                                                                \
    FOR7(mma_rs64<1, D64(0, t)>(al, AQ(A, b0, t), (b0) + t > 0, SWB(b0, t, db, 1)));           \
    FOR7(mma_rs64<1, D64(7168, t)>(al, AQ(A, (b0) + 1, t), 1, db)); }                          \
    wg_commit();                                                                               \
    if (b0) { PP_GO() }                                                                        \
    R_NEXT();
                float al[32];
                F1_LAST(0)
                mbar_wait(BAR(B_RECV + wgi), rcvph);
                rcvph ^= 1;
                mbar_wait(BAR(B_ACK2 + wgi), step >> 1);
                H_PUSH(32, 16384) H_PUSH(36, 16896)
                F1_LAST(2)
                H_PUSH(40, 17408) H_PUSH(44, 17920)
                wg_wait<1>();
                R_RELEASE(2);
                wg_wait<0>();
                R_RELEASE(1);
                uint32_t HP[56];
#pragma unroll
                for (int k = 0; k < 4; k++) lds4(H + 4 * k, sb + OFF_KVB + wgi * 8192 + w * 2048 + k * 512 + lane * 16);
#pragma unroll
                for (int t = 0; t < 8; t++) lds4(HP + 4 * t, hbuf + (t >> 2) * 8192 + w * 2048 + (t & 3) * 512 + lane * 16);
                F1_EPI(H + 48, 4, al)
                H_PUSH(48, 24576 - w * 1024) H_PUSH(52, 25088 - w * 1024)
                STAMP(7 + so);
                WSUM(84 + 7 * (step >> 1));
                FRESH();
                float acc[28];
                const uint32_t roA = hr ? 256u : 0u, roB = hr ? (uint32_t)-1536 : 0u;
                const uint32_t rpA = hr ? 0u : 256u, rpB = hr ? 0u : (uint32_t)-1536;
                float res[28];
                uint32_t v0[14], v1[14], P[14];
                const uint4* ps = xp0 + sl * 512;
#define F2_OWN_A()                                                                             \
    R_WAIT();                                                                                  \
    d0 = BASE128(0, 16, R_ADJ + roA); d1 = BASE128(0, 16, R_ADJ + roB);                        \
    wg_fence();                                                                                \
    FOR14(if constexpr (t < OT) mma_rs56<1, t * 128>(acc, H[4 * t], H[4 * t + 1], H[4 * t + 2], H[4 * t + 3], t > 0, d0)); \
    wg_commit();
#define F2_OWN_B()                                                                             \
    wg_fence();                                                                                \
    FOR14(if constexpr (t >= OT) mma_rs56<1, t * 128>(acc, H[4 * t], H[4 * t + 1], H[4 * t + 2], H[4 * t + 3], 1, t < 12 ? d0 : d1)); \
    wg_commit();                                                                               \
    R_NEXT();
#define F2_PEER()                                                                              \
    R_WAIT();                                                                                  \
    if (F2PP) { PP_WAIT() }                                                                    \
    d0 = BASE128(0, 16, R_ADJ + rpA); d1 = BASE128(0, 16, R_ADJ + rpB);                        \
    wg_fence();                                                                                \
    FOR14(mma_rs56<1, t * 128>(acc, HP[4 * t], HP[4 * t + 1], HP[4 * t + 2], HP[4 * t + 3], 1, t < 12 ? d0 : d1)); \
    wg_commit();                                                                               \
    if (F2PP) { PP_GO() }                                                                      \
    R_NEXT();
#define F2_TURN(u)                                                                             \
    wg_wait<1>();                                                                              \
    if ((u) < 2 || TDEF < 2) R_RELEASE(2);                                                     \
    wg_wait<0>();                                                                              \
    if ((u) < 2 || TDEF < 1) R_RELEASE(1);                                                     \
    _Pragma("unroll") for (int i = 0; i < 14; i++) P[i] = pack2(acc[2 * i], acc[2 * i + 1]);   \
    tag_slice(P, tag);                                                                         \
    asm volatile("" : RW4(P, 0), RW4(P, 4), RW4(P, 8), RW2(P, 12));                            \
    kill<28>(acc);                                                                             \
    F2_OWN_A()                                                                                 \
    if ((u) == 2) { slice_load<PL(3)>(v0, ps, lane); slice_load<PL(4)>(v1, ps, lane); } \
    send_slice<PL(3 + (u))>(xp0 + (2 * ((pr + (u) + 1) & 3) + hr) * 512, lane, P);             \
    seq++;                                                                                     \
    if (lane == 0) st_word(cx(sl), seq);                                                       \
    __syncwarp();                                                                              \
    STAMP(8 + (u) + so);                                                                       \
    F2_OWN_B()
                uint64_t d0, d1;
                F2_OWN_A()
                F2_OWN_B()
                R_WAIT();
                d0 = BASE128(0, 16, R_ADJ + rpA); d1 = BASE128(0, 16, R_ADJ + rpB);
                wg_fence();
                FOR8(mma_rs56<1, t * 128>(acc, HP[4 * t], HP[4 * t + 1], HP[4 * t + 2], HP[4 * t + 3], 1, d0));
                wg_commit();
                mbar_wait(BAR(B_RECV2 + wgi), step >> 1);
#pragma unroll
                for (int k = 0; k < 4; k++) lds4(HP + 32 + 4 * k, hbuf + 16384 + w * 2048 + k * 512 + lane * 16);
                lds4(HP + 48, hbuf + 24576 + w * 1024 + lane * 16);
                lds4(HP + 52, hbuf + 25088 + w * 1024 + lane * 16);
                if (step == 1) PUSH_ACK();
                wg_fence();
                FOR14(if constexpr (t >= 8) mma_rs56<1, t * 128>(acc, HP[4 * t], HP[4 * t + 1], HP[4 * t + 2], HP[4 * t + 3], 1, t < 12 ? d0 : d1));
                wg_commit();
                R_NEXT();
                F2_TURN(0)
                F2_PEER()
                F2_TURN(1)
                F2_PEER()
                F2_TURN(2)
                if (step == 1) STAMP(64);
                slice_check<PL(3)>(v0, ps, lane, tag);
                slice_check<PL(4)>(v1, ps, lane, tag);
#pragma unroll
                for (int i = 0; i < 14; i++) { res[2 * i] = bf_lo(v0[i]) + bf_lo(v1[i]); res[2 * i + 1] = bf_hi(v0[i]) + bf_hi(v1[i]); }
                slice_load<PL(2)>(X, ps, lane);
                if (step == 1) STAMP(65);
                F2_PEER()
                if (step == 1) STAMP(66);
                poll_cnt(cx(2 * ((pr + 1) & 3) + hr), seq);
                if (step == 1) STAMP(67);
                slice_load<PL(5)>(v0, ps, lane);
                x_fix(X, xbits);
                slice_check<PL(5)>(v0, ps, lane, tag);
                if (lane < TDEF) mbar_arrive(BAR(B_EMPTY + (slot + NST - 3 - lane) % NST));
#pragma unroll
                for (int i = 0; i < 14; i++) { res[2 * i] += bf_lo(v0[i]); res[2 * i + 1] += bf_hi(v0[i]); }
                STAMP(11 + so);
                wg_wait<0>();
                R_RELEASE(2);
                STAMP(12 + so);
                WSUM(85 + 7 * (step >> 1));
#pragma unroll
                for (int i = 0; i < 14; i++) X[i] = pack2(fmaf(res[2 * i] + acc[2 * i], 0.5f, bf_lo(X[i])), fmaf(res[2 * i + 1] + acc[2 * i + 1], 0.5f, bf_hi(X[i])));
            }
        }
        {
            const int m = lane >> 3, rr = lane & 7;
            const uint32_t ob = hbuf + w * 2048, rowa = ob + (rr + 8 * (m & 1)) * 112 + (m >> 1) * 16;
#pragma unroll
            for (int j = 0; j < 3; j++) stsm4(rowa + 32 * j, X[4 * j], X[4 * j + 1], X[4 * j + 2], X[4 * j + 3]);
            asm volatile("stmatrix.sync.aligned.m8n8.x2.shared.b16 [%0], {%1,%2};" ::"r"(ob + (rr + 8 * (m & 1)) * 112 + 96), "r"(X[12]), "r"(X[13]) : "memory");
            fence_async();
            __syncwarp();
            if (lane == 0) {
                asm volatile("cp.async.bulk.tensor.2d.global.shared::cta.bulk_group [%0, {%2, %3}], [%1];" ::"l"(&maps.out), "r"(ob), "r"(56 * sl), "r"(tile * 128 + wu * 16) : "memory");
                asm volatile("cp.async.bulk.commit_group;" ::: "memory");
                asm volatile("cp.async.bulk.wait_group.read 0;" ::: "memory");
            }
        }
        STAMP(50);
        GSTAMP(61);
        PDUMP();
    }
}

#undef g
#undef pr
#undef c
#undef t128

typedef CUresult (*EncodeFn)(CUtensorMap*, CUtensorMapDataType, cuuint32_t, void*, const cuuint64_t*, const cuuint64_t*, const cuuint32_t*,
                             const cuuint32_t*, CUtensorMapInterleave, CUtensorMapSwizzle, CUtensorMapL2promotion, CUtensorMapFloatOOBfill);

static void make_map(EncodeFn enc, CUtensorMap* m, const void* p, uint64_t cols, uint64_t rows, uint32_t bc, uint32_t br, CUtensorMapSwizzle sw) {
    cuuint64_t gd[2] = {cols, rows};
    cuuint64_t gs[1] = {cols * 2};
    cuuint32_t bd[2] = {bc, br};
    cuuint32_t es[2] = {1, 1};
    enc(m, CU_TENSOR_MAP_DATA_TYPE_BFLOAT16, 2, const_cast<void*>(p), gd, gs, bd, es, CU_TENSOR_MAP_INTERLEAVE_NONE, sw,
        CU_TENSOR_MAP_L2_PROMOTION_L2_128B, CU_TENSOR_MAP_FLOAT_OOB_FILL_NONE);
}

extern "C" void kernel_launch(void* const* d_in, const int* in_sizes, int n_in, void* d_out, int out_size) {
    (void)in_sizes; (void)n_in; (void)out_size;
    static EncodeFn enc = nullptr;
    static Scratch* scratch = nullptr;
    if (!enc) {
        void* fn = nullptr;
        cudaDriverEntryPointQueryResult qr;
        cudaGetDriverEntryPoint("cuTensorMapEncodeTiled", &fn, cudaEnableDefault, &qr);
        enc = (EncodeFn)fn;
        cudaGetSymbolAddress((void**)&scratch, g_scratch);
        cudaFuncSetAttribute(fused_kernel, cudaFuncAttributeMaxDynamicSharedMemorySize, SMEM_BYTES);
    }
    Maps maps;
    {
        cuuint64_t gd[3] = {64, 2048, 7};
        cuuint64_t gs[2] = {896, 128};
        cuuint32_t bd[3] = {64, 32, 7};
        cuuint32_t es[3] = {1, 1, 1};
        enc(&maps.x, CU_TENSOR_MAP_DATA_TYPE_BFLOAT16, 3, d_in[0], gd, gs, bd, es, CU_TENSOR_MAP_INTERLEAVE_NONE, CU_TENSOR_MAP_SWIZZLE_128B,
            CU_TENSOR_MAP_L2_PROMOTION_L2_128B, CU_TENSOR_MAP_FLOAT_OOB_FILL_NONE);
    }
    make_map(enc, &maps.out, d_out, 448, 2048, 56, 16, CU_TENSOR_MAP_SWIZZLE_NONE);
    make_map(enc, &maps.qkv, d_in[1], 1344, 448, 64, 112, CU_TENSOR_MAP_SWIZZLE_128B);
    make_map(enc, &maps.wo, d_in[3], 448, 448, 64, 112, CU_TENSOR_MAP_SWIZZLE_128B);
    make_map(enc, &maps.wg, d_in[5], 1792, 448, 64, 112, CU_TENSOR_MAP_SWIZZLE_128B);
    make_map(enc, &maps.wu, d_in[6], 1792, 448, 64, 112, CU_TENSOR_MAP_SWIZZLE_128B);
    make_map(enc, &maps.wg32, d_in[5], 1792, 448, 32, 112, CU_TENSOR_MAP_SWIZZLE_64B);
    make_map(enc, &maps.wu32, d_in[6], 1792, 448, 32, 112, CU_TENSOR_MAP_SWIZZLE_64B);
    make_map(enc, &maps.wd, d_in[7], 448, 1792, 64, 112, CU_TENSOR_MAP_SWIZZLE_128B);
    fused_kernel<<<128, 384, SMEM_BYTES>>>(scratch, (const __nv_bfloat16*)d_in[0], (const __nv_bfloat16*)d_in[2], 7, (const __nv_bfloat16*)d_in[5],
                                           (const __nv_bfloat16*)d_in[6], (const __nv_bfloat16*)d_in[7], maps);
}
```

```cpp
#include <cuda_runtime.h>
#include <cuda.h>
#include <cuda_bf16.h>
#include <stdint.h>
#include <type_traits>

#define PPF 2
#define PKP 0
#define TDEF 1
#define TMPF 0
#define NORM1 0
#define ACAN 0
#define SPLIT0 1
#define OT 2
#define F2PP 0
#define PPK 2
#define QE 1
#define OST 1
#define PP

namespace {

constexpr uint32_t STAGE = 28672, HALF = 14336;
constexpr int NST = 5;
constexpr uint32_t OFF_H = NST * STAGE;
constexpr uint32_t OFF_KVB = OFF_H + 2 * STAGE;
constexpr uint32_t OFF_WPHI = OFF_KVB + 16384;
constexpr uint32_t OFF_XR = OFF_WPHI + 7168;
constexpr uint32_t OFF_BAR = OFF_XR + 6144;
constexpr uint32_t SMEM_BYTES = OFF_BAR + 384 + 1408;
constexpr int B_EMPTY = NST, B_RECV = 2 * NST, B_RECV2 = B_RECV + 2, B_PACK = B_RECV2 + 2, B_GAT = B_PACK + 1, B_LATE = B_GAT + 16, B_ACK = B_LATE + 1, B_ACK2 = B_ACK + 2, B_COUNT = B_ACK2 + 2;

constexpr int PACK = 14 + 4 * PKP;

struct Maps { CUtensorMap x, qkv, wo, wg, wu, wg32, wu32, wd, out; };

}

constexpr int PLANE = 16 * 2 * 8 * 512;
struct Scratch {
    uint4 ex[6 * PLANE];
    uint4 kv1[8 * 16 * 16 * 32];
    uint4 kv2[8 * 512];
    uint32_t c1[8 * 8 * 16 * 32];
    uint32_t cw[8 * 32];
    uint4 wp[8 * 32 * (HALF / 16)];
};
__device__ __align__(1024) Scratch g_scratch;
#define g_ex (sc->ex)
#define g_kv1 (sc->kv1)
#define g_kv2 (sc->kv2)
#define g_c1 (sc->c1)
#define g_cw (sc->cw)
#define g_wp (sc->wp)
#define STAMP(i)
#define GSTAMP(i)
#define PDUMP()
#define ASTAMP(i)

namespace {

__device__ __forceinline__ int fresh_tid() { int t; asm volatile("mov.u32 %0, %%tid.x;" : "=r"(t)); return t; }
template <int N> __device__ __forceinline__ void kill(uint32_t* v) {
#pragma unroll
    for (int i = 0; i < N; i++) v[i] = 0;
}
template <int N> __device__ __forceinline__ void kill(float* v) {
#pragma unroll
    for (int i = 0; i < N; i++) v[i] = 0.f;
}
__device__ __forceinline__ uint32_t s2u(const void* p) { return (uint32_t)__cvta_generic_to_shared(p); }
__device__ __forceinline__ void mbar_init(uint32_t a, uint32_t c) { asm volatile("mbarrier.init.shared::cta.b64 [%0], %1;" ::"r"(a), "r"(c) : "memory"); }
__device__ __forceinline__ void mbar_expect_tx(uint32_t a, uint32_t b) { asm volatile("mbarrier.arrive.expect_tx.shared::cta.b64 _, [%0], %1;" ::"r"(a), "r"(b) : "memory"); }
__device__ __forceinline__ void mbar_arrive(uint32_t a) { asm volatile("mbarrier.arrive.shared::cta.b64 _, [%0];" ::"r"(a) : "memory"); }
#define GIVE_UP(id) "trap;\n"
#define SPIN_MAX "0x400000"
#define SPIN_TAIL(id) "add.u32 n, n, 1;\n setp.lt.u32 p, n, " SPIN_MAX ";\n @p bra.uni LP;\n" GIVE_UP(id) " DN:\n }"
__device__ __forceinline__ void mbar_wait(uint32_t a, uint32_t ph) {
    asm volatile("{ .reg .pred p; .reg .b32 n; mov.u32 n, 0;\n LP:\n"
                 "mbarrier.try_wait.parity.shared::cta.b64 p, [%0], %1;\n @p bra DN;\n"
                 "add.u32 n, n, 1;\n setp.lt.u32 p, n, " SPIN_MAX ";\n @p bra LP;\n"
                 GIVE_UP("")
                 " DN:\n }" ::"r"(a), "r"(ph) : "memory");
}
#define ELECT "{ .reg .pred e; elect.sync _|e, 0xffffffff; @e "
__device__ __forceinline__ void tma2d(uint32_t dst, const CUtensorMap* m, int c0, int c1, uint32_t bar) {
    asm volatile(ELECT "cp.async.bulk.tensor.2d.shared::cluster.global.mbarrier::complete_tx::bytes [%0], [%1, {%3, %4}], [%2]; }" ::"r"(dst), "l"(m), "r"(bar), "r"(c0), "r"(c1) : "memory");
}
__device__ __forceinline__ void tma3x(uint32_t dst, const CUtensorMap* m, int row, uint32_t bar) {
    asm volatile(ELECT "cp.async.bulk.tensor.3d.shared::cluster.global.mbarrier::complete_tx::bytes [%0], [%1, {0, %3, 0}], [%2]; }" ::"r"(dst), "l"(m), "r"(bar), "r"(row) : "memory");
}
template <int OFF>
__device__ __forceinline__ void ld_pkt(uint32_t* v, const uint4* p) {
    asm volatile("{ .reg .b128 t; ld.relaxed.gpu.global.b128 t, [%4+%5]; mov.b128 {%0,%1,%2,%3}, t; }" : "=r"(v[0]), "=r"(v[1]), "=r"(v[2]), "=r"(v[3]) : "l"(p), "n"(OFF * 16) : "memory");
}
template <int OFF>
__device__ __forceinline__ void st_pkt(uint4* p, uint32_t a, uint32_t b, uint32_t c, uint32_t d) {
    asm volatile("{ .reg .b128 t; mov.b128 t, {%1,%2,%3,%4}; st.relaxed.gpu.global.b128 [%0+%5], t; }" ::"l"(p), "r"(a), "r"(b), "r"(c), "r"(d), "n"(OFF * 16) : "memory");
}
__device__ __forceinline__ uint32_t pack2(float lo, float hi) {
    uint32_t r;
    asm("cvt.rn.bf16x2.f32 %0, %1, %2;" : "=r"(r) : "f"(hi), "f"(lo));
    return r;
}
__device__ __forceinline__ float bf_lo(uint32_t w) { return __uint_as_float(w << 16); }
__device__ __forceinline__ float bf_hi(uint32_t w) { return __uint_as_float(w & 0xffff0000u); }
__device__ __forceinline__ uint32_t settag(uint32_t w, uint32_t tag) { return (w & ~1u) | tag; }
__device__ __forceinline__ float ex2(float x) { float y; asm("ex2.approx.ftz.f32 %0, %1;" : "=f"(y) : "f"(x)); return y; }
__device__ __forceinline__ float rcp(float x) { float y; asm("rcp.approx.ftz.f32 %0, %1;" : "=f"(y) : "f"(x)); return y; }
__device__ __forceinline__ float tanh_hw(float x) { float y; asm("tanh.approx.f32 %0, %1;" : "=f"(y) : "f"(x)); return y; }
__device__ __forceinline__ void stsm4(uint32_t addr, uint32_t a, uint32_t b, uint32_t c, uint32_t d) {
    asm volatile("stmatrix.sync.aligned.m8n8.x4.shared.b16 [%0], {%1,%2,%3,%4};" ::"r"(addr), "r"(a), "r"(b), "r"(c), "r"(d) : "memory");
}
__device__ __forceinline__ void fence_async() { asm volatile("fence.proxy.async.shared::cta;" ::: "memory"); }
__device__ __forceinline__ void bar_sync(int id, int n) { asm volatile("bar.sync %0, %1;" ::"r"(id), "r"(n) : "memory"); }
__device__ __forceinline__ void bar_arrive(int id, int n) { asm volatile("bar.arrive %0, %1;" ::"r"(id), "r"(n) : "memory"); }
__device__ __forceinline__ void wg_fence() { asm volatile("wgmma.fence.sync.aligned;" ::: "memory"); }
__device__ __forceinline__ void wg_commit() { asm volatile("wgmma.commit_group.sync.aligned;" ::: "memory"); }
template <int N> __device__ __forceinline__ void wg_wait() { asm volatile("wgmma.wait_group.sync.aligned %0;" ::"n"(N) : "memory"); }

constexpr uint32_t SB0 = 1024;
__host__ __device__ constexpr uint32_t dlo(uint32_t off, uint32_t lbo) { return ((SB0 + off) >> 4) | ((lbo >> 4) << 16); }
__host__ __device__ constexpr uint32_t dhi(uint32_t sbo, uint32_t sw) { return (sbo >> 4) | (sw << 30); }
__device__ __forceinline__ uint64_t dbase(uint32_t lo, uint32_t hi) { uint64_t d; asm volatile("mov.b64 %0, {%1, %2};" : "=l"(d) : "r"(lo), "r"(hi)); return d; }
#define BASE128(off, lbo, adj) dbase(dlo(off, lbo) + (adj), dhi(1024, 1))
#define BASE64(off, lbo, adj) dbase(dlo(off, lbo) + (adj), dhi(512, 2))

#define ACC4(d, o) "+f"(d[o]), "+f"(d[o + 1]), "+f"(d[o + 2]), "+f"(d[o + 3])
#define ACC28(d) ACC4(d, 0), ACC4(d, 4), ACC4(d, 8), ACC4(d, 12), ACC4(d, 16), ACC4(d, 20), ACC4(d, 24)
#define ACC32(d, o) ACC4(d, o), ACC4(d, o + 4), ACC4(d, o + 8), ACC4(d, o + 12), ACC4(d, o + 16), ACC4(d, o + 20), ACC4(d, o + 24), ACC4(d, o + 28)

template <int TB, uint64_t D>
__device__ __forceinline__ void mma_rs56(float* d, uint32_t a0, uint32_t a1, uint32_t a2, uint32_t a3, int sd, uint64_t base) {
    asm volatile("{ .reg .pred p; .reg .b64 db; setp.ne.b32 p, %32, 0; add.u64 db, %33, %34;\n"
                 "wgmma.mma_async.sync.aligned.m64n56k16.f32.bf16.bf16 "
                 "{%0,%1,%2,%3,%4,%5,%6,%7,%8,%9,%10,%11,%12,%13,%14,%15,%16,%17,%18,%19,%20,%21,%22,%23,%24,%25,%26,%27}, "
                 "{%28,%29,%30,%31}, db, p, 1, 1, %35; }\n"
                 : ACC28(d)
                 : "r"(a0), "r"(a1), "r"(a2), "r"(a3), "r"(sd), "l"(base), "n"(D), "n"(TB));
}
template <int TB, uint64_t D>
__device__ __forceinline__ void mma_rs64(float* d, uint32_t a0, uint32_t a1, uint32_t a2, uint32_t a3, int sd, uint64_t base) {
    asm volatile("{ .reg .pred p; .reg .b64 db; setp.ne.b32 p, %36, 0; add.u64 db, %37, %38;\n"
                 "wgmma.mma_async.sync.aligned.m64n64k16.f32.bf16.bf16 "
                 "{%0,%1,%2,%3,%4,%5,%6,%7,%8,%9,%10,%11,%12,%13,%14,%15,%16,%17,%18,%19,%20,%21,%22,%23,%24,%25,%26,%27,%28,%29,%30,%31}, "
                 "{%32,%33,%34,%35}, db, p, 1, 1, %39; }\n"
                 : ACC32(d, 0)
                 : "r"(a0), "r"(a1), "r"(a2), "r"(a3), "r"(sd), "l"(base), "n"(D), "n"(TB));
}
template <int TB, uint64_t D>
__device__ __forceinline__ void mma_rs128(float* d, uint32_t a0, uint32_t a1, uint32_t a2, uint32_t a3, int sd, uint64_t base) {
    asm volatile("{ .reg .pred p; .reg .b64 db; setp.ne.b32 p, %68, 0; add.u64 db, %69, %70;\n"
                 "wgmma.mma_async.sync.aligned.m64n128k16.f32.bf16.bf16 "
                 "{%0,%1,%2,%3,%4,%5,%6,%7,%8,%9,%10,%11,%12,%13,%14,%15,%16,%17,%18,%19,%20,%21,%22,%23,%24,%25,%26,%27,%28,%29,%30,%31,%32,%33,%34,%35,%36,%37,%38,%39,%40,%41,%42,%43,%44,%45,%46,%47,%48,%49,%50,%51,%52,%53,%54,%55,%56,%57,%58,%59,%60,%61,%62,%63}, "
                 "{%64,%65,%66,%67}, db, p, 1, 1, %71; }\n"
                 : ACC32(d, 0), ACC32(d, 32)
                 : "r"(a0), "r"(a1), "r"(a2), "r"(a3), "r"(sd), "l"(base), "n"(D), "n"(TB));
}
template <uint64_t DA, uint64_t DB>
__device__ __forceinline__ void mma_ss56_tt(float* d, int sd, uint64_t ba, uint64_t bb) {
    asm volatile("{ .reg .pred p; .reg .b64 da, db; setp.ne.b32 p, %28, 0; add.u64 da, %29, %31; add.u64 db, %30, %32;\n"
                 "wgmma.mma_async.sync.aligned.m64n56k16.f32.bf16.bf16 "
                 "{%0,%1,%2,%3,%4,%5,%6,%7,%8,%9,%10,%11,%12,%13,%14,%15,%16,%17,%18,%19,%20,%21,%22,%23,%24,%25,%26,%27}, "
                 "da, db, p, 1, 1, 1, 1; }\n"
                 : ACC28(d)
                 : "r"(sd), "l"(ba), "l"(bb), "n"(DA), "n"(DB));
}
template <int... I> struct Seq {};
template <class F, int... I> __device__ __forceinline__ void static_for_impl(F&& f, Seq<I...>) { (f(std::integral_constant<int, I>{}), ...); }
#define FOR7(...) static_for_impl([&](auto T_) { constexpr int t = decltype(T_)::value; __VA_ARGS__; }, Seq<0, 1, 2, 3, 4, 5, 6>{})
#define FOR8(...) static_for_impl([&](auto T_) { constexpr int t = decltype(T_)::value; __VA_ARGS__; }, Seq<0, 1, 2, 3, 4, 5, 6, 7>{})
#define FOR14(...) static_for_impl([&](auto T_) { constexpr int t = decltype(T_)::value; __VA_ARGS__; }, Seq<0, 1, 2, 3, 4, 5, 6, 7, 8, 9, 10, 11, 12, 13>{})

__device__ __forceinline__ int kblk(int p, int b) { return b == 0 ? p : b - (b <= p); }
__host__ __device__ constexpr int krow(int t) { return t < 3 ? 16 * t : (t < 6 ? 56 + 16 * (t - 3) : 48); }
#define AQ(A, b, t) ((t) < 3 ? A[2 * (b)][4 * (t)] : (t) < 6 ? A[2 * (b) + 1][4 * ((t) - 3)] : A[2 * (b)][12]), \
                    ((t) < 3 ? A[2 * (b)][4 * (t) + 1] : (t) < 6 ? A[2 * (b) + 1][4 * ((t) - 3) + 1] : A[2 * (b)][13]), \
                    ((t) < 3 ? A[2 * (b)][4 * (t) + 2] : (t) < 6 ? A[2 * (b) + 1][4 * ((t) - 3) + 2] : A[2 * (b) + 1][12]), \
                    ((t) < 3 ? A[2 * (b)][4 * (t) + 3] : (t) < 6 ? A[2 * (b) + 1][4 * ((t) - 3) + 3] : A[2 * (b) + 1][13])
#define D128(off, t) ((uint64_t)(((off) + krow(t) * 128) >> 4) + ((uint64_t)((t) == 6 ? (7168 - 1024) >> 4 : 0) << 32))
#define D64(off, t) ((uint64_t)(((off) + krow(t) * 64) >> 4) + ((uint64_t)((t) == 6 ? (3584 - 512) >> 4 : 0) << 32))

#define PL(k) (((k) - 3) * PLANE)
__device__ __forceinline__ void st_word(uint32_t* p, uint32_t v) { asm volatile("st.relaxed.gpu.global.u32 [%0], %1;" ::"l"(p), "r"(v) : "memory"); }
__device__ __forceinline__ uint32_t ld_word(const uint32_t* p) { uint32_t v; asm volatile("ld.relaxed.gpu.global.u32 %0, [%1];" : "=r"(v) : "l"(p) : "memory"); return v; }
__device__ __forceinline__ void tag_slice(uint32_t* w, uint32_t tag) { w[0] = settag(w[0], tag); w[4] = settag(w[4], tag); w[8] = settag(w[8], tag); w[12] = settag(w[12], tag); }
template <int O>
__device__ __forceinline__ void send_slice(uint4* dst, int lane, const uint32_t* w) {
    st_pkt<O>(dst, w[0], w[1], w[2], w[3]);
    st_pkt<O + 32>(dst, w[4], w[5], w[6], w[7]);
    st_pkt<O + 64>(dst, w[8], w[9], w[10], w[11]);
    asm volatile("{ .reg .b64 t; mov.b64 t, {%1,%2}; st.relaxed.gpu.global.b64 [%0+%3], t; }" ::"l"((char*)dst - lane * 8), "r"(w[12]), "r"(w[13]), "n"(16 * (O + 96)) : "memory");
}
#define RW4(v, o) "+r"(v[o]), "+r"(v[(o) + 1]), "+r"(v[(o) + 2]), "+r"(v[(o) + 3])
#define RW2(v, o) "+r"(v[o]), "+r"(v[(o) + 1])
#define WR4(v, o) "=&r"(v[o]), "=&r"(v[(o) + 1]), "=&r"(v[(o) + 2]), "=&r"(v[(o) + 3])
#define LDP(a, b, c, d, addr, off) "ld.relaxed.gpu.global.b128 q, [" addr "+" off "];\n mov.b128 {" a "," b "," c "," d "}, q;\n"
#define LDH(a, b, addr, off) "ld.relaxed.gpu.global.b64 h, [" addr "+" off "];\n mov.b64 {" a "," b "}, h;\n"
#define VOTE_OK "and.b32 t, t, 1;\n setp.ne.u32 p, t, 0;\n vote.sync.any.pred p, p, 0xffffffff;\n @!p bra.uni DN;\n"
#define CHK(x, tag) "lop3.b32 t, " x ", " tag ", t, 0xBE;\n"
__device__ __forceinline__ void check_cnt(uint32_t v, const uint32_t* p, uint32_t target) {
    asm volatile("{ .reg .pred p; .reg .b32 n, t; mov.u32 n, 0; mov.u32 t, %2;\n LP:\n"
                 "sub.s32 t, t, %1;\n setp.lt.s32 p, t, 0;\n vote.sync.any.pred p, p, 0xffffffff;\n @!p bra.uni DN;\n ld.relaxed.gpu.global.u32 t, [%0];\n" SPIN_TAIL("7")
                 ::"l"(p), "r"(target), "r"(v) : "memory");
}
__device__ __forceinline__ void poll_cnt(const uint32_t* p, uint32_t target) {
    asm volatile("{ .reg .pred p; .reg .b32 n, t; mov.u32 n, 0;\n LP:\n"
                 "ld.relaxed.gpu.global.u32 t, [%0];\n sub.s32 t, t, %1;\n setp.lt.s32 p, t, 0;\n vote.sync.any.pred p, p, 0xffffffff;\n @!p bra.uni DN;\n" SPIN_TAIL("1")
                 ::"l"(p), "r"(target) : "memory");
}
template <int STR>
__device__ __forceinline__ void poll4_kv(uint32_t* v, const uint4* p, uint32_t tag) {
    asm volatile("{ .reg .pred p; .reg .b32 n, t; .reg .b128 q; mov.u32 n, 0;\n LP:\n"
                 LDP("%0", "%1", "%2", "%3", "%16", "0") LDP("%4", "%5", "%6", "%7", "%16", "%18")
                 LDP("%8", "%9", "%10", "%11", "%16", "%19") LDP("%12", "%13", "%14", "%15", "%16", "%20")
                 "xor.b32 t, %0, %17;\n" CHK("%4", "%17") CHK("%8", "%17") CHK("%12", "%17") VOTE_OK SPIN_TAIL("2")
                 : WR4(v, 0), WR4(v, 4), WR4(v, 8), WR4(v, 12)
                 : "l"(p), "r"(tag), "n"(16 * STR), "n"(32 * STR), "n"(48 * STR)
                 : "memory");
}
template <int B>
__device__ __forceinline__ void blk_load(uint32_t (&A)[8][14], const uint4* src, int lane) {
    ld_pkt<0>(&A[2 * B][0], src); ld_pkt<32>(&A[2 * B][4], src); ld_pkt<64>(&A[2 * B][8], src);
    ld_pkt<512>(&A[2 * B + 1][0], src); ld_pkt<544>(&A[2 * B + 1][4], src); ld_pkt<576>(&A[2 * B + 1][8], src);
    asm volatile("{ .reg .b64 h;\n" LDH("%0", "%1", "%4", "1536") LDH("%2", "%3", "%4", "9728") "}"
                 : "=&r"(A[2 * B][12]), "=&r"(A[2 * B][13]), "=&r"(A[2 * B + 1][12]), "=&r"(A[2 * B + 1][13])
                 : "l"((const char*)src - lane * 8) : "memory");
}
template <int B>
__device__ __forceinline__ void blk_check(uint32_t (&A)[8][14], const uint4* src, int lane, uint32_t tag) {
    asm volatile("{ .reg .pred p; .reg .b32 n, t; .reg .b128 q; .reg .b64 h, a8; mov.u32 n, 0;\n LP:\n"
                 "xor.b32 t, %0, %30;\n" CHK("%4", "%30") CHK("%8", "%30") CHK("%12", "%30") CHK("%16", "%30") CHK("%20", "%30") CHK("%24", "%30") CHK("%26", "%30") VOTE_OK
                 LDP("%0", "%1", "%2", "%3", "%28", "0") LDP("%4", "%5", "%6", "%7", "%28", "512") LDP("%8", "%9", "%10", "%11", "%28", "1024")
                 LDP("%12", "%13", "%14", "%15", "%28", "8192") LDP("%16", "%17", "%18", "%19", "%28", "8704") LDP("%20", "%21", "%22", "%23", "%28", "9216")
                 "mad.wide.s32 a8, %29, -8, %28;\n" LDH("%24", "%25", "a8", "1536") LDH("%26", "%27", "a8", "9728") SPIN_TAIL("3")
                 "\n and.b32 %0, %0, -2; and.b32 %4, %4, -2; and.b32 %8, %8, -2; and.b32 %12, %12, -2; and.b32 %16, %16, -2; and.b32 %20, %20, -2; and.b32 %24, %24, -2; and.b32 %26, %26, -2;"
                 : RW4(A[2 * B], 0), RW4(A[2 * B], 4), RW4(A[2 * B], 8), RW4(A[2 * B + 1], 0), RW4(A[2 * B + 1], 4), RW4(A[2 * B + 1], 8),
                   RW2(A[2 * B], 12), RW2(A[2 * B + 1], 12)
                 : "l"(src), "r"(lane), "r"(tag)
                 : "memory");
}
__device__ __forceinline__ void st_async4(uint32_t a, uint32_t x, uint32_t y, uint32_t z, uint32_t w, uint32_t bar) {
    asm volatile("st.async.weak.shared::cluster.mbarrier::complete_tx::bytes.v4.b32 [%0], {%1,%2,%3,%4}, [%5];" ::"r"(a), "r"(x), "r"(y), "r"(z), "r"(w), "r"(bar) : "memory");
}
__device__ __forceinline__ uint32_t mapa(uint32_t a, uint32_t cta) { uint32_t r; asm("mapa.shared::cluster.u32 %0, %1, %2;" : "=r"(r) : "r"(a), "r"(cta)); return r; }
__device__ __forceinline__ void stat_load(uint32_t* v, const uint4* p) { ld_pkt<0>(v, p); ld_pkt<512>(v + 4, p); }
__device__ __forceinline__ void stat_check(uint32_t* v, const uint4* p, uint32_t tag) {
    asm volatile("{ .reg .pred p; .reg .b32 n, t; .reg .b128 q; mov.u32 n, 0;\n LP:\n"
                 "xor.b32 t, %3, %9;\n" CHK("%7", "%9") VOTE_OK
                 LDP("%0", "%1", "%2", "%3", "%8", "0") LDP("%4", "%5", "%6", "%7", "%8", "8192") SPIN_TAIL("4")
                 : RW4(v, 0), RW4(v, 4) : "l"(p), "r"(tag) : "memory");
}
__device__ __forceinline__ uint32_t x_bits(const uint32_t* X) {
    uint32_t r;
    asm volatile("{ .reg .b32 a, b; prmt.b32 a, %1, %2, 0x0040; prmt.b32 b, %3, %4, 0x0040; prmt.b32 %0, a, b, 0x5410; }" : "=r"(r) : "r"(X[0]), "r"(X[4]), "r"(X[8]), "r"(X[12]));
    return r;
}
template <int O>
__device__ __forceinline__ void slice_load(uint32_t* v, const uint4* p, int lane) {
    ld_pkt<O>(v, p); ld_pkt<O + 32>(v + 4, p); ld_pkt<O + 64>(v + 8, p);
    asm volatile("{ .reg .b64 h;\n" LDH("%0", "%1", "%2", "%3") "}" : "=r"(v[12]), "=r"(v[13]) : "l"((const char*)p - lane * 8), "n"(16 * (O + 96)) : "memory");
}
template <int O>
__device__ __forceinline__ void slice_check(uint32_t* v, const uint4* p, int lane, uint32_t tag) {
    asm volatile("{ .reg .pred p; .reg .b32 n, t; .reg .b128 q; .reg .b64 h; mov.u32 n, 0;\n LP:\n"
                 "xor.b32 t, %0, %16;\n" CHK("%4", "%16") CHK("%8", "%16") CHK("%12", "%16") VOTE_OK
                 LDP("%0", "%1", "%2", "%3", "%14", "%17") LDP("%4", "%5", "%6", "%7", "%14", "%18") LDP("%8", "%9", "%10", "%11", "%14", "%19")
                 LDH("%12", "%13", "%15", "%20") SPIN_TAIL("5")
                 : RW4(v, 0), RW4(v, 4), RW4(v, 8), RW2(v, 12)
                 : "l"(p), "l"((const char*)p - lane * 8), "r"(tag), "n"(16 * O), "n"(16 * (O + 32)), "n"(16 * (O + 64)), "n"(16 * (O + 96))
                 : "memory");
}
__device__ __forceinline__ void x_fix(uint32_t* X, uint32_t bits) {
    X[0] = __byte_perm(X[0], bits, 0x3214); X[4] = __byte_perm(X[4], bits, 0x3215); X[8] = __byte_perm(X[8], bits, 0x3216); X[12] = __byte_perm(X[12], bits, 0x3217);
}
__device__ __forceinline__ void sts4(uint32_t a, uint32_t x, uint32_t y, uint32_t z, uint32_t w) {
    asm volatile("st.shared.v4.u32 [%0], {%1,%2,%3,%4};" ::"r"(a), "r"(x), "r"(y), "r"(z), "r"(w) : "memory");
}
__device__ __forceinline__ void lds4(uint32_t* v, uint32_t a) {
    asm volatile("ld.shared.v4.u32 {%0,%1,%2,%3}, [%4];" : "=r"(v[0]), "=r"(v[1]), "=r"(v[2]), "=r"(v[3]) : "r"(a) : "memory");
}
struct LnCoef { uint32_t hi, lo, sh; };
__device__ __forceinline__ LnCoef ln_coef(float sum, float sq) {
    sum += __shfl_xor_sync(0xffffffffu, sum, 1); sq += __shfl_xor_sync(0xffffffffu, sq, 1);
    sum += __shfl_xor_sync(0xffffffffu, sum, 2); sq += __shfl_xor_sync(0xffffffffu, sq, 2);
    const float mean = sum * (1.f / 448.f);
    const float var = fmaxf(fmaf(-mean, mean, sq * (1.f / 448.f)), 0.f);
    const float sc = rsqrtf(var + 1e-5f);
    LnCoef r;
    r.hi = pack2(sc, sc);
    const float lo = sc - bf_lo(r.hi), sh = -mean * sc;
    r.lo = pack2(lo, lo);
    r.sh = pack2(sh, sh);
    return r;
}
template <int B>
__device__ __forceinline__ void normalize(uint32_t (&A)[8][14], const LnCoef& c0, const LnCoef& c1) {
#pragma unroll
    for (int s = 2 * B; s < 2 * B + 2; s++)
#pragma unroll
        for (int i = 0; i < 14; i++) {
            const LnCoef& k = (i & 1) ? c1 : c0;
            asm("{ .reg .b32 t; fma.rn.bf16x2 t, %0, %2, %3; fma.rn.bf16x2 %0, %0, %1, t; }" : "+r"(A[s][i]) : "r"(k.hi), "r"(k.lo), "r"(k.sh));
        }
}
__device__ __forceinline__ void slice_stats(const uint32_t* w, float* st) {
    float a = 0.f, b = 0.f, p = 0.f, q = 0.f;
#pragma unroll
    for (int i = 0; i < 7; i++) {
        const float e0 = bf_lo(w[2 * i]), e1 = bf_hi(w[2 * i]), e2 = bf_lo(w[2 * i + 1]), e3 = bf_hi(w[2 * i + 1]);
        a += e0 + e1; b += e2 + e3;
        p = fmaf(e0, e0, p); p = fmaf(e1, e1, p); q = fmaf(e2, e2, q); q = fmaf(e3, e3, q);
    }
    a += __shfl_xor_sync(0xffffffffu, a, 1); p += __shfl_xor_sync(0xffffffffu, p, 1); b += __shfl_xor_sync(0xffffffffu, b, 1); q += __shfl_xor_sync(0xffffffffu, q, 1);
    a += __shfl_xor_sync(0xffffffffu, a, 2); p += __shfl_xor_sync(0xffffffffu, p, 2); b += __shfl_xor_sync(0xffffffffu, b, 2); q += __shfl_xor_sync(0xffffffffu, q, 2);
    st[0] = a; st[1] = p; st[2] = b; st[3] = q;
}
__device__ __forceinline__ void dual_softmax(const float* p, uint32_t* out) {
    constexpr float L = 1.4426950408889634f;
#pragma unroll
    for (int r = 0; r < 2; r++) {
        float mx = fmaxf(p[2 * r], p[2 * r + 1]), mn = fminf(p[2 * r], p[2 * r + 1]);
#pragma unroll
        for (int i = 1; i < 7; i++) {
            mx = fmaxf(mx, fmaxf(p[4 * i + 2 * r], p[4 * i + 2 * r + 1]));
            mn = fminf(mn, fminf(p[4 * i + 2 * r], p[4 * i + 2 * r + 1]));
        }
        mx = fmaxf(mx, __shfl_xor_sync(0xffffffffu, mx, 1));
        mn = fminf(mn, __shfl_xor_sync(0xffffffffu, mn, 1));
        const float bx = -mx * L, bn = mn * L;
        float ep[14], en[14], sp = 0.f, sn = 0.f;
#pragma unroll
        for (int i = 0; i < 14; i++) {
            const float v = p[4 * (i >> 1) + 2 * r + (i & 1)];
            ep[i] = ex2(fmaf(v, L, bx));
            en[i] = ex2(fmaf(v, -L, bn));
            sp += ep[i]; sn += en[i];
        }
        sp += __shfl_xor_sync(0xffffffffu, sp, 1);
        sn += __shfl_xor_sync(0xffffffffu, sn, 1);
        const float ip = rcp(sp), in = rcp(sn);
#pragma unroll
        for (int i = 0; i < 7; i++) {
            out[4 * i + r] = pack2(ep[2 * i] * ip, ep[2 * i + 1] * ip);
            out[4 * i + 2 + r] = pack2(en[2 * i] * in, en[2 * i + 1] * in);
        }
    }
}
__device__ __forceinline__ float geglu(float g, float u) {
    const float t = tanh_hw(g * fmaf(g * g, 0.7978845608028654f * 0.044715f, 0.7978845608028654f));
    const float gu = g * u;
    return fmaf(t, gu, gu);
}
__device__ __forceinline__ void phi_gemm(const float* t, float* p) {
    uint32_t w[14];
#pragma unroll
    for (int i = 0; i < 14; i++) w[i] = pack2(t[2 * i], t[2 * i + 1]);
    const uint64_t db = BASE128(OFF_WPHI, 16, 0);
    wg_fence();
    mma_rs56<0, 0>(p, w[0], w[1], w[2], w[3], 0, db);
    mma_rs56<0, 2>(p, w[4], w[5], w[6], w[7], 1, db);
    mma_rs56<0, 4>(p, w[8], w[9], w[10], w[11], 1, db);
    mma_rs56<0, 6>(p, w[12], w[13], 0u, 0u, 1, db);
    wg_commit();
    wg_wait<0>();
}

}

#define BAR(i) (bars + 8 * (i))
#define R_WAIT() mbar_wait(BAR(slot), ph)
#define WSUM(i)
#define R_ADJ (slot * (STAGE >> 4))
#define R_NEXT() do { eb2 = eb1; eb1 = BAR(B_EMPTY + slot); if (++slot == NST) { slot = 0; ph ^= 1; } } while (0)
#define R_RELEASE(k) do { if (lane == 0) mbar_arrive((k) == 1 ? eb1 : eb2); } while (0)
#define PUSH_BEGIN() do { mbar_wait(BAR(B_ACK + wgi), ackph); ackph ^= 1; } while (0)
#define PUSH_ACK() do { __syncwarp(); if (lane == 0) asm volatile("mbarrier.arrive.shared::cluster.b64 _, [%0];" ::"r"(mapa(BAR(B_ACK + wgi), hr ^ 1)) : "memory"); } while (0)

__global__ void __cluster_dims__(2, 1, 1) __launch_bounds__(384, 1)
fused_kernel(Scratch* const sc, const __nv_bfloat16* __restrict__ x_in, const __nv_bfloat16* __restrict__ w_phi, const int trips,
             const __nv_bfloat16* __restrict__ wg, const __nv_bfloat16* __restrict__ wu, const __nv_bfloat16* __restrict__ wd,
             const __grid_constant__ Maps maps) {
    extern __shared__ __align__(1024) unsigned char smem_raw[];
    const uint32_t sb = s2u(smem_raw);
    const uint32_t bars = sb + OFF_BAR;
    const int wgi = __shfl_sync(0xffffffffu, threadIdx.x >> 7, 0);
    const int hr = blockIdx.x & 1, ck = blockIdx.x >> 1;
    const int gp = (ck - 4) & 7, q7 = ((ck - 36) * 37) >> 8;
    const int pr = __shfl_sync(0xffffffffu, ck < 4 ? ck : (ck < 36 ? (ck - 4) >> 3 : q7), 0);
    const int tile = __shfl_sync(0xffffffffu, ck < 4 ? 0 : (ck < 36 ? (gp ? 2 * gp : 1) : 2 * (ck - 36 - 7 * q7) + 3), 0);
    const int sl = 2 * pr + hr;
    STAMP(0);
    GSTAMP(60);
    const bool first_loader = __shfl_sync(0xffffffffu, threadIdx.x >> 5, 0) == 8;
    if (first_loader) {
        if (threadIdx.x == 256) {
#pragma unroll
            for (int i = 0; i < NST; i++) mbar_init(BAR(i), 1);
            asm volatile("fence.mbarrier_init.release.cluster;" ::: "memory");
        }
        __syncwarp();
        asm volatile("barrier.cluster.arrive.relaxed.aligned;" ::: "memory");
#pragma unroll
        for (int n = 0; n < 3; n++) asm volatile(ELECT "mbarrier.arrive.expect_tx.shared::cta.b64 _, [%0], %1; }" ::"r"(BAR(n)), "r"(n < 2 ? 2 * STAGE : STAGE) : "memory");
#pragma unroll
        for (int n = 0; n < 2; n++) {
            tma3x(sb + OFF_H + n * STAGE, &maps.x, tile * 128 + n * 64, BAR(n));
            tma3x(sb + n * STAGE, &maps.x, tile * 128 + n * 64 + 32, BAR(n));
        }
        tma2d(sb + 2 * STAGE, &maps.qkv, 448 + 56 * sl, 0, BAR(2));
        tma2d(sb + 2 * STAGE + HALF, &maps.qkv, 896 + 56 * sl, 0, BAR(2));
    }
    if (threadIdx.x == 288) {
        if ((sb & 0x3FFFF) != SB0) asm volatile("trap;");
#pragma unroll
        for (int i = NST; i < B_COUNT; i++) mbar_init(BAR(i), i >= B_ACK ? 4 : (i < B_RECV || i == B_LATE ? 8 : 1));
        asm volatile("fence.mbarrier_init.release.cluster;" ::: "memory");
    }
    __syncwarp();
    if (!first_loader) asm volatile("barrier.cluster.arrive.relaxed.aligned;" ::: "memory");

    if (wgi == 2) {
        asm volatile("setmaxnreg.dec.sync.aligned.u32 40;");
        const int t128 = fresh_tid() & 127, w = __shfl_sync(0xffffffffu, t128 >> 5, 0), lane = t128 & 31;
        uint32_t e0[2] = {0, 0}, e1[2] = {0, 0}, cw_target = 0;
        if (w == 0) {
            mbar_wait(BAR(1), 0);
#pragma unroll 1
            for (int n = 3; n < NST; n++) {
                asm volatile(ELECT "mbarrier.arrive.expect_tx.shared::cta.b64 _, [%0], %1; }" ::"r"(BAR(n)), "r"(STAGE) : "memory");
                tma2d(sb + n * STAGE, &maps.qkv, 448 + 56 * sl, 112 * (n - 2), BAR(n));
                tma2d(sb + n * STAGE + HALF, &maps.qkv, 896 + 56 * sl, 112 * (n - 2), BAR(n));
            }
            asm volatile("barrier.cluster.wait.aligned;" ::: "memory");
            cw_target = (ld_word(g_cw + sl * 32) & ~15u) + 16;
#pragma unroll 1
            for (int k = 0; k < 2; k++) {
                const int n = t128 + 32 * k;
                int m = n - 2 - (n > PACK);
                const bool packed = m >= 30 ? (m < 38 || m >= 52) : m >= 22;
                if (m >= 30) m -= 30;
                if (n == PACK) m = tile < 8 ? tile : tile + 14;
                const int rot = n < 8 ? 0 : pr;
                const int ra = 112 * kblk(rot, m & 3), rb = 112 * kblk(rot, 2 * m & 3), rc = 112 * kblk(rot, (2 * m + 1) & 3);
                int kind = 0, m0, m1, c0, c1, r0, r1;
                if (m < 4) { m0 = m1 = 1; c0 = 448 + 56 * sl; c1 = c0 + 448; r0 = r1 = ra; }
                else if (m < 8) { m0 = m1 = m < 6 ? 1 : 2; c0 = c1 = 56 * sl; r0 = rb; r1 = rc; }
                else if (m < 20) { m0 = 3; m1 = 4; c0 = c1 = 224 * sl + 32 * hr + 64 * ((m - 8) >> 2); r0 = r1 = ra; }
                else if (m < 22) { kind = 2; m0 = 5; m1 = 6; c0 = c1 = 224 * sl + (hr ? 0 : 192); r0 = rb; r1 = rc; }
                else { m0 = m1 = 7; c0 = c1 = 56 * (2 * ((pr + (m >> 1) - 10) & 3) + hr); r0 = 224 * (sl ^ (m & 1)); r1 = r0 + 112; }
                if (packed) { kind = 1; r0 = sl * 16 + (m < 8 ? m : m - 14); r1 = 0; }
                e0[0] = e0[1]; e1[0] = e1[1];
                e0[1] = kind | (m0 << 2) | (m1 << 6) | (c0 << 10) | (c1 << 21);
                e1[1] = r0 | (r1 << 16);
            }
        } else {
            const int j = t128 - 32;
            asm volatile("barrier.cluster.wait.aligned;" ::: "memory");
            uint2 wv[7];
            const int k = j < 56 ? j : 55, hh = k >= 28;
#pragma unroll
            for (int i = 0; i < 7; i++) wv[i] = __ldg(reinterpret_cast<const uint2*>(w_phi + (sl * 56 + k) * 28) + i);
#pragma unroll 1
            for (int i = j; i < 7168 / 16; i += 96) sts4(sb + OFF_WPHI + i * 16, 0, 0, 0, 0);
            bar_sync(5, 96);
            if (j < 56) {
                uint32_t a4[4];
#pragma unroll
                for (int q = 0; q < 4; q++) a4[q] = sb + OFF_WPHI + (4 * hh + q) * 128 + ((((k >> 3) ^ (4 * hh + q)) & 7) << 4) + (k & 7) * 2;
                FOR14(const uint32_t v = (t & 1) ? wv[t >> 1].y : wv[t >> 1].x;
                      asm volatile("{ .reg .b16 l, h; mov.b32 {l, h}, %2; st.shared.u16 [%0+%3], l; st.shared.u16 [%1+%3], h; }"
                                   ::"r"(a4[t >= 7 ? 2 : 0]), "r"(a4[t >= 7 ? 3 : 1]), "r"(v), "n"((t % 7) * 1024) : "memory"));
            }
            __syncwarp();
            fence_async();
            bar_arrive(1, 224);
            bar_arrive(9, 224);
            if (w == 1) {
                mbar_wait(BAR(2), 0);
                mbar_wait(BAR(2), 1);
                const int b = blockIdx.x;
                asm volatile(ELECT "cp.async.bulk.prefetch.L2.global [%0], %1; }" ::"l"(wg + b * 6272), "r"(12544) : "memory");
                asm volatile(ELECT "cp.async.bulk.prefetch.L2.global [%0], %1; }" ::"l"(wu + b * 6272), "r"(12544) : "memory");
                asm volatile(ELECT "cp.async.bulk.prefetch.L2.global [%0], %1; }" ::"l"(wd + b * 6272), "r"(12544) : "memory");
            }
        }
        uint32_t kseq = ld_word(g_c1 + (sl * 8 * 16 + tile) * 32);
        int slot = 0, ph = 0, n = NST;
#pragma unroll 1
        for (int layer = 0; layer < 3; layer++) {
            if (w == 0) {
                const int nend = layer == 0 ? 11 : (layer == 1 ? 42 : 63);
#pragma unroll 1
                for (; n < nend; n++) {
                const uint32_t w0 = __shfl_sync(0xffffffffu, n < 32 ? e0[0] : e0[1], n & 31), w1 = __shfl_sync(0xffffffffu, n < 32 ? e1[0] : e1[1], n & 31);
                const uint32_t dst = sb + slot * STAGE, fb = BAR(n == PACK ? B_PACK : slot);
                const CUtensorMap* m0 = &maps.x + ((w0 >> 2) & 15);
                const CUtensorMap* m1 = &maps.x + ((w0 >> 6) & 15);
                const int c0 = (w0 >> 10) & 2047, c1 = w0 >> 21, r0 = w1 & 0xffff, r1 = w1 >> 16;
                if (n == 25) {
                    int it = 0;
                    uint32_t v;
                    do { asm volatile("ld.acquire.gpu.global.u32 %0, [%1];" : "=r"(v) : "l"(g_cw + sl * 32) : "memory"); } while ((int)(v - cw_target) < 0 && ++it < 0x400000);
                    asm volatile("fence.proxy.async.global;" ::: "memory");
                    __syncwarp();
                }
                mbar_wait(BAR(B_EMPTY + slot), ph);
                __syncwarp();
                asm volatile(ELECT "mbarrier.arrive.expect_tx.shared::cta.b64 _, [%0], %1; }" ::"r"(fb), "r"(STAGE) : "memory");
                if ((w0 & 3) == 0) {
                    tma2d(dst, m0, c0, r0, fb);
                    tma2d(dst + HALF, m1, c1, r1, fb);
                } else if (w0 & 1) {
                    asm volatile(ELECT "cp.async.bulk.shared::cluster.global.mbarrier::complete_tx::bytes [%0], [%1], %2, [%3]; }"
                                 ::"r"(dst), "l"(reinterpret_cast<const char*>(g_wp) + (size_t)r0 * STAGE), "r"(STAGE), "r"(fb) : "memory");
                } else {
                    tma2d(dst, m0, c0, r0, fb); tma2d(dst + 7168, m0, c0, r1, fb);
                    tma2d(dst + HALF, m1, c0, r0, fb); tma2d(dst + HALF + 7168, m1, c0, r1, fb);
                }
                if (n == PACK) asm volatile(ELECT "mbarrier.arrive.shared::cta.b64 _, [%0]; }" ::"r"(BAR(slot)) : "memory");
                if (++slot == NST) { slot = 0; ph ^= 1; }
                }
            } else if (w == 1 && layer == 1) {
                constexpr int ps = PACK % NST;
                mbar_wait(BAR(B_PACK), 0);
                asm volatile("{ .reg .pred e; elect.sync _|e, 0xffffffff;\n"
                             "@e cp.async.bulk.global.shared::cta.bulk_group [%0], [%1], %2;\n"
                             "@e cp.async.bulk.commit_group;\n"
                             "@e cp.async.bulk.wait_group.read 0;\n"
                             "@e mbarrier.arrive.shared::cta.b64 _, [%3], 8;\n"
                             "@e cp.async.bulk.wait_group 0;\n"
                             "@e fence.proxy.async.global;\n"
                             "@e red.release.gpu.global.add.u32 [%4], 1; }"
                             ::"l"(reinterpret_cast<char*>(g_wp) + (size_t)(sl * 16 + tile) * STAGE), "r"(sb + ps * STAGE), "r"(STAGE), "r"(BAR(B_EMPTY + ps)), "l"(g_cw + sl * 32) : "memory");
                __syncwarp();
            }
            if (layer < 2) {
            const uint32_t tag = layer ^ 1;
            kseq++;
            bar_sync(7, 384);
            ASTAMP(0);
            if (tile < 15) {
                const int sq = lane >> 3, pk = 8 * w + (lane & (tile == 14 ? 3 : 7));
                uint32_t v[16];
                if (layer == 0) poll_cnt(g_c1 + ((sl * 8 + (w >> 1) * 4 + (tile >> 2)) * 16 + (lane & 15)) * 32, kseq);
                ASTAMP(1);
                poll4_kv<32>(v, g_kv1 + ((sl * 16 + tile) * 16 + 4 * sq) * 32 + pk, tag);
#pragma unroll
                for (int k = 0; k < 4; k++) {
                    float lo = (bf_lo(v[k]) + bf_lo(v[4 + k])) + (bf_lo(v[8 + k]) + bf_lo(v[12 + k]));
                    float hi = (bf_hi(v[k]) + bf_hi(v[4 + k])) + (bf_hi(v[8 + k]) + bf_hi(v[12 + k]));
                    lo += __shfl_xor_sync(0xffffffffu, lo, 8); hi += __shfl_xor_sync(0xffffffffu, hi, 8);
                    lo += __shfl_xor_sync(0xffffffffu, lo, 16); hi += __shfl_xor_sync(0xffffffffu, hi, 16);
                    v[k] = pack2(lo, hi);
                }
                if (sq == 0) st_pkt<0>(g_kv2 + sl * 512 + 32 * tile + pk, settag(v[0], tag), v[1], v[2], v[3]);
            }
            ASTAMP(2);
            {
                const int item = t128 < 112 ? t128 : 112 + (t128 & 3), d = item >> 1;
                const int cc = t128 < 112 ? 2 * (d >= 28) + (item & 1) : item - 112;
                const int r = t128 < 112 ? d : 56 + (cc >> 1) + 2 * ((t128 - 112) >> 2);
                uint32_t ra = sb + OFF_KVB + r * 128 + 4 * cc, rx = (r & 7) << 4;
                asm volatile("" : "+r"(ra), "+r"(rx));
                FOR14(asm volatile("st.shared.u32 [%0+%2], %1;" ::"r"((ra ^ 8) + (((t & 7) << 4) ^ rx)), "r"(0), "n"((t >> 3) * 8192) : "memory"));
                uint32_t v[16];
                asm volatile("" : "+r"(ra), "+r"(rx));
                poll4_kv<8>(v, g_kv2 + sl * 512 + (item >> 3) * 32 + (item & 7), tag);
                FOR14(asm volatile("st.shared.u32 [%0+%2], %1;" ::"r"(ra + (((t & 7) << 4) ^ rx)), "r"(v[t < 7 ? t : t + 1]), "n"((t >> 3) * 8192) : "memory"));
                fence_async();
            }
            bar_arrive(3, 384);
            ASTAMP(3);
            }
        }
    } else {
        asm volatile("setmaxnreg.inc.sync.aligned.u32 232;");
        int lane = fresh_tid() & 31, prf = pr;
#define pr prf
#define g (lane >> 2)
#define c (lane & 3)
#define t128 (w * 32 + lane)
        const int wu = __shfl_sync(0xffffffffu, fresh_tid() >> 5, 0), w = wu & 3;
        const uint32_t xoff = __shfl_sync(0xffffffffu, (3 * PLANE + ((tile * 2 + wgi) * 8) * 512 + w * 128) * 16, 0);
        char* xu = reinterpret_cast<char*>(g_ex) + xoff;
#define FRESH() asm volatile("" : "+l"(xu), "+r"(lane), "+r"(prf))
#define xp0 (reinterpret_cast<uint4*>(xu) + lane)
        const uint32_t hbuf = sb + OFF_H + wgi * STAGE;
        uint32_t slot = 0, ph = 0, eb1 = 0, eb2 = 0, ackph = 0, rcvph = 0, gatph = 0, swp = 0;
        uint32_t ppid = 6;
#define cx(s) (reinterpret_cast<uint32_t*>(reinterpret_cast<uint4*>(xu) + PL(1) + 112 + (s) * 512))
#define stp (reinterpret_cast<uint4*>(xu) + g + PL(0) + 112)
        uint32_t seq = ld_word(cx(sl));
        uint32_t kseq = ld_word(g_c1 + ((sl * 8 + wu) * 16 + tile) * 32);
        uint32_t stag = ld_word(reinterpret_cast<const uint32_t*>(stp + sl * 512) + 3) & 1;
        asm volatile("barrier.cluster.wait.aligned;" ::: "memory");
        STAMP(1);
        uint32_t X[14];
        const uint32_t x0row = (w < 2 ? hbuf : sb + wgi * STAGE) + ((w & 1) * 16 + (lane & 15)) * 128;
        mbar_wait(BAR(wgi), 0);
        STAMP(51);
#pragma unroll
        for (int j = 0; j < 4; j++) {
            const int G = 7 * sl + min(2 * j + (lane >> 4), 6);
            uint32_t q2, q3;
            asm volatile("ldmatrix.sync.aligned.m8n8.x4.shared.b16 {%0,%1,%2,%3}, [%4];" : "=r"(X[4 * j]), "=r"(X[4 * j + 1]), "=r"(q2), "=r"(q3)
                         : "r"(x0row + (G >> 3) * 4096 + (((G ^ lane) & 7) << 4)) : "memory");
            if (j < 3) { X[(4 * j + 2) % 14] = q2; X[(4 * j + 3) % 14] = q3; }
        }
#define PUSH_SLICE(W)                                                                          \
    {                                                                                          \
        if (t128 == 0) mbar_expect_tx(BAR(B_RECV + wgi), 7168);                                \
        PUSH_BEGIN();                                                                          \
        const uint32_t ra = mapa(hbuf + 24576 + t128 * 16, hr ^ 1), rb = mapa(sb + OFF_XR + wgi * 3072, hr ^ 1), rbar = mapa(BAR(B_RECV + wgi), hr ^ 1); \
        st_async4(ra, W[0], W[1], W[2], W[3], rbar);                                           \
        st_async4(ra + 2048, W[4], W[5], W[6], W[7], rbar);                                    \
        st_async4(rb + t128 * 16, W[8], W[9], W[10], W[11], rbar);                             \
        asm volatile("st.async.weak.shared::cluster.mbarrier::complete_tx::bytes.v2.b32 [%0], {%1,%2}, [%3];" ::"r"(rb + 2048 + t128 * 8), "r"(W[12]), "r"(W[13]), "r"(rbar) : "memory"); \
    }
#define PULL_SLICE(W)                                                                          \
    {                                                                                          \
        uint32_t t0, t1;                                                                       \
        mbar_wait(BAR(B_RECV + wgi), rcvph);                                                   \
        rcvph ^= 1;                                                                            \
        lds4(&A[1][0], hbuf + 24576 + t128 * 16);                                              \
        lds4(&A[1][4], hbuf + 26624 + t128 * 16);                                              \
        lds4(&A[1][8], sb + OFF_XR + wgi * 3072 + t128 * 16);                                  \
        asm volatile("ld.shared.v2.u32 {%0,%1}, [%2];" : "=r"(t0), "=r"(t1) : "r"(sb + OFF_XR + wgi * 3072 + 2048 + t128 * 8) : "memory"); \
        _Pragma("unroll") for (int i = 0; i < 12; i++) A[0][i] = (i & 3) ? W[i] : W[i] & ~1u;  \
        A[1][0] &= ~1u; A[1][4] &= ~1u; A[1][8] &= ~1u;                                        \
        A[0][12] = (hr ? t0 : W[12]) & ~1u; A[0][13] = hr ? t1 : W[13];                        \
        A[1][12] = (hr ? W[12] : t0) & ~1u; A[1][13] = hr ? W[13] : t1;                        \
        asm volatile("" : RW4(A[0], 0), RW4(A[0], 4), RW4(A[0], 8), RW2(A[0], 12), RW4(A[1], 0), RW4(A[1], 4), RW4(A[1], 8), RW2(A[1], 12)); \
        swp = hr * 448;                                                                        \
    }
#define SWB(b, t, db, sh) ((b) == 0 && (t) < 6 ? ((t) < 3 ? db##p : db##m) : db)
#define DECL_DB(b, MK, lbo, sh) const uint64_t db = MK(0, lbo, R_ADJ), dbp = (b) == 0 ? MK(0, lbo, R_ADJ + (swp >> (sh))) : db, dbm = (b) == 0 ? MK(0, lbo, R_ADJ - (swp >> (sh))) : db;
#define PPB 2
#define PP_WAIT() if (wgi == 1) { bar_sync(ppid, 256); ppid ^= 14; }
#define PP_GO() if (wgi == 0) { bar_arrive(ppid, 256); ppid ^= 14; }
#define GAT_DST(B, s2) ((B) == 1 ? hbuf + w * 3584 + (s2) * 1792 : ((s2) ? sb + OFF_KVB + wgi * 8192 : hbuf + 14336) + w * 1792)
#define GAT_ISSUE(B, base)                                                                     \
    {                                                                                          \
        const char* gs = xu + ((base) + kblk(pr, B) * 1024) * 16;                              \
        asm volatile("{ .reg .pred e; elect.sync _|e, 0xffffffff;\n"                           \
                     "@e mbarrier.arrive.expect_tx.shared::cta.b64 _, [%3], 3584;\n"           \
                     "@e cp.async.bulk.shared::cluster.global.mbarrier::complete_tx::bytes [%0], [%2], 1792, [%3];\n" \
                     "@e cp.async.bulk.shared::cluster.global.mbarrier::complete_tx::bytes [%1], [%2+8192], 1792, [%3]; }" \
                     ::"r"(GAT_DST(B, 0)), "r"(GAT_DST(B, 1)), "l"(gs), "r"(BAR(B_GAT + wu * 2 + ((B) >> 1))) : "memory"); \
        __syncwarp();                                                                          \
    }
#define GAT_FETCH(B)                                                                           \
    {                                                                                          \
        mbar_wait(BAR(B_GAT + wu * 2 + ((B) >> 1)), (gatph >> (B)) & 1);                          \
        gatph ^= 1 << (B);                                                                     \
        _Pragma("unroll") for (int s2 = 0; s2 < 2; s2++) {                                     \
            const uint32_t ga = GAT_DST(B, s2) + lane * 16;                                    \
            lds4(&A[2 * (B) + s2][0], ga); lds4(&A[2 * (B) + s2][4], ga + 512); lds4(&A[2 * (B) + s2][8], ga + 1024); \
            asm volatile("ld.shared.v2.u32 {%0,%1}, [%2];" : "=r"(A[2 * (B) + s2][12]), "=r"(A[2 * (B) + s2][13]) : "r"(ga - lane * 8 + 1536) : "memory"); \
        }                                                                                      \
    }
#define LATE_ARRIVE() do { if (lane == 0) mbar_arrive(BAR(B_LATE)); } while (0)
#define LATE_WAIT() do { mbar_wait(BAR(B_LATE), gatph & 1); gatph ^= 1; } while (0)
#define PT 3
#define PREP(b, t, remote)                                                                     \
    if constexpr ((b) < 3 && (t) == PT) {                                                      \
        wg_commit();                                                                           \
        STAMP(74 + 6 * (step & 1) + 2 * (b));                                                  \
        if (remote) {                                                                          \
            if constexpr ((b) == 0) { blk_load<2>(A, BLK(xsrc, 2), lane); GAT_FETCH(1) }       \
            blk_check<((b) + 1) & 3>(A, BLK(xsrc, (b) + 1), lane, xtag);                       \
            if constexpr ((b) == 0) blk_load<3>(A, BLK(xsrc, 3), lane);                        \
        }                                                                                      \
        STAMP(75 + 6 * (step & 1) + 2 * (b));                                                  \
        normalize<((b) + 1) & 3>(A, k0, k1);                                                   \
        asm volatile("" : RW4(A[(2 * (b) + 2) & 7], 0), RW4(A[(2 * (b) + 2) & 7], 4), RW4(A[(2 * (b) + 2) & 7], 8), RW2(A[(2 * (b) + 2) & 7], 12), \
                          RW4(A[(2 * (b) + 3) & 7], 0), RW4(A[(2 * (b) + 3) & 7], 4), RW4(A[(2 * (b) + 3) & 7], 8), RW2(A[(2 * (b) + 3) & 7], 12)); \
        wg_fence();                                                                            \
    }
#define X0_BLOCK(b)                                                                            \
    { const int rr = lane & 7, hi = lane >> 4;                                                 \
    const uint32_t rowa = (w < 2 ? hbuf : sb + wgi * STAGE) + ((w & 1) * 16 + (lane & 15)) * 128; \
    FOR7(constexpr int G = 14 * (b) + (t < 3 ? 2 * t : (t < 6 ? 2 * t + 1 : 6));               \
         uint32_t q0, q1, q2, q3;                                                              \
         const uint32_t ad = t < 6 ? rowa + (((((G & 7) + hi) ^ rr) & 7) << 4) + ((G & 7) == 7 ? hi * 4096 : 0) : rowa + ((G + 7 * hi) >> 3) * 4096 + ((((G + 7 * hi) ^ rr) & 7) << 4); \
         asm volatile("ldmatrix.sync.aligned.m8n8.x4.shared.b16 {%0,%1,%2,%3}, [%4+%5];" : "=r"(q0), "=r"(q1), "=r"(q2), "=r"(q3) \
                      : "r"(ad), "n"(t < 6 ? (G >> 3) * 4096 : 0) : "memory");                 \
         if (t < 3) { A[2 * (b)][4 * t] = q0; A[2 * (b)][4 * t + 1] = q1; A[2 * (b)][4 * t + 2] = q2; A[2 * (b)][4 * t + 3] = q3; } \
         else if (t < 6) { A[2 * (b) + 1][(4 * t - 12) & 15] = q0; A[2 * (b) + 1][((4 * t - 12) & 15) + 1] = q1; A[2 * (b) + 1][((4 * t - 12) & 15) + 2] = q2; A[2 * (b) + 1][((4 * t - 12) & 15) + 3] = q3; } \
         else { A[2 * (b)][12] = q0; A[2 * (b)][13] = q1; A[2 * (b) + 1][12] = q2; A[2 * (b) + 1][13] = q3; }); }
#define BLK(base, b) ((base) + kblk(pr, b) * 1024)

#pragma unroll 1
        for (int step = 0; step < 4; step++) {
            FRESH();
            const uint32_t tag = (step >> 1) ^ 1;
            const int so = (step >> 1) * 24 + (step & 1) * 12;
            (void)so;
            uint32_t A[8][14];
            uint4* const xsrc = xp0 + ((step & 1) ? PL(2) : PL(0));
            const uint32_t xtag = (step & 1) ? tag : ((seq >> 3) & 1) ^ 1;
            uint32_t xbits;
            {
                float st[4];
                slice_stats(X, st);
                stag ^= 1;
                xbits = x_bits(X);
                tag_slice(X, xtag);
                if (step) send_slice<0>(xsrc + sl * 512, lane, X);
                if (c == 0) st_pkt<0>(stp + sl * 512, __float_as_uint(st[0]), __float_as_uint(st[1]), __float_as_uint(st[2]), settag(__float_as_uint(st[3]), stag));
            }
            STAMP(2 + so);
            uint32_t sv[8];
            if (step == 0) {
                X0_BLOCK(0) X0_BLOCK(1) X0_BLOCK(2) X0_BLOCK(3)
                mbar_wait(BAR(wgi ^ 1), 0);
                R_NEXT();
                R_NEXT();
                R_RELEASE(2);
                stat_load(sv, stp + c * 1024);
                stat_check(sv, stp + c * 1024, stag);
                STAMP(52 + step);
            } else {
                kill<14>(A[2]); kill<14>(A[3]); kill<14>(A[4]); kill<14>(A[5]); kill<14>(A[6]); kill<14>(A[7]);
                PUSH_SLICE(X)
                stat_load(sv, stp + c * 1024);
                PULL_SLICE(X)
                stat_check(sv, stp + c * 1024, stag);
                STAMP(52 + step);
                GAT_ISSUE(1, (step & 1) ? PL(2) : PL(0))
            }
            LnCoef k0, k1;
            {
                k0 = ln_coef(__uint_as_float(sv[0]) + __uint_as_float(sv[4]), __uint_as_float(sv[1]) + __uint_as_float(sv[5]));
                k1 = ln_coef(__uint_as_float(sv[2]) + __uint_as_float(sv[6]), __uint_as_float(sv[3] & ~1u) + __uint_as_float(sv[7] & ~1u));
            }
            STAMP(3 + so);
            GSTAMP(70 + step);

            if ((step & 1) == 0) {
                float tq[28];
                {
                    float av[28];
#define KV_BLOCK(b)                                                                           \
    if ((b) == 1) R_RELEASE(2);                                                               \
    if ((b) == 2) { PUSH_ACK(); wg_wait<2>(); R_RELEASE(2); }                                 \
    R_WAIT();                                                                                 \
    if ((b) == PPK) { PP_WAIT() }                                                             \
    { DECL_DB(b, BASE128, 16, 0)                                                              \
    wg_fence();                                                                               \
    FOR7(mma_rs56<1, D128(0, t)>(tq, AQ(A, b, t), (b) + t > 0, SWB(b, t, db, 0));             \
         mma_rs56<1, D128(HALF, t)>(av, AQ(A, b, t), (b) + t > 0, SWB(b, t, db, 0));          \
         PREP(b, t, step)); }                                                                 \
    wg_commit();                                                                              \
    if ((b) == 3 && PPK < 4) { PP_GO() }                                                      \
    R_NEXT();
                    normalize<0>(A, k0, k1);
                    KV_BLOCK(0) KV_BLOCK(1) KV_BLOCK(2) KV_BLOCK(3)
                    wg_wait<0>();
                    if (lane < 3) mbar_arrive(BAR(B_EMPTY + (slot + NST - 1 - lane) % NST));
                    STAMP(4 + so);
                    WSUM(80 + 7 * (step >> 1));
                    const int m = lane >> 3, rr = lane & 7;
                    const uint32_t rowa = hbuf + 16384 + (w * 16 + rr + 8 * (m & 1)) * 128;
                    const uint32_t one = c == 0 ? 0x00003f80u : 0u;
                    if (step == 0) { bar_sync(wgi ? 9 : 1, 224); }
#pragma unroll
                    for (int j = 0; j < 4; j++) {
                        const uint32_t a = rowa + (((2 * j + (m >> 1)) ^ rr) << 4);
                        if (j < 3) stsm4(a, pack2(av[8 * j], av[8 * j + 1]), pack2(av[8 * j + 2], av[8 * j + 3]), pack2(av[8 * j + 4], av[8 * j + 5]), pack2(av[8 * j + 6], av[8 * j + 7]));
                        else stsm4(a, pack2(av[24], av[25]), pack2(av[26], av[27]), one, one);
                    }
                }
                uint32_t PH[28];
                int it = 1;
#pragma unroll 1
                do {
                    float pp[28];
                    phi_gemm(tq, pp);
                    dual_softmax(pp, PH);
                    if (((trips >> (it + 1)) & 1) == 0) continue;
                    {
                        const int m = lane >> 3, rr = lane & 7;
                        const uint32_t rowa = hbuf + (w * 16 + rr + 8 * (m & 1)) * 128;
#pragma unroll
                        for (int j = 0; j < 7; j++) {
                            const int cg = 2 * j + (m >> 1), hi = cg >= 7;
                            stsm4(rowa + hi * 8192 + (((cg - 7 * hi) ^ rr) << 4), PH[4 * j], PH[4 * j + 1], PH[4 * j + 2], PH[4 * j + 3]);
                        }
                    }
                    fence_async();
                    STAMP(5 + so);
#define Q_STAGE(b0)                                                                           \
    R_WAIT();                                                                                 \
    { DECL_DB(b0, BASE128, 16, 0)                                                             \
    wg_fence();                                                                               \
    FOR7(mma_rs56<1, D128(0, t)>(tq, AQ(A, b0, t), (b0) + t > 0, SWB(b0, t, db, 0)));         \
    FOR7(mma_rs56<1, D128(HALF, t)>(tq, AQ(A, (b0) + 1, t), 1, db)); }                        \
    wg_commit();                                                                              \
    R_NEXT();
                    if (QE && wgi == 0) { kill<28>(tq); Q_STAGE(0) Q_STAGE(2) wg_wait<1>(); R_RELEASE(2); wg_wait<0>(); R_RELEASE(1); }
                    bar_sync(2, 256);
                    float kv[28];
                    const uint64_t da = BASE128(OFF_H + 16384, 16, 0), dbk = BASE128(OFF_H, 16, wgi * 512);
                    wg_fence();
                    FOR8(constexpr uint64_t o = ((t >> 2) * STAGE + (t & 3) * 2048) >> 4; mma_ss56_tt<o, o>(kv, t > 0, da, dbk));
                    wg_commit();
                    wg_wait<0>();
#pragma unroll
                    for (int hf = 0; hf < 2; hf++) {
                        const int d = 16 * w + g + 8 * hf;
                        if ((d < 56 && (d >= 28) == (c >= 2)) || d == 56) {
                            const int item = d < 56 ? 2 * d + (c & 1) : 112 + c;
                            uint4* dst = g_kv1 + ((sl * 16 + (item >> 3)) * 16 + tile) * 32 + wgi * 16 + (item & 7);
#define KVW(i) pack2(kv[4 * (i) + 2 * hf], kv[4 * (i) + 2 * hf + 1])
                            st_pkt<0>(dst, settag(KVW(0), tag), KVW(1), KVW(2), KVW(3));
                            st_pkt<8>(dst, settag(KVW(4), tag), KVW(5), KVW(6), 0u);
                        }
                    }
                    __syncwarp();
                    kseq++;
                    if (lane == 0) st_word(g_c1 + ((sl * 8 + wu) * 16 + tile) * 32, kseq);
                    bar_arrive(7, 384);
                    STAMP(6 + so);
                    if (!QE || wgi == 1) { kill<28>(tq); Q_STAGE(0) Q_STAGE(2) wg_wait<1>(); R_RELEASE(2); wg_wait<0>(); R_RELEASE(1); }
                    STAMP(7 + so);
                    kill<28>(PH);
                } while (((trips >> (++it)) & 1));
                STAMP(8 + so);
                FRESH();
                if (step) {
                    slice_load<PL(0)>(X, xp0 + sl * 512, lane);
                } else {
                    const uint32_t* xp = reinterpret_cast<const uint32_t*>(x_in + (size_t)(tile * 128 + wu * 16 + g) * 448 + 56 * sl + 2 * c);
#pragma unroll
                    for (int i = 0; i < 7; i++) { X[2 * i] = __ldg(xp + 4 * i); X[2 * i + 1] = __ldg(xp + 4 * i + 8 * 224); }
                }
                bar_sync(3, 384);
                STAMP(9 + so);
                const uint4* const osrc = xp0 + PL(1);
                {
                    float nm[32];
                    const uint64_t db = BASE128(OFF_KVB, 16, 0);
                    wg_fence();
                    FOR7(mma_rs64<0, ((t >> 2) * 8192 + (t & 3) * 32) / 16>(nm, PH[4 * t], PH[4 * t + 1], PH[4 * t + 2], PH[4 * t + 3], t > 0, db));
                    wg_commit();
                    wg_wait<0>();
                    LATE_ARRIVE();
                    const float i00 = rcp(nm[28] + 1e-6f), i01 = rcp(nm[29] + 1e-6f), i10 = rcp(nm[30] + 1e-6f), i11 = rcp(nm[31] + 1e-6f);
                    const float m0 = c >= 2 ? i01 : i00, m1 = c >= 2 ? i11 : i10;
                    uint32_t O[14];
#pragma unroll
                    for (int i = 0; i < 7; i++) {
                        const float f0 = i < 3 ? i00 : (i > 3 ? i01 : m0), f1 = i < 3 ? i10 : (i > 3 ? i11 : m1);
                        O[2 * i] = pack2(nm[4 * i] * f0, nm[4 * i + 1] * f0);
                        O[2 * i + 1] = pack2(nm[4 * i + 2] * f1, nm[4 * i + 3] * f1);
                    }
                    if (OST) { PP_WAIT() }
                    tag_slice(O, tag);
                    send_slice<PL(1)>(xp0 + sl * 512, lane, O);
                    seq++;
                    if (lane == 0) st_word(cx(sl), seq);
                    STAMP(10 + so);
                    PUSH_SLICE(O)
                    if (OST == 1) { PP_GO() }
                    const uint32_t cv = ld_word(cx(lane & 7));
                    PULL_SLICE(O)
                    LATE_WAIT();
                    check_cnt(cv, cx(lane & 7), seq);
                    if (OST == 2) { PP_GO() }
                    STAMP(56 + (step >> 1));
                    GAT_ISSUE(1, PL(1))
                    GAT_ISSUE(3, PL(1))
                    blk_load<2>(A, BLK(osrc, 2), lane);
                }
                float ao[28];
#define WO_BLOCK(b)                                                                           \
    if ((b) > 0) blk_check<b>(A, BLK(osrc, b), lane, tag);                                    \
    if (((b) & 1) == 0) R_WAIT();                                                             \
    { DECL_DB(b, BASE128, 16, 0)                                                              \
    wg_fence();                                                                               \
    FOR7(mma_rs56<1, D128(((b) & 1) * HALF, t)>(ao, AQ(A, b, t), (b) + t > 0, SWB(b, t, db, 0))); } \
    wg_commit();                                                                              \
    if ((b) & 1) R_NEXT();
                WO_BLOCK(0)
                STAMP(11 + so);
                GAT_FETCH(1)
                WO_BLOCK(1)
                WO_BLOCK(2)
                GAT_FETCH(3)
                WO_BLOCK(3)
                PUSH_ACK();
                wg_wait<0>();
                R_RELEASE(2);
                STAMP(12 + so);
                WSUM(86 + 7 * (step >> 1));
                x_fix(X, xbits);
#pragma unroll
                for (int i = 0; i < 14; i++) X[i] = pack2(bf_lo(X[i]) + ao[2 * i], bf_hi(X[i]) + ao[2 * i + 1]);
            } else {
                uint32_t H[56];
                float ag[64];
#define F1_EPI(dst, ng, ag)                                                                    \
    _Pragma("unroll") for (int i = 0; i < 2 * (ng); i++)                                       \
        (dst)[i] = pack2(geglu(ag[2 * i], ag[4 * (ng) + 2 * i]), geglu(ag[2 * i + 1], ag[4 * (ng) + 2 * i + 1]));
#define H_PUSH(h0, off) st_async4(rem_h + (off), H[h0], H[(h0) + 1], H[(h0) + 2], H[(h0) + 3], mapa(BAR(B_RECV2 + wgi), hr ^ 1));
#define F1_BLOCK(b, first)                                                                     \
    if ((first) && (b) == 1) R_RELEASE(2);                                                     \
    if ((first) && (b) == 2) PUSH_ACK();                                                       \
    R_WAIT();                                                                                  \
    if ((b) == ((first) ? PPF : PPB)) { PP_WAIT() }                                            \
    { DECL_DB(b, BASE128, HALF, 0)                                                             \
    wg_fence();                                                                                \
    FOR7(mma_rs128<1, D128(0, t)>(ag, AQ(A, b, t), (b) + t > 0, SWB(b, t, db, 0));             \
         if constexpr (first) { PREP(b, t, true) }); }                                         \
    wg_commit();                                                                               \
    if ((b) == 3) { PP_GO() }                                                                  \
    if ((b) > 0) { wg_wait<1>(); R_RELEASE(1); }       \
    R_NEXT();
                normalize<0>(A, k0, k1);
                F1_BLOCK(0, true) F1_BLOCK(1, true) F1_BLOCK(2, true) F1_BLOCK(3, true)
                if (t128 == 0) { mbar_expect_tx(BAR(B_RECV + wgi), 16384); mbar_expect_tx(BAR(B_RECV2 + wgi), 12288); }
                PUSH_BEGIN();
                wg_wait<0>();
                R_RELEASE(1);
                int p = 0;
#pragma unroll 1
                do {
                    F1_EPI(H + 32, 8, ag)
                    STAMP(4 + p + so);
                    WSUM(81 + p + 7 * (step >> 1));
                    if (((trips >> (p + 1)) & 1) == 0) continue;
                    {
                        const uint32_t pk = (p ? hbuf + 16384 : sb + OFF_KVB + wgi * 8192) + w * 2048;
#pragma unroll
                        for (int k = 0; k < 4; k++) sts4(pk + k * 512 + lane * 16, H[32 + 4 * k], H[33 + 4 * k], H[34 + 4 * k], H[35 + 4 * k]);
                        fence_async();
                        __syncwarp();
                        asm volatile(ELECT "cp.async.bulk.shared::cluster.shared::cta.mbarrier::complete_tx::bytes [%0], [%1], 2048, [%2]; }"
                                     ::"r"(mapa(hbuf + p * 8192 + w * 2048, hr ^ 1)), "r"(pk), "r"(mapa(BAR(B_RECV + wgi), hr ^ 1)) : "memory");
                    }
                    if (step == 1 && p == PKP) R_NEXT();
                    kill<64>(ag);
                    F1_BLOCK(0, false) F1_BLOCK(1, false) F1_BLOCK(2, false) F1_BLOCK(3, false)
                    wg_wait<0>();
                    R_RELEASE(1);
                    kill<16>(H + 32);
                } while (((trips >> (++p)) & 1));
#pragma unroll
                for (int k = 0; k < 4; k++) lds4(H + 16 + 4 * k, hbuf + 16384 + w * 2048 + k * 512 + lane * 16);
                __syncwarp();
                if (lane == 0) asm volatile("mbarrier.arrive.shared::cluster.b64 _, [%0];" ::"r"(mapa(BAR(B_ACK2 + wgi), hr ^ 1)) : "memory");
                const uint32_t rem_h = mapa(hbuf + w * 2048 + lane * 16, hr ^ 1);
#define F1_LAST(b0)                                                                            \
    R_WAIT();                                                                                  \
    if (b0) { PP_WAIT() }                                                                      \
    { DECL_DB(b0, BASE64, HALF, 1)                                                             \
    wg_fence();                                                                                \
    FOR7(mma_rs64<1, D64(0, t)>(al, AQ(A, b0, t), (b0) + t > 0, SWB(b0, t, db, 1)));           \
    FOR7(mma_rs64<1, D64(7168, t)>(al, AQ(A, (b0) + 1, t), 1, db)); }                          \
    wg_commit();                                                                               \
    if (b0) { PP_GO() }                                                                        \
    R_NEXT();
                float al[32];
                F1_LAST(0)
                mbar_wait(BAR(B_RECV + wgi), rcvph);
                rcvph ^= 1;
                mbar_wait(BAR(B_ACK2 + wgi), step >> 1);
                H_PUSH(32, 16384) H_PUSH(36, 16896)
                F1_LAST(2)
                H_PUSH(40, 17408) H_PUSH(44, 17920)
                wg_wait<1>();
                R_RELEASE(2);
                wg_wait<0>();
                R_RELEASE(1);
                uint32_t HP[56];
#pragma unroll
                for (int k = 0; k < 4; k++) lds4(H + 4 * k, sb + OFF_KVB + wgi * 8192 + w * 2048 + k * 512 + lane * 16);
#pragma unroll
                for (int t = 0; t < 8; t++) lds4(HP + 4 * t, hbuf + (t >> 2) * 8192 + w * 2048 + (t & 3) * 512 + lane * 16);
                F1_EPI(H + 48, 4, al)
                H_PUSH(48, 24576 - w * 1024) H_PUSH(52, 25088 - w * 1024)
                STAMP(7 + so);
                WSUM(84 + 7 * (step >> 1));
                FRESH();
                float acc[28];
                const uint32_t roA = hr ? 256u : 0u, roB = hr ? (uint32_t)-1536 : 0u;
                const uint32_t rpA = hr ? 0u : 256u, rpB = hr ? 0u : (uint32_t)-1536;
                float res[28];
                uint32_t v0[14], v1[14], P[14];
                const uint4* ps = xp0 + sl * 512;
#define F2_OWN_A()                                                                             \
    R_WAIT();                                                                                  \
    d0 = BASE128(0, 16, R_ADJ + roA); d1 = BASE128(0, 16, R_ADJ + roB);                        \
    wg_fence();                                                                                \
    FOR14(if constexpr (t < OT) mma_rs56<1, t * 128>(acc, H[4 * t], H[4 * t + 1], H[4 * t + 2], H[4 * t + 3], t > 0, d0)); \
    wg_commit();
#define F2_OWN_B()                                                                             \
    wg_fence();                                                                                \
    FOR14(if constexpr (t >= OT) mma_rs56<1, t * 128>(acc, H[4 * t], H[4 * t + 1], H[4 * t + 2], H[4 * t + 3], 1, t < 12 ? d0 : d1)); \
    wg_commit();                                                                               \
    R_NEXT();
#define F2_PEER()                                                                              \
    R_WAIT();                                                                                  \
    if (F2PP) { PP_WAIT() }                                                                    \
    d0 = BASE128(0, 16, R_ADJ + rpA); d1 = BASE128(0, 16, R_ADJ + rpB);                        \
    wg_fence();                                                                                \
    FOR14(mma_rs56<1, t * 128>(acc, HP[4 * t], HP[4 * t + 1], HP[4 * t + 2], HP[4 * t + 3], 1, t < 12 ? d0 : d1)); \
    wg_commit();                                                                               \
    if (F2PP) { PP_GO() }                                                                      \
    R_NEXT();
#define F2_TURN(u)                                                                             \
    wg_wait<1>();                                                                              \
    if ((u) < 2 || TDEF < 2) R_RELEASE(2);                                                     \
    wg_wait<0>();                                                                              \
    if ((u) < 2 || TDEF < 1) R_RELEASE(1);                                                     \
    _Pragma("unroll") for (int i = 0; i < 14; i++) P[i] = pack2(acc[2 * i], acc[2 * i + 1]);   \
    tag_slice(P, tag);                                                                         \
    asm volatile("" : RW4(P, 0), RW4(P, 4), RW4(P, 8), RW2(P, 12));                            \
    kill<28>(acc);                                                                             \
    F2_OWN_A()                                                                                 \
    if ((u) == 2) { slice_load<PL(3)>(v0, ps, lane); slice_load<PL(4)>(v1, ps, lane); } \
    send_slice<PL(3 + (u))>(xp0 + (2 * ((pr + (u) + 1) & 3) + hr) * 512, lane, P);             \
    seq++;                                                                                     \
    if (lane == 0) st_word(cx(sl), seq);                                                       \
    __syncwarp();                                                                              \
    STAMP(8 + (u) + so);                                                                       \
    F2_OWN_B()
                uint64_t d0, d1;
                F2_OWN_A()
                F2_OWN_B()
                R_WAIT();
                d0 = BASE128(0, 16, R_ADJ + rpA); d1 = BASE128(0, 16, R_ADJ + rpB);
                wg_fence();
                FOR8(mma_rs56<1, t * 128>(acc, HP[4 * t], HP[4 * t + 1], HP[4 * t + 2], HP[4 * t + 3], 1, d0));
                wg_commit();
                mbar_wait(BAR(B_RECV2 + wgi), step >> 1);
#pragma unroll
                for (int k = 0; k < 4; k++) lds4(HP + 32 + 4 * k, hbuf + 16384 + w * 2048 + k * 512 + lane * 16);
                lds4(HP + 48, hbuf + 24576 + w * 1024 + lane * 16);
                lds4(HP + 52, hbuf + 25088 + w * 1024 + lane * 16);
                if (step == 1) PUSH_ACK();
                wg_fence();
                FOR14(if constexpr (t >= 8) mma_rs56<1, t * 128>(acc, HP[4 * t], HP[4 * t + 1], HP[4 * t + 2], HP[4 * t + 3], 1, t < 12 ? d0 : d1));
                wg_commit();
                R_NEXT();
                F2_TURN(0)
                F2_PEER()
                F2_TURN(1)
                F2_PEER()
                F2_TURN(2)
                if (step == 1) STAMP(64);
                slice_check<PL(3)>(v0, ps, lane, tag);
                slice_check<PL(4)>(v1, ps, lane, tag);
#pragma unroll
                for (int i = 0; i < 14; i++) { res[2 * i] = bf_lo(v0[i]) + bf_lo(v1[i]); res[2 * i + 1] = bf_hi(v0[i]) + bf_hi(v1[i]); }
                slice_load<PL(2)>(X, ps, lane);
                if (step == 1) STAMP(65);
                F2_PEER()
                if (step == 1) STAMP(66);
                poll_cnt(cx(2 * ((pr + 1) & 3) + hr), seq);
                if (step == 1) STAMP(67);
                slice_load<PL(5)>(v0, ps, lane);
                x_fix(X, xbits);
                slice_check<PL(5)>(v0, ps, lane, tag);
                if (lane < TDEF) mbar_arrive(BAR(B_EMPTY + (slot + NST - 3 - lane) % NST));
#pragma unroll
                for (int i = 0; i < 14; i++) { res[2 * i] += bf_lo(v0[i]); res[2 * i + 1] += bf_hi(v0[i]); }
                STAMP(11 + so);
                wg_wait<0>();
                R_RELEASE(2);
                STAMP(12 + so);
                WSUM(85 + 7 * (step >> 1));
#pragma unroll
                for (int i = 0; i < 14; i++) X[i] = pack2(fmaf(res[2 * i] + acc[2 * i], 0.5f, bf_lo(X[i])), fmaf(res[2 * i + 1] + acc[2 * i + 1], 0.5f, bf_hi(X[i])));
            }
        }
        {
            const int m = lane >> 3, rr = lane & 7;
            const uint32_t ob = hbuf + w * 2048, rowa = ob + (rr + 8 * (m & 1)) * 112 + (m >> 1) * 16;
#pragma unroll
            for (int j = 0; j < 3; j++) stsm4(rowa + 32 * j, X[4 * j], X[4 * j + 1], X[4 * j + 2], X[4 * j + 3]);
            asm volatile("stmatrix.sync.aligned.m8n8.x2.shared.b16 [%0], {%1,%2};" ::"r"(ob + (rr + 8 * (m & 1)) * 112 + 96), "r"(X[12]), "r"(X[13]) : "memory");
            fence_async();
            __syncwarp();
            if (lane == 0) {
                asm volatile("cp.async.bulk.tensor.2d.global.shared::cta.bulk_group [%0, {%2, %3}], [%1];" ::"l"(&maps.out), "r"(ob), "r"(56 * sl), "r"(tile * 128 + wu * 16) : "memory");
                asm volatile("cp.async.bulk.commit_group;" ::: "memory");
                asm volatile("cp.async.bulk.wait_group.read 0;" ::: "memory");
            }
        }
        STAMP(50);
        GSTAMP(61);
        PDUMP();
    }
}

#undef g
#undef pr
#undef c
#undef t128

typedef CUresult (*EncodeFn)(CUtensorMap*, CUtensorMapDataType, cuuint32_t, void*, const cuuint64_t*, const cuuint64_t*, const cuuint32_t*,
                             const cuuint32_t*, CUtensorMapInterleave, CUtensorMapSwizzle, CUtensorMapL2promotion, CUtensorMapFloatOOBfill);

static void make_map(EncodeFn enc, CUtensorMap* m, const void* p, uint64_t cols, uint64_t rows, uint32_t bc, uint32_t br, CUtensorMapSwizzle sw) {
    cuuint64_t gd[2] = {cols, rows};
    cuuint64_t gs[1] = {cols * 2};
    cuuint32_t bd[2] = {bc, br};
    cuuint32_t es[2] = {1, 1};
    enc(m, CU_TENSOR_MAP_DATA_TYPE_BFLOAT16, 2, const_cast<void*>(p), gd, gs, bd, es, CU_TENSOR_MAP_INTERLEAVE_NONE, sw,
        CU_TENSOR_MAP_L2_PROMOTION_L2_128B, CU_TENSOR_MAP_FLOAT_OOB_FILL_NONE);
}

extern "C" void kernel_launch(void* const* d_in, const int* in_sizes, int n_in, void* d_out, int out_size) {
    (void)in_sizes; (void)n_in; (void)out_size;
    static EncodeFn enc = nullptr;
    static Scratch* scratch = nullptr;
    if (!enc) {
        void* fn = nullptr;
        cudaDriverEntryPointQueryResult qr;
        cudaGetDriverEntryPoint("cuTensorMapEncodeTiled", &fn, cudaEnableDefault, &qr);
        enc = (EncodeFn)fn;
        cudaGetSymbolAddress((void**)&scratch, g_scratch);
        cudaFuncSetAttribute(fused_kernel, cudaFuncAttributeMaxDynamicSharedMemorySize, SMEM_BYTES);
    }
    Maps maps;
    {
        cuuint64_t gd[3] = {64, 2048, 7};
        cuuint64_t gs[2] = {896, 128};
        cuuint32_t bd[3] = {64, 32, 7};
        cuuint32_t es[3] = {1, 1, 1};
        enc(&maps.x, CU_TENSOR_MAP_DATA_TYPE_BFLOAT16, 3, d_in[0], gd, gs, bd, es, CU_TENSOR_MAP_INTERLEAVE_NONE, CU_TENSOR_MAP_SWIZZLE_128B,
            CU_TENSOR_MAP_L2_PROMOTION_L2_128B, CU_TENSOR_MAP_FLOAT_OOB_FILL_NONE);
    }
    make_map(enc, &maps.out, d_out, 448, 2048, 56, 16, CU_TENSOR_MAP_SWIZZLE_NONE);
    make_map(enc, &maps.qkv, d_in[1], 1344, 448, 64, 112, CU_TENSOR_MAP_SWIZZLE_128B);
    make_map(enc, &maps.wo, d_in[3], 448, 448, 64, 112, CU_TENSOR_MAP_SWIZZLE_128B);
    make_map(enc, &maps.wg, d_in[5], 1792, 448, 64, 112, CU_TENSOR_MAP_SWIZZLE_128B);
    make_map(enc, &maps.wu, d_in[6], 1792, 448, 64, 112, CU_TENSOR_MAP_SWIZZLE_128B);
    make_map(enc, &maps.wg32, d_in[5], 1792, 448, 32, 112, CU_TENSOR_MAP_SWIZZLE_64B);
    make_map(enc, &maps.wu32, d_in[6], 1792, 448, 32, 112, CU_TENSOR_MAP_SWIZZLE_64B);
    make_map(enc, &maps.wd, d_in[7], 448, 1792, 64, 112, CU_TENSOR_MAP_SWIZZLE_128B);
    fused_kernel<<<128, 384, SMEM_BYTES>>>(scratch, (const __nv_bfloat16*)d_in[0], (const __nv_bfloat16*)d_in[2], 7, (const __nv_bfloat16*)d_in[5],
                                           (const __nv_bfloat16*)d_in[6], (const __nv_bfloat16*)d_in[7], maps);
}
```

```cpp
#include <cuda_runtime.h>
#include <cuda.h>
#include <cuda_bf16.h>
#include <stdint.h>
#include <type_traits>

#define PPF 2
#define PKP 0
#define TDEF 1
#define TMPF 0
#define NORM1 0
#define ACAN 0
#define SPLIT0 1
#define OT 2
#define F2PP 0
#define PPK 2
#define QE 1
#define OST 1
#define PP

namespace {

constexpr uint32_t STAGE = 28672, HALF = 14336;
constexpr int NST = 5;
constexpr uint32_t OFF_H = NST * STAGE;
constexpr uint32_t OFF_KVB = OFF_H + 2 * STAGE;
constexpr uint32_t OFF_WPHI = OFF_KVB + 16384;
constexpr uint32_t OFF_XR = OFF_WPHI + 7168;
constexpr uint32_t OFF_BAR = OFF_XR + 6144;
constexpr uint32_t SMEM_BYTES = OFF_BAR + 384 + 1408;
constexpr int B_EMPTY = NST, B_RECV = 2 * NST, B_RECV2 = B_RECV + 2, B_PACK = B_RECV2 + 2, B_GAT = B_PACK + 1, B_LATE = B_GAT + 16, B_ACK = B_LATE + 1, B_ACK2 = B_ACK + 2, B_COUNT = B_ACK2 + 2;

constexpr int PACK = 14 + 4 * PKP;

struct Maps { CUtensorMap x, qkv, wo, wg, wu, wg32, wu32, wd, out; };

}

constexpr int PLANE = 16 * 2 * 8 * 512;
struct Scratch {
    uint4 ex[6 * PLANE];
    uint4 kv1[8 * 16 * 16 * 32];
    uint4 kv2[8 * 512];
    uint32_t c1[8 * 8 * 16 * 32];
    uint32_t cw[8 * 32];
    uint4 wp[8 * 32 * (HALF / 16)];
};
__device__ __align__(1024) Scratch g_scratch;
#define g_ex (sc->ex)
#define g_kv1 (sc->kv1)
#define g_kv2 (sc->kv2)
#define g_c1 (sc->c1)
#define g_cw (sc->cw)
#define g_wp (sc->wp)
#define STAMP(i)
#define GSTAMP(i)
#define PDUMP()
#define ASTAMP(i)

namespace {

__device__ __forceinline__ int fresh_tid() { int t; asm volatile("mov.u32 %0, %%tid.x;" : "=r"(t)); return t; }
template <int N> __device__ __forceinline__ void kill(uint32_t* v) {
#pragma unroll
    for (int i = 0; i < N; i++) v[i] = 0;
}
template <int N> __device__ __forceinline__ void kill(float* v) {
#pragma unroll
    for (int i = 0; i < N; i++) v[i] = 0.f;
}
__device__ __forceinline__ uint32_t s2u(const void* p) { return (uint32_t)__cvta_generic_to_shared(p); }
__device__ __forceinline__ void mbar_init(uint32_t a, uint32_t c) { asm volatile("mbarrier.init.shared::cta.b64 [%0], %1;" ::"r"(a), "r"(c) : "memory"); }
__device__ __forceinline__ void mbar_expect_tx(uint32_t a, uint32_t b) { asm volatile("mbarrier.arrive.expect_tx.shared::cta.b64 _, [%0], %1;" ::"r"(a), "r"(b) : "memory"); }
__device__ __forceinline__ void mbar_arrive(uint32_t a) { asm volatile("mbarrier.arrive.shared::cta.b64 _, [%0];" ::"r"(a) : "memory"); }
#define GIVE_UP(id) "trap;\n"
#define SPIN_MAX "0x400000"
#define SPIN_TAIL(id) "add.u32 n, n, 1;\n setp.lt.u32 p, n, " SPIN_MAX ";\n @p bra.uni LP;\n" GIVE_UP(id) " DN:\n }"
__device__ __forceinline__ void mbar_wait(uint32_t a, uint32_t ph) {
    asm volatile("{ .reg .pred p; .reg .b32 n; mov.u32 n, 0;\n LP:\n"
                 "mbarrier.try_wait.parity.shared::cta.b64 p, [%0], %1;\n @p bra DN;\n"
                 "add.u32 n, n, 1;\n setp.lt.u32 p, n, " SPIN_MAX ";\n @p bra LP;\n"
                 GIVE_UP("")
                 " DN:\n }" ::"r"(a), "r"(ph) : "memory");
}
#define ELECT "{ .reg .pred e; elect.sync _|e, 0xffffffff; @e "
__device__ __forceinline__ void tma2d(uint32_t dst, const CUtensorMap* m, int c0, int c1, uint32_t bar) {
    asm volatile(ELECT "cp.async.bulk.tensor.2d.shared::cluster.global.mbarrier::complete_tx::bytes [%0], [%1, {%3, %4}], [%2]; }" ::"r"(dst), "l"(m), "r"(bar), "r"(c0), "r"(c1) : "memory");
}
__device__ __forceinline__ void tma3x(uint32_t dst, const CUtensorMap* m, int row, uint32_t bar) {
    asm volatile(ELECT "cp.async.bulk.tensor.3d.shared::cluster.global.mbarrier::complete_tx::bytes [%0], [%1, {0, %3, 0}], [%2]; }" ::"r"(dst), "l"(m), "r"(bar), "r"(row) : "memory");
}
template <int OFF>
__device__ __forceinline__ void ld_pkt(uint32_t* v, const uint4* p) {
    asm volatile("{ .reg .b128 t; ld.relaxed.gpu.global.b128 t, [%4+%5]; mov.b128 {%0,%1,%2,%3}, t; }" : "=r"(v[0]), "=r"(v[1]), "=r"(v[2]), "=r"(v[3]) : "l"(p), "n"(OFF * 16) : "memory");
}
template <int OFF>
__device__ __forceinline__ void st_pkt(uint4* p, uint32_t a, uint32_t b, uint32_t c, uint32_t d) {
    asm volatile("{ .reg .b128 t; mov.b128 t, {%1,%2,%3,%4}; st.relaxed.gpu.global.b128 [%0+%5], t; }" ::"l"(p), "r"(a), "r"(b), "r"(c), "r"(d), "n"(OFF * 16) : "memory");
}
__device__ __forceinline__ uint32_t pack2(float lo, float hi) {
    uint32_t r;
    asm("cvt.rn.bf16x2.f32 %0, %1, %2;" : "=r"(r) : "f"(hi), "f"(lo));
    return r;
}
__device__ __forceinline__ float bf_lo(uint32_t w) { return __uint_as_float(w << 16); }
__device__ __forceinline__ float bf_hi(uint32_t w) { return __uint_as_float(w & 0xffff0000u); }
__device__ __forceinline__ uint32_t settag(uint32_t w, uint32_t tag) { return (w & ~1u) | tag; }
__device__ __forceinline__ float ex2(float x) { float y; asm("ex2.approx.ftz.f32 %0, %1;" : "=f"(y) : "f"(x)); return y; }
__device__ __forceinline__ float rcp(float x) { float y; asm("rcp.approx.ftz.f32 %0, %1;" : "=f"(y) : "f"(x)); return y; }
__device__ __forceinline__ float tanh_hw(float x) { float y; asm("tanh.approx.f32 %0, %1;" : "=f"(y) : "f"(x)); return y; }
__device__ __forceinline__ void stsm4(uint32_t addr, uint32_t a, uint32_t b, uint32_t c, uint32_t d) {
    asm volatile("stmatrix.sync.aligned.m8n8.x4.shared.b16 [%0], {%1,%2,%3,%4};" ::"r"(addr), "r"(a), "r"(b), "r"(c), "r"(d) : "memory");
}
__device__ __forceinline__ void fence_async() { asm volatile("fence.proxy.async.shared::cta;" ::: "memory"); }
__device__ __forceinline__ void bar_sync(int id, int n) { asm volatile("bar.sync %0, %1;" ::"r"(id), "r"(n) : "memory"); }
__device__ __forceinline__ void bar_arrive(int id, int n) { asm volatile("bar.arrive %0, %1;" ::"r"(id), "r"(n) : "memory"); }
__device__ __forceinline__ void wg_fence() { asm volatile("wgmma.fence.sync.aligned;" ::: "memory"); }
__device__ __forceinline__ void wg_commit() { asm volatile("wgmma.commit_group.sync.aligned;" ::: "memory"); }
template <int N> __device__ __forceinline__ void wg_wait() { asm volatile("wgmma.wait_group.sync.aligned %0;" ::"n"(N) : "memory"); }

constexpr uint32_t SB0 = 1024;
__host__ __device__ constexpr uint32_t dlo(uint32_t off, uint32_t lbo) { return ((SB0 + off) >> 4) | ((lbo >> 4) << 16); }
__host__ __device__ constexpr uint32_t dhi(uint32_t sbo, uint32_t sw) { return (sbo >> 4) | (sw << 30); }
__device__ __forceinline__ uint64_t dbase(uint32_t lo, uint32_t hi) { uint64_t d; asm volatile("mov.b64 %0, {%1, %2};" : "=l"(d) : "r"(lo), "r"(hi)); return d; }
#define BASE128(off, lbo, adj) dbase(dlo(off, lbo) + (adj), dhi(1024, 1))
#define BASE64(off, lbo, adj) dbase(dlo(off, lbo) + (adj), dhi(512, 2))

#define ACC4(d, o) "+f"(d[o]), "+f"(d[o + 1]), "+f"(d[o + 2]), "+f"(d[o + 3])
#define ACC28(d) ACC4(d, 0), ACC4(d, 4), ACC4(d, 8), ACC4(d, 12), ACC4(d, 16), ACC4(d, 20), ACC4(d, 24)
#define ACC32(d, o) ACC4(d, o), ACC4(d, o + 4), ACC4(d, o + 8), ACC4(d, o + 12), ACC4(d, o + 16), ACC4(d, o + 20), ACC4(d, o + 24), ACC4(d, o + 28)

template <int TB, uint64_t D>
__device__ __forceinline__ void mma_rs56(float* d, uint32_t a0, uint32_t a1, uint32_t a2, uint32_t a3, int sd, uint64_t base) {
    asm volatile("{ .reg .pred p; .reg .b64 db; setp.ne.b32 p, %32, 0; add.u64 db, %33, %34;\n"
                 "wgmma.mma_async.sync.aligned.m64n56k16.f32.bf16.bf16 "
                 "{%0,%1,%2,%3,%4,%5,%6,%7,%8,%9,%10,%11,%12,%13,%14,%15,%16,%17,%18,%19,%20,%21,%22,%23,%24,%25,%26,%27}, "
                 "{%28,%29,%30,%31}, db, p, 1, 1, %35; }\n"
                 : ACC28(d)
                 : "r"(a0), "r"(a1), "r"(a2), "r"(a3), "r"(sd), "l"(base), "n"(D), "n"(TB));
}
template <int TB, uint64_t D>
__device__ __forceinline__ void mma_rs64(float* d, uint32_t a0, uint32_t a1, uint32_t a2, uint32_t a3, int sd, uint64_t base) {
    asm volatile("{ .reg .pred p; .reg .b64 db; setp.ne.b32 p, %36, 0; add.u64 db, %37, %38;\n"
                 "wgmma.mma_async.sync.aligned.m64n64k16.f32.bf16.bf16 "
                 "{%0,%1,%2,%3,%4,%5,%6,%7,%8,%9,%10,%11,%12,%13,%14,%15,%16,%17,%18,%19,%20,%21,%22,%23,%24,%25,%26,%27,%28,%29,%30,%31}, "
                 "{%32,%33,%34,%35}, db, p, 1, 1, %39; }\n"
                 : ACC32(d, 0)
                 : "r"(a0), "r"(a1), "r"(a2), "r"(a3), "r"(sd), "l"(base), "n"(D), "n"(TB));
}
template <int TB, uint64_t D>
__device__ __forceinline__ void mma_rs128(float* d, uint32_t a0, uint32_t a1, uint32_t a2, uint32_t a3, int sd, uint64_t base) {
    asm volatile("{ .reg .pred p; .reg .b64 db; setp.ne.b32 p, %68, 0; add.u64 db, %69, %70;\n"
                 "wgmma.mma_async.sync.aligned.m64n128k16.f32.bf16.bf16 "
                 "{%0,%1,%2,%3,%4,%5,%6,%7,%8,%9,%10,%11,%12,%13,%14,%15,%16,%17,%18,%19,%20,%21,%22,%23,%24,%25,%26,%27,%28,%29,%30,%31,%32,%33,%34,%35,%36,%37,%38,%39,%40,%41,%42,%43,%44,%45,%46,%47,%48,%49,%50,%51,%52,%53,%54,%55,%56,%57,%58,%59,%60,%61,%62,%63}, "
                 "{%64,%65,%66,%67}, db, p, 1, 1, %71; }\n"
                 : ACC32(d, 0), ACC32(d, 32)
                 : "r"(a0), "r"(a1), "r"(a2), "r"(a3), "r"(sd), "l"(base), "n"(D), "n"(TB));
}
template <uint64_t DA, uint64_t DB>
__device__ __forceinline__ void mma_ss56_tt(float* d, int sd, uint64_t ba, uint64_t bb) {
    asm volatile("{ .reg .pred p; .reg .b64 da, db; setp.ne.b32 p, %28, 0; add.u64 da, %29, %31; add.u64 db, %30, %32;\n"
                 "wgmma.mma_async.sync.aligned.m64n56k16.f32.bf16.bf16 "
                 "{%0,%1,%2,%3,%4,%5,%6,%7,%8,%9,%10,%11,%12,%13,%14,%15,%16,%17,%18,%19,%20,%21,%22,%23,%24,%25,%26,%27}, "
                 "da, db, p, 1, 1, 1, 1; }\n"
                 : ACC28(d)
                 : "r"(sd), "l"(ba), "l"(bb), "n"(DA), "n"(DB));
}
template <int... I> struct Seq {};
template <class F, int... I> __device__ __forceinline__ void static_for_impl(F&& f, Seq<I...>) { (f(std::integral_constant<int, I>{}), ...); }
#define FOR7(...) static_for_impl([&](auto T_) { constexpr int t = decltype(T_)::value; __VA_ARGS__; }, Seq<0, 1, 2, 3, 4, 5, 6>{})
#define FOR8(...) static_for_impl([&](auto T_) { constexpr int t = decltype(T_)::value; __VA_ARGS__; }, Seq<0, 1, 2, 3, 4, 5, 6, 7>{})
#define FOR14(...) static_for_impl([&](auto T_) { constexpr int t = decltype(T_)::value; __VA_ARGS__; }, Seq<0, 1, 2, 3, 4, 5, 6, 7, 8, 9, 10, 11, 12, 13>{})

__device__ __forceinline__ int kblk(int p, int b) { return b == 0 ? p : b - (b <= p); }
__host__ __device__ constexpr int krow(int t) { return t < 3 ? 16 * t : (t < 6 ? 56 + 16 * (t - 3) : 48); }
#define AQ(A, b, t) ((t) < 3 ? A[2 * (b)][4 * (t)] : (t) < 6 ? A[2 * (b) + 1][4 * ((t) - 3)] : A[2 * (b)][12]), \
                    ((t) < 3 ? A[2 * (b)][4 * (t) + 1] : (t) < 6 ? A[2 * (b) + 1][4 * ((t) - 3) + 1] : A[2 * (b)][13]), \
                    ((t) < 3 ? A[2 * (b)][4 * (t) + 2] : (t) < 6 ? A[2 * (b) + 1][4 * ((t) - 3) + 2] : A[2 * (b) + 1][12]), \
                    ((t) < 3 ? A[2 * (b)][4 * (t) + 3] : (t) < 6 ? A[2 * (b) + 1][4 * ((t) - 3) + 3] : A[2 * (b) + 1][13])
#define D128(off, t) ((uint64_t)(((off) + krow(t) * 128) >> 4) + ((uint64_t)((t) == 6 ? (7168 - 1024) >> 4 : 0) << 32))
#define D64(off, t) ((uint64_t)(((off) + krow(t) * 64) >> 4) + ((uint64_t)((t) == 6 ? (3584 - 512) >> 4 : 0) << 32))

#define PL(k) (((k) - 3) * PLANE)
__device__ __forceinline__ void st_word(uint32_t* p, uint32_t v) { asm volatile("st.relaxed.gpu.global.u32 [%0], %1;" ::"l"(p), "r"(v) : "memory"); }
__device__ __forceinline__ uint32_t ld_word(const uint32_t* p) { uint32_t v; asm volatile("ld.relaxed.gpu.global.u32 %0, [%1];" : "=r"(v) : "l"(p) : "memory"); return v; }
__device__ __forceinline__ void tag_slice(uint32_t* w, uint32_t tag) { w[0] = settag(w[0], tag); w[4] = settag(w[4], tag); w[8] = settag(w[8], tag); w[12] = settag(w[12], tag); }
template <int O>
__device__ __forceinline__ void send_slice(uint4* dst, int lane, const uint32_t* w) {
    st_pkt<O>(dst, w[0], w[1], w[2], w[3]);
    st_pkt<O + 32>(dst, w[4], w[5], w[6], w[7]);
    st_pkt<O + 64>(dst, w[8], w[9], w[10], w[11]);
    asm volatile("{ .reg .b64 t; mov.b64 t, {%1,%2}; st.relaxed.gpu.global.b64 [%0+%3], t; }" ::"l"((char*)dst - lane * 8), "r"(w[12]), "r"(w[13]), "n"(16 * (O + 96)) : "memory");
}
#define RW4(v, o) "+r"(v[o]), "+r"(v[(o) + 1]), "+r"(v[(o) + 2]), "+r"(v[(o) + 3])
#define RW2(v, o) "+r"(v[o]), "+r"(v[(o) + 1])
#define WR4(v, o) "=&r"(v[o]), "=&r"(v[(o) + 1]), "=&r"(v[(o) + 2]), "=&r"(v[(o) + 3])
#define LDP(a, b, c, d, addr, off) "ld.relaxed.gpu.global.b128 q, [" addr "+" off "];\n mov.b128 {" a "," b "," c "," d "}, q;\n"
#define LDH(a, b, addr, off) "ld.relaxed.gpu.global.b64 h, [" addr "+" off "];\n mov.b64 {" a "," b "}, h;\n"
#define VOTE_OK "and.b32 t, t, 1;\n setp.ne.u32 p, t, 0;\n vote.sync.any.pred p, p, 0xffffffff;\n @!p bra.uni DN;\n"
#define CHK(x, tag) "lop3.b32 t, " x ", " tag ", t, 0xBE;\n"
__device__ __forceinline__ void check_cnt(uint32_t v, const uint32_t* p, uint32_t target) {
    asm volatile("{ .reg .pred p; .reg .b32 n, t; mov.u32 n, 0; mov.u32 t, %2;\n LP:\n"
                 "sub.s32 t, t, %1;\n setp.lt.s32 p, t, 0;\n vote.sync.any.pred p, p, 0xffffffff;\n @!p bra.uni DN;\n ld.relaxed.gpu.global.u32 t, [%0];\n" SPIN_TAIL("7")
                 ::"l"(p), "r"(target), "r"(v) : "memory");
}
__device__ __forceinline__ void poll_cnt(const uint32_t* p, uint32_t target) {
    asm volatile("{ .reg .pred p; .reg .b32 n, t; mov.u32 n, 0;\n LP:\n"
                 "ld.relaxed.gpu.global.u32 t, [%0];\n sub.s32 t, t, %1;\n setp.lt.s32 p, t, 0;\n vote.sync.any.pred p, p, 0xffffffff;\n @!p bra.uni DN;\n" SPIN_TAIL("1")
                 ::"l"(p), "r"(target) : "memory");
}
template <int STR>
__device__ __forceinline__ void poll4_kv(uint32_t* v, const uint4* p, uint32_t tag) {
    asm volatile("{ .reg .pred p; .reg .b32 n, t; .reg .b128 q; mov.u32 n, 0;\n LP:\n"
                 LDP("%0", "%1", "%2", "%3", "%16", "0") LDP("%4", "%5", "%6", "%7", "%16", "%18")
                 LDP("%8", "%9", "%10", "%11", "%16", "%19") LDP("%12", "%13", "%14", "%15", "%16", "%20")
                 "xor.b32 t, %0, %17;\n" CHK("%4", "%17") CHK("%8", "%17") CHK("%12", "%17") VOTE_OK SPIN_TAIL("2")
                 : WR4(v, 0), WR4(v, 4), WR4(v, 8), WR4(v, 12)
                 : "l"(p), "r"(tag), "n"(16 * STR), "n"(32 * STR), "n"(48 * STR)
                 : "memory");
}
template <int B>
__device__ __forceinline__ void blk_load(uint32_t (&A)[8][14], const uint4* src, int lane) {
    ld_pkt<0>(&A[2 * B][0], src); ld_pkt<32>(&A[2 * B][4], src); ld_pkt<64>(&A[2 * B][8], src);
    ld_pkt<512>(&A[2 * B + 1][0], src); ld_pkt<544>(&A[2 * B + 1][4], src); ld_pkt<576>(&A[2 * B + 1][8], src);
    asm volatile("{ .reg .b64 h;\n" LDH("%0", "%1", "%4", "1536") LDH("%2", "%3", "%4", "9728") "}"
                 : "=&r"(A[2 * B][12]), "=&r"(A[2 * B][13]), "=&r"(A[2 * B + 1][12]), "=&r"(A[2 * B + 1][13])
                 : "l"((const char*)src - lane * 8) : "memory");
}
template <int B>
__device__ __forceinline__ void blk_check(uint32_t (&A)[8][14], const uint4* src, int lane, uint32_t tag) {
    asm volatile("{ .reg .pred p; .reg .b32 n, t; .reg .b128 q; .reg .b64 h, a8; mov.u32 n, 0;\n LP:\n"
                 "xor.b32 t, %0, %30;\n" CHK("%4", "%30") CHK("%8", "%30") CHK("%12", "%30") CHK("%16", "%30") CHK("%20", "%30") CHK("%24", "%30") CHK("%26", "%30") VOTE_OK
                 LDP("%0", "%1", "%2", "%3", "%28", "0") LDP("%4", "%5", "%6", "%7", "%28", "512") LDP("%8", "%9", "%10", "%11", "%28", "1024")
                 LDP("%12", "%13", "%14", "%15", "%28", "8192") LDP("%16", "%17", "%18", "%19", "%28", "8704") LDP("%20", "%21", "%22", "%23", "%28", "9216")
                 "mad.wide.s32 a8, %29, -8, %28;\n" LDH("%24", "%25", "a8", "1536") LDH("%26", "%27", "a8", "9728") SPIN_TAIL("3")
                 "\n and.b32 %0, %0, -2; and.b32 %4, %4, -2; and.b32 %8, %8, -2; and.b32 %12, %12, -2; and.b32 %16, %16, -2; and.b32 %20, %20, -2; and.b32 %24, %24, -2; and.b32 %26, %26, -2;"
                 : RW4(A[2 * B], 0), RW4(A[2 * B], 4), RW4(A[2 * B], 8), RW4(A[2 * B + 1], 0), RW4(A[2 * B + 1], 4), RW4(A[2 * B + 1], 8),
                   RW2(A[2 * B], 12), RW2(A[2 * B + 1], 12)
                 : "l"(src), "r"(lane), "r"(tag)
                 : "memory");
}
__device__ __forceinline__ void st_async4(uint32_t a, uint32_t x, uint32_t y, uint32_t z, uint32_t w, uint32_t bar) {
    asm volatile("st.async.weak.shared::cluster.mbarrier::complete_tx::bytes.v4.b32 [%0], {%1,%2,%3,%4}, [%5];" ::"r"(a), "r"(x), "r"(y), "r"(z), "r"(w), "r"(bar) : "memory");
}
__device__ __forceinline__ uint32_t mapa(uint32_t a, uint32_t cta) { uint32_t r; asm("mapa.shared::cluster.u32 %0, %1, %2;" : "=r"(r) : "r"(a), "r"(cta)); return r; }
__device__ __forceinline__ void stat_load(uint32_t* v, const uint4* p) { ld_pkt<0>(v, p); ld_pkt<512>(v + 4, p); }
__device__ __forceinline__ void stat_check(uint32_t* v, const uint4* p, uint32_t tag) {
    asm volatile("{ .reg .pred p; .reg .b32 n, t; .reg .b128 q; mov.u32 n, 0;\n LP:\n"
                 "xor.b32 t, %3, %9;\n" CHK("%7", "%9") VOTE_OK
                 LDP("%0", "%1", "%2", "%3", "%8", "0") LDP("%4", "%5", "%6", "%7", "%8", "8192") SPIN_TAIL("4")
                 : RW4(v, 0), RW4(v, 4) : "l"(p), "r"(tag) : "memory");
}
__device__ __forceinline__ uint32_t x_bits(const uint32_t* X) {
    uint32_t r;
    asm volatile("{ .reg .b32 a, b; prmt.b32 a, %1, %2, 0x0040; prmt.b32 b, %3, %4, 0x0040; prmt.b32 %0, a, b, 0x5410; }" : "=r"(r) : "r"(X[0]), "r"(X[4]), "r"(X[8]), "r"(X[12]));
    return r;
}
template <int O>
__device__ __forceinline__ void slice_load(uint32_t* v, const uint4* p, int lane) {
    ld_pkt<O>(v, p); ld_pkt<O + 32>(v + 4, p); ld_pkt<O + 64>(v + 8, p);
    asm volatile("{ .reg .b64 h;\n" LDH("%0", "%1", "%2", "%3") "}" : "=r"(v[12]), "=r"(v[13]) : "l"((const char*)p - lane * 8), "n"(16 * (O + 96)) : "memory");
}
template <int O>
__device__ __forceinline__ void slice_check(uint32_t* v, const uint4* p, int lane, uint32_t tag) {
    asm volatile("{ .reg .pred p; .reg .b32 n, t; .reg .b128 q; .reg .b64 h; mov.u32 n, 0;\n LP:\n"
                 "xor.b32 t, %0, %16;\n" CHK("%4", "%16") CHK("%8", "%16") CHK("%12", "%16") VOTE_OK
                 LDP("%0", "%1", "%2", "%3", "%14", "%17") LDP("%4", "%5", "%6", "%7", "%14", "%18") LDP("%8", "%9", "%10", "%11", "%14", "%19")
                 LDH("%12", "%13", "%15", "%20") SPIN_TAIL("5")
                 : RW4(v, 0), RW4(v, 4), RW4(v, 8), RW2(v, 12)
                 : "l"(p), "l"((const char*)p - lane * 8), "r"(tag), "n"(16 * O), "n"(16 * (O + 32)), "n"(16 * (O + 64)), "n"(16 * (O + 96))
                 : "memory");
}
__device__ __forceinline__ void x_fix(uint32_t* X, uint32_t bits) {
    X[0] = __byte_perm(X[0], bits, 0x3214); X[4] = __byte_perm(X[4], bits, 0x3215); X[8] = __byte_perm(X[8], bits, 0x3216); X[12] = __byte_perm(X[12], bits, 0x3217);
}
__device__ __forceinline__ void sts4(uint32_t a, uint32_t x, uint32_t y, uint32_t z, uint32_t w) {
    asm volatile("st.shared.v4.u32 [%0], {%1,%2,%3,%4};" ::"r"(a), "r"(x), "r"(y), "r"(z), "r"(w) : "memory");
}
__device__ __forceinline__ void lds4(uint32_t* v, uint32_t a) {
    asm volatile("ld.shared.v4.u32 {%0,%1,%2,%3}, [%4];" : "=r"(v[0]), "=r"(v[1]), "=r"(v[2]), "=r"(v[3]) : "r"(a) : "memory");
}
struct LnCoef { uint32_t hi, lo, sh; };
__device__ __forceinline__ LnCoef ln_coef(float sum, float sq) {
    sum += __shfl_xor_sync(0xffffffffu, sum, 1); sq += __shfl_xor_sync(0xffffffffu, sq, 1);
    sum += __shfl_xor_sync(0xffffffffu, sum, 2); sq += __shfl_xor_sync(0xffffffffu, sq, 2);
    const float mean = sum * (1.f / 448.f);
    const float var = fmaxf(fmaf(-mean, mean, sq * (1.f / 448.f)), 0.f);
    const float sc = rsqrtf(var + 1e-5f);
    LnCoef r;
    r.hi = pack2(sc, sc);
    const float lo = sc - bf_lo(r.hi), sh = -mean * sc;
    r.lo = pack2(lo, lo);
    r.sh = pack2(sh, sh);
    return r;
}
template <int B>
__device__ __forceinline__ void normalize(uint32_t (&A)[8][14], const LnCoef& c0, const LnCoef& c1) {
#pragma unroll
    for (int s = 2 * B; s < 2 * B + 2; s++)
#pragma unroll
        for (int i = 0; i < 14; i++) {
            const LnCoef& k = (i & 1) ? c1 : c0;
            asm("{ .reg .b32 t; fma.rn.bf16x2 t, %0, %2, %3; fma.rn.bf16x2 %0, %0, %1, t; }" : "+r"(A[s][i]) : "r"(k.hi), "r"(k.lo), "r"(k.sh));
        }
}
__device__ __forceinline__ void slice_stats(const uint32_t* w, float* st) {
    float a = 0.f, b = 0.f, p = 0.f, q = 0.f;
#pragma unroll
    for (int i = 0; i < 7; i++) {
        const float e0 = bf_lo(w[2 * i]), e1 = bf_hi(w[2 * i]), e2 = bf_lo(w[2 * i + 1]), e3 = bf_hi(w[2 * i + 1]);
        a += e0 + e1; b += e2 + e3;
        p = fmaf(e0, e0, p); p = fmaf(e1, e1, p); q = fmaf(e2, e2, q); q = fmaf(e3, e3, q);
    }
    a += __shfl_xor_sync(0xffffffffu, a, 1); p += __shfl_xor_sync(0xffffffffu, p, 1); b += __shfl_xor_sync(0xffffffffu, b, 1); q += __shfl_xor_sync(0xffffffffu, q, 1);
    a += __shfl_xor_sync(0xffffffffu, a, 2); p += __shfl_xor_sync(0xffffffffu, p, 2); b += __shfl_xor_sync(0xffffffffu, b, 2); q += __shfl_xor_sync(0xffffffffu, q, 2);
    st[0] = a; st[1] = p; st[2] = b; st[3] = q;
}
__device__ __forceinline__ void dual_softmax(const float* p, uint32_t* out) {
    constexpr float L = 1.4426950408889634f;
#pragma unroll
    for (int r = 0; r < 2; r++) {
        float mx = fmaxf(p[2 * r], p[2 * r + 1]), mn = fminf(p[2 * r], p[2 * r + 1]);
#pragma unroll
        for (int i = 1; i < 7; i++) {
            mx = fmaxf(mx, fmaxf(p[4 * i + 2 * r], p[4 * i + 2 * r + 1]));
            mn = fminf(mn, fminf(p[4 * i + 2 * r], p[4 * i + 2 * r + 1]));
        }
        mx = fmaxf(mx, __shfl_xor_sync(0xffffffffu, mx, 1));
        mn = fminf(mn, __shfl_xor_sync(0xffffffffu, mn, 1));
        const float bx = -mx * L, bn = mn * L;
        float ep[14], en[14], sp = 0.f, sn = 0.f;
#pragma unroll
        for (int i = 0; i < 14; i++) {
            const float v = p[4 * (i >> 1) + 2 * r + (i & 1)];
            ep[i] = ex2(fmaf(v, L, bx));
            en[i] = ex2(fmaf(v, -L, bn));
            sp += ep[i]; sn += en[i];
        }
        sp += __shfl_xor_sync(0xffffffffu, sp, 1);
        sn += __shfl_xor_sync(0xffffffffu, sn, 1);
        const float ip = rcp(sp), in = rcp(sn);
#pragma unroll
        for (int i = 0; i < 7; i++) {
            out[4 * i + r] = pack2(ep[2 * i] * ip, ep[2 * i + 1] * ip);
            out[4 * i + 2 + r] = pack2(en[2 * i] * in, en[2 * i + 1] * in);
        }
    }
}
__device__ __forceinline__ float geglu(float g, float u) {
    const float t = tanh_hw(g * fmaf(g * g, 0.7978845608028654f * 0.044715f, 0.7978845608028654f));
    const float gu = g * u;
    return fmaf(t, gu, gu);
}
__device__ __forceinline__ void phi_gemm(const float* t, float* p) {
    uint32_t w[14];
#pragma unroll
    for (int i = 0; i < 14; i++) w[i] = pack2(t[2 * i], t[2 * i + 1]);
    const uint64_t db = BASE128(OFF_WPHI, 16, 0);
    wg_fence();
    mma_rs56<0, 0>(p, w[0], w[1], w[2], w[3], 0, db);
    mma_rs56<0, 2>(p, w[4], w[5], w[6], w[7], 1, db);
    mma_rs56<0, 4>(p, w[8], w[9], w[10], w[11], 1, db);
    mma_rs56<0, 6>(p, w[12], w[13], 0u, 0u, 1, db);
    wg_commit();
    wg_wait<0>();
}

}

#define BAR(i) (bars + 8 * (i))
#define R_WAIT() mbar_wait(BAR(slot), ph)
#define WSUM(i)
#define R_ADJ (slot * (STAGE >> 4))
#define R_NEXT() do { eb2 = eb1; eb1 = BAR(B_EMPTY + slot); if (++slot == NST) { slot = 0; ph ^= 1; } } while (0)
#define R_RELEASE(k) do { if (lane == 0) mbar_arrive((k) == 1 ? eb1 : eb2); } while (0)
#define PUSH_BEGIN() do { mbar_wait(BAR(B_ACK + wgi), ackph); ackph ^= 1; } while (0)
#define PUSH_ACK() do { __syncwarp(); if (lane == 0) asm volatile("mbarrier.arrive.shared::cluster.b64 _, [%0];" ::"r"(mapa(BAR(B_ACK + wgi), hr ^ 1)) : "memory"); } while (0)

__global__ void __cluster_dims__(2, 1, 1) __launch_bounds__(384, 1)
fused_kernel(Scratch* const sc, const __nv_bfloat16* __restrict__ x_in, const __nv_bfloat16* __restrict__ w_phi, const int trips,
             const __nv_bfloat16* __restrict__ wg, const __nv_bfloat16* __restrict__ wu, const __nv_bfloat16* __restrict__ wd,
             const __grid_constant__ Maps maps) {
    extern __shared__ __align__(1024) unsigned char smem_raw[];
    const uint32_t sb = s2u(smem_raw);
    const uint32_t bars = sb + OFF_BAR;
    const int wgi = __shfl_sync(0xffffffffu, threadIdx.x >> 7, 0);
    const int hr = blockIdx.x & 1, ck = blockIdx.x >> 1;
    const int gp = (ck - 4) & 7, q7 = ((ck - 36) * 37) >> 8;
    const int pr = __shfl_sync(0xffffffffu, ck < 4 ? ck : (ck < 36 ? (ck - 4) >> 3 : q7), 0);
    const int tile = __shfl_sync(0xffffffffu, ck < 4 ? 0 : (ck < 36 ? (gp ? 2 * gp : 1) : 2 * (ck - 36 - 7 * q7) + 3), 0);
    const int sl = 2 * pr + hr;
    STAMP(0);
    GSTAMP(60);
    if (threadIdx.x == 256) {
#pragma unroll
        for (int i = 0; i < NST; i++) mbar_init(BAR(i), 1);
        asm volatile("fence.mbarrier_init.release.cluster;" ::: "memory");
    }
    if (threadIdx.x == 288) {
        if ((sb & 0x3FFFF) != SB0) asm volatile("trap;");
#pragma unroll
        for (int i = NST; i < B_COUNT; i++) mbar_init(BAR(i), i >= B_ACK ? 4 : (i < B_RECV || i == B_LATE ? 8 : 1));
        asm volatile("fence.mbarrier_init.release.cluster;" ::: "memory");
    }
    __syncwarp();
    asm volatile("barrier.cluster.arrive.relaxed.aligned;" ::: "memory");
    if (__shfl_sync(0xffffffffu, threadIdx.x >> 5, 0) == 8) {
#pragma unroll
        for (int n = 0; n < 3; n++) asm volatile(ELECT "mbarrier.arrive.expect_tx.shared::cta.b64 _, [%0], %1; }" ::"r"(BAR(n)), "r"(n < 2 ? 2 * STAGE : STAGE) : "memory");
#pragma unroll
        for (int n = 0; n < 2; n++) {
            tma3x(sb + OFF_H + n * STAGE, &maps.x, tile * 128 + n * 64, BAR(n));
            tma3x(sb + n * STAGE, &maps.x, tile * 128 + n * 64 + 32, BAR(n));
        }
        tma2d(sb + 2 * STAGE, &maps.qkv, 448 + 56 * sl, 0, BAR(2));
        tma2d(sb + 2 * STAGE + HALF, &maps.qkv, 896 + 56 * sl, 0, BAR(2));
    }

    if (wgi == 2) {
        asm volatile("setmaxnreg.dec.sync.aligned.u32 40;");
        const int t128 = fresh_tid() & 127, w = __shfl_sync(0xffffffffu, t128 >> 5, 0), lane = t128 & 31;
        uint32_t e0[2] = {0, 0}, e1[2] = {0, 0}, cw_target = 0;
        if (w == 0) {
            mbar_wait(BAR(1), 0);
#pragma unroll 1
            for (int n = 3; n < NST; n++) {
                asm volatile(ELECT "mbarrier.arrive.expect_tx.shared::cta.b64 _, [%0], %1; }" ::"r"(BAR(n)), "r"(STAGE) : "memory");
                tma2d(sb + n * STAGE, &maps.qkv, 448 + 56 * sl, 112 * (n - 2), BAR(n));
                tma2d(sb + n * STAGE + HALF, &maps.qkv, 896 + 56 * sl, 112 * (n - 2), BAR(n));
            }
            asm volatile("barrier.cluster.wait.aligned;" ::: "memory");
            cw_target = (ld_word(g_cw + sl * 32) & ~15u) + 16;
#pragma unroll 1
            for (int k = 0; k < 2; k++) {
                const int n = t128 + 32 * k;
                int m = n - 2 - (n > PACK);
                const bool packed = m >= 30 ? (m < 38 || m >= 52) : m >= 22;
                if (m >= 30) m -= 30;
                if (n == PACK) m = tile < 8 ? tile : tile + 14;
                const int rot = n < 8 ? 0 : pr;
                const int ra = 112 * kblk(rot, m & 3), rb = 112 * kblk(rot, 2 * m & 3), rc = 112 * kblk(rot, (2 * m + 1) & 3);
                int kind = 0, m0, m1, c0, c1, r0, r1;
                if (m < 4) { m0 = m1 = 1; c0 = 448 + 56 * sl; c1 = c0 + 448; r0 = r1 = ra; }
                else if (m < 8) { m0 = m1 = m < 6 ? 1 : 2; c0 = c1 = 56 * sl; r0 = rb; r1 = rc; }
                else if (m < 20) { m0 = 3; m1 = 4; c0 = c1 = 224 * sl + 32 * hr + 64 * ((m - 8) >> 2); r0 = r1 = ra; }
                else if (m < 22) { kind = 2; m0 = 5; m1 = 6; c0 = c1 = 224 * sl + (hr ? 0 : 192); r0 = rb; r1 = rc; }
                else { m0 = m1 = 7; c0 = c1 = 56 * (2 * ((pr + (m >> 1) - 10) & 3) + hr); r0 = 224 * (sl ^ (m & 1)); r1 = r0 + 112; }
                if (packed) { kind = 1; r0 = sl * 16 + (m < 8 ? m : m - 14); r1 = 0; }
                e0[0] = e0[1]; e1[0] = e1[1];
                e0[1] = kind | (m0 << 2) | (m1 << 6) | (c0 << 10) | (c1 << 21);
                e1[1] = r0 | (r1 << 16);
            }
        } else {
            const int j = t128 - 32;
            asm volatile("barrier.cluster.wait.aligned;" ::: "memory");
            uint2 wv[7];
            const int k = j < 56 ? j : 55, hh = k >= 28;
#pragma unroll
            for (int i = 0; i < 7; i++) wv[i] = __ldg(reinterpret_cast<const uint2*>(w_phi + (sl * 56 + k) * 28) + i);
#pragma unroll 1
            for (int i = j; i < 7168 / 16; i += 96) sts4(sb + OFF_WPHI + i * 16, 0, 0, 0, 0);
            bar_sync(5, 96);
            if (j < 56) {
                uint32_t a4[4];
#pragma unroll
                for (int q = 0; q < 4; q++) a4[q] = sb + OFF_WPHI + (4 * hh + q) * 128 + ((((k >> 3) ^ (4 * hh + q)) & 7) << 4) + (k & 7) * 2;
                FOR14(const uint32_t v = (t & 1) ? wv[t >> 1].y : wv[t >> 1].x;
                      asm volatile("{ .reg .b16 l, h; mov.b32 {l, h}, %2; st.shared.u16 [%0+%3], l; st.shared.u16 [%1+%3], h; }"
                                   ::"r"(a4[t >= 7 ? 2 : 0]), "r"(a4[t >= 7 ? 3 : 1]), "r"(v), "n"((t % 7) * 1024) : "memory"));
            }
            __syncwarp();
            fence_async();
            bar_arrive(1, 224);
            bar_arrive(9, 224);
            if (w == 1) {
                mbar_wait(BAR(2), 0);
                mbar_wait(BAR(2), 1);
                const int b = blockIdx.x;
                asm volatile(ELECT "cp.async.bulk.prefetch.L2.global [%0], %1; }" ::"l"(wg + b * 6272), "r"(12544) : "memory");
                asm volatile(ELECT "cp.async.bulk.prefetch.L2.global [%0], %1; }" ::"l"(wu + b * 6272), "r"(12544) : "memory");
                asm volatile(ELECT "cp.async.bulk.prefetch.L2.global [%0], %1; }" ::"l"(wd + b * 6272), "r"(12544) : "memory");
            }
        }
        uint32_t kseq = ld_word(g_c1 + (sl * 8 * 16 + tile) * 32);
        int slot = 0, ph = 0, n = NST;
#pragma unroll 1
        for (int layer = 0; layer < 3; layer++) {
            if (w == 0) {
                const int nend = layer == 0 ? 11 : (layer == 1 ? 42 : 63);
#pragma unroll 1
                for (; n < nend; n++) {
                const uint32_t w0 = __shfl_sync(0xffffffffu, n < 32 ? e0[0] : e0[1], n & 31), w1 = __shfl_sync(0xffffffffu, n < 32 ? e1[0] : e1[1], n & 31);
                const uint32_t dst = sb + slot * STAGE, fb = BAR(n == PACK ? B_PACK : slot);
                const CUtensorMap* m0 = &maps.x + ((w0 >> 2) & 15);
                const CUtensorMap* m1 = &maps.x + ((w0 >> 6) & 15);
                const int c0 = (w0 >> 10) & 2047, c1 = w0 >> 21, r0 = w1 & 0xffff, r1 = w1 >> 16;
                if (n == 25) {
                    int it = 0;
                    uint32_t v;
                    do { asm volatile("ld.acquire.gpu.global.u32 %0, [%1];" : "=r"(v) : "l"(g_cw + sl * 32) : "memory"); } while ((int)(v - cw_target) < 0 && ++it < 0x400000);
                    asm volatile("fence.proxy.async.global;" ::: "memory");
                    __syncwarp();
                }
                mbar_wait(BAR(B_EMPTY + slot), ph);
                __syncwarp();
                asm volatile(ELECT "mbarrier.arrive.expect_tx.shared::cta.b64 _, [%0], %1; }" ::"r"(fb), "r"(STAGE) : "memory");
                if ((w0 & 3) == 0) {
                    tma2d(dst, m0, c0, r0, fb);
                    tma2d(dst + HALF, m1, c1, r1, fb);
                } else if (w0 & 1) {
                    asm volatile(ELECT "cp.async.bulk.shared::cluster.global.mbarrier::complete_tx::bytes [%0], [%1], %2, [%3]; }"
                                 ::"r"(dst), "l"(reinterpret_cast<const char*>(g_wp) + (size_t)r0 * STAGE), "r"(STAGE), "r"(fb) : "memory");
                } else {
                    tma2d(dst, m0, c0, r0, fb); tma2d(dst + 7168, m0, c0, r1, fb);
                    tma2d(dst + HALF, m1, c0, r0, fb); tma2d(dst + HALF + 7168, m1, c0, r1, fb);
                }
                if (n == PACK) asm volatile(ELECT "mbarrier.arrive.shared::cta.b64 _, [%0]; }" ::"r"(BAR(slot)) : "memory");
                if (++slot == NST) { slot = 0; ph ^= 1; }
                }
            } else if (w == 1 && layer == 1) {
                constexpr int ps = PACK % NST;
                mbar_wait(BAR(B_PACK), 0);
                asm volatile("{ .reg .pred e; elect.sync _|e, 0xffffffff;\n"
                             "@e cp.async.bulk.global.shared::cta.bulk_group [%0], [%1], %2;\n"
                             "@e cp.async.bulk.commit_group;\n"
                             "@e cp.async.bulk.wait_group.read 0;\n"
                             "@e mbarrier.arrive.shared::cta.b64 _, [%3], 8;\n"
                             "@e cp.async.bulk.wait_group 0;\n"
                             "@e fence.proxy.async.global;\n"
                             "@e red.release.gpu.global.add.u32 [%4], 1; }"
                             ::"l"(reinterpret_cast<char*>(g_wp) + (size_t)(sl * 16 + tile) * STAGE), "r"(sb + ps * STAGE), "r"(STAGE), "r"(BAR(B_EMPTY + ps)), "l"(g_cw + sl * 32) : "memory");
                __syncwarp();
            }
            if (layer < 2) {
            const uint32_t tag = layer ^ 1;
            kseq++;
            bar_sync(7, 384);
            ASTAMP(0);
            if (tile < 15) {
                const int sq = lane >> 3, pk = 8 * w + (lane & (tile == 14 ? 3 : 7));
                uint32_t v[16];
                if (layer == 0) poll_cnt(g_c1 + ((sl * 8 + (w >> 1) * 4 + (tile >> 2)) * 16 + (lane & 15)) * 32, kseq);
                ASTAMP(1);
                poll4_kv<32>(v, g_kv1 + ((sl * 16 + tile) * 16 + 4 * sq) * 32 + pk, tag);
#pragma unroll
                for (int k = 0; k < 4; k++) {
                    float lo = (bf_lo(v[k]) + bf_lo(v[4 + k])) + (bf_lo(v[8 + k]) + bf_lo(v[12 + k]));
                    float hi = (bf_hi(v[k]) + bf_hi(v[4 + k])) + (bf_hi(v[8 + k]) + bf_hi(v[12 + k]));
                    lo += __shfl_xor_sync(0xffffffffu, lo, 8); hi += __shfl_xor_sync(0xffffffffu, hi, 8);
                    lo += __shfl_xor_sync(0xffffffffu, lo, 16); hi += __shfl_xor_sync(0xffffffffu, hi, 16);
                    v[k] = pack2(lo, hi);
                }
                if (sq == 0) st_pkt<0>(g_kv2 + sl * 512 + 32 * tile + pk, settag(v[0], tag), v[1], v[2], v[3]);
            }
            ASTAMP(2);
            {
                const int item = t128 < 112 ? t128 : 112 + (t128 & 3), d = item >> 1;
                const int cc = t128 < 112 ? 2 * (d >= 28) + (item & 1) : item - 112;
                const int r = t128 < 112 ? d : 56 + (cc >> 1) + 2 * ((t128 - 112) >> 2);
                uint32_t ra = sb + OFF_KVB + r * 128 + 4 * cc, rx = (r & 7) << 4;
                asm volatile("" : "+r"(ra), "+r"(rx));
                FOR14(asm volatile("st.shared.u32 [%0+%2], %1;" ::"r"((ra ^ 8) + (((t & 7) << 4) ^ rx)), "r"(0), "n"((t >> 3) * 8192) : "memory"));
                uint32_t v[16];
                asm volatile("" : "+r"(ra), "+r"(rx));
                poll4_kv<8>(v, g_kv2 + sl * 512 + (item >> 3) * 32 + (item & 7), tag);
                FOR14(asm volatile("st.shared.u32 [%0+%2], %1;" ::"r"(ra + (((t & 7) << 4) ^ rx)), "r"(v[t < 7 ? t : t + 1]), "n"((t >> 3) * 8192) : "memory"));
                fence_async();
            }
            bar_arrive(3, 384);
            ASTAMP(3);
            }
        }
    } else {
        asm volatile("setmaxnreg.inc.sync.aligned.u32 232;");
        int lane = fresh_tid() & 31, prf = pr;
#define pr prf
#define g (lane >> 2)
#define c (lane & 3)
#define t128 (w * 32 + lane)
        const int wu = __shfl_sync(0xffffffffu, fresh_tid() >> 5, 0), w = wu & 3;
        const uint32_t xoff = __shfl_sync(0xffffffffu, (3 * PLANE + ((tile * 2 + wgi) * 8) * 512 + w * 128) * 16, 0);
        char* xu = reinterpret_cast<char*>(g_ex) + xoff;
#define FRESH() asm volatile("" : "+l"(xu), "+r"(lane), "+r"(prf))
#define xp0 (reinterpret_cast<uint4*>(xu) + lane)
        const uint32_t hbuf = sb + OFF_H + wgi * STAGE;
        uint32_t slot = 0, ph = 0, eb1 = 0, eb2 = 0, ackph = 0, rcvph = 0, gatph = 0, swp = 0;
        uint32_t ppid = 6;
#define cx(s) (reinterpret_cast<uint32_t*>(reinterpret_cast<uint4*>(xu) + PL(1) + 112 + (s) * 512))
#define stp (reinterpret_cast<uint4*>(xu) + g + PL(0) + 112)
        uint32_t seq = ld_word(cx(sl));
        uint32_t kseq = ld_word(g_c1 + ((sl * 8 + wu) * 16 + tile) * 32);
        uint32_t stag = ld_word(reinterpret_cast<const uint32_t*>(stp + sl * 512) + 3) & 1;
        asm volatile("barrier.cluster.wait.aligned;" ::: "memory");
        STAMP(1);
        uint32_t X[14];
        const uint32_t x0row = (w < 2 ? hbuf : sb + wgi * STAGE) + ((w & 1) * 16 + (lane & 15)) * 128;
        mbar_wait(BAR(wgi), 0);
        STAMP(51);
#pragma unroll
        for (int j = 0; j < 4; j++) {
            const int G = 7 * sl + min(2 * j + (lane >> 4), 6);
            uint32_t q2, q3;
            asm volatile("ldmatrix.sync.aligned.m8n8.x4.shared.b16 {%0,%1,%2,%3}, [%4];" : "=r"(X[4 * j]), "=r"(X[4 * j + 1]), "=r"(q2), "=r"(q3)
                         : "r"(x0row + (G >> 3) * 4096 + (((G ^ lane) & 7) << 4)) : "memory");
            if (j < 3) { X[(4 * j + 2) % 14] = q2; X[(4 * j + 3) % 14] = q3; }
        }
#define PUSH_SLICE(W)                                                                          \
    {                                                                                          \
        if (t128 == 0) mbar_expect_tx(BAR(B_RECV + wgi), 7168);                                \
        PUSH_BEGIN();                                                                          \
        const uint32_t ra = mapa(hbuf + 24576 + t128 * 16, hr ^ 1), rb = mapa(sb + OFF_XR + wgi * 3072, hr ^ 1), rbar = mapa(BAR(B_RECV + wgi), hr ^ 1); \
        st_async4(ra, W[0], W[1], W[2], W[3], rbar);                                           \
        st_async4(ra + 2048, W[4], W[5], W[6], W[7], rbar);                                    \
        st_async4(rb + t128 * 16, W[8], W[9], W[10], W[11], rbar);                             \
        asm volatile("st.async.weak.shared::cluster.mbarrier::complete_tx::bytes.v2.b32 [%0], {%1,%2}, [%3];" ::"r"(rb + 2048 + t128 * 8), "r"(W[12]), "r"(W[13]), "r"(rbar) : "memory"); \
    }
#define PULL_SLICE(W)                                                                          \
    {                                                                                          \
        uint32_t t0, t1;                                                                       \
        mbar_wait(BAR(B_RECV + wgi), rcvph);                                                   \
        rcvph ^= 1;                                                                            \
        lds4(&A[1][0], hbuf + 24576 + t128 * 16);                                              \
        lds4(&A[1][4], hbuf + 26624 + t128 * 16);                                              \
        lds4(&A[1][8], sb + OFF_XR + wgi * 3072 + t128 * 16);                                  \
        asm volatile("ld.shared.v2.u32 {%0,%1}, [%2];" : "=r"(t0), "=r"(t1) : "r"(sb + OFF_XR + wgi * 3072 + 2048 + t128 * 8) : "memory"); \
        _Pragma("unroll") for (int i = 0; i < 12; i++) A[0][i] = (i & 3) ? W[i] : W[i] & ~1u;  \
        A[1][0] &= ~1u; A[1][4] &= ~1u; A[1][8] &= ~1u;                                        \
        A[0][12] = (hr ? t0 : W[12]) & ~1u; A[0][13] = hr ? t1 : W[13];                        \
        A[1][12] = (hr ? W[12] : t0) & ~1u; A[1][13] = hr ? W[13] : t1;                        \
        asm volatile("" : RW4(A[0], 0), RW4(A[0], 4), RW4(A[0], 8), RW2(A[0], 12), RW4(A[1], 0), RW4(A[1], 4), RW4(A[1], 8), RW2(A[1], 12)); \
        swp = hr * 448;                                                                        \
    }
#define SWB(b, t, db, sh) ((b) == 0 && (t) < 6 ? ((t) < 3 ? db##p : db##m) : db)
#define DECL_DB(b, MK, lbo, sh) const uint64_t db = MK(0, lbo, R_ADJ), dbp = (b) == 0 ? MK(0, lbo, R_ADJ + (swp >> (sh))) : db, dbm = (b) == 0 ? MK(0, lbo, R_ADJ - (swp >> (sh))) : db;
#define PPB 2
#define PP_WAIT() if (wgi == 1) { bar_sync(ppid, 256); ppid ^= 14; }
#define PP_GO() if (wgi == 0) { bar_arrive(ppid, 256); ppid ^= 14; }
#define GAT_DST(B, s2) ((B) == 1 ? hbuf + w * 3584 + (s2) * 1792 : ((s2) ? sb + OFF_KVB + wgi * 8192 : hbuf + 14336) + w * 1792)
#define GAT_ISSUE(B, base)                                                                     \
    {                                                                                          \
        const char* gs = xu + ((base) + kblk(pr, B) * 1024) * 16;                              \
        asm volatile("{ .reg .pred e; elect.sync _|e, 0xffffffff;\n"                           \
                     "@e mbarrier.arrive.expect_tx.shared::cta.b64 _, [%3], 3584;\n"           \
                     "@e cp.async.bulk.shared::cluster.global.mbarrier::complete_tx::bytes [%0], [%2], 1792, [%3];\n" \
                     "@e cp.async.bulk.shared::cluster.global.mbarrier::complete_tx::bytes [%1], [%2+8192], 1792, [%3]; }" \
                     ::"r"(GAT_DST(B, 0)), "r"(GAT_DST(B, 1)), "l"(gs), "r"(BAR(B_GAT + wu * 2 + ((B) >> 1))) : "memory"); \
        __syncwarp();                                                                          \
    }
#define GAT_FETCH(B)                                                                           \
    {                                                                                          \
        mbar_wait(BAR(B_GAT + wu * 2 + ((B) >> 1)), (gatph >> (B)) & 1);                          \
        gatph ^= 1 << (B);                                                                     \
        _Pragma("unroll") for (int s2 = 0; s2 < 2; s2++) {                                     \
            const uint32_t ga = GAT_DST(B, s2) + lane * 16;                                    \
            lds4(&A[2 * (B) + s2][0], ga); lds4(&A[2 * (B) + s2][4], ga + 512); lds4(&A[2 * (B) + s2][8], ga + 1024); \
            asm volatile("ld.shared.v2.u32 {%0,%1}, [%2];" : "=r"(A[2 * (B) + s2][12]), "=r"(A[2 * (B) + s2][13]) : "r"(ga - lane * 8 + 1536) : "memory"); \
        }                                                                                      \
    }
#define LATE_ARRIVE() do { if (lane == 0) mbar_arrive(BAR(B_LATE)); } while (0)
#define LATE_WAIT() do { mbar_wait(BAR(B_LATE), gatph & 1); gatph ^= 1; } while (0)
#define PT 3
#define PREP(b, t, remote)                                                                     \
    if constexpr ((b) < 3 && (t) == PT) {                                                      \
        wg_commit();                                                                           \
        STAMP(74 + 6 * (step & 1) + 2 * (b));                                                  \
        if (remote) {                                                                          \
            if constexpr ((b) == 0) { blk_load<2>(A, BLK(xsrc, 2), lane); GAT_FETCH(1) }       \
            blk_check<((b) + 1) & 3>(A, BLK(xsrc, (b) + 1), lane, xtag);                       \
            if constexpr ((b) == 0) blk_load<3>(A, BLK(xsrc, 3), lane);                        \
        }                                                                                      \
        STAMP(75 + 6 * (step & 1) + 2 * (b));                                                  \
        normalize<((b) + 1) & 3>(A, k0, k1);                                                   \
        asm volatile("" : RW4(A[(2 * (b) + 2) & 7], 0), RW4(A[(2 * (b) + 2) & 7], 4), RW4(A[(2 * (b) + 2) & 7], 8), RW2(A[(2 * (b) + 2) & 7], 12), \
                          RW4(A[(2 * (b) + 3) & 7], 0), RW4(A[(2 * (b) + 3) & 7], 4), RW4(A[(2 * (b) + 3) & 7], 8), RW2(A[(2 * (b) + 3) & 7], 12)); \
        wg_fence();                                                                            \
    }
#define X0_BLOCK(b)                                                                            \
    { const int rr = lane & 7, hi = lane >> 4;                                                 \
    const uint32_t rowa = (w < 2 ? hbuf : sb + wgi * STAGE) + ((w & 1) * 16 + (lane & 15)) * 128; \
    FOR7(constexpr int G = 14 * (b) + (t < 3 ? 2 * t : (t < 6 ? 2 * t + 1 : 6));               \
         uint32_t q0, q1, q2, q3;                                                              \
         const uint32_t ad = t < 6 ? rowa + (((((G & 7) + hi) ^ rr) & 7) << 4) + ((G & 7) == 7 ? hi * 4096 : 0) : rowa + ((G + 7 * hi) >> 3) * 4096 + ((((G + 7 * hi) ^ rr) & 7) << 4); \
         asm volatile("ldmatrix.sync.aligned.m8n8.x4.shared.b16 {%0,%1,%2,%3}, [%4+%5];" : "=r"(q0), "=r"(q1), "=r"(q2), "=r"(q3) \
                      : "r"(ad), "n"(t < 6 ? (G >> 3) * 4096 : 0) : "memory");                 \
         if (t < 3) { A[2 * (b)][4 * t] = q0; A[2 * (b)][4 * t + 1] = q1; A[2 * (b)][4 * t + 2] = q2; A[2 * (b)][4 * t + 3] = q3; } \
         else if (t < 6) { A[2 * (b) + 1][(4 * t - 12) & 15] = q0; A[2 * (b) + 1][((4 * t - 12) & 15) + 1] = q1; A[2 * (b) + 1][((4 * t - 12) & 15) + 2] = q2; A[2 * (b) + 1][((4 * t - 12) & 15) + 3] = q3; } \
         else { A[2 * (b)][12] = q0; A[2 * (b)][13] = q1; A[2 * (b) + 1][12] = q2; A[2 * (b) + 1][13] = q3; }); }
#define BLK(base, b) ((base) + kblk(pr, b) * 1024)

#pragma unroll 1
        for (int step = 0; step < 4; step++) {
            FRESH();
            const uint32_t tag = (step >> 1) ^ 1;
            const int so = (step >> 1) * 24 + (step & 1) * 12;
            (void)so;
            uint32_t A[8][14];
            uint4* const xsrc = xp0 + ((step & 1) ? PL(2) : PL(0));
            const uint32_t xtag = (step & 1) ? tag : ((seq >> 3) & 1) ^ 1;
            uint32_t xbits;
            {
                float st[4];
                slice_stats(X, st);
                stag ^= 1;
                xbits = x_bits(X);
                tag_slice(X, xtag);
                if (step) send_slice<0>(xsrc + sl * 512, lane, X);
                if (c == 0) st_pkt<0>(stp + sl * 512, __float_as_uint(st[0]), __float_as_uint(st[1]), __float_as_uint(st[2]), settag(__float_as_uint(st[3]), stag));
            }
            STAMP(2 + so);
            uint32_t sv[8];
            if (step == 0) {
                X0_BLOCK(0) X0_BLOCK(1) X0_BLOCK(2) X0_BLOCK(3)
                mbar_wait(BAR(wgi ^ 1), 0);
                R_NEXT();
                R_NEXT();
                R_RELEASE(2);
                stat_load(sv, stp + c * 1024);
                stat_check(sv, stp + c * 1024, stag);
                STAMP(52 + step);
            } else {
                kill<14>(A[2]); kill<14>(A[3]); kill<14>(A[4]); kill<14>(A[5]); kill<14>(A[6]); kill<14>(A[7]);
                PUSH_SLICE(X)
                stat_load(sv, stp + c * 1024);
                PULL_SLICE(X)
                stat_check(sv, stp + c * 1024, stag);
                STAMP(52 + step);
                GAT_ISSUE(1, (step & 1) ? PL(2) : PL(0))
            }
            LnCoef k0, k1;
            {
                k0 = ln_coef(__uint_as_float(sv[0]) + __uint_as_float(sv[4]), __uint_as_float(sv[1]) + __uint_as_float(sv[5]));
                k1 = ln_coef(__uint_as_float(sv[2]) + __uint_as_float(sv[6]), __uint_as_float(sv[3] & ~1u) + __uint_as_float(sv[7] & ~1u));
            }
            STAMP(3 + so);
            GSTAMP(70 + step);

            if ((step & 1) == 0) {
                float tq[28];
                {
                    float av[28];
#define KV_BLOCK(b)                                                                           \
    if ((b) == 1) R_RELEASE(2);                                                               \
    if ((b) == 2) { PUSH_ACK(); wg_wait<2>(); R_RELEASE(2); }                                 \
    R_WAIT();                                                                                 \
    if ((b) == PPK) { PP_WAIT() }                                                             \
    { DECL_DB(b, BASE128, 16, 0)                                                              \
    wg_fence();                                                                               \
    FOR7(mma_rs56<1, D128(0, t)>(tq, AQ(A, b, t), (b) + t > 0, SWB(b, t, db, 0));             \
         mma_rs56<1, D128(HALF, t)>(av, AQ(A, b, t), (b) + t > 0, SWB(b, t, db, 0));          \
         PREP(b, t, step)); }                                                                 \
    wg_commit();                                                                              \
    if ((b) == 3 && PPK < 4) { PP_GO() }                                                      \
    R_NEXT();
                    normalize<0>(A, k0, k1);
                    KV_BLOCK(0) KV_BLOCK(1) KV_BLOCK(2) KV_BLOCK(3)
                    wg_wait<0>();
                    if (lane < 3) mbar_arrive(BAR(B_EMPTY + (slot + NST - 1 - lane) % NST));
                    STAMP(4 + so);
                    WSUM(80 + 7 * (step >> 1));
                    const int m = lane >> 3, rr = lane & 7;
                    const uint32_t rowa = hbuf + 16384 + (w * 16 + rr + 8 * (m & 1)) * 128;
                    const uint32_t one = c == 0 ? 0x00003f80u : 0u;
                    if (step == 0) { bar_sync(wgi ? 9 : 1, 224); }
#pragma unroll
                    for (int j = 0; j < 4; j++) {
                        const uint32_t a = rowa + (((2 * j + (m >> 1)) ^ rr) << 4);
                        if (j < 3) stsm4(a, pack2(av[8 * j], av[8 * j + 1]), pack2(av[8 * j + 2], av[8 * j + 3]), pack2(av[8 * j + 4], av[8 * j + 5]), pack2(av[8 * j + 6], av[8 * j + 7]));
                        else stsm4(a, pack2(av[24], av[25]), pack2(av[26], av[27]), one, one);
                    }
                }
                uint32_t PH[28];
                int it = 1;
#pragma unroll 1
                do {
                    float pp[28];
                    phi_gemm(tq, pp);
                    dual_softmax(pp, PH);
                    if (((trips >> (it + 1)) & 1) == 0) continue;
                    {
                        const int m = lane >> 3, rr = lane & 7;
                        const uint32_t rowa = hbuf + (w * 16 + rr + 8 * (m & 1)) * 128;
#pragma unroll
                        for (int j = 0; j < 7; j++) {
                            const int cg = 2 * j + (m >> 1), hi = cg >= 7;
                            stsm4(rowa + hi * 8192 + (((cg - 7 * hi) ^ rr) << 4), PH[4 * j], PH[4 * j + 1], PH[4 * j + 2], PH[4 * j + 3]);
                        }
                    }
                    fence_async();
                    STAMP(5 + so);
#define Q_STAGE(b0)                                                                           \
    R_WAIT();                                                                                 \
    { DECL_DB(b0, BASE128, 16, 0)                                                             \
    wg_fence();                                                                               \
    FOR7(mma_rs56<1, D128(0, t)>(tq, AQ(A, b0, t), (b0) + t > 0, SWB(b0, t, db, 0)));         \
    FOR7(mma_rs56<1, D128(HALF, t)>(tq, AQ(A, (b0) + 1, t), 1, db)); }                        \
    wg_commit();                                                                              \
    R_NEXT();
                    if (QE && wgi == 0) { kill<28>(tq); Q_STAGE(0) Q_STAGE(2) wg_wait<1>(); R_RELEASE(2); wg_wait<0>(); R_RELEASE(1); }
                    bar_sync(2, 256);
                    float kv[28];
                    const uint64_t da = BASE128(OFF_H + 16384, 16, 0), dbk = BASE128(OFF_H, 16, wgi * 512);
                    wg_fence();
                    FOR8(constexpr uint64_t o = ((t >> 2) * STAGE + (t & 3) * 2048) >> 4; mma_ss56_tt<o, o>(kv, t > 0, da, dbk));
                    wg_commit();
                    wg_wait<0>();
#pragma unroll
                    for (int hf = 0; hf < 2; hf++) {
                        const int d = 16 * w + g + 8 * hf;
                        if ((d < 56 && (d >= 28) == (c >= 2)) || d == 56) {
                            const int item = d < 56 ? 2 * d + (c & 1) : 112 + c;
                            uint4* dst = g_kv1 + ((sl * 16 + (item >> 3)) * 16 + tile) * 32 + wgi * 16 + (item & 7);
#define KVW(i) pack2(kv[4 * (i) + 2 * hf], kv[4 * (i) + 2 * hf + 1])
                            st_pkt<0>(dst, settag(KVW(0), tag), KVW(1), KVW(2), KVW(3));
                            st_pkt<8>(dst, settag(KVW(4), tag), KVW(5), KVW(6), 0u);
                        }
                    }
                    __syncwarp();
                    kseq++;
                    if (lane == 0) st_word(g_c1 + ((sl * 8 + wu) * 16 + tile) * 32, kseq);
                    bar_arrive(7, 384);
                    STAMP(6 + so);
                    if (!QE || wgi == 1) { kill<28>(tq); Q_STAGE(0) Q_STAGE(2) wg_wait<1>(); R_RELEASE(2); wg_wait<0>(); R_RELEASE(1); }
                    STAMP(7 + so);
                    kill<28>(PH);
                } while (((trips >> (++it)) & 1));
                STAMP(8 + so);
                FRESH();
                if (step) {
                    slice_load<PL(0)>(X, xp0 + sl * 512, lane);
                } else {
                    const uint32_t* xp = reinterpret_cast<const uint32_t*>(x_in + (size_t)(tile * 128 + wu * 16 + g) * 448 + 56 * sl + 2 * c);
#pragma unroll
                    for (int i = 0; i < 7; i++) { X[2 * i] = __ldg(xp + 4 * i); X[2 * i + 1] = __ldg(xp + 4 * i + 8 * 224); }
                }
                bar_sync(3, 384);
                STAMP(9 + so);
                const uint4* const osrc = xp0 + PL(1);
                {
                    float nm[32];
                    const uint64_t db = BASE128(OFF_KVB, 16, 0);
                    wg_fence();
                    FOR7(mma_rs64<0, ((t >> 2) * 8192 + (t & 3) * 32) / 16>(nm, PH[4 * t], PH[4 * t + 1], PH[4 * t + 2], PH[4 * t + 3], t > 0, db));
                    wg_commit();
                    wg_wait<0>();
                    LATE_ARRIVE();
                    const float i00 = rcp(nm[28] + 1e-6f), i01 = rcp(nm[29] + 1e-6f), i10 = rcp(nm[30] + 1e-6f), i11 = rcp(nm[31] + 1e-6f);
                    const float m0 = c >= 2 ? i01 : i00, m1 = c >= 2 ? i11 : i10;
                    uint32_t O[14];
#pragma unroll
                    for (int i = 0; i < 7; i++) {
                        const float f0 = i < 3 ? i00 : (i > 3 ? i01 : m0), f1 = i < 3 ? i10 : (i > 3 ? i11 : m1);
                        O[2 * i] = pack2(nm[4 * i] * f0, nm[4 * i + 1] * f0);
                        O[2 * i + 1] = pack2(nm[4 * i + 2] * f1, nm[4 * i + 3] * f1);
                    }
                    if (OST) { PP_WAIT() }
                    tag_slice(O, tag);
                    send_slice<PL(1)>(xp0 + sl * 512, lane, O);
                    seq++;
                    if (lane == 0) st_word(cx(sl), seq);
                    STAMP(10 + so);
                    PUSH_SLICE(O)
                    if (OST == 1) { PP_GO() }
                    const uint32_t cv = ld_word(cx(lane & 7));
                    PULL_SLICE(O)
                    LATE_WAIT();
                    check_cnt(cv, cx(lane & 7), seq);
                    if (OST == 2) { PP_GO() }
                    STAMP(56 + (step >> 1));
                    GAT_ISSUE(1, PL(1))
                    GAT_ISSUE(3, PL(1))
                    blk_load<2>(A, BLK(osrc, 2), lane);
                }
                float ao[28];
#define WO_BLOCK(b)                                                                           \
    if ((b) > 0) blk_check<b>(A, BLK(osrc, b), lane, tag);                                    \
    if (((b) & 1) == 0) R_WAIT();                                                             \
    { DECL_DB(b, BASE128, 16, 0)                                                              \
    wg_fence();                                                                               \
    FOR7(mma_rs56<1, D128(((b) & 1) * HALF, t)>(ao, AQ(A, b, t), (b) + t > 0, SWB(b, t, db, 0))); } \
    wg_commit();                                                                              \
    if ((b) & 1) R_NEXT();
                WO_BLOCK(0)
                STAMP(11 + so);
                GAT_FETCH(1)
                WO_BLOCK(1)
                WO_BLOCK(2)
                GAT_FETCH(3)
                WO_BLOCK(3)
                PUSH_ACK();
                wg_wait<0>();
                R_RELEASE(2);
                STAMP(12 + so);
                WSUM(86 + 7 * (step >> 1));
                x_fix(X, xbits);
#pragma unroll
                for (int i = 0; i < 14; i++) X[i] = pack2(bf_lo(X[i]) + ao[2 * i], bf_hi(X[i]) + ao[2 * i + 1]);
            } else {
                uint32_t H[56];
                float ag[64];
#define F1_EPI(dst, ng, ag)                                                                    \
    _Pragma("unroll") for (int i = 0; i < 2 * (ng); i++)                                       \
        (dst)[i] = pack2(geglu(ag[2 * i], ag[4 * (ng) + 2 * i]), geglu(ag[2 * i + 1], ag[4 * (ng) + 2 * i + 1]));
#define H_PUSH(h0, off) st_async4(rem_h + (off), H[h0], H[(h0) + 1], H[(h0) + 2], H[(h0) + 3], mapa(BAR(B_RECV2 + wgi), hr ^ 1));
#define F1_BLOCK(b, first)                                                                     \
    if ((first) && (b) == 1) R_RELEASE(2);                                                     \
    if ((first) && (b) == 2) PUSH_ACK();                                                       \
    R_WAIT();                                                                                  \
    if ((b) == ((first) ? PPF : PPB)) { PP_WAIT() }                                            \
    { DECL_DB(b, BASE128, HALF, 0)                                                             \
    wg_fence();                                                                                \
    FOR7(mma_rs128<1, D128(0, t)>(ag, AQ(A, b, t), (b) + t > 0, SWB(b, t, db, 0));             \
         if constexpr (first) { PREP(b, t, true) }); }                                         \
    wg_commit();                                                                               \
    if ((b) == 3) { PP_GO() }                                                                  \
    if ((b) > 0) { wg_wait<1>(); R_RELEASE(1); }       \
    R_NEXT();
                normalize<0>(A, k0, k1);
                F1_BLOCK(0, true) F1_BLOCK(1, true) F1_BLOCK(2, true) F1_BLOCK(3, true)
                if (t128 == 0) { mbar_expect_tx(BAR(B_RECV + wgi), 16384); mbar_expect_tx(BAR(B_RECV2 + wgi), 12288); }
                PUSH_BEGIN();
                wg_wait<0>();
                R_RELEASE(1);
                int p = 0;
#pragma unroll 1
                do {
                    F1_EPI(H + 32, 8, ag)
                    STAMP(4 + p + so);
                    WSUM(81 + p + 7 * (step >> 1));
                    if (((trips >> (p + 1)) & 1) == 0) continue;
                    {
                        const uint32_t pk = (p ? hbuf + 16384 : sb + OFF_KVB + wgi * 8192) + w * 2048;
#pragma unroll
                        for (int k = 0; k < 4; k++) sts4(pk + k * 512 + lane * 16, H[32 + 4 * k], H[33 + 4 * k], H[34 + 4 * k], H[35 + 4 * k]);
                        fence_async();
                        __syncwarp();
                        asm volatile(ELECT "cp.async.bulk.shared::cluster.shared::cta.mbarrier::complete_tx::bytes [%0], [%1], 2048, [%2]; }"
                                     ::"r"(mapa(hbuf + p * 8192 + w * 2048, hr ^ 1)), "r"(pk), "r"(mapa(BAR(B_RECV + wgi), hr ^ 1)) : "memory");
                    }
                    if (step == 1 && p == PKP) R_NEXT();
                    kill<64>(ag);
                    F1_BLOCK(0, false) F1_BLOCK(1, false) F1_BLOCK(2, false) F1_BLOCK(3, false)
                    wg_wait<0>();
                    R_RELEASE(1);
                    kill<16>(H + 32);
                } while (((trips >> (++p)) & 1));
#pragma unroll
                for (int k = 0; k < 4; k++) lds4(H + 16 + 4 * k, hbuf + 16384 + w * 2048 + k * 512 + lane * 16);
                __syncwarp();
                if (lane == 0) asm volatile("mbarrier.arrive.shared::cluster.b64 _, [%0];" ::"r"(mapa(BAR(B_ACK2 + wgi), hr ^ 1)) : "memory");
                const uint32_t rem_h = mapa(hbuf + w * 2048 + lane * 16, hr ^ 1);
#define F1_LAST(b0)                                                                            \
    R_WAIT();                                                                                  \
    if (b0) { PP_WAIT() }                                                                      \
    { DECL_DB(b0, BASE64, HALF, 1)                                                             \
    wg_fence();                                                                                \
    FOR7(mma_rs64<1, D64(0, t)>(al, AQ(A, b0, t), (b0) + t > 0, SWB(b0, t, db, 1)));           \
    FOR7(mma_rs64<1, D64(7168, t)>(al, AQ(A, (b0) + 1, t), 1, db)); }                          \
    wg_commit();                                                                               \
    if (b0) { PP_GO() }                                                                        \
    R_NEXT();
                float al[32];
                F1_LAST(0)
                mbar_wait(BAR(B_RECV + wgi), rcvph);
                rcvph ^= 1;
                mbar_wait(BAR(B_ACK2 + wgi), step >> 1);
                H_PUSH(32, 16384) H_PUSH(36, 16896)
                F1_LAST(2)
                H_PUSH(40, 17408) H_PUSH(44, 17920)
                wg_wait<1>();
                R_RELEASE(2);
                wg_wait<0>();
                R_RELEASE(1);
                uint32_t HP[56];
#pragma unroll
                for (int k = 0; k < 4; k++) lds4(H + 4 * k, sb + OFF_KVB + wgi * 8192 + w * 2048 + k * 512 + lane * 16);
#pragma unroll
                for (int t = 0; t < 8; t++) lds4(HP + 4 * t, hbuf + (t >> 2) * 8192 + w * 2048 + (t & 3) * 512 + lane * 16);
                F1_EPI(H + 48, 4, al)
                H_PUSH(48, 24576 - w * 1024) H_PUSH(52, 25088 - w * 1024)
                STAMP(7 + so);
                WSUM(84 + 7 * (step >> 1));
                FRESH();
                float acc[28];
                const uint32_t roA = hr ? 256u : 0u, roB = hr ? (uint32_t)-1536 : 0u;
                const uint32_t rpA = hr ? 0u : 256u, rpB = hr ? 0u : (uint32_t)-1536;
                float res[28];
                uint32_t v0[14], v1[14], P[14];
                const uint4* ps = xp0 + sl * 512;
#define F2_OWN_A()                                                                             \
    R_WAIT();                                                                                  \
    d0 = BASE128(0, 16, R_ADJ + roA); d1 = BASE128(0, 16, R_ADJ + roB);                        \
    wg_fence();                                                                                \
    FOR14(if constexpr (t < OT) mma_rs56<1, t * 128>(acc, H[4 * t], H[4 * t + 1], H[4 * t + 2], H[4 * t + 3], t > 0, d0)); \
    wg_commit();
#define F2_OWN_B()                                                                             \
    wg_fence();                                                                                \
    FOR14(if constexpr (t >= OT) mma_rs56<1, t * 128>(acc, H[4 * t], H[4 * t + 1], H[4 * t + 2], H[4 * t + 3], 1, t < 12 ? d0 : d1)); \
    wg_commit();                                                                               \
    R_NEXT();
#define F2_PEER()                                                                              \
    R_WAIT();                                                                                  \
    if (F2PP) { PP_WAIT() }                                                                    \
    d0 = BASE128(0, 16, R_ADJ + rpA); d1 = BASE128(0, 16, R_ADJ + rpB);                        \
    wg_fence();                                                                                \
    FOR14(mma_rs56<1, t * 128>(acc, HP[4 * t], HP[4 * t + 1], HP[4 * t + 2], HP[4 * t + 3], 1, t < 12 ? d0 : d1)); \
    wg_commit();                                                                               \
    if (F2PP) { PP_GO() }                                                                      \
    R_NEXT();
#define F2_TURN(u)                                                                             \
    wg_wait<1>();                                                                              \
    if ((u) < 2 || TDEF < 2) R_RELEASE(2);                                                     \
    wg_wait<0>();                                                                              \
    if ((u) < 2 || TDEF < 1) R_RELEASE(1);                                                     \
    _Pragma("unroll") for (int i = 0; i < 14; i++) P[i] = pack2(acc[2 * i], acc[2 * i + 1]);   \
    tag_slice(P, tag);                                                                         \
    asm volatile("" : RW4(P, 0), RW4(P, 4), RW4(P, 8), RW2(P, 12));                            \
    kill<28>(acc);                                                                             \
    F2_OWN_A()                                                                                 \
    if ((u) == 2) { slice_load<PL(3)>(v0, ps, lane); slice_load<PL(4)>(v1, ps, lane); } \
    send_slice<PL(3 + (u))>(xp0 + (2 * ((pr + (u) + 1) & 3) + hr) * 512, lane, P);             \
    seq++;                                                                                     \
    if (lane == 0) st_word(cx(sl), seq);                                                       \
    __syncwarp();                                                                              \
    STAMP(8 + (u) + so);                                                                       \
    F2_OWN_B()
                uint64_t d0, d1;
                F2_OWN_A()
                F2_OWN_B()
                R_WAIT();
                d0 = BASE128(0, 16, R_ADJ + rpA); d1 = BASE128(0, 16, R_ADJ + rpB);
                wg_fence();
                FOR8(mma_rs56<1, t * 128>(acc, HP[4 * t], HP[4 * t + 1], HP[4 * t + 2], HP[4 * t + 3], 1, d0));
                wg_commit();
                mbar_wait(BAR(B_RECV2 + wgi), step >> 1);
#pragma unroll
                for (int k = 0; k < 4; k++) lds4(HP + 32 + 4 * k, hbuf + 16384 + w * 2048 + k * 512 + lane * 16);
                lds4(HP + 48, hbuf + 24576 + w * 1024 + lane * 16);
                lds4(HP + 52, hbuf + 25088 + w * 1024 + lane * 16);
                if (step == 1) PUSH_ACK();
                wg_fence();
                FOR14(if constexpr (t >= 8) mma_rs56<1, t * 128>(acc, HP[4 * t], HP[4 * t + 1], HP[4 * t + 2], HP[4 * t + 3], 1, t < 12 ? d0 : d1));
                wg_commit();
                R_NEXT();
                F2_TURN(0)
                F2_PEER()
                F2_TURN(1)
                F2_PEER()
                F2_TURN(2)
                if (step == 1) STAMP(64);
                slice_check<PL(3)>(v0, ps, lane, tag);
                slice_check<PL(4)>(v1, ps, lane, tag);
#pragma unroll
                for (int i = 0; i < 14; i++) { res[2 * i] = bf_lo(v0[i]) + bf_lo(v1[i]); res[2 * i + 1] = bf_hi(v0[i]) + bf_hi(v1[i]); }
                slice_load<PL(2)>(X, ps, lane);
                if (step == 1) STAMP(65);
                F2_PEER()
                if (step == 1) STAMP(66);
                poll_cnt(cx(2 * ((pr + 1) & 3) + hr), seq);
                if (step == 1) STAMP(67);
                slice_load<PL(5)>(v0, ps, lane);
                x_fix(X, xbits);
                slice_check<PL(5)>(v0, ps, lane, tag);
                if (lane < TDEF) mbar_arrive(BAR(B_EMPTY + (slot + NST - 3 - lane) % NST));
#pragma unroll
                for (int i = 0; i < 14; i++) { res[2 * i] += bf_lo(v0[i]); res[2 * i + 1] += bf_hi(v0[i]); }
                STAMP(11 + so);
                wg_wait<0>();
                R_RELEASE(2);
                STAMP(12 + so);
                WSUM(85 + 7 * (step >> 1));
#pragma unroll
                for (int i = 0; i < 14; i++) X[i] = pack2(fmaf(res[2 * i] + acc[2 * i], 0.5f, bf_lo(X[i])), fmaf(res[2 * i + 1] + acc[2 * i + 1], 0.5f, bf_hi(X[i])));
            }
        }
        {
            const int m = lane >> 3, rr = lane & 7;
            const uint32_t ob = hbuf + w * 2048, rowa = ob + (rr + 8 * (m & 1)) * 112 + (m >> 1) * 16;
#pragma unroll
            for (int j = 0; j < 3; j++) stsm4(rowa + 32 * j, X[4 * j], X[4 * j + 1], X[4 * j + 2], X[4 * j + 3]);
            asm volatile("stmatrix.sync.aligned.m8n8.x2.shared.b16 [%0], {%1,%2};" ::"r"(ob + (rr + 8 * (m & 1)) * 112 + 96), "r"(X[12]), "r"(X[13]) : "memory");
            fence_async();
            __syncwarp();
            if (lane == 0) {
                asm volatile("cp.async.bulk.tensor.2d.global.shared::cta.bulk_group [%0, {%2, %3}], [%1];" ::"l"(&maps.out), "r"(ob), "r"(56 * sl), "r"(tile * 128 + wu * 16) : "memory");
                asm volatile("cp.async.bulk.commit_group;" ::: "memory");
                asm volatile("cp.async.bulk.wait_group.read 0;" ::: "memory");
            }
        }
        STAMP(50);
        GSTAMP(61);
        PDUMP();
    }
}

#undef g
#undef pr
#undef c
#undef t128

typedef CUresult (*EncodeFn)(CUtensorMap*, CUtensorMapDataType, cuuint32_t, void*, const cuuint64_t*, const cuuint64_t*, const cuuint32_t*,
                             const cuuint32_t*, CUtensorMapInterleave, CUtensorMapSwizzle, CUtensorMapL2promotion, CUtensorMapFloatOOBfill);

static void make_map(EncodeFn enc, CUtensorMap* m, const void* p, uint64_t cols, uint64_t rows, uint32_t bc, uint32_t br, CUtensorMapSwizzle sw) {
    cuuint64_t gd[2] = {cols, rows};
    cuuint64_t gs[1] = {cols * 2};
    cuuint32_t bd[2] = {bc, br};
    cuuint32_t es[2] = {1, 1};
    enc(m, CU_TENSOR_MAP_DATA_TYPE_BFLOAT16, 2, const_cast<void*>(p), gd, gs, bd, es, CU_TENSOR_MAP_INTERLEAVE_NONE, sw,
        CU_TENSOR_MAP_L2_PROMOTION_L2_128B, CU_TENSOR_MAP_FLOAT_OOB_FILL_NONE);
}

extern "C" void kernel_launch(void* const* d_in, const int* in_sizes, int n_in, void* d_out, int out_size) {
    (void)in_sizes; (void)n_in; (void)out_size;
    static EncodeFn enc = nullptr;
    static Scratch* scratch = nullptr;
    if (!enc) {
        void* fn = nullptr;
        cudaDriverEntryPointQueryResult qr;
        cudaGetDriverEntryPoint("cuTensorMapEncodeTiled", &fn, cudaEnableDefault, &qr);
        enc = (EncodeFn)fn;
        cudaGetSymbolAddress((void**)&scratch, g_scratch);
        cudaFuncSetAttribute(fused_kernel, cudaFuncAttributeMaxDynamicSharedMemorySize, SMEM_BYTES);
    }
    Maps maps;
    {
        cuuint64_t gd[3] = {64, 2048, 7};
        cuuint64_t gs[2] = {896, 128};
        cuuint32_t bd[3] = {64, 32, 7};
        cuuint32_t es[3] = {1, 1, 1};
        enc(&maps.x, CU_TENSOR_MAP_DATA_TYPE_BFLOAT16, 3, d_in[0], gd, gs, bd, es, CU_TENSOR_MAP_INTERLEAVE_NONE, CU_TENSOR_MAP_SWIZZLE_128B,
            CU_TENSOR_MAP_L2_PROMOTION_L2_128B, CU_TENSOR_MAP_FLOAT_OOB_FILL_NONE);
    }
    make_map(enc, &maps.out, d_out, 448, 2048, 56, 16, CU_TENSOR_MAP_SWIZZLE_NONE);
    make_map(enc, &maps.qkv, d_in[1], 1344, 448, 64, 112, CU_TENSOR_MAP_SWIZZLE_128B);
    make_map(enc, &maps.wo, d_in[3], 448, 448, 64, 112, CU_TENSOR_MAP_SWIZZLE_128B);
    make_map(enc, &maps.wg, d_in[5], 1792, 448, 64, 112, CU_TENSOR_MAP_SWIZZLE_128B);
    make_map(enc, &maps.wu, d_in[6], 1792, 448, 64, 112, CU_TENSOR_MAP_SWIZZLE_128B);
    make_map(enc, &maps.wg32, d_in[5], 1792, 448, 32, 112, CU_TENSOR_MAP_SWIZZLE_64B);
    make_map(enc, &maps.wu32, d_in[6], 1792, 448, 32, 112, CU_TENSOR_MAP_SWIZZLE_64B);
    make_map(enc, &maps.wd, d_in[7], 448, 1792, 64, 112, CU_TENSOR_MAP_SWIZZLE_128B);
    fused_kernel<<<128, 384, SMEM_BYTES>>>(scratch, (const __nv_bfloat16*)d_in[0], (const __nv_bfloat16*)d_in[2], 7, (const __nv_bfloat16*)d_in[5],
                                           (const __nv_bfloat16*)d_in[6], (const __nv_bfloat16*)d_in[7], maps);
}
```

```cpp
#include <cuda_runtime.h>
#include <cuda.h>
#include <cuda_bf16.h>
#include <stdint.h>
#include <type_traits>

#define PPF 2
#define PKP 0
#define TDEF 1
#define TMPF 0
#define NORM1 0
#define LPARK 1
#define ACAN 0
#define SPLIT0 1
#define OT 2
#define F2PP 0
#define PPK 2
#define QE 1
#define OST 1
#define PP

namespace {

constexpr uint32_t STAGE = 28672, HALF = 14336;
constexpr int NST = 5;
constexpr uint32_t OFF_H = NST * STAGE;
constexpr uint32_t OFF_KVB = OFF_H + 2 * STAGE;
constexpr uint32_t OFF_WPHI = OFF_KVB + 16384;
constexpr uint32_t OFF_XR = OFF_WPHI + 7168;
constexpr uint32_t OFF_BAR = OFF_XR + 6144;
constexpr uint32_t SMEM_BYTES = OFF_BAR + 384 + 1408;
constexpr int B_EMPTY = NST, B_RECV = 2 * NST, B_RECV2 = B_RECV + 2, B_PACK = B_RECV2 + 2, B_GAT = B_PACK + 1, B_LATE = B_GAT + 16, B_ACK = B_LATE + 1, B_ACK2 = B_ACK + 2, B_COUNT = B_ACK2 + 2;

constexpr int PACK = 14 + 4 * PKP;

struct Maps { CUtensorMap x, qkv, wo, wg, wu, wg32, wu32, wd, out; };

}

constexpr int PLANE = 16 * 2 * 8 * 512;
struct Scratch {
    uint4 ex[6 * PLANE];
    uint4 kv1[8 * 16 * 16 * 32];
    uint4 kv2[8 * 512];
    uint32_t c1[8 * 8 * 16 * 32];
    uint32_t cw[8 * 32];
    uint4 wp[8 * 32 * (HALF / 16)];
};
__device__ __align__(1024) Scratch g_scratch;
#define g_ex (sc->ex)
#define g_kv1 (sc->kv1)
#define g_kv2 (sc->kv2)
#define g_c1 (sc->c1)
#define g_cw (sc->cw)
#define g_wp (sc->wp)
#define STAMP(i)
#define GSTAMP(i)
#define PDUMP()
#define ASTAMP(i)

namespace {

__device__ __forceinline__ int fresh_tid() { int t; asm volatile("mov.u32 %0, %%tid.x;" : "=r"(t)); return t; }
template <int N> __device__ __forceinline__ void kill(uint32_t* v) {
#pragma unroll
    for (int i = 0; i < N; i++) v[i] = 0;
}
template <int N> __device__ __forceinline__ void kill(float* v) {
#pragma unroll
    for (int i = 0; i < N; i++) v[i] = 0.f;
}
__device__ __forceinline__ uint32_t s2u(const void* p) { return (uint32_t)__cvta_generic_to_shared(p); }
__device__ __forceinline__ void mbar_init(uint32_t a, uint32_t c) { asm volatile("mbarrier.init.shared::cta.b64 [%0], %1;" ::"r"(a), "r"(c) : "memory"); }
__device__ __forceinline__ void mbar_expect_tx(uint32_t a, uint32_t b) { asm volatile("mbarrier.arrive.expect_tx.shared::cta.b64 _, [%0], %1;" ::"r"(a), "r"(b) : "memory"); }
__device__ __forceinline__ void mbar_arrive(uint32_t a) { asm volatile("mbarrier.arrive.shared::cta.b64 _, [%0];" ::"r"(a) : "memory"); }
#define GIVE_UP(id) "trap;\n"
#define SPIN_MAX "0x400000"
#define SPIN_TAIL(id) "add.u32 n, n, 1;\n setp.lt.u32 p, n, " SPIN_MAX ";\n @p bra.uni LP;\n" GIVE_UP(id) " DN:\n }"
__device__ __forceinline__ void mbar_wait(uint32_t a, uint32_t ph) {
    asm volatile("{ .reg .pred p; .reg .b32 n; mov.u32 n, 0;\n LP:\n"
                 "mbarrier.try_wait.parity.shared::cta.b64 p, [%0], %1;\n @p bra DN;\n"
                 "add.u32 n, n, 1;\n setp.lt.u32 p, n, " SPIN_MAX ";\n @p bra LP;\n"
                 GIVE_UP("")
                 " DN:\n }" ::"r"(a), "r"(ph) : "memory");
}
#define ELECT "{ .reg .pred e; elect.sync _|e, 0xffffffff; @e "
__device__ __forceinline__ void tma2d(uint32_t dst, const CUtensorMap* m, int c0, int c1, uint32_t bar) {
    asm volatile(ELECT "cp.async.bulk.tensor.2d.shared::cluster.global.mbarrier::complete_tx::bytes [%0], [%1, {%3, %4}], [%2]; }" ::"r"(dst), "l"(m), "r"(bar), "r"(c0), "r"(c1) : "memory");
}
__device__ __forceinline__ void tma3x(uint32_t dst, const CUtensorMap* m, int row, uint32_t bar) {
    asm volatile(ELECT "cp.async.bulk.tensor.3d.shared::cluster.global.mbarrier::complete_tx::bytes [%0], [%1, {0, %3, 0}], [%2]; }" ::"r"(dst), "l"(m), "r"(bar), "r"(row) : "memory");
}
template <int OFF>
__device__ __forceinline__ void ld_pkt(uint32_t* v, const uint4* p) {
    asm volatile("{ .reg .b128 t; ld.relaxed.gpu.global.b128 t, [%4+%5]; mov.b128 {%0,%1,%2,%3}, t; }" : "=r"(v[0]), "=r"(v[1]), "=r"(v[2]), "=r"(v[3]) : "l"(p), "n"(OFF * 16) : "memory");
}
template <int OFF>
__device__ __forceinline__ void st_pkt(uint4* p, uint32_t a, uint32_t b, uint32_t c, uint32_t d) {
    asm volatile("{ .reg .b128 t; mov.b128 t, {%1,%2,%3,%4}; st.relaxed.gpu.global.b128 [%0+%5], t; }" ::"l"(p), "r"(a), "r"(b), "r"(c), "r"(d), "n"(OFF * 16) : "memory");
}
__device__ __forceinline__ uint32_t pack2(float lo, float hi) {
    uint32_t r;
    asm("cvt.rn.bf16x2.f32 %0, %1, %2;" : "=r"(r) : "f"(hi), "f"(lo));
    return r;
}
__device__ __forceinline__ float bf_lo(uint32_t w) { return __uint_as_float(w << 16); }
__device__ __forceinline__ float bf_hi(uint32_t w) { return __uint_as_float(w & 0xffff0000u); }
__device__ __forceinline__ uint32_t settag(uint32_t w, uint32_t tag) { return (w & ~1u) | tag; }
__device__ __forceinline__ float ex2(float x) { float y; asm("ex2.approx.ftz.f32 %0, %1;" : "=f"(y) : "f"(x)); return y; }
__device__ __forceinline__ float rcp(float x) { float y; asm("rcp.approx.ftz.f32 %0, %1;" : "=f"(y) : "f"(x)); return y; }
__device__ __forceinline__ float tanh_hw(float x) { float y; asm("tanh.approx.f32 %0, %1;" : "=f"(y) : "f"(x)); return y; }
__device__ __forceinline__ void stsm4(uint32_t addr, uint32_t a, uint32_t b, uint32_t c, uint32_t d) {
    asm volatile("stmatrix.sync.aligned.m8n8.x4.shared.b16 [%0], {%1,%2,%3,%4};" ::"r"(addr), "r"(a), "r"(b), "r"(c), "r"(d) : "memory");
}
__device__ __forceinline__ void fence_async() { asm volatile("fence.proxy.async.shared::cta;" ::: "memory"); }
__device__ __forceinline__ void bar_sync(int id, int n) { asm volatile("bar.sync %0, %1;" ::"r"(id), "r"(n) : "memory"); }
__device__ __forceinline__ void bar_arrive(int id, int n) { asm volatile("bar.arrive %0, %1;" ::"r"(id), "r"(n) : "memory"); }
__device__ __forceinline__ void wg_fence() { asm volatile("wgmma.fence.sync.aligned;" ::: "memory"); }
__device__ __forceinline__ void wg_commit() { asm volatile("wgmma.commit_group.sync.aligned;" ::: "memory"); }
template <int N> __device__ __forceinline__ void wg_wait() { asm volatile("wgmma.wait_group.sync.aligned %0;" ::"n"(N) : "memory"); }

constexpr uint32_t SB0 = 1024;
__host__ __device__ constexpr uint32_t dlo(uint32_t off, uint32_t lbo) { return ((SB0 + off) >> 4) | ((lbo >> 4) << 16); }
__host__ __device__ constexpr uint32_t dhi(uint32_t sbo, uint32_t sw) { return (sbo >> 4) | (sw << 30); }
__device__ __forceinline__ uint64_t dbase(uint32_t lo, uint32_t hi) { uint64_t d; asm volatile("mov.b64 %0, {%1, %2};" : "=l"(d) : "r"(lo), "r"(hi)); return d; }
#define BASE128(off, lbo, adj) dbase(dlo(off, lbo) + (adj), dhi(1024, 1))
#define BASE64(off, lbo, adj) dbase(dlo(off, lbo) + (adj), dhi(512, 2))

#define ACC4(d, o) "+f"(d[o]), "+f"(d[o + 1]), "+f"(d[o + 2]), "+f"(d[o + 3])
#define ACC28(d) ACC4(d, 0), ACC4(d, 4), ACC4(d, 8), ACC4(d, 12), ACC4(d, 16), ACC4(d, 20), ACC4(d, 24)
#define ACC32(d, o) ACC4(d, o), ACC4(d, o + 4), ACC4(d, o + 8), ACC4(d, o + 12), ACC4(d, o + 16), ACC4(d, o + 20), ACC4(d, o + 24), ACC4(d, o + 28)

template <int TB, uint64_t D>
__device__ __forceinline__ void mma_rs56(float* d, uint32_t a0, uint32_t a1, uint32_t a2, uint32_t a3, int sd, uint64_t base) {
    asm volatile("{ .reg .pred p; .reg .b64 db; setp.ne.b32 p, %32, 0; add.u64 db, %33, %34;\n"
                 "wgmma.mma_async.sync.aligned.m64n56k16.f32.bf16.bf16 "
                 "{%0,%1,%2,%3,%4,%5,%6,%7,%8,%9,%10,%11,%12,%13,%14,%15,%16,%17,%18,%19,%20,%21,%22,%23,%24,%25,%26,%27}, "
                 "{%28,%29,%30,%31}, db, p, 1, 1, %35; }\n"
                 : ACC28(d)
                 : "r"(a0), "r"(a1), "r"(a2), "r"(a3), "r"(sd), "l"(base), "n"(D), "n"(TB));
}
template <int TB, uint64_t D>
__device__ __forceinline__ void mma_rs64(float* d, uint32_t a0, uint32_t a1, uint32_t a2, uint32_t a3, int sd, uint64_t base) {
    asm volatile("{ .reg .pred p; .reg .b64 db; setp.ne.b32 p, %36, 0; add.u64 db, %37, %38;\n"
                 "wgmma.mma_async.sync.aligned.m64n64k16.f32.bf16.bf16 "
                 "{%0,%1,%2,%3,%4,%5,%6,%7,%8,%9,%10,%11,%12,%13,%14,%15,%16,%17,%18,%19,%20,%21,%22,%23,%24,%25,%26,%27,%28,%29,%30,%31}, "
                 "{%32,%33,%34,%35}, db, p, 1, 1, %39; }\n"
                 : ACC32(d, 0)
                 : "r"(a0), "r"(a1), "r"(a2), "r"(a3), "r"(sd), "l"(base), "n"(D), "n"(TB));
}
template <int TB, uint64_t D>
__device__ __forceinline__ void mma_rs128(float* d, uint32_t a0, uint32_t a1, uint32_t a2, uint32_t a3, int sd, uint64_t base) {
    asm volatile("{ .reg .pred p; .reg .b64 db; setp.ne.b32 p, %68, 0; add.u64 db, %69, %70;\n"
                 "wgmma.mma_async.sync.aligned.m64n128k16.f32.bf16.bf16 "
                 "{%0,%1,%2,%3,%4,%5,%6,%7,%8,%9,%10,%11,%12,%13,%14,%15,%16,%17,%18,%19,%20,%21,%22,%23,%24,%25,%26,%27,%28,%29,%30,%31,%32,%33,%34,%35,%36,%37,%38,%39,%40,%41,%42,%43,%44,%45,%46,%47,%48,%49,%50,%51,%52,%53,%54,%55,%56,%57,%58,%59,%60,%61,%62,%63}, "
                 "{%64,%65,%66,%67}, db, p, 1, 1, %71; }\n"
                 : ACC32(d, 0), ACC32(d, 32)
                 : "r"(a0), "r"(a1), "r"(a2), "r"(a3), "r"(sd), "l"(base), "n"(D), "n"(TB));
}
template <uint64_t DA, uint64_t DB>
__device__ __forceinline__ void mma_ss56_tt(float* d, int sd, uint64_t ba, uint64_t bb) {
    asm volatile("{ .reg .pred p; .reg .b64 da, db; setp.ne.b32 p, %28, 0; add.u64 da, %29, %31; add.u64 db, %30, %32;\n"
                 "wgmma.mma_async.sync.aligned.m64n56k16.f32.bf16.bf16 "
                 "{%0,%1,%2,%3,%4,%5,%6,%7,%8,%9,%10,%11,%12,%13,%14,%15,%16,%17,%18,%19,%20,%21,%22,%23,%24,%25,%26,%27}, "
                 "da, db, p, 1, 1, 1, 1; }\n"
                 : ACC28(d)
                 : "r"(sd), "l"(ba), "l"(bb), "n"(DA), "n"(DB));
}
template <int... I> struct Seq {};
template <class F, int... I> __device__ __forceinline__ void static_for_impl(F&& f, Seq<I...>) { (f(std::integral_constant<int, I>{}), ...); }
#define FOR7(...) static_for_impl([&](auto T_) { constexpr int t = decltype(T_)::value; __VA_ARGS__; }, Seq<0, 1, 2, 3, 4, 5, 6>{})
#define FOR8(...) static_for_impl([&](auto T_) { constexpr int t = decltype(T_)::value; __VA_ARGS__; }, Seq<0, 1, 2, 3, 4, 5, 6, 7>{})
#define FOR14(...) static_for_impl([&](auto T_) { constexpr int t = decltype(T_)::value; __VA_ARGS__; }, Seq<0, 1, 2, 3, 4, 5, 6, 7, 8, 9, 10, 11, 12, 13>{})

__device__ __forceinline__ int kblk(int p, int b) { return b == 0 ? p : b - (b <= p); }
__host__ __device__ constexpr int krow(int t) { return t < 3 ? 16 * t : (t < 6 ? 56 + 16 * (t - 3) : 48); }
#define AQ(A, b, t) ((t) < 3 ? A[2 * (b)][4 * (t)] : (t) < 6 ? A[2 * (b) + 1][4 * ((t) - 3)] : A[2 * (b)][12]), \
                    ((t) < 3 ? A[2 * (b)][4 * (t) + 1] : (t) < 6 ? A[2 * (b) + 1][4 * ((t) - 3) + 1] : A[2 * (b)][13]), \
                    ((t) < 3 ? A[2 * (b)][4 * (t) + 2] : (t) < 6 ? A[2 * (b) + 1][4 * ((t) - 3) + 2] : A[2 * (b) + 1][12]), \
                    ((t) < 3 ? A[2 * (b)][4 * (t) + 3] : (t) < 6 ? A[2 * (b) + 1][4 * ((t) - 3) + 3] : A[2 * (b) + 1][13])
#define D128(off, t) ((uint64_t)(((off) + krow(t) * 128) >> 4) + ((uint64_t)((t) == 6 ? (7168 - 1024) >> 4 : 0) << 32))
#define D64(off, t) ((uint64_t)(((off) + krow(t) * 64) >> 4) + ((uint64_t)((t) == 6 ? (3584 - 512) >> 4 : 0) << 32))

#define PL(k) (((k) - 3) * PLANE)
__device__ __forceinline__ void st_word(uint32_t* p, uint32_t v) { asm volatile("st.relaxed.gpu.global.u32 [%0], %1;" ::"l"(p), "r"(v) : "memory"); }
__device__ __forceinline__ uint32_t ld_word(const uint32_t* p) { uint32_t v; asm volatile("ld.relaxed.gpu.global.u32 %0, [%1];" : "=r"(v) : "l"(p) : "memory"); return v; }
__device__ __forceinline__ void tag_slice(uint32_t* w, uint32_t tag) { w[0] = settag(w[0], tag); w[4] = settag(w[4], tag); w[8] = settag(w[8], tag); w[12] = settag(w[12], tag); }
template <int O>
__device__ __forceinline__ void send_slice(uint4* dst, int lane, const uint32_t* w) {
    st_pkt<O>(dst, w[0], w[1], w[2], w[3]);
    st_pkt<O + 32>(dst, w[4], w[5], w[6], w[7]);
    st_pkt<O + 64>(dst, w[8], w[9], w[10], w[11]);
    asm volatile("{ .reg .b64 t; mov.b64 t, {%1,%2}; st.relaxed.gpu.global.b64 [%0+%3], t; }" ::"l"((char*)dst - lane * 8), "r"(w[12]), "r"(w[13]), "n"(16 * (O + 96)) : "memory");
}
#define RW4(v, o) "+r"(v[o]), "+r"(v[(o) + 1]), "+r"(v[(o) + 2]), "+r"(v[(o) + 3])
#define RW2(v, o) "+r"(v[o]), "+r"(v[(o) + 1])
#define WR4(v, o) "=&r"(v[o]), "=&r"(v[(o) + 1]), "=&r"(v[(o) + 2]), "=&r"(v[(o) + 3])
#define LDP(a, b, c, d, addr, off) "ld.relaxed.gpu.global.b128 q, [" addr "+" off "];\n mov.b128 {" a "," b "," c "," d "}, q;\n"
#define LDH(a, b, addr, off) "ld.relaxed.gpu.global.b64 h, [" addr "+" off "];\n mov.b64 {" a "," b "}, h;\n"
#define VOTE_OK "and.b32 t, t, 1;\n setp.ne.u32 p, t, 0;\n vote.sync.any.pred p, p, 0xffffffff;\n @!p bra.uni DN;\n"
#define CHK(x, tag) "lop3.b32 t, " x ", " tag ", t, 0xBE;\n"
__device__ __forceinline__ void check_cnt(uint32_t v, const uint32_t* p, uint32_t target) {
    asm volatile("{ .reg .pred p; .reg .b32 n, t; mov.u32 n, 0; mov.u32 t, %2;\n LP:\n"
                 "sub.s32 t, t, %1;\n setp.lt.s32 p, t, 0;\n vote.sync.any.pred p, p, 0xffffffff;\n @!p bra.uni DN;\n ld.relaxed.gpu.global.u32 t, [%0];\n" SPIN_TAIL("7")
                 ::"l"(p), "r"(target), "r"(v) : "memory");
}
__device__ __forceinline__ void poll_cnt(const uint32_t* p, uint32_t target) {
    asm volatile("{ .reg .pred p; .reg .b32 n, t; mov.u32 n, 0;\n LP:\n"
                 "ld.relaxed.gpu.global.u32 t, [%0];\n sub.s32 t, t, %1;\n setp.lt.s32 p, t, 0;\n vote.sync.any.pred p, p, 0xffffffff;\n @!p bra.uni DN;\n" SPIN_TAIL("1")
                 ::"l"(p), "r"(target) : "memory");
}
template <int STR>
__device__ __forceinline__ void poll4_kv(uint32_t* v, const uint4* p, uint32_t tag) {
    asm volatile("{ .reg .pred p; .reg .b32 n, t; .reg .b128 q; mov.u32 n, 0;\n LP:\n"
                 LDP("%0", "%1", "%2", "%3", "%16", "0") LDP("%4", "%5", "%6", "%7", "%16", "%18")
                 LDP("%8", "%9", "%10", "%11", "%16", "%19") LDP("%12", "%13", "%14", "%15", "%16", "%20")
                 "xor.b32 t, %0, %17;\n" CHK("%4", "%17") CHK("%8", "%17") CHK("%12", "%17") VOTE_OK SPIN_TAIL("2")
                 : WR4(v, 0), WR4(v, 4), WR4(v, 8), WR4(v, 12)
                 : "l"(p), "r"(tag), "n"(16 * STR), "n"(32 * STR), "n"(48 * STR)
                 : "memory");
}
template <int B>
__device__ __forceinline__ void blk_load(uint32_t (&A)[8][14], const uint4* src, int lane) {
    ld_pkt<0>(&A[2 * B][0], src); ld_pkt<32>(&A[2 * B][4], src); ld_pkt<64>(&A[2 * B][8], src);
    ld_pkt<512>(&A[2 * B + 1][0], src); ld_pkt<544>(&A[2 * B + 1][4], src); ld_pkt<576>(&A[2 * B + 1][8], src);
    asm volatile("{ .reg .b64 h;\n" LDH("%0", "%1", "%4", "1536") LDH("%2", "%3", "%4", "9728") "}"
                 : "=&r"(A[2 * B][12]), "=&r"(A[2 * B][13]), "=&r"(A[2 * B + 1][12]), "=&r"(A[2 * B + 1][13])
                 : "l"((const char*)src - lane * 8) : "memory");
}
template <int B>
__device__ __forceinline__ void blk_check(uint32_t (&A)[8][14], const uint4* src, int lane, uint32_t tag) {
    asm volatile("{ .reg .pred p; .reg .b32 n, t; .reg .b128 q; .reg .b64 h, a8; mov.u32 n, 0;\n LP:\n"
                 "xor.b32 t, %0, %30;\n" CHK("%4", "%30") CHK("%8", "%30") CHK("%12", "%30") CHK("%16", "%30") CHK("%20", "%30") CHK("%24", "%30") CHK("%26", "%30") VOTE_OK
                 LDP("%0", "%1", "%2", "%3", "%28", "0") LDP("%4", "%5", "%6", "%7", "%28", "512") LDP("%8", "%9", "%10", "%11", "%28", "1024")
                 LDP("%12", "%13", "%14", "%15", "%28", "8192") LDP("%16", "%17", "%18", "%19", "%28", "8704") LDP("%20", "%21", "%22", "%23", "%28", "9216")
                 "mad.wide.s32 a8, %29, -8, %28;\n" LDH("%24", "%25", "a8", "1536") LDH("%26", "%27", "a8", "9728") SPIN_TAIL("3")
                 "\n and.b32 %0, %0, -2; and.b32 %4, %4, -2; and.b32 %8, %8, -2; and.b32 %12, %12, -2; and.b32 %16, %16, -2; and.b32 %20, %20, -2; and.b32 %24, %24, -2; and.b32 %26, %26, -2;"
                 : RW4(A[2 * B], 0), RW4(A[2 * B], 4), RW4(A[2 * B], 8), RW4(A[2 * B + 1], 0), RW4(A[2 * B + 1], 4), RW4(A[2 * B + 1], 8),
                   RW2(A[2 * B], 12), RW2(A[2 * B + 1], 12)
                 : "l"(src), "r"(lane), "r"(tag)
                 : "memory");
}
__device__ __forceinline__ void st_async4(uint32_t a, uint32_t x, uint32_t y, uint32_t z, uint32_t w, uint32_t bar) {
    asm volatile("st.async.weak.shared::cluster.mbarrier::complete_tx::bytes.v4.b32 [%0], {%1,%2,%3,%4}, [%5];" ::"r"(a), "r"(x), "r"(y), "r"(z), "r"(w), "r"(bar) : "memory");
}
__device__ __forceinline__ uint32_t mapa(uint32_t a, uint32_t cta) { uint32_t r; asm("mapa.shared::cluster.u32 %0, %1, %2;" : "=r"(r) : "r"(a), "r"(cta)); return r; }
__device__ __forceinline__ void stat_load(uint32_t* v, const uint4* p) { ld_pkt<0>(v, p); ld_pkt<512>(v + 4, p); }
__device__ __forceinline__ void stat_check(uint32_t* v, const uint4* p, uint32_t tag) {
    asm volatile("{ .reg .pred p; .reg .b32 n, t; .reg .b128 q; mov.u32 n, 0;\n LP:\n"
                 "xor.b32 t, %3, %9;\n" CHK("%7", "%9") VOTE_OK
                 LDP("%0", "%1", "%2", "%3", "%8", "0") LDP("%4", "%5", "%6", "%7", "%8", "8192") SPIN_TAIL("4")
                 : RW4(v, 0), RW4(v, 4) : "l"(p), "r"(tag) : "memory");
}
__device__ __forceinline__ uint32_t x_bits(const uint32_t* X) {
    uint32_t r;
    asm volatile("{ .reg .b32 a, b; prmt.b32 a, %1, %2, 0x0040; prmt.b32 b, %3, %4, 0x0040; prmt.b32 %0, a, b, 0x5410; }" : "=r"(r) : "r"(X[0]), "r"(X[4]), "r"(X[8]), "r"(X[12]));
    return r;
}
template <int O>
__device__ __forceinline__ void slice_load(uint32_t* v, const uint4* p, int lane) {
    ld_pkt<O>(v, p); ld_pkt<O + 32>(v + 4, p); ld_pkt<O + 64>(v + 8, p);
    asm volatile("{ .reg .b64 h;\n" LDH("%0", "%1", "%2", "%3") "}" : "=r"(v[12]), "=r"(v[13]) : "l"((const char*)p - lane * 8), "n"(16 * (O + 96)) : "memory");
}
template <int O>
__device__ __forceinline__ void slice_check(uint32_t* v, const uint4* p, int lane, uint32_t tag) {
    asm volatile("{ .reg .pred p; .reg .b32 n, t; .reg .b128 q; .reg .b64 h; mov.u32 n, 0;\n LP:\n"
                 "xor.b32 t, %0, %16;\n" CHK("%4", "%16") CHK("%8", "%16") CHK("%12", "%16") VOTE_OK
                 LDP("%0", "%1", "%2", "%3", "%14", "%17") LDP("%4", "%5", "%6", "%7", "%14", "%18") LDP("%8", "%9", "%10", "%11", "%14", "%19")
                 LDH("%12", "%13", "%15", "%20") SPIN_TAIL("5")
                 : RW4(v, 0), RW4(v, 4), RW4(v, 8), RW2(v, 12)
                 : "l"(p), "l"((const char*)p - lane * 8), "r"(tag), "n"(16 * O), "n"(16 * (O + 32)), "n"(16 * (O + 64)), "n"(16 * (O + 96))
                 : "memory");
}
__device__ __forceinline__ void x_fix(uint32_t* X, uint32_t bits) {
    X[0] = __byte_perm(X[0], bits, 0x3214); X[4] = __byte_perm(X[4], bits, 0x3215); X[8] = __byte_perm(X[8], bits, 0x3216); X[12] = __byte_perm(X[12], bits, 0x3217);
}
__device__ __forceinline__ void sts4(uint32_t a, uint32_t x, uint32_t y, uint32_t z, uint32_t w) {
    asm volatile("st.shared.v4.u32 [%0], {%1,%2,%3,%4};" ::"r"(a), "r"(x), "r"(y), "r"(z), "r"(w) : "memory");
}
__device__ __forceinline__ void lds4(uint32_t* v, uint32_t a) {
    asm volatile("ld.shared.v4.u32 {%0,%1,%2,%3}, [%4];" : "=r"(v[0]), "=r"(v[1]), "=r"(v[2]), "=r"(v[3]) : "r"(a) : "memory");
}
struct LnCoef { uint32_t hi, lo, sh; };
__device__ __forceinline__ LnCoef ln_coef(float sum, float sq) {
    sum += __shfl_xor_sync(0xffffffffu, sum, 1); sq += __shfl_xor_sync(0xffffffffu, sq, 1);
    sum += __shfl_xor_sync(0xffffffffu, sum, 2); sq += __shfl_xor_sync(0xffffffffu, sq, 2);
    const float mean = sum * (1.f / 448.f);
    const float var = fmaxf(fmaf(-mean, mean, sq * (1.f / 448.f)), 0.f);
    const float sc = rsqrtf(var + 1e-5f);
    LnCoef r;
    r.hi = pack2(sc, sc);
    const float lo = sc - bf_lo(r.hi), sh = -mean * sc;
    r.lo = pack2(lo, lo);
    r.sh = pack2(sh, sh);
    return r;
}
template <int B>
__device__ __forceinline__ void normalize(uint32_t (&A)[8][14], const LnCoef& c0, const LnCoef& c1) {
#pragma unroll
    for (int s = 2 * B; s < 2 * B + 2; s++)
#pragma unroll
        for (int i = 0; i < 14; i++) {
            const LnCoef& k = (i & 1) ? c1 : c0;
            asm("{ .reg .b32 t; fma.rn.bf16x2 t, %0, %2, %3; fma.rn.bf16x2 %0, %0, %1, t; }" : "+r"(A[s][i]) : "r"(k.hi), "r"(k.lo), "r"(k.sh));
        }
}
__device__ __forceinline__ void slice_stats(const uint32_t* w, float* st) {
    float a = 0.f, b = 0.f, p = 0.f, q = 0.f;
#pragma unroll
    for (int i = 0; i < 7; i++) {
        const float e0 = bf_lo(w[2 * i]), e1 = bf_hi(w[2 * i]), e2 = bf_lo(w[2 * i + 1]), e3 = bf_hi(w[2 * i + 1]);
        a += e0 + e1; b += e2 + e3;
        p = fmaf(e0, e0, p); p = fmaf(e1, e1, p); q = fmaf(e2, e2, q); q = fmaf(e3, e3, q);
    }
    a += __shfl_xor_sync(0xffffffffu, a, 1); p += __shfl_xor_sync(0xffffffffu, p, 1); b += __shfl_xor_sync(0xffffffffu, b, 1); q += __shfl_xor_sync(0xffffffffu, q, 1);
    a += __shfl_xor_sync(0xffffffffu, a, 2); p += __shfl_xor_sync(0xffffffffu, p, 2); b += __shfl_xor_sync(0xffffffffu, b, 2); q += __shfl_xor_sync(0xffffffffu, q, 2);
    st[0] = a; st[1] = p; st[2] = b; st[3] = q;
}
__device__ __forceinline__ void dual_softmax(const float* p, uint32_t* out) {
    constexpr float L = 1.4426950408889634f;
#pragma unroll
    for (int r = 0; r < 2; r++) {
        float mx = fmaxf(p[2 * r], p[2 * r + 1]), mn = fminf(p[2 * r], p[2 * r + 1]);
#pragma unroll
        for (int i = 1; i < 7; i++) {
            mx = fmaxf(mx, fmaxf(p[4 * i + 2 * r], p[4 * i + 2 * r + 1]));
            mn = fminf(mn, fminf(p[4 * i + 2 * r], p[4 * i + 2 * r + 1]));
        }
        mx = fmaxf(mx, __shfl_xor_sync(0xffffffffu, mx, 1));
        mn = fminf(mn, __shfl_xor_sync(0xffffffffu, mn, 1));
        const float bx = -mx * L, bn = mn * L;
        float ep[14], en[14], sp = 0.f, sn = 0.f;
#pragma unroll
        for (int i = 0; i < 14; i++) {
            const float v = p[4 * (i >> 1) + 2 * r + (i & 1)];
            ep[i] = ex2(fmaf(v, L, bx));
            en[i] = ex2(fmaf(v, -L, bn));
            sp += ep[i]; sn += en[i];
        }
        sp += __shfl_xor_sync(0xffffffffu, sp, 1);
        sn += __shfl_xor_sync(0xffffffffu, sn, 1);
        const float ip = rcp(sp), in = rcp(sn);
#pragma unroll
        for (int i = 0; i < 7; i++) {
            out[4 * i + r] = pack2(ep[2 * i] * ip, ep[2 * i + 1] * ip);
            out[4 * i + 2 + r] = pack2(en[2 * i] * in, en[2 * i + 1] * in);
        }
    }
}
__device__ __forceinline__ float geglu(float g, float u) {
    const float t = tanh_hw(g * fmaf(g * g, 0.7978845608028654f * 0.044715f, 0.7978845608028654f));
    const float gu = g * u;
    return fmaf(t, gu, gu);
}
__device__ __forceinline__ void phi_gemm(const float* t, float* p) {
    uint32_t w[14];
#pragma unroll
    for (int i = 0; i < 14; i++) w[i] = pack2(t[2 * i], t[2 * i + 1]);
    const uint64_t db = BASE128(OFF_WPHI, 16, 0);
    wg_fence();
    mma_rs56<0, 0>(p, w[0], w[1], w[2], w[3], 0, db);
    mma_rs56<0, 2>(p, w[4], w[5], w[6], w[7], 1, db);
    mma_rs56<0, 4>(p, w[8], w[9], w[10], w[11], 1, db);
    mma_rs56<0, 6>(p, w[12], w[13], 0u, 0u, 1, db);
    wg_commit();
    wg_wait<0>();
}

}

#define BAR(i) (bars + 8 * (i))
#define R_WAIT() mbar_wait(BAR(slot), ph)
#define WSUM(i)
#define R_ADJ (slot * (STAGE >> 4))
#define R_NEXT() do { eb2 = eb1; eb1 = BAR(B_EMPTY + slot); if (++slot == NST) { slot = 0; ph ^= 1; } } while (0)
#define R_RELEASE(k) do { if (lane == 0) mbar_arrive((k) == 1 ? eb1 : eb2); } while (0)
#define PUSH_BEGIN() do { mbar_wait(BAR(B_ACK + wgi), ackph); ackph ^= 1; } while (0)
#define PUSH_ACK() do { __syncwarp(); if (lane == 0) asm volatile("mbarrier.arrive.shared::cluster.b64 _, [%0];" ::"r"(mapa(BAR(B_ACK + wgi), hr ^ 1)) : "memory"); } while (0)

__global__ void __cluster_dims__(2, 1, 1) __launch_bounds__(384, 1)
fused_kernel(Scratch* const sc, const __nv_bfloat16* __restrict__ x_in, const __nv_bfloat16* __restrict__ w_phi, const int trips,
             const __nv_bfloat16* __restrict__ wg, const __nv_bfloat16* __restrict__ wu, const __nv_bfloat16* __restrict__ wd,
             const __grid_constant__ Maps maps) {
    extern __shared__ __align__(1024) unsigned char smem_raw[];
    const uint32_t sb = s2u(smem_raw);
    const uint32_t bars = sb + OFF_BAR;
    const int wgi = __shfl_sync(0xffffffffu, threadIdx.x >> 7, 0);
    const int hr = blockIdx.x & 1, ck = blockIdx.x >> 1;
    const int gp = (ck - 4) & 7, q7 = ((ck - 36) * 37) >> 8;
    const int pr = __shfl_sync(0xffffffffu, ck < 4 ? ck : (ck < 36 ? (ck - 4) >> 3 : q7), 0);
    const int tile = __shfl_sync(0xffffffffu, ck < 4 ? 0 : (ck < 36 ? (gp ? 2 * gp : 1) : 2 * (ck - 36 - 7 * q7) + 3), 0);
    const int sl = 2 * pr + hr;
    STAMP(0);
    GSTAMP(60);
    if (threadIdx.x == 256) {
#pragma unroll
        for (int i = 0; i < NST; i++) mbar_init(BAR(i), 1);
        asm volatile("fence.mbarrier_init.release.cluster;" ::: "memory");
    }
    if (threadIdx.x == 288) {
        if ((sb & 0x3FFFF) != SB0) asm volatile("trap;");
#pragma unroll
        for (int i = NST; i < B_COUNT; i++) mbar_init(BAR(i), i >= B_ACK ? 4 : (i < B_RECV || i == B_LATE ? 8 : 1));
        asm volatile("fence.mbarrier_init.release.cluster;" ::: "memory");
    }
    __syncwarp();
    asm volatile("barrier.cluster.arrive.relaxed.aligned;" ::: "memory");

    if (wgi == 2) {
        asm volatile("setmaxnreg.dec.sync.aligned.u32 40;");
        const int t128 = fresh_tid() & 127, w = __shfl_sync(0xffffffffu, t128 >> 5, 0), lane = t128 & 31;
        uint32_t e0[2] = {0, 0}, e1[2] = {0, 0}, cw_target = 0;
        if (w == 0) {
#pragma unroll 1
            for (int n = 0; n < NST; n++) {
                const uint32_t dst = sb + n * STAGE, fb = BAR(n);
                asm volatile(ELECT "mbarrier.arrive.expect_tx.shared::cta.b64 _, [%0], %1; }" ::"r"(fb), "r"(n < 2 ? 2 * STAGE : STAGE) : "memory");
                if (n < 2) {
                    tma3x(sb + OFF_H + n * STAGE, &maps.x, tile * 128 + n * 64, fb);
                    tma3x(dst, &maps.x, tile * 128 + n * 64 + 32, fb);
                } else {
                    if (n == 3) mbar_wait(BAR(1), 0);
                    const int ra = 112 * (n - 2);
                    tma2d(dst, &maps.qkv, 448 + 56 * sl, ra, fb);
                    tma2d(dst + HALF, &maps.qkv, 896 + 56 * sl, ra, fb);
                }
            }
            asm volatile("barrier.cluster.wait.aligned;" ::: "memory");
            cw_target = (ld_word(g_cw + sl * 32) & ~15u) + 16;
#pragma unroll 1
            for (int k = 0; k < 2; k++) {
                const int n = t128 + 32 * k;
                int m = n - 2 - (n > PACK);
                const bool packed = m >= 30 ? (m < 38 || m >= 52) : m >= 22;
                if (m >= 30) m -= 30;
                if (n == PACK) m = tile < 8 ? tile : tile + 14;
                const int rot = n < 8 ? 0 : pr;
                const int ra = 112 * kblk(rot, m & 3), rb = 112 * kblk(rot, 2 * m & 3), rc = 112 * kblk(rot, (2 * m + 1) & 3);
                int kind = 0, m0, m1, c0, c1, r0, r1;
                if (m < 4) { m0 = m1 = 1; c0 = 448 + 56 * sl; c1 = c0 + 448; r0 = r1 = ra; }
                else if (m < 8) { m0 = m1 = m < 6 ? 1 : 2; c0 = c1 = 56 * sl; r0 = rb; r1 = rc; }
                else if (m < 20) { m0 = 3; m1 = 4; c0 = c1 = 224 * sl + 32 * hr + 64 * ((m - 8) >> 2); r0 = r1 = ra; }
                else if (m < 22) { kind = 2; m0 = 5; m1 = 6; c0 = c1 = 224 * sl + (hr ? 0 : 192); r0 = rb; r1 = rc; }
                else { m0 = m1 = 7; c0 = c1 = 56 * (2 * ((pr + (m >> 1) - 10) & 3) + hr); r0 = 224 * (sl ^ (m & 1)); r1 = r0 + 112; }
                if (packed) { kind = 1; r0 = sl * 16 + (m < 8 ? m : m - 14); r1 = 0; }
                e0[0] = e0[1]; e1[0] = e1[1];
                e0[1] = kind | (m0 << 2) | (m1 << 6) | (c0 << 10) | (c1 << 21);
                e1[1] = r0 | (r1 << 16);
            }
        } else {
            const int j = t128 - 32;
            asm volatile("barrier.cluster.wait.aligned;" ::: "memory");
            uint2 wv[7];
            const int k = j < 56 ? j : 55, hh = k >= 28;
#pragma unroll
            for (int i = 0; i < 7; i++) wv[i] = __ldg(reinterpret_cast<const uint2*>(w_phi + (sl * 56 + k) * 28) + i);
#pragma unroll 1
            for (int i = j; i < 7168 / 16; i += 96) sts4(sb + OFF_WPHI + i * 16, 0, 0, 0, 0);
            bar_sync(5, 96);
            if (j < 56) {
                uint32_t a4[4];
#pragma unroll
                for (int q = 0; q < 4; q++) a4[q] = sb + OFF_WPHI + (4 * hh + q) * 128 + ((((k >> 3) ^ (4 * hh + q)) & 7) << 4) + (k & 7) * 2;
                FOR14(const uint32_t v = (t & 1) ? wv[t >> 1].y : wv[t >> 1].x;
                      asm volatile("{ .reg .b16 l, h; mov.b32 {l, h}, %2; st.shared.u16 [%0+%3], l; st.shared.u16 [%1+%3], h; }"
                                   ::"r"(a4[t >= 7 ? 2 : 0]), "r"(a4[t >= 7 ? 3 : 1]), "r"(v), "n"((t % 7) * 1024) : "memory"));
            }
            __syncwarp();
            fence_async();
            bar_arrive(1, 224);
            bar_arrive(9, 224);
            if (w == 1) {
                mbar_wait(BAR(2), 0);
                mbar_wait(BAR(2), 1);
                const int b = blockIdx.x;
                asm volatile(ELECT "cp.async.bulk.prefetch.L2.global [%0], %1; }" ::"l"(wg + b * 6272), "r"(12544) : "memory");
                asm volatile(ELECT "cp.async.bulk.prefetch.L2.global [%0], %1; }" ::"l"(wu + b * 6272), "r"(12544) : "memory");
                asm volatile(ELECT "cp.async.bulk.prefetch.L2.global [%0], %1; }" ::"l"(wd + b * 6272), "r"(12544) : "memory");
            }
        }
        uint32_t kseq = ld_word(g_c1 + (sl * 8 * 16 + tile) * 32);
        int slot = 0, ph = 0, n = NST;
#pragma unroll 1
        for (int layer = 0; layer < 3; layer++) {
            if (w == 0) {
                const int nend = layer == 0 ? 11 : (layer == 1 ? 42 : 63);
#pragma unroll 1
                for (; n < nend; n++) {
                const uint32_t w0 = __shfl_sync(0xffffffffu, n < 32 ? e0[0] : e0[1], n & 31), w1 = __shfl_sync(0xffffffffu, n < 32 ? e1[0] : e1[1], n & 31);
                const uint32_t dst = sb + slot * STAGE, fb = BAR(n == PACK ? B_PACK : slot);
                const CUtensorMap* m0 = &maps.x + ((w0 >> 2) & 15);
                const CUtensorMap* m1 = &maps.x + ((w0 >> 6) & 15);
                const int c0 = (w0 >> 10) & 2047, c1 = w0 >> 21, r0 = w1 & 0xffff, r1 = w1 >> 16;
                if (n == 25) {
                    int it = 0;
                    uint32_t v;
                    do { asm volatile("ld.acquire.gpu.global.u32 %0, [%1];" : "=r"(v) : "l"(g_cw + sl * 32) : "memory"); } while ((int)(v - cw_target) < 0 && ++it < 0x400000);
                    asm volatile("fence.proxy.async.global;" ::: "memory");
                    __syncwarp();
                }
                mbar_wait(BAR(B_EMPTY + slot), ph);
                __syncwarp();
                asm volatile(ELECT "mbarrier.arrive.expect_tx.shared::cta.b64 _, [%0], %1; }" ::"r"(fb), "r"(STAGE) : "memory");
                if ((w0 & 3) == 0) {
                    tma2d(dst, m0, c0, r0, fb);
                    tma2d(dst + HALF, m1, c1, r1, fb);
                } else if (w0 & 1) {
                    asm volatile(ELECT "cp.async.bulk.shared::cluster.global.mbarrier::complete_tx::bytes [%0], [%1], %2, [%3]; }"
                                 ::"r"(dst), "l"(reinterpret_cast<const char*>(g_wp) + (size_t)r0 * STAGE), "r"(STAGE), "r"(fb) : "memory");
                } else {
                    tma2d(dst, m0, c0, r0, fb); tma2d(dst + 7168, m0, c0, r1, fb);
                    tma2d(dst + HALF, m1, c0, r0, fb); tma2d(dst + HALF + 7168, m1, c0, r1, fb);
                }
                if (n == PACK) asm volatile(ELECT "mbarrier.arrive.shared::cta.b64 _, [%0]; }" ::"r"(BAR(slot)) : "memory");
                if (++slot == NST) { slot = 0; ph ^= 1; }
                }
            } else if (w == 1 && layer == 1) {
                constexpr int ps = PACK % NST;
                mbar_wait(BAR(B_PACK), 0);
                asm volatile("{ .reg .pred e; elect.sync _|e, 0xffffffff;\n"
                             "@e cp.async.bulk.global.shared::cta.bulk_group [%0], [%1], %2;\n"
                             "@e cp.async.bulk.commit_group;\n"
                             "@e cp.async.bulk.wait_group.read 0;\n"
                             "@e mbarrier.arrive.shared::cta.b64 _, [%3], 8;\n"
                             "@e cp.async.bulk.wait_group 0;\n"
                             "@e fence.proxy.async.global;\n"
                             "@e red.release.gpu.global.add.u32 [%4], 1; }"
                             ::"l"(reinterpret_cast<char*>(g_wp) + (size_t)(sl * 16 + tile) * STAGE), "r"(sb + ps * STAGE), "r"(STAGE), "r"(BAR(B_EMPTY + ps)), "l"(g_cw + sl * 32) : "memory");
                __syncwarp();
            }
            if (layer < 2) {
            const uint32_t tag = layer ^ 1;
            kseq++;
            bar_sync(7, 384);
            ASTAMP(0);
            if (tile < 15) {
                const int sq = lane >> 3, pk = 8 * w + (lane & (tile == 14 ? 3 : 7));
                uint32_t v[16];
                if (layer == 0) poll_cnt(g_c1 + ((sl * 8 + (w >> 1) * 4 + (tile >> 2)) * 16 + (lane & 15)) * 32, kseq);
                ASTAMP(1);
                poll4_kv<32>(v, g_kv1 + ((sl * 16 + tile) * 16 + 4 * sq) * 32 + pk, tag);
#pragma unroll
                for (int k = 0; k < 4; k++) {
                    float lo = (bf_lo(v[k]) + bf_lo(v[4 + k])) + (bf_lo(v[8 + k]) + bf_lo(v[12 + k]));
                    float hi = (bf_hi(v[k]) + bf_hi(v[4 + k])) + (bf_hi(v[8 + k]) + bf_hi(v[12 + k]));
                    lo += __shfl_xor_sync(0xffffffffu, lo, 8); hi += __shfl_xor_sync(0xffffffffu, hi, 8);
                    lo += __shfl_xor_sync(0xffffffffu, lo, 16); hi += __shfl_xor_sync(0xffffffffu, hi, 16);
                    v[k] = pack2(lo, hi);
                }
                if (sq == 0) st_pkt<0>(g_kv2 + sl * 512 + 32 * tile + pk, settag(v[0], tag), v[1], v[2], v[3]);
            }
            ASTAMP(2);
            {
                const int item = t128 < 112 ? t128 : 112 + (t128 & 3), d = item >> 1;
                const int cc = t128 < 112 ? 2 * (d >= 28) + (item & 1) : item - 112;
                const int r = t128 < 112 ? d : 56 + (cc >> 1) + 2 * ((t128 - 112) >> 2);
                uint32_t ra = sb + OFF_KVB + r * 128 + 4 * cc, rx = (r & 7) << 4;
                asm volatile("" : "+r"(ra), "+r"(rx));
                FOR14(asm volatile("st.shared.u32 [%0+%2], %1;" ::"r"((ra ^ 8) + (((t & 7) << 4) ^ rx)), "r"(0), "n"((t >> 3) * 8192) : "memory"));
                uint32_t v[16];
                asm volatile("" : "+r"(ra), "+r"(rx));
                poll4_kv<8>(v, g_kv2 + sl * 512 + (item >> 3) * 32 + (item & 7), tag);
                FOR14(asm volatile("st.shared.u32 [%0+%2], %1;" ::"r"(ra + (((t & 7) << 4) ^ rx)), "r"(v[t < 7 ? t : t + 1]), "n"((t >> 3) * 8192) : "memory"));
                fence_async();
            }
            bar_arrive(3, 384);
            ASTAMP(3);
            }
        }
    } else {
        asm volatile("setmaxnreg.inc.sync.aligned.u32 232;");
        int lane = fresh_tid() & 31, prf = pr;
#define pr prf
#define g (lane >> 2)
#define c (lane & 3)
#define t128 (w * 32 + lane)
        const int wu = __shfl_sync(0xffffffffu, fresh_tid() >> 5, 0), w = wu & 3;
        const uint32_t xoff = __shfl_sync(0xffffffffu, (3 * PLANE + ((tile * 2 + wgi) * 8) * 512 + w * 128) * 16, 0);
        char* xu = reinterpret_cast<char*>(g_ex) + xoff;
#define FRESH() asm volatile("" : "+l"(xu), "+r"(lane), "+r"(prf))
#define xp0 (reinterpret_cast<uint4*>(xu) + lane)
        const uint32_t hbuf = sb + OFF_H + wgi * STAGE;
        uint32_t slot = 0, ph = 0, eb1 = 0, eb2 = 0, ackph = 0, rcvph = 0, gatph = 0, swp = 0;
        uint32_t ppid = 6;
#define cx(s) (reinterpret_cast<uint32_t*>(reinterpret_cast<uint4*>(xu) + PL(1) + 112 + (s) * 512))
#define stp (reinterpret_cast<uint4*>(xu) + g + PL(0) + 112)
        uint32_t seq = ld_word(cx(sl));
        uint32_t kseq = ld_word(g_c1 + ((sl * 8 + wu) * 16 + tile) * 32);
        uint32_t stag = ld_word(reinterpret_cast<const uint32_t*>(stp + sl * 512) + 3) & 1;
        asm volatile("barrier.cluster.wait.aligned;" ::: "memory");
        STAMP(1);
        uint32_t X[14];
        const uint32_t x0row = (w < 2 ? hbuf : sb + wgi * STAGE) + ((w & 1) * 16 + (lane & 15)) * 128;
        mbar_wait(BAR(wgi), 0);
        STAMP(51);
#pragma unroll
        for (int j = 0; j < 4; j++) {
            const int G = 7 * sl + min(2 * j + (lane >> 4), 6);
            uint32_t q2, q3;
            asm volatile("ldmatrix.sync.aligned.m8n8.x4.shared.b16 {%0,%1,%2,%3}, [%4];" : "=r"(X[4 * j]), "=r"(X[4 * j + 1]), "=r"(q2), "=r"(q3)
                         : "r"(x0row + (G >> 3) * 4096 + (((G ^ lane) & 7) << 4)) : "memory");
            if (j < 3) { X[(4 * j + 2) % 14] = q2; X[(4 * j + 3) % 14] = q3; }
        }
#define PUSH_SLICE(W)                                                                          \
    {                                                                                          \
        if (t128 == 0) mbar_expect_tx(BAR(B_RECV + wgi), 7168);                                \
        PUSH_BEGIN();                                                                          \
        const uint32_t ra = mapa(hbuf + 24576 + t128 * 16, hr ^ 1), rb = mapa(sb + OFF_XR + wgi * 3072, hr ^ 1), rbar = mapa(BAR(B_RECV + wgi), hr ^ 1); \
        st_async4(ra, W[0], W[1], W[2], W[3], rbar);                                           \
        st_async4(ra + 2048, W[4], W[5], W[6], W[7], rbar);                                    \
        st_async4(rb + t128 * 16, W[8], W[9], W[10], W[11], rbar);                             \
        asm volatile("st.async.weak.shared::cluster.mbarrier::complete_tx::bytes.v2.b32 [%0], {%1,%2}, [%3];" ::"r"(rb + 2048 + t128 * 8), "r"(W[12]), "r"(W[13]), "r"(rbar) : "memory"); \
    }
#define PULL_SLICE(W)                                                                          \
    {                                                                                          \
        uint32_t t0, t1;                                                                       \
        mbar_wait(BAR(B_RECV + wgi), rcvph);                                                   \
        rcvph ^= 1;                                                                            \
        lds4(&A[1][0], hbuf + 24576 + t128 * 16);                                              \
        lds4(&A[1][4], hbuf + 26624 + t128 * 16);                                              \
        lds4(&A[1][8], sb + OFF_XR + wgi * 3072 + t128 * 16);                                  \
        asm volatile("ld.shared.v2.u32 {%0,%1}, [%2];" : "=r"(t0), "=r"(t1) : "r"(sb + OFF_XR + wgi * 3072 + 2048 + t128 * 8) : "memory"); \
        _Pragma("unroll") for (int i = 0; i < 12; i++) A[0][i] = (i & 3) ? W[i] : W[i] & ~1u;  \
        A[1][0] &= ~1u; A[1][4] &= ~1u; A[1][8] &= ~1u;                                        \
        A[0][12] = (hr ? t0 : W[12]) & ~1u; A[0][13] = hr ? t1 : W[13];                        \
        A[1][12] = (hr ? W[12] : t0) & ~1u; A[1][13] = hr ? W[13] : t1;                        \
        asm volatile("" : RW4(A[0], 0), RW4(A[0], 4), RW4(A[0], 8), RW2(A[0], 12), RW4(A[1], 0), RW4(A[1], 4), RW4(A[1], 8), RW2(A[1], 12)); \
        swp = hr * 448;                                                                        \
    }
#define SWB(b, t, db, sh) ((b) == 0 && (t) < 6 ? ((t) < 3 ? db##p : db##m) : db)
#define DECL_DB(b, MK, lbo, sh) const uint64_t db = MK(0, lbo, R_ADJ), dbp = (b) == 0 ? MK(0, lbo, R_ADJ + (swp >> (sh))) : db, dbm = (b) == 0 ? MK(0, lbo, R_ADJ - (swp >> (sh))) : db;
#define PPB 2
#define PP_WAIT() if (wgi == 1) { bar_sync(ppid, 256); ppid ^= 14; }
#define PP_GO() if (wgi == 0) { bar_arrive(ppid, 256); ppid ^= 14; }
#define GAT_DST(B, s2) ((B) == 1 ? hbuf + w * 3584 + (s2) * 1792 : ((s2) ? sb + OFF_KVB + wgi * 8192 : hbuf + 14336) + w * 1792)
#define GAT_ISSUE(B, base)                                                                     \
    {                                                                                          \
        const char* gs = xu + ((base) + kblk(pr, B) * 1024) * 16;                              \
        asm volatile("{ .reg .pred e; elect.sync _|e, 0xffffffff;\n"                           \
                     "@e mbarrier.arrive.expect_tx.shared::cta.b64 _, [%3], 3584;\n"           \
                     "@e cp.async.bulk.shared::cluster.global.mbarrier::complete_tx::bytes [%0], [%2], 1792, [%3];\n" \
                     "@e cp.async.bulk.shared::cluster.global.mbarrier::complete_tx::bytes [%1], [%2+8192], 1792, [%3]; }" \
                     ::"r"(GAT_DST(B, 0)), "r"(GAT_DST(B, 1)), "l"(gs), "r"(BAR(B_GAT + wu * 2 + ((B) >> 1))) : "memory"); \
        __syncwarp();                                                                          \
    }
#define GAT_FETCH(B)                                                                           \
    {                                                                                          \
        mbar_wait(BAR(B_GAT + wu * 2 + ((B) >> 1)), (gatph >> (B)) & 1);                          \
        gatph ^= 1 << (B);                                                                     \
        _Pragma("unroll") for (int s2 = 0; s2 < 2; s2++) {                                     \
            const uint32_t ga = GAT_DST(B, s2) + lane * 16;                                    \
            lds4(&A[2 * (B) + s2][0], ga); lds4(&A[2 * (B) + s2][4], ga + 512); lds4(&A[2 * (B) + s2][8], ga + 1024); \
            asm volatile("ld.shared.v2.u32 {%0,%1}, [%2];" : "=r"(A[2 * (B) + s2][12]), "=r"(A[2 * (B) + s2][13]) : "r"(ga - lane * 8 + 1536) : "memory"); \
        }                                                                                      \
    }
#define LATE_ARRIVE() do { if (lane == 0) mbar_arrive(BAR(B_LATE)); } while (0)
#define LATE_WAIT() do { mbar_wait(BAR(B_LATE), gatph & 1); gatph ^= 1; } while (0)
#define PT 3
#define PREP(b, t, remote)                                                                     \
    if constexpr ((b) < 3 && (t) == PT) {                                                      \
        wg_commit();                                                                           \
        STAMP(74 + 6 * (step & 1) + 2 * (b));                                                  \
        if (remote) {                                                                          \
            if constexpr ((b) == 0) { blk_load<2>(A, BLK(xsrc, 2), lane); GAT_FETCH(1) }       \
            blk_check<((b) + 1) & 3>(A, BLK(xsrc, (b) + 1), lane, xtag);                       \
            if constexpr ((b) == 0) blk_load<3>(A, BLK(xsrc, 3), lane);                        \
        }                                                                                      \
        STAMP(75 + 6 * (step & 1) + 2 * (b));                                                  \
        normalize<((b) + 1) & 3>(A, k0, k1);                                                   \
        asm volatile("" : RW4(A[(2 * (b) + 2) & 7], 0), RW4(A[(2 * (b) + 2) & 7], 4), RW4(A[(2 * (b) + 2) & 7], 8), RW2(A[(2 * (b) + 2) & 7], 12), \
                          RW4(A[(2 * (b) + 3) & 7], 0), RW4(A[(2 * (b) + 3) & 7], 4), RW4(A[(2 * (b) + 3) & 7], 8), RW2(A[(2 * (b) + 3) & 7], 12)); \
        wg_fence();                                                                            \
    }
#define X0_BLOCK(b)                                                                            \
    { const int rr = lane & 7, hi = lane >> 4;                                                 \
    const uint32_t rowa = (w < 2 ? hbuf : sb + wgi * STAGE) + ((w & 1) * 16 + (lane & 15)) * 128; \
    FOR7(constexpr int G = 14 * (b) + (t < 3 ? 2 * t : (t < 6 ? 2 * t + 1 : 6));               \
         uint32_t q0, q1, q2, q3;                                                              \
         const uint32_t ad = t < 6 ? rowa + (((((G & 7) + hi) ^ rr) & 7) << 4) + ((G & 7) == 7 ? hi * 4096 : 0) : rowa + ((G + 7 * hi) >> 3) * 4096 + ((((G + 7 * hi) ^ rr) & 7) << 4); \
         asm volatile("ldmatrix.sync.aligned.m8n8.x4.shared.b16 {%0,%1,%2,%3}, [%4+%5];" : "=r"(q0), "=r"(q1), "=r"(q2), "=r"(q3) \
                      : "r"(ad), "n"(t < 6 ? (G >> 3) * 4096 : 0) : "memory");                 \
         if (t < 3) { A[2 * (b)][4 * t] = q0; A[2 * (b)][4 * t + 1] = q1; A[2 * (b)][4 * t + 2] = q2; A[2 * (b)][4 * t + 3] = q3; } \
         else if (t < 6) { A[2 * (b) + 1][(4 * t - 12) & 15] = q0; A[2 * (b) + 1][((4 * t - 12) & 15) + 1] = q1; A[2 * (b) + 1][((4 * t - 12) & 15) + 2] = q2; A[2 * (b) + 1][((4 * t - 12) & 15) + 3] = q3; } \
         else { A[2 * (b)][12] = q0; A[2 * (b)][13] = q1; A[2 * (b) + 1][12] = q2; A[2 * (b) + 1][13] = q3; }); }
#define BLK(base, b) ((base) + kblk(pr, b) * 1024)

#pragma unroll 1
        for (int step = 0; step < 4; step++) {
            FRESH();
            const uint32_t tag = (step >> 1) ^ 1;
            const int so = (step >> 1) * 24 + (step & 1) * 12;
            (void)so;
            uint32_t A[8][14];
            uint4* const xsrc = xp0 + ((step & 1) ? PL(2) : PL(0));
            const uint32_t xtag = (step & 1) ? tag : ((seq >> 3) & 1) ^ 1;
            uint32_t xbits;
            {
                float st[4];
                slice_stats(X, st);
                stag ^= 1;
                xbits = x_bits(X);
                tag_slice(X, xtag);
                if (step) send_slice<0>(xsrc + sl * 512, lane, X);
                if (c == 0) st_pkt<0>(stp + sl * 512, __float_as_uint(st[0]), __float_as_uint(st[1]), __float_as_uint(st[2]), settag(__float_as_uint(st[3]), stag));
            }
            STAMP(2 + so);
            uint32_t sv[8];
            if (step == 0) {
                X0_BLOCK(0) X0_BLOCK(1) X0_BLOCK(2) X0_BLOCK(3)
                mbar_wait(BAR(wgi ^ 1), 0);
                R_NEXT();
                R_NEXT();
                R_RELEASE(2);
                stat_load(sv, stp + c * 1024);
                stat_check(sv, stp + c * 1024, stag);
                STAMP(52 + step);
            } else {
                kill<14>(A[2]); kill<14>(A[3]); kill<14>(A[4]); kill<14>(A[5]); kill<14>(A[6]); kill<14>(A[7]);
                PUSH_SLICE(X)
                stat_load(sv, stp + c * 1024);
                PULL_SLICE(X)
                stat_check(sv, stp + c * 1024, stag);
                STAMP(52 + step);
                GAT_ISSUE(1, (step & 1) ? PL(2) : PL(0))
            }
            LnCoef k0, k1;
            {
                k0 = ln_coef(__uint_as_float(sv[0]) + __uint_as_float(sv[4]), __uint_as_float(sv[1]) + __uint_as_float(sv[5]));
                k1 = ln_coef(__uint_as_float(sv[2]) + __uint_as_float(sv[6]), __uint_as_float(sv[3] & ~1u) + __uint_as_float(sv[7] & ~1u));
            }
            STAMP(3 + so);
            GSTAMP(70 + step);

            if ((step & 1) == 0) {
                float tq[28];
                {
                    float av[28];
#define KV_BLOCK(b)                                                                           \
    if ((b) == 1) R_RELEASE(2);                                                               \
    if ((b) == 2) { PUSH_ACK(); wg_wait<2>(); R_RELEASE(2); }                                 \
    R_WAIT();                                                                                 \
    if ((b) == PPK) { PP_WAIT() }                                                             \
    { DECL_DB(b, BASE128, 16, 0)                                                              \
    wg_fence();                                                                               \
    FOR7(mma_rs56<1, D128(0, t)>(tq, AQ(A, b, t), (b) + t > 0, SWB(b, t, db, 0));             \
         mma_rs56<1, D128(HALF, t)>(av, AQ(A, b, t), (b) + t > 0, SWB(b, t, db, 0));          \
         PREP(b, t, step)); }                                                                 \
    wg_commit();                                                                              \
    if ((b) == 3 && PPK < 4) { PP_GO() }                                                      \
    R_NEXT();
                    normalize<0>(A, k0, k1);
                    KV_BLOCK(0) KV_BLOCK(1) KV_BLOCK(2) KV_BLOCK(3)
                    wg_wait<0>();
                    if (lane < 3) mbar_arrive(BAR(B_EMPTY + (slot + NST - 1 - lane) % NST));
                    STAMP(4 + so);
                    WSUM(80 + 7 * (step >> 1));
                    const int m = lane >> 3, rr = lane & 7;
                    const uint32_t rowa = hbuf + 16384 + (w * 16 + rr + 8 * (m & 1)) * 128;
                    const uint32_t one = c == 0 ? 0x00003f80u : 0u;
                    if (step == 0) { bar_sync(wgi ? 9 : 1, 224); }
#pragma unroll
                    for (int j = 0; j < 4; j++) {
                        const uint32_t a = rowa + (((2 * j + (m >> 1)) ^ rr) << 4);
                        if (j < 3) stsm4(a, pack2(av[8 * j], av[8 * j + 1]), pack2(av[8 * j + 2], av[8 * j + 3]), pack2(av[8 * j + 4], av[8 * j + 5]), pack2(av[8 * j + 6], av[8 * j + 7]));
                        else stsm4(a, pack2(av[24], av[25]), pack2(av[26], av[27]), one, one);
                    }
                }
                uint32_t PH[28];
                int it = 1;
#pragma unroll 1
                do {
                    float pp[28];
                    phi_gemm(tq, pp);
                    dual_softmax(pp, PH);
                    if (((trips >> (it + 1)) & 1) == 0) continue;
                    {
                        const int m = lane >> 3, rr = lane & 7;
                        const uint32_t rowa = hbuf + (w * 16 + rr + 8 * (m & 1)) * 128;
#pragma unroll
                        for (int j = 0; j < 7; j++) {
                            const int cg = 2 * j + (m >> 1), hi = cg >= 7;
                            stsm4(rowa + hi * 8192 + (((cg - 7 * hi) ^ rr) << 4), PH[4 * j], PH[4 * j + 1], PH[4 * j + 2], PH[4 * j + 3]);
                        }
                    }
                    fence_async();
                    STAMP(5 + so);
#define Q_STAGE(b0)                                                                           \
    R_WAIT();                                                                                 \
    { DECL_DB(b0, BASE128, 16, 0)                                                             \
    wg_fence();                                                                               \
    FOR7(mma_rs56<1, D128(0, t)>(tq, AQ(A, b0, t), (b0) + t > 0, SWB(b0, t, db, 0)));         \
    FOR7(mma_rs56<1, D128(HALF, t)>(tq, AQ(A, (b0) + 1, t), 1, db)); }                        \
    wg_commit();                                                                              \
    R_NEXT();
                    if (QE && wgi == 0) { kill<28>(tq); Q_STAGE(0) Q_STAGE(2) wg_wait<1>(); R_RELEASE(2); wg_wait<0>(); R_RELEASE(1); }
                    bar_sync(2, 256);
                    float kv[28];
                    const uint64_t da = BASE128(OFF_H + 16384, 16, 0), dbk = BASE128(OFF_H, 16, wgi * 512);
                    wg_fence();
                    FOR8(constexpr uint64_t o = ((t >> 2) * STAGE + (t & 3) * 2048) >> 4; mma_ss56_tt<o, o>(kv, t > 0, da, dbk));
                    wg_commit();
                    wg_wait<0>();
#pragma unroll
                    for (int hf = 0; hf < 2; hf++) {
                        const int d = 16 * w + g + 8 * hf;
                        if ((d < 56 && (d >= 28) == (c >= 2)) || d == 56) {
                            const int item = d < 56 ? 2 * d + (c & 1) : 112 + c;
                            uint4* dst = g_kv1 + ((sl * 16 + (item >> 3)) * 16 + tile) * 32 + wgi * 16 + (item & 7);
#define KVW(i) pack2(kv[4 * (i) + 2 * hf], kv[4 * (i) + 2 * hf + 1])
                            st_pkt<0>(dst, settag(KVW(0), tag), KVW(1), KVW(2), KVW(3));
                            st_pkt<8>(dst, settag(KVW(4), tag), KVW(5), KVW(6), 0u);
                        }
                    }
                    __syncwarp();
                    kseq++;
                    if (lane == 0) st_word(g_c1 + ((sl * 8 + wu) * 16 + tile) * 32, kseq);
                    bar_arrive(7, 384);
                    STAMP(6 + so);
                    if (!QE || wgi == 1) { kill<28>(tq); Q_STAGE(0) Q_STAGE(2) wg_wait<1>(); R_RELEASE(2); wg_wait<0>(); R_RELEASE(1); }
                    STAMP(7 + so);
                    kill<28>(PH);
                } while (((trips >> (++it)) & 1));
                STAMP(8 + so);
                FRESH();
                if (step) {
                    slice_load<PL(0)>(X, xp0 + sl * 512, lane);
                } else {
                    const uint32_t* xp = reinterpret_cast<const uint32_t*>(x_in + (size_t)(tile * 128 + wu * 16 + g) * 448 + 56 * sl + 2 * c);
#pragma unroll
                    for (int i = 0; i < 7; i++) { X[2 * i] = __ldg(xp + 4 * i); X[2 * i + 1] = __ldg(xp + 4 * i + 8 * 224); }
                }
                bar_sync(3, 384);
                STAMP(9 + so);
                const uint4* const osrc = xp0 + PL(1);
                {
                    float nm[32];
                    const uint64_t db = BASE128(OFF_KVB, 16, 0);
                    wg_fence();
                    FOR7(mma_rs64<0, ((t >> 2) * 8192 + (t & 3) * 32) / 16>(nm, PH[4 * t], PH[4 * t + 1], PH[4 * t + 2], PH[4 * t + 3], t > 0, db));
                    wg_commit();
                    wg_wait<0>();
                    LATE_ARRIVE();
                    const float i00 = rcp(nm[28] + 1e-6f), i01 = rcp(nm[29] + 1e-6f), i10 = rcp(nm[30] + 1e-6f), i11 = rcp(nm[31] + 1e-6f);
                    const float m0 = c >= 2 ? i01 : i00, m1 = c >= 2 ? i11 : i10;
                    uint32_t O[14];
#pragma unroll
                    for (int i = 0; i < 7; i++) {
                        const float f0 = i < 3 ? i00 : (i > 3 ? i01 : m0), f1 = i < 3 ? i10 : (i > 3 ? i11 : m1);
                        O[2 * i] = pack2(nm[4 * i] * f0, nm[4 * i + 1] * f0);
                        O[2 * i + 1] = pack2(nm[4 * i + 2] * f1, nm[4 * i + 3] * f1);
                    }
                    if (OST) { PP_WAIT() }
                    tag_slice(O, tag);
                    send_slice<PL(1)>(xp0 + sl * 512, lane, O);
                    seq++;
                    if (lane == 0) st_word(cx(sl), seq);
                    STAMP(10 + so);
                    PUSH_SLICE(O)
                    if (OST == 1) { PP_GO() }
                    const uint32_t cv = ld_word(cx(lane & 7));
                    PULL_SLICE(O)
                    LATE_WAIT();
                    check_cnt(cv, cx(lane & 7), seq);
                    if (OST == 2) { PP_GO() }
                    STAMP(56 + (step >> 1));
                    GAT_ISSUE(1, PL(1))
                    GAT_ISSUE(3, PL(1))
                    blk_load<2>(A, BLK(osrc, 2), lane);
                }
                float ao[28];
#define WO_BLOCK(b)                                                                           \
    if ((b) > 0) blk_check<b>(A, BLK(osrc, b), lane, tag);                                    \
    if (((b) & 1) == 0) R_WAIT();                                                             \
    { DECL_DB(b, BASE128, 16, 0)                                                              \
    wg_fence();                                                                               \
    FOR7(mma_rs56<1, D128(((b) & 1) * HALF, t)>(ao, AQ(A, b, t), (b) + t > 0, SWB(b, t, db, 0))); } \
    wg_commit();                                                                              \
    if ((b) & 1) R_NEXT();
                WO_BLOCK(0)
                STAMP(11 + so);
                GAT_FETCH(1)
                WO_BLOCK(1)
                WO_BLOCK(2)
                GAT_FETCH(3)
                WO_BLOCK(3)
                PUSH_ACK();
                wg_wait<0>();
                R_RELEASE(2);
                STAMP(12 + so);
                WSUM(86 + 7 * (step >> 1));
                x_fix(X, xbits);
#pragma unroll
                for (int i = 0; i < 14; i++) X[i] = pack2(bf_lo(X[i]) + ao[2 * i], bf_hi(X[i]) + ao[2 * i + 1]);
            } else {
                uint32_t H[56];
                float ag[64];
#define F1_EPI(dst, ng, ag)                                                                    \
    _Pragma("unroll") for (int i = 0; i < 2 * (ng); i++)                                       \
        (dst)[i] = pack2(geglu(ag[2 * i], ag[4 * (ng) + 2 * i]), geglu(ag[2 * i + 1], ag[4 * (ng) + 2 * i + 1]));
#define H_PUSH(h0, off) st_async4(rem_h + (off), H[h0], H[(h0) + 1], H[(h0) + 2], H[(h0) + 3], mapa(BAR(B_RECV2 + wgi), hr ^ 1));
#define F1_BLOCK(b, first)                                                                     \
    if ((first) && (b) == 1) R_RELEASE(2);                                                     \
    if ((first) && (b) == 2) PUSH_ACK();                                                       \
    R_WAIT();                                                                                  \
    if ((b) == ((first) ? PPF : PPB)) { PP_WAIT() }                                            \
    { DECL_DB(b, BASE128, HALF, 0)                                                             \
    wg_fence();                                                                                \
    FOR7(mma_rs128<1, D128(0, t)>(ag, AQ(A, b, t), (b) + t > 0, SWB(b, t, db, 0));             \
         if constexpr (first) { PREP(b, t, true) }); }                                         \
    wg_commit();                                                                               \
    if ((b) == 3) { PP_GO() }                                                                  \
    if ((b) > 0) { wg_wait<1>(); R_RELEASE(1); }       \
    R_NEXT();
                normalize<0>(A, k0, k1);
                F1_BLOCK(0, true) F1_BLOCK(1, true) F1_BLOCK(2, true) F1_BLOCK(3, true)
                if (t128 == 0) { mbar_expect_tx(BAR(B_RECV + wgi), 16384); mbar_expect_tx(BAR(B_RECV2 + wgi), 12288); }
                PUSH_BEGIN();
                wg_wait<0>();
                R_RELEASE(1);
                int p = 0;
#pragma unroll 1
                do {
                    F1_EPI(H + 32, 8, ag)
                    STAMP(4 + p + so);
                    WSUM(81 + p + 7 * (step >> 1));
                    if (((trips >> (p + 1)) & 1) == 0) continue;
                    if (step == 1 && p == PKP) R_NEXT();
                    kill<64>(ag);
                    F1_BLOCK(0, false)
                    {
                        const uint32_t pk = (p ? hbuf + 16384 : sb + OFF_KVB + wgi * 8192) + w * 2048;
#pragma unroll
                        for (int k = 0; k < 4; k++) sts4(pk + k * 512 + lane * 16, H[32 + 4 * k], H[33 + 4 * k], H[34 + 4 * k], H[35 + 4 * k]);
                        fence_async();
                        __syncwarp();
                        asm volatile(ELECT "cp.async.bulk.shared::cluster.shared::cta.mbarrier::complete_tx::bytes [%0], [%1], 2048, [%2]; }"
                                     ::"r"(mapa(hbuf + p * 8192 + w * 2048, hr ^ 1)), "r"(pk), "r"(mapa(BAR(B_RECV + wgi), hr ^ 1)) : "memory");
                    }
                    F1_BLOCK(1, false) F1_BLOCK(2, false) F1_BLOCK(3, false)
                    wg_wait<0>();
                    R_RELEASE(1);
                    kill<16>(H + 32);
                } while (((trips >> (++p)) & 1));
#pragma unroll
                for (int k = 0; k < 4; k++) lds4(H + 16 + 4 * k, hbuf + 16384 + w * 2048 + k * 512 + lane * 16);
                __syncwarp();
                if (lane == 0) asm volatile("mbarrier.arrive.shared::cluster.b64 _, [%0];" ::"r"(mapa(BAR(B_ACK2 + wgi), hr ^ 1)) : "memory");
                const uint32_t rem_h = mapa(hbuf + w * 2048 + lane * 16, hr ^ 1);
#define F1_LAST(b0)                                                                            \
    R_WAIT();                                                                                  \
    if (b0) { PP_WAIT() }                                                                      \
    { DECL_DB(b0, BASE64, HALF, 1)                                                             \
    wg_fence();                                                                                \
    FOR7(mma_rs64<1, D64(0, t)>(al, AQ(A, b0, t), (b0) + t > 0, SWB(b0, t, db, 1)));           \
    FOR7(mma_rs64<1, D64(7168, t)>(al, AQ(A, (b0) + 1, t), 1, db)); }                          \
    wg_commit();                                                                               \
    if (b0) { PP_GO() }                                                                        \
    R_NEXT();
                float al[32];
                F1_LAST(0)
                mbar_wait(BAR(B_RECV + wgi), rcvph);
                rcvph ^= 1;
                mbar_wait(BAR(B_ACK2 + wgi), step >> 1);
                H_PUSH(32, 16384) H_PUSH(36, 16896)
                F1_LAST(2)
                H_PUSH(40, 17408) H_PUSH(44, 17920)
                wg_wait<1>();
                R_RELEASE(2);
                wg_wait<0>();
                R_RELEASE(1);
                uint32_t HP[56];
#pragma unroll
                for (int k = 0; k < 4; k++) lds4(H + 4 * k, sb + OFF_KVB + wgi * 8192 + w * 2048 + k * 512 + lane * 16);
#pragma unroll
                for (int t = 0; t < 8; t++) lds4(HP + 4 * t, hbuf + (t >> 2) * 8192 + w * 2048 + (t & 3) * 512 + lane * 16);
                F1_EPI(H + 48, 4, al)
                H_PUSH(48, 24576 - w * 1024) H_PUSH(52, 25088 - w * 1024)
                STAMP(7 + so);
                WSUM(84 + 7 * (step >> 1));
                FRESH();
                float acc[28];
                const uint32_t roA = hr ? 256u : 0u, roB = hr ? (uint32_t)-1536 : 0u;
                const uint32_t rpA = hr ? 0u : 256u, rpB = hr ? 0u : (uint32_t)-1536;
                float res[28];
                uint32_t v0[14], v1[14], P[14];
                const uint4* ps = xp0 + sl * 512;
#define F2_OWN_A()                                                                             \
    R_WAIT();                                                                                  \
    d0 = BASE128(0, 16, R_ADJ + roA); d1 = BASE128(0, 16, R_ADJ + roB);                        \
    wg_fence();                                                                                \
    FOR14(if constexpr (t < OT) mma_rs56<1, t * 128>(acc, H[4 * t], H[4 * t + 1], H[4 * t + 2], H[4 * t + 3], t > 0, d0)); \
    wg_commit();
#define F2_OWN_B()                                                                             \
    wg_fence();                                                                                \
    FOR14(if constexpr (t >= OT) mma_rs56<1, t * 128>(acc, H[4 * t], H[4 * t + 1], H[4 * t + 2], H[4 * t + 3], 1, t < 12 ? d0 : d1)); \
    wg_commit();                                                                               \
    R_NEXT();
#define F2_PEER()                                                                              \
    R_WAIT();                                                                                  \
    if (F2PP) { PP_WAIT() }                                                                    \
    d0 = BASE128(0, 16, R_ADJ + rpA); d1 = BASE128(0, 16, R_ADJ + rpB);                        \
    wg_fence();                                                                                \
    FOR14(mma_rs56<1, t * 128>(acc, HP[4 * t], HP[4 * t + 1], HP[4 * t + 2], HP[4 * t + 3], 1, t < 12 ? d0 : d1)); \
    wg_commit();                                                                               \
    if (F2PP) { PP_GO() }                                                                      \
    R_NEXT();
#define F2_TURN(u)                                                                             \
    wg_wait<1>();                                                                              \
    if ((u) < 2 || TDEF < 2) R_RELEASE(2);                                                     \
    wg_wait<0>();                                                                              \
    if ((u) < 2 || TDEF < 1) R_RELEASE(1);                                                     \
    _Pragma("unroll") for (int i = 0; i < 14; i++) P[i] = pack2(acc[2 * i], acc[2 * i + 1]);   \
    tag_slice(P, tag);                                                                         \
    asm volatile("" : RW4(P, 0), RW4(P, 4), RW4(P, 8), RW2(P, 12));                            \
    kill<28>(acc);                                                                             \
    F2_OWN_A()                                                                                 \
    if ((u) == 2) { slice_load<PL(3)>(v0, ps, lane); slice_load<PL(4)>(v1, ps, lane); } \
    send_slice<PL(3 + (u))>(xp0 + (2 * ((pr + (u) + 1) & 3) + hr) * 512, lane, P);             \
    seq++;                                                                                     \
    if (lane == 0) st_word(cx(sl), seq);                                                       \
    __syncwarp();                                                                              \
    STAMP(8 + (u) + so);                                                                       \
    F2_OWN_B()
                uint64_t d0, d1;
                F2_OWN_A()
                F2_OWN_B()
                R_WAIT();
                d0 = BASE128(0, 16, R_ADJ + rpA); d1 = BASE128(0, 16, R_ADJ + rpB);
                wg_fence();
                FOR8(mma_rs56<1, t * 128>(acc, HP[4 * t], HP[4 * t + 1], HP[4 * t + 2], HP[4 * t + 3], 1, d0));
                wg_commit();
                mbar_wait(BAR(B_RECV2 + wgi), step >> 1);
#pragma unroll
                for (int k = 0; k < 4; k++) lds4(HP + 32 + 4 * k, hbuf + 16384 + w * 2048 + k * 512 + lane * 16);
                lds4(HP + 48, hbuf + 24576 + w * 1024 + lane * 16);
                lds4(HP + 52, hbuf + 25088 + w * 1024 + lane * 16);
                if (step == 1) PUSH_ACK();
                wg_fence();
                FOR14(if constexpr (t >= 8) mma_rs56<1, t * 128>(acc, HP[4 * t], HP[4 * t + 1], HP[4 * t + 2], HP[4 * t + 3], 1, t < 12 ? d0 : d1));
                wg_commit();
                R_NEXT();
                F2_TURN(0)
                F2_PEER()
                F2_TURN(1)
                F2_PEER()
                F2_TURN(2)
                if (step == 1) STAMP(64);
                slice_check<PL(3)>(v0, ps, lane, tag);
                slice_check<PL(4)>(v1, ps, lane, tag);
#pragma unroll
                for (int i = 0; i < 14; i++) { res[2 * i] = bf_lo(v0[i]) + bf_lo(v1[i]); res[2 * i + 1] = bf_hi(v0[i]) + bf_hi(v1[i]); }
                slice_load<PL(2)>(X, ps, lane);
                if (step == 1) STAMP(65);
                F2_PEER()
                if (step == 1) STAMP(66);
                poll_cnt(cx(2 * ((pr + 1) & 3) + hr), seq);
                if (step == 1) STAMP(67);
                slice_load<PL(5)>(v0, ps, lane);
                x_fix(X, xbits);
                slice_check<PL(5)>(v0, ps, lane, tag);
                if (lane < TDEF) mbar_arrive(BAR(B_EMPTY + (slot + NST - 3 - lane) % NST));
#pragma unroll
                for (int i = 0; i < 14; i++) { res[2 * i] += bf_lo(v0[i]); res[2 * i + 1] += bf_hi(v0[i]); }
                STAMP(11 + so);
                wg_wait<0>();
                R_RELEASE(2);
                STAMP(12 + so);
                WSUM(85 + 7 * (step >> 1));
#pragma unroll
                for (int i = 0; i < 14; i++) X[i] = pack2(fmaf(res[2 * i] + acc[2 * i], 0.5f, bf_lo(X[i])), fmaf(res[2 * i + 1] + acc[2 * i + 1], 0.5f, bf_hi(X[i])));
            }
        }
        {
            const int m = lane >> 3, rr = lane & 7;
            const uint32_t ob = hbuf + w * 2048, rowa = ob + (rr + 8 * (m & 1)) * 112 + (m >> 1) * 16;
#pragma unroll
            for (int j = 0; j < 3; j++) stsm4(rowa + 32 * j, X[4 * j], X[4 * j + 1], X[4 * j + 2], X[4 * j + 3]);
            asm volatile("stmatrix.sync.aligned.m8n8.x2.shared.b16 [%0], {%1,%2};" ::"r"(ob + (rr + 8 * (m & 1)) * 112 + 96), "r"(X[12]), "r"(X[13]) : "memory");
            fence_async();
            __syncwarp();
            if (lane == 0) {
                asm volatile("cp.async.bulk.tensor.2d.global.shared::cta.bulk_group [%0, {%2, %3}], [%1];" ::"l"(&maps.out), "r"(ob), "r"(56 * sl), "r"(tile * 128 + wu * 16) : "memory");
                asm volatile("cp.async.bulk.commit_group;" ::: "memory");
                asm volatile("cp.async.bulk.wait_group.read 0;" ::: "memory");
            }
        }
        STAMP(50);
        GSTAMP(61);
        PDUMP();
    }
}

#undef g
#undef pr
#undef c
#undef t128

typedef CUresult (*EncodeFn)(CUtensorMap*, CUtensorMapDataType, cuuint32_t, void*, const cuuint64_t*, const cuuint64_t*, const cuuint32_t*,
                             const cuuint32_t*, CUtensorMapInterleave, CUtensorMapSwizzle, CUtensorMapL2promotion, CUtensorMapFloatOOBfill);

static void make_map(EncodeFn enc, CUtensorMap* m, const void* p, uint64_t cols, uint64_t rows, uint32_t bc, uint32_t br, CUtensorMapSwizzle sw) {
    cuuint64_t gd[2] = {cols, rows};
    cuuint64_t gs[1] = {cols * 2};
    cuuint32_t bd[2] = {bc, br};
    cuuint32_t es[2] = {1, 1};
    enc(m, CU_TENSOR_MAP_DATA_TYPE_BFLOAT16, 2, const_cast<void*>(p), gd, gs, bd, es, CU_TENSOR_MAP_INTERLEAVE_NONE, sw,
        CU_TENSOR_MAP_L2_PROMOTION_L2_128B, CU_TENSOR_MAP_FLOAT_OOB_FILL_NONE);
}

extern "C" void kernel_launch(void* const* d_in, const int* in_sizes, int n_in, void* d_out, int out_size) {
    (void)in_sizes; (void)n_in; (void)out_size;
    static EncodeFn enc = nullptr;
    static Scratch* scratch = nullptr;
    if (!enc) {
        void* fn = nullptr;
        cudaDriverEntryPointQueryResult qr;
        cudaGetDriverEntryPoint("cuTensorMapEncodeTiled", &fn, cudaEnableDefault, &qr);
        enc = (EncodeFn)fn;
        cudaGetSymbolAddress((void**)&scratch, g_scratch);
        cudaFuncSetAttribute(fused_kernel, cudaFuncAttributeMaxDynamicSharedMemorySize, SMEM_BYTES);
    }
    Maps maps;
    {
        cuuint64_t gd[3] = {64, 2048, 7};
        cuuint64_t gs[2] = {896, 128};
        cuuint32_t bd[3] = {64, 32, 7};
        cuuint32_t es[3] = {1, 1, 1};
        enc(&maps.x, CU_TENSOR_MAP_DATA_TYPE_BFLOAT16, 3, d_in[0], gd, gs, bd, es, CU_TENSOR_MAP_INTERLEAVE_NONE, CU_TENSOR_MAP_SWIZZLE_128B,
            CU_TENSOR_MAP_L2_PROMOTION_L2_128B, CU_TENSOR_MAP_FLOAT_OOB_FILL_NONE);
    }
    make_map(enc, &maps.out, d_out, 448, 2048, 56, 16, CU_TENSOR_MAP_SWIZZLE_NONE);
    make_map(enc, &maps.qkv, d_in[1], 1344, 448, 64, 112, CU_TENSOR_MAP_SWIZZLE_128B);
    make_map(enc, &maps.wo, d_in[3], 448, 448, 64, 112, CU_TENSOR_MAP_SWIZZLE_128B);
    make_map(enc, &maps.wg, d_in[5], 1792, 448, 64, 112, CU_TENSOR_MAP_SWIZZLE_128B);
    make_map(enc, &maps.wu, d_in[6], 1792, 448, 64, 112, CU_TENSOR_MAP_SWIZZLE_128B);
    make_map(enc, &maps.wg32, d_in[5], 1792, 448, 32, 112, CU_TENSOR_MAP_SWIZZLE_64B);
    make_map(enc, &maps.wu32, d_in[6], 1792, 448, 32, 112, CU_TENSOR_MAP_SWIZZLE_64B);
    make_map(enc, &maps.wd, d_in[7], 448, 1792, 64, 112, CU_TENSOR_MAP_SWIZZLE_128B);
    fused_kernel<<<128, 384, SMEM_BYTES>>>(scratch, (const __nv_bfloat16*)d_in[0], (const __nv_bfloat16*)d_in[2], 7, (const __nv_bfloat16*)d_in[5],
                                           (const __nv_bfloat16*)d_in[6], (const __nv_bfloat16*)d_in[7], maps);
}
```

```cpp
#include <cuda_runtime.h>
#include <cuda.h>
#include <cuda_bf16.h>
#include <stdint.h>
#include <type_traits>

#define PPF 2
#define PKP 0
#define TDEF 1
#define TMPF 0
#define NORM1 0
#define LPARK 1
#define EOWN 8
#define ACAN 0
#define SPLIT0 1
#define OT 2
#define F2PP 0
#define PPK 2
#define QE 1
#define OST 1
#define PP

namespace {

constexpr uint32_t STAGE = 28672, HALF = 14336;
constexpr int NST = 5;
constexpr uint32_t OFF_H = NST * STAGE;
constexpr uint32_t OFF_KVB = OFF_H + 2 * STAGE;
constexpr uint32_t OFF_WPHI = OFF_KVB + 16384;
constexpr uint32_t OFF_XR = OFF_WPHI + 7168;
constexpr uint32_t OFF_BAR = OFF_XR + 6144;
constexpr uint32_t SMEM_BYTES = OFF_BAR + 384 + 1408;
constexpr int B_EMPTY = NST, B_RECV = 2 * NST, B_RECV2 = B_RECV + 2, B_PACK = B_RECV2 + 2, B_GAT = B_PACK + 1, B_LATE = B_GAT + 16, B_ACK = B_LATE + 1, B_ACK2 = B_ACK + 2, B_COUNT = B_ACK2 + 2;

constexpr int PACK = 14 + 4 * PKP;

struct Maps { CUtensorMap x, qkv, wo, wg, wu, wg32, wu32, wd, out; };

}

constexpr int PLANE = 16 * 2 * 8 * 512;
struct Scratch {
    uint4 ex[6 * PLANE];
    uint4 kv1[8 * 16 * 16 * 32];
    uint4 kv2[8 * 512];
    uint32_t c1[8 * 8 * 16 * 32];
    uint32_t cw[8 * 32];
    uint4 wp[8 * 32 * (HALF / 16)];
};
__device__ __align__(1024) Scratch g_scratch;
#define g_ex (sc->ex)
#define g_kv1 (sc->kv1)
#define g_kv2 (sc->kv2)
#define g_c1 (sc->c1)
#define g_cw (sc->cw)
#define g_wp (sc->wp)
#define STAMP(i)
#define GSTAMP(i)
#define PDUMP()
#define ASTAMP(i)

namespace {

__device__ __forceinline__ int fresh_tid() { int t; asm volatile("mov.u32 %0, %%tid.x;" : "=r"(t)); return t; }
template <int N> __device__ __forceinline__ void kill(uint32_t* v) {
#pragma unroll
    for (int i = 0; i < N; i++) v[i] = 0;
}
template <int N> __device__ __forceinline__ void kill(float* v) {
#pragma unroll
    for (int i = 0; i < N; i++) v[i] = 0.f;
}
__device__ __forceinline__ uint32_t s2u(const void* p) { return (uint32_t)__cvta_generic_to_shared(p); }
__device__ __forceinline__ void mbar_init(uint32_t a, uint32_t c) { asm volatile("mbarrier.init.shared::cta.b64 [%0], %1;" ::"r"(a), "r"(c) : "memory"); }
__device__ __forceinline__ void mbar_expect_tx(uint32_t a, uint32_t b) { asm volatile("mbarrier.arrive.expect_tx.shared::cta.b64 _, [%0], %1;" ::"r"(a), "r"(b) : "memory"); }
__device__ __forceinline__ void mbar_arrive(uint32_t a) { asm volatile("mbarrier.arrive.shared::cta.b64 _, [%0];" ::"r"(a) : "memory"); }
#define GIVE_UP(id) "trap;\n"
#define SPIN_MAX "0x400000"
#define SPIN_TAIL(id) "add.u32 n, n, 1;\n setp.lt.u32 p, n, " SPIN_MAX ";\n @p bra.uni LP;\n" GIVE_UP(id) " DN:\n }"
__device__ __forceinline__ void mbar_wait(uint32_t a, uint32_t ph) {
    asm volatile("{ .reg .pred p; .reg .b32 n; mov.u32 n, 0;\n LP:\n"
                 "mbarrier.try_wait.parity.shared::cta.b64 p, [%0], %1;\n @p bra DN;\n"
                 "add.u32 n, n, 1;\n setp.lt.u32 p, n, " SPIN_MAX ";\n @p bra LP;\n"
                 GIVE_UP("")
                 " DN:\n }" ::"r"(a), "r"(ph) : "memory");
}
#define ELECT "{ .reg .pred e; elect.sync _|e, 0xffffffff; @e "
__device__ __forceinline__ void tma2d(uint32_t dst, const CUtensorMap* m, int c0, int c1, uint32_t bar) {
    asm volatile(ELECT "cp.async.bulk.tensor.2d.shared::cluster.global.mbarrier::complete_tx::bytes [%0], [%1, {%3, %4}], [%2]; }" ::"r"(dst), "l"(m), "r"(bar), "r"(c0), "r"(c1) : "memory");
}
__device__ __forceinline__ void tma3x(uint32_t dst, const CUtensorMap* m, int row, uint32_t bar) {
    asm volatile(ELECT "cp.async.bulk.tensor.3d.shared::cluster.global.mbarrier::complete_tx::bytes [%0], [%1, {0, %3, 0}], [%2]; }" ::"r"(dst), "l"(m), "r"(bar), "r"(row) : "memory");
}
template <int OFF>
__device__ __forceinline__ void ld_pkt(uint32_t* v, const uint4* p) {
    asm volatile("{ .reg .b128 t; ld.relaxed.gpu.global.b128 t, [%4+%5]; mov.b128 {%0,%1,%2,%3}, t; }" : "=r"(v[0]), "=r"(v[1]), "=r"(v[2]), "=r"(v[3]) : "l"(p), "n"(OFF * 16) : "memory");
}
template <int OFF>
__device__ __forceinline__ void st_pkt(uint4* p, uint32_t a, uint32_t b, uint32_t c, uint32_t d) {
    asm volatile("{ .reg .b128 t; mov.b128 t, {%1,%2,%3,%4}; st.relaxed.gpu.global.b128 [%0+%5], t; }" ::"l"(p), "r"(a), "r"(b), "r"(c), "r"(d), "n"(OFF * 16) : "memory");
}
__device__ __forceinline__ uint32_t pack2(float lo, float hi) {
    uint32_t r;
    asm("cvt.rn.bf16x2.f32 %0, %1, %2;" : "=r"(r) : "f"(hi), "f"(lo));
    return r;
}
__device__ __forceinline__ float bf_lo(uint32_t w) { return __uint_as_float(w << 16); }
__device__ __forceinline__ float bf_hi(uint32_t w) { return __uint_as_float(w & 0xffff0000u); }
__device__ __forceinline__ uint32_t settag(uint32_t w, uint32_t tag) { return (w & ~1u) | tag; }
__device__ __forceinline__ float ex2(float x) { float y; asm("ex2.approx.ftz.f32 %0, %1;" : "=f"(y) : "f"(x)); return y; }
__device__ __forceinline__ float rcp(float x) { float y; asm("rcp.approx.ftz.f32 %0, %1;" : "=f"(y) : "f"(x)); return y; }
__device__ __forceinline__ float tanh_hw(float x) { float y; asm("tanh.approx.f32 %0, %1;" : "=f"(y) : "f"(x)); return y; }
__device__ __forceinline__ void stsm4(uint32_t addr, uint32_t a, uint32_t b, uint32_t c, uint32_t d) {
    asm volatile("stmatrix.sync.aligned.m8n8.x4.shared.b16 [%0], {%1,%2,%3,%4};" ::"r"(addr), "r"(a), "r"(b), "r"(c), "r"(d) : "memory");
}
__device__ __forceinline__ void fence_async() { asm volatile("fence.proxy.async.shared::cta;" ::: "memory"); }
__device__ __forceinline__ void bar_sync(int id, int n) { asm volatile("bar.sync %0, %1;" ::"r"(id), "r"(n) : "memory"); }
__device__ __forceinline__ void bar_arrive(int id, int n) { asm volatile("bar.arrive %0, %1;" ::"r"(id), "r"(n) : "memory"); }
__device__ __forceinline__ void wg_fence() { asm volatile("wgmma.fence.sync.aligned;" ::: "memory"); }
__device__ __forceinline__ void wg_commit() { asm volatile("wgmma.commit_group.sync.aligned;" ::: "memory"); }
template <int N> __device__ __forceinline__ void wg_wait() { asm volatile("wgmma.wait_group.sync.aligned %0;" ::"n"(N) : "memory"); }

constexpr uint32_t SB0 = 1024;
__host__ __device__ constexpr uint32_t dlo(uint32_t off, uint32_t lbo) { return ((SB0 + off) >> 4) | ((lbo >> 4) << 16); }
__host__ __device__ constexpr uint32_t dhi(uint32_t sbo, uint32_t sw) { return (sbo >> 4) | (sw << 30); }
__device__ __forceinline__ uint64_t dbase(uint32_t lo, uint32_t hi) { uint64_t d; asm volatile("mov.b64 %0, {%1, %2};" : "=l"(d) : "r"(lo), "r"(hi)); return d; }
#define BASE128(off, lbo, adj) dbase(dlo(off, lbo) + (adj), dhi(1024, 1))
#define BASE64(off, lbo, adj) dbase(dlo(off, lbo) + (adj), dhi(512, 2))

#define ACC4(d, o) "+f"(d[o]), "+f"(d[o + 1]), "+f"(d[o + 2]), "+f"(d[o + 3])
#define ACC28(d) ACC4(d, 0), ACC4(d, 4), ACC4(d, 8), ACC4(d, 12), ACC4(d, 16), ACC4(d, 20), ACC4(d, 24)
#define ACC32(d, o) ACC4(d, o), ACC4(d, o + 4), ACC4(d, o + 8), ACC4(d, o + 12), ACC4(d, o + 16), ACC4(d, o + 20), ACC4(d, o + 24), ACC4(d, o + 28)

template <int TB, uint64_t D>
__device__ __forceinline__ void mma_rs56(float* d, uint32_t a0, uint32_t a1, uint32_t a2, uint32_t a3, int sd, uint64_t base) {
    asm volatile("{ .reg .pred p; .reg .b64 db; setp.ne.b32 p, %32, 0; add.u64 db, %33, %34;\n"
                 "wgmma.mma_async.sync.aligned.m64n56k16.f32.bf16.bf16 "
                 "{%0,%1,%2,%3,%4,%5,%6,%7,%8,%9,%10,%11,%12,%13,%14,%15,%16,%17,%18,%19,%20,%21,%22,%23,%24,%25,%26,%27}, "
                 "{%28,%29,%30,%31}, db, p, 1, 1, %35; }\n"
                 : ACC28(d)
                 : "r"(a0), "r"(a1), "r"(a2), "r"(a3), "r"(sd), "l"(base), "n"(D), "n"(TB));
}
template <int TB, uint64_t D>
__device__ __forceinline__ void mma_rs64(float* d, uint32_t a0, uint32_t a1, uint32_t a2, uint32_t a3, int sd, uint64_t base) {
    asm volatile("{ .reg .pred p; .reg .b64 db; setp.ne.b32 p, %36, 0; add.u64 db, %37, %38;\n"
                 "wgmma.mma_async.sync.aligned.m64n64k16.f32.bf16.bf16 "
                 "{%0,%1,%2,%3,%4,%5,%6,%7,%8,%9,%10,%11,%12,%13,%14,%15,%16,%17,%18,%19,%20,%21,%22,%23,%24,%25,%26,%27,%28,%29,%30,%31}, "
                 "{%32,%33,%34,%35}, db, p, 1, 1, %39; }\n"
                 : ACC32(d, 0)
                 : "r"(a0), "r"(a1), "r"(a2), "r"(a3), "r"(sd), "l"(base), "n"(D), "n"(TB));
}
template <int TB, uint64_t D>
__device__ __forceinline__ void mma_rs128(float* d, uint32_t a0, uint32_t a1, uint32_t a2, uint32_t a3, int sd, uint64_t base) {
    asm volatile("{ .reg .pred p; .reg .b64 db; setp.ne.b32 p, %68, 0; add.u64 db, %69, %70;\n"
                 "wgmma.mma_async.sync.aligned.m64n128k16.f32.bf16.bf16 "
                 "{%0,%1,%2,%3,%4,%5,%6,%7,%8,%9,%10,%11,%12,%13,%14,%15,%16,%17,%18,%19,%20,%21,%22,%23,%24,%25,%26,%27,%28,%29,%30,%31,%32,%33,%34,%35,%36,%37,%38,%39,%40,%41,%42,%43,%44,%45,%46,%47,%48,%49,%50,%51,%52,%53,%54,%55,%56,%57,%58,%59,%60,%61,%62,%63}, "
                 "{%64,%65,%66,%67}, db, p, 1, 1, %71; }\n"
                 : ACC32(d, 0), ACC32(d, 32)
                 : "r"(a0), "r"(a1), "r"(a2), "r"(a3), "r"(sd), "l"(base), "n"(D), "n"(TB));
}
template <uint64_t DA, uint64_t DB>
__device__ __forceinline__ void mma_ss56_tt(float* d, int sd, uint64_t ba, uint64_t bb) {
    asm volatile("{ .reg .pred p; .reg .b64 da, db; setp.ne.b32 p, %28, 0; add.u64 da, %29, %31; add.u64 db, %30, %32;\n"
                 "wgmma.mma_async.sync.aligned.m64n56k16.f32.bf16.bf16 "
                 "{%0,%1,%2,%3,%4,%5,%6,%7,%8,%9,%10,%11,%12,%13,%14,%15,%16,%17,%18,%19,%20,%21,%22,%23,%24,%25,%26,%27}, "
                 "da, db, p, 1, 1, 1, 1; }\n"
                 : ACC28(d)
                 : "r"(sd), "l"(ba), "l"(bb), "n"(DA), "n"(DB));
}
template <int... I> struct Seq {};
template <class F, int... I> __device__ __forceinline__ void static_for_impl(F&& f, Seq<I...>) { (f(std::integral_constant<int, I>{}), ...); }
#define FOR7(...) static_for_impl([&](auto T_) { constexpr int t = decltype(T_)::value; __VA_ARGS__; }, Seq<0, 1, 2, 3, 4, 5, 6>{})
#define FOR8(...) static_for_impl([&](auto T_) { constexpr int t = decltype(T_)::value; __VA_ARGS__; }, Seq<0, 1, 2, 3, 4, 5, 6, 7>{})
#define FOR14(...) static_for_impl([&](auto T_) { constexpr int t = decltype(T_)::value; __VA_ARGS__; }, Seq<0, 1, 2, 3, 4, 5, 6, 7, 8, 9, 10, 11, 12, 13>{})

__device__ __forceinline__ int kblk(int p, int b) { return b == 0 ? p : b - (b <= p); }
__host__ __device__ constexpr int krow(int t) { return t < 3 ? 16 * t : (t < 6 ? 56 + 16 * (t - 3) : 48); }
#define AQ(A, b, t) ((t) < 3 ? A[2 * (b)][4 * (t)] : (t) < 6 ? A[2 * (b) + 1][4 * ((t) - 3)] : A[2 * (b)][12]), \
                    ((t) < 3 ? A[2 * (b)][4 * (t) + 1] : (t) < 6 ? A[2 * (b) + 1][4 * ((t) - 3) + 1] : A[2 * (b)][13]), \
                    ((t) < 3 ? A[2 * (b)][4 * (t) + 2] : (t) < 6 ? A[2 * (b) + 1][4 * ((t) - 3) + 2] : A[2 * (b) + 1][12]), \
                    ((t) < 3 ? A[2 * (b)][4 * (t) + 3] : (t) < 6 ? A[2 * (b) + 1][4 * ((t) - 3) + 3] : A[2 * (b) + 1][13])
#define D128(off, t) ((uint64_t)(((off) + krow(t) * 128) >> 4) + ((uint64_t)((t) == 6 ? (7168 - 1024) >> 4 : 0) << 32))
#define D64(off, t) ((uint64_t)(((off) + krow(t) * 64) >> 4) + ((uint64_t)((t) == 6 ? (3584 - 512) >> 4 : 0) << 32))

#define PL(k) (((k) - 3) * PLANE)
__device__ __forceinline__ void st_word(uint32_t* p, uint32_t v) { asm volatile("st.relaxed.gpu.global.u32 [%0], %1;" ::"l"(p), "r"(v) : "memory"); }
__device__ __forceinline__ uint32_t ld_word(const uint32_t* p) { uint32_t v; asm volatile("ld.relaxed.gpu.global.u32 %0, [%1];" : "=r"(v) : "l"(p) : "memory"); return v; }
__device__ __forceinline__ void tag_slice(uint32_t* w, uint32_t tag) { w[0] = settag(w[0], tag); w[4] = settag(w[4], tag); w[8] = settag(w[8], tag); w[12] = settag(w[12], tag); }
template <int O>
__device__ __forceinline__ void send_slice(uint4* dst, int lane, const uint32_t* w) {
    st_pkt<O>(dst, w[0], w[1], w[2], w[3]);
    st_pkt<O + 32>(dst, w[4], w[5], w[6], w[7]);
    st_pkt<O + 64>(dst, w[8], w[9], w[10], w[11]);
    asm volatile("{ .reg .b64 t; mov.b64 t, {%1,%2}; st.relaxed.gpu.global.b64 [%0+%3], t; }" ::"l"((char*)dst - lane * 8), "r"(w[12]), "r"(w[13]), "n"(16 * (O + 96)) : "memory");
}
#define RW4(v, o) "+r"(v[o]), "+r"(v[(o) + 1]), "+r"(v[(o) + 2]), "+r"(v[(o) + 3])
#define RW2(v, o) "+r"(v[o]), "+r"(v[(o) + 1])
#define WR4(v, o) "=&r"(v[o]), "=&r"(v[(o) + 1]), "=&r"(v[(o) + 2]), "=&r"(v[(o) + 3])
#define LDP(a, b, c, d, addr, off) "ld.relaxed.gpu.global.b128 q, [" addr "+" off "];\n mov.b128 {" a "," b "," c "," d "}, q;\n"
#define LDH(a, b, addr, off) "ld.relaxed.gpu.global.b64 h, [" addr "+" off "];\n mov.b64 {" a "," b "}, h;\n"
#define VOTE_OK "and.b32 t, t, 1;\n setp.ne.u32 p, t, 0;\n vote.sync.any.pred p, p, 0xffffffff;\n @!p bra.uni DN;\n"
#define CHK(x, tag) "lop3.b32 t, " x ", " tag ", t, 0xBE;\n"
__device__ __forceinline__ void check_cnt(uint32_t v, const uint32_t* p, uint32_t target) {
    asm volatile("{ .reg .pred p; .reg .b32 n, t; mov.u32 n, 0; mov.u32 t, %2;\n LP:\n"
                 "sub.s32 t, t, %1;\n setp.lt.s32 p, t, 0;\n vote.sync.any.pred p, p, 0xffffffff;\n @!p bra.uni DN;\n ld.relaxed.gpu.global.u32 t, [%0];\n" SPIN_TAIL("7")
                 ::"l"(p), "r"(target), "r"(v) : "memory");
}
__device__ __forceinline__ void poll_cnt(const uint32_t* p, uint32_t target) {
    asm volatile("{ .reg .pred p; .reg .b32 n, t; mov.u32 n, 0;\n LP:\n"
                 "ld.relaxed.gpu.global.u32 t, [%0];\n sub.s32 t, t, %1;\n setp.lt.s32 p, t, 0;\n vote.sync.any.pred p, p, 0xffffffff;\n @!p bra.uni DN;\n" SPIN_TAIL("1")
                 ::"l"(p), "r"(target) : "memory");
}
template <int STR>
__device__ __forceinline__ void poll4_kv(uint32_t* v, const uint4* p, uint32_t tag) {
    asm volatile("{ .reg .pred p; .reg .b32 n, t; .reg .b128 q; mov.u32 n, 0;\n LP:\n"
                 LDP("%0", "%1", "%2", "%3", "%16", "0") LDP("%4", "%5", "%6", "%7", "%16", "%18")
                 LDP("%8", "%9", "%10", "%11", "%16", "%19") LDP("%12", "%13", "%14", "%15", "%16", "%20")
                 "xor.b32 t, %0, %17;\n" CHK("%4", "%17") CHK("%8", "%17") CHK("%12", "%17") VOTE_OK SPIN_TAIL("2")
                 : WR4(v, 0), WR4(v, 4), WR4(v, 8), WR4(v, 12)
                 : "l"(p), "r"(tag), "n"(16 * STR), "n"(32 * STR), "n"(48 * STR)
                 : "memory");
}
template <int B>
__device__ __forceinline__ void blk_load(uint32_t (&A)[8][14], const uint4* src, int lane) {
    ld_pkt<0>(&A[2 * B][0], src); ld_pkt<32>(&A[2 * B][4], src); ld_pkt<64>(&A[2 * B][8], src);
    ld_pkt<512>(&A[2 * B + 1][0], src); ld_pkt<544>(&A[2 * B + 1][4], src); ld_pkt<576>(&A[2 * B + 1][8], src);
    asm volatile("{ .reg .b64 h;\n" LDH("%0", "%1", "%4", "1536") LDH("%2", "%3", "%4", "9728") "}"
                 : "=&r"(A[2 * B][12]), "=&r"(A[2 * B][13]), "=&r"(A[2 * B + 1][12]), "=&r"(A[2 * B + 1][13])
                 : "l"((const char*)src - lane * 8) : "memory");
}
template <int B>
__device__ __forceinline__ void blk_check(uint32_t (&A)[8][14], const uint4* src, int lane, uint32_t tag) {
    asm volatile("{ .reg .pred p; .reg .b32 n, t; .reg .b128 q; .reg .b64 h, a8; mov.u32 n, 0;\n LP:\n"
                 "xor.b32 t, %0, %30;\n" CHK("%4", "%30") CHK("%8", "%30") CHK("%12", "%30") CHK("%16", "%30") CHK("%20", "%30") CHK("%24", "%30") CHK("%26", "%30") VOTE_OK
                 LDP("%0", "%1", "%2", "%3", "%28", "0") LDP("%4", "%5", "%6", "%7", "%28", "512") LDP("%8", "%9", "%10", "%11", "%28", "1024")
                 LDP("%12", "%13", "%14", "%15", "%28", "8192") LDP("%16", "%17", "%18", "%19", "%28", "8704") LDP("%20", "%21", "%22", "%23", "%28", "9216")
                 "mad.wide.s32 a8, %29, -8, %28;\n" LDH("%24", "%25", "a8", "1536") LDH("%26", "%27", "a8", "9728") SPIN_TAIL("3")
                 "\n and.b32 %0, %0, -2; and.b32 %4, %4, -2; and.b32 %8, %8, -2; and.b32 %12, %12, -2; and.b32 %16, %16, -2; and.b32 %20, %20, -2; and.b32 %24, %24, -2; and.b32 %26, %26, -2;"
                 : RW4(A[2 * B], 0), RW4(A[2 * B], 4), RW4(A[2 * B], 8), RW4(A[2 * B + 1], 0), RW4(A[2 * B + 1], 4), RW4(A[2 * B + 1], 8),
                   RW2(A[2 * B], 12), RW2(A[2 * B + 1], 12)
                 : "l"(src), "r"(lane), "r"(tag)
                 : "memory");
}
__device__ __forceinline__ void st_async4(uint32_t a, uint32_t x, uint32_t y, uint32_t z, uint32_t w, uint32_t bar) {
    asm volatile("st.async.weak.shared::cluster.mbarrier::complete_tx::bytes.v4.b32 [%0], {%1,%2,%3,%4}, [%5];" ::"r"(a), "r"(x), "r"(y), "r"(z), "r"(w), "r"(bar) : "memory");
}
__device__ __forceinline__ uint32_t mapa(uint32_t a, uint32_t cta) { uint32_t r; asm("mapa.shared::cluster.u32 %0, %1, %2;" : "=r"(r) : "r"(a), "r"(cta)); return r; }
__device__ __forceinline__ void stat_load(uint32_t* v, const uint4* p) { ld_pkt<0>(v, p); ld_pkt<512>(v + 4, p); }
__device__ __forceinline__ void stat_check(uint32_t* v, const uint4* p, uint32_t tag) {
    asm volatile("{ .reg .pred p; .reg .b32 n, t; .reg .b128 q; mov.u32 n, 0;\n LP:\n"
                 "xor.b32 t, %3, %9;\n" CHK("%7", "%9") VOTE_OK
                 LDP("%0", "%1", "%2", "%3", "%8", "0") LDP("%4", "%5", "%6", "%7", "%8", "8192") SPIN_TAIL("4")
                 : RW4(v, 0), RW4(v, 4) : "l"(p), "r"(tag) : "memory");
}
__device__ __forceinline__ uint32_t x_bits(const uint32_t* X) {
    uint32_t r;
    asm volatile("{ .reg .b32 a, b; prmt.b32 a, %1, %2, 0x0040; prmt.b32 b, %3, %4, 0x0040; prmt.b32 %0, a, b, 0x5410; }" : "=r"(r) : "r"(X[0]), "r"(X[4]), "r"(X[8]), "r"(X[12]));
    return r;
}
template <int O>
__device__ __forceinline__ void slice_load(uint32_t* v, const uint4* p, int lane) {
    ld_pkt<O>(v, p); ld_pkt<O + 32>(v + 4, p); ld_pkt<O + 64>(v + 8, p);
    asm volatile("{ .reg .b64 h;\n" LDH("%0", "%1", "%2", "%3") "}" : "=r"(v[12]), "=r"(v[13]) : "l"((const char*)p - lane * 8), "n"(16 * (O + 96)) : "memory");
}
template <int O>
__device__ __forceinline__ void slice_check(uint32_t* v, const uint4* p, int lane, uint32_t tag) {
    asm volatile("{ .reg .pred p; .reg .b32 n, t; .reg .b128 q; .reg .b64 h; mov.u32 n, 0;\n LP:\n"
                 "xor.b32 t, %0, %16;\n" CHK("%4", "%16") CHK("%8", "%16") CHK("%12", "%16") VOTE_OK
                 LDP("%0", "%1", "%2", "%3", "%14", "%17") LDP("%4", "%5", "%6", "%7", "%14", "%18") LDP("%8", "%9", "%10", "%11", "%14", "%19")
                 LDH("%12", "%13", "%15", "%20") SPIN_TAIL("5")
                 : RW4(v, 0), RW4(v, 4), RW4(v, 8), RW2(v, 12)
                 : "l"(p), "l"((const char*)p - lane * 8), "r"(tag), "n"(16 * O), "n"(16 * (O + 32)), "n"(16 * (O + 64)), "n"(16 * (O + 96))
                 : "memory");
}
__device__ __forceinline__ void x_fix(uint32_t* X, uint32_t bits) {
    X[0] = __byte_perm(X[0], bits, 0x3214); X[4] = __byte_perm(X[4], bits, 0x3215); X[8] = __byte_perm(X[8], bits, 0x3216); X[12] = __byte_perm(X[12], bits, 0x3217);
}
__device__ __forceinline__ void sts4(uint32_t a, uint32_t x, uint32_t y, uint32_t z, uint32_t w) {
    asm volatile("st.shared.v4.u32 [%0], {%1,%2,%3,%4};" ::"r"(a), "r"(x), "r"(y), "r"(z), "r"(w) : "memory");
}
__device__ __forceinline__ void lds4(uint32_t* v, uint32_t a) {
    asm volatile("ld.shared.v4.u32 {%0,%1,%2,%3}, [%4];" : "=r"(v[0]), "=r"(v[1]), "=r"(v[2]), "=r"(v[3]) : "r"(a) : "memory");
}
struct LnCoef { uint32_t hi, lo, sh; };
__device__ __forceinline__ LnCoef ln_coef(float sum, float sq) {
    sum += __shfl_xor_sync(0xffffffffu, sum, 1); sq += __shfl_xor_sync(0xffffffffu, sq, 1);
    sum += __shfl_xor_sync(0xffffffffu, sum, 2); sq += __shfl_xor_sync(0xffffffffu, sq, 2);
    const float mean = sum * (1.f / 448.f);
    const float var = fmaxf(fmaf(-mean, mean, sq * (1.f / 448.f)), 0.f);
    const float sc = rsqrtf(var + 1e-5f);
    LnCoef r;
    r.hi = pack2(sc, sc);
    const float lo = sc - bf_lo(r.hi), sh = -mean * sc;
    r.lo = pack2(lo, lo);
    r.sh = pack2(sh, sh);
    return r;
}
template <int B>
__device__ __forceinline__ void normalize(uint32_t (&A)[8][14], const LnCoef& c0, const LnCoef& c1) {
#pragma unroll
    for (int s = 2 * B; s < 2 * B + 2; s++)
#pragma unroll
        for (int i = 0; i < 14; i++) {
            const LnCoef& k = (i & 1) ? c1 : c0;
            asm("{ .reg .b32 t; fma.rn.bf16x2 t, %0, %2, %3; fma.rn.bf16x2 %0, %0, %1, t; }" : "+r"(A[s][i]) : "r"(k.hi), "r"(k.lo), "r"(k.sh));
        }
}
__device__ __forceinline__ void slice_stats(const uint32_t* w, float* st) {
    float a = 0.f, b = 0.f, p = 0.f, q = 0.f;
#pragma unroll
    for (int i = 0; i < 7; i++) {
        const float e0 = bf_lo(w[2 * i]), e1 = bf_hi(w[2 * i]), e2 = bf_lo(w[2 * i + 1]), e3 = bf_hi(w[2 * i + 1]);
        a += e0 + e1; b += e2 + e3;
        p = fmaf(e0, e0, p); p = fmaf(e1, e1, p); q = fmaf(e2, e2, q); q = fmaf(e3, e3, q);
    }
    a += __shfl_xor_sync(0xffffffffu, a, 1); p += __shfl_xor_sync(0xffffffffu, p, 1); b += __shfl_xor_sync(0xffffffffu, b, 1); q += __shfl_xor_sync(0xffffffffu, q, 1);
    a += __shfl_xor_sync(0xffffffffu, a, 2); p += __shfl_xor_sync(0xffffffffu, p, 2); b += __shfl_xor_sync(0xffffffffu, b, 2); q += __shfl_xor_sync(0xffffffffu, q, 2);
    st[0] = a; st[1] = p; st[2] = b; st[3] = q;
}
__device__ __forceinline__ void dual_softmax(const float* p, uint32_t* out) {
    constexpr float L = 1.4426950408889634f;
#pragma unroll
    for (int r = 0; r < 2; r++) {
        float mx = fmaxf(p[2 * r], p[2 * r + 1]), mn = fminf(p[2 * r], p[2 * r + 1]);
#pragma unroll
        for (int i = 1; i < 7; i++) {
            mx = fmaxf(mx, fmaxf(p[4 * i + 2 * r], p[4 * i + 2 * r + 1]));
            mn = fminf(mn, fminf(p[4 * i + 2 * r], p[4 * i + 2 * r + 1]));
        }
        mx = fmaxf(mx, __shfl_xor_sync(0xffffffffu, mx, 1));
        mn = fminf(mn, __shfl_xor_sync(0xffffffffu, mn, 1));
        const float bx = -mx * L, bn = mn * L;
        float ep[14], en[14], sp = 0.f, sn = 0.f;
#pragma unroll
        for (int i = 0; i < 14; i++) {
            const float v = p[4 * (i >> 1) + 2 * r + (i & 1)];
            ep[i] = ex2(fmaf(v, L, bx));
            en[i] = ex2(fmaf(v, -L, bn));
            sp += ep[i]; sn += en[i];
        }
        sp += __shfl_xor_sync(0xffffffffu, sp, 1);
        sn += __shfl_xor_sync(0xffffffffu, sn, 1);
        const float ip = rcp(sp), in = rcp(sn);
#pragma unroll
        for (int i = 0; i < 7; i++) {
            out[4 * i + r] = pack2(ep[2 * i] * ip, ep[2 * i + 1] * ip);
            out[4 * i + 2 + r] = pack2(en[2 * i] * in, en[2 * i + 1] * in);
        }
    }
}
__device__ __forceinline__ float geglu(float g, float u) {
    const float t = tanh_hw(g * fmaf(g * g, 0.7978845608028654f * 0.044715f, 0.7978845608028654f));
    const float gu = g * u;
    return fmaf(t, gu, gu);
}
__device__ __forceinline__ void phi_gemm(const float* t, float* p) {
    uint32_t w[14];
#pragma unroll
    for (int i = 0; i < 14; i++) w[i] = pack2(t[2 * i], t[2 * i + 1]);
    const uint64_t db = BASE128(OFF_WPHI, 16, 0);
    wg_fence();
    mma_rs56<0, 0>(p, w[0], w[1], w[2], w[3], 0, db);
    mma_rs56<0, 2>(p, w[4], w[5], w[6], w[7], 1, db);
    mma_rs56<0, 4>(p, w[8], w[9], w[10], w[11], 1, db);
    mma_rs56<0, 6>(p, w[12], w[13], 0u, 0u, 1, db);
    wg_commit();
    wg_wait<0>();
}

}

#define BAR(i) (bars + 8 * (i))
#define R_WAIT() mbar_wait(BAR(slot), ph)
#define WSUM(i)
#define R_ADJ (slot * (STAGE >> 4))
#define R_NEXT() do { eb2 = eb1; eb1 = BAR(B_EMPTY + slot); if (++slot == NST) { slot = 0; ph ^= 1; } } while (0)
#define R_RELEASE(k) do { if (lane == 0) mbar_arrive((k) == 1 ? eb1 : eb2); } while (0)
#define PUSH_BEGIN() do { mbar_wait(BAR(B_ACK + wgi), ackph); ackph ^= 1; } while (0)
#define PUSH_ACK() do { __syncwarp(); if (lane == 0) asm volatile("mbarrier.arrive.shared::cluster.b64 _, [%0];" ::"r"(mapa(BAR(B_ACK + wgi), hr ^ 1)) : "memory"); } while (0)

__global__ void __cluster_dims__(2, 1, 1) __launch_bounds__(384, 1)
fused_kernel(Scratch* const sc, const __nv_bfloat16* __restrict__ x_in, const __nv_bfloat16* __restrict__ w_phi, const int trips,
             const __nv_bfloat16* __restrict__ wg, const __nv_bfloat16* __restrict__ wu, const __nv_bfloat16* __restrict__ wd,
             const __grid_constant__ Maps maps) {
    extern __shared__ __align__(1024) unsigned char smem_raw[];
    const uint32_t sb = s2u(smem_raw);
    const uint32_t bars = sb + OFF_BAR;
    const int wgi = __shfl_sync(0xffffffffu, threadIdx.x >> 7, 0);
    const int hr = blockIdx.x & 1, ck = blockIdx.x >> 1;
    const int gp = (ck - 4) & 7, q7 = ((ck - 36) * 37) >> 8;
    const int pr = __shfl_sync(0xffffffffu, ck < 4 ? ck : (ck < 36 ? (ck - 4) >> 3 : q7), 0);
    const int tile = __shfl_sync(0xffffffffu, ck < 4 ? 0 : (ck < 36 ? (gp ? 2 * gp : 1) : 2 * (ck - 36 - 7 * q7) + 3), 0);
    const int sl = 2 * pr + hr;
    STAMP(0);
    GSTAMP(60);
    if (threadIdx.x == 256) {
#pragma unroll
        for (int i = 0; i < NST; i++) mbar_init(BAR(i), 1);
        asm volatile("fence.mbarrier_init.release.cluster;" ::: "memory");
    }
    if (threadIdx.x == 288) {
        if ((sb & 0x3FFFF) != SB0) asm volatile("trap;");
#pragma unroll
        for (int i = NST; i < B_COUNT; i++) mbar_init(BAR(i), i >= B_ACK ? 4 : (i < B_RECV || i == B_LATE ? 8 : 1));
        asm volatile("fence.mbarrier_init.release.cluster;" ::: "memory");
    }
    __syncwarp();
    asm volatile("barrier.cluster.arrive.relaxed.aligned;" ::: "memory");

    if (wgi == 2) {
        asm volatile("setmaxnreg.dec.sync.aligned.u32 40;");
        const int t128 = fresh_tid() & 127, w = __shfl_sync(0xffffffffu, t128 >> 5, 0), lane = t128 & 31;
        uint32_t e0[2] = {0, 0}, e1[2] = {0, 0}, cw_target = 0;
        if (w == 0) {
#pragma unroll 1
            for (int n = 0; n < NST; n++) {
                const uint32_t dst = sb + n * STAGE, fb = BAR(n);
                asm volatile(ELECT "mbarrier.arrive.expect_tx.shared::cta.b64 _, [%0], %1; }" ::"r"(fb), "r"(n < 2 ? 2 * STAGE : STAGE) : "memory");
                if (n < 2) {
                    tma3x(sb + OFF_H + n * STAGE, &maps.x, tile * 128 + n * 64, fb);
                    tma3x(dst, &maps.x, tile * 128 + n * 64 + 32, fb);
                } else {
                    if (n == 3) mbar_wait(BAR(1), 0);
                    const int ra = 112 * (n - 2);
                    tma2d(dst, &maps.qkv, 448 + 56 * sl, ra, fb);
                    tma2d(dst + HALF, &maps.qkv, 896 + 56 * sl, ra, fb);
                }
            }
            asm volatile("barrier.cluster.wait.aligned;" ::: "memory");
            cw_target = (ld_word(g_cw + sl * 32) & ~15u) + 16;
#pragma unroll 1
            for (int k = 0; k < 2; k++) {
                const int n = t128 + 32 * k;
                int m = n - 2 - (n > PACK);
                const bool packed = m >= 30 ? (m < 38 || m >= 52) : m >= 22;
                if (m >= 30) m -= 30;
                if (n == PACK) m = tile < 8 ? tile : tile + 14;
                const int rot = n < 8 ? 0 : pr;
                const int ra = 112 * kblk(rot, m & 3), rb = 112 * kblk(rot, 2 * m & 3), rc = 112 * kblk(rot, (2 * m + 1) & 3);
                int kind = 0, m0, m1, c0, c1, r0, r1;
                if (m < 4) { m0 = m1 = 1; c0 = 448 + 56 * sl; c1 = c0 + 448; r0 = r1 = ra; }
                else if (m < 8) { m0 = m1 = m < 6 ? 1 : 2; c0 = c1 = 56 * sl; r0 = rb; r1 = rc; }
                else if (m < 20) { m0 = 3; m1 = 4; c0 = c1 = 224 * sl + 32 * hr + 64 * ((m - 8) >> 2); r0 = r1 = ra; }
                else if (m < 22) { kind = 2; m0 = 5; m1 = 6; c0 = c1 = 224 * sl + (hr ? 0 : 192); r0 = rb; r1 = rc; }
                else { m0 = m1 = 7; c0 = c1 = 56 * (2 * ((pr + (m >> 1) - 10) & 3) + hr); r0 = 224 * (sl ^ (m & 1)); r1 = r0 + 112; }
                if (packed) { kind = 1; r0 = sl * 16 + (m < 8 ? m : m - 14); r1 = 0; }
                e0[0] = e0[1]; e1[0] = e1[1];
                e0[1] = kind | (m0 << 2) | (m1 << 6) | (c0 << 10) | (c1 << 21);
                e1[1] = r0 | (r1 << 16);
            }
        } else {
            const int j = t128 - 32;
            asm volatile("barrier.cluster.wait.aligned;" ::: "memory");
            uint2 wv[7];
            const int k = j < 56 ? j : 55, hh = k >= 28;
#pragma unroll
            for (int i = 0; i < 7; i++) wv[i] = __ldg(reinterpret_cast<const uint2*>(w_phi + (sl * 56 + k) * 28) + i);
#pragma unroll 1
            for (int i = j; i < 7168 / 16; i += 96) sts4(sb + OFF_WPHI + i * 16, 0, 0, 0, 0);
            bar_sync(5, 96);
            if (j < 56) {
                uint32_t a4[4];
#pragma unroll
                for (int q = 0; q < 4; q++) a4[q] = sb + OFF_WPHI + (4 * hh + q) * 128 + ((((k >> 3) ^ (4 * hh + q)) & 7) << 4) + (k & 7) * 2;
                FOR14(const uint32_t v = (t & 1) ? wv[t >> 1].y : wv[t >> 1].x;
                      asm volatile("{ .reg .b16 l, h; mov.b32 {l, h}, %2; st.shared.u16 [%0+%3], l; st.shared.u16 [%1+%3], h; }"
                                   ::"r"(a4[t >= 7 ? 2 : 0]), "r"(a4[t >= 7 ? 3 : 1]), "r"(v), "n"((t % 7) * 1024) : "memory"));
            }
            __syncwarp();
            fence_async();
            bar_arrive(1, 224);
            bar_arrive(9, 224);
            if (w == 1) {
                mbar_wait(BAR(2), 0);
                mbar_wait(BAR(2), 1);
                const int b = blockIdx.x;
                asm volatile(ELECT "cp.async.bulk.prefetch.L2.global [%0], %1; }" ::"l"(wg + b * 6272), "r"(12544) : "memory");
                asm volatile(ELECT "cp.async.bulk.prefetch.L2.global [%0], %1; }" ::"l"(wu + b * 6272), "r"(12544) : "memory");
                asm volatile(ELECT "cp.async.bulk.prefetch.L2.global [%0], %1; }" ::"l"(wd + b * 6272), "r"(12544) : "memory");
            }
        }
        uint32_t kseq = ld_word(g_c1 + (sl * 8 * 16 + tile) * 32);
        int slot = 0, ph = 0, n = NST;
#pragma unroll 1
        for (int layer = 0; layer < 3; layer++) {
            if (w == 0) {
                const int nend = layer == 0 ? 11 : (layer == 1 ? 42 : 63);
#pragma unroll 1
                for (; n < nend; n++) {
                const uint32_t w0 = __shfl_sync(0xffffffffu, n < 32 ? e0[0] : e0[1], n & 31), w1 = __shfl_sync(0xffffffffu, n < 32 ? e1[0] : e1[1], n & 31);
                const uint32_t dst = sb + slot * STAGE, fb = BAR(n == PACK ? B_PACK : slot);
                const CUtensorMap* m0 = &maps.x + ((w0 >> 2) & 15);
                const CUtensorMap* m1 = &maps.x + ((w0 >> 6) & 15);
                const int c0 = (w0 >> 10) & 2047, c1 = w0 >> 21, r0 = w1 & 0xffff, r1 = w1 >> 16;
                if (n == 25) {
                    int it = 0;
                    uint32_t v;
                    do { asm volatile("ld.acquire.gpu.global.u32 %0, [%1];" : "=r"(v) : "l"(g_cw + sl * 32) : "memory"); } while ((int)(v - cw_target) < 0 && ++it < 0x400000);
                    asm volatile("fence.proxy.async.global;" ::: "memory");
                    __syncwarp();
                }
                mbar_wait(BAR(B_EMPTY + slot), ph);
                __syncwarp();
                asm volatile(ELECT "mbarrier.arrive.expect_tx.shared::cta.b64 _, [%0], %1; }" ::"r"(fb), "r"(STAGE) : "memory");
                if ((w0 & 3) == 0) {
                    tma2d(dst, m0, c0, r0, fb);
                    tma2d(dst + HALF, m1, c1, r1, fb);
                } else if (w0 & 1) {
                    asm volatile(ELECT "cp.async.bulk.shared::cluster.global.mbarrier::complete_tx::bytes [%0], [%1], %2, [%3]; }"
                                 ::"r"(dst), "l"(reinterpret_cast<const char*>(g_wp) + (size_t)r0 * STAGE), "r"(STAGE), "r"(fb) : "memory");
                } else {
                    tma2d(dst, m0, c0, r0, fb); tma2d(dst + 7168, m0, c0, r1, fb);
                    tma2d(dst + HALF, m1, c0, r0, fb); tma2d(dst + HALF + 7168, m1, c0, r1, fb);
                }
                if (n == PACK) asm volatile(ELECT "mbarrier.arrive.shared::cta.b64 _, [%0]; }" ::"r"(BAR(slot)) : "memory");
                if (++slot == NST) { slot = 0; ph ^= 1; }
                }
            } else if (w == 1 && layer == 1) {
                constexpr int ps = PACK % NST;
                mbar_wait(BAR(B_PACK), 0);
                asm volatile("{ .reg .pred e; elect.sync _|e, 0xffffffff;\n"
                             "@e cp.async.bulk.global.shared::cta.bulk_group [%0], [%1], %2;\n"
                             "@e cp.async.bulk.commit_group;\n"
                             "@e cp.async.bulk.wait_group.read 0;\n"
                             "@e mbarrier.arrive.shared::cta.b64 _, [%3], 8;\n"
                             "@e cp.async.bulk.wait_group 0;\n"
                             "@e fence.proxy.async.global;\n"
                             "@e red.release.gpu.global.add.u32 [%4], 1; }"
                             ::"l"(reinterpret_cast<char*>(g_wp) + (size_t)(sl * 16 + tile) * STAGE), "r"(sb + ps * STAGE), "r"(STAGE), "r"(BAR(B_EMPTY + ps)), "l"(g_cw + sl * 32) : "memory");
                __syncwarp();
            }
            if (layer < 2) {
            const uint32_t tag = layer ^ 1;
            kseq++;
            bar_sync(7, 384);
            ASTAMP(0);
            if (tile < 15) {
                const int sq = lane >> 3, pk = 8 * w + (lane & (tile == 14 ? 3 : 7));
                uint32_t v[16];
                if (layer == 0) poll_cnt(g_c1 + ((sl * 8 + (w >> 1) * 4 + (tile >> 2)) * 16 + (lane & 15)) * 32, kseq);
                ASTAMP(1);
                poll4_kv<32>(v, g_kv1 + ((sl * 16 + tile) * 16 + 4 * sq) * 32 + pk, tag);
#pragma unroll
                for (int k = 0; k < 4; k++) {
                    float lo = (bf_lo(v[k]) + bf_lo(v[4 + k])) + (bf_lo(v[8 + k]) + bf_lo(v[12 + k]));
                    float hi = (bf_hi(v[k]) + bf_hi(v[4 + k])) + (bf_hi(v[8 + k]) + bf_hi(v[12 + k]));
                    lo += __shfl_xor_sync(0xffffffffu, lo, 8); hi += __shfl_xor_sync(0xffffffffu, hi, 8);
                    lo += __shfl_xor_sync(0xffffffffu, lo, 16); hi += __shfl_xor_sync(0xffffffffu, hi, 16);
                    v[k] = pack2(lo, hi);
                }
                if (sq == 0) st_pkt<0>(g_kv2 + sl * 512 + 32 * tile + pk, settag(v[0], tag), v[1], v[2], v[3]);
            }
            ASTAMP(2);
            {
                const int item = t128 < 112 ? t128 : 112 + (t128 & 3), d = item >> 1;
                const int cc = t128 < 112 ? 2 * (d >= 28) + (item & 1) : item - 112;
                const int r = t128 < 112 ? d : 56 + (cc >> 1) + 2 * ((t128 - 112) >> 2);
                uint32_t ra = sb + OFF_KVB + r * 128 + 4 * cc, rx = (r & 7) << 4;
                asm volatile("" : "+r"(ra), "+r"(rx));
                FOR14(asm volatile("st.shared.u32 [%0+%2], %1;" ::"r"((ra ^ 8) + (((t & 7) << 4) ^ rx)), "r"(0), "n"((t >> 3) * 8192) : "memory"));
                uint32_t v[16];
                asm volatile("" : "+r"(ra), "+r"(rx));
                poll4_kv<8>(v, g_kv2 + sl * 512 + (item >> 3) * 32 + (item & 7), tag);
                FOR14(asm volatile("st.shared.u32 [%0+%2], %1;" ::"r"(ra + (((t & 7) << 4) ^ rx)), "r"(v[t < 7 ? t : t + 1]), "n"((t >> 3) * 8192) : "memory"));
                fence_async();
            }
            bar_arrive(3, 384);
            ASTAMP(3);
            }
        }
    } else {
        asm volatile("setmaxnreg.inc.sync.aligned.u32 232;");
        int lane = fresh_tid() & 31, prf = pr;
#define pr prf
#define g (lane >> 2)
#define c (lane & 3)
#define t128 (w * 32 + lane)
        const int wu = __shfl_sync(0xffffffffu, fresh_tid() >> 5, 0), w = wu & 3;
        const uint32_t xoff = __shfl_sync(0xffffffffu, (3 * PLANE + ((tile * 2 + wgi) * 8) * 512 + w * 128) * 16, 0);
        char* xu = reinterpret_cast<char*>(g_ex) + xoff;
#define FRESH() asm volatile("" : "+l"(xu), "+r"(lane), "+r"(prf))
#define xp0 (reinterpret_cast<uint4*>(xu) + lane)
        const uint32_t hbuf = sb + OFF_H + wgi * STAGE;
        uint32_t slot = 0, ph = 0, eb1 = 0, eb2 = 0, ackph = 0, rcvph = 0, gatph = 0, swp = 0;
        uint32_t ppid = 6;
#define cx(s) (reinterpret_cast<uint32_t*>(reinterpret_cast<uint4*>(xu) + PL(1) + 112 + (s) * 512))
#define stp (reinterpret_cast<uint4*>(xu) + g + PL(0) + 112)
        uint32_t seq = ld_word(cx(sl));
        uint32_t kseq = ld_word(g_c1 + ((sl * 8 + wu) * 16 + tile) * 32);
        uint32_t stag = ld_word(reinterpret_cast<const uint32_t*>(stp + sl * 512) + 3) & 1;
        asm volatile("barrier.cluster.wait.aligned;" ::: "memory");
        STAMP(1);
        uint32_t X[14];
        const uint32_t x0row = (w < 2 ? hbuf : sb + wgi * STAGE) + ((w & 1) * 16 + (lane & 15)) * 128;
        mbar_wait(BAR(wgi), 0);
        STAMP(51);
#pragma unroll
        for (int j = 0; j < 4; j++) {
            const int G = 7 * sl + min(2 * j + (lane >> 4), 6);
            uint32_t q2, q3;
            asm volatile("ldmatrix.sync.aligned.m8n8.x4.shared.b16 {%0,%1,%2,%3}, [%4];" : "=r"(X[4 * j]), "=r"(X[4 * j + 1]), "=r"(q2), "=r"(q3)
                         : "r"(x0row + (G >> 3) * 4096 + (((G ^ lane) & 7) << 4)) : "memory");
            if (j < 3) { X[(4 * j + 2) % 14] = q2; X[(4 * j + 3) % 14] = q3; }
        }
#define PUSH_SLICE(W)                                                                          \
    {                                                                                          \
        if (t128 == 0) mbar_expect_tx(BAR(B_RECV + wgi), 7168);                                \
        PUSH_BEGIN();                                                                          \
        const uint32_t ra = mapa(hbuf + 24576 + t128 * 16, hr ^ 1), rb = mapa(sb + OFF_XR + wgi * 3072, hr ^ 1), rbar = mapa(BAR(B_RECV + wgi), hr ^ 1); \
        st_async4(ra, W[0], W[1], W[2], W[3], rbar);                                           \
        st_async4(ra + 2048, W[4], W[5], W[6], W[7], rbar);                                    \
        st_async4(rb + t128 * 16, W[8], W[9], W[10], W[11], rbar);                             \
        asm volatile("st.async.weak.shared::cluster.mbarrier::complete_tx::bytes.v2.b32 [%0], {%1,%2}, [%3];" ::"r"(rb + 2048 + t128 * 8), "r"(W[12]), "r"(W[13]), "r"(rbar) : "memory"); \
    }
#define PULL_SLICE(W)                                                                          \
    {                                                                                          \
        uint32_t t0, t1;                                                                       \
        mbar_wait(BAR(B_RECV + wgi), rcvph);                                                   \
        rcvph ^= 1;                                                                            \
        lds4(&A[1][0], hbuf + 24576 + t128 * 16);                                              \
        lds4(&A[1][4], hbuf + 26624 + t128 * 16);                                              \
        lds4(&A[1][8], sb + OFF_XR + wgi * 3072 + t128 * 16);                                  \
        asm volatile("ld.shared.v2.u32 {%0,%1}, [%2];" : "=r"(t0), "=r"(t1) : "r"(sb + OFF_XR + wgi * 3072 + 2048 + t128 * 8) : "memory"); \
        _Pragma("unroll") for (int i = 0; i < 12; i++) A[0][i] = (i & 3) ? W[i] : W[i] & ~1u;  \
        A[1][0] &= ~1u; A[1][4] &= ~1u; A[1][8] &= ~1u;                                        \
        A[0][12] = (hr ? t0 : W[12]) & ~1u; A[0][13] = hr ? t1 : W[13];                        \
        A[1][12] = (hr ? W[12] : t0) & ~1u; A[1][13] = hr ? W[13] : t1;                        \
        asm volatile("" : RW4(A[0], 0), RW4(A[0], 4), RW4(A[0], 8), RW2(A[0], 12), RW4(A[1], 0), RW4(A[1], 4), RW4(A[1], 8), RW2(A[1], 12)); \
        swp = hr * 448;                                                                        \
    }
#define SWB(b, t, db, sh) ((b) == 0 && (t) < 6 ? ((t) < 3 ? db##p : db##m) : db)
#define DECL_DB(b, MK, lbo, sh) const uint64_t db = MK(0, lbo, R_ADJ), dbp = (b) == 0 ? MK(0, lbo, R_ADJ + (swp >> (sh))) : db, dbm = (b) == 0 ? MK(0, lbo, R_ADJ - (swp >> (sh))) : db;
#define PPB 2
#define PP_WAIT() if (wgi == 1) { bar_sync(ppid, 256); ppid ^= 14; }
#define PP_GO() if (wgi == 0) { bar_arrive(ppid, 256); ppid ^= 14; }
#define GAT_DST(B, s2) ((B) == 1 ? hbuf + w * 3584 + (s2) * 1792 : ((s2) ? sb + OFF_KVB + wgi * 8192 : hbuf + 14336) + w * 1792)
#define GAT_ISSUE(B, base)                                                                     \
    {                                                                                          \
        const char* gs = xu + ((base) + kblk(pr, B) * 1024) * 16;                              \
        asm volatile("{ .reg .pred e; elect.sync _|e, 0xffffffff;\n"                           \
                     "@e mbarrier.arrive.expect_tx.shared::cta.b64 _, [%3], 3584;\n"           \
                     "@e cp.async.bulk.shared::cluster.global.mbarrier::complete_tx::bytes [%0], [%2], 1792, [%3];\n" \
                     "@e cp.async.bulk.shared::cluster.global.mbarrier::complete_tx::bytes [%1], [%2+8192], 1792, [%3]; }" \
                     ::"r"(GAT_DST(B, 0)), "r"(GAT_DST(B, 1)), "l"(gs), "r"(BAR(B_GAT + wu * 2 + ((B) >> 1))) : "memory"); \
        __syncwarp();                                                                          \
    }
#define GAT_FETCH(B)                                                                           \
    {                                                                                          \
        mbar_wait(BAR(B_GAT + wu * 2 + ((B) >> 1)), (gatph >> (B)) & 1);                          \
        gatph ^= 1 << (B);                                                                     \
        _Pragma("unroll") for (int s2 = 0; s2 < 2; s2++) {                                     \
            const uint32_t ga = GAT_DST(B, s2) + lane * 16;                                    \
            lds4(&A[2 * (B) + s2][0], ga); lds4(&A[2 * (B) + s2][4], ga + 512); lds4(&A[2 * (B) + s2][8], ga + 1024); \
            asm volatile("ld.shared.v2.u32 {%0,%1}, [%2];" : "=r"(A[2 * (B) + s2][12]), "=r"(A[2 * (B) + s2][13]) : "r"(ga - lane * 8 + 1536) : "memory"); \
        }                                                                                      \
    }
#define LATE_ARRIVE() do { if (lane == 0) mbar_arrive(BAR(B_LATE)); } while (0)
#define LATE_WAIT() do { mbar_wait(BAR(B_LATE), gatph & 1); gatph ^= 1; } while (0)
#define PT 3
#define PREP(b, t, remote)                                                                     \
    if constexpr ((b) < 3 && (t) == PT) {                                                      \
        wg_commit();                                                                           \
        STAMP(74 + 6 * (step & 1) + 2 * (b));                                                  \
        if (remote) {                                                                          \
            if constexpr ((b) == 0) { blk_load<2>(A, BLK(xsrc, 2), lane); GAT_FETCH(1) }       \
            blk_check<((b) + 1) & 3>(A, BLK(xsrc, (b) + 1), lane, xtag);                       \
            if constexpr ((b) == 0) blk_load<3>(A, BLK(xsrc, 3), lane);                        \
        }                                                                                      \
        STAMP(75 + 6 * (step & 1) + 2 * (b));                                                  \
        normalize<((b) + 1) & 3>(A, k0, k1);                                                   \
        asm volatile("" : RW4(A[(2 * (b) + 2) & 7], 0), RW4(A[(2 * (b) + 2) & 7], 4), RW4(A[(2 * (b) + 2) & 7], 8), RW2(A[(2 * (b) + 2) & 7], 12), \
                          RW4(A[(2 * (b) + 3) & 7], 0), RW4(A[(2 * (b) + 3) & 7], 4), RW4(A[(2 * (b) + 3) & 7], 8), RW2(A[(2 * (b) + 3) & 7], 12)); \
        wg_fence();                                                                            \
    }
#define X0_BLOCK(b)                                                                            \
    { const int rr = lane & 7, hi = lane >> 4;                                                 \
    const uint32_t rowa = (w < 2 ? hbuf : sb + wgi * STAGE) + ((w & 1) * 16 + (lane & 15)) * 128; \
    FOR7(constexpr int G = 14 * (b) + (t < 3 ? 2 * t : (t < 6 ? 2 * t + 1 : 6));               \
         uint32_t q0, q1, q2, q3;                                                              \
         const uint32_t ad = t < 6 ? rowa + (((((G & 7) + hi) ^ rr) & 7) << 4) + ((G & 7) == 7 ? hi * 4096 : 0) : rowa + ((G + 7 * hi) >> 3) * 4096 + ((((G + 7 * hi) ^ rr) & 7) << 4); \
         asm volatile("ldmatrix.sync.aligned.m8n8.x4.shared.b16 {%0,%1,%2,%3}, [%4+%5];" : "=r"(q0), "=r"(q1), "=r"(q2), "=r"(q3) \
                      : "r"(ad), "n"(t < 6 ? (G >> 3) * 4096 : 0) : "memory");                 \
         if (t < 3) { A[2 * (b)][4 * t] = q0; A[2 * (b)][4 * t + 1] = q1; A[2 * (b)][4 * t + 2] = q2; A[2 * (b)][4 * t + 3] = q3; } \
         else if (t < 6) { A[2 * (b) + 1][(4 * t - 12) & 15] = q0; A[2 * (b) + 1][((4 * t - 12) & 15) + 1] = q1; A[2 * (b) + 1][((4 * t - 12) & 15) + 2] = q2; A[2 * (b) + 1][((4 * t - 12) & 15) + 3] = q3; } \
         else { A[2 * (b)][12] = q0; A[2 * (b)][13] = q1; A[2 * (b) + 1][12] = q2; A[2 * (b) + 1][13] = q3; }); }
#define BLK(base, b) ((base) + kblk(pr, b) * 1024)

#pragma unroll 1
        for (int step = 0; step < 4; step++) {
            FRESH();
            const uint32_t tag = (step >> 1) ^ 1;
            const int so = (step >> 1) * 24 + (step & 1) * 12;
            (void)so;
            uint32_t A[8][14];
            uint4* const xsrc = xp0 + ((step & 1) ? PL(2) : PL(0));
            const uint32_t xtag = (step & 1) ? tag : ((seq >> 3) & 1) ^ 1;
            uint32_t xbits;
            {
                float st[4];
                slice_stats(X, st);
                stag ^= 1;
                xbits = x_bits(X);
                tag_slice(X, xtag);
                if (step) send_slice<0>(xsrc + sl * 512, lane, X);
                if (c == 0) st_pkt<0>(stp + sl * 512, __float_as_uint(st[0]), __float_as_uint(st[1]), __float_as_uint(st[2]), settag(__float_as_uint(st[3]), stag));
            }
            STAMP(2 + so);
            uint32_t sv[8];
            if (step == 0) {
                X0_BLOCK(0) X0_BLOCK(1) X0_BLOCK(2) X0_BLOCK(3)
                mbar_wait(BAR(wgi ^ 1), 0);
                R_NEXT();
                R_NEXT();
                R_RELEASE(2);
                stat_load(sv, stp + c * 1024);
                stat_check(sv, stp + c * 1024, stag);
                STAMP(52 + step);
            } else {
                kill<14>(A[2]); kill<14>(A[3]); kill<14>(A[4]); kill<14>(A[5]); kill<14>(A[6]); kill<14>(A[7]);
                PUSH_SLICE(X)
                stat_load(sv, stp + c * 1024);
                PULL_SLICE(X)
                stat_check(sv, stp + c * 1024, stag);
                STAMP(52 + step);
                GAT_ISSUE(1, (step & 1) ? PL(2) : PL(0))
            }
            LnCoef k0, k1;
            {
                k0 = ln_coef(__uint_as_float(sv[0]) + __uint_as_float(sv[4]), __uint_as_float(sv[1]) + __uint_as_float(sv[5]));
                k1 = ln_coef(__uint_as_float(sv[2]) + __uint_as_float(sv[6]), __uint_as_float(sv[3] & ~1u) + __uint_as_float(sv[7] & ~1u));
            }
            STAMP(3 + so);
            GSTAMP(70 + step);

            if ((step & 1) == 0) {
                float tq[28];
                {
                    float av[28];
#define KV_BLOCK(b)                                                                           \
    if ((b) == 1) R_RELEASE(2);                                                               \
    if ((b) == 2) { PUSH_ACK(); wg_wait<2>(); R_RELEASE(2); }                                 \
    R_WAIT();                                                                                 \
    if ((b) == PPK) { PP_WAIT() }                                                             \
    { DECL_DB(b, BASE128, 16, 0)                                                              \
    wg_fence();                                                                               \
    FOR7(mma_rs56<1, D128(0, t)>(tq, AQ(A, b, t), (b) + t > 0, SWB(b, t, db, 0));             \
         mma_rs56<1, D128(HALF, t)>(av, AQ(A, b, t), (b) + t > 0, SWB(b, t, db, 0));          \
         PREP(b, t, step)); }                                                                 \
    wg_commit();                                                                              \
    if ((b) == 3 && PPK < 4) { PP_GO() }                                                      \
    R_NEXT();
                    normalize<0>(A, k0, k1);
                    KV_BLOCK(0) KV_BLOCK(1) KV_BLOCK(2) KV_BLOCK(3)
                    wg_wait<0>();
                    if (lane < 3) mbar_arrive(BAR(B_EMPTY + (slot + NST - 1 - lane) % NST));
                    STAMP(4 + so);
                    WSUM(80 + 7 * (step >> 1));
                    const int m = lane >> 3, rr = lane & 7;
                    const uint32_t rowa = hbuf + 16384 + (w * 16 + rr + 8 * (m & 1)) * 128;
                    const uint32_t one = c == 0 ? 0x00003f80u : 0u;
                    if (step == 0) { bar_sync(wgi ? 9 : 1, 224); }
#pragma unroll
                    for (int j = 0; j < 4; j++) {
                        const uint32_t a = rowa + (((2 * j + (m >> 1)) ^ rr) << 4);
                        if (j < 3) stsm4(a, pack2(av[8 * j], av[8 * j + 1]), pack2(av[8 * j + 2], av[8 * j + 3]), pack2(av[8 * j + 4], av[8 * j + 5]), pack2(av[8 * j + 6], av[8 * j + 7]));
                        else stsm4(a, pack2(av[24], av[25]), pack2(av[26], av[27]), one, one);
                    }
                }
                uint32_t PH[28];
                int it = 1;
#pragma unroll 1
                do {
                    float pp[28];
                    phi_gemm(tq, pp);
                    dual_softmax(pp, PH);
                    if (((trips >> (it + 1)) & 1) == 0) continue;
                    {
                        const int m = lane >> 3, rr = lane & 7;
                        const uint32_t rowa = hbuf + (w * 16 + rr + 8 * (m & 1)) * 128;
#pragma unroll
                        for (int j = 0; j < 7; j++) {
                            const int cg = 2 * j + (m >> 1), hi = cg >= 7;
                            stsm4(rowa + hi * 8192 + (((cg - 7 * hi) ^ rr) << 4), PH[4 * j], PH[4 * j + 1], PH[4 * j + 2], PH[4 * j + 3]);
                        }
                    }
                    fence_async();
                    STAMP(5 + so);
#define Q_STAGE(b0)                                                                           \
    R_WAIT();                                                                                 \
    { DECL_DB(b0, BASE128, 16, 0)                                                             \
    wg_fence();                                                                               \
    FOR7(mma_rs56<1, D128(0, t)>(tq, AQ(A, b0, t), (b0) + t > 0, SWB(b0, t, db, 0)));         \
    FOR7(mma_rs56<1, D128(HALF, t)>(tq, AQ(A, (b0) + 1, t), 1, db)); }                        \
    wg_commit();                                                                              \
    R_NEXT();
                    if (QE && wgi == 0) { kill<28>(tq); Q_STAGE(0) Q_STAGE(2) wg_wait<1>(); R_RELEASE(2); wg_wait<0>(); R_RELEASE(1); }
                    bar_sync(2, 256);
                    float kv[28];
                    const uint64_t da = BASE128(OFF_H + 16384, 16, 0), dbk = BASE128(OFF_H, 16, wgi * 512);
                    wg_fence();
                    FOR8(constexpr uint64_t o = ((t >> 2) * STAGE + (t & 3) * 2048) >> 4; mma_ss56_tt<o, o>(kv, t > 0, da, dbk));
                    wg_commit();
                    wg_wait<0>();
#pragma unroll
                    for (int hf = 0; hf < 2; hf++) {
                        const int d = 16 * w + g + 8 * hf;
                        if ((d < 56 && (d >= 28) == (c >= 2)) || d == 56) {
                            const int item = d < 56 ? 2 * d + (c & 1) : 112 + c;
                            uint4* dst = g_kv1 + ((sl * 16 + (item >> 3)) * 16 + tile) * 32 + wgi * 16 + (item & 7);
#define KVW(i) pack2(kv[4 * (i) + 2 * hf], kv[4 * (i) + 2 * hf + 1])
                            st_pkt<0>(dst, settag(KVW(0), tag), KVW(1), KVW(2), KVW(3));
                            st_pkt<8>(dst, settag(KVW(4), tag), KVW(5), KVW(6), 0u);
                        }
                    }
                    __syncwarp();
                    kseq++;
                    if (lane == 0) st_word(g_c1 + ((sl * 8 + wu) * 16 + tile) * 32, kseq);
                    bar_arrive(7, 384);
                    STAMP(6 + so);
                    if (!QE || wgi == 1) { kill<28>(tq); Q_STAGE(0) Q_STAGE(2) wg_wait<1>(); R_RELEASE(2); wg_wait<0>(); R_RELEASE(1); }
                    STAMP(7 + so);
                    kill<28>(PH);
                } while (((trips >> (++it)) & 1));
                STAMP(8 + so);
                FRESH();
                if (step) {
                    slice_load<PL(0)>(X, xp0 + sl * 512, lane);
                } else {
                    const uint32_t* xp = reinterpret_cast<const uint32_t*>(x_in + (size_t)(tile * 128 + wu * 16 + g) * 448 + 56 * sl + 2 * c);
#pragma unroll
                    for (int i = 0; i < 7; i++) { X[2 * i] = __ldg(xp + 4 * i); X[2 * i + 1] = __ldg(xp + 4 * i + 8 * 224); }
                }
                bar_sync(3, 384);
                STAMP(9 + so);
                const uint4* const osrc = xp0 + PL(1);
                {
                    float nm[32];
                    const uint64_t db = BASE128(OFF_KVB, 16, 0);
                    wg_fence();
                    FOR7(mma_rs64<0, ((t >> 2) * 8192 + (t & 3) * 32) / 16>(nm, PH[4 * t], PH[4 * t + 1], PH[4 * t + 2], PH[4 * t + 3], t > 0, db));
                    wg_commit();
                    wg_wait<0>();
                    LATE_ARRIVE();
                    const float i00 = rcp(nm[28] + 1e-6f), i01 = rcp(nm[29] + 1e-6f), i10 = rcp(nm[30] + 1e-6f), i11 = rcp(nm[31] + 1e-6f);
                    const float m0 = c >= 2 ? i01 : i00, m1 = c >= 2 ? i11 : i10;
                    uint32_t O[14];
#pragma unroll
                    for (int i = 0; i < 7; i++) {
                        const float f0 = i < 3 ? i00 : (i > 3 ? i01 : m0), f1 = i < 3 ? i10 : (i > 3 ? i11 : m1);
                        O[2 * i] = pack2(nm[4 * i] * f0, nm[4 * i + 1] * f0);
                        O[2 * i + 1] = pack2(nm[4 * i + 2] * f1, nm[4 * i + 3] * f1);
                    }
                    if (OST) { PP_WAIT() }
                    tag_slice(O, tag);
                    send_slice<PL(1)>(xp0 + sl * 512, lane, O);
                    seq++;
                    if (lane == 0) st_word(cx(sl), seq);
                    STAMP(10 + so);
                    PUSH_SLICE(O)
                    if (OST == 1) { PP_GO() }
                    const uint32_t cv = ld_word(cx(lane & 7));
                    PULL_SLICE(O)
                    LATE_WAIT();
                    check_cnt(cv, cx(lane & 7), seq);
                    if (OST == 2) { PP_GO() }
                    STAMP(56 + (step >> 1));
                    GAT_ISSUE(1, PL(1))
                    GAT_ISSUE(3, PL(1))
                    blk_load<2>(A, BLK(osrc, 2), lane);
                }
                float ao[28];
#define WO_BLOCK(b)                                                                           \
    if ((b) > 0) blk_check<b>(A, BLK(osrc, b), lane, tag);                                    \
    if (((b) & 1) == 0) R_WAIT();                                                             \
    { DECL_DB(b, BASE128, 16, 0)                                                              \
    wg_fence();                                                                               \
    FOR7(mma_rs56<1, D128(((b) & 1) * HALF, t)>(ao, AQ(A, b, t), (b) + t > 0, SWB(b, t, db, 0))); } \
    wg_commit();                                                                              \
    if ((b) & 1) R_NEXT();
                WO_BLOCK(0)
                STAMP(11 + so);
                GAT_FETCH(1)
                WO_BLOCK(1)
                WO_BLOCK(2)
                GAT_FETCH(3)
                WO_BLOCK(3)
                PUSH_ACK();
                wg_wait<0>();
                R_RELEASE(2);
                STAMP(12 + so);
                WSUM(86 + 7 * (step >> 1));
                x_fix(X, xbits);
#pragma unroll
                for (int i = 0; i < 14; i++) X[i] = pack2(bf_lo(X[i]) + ao[2 * i], bf_hi(X[i]) + ao[2 * i + 1]);
            } else {
                uint32_t H[56];
                float ag[64];
#define F1_EPI(dst, ng, ag)                                                                    \
    _Pragma("unroll") for (int i = 0; i < 2 * (ng); i++)                                       \
        (dst)[i] = pack2(geglu(ag[2 * i], ag[4 * (ng) + 2 * i]), geglu(ag[2 * i + 1], ag[4 * (ng) + 2 * i + 1]));
#define H_PUSH(h0, off) st_async4(rem_h + (off), H[h0], H[(h0) + 1], H[(h0) + 2], H[(h0) + 3], mapa(BAR(B_RECV2 + wgi), hr ^ 1));
#define F1_BLOCK(b, first)                                                                     \
    if ((first) && (b) == 1) R_RELEASE(2);                                                     \
    if ((first) && (b) == 2) PUSH_ACK();                                                       \
    R_WAIT();                                                                                  \
    if ((b) == ((first) ? PPF : PPB)) { PP_WAIT() }                                            \
    { DECL_DB(b, BASE128, HALF, 0)                                                             \
    wg_fence();                                                                                \
    FOR7(mma_rs128<1, D128(0, t)>(ag, AQ(A, b, t), (b) + t > 0, SWB(b, t, db, 0));             \
         if constexpr (first) { PREP(b, t, true) }); }                                         \
    wg_commit();                                                                               \
    if ((b) == 3) { PP_GO() }                                                                  \
    if ((b) > 0) { wg_wait<1>(); R_RELEASE(1); }       \
    R_NEXT();
                normalize<0>(A, k0, k1);
                F1_BLOCK(0, true) F1_BLOCK(1, true) F1_BLOCK(2, true) F1_BLOCK(3, true)
                if (t128 == 0) { mbar_expect_tx(BAR(B_RECV + wgi), 16384); mbar_expect_tx(BAR(B_RECV2 + wgi), 12288); }
                PUSH_BEGIN();
                wg_wait<0>();
                R_RELEASE(1);
                int p = 0;
#pragma unroll 1
                do {
                    F1_EPI(H + 32, 8, ag)
                    STAMP(4 + p + so);
                    WSUM(81 + p + 7 * (step >> 1));
                    if (((trips >> (p + 1)) & 1) == 0) continue;
                    if (step == 1 && p == PKP) R_NEXT();
                    kill<64>(ag);
                    F1_BLOCK(0, false)
                    {
                        const uint32_t pk = (p ? hbuf + 16384 : sb + OFF_KVB + wgi * 8192) + w * 2048;
#pragma unroll
                        for (int k = 0; k < 4; k++) sts4(pk + k * 512 + lane * 16, H[32 + 4 * k], H[33 + 4 * k], H[34 + 4 * k], H[35 + 4 * k]);
                        fence_async();
                        __syncwarp();
                        asm volatile(ELECT "cp.async.bulk.shared::cluster.shared::cta.mbarrier::complete_tx::bytes [%0], [%1], 2048, [%2]; }"
                                     ::"r"(mapa(hbuf + p * 8192 + w * 2048, hr ^ 1)), "r"(pk), "r"(mapa(BAR(B_RECV + wgi), hr ^ 1)) : "memory");
                    }
                    F1_BLOCK(1, false) F1_BLOCK(2, false) F1_BLOCK(3, false)
                    wg_wait<0>();
                    R_RELEASE(1);
                    kill<16>(H + 32);
                } while (((trips >> (++p)) & 1));
#pragma unroll
                for (int k = 0; k < 4; k++) lds4(H + 16 + 4 * k, hbuf + 16384 + w * 2048 + k * 512 + lane * 16);
                __syncwarp();
                if (lane == 0) asm volatile("mbarrier.arrive.shared::cluster.b64 _, [%0];" ::"r"(mapa(BAR(B_ACK2 + wgi), hr ^ 1)) : "memory");
                const uint32_t rem_h = mapa(hbuf + w * 2048 + lane * 16, hr ^ 1);
#define F1_LAST(b0)                                                                            \
    R_WAIT();                                                                                  \
    if (b0) { PP_WAIT() }                                                                      \
    { DECL_DB(b0, BASE64, HALF, 1)                                                             \
    wg_fence();                                                                                \
    FOR7(mma_rs64<1, D64(0, t)>(al, AQ(A, b0, t), (b0) + t > 0, SWB(b0, t, db, 1)));           \
    FOR7(mma_rs64<1, D64(7168, t)>(al, AQ(A, (b0) + 1, t), 1, db)); }                          \
    wg_commit();                                                                               \
    if (b0) { PP_GO() }                                                                        \
    R_NEXT();
                float al[32];
                F1_LAST(0)
                mbar_wait(BAR(B_RECV + wgi), rcvph);
                rcvph ^= 1;
                mbar_wait(BAR(B_ACK2 + wgi), step >> 1);
                H_PUSH(32, 16384) H_PUSH(36, 16896)
                F1_LAST(2)
                H_PUSH(40, 17408) H_PUSH(44, 17920)
                wg_wait<1>();
                R_RELEASE(2);
                wg_wait<0>();
                R_RELEASE(1);
                float acc[28];
                const uint32_t roA = hr ? 256u : 0u, roB = hr ? (uint32_t)-1536 : 0u;
                const uint32_t rpA = hr ? 0u : 256u, rpB = hr ? 0u : (uint32_t)-1536;
                uint64_t d0, d1;
                R_WAIT();
                d0 = BASE128(0, 16, R_ADJ + roA); d1 = BASE128(0, 16, R_ADJ + roB);
                wg_fence();
                FOR14(if constexpr (t >= 4 && t < 4 + EOWN) mma_rs56<1, t * 128>(acc, H[4 * t], H[4 * t + 1], H[4 * t + 2], H[4 * t + 3], t > 4, d0));
                wg_commit();
                uint32_t HP[56];
#pragma unroll
                for (int k = 0; k < 4; k++) lds4(H + 4 * k, sb + OFF_KVB + wgi * 8192 + w * 2048 + k * 512 + lane * 16);
#pragma unroll
                for (int t = 0; t < 8; t++) lds4(HP + 4 * t, hbuf + (t >> 2) * 8192 + w * 2048 + (t & 3) * 512 + lane * 16);
                F1_EPI(H + 48, 4, al)
                H_PUSH(48, 24576 - w * 1024) H_PUSH(52, 25088 - w * 1024)
                STAMP(7 + so);
                WSUM(84 + 7 * (step >> 1));
                FRESH();
                float res[28];
                uint32_t v0[14], v1[14], P[14];
                const uint4* ps = xp0 + sl * 512;
#define F2_OWN_A()                                                                             \
    R_WAIT();                                                                                  \
    d0 = BASE128(0, 16, R_ADJ + roA); d1 = BASE128(0, 16, R_ADJ + roB);                        \
    wg_fence();                                                                                \
    FOR14(if constexpr (t < OT) mma_rs56<1, t * 128>(acc, H[4 * t], H[4 * t + 1], H[4 * t + 2], H[4 * t + 3], t > 0, d0)); \
    wg_commit();
#define F2_OWN_B()                                                                             \
    wg_fence();                                                                                \
    FOR14(if constexpr (t >= OT) mma_rs56<1, t * 128>(acc, H[4 * t], H[4 * t + 1], H[4 * t + 2], H[4 * t + 3], 1, t < 12 ? d0 : d1)); \
    wg_commit();                                                                               \
    R_NEXT();
#define F2_PEER()                                                                              \
    R_WAIT();                                                                                  \
    if (F2PP) { PP_WAIT() }                                                                    \
    d0 = BASE128(0, 16, R_ADJ + rpA); d1 = BASE128(0, 16, R_ADJ + rpB);                        \
    wg_fence();                                                                                \
    FOR14(mma_rs56<1, t * 128>(acc, HP[4 * t], HP[4 * t + 1], HP[4 * t + 2], HP[4 * t + 3], 1, t < 12 ? d0 : d1)); \
    wg_commit();                                                                               \
    if (F2PP) { PP_GO() }                                                                      \
    R_NEXT();
#define F2_TURN(u)                                                                             \
    wg_wait<1>();                                                                              \
    if ((u) < 2 || TDEF < 2) R_RELEASE(2);                                                     \
    wg_wait<0>();                                                                              \
    if ((u) < 2 || TDEF < 1) R_RELEASE(1);                                                     \
    _Pragma("unroll") for (int i = 0; i < 14; i++) P[i] = pack2(acc[2 * i], acc[2 * i + 1]);   \
    tag_slice(P, tag);                                                                         \
    asm volatile("" : RW4(P, 0), RW4(P, 4), RW4(P, 8), RW2(P, 12));                            \
    kill<28>(acc);                                                                             \
    F2_OWN_A()                                                                                 \
    if ((u) == 2) { slice_load<PL(3)>(v0, ps, lane); slice_load<PL(4)>(v1, ps, lane); } \
    send_slice<PL(3 + (u))>(xp0 + (2 * ((pr + (u) + 1) & 3) + hr) * 512, lane, P);             \
    seq++;                                                                                     \
    if (lane == 0) st_word(cx(sl), seq);                                                       \
    __syncwarp();                                                                              \
    STAMP(8 + (u) + so);                                                                       \
    F2_OWN_B()
                wg_fence();
                FOR14(if constexpr (t < 4 || t >= 4 + EOWN) mma_rs56<1, t * 128>(acc, H[4 * t], H[4 * t + 1], H[4 * t + 2], H[4 * t + 3], 1, t < 12 ? d0 : d1));
                wg_commit();
                R_NEXT();
                R_WAIT();
                d0 = BASE128(0, 16, R_ADJ + rpA); d1 = BASE128(0, 16, R_ADJ + rpB);
                wg_fence();
                FOR8(mma_rs56<1, t * 128>(acc, HP[4 * t], HP[4 * t + 1], HP[4 * t + 2], HP[4 * t + 3], 1, d0));
                wg_commit();
                mbar_wait(BAR(B_RECV2 + wgi), step >> 1);
#pragma unroll
                for (int k = 0; k < 4; k++) lds4(HP + 32 + 4 * k, hbuf + 16384 + w * 2048 + k * 512 + lane * 16);
                lds4(HP + 48, hbuf + 24576 + w * 1024 + lane * 16);
                lds4(HP + 52, hbuf + 25088 + w * 1024 + lane * 16);
                if (step == 1) PUSH_ACK();
                wg_fence();
                FOR14(if constexpr (t >= 8) mma_rs56<1, t * 128>(acc, HP[4 * t], HP[4 * t + 1], HP[4 * t + 2], HP[4 * t + 3], 1, t < 12 ? d0 : d1));
                wg_commit();
                R_NEXT();
                F2_TURN(0)
                F2_PEER()
                F2_TURN(1)
                F2_PEER()
                F2_TURN(2)
                if (step == 1) STAMP(64);
                slice_check<PL(3)>(v0, ps, lane, tag);
                slice_check<PL(4)>(v1, ps, lane, tag);
#pragma unroll
                for (int i = 0; i < 14; i++) { res[2 * i] = bf_lo(v0[i]) + bf_lo(v1[i]); res[2 * i + 1] = bf_hi(v0[i]) + bf_hi(v1[i]); }
                slice_load<PL(2)>(X, ps, lane);
                if (step == 1) STAMP(65);
                F2_PEER()
                if (step == 1) STAMP(66);
                poll_cnt(cx(2 * ((pr + 1) & 3) + hr), seq);
                if (step == 1) STAMP(67);
                slice_load<PL(5)>(v0, ps, lane);
                x_fix(X, xbits);
                slice_check<PL(5)>(v0, ps, lane, tag);
                if (lane < TDEF) mbar_arrive(BAR(B_EMPTY + (slot + NST - 3 - lane) % NST));
#pragma unroll
                for (int i = 0; i < 14; i++) { res[2 * i] += bf_lo(v0[i]); res[2 * i + 1] += bf_hi(v0[i]); }
                STAMP(11 + so);
                wg_wait<0>();
                R_RELEASE(2);
                STAMP(12 + so);
                WSUM(85 + 7 * (step >> 1));
#pragma unroll
                for (int i = 0; i < 14; i++) X[i] = pack2(fmaf(res[2 * i] + acc[2 * i], 0.5f, bf_lo(X[i])), fmaf(res[2 * i + 1] + acc[2 * i + 1], 0.5f, bf_hi(X[i])));
            }
        }
        {
            const int m = lane >> 3, rr = lane & 7;
            const uint32_t ob = hbuf + w * 2048, rowa = ob + (rr + 8 * (m & 1)) * 112 + (m >> 1) * 16;
#pragma unroll
            for (int j = 0; j < 3; j++) stsm4(rowa + 32 * j, X[4 * j], X[4 * j + 1], X[4 * j + 2], X[4 * j + 3]);
            asm volatile("stmatrix.sync.aligned.m8n8.x2.shared.b16 [%0], {%1,%2};" ::"r"(ob + (rr + 8 * (m & 1)) * 112 + 96), "r"(X[12]), "r"(X[13]) : "memory");
            fence_async();
            __syncwarp();
            if (lane == 0) {
                asm volatile("cp.async.bulk.tensor.2d.global.shared::cta.bulk_group [%0, {%2, %3}], [%1];" ::"l"(&maps.out), "r"(ob), "r"(56 * sl), "r"(tile * 128 + wu * 16) : "memory");
                asm volatile("cp.async.bulk.commit_group;" ::: "memory");
                asm volatile("cp.async.bulk.wait_group.read 0;" ::: "memory");
            }
        }
        STAMP(50);
        GSTAMP(61);
        PDUMP();
    }
}

#undef g
#undef pr
#undef c
#undef t128

typedef CUresult (*EncodeFn)(CUtensorMap*, CUtensorMapDataType, cuuint32_t, void*, const cuuint64_t*, const cuuint64_t*, const cuuint32_t*,
                             const cuuint32_t*, CUtensorMapInterleave, CUtensorMapSwizzle, CUtensorMapL2promotion, CUtensorMapFloatOOBfill);

static void make_map(EncodeFn enc, CUtensorMap* m, const void* p, uint64_t cols, uint64_t rows, uint32_t bc, uint32_t br, CUtensorMapSwizzle sw) {
    cuuint64_t gd[2] = {cols, rows};
    cuuint64_t gs[1] = {cols * 2};
    cuuint32_t bd[2] = {bc, br};
    cuuint32_t es[2] = {1, 1};
    enc(m, CU_TENSOR_MAP_DATA_TYPE_BFLOAT16, 2, const_cast<void*>(p), gd, gs, bd, es, CU_TENSOR_MAP_INTERLEAVE_NONE, sw,
        CU_TENSOR_MAP_L2_PROMOTION_L2_128B, CU_TENSOR_MAP_FLOAT_OOB_FILL_NONE);
}

extern "C" void kernel_launch(void* const* d_in, const int* in_sizes, int n_in, void* d_out, int out_size) {
    (void)in_sizes; (void)n_in; (void)out_size;
    static EncodeFn enc = nullptr;
    static Scratch* scratch = nullptr;
    if (!enc) {
        void* fn = nullptr;
        cudaDriverEntryPointQueryResult qr;
        cudaGetDriverEntryPoint("cuTensorMapEncodeTiled", &fn, cudaEnableDefault, &qr);
        enc = (EncodeFn)fn;
        cudaGetSymbolAddress((void**)&scratch, g_scratch);
        cudaFuncSetAttribute(fused_kernel, cudaFuncAttributeMaxDynamicSharedMemorySize, SMEM_BYTES);
    }
    Maps maps;
    {
        cuuint64_t gd[3] = {64, 2048, 7};
        cuuint64_t gs[2] = {896, 128};
        cuuint32_t bd[3] = {64, 32, 7};
        cuuint32_t es[3] = {1, 1, 1};
        enc(&maps.x, CU_TENSOR_MAP_DATA_TYPE_BFLOAT16, 3, d_in[0], gd, gs, bd, es, CU_TENSOR_MAP_INTERLEAVE_NONE, CU_TENSOR_MAP_SWIZZLE_128B,
            CU_TENSOR_MAP_L2_PROMOTION_L2_128B, CU_TENSOR_MAP_FLOAT_OOB_FILL_NONE);
    }
    make_map(enc, &maps.out, d_out, 448, 2048, 56, 16, CU_TENSOR_MAP_SWIZZLE_NONE);
    make_map(enc, &maps.qkv, d_in[1], 1344, 448, 64, 112, CU_TENSOR_MAP_SWIZZLE_128B);
    make_map(enc, &maps.wo, d_in[3], 448, 448, 64, 112, CU_TENSOR_MAP_SWIZZLE_128B);
    make_map(enc, &maps.wg, d_in[5], 1792, 448, 64, 112, CU_TENSOR_MAP_SWIZZLE_128B);
    make_map(enc, &maps.wu, d_in[6], 1792, 448, 64, 112, CU_TENSOR_MAP_SWIZZLE_128B);
    make_map(enc, &maps.wg32, d_in[5], 1792, 448, 32, 112, CU_TENSOR_MAP_SWIZZLE_64B);
    make_map(enc, &maps.wu32, d_in[6], 1792, 448, 32, 112, CU_TENSOR_MAP_SWIZZLE_64B);
    make_map(enc, &maps.wd, d_in[7], 448, 1792, 64, 112, CU_TENSOR_MAP_SWIZZLE_128B);
    fused_kernel<<<128, 384, SMEM_BYTES>>>(scratch, (const __nv_bfloat16*)d_in[0], (const __nv_bfloat16*)d_in[2], 7, (const __nv_bfloat16*)d_in[5],
                                           (const __nv_bfloat16*)d_in[6], (const __nv_bfloat16*)d_in[7], maps);
}
```

```cpp
#include <cuda_runtime.h>
#include <cuda.h>
#include <cuda_bf16.h>
#include <stdint.h>
#include <type_traits>

#define PPF 2
#define PKP 0
#define TDEF 1
#define TMPF 0
#define NORM1 0
#define LPARK 1
#define PT0 3
#define L2T PT0
#define ACAN 0
#define SPLIT0 1
#define OT 2
#define F2PP 0
#define PPK 2
#define QE 1
#define OST 1
#define PP

namespace {

constexpr uint32_t STAGE = 28672, HALF = 14336;
constexpr int NST = 5;
constexpr uint32_t OFF_H = NST * STAGE;
constexpr uint32_t OFF_KVB = OFF_H + 2 * STAGE;
constexpr uint32_t OFF_WPHI = OFF_KVB + 16384;
constexpr uint32_t OFF_XR = OFF_WPHI + 7168;
constexpr uint32_t OFF_BAR = OFF_XR + 6144;
constexpr uint32_t SMEM_BYTES = OFF_BAR + 384 + 1408;
constexpr int B_EMPTY = NST, B_RECV = 2 * NST, B_RECV2 = B_RECV + 2, B_PACK = B_RECV2 + 2, B_GAT = B_PACK + 1, B_LATE = B_GAT + 16, B_ACK = B_LATE + 1, B_ACK2 = B_ACK + 2, B_COUNT = B_ACK2 + 2;

constexpr int PACK = 14 + 4 * PKP;

struct Maps { CUtensorMap x, qkv, wo, wg, wu, wg32, wu32, wd, out; };

}

constexpr int PLANE = 16 * 2 * 8 * 512;
struct Scratch {
    uint4 ex[6 * PLANE];
    uint4 kv1[8 * 16 * 16 * 32];
    uint4 kv2[8 * 512];
    uint32_t c1[8 * 8 * 16 * 32];
    uint32_t cw[8 * 32];
    uint4 wp[8 * 32 * (HALF / 16)];
};
__device__ __align__(1024) Scratch g_scratch;
#define g_ex (sc->ex)
#define g_kv1 (sc->kv1)
#define g_kv2 (sc->kv2)
#define g_c1 (sc->c1)
#define g_cw (sc->cw)
#define g_wp (sc->wp)
#define STAMP(i)
#define GSTAMP(i)
#define PDUMP()
#define ASTAMP(i)

namespace {

__device__ __forceinline__ int fresh_tid() { int t; asm volatile("mov.u32 %0, %%tid.x;" : "=r"(t)); return t; }
template <int N> __device__ __forceinline__ void kill(uint32_t* v) {
#pragma unroll
    for (int i = 0; i < N; i++) v[i] = 0;
}
template <int N> __device__ __forceinline__ void kill(float* v) {
#pragma unroll
    for (int i = 0; i < N; i++) v[i] = 0.f;
}
__device__ __forceinline__ uint32_t s2u(const void* p) { return (uint32_t)__cvta_generic_to_shared(p); }
__device__ __forceinline__ void mbar_init(uint32_t a, uint32_t c) { asm volatile("mbarrier.init.shared::cta.b64 [%0], %1;" ::"r"(a), "r"(c) : "memory"); }
__device__ __forceinline__ void mbar_expect_tx(uint32_t a, uint32_t b) { asm volatile("mbarrier.arrive.expect_tx.shared::cta.b64 _, [%0], %1;" ::"r"(a), "r"(b) : "memory"); }
__device__ __forceinline__ void mbar_arrive(uint32_t a) { asm volatile("mbarrier.arrive.shared::cta.b64 _, [%0];" ::"r"(a) : "memory"); }
#define GIVE_UP(id) "trap;\n"
#define SPIN_MAX "0x400000"
#define SPIN_TAIL(id) "add.u32 n, n, 1;\n setp.lt.u32 p, n, " SPIN_MAX ";\n @p bra.uni LP;\n" GIVE_UP(id) " DN:\n }"
__device__ __forceinline__ void mbar_wait(uint32_t a, uint32_t ph) {
    asm volatile("{ .reg .pred p; .reg .b32 n; mov.u32 n, 0;\n LP:\n"
                 "mbarrier.try_wait.parity.shared::cta.b64 p, [%0], %1;\n @p bra DN;\n"
                 "add.u32 n, n, 1;\n setp.lt.u32 p, n, " SPIN_MAX ";\n @p bra LP;\n"
                 GIVE_UP("")
                 " DN:\n }" ::"r"(a), "r"(ph) : "memory");
}
#define ELECT "{ .reg .pred e; elect.sync _|e, 0xffffffff; @e "
__device__ __forceinline__ void tma2d(uint32_t dst, const CUtensorMap* m, int c0, int c1, uint32_t bar) {
    asm volatile(ELECT "cp.async.bulk.tensor.2d.shared::cluster.global.mbarrier::complete_tx::bytes [%0], [%1, {%3, %4}], [%2]; }" ::"r"(dst), "l"(m), "r"(bar), "r"(c0), "r"(c1) : "memory");
}
__device__ __forceinline__ void tma3x(uint32_t dst, const CUtensorMap* m, int row, uint32_t bar) {
    asm volatile(ELECT "cp.async.bulk.tensor.3d.shared::cluster.global.mbarrier::complete_tx::bytes [%0], [%1, {0, %3, 0}], [%2]; }" ::"r"(dst), "l"(m), "r"(bar), "r"(row) : "memory");
}
template <int OFF>
__device__ __forceinline__ void ld_pkt(uint32_t* v, const uint4* p) {
    asm volatile("{ .reg .b128 t; ld.relaxed.gpu.global.b128 t, [%4+%5]; mov.b128 {%0,%1,%2,%3}, t; }" : "=r"(v[0]), "=r"(v[1]), "=r"(v[2]), "=r"(v[3]) : "l"(p), "n"(OFF * 16) : "memory");
}
template <int OFF>
__device__ __forceinline__ void st_pkt(uint4* p, uint32_t a, uint32_t b, uint32_t c, uint32_t d) {
    asm volatile("{ .reg .b128 t; mov.b128 t, {%1,%2,%3,%4}; st.relaxed.gpu.global.b128 [%0+%5], t; }" ::"l"(p), "r"(a), "r"(b), "r"(c), "r"(d), "n"(OFF * 16) : "memory");
}
__device__ __forceinline__ uint32_t pack2(float lo, float hi) {
    uint32_t r;
    asm("cvt.rn.bf16x2.f32 %0, %1, %2;" : "=r"(r) : "f"(hi), "f"(lo));
    return r;
}
__device__ __forceinline__ float bf_lo(uint32_t w) { return __uint_as_float(w << 16); }
__device__ __forceinline__ float bf_hi(uint32_t w) { return __uint_as_float(w & 0xffff0000u); }
__device__ __forceinline__ uint32_t settag(uint32_t w, uint32_t tag) { return (w & ~1u) | tag; }
__device__ __forceinline__ float ex2(float x) { float y; asm("ex2.approx.ftz.f32 %0, %1;" : "=f"(y) : "f"(x)); return y; }
__device__ __forceinline__ float rcp(float x) { float y; asm("rcp.approx.ftz.f32 %0, %1;" : "=f"(y) : "f"(x)); return y; }
__device__ __forceinline__ float tanh_hw(float x) { float y; asm("tanh.approx.f32 %0, %1;" : "=f"(y) : "f"(x)); return y; }
__device__ __forceinline__ void stsm4(uint32_t addr, uint32_t a, uint32_t b, uint32_t c, uint32_t d) {
    asm volatile("stmatrix.sync.aligned.m8n8.x4.shared.b16 [%0], {%1,%2,%3,%4};" ::"r"(addr), "r"(a), "r"(b), "r"(c), "r"(d) : "memory");
}
__device__ __forceinline__ void fence_async() { asm volatile("fence.proxy.async.shared::cta;" ::: "memory"); }
__device__ __forceinline__ void bar_sync(int id, int n) { asm volatile("bar.sync %0, %1;" ::"r"(id), "r"(n) : "memory"); }
__device__ __forceinline__ void bar_arrive(int id, int n) { asm volatile("bar.arrive %0, %1;" ::"r"(id), "r"(n) : "memory"); }
__device__ __forceinline__ void wg_fence() { asm volatile("wgmma.fence.sync.aligned;" ::: "memory"); }
__device__ __forceinline__ void wg_commit() { asm volatile("wgmma.commit_group.sync.aligned;" ::: "memory"); }
template <int N> __device__ __forceinline__ void wg_wait() { asm volatile("wgmma.wait_group.sync.aligned %0;" ::"n"(N) : "memory"); }

constexpr uint32_t SB0 = 1024;
__host__ __device__ constexpr uint32_t dlo(uint32_t off, uint32_t lbo) { return ((SB0 + off) >> 4) | ((lbo >> 4) << 16); }
__host__ __device__ constexpr uint32_t dhi(uint32_t sbo, uint32_t sw) { return (sbo >> 4) | (sw << 30); }
__device__ __forceinline__ uint64_t dbase(uint32_t lo, uint32_t hi) { uint64_t d; asm volatile("mov.b64 %0, {%1, %2};" : "=l"(d) : "r"(lo), "r"(hi)); return d; }
#define BASE128(off, lbo, adj) dbase(dlo(off, lbo) + (adj), dhi(1024, 1))
#define BASE64(off, lbo, adj) dbase(dlo(off, lbo) + (adj), dhi(512, 2))

#define ACC4(d, o) "+f"(d[o]), "+f"(d[o + 1]), "+f"(d[o + 2]), "+f"(d[o + 3])
#define ACC28(d) ACC4(d, 0), ACC4(d, 4), ACC4(d, 8), ACC4(d, 12), ACC4(d, 16), ACC4(d, 20), ACC4(d, 24)
#define ACC32(d, o) ACC4(d, o), ACC4(d, o + 4), ACC4(d, o + 8), ACC4(d, o + 12), ACC4(d, o + 16), ACC4(d, o + 20), ACC4(d, o + 24), ACC4(d, o + 28)

template <int TB, uint64_t D>
__device__ __forceinline__ void mma_rs56(float* d, uint32_t a0, uint32_t a1, uint32_t a2, uint32_t a3, int sd, uint64_t base) {
    asm volatile("{ .reg .pred p; .reg .b64 db; setp.ne.b32 p, %32, 0; add.u64 db, %33, %34;\n"
                 "wgmma.mma_async.sync.aligned.m64n56k16.f32.bf16.bf16 "
                 "{%0,%1,%2,%3,%4,%5,%6,%7,%8,%9,%10,%11,%12,%13,%14,%15,%16,%17,%18,%19,%20,%21,%22,%23,%24,%25,%26,%27}, "
                 "{%28,%29,%30,%31}, db, p, 1, 1, %35; }\n"
                 : ACC28(d)
                 : "r"(a0), "r"(a1), "r"(a2), "r"(a3), "r"(sd), "l"(base), "n"(D), "n"(TB));
}
template <int TB, uint64_t D>
__device__ __forceinline__ void mma_rs64(float* d, uint32_t a0, uint32_t a1, uint32_t a2, uint32_t a3, int sd, uint64_t base) {
    asm volatile("{ .reg .pred p; .reg .b64 db; setp.ne.b32 p, %36, 0; add.u64 db, %37, %38;\n"
                 "wgmma.mma_async.sync.aligned.m64n64k16.f32.bf16.bf16 "
                 "{%0,%1,%2,%3,%4,%5,%6,%7,%8,%9,%10,%11,%12,%13,%14,%15,%16,%17,%18,%19,%20,%21,%22,%23,%24,%25,%26,%27,%28,%29,%30,%31}, "
                 "{%32,%33,%34,%35}, db, p, 1, 1, %39; }\n"
                 : ACC32(d, 0)
                 : "r"(a0), "r"(a1), "r"(a2), "r"(a3), "r"(sd), "l"(base), "n"(D), "n"(TB));
}
template <int TB, uint64_t D>
__device__ __forceinline__ void mma_rs128(float* d, uint32_t a0, uint32_t a1, uint32_t a2, uint32_t a3, int sd, uint64_t base) {
    asm volatile("{ .reg .pred p; .reg .b64 db; setp.ne.b32 p, %68, 0; add.u64 db, %69, %70;\n"
                 "wgmma.mma_async.sync.aligned.m64n128k16.f32.bf16.bf16 "
                 "{%0,%1,%2,%3,%4,%5,%6,%7,%8,%9,%10,%11,%12,%13,%14,%15,%16,%17,%18,%19,%20,%21,%22,%23,%24,%25,%26,%27,%28,%29,%30,%31,%32,%33,%34,%35,%36,%37,%38,%39,%40,%41,%42,%43,%44,%45,%46,%47,%48,%49,%50,%51,%52,%53,%54,%55,%56,%57,%58,%59,%60,%61,%62,%63}, "
                 "{%64,%65,%66,%67}, db, p, 1, 1, %71; }\n"
                 : ACC32(d, 0), ACC32(d, 32)
                 : "r"(a0), "r"(a1), "r"(a2), "r"(a3), "r"(sd), "l"(base), "n"(D), "n"(TB));
}
template <uint64_t DA, uint64_t DB>
__device__ __forceinline__ void mma_ss56_tt(float* d, int sd, uint64_t ba, uint64_t bb) {
    asm volatile("{ .reg .pred p; .reg .b64 da, db; setp.ne.b32 p, %28, 0; add.u64 da, %29, %31; add.u64 db, %30, %32;\n"
                 "wgmma.mma_async.sync.aligned.m64n56k16.f32.bf16.bf16 "
                 "{%0,%1,%2,%3,%4,%5,%6,%7,%8,%9,%10,%11,%12,%13,%14,%15,%16,%17,%18,%19,%20,%21,%22,%23,%24,%25,%26,%27}, "
                 "da, db, p, 1, 1, 1, 1; }\n"
                 : ACC28(d)
                 : "r"(sd), "l"(ba), "l"(bb), "n"(DA), "n"(DB));
}
template <int... I> struct Seq {};
template <class F, int... I> __device__ __forceinline__ void static_for_impl(F&& f, Seq<I...>) { (f(std::integral_constant<int, I>{}), ...); }
#define FOR7(...) static_for_impl([&](auto T_) { constexpr int t = decltype(T_)::value; __VA_ARGS__; }, Seq<0, 1, 2, 3, 4, 5, 6>{})
#define FOR8(...) static_for_impl([&](auto T_) { constexpr int t = decltype(T_)::value; __VA_ARGS__; }, Seq<0, 1, 2, 3, 4, 5, 6, 7>{})
#define FOR14(...) static_for_impl([&](auto T_) { constexpr int t = decltype(T_)::value; __VA_ARGS__; }, Seq<0, 1, 2, 3, 4, 5, 6, 7, 8, 9, 10, 11, 12, 13>{})

__device__ __forceinline__ int kblk(int p, int b) { return b == 0 ? p : b - (b <= p); }
__host__ __device__ constexpr int krow(int t) { return t < 3 ? 16 * t : (t < 6 ? 56 + 16 * (t - 3) : 48); }
#define AQ(A, b, t) ((t) < 3 ? A[2 * (b)][4 * (t)] : (t) < 6 ? A[2 * (b) + 1][4 * ((t) - 3)] : A[2 * (b)][12]), \
                    ((t) < 3 ? A[2 * (b)][4 * (t) + 1] : (t) < 6 ? A[2 * (b) + 1][4 * ((t) - 3) + 1] : A[2 * (b)][13]), \
                    ((t) < 3 ? A[2 * (b)][4 * (t) + 2] : (t) < 6 ? A[2 * (b) + 1][4 * ((t) - 3) + 2] : A[2 * (b) + 1][12]), \
                    ((t) < 3 ? A[2 * (b)][4 * (t) + 3] : (t) < 6 ? A[2 * (b) + 1][4 * ((t) - 3) + 3] : A[2 * (b) + 1][13])
#define D128(off, t) ((uint64_t)(((off) + krow(t) * 128) >> 4) + ((uint64_t)((t) == 6 ? (7168 - 1024) >> 4 : 0) << 32))
#define D64(off, t) ((uint64_t)(((off) + krow(t) * 64) >> 4) + ((uint64_t)((t) == 6 ? (3584 - 512) >> 4 : 0) << 32))

#define PL(k) (((k) - 3) * PLANE)
__device__ __forceinline__ void st_word(uint32_t* p, uint32_t v) { asm volatile("st.relaxed.gpu.global.u32 [%0], %1;" ::"l"(p), "r"(v) : "memory"); }
__device__ __forceinline__ uint32_t ld_word(const uint32_t* p) { uint32_t v; asm volatile("ld.relaxed.gpu.global.u32 %0, [%1];" : "=r"(v) : "l"(p) : "memory"); return v; }
__device__ __forceinline__ void tag_slice(uint32_t* w, uint32_t tag) { w[0] = settag(w[0], tag); w[4] = settag(w[4], tag); w[8] = settag(w[8], tag); w[12] = settag(w[12], tag); }
template <int O>
__device__ __forceinline__ void send_slice(uint4* dst, int lane, const uint32_t* w) {
    st_pkt<O>(dst, w[0], w[1], w[2], w[3]);
    st_pkt<O + 32>(dst, w[4], w[5], w[6], w[7]);
    st_pkt<O + 64>(dst, w[8], w[9], w[10], w[11]);
    asm volatile("{ .reg .b64 t; mov.b64 t, {%1,%2}; st.relaxed.gpu.global.b64 [%0+%3], t; }" ::"l"((char*)dst - lane * 8), "r"(w[12]), "r"(w[13]), "n"(16 * (O + 96)) : "memory");
}
#define RW4(v, o) "+r"(v[o]), "+r"(v[(o) + 1]), "+r"(v[(o) + 2]), "+r"(v[(o) + 3])
#define RW2(v, o) "+r"(v[o]), "+r"(v[(o) + 1])
#define WR4(v, o) "=&r"(v[o]), "=&r"(v[(o) + 1]), "=&r"(v[(o) + 2]), "=&r"(v[(o) + 3])
#define LDP(a, b, c, d, addr, off) "ld.relaxed.gpu.global.b128 q, [" addr "+" off "];\n mov.b128 {" a "," b "," c "," d "}, q;\n"
#define LDH(a, b, addr, off) "ld.relaxed.gpu.global.b64 h, [" addr "+" off "];\n mov.b64 {" a "," b "}, h;\n"
#define VOTE_OK "and.b32 t, t, 1;\n setp.ne.u32 p, t, 0;\n vote.sync.any.pred p, p, 0xffffffff;\n @!p bra.uni DN;\n"
#define CHK(x, tag) "lop3.b32 t, " x ", " tag ", t, 0xBE;\n"
__device__ __forceinline__ void check_cnt(uint32_t v, const uint32_t* p, uint32_t target) {
    asm volatile("{ .reg .pred p; .reg .b32 n, t; mov.u32 n, 0; mov.u32 t, %2;\n LP:\n"
                 "sub.s32 t, t, %1;\n setp.lt.s32 p, t, 0;\n vote.sync.any.pred p, p, 0xffffffff;\n @!p bra.uni DN;\n ld.relaxed.gpu.global.u32 t, [%0];\n" SPIN_TAIL("7")
                 ::"l"(p), "r"(target), "r"(v) : "memory");
}
__device__ __forceinline__ void poll_cnt(const uint32_t* p, uint32_t target) {
    asm volatile("{ .reg .pred p; .reg .b32 n, t; mov.u32 n, 0;\n LP:\n"
                 "ld.relaxed.gpu.global.u32 t, [%0];\n sub.s32 t, t, %1;\n setp.lt.s32 p, t, 0;\n vote.sync.any.pred p, p, 0xffffffff;\n @!p bra.uni DN;\n" SPIN_TAIL("1")
                 ::"l"(p), "r"(target) : "memory");
}
template <int STR>
__device__ __forceinline__ void poll4_kv(uint32_t* v, const uint4* p, uint32_t tag) {
    asm volatile("{ .reg .pred p; .reg .b32 n, t; .reg .b128 q; mov.u32 n, 0;\n LP:\n"
                 LDP("%0", "%1", "%2", "%3", "%16", "0") LDP("%4", "%5", "%6", "%7", "%16", "%18")
                 LDP("%8", "%9", "%10", "%11", "%16", "%19") LDP("%12", "%13", "%14", "%15", "%16", "%20")
                 "xor.b32 t, %0, %17;\n" CHK("%4", "%17") CHK("%8", "%17") CHK("%12", "%17") VOTE_OK SPIN_TAIL("2")
                 : WR4(v, 0), WR4(v, 4), WR4(v, 8), WR4(v, 12)
                 : "l"(p), "r"(tag), "n"(16 * STR), "n"(32 * STR), "n"(48 * STR)
                 : "memory");
}
template <int B>
__device__ __forceinline__ void blk_load(uint32_t (&A)[8][14], const uint4* src, int lane) {
    ld_pkt<0>(&A[2 * B][0], src); ld_pkt<32>(&A[2 * B][4], src); ld_pkt<64>(&A[2 * B][8], src);
    ld_pkt<512>(&A[2 * B + 1][0], src); ld_pkt<544>(&A[2 * B + 1][4], src); ld_pkt<576>(&A[2 * B + 1][8], src);
    asm volatile("{ .reg .b64 h;\n" LDH("%0", "%1", "%4", "1536") LDH("%2", "%3", "%4", "9728") "}"
                 : "=&r"(A[2 * B][12]), "=&r"(A[2 * B][13]), "=&r"(A[2 * B + 1][12]), "=&r"(A[2 * B + 1][13])
                 : "l"((const char*)src - lane * 8) : "memory");
}
template <int B>
__device__ __forceinline__ void blk_check(uint32_t (&A)[8][14], const uint4* src, int lane, uint32_t tag) {
    asm volatile("{ .reg .pred p; .reg .b32 n, t; .reg .b128 q; .reg .b64 h, a8; mov.u32 n, 0;\n LP:\n"
                 "xor.b32 t, %0, %30;\n" CHK("%4", "%30") CHK("%8", "%30") CHK("%12", "%30") CHK("%16", "%30") CHK("%20", "%30") CHK("%24", "%30") CHK("%26", "%30") VOTE_OK
                 LDP("%0", "%1", "%2", "%3", "%28", "0") LDP("%4", "%5", "%6", "%7", "%28", "512") LDP("%8", "%9", "%10", "%11", "%28", "1024")
                 LDP("%12", "%13", "%14", "%15", "%28", "8192") LDP("%16", "%17", "%18", "%19", "%28", "8704") LDP("%20", "%21", "%22", "%23", "%28", "9216")
                 "mad.wide.s32 a8, %29, -8, %28;\n" LDH("%24", "%25", "a8", "1536") LDH("%26", "%27", "a8", "9728") SPIN_TAIL("3")
                 "\n and.b32 %0, %0, -2; and.b32 %4, %4, -2; and.b32 %8, %8, -2; and.b32 %12, %12, -2; and.b32 %16, %16, -2; and.b32 %20, %20, -2; and.b32 %24, %24, -2; and.b32 %26, %26, -2;"
                 : RW4(A[2 * B], 0), RW4(A[2 * B], 4), RW4(A[2 * B], 8), RW4(A[2 * B + 1], 0), RW4(A[2 * B + 1], 4), RW4(A[2 * B + 1], 8),
                   RW2(A[2 * B], 12), RW2(A[2 * B + 1], 12)
                 : "l"(src), "r"(lane), "r"(tag)
                 : "memory");
}
__device__ __forceinline__ void st_async4(uint32_t a, uint32_t x, uint32_t y, uint32_t z, uint32_t w, uint32_t bar) {
    asm volatile("st.async.weak.shared::cluster.mbarrier::complete_tx::bytes.v4.b32 [%0], {%1,%2,%3,%4}, [%5];" ::"r"(a), "r"(x), "r"(y), "r"(z), "r"(w), "r"(bar) : "memory");
}
__device__ __forceinline__ uint32_t mapa(uint32_t a, uint32_t cta) { uint32_t r; asm("mapa.shared::cluster.u32 %0, %1, %2;" : "=r"(r) : "r"(a), "r"(cta)); return r; }
__device__ __forceinline__ void stat_load(uint32_t* v, const uint4* p) { ld_pkt<0>(v, p); ld_pkt<512>(v + 4, p); }
__device__ __forceinline__ void stat_check(uint32_t* v, const uint4* p, uint32_t tag) {
    asm volatile("{ .reg .pred p; .reg .b32 n, t; .reg .b128 q; mov.u32 n, 0;\n LP:\n"
                 "xor.b32 t, %3, %9;\n" CHK("%7", "%9") VOTE_OK
                 LDP("%0", "%1", "%2", "%3", "%8", "0") LDP("%4", "%5", "%6", "%7", "%8", "8192") SPIN_TAIL("4")
                 : RW4(v, 0), RW4(v, 4) : "l"(p), "r"(tag) : "memory");
}
__device__ __forceinline__ uint32_t x_bits(const uint32_t* X) {
    uint32_t r;
    asm volatile("{ .reg .b32 a, b; prmt.b32 a, %1, %2, 0x0040; prmt.b32 b, %3, %4, 0x0040; prmt.b32 %0, a, b, 0x5410; }" : "=r"(r) : "r"(X[0]), "r"(X[4]), "r"(X[8]), "r"(X[12]));
    return r;
}
template <int O>
__device__ __forceinline__ void slice_load(uint32_t* v, const uint4* p, int lane) {
    ld_pkt<O>(v, p); ld_pkt<O + 32>(v + 4, p); ld_pkt<O + 64>(v + 8, p);
    asm volatile("{ .reg .b64 h;\n" LDH("%0", "%1", "%2", "%3") "}" : "=r"(v[12]), "=r"(v[13]) : "l"((const char*)p - lane * 8), "n"(16 * (O + 96)) : "memory");
}
template <int O>
__device__ __forceinline__ void slice_check(uint32_t* v, const uint4* p, int lane, uint32_t tag) {
    asm volatile("{ .reg .pred p; .reg .b32 n, t; .reg .b128 q; .reg .b64 h; mov.u32 n, 0;\n LP:\n"
                 "xor.b32 t, %0, %16;\n" CHK("%4", "%16") CHK("%8", "%16") CHK("%12", "%16") VOTE_OK
                 LDP("%0", "%1", "%2", "%3", "%14", "%17") LDP("%4", "%5", "%6", "%7", "%14", "%18") LDP("%8", "%9", "%10", "%11", "%14", "%19")
                 LDH("%12", "%13", "%15", "%20") SPIN_TAIL("5")
                 : RW4(v, 0), RW4(v, 4), RW4(v, 8), RW2(v, 12)
                 : "l"(p), "l"((const char*)p - lane * 8), "r"(tag), "n"(16 * O), "n"(16 * (O + 32)), "n"(16 * (O + 64)), "n"(16 * (O + 96))
                 : "memory");
}
__device__ __forceinline__ void x_fix(uint32_t* X, uint32_t bits) {
    X[0] = __byte_perm(X[0], bits, 0x3214); X[4] = __byte_perm(X[4], bits, 0x3215); X[8] = __byte_perm(X[8], bits, 0x3216); X[12] = __byte_perm(X[12], bits, 0x3217);
}
__device__ __forceinline__ void sts4(uint32_t a, uint32_t x, uint32_t y, uint32_t z, uint32_t w) {
    asm volatile("st.shared.v4.u32 [%0], {%1,%2,%3,%4};" ::"r"(a), "r"(x), "r"(y), "r"(z), "r"(w) : "memory");
}
__device__ __forceinline__ void lds4(uint32_t* v, uint32_t a) {
    asm volatile("ld.shared.v4.u32 {%0,%1,%2,%3}, [%4];" : "=r"(v[0]), "=r"(v[1]), "=r"(v[2]), "=r"(v[3]) : "r"(a) : "memory");
}
struct LnCoef { uint32_t hi, lo, sh; };
__device__ __forceinline__ LnCoef ln_coef(float sum, float sq) {
    sum += __shfl_xor_sync(0xffffffffu, sum, 1); sq += __shfl_xor_sync(0xffffffffu, sq, 1);
    sum += __shfl_xor_sync(0xffffffffu, sum, 2); sq += __shfl_xor_sync(0xffffffffu, sq, 2);
    const float mean = sum * (1.f / 448.f);
    const float var = fmaxf(fmaf(-mean, mean, sq * (1.f / 448.f)), 0.f);
    const float sc = rsqrtf(var + 1e-5f);
    LnCoef r;
    r.hi = pack2(sc, sc);
    const float lo = sc - bf_lo(r.hi), sh = -mean * sc;
    r.lo = pack2(lo, lo);
    r.sh = pack2(sh, sh);
    return r;
}
template <int B>
__device__ __forceinline__ void normalize(uint32_t (&A)[8][14], const LnCoef& c0, const LnCoef& c1) {
#pragma unroll
    for (int s = 2 * B; s < 2 * B + 2; s++)
#pragma unroll
        for (int i = 0; i < 14; i++) {
            const LnCoef& k = (i & 1) ? c1 : c0;
            asm("{ .reg .b32 t; fma.rn.bf16x2 t, %0, %2, %3; fma.rn.bf16x2 %0, %0, %1, t; }" : "+r"(A[s][i]) : "r"(k.hi), "r"(k.lo), "r"(k.sh));
        }
}
__device__ __forceinline__ void slice_stats(const uint32_t* w, float* st) {
    float a = 0.f, b = 0.f, p = 0.f, q = 0.f;
#pragma unroll
    for (int i = 0; i < 7; i++) {
        const float e0 = bf_lo(w[2 * i]), e1 = bf_hi(w[2 * i]), e2 = bf_lo(w[2 * i + 1]), e3 = bf_hi(w[2 * i + 1]);
        a += e0 + e1; b += e2 + e3;
        p = fmaf(e0, e0, p); p = fmaf(e1, e1, p); q = fmaf(e2, e2, q); q = fmaf(e3, e3, q);
    }
    a += __shfl_xor_sync(0xffffffffu, a, 1); p += __shfl_xor_sync(0xffffffffu, p, 1); b += __shfl_xor_sync(0xffffffffu, b, 1); q += __shfl_xor_sync(0xffffffffu, q, 1);
    a += __shfl_xor_sync(0xffffffffu, a, 2); p += __shfl_xor_sync(0xffffffffu, p, 2); b += __shfl_xor_sync(0xffffffffu, b, 2); q += __shfl_xor_sync(0xffffffffu, q, 2);
    st[0] = a; st[1] = p; st[2] = b; st[3] = q;
}
__device__ __forceinline__ void dual_softmax(const float* p, uint32_t* out) {
    constexpr float L = 1.4426950408889634f;
#pragma unroll
    for (int r = 0; r < 2; r++) {
        float mx = fmaxf(p[2 * r], p[2 * r + 1]), mn = fminf(p[2 * r], p[2 * r + 1]);
#pragma unroll
        for (int i = 1; i < 7; i++) {
            mx = fmaxf(mx, fmaxf(p[4 * i + 2 * r], p[4 * i + 2 * r + 1]));
            mn = fminf(mn, fminf(p[4 * i + 2 * r], p[4 * i + 2 * r + 1]));
        }
        mx = fmaxf(mx, __shfl_xor_sync(0xffffffffu, mx, 1));
        mn = fminf(mn, __shfl_xor_sync(0xffffffffu, mn, 1));
        const float bx = -mx * L, bn = mn * L;
        float ep[14], en[14], sp = 0.f, sn = 0.f;
#pragma unroll
        for (int i = 0; i < 14; i++) {
            const float v = p[4 * (i >> 1) + 2 * r + (i & 1)];
            ep[i] = ex2(fmaf(v, L, bx));
            en[i] = ex2(fmaf(v, -L, bn));
            sp += ep[i]; sn += en[i];
        }
        sp += __shfl_xor_sync(0xffffffffu, sp, 1);
        sn += __shfl_xor_sync(0xffffffffu, sn, 1);
        const float ip = rcp(sp), in = rcp(sn);
#pragma unroll
        for (int i = 0; i < 7; i++) {
            out[4 * i + r] = pack2(ep[2 * i] * ip, ep[2 * i + 1] * ip);
            out[4 * i + 2 + r] = pack2(en[2 * i] * in, en[2 * i + 1] * in);
        }
    }
}
__device__ __forceinline__ float geglu(float g, float u) {
    const float t = tanh_hw(g * fmaf(g * g, 0.7978845608028654f * 0.044715f, 0.7978845608028654f));
    const float gu = g * u;
    return fmaf(t, gu, gu);
}
__device__ __forceinline__ void phi_gemm(const float* t, float* p) {
    uint32_t w[14];
#pragma unroll
    for (int i = 0; i < 14; i++) w[i] = pack2(t[2 * i], t[2 * i + 1]);
    const uint64_t db = BASE128(OFF_WPHI, 16, 0);
    wg_fence();
    mma_rs56<0, 0>(p, w[0], w[1], w[2], w[3], 0, db);
    mma_rs56<0, 2>(p, w[4], w[5], w[6], w[7], 1, db);
    mma_rs56<0, 4>(p, w[8], w[9], w[10], w[11], 1, db);
    mma_rs56<0, 6>(p, w[12], w[13], 0u, 0u, 1, db);
    wg_commit();
    wg_wait<0>();
}

}

#define BAR(i) (bars + 8 * (i))
#define R_WAIT() mbar_wait(BAR(slot), ph)
#define WSUM(i)
#define R_ADJ (slot * (STAGE >> 4))
#define R_NEXT() do { eb2 = eb1; eb1 = BAR(B_EMPTY + slot); if (++slot == NST) { slot = 0; ph ^= 1; } } while (0)
#define R_RELEASE(k) do { if (lane == 0) mbar_arrive((k) == 1 ? eb1 : eb2); } while (0)
#define PUSH_BEGIN() do { mbar_wait(BAR(B_ACK + wgi), ackph); ackph ^= 1; } while (0)
#define PUSH_ACK() do { __syncwarp(); if (lane == 0) asm volatile("mbarrier.arrive.shared::cluster.b64 _, [%0];" ::"r"(mapa(BAR(B_ACK + wgi), hr ^ 1)) : "memory"); } while (0)

__global__ void __cluster_dims__(2, 1, 1) __launch_bounds__(384, 1)
fused_kernel(Scratch* const sc, const __nv_bfloat16* __restrict__ x_in, const __nv_bfloat16* __restrict__ w_phi, const int trips,
             const __nv_bfloat16* __restrict__ wg, const __nv_bfloat16* __restrict__ wu, const __nv_bfloat16* __restrict__ wd,
             const __grid_constant__ Maps maps) {
    extern __shared__ __align__(1024) unsigned char smem_raw[];
    const uint32_t sb = s2u(smem_raw);
    const uint32_t bars = sb + OFF_BAR;
    const int wgi = __shfl_sync(0xffffffffu, threadIdx.x >> 7, 0);
    const int hr = blockIdx.x & 1, ck = blockIdx.x >> 1;
    const int gp = (ck - 4) & 7, q7 = ((ck - 36) * 37) >> 8;
    const int pr = __shfl_sync(0xffffffffu, ck < 4 ? ck : (ck < 36 ? (ck - 4) >> 3 : q7), 0);
    const int tile = __shfl_sync(0xffffffffu, ck < 4 ? 0 : (ck < 36 ? (gp ? 2 * gp : 1) : 2 * (ck - 36 - 7 * q7) + 3), 0);
    const int sl = 2 * pr + hr;
    STAMP(0);
    GSTAMP(60);
    if (threadIdx.x == 256) {
#pragma unroll
        for (int i = 0; i < NST; i++) mbar_init(BAR(i), 1);
        asm volatile("fence.mbarrier_init.release.cluster;" ::: "memory");
    }
    if (threadIdx.x == 288) {
        if ((sb & 0x3FFFF) != SB0) asm volatile("trap;");
#pragma unroll
        for (int i = NST; i < B_COUNT; i++) mbar_init(BAR(i), i >= B_ACK ? 4 : (i < B_RECV || i == B_LATE ? 8 : 1));
        asm volatile("fence.mbarrier_init.release.cluster;" ::: "memory");
    }
    __syncwarp();
    asm volatile("barrier.cluster.arrive.relaxed.aligned;" ::: "memory");

    if (wgi == 2) {
        asm volatile("setmaxnreg.dec.sync.aligned.u32 40;");
        const int t128 = fresh_tid() & 127, w = __shfl_sync(0xffffffffu, t128 >> 5, 0), lane = t128 & 31;
        uint32_t e0[2] = {0, 0}, e1[2] = {0, 0}, cw_target = 0;
        if (w == 0) {
#pragma unroll 1
            for (int n = 0; n < NST; n++) {
                const uint32_t dst = sb + n * STAGE, fb = BAR(n);
                asm volatile(ELECT "mbarrier.arrive.expect_tx.shared::cta.b64 _, [%0], %1; }" ::"r"(fb), "r"(n < 2 ? 2 * STAGE : STAGE) : "memory");
                if (n < 2) {
                    tma3x(sb + OFF_H + n * STAGE, &maps.x, tile * 128 + n * 64, fb);
                    tma3x(dst, &maps.x, tile * 128 + n * 64 + 32, fb);
                } else {
                    if (n == 3) mbar_wait(BAR(1), 0);
                    const int ra = 112 * (n - 2);
                    tma2d(dst, &maps.qkv, 448 + 56 * sl, ra, fb);
                    tma2d(dst + HALF, &maps.qkv, 896 + 56 * sl, ra, fb);
                }
            }
            asm volatile("barrier.cluster.wait.aligned;" ::: "memory");
            cw_target = (ld_word(g_cw + sl * 32) & ~15u) + 16;
#pragma unroll 1
            for (int k = 0; k < 2; k++) {
                const int n = t128 + 32 * k;
                int m = n - 2 - (n > PACK);
                const bool packed = m >= 30 ? (m < 38 || m >= 52) : m >= 22;
                if (m >= 30) m -= 30;
                if (n == PACK) m = tile < 8 ? tile : tile + 14;
                const int rot = n < 8 ? 0 : pr;
                const int ra = 112 * kblk(rot, m & 3), rb = 112 * kblk(rot, 2 * m & 3), rc = 112 * kblk(rot, (2 * m + 1) & 3);
                int kind = 0, m0, m1, c0, c1, r0, r1;
                if (m < 4) { m0 = m1 = 1; c0 = 448 + 56 * sl; c1 = c0 + 448; r0 = r1 = ra; }
                else if (m < 8) { m0 = m1 = m < 6 ? 1 : 2; c0 = c1 = 56 * sl; r0 = rb; r1 = rc; }
                else if (m < 20) { m0 = 3; m1 = 4; c0 = c1 = 224 * sl + 32 * hr + 64 * ((m - 8) >> 2); r0 = r1 = ra; }
                else if (m < 22) { kind = 2; m0 = 5; m1 = 6; c0 = c1 = 224 * sl + (hr ? 0 : 192); r0 = rb; r1 = rc; }
                else { m0 = m1 = 7; c0 = c1 = 56 * (2 * ((pr + (m >> 1) - 10) & 3) + hr); r0 = 224 * (sl ^ (m & 1)); r1 = r0 + 112; }
                if (packed) { kind = 1; r0 = sl * 16 + (m < 8 ? m : m - 14); r1 = 0; }
                e0[0] = e0[1]; e1[0] = e1[1];
                e0[1] = kind | (m0 << 2) | (m1 << 6) | (c0 << 10) | (c1 << 21);
                e1[1] = r0 | (r1 << 16);
            }
        } else {
            const int j = t128 - 32;
            asm volatile("barrier.cluster.wait.aligned;" ::: "memory");
            uint2 wv[7];
            const int k = j < 56 ? j : 55, hh = k >= 28;
#pragma unroll
            for (int i = 0; i < 7; i++) wv[i] = __ldg(reinterpret_cast<const uint2*>(w_phi + (sl * 56 + k) * 28) + i);
#pragma unroll 1
            for (int i = j; i < 7168 / 16; i += 96) sts4(sb + OFF_WPHI + i * 16, 0, 0, 0, 0);
            bar_sync(5, 96);
            if (j < 56) {
                uint32_t a4[4];
#pragma unroll
                for (int q = 0; q < 4; q++) a4[q] = sb + OFF_WPHI + (4 * hh + q) * 128 + ((((k >> 3) ^ (4 * hh + q)) & 7) << 4) + (k & 7) * 2;
                FOR14(const uint32_t v = (t & 1) ? wv[t >> 1].y : wv[t >> 1].x;
                      asm volatile("{ .reg .b16 l, h; mov.b32 {l, h}, %2; st.shared.u16 [%0+%3], l; st.shared.u16 [%1+%3], h; }"
                                   ::"r"(a4[t >= 7 ? 2 : 0]), "r"(a4[t >= 7 ? 3 : 1]), "r"(v), "n"((t % 7) * 1024) : "memory"));
            }
            __syncwarp();
            fence_async();
            bar_arrive(1, 224);
            bar_arrive(9, 224);
            if (w == 1) {
                mbar_wait(BAR(2), 0);
                mbar_wait(BAR(2), 1);
                const int b = blockIdx.x;
                asm volatile(ELECT "cp.async.bulk.prefetch.L2.global [%0], %1; }" ::"l"(wg + b * 6272), "r"(12544) : "memory");
                asm volatile(ELECT "cp.async.bulk.prefetch.L2.global [%0], %1; }" ::"l"(wu + b * 6272), "r"(12544) : "memory");
                asm volatile(ELECT "cp.async.bulk.prefetch.L2.global [%0], %1; }" ::"l"(wd + b * 6272), "r"(12544) : "memory");
            }
        }
        uint32_t kseq = ld_word(g_c1 + (sl * 8 * 16 + tile) * 32);
        int slot = 0, ph = 0, n = NST;
#pragma unroll 1
        for (int layer = 0; layer < 3; layer++) {
            if (w == 0) {
                const int nend = layer == 0 ? 11 : (layer == 1 ? 42 : 63);
#pragma unroll 1
                for (; n < nend; n++) {
                const uint32_t w0 = __shfl_sync(0xffffffffu, n < 32 ? e0[0] : e0[1], n & 31), w1 = __shfl_sync(0xffffffffu, n < 32 ? e1[0] : e1[1], n & 31);
                const uint32_t dst = sb + slot * STAGE, fb = BAR(n == PACK ? B_PACK : slot);
                const CUtensorMap* m0 = &maps.x + ((w0 >> 2) & 15);
                const CUtensorMap* m1 = &maps.x + ((w0 >> 6) & 15);
                const int c0 = (w0 >> 10) & 2047, c1 = w0 >> 21, r0 = w1 & 0xffff, r1 = w1 >> 16;
                if (n == 25) {
                    int it = 0;
                    uint32_t v;
                    do { asm volatile("ld.acquire.gpu.global.u32 %0, [%1];" : "=r"(v) : "l"(g_cw + sl * 32) : "memory"); } while ((int)(v - cw_target) < 0 && ++it < 0x400000);
                    asm volatile("fence.proxy.async.global;" ::: "memory");
                    __syncwarp();
                }
                mbar_wait(BAR(B_EMPTY + slot), ph);
                __syncwarp();
                asm volatile(ELECT "mbarrier.arrive.expect_tx.shared::cta.b64 _, [%0], %1; }" ::"r"(fb), "r"(STAGE) : "memory");
                if ((w0 & 3) == 0) {
                    tma2d(dst, m0, c0, r0, fb);
                    tma2d(dst + HALF, m1, c1, r1, fb);
                } else if (w0 & 1) {
                    asm volatile(ELECT "cp.async.bulk.shared::cluster.global.mbarrier::complete_tx::bytes [%0], [%1], %2, [%3]; }"
                                 ::"r"(dst), "l"(reinterpret_cast<const char*>(g_wp) + (size_t)r0 * STAGE), "r"(STAGE), "r"(fb) : "memory");
                } else {
                    tma2d(dst, m0, c0, r0, fb); tma2d(dst + 7168, m0, c0, r1, fb);
                    tma2d(dst + HALF, m1, c0, r0, fb); tma2d(dst + HALF + 7168, m1, c0, r1, fb);
                }
                if (n == PACK) asm volatile(ELECT "mbarrier.arrive.shared::cta.b64 _, [%0]; }" ::"r"(BAR(slot)) : "memory");
                if (++slot == NST) { slot = 0; ph ^= 1; }
                }
            } else if (w == 1 && layer == 1) {
                constexpr int ps = PACK % NST;
                mbar_wait(BAR(B_PACK), 0);
                asm volatile("{ .reg .pred e; elect.sync _|e, 0xffffffff;\n"
                             "@e cp.async.bulk.global.shared::cta.bulk_group [%0], [%1], %2;\n"
                             "@e cp.async.bulk.commit_group;\n"
                             "@e cp.async.bulk.wait_group.read 0;\n"
                             "@e mbarrier.arrive.shared::cta.b64 _, [%3], 8;\n"
                             "@e cp.async.bulk.wait_group 0;\n"
                             "@e fence.proxy.async.global;\n"
                             "@e red.release.gpu.global.add.u32 [%4], 1; }"
                             ::"l"(reinterpret_cast<char*>(g_wp) + (size_t)(sl * 16 + tile) * STAGE), "r"(sb + ps * STAGE), "r"(STAGE), "r"(BAR(B_EMPTY + ps)), "l"(g_cw + sl * 32) : "memory");
                __syncwarp();
            }
            if (layer < 2) {
            const uint32_t tag = layer ^ 1;
            kseq++;
            bar_sync(7, 384);
            ASTAMP(0);
            if (tile < 15) {
                const int sq = lane >> 3, pk = 8 * w + (lane & (tile == 14 ? 3 : 7));
                uint32_t v[16];
                if (layer == 0) poll_cnt(g_c1 + ((sl * 8 + (w >> 1) * 4 + (tile >> 2)) * 16 + (lane & 15)) * 32, kseq);
                ASTAMP(1);
                poll4_kv<32>(v, g_kv1 + ((sl * 16 + tile) * 16 + 4 * sq) * 32 + pk, tag);
#pragma unroll
                for (int k = 0; k < 4; k++) {
                    float lo = (bf_lo(v[k]) + bf_lo(v[4 + k])) + (bf_lo(v[8 + k]) + bf_lo(v[12 + k]));
                    float hi = (bf_hi(v[k]) + bf_hi(v[4 + k])) + (bf_hi(v[8 + k]) + bf_hi(v[12 + k]));
                    lo += __shfl_xor_sync(0xffffffffu, lo, 8); hi += __shfl_xor_sync(0xffffffffu, hi, 8);
                    lo += __shfl_xor_sync(0xffffffffu, lo, 16); hi += __shfl_xor_sync(0xffffffffu, hi, 16);
                    v[k] = pack2(lo, hi);
                }
                if (sq == 0) st_pkt<0>(g_kv2 + sl * 512 + 32 * tile + pk, settag(v[0], tag), v[1], v[2], v[3]);
            }
            ASTAMP(2);
            {
                const int item = t128 < 112 ? t128 : 112 + (t128 & 3), d = item >> 1;
                const int cc = t128 < 112 ? 2 * (d >= 28) + (item & 1) : item - 112;
                const int r = t128 < 112 ? d : 56 + (cc >> 1) + 2 * ((t128 - 112) >> 2);
                uint32_t ra = sb + OFF_KVB + r * 128 + 4 * cc, rx = (r & 7) << 4;
                asm volatile("" : "+r"(ra), "+r"(rx));
                FOR14(asm volatile("st.shared.u32 [%0+%2], %1;" ::"r"((ra ^ 8) + (((t & 7) << 4) ^ rx)), "r"(0), "n"((t >> 3) * 8192) : "memory"));
                uint32_t v[16];
                asm volatile("" : "+r"(ra), "+r"(rx));
                poll4_kv<8>(v, g_kv2 + sl * 512 + (item >> 3) * 32 + (item & 7), tag);
                FOR14(asm volatile("st.shared.u32 [%0+%2], %1;" ::"r"(ra + (((t & 7) << 4) ^ rx)), "r"(v[t < 7 ? t : t + 1]), "n"((t >> 3) * 8192) : "memory"));
                fence_async();
            }
            bar_arrive(3, 384);
            ASTAMP(3);
            }
        }
    } else {
        asm volatile("setmaxnreg.inc.sync.aligned.u32 232;");
        int lane = fresh_tid() & 31, prf = pr;
#define pr prf
#define g (lane >> 2)
#define c (lane & 3)
#define t128 (w * 32 + lane)
        const int wu = __shfl_sync(0xffffffffu, fresh_tid() >> 5, 0), w = wu & 3;
        const uint32_t xoff = __shfl_sync(0xffffffffu, (3 * PLANE + ((tile * 2 + wgi) * 8) * 512 + w * 128) * 16, 0);
        char* xu = reinterpret_cast<char*>(g_ex) + xoff;
#define FRESH() asm volatile("" : "+l"(xu), "+r"(lane), "+r"(prf))
#define xp0 (reinterpret_cast<uint4*>(xu) + lane)
        const uint32_t hbuf = sb + OFF_H + wgi * STAGE;
        uint32_t slot = 0, ph = 0, eb1 = 0, eb2 = 0, ackph = 0, rcvph = 0, gatph = 0, swp = 0;
        uint32_t ppid = 6;
#define cx(s) (reinterpret_cast<uint32_t*>(reinterpret_cast<uint4*>(xu) + PL(1) + 112 + (s) * 512))
#define stp (reinterpret_cast<uint4*>(xu) + g + PL(0) + 112)
        uint32_t seq = ld_word(cx(sl));
        uint32_t kseq = ld_word(g_c1 + ((sl * 8 + wu) * 16 + tile) * 32);
        uint32_t stag = ld_word(reinterpret_cast<const uint32_t*>(stp + sl * 512) + 3) & 1;
        asm volatile("barrier.cluster.wait.aligned;" ::: "memory");
        STAMP(1);
        uint32_t X[14];
        const uint32_t x0row = (w < 2 ? hbuf : sb + wgi * STAGE) + ((w & 1) * 16 + (lane & 15)) * 128;
        mbar_wait(BAR(wgi), 0);
        STAMP(51);
#pragma unroll
        for (int j = 0; j < 4; j++) {
            const int G = 7 * sl + min(2 * j + (lane >> 4), 6);
            uint32_t q2, q3;
            asm volatile("ldmatrix.sync.aligned.m8n8.x4.shared.b16 {%0,%1,%2,%3}, [%4];" : "=r"(X[4 * j]), "=r"(X[4 * j + 1]), "=r"(q2), "=r"(q3)
                         : "r"(x0row + (G >> 3) * 4096 + (((G ^ lane) & 7) << 4)) : "memory");
            if (j < 3) { X[(4 * j + 2) % 14] = q2; X[(4 * j + 3) % 14] = q3; }
        }
#define PUSH_SLICE(W)                                                                          \
    {                                                                                          \
        if (t128 == 0) mbar_expect_tx(BAR(B_RECV + wgi), 7168);                                \
        PUSH_BEGIN();                                                                          \
        const uint32_t ra = mapa(hbuf + 24576 + t128 * 16, hr ^ 1), rb = mapa(sb + OFF_XR + wgi * 3072, hr ^ 1), rbar = mapa(BAR(B_RECV + wgi), hr ^ 1); \
        st_async4(ra, W[0], W[1], W[2], W[3], rbar);                                           \
        st_async4(ra + 2048, W[4], W[5], W[6], W[7], rbar);                                    \
        st_async4(rb + t128 * 16, W[8], W[9], W[10], W[11], rbar);                             \
        asm volatile("st.async.weak.shared::cluster.mbarrier::complete_tx::bytes.v2.b32 [%0], {%1,%2}, [%3];" ::"r"(rb + 2048 + t128 * 8), "r"(W[12]), "r"(W[13]), "r"(rbar) : "memory"); \
    }
#define PULL_SLICE(W)                                                                          \
    {                                                                                          \
        uint32_t t0, t1;                                                                       \
        mbar_wait(BAR(B_RECV + wgi), rcvph);                                                   \
        rcvph ^= 1;                                                                            \
        lds4(&A[1][0], hbuf + 24576 + t128 * 16);                                              \
        lds4(&A[1][4], hbuf + 26624 + t128 * 16);                                              \
        lds4(&A[1][8], sb + OFF_XR + wgi * 3072 + t128 * 16);                                  \
        asm volatile("ld.shared.v2.u32 {%0,%1}, [%2];" : "=r"(t0), "=r"(t1) : "r"(sb + OFF_XR + wgi * 3072 + 2048 + t128 * 8) : "memory"); \
        _Pragma("unroll") for (int i = 0; i < 12; i++) A[0][i] = (i & 3) ? W[i] : W[i] & ~1u;  \
        A[1][0] &= ~1u; A[1][4] &= ~1u; A[1][8] &= ~1u;                                        \
        A[0][12] = (hr ? t0 : W[12]) & ~1u; A[0][13] = hr ? t1 : W[13];                        \
        A[1][12] = (hr ? W[12] : t0) & ~1u; A[1][13] = hr ? W[13] : t1;                        \
        asm volatile("" : RW4(A[0], 0), RW4(A[0], 4), RW4(A[0], 8), RW2(A[0], 12), RW4(A[1], 0), RW4(A[1], 4), RW4(A[1], 8), RW2(A[1], 12)); \
        swp = hr * 448;                                                                        \
    }
#define SWB(b, t, db, sh) ((b) == 0 && (t) < 6 ? ((t) < 3 ? db##p : db##m) : db)
#define DECL_DB(b, MK, lbo, sh) const uint64_t db = MK(0, lbo, R_ADJ), dbp = (b) == 0 ? MK(0, lbo, R_ADJ + (swp >> (sh))) : db, dbm = (b) == 0 ? MK(0, lbo, R_ADJ - (swp >> (sh))) : db;
#define PPB 2
#define PP_WAIT() if (wgi == 1) { bar_sync(ppid, 256); ppid ^= 14; }
#define PP_GO() if (wgi == 0) { bar_arrive(ppid, 256); ppid ^= 14; }
#define GAT_DST(B, s2) ((B) == 1 ? hbuf + w * 3584 + (s2) * 1792 : ((s2) ? sb + OFF_KVB + wgi * 8192 : hbuf + 14336) + w * 1792)
#define GAT_ISSUE(B, base)                                                                     \
    {                                                                                          \
        const char* gs = xu + ((base) + kblk(pr, B) * 1024) * 16;                              \
        asm volatile("{ .reg .pred e; elect.sync _|e, 0xffffffff;\n"                           \
                     "@e mbarrier.arrive.expect_tx.shared::cta.b64 _, [%3], 3584;\n"           \
                     "@e cp.async.bulk.shared::cluster.global.mbarrier::complete_tx::bytes [%0], [%2], 1792, [%3];\n" \
                     "@e cp.async.bulk.shared::cluster.global.mbarrier::complete_tx::bytes [%1], [%2+8192], 1792, [%3]; }" \
                     ::"r"(GAT_DST(B, 0)), "r"(GAT_DST(B, 1)), "l"(gs), "r"(BAR(B_GAT + wu * 2 + ((B) >> 1))) : "memory"); \
        __syncwarp();                                                                          \
    }
#define GAT_FETCH(B)                                                                           \
    {                                                                                          \
        mbar_wait(BAR(B_GAT + wu * 2 + ((B) >> 1)), (gatph >> (B)) & 1);                          \
        gatph ^= 1 << (B);                                                                     \
        _Pragma("unroll") for (int s2 = 0; s2 < 2; s2++) {                                     \
            const uint32_t ga = GAT_DST(B, s2) + lane * 16;                                    \
            lds4(&A[2 * (B) + s2][0], ga); lds4(&A[2 * (B) + s2][4], ga + 512); lds4(&A[2 * (B) + s2][8], ga + 1024); \
            asm volatile("ld.shared.v2.u32 {%0,%1}, [%2];" : "=r"(A[2 * (B) + s2][12]), "=r"(A[2 * (B) + s2][13]) : "r"(ga - lane * 8 + 1536) : "memory"); \
        }                                                                                      \
    }
#define LATE_ARRIVE() do { if (lane == 0) mbar_arrive(BAR(B_LATE)); } while (0)
#define LATE_WAIT() do { mbar_wait(BAR(B_LATE), gatph & 1); gatph ^= 1; } while (0)
#define PT 3
#define PREP(b, t, remote)                                                                     \
    if constexpr ((b) == 0 && (t) == L2T && L2T != PT0) { if (remote) blk_load<2>(A, BLK(xsrc, 2), lane); } \
    if constexpr ((b) < 3 && (t) == ((b) ? PT : PT0)) {                                                      \
        wg_commit();                                                                           \
        STAMP(74 + 6 * (step & 1) + 2 * (b));                                                  \
        if (remote) {                                                                          \
            if constexpr ((b) == 0) { if (L2T == PT0) blk_load<2>(A, BLK(xsrc, 2), lane); GAT_FETCH(1) }       \
            blk_check<((b) + 1) & 3>(A, BLK(xsrc, (b) + 1), lane, xtag);                       \
            if constexpr ((b) == 0) blk_load<3>(A, BLK(xsrc, 3), lane);                        \
        }                                                                                      \
        STAMP(75 + 6 * (step & 1) + 2 * (b));                                                  \
        normalize<((b) + 1) & 3>(A, k0, k1);                                                   \
        asm volatile("" : RW4(A[(2 * (b) + 2) & 7], 0), RW4(A[(2 * (b) + 2) & 7], 4), RW4(A[(2 * (b) + 2) & 7], 8), RW2(A[(2 * (b) + 2) & 7], 12), \
                          RW4(A[(2 * (b) + 3) & 7], 0), RW4(A[(2 * (b) + 3) & 7], 4), RW4(A[(2 * (b) + 3) & 7], 8), RW2(A[(2 * (b) + 3) & 7], 12)); \
        wg_fence();                                                                            \
    }
#define X0_BLOCK(b)                                                                            \
    { const int rr = lane & 7, hi = lane >> 4;                                                 \
    const uint32_t rowa = (w < 2 ? hbuf : sb + wgi * STAGE) + ((w & 1) * 16 + (lane & 15)) * 128; \
    FOR7(constexpr int G = 14 * (b) + (t < 3 ? 2 * t : (t < 6 ? 2 * t + 1 : 6));               \
         uint32_t q0, q1, q2, q3;                                                              \
         const uint32_t ad = t < 6 ? rowa + (((((G & 7) + hi) ^ rr) & 7) << 4) + ((G & 7) == 7 ? hi * 4096 : 0) : rowa + ((G + 7 * hi) >> 3) * 4096 + ((((G + 7 * hi) ^ rr) & 7) << 4); \
         asm volatile("ldmatrix.sync.aligned.m8n8.x4.shared.b16 {%0,%1,%2,%3}, [%4+%5];" : "=r"(q0), "=r"(q1), "=r"(q2), "=r"(q3) \
                      : "r"(ad), "n"(t < 6 ? (G >> 3) * 4096 : 0) : "memory");                 \
         if (t < 3) { A[2 * (b)][4 * t] = q0; A[2 * (b)][4 * t + 1] = q1; A[2 * (b)][4 * t + 2] = q2; A[2 * (b)][4 * t + 3] = q3; } \
         else if (t < 6) { A[2 * (b) + 1][(4 * t - 12) & 15] = q0; A[2 * (b) + 1][((4 * t - 12) & 15) + 1] = q1; A[2 * (b) + 1][((4 * t - 12) & 15) + 2] = q2; A[2 * (b) + 1][((4 * t - 12) & 15) + 3] = q3; } \
         else { A[2 * (b)][12] = q0; A[2 * (b)][13] = q1; A[2 * (b) + 1][12] = q2; A[2 * (b) + 1][13] = q3; }); }
#define BLK(base, b) ((base) + kblk(pr, b) * 1024)

#pragma unroll 1
        for (int step = 0; step < 4; step++) {
            FRESH();
            const uint32_t tag = (step >> 1) ^ 1;
            const int so = (step >> 1) * 24 + (step & 1) * 12;
            (void)so;
            uint32_t A[8][14];
            uint4* const xsrc = xp0 + ((step & 1) ? PL(2) : PL(0));
            const uint32_t xtag = (step & 1) ? tag : ((seq >> 3) & 1) ^ 1;
            uint32_t xbits;
            {
                float st[4];
                slice_stats(X, st);
                stag ^= 1;
                xbits = x_bits(X);
                tag_slice(X, xtag);
                if (step) send_slice<0>(xsrc + sl * 512, lane, X);
                if (c == 0) st_pkt<0>(stp + sl * 512, __float_as_uint(st[0]), __float_as_uint(st[1]), __float_as_uint(st[2]), settag(__float_as_uint(st[3]), stag));
            }
            STAMP(2 + so);
            uint32_t sv[8];
            if (step == 0) {
                X0_BLOCK(0) X0_BLOCK(1) X0_BLOCK(2) X0_BLOCK(3)
                mbar_wait(BAR(wgi ^ 1), 0);
                R_NEXT();
                R_NEXT();
                R_RELEASE(2);
                stat_load(sv, stp + c * 1024);
                stat_check(sv, stp + c * 1024, stag);
                STAMP(52 + step);
            } else {
                kill<14>(A[2]); kill<14>(A[3]); kill<14>(A[4]); kill<14>(A[5]); kill<14>(A[6]); kill<14>(A[7]);
                PUSH_SLICE(X)
                stat_load(sv, stp + c * 1024);
                PULL_SLICE(X)
                stat_check(sv, stp + c * 1024, stag);
                STAMP(52 + step);
                GAT_ISSUE(1, (step & 1) ? PL(2) : PL(0))
            }
            LnCoef k0, k1;
            {
                k0 = ln_coef(__uint_as_float(sv[0]) + __uint_as_float(sv[4]), __uint_as_float(sv[1]) + __uint_as_float(sv[5]));
                k1 = ln_coef(__uint_as_float(sv[2]) + __uint_as_float(sv[6]), __uint_as_float(sv[3] & ~1u) + __uint_as_float(sv[7] & ~1u));
            }
            STAMP(3 + so);
            GSTAMP(70 + step);

            if ((step & 1) == 0) {
                float tq[28];
                {
                    float av[28];
#define KV_BLOCK(b)                                                                           \
    if ((b) == 1) R_RELEASE(2);                                                               \
    if ((b) == 2) { PUSH_ACK(); wg_wait<2>(); R_RELEASE(2); }                                 \
    R_WAIT();                                                                                 \
    if ((b) == PPK) { PP_WAIT() }                                                             \
    { DECL_DB(b, BASE128, 16, 0)                                                              \
    wg_fence();                                                                               \
    FOR7(mma_rs56<1, D128(0, t)>(tq, AQ(A, b, t), (b) + t > 0, SWB(b, t, db, 0));             \
         mma_rs56<1, D128(HALF, t)>(av, AQ(A, b, t), (b) + t > 0, SWB(b, t, db, 0));          \
         PREP(b, t, step)); }                                                                 \
    wg_commit();                                                                              \
    if ((b) == 3 && PPK < 4) { PP_GO() }                                                      \
    R_NEXT();
                    normalize<0>(A, k0, k1);
                    KV_BLOCK(0) KV_BLOCK(1) KV_BLOCK(2) KV_BLOCK(3)
                    wg_wait<0>();
                    if (lane < 3) mbar_arrive(BAR(B_EMPTY + (slot + NST - 1 - lane) % NST));
                    STAMP(4 + so);
                    WSUM(80 + 7 * (step >> 1));
                    const int m = lane >> 3, rr = lane & 7;
                    const uint32_t rowa = hbuf + 16384 + (w * 16 + rr + 8 * (m & 1)) * 128;
                    const uint32_t one = c == 0 ? 0x00003f80u : 0u;
                    if (step == 0) { bar_sync(wgi ? 9 : 1, 224); }
#pragma unroll
                    for (int j = 0; j < 4; j++) {
                        const uint32_t a = rowa + (((2 * j + (m >> 1)) ^ rr) << 4);
                        if (j < 3) stsm4(a, pack2(av[8 * j], av[8 * j + 1]), pack2(av[8 * j + 2], av[8 * j + 3]), pack2(av[8 * j + 4], av[8 * j + 5]), pack2(av[8 * j + 6], av[8 * j + 7]));
                        else stsm4(a, pack2(av[24], av[25]), pack2(av[26], av[27]), one, one);
                    }
                }
                uint32_t PH[28];
                int it = 1;
#pragma unroll 1
                do {
                    float pp[28];
                    phi_gemm(tq, pp);
                    dual_softmax(pp, PH);
                    if (((trips >> (it + 1)) & 1) == 0) continue;
                    {
                        const int m = lane >> 3, rr = lane & 7;
                        const uint32_t rowa = hbuf + (w * 16 + rr + 8 * (m & 1)) * 128;
#pragma unroll
                        for (int j = 0; j < 7; j++) {
                            const int cg = 2 * j + (m >> 1), hi = cg >= 7;
                            stsm4(rowa + hi * 8192 + (((cg - 7 * hi) ^ rr) << 4), PH[4 * j], PH[4 * j + 1], PH[4 * j + 2], PH[4 * j + 3]);
                        }
                    }
                    fence_async();
                    STAMP(5 + so);
#define Q_STAGE(b0)                                                                           \
    R_WAIT();                                                                                 \
    { DECL_DB(b0, BASE128, 16, 0)                                                             \
    wg_fence();                                                                               \
    FOR7(mma_rs56<1, D128(0, t)>(tq, AQ(A, b0, t), (b0) + t > 0, SWB(b0, t, db, 0)));         \
    FOR7(mma_rs56<1, D128(HALF, t)>(tq, AQ(A, (b0) + 1, t), 1, db)); }                        \
    wg_commit();                                                                              \
    R_NEXT();
                    if (QE && wgi == 0) { kill<28>(tq); Q_STAGE(0) Q_STAGE(2) wg_wait<1>(); R_RELEASE(2); wg_wait<0>(); R_RELEASE(1); }
                    bar_sync(2, 256);
                    float kv[28];
                    const uint64_t da = BASE128(OFF_H + 16384, 16, 0), dbk = BASE128(OFF_H, 16, wgi * 512);
                    wg_fence();
                    FOR8(constexpr uint64_t o = ((t >> 2) * STAGE + (t & 3) * 2048) >> 4; mma_ss56_tt<o, o>(kv, t > 0, da, dbk));
                    wg_commit();
                    wg_wait<0>();
#pragma unroll
                    for (int hf = 0; hf < 2; hf++) {
                        const int d = 16 * w + g + 8 * hf;
                        if ((d < 56 && (d >= 28) == (c >= 2)) || d == 56) {
                            const int item = d < 56 ? 2 * d + (c & 1) : 112 + c;
                            uint4* dst = g_kv1 + ((sl * 16 + (item >> 3)) * 16 + tile) * 32 + wgi * 16 + (item & 7);
#define KVW(i) pack2(kv[4 * (i) + 2 * hf], kv[4 * (i) + 2 * hf + 1])
                            st_pkt<0>(dst, settag(KVW(0), tag), KVW(1), KVW(2), KVW(3));
                            st_pkt<8>(dst, settag(KVW(4), tag), KVW(5), KVW(6), 0u);
                        }
                    }
                    __syncwarp();
                    kseq++;
                    if (lane == 0) st_word(g_c1 + ((sl * 8 + wu) * 16 + tile) * 32, kseq);
                    bar_arrive(7, 384);
                    STAMP(6 + so);
                    if (!QE || wgi == 1) { kill<28>(tq); Q_STAGE(0) Q_STAGE(2) wg_wait<1>(); R_RELEASE(2); wg_wait<0>(); R_RELEASE(1); }
                    STAMP(7 + so);
                    kill<28>(PH);
                } while (((trips >> (++it)) & 1));
                STAMP(8 + so);
                FRESH();
                if (step) {
                    slice_load<PL(0)>(X, xp0 + sl * 512, lane);
                } else {
                    const uint32_t* xp = reinterpret_cast<const uint32_t*>(x_in + (size_t)(tile * 128 + wu * 16 + g) * 448 + 56 * sl + 2 * c);
#pragma unroll
                    for (int i = 0; i < 7; i++) { X[2 * i] = __ldg(xp + 4 * i); X[2 * i + 1] = __ldg(xp + 4 * i + 8 * 224); }
                }
                bar_sync(3, 384);
                STAMP(9 + so);
                const uint4* const osrc = xp0 + PL(1);
                {
                    float nm[32];
                    const uint64_t db = BASE128(OFF_KVB, 16, 0);
                    wg_fence();
                    FOR7(mma_rs64<0, ((t >> 2) * 8192 + (t & 3) * 32) / 16>(nm, PH[4 * t], PH[4 * t + 1], PH[4 * t + 2], PH[4 * t + 3], t > 0, db));
                    wg_commit();
                    wg_wait<0>();
                    LATE_ARRIVE();
                    const float i00 = rcp(nm[28] + 1e-6f), i01 = rcp(nm[29] + 1e-6f), i10 = rcp(nm[30] + 1e-6f), i11 = rcp(nm[31] + 1e-6f);
                    const float m0 = c >= 2 ? i01 : i00, m1 = c >= 2 ? i11 : i10;
                    uint32_t O[14];
#pragma unroll
                    for (int i = 0; i < 7; i++) {
                        const float f0 = i < 3 ? i00 : (i > 3 ? i01 : m0), f1 = i < 3 ? i10 : (i > 3 ? i11 : m1);
                        O[2 * i] = pack2(nm[4 * i] * f0, nm[4 * i + 1] * f0);
                        O[2 * i + 1] = pack2(nm[4 * i + 2] * f1, nm[4 * i + 3] * f1);
                    }
                    if (OST) { PP_WAIT() }
                    tag_slice(O, tag);
                    send_slice<PL(1)>(xp0 + sl * 512, lane, O);
                    seq++;
                    if (lane == 0) st_word(cx(sl), seq);
                    STAMP(10 + so);
                    PUSH_SLICE(O)
                    if (OST == 1) { PP_GO() }
                    const uint32_t cv = ld_word(cx(lane & 7));
                    PULL_SLICE(O)
                    LATE_WAIT();
                    check_cnt(cv, cx(lane & 7), seq);
                    if (OST == 2) { PP_GO() }
                    STAMP(56 + (step >> 1));
                    GAT_ISSUE(1, PL(1))
                    GAT_ISSUE(3, PL(1))
                    blk_load<2>(A, BLK(osrc, 2), lane);
                }
                float ao[28];
#define WO_BLOCK(b)                                                                           \
    if ((b) > 0) blk_check<b>(A, BLK(osrc, b), lane, tag);                                    \
    if (((b) & 1) == 0) R_WAIT();                                                             \
    { DECL_DB(b, BASE128, 16, 0)                                                              \
    wg_fence();                                                                               \
    FOR7(mma_rs56<1, D128(((b) & 1) * HALF, t)>(ao, AQ(A, b, t), (b) + t > 0, SWB(b, t, db, 0))); } \
    wg_commit();                                                                              \
    if ((b) & 1) R_NEXT();
                WO_BLOCK(0)
                STAMP(11 + so);
                GAT_FETCH(1)
                WO_BLOCK(1)
                WO_BLOCK(2)
                GAT_FETCH(3)
                WO_BLOCK(3)
                PUSH_ACK();
                wg_wait<0>();
                R_RELEASE(2);
                STAMP(12 + so);
                WSUM(86 + 7 * (step >> 1));
                x_fix(X, xbits);
#pragma unroll
                for (int i = 0; i < 14; i++) X[i] = pack2(bf_lo(X[i]) + ao[2 * i], bf_hi(X[i]) + ao[2 * i + 1]);
            } else {
                uint32_t H[56];
                float ag[64];
#define F1_EPI(dst, ng, ag)                                                                    \
    _Pragma("unroll") for (int i = 0; i < 2 * (ng); i++)                                       \
        (dst)[i] = pack2(geglu(ag[2 * i], ag[4 * (ng) + 2 * i]), geglu(ag[2 * i + 1], ag[4 * (ng) + 2 * i + 1]));
#define H_PUSH(h0, off) st_async4(rem_h + (off), H[h0], H[(h0) + 1], H[(h0) + 2], H[(h0) + 3], mapa(BAR(B_RECV2 + wgi), hr ^ 1));
#define F1_BLOCK(b, first)                                                                     \
    if ((first) && (b) == 1) R_RELEASE(2);                                                     \
    if ((first) && (b) == 2) PUSH_ACK();                                                       \
    R_WAIT();                                                                                  \
    if ((b) == ((first) ? PPF : PPB)) { PP_WAIT() }                                            \
    { DECL_DB(b, BASE128, HALF, 0)                                                             \
    wg_fence();                                                                                \
    FOR7(mma_rs128<1, D128(0, t)>(ag, AQ(A, b, t), (b) + t > 0, SWB(b, t, db, 0));             \
         if constexpr (first) { PREP(b, t, true) }); }                                         \
    wg_commit();                                                                               \
    if ((b) == 3) { PP_GO() }                                                                  \
    if ((b) > 0) { wg_wait<1>(); R_RELEASE(1); }       \
    R_NEXT();
                normalize<0>(A, k0, k1);
                F1_BLOCK(0, true) F1_BLOCK(1, true) F1_BLOCK(2, true) F1_BLOCK(3, true)
                if (t128 == 0) { mbar_expect_tx(BAR(B_RECV + wgi), 16384); mbar_expect_tx(BAR(B_RECV2 + wgi), 12288); }
                PUSH_BEGIN();
                wg_wait<0>();
                R_RELEASE(1);
                int p = 0;
#pragma unroll 1
                do {
                    F1_EPI(H + 32, 8, ag)
                    STAMP(4 + p + so);
                    WSUM(81 + p + 7 * (step >> 1));
                    if (((trips >> (p + 1)) & 1) == 0) continue;
                    if (step == 1 && p == PKP) R_NEXT();
                    kill<64>(ag);
                    F1_BLOCK(0, false)
                    {
                        const uint32_t pk = (p ? hbuf + 16384 : sb + OFF_KVB + wgi * 8192) + w * 2048;
#pragma unroll
                        for (int k = 0; k < 4; k++) sts4(pk + k * 512 + lane * 16, H[32 + 4 * k], H[33 + 4 * k], H[34 + 4 * k], H[35 + 4 * k]);
                        fence_async();
                        __syncwarp();
                        asm volatile(ELECT "cp.async.bulk.shared::cluster.shared::cta.mbarrier::complete_tx::bytes [%0], [%1], 2048, [%2]; }"
                                     ::"r"(mapa(hbuf + p * 8192 + w * 2048, hr ^ 1)), "r"(pk), "r"(mapa(BAR(B_RECV + wgi), hr ^ 1)) : "memory");
                    }
                    F1_BLOCK(1, false) F1_BLOCK(2, false) F1_BLOCK(3, false)
                    wg_wait<0>();
                    R_RELEASE(1);
                    kill<16>(H + 32);
                } while (((trips >> (++p)) & 1));
#pragma unroll
                for (int k = 0; k < 4; k++) lds4(H + 16 + 4 * k, hbuf + 16384 + w * 2048 + k * 512 + lane * 16);
                __syncwarp();
                if (lane == 0) asm volatile("mbarrier.arrive.shared::cluster.b64 _, [%0];" ::"r"(mapa(BAR(B_ACK2 + wgi), hr ^ 1)) : "memory");
                const uint32_t rem_h = mapa(hbuf + w * 2048 + lane * 16, hr ^ 1);
#define F1_LAST(b0)                                                                            \
    R_WAIT();                                                                                  \
    if (b0) { PP_WAIT() }                                                                      \
    { DECL_DB(b0, BASE64, HALF, 1)                                                             \
    wg_fence();                                                                                \
    FOR7(mma_rs64<1, D64(0, t)>(al, AQ(A, b0, t), (b0) + t > 0, SWB(b0, t, db, 1)));           \
    FOR7(mma_rs64<1, D64(7168, t)>(al, AQ(A, (b0) + 1, t), 1, db)); }                          \
    wg_commit();                                                                               \
    if (b0) { PP_GO() }                                                                        \
    R_NEXT();
                float al[32];
                F1_LAST(0)
                mbar_wait(BAR(B_RECV + wgi), rcvph);
                rcvph ^= 1;
                mbar_wait(BAR(B_ACK2 + wgi), step >> 1);
                H_PUSH(32, 16384) H_PUSH(36, 16896)
                F1_LAST(2)
                H_PUSH(40, 17408) H_PUSH(44, 17920)
                wg_wait<1>();
                R_RELEASE(2);
                wg_wait<0>();
                R_RELEASE(1);
                uint32_t HP[56];
#pragma unroll
                for (int k = 0; k < 4; k++) lds4(H + 4 * k, sb + OFF_KVB + wgi * 8192 + w * 2048 + k * 512 + lane * 16);
#pragma unroll
                for (int t = 0; t < 8; t++) lds4(HP + 4 * t, hbuf + (t >> 2) * 8192 + w * 2048 + (t & 3) * 512 + lane * 16);
                F1_EPI(H + 48, 4, al)
                H_PUSH(48, 24576 - w * 1024) H_PUSH(52, 25088 - w * 1024)
                STAMP(7 + so);
                WSUM(84 + 7 * (step >> 1));
                FRESH();
                float acc[28];
                const uint32_t roA = hr ? 256u : 0u, roB = hr ? (uint32_t)-1536 : 0u;
                const uint32_t rpA = hr ? 0u : 256u, rpB = hr ? 0u : (uint32_t)-1536;
                float res[28];
                uint32_t v0[14], v1[14], P[14];
                const uint4* ps = xp0 + sl * 512;
#define F2_OWN_A()                                                                             \
    R_WAIT();                                                                                  \
    d0 = BASE128(0, 16, R_ADJ + roA); d1 = BASE128(0, 16, R_ADJ + roB);                        \
    wg_fence();                                                                                \
    FOR14(if constexpr (t < OT) mma_rs56<1, t * 128>(acc, H[4 * t], H[4 * t + 1], H[4 * t + 2], H[4 * t + 3], t > 0, d0)); \
    wg_commit();
#define F2_OWN_B()                                                                             \
    wg_fence();                                                                                \
    FOR14(if constexpr (t >= OT) mma_rs56<1, t * 128>(acc, H[4 * t], H[4 * t + 1], H[4 * t + 2], H[4 * t + 3], 1, t < 12 ? d0 : d1)); \
    wg_commit();                                                                               \
    R_NEXT();
#define F2_PEER()                                                                              \
    R_WAIT();                                                                                  \
    if (F2PP) { PP_WAIT() }                                                                    \
    d0 = BASE128(0, 16, R_ADJ + rpA); d1 = BASE128(0, 16, R_ADJ + rpB);                        \
    wg_fence();                                                                                \
    FOR14(mma_rs56<1, t * 128>(acc, HP[4 * t], HP[4 * t + 1], HP[4 * t + 2], HP[4 * t + 3], 1, t < 12 ? d0 : d1)); \
    wg_commit();                                                                               \
    if (F2PP) { PP_GO() }                                                                      \
    R_NEXT();
#define F2_TURN(u)                                                                             \
    wg_wait<1>();                                                                              \
    if ((u) < 2 || TDEF < 2) R_RELEASE(2);                                                     \
    wg_wait<0>();                                                                              \
    if ((u) < 2 || TDEF < 1) R_RELEASE(1);                                                     \
    _Pragma("unroll") for (int i = 0; i < 14; i++) P[i] = pack2(acc[2 * i], acc[2 * i + 1]);   \
    tag_slice(P, tag);                                                                         \
    asm volatile("" : RW4(P, 0), RW4(P, 4), RW4(P, 8), RW2(P, 12));                            \
    kill<28>(acc);                                                                             \
    F2_OWN_A()                                                                                 \
    if ((u) == 2) { slice_load<PL(3)>(v0, ps, lane); slice_load<PL(4)>(v1, ps, lane); } \
    send_slice<PL(3 + (u))>(xp0 + (2 * ((pr + (u) + 1) & 3) + hr) * 512, lane, P);             \
    seq++;                                                                                     \
    if (lane == 0) st_word(cx(sl), seq);                                                       \
    __syncwarp();                                                                              \
    STAMP(8 + (u) + so);                                                                       \
    F2_OWN_B()
                uint64_t d0, d1;
                F2_OWN_A()
                F2_OWN_B()
                R_WAIT();
                d0 = BASE128(0, 16, R_ADJ + rpA); d1 = BASE128(0, 16, R_ADJ + rpB);
                wg_fence();
                FOR8(mma_rs56<1, t * 128>(acc, HP[4 * t], HP[4 * t + 1], HP[4 * t + 2], HP[4 * t + 3], 1, d0));
                wg_commit();
                mbar_wait(BAR(B_RECV2 + wgi), step >> 1);
#pragma unroll
                for (int k = 0; k < 4; k++) lds4(HP + 32 + 4 * k, hbuf + 16384 + w * 2048 + k * 512 + lane * 16);
                lds4(HP + 48, hbuf + 24576 + w * 1024 + lane * 16);
                lds4(HP + 52, hbuf + 25088 + w * 1024 + lane * 16);
                if (step == 1) PUSH_ACK();
                wg_fence();
                FOR14(if constexpr (t >= 8) mma_rs56<1, t * 128>(acc, HP[4 * t], HP[4 * t + 1], HP[4 * t + 2], HP[4 * t + 3], 1, t < 12 ? d0 : d1));
                wg_commit();
                R_NEXT();
                F2_TURN(0)
                F2_PEER()
                F2_TURN(1)
                F2_PEER()
                F2_TURN(2)
                if (step == 1) STAMP(64);
                slice_check<PL(3)>(v0, ps, lane, tag);
                slice_check<PL(4)>(v1, ps, lane, tag);
#pragma unroll
                for (int i = 0; i < 14; i++) { res[2 * i] = bf_lo(v0[i]) + bf_lo(v1[i]); res[2 * i + 1] = bf_hi(v0[i]) + bf_hi(v1[i]); }
                slice_load<PL(2)>(X, ps, lane);
                if (step == 1) STAMP(65);
                F2_PEER()
                if (step == 1) STAMP(66);
                poll_cnt(cx(2 * ((pr + 1) & 3) + hr), seq);
                if (step == 1) STAMP(67);
                slice_load<PL(5)>(v0, ps, lane);
                x_fix(X, xbits);
                slice_check<PL(5)>(v0, ps, lane, tag);
                if (lane < TDEF) mbar_arrive(BAR(B_EMPTY + (slot + NST - 3 - lane) % NST));
#pragma unroll
                for (int i = 0; i < 14; i++) { res[2 * i] += bf_lo(v0[i]); res[2 * i + 1] += bf_hi(v0[i]); }
                STAMP(11 + so);
                wg_wait<0>();
                R_RELEASE(2);
                STAMP(12 + so);
                WSUM(85 + 7 * (step >> 1));
#pragma unroll
                for (int i = 0; i < 14; i++) X[i] = pack2(fmaf(res[2 * i] + acc[2 * i], 0.5f, bf_lo(X[i])), fmaf(res[2 * i + 1] + acc[2 * i + 1], 0.5f, bf_hi(X[i])));
            }
        }
        {
            const int m = lane >> 3, rr = lane & 7;
            const uint32_t ob = hbuf + w * 2048, rowa = ob + (rr + 8 * (m & 1)) * 112 + (m >> 1) * 16;
#pragma unroll
            for (int j = 0; j < 3; j++) stsm4(rowa + 32 * j, X[4 * j], X[4 * j + 1], X[4 * j + 2], X[4 * j + 3]);
            asm volatile("stmatrix.sync.aligned.m8n8.x2.shared.b16 [%0], {%1,%2};" ::"r"(ob + (rr + 8 * (m & 1)) * 112 + 96), "r"(X[12]), "r"(X[13]) : "memory");
            fence_async();
            __syncwarp();
            if (lane == 0) {
                asm volatile("cp.async.bulk.tensor.2d.global.shared::cta.bulk_group [%0, {%2, %3}], [%1];" ::"l"(&maps.out), "r"(ob), "r"(56 * sl), "r"(tile * 128 + wu * 16) : "memory");
                asm volatile("cp.async.bulk.commit_group;" ::: "memory");
                asm volatile("cp.async.bulk.wait_group.read 0;" ::: "memory");
            }
        }
        STAMP(50);
        GSTAMP(61);
        PDUMP();
    }
}

#undef g
#undef pr
#undef c
#undef t128

typedef CUresult (*EncodeFn)(CUtensorMap*, CUtensorMapDataType, cuuint32_t, void*, const cuuint64_t*, const cuuint64_t*, const cuuint32_t*,
                             const cuuint32_t*, CUtensorMapInterleave, CUtensorMapSwizzle, CUtensorMapL2promotion, CUtensorMapFloatOOBfill);

static void make_map(EncodeFn enc, CUtensorMap* m, const void* p, uint64_t cols, uint64_t rows, uint32_t bc, uint32_t br, CUtensorMapSwizzle sw) {
    cuuint64_t gd[2] = {cols, rows};
    cuuint64_t gs[1] = {cols * 2};
    cuuint32_t bd[2] = {bc, br};
    cuuint32_t es[2] = {1, 1};
    enc(m, CU_TENSOR_MAP_DATA_TYPE_BFLOAT16, 2, const_cast<void*>(p), gd, gs, bd, es, CU_TENSOR_MAP_INTERLEAVE_NONE, sw,
        CU_TENSOR_MAP_L2_PROMOTION_L2_128B, CU_TENSOR_MAP_FLOAT_OOB_FILL_NONE);
}

extern "C" void kernel_launch(void* const* d_in, const int* in_sizes, int n_in, void* d_out, int out_size) {
    (void)in_sizes; (void)n_in; (void)out_size;
    static EncodeFn enc = nullptr;
    static Scratch* scratch = nullptr;
    if (!enc) {
        void* fn = nullptr;
        cudaDriverEntryPointQueryResult qr;
        cudaGetDriverEntryPoint("cuTensorMapEncodeTiled", &fn, cudaEnableDefault, &qr);
        enc = (EncodeFn)fn;
        cudaGetSymbolAddress((void**)&scratch, g_scratch);
        cudaFuncSetAttribute(fused_kernel, cudaFuncAttributeMaxDynamicSharedMemorySize, SMEM_BYTES);
    }
    Maps maps;
    {
        cuuint64_t gd[3] = {64, 2048, 7};
        cuuint64_t gs[2] = {896, 128};
        cuuint32_t bd[3] = {64, 32, 7};
        cuuint32_t es[3] = {1, 1, 1};
        enc(&maps.x, CU_TENSOR_MAP_DATA_TYPE_BFLOAT16, 3, d_in[0], gd, gs, bd, es, CU_TENSOR_MAP_INTERLEAVE_NONE, CU_TENSOR_MAP_SWIZZLE_128B,
            CU_TENSOR_MAP_L2_PROMOTION_L2_128B, CU_TENSOR_MAP_FLOAT_OOB_FILL_NONE);
    }
    make_map(enc, &maps.out, d_out, 448, 2048, 56, 16, CU_TENSOR_MAP_SWIZZLE_NONE);
    make_map(enc, &maps.qkv, d_in[1], 1344, 448, 64, 112, CU_TENSOR_MAP_SWIZZLE_128B);
    make_map(enc, &maps.wo, d_in[3], 448, 448, 64, 112, CU_TENSOR_MAP_SWIZZLE_128B);
    make_map(enc, &maps.wg, d_in[5], 1792, 448, 64, 112, CU_TENSOR_MAP_SWIZZLE_128B);
    make_map(enc, &maps.wu, d_in[6], 1792, 448, 64, 112, CU_TENSOR_MAP_SWIZZLE_128B);
    make_map(enc, &maps.wg32, d_in[5], 1792, 448, 32, 112, CU_TENSOR_MAP_SWIZZLE_64B);
    make_map(enc, &maps.wu32, d_in[6], 1792, 448, 32, 112, CU_TENSOR_MAP_SWIZZLE_64B);
    make_map(enc, &maps.wd, d_in[7], 448, 1792, 64, 112, CU_TENSOR_MAP_SWIZZLE_128B);
    fused_kernel<<<128, 384, SMEM_BYTES>>>(scratch, (const __nv_bfloat16*)d_in[0], (const __nv_bfloat16*)d_in[2], 7, (const __nv_bfloat16*)d_in[5],
                                           (const __nv_bfloat16*)d_in[6], (const __nv_bfloat16*)d_in[7], maps);
}
```

```cpp
#include <cuda_runtime.h>
#include <cuda.h>
#include <cuda_bf16.h>
#include <stdint.h>
#include <type_traits>

#define PPF 2
#define PKP 0
#define TDEF 1
#define TMPF 0
#define NORM1 0
#define LPARK 1
#define PFP 0
#define ACAN 0
#define SPLIT0 1
#define OT 2
#define F2PP 0
#define PPK 2
#define QE 1
#define OST 1
#define PP

namespace {

constexpr uint32_t STAGE = 28672, HALF = 14336;
constexpr int NST = 5;
constexpr uint32_t OFF_H = NST * STAGE;
constexpr uint32_t OFF_KVB = OFF_H + 2 * STAGE;
constexpr uint32_t OFF_WPHI = OFF_KVB + 16384;
constexpr uint32_t OFF_XR = OFF_WPHI + 7168;
constexpr uint32_t OFF_BAR = OFF_XR + 6144;
constexpr uint32_t SMEM_BYTES = OFF_BAR + 384 + 1408;
constexpr int B_EMPTY = NST, B_RECV = 2 * NST, B_RECV2 = B_RECV + 2, B_PACK = B_RECV2 + 2, B_GAT = B_PACK + 1, B_LATE = B_GAT + 16, B_ACK = B_LATE + 1, B_ACK2 = B_ACK + 2, B_COUNT = B_ACK2 + 2;

constexpr int PACK = 14 + 4 * PKP;

struct Maps { CUtensorMap x, qkv, wo, wg, wu, wg32, wu32, wd, out; };

}

constexpr int PLANE = 16 * 2 * 8 * 512;
struct Scratch {
    uint4 ex[6 * PLANE];
    uint4 kv1[8 * 16 * 16 * 32];
    uint4 kv2[8 * 512];
    uint32_t c1[8 * 8 * 16 * 32];
    uint32_t cw[8 * 32];
    uint4 wp[8 * 32 * (HALF / 16)];
};
__device__ __align__(1024) Scratch g_scratch;
#define g_ex (sc->ex)
#define g_kv1 (sc->kv1)
#define g_kv2 (sc->kv2)
#define g_c1 (sc->c1)
#define g_cw (sc->cw)
#define g_wp (sc->wp)
#define STAMP(i)
#define GSTAMP(i)
#define PDUMP()
#define ASTAMP(i)

namespace {

__device__ __forceinline__ int fresh_tid() { int t; asm volatile("mov.u32 %0, %%tid.x;" : "=r"(t)); return t; }
template <int N> __device__ __forceinline__ void kill(uint32_t* v) {
#pragma unroll
    for (int i = 0; i < N; i++) v[i] = 0;
}
template <int N> __device__ __forceinline__ void kill(float* v) {
#pragma unroll
    for (int i = 0; i < N; i++) v[i] = 0.f;
}
__device__ __forceinline__ uint32_t s2u(const void* p) { return (uint32_t)__cvta_generic_to_shared(p); }
__device__ __forceinline__ void mbar_init(uint32_t a, uint32_t c) { asm volatile("mbarrier.init.shared::cta.b64 [%0], %1;" ::"r"(a), "r"(c) : "memory"); }
__device__ __forceinline__ void mbar_expect_tx(uint32_t a, uint32_t b) { asm volatile("mbarrier.arrive.expect_tx.shared::cta.b64 _, [%0], %1;" ::"r"(a), "r"(b) : "memory"); }
__device__ __forceinline__ void mbar_arrive(uint32_t a) { asm volatile("mbarrier.arrive.shared::cta.b64 _, [%0];" ::"r"(a) : "memory"); }
#define GIVE_UP(id) "trap;\n"
#define SPIN_MAX "0x400000"
#define SPIN_TAIL(id) "add.u32 n, n, 1;\n setp.lt.u32 p, n, " SPIN_MAX ";\n @p bra.uni LP;\n" GIVE_UP(id) " DN:\n }"
__device__ __forceinline__ void mbar_wait(uint32_t a, uint32_t ph) {
    asm volatile("{ .reg .pred p; .reg .b32 n; mov.u32 n, 0;\n LP:\n"
                 "mbarrier.try_wait.parity.shared::cta.b64 p, [%0], %1;\n @p bra DN;\n"
                 "add.u32 n, n, 1;\n setp.lt.u32 p, n, " SPIN_MAX ";\n @p bra LP;\n"
                 GIVE_UP("")
                 " DN:\n }" ::"r"(a), "r"(ph) : "memory");
}
#define ELECT "{ .reg .pred e; elect.sync _|e, 0xffffffff; @e "
__device__ __forceinline__ void tma2d(uint32_t dst, const CUtensorMap* m, int c0, int c1, uint32_t bar) {
    asm volatile(ELECT "cp.async.bulk.tensor.2d.shared::cluster.global.mbarrier::complete_tx::bytes [%0], [%1, {%3, %4}], [%2]; }" ::"r"(dst), "l"(m), "r"(bar), "r"(c0), "r"(c1) : "memory");
}
__device__ __forceinline__ void tma3x(uint32_t dst, const CUtensorMap* m, int row, uint32_t bar) {
    asm volatile(ELECT "cp.async.bulk.tensor.3d.shared::cluster.global.mbarrier::complete_tx::bytes [%0], [%1, {0, %3, 0}], [%2]; }" ::"r"(dst), "l"(m), "r"(bar), "r"(row) : "memory");
}
template <int OFF>
__device__ __forceinline__ void ld_pkt(uint32_t* v, const uint4* p) {
    asm volatile("{ .reg .b128 t; ld.relaxed.gpu.global.b128 t, [%4+%5]; mov.b128 {%0,%1,%2,%3}, t; }" : "=r"(v[0]), "=r"(v[1]), "=r"(v[2]), "=r"(v[3]) : "l"(p), "n"(OFF * 16) : "memory");
}
template <int OFF>
__device__ __forceinline__ void st_pkt(uint4* p, uint32_t a, uint32_t b, uint32_t c, uint32_t d) {
    asm volatile("{ .reg .b128 t; mov.b128 t, {%1,%2,%3,%4}; st.relaxed.gpu.global.b128 [%0+%5], t; }" ::"l"(p), "r"(a), "r"(b), "r"(c), "r"(d), "n"(OFF * 16) : "memory");
}
__device__ __forceinline__ uint32_t pack2(float lo, float hi) {
    uint32_t r;
    asm("cvt.rn.bf16x2.f32 %0, %1, %2;" : "=r"(r) : "f"(hi), "f"(lo));
    return r;
}
__device__ __forceinline__ float bf_lo(uint32_t w) { return __uint_as_float(w << 16); }
__device__ __forceinline__ float bf_hi(uint32_t w) { return __uint_as_float(w & 0xffff0000u); }
__device__ __forceinline__ uint32_t settag(uint32_t w, uint32_t tag) { return (w & ~1u) | tag; }
__device__ __forceinline__ float ex2(float x) { float y; asm("ex2.approx.ftz.f32 %0, %1;" : "=f"(y) : "f"(x)); return y; }
__device__ __forceinline__ float rcp(float x) { float y; asm("rcp.approx.ftz.f32 %0, %1;" : "=f"(y) : "f"(x)); return y; }
__device__ __forceinline__ float tanh_hw(float x) { float y; asm("tanh.approx.f32 %0, %1;" : "=f"(y) : "f"(x)); return y; }
__device__ __forceinline__ void stsm4(uint32_t addr, uint32_t a, uint32_t b, uint32_t c, uint32_t d) {
    asm volatile("stmatrix.sync.aligned.m8n8.x4.shared.b16 [%0], {%1,%2,%3,%4};" ::"r"(addr), "r"(a), "r"(b), "r"(c), "r"(d) : "memory");
}
__device__ __forceinline__ void fence_async() { asm volatile("fence.proxy.async.shared::cta;" ::: "memory"); }
__device__ __forceinline__ void bar_sync(int id, int n) { asm volatile("bar.sync %0, %1;" ::"r"(id), "r"(n) : "memory"); }
__device__ __forceinline__ void bar_arrive(int id, int n) { asm volatile("bar.arrive %0, %1;" ::"r"(id), "r"(n) : "memory"); }
__device__ __forceinline__ void wg_fence() { asm volatile("wgmma.fence.sync.aligned;" ::: "memory"); }
__device__ __forceinline__ void wg_commit() { asm volatile("wgmma.commit_group.sync.aligned;" ::: "memory"); }
template <int N> __device__ __forceinline__ void wg_wait() { asm volatile("wgmma.wait_group.sync.aligned %0;" ::"n"(N) : "memory"); }

constexpr uint32_t SB0 = 1024;
__host__ __device__ constexpr uint32_t dlo(uint32_t off, uint32_t lbo) { return ((SB0 + off) >> 4) | ((lbo >> 4) << 16); }
__host__ __device__ constexpr uint32_t dhi(uint32_t sbo, uint32_t sw) { return (sbo >> 4) | (sw << 30); }
__device__ __forceinline__ uint64_t dbase(uint32_t lo, uint32_t hi) { uint64_t d; asm volatile("mov.b64 %0, {%1, %2};" : "=l"(d) : "r"(lo), "r"(hi)); return d; }
#define BASE128(off, lbo, adj) dbase(dlo(off, lbo) + (adj), dhi(1024, 1))
#define BASE64(off, lbo, adj) dbase(dlo(off, lbo) + (adj), dhi(512, 2))

#define ACC4(d, o) "+f"(d[o]), "+f"(d[o + 1]), "+f"(d[o + 2]), "+f"(d[o + 3])
#define ACC28(d) ACC4(d, 0), ACC4(d, 4), ACC4(d, 8), ACC4(d, 12), ACC4(d, 16), ACC4(d, 20), ACC4(d, 24)
#define ACC32(d, o) ACC4(d, o), ACC4(d, o + 4), ACC4(d, o + 8), ACC4(d, o + 12), ACC4(d, o + 16), ACC4(d, o + 20), ACC4(d, o + 24), ACC4(d, o + 28)

template <int TB, uint64_t D>
__device__ __forceinline__ void mma_rs56(float* d, uint32_t a0, uint32_t a1, uint32_t a2, uint32_t a3, int sd, uint64_t base) {
    asm volatile("{ .reg .pred p; .reg .b64 db; setp.ne.b32 p, %32, 0; add.u64 db, %33, %34;\n"
                 "wgmma.mma_async.sync.aligned.m64n56k16.f32.bf16.bf16 "
                 "{%0,%1,%2,%3,%4,%5,%6,%7,%8,%9,%10,%11,%12,%13,%14,%15,%16,%17,%18,%19,%20,%21,%22,%23,%24,%25,%26,%27}, "
                 "{%28,%29,%30,%31}, db, p, 1, 1, %35; }\n"
                 : ACC28(d)
                 : "r"(a0), "r"(a1), "r"(a2), "r"(a3), "r"(sd), "l"(base), "n"(D), "n"(TB));
}
template <int TB, uint64_t D>
__device__ __forceinline__ void mma_rs64(float* d, uint32_t a0, uint32_t a1, uint32_t a2, uint32_t a3, int sd, uint64_t base) {
    asm volatile("{ .reg .pred p; .reg .b64 db; setp.ne.b32 p, %36, 0; add.u64 db, %37, %38;\n"
                 "wgmma.mma_async.sync.aligned.m64n64k16.f32.bf16.bf16 "
                 "{%0,%1,%2,%3,%4,%5,%6,%7,%8,%9,%10,%11,%12,%13,%14,%15,%16,%17,%18,%19,%20,%21,%22,%23,%24,%25,%26,%27,%28,%29,%30,%31}, "
                 "{%32,%33,%34,%35}, db, p, 1, 1, %39; }\n"
                 : ACC32(d, 0)
                 : "r"(a0), "r"(a1), "r"(a2), "r"(a3), "r"(sd), "l"(base), "n"(D), "n"(TB));
}
template <int TB, uint64_t D>
__device__ __forceinline__ void mma_rs128(float* d, uint32_t a0, uint32_t a1, uint32_t a2, uint32_t a3, int sd, uint64_t base) {
    asm volatile("{ .reg .pred p; .reg .b64 db; setp.ne.b32 p, %68, 0; add.u64 db, %69, %70;\n"
                 "wgmma.mma_async.sync.aligned.m64n128k16.f32.bf16.bf16 "
                 "{%0,%1,%2,%3,%4,%5,%6,%7,%8,%9,%10,%11,%12,%13,%14,%15,%16,%17,%18,%19,%20,%21,%22,%23,%24,%25,%26,%27,%28,%29,%30,%31,%32,%33,%34,%35,%36,%37,%38,%39,%40,%41,%42,%43,%44,%45,%46,%47,%48,%49,%50,%51,%52,%53,%54,%55,%56,%57,%58,%59,%60,%61,%62,%63}, "
                 "{%64,%65,%66,%67}, db, p, 1, 1, %71; }\n"
                 : ACC32(d, 0), ACC32(d, 32)
                 : "r"(a0), "r"(a1), "r"(a2), "r"(a3), "r"(sd), "l"(base), "n"(D), "n"(TB));
}
template <uint64_t DA, uint64_t DB>
__device__ __forceinline__ void mma_ss56_tt(float* d, int sd, uint64_t ba, uint64_t bb) {
    asm volatile("{ .reg .pred p; .reg .b64 da, db; setp.ne.b32 p, %28, 0; add.u64 da, %29, %31; add.u64 db, %30, %32;\n"
                 "wgmma.mma_async.sync.aligned.m64n56k16.f32.bf16.bf16 "
                 "{%0,%1,%2,%3,%4,%5,%6,%7,%8,%9,%10,%11,%12,%13,%14,%15,%16,%17,%18,%19,%20,%21,%22,%23,%24,%25,%26,%27}, "
                 "da, db, p, 1, 1, 1, 1; }\n"
                 : ACC28(d)
                 : "r"(sd), "l"(ba), "l"(bb), "n"(DA), "n"(DB));
}
template <int... I> struct Seq {};
template <class F, int... I> __device__ __forceinline__ void static_for_impl(F&& f, Seq<I...>) { (f(std::integral_constant<int, I>{}), ...); }
#define FOR7(...) static_for_impl([&](auto T_) { constexpr int t = decltype(T_)::value; __VA_ARGS__; }, Seq<0, 1, 2, 3, 4, 5, 6>{})
#define FOR8(...) static_for_impl([&](auto T_) { constexpr int t = decltype(T_)::value; __VA_ARGS__; }, Seq<0, 1, 2, 3, 4, 5, 6, 7>{})
#define FOR14(...) static_for_impl([&](auto T_) { constexpr int t = decltype(T_)::value; __VA_ARGS__; }, Seq<0, 1, 2, 3, 4, 5, 6, 7, 8, 9, 10, 11, 12, 13>{})

__device__ __forceinline__ int kblk(int p, int b) { return b == 0 ? p : b - (b <= p); }
__host__ __device__ constexpr int krow(int t) { return t < 3 ? 16 * t : (t < 6 ? 56 + 16 * (t - 3) : 48); }
#define AQ(A, b, t) ((t) < 3 ? A[2 * (b)][4 * (t)] : (t) < 6 ? A[2 * (b) + 1][4 * ((t) - 3)] : A[2 * (b)][12]), \
                    ((t) < 3 ? A[2 * (b)][4 * (t) + 1] : (t) < 6 ? A[2 * (b) + 1][4 * ((t) - 3) + 1] : A[2 * (b)][13]), \
                    ((t) < 3 ? A[2 * (b)][4 * (t) + 2] : (t) < 6 ? A[2 * (b) + 1][4 * ((t) - 3) + 2] : A[2 * (b) + 1][12]), \
                    ((t) < 3 ? A[2 * (b)][4 * (t) + 3] : (t) < 6 ? A[2 * (b) + 1][4 * ((t) - 3) + 3] : A[2 * (b) + 1][13])
#define D128(off, t) ((uint64_t)(((off) + krow(t) * 128) >> 4) + ((uint64_t)((t) == 6 ? (7168 - 1024) >> 4 : 0) << 32))
#define D64(off, t) ((uint64_t)(((off) + krow(t) * 64) >> 4) + ((uint64_t)((t) == 6 ? (3584 - 512) >> 4 : 0) << 32))

#define PL(k) (((k) - 3) * PLANE)
__device__ __forceinline__ void st_word(uint32_t* p, uint32_t v) { asm volatile("st.relaxed.gpu.global.u32 [%0], %1;" ::"l"(p), "r"(v) : "memory"); }
__device__ __forceinline__ uint32_t ld_word(const uint32_t* p) { uint32_t v; asm volatile("ld.relaxed.gpu.global.u32 %0, [%1];" : "=r"(v) : "l"(p) : "memory"); return v; }
__device__ __forceinline__ void tag_slice(uint32_t* w, uint32_t tag) { w[0] = settag(w[0], tag); w[4] = settag(w[4], tag); w[8] = settag(w[8], tag); w[12] = settag(w[12], tag); }
template <int O>
__device__ __forceinline__ void send_slice(uint4* dst, int lane, const uint32_t* w) {
    st_pkt<O>(dst, w[0], w[1], w[2], w[3]);
    st_pkt<O + 32>(dst, w[4], w[5], w[6], w[7]);
    st_pkt<O + 64>(dst, w[8], w[9], w[10], w[11]);
    asm volatile("{ .reg .b64 t; mov.b64 t, {%1,%2}; st.relaxed.gpu.global.b64 [%0+%3], t; }" ::"l"((char*)dst - lane * 8), "r"(w[12]), "r"(w[13]), "n"(16 * (O + 96)) : "memory");
}
#define RW4(v, o) "+r"(v[o]), "+r"(v[(o) + 1]), "+r"(v[(o) + 2]), "+r"(v[(o) + 3])
#define RW2(v, o) "+r"(v[o]), "+r"(v[(o) + 1])
#define WR4(v, o) "=&r"(v[o]), "=&r"(v[(o) + 1]), "=&r"(v[(o) + 2]), "=&r"(v[(o) + 3])
#define LDP(a, b, c, d, addr, off) "ld.relaxed.gpu.global.b128 q, [" addr "+" off "];\n mov.b128 {" a "," b "," c "," d "}, q;\n"
#define LDH(a, b, addr, off) "ld.relaxed.gpu.global.b64 h, [" addr "+" off "];\n mov.b64 {" a "," b "}, h;\n"
#define VOTE_OK "and.b32 t, t, 1;\n setp.ne.u32 p, t, 0;\n vote.sync.any.pred p, p, 0xffffffff;\n @!p bra.uni DN;\n"
#define CHK(x, tag) "lop3.b32 t, " x ", " tag ", t, 0xBE;\n"
__device__ __forceinline__ void check_cnt(uint32_t v, const uint32_t* p, uint32_t target) {
    asm volatile("{ .reg .pred p; .reg .b32 n, t; mov.u32 n, 0; mov.u32 t, %2;\n LP:\n"
                 "sub.s32 t, t, %1;\n setp.lt.s32 p, t, 0;\n vote.sync.any.pred p, p, 0xffffffff;\n @!p bra.uni DN;\n ld.relaxed.gpu.global.u32 t, [%0];\n" SPIN_TAIL("7")
                 ::"l"(p), "r"(target), "r"(v) : "memory");
}
__device__ __forceinline__ void poll_cnt(const uint32_t* p, uint32_t target) {
    asm volatile("{ .reg .pred p; .reg .b32 n, t; mov.u32 n, 0;\n LP:\n"
                 "ld.relaxed.gpu.global.u32 t, [%0];\n sub.s32 t, t, %1;\n setp.lt.s32 p, t, 0;\n vote.sync.any.pred p, p, 0xffffffff;\n @!p bra.uni DN;\n" SPIN_TAIL("1")
                 ::"l"(p), "r"(target) : "memory");
}
template <int STR>
__device__ __forceinline__ void poll4_kv(uint32_t* v, const uint4* p, uint32_t tag) {
    asm volatile("{ .reg .pred p; .reg .b32 n, t; .reg .b128 q; mov.u32 n, 0;\n LP:\n"
                 LDP("%0", "%1", "%2", "%3", "%16", "0") LDP("%4", "%5", "%6", "%7", "%16", "%18")
                 LDP("%8", "%9", "%10", "%11", "%16", "%19") LDP("%12", "%13", "%14", "%15", "%16", "%20")
                 "xor.b32 t, %0, %17;\n" CHK("%4", "%17") CHK("%8", "%17") CHK("%12", "%17") VOTE_OK SPIN_TAIL("2")
                 : WR4(v, 0), WR4(v, 4), WR4(v, 8), WR4(v, 12)
                 : "l"(p), "r"(tag), "n"(16 * STR), "n"(32 * STR), "n"(48 * STR)
                 : "memory");
}
template <int B>
__device__ __forceinline__ void blk_load(uint32_t (&A)[8][14], const uint4* src, int lane) {
    ld_pkt<0>(&A[2 * B][0], src); ld_pkt<32>(&A[2 * B][4], src); ld_pkt<64>(&A[2 * B][8], src);
    ld_pkt<512>(&A[2 * B + 1][0], src); ld_pkt<544>(&A[2 * B + 1][4], src); ld_pkt<576>(&A[2 * B + 1][8], src);
    asm volatile("{ .reg .b64 h;\n" LDH("%0", "%1", "%4", "1536") LDH("%2", "%3", "%4", "9728") "}"
                 : "=&r"(A[2 * B][12]), "=&r"(A[2 * B][13]), "=&r"(A[2 * B + 1][12]), "=&r"(A[2 * B + 1][13])
                 : "l"((const char*)src - lane * 8) : "memory");
}
template <int B>
__device__ __forceinline__ void blk_check(uint32_t (&A)[8][14], const uint4* src, int lane, uint32_t tag) {
    asm volatile("{ .reg .pred p; .reg .b32 n, t; .reg .b128 q; .reg .b64 h, a8; mov.u32 n, 0;\n LP:\n"
                 "xor.b32 t, %0, %30;\n" CHK("%4", "%30") CHK("%8", "%30") CHK("%12", "%30") CHK("%16", "%30") CHK("%20", "%30") CHK("%24", "%30") CHK("%26", "%30") VOTE_OK
                 LDP("%0", "%1", "%2", "%3", "%28", "0") LDP("%4", "%5", "%6", "%7", "%28", "512") LDP("%8", "%9", "%10", "%11", "%28", "1024")
                 LDP("%12", "%13", "%14", "%15", "%28", "8192") LDP("%16", "%17", "%18", "%19", "%28", "8704") LDP("%20", "%21", "%22", "%23", "%28", "9216")
                 "mad.wide.s32 a8, %29, -8, %28;\n" LDH("%24", "%25", "a8", "1536") LDH("%26", "%27", "a8", "9728") SPIN_TAIL("3")
                 "\n and.b32 %0, %0, -2; and.b32 %4, %4, -2; and.b32 %8, %8, -2; and.b32 %12, %12, -2; and.b32 %16, %16, -2; and.b32 %20, %20, -2; and.b32 %24, %24, -2; and.b32 %26, %26, -2;"
                 : RW4(A[2 * B], 0), RW4(A[2 * B], 4), RW4(A[2 * B], 8), RW4(A[2 * B + 1], 0), RW4(A[2 * B + 1], 4), RW4(A[2 * B + 1], 8),
                   RW2(A[2 * B], 12), RW2(A[2 * B + 1], 12)
                 : "l"(src), "r"(lane), "r"(tag)
                 : "memory");
}
__device__ __forceinline__ void st_async4(uint32_t a, uint32_t x, uint32_t y, uint32_t z, uint32_t w, uint32_t bar) {
    asm volatile("st.async.weak.shared::cluster.mbarrier::complete_tx::bytes.v4.b32 [%0], {%1,%2,%3,%4}, [%5];" ::"r"(a), "r"(x), "r"(y), "r"(z), "r"(w), "r"(bar) : "memory");
}
__device__ __forceinline__ uint32_t mapa(uint32_t a, uint32_t cta) { uint32_t r; asm("mapa.shared::cluster.u32 %0, %1, %2;" : "=r"(r) : "r"(a), "r"(cta)); return r; }
__device__ __forceinline__ void stat_load(uint32_t* v, const uint4* p) { ld_pkt<0>(v, p); ld_pkt<512>(v + 4, p); }
__device__ __forceinline__ void stat_check(uint32_t* v, const uint4* p, uint32_t tag) {
    asm volatile("{ .reg .pred p; .reg .b32 n, t; .reg .b128 q; mov.u32 n, 0;\n LP:\n"
                 "xor.b32 t, %3, %9;\n" CHK("%7", "%9") VOTE_OK
                 LDP("%0", "%1", "%2", "%3", "%8", "0") LDP("%4", "%5", "%6", "%7", "%8", "8192") SPIN_TAIL("4")
                 : RW4(v, 0), RW4(v, 4) : "l"(p), "r"(tag) : "memory");
}
__device__ __forceinline__ uint32_t x_bits(const uint32_t* X) {
    uint32_t r;
    asm volatile("{ .reg .b32 a, b; prmt.b32 a, %1, %2, 0x0040; prmt.b32 b, %3, %4, 0x0040; prmt.b32 %0, a, b, 0x5410; }" : "=r"(r) : "r"(X[0]), "r"(X[4]), "r"(X[8]), "r"(X[12]));
    return r;
}
template <int O>
__device__ __forceinline__ void slice_load(uint32_t* v, const uint4* p, int lane) {
    ld_pkt<O>(v, p); ld_pkt<O + 32>(v + 4, p); ld_pkt<O + 64>(v + 8, p);
    asm volatile("{ .reg .b64 h;\n" LDH("%0", "%1", "%2", "%3") "}" : "=r"(v[12]), "=r"(v[13]) : "l"((const char*)p - lane * 8), "n"(16 * (O + 96)) : "memory");
}
template <int O>
__device__ __forceinline__ void slice_check(uint32_t* v, const uint4* p, int lane, uint32_t tag) {
    asm volatile("{ .reg .pred p; .reg .b32 n, t; .reg .b128 q; .reg .b64 h; mov.u32 n, 0;\n LP:\n"
                 "xor.b32 t, %0, %16;\n" CHK("%4", "%16") CHK("%8", "%16") CHK("%12", "%16") VOTE_OK
                 LDP("%0", "%1", "%2", "%3", "%14", "%17") LDP("%4", "%5", "%6", "%7", "%14", "%18") LDP("%8", "%9", "%10", "%11", "%14", "%19")
                 LDH("%12", "%13", "%15", "%20") SPIN_TAIL("5")
                 : RW4(v, 0), RW4(v, 4), RW4(v, 8), RW2(v, 12)
                 : "l"(p), "l"((const char*)p - lane * 8), "r"(tag), "n"(16 * O), "n"(16 * (O + 32)), "n"(16 * (O + 64)), "n"(16 * (O + 96))
                 : "memory");
}
__device__ __forceinline__ void x_fix(uint32_t* X, uint32_t bits) {
    X[0] = __byte_perm(X[0], bits, 0x3214); X[4] = __byte_perm(X[4], bits, 0x3215); X[8] = __byte_perm(X[8], bits, 0x3216); X[12] = __byte_perm(X[12], bits, 0x3217);
}
__device__ __forceinline__ void sts4(uint32_t a, uint32_t x, uint32_t y, uint32_t z, uint32_t w) {
    asm volatile("st.shared.v4.u32 [%0], {%1,%2,%3,%4};" ::"r"(a), "r"(x), "r"(y), "r"(z), "r"(w) : "memory");
}
__device__ __forceinline__ void lds4(uint32_t* v, uint32_t a) {
    asm volatile("ld.shared.v4.u32 {%0,%1,%2,%3}, [%4];" : "=r"(v[0]), "=r"(v[1]), "=r"(v[2]), "=r"(v[3]) : "r"(a) : "memory");
}
struct LnCoef { uint32_t hi, lo, sh; };
__device__ __forceinline__ LnCoef ln_coef(float sum, float sq) {
    sum += __shfl_xor_sync(0xffffffffu, sum, 1); sq += __shfl_xor_sync(0xffffffffu, sq, 1);
    sum += __shfl_xor_sync(0xffffffffu, sum, 2); sq += __shfl_xor_sync(0xffffffffu, sq, 2);
    const float mean = sum * (1.f / 448.f);
    const float var = fmaxf(fmaf(-mean, mean, sq * (1.f / 448.f)), 0.f);
    const float sc = rsqrtf(var + 1e-5f);
    LnCoef r;
    r.hi = pack2(sc, sc);
    const float lo = sc - bf_lo(r.hi), sh = -mean * sc;
    r.lo = pack2(lo, lo);
    r.sh = pack2(sh, sh);
    return r;
}
template <int B>
__device__ __forceinline__ void normalize(uint32_t (&A)[8][14], const LnCoef& c0, const LnCoef& c1) {
#pragma unroll
    for (int s = 2 * B; s < 2 * B + 2; s++)
#pragma unroll
        for (int i = 0; i < 14; i++) {
            const LnCoef& k = (i & 1) ? c1 : c0;
            asm("{ .reg .b32 t; fma.rn.bf16x2 t, %0, %2, %3; fma.rn.bf16x2 %0, %0, %1, t; }" : "+r"(A[s][i]) : "r"(k.hi), "r"(k.lo), "r"(k.sh));
        }
}
__device__ __forceinline__ void slice_stats(const uint32_t* w, float* st) {
    float a = 0.f, b = 0.f, p = 0.f, q = 0.f;
#pragma unroll
    for (int i = 0; i < 7; i++) {
        const float e0 = bf_lo(w[2 * i]), e1 = bf_hi(w[2 * i]), e2 = bf_lo(w[2 * i + 1]), e3 = bf_hi(w[2 * i + 1]);
        a += e0 + e1; b += e2 + e3;
        p = fmaf(e0, e0, p); p = fmaf(e1, e1, p); q = fmaf(e2, e2, q); q = fmaf(e3, e3, q);
    }
    a += __shfl_xor_sync(0xffffffffu, a, 1); p += __shfl_xor_sync(0xffffffffu, p, 1); b += __shfl_xor_sync(0xffffffffu, b, 1); q += __shfl_xor_sync(0xffffffffu, q, 1);
    a += __shfl_xor_sync(0xffffffffu, a, 2); p += __shfl_xor_sync(0xffffffffu, p, 2); b += __shfl_xor_sync(0xffffffffu, b, 2); q += __shfl_xor_sync(0xffffffffu, q, 2);
    st[0] = a; st[1] = p; st[2] = b; st[3] = q;
}
__device__ __forceinline__ void dual_softmax(const float* p, uint32_t* out) {
    constexpr float L = 1.4426950408889634f;
#pragma unroll
    for (int r = 0; r < 2; r++) {
        float mx = fmaxf(p[2 * r], p[2 * r + 1]), mn = fminf(p[2 * r], p[2 * r + 1]);
#pragma unroll
        for (int i = 1; i < 7; i++) {
            mx = fmaxf(mx, fmaxf(p[4 * i + 2 * r], p[4 * i + 2 * r + 1]));
            mn = fminf(mn, fminf(p[4 * i + 2 * r], p[4 * i + 2 * r + 1]));
        }
        mx = fmaxf(mx, __shfl_xor_sync(0xffffffffu, mx, 1));
        mn = fminf(mn, __shfl_xor_sync(0xffffffffu, mn, 1));
        const float bx = -mx * L, bn = mn * L;
        float ep[14], en[14], sp = 0.f, sn = 0.f;
#pragma unroll
        for (int i = 0; i < 14; i++) {
            const float v = p[4 * (i >> 1) + 2 * r + (i & 1)];
            ep[i] = ex2(fmaf(v, L, bx));
            en[i] = ex2(fmaf(v, -L, bn));
            sp += ep[i]; sn += en[i];
        }
        sp += __shfl_xor_sync(0xffffffffu, sp, 1);
        sn += __shfl_xor_sync(0xffffffffu, sn, 1);
        const float ip = rcp(sp), in = rcp(sn);
#pragma unroll
        for (int i = 0; i < 7; i++) {
            out[4 * i + r] = pack2(ep[2 * i] * ip, ep[2 * i + 1] * ip);
            out[4 * i + 2 + r] = pack2(en[2 * i] * in, en[2 * i + 1] * in);
        }
    }
}
__device__ __forceinline__ float geglu(float g, float u) {
    const float t = tanh_hw(g * fmaf(g * g, 0.7978845608028654f * 0.044715f, 0.7978845608028654f));
    const float gu = g * u;
    return fmaf(t, gu, gu);
}
__device__ __forceinline__ void phi_gemm(const float* t, float* p) {
    uint32_t w[14];
#pragma unroll
    for (int i = 0; i < 14; i++) w[i] = pack2(t[2 * i], t[2 * i + 1]);
    const uint64_t db = BASE128(OFF_WPHI, 16, 0);
    wg_fence();
    mma_rs56<0, 0>(p, w[0], w[1], w[2], w[3], 0, db);
    mma_rs56<0, 2>(p, w[4], w[5], w[6], w[7], 1, db);
    mma_rs56<0, 4>(p, w[8], w[9], w[10], w[11], 1, db);
    mma_rs56<0, 6>(p, w[12], w[13], 0u, 0u, 1, db);
    wg_commit();
    wg_wait<0>();
}

}

#define BAR(i) (bars + 8 * (i))
#define R_WAIT() mbar_wait(BAR(slot), ph)
#define WSUM(i)
#define R_ADJ (slot * (STAGE >> 4))
#define R_NEXT() do { eb2 = eb1; eb1 = BAR(B_EMPTY + slot); if (++slot == NST) { slot = 0; ph ^= 1; } } while (0)
#define R_RELEASE(k) do { if (lane == 0) mbar_arrive((k) == 1 ? eb1 : eb2); } while (0)
#define PUSH_BEGIN() do { mbar_wait(BAR(B_ACK + wgi), ackph); ackph ^= 1; } while (0)
#define PUSH_ACK() do { __syncwarp(); if (lane == 0) asm volatile("mbarrier.arrive.shared::cluster.b64 _, [%0];" ::"r"(mapa(BAR(B_ACK + wgi), hr ^ 1)) : "memory"); } while (0)

__global__ void __cluster_dims__(2, 1, 1) __launch_bounds__(384, 1)
fused_kernel(Scratch* const sc, const __nv_bfloat16* __restrict__ x_in, const __nv_bfloat16* __restrict__ w_phi, const int trips,
             const __nv_bfloat16* __restrict__ wg, const __nv_bfloat16* __restrict__ wu, const __nv_bfloat16* __restrict__ wd,
             const __grid_constant__ Maps maps) {
    extern __shared__ __align__(1024) unsigned char smem_raw[];
    const uint32_t sb = s2u(smem_raw);
    const uint32_t bars = sb + OFF_BAR;
    const int wgi = __shfl_sync(0xffffffffu, threadIdx.x >> 7, 0);
    const int hr = blockIdx.x & 1, ck = blockIdx.x >> 1;
    const int gp = (ck - 4) & 7, q7 = ((ck - 36) * 37) >> 8;
    const int pr = __shfl_sync(0xffffffffu, ck < 4 ? ck : (ck < 36 ? (ck - 4) >> 3 : q7), 0);
    const int tile = __shfl_sync(0xffffffffu, ck < 4 ? 0 : (ck < 36 ? (gp ? 2 * gp : 1) : 2 * (ck - 36 - 7 * q7) + 3), 0);
    const int sl = 2 * pr + hr;
    STAMP(0);
    GSTAMP(60);
    if (threadIdx.x == 256) {
#pragma unroll
        for (int i = 0; i < NST; i++) mbar_init(BAR(i), 1);
        asm volatile("fence.mbarrier_init.release.cluster;" ::: "memory");
    }
    if (threadIdx.x == 288) {
        if ((sb & 0x3FFFF) != SB0) asm volatile("trap;");
#pragma unroll
        for (int i = NST; i < B_COUNT; i++) mbar_init(BAR(i), i >= B_ACK ? 4 : (i < B_RECV || i == B_LATE ? 8 : 1));
        asm volatile("fence.mbarrier_init.release.cluster;" ::: "memory");
    }
    __syncwarp();
    asm volatile("barrier.cluster.arrive.relaxed.aligned;" ::: "memory");

    if (wgi == 2) {
        asm volatile("setmaxnreg.dec.sync.aligned.u32 40;");
        const int t128 = fresh_tid() & 127, w = __shfl_sync(0xffffffffu, t128 >> 5, 0), lane = t128 & 31;
        uint32_t e0[2] = {0, 0}, e1[2] = {0, 0}, cw_target = 0;
        if (w == 0) {
#pragma unroll 1
            for (int n = 0; n < NST; n++) {
                const uint32_t dst = sb + n * STAGE, fb = BAR(n);
                asm volatile(ELECT "mbarrier.arrive.expect_tx.shared::cta.b64 _, [%0], %1; }" ::"r"(fb), "r"(n < 2 ? 2 * STAGE : STAGE) : "memory");
                if (n < 2) {
                    tma3x(sb + OFF_H + n * STAGE, &maps.x, tile * 128 + n * 64, fb);
                    tma3x(dst, &maps.x, tile * 128 + n * 64 + 32, fb);
                } else {
                    if (n == 3) mbar_wait(BAR(1), 0);
                    const int ra = 112 * (n - 2);
                    tma2d(dst, &maps.qkv, 448 + 56 * sl, ra, fb);
                    tma2d(dst + HALF, &maps.qkv, 896 + 56 * sl, ra, fb);
                }
            }
            asm volatile("barrier.cluster.wait.aligned;" ::: "memory");
            cw_target = (ld_word(g_cw + sl * 32) & ~15u) + 16;
#pragma unroll 1
            for (int k = 0; k < 2; k++) {
                const int n = t128 + 32 * k;
                int m = n - 2 - (n > PACK);
                const bool packed = m >= 30 ? (m < 38 || m >= 52) : m >= 22;
                if (m >= 30) m -= 30;
                if (n == PACK) m = tile < 8 ? tile : tile + 14;
                const int rot = n < 8 ? 0 : pr;
                const int ra = 112 * kblk(rot, m & 3), rb = 112 * kblk(rot, 2 * m & 3), rc = 112 * kblk(rot, (2 * m + 1) & 3);
                int kind = 0, m0, m1, c0, c1, r0, r1;
                if (m < 4) { m0 = m1 = 1; c0 = 448 + 56 * sl; c1 = c0 + 448; r0 = r1 = ra; }
                else if (m < 8) { m0 = m1 = m < 6 ? 1 : 2; c0 = c1 = 56 * sl; r0 = rb; r1 = rc; }
                else if (m < 20) { m0 = 3; m1 = 4; c0 = c1 = 224 * sl + 32 * hr + 64 * ((m - 8) >> 2); r0 = r1 = ra; }
                else if (m < 22) { kind = 2; m0 = 5; m1 = 6; c0 = c1 = 224 * sl + (hr ? 0 : 192); r0 = rb; r1 = rc; }
                else { m0 = m1 = 7; c0 = c1 = 56 * (2 * ((pr + (m >> 1) - 10) & 3) + hr); r0 = 224 * (sl ^ (m & 1)); r1 = r0 + 112; }
                if (packed) { kind = 1; r0 = sl * 16 + (m < 8 ? m : m - 14); r1 = 0; }
                e0[0] = e0[1]; e1[0] = e1[1];
                e0[1] = kind | (m0 << 2) | (m1 << 6) | (c0 << 10) | (c1 << 21);
                e1[1] = r0 | (r1 << 16);
            }
        } else {
            const int j = t128 - 32;
            asm volatile("barrier.cluster.wait.aligned;" ::: "memory");
            uint2 wv[7];
            const int k = j < 56 ? j : 55, hh = k >= 28;
#pragma unroll
            for (int i = 0; i < 7; i++) wv[i] = __ldg(reinterpret_cast<const uint2*>(w_phi + (sl * 56 + k) * 28) + i);
#pragma unroll 1
            for (int i = j; i < 7168 / 16; i += 96) sts4(sb + OFF_WPHI + i * 16, 0, 0, 0, 0);
            bar_sync(5, 96);
            if (j < 56) {
                uint32_t a4[4];
#pragma unroll
                for (int q = 0; q < 4; q++) a4[q] = sb + OFF_WPHI + (4 * hh + q) * 128 + ((((k >> 3) ^ (4 * hh + q)) & 7) << 4) + (k & 7) * 2;
                FOR14(const uint32_t v = (t & 1) ? wv[t >> 1].y : wv[t >> 1].x;
                      asm volatile("{ .reg .b16 l, h; mov.b32 {l, h}, %2; st.shared.u16 [%0+%3], l; st.shared.u16 [%1+%3], h; }"
                                   ::"r"(a4[t >= 7 ? 2 : 0]), "r"(a4[t >= 7 ? 3 : 1]), "r"(v), "n"((t % 7) * 1024) : "memory"));
            }
            __syncwarp();
            fence_async();
            bar_arrive(1, 224);
            bar_arrive(9, 224);
            if (w == 1 && PFP < 2) {
                mbar_wait(BAR(2), 0);
                if (PFP == 0) mbar_wait(BAR(2), 1);
                if (PFP == 1) mbar_wait(BAR(4), 0);
                const int b = blockIdx.x;
                asm volatile(ELECT "cp.async.bulk.prefetch.L2.global [%0], %1; }" ::"l"(wg + b * 6272), "r"(12544) : "memory");
                asm volatile(ELECT "cp.async.bulk.prefetch.L2.global [%0], %1; }" ::"l"(wu + b * 6272), "r"(12544) : "memory");
                asm volatile(ELECT "cp.async.bulk.prefetch.L2.global [%0], %1; }" ::"l"(wd + b * 6272), "r"(12544) : "memory");
            }
        }
        uint32_t kseq = ld_word(g_c1 + (sl * 8 * 16 + tile) * 32);
        int slot = 0, ph = 0, n = NST;
#pragma unroll 1
        for (int layer = 0; layer < 3; layer++) {
            if (w == 0) {
                const int nend = layer == 0 ? 11 : (layer == 1 ? 42 : 63);
#pragma unroll 1
                for (; n < nend; n++) {
                const uint32_t w0 = __shfl_sync(0xffffffffu, n < 32 ? e0[0] : e0[1], n & 31), w1 = __shfl_sync(0xffffffffu, n < 32 ? e1[0] : e1[1], n & 31);
                const uint32_t dst = sb + slot * STAGE, fb = BAR(n == PACK ? B_PACK : slot);
                const CUtensorMap* m0 = &maps.x + ((w0 >> 2) & 15);
                const CUtensorMap* m1 = &maps.x + ((w0 >> 6) & 15);
                const int c0 = (w0 >> 10) & 2047, c1 = w0 >> 21, r0 = w1 & 0xffff, r1 = w1 >> 16;
                if (n == 25) {
                    int it = 0;
                    uint32_t v;
                    do { asm volatile("ld.acquire.gpu.global.u32 %0, [%1];" : "=r"(v) : "l"(g_cw + sl * 32) : "memory"); } while ((int)(v - cw_target) < 0 && ++it < 0x400000);
                    asm volatile("fence.proxy.async.global;" ::: "memory");
                    __syncwarp();
                }
                mbar_wait(BAR(B_EMPTY + slot), ph);
                __syncwarp();
                asm volatile(ELECT "mbarrier.arrive.expect_tx.shared::cta.b64 _, [%0], %1; }" ::"r"(fb), "r"(STAGE) : "memory");
                if ((w0 & 3) == 0) {
                    tma2d(dst, m0, c0, r0, fb);
                    tma2d(dst + HALF, m1, c1, r1, fb);
                } else if (w0 & 1) {
                    asm volatile(ELECT "cp.async.bulk.shared::cluster.global.mbarrier::complete_tx::bytes [%0], [%1], %2, [%3]; }"
                                 ::"r"(dst), "l"(reinterpret_cast<const char*>(g_wp) + (size_t)r0 * STAGE), "r"(STAGE), "r"(fb) : "memory");
                } else {
                    tma2d(dst, m0, c0, r0, fb); tma2d(dst + 7168, m0, c0, r1, fb);
                    tma2d(dst + HALF, m1, c0, r0, fb); tma2d(dst + HALF + 7168, m1, c0, r1, fb);
                }
                if (n == PACK) asm volatile(ELECT "mbarrier.arrive.shared::cta.b64 _, [%0]; }" ::"r"(BAR(slot)) : "memory");
                if (++slot == NST) { slot = 0; ph ^= 1; }
                }
            } else if (w == 1 && layer == 1) {
                if (PFP == 2) {
                const int b = blockIdx.x;
                asm volatile(ELECT "cp.async.bulk.prefetch.L2.global [%0], %1; }" ::"l"(wg + b * 6272), "r"(12544) : "memory");
                asm volatile(ELECT "cp.async.bulk.prefetch.L2.global [%0], %1; }" ::"l"(wu + b * 6272), "r"(12544) : "memory");
                asm volatile(ELECT "cp.async.bulk.prefetch.L2.global [%0], %1; }" ::"l"(wd + b * 6272), "r"(12544) : "memory");
                }
                constexpr int ps = PACK % NST;
                mbar_wait(BAR(B_PACK), 0);
                asm volatile("{ .reg .pred e; elect.sync _|e, 0xffffffff;\n"
                             "@e cp.async.bulk.global.shared::cta.bulk_group [%0], [%1], %2;\n"
                             "@e cp.async.bulk.commit_group;\n"
                             "@e cp.async.bulk.wait_group.read 0;\n"
                             "@e mbarrier.arrive.shared::cta.b64 _, [%3], 8;\n"
                             "@e cp.async.bulk.wait_group 0;\n"
                             "@e fence.proxy.async.global;\n"
                             "@e red.release.gpu.global.add.u32 [%4], 1; }"
                             ::"l"(reinterpret_cast<char*>(g_wp) + (size_t)(sl * 16 + tile) * STAGE), "r"(sb + ps * STAGE), "r"(STAGE), "r"(BAR(B_EMPTY + ps)), "l"(g_cw + sl * 32) : "memory");
                __syncwarp();
            }
            if (layer < 2) {
            const uint32_t tag = layer ^ 1;
            kseq++;
            bar_sync(7, 384);
            ASTAMP(0);
            if (tile < 15) {
                const int sq = lane >> 3, pk = 8 * w + (lane & (tile == 14 ? 3 : 7));
                uint32_t v[16];
                if (layer == 0) poll_cnt(g_c1 + ((sl * 8 + (w >> 1) * 4 + (tile >> 2)) * 16 + (lane & 15)) * 32, kseq);
                ASTAMP(1);
                poll4_kv<32>(v, g_kv1 + ((sl * 16 + tile) * 16 + 4 * sq) * 32 + pk, tag);
#pragma unroll
                for (int k = 0; k < 4; k++) {
                    float lo = (bf_lo(v[k]) + bf_lo(v[4 + k])) + (bf_lo(v[8 + k]) + bf_lo(v[12 + k]));
                    float hi = (bf_hi(v[k]) + bf_hi(v[4 + k])) + (bf_hi(v[8 + k]) + bf_hi(v[12 + k]));
                    lo += __shfl_xor_sync(0xffffffffu, lo, 8); hi += __shfl_xor_sync(0xffffffffu, hi, 8);
                    lo += __shfl_xor_sync(0xffffffffu, lo, 16); hi += __shfl_xor_sync(0xffffffffu, hi, 16);
                    v[k] = pack2(lo, hi);
                }
                if (sq == 0) st_pkt<0>(g_kv2 + sl * 512 + 32 * tile + pk, settag(v[0], tag), v[1], v[2], v[3]);
            }
            ASTAMP(2);
            {
                const int item = t128 < 112 ? t128 : 112 + (t128 & 3), d = item >> 1;
                const int cc = t128 < 112 ? 2 * (d >= 28) + (item & 1) : item - 112;
                const int r = t128 < 112 ? d : 56 + (cc >> 1) + 2 * ((t128 - 112) >> 2);
                uint32_t ra = sb + OFF_KVB + r * 128 + 4 * cc, rx = (r & 7) << 4;
                asm volatile("" : "+r"(ra), "+r"(rx));
                FOR14(asm volatile("st.shared.u32 [%0+%2], %1;" ::"r"((ra ^ 8) + (((t & 7) << 4) ^ rx)), "r"(0), "n"((t >> 3) * 8192) : "memory"));
                uint32_t v[16];
                asm volatile("" : "+r"(ra), "+r"(rx));
                poll4_kv<8>(v, g_kv2 + sl * 512 + (item >> 3) * 32 + (item & 7), tag);
                FOR14(asm volatile("st.shared.u32 [%0+%2], %1;" ::"r"(ra + (((t & 7) << 4) ^ rx)), "r"(v[t < 7 ? t : t + 1]), "n"((t >> 3) * 8192) : "memory"));
                fence_async();
            }
            bar_arrive(3, 384);
            ASTAMP(3);
            }
        }
    } else {
        asm volatile("setmaxnreg.inc.sync.aligned.u32 232;");
        int lane = fresh_tid() & 31, prf = pr;
#define pr prf
#define g (lane >> 2)
#define c (lane & 3)
#define t128 (w * 32 + lane)
        const int wu = __shfl_sync(0xffffffffu, fresh_tid() >> 5, 0), w = wu & 3;
        const uint32_t xoff = __shfl_sync(0xffffffffu, (3 * PLANE + ((tile * 2 + wgi) * 8) * 512 + w * 128) * 16, 0);
        char* xu = reinterpret_cast<char*>(g_ex) + xoff;
#define FRESH() asm volatile("" : "+l"(xu), "+r"(lane), "+r"(prf))
#define xp0 (reinterpret_cast<uint4*>(xu) + lane)
        const uint32_t hbuf = sb + OFF_H + wgi * STAGE;
        uint32_t slot = 0, ph = 0, eb1 = 0, eb2 = 0, ackph = 0, rcvph = 0, gatph = 0, swp = 0;
        uint32_t ppid = 6;
#define cx(s) (reinterpret_cast<uint32_t*>(reinterpret_cast<uint4*>(xu) + PL(1) + 112 + (s) * 512))
#define stp (reinterpret_cast<uint4*>(xu) + g + PL(0) + 112)
        uint32_t seq = ld_word(cx(sl));
        uint32_t kseq = ld_word(g_c1 + ((sl * 8 + wu) * 16 + tile) * 32);
        uint32_t stag = ld_word(reinterpret_cast<const uint32_t*>(stp + sl * 512) + 3) & 1;
        asm volatile("barrier.cluster.wait.aligned;" ::: "memory");
        STAMP(1);
        uint32_t X[14];
        const uint32_t x0row = (w < 2 ? hbuf : sb + wgi * STAGE) + ((w & 1) * 16 + (lane & 15)) * 128;
        mbar_wait(BAR(wgi), 0);
        STAMP(51);
#pragma unroll
        for (int j = 0; j < 4; j++) {
            const int G = 7 * sl + min(2 * j + (lane >> 4), 6);
            uint32_t q2, q3;
            asm volatile("ldmatrix.sync.aligned.m8n8.x4.shared.b16 {%0,%1,%2,%3}, [%4];" : "=r"(X[4 * j]), "=r"(X[4 * j + 1]), "=r"(q2), "=r"(q3)
                         : "r"(x0row + (G >> 3) * 4096 + (((G ^ lane) & 7) << 4)) : "memory");
            if (j < 3) { X[(4 * j + 2) % 14] = q2; X[(4 * j + 3) % 14] = q3; }
        }
#define PUSH_SLICE(W)                                                                          \
    {                                                                                          \
        if (t128 == 0) mbar_expect_tx(BAR(B_RECV + wgi), 7168);                                \
        PUSH_BEGIN();                                                                          \
        const uint32_t ra = mapa(hbuf + 24576 + t128 * 16, hr ^ 1), rb = mapa(sb + OFF_XR + wgi * 3072, hr ^ 1), rbar = mapa(BAR(B_RECV + wgi), hr ^ 1); \
        st_async4(ra, W[0], W[1], W[2], W[3], rbar);                                           \
        st_async4(ra + 2048, W[4], W[5], W[6], W[7], rbar);                                    \
        st_async4(rb + t128 * 16, W[8], W[9], W[10], W[11], rbar);                             \
        asm volatile("st.async.weak.shared::cluster.mbarrier::complete_tx::bytes.v2.b32 [%0], {%1,%2}, [%3];" ::"r"(rb + 2048 + t128 * 8), "r"(W[12]), "r"(W[13]), "r"(rbar) : "memory"); \
    }
#define PULL_SLICE(W)                                                                          \
    {                                                                                          \
        uint32_t t0, t1;                                                                       \
        mbar_wait(BAR(B_RECV + wgi), rcvph);                                                   \
        rcvph ^= 1;                                                                            \
        lds4(&A[1][0], hbuf + 24576 + t128 * 16);                                              \
        lds4(&A[1][4], hbuf + 26624 + t128 * 16);                                              \
        lds4(&A[1][8], sb + OFF_XR + wgi * 3072 + t128 * 16);                                  \
        asm volatile("ld.shared.v2.u32 {%0,%1}, [%2];" : "=r"(t0), "=r"(t1) : "r"(sb + OFF_XR + wgi * 3072 + 2048 + t128 * 8) : "memory"); \
        _Pragma("unroll") for (int i = 0; i < 12; i++) A[0][i] = (i & 3) ? W[i] : W[i] & ~1u;  \
        A[1][0] &= ~1u; A[1][4] &= ~1u; A[1][8] &= ~1u;                                        \
        A[0][12] = (hr ? t0 : W[12]) & ~1u; A[0][13] = hr ? t1 : W[13];                        \
        A[1][12] = (hr ? W[12] : t0) & ~1u; A[1][13] = hr ? W[13] : t1;                        \
        asm volatile("" : RW4(A[0], 0), RW4(A[0], 4), RW4(A[0], 8), RW2(A[0], 12), RW4(A[1], 0), RW4(A[1], 4), RW4(A[1], 8), RW2(A[1], 12)); \
        swp = hr * 448;                                                                        \
    }
#define SWB(b, t, db, sh) ((b) == 0 && (t) < 6 ? ((t) < 3 ? db##p : db##m) : db)
#define DECL_DB(b, MK, lbo, sh) const uint64_t db = MK(0, lbo, R_ADJ), dbp = (b) == 0 ? MK(0, lbo, R_ADJ + (swp >> (sh))) : db, dbm = (b) == 0 ? MK(0, lbo, R_ADJ - (swp >> (sh))) : db;
#define PPB 2
#define PP_WAIT() if (wgi == 1) { bar_sync(ppid, 256); ppid ^= 14; }
#define PP_GO() if (wgi == 0) { bar_arrive(ppid, 256); ppid ^= 14; }
#define GAT_DST(B, s2) ((B) == 1 ? hbuf + w * 3584 + (s2) * 1792 : ((s2) ? sb + OFF_KVB + wgi * 8192 : hbuf + 14336) + w * 1792)
#define GAT_ISSUE(B, base)                                                                     \
    {                                                                                          \
        const char* gs = xu + ((base) + kblk(pr, B) * 1024) * 16;                              \
        asm volatile("{ .reg .pred e; elect.sync _|e, 0xffffffff;\n"                           \
                     "@e mbarrier.arrive.expect_tx.shared::cta.b64 _, [%3], 3584;\n"           \
                     "@e cp.async.bulk.shared::cluster.global.mbarrier::complete_tx::bytes [%0], [%2], 1792, [%3];\n" \
                     "@e cp.async.bulk.shared::cluster.global.mbarrier::complete_tx::bytes [%1], [%2+8192], 1792, [%3]; }" \
                     ::"r"(GAT_DST(B, 0)), "r"(GAT_DST(B, 1)), "l"(gs), "r"(BAR(B_GAT + wu * 2 + ((B) >> 1))) : "memory"); \
        __syncwarp();                                                                          \
    }
#define GAT_FETCH(B)                                                                           \
    {                                                                                          \
        mbar_wait(BAR(B_GAT + wu * 2 + ((B) >> 1)), (gatph >> (B)) & 1);                          \
        gatph ^= 1 << (B);                                                                     \
        _Pragma("unroll") for (int s2 = 0; s2 < 2; s2++) {                                     \
            const uint32_t ga = GAT_DST(B, s2) + lane * 16;                                    \
            lds4(&A[2 * (B) + s2][0], ga); lds4(&A[2 * (B) + s2][4], ga + 512); lds4(&A[2 * (B) + s2][8], ga + 1024); \
            asm volatile("ld.shared.v2.u32 {%0,%1}, [%2];" : "=r"(A[2 * (B) + s2][12]), "=r"(A[2 * (B) + s2][13]) : "r"(ga - lane * 8 + 1536) : "memory"); \
        }                                                                                      \
    }
#define LATE_ARRIVE() do { if (lane == 0) mbar_arrive(BAR(B_LATE)); } while (0)
#define LATE_WAIT() do { mbar_wait(BAR(B_LATE), gatph & 1); gatph ^= 1; } while (0)
#define PT 3
#define PREP(b, t, remote)                                                                     \
    if constexpr ((b) < 3 && (t) == PT) {                                                      \
        wg_commit();                                                                           \
        STAMP(74 + 6 * (step & 1) + 2 * (b));                                                  \
        if (remote) {                                                                          \
            if constexpr ((b) == 0) { blk_load<2>(A, BLK(xsrc, 2), lane); GAT_FETCH(1) }       \
            blk_check<((b) + 1) & 3>(A, BLK(xsrc, (b) + 1), lane, xtag);                       \
            if constexpr ((b) == 0) blk_load<3>(A, BLK(xsrc, 3), lane);                        \
        }                                                                                      \
        STAMP(75 + 6 * (step & 1) + 2 * (b));                                                  \
        normalize<((b) + 1) & 3>(A, k0, k1);                                                   \
        asm volatile("" : RW4(A[(2 * (b) + 2) & 7], 0), RW4(A[(2 * (b) + 2) & 7], 4), RW4(A[(2 * (b) + 2) & 7], 8), RW2(A[(2 * (b) + 2) & 7], 12), \
                          RW4(A[(2 * (b) + 3) & 7], 0), RW4(A[(2 * (b) + 3) & 7], 4), RW4(A[(2 * (b) + 3) & 7], 8), RW2(A[(2 * (b) + 3) & 7], 12)); \
        wg_fence();                                                                            \
    }
#define X0_BLOCK(b)                                                                            \
    { const int rr = lane & 7, hi = lane >> 4;                                                 \
    const uint32_t rowa = (w < 2 ? hbuf : sb + wgi * STAGE) + ((w & 1) * 16 + (lane & 15)) * 128; \
    FOR7(constexpr int G = 14 * (b) + (t < 3 ? 2 * t : (t < 6 ? 2 * t + 1 : 6));               \
         uint32_t q0, q1, q2, q3;                                                              \
         const uint32_t ad = t < 6 ? rowa + (((((G & 7) + hi) ^ rr) & 7) << 4) + ((G & 7) == 7 ? hi * 4096 : 0) : rowa + ((G + 7 * hi) >> 3) * 4096 + ((((G + 7 * hi) ^ rr) & 7) << 4); \
         asm volatile("ldmatrix.sync.aligned.m8n8.x4.shared.b16 {%0,%1,%2,%3}, [%4+%5];" : "=r"(q0), "=r"(q1), "=r"(q2), "=r"(q3) \
                      : "r"(ad), "n"(t < 6 ? (G >> 3) * 4096 : 0) : "memory");                 \
         if (t < 3) { A[2 * (b)][4 * t] = q0; A[2 * (b)][4 * t + 1] = q1; A[2 * (b)][4 * t + 2] = q2; A[2 * (b)][4 * t + 3] = q3; } \
         else if (t < 6) { A[2 * (b) + 1][(4 * t - 12) & 15] = q0; A[2 * (b) + 1][((4 * t - 12) & 15) + 1] = q1; A[2 * (b) + 1][((4 * t - 12) & 15) + 2] = q2; A[2 * (b) + 1][((4 * t - 12) & 15) + 3] = q3; } \
         else { A[2 * (b)][12] = q0; A[2 * (b)][13] = q1; A[2 * (b) + 1][12] = q2; A[2 * (b) + 1][13] = q3; }); }
#define BLK(base, b) ((base) + kblk(pr, b) * 1024)

#pragma unroll 1
        for (int step = 0; step < 4; step++) {
            FRESH();
            const uint32_t tag = (step >> 1) ^ 1;
            const int so = (step >> 1) * 24 + (step & 1) * 12;
            (void)so;
            uint32_t A[8][14];
            uint4* const xsrc = xp0 + ((step & 1) ? PL(2) : PL(0));
            const uint32_t xtag = (step & 1) ? tag : ((seq >> 3) & 1) ^ 1;
            uint32_t xbits;
            {
                float st[4];
                slice_stats(X, st);
                stag ^= 1;
                xbits = x_bits(X);
                tag_slice(X, xtag);
                if (step) send_slice<0>(xsrc + sl * 512, lane, X);
                if (c == 0) st_pkt<0>(stp + sl * 512, __float_as_uint(st[0]), __float_as_uint(st[1]), __float_as_uint(st[2]), settag(__float_as_uint(st[3]), stag));
            }
            STAMP(2 + so);
            uint32_t sv[8];
            if (step == 0) {
                X0_BLOCK(0) X0_BLOCK(1) X0_BLOCK(2) X0_BLOCK(3)
                mbar_wait(BAR(wgi ^ 1), 0);
                R_NEXT();
                R_NEXT();
                R_RELEASE(2);
                stat_load(sv, stp + c * 1024);
                stat_check(sv, stp + c * 1024, stag);
                STAMP(52 + step);
            } else {
                kill<14>(A[2]); kill<14>(A[3]); kill<14>(A[4]); kill<14>(A[5]); kill<14>(A[6]); kill<14>(A[7]);
                PUSH_SLICE(X)
                stat_load(sv, stp + c * 1024);
                PULL_SLICE(X)
                stat_check(sv, stp + c * 1024, stag);
                STAMP(52 + step);
                GAT_ISSUE(1, (step & 1) ? PL(2) : PL(0))
            }
            LnCoef k0, k1;
            {
                k0 = ln_coef(__uint_as_float(sv[0]) + __uint_as_float(sv[4]), __uint_as_float(sv[1]) + __uint_as_float(sv[5]));
                k1 = ln_coef(__uint_as_float(sv[2]) + __uint_as_float(sv[6]), __uint_as_float(sv[3] & ~1u) + __uint_as_float(sv[7] & ~1u));
            }
            STAMP(3 + so);
            GSTAMP(70 + step);

            if ((step & 1) == 0) {
                float tq[28];
                {
                    float av[28];
#define KV_BLOCK(b)                                                                           \
    if ((b) == 1) R_RELEASE(2);                                                               \
    if ((b) == 2) { PUSH_ACK(); wg_wait<2>(); R_RELEASE(2); }                                 \
    R_WAIT();                                                                                 \
    if ((b) == PPK) { PP_WAIT() }                                                             \
    { DECL_DB(b, BASE128, 16, 0)                                                              \
    wg_fence();                                                                               \
    FOR7(mma_rs56<1, D128(0, t)>(tq, AQ(A, b, t), (b) + t > 0, SWB(b, t, db, 0));             \
         mma_rs56<1, D128(HALF, t)>(av, AQ(A, b, t), (b) + t > 0, SWB(b, t, db, 0));          \
         PREP(b, t, step)); }                                                                 \
    wg_commit();                                                                              \
    if ((b) == 3 && PPK < 4) { PP_GO() }                                                      \
    R_NEXT();
                    normalize<0>(A, k0, k1);
                    KV_BLOCK(0) KV_BLOCK(1) KV_BLOCK(2) KV_BLOCK(3)
                    wg_wait<0>();
                    if (lane < 3) mbar_arrive(BAR(B_EMPTY + (slot + NST - 1 - lane) % NST));
                    STAMP(4 + so);
                    WSUM(80 + 7 * (step >> 1));
                    const int m = lane >> 3, rr = lane & 7;
                    const uint32_t rowa = hbuf + 16384 + (w * 16 + rr + 8 * (m & 1)) * 128;
                    const uint32_t one = c == 0 ? 0x00003f80u : 0u;
                    if (step == 0) { bar_sync(wgi ? 9 : 1, 224); }
#pragma unroll
                    for (int j = 0; j < 4; j++) {
                        const uint32_t a = rowa + (((2 * j + (m >> 1)) ^ rr) << 4);
                        if (j < 3) stsm4(a, pack2(av[8 * j], av[8 * j + 1]), pack2(av[8 * j + 2], av[8 * j + 3]), pack2(av[8 * j + 4], av[8 * j + 5]), pack2(av[8 * j + 6], av[8 * j + 7]));
                        else stsm4(a, pack2(av[24], av[25]), pack2(av[26], av[27]), one, one);
                    }
                }
                uint32_t PH[28];
                int it = 1;
#pragma unroll 1
                do {
                    float pp[28];
                    phi_gemm(tq, pp);
                    dual_softmax(pp, PH);
                    if (((trips >> (it + 1)) & 1) == 0) continue;
                    {
                        const int m = lane >> 3, rr = lane & 7;
                        const uint32_t rowa = hbuf + (w * 16 + rr + 8 * (m & 1)) * 128;
#pragma unroll
                        for (int j = 0; j < 7; j++) {
                            const int cg = 2 * j + (m >> 1), hi = cg >= 7;
                            stsm4(rowa + hi * 8192 + (((cg - 7 * hi) ^ rr) << 4), PH[4 * j], PH[4 * j + 1], PH[4 * j + 2], PH[4 * j + 3]);
                        }
                    }
                    fence_async();
                    STAMP(5 + so);
#define Q_STAGE(b0)                                                                           \
    R_WAIT();                                                                                 \
    { DECL_DB(b0, BASE128, 16, 0)                                                             \
    wg_fence();                                                                               \
    FOR7(mma_rs56<1, D128(0, t)>(tq, AQ(A, b0, t), (b0) + t > 0, SWB(b0, t, db, 0)));         \
    FOR7(mma_rs56<1, D128(HALF, t)>(tq, AQ(A, (b0) + 1, t), 1, db)); }                        \
    wg_commit();                                                                              \
    R_NEXT();
                    if (QE && wgi == 0) { kill<28>(tq); Q_STAGE(0) Q_STAGE(2) wg_wait<1>(); R_RELEASE(2); wg_wait<0>(); R_RELEASE(1); }
                    bar_sync(2, 256);
                    float kv[28];
                    const uint64_t da = BASE128(OFF_H + 16384, 16, 0), dbk = BASE128(OFF_H, 16, wgi * 512);
                    wg_fence();
                    FOR8(constexpr uint64_t o = ((t >> 2) * STAGE + (t & 3) * 2048) >> 4; mma_ss56_tt<o, o>(kv, t > 0, da, dbk));
                    wg_commit();
                    wg_wait<0>();
#pragma unroll
                    for (int hf = 0; hf < 2; hf++) {
                        const int d = 16 * w + g + 8 * hf;
                        if ((d < 56 && (d >= 28) == (c >= 2)) || d == 56) {
                            const int item = d < 56 ? 2 * d + (c & 1) : 112 + c;
                            uint4* dst = g_kv1 + ((sl * 16 + (item >> 3)) * 16 + tile) * 32 + wgi * 16 + (item & 7);
#define KVW(i) pack2(kv[4 * (i) + 2 * hf], kv[4 * (i) + 2 * hf + 1])
                            st_pkt<0>(dst, settag(KVW(0), tag), KVW(1), KVW(2), KVW(3));
                            st_pkt<8>(dst, settag(KVW(4), tag), KVW(5), KVW(6), 0u);
                        }
                    }
                    __syncwarp();
                    kseq++;
                    if (lane == 0) st_word(g_c1 + ((sl * 8 + wu) * 16 + tile) * 32, kseq);
                    bar_arrive(7, 384);
                    STAMP(6 + so);
                    if (!QE || wgi == 1) { kill<28>(tq); Q_STAGE(0) Q_STAGE(2) wg_wait<1>(); R_RELEASE(2); wg_wait<0>(); R_RELEASE(1); }
                    STAMP(7 + so);
                    kill<28>(PH);
                } while (((trips >> (++it)) & 1));
                STAMP(8 + so);
                FRESH();
                if (step) {
                    slice_load<PL(0)>(X, xp0 + sl * 512, lane);
                } else {
                    const uint32_t* xp = reinterpret_cast<const uint32_t*>(x_in + (size_t)(tile * 128 + wu * 16 + g) * 448 + 56 * sl + 2 * c);
#pragma unroll
                    for (int i = 0; i < 7; i++) { X[2 * i] = __ldg(xp + 4 * i); X[2 * i + 1] = __ldg(xp + 4 * i + 8 * 224); }
                }
                bar_sync(3, 384);
                STAMP(9 + so);
                const uint4* const osrc = xp0 + PL(1);
                {
                    float nm[32];
                    const uint64_t db = BASE128(OFF_KVB, 16, 0);
                    wg_fence();
                    FOR7(mma_rs64<0, ((t >> 2) * 8192 + (t & 3) * 32) / 16>(nm, PH[4 * t], PH[4 * t + 1], PH[4 * t + 2], PH[4 * t + 3], t > 0, db));
                    wg_commit();
                    wg_wait<0>();
                    LATE_ARRIVE();
                    const float i00 = rcp(nm[28] + 1e-6f), i01 = rcp(nm[29] + 1e-6f), i10 = rcp(nm[30] + 1e-6f), i11 = rcp(nm[31] + 1e-6f);
                    const float m0 = c >= 2 ? i01 : i00, m1 = c >= 2 ? i11 : i10;
                    uint32_t O[14];
#pragma unroll
                    for (int i = 0; i < 7; i++) {
                        const float f0 = i < 3 ? i00 : (i > 3 ? i01 : m0), f1 = i < 3 ? i10 : (i > 3 ? i11 : m1);
                        O[2 * i] = pack2(nm[4 * i] * f0, nm[4 * i + 1] * f0);
                        O[2 * i + 1] = pack2(nm[4 * i + 2] * f1, nm[4 * i + 3] * f1);
                    }
                    if (OST) { PP_WAIT() }
                    tag_slice(O, tag);
                    send_slice<PL(1)>(xp0 + sl * 512, lane, O);
                    seq++;
                    if (lane == 0) st_word(cx(sl), seq);
                    STAMP(10 + so);
                    PUSH_SLICE(O)
                    if (OST == 1) { PP_GO() }
                    const uint32_t cv = ld_word(cx(lane & 7));
                    PULL_SLICE(O)
                    LATE_WAIT();
                    check_cnt(cv, cx(lane & 7), seq);
                    if (OST == 2) { PP_GO() }
                    STAMP(56 + (step >> 1));
                    GAT_ISSUE(1, PL(1))
                    GAT_ISSUE(3, PL(1))
                    blk_load<2>(A, BLK(osrc, 2), lane);
                }
                float ao[28];
#define WO_BLOCK(b)                                                                           \
    if ((b) > 0) blk_check<b>(A, BLK(osrc, b), lane, tag);                                    \
    if (((b) & 1) == 0) R_WAIT();                                                             \
    { DECL_DB(b, BASE128, 16, 0)                                                              \
    wg_fence();                                                                               \
    FOR7(mma_rs56<1, D128(((b) & 1) * HALF, t)>(ao, AQ(A, b, t), (b) + t > 0, SWB(b, t, db, 0))); } \
    wg_commit();                                                                              \
    if ((b) & 1) R_NEXT();
                WO_BLOCK(0)
                STAMP(11 + so);
                GAT_FETCH(1)
                WO_BLOCK(1)
                WO_BLOCK(2)
                GAT_FETCH(3)
                WO_BLOCK(3)
                PUSH_ACK();
                wg_wait<0>();
                R_RELEASE(2);
                STAMP(12 + so);
                WSUM(86 + 7 * (step >> 1));
                x_fix(X, xbits);
#pragma unroll
                for (int i = 0; i < 14; i++) X[i] = pack2(bf_lo(X[i]) + ao[2 * i], bf_hi(X[i]) + ao[2 * i + 1]);
            } else {
                uint32_t H[56];
                float ag[64];
#define F1_EPI(dst, ng, ag)                                                                    \
    _Pragma("unroll") for (int i = 0; i < 2 * (ng); i++)                                       \
        (dst)[i] = pack2(geglu(ag[2 * i], ag[4 * (ng) + 2 * i]), geglu(ag[2 * i + 1], ag[4 * (ng) + 2 * i + 1]));
#define H_PUSH(h0, off) st_async4(rem_h + (off), H[h0], H[(h0) + 1], H[(h0) + 2], H[(h0) + 3], mapa(BAR(B_RECV2 + wgi), hr ^ 1));
#define F1_BLOCK(b, first)                                                                     \
    if ((first) && (b) == 1) R_RELEASE(2);                                                     \
    if ((first) && (b) == 2) PUSH_ACK();                                                       \
    R_WAIT();                                                                                  \
    if ((b) == ((first) ? PPF : PPB)) { PP_WAIT() }                                            \
    { DECL_DB(b, BASE128, HALF, 0)                                                             \
    wg_fence();                                                                                \
    FOR7(mma_rs128<1, D128(0, t)>(ag, AQ(A, b, t), (b) + t > 0, SWB(b, t, db, 0));             \
         if constexpr (first) { PREP(b, t, true) }); }                                         \
    wg_commit();                                                                               \
    if ((b) == 3) { PP_GO() }                                                                  \
    if ((b) > 0) { wg_wait<1>(); R_RELEASE(1); }       \
    R_NEXT();
                normalize<0>(A, k0, k1);
                F1_BLOCK(0, true) F1_BLOCK(1, true) F1_BLOCK(2, true) F1_BLOCK(3, true)
                if (t128 == 0) { mbar_expect_tx(BAR(B_RECV + wgi), 16384); mbar_expect_tx(BAR(B_RECV2 + wgi), 12288); }
                PUSH_BEGIN();
                wg_wait<0>();
                R_RELEASE(1);
                int p = 0;
#pragma unroll 1
                do {
                    F1_EPI(H + 32, 8, ag)
                    STAMP(4 + p + so);
                    WSUM(81 + p + 7 * (step >> 1));
                    if (((trips >> (p + 1)) & 1) == 0) continue;
                    if (step == 1 && p == PKP) R_NEXT();
                    kill<64>(ag);
                    F1_BLOCK(0, false)
                    {
                        const uint32_t pk = (p ? hbuf + 16384 : sb + OFF_KVB + wgi * 8192) + w * 2048;
#pragma unroll
                        for (int k = 0; k < 4; k++) sts4(pk + k * 512 + lane * 16, H[32 + 4 * k], H[33 + 4 * k], H[34 + 4 * k], H[35 + 4 * k]);
                        fence_async();
                        __syncwarp();
                        asm volatile(ELECT "cp.async.bulk.shared::cluster.shared::cta.mbarrier::complete_tx::bytes [%0], [%1], 2048, [%2]; }"
                                     ::"r"(mapa(hbuf + p * 8192 + w * 2048, hr ^ 1)), "r"(pk), "r"(mapa(BAR(B_RECV + wgi), hr ^ 1)) : "memory");
                    }
                    F1_BLOCK(1, false) F1_BLOCK(2, false) F1_BLOCK(3, false)
                    wg_wait<0>();
                    R_RELEASE(1);
                    kill<16>(H + 32);
                } while (((trips >> (++p)) & 1));
#pragma unroll
                for (int k = 0; k < 4; k++) lds4(H + 16 + 4 * k, hbuf + 16384 + w * 2048 + k * 512 + lane * 16);
                __syncwarp();
                if (lane == 0) asm volatile("mbarrier.arrive.shared::cluster.b64 _, [%0];" ::"r"(mapa(BAR(B_ACK2 + wgi), hr ^ 1)) : "memory");
                const uint32_t rem_h = mapa(hbuf + w * 2048 + lane * 16, hr ^ 1);
#define F1_LAST(b0)                                                                            \
    R_WAIT();                                                                                  \
    if (b0) { PP_WAIT() }                                                                      \
    { DECL_DB(b0, BASE64, HALF, 1)                                                             \
    wg_fence();                                                                                \
    FOR7(mma_rs64<1, D64(0, t)>(al, AQ(A, b0, t), (b0) + t > 0, SWB(b0, t, db, 1)));           \
    FOR7(mma_rs64<1, D64(7168, t)>(al, AQ(A, (b0) + 1, t), 1, db)); }                          \
    wg_commit();                                                                               \
    if (b0) { PP_GO() }                                                                        \
    R_NEXT();
                float al[32];
                F1_LAST(0)
                mbar_wait(BAR(B_RECV + wgi), rcvph);
                rcvph ^= 1;
                mbar_wait(BAR(B_ACK2 + wgi), step >> 1);
                H_PUSH(32, 16384) H_PUSH(36, 16896)
                F1_LAST(2)
                H_PUSH(40, 17408) H_PUSH(44, 17920)
                wg_wait<1>();
                R_RELEASE(2);
                wg_wait<0>();
                R_RELEASE(1);
                uint32_t HP[56];
#pragma unroll
                for (int k = 0; k < 4; k++) lds4(H + 4 * k, sb + OFF_KVB + wgi * 8192 + w * 2048 + k * 512 + lane * 16);
#pragma unroll
                for (int t = 0; t < 8; t++) lds4(HP + 4 * t, hbuf + (t >> 2) * 8192 + w * 2048 + (t & 3) * 512 + lane * 16);
                F1_EPI(H + 48, 4, al)
                H_PUSH(48, 24576 - w * 1024) H_PUSH(52, 25088 - w * 1024)
                STAMP(7 + so);
                WSUM(84 + 7 * (step >> 1));
                FRESH();
                float acc[28];
                const uint32_t roA = hr ? 256u : 0u, roB = hr ? (uint32_t)-1536 : 0u;
                const uint32_t rpA = hr ? 0u : 256u, rpB = hr ? 0u : (uint32_t)-1536;
                float res[28];
                uint32_t v0[14], v1[14], P[14];
                const uint4* ps = xp0 + sl * 512;
#define F2_OWN_A()                                                                             \
    R_WAIT();                                                                                  \
    d0 = BASE128(0, 16, R_ADJ + roA); d1 = BASE128(0, 16, R_ADJ + roB);                        \
    wg_fence();                                                                                \
    FOR14(if constexpr (t < OT) mma_rs56<1, t * 128>(acc, H[4 * t], H[4 * t + 1], H[4 * t + 2], H[4 * t + 3], t > 0, d0)); \
    wg_commit();
#define F2_OWN_B()                                                                             \
    wg_fence();                                                                                \
    FOR14(if constexpr (t >= OT) mma_rs56<1, t * 128>(acc, H[4 * t], H[4 * t + 1], H[4 * t + 2], H[4 * t + 3], 1, t < 12 ? d0 : d1)); \
    wg_commit();                                                                               \
    R_NEXT();
#define F2_PEER()                                                                              \
    R_WAIT();                                                                                  \
    if (F2PP) { PP_WAIT() }                                                                    \
    d0 = BASE128(0, 16, R_ADJ + rpA); d1 = BASE128(0, 16, R_ADJ + rpB);                        \
    wg_fence();                                                                                \
    FOR14(mma_rs56<1, t * 128>(acc, HP[4 * t], HP[4 * t + 1], HP[4 * t + 2], HP[4 * t + 3], 1, t < 12 ? d0 : d1)); \
    wg_commit();                                                                               \
    if (F2PP) { PP_GO() }                                                                      \
    R_NEXT();
#define F2_TURN(u)                                                                             \
    wg_wait<1>();                                                                              \
    if ((u) < 2 || TDEF < 2) R_RELEASE(2);                                                     \
    wg_wait<0>();                                                                              \
    if ((u) < 2 || TDEF < 1) R_RELEASE(1);                                                     \
    _Pragma("unroll") for (int i = 0; i < 14; i++) P[i] = pack2(acc[2 * i], acc[2 * i + 1]);   \
    tag_slice(P, tag);                                                                         \
    asm volatile("" : RW4(P, 0), RW4(P, 4), RW4(P, 8), RW2(P, 12));                            \
    kill<28>(acc);                                                                             \
    F2_OWN_A()                                                                                 \
    if ((u) == 2) { slice_load<PL(3)>(v0, ps, lane); slice_load<PL(4)>(v1, ps, lane); } \
    send_slice<PL(3 + (u))>(xp0 + (2 * ((pr + (u) + 1) & 3) + hr) * 512, lane, P);             \
    seq++;                                                                                     \
    if (lane == 0) st_word(cx(sl), seq);                                                       \
    __syncwarp();                                                                              \
    STAMP(8 + (u) + so);                                                                       \
    F2_OWN_B()
                uint64_t d0, d1;
                F2_OWN_A()
                F2_OWN_B()
                R_WAIT();
                d0 = BASE128(0, 16, R_ADJ + rpA); d1 = BASE128(0, 16, R_ADJ + rpB);
                wg_fence();
                FOR8(mma_rs56<1, t * 128>(acc, HP[4 * t], HP[4 * t + 1], HP[4 * t + 2], HP[4 * t + 3], 1, d0));
                wg_commit();
                mbar_wait(BAR(B_RECV2 + wgi), step >> 1);
#pragma unroll
                for (int k = 0; k < 4; k++) lds4(HP + 32 + 4 * k, hbuf + 16384 + w * 2048 + k * 512 + lane * 16);
                lds4(HP + 48, hbuf + 24576 + w * 1024 + lane * 16);
                lds4(HP + 52, hbuf + 25088 + w * 1024 + lane * 16);
                if (step == 1) PUSH_ACK();
                wg_fence();
                FOR14(if constexpr (t >= 8) mma_rs56<1, t * 128>(acc, HP[4 * t], HP[4 * t + 1], HP[4 * t + 2], HP[4 * t + 3], 1, t < 12 ? d0 : d1));
                wg_commit();
                R_NEXT();
                F2_TURN(0)
                F2_PEER()
                F2_TURN(1)
                F2_PEER()
                F2_TURN(2)
                if (step == 1) STAMP(64);
                slice_check<PL(3)>(v0, ps, lane, tag);
                slice_check<PL(4)>(v1, ps, lane, tag);
#pragma unroll
                for (int i = 0; i < 14; i++) { res[2 * i] = bf_lo(v0[i]) + bf_lo(v1[i]); res[2 * i + 1] = bf_hi(v0[i]) + bf_hi(v1[i]); }
                slice_load<PL(2)>(X, ps, lane);
                if (step == 1) STAMP(65);
                F2_PEER()
                if (step == 1) STAMP(66);
                poll_cnt(cx(2 * ((pr + 1) & 3) + hr), seq);
                if (step == 1) STAMP(67);
                slice_load<PL(5)>(v0, ps, lane);
                x_fix(X, xbits);
                slice_check<PL(5)>(v0, ps, lane, tag);
                if (lane < TDEF) mbar_arrive(BAR(B_EMPTY + (slot + NST - 3 - lane) % NST));
#pragma unroll
                for (int i = 0; i < 14; i++) { res[2 * i] += bf_lo(v0[i]); res[2 * i + 1] += bf_hi(v0[i]); }
                STAMP(11 + so);
                wg_wait<0>();
                R_RELEASE(2);
                STAMP(12 + so);
                WSUM(85 + 7 * (step >> 1));
#pragma unroll
                for (int i = 0; i < 14; i++) X[i] = pack2(fmaf(res[2 * i] + acc[2 * i], 0.5f, bf_lo(X[i])), fmaf(res[2 * i + 1] + acc[2 * i + 1], 0.5f, bf_hi(X[i])));
            }
        }
        {
            const int m = lane >> 3, rr = lane & 7;
            const uint32_t ob = hbuf + w * 2048, rowa = ob + (rr + 8 * (m & 1)) * 112 + (m >> 1) * 16;
#pragma unroll
            for (int j = 0; j < 3; j++) stsm4(rowa + 32 * j, X[4 * j], X[4 * j + 1], X[4 * j + 2], X[4 * j + 3]);
            asm volatile("stmatrix.sync.aligned.m8n8.x2.shared.b16 [%0], {%1,%2};" ::"r"(ob + (rr + 8 * (m & 1)) * 112 + 96), "r"(X[12]), "r"(X[13]) : "memory");
            fence_async();
            __syncwarp();
            if (lane == 0) {
                asm volatile("cp.async.bulk.tensor.2d.global.shared::cta.bulk_group [%0, {%2, %3}], [%1];" ::"l"(&maps.out), "r"(ob), "r"(56 * sl), "r"(tile * 128 + wu * 16) : "memory");
                asm volatile("cp.async.bulk.commit_group;" ::: "memory");
                asm volatile("cp.async.bulk.wait_group.read 0;" ::: "memory");
            }
        }
        STAMP(50);
        GSTAMP(61);
        PDUMP();
    }
}

#undef g
#undef pr
#undef c
#undef t128

typedef CUresult (*EncodeFn)(CUtensorMap*, CUtensorMapDataType, cuuint32_t, void*, const cuuint64_t*, const cuuint64_t*, const cuuint32_t*,
                             const cuuint32_t*, CUtensorMapInterleave, CUtensorMapSwizzle, CUtensorMapL2promotion, CUtensorMapFloatOOBfill);

static void make_map(EncodeFn enc, CUtensorMap* m, const void* p, uint64_t cols, uint64_t rows, uint32_t bc, uint32_t br, CUtensorMapSwizzle sw) {
    cuuint64_t gd[2] = {cols, rows};
    cuuint64_t gs[1] = {cols * 2};
    cuuint32_t bd[2] = {bc, br};
    cuuint32_t es[2] = {1, 1};
    enc(m, CU_TENSOR_MAP_DATA_TYPE_BFLOAT16, 2, const_cast<void*>(p), gd, gs, bd, es, CU_TENSOR_MAP_INTERLEAVE_NONE, sw,
        CU_TENSOR_MAP_L2_PROMOTION_L2_128B, CU_TENSOR_MAP_FLOAT_OOB_FILL_NONE);
}

extern "C" void kernel_launch(void* const* d_in, const int* in_sizes, int n_in, void* d_out, int out_size) {
    (void)in_sizes; (void)n_in; (void)out_size;
    static EncodeFn enc = nullptr;
    static Scratch* scratch = nullptr;
    if (!enc) {
        void* fn = nullptr;
        cudaDriverEntryPointQueryResult qr;
        cudaGetDriverEntryPoint("cuTensorMapEncodeTiled", &fn, cudaEnableDefault, &qr);
        enc = (EncodeFn)fn;
        cudaGetSymbolAddress((void**)&scratch, g_scratch);
        cudaFuncSetAttribute(fused_kernel, cudaFuncAttributeMaxDynamicSharedMemorySize, SMEM_BYTES);
    }
    Maps maps;
    {
        cuuint64_t gd[3] = {64, 2048, 7};
        cuuint64_t gs[2] = {896, 128};
        cuuint32_t bd[3] = {64, 32, 7};
        cuuint32_t es[3] = {1, 1, 1};
        enc(&maps.x, CU_TENSOR_MAP_DATA_TYPE_BFLOAT16, 3, d_in[0], gd, gs, bd, es, CU_TENSOR_MAP_INTERLEAVE_NONE, CU_TENSOR_MAP_SWIZZLE_128B,
            CU_TENSOR_MAP_L2_PROMOTION_L2_128B, CU_TENSOR_MAP_FLOAT_OOB_FILL_NONE);
    }
    make_map(enc, &maps.out, d_out, 448, 2048, 56, 16, CU_TENSOR_MAP_SWIZZLE_NONE);
    make_map(enc, &maps.qkv, d_in[1], 1344, 448, 64, 112, CU_TENSOR_MAP_SWIZZLE_128B);
    make_map(enc, &maps.wo, d_in[3], 448, 448, 64, 112, CU_TENSOR_MAP_SWIZZLE_128B);
    make_map(enc, &maps.wg, d_in[5], 1792, 448, 64, 112, CU_TENSOR_MAP_SWIZZLE_128B);
    make_map(enc, &maps.wu, d_in[6], 1792, 448, 64, 112, CU_TENSOR_MAP_SWIZZLE_128B);
    make_map(enc, &maps.wg32, d_in[5], 1792, 448, 32, 112, CU_TENSOR_MAP_SWIZZLE_64B);
    make_map(enc, &maps.wu32, d_in[6], 1792, 448, 32, 112, CU_TENSOR_MAP_SWIZZLE_64B);
    make_map(enc, &maps.wd, d_in[7], 448, 1792, 64, 112, CU_TENSOR_MAP_SWIZZLE_128B);
    fused_kernel<<<128, 384, SMEM_BYTES>>>(scratch, (const __nv_bfloat16*)d_in[0], (const __nv_bfloat16*)d_in[2], 7, (const __nv_bfloat16*)d_in[5],
                                           (const __nv_bfloat16*)d_in[6], (const __nv_bfloat16*)d_in[7], maps);
}
```

```cpp
#include <cuda_runtime.h>
#include <cuda.h>
#include <cuda_bf16.h>
#include <stdint.h>
#include <type_traits>

#define PPF 2
#define PKP 0
#define TDEF 1
#define TMPF 0
#define NORM1 0
#define LPARK 1
#define PFP 0
#define ACAN 0
#define SPLIT0 1
#define OT 2
#define F2PP 0
#define PPK 2
#define QE 1
#define OST 1
#define PP

namespace {

constexpr uint32_t STAGE = 28672, HALF = 14336;
constexpr int NST = 5;
constexpr uint32_t OFF_H = NST * STAGE;
constexpr uint32_t OFF_KVB = OFF_H + 2 * STAGE;
constexpr uint32_t OFF_WPHI = OFF_KVB + 16384;
constexpr uint32_t OFF_XR = OFF_WPHI + 7168;
constexpr uint32_t OFF_BAR = OFF_XR + 6144;
constexpr uint32_t SMEM_BYTES = OFF_BAR + 384 + 1408;
constexpr int B_EMPTY = NST, B_RECV = 2 * NST, B_RECV2 = B_RECV + 2, B_PACK = B_RECV2 + 2, B_GAT = B_PACK + 1, B_LATE = B_GAT + 16, B_ACK = B_LATE + 1, B_ACK2 = B_ACK + 2, B_COUNT = B_ACK2 + 2;

constexpr int PACK = 14 + 4 * PKP;

struct Maps { CUtensorMap x, qkv, wo, wg, wu, wg32, wu32, wd, out; };

}

constexpr int PLANE = 16 * 2 * 8 * 512;
struct Scratch {
    uint4 ex[6 * PLANE];
    uint4 kv1[8 * 16 * 16 * 32];
    uint4 kv2[8 * 512];
    uint32_t c1[8 * 8 * 16 * 32];
    uint32_t cw[8 * 32];
    uint4 wp[8 * 32 * (HALF / 16)];
};
__device__ __align__(1024) Scratch g_scratch;
#define g_ex (sc->ex)
#define g_kv1 (sc->kv1)
#define g_kv2 (sc->kv2)
#define g_c1 (sc->c1)
#define g_cw (sc->cw)
#define g_wp (sc->wp)
#define STAMP(i)
#define GSTAMP(i)
#define PDUMP()
#define ASTAMP(i)

namespace {

__device__ __forceinline__ int fresh_tid() { int t; asm volatile("mov.u32 %0, %%tid.x;" : "=r"(t)); return t; }
template <int N> __device__ __forceinline__ void kill(uint32_t* v) {
#pragma unroll
    for (int i = 0; i < N; i++) v[i] = 0;
}
template <int N> __device__ __forceinline__ void kill(float* v) {
#pragma unroll
    for (int i = 0; i < N; i++) v[i] = 0.f;
}
__device__ __forceinline__ uint32_t s2u(const void* p) { return (uint32_t)__cvta_generic_to_shared(p); }
__device__ __forceinline__ void mbar_init(uint32_t a, uint32_t c) { asm volatile("mbarrier.init.shared::cta.b64 [%0], %1;" ::"r"(a), "r"(c) : "memory"); }
__device__ __forceinline__ void mbar_expect_tx(uint32_t a, uint32_t b) { asm volatile("mbarrier.arrive.expect_tx.shared::cta.b64 _, [%0], %1;" ::"r"(a), "r"(b) : "memory"); }
__device__ __forceinline__ void mbar_arrive(uint32_t a) { asm volatile("mbarrier.arrive.shared::cta.b64 _, [%0];" ::"r"(a) : "memory"); }
#define GIVE_UP(id) "trap;\n"
#define SPIN_MAX "0x400000"
#define SPIN_TAIL(id) "add.u32 n, n, 1;\n setp.lt.u32 p, n, " SPIN_MAX ";\n @p bra.uni LP;\n" GIVE_UP(id) " DN:\n }"
__device__ __forceinline__ void mbar_wait(uint32_t a, uint32_t ph) {
    asm volatile("{ .reg .pred p; .reg .b32 n; mov.u32 n, 0;\n LP:\n"
                 "mbarrier.try_wait.parity.shared::cta.b64 p, [%0], %1;\n @p bra DN;\n"
                 "add.u32 n, n, 1;\n setp.lt.u32 p, n, " SPIN_MAX ";\n @p bra LP;\n"
                 GIVE_UP("")
                 " DN:\n }" ::"r"(a), "r"(ph) : "memory");
}
#define ELECT "{ .reg .pred e; elect.sync _|e, 0xffffffff; @e "
__device__ __forceinline__ void tma2d(uint32_t dst, const CUtensorMap* m, int c0, int c1, uint32_t bar) {
    asm volatile(ELECT "cp.async.bulk.tensor.2d.shared::cluster.global.mbarrier::complete_tx::bytes [%0], [%1, {%3, %4}], [%2]; }" ::"r"(dst), "l"(m), "r"(bar), "r"(c0), "r"(c1) : "memory");
}
__device__ __forceinline__ void tma3x(uint32_t dst, const CUtensorMap* m, int row, uint32_t bar) {
    asm volatile(ELECT "cp.async.bulk.tensor.3d.shared::cluster.global.mbarrier::complete_tx::bytes [%0], [%1, {0, %3, 0}], [%2]; }" ::"r"(dst), "l"(m), "r"(bar), "r"(row) : "memory");
}
template <int OFF>
__device__ __forceinline__ void ld_pkt(uint32_t* v, const uint4* p) {
    asm volatile("{ .reg .b128 t; ld.relaxed.gpu.global.b128 t, [%4+%5]; mov.b128 {%0,%1,%2,%3}, t; }" : "=r"(v[0]), "=r"(v[1]), "=r"(v[2]), "=r"(v[3]) : "l"(p), "n"(OFF * 16) : "memory");
}
template <int OFF>
__device__ __forceinline__ void st_pkt(uint4* p, uint32_t a, uint32_t b, uint32_t c, uint32_t d) {
    asm volatile("{ .reg .b128 t; mov.b128 t, {%1,%2,%3,%4}; st.relaxed.gpu.global.b128 [%0+%5], t; }" ::"l"(p), "r"(a), "r"(b), "r"(c), "r"(d), "n"(OFF * 16) : "memory");
}
__device__ __forceinline__ uint32_t pack2(float lo, float hi) {
    uint32_t r;
    asm("cvt.rn.bf16x2.f32 %0, %1, %2;" : "=r"(r) : "f"(hi), "f"(lo));
    return r;
}
__device__ __forceinline__ float bf_lo(uint32_t w) { return __uint_as_float(w << 16); }
__device__ __forceinline__ float bf_hi(uint32_t w) { return __uint_as_float(w & 0xffff0000u); }
__device__ __forceinline__ uint32_t settag(uint32_t w, uint32_t tag) { return (w & ~1u) | tag; }
__device__ __forceinline__ float ex2(float x) { float y; asm("ex2.approx.ftz.f32 %0, %1;" : "=f"(y) : "f"(x)); return y; }
__device__ __forceinline__ float rcp(float x) { float y; asm("rcp.approx.ftz.f32 %0, %1;" : "=f"(y) : "f"(x)); return y; }
__device__ __forceinline__ float tanh_hw(float x) { float y; asm("tanh.approx.f32 %0, %1;" : "=f"(y) : "f"(x)); return y; }
__device__ __forceinline__ void stsm4(uint32_t addr, uint32_t a, uint32_t b, uint32_t c, uint32_t d) {
    asm volatile("stmatrix.sync.aligned.m8n8.x4.shared.b16 [%0], {%1,%2,%3,%4};" ::"r"(addr), "r"(a), "r"(b), "r"(c), "r"(d) : "memory");
}
__device__ __forceinline__ void fence_async() { asm volatile("fence.proxy.async.shared::cta;" ::: "memory"); }
__device__ __forceinline__ void bar_sync(int id, int n) { asm volatile("bar.sync %0, %1;" ::"r"(id), "r"(n) : "memory"); }
__device__ __forceinline__ void bar_arrive(int id, int n) { asm volatile("bar.arrive %0, %1;" ::"r"(id), "r"(n) : "memory"); }
__device__ __forceinline__ void wg_fence() { asm volatile("wgmma.fence.sync.aligned;" ::: "memory"); }
__device__ __forceinline__ void wg_commit() { asm volatile("wgmma.commit_group.sync.aligned;" ::: "memory"); }
template <int N> __device__ __forceinline__ void wg_wait() { asm volatile("wgmma.wait_group.sync.aligned %0;" ::"n"(N) : "memory"); }

constexpr uint32_t SB0 = 1024;
__host__ __device__ constexpr uint32_t dlo(uint32_t off, uint32_t lbo) { return ((SB0 + off) >> 4) | ((lbo >> 4) << 16); }
__host__ __device__ constexpr uint32_t dhi(uint32_t sbo, uint32_t sw) { return (sbo >> 4) | (sw << 30); }
__device__ __forceinline__ uint64_t dbase(uint32_t lo, uint32_t hi) { uint64_t d; asm volatile("mov.b64 %0, {%1, %2};" : "=l"(d) : "r"(lo), "r"(hi)); return d; }
#define BASE128(off, lbo, adj) dbase(dlo(off, lbo) + (adj), dhi(1024, 1))
#define BASE64(off, lbo, adj) dbase(dlo(off, lbo) + (adj), dhi(512, 2))

#define ACC4(d, o) "+f"(d[o]), "+f"(d[o + 1]), "+f"(d[o + 2]), "+f"(d[o + 3])
#define ACC28(d) ACC4(d, 0), ACC4(d, 4), ACC4(d, 8), ACC4(d, 12), ACC4(d, 16), ACC4(d, 20), ACC4(d, 24)
#define ACC32(d, o) ACC4(d, o), ACC4(d, o + 4), ACC4(d, o + 8), ACC4(d, o + 12), ACC4(d, o + 16), ACC4(d, o + 20), ACC4(d, o + 24), ACC4(d, o + 28)

template <int TB, uint64_t D>
__device__ __forceinline__ void mma_rs56(float* d, uint32_t a0, uint32_t a1, uint32_t a2, uint32_t a3, int sd, uint64_t base) {
    asm volatile("{ .reg .pred p; .reg .b64 db; setp.ne.b32 p, %32, 0; add.u64 db, %33, %34;\n"
                 "wgmma.mma_async.sync.aligned.m64n56k16.f32.bf16.bf16 "
                 "{%0,%1,%2,%3,%4,%5,%6,%7,%8,%9,%10,%11,%12,%13,%14,%15,%16,%17,%18,%19,%20,%21,%22,%23,%24,%25,%26,%27}, "
                 "{%28,%29,%30,%31}, db, p, 1, 1, %35; }\n"
                 : ACC28(d)
                 : "r"(a0), "r"(a1), "r"(a2), "r"(a3), "r"(sd), "l"(base), "n"(D), "n"(TB));
}
template <int TB, uint64_t D>
__device__ __forceinline__ void mma_rs64(float* d, uint32_t a0, uint32_t a1, uint32_t a2, uint32_t a3, int sd, uint64_t base) {
    asm volatile("{ .reg .pred p; .reg .b64 db; setp.ne.b32 p, %36, 0; add.u64 db, %37, %38;\n"
                 "wgmma.mma_async.sync.aligned.m64n64k16.f32.bf16.bf16 "
                 "{%0,%1,%2,%3,%4,%5,%6,%7,%8,%9,%10,%11,%12,%13,%14,%15,%16,%17,%18,%19,%20,%21,%22,%23,%24,%25,%26,%27,%28,%29,%30,%31}, "
                 "{%32,%33,%34,%35}, db, p, 1, 1, %39; }\n"
                 : ACC32(d, 0)
                 : "r"(a0), "r"(a1), "r"(a2), "r"(a3), "r"(sd), "l"(base), "n"(D), "n"(TB));
}
template <int TB, uint64_t D>
__device__ __forceinline__ void mma_rs128(float* d, uint32_t a0, uint32_t a1, uint32_t a2, uint32_t a3, int sd, uint64_t base) {
    asm volatile("{ .reg .pred p; .reg .b64 db; setp.ne.b32 p, %68, 0; add.u64 db, %69, %70;\n"
                 "wgmma.mma_async.sync.aligned.m64n128k16.f32.bf16.bf16 "
                 "{%0,%1,%2,%3,%4,%5,%6,%7,%8,%9,%10,%11,%12,%13,%14,%15,%16,%17,%18,%19,%20,%21,%22,%23,%24,%25,%26,%27,%28,%29,%30,%31,%32,%33,%34,%35,%36,%37,%38,%39,%40,%41,%42,%43,%44,%45,%46,%47,%48,%49,%50,%51,%52,%53,%54,%55,%56,%57,%58,%59,%60,%61,%62,%63}, "
                 "{%64,%65,%66,%67}, db, p, 1, 1, %71; }\n"
                 : ACC32(d, 0), ACC32(d, 32)
                 : "r"(a0), "r"(a1), "r"(a2), "r"(a3), "r"(sd), "l"(base), "n"(D), "n"(TB));
}
template <uint64_t DA, uint64_t DB>
__device__ __forceinline__ void mma_ss56_tt(float* d, int sd, uint64_t ba, uint64_t bb) {
    asm volatile("{ .reg .pred p; .reg .b64 da, db; setp.ne.b32 p, %28, 0; add.u64 da, %29, %31; add.u64 db, %30, %32;\n"
                 "wgmma.mma_async.sync.aligned.m64n56k16.f32.bf16.bf16 "
                 "{%0,%1,%2,%3,%4,%5,%6,%7,%8,%9,%10,%11,%12,%13,%14,%15,%16,%17,%18,%19,%20,%21,%22,%23,%24,%25,%26,%27}, "
                 "da, db, p, 1, 1, 1, 1; }\n"
                 : ACC28(d)
                 : "r"(sd), "l"(ba), "l"(bb), "n"(DA), "n"(DB));
}
template <int... I> struct Seq {};
template <class F, int... I> __device__ __forceinline__ void static_for_impl(F&& f, Seq<I...>) { (f(std::integral_constant<int, I>{}), ...); }
#define FOR7(...) static_for_impl([&](auto T_) { constexpr int t = decltype(T_)::value; __VA_ARGS__; }, Seq<0, 1, 2, 3, 4, 5, 6>{})
#define FOR8(...) static_for_impl([&](auto T_) { constexpr int t = decltype(T_)::value; __VA_ARGS__; }, Seq<0, 1, 2, 3, 4, 5, 6, 7>{})
#define FOR14(...) static_for_impl([&](auto T_) { constexpr int t = decltype(T_)::value; __VA_ARGS__; }, Seq<0, 1, 2, 3, 4, 5, 6, 7, 8, 9, 10, 11, 12, 13>{})

__device__ __forceinline__ int kblk(int p, int b) { return b == 0 ? p : b - (b <= p); }
__host__ __device__ constexpr int krow(int t) { return t < 3 ? 16 * t : (t < 6 ? 56 + 16 * (t - 3) : 48); }
#define AQ(A, b, t) ((t) < 3 ? A[2 * (b)][4 * (t)] : (t) < 6 ? A[2 * (b) + 1][4 * ((t) - 3)] : A[2 * (b)][12]), \
                    ((t) < 3 ? A[2 * (b)][4 * (t) + 1] : (t) < 6 ? A[2 * (b) + 1][4 * ((t) - 3) + 1] : A[2 * (b)][13]), \
                    ((t) < 3 ? A[2 * (b)][4 * (t) + 2] : (t) < 6 ? A[2 * (b) + 1][4 * ((t) - 3) + 2] : A[2 * (b) + 1][12]), \
                    ((t) < 3 ? A[2 * (b)][4 * (t) + 3] : (t) < 6 ? A[2 * (b) + 1][4 * ((t) - 3) + 3] : A[2 * (b) + 1][13])
#define D128(off, t) ((uint64_t)(((off) + krow(t) * 128) >> 4) + ((uint64_t)((t) == 6 ? (7168 - 1024) >> 4 : 0) << 32))
#define D64(off, t) ((uint64_t)(((off) + krow(t) * 64) >> 4) + ((uint64_t)((t) == 6 ? (3584 - 512) >> 4 : 0) << 32))

#define PL(k) (((k) - 3) * PLANE)
__device__ __forceinline__ void st_word(uint32_t* p, uint32_t v) { asm volatile("st.relaxed.gpu.global.u32 [%0], %1;" ::"l"(p), "r"(v) : "memory"); }
__device__ __forceinline__ uint32_t ld_word(const uint32_t* p) { uint32_t v; asm volatile("ld.relaxed.gpu.global.u32 %0, [%1];" : "=r"(v) : "l"(p) : "memory"); return v; }
__device__ __forceinline__ void tag_slice(uint32_t* w, uint32_t tag) { w[0] = settag(w[0], tag); w[4] = settag(w[4], tag); w[8] = settag(w[8], tag); w[12] = settag(w[12], tag); }
template <int O>
__device__ __forceinline__ void send_slice(uint4* dst, int lane, const uint32_t* w) {
    st_pkt<O>(dst, w[0], w[1], w[2], w[3]);
    st_pkt<O + 32>(dst, w[4], w[5], w[6], w[7]);
    st_pkt<O + 64>(dst, w[8], w[9], w[10], w[11]);
    asm volatile("{ .reg .b64 t; mov.b64 t, {%1,%2}; st.relaxed.gpu.global.b64 [%0+%3], t; }" ::"l"((char*)dst - lane * 8), "r"(w[12]), "r"(w[13]), "n"(16 * (O + 96)) : "memory");
}
#define RW4(v, o) "+r"(v[o]), "+r"(v[(o) + 1]), "+r"(v[(o) + 2]), "+r"(v[(o) + 3])
#define RW2(v, o) "+r"(v[o]), "+r"(v[(o) + 1])
#define WR4(v, o) "=&r"(v[o]), "=&r"(v[(o) + 1]), "=&r"(v[(o) + 2]), "=&r"(v[(o) + 3])
#define LDP(a, b, c, d, addr, off) "ld.relaxed.gpu.global.b128 q, [" addr "+" off "];\n mov.b128 {" a "," b "," c "," d "}, q;\n"
#define LDH(a, b, addr, off) "ld.relaxed.gpu.global.b64 h, [" addr "+" off "];\n mov.b64 {" a "," b "}, h;\n"
#define VOTE_OK "and.b32 t, t, 1;\n setp.ne.u32 p, t, 0;\n vote.sync.any.pred p, p, 0xffffffff;\n @!p bra.uni DN;\n"
#define CHK(x, tag) "lop3.b32 t, " x ", " tag ", t, 0xBE;\n"
__device__ __forceinline__ void check_cnt(uint32_t v, const uint32_t* p, uint32_t target) {
    asm volatile("{ .reg .pred p; .reg .b32 n, t; mov.u32 n, 0; mov.u32 t, %2;\n LP:\n"
                 "sub.s32 t, t, %1;\n setp.lt.s32 p, t, 0;\n vote.sync.any.pred p, p, 0xffffffff;\n @!p bra.uni DN;\n ld.relaxed.gpu.global.u32 t, [%0];\n" SPIN_TAIL("7")
                 ::"l"(p), "r"(target), "r"(v) : "memory");
}
__device__ __forceinline__ void poll_cnt(const uint32_t* p, uint32_t target) {
    asm volatile("{ .reg .pred p; .reg .b32 n, t; mov.u32 n, 0;\n LP:\n"
                 "ld.relaxed.gpu.global.u32 t, [%0];\n sub.s32 t, t, %1;\n setp.lt.s32 p, t, 0;\n vote.sync.any.pred p, p, 0xffffffff;\n @!p bra.uni DN;\n" SPIN_TAIL("1")
                 ::"l"(p), "r"(target) : "memory");
}
template <int STR>
__device__ __forceinline__ void poll4_kv(uint32_t* v, const uint4* p, uint32_t tag) {
    asm volatile("{ .reg .pred p; .reg .b32 n, t; .reg .b128 q; mov.u32 n, 0;\n LP:\n"
                 LDP("%0", "%1", "%2", "%3", "%16", "0") LDP("%4", "%5", "%6", "%7", "%16", "%18")
                 LDP("%8", "%9", "%10", "%11", "%16", "%19") LDP("%12", "%13", "%14", "%15", "%16", "%20")
                 "xor.b32 t, %0, %17;\n" CHK("%4", "%17") CHK("%8", "%17") CHK("%12", "%17") VOTE_OK SPIN_TAIL("2")
                 : WR4(v, 0), WR4(v, 4), WR4(v, 8), WR4(v, 12)
                 : "l"(p), "r"(tag), "n"(16 * STR), "n"(32 * STR), "n"(48 * STR)
                 : "memory");
}
template <int B>
__device__ __forceinline__ void blk_load(uint32_t (&A)[8][14], const uint4* src, int lane) {
    ld_pkt<0>(&A[2 * B][0], src); ld_pkt<32>(&A[2 * B][4], src); ld_pkt<64>(&A[2 * B][8], src);
    ld_pkt<512>(&A[2 * B + 1][0], src); ld_pkt<544>(&A[2 * B + 1][4], src); ld_pkt<576>(&A[2 * B + 1][8], src);
    asm volatile("{ .reg .b64 h;\n" LDH("%0", "%1", "%4", "1536") LDH("%2", "%3", "%4", "9728") "}"
                 : "=&r"(A[2 * B][12]), "=&r"(A[2 * B][13]), "=&r"(A[2 * B + 1][12]), "=&r"(A[2 * B + 1][13])
                 : "l"((const char*)src - lane * 8) : "memory");
}
template <int B>
__device__ __forceinline__ void blk_check(uint32_t (&A)[8][14], const uint4* src, int lane, uint32_t tag) {
    asm volatile("{ .reg .pred p; .reg .b32 n, t; .reg .b128 q; .reg .b64 h, a8; mov.u32 n, 0;\n LP:\n"
                 "xor.b32 t, %0, %30;\n" CHK("%4", "%30") CHK("%8", "%30") CHK("%12", "%30") CHK("%16", "%30") CHK("%20", "%30") CHK("%24", "%30") CHK("%26", "%30") VOTE_OK
                 LDP("%0", "%1", "%2", "%3", "%28", "0") LDP("%4", "%5", "%6", "%7", "%28", "512") LDP("%8", "%9", "%10", "%11", "%28", "1024")
                 LDP("%12", "%13", "%14", "%15", "%28", "8192") LDP("%16", "%17", "%18", "%19", "%28", "8704") LDP("%20", "%21", "%22", "%23", "%28", "9216")
                 "mad.wide.s32 a8, %29, -8, %28;\n" LDH("%24", "%25", "a8", "1536") LDH("%26", "%27", "a8", "9728") SPIN_TAIL("3")
                 "\n and.b32 %0, %0, -2; and.b32 %4, %4, -2; and.b32 %8, %8, -2; and.b32 %12, %12, -2; and.b32 %16, %16, -2; and.b32 %20, %20, -2; and.b32 %24, %24, -2; and.b32 %26, %26, -2;"
                 : RW4(A[2 * B], 0), RW4(A[2 * B], 4), RW4(A[2 * B], 8), RW4(A[2 * B + 1], 0), RW4(A[2 * B + 1], 4), RW4(A[2 * B + 1], 8),
                   RW2(A[2 * B], 12), RW2(A[2 * B + 1], 12)
                 : "l"(src), "r"(lane), "r"(tag)
                 : "memory");
}
__device__ __forceinline__ void st_async4(uint32_t a, uint32_t x, uint32_t y, uint32_t z, uint32_t w, uint32_t bar) {
    asm volatile("st.async.weak.shared::cluster.mbarrier::complete_tx::bytes.v4.b32 [%0], {%1,%2,%3,%4}, [%5];" ::"r"(a), "r"(x), "r"(y), "r"(z), "r"(w), "r"(bar) : "memory");
}
__device__ __forceinline__ uint32_t mapa(uint32_t a, uint32_t cta) { uint32_t r; asm("mapa.shared::cluster.u32 %0, %1, %2;" : "=r"(r) : "r"(a), "r"(cta)); return r; }
__device__ __forceinline__ void stat_load(uint32_t* v, const uint4* p) { ld_pkt<0>(v, p); ld_pkt<512>(v + 4, p); }
__device__ __forceinline__ void stat_check(uint32_t* v, const uint4* p, uint32_t tag) {
    asm volatile("{ .reg .pred p; .reg .b32 n, t; .reg .b128 q; mov.u32 n, 0;\n LP:\n"
                 "xor.b32 t, %3, %9;\n" CHK("%7", "%9") VOTE_OK
                 LDP("%0", "%1", "%2", "%3", "%8", "0") LDP("%4", "%5", "%6", "%7", "%8", "8192") SPIN_TAIL("4")
                 : RW4(v, 0), RW4(v, 4) : "l"(p), "r"(tag) : "memory");
}
__device__ __forceinline__ uint32_t x_bits(const uint32_t* X) {
    uint32_t r;
    asm volatile("{ .reg .b32 a, b; prmt.b32 a, %1, %2, 0x0040; prmt.b32 b, %3, %4, 0x0040; prmt.b32 %0, a, b, 0x5410; }" : "=r"(r) : "r"(X[0]), "r"(X[4]), "r"(X[8]), "r"(X[12]));
    return r;
}
template <int O>
__device__ __forceinline__ void slice_load(uint32_t* v, const uint4* p, int lane) {
    ld_pkt<O>(v, p); ld_pkt<O + 32>(v + 4, p); ld_pkt<O + 64>(v + 8, p);
    asm volatile("{ .reg .b64 h;\n" LDH("%0", "%1", "%2", "%3") "}" : "=r"(v[12]), "=r"(v[13]) : "l"((const char*)p - lane * 8), "n"(16 * (O + 96)) : "memory");
}
template <int O>
__device__ __forceinline__ void slice_check(uint32_t* v, const uint4* p, int lane, uint32_t tag) {
    asm volatile("{ .reg .pred p; .reg .b32 n, t; .reg .b128 q; .reg .b64 h; mov.u32 n, 0;\n LP:\n"
                 "xor.b32 t, %0, %16;\n" CHK("%4", "%16") CHK("%8", "%16") CHK("%12", "%16") VOTE_OK
                 LDP("%0", "%1", "%2", "%3", "%14", "%17") LDP("%4", "%5", "%6", "%7", "%14", "%18") LDP("%8", "%9", "%10", "%11", "%14", "%19")
                 LDH("%12", "%13", "%15", "%20") SPIN_TAIL("5")
                 : RW4(v, 0), RW4(v, 4), RW4(v, 8), RW2(v, 12)
                 : "l"(p), "l"((const char*)p - lane * 8), "r"(tag), "n"(16 * O), "n"(16 * (O + 32)), "n"(16 * (O + 64)), "n"(16 * (O + 96))
                 : "memory");
}
__device__ __forceinline__ void x_fix(uint32_t* X, uint32_t bits) {
    X[0] = __byte_perm(X[0], bits, 0x3214); X[4] = __byte_perm(X[4], bits, 0x3215); X[8] = __byte_perm(X[8], bits, 0x3216); X[12] = __byte_perm(X[12], bits, 0x3217);
}
__device__ __forceinline__ void sts4(uint32_t a, uint32_t x, uint32_t y, uint32_t z, uint32_t w) {
    asm volatile("st.shared.v4.u32 [%0], {%1,%2,%3,%4};" ::"r"(a), "r"(x), "r"(y), "r"(z), "r"(w) : "memory");
}
__device__ __forceinline__ void lds4(uint32_t* v, uint32_t a) {
    asm volatile("ld.shared.v4.u32 {%0,%1,%2,%3}, [%4];" : "=r"(v[0]), "=r"(v[1]), "=r"(v[2]), "=r"(v[3]) : "r"(a) : "memory");
}
struct LnCoef { uint32_t hi, lo, sh; };
__device__ __forceinline__ LnCoef ln_coef(float sum, float sq) {
    sum += __shfl_xor_sync(0xffffffffu, sum, 1); sq += __shfl_xor_sync(0xffffffffu, sq, 1);
    sum += __shfl_xor_sync(0xffffffffu, sum, 2); sq += __shfl_xor_sync(0xffffffffu, sq, 2);
    const float mean = sum * (1.f / 448.f);
    const float var = fmaxf(fmaf(-mean, mean, sq * (1.f / 448.f)), 0.f);
    const float sc = rsqrtf(var + 1e-5f);
    LnCoef r;
    r.hi = pack2(sc, sc);
    const float lo = sc - bf_lo(r.hi), sh = -mean * sc;
    r.lo = pack2(lo, lo);
    r.sh = pack2(sh, sh);
    return r;
}
template <int B>
__device__ __forceinline__ void normalize(uint32_t (&A)[8][14], const LnCoef& c0, const LnCoef& c1) {
#pragma unroll
    for (int s = 2 * B; s < 2 * B + 2; s++)
#pragma unroll
        for (int i = 0; i < 14; i++) {
            const LnCoef& k = (i & 1) ? c1 : c0;
            asm("{ .reg .b32 t; fma.rn.bf16x2 t, %0, %2, %3; fma.rn.bf16x2 %0, %0, %1, t; }" : "+r"(A[s][i]) : "r"(k.hi), "r"(k.lo), "r"(k.sh));
        }
}
__device__ __forceinline__ void slice_stats(const uint32_t* w, float* st) {
    float a = 0.f, b = 0.f, p = 0.f, q = 0.f;
#pragma unroll
    for (int i = 0; i < 7; i++) {
        const float e0 = bf_lo(w[2 * i]), e1 = bf_hi(w[2 * i]), e2 = bf_lo(w[2 * i + 1]), e3 = bf_hi(w[2 * i + 1]);
        a += e0 + e1; b += e2 + e3;
        p = fmaf(e0, e0, p); p = fmaf(e1, e1, p); q = fmaf(e2, e2, q); q = fmaf(e3, e3, q);
    }
    a += __shfl_xor_sync(0xffffffffu, a, 1); p += __shfl_xor_sync(0xffffffffu, p, 1); b += __shfl_xor_sync(0xffffffffu, b, 1); q += __shfl_xor_sync(0xffffffffu, q, 1);
    a += __shfl_xor_sync(0xffffffffu, a, 2); p += __shfl_xor_sync(0xffffffffu, p, 2); b += __shfl_xor_sync(0xffffffffu, b, 2); q += __shfl_xor_sync(0xffffffffu, q, 2);
    st[0] = a; st[1] = p; st[2] = b; st[3] = q;
}
__device__ __forceinline__ void dual_softmax(const float* p, uint32_t* out) {
    constexpr float L = 1.4426950408889634f;
#pragma unroll
    for (int r = 0; r < 2; r++) {
        float mx = fmaxf(p[2 * r], p[2 * r + 1]), mn = fminf(p[2 * r], p[2 * r + 1]);
#pragma unroll
        for (int i = 1; i < 7; i++) {
            mx = fmaxf(mx, fmaxf(p[4 * i + 2 * r], p[4 * i + 2 * r + 1]));
            mn = fminf(mn, fminf(p[4 * i + 2 * r], p[4 * i + 2 * r + 1]));
        }
        mx = fmaxf(mx, __shfl_xor_sync(0xffffffffu, mx, 1));
        mn = fminf(mn, __shfl_xor_sync(0xffffffffu, mn, 1));
        const float bx = -mx * L, bn = mn * L;
        float ep[14], en[14], sp = 0.f, sn = 0.f;
#pragma unroll
        for (int i = 0; i < 14; i++) {
            const float v = p[4 * (i >> 1) + 2 * r + (i & 1)];
            ep[i] = ex2(fmaf(v, L, bx));
            en[i] = ex2(fmaf(v, -L, bn));
            sp += ep[i]; sn += en[i];
        }
        sp += __shfl_xor_sync(0xffffffffu, sp, 1);
        sn += __shfl_xor_sync(0xffffffffu, sn, 1);
        const float ip = rcp(sp), in = rcp(sn);
#pragma unroll
        for (int i = 0; i < 7; i++) {
            out[4 * i + r] = pack2(ep[2 * i] * ip, ep[2 * i + 1] * ip);
            out[4 * i + 2 + r] = pack2(en[2 * i] * in, en[2 * i + 1] * in);
        }
    }
}
__device__ __forceinline__ float geglu(float g, float u) {
    const float t = tanh_hw(g * fmaf(g * g, 0.7978845608028654f * 0.044715f, 0.7978845608028654f));
    const float gu = g * u;
    return fmaf(t, gu, gu);
}
__device__ __forceinline__ void phi_gemm(const float* t, float* p) {
    uint32_t w[14];
#pragma unroll
    for (int i = 0; i < 14; i++) w[i] = pack2(t[2 * i], t[2 * i + 1]);
    const uint64_t db = BASE128(OFF_WPHI, 16, 0);
    wg_fence();
    mma_rs56<0, 0>(p, w[0], w[1], w[2], w[3], 0, db);
    mma_rs56<0, 2>(p, w[4], w[5], w[6], w[7], 1, db);
    mma_rs56<0, 4>(p, w[8], w[9], w[10], w[11], 1, db);
    mma_rs56<0, 6>(p, w[12], w[13], 0u, 0u, 1, db);
    wg_commit();
    wg_wait<0>();
}

}

#define BAR(i) (bars + 8 * (i))
#define R_WAIT() mbar_wait(BAR(slot), ph)
#define WSUM(i)
#define R_ADJ (slot * (STAGE >> 4))
#define R_NEXT() do { eb2 = eb1; eb1 = BAR(B_EMPTY + slot); if (++slot == NST) { slot = 0; ph ^= 1; } } while (0)
#define R_RELEASE(k) do { if (lane == 0) mbar_arrive((k) == 1 ? eb1 : eb2); } while (0)
#define PUSH_BEGIN() do { mbar_wait(BAR(B_ACK + wgi), ackph); ackph ^= 1; } while (0)
#define PUSH_ACK() do { __syncwarp(); if (lane == 0) asm volatile("mbarrier.arrive.shared::cluster.b64 _, [%0];" ::"r"(mapa(BAR(B_ACK + wgi), hr ^ 1)) : "memory"); } while (0)

__global__ void __cluster_dims__(2, 1, 1) __launch_bounds__(384, 1)
fused_kernel(Scratch* const sc, const __nv_bfloat16* __restrict__ x_in, const __nv_bfloat16* __restrict__ w_phi, const int trips,
             const __nv_bfloat16* __restrict__ wg, const __nv_bfloat16* __restrict__ wu, const __nv_bfloat16* __restrict__ wd,
             const __grid_constant__ Maps maps) {
    extern __shared__ __align__(1024) unsigned char smem_raw[];
    const uint32_t sb = s2u(smem_raw);
    const uint32_t bars = sb + OFF_BAR;
    const int wgi = __shfl_sync(0xffffffffu, threadIdx.x >> 7, 0);
    const int hr = blockIdx.x & 1, ck = blockIdx.x >> 1;
    const int gp = (ck - 4) & 7, q7 = ((ck - 36) * 37) >> 8;
    const int pr = __shfl_sync(0xffffffffu, ck < 4 ? ck : (ck < 36 ? (ck - 4) >> 3 : q7), 0);
    const int tile = __shfl_sync(0xffffffffu, ck < 4 ? 0 : (ck < 36 ? (gp ? 2 * gp : 1) : 2 * (ck - 36 - 7 * q7) + 3), 0);
    const int sl = 2 * pr + hr;
    STAMP(0);
    GSTAMP(60);
    if (threadIdx.x == 256) {
#pragma unroll
        for (int i = 0; i < NST; i++) mbar_init(BAR(i), 1);
        asm volatile("fence.mbarrier_init.release.cluster;" ::: "memory");
    }
    if (threadIdx.x == 288) {
        if ((sb & 0x3FFFF) != SB0) asm volatile("trap;");
#pragma unroll
        for (int i = NST; i < B_COUNT; i++) mbar_init(BAR(i), i >= B_ACK ? 4 : (i < B_RECV || i == B_LATE ? 8 : 1));
        asm volatile("fence.mbarrier_init.release.cluster;" ::: "memory");
    }
    __syncwarp();
    asm volatile("barrier.cluster.arrive.relaxed.aligned;" ::: "memory");

    if (wgi == 2) {
        asm volatile("setmaxnreg.dec.sync.aligned.u32 40;");
        const int t128 = fresh_tid() & 127, w = __shfl_sync(0xffffffffu, t128 >> 5, 0), lane = t128 & 31;
        uint32_t e0[2] = {0, 0}, e1[2] = {0, 0}, cw_target = 0, kseq;
        if (w == 0) {
#pragma unroll 1
            for (int n = 0; n < NST; n++) {
                const uint32_t dst = sb + n * STAGE, fb = BAR(n);
                asm volatile(ELECT "mbarrier.arrive.expect_tx.shared::cta.b64 _, [%0], %1; }" ::"r"(fb), "r"(n < 2 ? 2 * STAGE : STAGE) : "memory");
                if (n < 2) {
                    tma3x(sb + OFF_H + n * STAGE, &maps.x, tile * 128 + n * 64, fb);
                    tma3x(dst, &maps.x, tile * 128 + n * 64 + 32, fb);
                } else {
                    if (n == 3) mbar_wait(BAR(1), 0);
                    const int ra = 112 * (n - 2);
                    tma2d(dst, &maps.qkv, 448 + 56 * sl, ra, fb);
                    tma2d(dst + HALF, &maps.qkv, 896 + 56 * sl, ra, fb);
                }
            }
            asm volatile("barrier.cluster.wait.aligned;" ::: "memory");
            kseq = ld_word(g_c1 + (sl * 8 * 16 + tile) * 32);
            cw_target = (ld_word(g_cw + sl * 32) & ~15u) + 16;
#pragma unroll 1
            for (int k = 0; k < 2; k++) {
                const int n = t128 + 32 * k;
                int m = n - 2 - (n > PACK);
                const bool packed = m >= 30 ? (m < 38 || m >= 52) : m >= 22;
                if (m >= 30) m -= 30;
                if (n == PACK) m = tile < 8 ? tile : tile + 14;
                const int rot = n < 8 ? 0 : pr;
                const int ra = 112 * kblk(rot, m & 3), rb = 112 * kblk(rot, 2 * m & 3), rc = 112 * kblk(rot, (2 * m + 1) & 3);
                int kind = 0, m0, m1, c0, c1, r0, r1;
                if (m < 4) { m0 = m1 = 1; c0 = 448 + 56 * sl; c1 = c0 + 448; r0 = r1 = ra; }
                else if (m < 8) { m0 = m1 = m < 6 ? 1 : 2; c0 = c1 = 56 * sl; r0 = rb; r1 = rc; }
                else if (m < 20) { m0 = 3; m1 = 4; c0 = c1 = 224 * sl + 32 * hr + 64 * ((m - 8) >> 2); r0 = r1 = ra; }
                else if (m < 22) { kind = 2; m0 = 5; m1 = 6; c0 = c1 = 224 * sl + (hr ? 0 : 192); r0 = rb; r1 = rc; }
                else { m0 = m1 = 7; c0 = c1 = 56 * (2 * ((pr + (m >> 1) - 10) & 3) + hr); r0 = 224 * (sl ^ (m & 1)); r1 = r0 + 112; }
                if (packed) { kind = 1; r0 = sl * 16 + (m < 8 ? m : m - 14); r1 = 0; }
                e0[0] = e0[1]; e1[0] = e1[1];
                e0[1] = kind | (m0 << 2) | (m1 << 6) | (c0 << 10) | (c1 << 21);
                e1[1] = r0 | (r1 << 16);
            }
        } else {
            const int j = t128 - 32;
            kseq = ld_word(g_c1 + (sl * 8 * 16 + tile) * 32);
            asm volatile("barrier.cluster.wait.aligned;" ::: "memory");
            uint2 wv[7];
            const int k = j < 56 ? j : 55, hh = k >= 28;
#pragma unroll
            for (int i = 0; i < 7; i++) wv[i] = __ldg(reinterpret_cast<const uint2*>(w_phi + (sl * 56 + k) * 28) + i);
#pragma unroll 1
            for (int i = j; i < 7168 / 16; i += 96) sts4(sb + OFF_WPHI + i * 16, 0, 0, 0, 0);
            bar_sync(5, 96);
            if (j < 56) {
                uint32_t a4[4];
#pragma unroll
                for (int q = 0; q < 4; q++) a4[q] = sb + OFF_WPHI + (4 * hh + q) * 128 + ((((k >> 3) ^ (4 * hh + q)) & 7) << 4) + (k & 7) * 2;
                FOR14(const uint32_t v = (t & 1) ? wv[t >> 1].y : wv[t >> 1].x;
                      asm volatile("{ .reg .b16 l, h; mov.b32 {l, h}, %2; st.shared.u16 [%0+%3], l; st.shared.u16 [%1+%3], h; }"
                                   ::"r"(a4[t >= 7 ? 2 : 0]), "r"(a4[t >= 7 ? 3 : 1]), "r"(v), "n"((t % 7) * 1024) : "memory"));
            }
            __syncwarp();
            fence_async();
            kseq = __shfl_sync(0xffffffffu, kseq, 0);
            bar_arrive(1, 224);
            bar_arrive(9, 224);
            if (w == 1 && PFP < 2) {
                mbar_wait(BAR(2), 0);
                if (PFP == 0) mbar_wait(BAR(2), 1);
                if (PFP == 1) mbar_wait(BAR(4), 0);
                const int b = blockIdx.x;
                asm volatile(ELECT "cp.async.bulk.prefetch.L2.global [%0], %1; }" ::"l"(wg + b * 6272), "r"(12544) : "memory");
                asm volatile(ELECT "cp.async.bulk.prefetch.L2.global [%0], %1; }" ::"l"(wu + b * 6272), "r"(12544) : "memory");
                asm volatile(ELECT "cp.async.bulk.prefetch.L2.global [%0], %1; }" ::"l"(wd + b * 6272), "r"(12544) : "memory");
            }
        }
        kseq = __shfl_sync(0xffffffffu, kseq, 0);
        int slot = 0, ph = 0, n = NST;
#pragma unroll 1
        for (int layer = 0; layer < 3; layer++) {
            if (w == 0) {
                const int nend = layer == 0 ? 11 : (layer == 1 ? 42 : 63);
#pragma unroll 1
                for (; n < nend; n++) {
                const uint32_t w0 = __shfl_sync(0xffffffffu, n < 32 ? e0[0] : e0[1], n & 31), w1 = __shfl_sync(0xffffffffu, n < 32 ? e1[0] : e1[1], n & 31);
                const uint32_t dst = sb + slot * STAGE, fb = BAR(n == PACK ? B_PACK : slot);
                const CUtensorMap* m0 = &maps.x + ((w0 >> 2) & 15);
                const CUtensorMap* m1 = &maps.x + ((w0 >> 6) & 15);
                const int c0 = (w0 >> 10) & 2047, c1 = w0 >> 21, r0 = w1 & 0xffff, r1 = w1 >> 16;
                if (n == 25) {
                    int it = 0;
                    uint32_t v;
                    do { asm volatile("ld.acquire.gpu.global.u32 %0, [%1];" : "=r"(v) : "l"(g_cw + sl * 32) : "memory"); } while ((int)(v - cw_target) < 0 && ++it < 0x400000);
                    asm volatile("fence.proxy.async.global;" ::: "memory");
                    __syncwarp();
                }
                mbar_wait(BAR(B_EMPTY + slot), ph);
                __syncwarp();
                asm volatile(ELECT "mbarrier.arrive.expect_tx.shared::cta.b64 _, [%0], %1; }" ::"r"(fb), "r"(STAGE) : "memory");
                if ((w0 & 3) == 0) {
                    tma2d(dst, m0, c0, r0, fb);
                    tma2d(dst + HALF, m1, c1, r1, fb);
                } else if (w0 & 1) {
                    asm volatile(ELECT "cp.async.bulk.shared::cluster.global.mbarrier::complete_tx::bytes [%0], [%1], %2, [%3]; }"
                                 ::"r"(dst), "l"(reinterpret_cast<const char*>(g_wp) + (size_t)r0 * STAGE), "r"(STAGE), "r"(fb) : "memory");
                } else {
                    tma2d(dst, m0, c0, r0, fb); tma2d(dst + 7168, m0, c0, r1, fb);
                    tma2d(dst + HALF, m1, c0, r0, fb); tma2d(dst + HALF + 7168, m1, c0, r1, fb);
                }
                if (n == PACK) asm volatile(ELECT "mbarrier.arrive.shared::cta.b64 _, [%0]; }" ::"r"(BAR(slot)) : "memory");
                if (++slot == NST) { slot = 0; ph ^= 1; }
                }
            } else if (w == 1 && layer == 1) {
                if (PFP == 2) {
                const int b = blockIdx.x;
                asm volatile(ELECT "cp.async.bulk.prefetch.L2.global [%0], %1; }" ::"l"(wg + b * 6272), "r"(12544) : "memory");
                asm volatile(ELECT "cp.async.bulk.prefetch.L2.global [%0], %1; }" ::"l"(wu + b * 6272), "r"(12544) : "memory");
                asm volatile(ELECT "cp.async.bulk.prefetch.L2.global [%0], %1; }" ::"l"(wd + b * 6272), "r"(12544) : "memory");
                }
                constexpr int ps = PACK % NST;
                mbar_wait(BAR(B_PACK), 0);
                asm volatile("{ .reg .pred e; elect.sync _|e, 0xffffffff;\n"
                             "@e cp.async.bulk.global.shared::cta.bulk_group [%0], [%1], %2;\n"
                             "@e cp.async.bulk.commit_group;\n"
                             "@e cp.async.bulk.wait_group.read 0;\n"
                             "@e mbarrier.arrive.shared::cta.b64 _, [%3], 8;\n"
                             "@e cp.async.bulk.wait_group 0;\n"
                             "@e fence.proxy.async.global;\n"
                             "@e red.release.gpu.global.add.u32 [%4], 1; }"
                             ::"l"(reinterpret_cast<char*>(g_wp) + (size_t)(sl * 16 + tile) * STAGE), "r"(sb + ps * STAGE), "r"(STAGE), "r"(BAR(B_EMPTY + ps)), "l"(g_cw + sl * 32) : "memory");
                __syncwarp();
            }
            if (layer < 2) {
            const uint32_t tag = layer ^ 1;
            kseq++;
            bar_sync(7, 384);
            ASTAMP(0);
            if (tile < 15) {
                const int sq = lane >> 3, pk = 8 * w + (lane & (tile == 14 ? 3 : 7));
                uint32_t v[16];
                if (layer == 0) poll_cnt(g_c1 + ((sl * 8 + (w >> 1) * 4 + (tile >> 2)) * 16 + (lane & 15)) * 32, kseq);
                ASTAMP(1);
                poll4_kv<32>(v, g_kv1 + ((sl * 16 + tile) * 16 + 4 * sq) * 32 + pk, tag);
#pragma unroll
                for (int k = 0; k < 4; k++) {
                    float lo = (bf_lo(v[k]) + bf_lo(v[4 + k])) + (bf_lo(v[8 + k]) + bf_lo(v[12 + k]));
                    float hi = (bf_hi(v[k]) + bf_hi(v[4 + k])) + (bf_hi(v[8 + k]) + bf_hi(v[12 + k]));
                    lo += __shfl_xor_sync(0xffffffffu, lo, 8); hi += __shfl_xor_sync(0xffffffffu, hi, 8);
                    lo += __shfl_xor_sync(0xffffffffu, lo, 16); hi += __shfl_xor_sync(0xffffffffu, hi, 16);
                    v[k] = pack2(lo, hi);
                }
                if (sq == 0) st_pkt<0>(g_kv2 + sl * 512 + 32 * tile + pk, settag(v[0], tag), v[1], v[2], v[3]);
            }
            ASTAMP(2);
            {
                const int item = t128 < 112 ? t128 : 112 + (t128 & 3), d = item >> 1;
                const int cc = t128 < 112 ? 2 * (d >= 28) + (item & 1) : item - 112;
                const int r = t128 < 112 ? d : 56 + (cc >> 1) + 2 * ((t128 - 112) >> 2);
                uint32_t ra = sb + OFF_KVB + r * 128 + 4 * cc, rx = (r & 7) << 4;
                asm volatile("" : "+r"(ra), "+r"(rx));
                FOR14(asm volatile("st.shared.u32 [%0+%2], %1;" ::"r"((ra ^ 8) + (((t & 7) << 4) ^ rx)), "r"(0), "n"((t >> 3) * 8192) : "memory"));
                uint32_t v[16];
                asm volatile("" : "+r"(ra), "+r"(rx));
                poll4_kv<8>(v, g_kv2 + sl * 512 + (item >> 3) * 32 + (item & 7), tag);
                FOR14(asm volatile("st.shared.u32 [%0+%2], %1;" ::"r"(ra + (((t & 7) << 4) ^ rx)), "r"(v[t < 7 ? t : t + 1]), "n"((t >> 3) * 8192) : "memory"));
                fence_async();
            }
            bar_arrive(3, 384);
            ASTAMP(3);
            }
        }
    } else {
        asm volatile("setmaxnreg.inc.sync.aligned.u32 232;");
        int lane = fresh_tid() & 31, prf = pr;
#define pr prf
#define g (lane >> 2)
#define c (lane & 3)
#define t128 (w * 32 + lane)
        const int wu = __shfl_sync(0xffffffffu, fresh_tid() >> 5, 0), w = wu & 3;
        const uint32_t xoff = __shfl_sync(0xffffffffu, (3 * PLANE + ((tile * 2 + wgi) * 8) * 512 + w * 128) * 16, 0);
        char* xu = reinterpret_cast<char*>(g_ex) + xoff;
#define FRESH() asm volatile("" : "+l"(xu), "+r"(lane), "+r"(prf))
#define xp0 (reinterpret_cast<uint4*>(xu) + lane)
        const uint32_t hbuf = sb + OFF_H + wgi * STAGE;
        uint32_t slot = 0, ph = 0, eb1 = 0, eb2 = 0, ackph = 0, rcvph = 0, gatph = 0, swp = 0;
        uint32_t ppid = 6;
#define cx(s) (reinterpret_cast<uint32_t*>(reinterpret_cast<uint4*>(xu) + PL(1) + 112 + (s) * 512))
#define stp (reinterpret_cast<uint4*>(xu) + g + PL(0) + 112)
        uint32_t seq = ld_word(cx(sl));
        uint32_t kseq = ld_word(g_c1 + ((sl * 8 + wu) * 16 + tile) * 32);
        uint32_t stag = ld_word(reinterpret_cast<const uint32_t*>(stp + sl * 512) + 3) & 1;
        asm volatile("barrier.cluster.wait.aligned;" ::: "memory");
        STAMP(1);
        uint32_t X[14];
        const uint32_t x0row = (w < 2 ? hbuf : sb + wgi * STAGE) + ((w & 1) * 16 + (lane & 15)) * 128;
        mbar_wait(BAR(wgi), 0);
        STAMP(51);
#pragma unroll
        for (int j = 0; j < 4; j++) {
            const int G = 7 * sl + min(2 * j + (lane >> 4), 6);
            uint32_t q2, q3;
            asm volatile("ldmatrix.sync.aligned.m8n8.x4.shared.b16 {%0,%1,%2,%3}, [%4];" : "=r"(X[4 * j]), "=r"(X[4 * j + 1]), "=r"(q2), "=r"(q3)
                         : "r"(x0row + (G >> 3) * 4096 + (((G ^ lane) & 7) << 4)) : "memory");
            if (j < 3) { X[(4 * j + 2) % 14] = q2; X[(4 * j + 3) % 14] = q3; }
        }
#define PUSH_SLICE(W)                                                                          \
    {                                                                                          \
        if (t128 == 0) mbar_expect_tx(BAR(B_RECV + wgi), 7168);                                \
        PUSH_BEGIN();                                                                          \
        const uint32_t ra = mapa(hbuf + 24576 + t128 * 16, hr ^ 1), rb = mapa(sb + OFF_XR + wgi * 3072, hr ^ 1), rbar = mapa(BAR(B_RECV + wgi), hr ^ 1); \
        st_async4(ra, W[0], W[1], W[2], W[3], rbar);                                           \
        st_async4(ra + 2048, W[4], W[5], W[6], W[7], rbar);                                    \
        st_async4(rb + t128 * 16, W[8], W[9], W[10], W[11], rbar);                             \
        asm volatile("st.async.weak.shared::cluster.mbarrier::complete_tx::bytes.v2.b32 [%0], {%1,%2}, [%3];" ::"r"(rb + 2048 + t128 * 8), "r"(W[12]), "r"(W[13]), "r"(rbar) : "memory"); \
    }
#define PULL_SLICE(W)                                                                          \
    {                                                                                          \
        uint32_t t0, t1;                                                                       \
        mbar_wait(BAR(B_RECV + wgi), rcvph);                                                   \
        rcvph ^= 1;                                                                            \
        lds4(&A[1][0], hbuf + 24576 + t128 * 16);                                              \
        lds4(&A[1][4], hbuf + 26624 + t128 * 16);                                              \
        lds4(&A[1][8], sb + OFF_XR + wgi * 3072 + t128 * 16);                                  \
        asm volatile("ld.shared.v2.u32 {%0,%1}, [%2];" : "=r"(t0), "=r"(t1) : "r"(sb + OFF_XR + wgi * 3072 + 2048 + t128 * 8) : "memory"); \
        _Pragma("unroll") for (int i = 0; i < 12; i++) A[0][i] = (i & 3) ? W[i] : W[i] & ~1u;  \
        A[1][0] &= ~1u; A[1][4] &= ~1u; A[1][8] &= ~1u;                                        \
        A[0][12] = (hr ? t0 : W[12]) & ~1u; A[0][13] = hr ? t1 : W[13];                        \
        A[1][12] = (hr ? W[12] : t0) & ~1u; A[1][13] = hr ? W[13] : t1;                        \
        asm volatile("" : RW4(A[0], 0), RW4(A[0], 4), RW4(A[0], 8), RW2(A[0], 12), RW4(A[1], 0), RW4(A[1], 4), RW4(A[1], 8), RW2(A[1], 12)); \
        swp = hr * 448;                                                                        \
    }
#define SWB(b, t, db, sh) ((b) == 0 && (t) < 6 ? ((t) < 3 ? db##p : db##m) : db)
#define DECL_DB(b, MK, lbo, sh) const uint64_t db = MK(0, lbo, R_ADJ), dbp = (b) == 0 ? MK(0, lbo, R_ADJ + (swp >> (sh))) : db, dbm = (b) == 0 ? MK(0, lbo, R_ADJ - (swp >> (sh))) : db;
#define PPB 2
#define PP_WAIT() if (wgi == 1) { bar_sync(ppid, 256); ppid ^= 14; }
#define PP_GO() if (wgi == 0) { bar_arrive(ppid, 256); ppid ^= 14; }
#define GAT_DST(B, s2) ((B) == 1 ? hbuf + w * 3584 + (s2) * 1792 : ((s2) ? sb + OFF_KVB + wgi * 8192 : hbuf + 14336) + w * 1792)
#define GAT_ISSUE(B, base)                                                                     \
    {                                                                                          \
        const char* gs = xu + ((base) + kblk(pr, B) * 1024) * 16;                              \
        asm volatile("{ .reg .pred e; elect.sync _|e, 0xffffffff;\n"                           \
                     "@e mbarrier.arrive.expect_tx.shared::cta.b64 _, [%3], 3584;\n"           \
                     "@e cp.async.bulk.shared::cluster.global.mbarrier::complete_tx::bytes [%0], [%2], 1792, [%3];\n" \
                     "@e cp.async.bulk.shared::cluster.global.mbarrier::complete_tx::bytes [%1], [%2+8192], 1792, [%3]; }" \
                     ::"r"(GAT_DST(B, 0)), "r"(GAT_DST(B, 1)), "l"(gs), "r"(BAR(B_GAT + wu * 2 + ((B) >> 1))) : "memory"); \
        __syncwarp();                                                                          \
    }
#define GAT_FETCH(B)                                                                           \
    {                                                                                          \
        mbar_wait(BAR(B_GAT + wu * 2 + ((B) >> 1)), (gatph >> (B)) & 1);                          \
        gatph ^= 1 << (B);                                                                     \
        _Pragma("unroll") for (int s2 = 0; s2 < 2; s2++) {                                     \
            const uint32_t ga = GAT_DST(B, s2) + lane * 16;                                    \
            lds4(&A[2 * (B) + s2][0], ga); lds4(&A[2 * (B) + s2][4], ga + 512); lds4(&A[2 * (B) + s2][8], ga + 1024); \
            asm volatile("ld.shared.v2.u32 {%0,%1}, [%2];" : "=r"(A[2 * (B) + s2][12]), "=r"(A[2 * (B) + s2][13]) : "r"(ga - lane * 8 + 1536) : "memory"); \
        }                                                                                      \
    }
#define LATE_ARRIVE() do { if (lane == 0) mbar_arrive(BAR(B_LATE)); } while (0)
#define LATE_WAIT() do { mbar_wait(BAR(B_LATE), gatph & 1); gatph ^= 1; } while (0)
#define PT 3
#define PREP(b, t, remote)                                                                     \
    if constexpr ((b) < 3 && (t) == PT) {                                                      \
        wg_commit();                                                                           \
        STAMP(74 + 6 * (step & 1) + 2 * (b));                                                  \
        if (remote) {                                                                          \
            if constexpr ((b) == 0) { blk_load<2>(A, BLK(xsrc, 2), lane); GAT_FETCH(1) }       \
            blk_check<((b) + 1) & 3>(A, BLK(xsrc, (b) + 1), lane, xtag);                       \
            if constexpr ((b) == 0) blk_load<3>(A, BLK(xsrc, 3), lane);                        \
        }                                                                                      \
        STAMP(75 + 6 * (step & 1) + 2 * (b));                                                  \
        normalize<((b) + 1) & 3>(A, k0, k1);                                                   \
        asm volatile("" : RW4(A[(2 * (b) + 2) & 7], 0), RW4(A[(2 * (b) + 2) & 7], 4), RW4(A[(2 * (b) + 2) & 7], 8), RW2(A[(2 * (b) + 2) & 7], 12), \
                          RW4(A[(2 * (b) + 3) & 7], 0), RW4(A[(2 * (b) + 3) & 7], 4), RW4(A[(2 * (b) + 3) & 7], 8), RW2(A[(2 * (b) + 3) & 7], 12)); \
        wg_fence();                                                                            \
    }
#define X0_BLOCK(b)                                                                            \
    { const int rr = lane & 7, hi = lane >> 4;                                                 \
    const uint32_t rowa = (w < 2 ? hbuf : sb + wgi * STAGE) + ((w & 1) * 16 + (lane & 15)) * 128; \
    FOR7(constexpr int G = 14 * (b) + (t < 3 ? 2 * t : (t < 6 ? 2 * t + 1 : 6));               \
         uint32_t q0, q1, q2, q3;                                                              \
         const uint32_t ad = t < 6 ? rowa + (((((G & 7) + hi) ^ rr) & 7) << 4) + ((G & 7) == 7 ? hi * 4096 : 0) : rowa + ((G + 7 * hi) >> 3) * 4096 + ((((G + 7 * hi) ^ rr) & 7) << 4); \
         asm volatile("ldmatrix.sync.aligned.m8n8.x4.shared.b16 {%0,%1,%2,%3}, [%4+%5];" : "=r"(q0), "=r"(q1), "=r"(q2), "=r"(q3) \
                      : "r"(ad), "n"(t < 6 ? (G >> 3) * 4096 : 0) : "memory");                 \
         if (t < 3) { A[2 * (b)][4 * t] = q0; A[2 * (b)][4 * t + 1] = q1; A[2 * (b)][4 * t + 2] = q2; A[2 * (b)][4 * t + 3] = q3; } \
         else if (t < 6) { A[2 * (b) + 1][(4 * t - 12) & 15] = q0; A[2 * (b) + 1][((4 * t - 12) & 15) + 1] = q1; A[2 * (b) + 1][((4 * t - 12) & 15) + 2] = q2; A[2 * (b) + 1][((4 * t - 12) & 15) + 3] = q3; } \
         else { A[2 * (b)][12] = q0; A[2 * (b)][13] = q1; A[2 * (b) + 1][12] = q2; A[2 * (b) + 1][13] = q3; }); }
#define BLK(base, b) ((base) + kblk(pr, b) * 1024)

#pragma unroll 1
        for (int step = 0; step < 4; step++) {
            FRESH();
            const uint32_t tag = (step >> 1) ^ 1;
            const int so = (step >> 1) * 24 + (step & 1) * 12;
            (void)so;
            uint32_t A[8][14];
            uint4* const xsrc = xp0 + ((step & 1) ? PL(2) : PL(0));
            const uint32_t xtag = (step & 1) ? tag : ((seq >> 3) & 1) ^ 1;
            uint32_t xbits;
            {
                float st[4];
                slice_stats(X, st);
                stag ^= 1;
                xbits = x_bits(X);
                tag_slice(X, xtag);
                if (step) send_slice<0>(xsrc + sl * 512, lane, X);
                if (c == 0) st_pkt<0>(stp + sl * 512, __float_as_uint(st[0]), __float_as_uint(st[1]), __float_as_uint(st[2]), settag(__float_as_uint(st[3]), stag));
            }
            STAMP(2 + so);
            uint32_t sv[8];
            if (step == 0) {
                X0_BLOCK(0) X0_BLOCK(1) X0_BLOCK(2) X0_BLOCK(3)
                mbar_wait(BAR(wgi ^ 1), 0);
                R_NEXT();
                R_NEXT();
                R_RELEASE(2);
                stat_load(sv, stp + c * 1024);
                stat_check(sv, stp + c * 1024, stag);
                STAMP(52 + step);
            } else {
                kill<14>(A[2]); kill<14>(A[3]); kill<14>(A[4]); kill<14>(A[5]); kill<14>(A[6]); kill<14>(A[7]);
                PUSH_SLICE(X)
                stat_load(sv, stp + c * 1024);
                PULL_SLICE(X)
                stat_check(sv, stp + c * 1024, stag);
                STAMP(52 + step);
                GAT_ISSUE(1, (step & 1) ? PL(2) : PL(0))
            }
            LnCoef k0, k1;
            {
                k0 = ln_coef(__uint_as_float(sv[0]) + __uint_as_float(sv[4]), __uint_as_float(sv[1]) + __uint_as_float(sv[5]));
                k1 = ln_coef(__uint_as_float(sv[2]) + __uint_as_float(sv[6]), __uint_as_float(sv[3] & ~1u) + __uint_as_float(sv[7] & ~1u));
            }
            STAMP(3 + so);
            GSTAMP(70 + step);

            if ((step & 1) == 0) {
                float tq[28];
                {
                    float av[28];
#define KV_BLOCK(b)                                                                           \
    if ((b) == 1) R_RELEASE(2);                                                               \
    if ((b) == 2) { PUSH_ACK(); wg_wait<2>(); R_RELEASE(2); }                                 \
    R_WAIT();                                                                                 \
    if ((b) == PPK) { PP_WAIT() }                                                             \
    { DECL_DB(b, BASE128, 16, 0)                                                              \
    wg_fence();                                                                               \
    FOR7(mma_rs56<1, D128(0, t)>(tq, AQ(A, b, t), (b) + t > 0, SWB(b, t, db, 0));             \
         mma_rs56<1, D128(HALF, t)>(av, AQ(A, b, t), (b) + t > 0, SWB(b, t, db, 0));          \
         PREP(b, t, step)); }                                                                 \
    wg_commit();                                                                              \
    if ((b) == 3 && PPK < 4) { PP_GO() }                                                      \
    R_NEXT();
                    normalize<0>(A, k0, k1);
                    KV_BLOCK(0) KV_BLOCK(1) KV_BLOCK(2) KV_BLOCK(3)
                    wg_wait<0>();
                    if (lane < 3) mbar_arrive(BAR(B_EMPTY + (slot + NST - 1 - lane) % NST));
                    STAMP(4 + so);
                    WSUM(80 + 7 * (step >> 1));
                    const int m = lane >> 3, rr = lane & 7;
                    const uint32_t rowa = hbuf + 16384 + (w * 16 + rr + 8 * (m & 1)) * 128;
                    const uint32_t one = c == 0 ? 0x00003f80u : 0u;
                    if (step == 0) { bar_sync(wgi ? 9 : 1, 224); }
#pragma unroll
                    for (int j = 0; j < 4; j++) {
                        const uint32_t a = rowa + (((2 * j + (m >> 1)) ^ rr) << 4);
                        if (j < 3) stsm4(a, pack2(av[8 * j], av[8 * j + 1]), pack2(av[8 * j + 2], av[8 * j + 3]), pack2(av[8 * j + 4], av[8 * j + 5]), pack2(av[8 * j + 6], av[8 * j + 7]));
                        else stsm4(a, pack2(av[24], av[25]), pack2(av[26], av[27]), one, one);
                    }
                }
                uint32_t PH[28];
                int it = 1;
#pragma unroll 1
                do {
                    float pp[28];
                    phi_gemm(tq, pp);
                    dual_softmax(pp, PH);
                    if (((trips >> (it + 1)) & 1) == 0) continue;
                    {
                        const int m = lane >> 3, rr = lane & 7;
                        const uint32_t rowa = hbuf + (w * 16 + rr + 8 * (m & 1)) * 128;
#pragma unroll
                        for (int j = 0; j < 7; j++) {
                            const int cg = 2 * j + (m >> 1), hi = cg >= 7;
                            stsm4(rowa + hi * 8192 + (((cg - 7 * hi) ^ rr) << 4), PH[4 * j], PH[4 * j + 1], PH[4 * j + 2], PH[4 * j + 3]);
                        }
                    }
                    fence_async();
                    STAMP(5 + so);
#define Q_STAGE(b0)                                                                           \
    R_WAIT();                                                                                 \
    { DECL_DB(b0, BASE128, 16, 0)                                                             \
    wg_fence();                                                                               \
    FOR7(mma_rs56<1, D128(0, t)>(tq, AQ(A, b0, t), (b0) + t > 0, SWB(b0, t, db, 0)));         \
    FOR7(mma_rs56<1, D128(HALF, t)>(tq, AQ(A, (b0) + 1, t), 1, db)); }                        \
    wg_commit();                                                                              \
    R_NEXT();
                    if (QE && wgi == 0) { kill<28>(tq); Q_STAGE(0) Q_STAGE(2) wg_wait<1>(); R_RELEASE(2); wg_wait<0>(); R_RELEASE(1); }
                    bar_sync(2, 256);
                    float kv[28];
                    const uint64_t da = BASE128(OFF_H + 16384, 16, 0), dbk = BASE128(OFF_H, 16, wgi * 512);
                    wg_fence();
                    FOR8(constexpr uint64_t o = ((t >> 2) * STAGE + (t & 3) * 2048) >> 4; mma_ss56_tt<o, o>(kv, t > 0, da, dbk));
                    wg_commit();
                    wg_wait<0>();
#pragma unroll
                    for (int hf = 0; hf < 2; hf++) {
                        const int d = 16 * w + g + 8 * hf;
                        if ((d < 56 && (d >= 28) == (c >= 2)) || d == 56) {
                            const int item = d < 56 ? 2 * d + (c & 1) : 112 + c;
                            uint4* dst = g_kv1 + ((sl * 16 + (item >> 3)) * 16 + tile) * 32 + wgi * 16 + (item & 7);
#define KVW(i) pack2(kv[4 * (i) + 2 * hf], kv[4 * (i) + 2 * hf + 1])
                            st_pkt<0>(dst, settag(KVW(0), tag), KVW(1), KVW(2), KVW(3));
                            st_pkt<8>(dst, settag(KVW(4), tag), KVW(5), KVW(6), 0u);
                        }
                    }
                    __syncwarp();
                    kseq++;
                    if (lane == 0) st_word(g_c1 + ((sl * 8 + wu) * 16 + tile) * 32, kseq);
                    bar_arrive(7, 384);
                    STAMP(6 + so);
                    if (!QE || wgi == 1) { kill<28>(tq); Q_STAGE(0) Q_STAGE(2) wg_wait<1>(); R_RELEASE(2); wg_wait<0>(); R_RELEASE(1); }
                    STAMP(7 + so);
                    kill<28>(PH);
                } while (((trips >> (++it)) & 1));
                STAMP(8 + so);
                FRESH();
                if (step) {
                    slice_load<PL(0)>(X, xp0 + sl * 512, lane);
                } else {
                    const uint32_t* xp = reinterpret_cast<const uint32_t*>(x_in + (size_t)(tile * 128 + wu * 16 + g) * 448 + 56 * sl + 2 * c);
#pragma unroll
                    for (int i = 0; i < 7; i++) { X[2 * i] = __ldg(xp + 4 * i); X[2 * i + 1] = __ldg(xp + 4 * i + 8 * 224); }
                }
                bar_sync(3, 384);
                STAMP(9 + so);
                const uint4* const osrc = xp0 + PL(1);
                {
                    float nm[32];
                    const uint64_t db = BASE128(OFF_KVB, 16, 0);
                    wg_fence();
                    FOR7(mma_rs64<0, ((t >> 2) * 8192 + (t & 3) * 32) / 16>(nm, PH[4 * t], PH[4 * t + 1], PH[4 * t + 2], PH[4 * t + 3], t > 0, db));
                    wg_commit();
                    wg_wait<0>();
                    LATE_ARRIVE();
                    const float i00 = rcp(nm[28] + 1e-6f), i01 = rcp(nm[29] + 1e-6f), i10 = rcp(nm[30] + 1e-6f), i11 = rcp(nm[31] + 1e-6f);
                    const float m0 = c >= 2 ? i01 : i00, m1 = c >= 2 ? i11 : i10;
                    uint32_t O[14];
#pragma unroll
                    for (int i = 0; i < 7; i++) {
                        const float f0 = i < 3 ? i00 : (i > 3 ? i01 : m0), f1 = i < 3 ? i10 : (i > 3 ? i11 : m1);
                        O[2 * i] = pack2(nm[4 * i] * f0, nm[4 * i + 1] * f0);
                        O[2 * i + 1] = pack2(nm[4 * i + 2] * f1, nm[4 * i + 3] * f1);
                    }
                    if (OST) { PP_WAIT() }
                    tag_slice(O, tag);
                    send_slice<PL(1)>(xp0 + sl * 512, lane, O);
                    seq++;
                    if (lane == 0) st_word(cx(sl), seq);
                    STAMP(10 + so);
                    PUSH_SLICE(O)
                    if (OST == 1) { PP_GO() }
                    const uint32_t cv = ld_word(cx(lane & 7));
                    PULL_SLICE(O)
                    LATE_WAIT();
                    check_cnt(cv, cx(lane & 7), seq);
                    if (OST == 2) { PP_GO() }
                    STAMP(56 + (step >> 1));
                    GAT_ISSUE(1, PL(1))
                    GAT_ISSUE(3, PL(1))
                    blk_load<2>(A, BLK(osrc, 2), lane);
                }
                float ao[28];
#define WO_BLOCK(b)                                                                           \
    if ((b) > 0) blk_check<b>(A, BLK(osrc, b), lane, tag);                                    \
    if (((b) & 1) == 0) R_WAIT();                                                             \
    { DECL_DB(b, BASE128, 16, 0)                                                              \
    wg_fence();                                                                               \
    FOR7(mma_rs56<1, D128(((b) & 1) * HALF, t)>(ao, AQ(A, b, t), (b) + t > 0, SWB(b, t, db, 0))); } \
    wg_commit();                                                                              \
    if ((b) & 1) R_NEXT();
                WO_BLOCK(0)
                STAMP(11 + so);
                GAT_FETCH(1)
                WO_BLOCK(1)
                WO_BLOCK(2)
                GAT_FETCH(3)
                WO_BLOCK(3)
                PUSH_ACK();
                wg_wait<0>();
                R_RELEASE(2);
                STAMP(12 + so);
                WSUM(86 + 7 * (step >> 1));
                x_fix(X, xbits);
#pragma unroll
                for (int i = 0; i < 14; i++) X[i] = pack2(bf_lo(X[i]) + ao[2 * i], bf_hi(X[i]) + ao[2 * i + 1]);
            } else {
                uint32_t H[56];
                float ag[64];
#define F1_EPI(dst, ng, ag)                                                                    \
    _Pragma("unroll") for (int i = 0; i < 2 * (ng); i++)                                       \
        (dst)[i] = pack2(geglu(ag[2 * i], ag[4 * (ng) + 2 * i]), geglu(ag[2 * i + 1], ag[4 * (ng) + 2 * i + 1]));
#define H_PUSH(h0, off) st_async4(rem_h + (off), H[h0], H[(h0) + 1], H[(h0) + 2], H[(h0) + 3], mapa(BAR(B_RECV2 + wgi), hr ^ 1));
#define F1_BLOCK(b, first)                                                                     \
    if ((first) && (b) == 1) R_RELEASE(2);                                                     \
    if ((first) && (b) == 2) PUSH_ACK();                                                       \
    R_WAIT();                                                                                  \
    if ((b) == ((first) ? PPF : PPB)) { PP_WAIT() }                                            \
    { DECL_DB(b, BASE128, HALF, 0)                                                             \
    wg_fence();                                                                                \
    FOR7(mma_rs128<1, D128(0, t)>(ag, AQ(A, b, t), (b) + t > 0, SWB(b, t, db, 0));             \
         if constexpr (first) { PREP(b, t, true) }); }                                         \
    wg_commit();                                                                               \
    if ((b) == 3) { PP_GO() }                                                                  \
    if ((b) > 0) { wg_wait<1>(); R_RELEASE(1); }       \
    R_NEXT();
                normalize<0>(A, k0, k1);
                F1_BLOCK(0, true) F1_BLOCK(1, true) F1_BLOCK(2, true) F1_BLOCK(3, true)
                if (t128 == 0) { mbar_expect_tx(BAR(B_RECV + wgi), 16384); mbar_expect_tx(BAR(B_RECV2 + wgi), 12288); }
                PUSH_BEGIN();
                wg_wait<0>();
                R_RELEASE(1);
                int p = 0;
#pragma unroll 1
                do {
                    F1_EPI(H + 32, 8, ag)
                    STAMP(4 + p + so);
                    WSUM(81 + p + 7 * (step >> 1));
                    if (((trips >> (p + 1)) & 1) == 0) continue;
                    if (step == 1 && p == PKP) R_NEXT();
                    kill<64>(ag);
                    F1_BLOCK(0, false)
                    {
                        const uint32_t pk = (p ? hbuf + 16384 : sb + OFF_KVB + wgi * 8192) + w * 2048;
#pragma unroll
                        for (int k = 0; k < 4; k++) sts4(pk + k * 512 + lane * 16, H[32 + 4 * k], H[33 + 4 * k], H[34 + 4 * k], H[35 + 4 * k]);
                        fence_async();
                        __syncwarp();
                        asm volatile(ELECT "cp.async.bulk.shared::cluster.shared::cta.mbarrier::complete_tx::bytes [%0], [%1], 2048, [%2]; }"
                                     ::"r"(mapa(hbuf + p * 8192 + w * 2048, hr ^ 1)), "r"(pk), "r"(mapa(BAR(B_RECV + wgi), hr ^ 1)) : "memory");
                    }
                    F1_BLOCK(1, false) F1_BLOCK(2, false) F1_BLOCK(3, false)
                    wg_wait<0>();
                    R_RELEASE(1);
                    kill<16>(H + 32);
                } while (((trips >> (++p)) & 1));
#pragma unroll
                for (int k = 0; k < 4; k++) lds4(H + 16 + 4 * k, hbuf + 16384 + w * 2048 + k * 512 + lane * 16);
                __syncwarp();
                if (lane == 0) asm volatile("mbarrier.arrive.shared::cluster.b64 _, [%0];" ::"r"(mapa(BAR(B_ACK2 + wgi), hr ^ 1)) : "memory");
                const uint32_t rem_h = mapa(hbuf + w * 2048 + lane * 16, hr ^ 1);
#define F1_LAST(b0)                                                                            \
    R_WAIT();                                                                                  \
    if (b0) { PP_WAIT() }                                                                      \
    { DECL_DB(b0, BASE64, HALF, 1)                                                             \
    wg_fence();                                                                                \
    FOR7(mma_rs64<1, D64(0, t)>(al, AQ(A, b0, t), (b0) + t > 0, SWB(b0, t, db, 1)));           \
    FOR7(mma_rs64<1, D64(7168, t)>(al, AQ(A, (b0) + 1, t), 1, db)); }                          \
    wg_commit();                                                                               \
    if (b0) { PP_GO() }                                                                        \
    R_NEXT();
                float al[32];
                F1_LAST(0)
                mbar_wait(BAR(B_RECV + wgi), rcvph);
                rcvph ^= 1;
                mbar_wait(BAR(B_ACK2 + wgi), step >> 1);
                H_PUSH(32, 16384) H_PUSH(36, 16896)
                F1_LAST(2)
                H_PUSH(40, 17408) H_PUSH(44, 17920)
                wg_wait<1>();
                R_RELEASE(2);
                wg_wait<0>();
                R_RELEASE(1);
                uint32_t HP[56];
#pragma unroll
                for (int k = 0; k < 4; k++) lds4(H + 4 * k, sb + OFF_KVB + wgi * 8192 + w * 2048 + k * 512 + lane * 16);
#pragma unroll
                for (int t = 0; t < 8; t++) lds4(HP + 4 * t, hbuf + (t >> 2) * 8192 + w * 2048 + (t & 3) * 512 + lane * 16);
                F1_EPI(H + 48, 4, al)
                H_PUSH(48, 24576 - w * 1024) H_PUSH(52, 25088 - w * 1024)
                STAMP(7 + so);
                WSUM(84 + 7 * (step >> 1));
                FRESH();
                float acc[28];
                const uint32_t roA = hr ? 256u : 0u, roB = hr ? (uint32_t)-1536 : 0u;
                const uint32_t rpA = hr ? 0u : 256u, rpB = hr ? 0u : (uint32_t)-1536;
                float res[28];
                uint32_t v0[14], v1[14], P[14];
                const uint4* ps = xp0 + sl * 512;
#define F2_OWN_A()                                                                             \
    R_WAIT();                                                                                  \
    d0 = BASE128(0, 16, R_ADJ + roA); d1 = BASE128(0, 16, R_ADJ + roB);                        \
    wg_fence();                                                                                \
    FOR14(if constexpr (t < OT) mma_rs56<1, t * 128>(acc, H[4 * t], H[4 * t + 1], H[4 * t + 2], H[4 * t + 3], t > 0, d0)); \
    wg_commit();
#define F2_OWN_B()                                                                             \
    wg_fence();                                                                                \
    FOR14(if constexpr (t >= OT) mma_rs56<1, t * 128>(acc, H[4 * t], H[4 * t + 1], H[4 * t + 2], H[4 * t + 3], 1, t < 12 ? d0 : d1)); \
    wg_commit();                                                                               \
    R_NEXT();
#define F2_PEER()                                                                              \
    R_WAIT();                                                                                  \
    if (F2PP) { PP_WAIT() }                                                                    \
    d0 = BASE128(0, 16, R_ADJ + rpA); d1 = BASE128(0, 16, R_ADJ + rpB);                        \
    wg_fence();                                                                                \
    FOR14(mma_rs56<1, t * 128>(acc, HP[4 * t], HP[4 * t + 1], HP[4 * t + 2], HP[4 * t + 3], 1, t < 12 ? d0 : d1)); \
    wg_commit();                                                                               \
    if (F2PP) { PP_GO() }                                                                      \
    R_NEXT();
#define F2_TURN(u)                                                                             \
    wg_wait<1>();                                                                              \
    if ((u) < 2 || TDEF < 2) R_RELEASE(2);                                                     \
    wg_wait<0>();                                                                              \
    if ((u) < 2 || TDEF < 1) R_RELEASE(1);                                                     \
    _Pragma("unroll") for (int i = 0; i < 14; i++) P[i] = pack2(acc[2 * i], acc[2 * i + 1]);   \
    tag_slice(P, tag);                                                                         \
    asm volatile("" : RW4(P, 0), RW4(P, 4), RW4(P, 8), RW2(P, 12));                            \
    kill<28>(acc);                                                                             \
    F2_OWN_A()                                                                                 \
    if ((u) == 2) { slice_load<PL(3)>(v0, ps, lane); slice_load<PL(4)>(v1, ps, lane); } \
    send_slice<PL(3 + (u))>(xp0 + (2 * ((pr + (u) + 1) & 3) + hr) * 512, lane, P);             \
    seq++;                                                                                     \
    if (lane == 0) st_word(cx(sl), seq);                                                       \
    __syncwarp();                                                                              \
    STAMP(8 + (u) + so);                                                                       \
    F2_OWN_B()
                uint64_t d0, d1;
                F2_OWN_A()
                F2_OWN_B()
                R_WAIT();
                d0 = BASE128(0, 16, R_ADJ + rpA); d1 = BASE128(0, 16, R_ADJ + rpB);
                wg_fence();
                FOR8(mma_rs56<1, t * 128>(acc, HP[4 * t], HP[4 * t + 1], HP[4 * t + 2], HP[4 * t + 3], 1, d0));
                wg_commit();
                mbar_wait(BAR(B_RECV2 + wgi), step >> 1);
#pragma unroll
                for (int k = 0; k < 4; k++) lds4(HP + 32 + 4 * k, hbuf + 16384 + w * 2048 + k * 512 + lane * 16);
                lds4(HP + 48, hbuf + 24576 + w * 1024 + lane * 16);
                lds4(HP + 52, hbuf + 25088 + w * 1024 + lane * 16);
                if (step == 1) PUSH_ACK();
                wg_fence();
                FOR14(if constexpr (t >= 8) mma_rs56<1, t * 128>(acc, HP[4 * t], HP[4 * t + 1], HP[4 * t + 2], HP[4 * t + 3], 1, t < 12 ? d0 : d1));
                wg_commit();
                R_NEXT();
                F2_TURN(0)
                F2_PEER()
                F2_TURN(1)
                F2_PEER()
                F2_TURN(2)
                if (step == 1) STAMP(64);
                slice_check<PL(3)>(v0, ps, lane, tag);
                slice_check<PL(4)>(v1, ps, lane, tag);
#pragma unroll
                for (int i = 0; i < 14; i++) { res[2 * i] = bf_lo(v0[i]) + bf_lo(v1[i]); res[2 * i + 1] = bf_hi(v0[i]) + bf_hi(v1[i]); }
                slice_load<PL(2)>(X, ps, lane);
                if (step == 1) STAMP(65);
                F2_PEER()
                if (step == 1) STAMP(66);
                poll_cnt(cx(2 * ((pr + 1) & 3) + hr), seq);
                if (step == 1) STAMP(67);
                slice_load<PL(5)>(v0, ps, lane);
                x_fix(X, xbits);
                slice_check<PL(5)>(v0, ps, lane, tag);
                if (lane < TDEF) mbar_arrive(BAR(B_EMPTY + (slot + NST - 3 - lane) % NST));
#pragma unroll
                for (int i = 0; i < 14; i++) { res[2 * i] += bf_lo(v0[i]); res[2 * i + 1] += bf_hi(v0[i]); }
                STAMP(11 + so);
                wg_wait<0>();
                R_RELEASE(2);
                STAMP(12 + so);
                WSUM(85 + 7 * (step >> 1));
#pragma unroll
                for (int i = 0; i < 14; i++) X[i] = pack2(fmaf(res[2 * i] + acc[2 * i], 0.5f, bf_lo(X[i])), fmaf(res[2 * i + 1] + acc[2 * i + 1], 0.5f, bf_hi(X[i])));
            }
        }
        {
            const int m = lane >> 3, rr = lane & 7;
            const uint32_t ob = hbuf + w * 2048, rowa = ob + (rr + 8 * (m & 1)) * 112 + (m >> 1) * 16;
#pragma unroll
            for (int j = 0; j < 3; j++) stsm4(rowa + 32 * j, X[4 * j], X[4 * j + 1], X[4 * j + 2], X[4 * j + 3]);
            asm volatile("stmatrix.sync.aligned.m8n8.x2.shared.b16 [%0], {%1,%2};" ::"r"(ob + (rr + 8 * (m & 1)) * 112 + 96), "r"(X[12]), "r"(X[13]) : "memory");
            fence_async();
            __syncwarp();
            if (lane == 0) {
                asm volatile("cp.async.bulk.tensor.2d.global.shared::cta.bulk_group [%0, {%2, %3}], [%1];" ::"l"(&maps.out), "r"(ob), "r"(56 * sl), "r"(tile * 128 + wu * 16) : "memory");
                asm volatile("cp.async.bulk.commit_group;" ::: "memory");
                asm volatile("cp.async.bulk.wait_group.read 0;" ::: "memory");
            }
        }
        STAMP(50);
        GSTAMP(61);
        PDUMP();
    }
}

#undef g
#undef pr
#undef c
#undef t128

typedef CUresult (*EncodeFn)(CUtensorMap*, CUtensorMapDataType, cuuint32_t, void*, const cuuint64_t*, const cuuint64_t*, const cuuint32_t*,
                             const cuuint32_t*, CUtensorMapInterleave, CUtensorMapSwizzle, CUtensorMapL2promotion, CUtensorMapFloatOOBfill);

static void make_map(EncodeFn enc, CUtensorMap* m, const void* p, uint64_t cols, uint64_t rows, uint32_t bc, uint32_t br, CUtensorMapSwizzle sw) {
    cuuint64_t gd[2] = {cols, rows};
    cuuint64_t gs[1] = {cols * 2};
    cuuint32_t bd[2] = {bc, br};
    cuuint32_t es[2] = {1, 1};
    enc(m, CU_TENSOR_MAP_DATA_TYPE_BFLOAT16, 2, const_cast<void*>(p), gd, gs, bd, es, CU_TENSOR_MAP_INTERLEAVE_NONE, sw,
        CU_TENSOR_MAP_L2_PROMOTION_L2_128B, CU_TENSOR_MAP_FLOAT_OOB_FILL_NONE);
}

extern "C" void kernel_launch(void* const* d_in, const int* in_sizes, int n_in, void* d_out, int out_size) {
    (void)in_sizes; (void)n_in; (void)out_size;
    static EncodeFn enc = nullptr;
    static Scratch* scratch = nullptr;
    if (!enc) {
        void* fn = nullptr;
        cudaDriverEntryPointQueryResult qr;
        cudaGetDriverEntryPoint("cuTensorMapEncodeTiled", &fn, cudaEnableDefault, &qr);
        enc = (EncodeFn)fn;
        cudaGetSymbolAddress((void**)&scratch, g_scratch);
        cudaFuncSetAttribute(fused_kernel, cudaFuncAttributeMaxDynamicSharedMemorySize, SMEM_BYTES);
    }
    Maps maps;
    {
        cuuint64_t gd[3] = {64, 2048, 7};
        cuuint64_t gs[2] = {896, 128};
        cuuint32_t bd[3] = {64, 32, 7};
        cuuint32_t es[3] = {1, 1, 1};
        enc(&maps.x, CU_TENSOR_MAP_DATA_TYPE_BFLOAT16, 3, d_in[0], gd, gs, bd, es, CU_TENSOR_MAP_INTERLEAVE_NONE, CU_TENSOR_MAP_SWIZZLE_128B,
            CU_TENSOR_MAP_L2_PROMOTION_L2_128B, CU_TENSOR_MAP_FLOAT_OOB_FILL_NONE);
    }
    make_map(enc, &maps.out, d_out, 448, 2048, 56, 16, CU_TENSOR_MAP_SWIZZLE_NONE);
    make_map(enc, &maps.qkv, d_in[1], 1344, 448, 64, 112, CU_TENSOR_MAP_SWIZZLE_128B);
    make_map(enc, &maps.wo, d_in[3], 448, 448, 64, 112, CU_TENSOR_MAP_SWIZZLE_128B);
    make_map(enc, &maps.wg, d_in[5], 1792, 448, 64, 112, CU_TENSOR_MAP_SWIZZLE_128B);
    make_map(enc, &maps.wu, d_in[6], 1792, 448, 64, 112, CU_TENSOR_MAP_SWIZZLE_128B);
    make_map(enc, &maps.wg32, d_in[5], 1792, 448, 32, 112, CU_TENSOR_MAP_SWIZZLE_64B);
    make_map(enc, &maps.wu32, d_in[6], 1792, 448, 32, 112, CU_TENSOR_MAP_SWIZZLE_64B);
    make_map(enc, &maps.wd, d_in[7], 448, 1792, 64, 112, CU_TENSOR_MAP_SWIZZLE_128B);
    fused_kernel<<<128, 384, SMEM_BYTES>>>(scratch, (const __nv_bfloat16*)d_in[0], (const __nv_bfloat16*)d_in[2], 7, (const __nv_bfloat16*)d_in[5],
                                           (const __nv_bfloat16*)d_in[6], (const __nv_bfloat16*)d_in[7], maps);
}
```

```cpp
#include <cuda_runtime.h>
#include <cuda.h>
#include <cuda_bf16.h>
#include <stdint.h>
#include <type_traits>

#define PPF 2
#define PKP 0
#define TDEF 1
#define TMPF 0
#define NORM1 0
#define LPARK 1
#define PFN 9
#define ACAN 0
#define SPLIT0 1
#define OT 2
#define F2PP 0
#define PPK 2
#define QE 1
#define OST 1
#define PP

namespace {

constexpr uint32_t STAGE = 28672, HALF = 14336;
constexpr int NST = 5;
constexpr uint32_t OFF_H = NST * STAGE;
constexpr uint32_t OFF_KVB = OFF_H + 2 * STAGE;
constexpr uint32_t OFF_WPHI = OFF_KVB + 16384;
constexpr uint32_t OFF_XR = OFF_WPHI + 7168;
constexpr uint32_t OFF_BAR = OFF_XR + 6144;
constexpr uint32_t SMEM_BYTES = OFF_BAR + 384 + 1408;
constexpr int B_EMPTY = NST, B_RECV = 2 * NST, B_RECV2 = B_RECV + 2, B_PACK = B_RECV2 + 2, B_GAT = B_PACK + 1, B_LATE = B_GAT + 16, B_ACK = B_LATE + 1, B_ACK2 = B_ACK + 2, B_COUNT = B_ACK2 + 2;

constexpr int PACK = 14 + 4 * PKP;

struct Maps { CUtensorMap x, qkv, wo, wg, wu, wg32, wu32, wd, out; };

}

constexpr int PLANE = 16 * 2 * 8 * 512;
struct Scratch {
    uint4 ex[6 * PLANE];
    uint4 kv1[8 * 16 * 16 * 32];
    uint4 kv2[8 * 512];
    uint32_t c1[8 * 8 * 16 * 32];
    uint32_t cw[8 * 32];
    uint4 wp[8 * 32 * (HALF / 16)];
};
__device__ __align__(1024) Scratch g_scratch;
#define g_ex (sc->ex)
#define g_kv1 (sc->kv1)
#define g_kv2 (sc->kv2)
#define g_c1 (sc->c1)
#define g_cw (sc->cw)
#define g_wp (sc->wp)
#define STAMP(i)
#define GSTAMP(i)
#define PDUMP()
#define ASTAMP(i)

namespace {

__device__ __forceinline__ int fresh_tid() { int t; asm volatile("mov.u32 %0, %%tid.x;" : "=r"(t)); return t; }
template <int N> __device__ __forceinline__ void kill(uint32_t* v) {
#pragma unroll
    for (int i = 0; i < N; i++) v[i] = 0;
}
template <int N> __device__ __forceinline__ void kill(float* v) {
#pragma unroll
    for (int i = 0; i < N; i++) v[i] = 0.f;
}
__device__ __forceinline__ uint32_t s2u(const void* p) { return (uint32_t)__cvta_generic_to_shared(p); }
__device__ __forceinline__ void mbar_init(uint32_t a, uint32_t c) { asm volatile("mbarrier.init.shared::cta.b64 [%0], %1;" ::"r"(a), "r"(c) : "memory"); }
__device__ __forceinline__ void mbar_expect_tx(uint32_t a, uint32_t b) { asm volatile("mbarrier.arrive.expect_tx.shared::cta.b64 _, [%0], %1;" ::"r"(a), "r"(b) : "memory"); }
__device__ __forceinline__ void mbar_arrive(uint32_t a) { asm volatile("mbarrier.arrive.shared::cta.b64 _, [%0];" ::"r"(a) : "memory"); }
#define GIVE_UP(id) "trap;\n"
#define SPIN_MAX "0x400000"
#define SPIN_TAIL(id) "add.u32 n, n, 1;\n setp.lt.u32 p, n, " SPIN_MAX ";\n @p bra.uni LP;\n" GIVE_UP(id) " DN:\n }"
__device__ __forceinline__ void mbar_wait(uint32_t a, uint32_t ph) {
    asm volatile("{ .reg .pred p; .reg .b32 n; mov.u32 n, 0;\n LP:\n"
                 "mbarrier.try_wait.parity.shared::cta.b64 p, [%0], %1;\n @p bra DN;\n"
                 "add.u32 n, n, 1;\n setp.lt.u32 p, n, " SPIN_MAX ";\n @p bra LP;\n"
                 GIVE_UP("")
                 " DN:\n }" ::"r"(a), "r"(ph) : "memory");
}
#define ELECT "{ .reg .pred e; elect.sync _|e, 0xffffffff; @e "
__device__ __forceinline__ void tma2d(uint32_t dst, const CUtensorMap* m, int c0, int c1, uint32_t bar) {
    asm volatile(ELECT "cp.async.bulk.tensor.2d.shared::cluster.global.mbarrier::complete_tx::bytes [%0], [%1, {%3, %4}], [%2]; }" ::"r"(dst), "l"(m), "r"(bar), "r"(c0), "r"(c1) : "memory");
}
__device__ __forceinline__ void tma3x(uint32_t dst, const CUtensorMap* m, int row, uint32_t bar) {
    asm volatile(ELECT "cp.async.bulk.tensor.3d.shared::cluster.global.mbarrier::complete_tx::bytes [%0], [%1, {0, %3, 0}], [%2]; }" ::"r"(dst), "l"(m), "r"(bar), "r"(row) : "memory");
}
template <int OFF>
__device__ __forceinline__ void ld_pkt(uint32_t* v, const uint4* p) {
    asm volatile("{ .reg .b128 t; ld.relaxed.gpu.global.b128 t, [%4+%5]; mov.b128 {%0,%1,%2,%3}, t; }" : "=r"(v[0]), "=r"(v[1]), "=r"(v[2]), "=r"(v[3]) : "l"(p), "n"(OFF * 16) : "memory");
}
template <int OFF>
__device__ __forceinline__ void st_pkt(uint4* p, uint32_t a, uint32_t b, uint32_t c, uint32_t d) {
    asm volatile("{ .reg .b128 t; mov.b128 t, {%1,%2,%3,%4}; st.relaxed.gpu.global.b128 [%0+%5], t; }" ::"l"(p), "r"(a), "r"(b), "r"(c), "r"(d), "n"(OFF * 16) : "memory");
}
__device__ __forceinline__ uint32_t pack2(float lo, float hi) {
    uint32_t r;
    asm("cvt.rn.bf16x2.f32 %0, %1, %2;" : "=r"(r) : "f"(hi), "f"(lo));
    return r;
}
__device__ __forceinline__ float bf_lo(uint32_t w) { return __uint_as_float(w << 16); }
__device__ __forceinline__ float bf_hi(uint32_t w) { return __uint_as_float(w & 0xffff0000u); }
__device__ __forceinline__ uint32_t settag(uint32_t w, uint32_t tag) { return (w & ~1u) | tag; }
__device__ __forceinline__ float ex2(float x) { float y; asm("ex2.approx.ftz.f32 %0, %1;" : "=f"(y) : "f"(x)); return y; }
__device__ __forceinline__ float rcp(float x) { float y; asm("rcp.approx.ftz.f32 %0, %1;" : "=f"(y) : "f"(x)); return y; }
__device__ __forceinline__ float tanh_hw(float x) { float y; asm("tanh.approx.f32 %0, %1;" : "=f"(y) : "f"(x)); return y; }
__device__ __forceinline__ void stsm4(uint32_t addr, uint32_t a, uint32_t b, uint32_t c, uint32_t d) {
    asm volatile("stmatrix.sync.aligned.m8n8.x4.shared.b16 [%0], {%1,%2,%3,%4};" ::"r"(addr), "r"(a), "r"(b), "r"(c), "r"(d) : "memory");
}
__device__ __forceinline__ void fence_async() { asm volatile("fence.proxy.async.shared::cta;" ::: "memory"); }
__device__ __forceinline__ void bar_sync(int id, int n) { asm volatile("bar.sync %0, %1;" ::"r"(id), "r"(n) : "memory"); }
__device__ __forceinline__ void bar_arrive(int id, int n) { asm volatile("bar.arrive %0, %1;" ::"r"(id), "r"(n) : "memory"); }
__device__ __forceinline__ void wg_fence() { asm volatile("wgmma.fence.sync.aligned;" ::: "memory"); }
__device__ __forceinline__ void wg_commit() { asm volatile("wgmma.commit_group.sync.aligned;" ::: "memory"); }
template <int N> __device__ __forceinline__ void wg_wait() { asm volatile("wgmma.wait_group.sync.aligned %0;" ::"n"(N) : "memory"); }

constexpr uint32_t SB0 = 1024;
__host__ __device__ constexpr uint32_t dlo(uint32_t off, uint32_t lbo) { return ((SB0 + off) >> 4) | ((lbo >> 4) << 16); }
__host__ __device__ constexpr uint32_t dhi(uint32_t sbo, uint32_t sw) { return (sbo >> 4) | (sw << 30); }
__device__ __forceinline__ uint64_t dbase(uint32_t lo, uint32_t hi) { uint64_t d; asm volatile("mov.b64 %0, {%1, %2};" : "=l"(d) : "r"(lo), "r"(hi)); return d; }
#define BASE128(off, lbo, adj) dbase(dlo(off, lbo) + (adj), dhi(1024, 1))
#define BASE64(off, lbo, adj) dbase(dlo(off, lbo) + (adj), dhi(512, 2))

#define ACC4(d, o) "+f"(d[o]), "+f"(d[o + 1]), "+f"(d[o + 2]), "+f"(d[o + 3])
#define ACC28(d) ACC4(d, 0), ACC4(d, 4), ACC4(d, 8), ACC4(d, 12), ACC4(d, 16), ACC4(d, 20), ACC4(d, 24)
#define ACC32(d, o) ACC4(d, o), ACC4(d, o + 4), ACC4(d, o + 8), ACC4(d, o + 12), ACC4(d, o + 16), ACC4(d, o + 20), ACC4(d, o + 24), ACC4(d, o + 28)

template <int TB, uint64_t D>
__device__ __forceinline__ void mma_rs56(float* d, uint32_t a0, uint32_t a1, uint32_t a2, uint32_t a3, int sd, uint64_t base) {
    asm volatile("{ .reg .pred p; .reg .b64 db; setp.ne.b32 p, %32, 0; add.u64 db, %33, %34;\n"
                 "wgmma.mma_async.sync.aligned.m64n56k16.f32.bf16.bf16 "
                 "{%0,%1,%2,%3,%4,%5,%6,%7,%8,%9,%10,%11,%12,%13,%14,%15,%16,%17,%18,%19,%20,%21,%22,%23,%24,%25,%26,%27}, "
                 "{%28,%29,%30,%31}, db, p, 1, 1, %35; }\n"
                 : ACC28(d)
                 : "r"(a0), "r"(a1), "r"(a2), "r"(a3), "r"(sd), "l"(base), "n"(D), "n"(TB));
}
template <int TB, uint64_t D>
__device__ __forceinline__ void mma_rs64(float* d, uint32_t a0, uint32_t a1, uint32_t a2, uint32_t a3, int sd, uint64_t base) {
    asm volatile("{ .reg .pred p; .reg .b64 db; setp.ne.b32 p, %36, 0; add.u64 db, %37, %38;\n"
                 "wgmma.mma_async.sync.aligned.m64n64k16.f32.bf16.bf16 "
                 "{%0,%1,%2,%3,%4,%5,%6,%7,%8,%9,%10,%11,%12,%13,%14,%15,%16,%17,%18,%19,%20,%21,%22,%23,%24,%25,%26,%27,%28,%29,%30,%31}, "
                 "{%32,%33,%34,%35}, db, p, 1, 1, %39; }\n"
                 : ACC32(d, 0)
                 : "r"(a0), "r"(a1), "r"(a2), "r"(a3), "r"(sd), "l"(base), "n"(D), "n"(TB));
}
template <int TB, uint64_t D>
__device__ __forceinline__ void mma_rs128(float* d, uint32_t a0, uint32_t a1, uint32_t a2, uint32_t a3, int sd, uint64_t base) {
    asm volatile("{ .reg .pred p; .reg .b64 db; setp.ne.b32 p, %68, 0; add.u64 db, %69, %70;\n"
                 "wgmma.mma_async.sync.aligned.m64n128k16.f32.bf16.bf16 "
                 "{%0,%1,%2,%3,%4,%5,%6,%7,%8,%9,%10,%11,%12,%13,%14,%15,%16,%17,%18,%19,%20,%21,%22,%23,%24,%25,%26,%27,%28,%29,%30,%31,%32,%33,%34,%35,%36,%37,%38,%39,%40,%41,%42,%43,%44,%45,%46,%47,%48,%49,%50,%51,%52,%53,%54,%55,%56,%57,%58,%59,%60,%61,%62,%63}, "
                 "{%64,%65,%66,%67}, db, p, 1, 1, %71; }\n"
                 : ACC32(d, 0), ACC32(d, 32)
                 : "r"(a0), "r"(a1), "r"(a2), "r"(a3), "r"(sd), "l"(base), "n"(D), "n"(TB));
}
template <uint64_t DA, uint64_t DB>
__device__ __forceinline__ void mma_ss56_tt(float* d, int sd, uint64_t ba, uint64_t bb) {
    asm volatile("{ .reg .pred p; .reg .b64 da, db; setp.ne.b32 p, %28, 0; add.u64 da, %29, %31; add.u64 db, %30, %32;\n"
                 "wgmma.mma_async.sync.aligned.m64n56k16.f32.bf16.bf16 "
                 "{%0,%1,%2,%3,%4,%5,%6,%7,%8,%9,%10,%11,%12,%13,%14,%15,%16,%17,%18,%19,%20,%21,%22,%23,%24,%25,%26,%27}, "
                 "da, db, p, 1, 1, 1, 1; }\n"
                 : ACC28(d)
                 : "r"(sd), "l"(ba), "l"(bb), "n"(DA), "n"(DB));
}
template <int... I> struct Seq {};
template <class F, int... I> __device__ __forceinline__ void static_for_impl(F&& f, Seq<I...>) { (f(std::integral_constant<int, I>{}), ...); }
#define FOR7(...) static_for_impl([&](auto T_) { constexpr int t = decltype(T_)::value; __VA_ARGS__; }, Seq<0, 1, 2, 3, 4, 5, 6>{})
#define FOR8(...) static_for_impl([&](auto T_) { constexpr int t = decltype(T_)::value; __VA_ARGS__; }, Seq<0, 1, 2, 3, 4, 5, 6, 7>{})
#define FOR14(...) static_for_impl([&](auto T_) { constexpr int t = decltype(T_)::value; __VA_ARGS__; }, Seq<0, 1, 2, 3, 4, 5, 6, 7, 8, 9, 10, 11, 12, 13>{})

__device__ __forceinline__ int kblk(int p, int b) { return b == 0 ? p : b - (b <= p); }
__host__ __device__ constexpr int krow(int t) { return t < 3 ? 16 * t : (t < 6 ? 56 + 16 * (t - 3) : 48); }
#define AQ(A, b, t) ((t) < 3 ? A[2 * (b)][4 * (t)] : (t) < 6 ? A[2 * (b) + 1][4 * ((t) - 3)] : A[2 * (b)][12]), \
                    ((t) < 3 ? A[2 * (b)][4 * (t) + 1] : (t) < 6 ? A[2 * (b) + 1][4 * ((t) - 3) + 1] : A[2 * (b)][13]), \
                    ((t) < 3 ? A[2 * (b)][4 * (t) + 2] : (t) < 6 ? A[2 * (b) + 1][4 * ((t) - 3) + 2] : A[2 * (b) + 1][12]), \
                    ((t) < 3 ? A[2 * (b)][4 * (t) + 3] : (t) < 6 ? A[2 * (b) + 1][4 * ((t) - 3) + 3] : A[2 * (b) + 1][13])
#define D128(off, t) ((uint64_t)(((off) + krow(t) * 128) >> 4) + ((uint64_t)((t) == 6 ? (7168 - 1024) >> 4 : 0) << 32))
#define D64(off, t) ((uint64_t)(((off) + krow(t) * 64) >> 4) + ((uint64_t)((t) == 6 ? (3584 - 512) >> 4 : 0) << 32))

#define PL(k) (((k) - 3) * PLANE)
__device__ __forceinline__ void st_word(uint32_t* p, uint32_t v) { asm volatile("st.relaxed.gpu.global.u32 [%0], %1;" ::"l"(p), "r"(v) : "memory"); }
__device__ __forceinline__ uint32_t ld_word(const uint32_t* p) { uint32_t v; asm volatile("ld.relaxed.gpu.global.u32 %0, [%1];" : "=r"(v) : "l"(p) : "memory"); return v; }
__device__ __forceinline__ void tag_slice(uint32_t* w, uint32_t tag) { w[0] = settag(w[0], tag); w[4] = settag(w[4], tag); w[8] = settag(w[8], tag); w[12] = settag(w[12], tag); }
template <int O>
__device__ __forceinline__ void send_slice(uint4* dst, int lane, const uint32_t* w) {
    st_pkt<O>(dst, w[0], w[1], w[2], w[3]);
    st_pkt<O + 32>(dst, w[4], w[5], w[6], w[7]);
    st_pkt<O + 64>(dst, w[8], w[9], w[10], w[11]);
    asm volatile("{ .reg .b64 t; mov.b64 t, {%1,%2}; st.relaxed.gpu.global.b64 [%0+%3], t; }" ::"l"((char*)dst - lane * 8), "r"(w[12]), "r"(w[13]), "n"(16 * (O + 96)) : "memory");
}
#define RW4(v, o) "+r"(v[o]), "+r"(v[(o) + 1]), "+r"(v[(o) + 2]), "+r"(v[(o) + 3])
#define RW2(v, o) "+r"(v[o]), "+r"(v[(o) + 1])
#define WR4(v, o) "=&r"(v[o]), "=&r"(v[(o) + 1]), "=&r"(v[(o) + 2]), "=&r"(v[(o) + 3])
#define LDP(a, b, c, d, addr, off) "ld.relaxed.gpu.global.b128 q, [" addr "+" off "];\n mov.b128 {" a "," b "," c "," d "}, q;\n"
#define LDH(a, b, addr, off) "ld.relaxed.gpu.global.b64 h, [" addr "+" off "];\n mov.b64 {" a "," b "}, h;\n"
#define VOTE_OK "and.b32 t, t, 1;\n setp.ne.u32 p, t, 0;\n vote.sync.any.pred p, p, 0xffffffff;\n @!p bra.uni DN;\n"
#define CHK(x, tag) "lop3.b32 t, " x ", " tag ", t, 0xBE;\n"
__device__ __forceinline__ void check_cnt(uint32_t v, const uint32_t* p, uint32_t target) {
    asm volatile("{ .reg .pred p; .reg .b32 n, t; mov.u32 n, 0; mov.u32 t, %2;\n LP:\n"
                 "sub.s32 t, t, %1;\n setp.lt.s32 p, t, 0;\n vote.sync.any.pred p, p, 0xffffffff;\n @!p bra.uni DN;\n ld.relaxed.gpu.global.u32 t, [%0];\n" SPIN_TAIL("7")
                 ::"l"(p), "r"(target), "r"(v) : "memory");
}
__device__ __forceinline__ void poll_cnt(const uint32_t* p, uint32_t target) {
    asm volatile("{ .reg .pred p; .reg .b32 n, t; mov.u32 n, 0;\n LP:\n"
                 "ld.relaxed.gpu.global.u32 t, [%0];\n sub.s32 t, t, %1;\n setp.lt.s32 p, t, 0;\n vote.sync.any.pred p, p, 0xffffffff;\n @!p bra.uni DN;\n" SPIN_TAIL("1")
                 ::"l"(p), "r"(target) : "memory");
}
template <int STR>
__device__ __forceinline__ void poll4_kv(uint32_t* v, const uint4* p, uint32_t tag) {
    asm volatile("{ .reg .pred p; .reg .b32 n, t; .reg .b128 q; mov.u32 n, 0;\n LP:\n"
                 LDP("%0", "%1", "%2", "%3", "%16", "0") LDP("%4", "%5", "%6", "%7", "%16", "%18")
                 LDP("%8", "%9", "%10", "%11", "%16", "%19") LDP("%12", "%13", "%14", "%15", "%16", "%20")
                 "xor.b32 t, %0, %17;\n" CHK("%4", "%17") CHK("%8", "%17") CHK("%12", "%17") VOTE_OK SPIN_TAIL("2")
                 : WR4(v, 0), WR4(v, 4), WR4(v, 8), WR4(v, 12)
                 : "l"(p), "r"(tag), "n"(16 * STR), "n"(32 * STR), "n"(48 * STR)
                 : "memory");
}
template <int B>
__device__ __forceinline__ void blk_load(uint32_t (&A)[8][14], const uint4* src, int lane) {
    ld_pkt<0>(&A[2 * B][0], src); ld_pkt<32>(&A[2 * B][4], src); ld_pkt<64>(&A[2 * B][8], src);
    ld_pkt<512>(&A[2 * B + 1][0], src); ld_pkt<544>(&A[2 * B + 1][4], src); ld_pkt<576>(&A[2 * B + 1][8], src);
    asm volatile("{ .reg .b64 h;\n" LDH("%0", "%1", "%4", "1536") LDH("%2", "%3", "%4", "9728") "}"
                 : "=&r"(A[2 * B][12]), "=&r"(A[2 * B][13]), "=&r"(A[2 * B + 1][12]), "=&r"(A[2 * B + 1][13])
                 : "l"((const char*)src - lane * 8) : "memory");
}
template <int B>
__device__ __forceinline__ void blk_check(uint32_t (&A)[8][14], const uint4* src, int lane, uint32_t tag) {
    asm volatile("{ .reg .pred p; .reg .b32 n, t; .reg .b128 q; .reg .b64 h, a8; mov.u32 n, 0;\n LP:\n"
                 "xor.b32 t, %0, %30;\n" CHK("%4", "%30") CHK("%8", "%30") CHK("%12", "%30") CHK("%16", "%30") CHK("%20", "%30") CHK("%24", "%30") CHK("%26", "%30") VOTE_OK
                 LDP("%0", "%1", "%2", "%3", "%28", "0") LDP("%4", "%5", "%6", "%7", "%28", "512") LDP("%8", "%9", "%10", "%11", "%28", "1024")
                 LDP("%12", "%13", "%14", "%15", "%28", "8192") LDP("%16", "%17", "%18", "%19", "%28", "8704") LDP("%20", "%21", "%22", "%23", "%28", "9216")
                 "mad.wide.s32 a8, %29, -8, %28;\n" LDH("%24", "%25", "a8", "1536") LDH("%26", "%27", "a8", "9728") SPIN_TAIL("3")
                 "\n and.b32 %0, %0, -2; and.b32 %4, %4, -2; and.b32 %8, %8, -2; and.b32 %12, %12, -2; and.b32 %16, %16, -2; and.b32 %20, %20, -2; and.b32 %24, %24, -2; and.b32 %26, %26, -2;"
                 : RW4(A[2 * B], 0), RW4(A[2 * B], 4), RW4(A[2 * B], 8), RW4(A[2 * B + 1], 0), RW4(A[2 * B + 1], 4), RW4(A[2 * B + 1], 8),
                   RW2(A[2 * B], 12), RW2(A[2 * B + 1], 12)
                 : "l"(src), "r"(lane), "r"(tag)
                 : "memory");
}
__device__ __forceinline__ void st_async4(uint32_t a, uint32_t x, uint32_t y, uint32_t z, uint32_t w, uint32_t bar) {
    asm volatile("st.async.weak.shared::cluster.mbarrier::complete_tx::bytes.v4.b32 [%0], {%1,%2,%3,%4}, [%5];" ::"r"(a), "r"(x), "r"(y), "r"(z), "r"(w), "r"(bar) : "memory");
}
__device__ __forceinline__ uint32_t mapa(uint32_t a, uint32_t cta) { uint32_t r; asm("mapa.shared::cluster.u32 %0, %1, %2;" : "=r"(r) : "r"(a), "r"(cta)); return r; }
__device__ __forceinline__ void stat_load(uint32_t* v, const uint4* p) { ld_pkt<0>(v, p); ld_pkt<512>(v + 4, p); }
__device__ __forceinline__ void stat_check(uint32_t* v, const uint4* p, uint32_t tag) {
    asm volatile("{ .reg .pred p; .reg .b32 n, t; .reg .b128 q; mov.u32 n, 0;\n LP:\n"
                 "xor.b32 t, %3, %9;\n" CHK("%7", "%9") VOTE_OK
                 LDP("%0", "%1", "%2", "%3", "%8", "0") LDP("%4", "%5", "%6", "%7", "%8", "8192") SPIN_TAIL("4")
                 : RW4(v, 0), RW4(v, 4) : "l"(p), "r"(tag) : "memory");
}
__device__ __forceinline__ uint32_t x_bits(const uint32_t* X) {
    uint32_t r;
    asm volatile("{ .reg .b32 a, b; prmt.b32 a, %1, %2, 0x0040; prmt.b32 b, %3, %4, 0x0040; prmt.b32 %0, a, b, 0x5410; }" : "=r"(r) : "r"(X[0]), "r"(X[4]), "r"(X[8]), "r"(X[12]));
    return r;
}
template <int O>
__device__ __forceinline__ void slice_load(uint32_t* v, const uint4* p, int lane) {
    ld_pkt<O>(v, p); ld_pkt<O + 32>(v + 4, p); ld_pkt<O + 64>(v + 8, p);
    asm volatile("{ .reg .b64 h;\n" LDH("%0", "%1", "%2", "%3") "}" : "=r"(v[12]), "=r"(v[13]) : "l"((const char*)p - lane * 8), "n"(16 * (O + 96)) : "memory");
}
template <int O>
__device__ __forceinline__ void slice_check(uint32_t* v, const uint4* p, int lane, uint32_t tag) {
    asm volatile("{ .reg .pred p; .reg .b32 n, t; .reg .b128 q; .reg .b64 h; mov.u32 n, 0;\n LP:\n"
                 "xor.b32 t, %0, %16;\n" CHK("%4", "%16") CHK("%8", "%16") CHK("%12", "%16") VOTE_OK
                 LDP("%0", "%1", "%2", "%3", "%14", "%17") LDP("%4", "%5", "%6", "%7", "%14", "%18") LDP("%8", "%9", "%10", "%11", "%14", "%19")
                 LDH("%12", "%13", "%15", "%20") SPIN_TAIL("5")
                 : RW4(v, 0), RW4(v, 4), RW4(v, 8), RW2(v, 12)
                 : "l"(p), "l"((const char*)p - lane * 8), "r"(tag), "n"(16 * O), "n"(16 * (O + 32)), "n"(16 * (O + 64)), "n"(16 * (O + 96))
                 : "memory");
}
__device__ __forceinline__ void x_fix(uint32_t* X, uint32_t bits) {
    X[0] = __byte_perm(X[0], bits, 0x3214); X[4] = __byte_perm(X[4], bits, 0x3215); X[8] = __byte_perm(X[8], bits, 0x3216); X[12] = __byte_perm(X[12], bits, 0x3217);
}
__device__ __forceinline__ void sts4(uint32_t a, uint32_t x, uint32_t y, uint32_t z, uint32_t w) {
    asm volatile("st.shared.v4.u32 [%0], {%1,%2,%3,%4};" ::"r"(a), "r"(x), "r"(y), "r"(z), "r"(w) : "memory");
}
__device__ __forceinline__ void lds4(uint32_t* v, uint32_t a) {
    asm volatile("ld.shared.v4.u32 {%0,%1,%2,%3}, [%4];" : "=r"(v[0]), "=r"(v[1]), "=r"(v[2]), "=r"(v[3]) : "r"(a) : "memory");
}
struct LnCoef { uint32_t hi, lo, sh; };
__device__ __forceinline__ LnCoef ln_coef(float sum, float sq) {
    sum += __shfl_xor_sync(0xffffffffu, sum, 1); sq += __shfl_xor_sync(0xffffffffu, sq, 1);
    sum += __shfl_xor_sync(0xffffffffu, sum, 2); sq += __shfl_xor_sync(0xffffffffu, sq, 2);
    const float mean = sum * (1.f / 448.f);
    const float var = fmaxf(fmaf(-mean, mean, sq * (1.f / 448.f)), 0.f);
    const float sc = rsqrtf(var + 1e-5f);
    LnCoef r;
    r.hi = pack2(sc, sc);
    const float lo = sc - bf_lo(r.hi), sh = -mean * sc;
    r.lo = pack2(lo, lo);
    r.sh = pack2(sh, sh);
    return r;
}
template <int B>
__device__ __forceinline__ void normalize(uint32_t (&A)[8][14], const LnCoef& c0, const LnCoef& c1) {
#pragma unroll
    for (int s = 2 * B; s < 2 * B + 2; s++)
#pragma unroll
        for (int i = 0; i < 14; i++) {
            const LnCoef& k = (i & 1) ? c1 : c0;
            asm("{ .reg .b32 t; fma.rn.bf16x2 t, %0, %2, %3; fma.rn.bf16x2 %0, %0, %1, t; }" : "+r"(A[s][i]) : "r"(k.hi), "r"(k.lo), "r"(k.sh));
        }
}
__device__ __forceinline__ void slice_stats(const uint32_t* w, float* st) {
    float a = 0.f, b = 0.f, p = 0.f, q = 0.f;
#pragma unroll
    for (int i = 0; i < 7; i++) {
        const float e0 = bf_lo(w[2 * i]), e1 = bf_hi(w[2 * i]), e2 = bf_lo(w[2 * i + 1]), e3 = bf_hi(w[2 * i + 1]);
        a += e0 + e1; b += e2 + e3;
        p = fmaf(e0, e0, p); p = fmaf(e1, e1, p); q = fmaf(e2, e2, q); q = fmaf(e3, e3, q);
    }
    a += __shfl_xor_sync(0xffffffffu, a, 1); p += __shfl_xor_sync(0xffffffffu, p, 1); b += __shfl_xor_sync(0xffffffffu, b, 1); q += __shfl_xor_sync(0xffffffffu, q, 1);
    a += __shfl_xor_sync(0xffffffffu, a, 2); p += __shfl_xor_sync(0xffffffffu, p, 2); b += __shfl_xor_sync(0xffffffffu, b, 2); q += __shfl_xor_sync(0xffffffffu, q, 2);
    st[0] = a; st[1] = p; st[2] = b; st[3] = q;
}
__device__ __forceinline__ void dual_softmax(const float* p, uint32_t* out) {
    constexpr float L = 1.4426950408889634f;
#pragma unroll
    for (int r = 0; r < 2; r++) {
        float mx = fmaxf(p[2 * r], p[2 * r + 1]), mn = fminf(p[2 * r], p[2 * r + 1]);
#pragma unroll
        for (int i = 1; i < 7; i++) {
            mx = fmaxf(mx, fmaxf(p[4 * i + 2 * r], p[4 * i + 2 * r + 1]));
            mn = fminf(mn, fminf(p[4 * i + 2 * r], p[4 * i + 2 * r + 1]));
        }
        mx = fmaxf(mx, __shfl_xor_sync(0xffffffffu, mx, 1));
        mn = fminf(mn, __shfl_xor_sync(0xffffffffu, mn, 1));
        const float bx = -mx * L, bn = mn * L;
        float ep[14], en[14], sp = 0.f, sn = 0.f;
#pragma unroll
        for (int i = 0; i < 14; i++) {
            const float v = p[4 * (i >> 1) + 2 * r + (i & 1)];
            ep[i] = ex2(fmaf(v, L, bx));
            en[i] = ex2(fmaf(v, -L, bn));
            sp += ep[i]; sn += en[i];
        }
        sp += __shfl_xor_sync(0xffffffffu, sp, 1);
        sn += __shfl_xor_sync(0xffffffffu, sn, 1);
        const float ip = rcp(sp), in = rcp(sn);
#pragma unroll
        for (int i = 0; i < 7; i++) {
            out[4 * i + r] = pack2(ep[2 * i] * ip, ep[2 * i + 1] * ip);
            out[4 * i + 2 + r] = pack2(en[2 * i] * in, en[2 * i + 1] * in);
        }
    }
}
__device__ __forceinline__ float geglu(float g, float u) {
    const float t = tanh_hw(g * fmaf(g * g, 0.7978845608028654f * 0.044715f, 0.7978845608028654f));
    const float gu = g * u;
    return fmaf(t, gu, gu);
}
__device__ __forceinline__ void phi_gemm(const float* t, float* p) {
    uint32_t w[14];
#pragma unroll
    for (int i = 0; i < 14; i++) w[i] = pack2(t[2 * i], t[2 * i + 1]);
    const uint64_t db = BASE128(OFF_WPHI, 16, 0);
    wg_fence();
    mma_rs56<0, 0>(p, w[0], w[1], w[2], w[3], 0, db);
    mma_rs56<0, 2>(p, w[4], w[5], w[6], w[7], 1, db);
    mma_rs56<0, 4>(p, w[8], w[9], w[10], w[11], 1, db);
    mma_rs56<0, 6>(p, w[12], w[13], 0u, 0u, 1, db);
    wg_commit();
    wg_wait<0>();
}

}

#define BAR(i) (bars + 8 * (i))
#define R_WAIT() mbar_wait(BAR(slot), ph)
#define WSUM(i)
#define R_ADJ (slot * (STAGE >> 4))
#define R_NEXT() do { eb2 = eb1; eb1 = BAR(B_EMPTY + slot); if (++slot == NST) { slot = 0; ph ^= 1; } } while (0)
#define R_RELEASE(k) do { if (lane == 0) mbar_arrive((k) == 1 ? eb1 : eb2); } while (0)
#define PUSH_BEGIN() do { mbar_wait(BAR(B_ACK + wgi), ackph); ackph ^= 1; } while (0)
#define PUSH_ACK() do { __syncwarp(); if (lane == 0) asm volatile("mbarrier.arrive.shared::cluster.b64 _, [%0];" ::"r"(mapa(BAR(B_ACK + wgi), hr ^ 1)) : "memory"); } while (0)

__global__ void __cluster_dims__(2, 1, 1) __launch_bounds__(384, 1)
fused_kernel(Scratch* const sc, const __nv_bfloat16* __restrict__ x_in, const __nv_bfloat16* __restrict__ w_phi, const int trips,
             const __nv_bfloat16* __restrict__ wg, const __nv_bfloat16* __restrict__ wu, const __nv_bfloat16* __restrict__ wd,
             const __grid_constant__ Maps maps) {
    extern __shared__ __align__(1024) unsigned char smem_raw[];
    const uint32_t sb = s2u(smem_raw);
    const uint32_t bars = sb + OFF_BAR;
    const int wgi = __shfl_sync(0xffffffffu, threadIdx.x >> 7, 0);
    const int hr = blockIdx.x & 1, ck = blockIdx.x >> 1;
    const int gp = (ck - 4) & 7, q7 = ((ck - 36) * 37) >> 8;
    const int pr = __shfl_sync(0xffffffffu, ck < 4 ? ck : (ck < 36 ? (ck - 4) >> 3 : q7), 0);
    const int tile = __shfl_sync(0xffffffffu, ck < 4 ? 0 : (ck < 36 ? (gp ? 2 * gp : 1) : 2 * (ck - 36 - 7 * q7) + 3), 0);
    const int sl = 2 * pr + hr;
    STAMP(0);
    GSTAMP(60);
    if (threadIdx.x == 256) {
#pragma unroll
        for (int i = 0; i < NST; i++) mbar_init(BAR(i), 1);
        asm volatile("fence.mbarrier_init.release.cluster;" ::: "memory");
    }
    if (threadIdx.x == 288) {
        if ((sb & 0x3FFFF) != SB0) asm volatile("trap;");
#pragma unroll
        for (int i = NST; i < B_COUNT; i++) mbar_init(BAR(i), i >= B_ACK ? 4 : (i < B_RECV || i == B_LATE ? 8 : 1));
        asm volatile("fence.mbarrier_init.release.cluster;" ::: "memory");
    }
    __syncwarp();
    asm volatile("barrier.cluster.arrive.relaxed.aligned;" ::: "memory");

    if (wgi == 2) {
        asm volatile("setmaxnreg.dec.sync.aligned.u32 40;");
        const int t128 = fresh_tid() & 127, w = __shfl_sync(0xffffffffu, t128 >> 5, 0), lane = t128 & 31;
        uint32_t e0[2] = {0, 0}, e1[2] = {0, 0}, cw_target = 0, kseq;
        if (w == 0) {
#pragma unroll 1
            for (int n = 0; n < NST; n++) {
                const uint32_t dst = sb + n * STAGE, fb = BAR(n);
                asm volatile(ELECT "mbarrier.arrive.expect_tx.shared::cta.b64 _, [%0], %1; }" ::"r"(fb), "r"(n < 2 ? 2 * STAGE : STAGE) : "memory");
                if (n < 2) {
                    tma3x(sb + OFF_H + n * STAGE, &maps.x, tile * 128 + n * 64, fb);
                    tma3x(dst, &maps.x, tile * 128 + n * 64 + 32, fb);
                } else {
                    if (n == 3) mbar_wait(BAR(1), 0);
                    const int ra = 112 * (n - 2);
                    tma2d(dst, &maps.qkv, 448 + 56 * sl, ra, fb);
                    tma2d(dst + HALF, &maps.qkv, 896 + 56 * sl, ra, fb);
                }
            }
            asm volatile("barrier.cluster.wait.aligned;" ::: "memory");
            kseq = ld_word(g_c1 + (sl * 8 * 16 + tile) * 32);
            cw_target = (ld_word(g_cw + sl * 32) & ~15u) + 16;
#pragma unroll 1
            for (int k = 0; k < 2; k++) {
                const int n = t128 + 32 * k;
                int m = n - 2 - (n > PACK);
                const bool packed = m >= 30 ? (m < 38 || m >= 52) : m >= 22;
                if (m >= 30) m -= 30;
                if (n == PACK) m = tile < 8 ? tile : tile + 14;
                const int rot = n < 8 ? 0 : pr;
                const int ra = 112 * kblk(rot, m & 3), rb = 112 * kblk(rot, 2 * m & 3), rc = 112 * kblk(rot, (2 * m + 1) & 3);
                int kind = 0, m0, m1, c0, c1, r0, r1;
                if (m < 4) { m0 = m1 = 1; c0 = 448 + 56 * sl; c1 = c0 + 448; r0 = r1 = ra; }
                else if (m < 8) { m0 = m1 = m < 6 ? 1 : 2; c0 = c1 = 56 * sl; r0 = rb; r1 = rc; }
                else if (m < 20) { m0 = 3; m1 = 4; c0 = c1 = 224 * sl + 32 * hr + 64 * ((m - 8) >> 2); r0 = r1 = ra; }
                else if (m < 22) { kind = 2; m0 = 5; m1 = 6; c0 = c1 = 224 * sl + (hr ? 0 : 192); r0 = rb; r1 = rc; }
                else { m0 = m1 = 7; c0 = c1 = 56 * (2 * ((pr + (m >> 1) - 10) & 3) + hr); r0 = 224 * (sl ^ (m & 1)); r1 = r0 + 112; }
                if (packed) { kind = 1; r0 = sl * 16 + (m < 8 ? m : m - 14); r1 = 0; }
                e0[0] = e0[1]; e1[0] = e1[1];
                e0[1] = kind | (m0 << 2) | (m1 << 6) | (c0 << 10) | (c1 << 21);
                e1[1] = r0 | (r1 << 16);
            }
        } else {
            const int j = t128 - 32;
            kseq = ld_word(g_c1 + (sl * 8 * 16 + tile) * 32);
            asm volatile("barrier.cluster.wait.aligned;" ::: "memory");
            uint2 wv[7];
            const int k = j < 56 ? j : 55, hh = k >= 28;
#pragma unroll
            for (int i = 0; i < 7; i++) wv[i] = __ldg(reinterpret_cast<const uint2*>(w_phi + (sl * 56 + k) * 28) + i);
#pragma unroll 1
            for (int i = j; i < 7168 / 16; i += 96) sts4(sb + OFF_WPHI + i * 16, 0, 0, 0, 0);
            bar_sync(5, 96);
            if (j < 56) {
                uint32_t a4[4];
#pragma unroll
                for (int q = 0; q < 4; q++) a4[q] = sb + OFF_WPHI + (4 * hh + q) * 128 + ((((k >> 3) ^ (4 * hh + q)) & 7) << 4) + (k & 7) * 2;
                FOR14(const uint32_t v = (t & 1) ? wv[t >> 1].y : wv[t >> 1].x;
                      asm volatile("{ .reg .b16 l, h; mov.b32 {l, h}, %2; st.shared.u16 [%0+%3], l; st.shared.u16 [%1+%3], h; }"
                                   ::"r"(a4[t >= 7 ? 2 : 0]), "r"(a4[t >= 7 ? 3 : 1]), "r"(v), "n"((t % 7) * 1024) : "memory"));
            }
            __syncwarp();
            fence_async();
            kseq = __shfl_sync(0xffffffffu, kseq, 0);
            bar_arrive(1, 224);
            bar_arrive(9, 224);
        }
        kseq = __shfl_sync(0xffffffffu, kseq, 0);
        int slot = 0, ph = 0, n = NST;
#pragma unroll 1
        for (int layer = 0; layer < 3; layer++) {
            if (w == 0) {
                const int nend = layer == 0 ? 11 : (layer == 1 ? 42 : 63);
#pragma unroll 1
                for (; n < nend; n++) {
                const uint32_t w0 = __shfl_sync(0xffffffffu, n < 32 ? e0[0] : e0[1], n & 31), w1 = __shfl_sync(0xffffffffu, n < 32 ? e1[0] : e1[1], n & 31);
                const uint32_t dst = sb + slot * STAGE, fb = BAR(n == PACK ? B_PACK : slot);
                const CUtensorMap* m0 = &maps.x + ((w0 >> 2) & 15);
                const CUtensorMap* m1 = &maps.x + ((w0 >> 6) & 15);
                const int c0 = (w0 >> 10) & 2047, c1 = w0 >> 21, r0 = w1 & 0xffff, r1 = w1 >> 16;
                if (n == 25) {
                    int it = 0;
                    uint32_t v;
                    do { asm volatile("ld.acquire.gpu.global.u32 %0, [%1];" : "=r"(v) : "l"(g_cw + sl * 32) : "memory"); } while ((int)(v - cw_target) < 0 && ++it < 0x400000);
                    asm volatile("fence.proxy.async.global;" ::: "memory");
                    __syncwarp();
                }
                mbar_wait(BAR(B_EMPTY + slot), ph);
                __syncwarp();
                asm volatile(ELECT "mbarrier.arrive.expect_tx.shared::cta.b64 _, [%0], %1; }" ::"r"(fb), "r"(STAGE) : "memory");
                if ((w0 & 3) == 0) {
                    tma2d(dst, m0, c0, r0, fb);
                    tma2d(dst + HALF, m1, c1, r1, fb);
                } else if (w0 & 1) {
                    asm volatile(ELECT "cp.async.bulk.shared::cluster.global.mbarrier::complete_tx::bytes [%0], [%1], %2, [%3]; }"
                                 ::"r"(dst), "l"(reinterpret_cast<const char*>(g_wp) + (size_t)r0 * STAGE), "r"(STAGE), "r"(fb) : "memory");
                } else {
                    tma2d(dst, m0, c0, r0, fb); tma2d(dst + 7168, m0, c0, r1, fb);
                    tma2d(dst + HALF, m1, c0, r0, fb); tma2d(dst + HALF + 7168, m1, c0, r1, fb);
                }
                if (n == PFN) {
                    const int b = blockIdx.x;
                    asm volatile(ELECT "cp.async.bulk.prefetch.L2.global [%0], %1; }" ::"l"(wg + b * 6272), "r"(12544) : "memory");
                    asm volatile(ELECT "cp.async.bulk.prefetch.L2.global [%0], %1; }" ::"l"(wu + b * 6272), "r"(12544) : "memory");
                    asm volatile(ELECT "cp.async.bulk.prefetch.L2.global [%0], %1; }" ::"l"(wd + b * 6272), "r"(12544) : "memory");
                }
                if (n == PACK) asm volatile(ELECT "mbarrier.arrive.shared::cta.b64 _, [%0]; }" ::"r"(BAR(slot)) : "memory");
                if (++slot == NST) { slot = 0; ph ^= 1; }
                }
            } else if (w == 1 && layer == 1) {
                constexpr int ps = PACK % NST;
                mbar_wait(BAR(B_PACK), 0);
                asm volatile("{ .reg .pred e; elect.sync _|e, 0xffffffff;\n"
                             "@e cp.async.bulk.global.shared::cta.bulk_group [%0], [%1], %2;\n"
                             "@e cp.async.bulk.commit_group;\n"
                             "@e cp.async.bulk.wait_group.read 0;\n"
                             "@e mbarrier.arrive.shared::cta.b64 _, [%3], 8;\n"
                             "@e cp.async.bulk.wait_group 0;\n"
                             "@e fence.proxy.async.global;\n"
                             "@e red.release.gpu.global.add.u32 [%4], 1; }"
                             ::"l"(reinterpret_cast<char*>(g_wp) + (size_t)(sl * 16 + tile) * STAGE), "r"(sb + ps * STAGE), "r"(STAGE), "r"(BAR(B_EMPTY + ps)), "l"(g_cw + sl * 32) : "memory");
                __syncwarp();
            }
            if (layer < 2) {
            const uint32_t tag = layer ^ 1;
            kseq++;
            bar_sync(7, 384);
            ASTAMP(0);
            if (tile < 15) {
                const int sq = lane >> 3, pk = 8 * w + (lane & (tile == 14 ? 3 : 7));
                uint32_t v[16];
                if (layer == 0) poll_cnt(g_c1 + ((sl * 8 + (w >> 1) * 4 + (tile >> 2)) * 16 + (lane & 15)) * 32, kseq);
                ASTAMP(1);
                poll4_kv<32>(v, g_kv1 + ((sl * 16 + tile) * 16 + 4 * sq) * 32 + pk, tag);
#pragma unroll
                for (int k = 0; k < 4; k++) {
                    float lo = (bf_lo(v[k]) + bf_lo(v[4 + k])) + (bf_lo(v[8 + k]) + bf_lo(v[12 + k]));
                    float hi = (bf_hi(v[k]) + bf_hi(v[4 + k])) + (bf_hi(v[8 + k]) + bf_hi(v[12 + k]));
                    lo += __shfl_xor_sync(0xffffffffu, lo, 8); hi += __shfl_xor_sync(0xffffffffu, hi, 8);
                    lo += __shfl_xor_sync(0xffffffffu, lo, 16); hi += __shfl_xor_sync(0xffffffffu, hi, 16);
                    v[k] = pack2(lo, hi);
                }
                if (sq == 0) st_pkt<0>(g_kv2 + sl * 512 + 32 * tile + pk, settag(v[0], tag), v[1], v[2], v[3]);
            }
            ASTAMP(2);
            {
                const int item = t128 < 112 ? t128 : 112 + (t128 & 3), d = item >> 1;
                const int cc = t128 < 112 ? 2 * (d >= 28) + (item & 1) : item - 112;
                const int r = t128 < 112 ? d : 56 + (cc >> 1) + 2 * ((t128 - 112) >> 2);
                uint32_t ra = sb + OFF_KVB + r * 128 + 4 * cc, rx = (r & 7) << 4;
                asm volatile("" : "+r"(ra), "+r"(rx));
                FOR14(asm volatile("st.shared.u32 [%0+%2], %1;" ::"r"((ra ^ 8) + (((t & 7) << 4) ^ rx)), "r"(0), "n"((t >> 3) * 8192) : "memory"));
                uint32_t v[16];
                asm volatile("" : "+r"(ra), "+r"(rx));
                poll4_kv<8>(v, g_kv2 + sl * 512 + (item >> 3) * 32 + (item & 7), tag);
                FOR14(asm volatile("st.shared.u32 [%0+%2], %1;" ::"r"(ra + (((t & 7) << 4) ^ rx)), "r"(v[t < 7 ? t : t + 1]), "n"((t >> 3) * 8192) : "memory"));
                fence_async();
            }
            bar_arrive(3, 384);
            ASTAMP(3);
            }
        }
    } else {
        asm volatile("setmaxnreg.inc.sync.aligned.u32 232;");
        int lane = fresh_tid() & 31, prf = pr;
#define pr prf
#define g (lane >> 2)
#define c (lane & 3)
#define t128 (w * 32 + lane)
        const int wu = __shfl_sync(0xffffffffu, fresh_tid() >> 5, 0), w = wu & 3;
        const uint32_t xoff = __shfl_sync(0xffffffffu, (3 * PLANE + ((tile * 2 + wgi) * 8) * 512 + w * 128) * 16, 0);
        char* xu = reinterpret_cast<char*>(g_ex) + xoff;
#define FRESH() asm volatile("" : "+l"(xu), "+r"(lane), "+r"(prf))
#define xp0 (reinterpret_cast<uint4*>(xu) + lane)
        const uint32_t hbuf = sb + OFF_H + wgi * STAGE;
        uint32_t slot = 0, ph = 0, eb1 = 0, eb2 = 0, ackph = 0, rcvph = 0, gatph = 0, swp = 0;
        uint32_t ppid = 6;
#define cx(s) (reinterpret_cast<uint32_t*>(reinterpret_cast<uint4*>(xu) + PL(1) + 112 + (s) * 512))
#define stp (reinterpret_cast<uint4*>(xu) + g + PL(0) + 112)
        uint32_t seq = ld_word(cx(sl));
        uint32_t kseq = ld_word(g_c1 + ((sl * 8 + wu) * 16 + tile) * 32);
        uint32_t stag = ld_word(reinterpret_cast<const uint32_t*>(stp + sl * 512) + 3) & 1;
        asm volatile("barrier.cluster.wait.aligned;" ::: "memory");
        STAMP(1);
        uint32_t X[14];
        const uint32_t x0row = (w < 2 ? hbuf : sb + wgi * STAGE) + ((w & 1) * 16 + (lane & 15)) * 128;
        mbar_wait(BAR(wgi), 0);
        STAMP(51);
#pragma unroll
        for (int j = 0; j < 4; j++) {
            const int G = 7 * sl + min(2 * j + (lane >> 4), 6);
            uint32_t q2, q3;
            asm volatile("ldmatrix.sync.aligned.m8n8.x4.shared.b16 {%0,%1,%2,%3}, [%4];" : "=r"(X[4 * j]), "=r"(X[4 * j + 1]), "=r"(q2), "=r"(q3)
                         : "r"(x0row + (G >> 3) * 4096 + (((G ^ lane) & 7) << 4)) : "memory");
            if (j < 3) { X[(4 * j + 2) % 14] = q2; X[(4 * j + 3) % 14] = q3; }
        }
#define PUSH_SLICE(W)                                                                          \
    {                                                                                          \
        if (t128 == 0) mbar_expect_tx(BAR(B_RECV + wgi), 7168);                                \
        PUSH_BEGIN();                                                                          \
        const uint32_t ra = mapa(hbuf + 24576 + t128 * 16, hr ^ 1), rb = mapa(sb + OFF_XR + wgi * 3072, hr ^ 1), rbar = mapa(BAR(B_RECV + wgi), hr ^ 1); \
        st_async4(ra, W[0], W[1], W[2], W[3], rbar);                                           \
        st_async4(ra + 2048, W[4], W[5], W[6], W[7], rbar);                                    \
        st_async4(rb + t128 * 16, W[8], W[9], W[10], W[11], rbar);                             \
        asm volatile("st.async.weak.shared::cluster.mbarrier::complete_tx::bytes.v2.b32 [%0], {%1,%2}, [%3];" ::"r"(rb + 2048 + t128 * 8), "r"(W[12]), "r"(W[13]), "r"(rbar) : "memory"); \
    }
#define PULL_SLICE(W)                                                                          \
    {                                                                                          \
        uint32_t t0, t1;                                                                       \
        mbar_wait(BAR(B_RECV + wgi), rcvph);                                                   \
        rcvph ^= 1;                                                                            \
        lds4(&A[1][0], hbuf + 24576 + t128 * 16);                                              \
        lds4(&A[1][4], hbuf + 26624 + t128 * 16);                                              \
        lds4(&A[1][8], sb + OFF_XR + wgi * 3072 + t128 * 16);                                  \
        asm volatile("ld.shared.v2.u32 {%0,%1}, [%2];" : "=r"(t0), "=r"(t1) : "r"(sb + OFF_XR + wgi * 3072 + 2048 + t128 * 8) : "memory"); \
        _Pragma("unroll") for (int i = 0; i < 12; i++) A[0][i] = (i & 3) ? W[i] : W[i] & ~1u;  \
        A[1][0] &= ~1u; A[1][4] &= ~1u; A[1][8] &= ~1u;                                        \
        A[0][12] = (hr ? t0 : W[12]) & ~1u; A[0][13] = hr ? t1 : W[13];                        \
        A[1][12] = (hr ? W[12] : t0) & ~1u; A[1][13] = hr ? W[13] : t1;                        \
        asm volatile("" : RW4(A[0], 0), RW4(A[0], 4), RW4(A[0], 8), RW2(A[0], 12), RW4(A[1], 0), RW4(A[1], 4), RW4(A[1], 8), RW2(A[1], 12)); \
        swp = hr * 448;                                                                        \
    }
#define SWB(b, t, db, sh) ((b) == 0 && (t) < 6 ? ((t) < 3 ? db##p : db##m) : db)
#define DECL_DB(b, MK, lbo, sh) const uint64_t db = MK(0, lbo, R_ADJ), dbp = (b) == 0 ? MK(0, lbo, R_ADJ + (swp >> (sh))) : db, dbm = (b) == 0 ? MK(0, lbo, R_ADJ - (swp >> (sh))) : db;
#define PPB 2
#define PP_WAIT() if (wgi == 1) { bar_sync(ppid, 256); ppid ^= 14; }
#define PP_GO() if (wgi == 0) { bar_arrive(ppid, 256); ppid ^= 14; }
#define GAT_DST(B, s2) ((B) == 1 ? hbuf + w * 3584 + (s2) * 1792 : ((s2) ? sb + OFF_KVB + wgi * 8192 : hbuf + 14336) + w * 1792)
#define GAT_ISSUE(B, base)                                                                     \
    {                                                                                          \
        const char* gs = xu + ((base) + kblk(pr, B) * 1024) * 16;                              \
        asm volatile("{ .reg .pred e; elect.sync _|e, 0xffffffff;\n"                           \
                     "@e mbarrier.arrive.expect_tx.shared::cta.b64 _, [%3], 3584;\n"           \
                     "@e cp.async.bulk.shared::cluster.global.mbarrier::complete_tx::bytes [%0], [%2], 1792, [%3];\n" \
                     "@e cp.async.bulk.shared::cluster.global.mbarrier::complete_tx::bytes [%1], [%2+8192], 1792, [%3]; }" \
                     ::"r"(GAT_DST(B, 0)), "r"(GAT_DST(B, 1)), "l"(gs), "r"(BAR(B_GAT + wu * 2 + ((B) >> 1))) : "memory"); \
        __syncwarp();                                                                          \
    }
#define GAT_FETCH(B)                                                                           \
    {                                                                                          \
        mbar_wait(BAR(B_GAT + wu * 2 + ((B) >> 1)), (gatph >> (B)) & 1);                          \
        gatph ^= 1 << (B);                                                                     \
        _Pragma("unroll") for (int s2 = 0; s2 < 2; s2++) {                                     \
            const uint32_t ga = GAT_DST(B, s2) + lane * 16;                                    \
            lds4(&A[2 * (B) + s2][0], ga); lds4(&A[2 * (B) + s2][4], ga + 512); lds4(&A[2 * (B) + s2][8], ga + 1024); \
            asm volatile("ld.shared.v2.u32 {%0,%1}, [%2];" : "=r"(A[2 * (B) + s2][12]), "=r"(A[2 * (B) + s2][13]) : "r"(ga - lane * 8 + 1536) : "memory"); \
        }                                                                                      \
    }
#define LATE_ARRIVE() do { if (lane == 0) mbar_arrive(BAR(B_LATE)); } while (0)
#define LATE_WAIT() do { mbar_wait(BAR(B_LATE), gatph & 1); gatph ^= 1; } while (0)
#define PT 3
#define PREP(b, t, remote)                                                                     \
    if constexpr ((b) < 3 && (t) == PT) {                                                      \
        wg_commit();                                                                           \
        STAMP(74 + 6 * (step & 1) + 2 * (b));                                                  \
        if (remote) {                                                                          \
            if constexpr ((b) == 0) { blk_load<2>(A, BLK(xsrc, 2), lane); GAT_FETCH(1) }       \
            blk_check<((b) + 1) & 3>(A, BLK(xsrc, (b) + 1), lane, xtag);                       \
            if constexpr ((b) == 0) blk_load<3>(A, BLK(xsrc, 3), lane);                        \
        }                                                                                      \
        STAMP(75 + 6 * (step & 1) + 2 * (b));                                                  \
        normalize<((b) + 1) & 3>(A, k0, k1);                                                   \
        asm volatile("" : RW4(A[(2 * (b) + 2) & 7], 0), RW4(A[(2 * (b) + 2) & 7], 4), RW4(A[(2 * (b) + 2) & 7], 8), RW2(A[(2 * (b) + 2) & 7], 12), \
                          RW4(A[(2 * (b) + 3) & 7], 0), RW4(A[(2 * (b) + 3) & 7], 4), RW4(A[(2 * (b) + 3) & 7], 8), RW2(A[(2 * (b) + 3) & 7], 12)); \
        wg_fence();                                                                            \
    }
#define X0_BLOCK(b)                                                                            \
    { const int rr = lane & 7, hi = lane >> 4;                                                 \
    const uint32_t rowa = (w < 2 ? hbuf : sb + wgi * STAGE) + ((w & 1) * 16 + (lane & 15)) * 128; \
    FOR7(constexpr int G = 14 * (b) + (t < 3 ? 2 * t : (t < 6 ? 2 * t + 1 : 6));               \
         uint32_t q0, q1, q2, q3;                                                              \
         const uint32_t ad = t < 6 ? rowa + (((((G & 7) + hi) ^ rr) & 7) << 4) + ((G & 7) == 7 ? hi * 4096 : 0) : rowa + ((G + 7 * hi) >> 3) * 4096 + ((((G + 7 * hi) ^ rr) & 7) << 4); \
         asm volatile("ldmatrix.sync.aligned.m8n8.x4.shared.b16 {%0,%1,%2,%3}, [%4+%5];" : "=r"(q0), "=r"(q1), "=r"(q2), "=r"(q3) \
                      : "r"(ad), "n"(t < 6 ? (G >> 3) * 4096 : 0) : "memory");                 \
         if (t < 3) { A[2 * (b)][4 * t] = q0; A[2 * (b)][4 * t + 1] = q1; A[2 * (b)][4 * t + 2] = q2; A[2 * (b)][4 * t + 3] = q3; } \
         else if (t < 6) { A[2 * (b) + 1][(4 * t - 12) & 15] = q0; A[2 * (b) + 1][((4 * t - 12) & 15) + 1] = q1; A[2 * (b) + 1][((4 * t - 12) & 15) + 2] = q2; A[2 * (b) + 1][((4 * t - 12) & 15) + 3] = q3; } \
         else { A[2 * (b)][12] = q0; A[2 * (b)][13] = q1; A[2 * (b) + 1][12] = q2; A[2 * (b) + 1][13] = q3; }); }
#define BLK(base, b) ((base) + kblk(pr, b) * 1024)

#pragma unroll 1
        for (int step = 0; step < 4; step++) {
            FRESH();
            const uint32_t tag = (step >> 1) ^ 1;
            const int so = (step >> 1) * 24 + (step & 1) * 12;
            (void)so;
            uint32_t A[8][14];
            uint4* const xsrc = xp0 + ((step & 1) ? PL(2) : PL(0));
            const uint32_t xtag = (step & 1) ? tag : ((seq >> 3) & 1) ^ 1;
            uint32_t xbits;
            {
                float st[4];
                slice_stats(X, st);
                stag ^= 1;
                xbits = x_bits(X);
                tag_slice(X, xtag);
                if (step) send_slice<0>(xsrc + sl * 512, lane, X);
                if (c == 0) st_pkt<0>(stp + sl * 512, __float_as_uint(st[0]), __float_as_uint(st[1]), __float_as_uint(st[2]), settag(__float_as_uint(st[3]), stag));
            }
            STAMP(2 + so);
            uint32_t sv[8];
            if (step == 0) {
                X0_BLOCK(0) X0_BLOCK(1) X0_BLOCK(2) X0_BLOCK(3)
                mbar_wait(BAR(wgi ^ 1), 0);
                R_NEXT();
                R_NEXT();
                R_RELEASE(2);
                stat_load(sv, stp + c * 1024);
                stat_check(sv, stp + c * 1024, stag);
                STAMP(52 + step);
            } else {
                kill<14>(A[2]); kill<14>(A[3]); kill<14>(A[4]); kill<14>(A[5]); kill<14>(A[6]); kill<14>(A[7]);
                PUSH_SLICE(X)
                stat_load(sv, stp + c * 1024);
                PULL_SLICE(X)
                stat_check(sv, stp + c * 1024, stag);
                STAMP(52 + step);
                GAT_ISSUE(1, (step & 1) ? PL(2) : PL(0))
            }
            LnCoef k0, k1;
            {
                k0 = ln_coef(__uint_as_float(sv[0]) + __uint_as_float(sv[4]), __uint_as_float(sv[1]) + __uint_as_float(sv[5]));
                k1 = ln_coef(__uint_as_float(sv[2]) + __uint_as_float(sv[6]), __uint_as_float(sv[3] & ~1u) + __uint_as_float(sv[7] & ~1u));
            }
            STAMP(3 + so);
            GSTAMP(70 + step);

            if ((step & 1) == 0) {
                float tq[28];
                {
                    float av[28];
#define KV_BLOCK(b)                                                                           \
    if ((b) == 1) R_RELEASE(2);                                                               \
    if ((b) == 2) { PUSH_ACK(); wg_wait<2>(); R_RELEASE(2); }                                 \
    R_WAIT();                                                                                 \
    if ((b) == PPK) { PP_WAIT() }                                                             \
    { DECL_DB(b, BASE128, 16, 0)                                                              \
    wg_fence();                                                                               \
    FOR7(mma_rs56<1, D128(0, t)>(tq, AQ(A, b, t), (b) + t > 0, SWB(b, t, db, 0));             \
         mma_rs56<1, D128(HALF, t)>(av, AQ(A, b, t), (b) + t > 0, SWB(b, t, db, 0));          \
         PREP(b, t, step)); }                                                                 \
    wg_commit();                                                                              \
    if ((b) == 3 && PPK < 4) { PP_GO() }                                                      \
    R_NEXT();
                    normalize<0>(A, k0, k1);
                    KV_BLOCK(0) KV_BLOCK(1) KV_BLOCK(2) KV_BLOCK(3)
                    wg_wait<0>();
                    if (lane < 3) mbar_arrive(BAR(B_EMPTY + (slot + NST - 1 - lane) % NST));
                    STAMP(4 + so);
                    WSUM(80 + 7 * (step >> 1));
                    const int m = lane >> 3, rr = lane & 7;
                    const uint32_t rowa = hbuf + 16384 + (w * 16 + rr + 8 * (m & 1)) * 128;
                    const uint32_t one = c == 0 ? 0x00003f80u : 0u;
                    if (step == 0) { bar_sync(wgi ? 9 : 1, 224); }
#pragma unroll
                    for (int j = 0; j < 4; j++) {
                        const uint32_t a = rowa + (((2 * j + (m >> 1)) ^ rr) << 4);
                        if (j < 3) stsm4(a, pack2(av[8 * j], av[8 * j + 1]), pack2(av[8 * j + 2], av[8 * j + 3]), pack2(av[8 * j + 4], av[8 * j + 5]), pack2(av[8 * j + 6], av[8 * j + 7]));
                        else stsm4(a, pack2(av[24], av[25]), pack2(av[26], av[27]), one, one);
                    }
                }
                uint32_t PH[28];
                int it = 1;
#pragma unroll 1
                do {
                    float pp[28];
                    phi_gemm(tq, pp);
                    dual_softmax(pp, PH);
                    if (((trips >> (it + 1)) & 1) == 0) continue;
                    {
                        const int m = lane >> 3, rr = lane & 7;
                        const uint32_t rowa = hbuf + (w * 16 + rr + 8 * (m & 1)) * 128;
#pragma unroll
                        for (int j = 0; j < 7; j++) {
                            const int cg = 2 * j + (m >> 1), hi = cg >= 7;
                            stsm4(rowa + hi * 8192 + (((cg - 7 * hi) ^ rr) << 4), PH[4 * j], PH[4 * j + 1], PH[4 * j + 2], PH[4 * j + 3]);
                        }
                    }
                    fence_async();
                    STAMP(5 + so);
#define Q_STAGE(b0)                                                                           \
    R_WAIT();                                                                                 \
    { DECL_DB(b0, BASE128, 16, 0)                                                             \
    wg_fence();                                                                               \
    FOR7(mma_rs56<1, D128(0, t)>(tq, AQ(A, b0, t), (b0) + t > 0, SWB(b0, t, db, 0)));         \
    FOR7(mma_rs56<1, D128(HALF, t)>(tq, AQ(A, (b0) + 1, t), 1, db)); }                        \
    wg_commit();                                                                              \
    R_NEXT();
                    if (QE && wgi == 0) { kill<28>(tq); Q_STAGE(0) Q_STAGE(2) wg_wait<1>(); R_RELEASE(2); wg_wait<0>(); R_RELEASE(1); }
                    bar_sync(2, 256);
                    float kv[28];
                    const uint64_t da = BASE128(OFF_H + 16384, 16, 0), dbk = BASE128(OFF_H, 16, wgi * 512);
                    wg_fence();
                    FOR8(constexpr uint64_t o = ((t >> 2) * STAGE + (t & 3) * 2048) >> 4; mma_ss56_tt<o, o>(kv, t > 0, da, dbk));
                    wg_commit();
                    wg_wait<0>();
#pragma unroll
                    for (int hf = 0; hf < 2; hf++) {
                        const int d = 16 * w + g + 8 * hf;
                        if ((d < 56 && (d >= 28) == (c >= 2)) || d == 56) {
                            const int item = d < 56 ? 2 * d + (c & 1) : 112 + c;
                            uint4* dst = g_kv1 + ((sl * 16 + (item >> 3)) * 16 + tile) * 32 + wgi * 16 + (item & 7);
#define KVW(i) pack2(kv[4 * (i) + 2 * hf], kv[4 * (i) + 2 * hf + 1])
                            st_pkt<0>(dst, settag(KVW(0), tag), KVW(1), KVW(2), KVW(3));
                            st_pkt<8>(dst, settag(KVW(4), tag), KVW(5), KVW(6), 0u);
                        }
                    }
                    __syncwarp();
                    kseq++;
                    if (lane == 0) st_word(g_c1 + ((sl * 8 + wu) * 16 + tile) * 32, kseq);
                    bar_arrive(7, 384);
                    STAMP(6 + so);
                    if (!QE || wgi == 1) { kill<28>(tq); Q_STAGE(0) Q_STAGE(2) wg_wait<1>(); R_RELEASE(2); wg_wait<0>(); R_RELEASE(1); }
                    STAMP(7 + so);
                    kill<28>(PH);
                } while (((trips >> (++it)) & 1));
                STAMP(8 + so);
                FRESH();
                if (step) {
                    slice_load<PL(0)>(X, xp0 + sl * 512, lane);
                } else {
                    const uint32_t* xp = reinterpret_cast<const uint32_t*>(x_in + (size_t)(tile * 128 + wu * 16 + g) * 448 + 56 * sl + 2 * c);
#pragma unroll
                    for (int i = 0; i < 7; i++) { X[2 * i] = __ldg(xp + 4 * i); X[2 * i + 1] = __ldg(xp + 4 * i + 8 * 224); }
                }
                bar_sync(3, 384);
                STAMP(9 + so);
                const uint4* const osrc = xp0 + PL(1);
                {
                    float nm[32];
                    const uint64_t db = BASE128(OFF_KVB, 16, 0);
                    wg_fence();
                    FOR7(mma_rs64<0, ((t >> 2) * 8192 + (t & 3) * 32) / 16>(nm, PH[4 * t], PH[4 * t + 1], PH[4 * t + 2], PH[4 * t + 3], t > 0, db));
                    wg_commit();
                    wg_wait<0>();
                    LATE_ARRIVE();
                    const float i00 = rcp(nm[28] + 1e-6f), i01 = rcp(nm[29] + 1e-6f), i10 = rcp(nm[30] + 1e-6f), i11 = rcp(nm[31] + 1e-6f);
                    const float m0 = c >= 2 ? i01 : i00, m1 = c >= 2 ? i11 : i10;
                    uint32_t O[14];
#pragma unroll
                    for (int i = 0; i < 7; i++) {
                        const float f0 = i < 3 ? i00 : (i > 3 ? i01 : m0), f1 = i < 3 ? i10 : (i > 3 ? i11 : m1);
                        O[2 * i] = pack2(nm[4 * i] * f0, nm[4 * i + 1] * f0);
                        O[2 * i + 1] = pack2(nm[4 * i + 2] * f1, nm[4 * i + 3] * f1);
                    }
                    if (OST) { PP_WAIT() }
                    tag_slice(O, tag);
                    send_slice<PL(1)>(xp0 + sl * 512, lane, O);
                    seq++;
                    if (lane == 0) st_word(cx(sl), seq);
                    STAMP(10 + so);
                    PUSH_SLICE(O)
                    if (OST == 1) { PP_GO() }
                    const uint32_t cv = ld_word(cx(lane & 7));
                    PULL_SLICE(O)
                    LATE_WAIT();
                    check_cnt(cv, cx(lane & 7), seq);
                    if (OST == 2) { PP_GO() }
                    STAMP(56 + (step >> 1));
                    GAT_ISSUE(1, PL(1))
                    GAT_ISSUE(3, PL(1))
                    blk_load<2>(A, BLK(osrc, 2), lane);
                }
                float ao[28];
#define WO_BLOCK(b)                                                                           \
    if ((b) > 0) blk_check<b>(A, BLK(osrc, b), lane, tag);                                    \
    if (((b) & 1) == 0) R_WAIT();                                                             \
    { DECL_DB(b, BASE128, 16, 0)                                                              \
    wg_fence();                                                                               \
    FOR7(mma_rs56<1, D128(((b) & 1) * HALF, t)>(ao, AQ(A, b, t), (b) + t > 0, SWB(b, t, db, 0))); } \
    wg_commit();                                                                              \
    if ((b) & 1) R_NEXT();
                WO_BLOCK(0)
                STAMP(11 + so);
                GAT_FETCH(1)
                WO_BLOCK(1)
                WO_BLOCK(2)
                GAT_FETCH(3)
                WO_BLOCK(3)
                PUSH_ACK();
                wg_wait<0>();
                R_RELEASE(2);
                STAMP(12 + so);
                WSUM(86 + 7 * (step >> 1));
                x_fix(X, xbits);
#pragma unroll
                for (int i = 0; i < 14; i++) X[i] = pack2(bf_lo(X[i]) + ao[2 * i], bf_hi(X[i]) + ao[2 * i + 1]);
            } else {
                uint32_t H[56];
                float ag[64];
#define F1_EPI(dst, ng, ag)                                                                    \
    _Pragma("unroll") for (int i = 0; i < 2 * (ng); i++)                                       \
        (dst)[i] = pack2(geglu(ag[2 * i], ag[4 * (ng) + 2 * i]), geglu(ag[2 * i + 1], ag[4 * (ng) + 2 * i + 1]));
#define H_PUSH(h0, off) st_async4(rem_h + (off), H[h0], H[(h0) + 1], H[(h0) + 2], H[(h0) + 3], mapa(BAR(B_RECV2 + wgi), hr ^ 1));
#define F1_BLOCK(b, first)                                                                     \
    if ((first) && (b) == 1) R_RELEASE(2);                                                     \
    if ((first) && (b) == 2) PUSH_ACK();                                                       \
    R_WAIT();                                                                                  \
    if ((b) == ((first) ? PPF : PPB)) { PP_WAIT() }                                            \
    { DECL_DB(b, BASE128, HALF, 0)                                                             \
    wg_fence();                                                                                \
    FOR7(mma_rs128<1, D128(0, t)>(ag, AQ(A, b, t), (b) + t > 0, SWB(b, t, db, 0));             \
         if constexpr (first) { PREP(b, t, true) }); }                                         \
    wg_commit();                                                                               \
    if ((b) == 3) { PP_GO() }                                                                  \
    if ((b) > 0) { wg_wait<1>(); R_RELEASE(1); }       \
    R_NEXT();
                normalize<0>(A, k0, k1);
                F1_BLOCK(0, true) F1_BLOCK(1, true) F1_BLOCK(2, true) F1_BLOCK(3, true)
                if (t128 == 0) { mbar_expect_tx(BAR(B_RECV + wgi), 16384); mbar_expect_tx(BAR(B_RECV2 + wgi), 12288); }
                PUSH_BEGIN();
                wg_wait<0>();
                R_RELEASE(1);
                int p = 0;
#pragma unroll 1
                do {
                    F1_EPI(H + 32, 8, ag)
                    STAMP(4 + p + so);
                    WSUM(81 + p + 7 * (step >> 1));
                    if (((trips >> (p + 1)) & 1) == 0) continue;
                    if (step == 1 && p == PKP) R_NEXT();
                    kill<64>(ag);
                    F1_BLOCK(0, false)
                    {
                        const uint32_t pk = (p ? hbuf + 16384 : sb + OFF_KVB + wgi * 8192) + w * 2048;
#pragma unroll
                        for (int k = 0; k < 4; k++) sts4(pk + k * 512 + lane * 16, H[32 + 4 * k], H[33 + 4 * k], H[34 + 4 * k], H[35 + 4 * k]);
                        fence_async();
                        __syncwarp();
                        asm volatile(ELECT "cp.async.bulk.shared::cluster.shared::cta.mbarrier::complete_tx::bytes [%0], [%1], 2048, [%2]; }"
                                     ::"r"(mapa(hbuf + p * 8192 + w * 2048, hr ^ 1)), "r"(pk), "r"(mapa(BAR(B_RECV + wgi), hr ^ 1)) : "memory");
                    }
                    F1_BLOCK(1, false) F1_BLOCK(2, false) F1_BLOCK(3, false)
                    wg_wait<0>();
                    R_RELEASE(1);
                    kill<16>(H + 32);
                } while (((trips >> (++p)) & 1));
#pragma unroll
                for (int k = 0; k < 4; k++) lds4(H + 16 + 4 * k, hbuf + 16384 + w * 2048 + k * 512 + lane * 16);
                __syncwarp();
                if (lane == 0) asm volatile("mbarrier.arrive.shared::cluster.b64 _, [%0];" ::"r"(mapa(BAR(B_ACK2 + wgi), hr ^ 1)) : "memory");
                const uint32_t rem_h = mapa(hbuf + w * 2048 + lane * 16, hr ^ 1);
#define F1_LAST(b0)                                                                            \
    R_WAIT();                                                                                  \
    if (b0) { PP_WAIT() }                                                                      \
    { DECL_DB(b0, BASE64, HALF, 1)                                                             \
    wg_fence();                                                                                \
    FOR7(mma_rs64<1, D64(0, t)>(al, AQ(A, b0, t), (b0) + t > 0, SWB(b0, t, db, 1)));           \
    FOR7(mma_rs64<1, D64(7168, t)>(al, AQ(A, (b0) + 1, t), 1, db)); }                          \
    wg_commit();                                                                               \
    if (b0) { PP_GO() }                                                                        \
    R_NEXT();
                float al[32];
                F1_LAST(0)
                mbar_wait(BAR(B_RECV + wgi), rcvph);
                rcvph ^= 1;
                mbar_wait(BAR(B_ACK2 + wgi), step >> 1);
                H_PUSH(32, 16384) H_PUSH(36, 16896)
                F1_LAST(2)
                H_PUSH(40, 17408) H_PUSH(44, 17920)
                wg_wait<1>();
                R_RELEASE(2);
                wg_wait<0>();
                R_RELEASE(1);
                uint32_t HP[56];
#pragma unroll
                for (int k = 0; k < 4; k++) lds4(H + 4 * k, sb + OFF_KVB + wgi * 8192 + w * 2048 + k * 512 + lane * 16);
#pragma unroll
                for (int t = 0; t < 8; t++) lds4(HP + 4 * t, hbuf + (t >> 2) * 8192 + w * 2048 + (t & 3) * 512 + lane * 16);
                F1_EPI(H + 48, 4, al)
                H_PUSH(48, 24576 - w * 1024) H_PUSH(52, 25088 - w * 1024)
                STAMP(7 + so);
                WSUM(84 + 7 * (step >> 1));
                FRESH();
                float acc[28];
                const uint32_t roA = hr ? 256u : 0u, roB = hr ? (uint32_t)-1536 : 0u;
                const uint32_t rpA = hr ? 0u : 256u, rpB = hr ? 0u : (uint32_t)-1536;
                float res[28];
                uint32_t v0[14], v1[14], P[14];
                const uint4* ps = xp0 + sl * 512;
#define F2_OWN_A()                                                                             \
    R_WAIT();                                                                                  \
    d0 = BASE128(0, 16, R_ADJ + roA); d1 = BASE128(0, 16, R_ADJ + roB);                        \
    wg_fence();                                                                                \
    FOR14(if constexpr (t < OT) mma_rs56<1, t * 128>(acc, H[4 * t], H[4 * t + 1], H[4 * t + 2], H[4 * t + 3], t > 0, d0)); \
    wg_commit();
#define F2_OWN_B()                                                                             \
    wg_fence();                                                                                \
    FOR14(if constexpr (t >= OT) mma_rs56<1, t * 128>(acc, H[4 * t], H[4 * t + 1], H[4 * t + 2], H[4 * t + 3], 1, t < 12 ? d0 : d1)); \
    wg_commit();                                                                               \
    R_NEXT();
#define F2_PEER()                                                                              \
    R_WAIT();                                                                                  \
    if (F2PP) { PP_WAIT() }                                                                    \
    d0 = BASE128(0, 16, R_ADJ + rpA); d1 = BASE128(0, 16, R_ADJ + rpB);                        \
    wg_fence();                                                                                \
    FOR14(mma_rs56<1, t * 128>(acc, HP[4 * t], HP[4 * t + 1], HP[4 * t + 2], HP[4 * t + 3], 1, t < 12 ? d0 : d1)); \
    wg_commit();                                                                               \
    if (F2PP) { PP_GO() }                                                                      \
    R_NEXT();
#define F2_TURN(u)                                                                             \
    wg_wait<1>();                                                                              \
    if ((u) < 2 || TDEF < 2) R_RELEASE(2);                                                     \
    wg_wait<0>();                                                                              \
    if ((u) < 2 || TDEF < 1) R_RELEASE(1);                                                     \
    _Pragma("unroll") for (int i = 0; i < 14; i++) P[i] = pack2(acc[2 * i], acc[2 * i + 1]);   \
    tag_slice(P, tag);                                                                         \
    asm volatile("" : RW4(P, 0), RW4(P, 4), RW4(P, 8), RW2(P, 12));                            \
    kill<28>(acc);                                                                             \
    F2_OWN_A()                                                                                 \
    if ((u) == 2) { slice_load<PL(3)>(v0, ps, lane); slice_load<PL(4)>(v1, ps, lane); } \
    send_slice<PL(3 + (u))>(xp0 + (2 * ((pr + (u) + 1) & 3) + hr) * 512, lane, P);             \
    seq++;                                                                                     \
    if (lane == 0) st_word(cx(sl), seq);                                                       \
    __syncwarp();                                                                              \
    STAMP(8 + (u) + so);                                                                       \
    F2_OWN_B()
                uint64_t d0, d1;
                F2_OWN_A()
                F2_OWN_B()
                R_WAIT();
                d0 = BASE128(0, 16, R_ADJ + rpA); d1 = BASE128(0, 16, R_ADJ + rpB);
                wg_fence();
                FOR8(mma_rs56<1, t * 128>(acc, HP[4 * t], HP[4 * t + 1], HP[4 * t + 2], HP[4 * t + 3], 1, d0));
                wg_commit();
                mbar_wait(BAR(B_RECV2 + wgi), step >> 1);
#pragma unroll
                for (int k = 0; k < 4; k++) lds4(HP + 32 + 4 * k, hbuf + 16384 + w * 2048 + k * 512 + lane * 16);
                lds4(HP + 48, hbuf + 24576 + w * 1024 + lane * 16);
                lds4(HP + 52, hbuf + 25088 + w * 1024 + lane * 16);
                if (step == 1) PUSH_ACK();
                wg_fence();
                FOR14(if constexpr (t >= 8) mma_rs56<1, t * 128>(acc, HP[4 * t], HP[4 * t + 1], HP[4 * t + 2], HP[4 * t + 3], 1, t < 12 ? d0 : d1));
                wg_commit();
                R_NEXT();
                F2_TURN(0)
                F2_PEER()
                F2_TURN(1)
                F2_PEER()
                F2_TURN(2)
                if (step == 1) STAMP(64);
                slice_check<PL(3)>(v0, ps, lane, tag);
                slice_check<PL(4)>(v1, ps, lane, tag);
#pragma unroll
                for (int i = 0; i < 14; i++) { res[2 * i] = bf_lo(v0[i]) + bf_lo(v1[i]); res[2 * i + 1] = bf_hi(v0[i]) + bf_hi(v1[i]); }
                slice_load<PL(2)>(X, ps, lane);
                if (step == 1) STAMP(65);
                F2_PEER()
                if (step == 1) STAMP(66);
                poll_cnt(cx(2 * ((pr + 1) & 3) + hr), seq);
                if (step == 1) STAMP(67);
                slice_load<PL(5)>(v0, ps, lane);
                x_fix(X, xbits);
                slice_check<PL(5)>(v0, ps, lane, tag);
                if (lane < TDEF) mbar_arrive(BAR(B_EMPTY + (slot + NST - 3 - lane) % NST));
#pragma unroll
                for (int i = 0; i < 14; i++) { res[2 * i] += bf_lo(v0[i]); res[2 * i + 1] += bf_hi(v0[i]); }
                STAMP(11 + so);
                wg_wait<0>();
                R_RELEASE(2);
                STAMP(12 + so);
                WSUM(85 + 7 * (step >> 1));
#pragma unroll
                for (int i = 0; i < 14; i++) X[i] = pack2(fmaf(res[2 * i] + acc[2 * i], 0.5f, bf_lo(X[i])), fmaf(res[2 * i + 1] + acc[2 * i + 1], 0.5f, bf_hi(X[i])));
            }
        }
        {
            const int m = lane >> 3, rr = lane & 7;
            const uint32_t ob = hbuf + w * 2048, rowa = ob + (rr + 8 * (m & 1)) * 112 + (m >> 1) * 16;
#pragma unroll
            for (int j = 0; j < 3; j++) stsm4(rowa + 32 * j, X[4 * j], X[4 * j + 1], X[4 * j + 2], X[4 * j + 3]);
            asm volatile("stmatrix.sync.aligned.m8n8.x2.shared.b16 [%0], {%1,%2};" ::"r"(ob + (rr + 8 * (m & 1)) * 112 + 96), "r"(X[12]), "r"(X[13]) : "memory");
            fence_async();
            __syncwarp();
            if (lane == 0) {
                asm volatile("cp.async.bulk.tensor.2d.global.shared::cta.bulk_group [%0, {%2, %3}], [%1];" ::"l"(&maps.out), "r"(ob), "r"(56 * sl), "r"(tile * 128 + wu * 16) : "memory");
                asm volatile("cp.async.bulk.commit_group;" ::: "memory");
                asm volatile("cp.async.bulk.wait_group.read 0;" ::: "memory");
            }
        }
        STAMP(50);
        GSTAMP(61);
        PDUMP();
    }
}

#undef g
#undef pr
#undef c
#undef t128

typedef CUresult (*EncodeFn)(CUtensorMap*, CUtensorMapDataType, cuuint32_t, void*, const cuuint64_t*, const cuuint64_t*, const cuuint32_t*,
                             const cuuint32_t*, CUtensorMapInterleave, CUtensorMapSwizzle, CUtensorMapL2promotion, CUtensorMapFloatOOBfill);

static void make_map(EncodeFn enc, CUtensorMap* m, const void* p, uint64_t cols, uint64_t rows, uint32_t bc, uint32_t br, CUtensorMapSwizzle sw) {
    cuuint64_t gd[2] = {cols, rows};
    cuuint64_t gs[1] = {cols * 2};
    cuuint32_t bd[2] = {bc, br};
    cuuint32_t es[2] = {1, 1};
    enc(m, CU_TENSOR_MAP_DATA_TYPE_BFLOAT16, 2, const_cast<void*>(p), gd, gs, bd, es, CU_TENSOR_MAP_INTERLEAVE_NONE, sw,
        CU_TENSOR_MAP_L2_PROMOTION_L2_128B, CU_TENSOR_MAP_FLOAT_OOB_FILL_NONE);
}

extern "C" void kernel_launch(void* const* d_in, const int* in_sizes, int n_in, void* d_out, int out_size) {
    (void)in_sizes; (void)n_in; (void)out_size;
    static EncodeFn enc = nullptr;
    static Scratch* scratch = nullptr;
    if (!enc) {
        void* fn = nullptr;
        cudaDriverEntryPointQueryResult qr;
        cudaGetDriverEntryPoint("cuTensorMapEncodeTiled", &fn, cudaEnableDefault, &qr);
        enc = (EncodeFn)fn;
        cudaGetSymbolAddress((void**)&scratch, g_scratch);
        cudaFuncSetAttribute(fused_kernel, cudaFuncAttributeMaxDynamicSharedMemorySize, SMEM_BYTES);
    }
    Maps maps;
    {
        cuuint64_t gd[3] = {64, 2048, 7};
        cuuint64_t gs[2] = {896, 128};
        cuuint32_t bd[3] = {64, 32, 7};
        cuuint32_t es[3] = {1, 1, 1};
        enc(&maps.x, CU_TENSOR_MAP_DATA_TYPE_BFLOAT16, 3, d_in[0], gd, gs, bd, es, CU_TENSOR_MAP_INTERLEAVE_NONE, CU_TENSOR_MAP_SWIZZLE_128B,
            CU_TENSOR_MAP_L2_PROMOTION_L2_128B, CU_TENSOR_MAP_FLOAT_OOB_FILL_NONE);
    }
    make_map(enc, &maps.out, d_out, 448, 2048, 56, 16, CU_TENSOR_MAP_SWIZZLE_NONE);
    make_map(enc, &maps.qkv, d_in[1], 1344, 448, 64, 112, CU_TENSOR_MAP_SWIZZLE_128B);
    make_map(enc, &maps.wo, d_in[3], 448, 448, 64, 112, CU_TENSOR_MAP_SWIZZLE_128B);
    make_map(enc, &maps.wg, d_in[5], 1792, 448, 64, 112, CU_TENSOR_MAP_SWIZZLE_128B);
    make_map(enc, &maps.wu, d_in[6], 1792, 448, 64, 112, CU_TENSOR_MAP_SWIZZLE_128B);
    make_map(enc, &maps.wg32, d_in[5], 1792, 448, 32, 112, CU_TENSOR_MAP_SWIZZLE_64B);
    make_map(enc, &maps.wu32, d_in[6], 1792, 448, 32, 112, CU_TENSOR_MAP_SWIZZLE_64B);
    make_map(enc, &maps.wd, d_in[7], 448, 1792, 64, 112, CU_TENSOR_MAP_SWIZZLE_128B);
    fused_kernel<<<128, 384, SMEM_BYTES>>>(scratch, (const __nv_bfloat16*)d_in[0], (const __nv_bfloat16*)d_in[2], 7, (const __nv_bfloat16*)d_in[5],
                                           (const __nv_bfloat16*)d_in[6], (const __nv_bfloat16*)d_in[7], maps);
}
```

```cpp
#include <cuda_runtime.h>
#include <cuda.h>
#include <cuda_bf16.h>
#include <stdint.h>
#include <type_traits>

#define PPF 2
#define PKP 0
#define TDEF 1
#define TMPF 0
#define NORM1 0
#define LPARK 1
#define PFN 9
#define PT0 3
#define L2T PT0
#define L3T PT0
#define ACAN 0
#define SPLIT0 1
#define OT 2
#define F2PP 0
#define PPK 2
#define QE 1
#define OST 1
#define PP

namespace {

constexpr uint32_t STAGE = 28672, HALF = 14336;
constexpr int NST = 5;
constexpr uint32_t OFF_H = NST * STAGE;
constexpr uint32_t OFF_KVB = OFF_H + 2 * STAGE;
constexpr uint32_t OFF_WPHI = OFF_KVB + 16384;
constexpr uint32_t OFF_XR = OFF_WPHI + 7168;
constexpr uint32_t OFF_BAR = OFF_XR + 6144;
constexpr uint32_t SMEM_BYTES = OFF_BAR + 384 + 1408;
constexpr int B_EMPTY = NST, B_RECV = 2 * NST, B_RECV2 = B_RECV + 2, B_PACK = B_RECV2 + 2, B_GAT = B_PACK + 1, B_LATE = B_GAT + 16, B_ACK = B_LATE + 1, B_ACK2 = B_ACK + 2, B_COUNT = B_ACK2 + 2;

constexpr int PACK = 14 + 4 * PKP;

struct Maps { CUtensorMap x, qkv, wo, wg, wu, wg32, wu32, wd, out; };

}

constexpr int PLANE = 16 * 2 * 8 * 512;
struct Scratch {
    uint4 ex[6 * PLANE];
    uint4 kv1[8 * 16 * 16 * 32];
    uint4 kv2[8 * 512];
    uint32_t c1[8 * 8 * 16 * 32];
    uint32_t cw[8 * 32];
    uint4 wp[8 * 32 * (HALF / 16)];
};
__device__ __align__(1024) Scratch g_scratch;
#define g_ex (sc->ex)
#define g_kv1 (sc->kv1)
#define g_kv2 (sc->kv2)
#define g_c1 (sc->c1)
#define g_cw (sc->cw)
#define g_wp (sc->wp)
#define STAMP(i)
#define GSTAMP(i)
#define PDUMP()
#define ASTAMP(i)

namespace {

__device__ __forceinline__ int fresh_tid() { int t; asm volatile("mov.u32 %0, %%tid.x;" : "=r"(t)); return t; }
template <int N> __device__ __forceinline__ void kill(uint32_t* v) {
#pragma unroll
    for (int i = 0; i < N; i++) v[i] = 0;
}
template <int N> __device__ __forceinline__ void kill(float* v) {
#pragma unroll
    for (int i = 0; i < N; i++) v[i] = 0.f;
}
__device__ __forceinline__ uint32_t s2u(const void* p) { return (uint32_t)__cvta_generic_to_shared(p); }
__device__ __forceinline__ void mbar_init(uint32_t a, uint32_t c) { asm volatile("mbarrier.init.shared::cta.b64 [%0], %1;" ::"r"(a), "r"(c) : "memory"); }
__device__ __forceinline__ void mbar_expect_tx(uint32_t a, uint32_t b) { asm volatile("mbarrier.arrive.expect_tx.shared::cta.b64 _, [%0], %1;" ::"r"(a), "r"(b) : "memory"); }
__device__ __forceinline__ void mbar_arrive(uint32_t a) { asm volatile("mbarrier.arrive.shared::cta.b64 _, [%0];" ::"r"(a) : "memory"); }
#define GIVE_UP(id) "trap;\n"
#define SPIN_MAX "0x400000"
#define SPIN_TAIL(id) "add.u32 n, n, 1;\n setp.lt.u32 p, n, " SPIN_MAX ";\n @p bra.uni LP;\n" GIVE_UP(id) " DN:\n }"
__device__ __forceinline__ void mbar_wait(uint32_t a, uint32_t ph) {
    asm volatile("{ .reg .pred p; .reg .b32 n; mov.u32 n, 0;\n LP:\n"
                 "mbarrier.try_wait.parity.shared::cta.b64 p, [%0], %1;\n @p bra DN;\n"
                 "add.u32 n, n, 1;\n setp.lt.u32 p, n, " SPIN_MAX ";\n @p bra LP;\n"
                 GIVE_UP("")
                 " DN:\n }" ::"r"(a), "r"(ph) : "memory");
}
#define ELECT "{ .reg .pred e; elect.sync _|e, 0xffffffff; @e "
__device__ __forceinline__ void tma2d(uint32_t dst, const CUtensorMap* m, int c0, int c1, uint32_t bar) {
    asm volatile(ELECT "cp.async.bulk.tensor.2d.shared::cluster.global.mbarrier::complete_tx::bytes [%0], [%1, {%3, %4}], [%2]; }" ::"r"(dst), "l"(m), "r"(bar), "r"(c0), "r"(c1) : "memory");
}
__device__ __forceinline__ void tma3x(uint32_t dst, const CUtensorMap* m, int row, uint32_t bar) {
    asm volatile(ELECT "cp.async.bulk.tensor.3d.shared::cluster.global.mbarrier::complete_tx::bytes [%0], [%1, {0, %3, 0}], [%2]; }" ::"r"(dst), "l"(m), "r"(bar), "r"(row) : "memory");
}
template <int OFF>
__device__ __forceinline__ void ld_pkt(uint32_t* v, const uint4* p) {
    asm volatile("{ .reg .b128 t; ld.relaxed.gpu.global.b128 t, [%4+%5]; mov.b128 {%0,%1,%2,%3}, t; }" : "=r"(v[0]), "=r"(v[1]), "=r"(v[2]), "=r"(v[3]) : "l"(p), "n"(OFF * 16) : "memory");
}
template <int OFF>
__device__ __forceinline__ void st_pkt(uint4* p, uint32_t a, uint32_t b, uint32_t c, uint32_t d) {
    asm volatile("{ .reg .b128 t; mov.b128 t, {%1,%2,%3,%4}; st.relaxed.gpu.global.b128 [%0+%5], t; }" ::"l"(p), "r"(a), "r"(b), "r"(c), "r"(d), "n"(OFF * 16) : "memory");
}
__device__ __forceinline__ uint32_t pack2(float lo, float hi) {
    uint32_t r;
    asm("cvt.rn.bf16x2.f32 %0, %1, %2;" : "=r"(r) : "f"(hi), "f"(lo));
    return r;
}
__device__ __forceinline__ float bf_lo(uint32_t w) { return __uint_as_float(w << 16); }
__device__ __forceinline__ float bf_hi(uint32_t w) { return __uint_as_float(w & 0xffff0000u); }
__device__ __forceinline__ uint32_t settag(uint32_t w, uint32_t tag) { return (w & ~1u) | tag; }
__device__ __forceinline__ float ex2(float x) { float y; asm("ex2.approx.ftz.f32 %0, %1;" : "=f"(y) : "f"(x)); return y; }
__device__ __forceinline__ float rcp(float x) { float y; asm("rcp.approx.ftz.f32 %0, %1;" : "=f"(y) : "f"(x)); return y; }
__device__ __forceinline__ float tanh_hw(float x) { float y; asm("tanh.approx.f32 %0, %1;" : "=f"(y) : "f"(x)); return y; }
__device__ __forceinline__ void stsm4(uint32_t addr, uint32_t a, uint32_t b, uint32_t c, uint32_t d) {
    asm volatile("stmatrix.sync.aligned.m8n8.x4.shared.b16 [%0], {%1,%2,%3,%4};" ::"r"(addr), "r"(a), "r"(b), "r"(c), "r"(d) : "memory");
}
__device__ __forceinline__ void fence_async() { asm volatile("fence.proxy.async.shared::cta;" ::: "memory"); }
__device__ __forceinline__ void bar_sync(int id, int n) { asm volatile("bar.sync %0, %1;" ::"r"(id), "r"(n) : "memory"); }
__device__ __forceinline__ void bar_arrive(int id, int n) { asm volatile("bar.arrive %0, %1;" ::"r"(id), "r"(n) : "memory"); }
__device__ __forceinline__ void wg_fence() { asm volatile("wgmma.fence.sync.aligned;" ::: "memory"); }
__device__ __forceinline__ void wg_commit() { asm volatile("wgmma.commit_group.sync.aligned;" ::: "memory"); }
template <int N> __device__ __forceinline__ void wg_wait() { asm volatile("wgmma.wait_group.sync.aligned %0;" ::"n"(N) : "memory"); }

constexpr uint32_t SB0 = 1024;
__host__ __device__ constexpr uint32_t dlo(uint32_t off, uint32_t lbo) { return ((SB0 + off) >> 4) | ((lbo >> 4) << 16); }
__host__ __device__ constexpr uint32_t dhi(uint32_t sbo, uint32_t sw) { return (sbo >> 4) | (sw << 30); }
__device__ __forceinline__ uint64_t dbase(uint32_t lo, uint32_t hi) { uint64_t d; asm volatile("mov.b64 %0, {%1, %2};" : "=l"(d) : "r"(lo), "r"(hi)); return d; }
#define BASE128(off, lbo, adj) dbase(dlo(off, lbo) + (adj), dhi(1024, 1))
#define BASE64(off, lbo, adj) dbase(dlo(off, lbo) + (adj), dhi(512, 2))

#define ACC4(d, o) "+f"(d[o]), "+f"(d[o + 1]), "+f"(d[o + 2]), "+f"(d[o + 3])
#define ACC28(d) ACC4(d, 0), ACC4(d, 4), ACC4(d, 8), ACC4(d, 12), ACC4(d, 16), ACC4(d, 20), ACC4(d, 24)
#define ACC32(d, o) ACC4(d, o), ACC4(d, o + 4), ACC4(d, o + 8), ACC4(d, o + 12), ACC4(d, o + 16), ACC4(d, o + 20), ACC4(d, o + 24), ACC4(d, o + 28)

template <int TB, uint64_t D>
__device__ __forceinline__ void mma_rs56(float* d, uint32_t a0, uint32_t a1, uint32_t a2, uint32_t a3, int sd, uint64_t base) {
    asm volatile("{ .reg .pred p; .reg .b64 db; setp.ne.b32 p, %32, 0; add.u64 db, %33, %34;\n"
                 "wgmma.mma_async.sync.aligned.m64n56k16.f32.bf16.bf16 "
                 "{%0,%1,%2,%3,%4,%5,%6,%7,%8,%9,%10,%11,%12,%13,%14,%15,%16,%17,%18,%19,%20,%21,%22,%23,%24,%25,%26,%27}, "
                 "{%28,%29,%30,%31}, db, p, 1, 1, %35; }\n"
                 : ACC28(d)
                 : "r"(a0), "r"(a1), "r"(a2), "r"(a3), "r"(sd), "l"(base), "n"(D), "n"(TB));
}
template <int TB, uint64_t D>
__device__ __forceinline__ void mma_rs64(float* d, uint32_t a0, uint32_t a1, uint32_t a2, uint32_t a3, int sd, uint64_t base) {
    asm volatile("{ .reg .pred p; .reg .b64 db; setp.ne.b32 p, %36, 0; add.u64 db, %37, %38;\n"
                 "wgmma.mma_async.sync.aligned.m64n64k16.f32.bf16.bf16 "
                 "{%0,%1,%2,%3,%4,%5,%6,%7,%8,%9,%10,%11,%12,%13,%14,%15,%16,%17,%18,%19,%20,%21,%22,%23,%24,%25,%26,%27,%28,%29,%30,%31}, "
                 "{%32,%33,%34,%35}, db, p, 1, 1, %39; }\n"
                 : ACC32(d, 0)
                 : "r"(a0), "r"(a1), "r"(a2), "r"(a3), "r"(sd), "l"(base), "n"(D), "n"(TB));
}
template <int TB, uint64_t D>
__device__ __forceinline__ void mma_rs128(float* d, uint32_t a0, uint32_t a1, uint32_t a2, uint32_t a3, int sd, uint64_t base) {
    asm volatile("{ .reg .pred p; .reg .b64 db; setp.ne.b32 p, %68, 0; add.u64 db, %69, %70;\n"
                 "wgmma.mma_async.sync.aligned.m64n128k16.f32.bf16.bf16 "
                 "{%0,%1,%2,%3,%4,%5,%6,%7,%8,%9,%10,%11,%12,%13,%14,%15,%16,%17,%18,%19,%20,%21,%22,%23,%24,%25,%26,%27,%28,%29,%30,%31,%32,%33,%34,%35,%36,%37,%38,%39,%40,%41,%42,%43,%44,%45,%46,%47,%48,%49,%50,%51,%52,%53,%54,%55,%56,%57,%58,%59,%60,%61,%62,%63}, "
                 "{%64,%65,%66,%67}, db, p, 1, 1, %71; }\n"
                 : ACC32(d, 0), ACC32(d, 32)
                 : "r"(a0), "r"(a1), "r"(a2), "r"(a3), "r"(sd), "l"(base), "n"(D), "n"(TB));
}
template <uint64_t DA, uint64_t DB>
__device__ __forceinline__ void mma_ss56_tt(float* d, int sd, uint64_t ba, uint64_t bb) {
    asm volatile("{ .reg .pred p; .reg .b64 da, db; setp.ne.b32 p, %28, 0; add.u64 da, %29, %31; add.u64 db, %30, %32;\n"
                 "wgmma.mma_async.sync.aligned.m64n56k16.f32.bf16.bf16 "
                 "{%0,%1,%2,%3,%4,%5,%6,%7,%8,%9,%10,%11,%12,%13,%14,%15,%16,%17,%18,%19,%20,%21,%22,%23,%24,%25,%26,%27}, "
                 "da, db, p, 1, 1, 1, 1; }\n"
                 : ACC28(d)
                 : "r"(sd), "l"(ba), "l"(bb), "n"(DA), "n"(DB));
}
template <int... I> struct Seq {};
template <class F, int... I> __device__ __forceinline__ void static_for_impl(F&& f, Seq<I...>) { (f(std::integral_constant<int, I>{}), ...); }
#define FOR7(...) static_for_impl([&](auto T_) { constexpr int t = decltype(T_)::value; __VA_ARGS__; }, Seq<0, 1, 2, 3, 4, 5, 6>{})
#define FOR8(...) static_for_impl([&](auto T_) { constexpr int t = decltype(T_)::value; __VA_ARGS__; }, Seq<0, 1, 2, 3, 4, 5, 6, 7>{})
#define FOR14(...) static_for_impl([&](auto T_) { constexpr int t = decltype(T_)::value; __VA_ARGS__; }, Seq<0, 1, 2, 3, 4, 5, 6, 7, 8, 9, 10, 11, 12, 13>{})

__device__ __forceinline__ int kblk(int p, int b) { return b == 0 ? p : b - (b <= p); }
__host__ __device__ constexpr int krow(int t) { return t < 3 ? 16 * t : (t < 6 ? 56 + 16 * (t - 3) : 48); }
#define AQ(A, b, t) ((t) < 3 ? A[2 * (b)][4 * (t)] : (t) < 6 ? A[2 * (b) + 1][4 * ((t) - 3)] : A[2 * (b)][12]), \
                    ((t) < 3 ? A[2 * (b)][4 * (t) + 1] : (t) < 6 ? A[2 * (b) + 1][4 * ((t) - 3) + 1] : A[2 * (b)][13]), \
                    ((t) < 3 ? A[2 * (b)][4 * (t) + 2] : (t) < 6 ? A[2 * (b) + 1][4 * ((t) - 3) + 2] : A[2 * (b) + 1][12]), \
                    ((t) < 3 ? A[2 * (b)][4 * (t) + 3] : (t) < 6 ? A[2 * (b) + 1][4 * ((t) - 3) + 3] : A[2 * (b) + 1][13])
#define D128(off, t) ((uint64_t)(((off) + krow(t) * 128) >> 4) + ((uint64_t)((t) == 6 ? (7168 - 1024) >> 4 : 0) << 32))
#define D64(off, t) ((uint64_t)(((off) + krow(t) * 64) >> 4) + ((uint64_t)((t) == 6 ? (3584 - 512) >> 4 : 0) << 32))

#define PL(k) (((k) - 3) * PLANE)
__device__ __forceinline__ void st_word(uint32_t* p, uint32_t v) { asm volatile("st.relaxed.gpu.global.u32 [%0], %1;" ::"l"(p), "r"(v) : "memory"); }
__device__ __forceinline__ uint32_t ld_word(const uint32_t* p) { uint32_t v; asm volatile("ld.relaxed.gpu.global.u32 %0, [%1];" : "=r"(v) : "l"(p) : "memory"); return v; }
__device__ __forceinline__ void tag_slice(uint32_t* w, uint32_t tag) { w[0] = settag(w[0], tag); w[4] = settag(w[4], tag); w[8] = settag(w[8], tag); w[12] = settag(w[12], tag); }
template <int O>
__device__ __forceinline__ void send_slice(uint4* dst, int lane, const uint32_t* w) {
    st_pkt<O>(dst, w[0], w[1], w[2], w[3]);
    st_pkt<O + 32>(dst, w[4], w[5], w[6], w[7]);
    st_pkt<O + 64>(dst, w[8], w[9], w[10], w[11]);
    asm volatile("{ .reg .b64 t; mov.b64 t, {%1,%2}; st.relaxed.gpu.global.b64 [%0+%3], t; }" ::"l"((char*)dst - lane * 8), "r"(w[12]), "r"(w[13]), "n"(16 * (O + 96)) : "memory");
}
#define RW4(v, o) "+r"(v[o]), "+r"(v[(o) + 1]), "+r"(v[(o) + 2]), "+r"(v[(o) + 3])
#define RW2(v, o) "+r"(v[o]), "+r"(v[(o) + 1])
#define WR4(v, o) "=&r"(v[o]), "=&r"(v[(o) + 1]), "=&r"(v[(o) + 2]), "=&r"(v[(o) + 3])
#define LDP(a, b, c, d, addr, off) "ld.relaxed.gpu.global.b128 q, [" addr "+" off "];\n mov.b128 {" a "," b "," c "," d "}, q;\n"
#define LDH(a, b, addr, off) "ld.relaxed.gpu.global.b64 h, [" addr "+" off "];\n mov.b64 {" a "," b "}, h;\n"
#define VOTE_OK "and.b32 t, t, 1;\n setp.ne.u32 p, t, 0;\n vote.sync.any.pred p, p, 0xffffffff;\n @!p bra.uni DN;\n"
#define CHK(x, tag) "lop3.b32 t, " x ", " tag ", t, 0xBE;\n"
__device__ __forceinline__ void check_cnt(uint32_t v, const uint32_t* p, uint32_t target) {
    asm volatile("{ .reg .pred p; .reg .b32 n, t; mov.u32 n, 0; mov.u32 t, %2;\n LP:\n"
                 "sub.s32 t, t, %1;\n setp.lt.s32 p, t, 0;\n vote.sync.any.pred p, p, 0xffffffff;\n @!p bra.uni DN;\n ld.relaxed.gpu.global.u32 t, [%0];\n" SPIN_TAIL("7")
                 ::"l"(p), "r"(target), "r"(v) : "memory");
}
__device__ __forceinline__ void poll_cnt(const uint32_t* p, uint32_t target) {
    asm volatile("{ .reg .pred p; .reg .b32 n, t; mov.u32 n, 0;\n LP:\n"
                 "ld.relaxed.gpu.global.u32 t, [%0];\n sub.s32 t, t, %1;\n setp.lt.s32 p, t, 0;\n vote.sync.any.pred p, p, 0xffffffff;\n @!p bra.uni DN;\n" SPIN_TAIL("1")
                 ::"l"(p), "r"(target) : "memory");
}
template <int STR>
__device__ __forceinline__ void poll4_kv(uint32_t* v, const uint4* p, uint32_t tag) {
    asm volatile("{ .reg .pred p; .reg .b32 n, t; .reg .b128 q; mov.u32 n, 0;\n LP:\n"
                 LDP("%0", "%1", "%2", "%3", "%16", "0") LDP("%4", "%5", "%6", "%7", "%16", "%18")
                 LDP("%8", "%9", "%10", "%11", "%16", "%19") LDP("%12", "%13", "%14", "%15", "%16", "%20")
                 "xor.b32 t, %0, %17;\n" CHK("%4", "%17") CHK("%8", "%17") CHK("%12", "%17") VOTE_OK SPIN_TAIL("2")
                 : WR4(v, 0), WR4(v, 4), WR4(v, 8), WR4(v, 12)
                 : "l"(p), "r"(tag), "n"(16 * STR), "n"(32 * STR), "n"(48 * STR)
                 : "memory");
}
template <int B>
__device__ __forceinline__ void blk_load(uint32_t (&A)[8][14], const uint4* src, int lane) {
    ld_pkt<0>(&A[2 * B][0], src); ld_pkt<32>(&A[2 * B][4], src); ld_pkt<64>(&A[2 * B][8], src);
    ld_pkt<512>(&A[2 * B + 1][0], src); ld_pkt<544>(&A[2 * B + 1][4], src); ld_pkt<576>(&A[2 * B + 1][8], src);
    asm volatile("{ .reg .b64 h;\n" LDH("%0", "%1", "%4", "1536") LDH("%2", "%3", "%4", "9728") "}"
                 : "=&r"(A[2 * B][12]), "=&r"(A[2 * B][13]), "=&r"(A[2 * B + 1][12]), "=&r"(A[2 * B + 1][13])
                 : "l"((const char*)src - lane * 8) : "memory");
}
template <int B>
__device__ __forceinline__ void blk_check(uint32_t (&A)[8][14], const uint4* src, int lane, uint32_t tag) {
    asm volatile("{ .reg .pred p; .reg .b32 n, t; .reg .b128 q; .reg .b64 h, a8; mov.u32 n, 0;\n LP:\n"
                 "xor.b32 t, %0, %30;\n" CHK("%4", "%30") CHK("%8", "%30") CHK("%12", "%30") CHK("%16", "%30") CHK("%20", "%30") CHK("%24", "%30") CHK("%26", "%30") VOTE_OK
                 LDP("%0", "%1", "%2", "%3", "%28", "0") LDP("%4", "%5", "%6", "%7", "%28", "512") LDP("%8", "%9", "%10", "%11", "%28", "1024")
                 LDP("%12", "%13", "%14", "%15", "%28", "8192") LDP("%16", "%17", "%18", "%19", "%28", "8704") LDP("%20", "%21", "%22", "%23", "%28", "9216")
                 "mad.wide.s32 a8, %29, -8, %28;\n" LDH("%24", "%25", "a8", "1536") LDH("%26", "%27", "a8", "9728") SPIN_TAIL("3")
                 "\n and.b32 %0, %0, -2; and.b32 %4, %4, -2; and.b32 %8, %8, -2; and.b32 %12, %12, -2; and.b32 %16, %16, -2; and.b32 %20, %20, -2; and.b32 %24, %24, -2; and.b32 %26, %26, -2;"
                 : RW4(A[2 * B], 0), RW4(A[2 * B], 4), RW4(A[2 * B], 8), RW4(A[2 * B + 1], 0), RW4(A[2 * B + 1], 4), RW4(A[2 * B + 1], 8),
                   RW2(A[2 * B], 12), RW2(A[2 * B + 1], 12)
                 : "l"(src), "r"(lane), "r"(tag)
                 : "memory");
}
__device__ __forceinline__ void st_async4(uint32_t a, uint32_t x, uint32_t y, uint32_t z, uint32_t w, uint32_t bar) {
    asm volatile("st.async.weak.shared::cluster.mbarrier::complete_tx::bytes.v4.b32 [%0], {%1,%2,%3,%4}, [%5];" ::"r"(a), "r"(x), "r"(y), "r"(z), "r"(w), "r"(bar) : "memory");
}
__device__ __forceinline__ uint32_t mapa(uint32_t a, uint32_t cta) { uint32_t r; asm("mapa.shared::cluster.u32 %0, %1, %2;" : "=r"(r) : "r"(a), "r"(cta)); return r; }
__device__ __forceinline__ void stat_load(uint32_t* v, const uint4* p) { ld_pkt<0>(v, p); ld_pkt<512>(v + 4, p); }
__device__ __forceinline__ void stat_check(uint32_t* v, const uint4* p, uint32_t tag) {
    asm volatile("{ .reg .pred p; .reg .b32 n, t; .reg .b128 q; mov.u32 n, 0;\n LP:\n"
                 "xor.b32 t, %3, %9;\n" CHK("%7", "%9") VOTE_OK
                 LDP("%0", "%1", "%2", "%3", "%8", "0") LDP("%4", "%5", "%6", "%7", "%8", "8192") SPIN_TAIL("4")
                 : RW4(v, 0), RW4(v, 4) : "l"(p), "r"(tag) : "memory");
}
__device__ __forceinline__ uint32_t x_bits(const uint32_t* X) {
    uint32_t r;
    asm volatile("{ .reg .b32 a, b; prmt.b32 a, %1, %2, 0x0040; prmt.b32 b, %3, %4, 0x0040; prmt.b32 %0, a, b, 0x5410; }" : "=r"(r) : "r"(X[0]), "r"(X[4]), "r"(X[8]), "r"(X[12]));
    return r;
}
template <int O>
__device__ __forceinline__ void slice_load(uint32_t* v, const uint4* p, int lane) {
    ld_pkt<O>(v, p); ld_pkt<O + 32>(v + 4, p); ld_pkt<O + 64>(v + 8, p);
    asm volatile("{ .reg .b64 h;\n" LDH("%0", "%1", "%2", "%3") "}" : "=r"(v[12]), "=r"(v[13]) : "l"((const char*)p - lane * 8), "n"(16 * (O + 96)) : "memory");
}
template <int O>
__device__ __forceinline__ void slice_check(uint32_t* v, const uint4* p, int lane, uint32_t tag) {
    asm volatile("{ .reg .pred p; .reg .b32 n, t; .reg .b128 q; .reg .b64 h; mov.u32 n, 0;\n LP:\n"
                 "xor.b32 t, %0, %16;\n" CHK("%4", "%16") CHK("%8", "%16") CHK("%12", "%16") VOTE_OK
                 LDP("%0", "%1", "%2", "%3", "%14", "%17") LDP("%4", "%5", "%6", "%7", "%14", "%18") LDP("%8", "%9", "%10", "%11", "%14", "%19")
                 LDH("%12", "%13", "%15", "%20") SPIN_TAIL("5")
                 : RW4(v, 0), RW4(v, 4), RW4(v, 8), RW2(v, 12)
                 : "l"(p), "l"((const char*)p - lane * 8), "r"(tag), "n"(16 * O), "n"(16 * (O + 32)), "n"(16 * (O + 64)), "n"(16 * (O + 96))
                 : "memory");
}
__device__ __forceinline__ void x_fix(uint32_t* X, uint32_t bits) {
    X[0] = __byte_perm(X[0], bits, 0x3214); X[4] = __byte_perm(X[4], bits, 0x3215); X[8] = __byte_perm(X[8], bits, 0x3216); X[12] = __byte_perm(X[12], bits, 0x3217);
}
__device__ __forceinline__ void sts4(uint32_t a, uint32_t x, uint32_t y, uint32_t z, uint32_t w) {
    asm volatile("st.shared.v4.u32 [%0], {%1,%2,%3,%4};" ::"r"(a), "r"(x), "r"(y), "r"(z), "r"(w) : "memory");
}
__device__ __forceinline__ void lds4(uint32_t* v, uint32_t a) {
    asm volatile("ld.shared.v4.u32 {%0,%1,%2,%3}, [%4];" : "=r"(v[0]), "=r"(v[1]), "=r"(v[2]), "=r"(v[3]) : "r"(a) : "memory");
}
struct LnCoef { uint32_t hi, lo, sh; };
__device__ __forceinline__ LnCoef ln_coef(float sum, float sq) {
    sum += __shfl_xor_sync(0xffffffffu, sum, 1); sq += __shfl_xor_sync(0xffffffffu, sq, 1);
    sum += __shfl_xor_sync(0xffffffffu, sum, 2); sq += __shfl_xor_sync(0xffffffffu, sq, 2);
    const float mean = sum * (1.f / 448.f);
    const float var = fmaxf(fmaf(-mean, mean, sq * (1.f / 448.f)), 0.f);
    const float sc = rsqrtf(var + 1e-5f);
    LnCoef r;
    r.hi = pack2(sc, sc);
    const float lo = sc - bf_lo(r.hi), sh = -mean * sc;
    r.lo = pack2(lo, lo);
    r.sh = pack2(sh, sh);
    return r;
}
template <int B>
__device__ __forceinline__ void normalize(uint32_t (&A)[8][14], const LnCoef& c0, const LnCoef& c1) {
#pragma unroll
    for (int s = 2 * B; s < 2 * B + 2; s++)
#pragma unroll
        for (int i = 0; i < 14; i++) {
            const LnCoef& k = (i & 1) ? c1 : c0;
            asm("{ .reg .b32 t; fma.rn.bf16x2 t, %0, %2, %3; fma.rn.bf16x2 %0, %0, %1, t; }" : "+r"(A[s][i]) : "r"(k.hi), "r"(k.lo), "r"(k.sh));
        }
}
__device__ __forceinline__ void slice_stats(const uint32_t* w, float* st) {
    float a = 0.f, b = 0.f, p = 0.f, q = 0.f;
#pragma unroll
    for (int i = 0; i < 7; i++) {
        const float e0 = bf_lo(w[2 * i]), e1 = bf_hi(w[2 * i]), e2 = bf_lo(w[2 * i + 1]), e3 = bf_hi(w[2 * i + 1]);
        a += e0 + e1; b += e2 + e3;
        p = fmaf(e0, e0, p); p = fmaf(e1, e1, p); q = fmaf(e2, e2, q); q = fmaf(e3, e3, q);
    }
    a += __shfl_xor_sync(0xffffffffu, a, 1); p += __shfl_xor_sync(0xffffffffu, p, 1); b += __shfl_xor_sync(0xffffffffu, b, 1); q += __shfl_xor_sync(0xffffffffu, q, 1);
    a += __shfl_xor_sync(0xffffffffu, a, 2); p += __shfl_xor_sync(0xffffffffu, p, 2); b += __shfl_xor_sync(0xffffffffu, b, 2); q += __shfl_xor_sync(0xffffffffu, q, 2);
    st[0] = a; st[1] = p; st[2] = b; st[3] = q;
}
__device__ __forceinline__ void dual_softmax(const float* p, uint32_t* out) {
    constexpr float L = 1.4426950408889634f;
#pragma unroll
    for (int r = 0; r < 2; r++) {
        float mx = fmaxf(p[2 * r], p[2 * r + 1]), mn = fminf(p[2 * r], p[2 * r + 1]);
#pragma unroll
        for (int i = 1; i < 7; i++) {
            mx = fmaxf(mx, fmaxf(p[4 * i + 2 * r], p[4 * i + 2 * r + 1]));
            mn = fminf(mn, fminf(p[4 * i + 2 * r], p[4 * i + 2 * r + 1]));
        }
        mx = fmaxf(mx, __shfl_xor_sync(0xffffffffu, mx, 1));
        mn = fminf(mn, __shfl_xor_sync(0xffffffffu, mn, 1));
        const float bx = -mx * L, bn = mn * L;
        float ep[14], en[14], sp = 0.f, sn = 0.f;
#pragma unroll
        for (int i = 0; i < 14; i++) {
            const float v = p[4 * (i >> 1) + 2 * r + (i & 1)];
            ep[i] = ex2(fmaf(v, L, bx));
            en[i] = ex2(fmaf(v, -L, bn));
            sp += ep[i]; sn += en[i];
        }
        sp += __shfl_xor_sync(0xffffffffu, sp, 1);
        sn += __shfl_xor_sync(0xffffffffu, sn, 1);
        const float ip = rcp(sp), in = rcp(sn);
#pragma unroll
        for (int i = 0; i < 7; i++) {
            out[4 * i + r] = pack2(ep[2 * i] * ip, ep[2 * i + 1] * ip);
            out[4 * i + 2 + r] = pack2(en[2 * i] * in, en[2 * i + 1] * in);
        }
    }
}
__device__ __forceinline__ float geglu(float g, float u) {
    const float t = tanh_hw(g * fmaf(g * g, 0.7978845608028654f * 0.044715f, 0.7978845608028654f));
    const float gu = g * u;
    return fmaf(t, gu, gu);
}
__device__ __forceinline__ void phi_gemm(const float* t, float* p) {
    uint32_t w[14];
#pragma unroll
    for (int i = 0; i < 14; i++) w[i] = pack2(t[2 * i], t[2 * i + 1]);
    const uint64_t db = BASE128(OFF_WPHI, 16, 0);
    wg_fence();
    mma_rs56<0, 0>(p, w[0], w[1], w[2], w[3], 0, db);
    mma_rs56<0, 2>(p, w[4], w[5], w[6], w[7], 1, db);
    mma_rs56<0, 4>(p, w[8], w[9], w[10], w[11], 1, db);
    mma_rs56<0, 6>(p, w[12], w[13], 0u, 0u, 1, db);
    wg_commit();
    wg_wait<0>();
}

}

#define BAR(i) (bars + 8 * (i))
#define R_WAIT() mbar_wait(BAR(slot), ph)
#define WSUM(i)
#define R_ADJ (slot * (STAGE >> 4))
#define R_NEXT() do { eb2 = eb1; eb1 = BAR(B_EMPTY + slot); if (++slot == NST) { slot = 0; ph ^= 1; } } while (0)
#define R_RELEASE(k) do { if (lane == 0) mbar_arrive((k) == 1 ? eb1 : eb2); } while (0)
#define PUSH_BEGIN() do { mbar_wait(BAR(B_ACK + wgi), ackph); ackph ^= 1; } while (0)
#define PUSH_ACK() do { __syncwarp(); if (lane == 0) asm volatile("mbarrier.arrive.shared::cluster.b64 _, [%0];" ::"r"(mapa(BAR(B_ACK + wgi), hr ^ 1)) : "memory"); } while (0)

__global__ void __cluster_dims__(2, 1, 1) __launch_bounds__(384, 1)
fused_kernel(Scratch* const sc, const __nv_bfloat16* __restrict__ x_in, const __nv_bfloat16* __restrict__ w_phi, const int trips,
             const __nv_bfloat16* __restrict__ wg, const __nv_bfloat16* __restrict__ wu, const __nv_bfloat16* __restrict__ wd,
             const __grid_constant__ Maps maps) {
    extern __shared__ __align__(1024) unsigned char smem_raw[];
    const uint32_t sb = s2u(smem_raw);
    const uint32_t bars = sb + OFF_BAR;
    const int wgi = __shfl_sync(0xffffffffu, threadIdx.x >> 7, 0);
    const int hr = blockIdx.x & 1, ck = blockIdx.x >> 1;
    const int gp = (ck - 4) & 7, q7 = ((ck - 36) * 37) >> 8;
    const int pr = __shfl_sync(0xffffffffu, ck < 4 ? ck : (ck < 36 ? (ck - 4) >> 3 : q7), 0);
    const int tile = __shfl_sync(0xffffffffu, ck < 4 ? 0 : (ck < 36 ? (gp ? 2 * gp : 1) : 2 * (ck - 36 - 7 * q7) + 3), 0);
    const int sl = 2 * pr + hr;
    STAMP(0);
    GSTAMP(60);
    if (threadIdx.x == 256) {
#pragma unroll
        for (int i = 0; i < NST; i++) mbar_init(BAR(i), 1);
        asm volatile("fence.mbarrier_init.release.cluster;" ::: "memory");
    }
    if (threadIdx.x == 288) {
        if ((sb & 0x3FFFF) != SB0) asm volatile("trap;");
#pragma unroll
        for (int i = NST; i < B_COUNT; i++) mbar_init(BAR(i), i >= B_ACK ? 4 : (i < B_RECV || i == B_LATE ? 8 : 1));
        asm volatile("fence.mbarrier_init.release.cluster;" ::: "memory");
    }
    __syncwarp();
    asm volatile("barrier.cluster.arrive.relaxed.aligned;" ::: "memory");

    if (wgi == 2) {
        asm volatile("setmaxnreg.dec.sync.aligned.u32 40;");
        const int t128 = fresh_tid() & 127, w = __shfl_sync(0xffffffffu, t128 >> 5, 0), lane = t128 & 31;
        uint32_t e0[2] = {0, 0}, e1[2] = {0, 0}, cw_target = 0, kseq;
        if (w == 0) {
#pragma unroll 1
            for (int n = 0; n < NST; n++) {
                const uint32_t dst = sb + n * STAGE, fb = BAR(n);
                asm volatile(ELECT "mbarrier.arrive.expect_tx.shared::cta.b64 _, [%0], %1; }" ::"r"(fb), "r"(n < 2 ? 2 * STAGE : STAGE) : "memory");
                if (n < 2) {
                    tma3x(sb + OFF_H + n * STAGE, &maps.x, tile * 128 + n * 64, fb);
                    tma3x(dst, &maps.x, tile * 128 + n * 64 + 32, fb);
                } else {
                    if (n == 3) mbar_wait(BAR(1), 0);
                    const int ra = 112 * (n - 2);
                    tma2d(dst, &maps.qkv, 448 + 56 * sl, ra, fb);
                    tma2d(dst + HALF, &maps.qkv, 896 + 56 * sl, ra, fb);
                }
            }
            asm volatile("barrier.cluster.wait.aligned;" ::: "memory");
            kseq = ld_word(g_c1 + (sl * 8 * 16 + tile) * 32);
            cw_target = (ld_word(g_cw + sl * 32) & ~15u) + 16;
#pragma unroll 1
            for (int k = 0; k < 2; k++) {
                const int n = t128 + 32 * k;
                int m = n - 2 - (n > PACK);
                const bool packed = m >= 30 ? (m < 38 || m >= 52) : m >= 22;
                if (m >= 30) m -= 30;
                if (n == PACK) m = tile < 8 ? tile : tile + 14;
                const int rot = n < 8 ? 0 : pr;
                const int ra = 112 * kblk(rot, m & 3), rb = 112 * kblk(rot, 2 * m & 3), rc = 112 * kblk(rot, (2 * m + 1) & 3);
                int kind = 0, m0, m1, c0, c1, r0, r1;
                if (m < 4) { m0 = m1 = 1; c0 = 448 + 56 * sl; c1 = c0 + 448; r0 = r1 = ra; }
                else if (m < 8) { m0 = m1 = m < 6 ? 1 : 2; c0 = c1 = 56 * sl; r0 = rb; r1 = rc; }
                else if (m < 20) { m0 = 3; m1 = 4; c0 = c1 = 224 * sl + 32 * hr + 64 * ((m - 8) >> 2); r0 = r1 = ra; }
                else if (m < 22) { kind = 2; m0 = 5; m1 = 6; c0 = c1 = 224 * sl + (hr ? 0 : 192); r0 = rb; r1 = rc; }
                else { m0 = m1 = 7; c0 = c1 = 56 * (2 * ((pr + (m >> 1) - 10) & 3) + hr); r0 = 224 * (sl ^ (m & 1)); r1 = r0 + 112; }
                if (packed) { kind = 1; r0 = sl * 16 + (m < 8 ? m : m - 14); r1 = 0; }
                e0[0] = e0[1]; e1[0] = e1[1];
                e0[1] = kind | (m0 << 2) | (m1 << 6) | (c0 << 10) | (c1 << 21);
                e1[1] = r0 | (r1 << 16);
            }
        } else {
            const int j = t128 - 32;
            kseq = ld_word(g_c1 + (sl * 8 * 16 + tile) * 32);
            asm volatile("barrier.cluster.wait.aligned;" ::: "memory");
            uint2 wv[7];
            const int k = j < 56 ? j : 55, hh = k >= 28;
#pragma unroll
            for (int i = 0; i < 7; i++) wv[i] = __ldg(reinterpret_cast<const uint2*>(w_phi + (sl * 56 + k) * 28) + i);
#pragma unroll 1
            for (int i = j; i < 7168 / 16; i += 96) sts4(sb + OFF_WPHI + i * 16, 0, 0, 0, 0);
            bar_sync(5, 96);
            if (j < 56) {
                uint32_t a4[4];
#pragma unroll
                for (int q = 0; q < 4; q++) a4[q] = sb + OFF_WPHI + (4 * hh + q) * 128 + ((((k >> 3) ^ (4 * hh + q)) & 7) << 4) + (k & 7) * 2;
                FOR14(const uint32_t v = (t & 1) ? wv[t >> 1].y : wv[t >> 1].x;
                      asm volatile("{ .reg .b16 l, h; mov.b32 {l, h}, %2; st.shared.u16 [%0+%3], l; st.shared.u16 [%1+%3], h; }"
                                   ::"r"(a4[t >= 7 ? 2 : 0]), "r"(a4[t >= 7 ? 3 : 1]), "r"(v), "n"((t % 7) * 1024) : "memory"));
            }
            __syncwarp();
            fence_async();
            kseq = __shfl_sync(0xffffffffu, kseq, 0);
            bar_arrive(1, 224);
            bar_arrive(9, 224);
        }
        kseq = __shfl_sync(0xffffffffu, kseq, 0);
        int slot = 0, ph = 0, n = NST;
#pragma unroll 1
        for (int layer = 0; layer < 3; layer++) {
            if (w == 0) {
                const int nend = layer == 0 ? 11 : (layer == 1 ? 42 : 63);
#pragma unroll 1
                for (; n < nend; n++) {
                const uint32_t w0 = __shfl_sync(0xffffffffu, n < 32 ? e0[0] : e0[1], n & 31), w1 = __shfl_sync(0xffffffffu, n < 32 ? e1[0] : e1[1], n & 31);
                const uint32_t dst = sb + slot * STAGE, fb = BAR(n == PACK ? B_PACK : slot);
                const CUtensorMap* m0 = &maps.x + ((w0 >> 2) & 15);
                const CUtensorMap* m1 = &maps.x + ((w0 >> 6) & 15);
                const int c0 = (w0 >> 10) & 2047, c1 = w0 >> 21, r0 = w1 & 0xffff, r1 = w1 >> 16;
                if (n == 25) {
                    int it = 0;
                    uint32_t v;
                    do { asm volatile("ld.acquire.gpu.global.u32 %0, [%1];" : "=r"(v) : "l"(g_cw + sl * 32) : "memory"); } while ((int)(v - cw_target) < 0 && ++it < 0x400000);
                    asm volatile("fence.proxy.async.global;" ::: "memory");
                    __syncwarp();
                }
                mbar_wait(BAR(B_EMPTY + slot), ph);
                __syncwarp();
                asm volatile(ELECT "mbarrier.arrive.expect_tx.shared::cta.b64 _, [%0], %1; }" ::"r"(fb), "r"(STAGE) : "memory");
                if ((w0 & 3) == 0) {
                    tma2d(dst, m0, c0, r0, fb);
                    tma2d(dst + HALF, m1, c1, r1, fb);
                } else if (w0 & 1) {
                    asm volatile(ELECT "cp.async.bulk.shared::cluster.global.mbarrier::complete_tx::bytes [%0], [%1], %2, [%3]; }"
                                 ::"r"(dst), "l"(reinterpret_cast<const char*>(g_wp) + (size_t)r0 * STAGE), "r"(STAGE), "r"(fb) : "memory");
                } else {
                    tma2d(dst, m0, c0, r0, fb); tma2d(dst + 7168, m0, c0, r1, fb);
                    tma2d(dst + HALF, m1, c0, r0, fb); tma2d(dst + HALF + 7168, m1, c0, r1, fb);
                }
                if (n == PFN) {
                    const int b = blockIdx.x;
                    asm volatile(ELECT "cp.async.bulk.prefetch.L2.global [%0], %1; }" ::"l"(wg + b * 6272), "r"(12544) : "memory");
                    asm volatile(ELECT "cp.async.bulk.prefetch.L2.global [%0], %1; }" ::"l"(wu + b * 6272), "r"(12544) : "memory");
                    asm volatile(ELECT "cp.async.bulk.prefetch.L2.global [%0], %1; }" ::"l"(wd + b * 6272), "r"(12544) : "memory");
                }
                if (n == PACK) asm volatile(ELECT "mbarrier.arrive.shared::cta.b64 _, [%0]; }" ::"r"(BAR(slot)) : "memory");
                if (++slot == NST) { slot = 0; ph ^= 1; }
                }
            } else if (w == 1 && layer == 1) {
                constexpr int ps = PACK % NST;
                mbar_wait(BAR(B_PACK), 0);
                asm volatile("{ .reg .pred e; elect.sync _|e, 0xffffffff;\n"
                             "@e cp.async.bulk.global.shared::cta.bulk_group [%0], [%1], %2;\n"
                             "@e cp.async.bulk.commit_group;\n"
                             "@e cp.async.bulk.wait_group.read 0;\n"
                             "@e mbarrier.arrive.shared::cta.b64 _, [%3], 8;\n"
                             "@e cp.async.bulk.wait_group 0;\n"
                             "@e fence.proxy.async.global;\n"
                             "@e red.release.gpu.global.add.u32 [%4], 1; }"
                             ::"l"(reinterpret_cast<char*>(g_wp) + (size_t)(sl * 16 + tile) * STAGE), "r"(sb + ps * STAGE), "r"(STAGE), "r"(BAR(B_EMPTY + ps)), "l"(g_cw + sl * 32) : "memory");
                __syncwarp();
            }
            if (layer < 2) {
            const uint32_t tag = layer ^ 1;
            kseq++;
            bar_sync(7, 384);
            ASTAMP(0);
            if (tile < 15) {
                const int sq = lane >> 3, pk = 8 * w + (lane & (tile == 14 ? 3 : 7));
                uint32_t v[16];
                if (layer == 0) poll_cnt(g_c1 + ((sl * 8 + (w >> 1) * 4 + (tile >> 2)) * 16 + (lane & 15)) * 32, kseq);
                ASTAMP(1);
                poll4_kv<32>(v, g_kv1 + ((sl * 16 + tile) * 16 + 4 * sq) * 32 + pk, tag);
#pragma unroll
                for (int k = 0; k < 4; k++) {
                    float lo = (bf_lo(v[k]) + bf_lo(v[4 + k])) + (bf_lo(v[8 + k]) + bf_lo(v[12 + k]));
                    float hi = (bf_hi(v[k]) + bf_hi(v[4 + k])) + (bf_hi(v[8 + k]) + bf_hi(v[12 + k]));
                    lo += __shfl_xor_sync(0xffffffffu, lo, 8); hi += __shfl_xor_sync(0xffffffffu, hi, 8);
                    lo += __shfl_xor_sync(0xffffffffu, lo, 16); hi += __shfl_xor_sync(0xffffffffu, hi, 16);
                    v[k] = pack2(lo, hi);
                }
                if (sq == 0) st_pkt<0>(g_kv2 + sl * 512 + 32 * tile + pk, settag(v[0], tag), v[1], v[2], v[3]);
            }
            ASTAMP(2);
            {
                const int item = t128 < 112 ? t128 : 112 + (t128 & 3), d = item >> 1;
                const int cc = t128 < 112 ? 2 * (d >= 28) + (item & 1) : item - 112;
                const int r = t128 < 112 ? d : 56 + (cc >> 1) + 2 * ((t128 - 112) >> 2);
                uint32_t ra = sb + OFF_KVB + r * 128 + 4 * cc, rx = (r & 7) << 4;
                asm volatile("" : "+r"(ra), "+r"(rx));
                FOR14(asm volatile("st.shared.u32 [%0+%2], %1;" ::"r"((ra ^ 8) + (((t & 7) << 4) ^ rx)), "r"(0), "n"((t >> 3) * 8192) : "memory"));
                uint32_t v[16];
                asm volatile("" : "+r"(ra), "+r"(rx));
                poll4_kv<8>(v, g_kv2 + sl * 512 + (item >> 3) * 32 + (item & 7), tag);
                FOR14(asm volatile("st.shared.u32 [%0+%2], %1;" ::"r"(ra + (((t & 7) << 4) ^ rx)), "r"(v[t < 7 ? t : t + 1]), "n"((t >> 3) * 8192) : "memory"));
                fence_async();
            }
            bar_arrive(3, 384);
            ASTAMP(3);
            }
        }
    } else {
        asm volatile("setmaxnreg.inc.sync.aligned.u32 232;");
        int lane = fresh_tid() & 31, prf = pr;
#define pr prf
#define g (lane >> 2)
#define c (lane & 3)
#define t128 (w * 32 + lane)
        const int wu = __shfl_sync(0xffffffffu, fresh_tid() >> 5, 0), w = wu & 3;
        const uint32_t xoff = __shfl_sync(0xffffffffu, (3 * PLANE + ((tile * 2 + wgi) * 8) * 512 + w * 128) * 16, 0);
        char* xu = reinterpret_cast<char*>(g_ex) + xoff;
#define FRESH() asm volatile("" : "+l"(xu), "+r"(lane), "+r"(prf))
#define xp0 (reinterpret_cast<uint4*>(xu) + lane)
        const uint32_t hbuf = sb + OFF_H + wgi * STAGE;
        uint32_t slot = 0, ph = 0, eb1 = 0, eb2 = 0, ackph = 0, rcvph = 0, gatph = 0, swp = 0;
        uint32_t ppid = 6;
#define cx(s) (reinterpret_cast<uint32_t*>(reinterpret_cast<uint4*>(xu) + PL(1) + 112 + (s) * 512))
#define stp (reinterpret_cast<uint4*>(xu) + g + PL(0) + 112)
        uint32_t seq = ld_word(cx(sl));
        uint32_t kseq = ld_word(g_c1 + ((sl * 8 + wu) * 16 + tile) * 32);
        uint32_t stag = ld_word(reinterpret_cast<const uint32_t*>(stp + sl * 512) + 3) & 1;
        asm volatile("barrier.cluster.wait.aligned;" ::: "memory");
        STAMP(1);
        uint32_t X[14];
        const uint32_t x0row = (w < 2 ? hbuf : sb + wgi * STAGE) + ((w & 1) * 16 + (lane & 15)) * 128;
        mbar_wait(BAR(wgi), 0);
        STAMP(51);
#pragma unroll
        for (int j = 0; j < 4; j++) {
            const int G = 7 * sl + min(2 * j + (lane >> 4), 6);
            uint32_t q2, q3;
            asm volatile("ldmatrix.sync.aligned.m8n8.x4.shared.b16 {%0,%1,%2,%3}, [%4];" : "=r"(X[4 * j]), "=r"(X[4 * j + 1]), "=r"(q2), "=r"(q3)
                         : "r"(x0row + (G >> 3) * 4096 + (((G ^ lane) & 7) << 4)) : "memory");
            if (j < 3) { X[(4 * j + 2) % 14] = q2; X[(4 * j + 3) % 14] = q3; }
        }
#define PUSH_SLICE(W)                                                                          \
    {                                                                                          \
        if (t128 == 0) mbar_expect_tx(BAR(B_RECV + wgi), 7168);                                \
        PUSH_BEGIN();                                                                          \
        const uint32_t ra = mapa(hbuf + 24576 + t128 * 16, hr ^ 1), rb = mapa(sb + OFF_XR + wgi * 3072, hr ^ 1), rbar = mapa(BAR(B_RECV + wgi), hr ^ 1); \
        st_async4(ra, W[0], W[1], W[2], W[3], rbar);                                           \
        st_async4(ra + 2048, W[4], W[5], W[6], W[7], rbar);                                    \
        st_async4(rb + t128 * 16, W[8], W[9], W[10], W[11], rbar);                             \
        asm volatile("st.async.weak.shared::cluster.mbarrier::complete_tx::bytes.v2.b32 [%0], {%1,%2}, [%3];" ::"r"(rb + 2048 + t128 * 8), "r"(W[12]), "r"(W[13]), "r"(rbar) : "memory"); \
    }
#define PULL_SLICE(W)                                                                          \
    {                                                                                          \
        uint32_t t0, t1;                                                                       \
        mbar_wait(BAR(B_RECV + wgi), rcvph);                                                   \
        rcvph ^= 1;                                                                            \
        lds4(&A[1][0], hbuf + 24576 + t128 * 16);                                              \
        lds4(&A[1][4], hbuf + 26624 + t128 * 16);                                              \
        lds4(&A[1][8], sb + OFF_XR + wgi * 3072 + t128 * 16);                                  \
        asm volatile("ld.shared.v2.u32 {%0,%1}, [%2];" : "=r"(t0), "=r"(t1) : "r"(sb + OFF_XR + wgi * 3072 + 2048 + t128 * 8) : "memory"); \
        _Pragma("unroll") for (int i = 0; i < 12; i++) A[0][i] = (i & 3) ? W[i] : W[i] & ~1u;  \
        A[1][0] &= ~1u; A[1][4] &= ~1u; A[1][8] &= ~1u;                                        \
        A[0][12] = (hr ? t0 : W[12]) & ~1u; A[0][13] = hr ? t1 : W[13];                        \
        A[1][12] = (hr ? W[12] : t0) & ~1u; A[1][13] = hr ? W[13] : t1;                        \
        asm volatile("" : RW4(A[0], 0), RW4(A[0], 4), RW4(A[0], 8), RW2(A[0], 12), RW4(A[1], 0), RW4(A[1], 4), RW4(A[1], 8), RW2(A[1], 12)); \
        swp = hr * 448;                                                                        \
    }
#define SWB(b, t, db, sh) ((b) == 0 && (t) < 6 ? ((t) < 3 ? db##p : db##m) : db)
#define DECL_DB(b, MK, lbo, sh) const uint64_t db = MK(0, lbo, R_ADJ), dbp = (b) == 0 ? MK(0, lbo, R_ADJ + (swp >> (sh))) : db, dbm = (b) == 0 ? MK(0, lbo, R_ADJ - (swp >> (sh))) : db;
#define PPB 2
#define PP_WAIT() if (wgi == 1) { bar_sync(ppid, 256); ppid ^= 14; }
#define PP_GO() if (wgi == 0) { bar_arrive(ppid, 256); ppid ^= 14; }
#define GAT_DST(B, s2) ((B) == 1 ? hbuf + w * 3584 + (s2) * 1792 : ((s2) ? sb + OFF_KVB + wgi * 8192 : hbuf + 14336) + w * 1792)
#define GAT_ISSUE(B, base)                                                                     \
    {                                                                                          \
        const char* gs = xu + ((base) + kblk(pr, B) * 1024) * 16;                              \
        asm volatile("{ .reg .pred e; elect.sync _|e, 0xffffffff;\n"                           \
                     "@e mbarrier.arrive.expect_tx.shared::cta.b64 _, [%3], 3584;\n"           \
                     "@e cp.async.bulk.shared::cluster.global.mbarrier::complete_tx::bytes [%0], [%2], 1792, [%3];\n" \
                     "@e cp.async.bulk.shared::cluster.global.mbarrier::complete_tx::bytes [%1], [%2+8192], 1792, [%3]; }" \
                     ::"r"(GAT_DST(B, 0)), "r"(GAT_DST(B, 1)), "l"(gs), "r"(BAR(B_GAT + wu * 2 + ((B) >> 1))) : "memory"); \
        __syncwarp();                                                                          \
    }
#define GAT_FETCH(B)                                                                           \
    {                                                                                          \
        mbar_wait(BAR(B_GAT + wu * 2 + ((B) >> 1)), (gatph >> (B)) & 1);                          \
        gatph ^= 1 << (B);                                                                     \
        _Pragma("unroll") for (int s2 = 0; s2 < 2; s2++) {                                     \
            const uint32_t ga = GAT_DST(B, s2) + lane * 16;                                    \
            lds4(&A[2 * (B) + s2][0], ga); lds4(&A[2 * (B) + s2][4], ga + 512); lds4(&A[2 * (B) + s2][8], ga + 1024); \
            asm volatile("ld.shared.v2.u32 {%0,%1}, [%2];" : "=r"(A[2 * (B) + s2][12]), "=r"(A[2 * (B) + s2][13]) : "r"(ga - lane * 8 + 1536) : "memory"); \
        }                                                                                      \
    }
#define LATE_ARRIVE() do { if (lane == 0) mbar_arrive(BAR(B_LATE)); } while (0)
#define LATE_WAIT() do { mbar_wait(BAR(B_LATE), gatph & 1); gatph ^= 1; } while (0)
#define PT 3
#define PREP(b, t, remote)                                                                     \
    if constexpr ((b) == 0 && (t) == L2T && L2T != PT0) { if (remote) blk_load<2>(A, BLK(xsrc, 2), lane); } \
    if constexpr ((b) == 0 && (t) == L3T && L3T != PT0) { if (remote) blk_load<3>(A, BLK(xsrc, 3), lane); } \
    if constexpr ((b) < 3 && (t) == ((b) ? PT : PT0)) {                                                      \
        wg_commit();                                                                           \
        STAMP(74 + 6 * (step & 1) + 2 * (b));                                                  \
        if (remote) {                                                                          \
            if constexpr ((b) == 0) { if (L2T == PT0) blk_load<2>(A, BLK(xsrc, 2), lane); GAT_FETCH(1) }       \
            blk_check<((b) + 1) & 3>(A, BLK(xsrc, (b) + 1), lane, xtag);                       \
            if constexpr ((b) == 0 && L3T == PT0) blk_load<3>(A, BLK(xsrc, 3), lane);                        \
        }                                                                                      \
        STAMP(75 + 6 * (step & 1) + 2 * (b));                                                  \
        normalize<((b) + 1) & 3>(A, k0, k1);                                                   \
        asm volatile("" : RW4(A[(2 * (b) + 2) & 7], 0), RW4(A[(2 * (b) + 2) & 7], 4), RW4(A[(2 * (b) + 2) & 7], 8), RW2(A[(2 * (b) + 2) & 7], 12), \
                          RW4(A[(2 * (b) + 3) & 7], 0), RW4(A[(2 * (b) + 3) & 7], 4), RW4(A[(2 * (b) + 3) & 7], 8), RW2(A[(2 * (b) + 3) & 7], 12)); \
        wg_fence();                                                                            \
    }
#define X0_BLOCK(b)                                                                            \
    { const int rr = lane & 7, hi = lane >> 4;                                                 \
    const uint32_t rowa = (w < 2 ? hbuf : sb + wgi * STAGE) + ((w & 1) * 16 + (lane & 15)) * 128; \
    FOR7(constexpr int G = 14 * (b) + (t < 3 ? 2 * t : (t < 6 ? 2 * t + 1 : 6));               \
         uint32_t q0, q1, q2, q3;                                                              \
         const uint32_t ad = t < 6 ? rowa + (((((G & 7) + hi) ^ rr) & 7) << 4) + ((G & 7) == 7 ? hi * 4096 : 0) : rowa + ((G + 7 * hi) >> 3) * 4096 + ((((G + 7 * hi) ^ rr) & 7) << 4); \
         asm volatile("ldmatrix.sync.aligned.m8n8.x4.shared.b16 {%0,%1,%2,%3}, [%4+%5];" : "=r"(q0), "=r"(q1), "=r"(q2), "=r"(q3) \
                      : "r"(ad), "n"(t < 6 ? (G >> 3) * 4096 : 0) : "memory");                 \
         if (t < 3) { A[2 * (b)][4 * t] = q0; A[2 * (b)][4 * t + 1] = q1; A[2 * (b)][4 * t + 2] = q2; A[2 * (b)][4 * t + 3] = q3; } \
         else if (t < 6) { A[2 * (b) + 1][(4 * t - 12) & 15] = q0; A[2 * (b) + 1][((4 * t - 12) & 15) + 1] = q1; A[2 * (b) + 1][((4 * t - 12) & 15) + 2] = q2; A[2 * (b) + 1][((4 * t - 12) & 15) + 3] = q3; } \
         else { A[2 * (b)][12] = q0; A[2 * (b)][13] = q1; A[2 * (b) + 1][12] = q2; A[2 * (b) + 1][13] = q3; }); }
#define BLK(base, b) ((base) + kblk(pr, b) * 1024)

#pragma unroll 1
        for (int step = 0; step < 4; step++) {
            FRESH();
            const uint32_t tag = (step >> 1) ^ 1;
            const int so = (step >> 1) * 24 + (step & 1) * 12;
            (void)so;
            uint32_t A[8][14];
            uint4* const xsrc = xp0 + ((step & 1) ? PL(2) : PL(0));
            const uint32_t xtag = (step & 1) ? tag : ((seq >> 3) & 1) ^ 1;
            uint32_t xbits;
            {
                float st[4];
                slice_stats(X, st);
                stag ^= 1;
                xbits = x_bits(X);
                tag_slice(X, xtag);
                if (step) send_slice<0>(xsrc + sl * 512, lane, X);
                if (c == 0) st_pkt<0>(stp + sl * 512, __float_as_uint(st[0]), __float_as_uint(st[1]), __float_as_uint(st[2]), settag(__float_as_uint(st[3]), stag));
            }
            STAMP(2 + so);
            uint32_t sv[8];
            if (step == 0) {
                X0_BLOCK(0) X0_BLOCK(1) X0_BLOCK(2) X0_BLOCK(3)
                mbar_wait(BAR(wgi ^ 1), 0);
                R_NEXT();
                R_NEXT();
                R_RELEASE(2);
                stat_load(sv, stp + c * 1024);
                stat_check(sv, stp + c * 1024, stag);
                STAMP(52 + step);
            } else {
                kill<14>(A[2]); kill<14>(A[3]); kill<14>(A[4]); kill<14>(A[5]); kill<14>(A[6]); kill<14>(A[7]);
                PUSH_SLICE(X)
                stat_load(sv, stp + c * 1024);
                PULL_SLICE(X)
                stat_check(sv, stp + c * 1024, stag);
                STAMP(52 + step);
                GAT_ISSUE(1, (step & 1) ? PL(2) : PL(0))
            }
            LnCoef k0, k1;
            {
                k0 = ln_coef(__uint_as_float(sv[0]) + __uint_as_float(sv[4]), __uint_as_float(sv[1]) + __uint_as_float(sv[5]));
                k1 = ln_coef(__uint_as_float(sv[2]) + __uint_as_float(sv[6]), __uint_as_float(sv[3] & ~1u) + __uint_as_float(sv[7] & ~1u));
            }
            STAMP(3 + so);
            GSTAMP(70 + step);

            if ((step & 1) == 0) {
                float tq[28];
                {
                    float av[28];
#define KV_BLOCK(b)                                                                           \
    if ((b) == 1) R_RELEASE(2);                                                               \
    if ((b) == 2) { PUSH_ACK(); wg_wait<2>(); R_RELEASE(2); }                                 \
    R_WAIT();                                                                                 \
    if ((b) == PPK) { PP_WAIT() }                                                             \
    { DECL_DB(b, BASE128, 16, 0)                                                              \
    wg_fence();                                                                               \
    FOR7(mma_rs56<1, D128(0, t)>(tq, AQ(A, b, t), (b) + t > 0, SWB(b, t, db, 0));             \
         mma_rs56<1, D128(HALF, t)>(av, AQ(A, b, t), (b) + t > 0, SWB(b, t, db, 0));          \
         PREP(b, t, step)); }                                                                 \
    wg_commit();                                                                              \
    if ((b) == 3 && PPK < 4) { PP_GO() }                                                      \
    R_NEXT();
                    normalize<0>(A, k0, k1);
                    KV_BLOCK(0) KV_BLOCK(1) KV_BLOCK(2) KV_BLOCK(3)
                    wg_wait<0>();
                    if (lane < 3) mbar_arrive(BAR(B_EMPTY + (slot + NST - 1 - lane) % NST));
                    STAMP(4 + so);
                    WSUM(80 + 7 * (step >> 1));
                    const int m = lane >> 3, rr = lane & 7;
                    const uint32_t rowa = hbuf + 16384 + (w * 16 + rr + 8 * (m & 1)) * 128;
                    const uint32_t one = c == 0 ? 0x00003f80u : 0u;
                    if (step == 0) { bar_sync(wgi ? 9 : 1, 224); }
#pragma unroll
                    for (int j = 0; j < 4; j++) {
                        const uint32_t a = rowa + (((2 * j + (m >> 1)) ^ rr) << 4);
                        if (j < 3) stsm4(a, pack2(av[8 * j], av[8 * j + 1]), pack2(av[8 * j + 2], av[8 * j + 3]), pack2(av[8 * j + 4], av[8 * j + 5]), pack2(av[8 * j + 6], av[8 * j + 7]));
                        else stsm4(a, pack2(av[24], av[25]), pack2(av[26], av[27]), one, one);
                    }
                }
                uint32_t PH[28];
                int it = 1;
#pragma unroll 1
                do {
                    float pp[28];
                    phi_gemm(tq, pp);
                    dual_softmax(pp, PH);
                    if (((trips >> (it + 1)) & 1) == 0) continue;
                    {
                        const int m = lane >> 3, rr = lane & 7;
                        const uint32_t rowa = hbuf + (w * 16 + rr + 8 * (m & 1)) * 128;
#pragma unroll
                        for (int j = 0; j < 7; j++) {
                            const int cg = 2 * j + (m >> 1), hi = cg >= 7;
                            stsm4(rowa + hi * 8192 + (((cg - 7 * hi) ^ rr) << 4), PH[4 * j], PH[4 * j + 1], PH[4 * j + 2], PH[4 * j + 3]);
                        }
                    }
                    fence_async();
                    STAMP(5 + so);
#define Q_STAGE(b0)                                                                           \
    R_WAIT();                                                                                 \
    { DECL_DB(b0, BASE128, 16, 0)                                                             \
    wg_fence();                                                                               \
    FOR7(mma_rs56<1, D128(0, t)>(tq, AQ(A, b0, t), (b0) + t > 0, SWB(b0, t, db, 0)));         \
    FOR7(mma_rs56<1, D128(HALF, t)>(tq, AQ(A, (b0) + 1, t), 1, db)); }                        \
    wg_commit();                                                                              \
    R_NEXT();
                    if (QE && wgi == 0) { kill<28>(tq); Q_STAGE(0) Q_STAGE(2) wg_wait<1>(); R_RELEASE(2); wg_wait<0>(); R_RELEASE(1); }
                    bar_sync(2, 256);
                    float kv[28];
                    const uint64_t da = BASE128(OFF_H + 16384, 16, 0), dbk = BASE128(OFF_H, 16, wgi * 512);
                    wg_fence();
                    FOR8(constexpr uint64_t o = ((t >> 2) * STAGE + (t & 3) * 2048) >> 4; mma_ss56_tt<o, o>(kv, t > 0, da, dbk));
                    wg_commit();
                    wg_wait<0>();
#pragma unroll
                    for (int hf = 0; hf < 2; hf++) {
                        const int d = 16 * w + g + 8 * hf;
                        if ((d < 56 && (d >= 28) == (c >= 2)) || d == 56) {
                            const int item = d < 56 ? 2 * d + (c & 1) : 112 + c;
                            uint4* dst = g_kv1 + ((sl * 16 + (item >> 3)) * 16 + tile) * 32 + wgi * 16 + (item & 7);
#define KVW(i) pack2(kv[4 * (i) + 2 * hf], kv[4 * (i) + 2 * hf + 1])
                            st_pkt<0>(dst, settag(KVW(0), tag), KVW(1), KVW(2), KVW(3));
                            st_pkt<8>(dst, settag(KVW(4), tag), KVW(5), KVW(6), 0u);
                        }
                    }
                    __syncwarp();
                    kseq++;
                    if (lane == 0) st_word(g_c1 + ((sl * 8 + wu) * 16 + tile) * 32, kseq);
                    bar_arrive(7, 384);
                    STAMP(6 + so);
                    if (!QE || wgi == 1) { kill<28>(tq); Q_STAGE(0) Q_STAGE(2) wg_wait<1>(); R_RELEASE(2); wg_wait<0>(); R_RELEASE(1); }
                    STAMP(7 + so);
                    kill<28>(PH);
                } while (((trips >> (++it)) & 1));
                STAMP(8 + so);
                FRESH();
                if (step) {
                    slice_load<PL(0)>(X, xp0 + sl * 512, lane);
                } else {
                    const uint32_t* xp = reinterpret_cast<const uint32_t*>(x_in + (size_t)(tile * 128 + wu * 16 + g) * 448 + 56 * sl + 2 * c);
#pragma unroll
                    for (int i = 0; i < 7; i++) { X[2 * i] = __ldg(xp + 4 * i); X[2 * i + 1] = __ldg(xp + 4 * i + 8 * 224); }
                }
                bar_sync(3, 384);
                STAMP(9 + so);
                const uint4* const osrc = xp0 + PL(1);
                {
                    float nm[32];
                    const uint64_t db = BASE128(OFF_KVB, 16, 0);
                    wg_fence();
                    FOR7(mma_rs64<0, ((t >> 2) * 8192 + (t & 3) * 32) / 16>(nm, PH[4 * t], PH[4 * t + 1], PH[4 * t + 2], PH[4 * t + 3], t > 0, db));
                    wg_commit();
                    wg_wait<0>();
                    LATE_ARRIVE();
                    const float i00 = rcp(nm[28] + 1e-6f), i01 = rcp(nm[29] + 1e-6f), i10 = rcp(nm[30] + 1e-6f), i11 = rcp(nm[31] + 1e-6f);
                    const float m0 = c >= 2 ? i01 : i00, m1 = c >= 2 ? i11 : i10;
                    uint32_t O[14];
#pragma unroll
                    for (int i = 0; i < 7; i++) {
                        const float f0 = i < 3 ? i00 : (i > 3 ? i01 : m0), f1 = i < 3 ? i10 : (i > 3 ? i11 : m1);
                        O[2 * i] = pack2(nm[4 * i] * f0, nm[4 * i + 1] * f0);
                        O[2 * i + 1] = pack2(nm[4 * i + 2] * f1, nm[4 * i + 3] * f1);
                    }
                    if (OST) { PP_WAIT() }
                    tag_slice(O, tag);
                    send_slice<PL(1)>(xp0 + sl * 512, lane, O);
                    seq++;
                    if (lane == 0) st_word(cx(sl), seq);
                    STAMP(10 + so);
                    PUSH_SLICE(O)
                    if (OST == 1) { PP_GO() }
                    const uint32_t cv = ld_word(cx(lane & 7));
                    PULL_SLICE(O)
                    LATE_WAIT();
                    check_cnt(cv, cx(lane & 7), seq);
                    if (OST == 2) { PP_GO() }
                    STAMP(56 + (step >> 1));
                    GAT_ISSUE(1, PL(1))
                    GAT_ISSUE(3, PL(1))
                    blk_load<2>(A, BLK(osrc, 2), lane);
                }
                float ao[28];
#define WO_BLOCK(b)                                                                           \
    if ((b) > 0) blk_check<b>(A, BLK(osrc, b), lane, tag);                                    \
    if (((b) & 1) == 0) R_WAIT();                                                             \
    { DECL_DB(b, BASE128, 16, 0)                                                              \
    wg_fence();                                                                               \
    FOR7(mma_rs56<1, D128(((b) & 1) * HALF, t)>(ao, AQ(A, b, t), (b) + t > 0, SWB(b, t, db, 0))); } \
    wg_commit();                                                                              \
    if ((b) & 1) R_NEXT();
                WO_BLOCK(0)
                STAMP(11 + so);
                GAT_FETCH(1)
                WO_BLOCK(1)
                WO_BLOCK(2)
                GAT_FETCH(3)
                WO_BLOCK(3)
                PUSH_ACK();
                wg_wait<0>();
                R_RELEASE(2);
                STAMP(12 + so);
                WSUM(86 + 7 * (step >> 1));
                x_fix(X, xbits);
#pragma unroll
                for (int i = 0; i < 14; i++) X[i] = pack2(bf_lo(X[i]) + ao[2 * i], bf_hi(X[i]) + ao[2 * i + 1]);
            } else {
                uint32_t H[56];
                float ag[64];
#define F1_EPI(dst, ng, ag)                                                                    \
    _Pragma("unroll") for (int i = 0; i < 2 * (ng); i++)                                       \
        (dst)[i] = pack2(geglu(ag[2 * i], ag[4 * (ng) + 2 * i]), geglu(ag[2 * i + 1], ag[4 * (ng) + 2 * i + 1]));
#define H_PUSH(h0, off) st_async4(rem_h + (off), H[h0], H[(h0) + 1], H[(h0) + 2], H[(h0) + 3], mapa(BAR(B_RECV2 + wgi), hr ^ 1));
#define F1_BLOCK(b, first)                                                                     \
    if ((first) && (b) == 1) R_RELEASE(2);                                                     \
    if ((first) && (b) == 2) PUSH_ACK();                                                       \
    R_WAIT();                                                                                  \
    if ((b) == ((first) ? PPF : PPB)) { PP_WAIT() }                                            \
    { DECL_DB(b, BASE128, HALF, 0)                                                             \
    wg_fence();                                                                                \
    FOR7(mma_rs128<1, D128(0, t)>(ag, AQ(A, b, t), (b) + t > 0, SWB(b, t, db, 0));             \
         if constexpr (first) { PREP(b, t, true) }); }                                         \
    wg_commit();                                                                               \
    if ((b) == 3) { PP_GO() }                                                                  \
    if ((b) > 0) { wg_wait<1>(); R_RELEASE(1); }       \
    R_NEXT();
                normalize<0>(A, k0, k1);
                F1_BLOCK(0, true) F1_BLOCK(1, true) F1_BLOCK(2, true) F1_BLOCK(3, true)
                if (t128 == 0) { mbar_expect_tx(BAR(B_RECV + wgi), 16384); mbar_expect_tx(BAR(B_RECV2 + wgi), 12288); }
                PUSH_BEGIN();
                wg_wait<0>();
                R_RELEASE(1);
                int p = 0;
#pragma unroll 1
                do {
                    F1_EPI(H + 32, 8, ag)
                    STAMP(4 + p + so);
                    WSUM(81 + p + 7 * (step >> 1));
                    if (((trips >> (p + 1)) & 1) == 0) continue;
                    if (step == 1 && p == PKP) R_NEXT();
                    kill<64>(ag);
                    F1_BLOCK(0, false)
                    {
                        const uint32_t pk = (p ? hbuf + 16384 : sb + OFF_KVB + wgi * 8192) + w * 2048;
#pragma unroll
                        for (int k = 0; k < 4; k++) sts4(pk + k * 512 + lane * 16, H[32 + 4 * k], H[33 + 4 * k], H[34 + 4 * k], H[35 + 4 * k]);
                        fence_async();
                        __syncwarp();
                        asm volatile(ELECT "cp.async.bulk.shared::cluster.shared::cta.mbarrier::complete_tx::bytes [%0], [%1], 2048, [%2]; }"
                                     ::"r"(mapa(hbuf + p * 8192 + w * 2048, hr ^ 1)), "r"(pk), "r"(mapa(BAR(B_RECV + wgi), hr ^ 1)) : "memory");
                    }
                    F1_BLOCK(1, false) F1_BLOCK(2, false) F1_BLOCK(3, false)
                    wg_wait<0>();
                    R_RELEASE(1);
                    kill<16>(H + 32);
                } while (((trips >> (++p)) & 1));
#pragma unroll
                for (int k = 0; k < 4; k++) lds4(H + 16 + 4 * k, hbuf + 16384 + w * 2048 + k * 512 + lane * 16);
                __syncwarp();
                if (lane == 0) asm volatile("mbarrier.arrive.shared::cluster.b64 _, [%0];" ::"r"(mapa(BAR(B_ACK2 + wgi), hr ^ 1)) : "memory");
                const uint32_t rem_h = mapa(hbuf + w * 2048 + lane * 16, hr ^ 1);
#define F1_LAST(b0)                                                                            \
    R_WAIT();                                                                                  \
    if (b0) { PP_WAIT() }                                                                      \
    { DECL_DB(b0, BASE64, HALF, 1)                                                             \
    wg_fence();                                                                                \
    FOR7(mma_rs64<1, D64(0, t)>(al, AQ(A, b0, t), (b0) + t > 0, SWB(b0, t, db, 1)));           \
    FOR7(mma_rs64<1, D64(7168, t)>(al, AQ(A, (b0) + 1, t), 1, db)); }                          \
    wg_commit();                                                                               \
    if (b0) { PP_GO() }                                                                        \
    R_NEXT();
                float al[32];
                F1_LAST(0)
                mbar_wait(BAR(B_RECV + wgi), rcvph);
                rcvph ^= 1;
                mbar_wait(BAR(B_ACK2 + wgi), step >> 1);
                H_PUSH(32, 16384) H_PUSH(36, 16896)
                F1_LAST(2)
                H_PUSH(40, 17408) H_PUSH(44, 17920)
                wg_wait<1>();
                R_RELEASE(2);
                wg_wait<0>();
                R_RELEASE(1);
                uint32_t HP[56];
#pragma unroll
                for (int k = 0; k < 4; k++) lds4(H + 4 * k, sb + OFF_KVB + wgi * 8192 + w * 2048 + k * 512 + lane * 16);
#pragma unroll
                for (int t = 0; t < 8; t++) lds4(HP + 4 * t, hbuf + (t >> 2) * 8192 + w * 2048 + (t & 3) * 512 + lane * 16);
                F1_EPI(H + 48, 4, al)
                H_PUSH(48, 24576 - w * 1024) H_PUSH(52, 25088 - w * 1024)
                STAMP(7 + so);
                WSUM(84 + 7 * (step >> 1));
                FRESH();
                float acc[28];
                const uint32_t roA = hr ? 256u : 0u, roB = hr ? (uint32_t)-1536 : 0u;
                const uint32_t rpA = hr ? 0u : 256u, rpB = hr ? 0u : (uint32_t)-1536;
                float res[28];
                uint32_t v0[14], v1[14], P[14];
                const uint4* ps = xp0 + sl * 512;
#define F2_OWN_A()                                                                             \
    R_WAIT();                                                                                  \
    d0 = BASE128(0, 16, R_ADJ + roA); d1 = BASE128(0, 16, R_ADJ + roB);                        \
    wg_fence();                                                                                \
    FOR14(if constexpr (t < OT) mma_rs56<1, t * 128>(acc, H[4 * t], H[4 * t + 1], H[4 * t + 2], H[4 * t + 3], t > 0, d0)); \
    wg_commit();
#define F2_OWN_B()                                                                             \
    wg_fence();                                                                                \
    FOR14(if constexpr (t >= OT) mma_rs56<1, t * 128>(acc, H[4 * t], H[4 * t + 1], H[4 * t + 2], H[4 * t + 3], 1, t < 12 ? d0 : d1)); \
    wg_commit();                                                                               \
    R_NEXT();
#define F2_PEER()                                                                              \
    R_WAIT();                                                                                  \
    if (F2PP) { PP_WAIT() }                                                                    \
    d0 = BASE128(0, 16, R_ADJ + rpA); d1 = BASE128(0, 16, R_ADJ + rpB);                        \
    wg_fence();                                                                                \
    FOR14(mma_rs56<1, t * 128>(acc, HP[4 * t], HP[4 * t + 1], HP[4 * t + 2], HP[4 * t + 3], 1, t < 12 ? d0 : d1)); \
    wg_commit();                                                                               \
    if (F2PP) { PP_GO() }                                                                      \
    R_NEXT();
#define F2_TURN(u)                                                                             \
    wg_wait<1>();                                                                              \
    if ((u) < 2 || TDEF < 2) R_RELEASE(2);                                                     \
    wg_wait<0>();                                                                              \
    if ((u) < 2 || TDEF < 1) R_RELEASE(1);                                                     \
    _Pragma("unroll") for (int i = 0; i < 14; i++) P[i] = pack2(acc[2 * i], acc[2 * i + 1]);   \
    tag_slice(P, tag);                                                                         \
    asm volatile("" : RW4(P, 0), RW4(P, 4), RW4(P, 8), RW2(P, 12));                            \
    kill<28>(acc);                                                                             \
    F2_OWN_A()                                                                                 \
    if ((u) == 2) { slice_load<PL(3)>(v0, ps, lane); slice_load<PL(4)>(v1, ps, lane); } \
    send_slice<PL(3 + (u))>(xp0 + (2 * ((pr + (u) + 1) & 3) + hr) * 512, lane, P);             \
    seq++;                                                                                     \
    if (lane == 0) st_word(cx(sl), seq);                                                       \
    __syncwarp();                                                                              \
    STAMP(8 + (u) + so);                                                                       \
    F2_OWN_B()
                uint64_t d0, d1;
                F2_OWN_A()
                F2_OWN_B()
                R_WAIT();
                d0 = BASE128(0, 16, R_ADJ + rpA); d1 = BASE128(0, 16, R_ADJ + rpB);
                wg_fence();
                FOR8(mma_rs56<1, t * 128>(acc, HP[4 * t], HP[4 * t + 1], HP[4 * t + 2], HP[4 * t + 3], 1, d0));
                wg_commit();
                mbar_wait(BAR(B_RECV2 + wgi), step >> 1);
#pragma unroll
                for (int k = 0; k < 4; k++) lds4(HP + 32 + 4 * k, hbuf + 16384 + w * 2048 + k * 512 + lane * 16);
                lds4(HP + 48, hbuf + 24576 + w * 1024 + lane * 16);
                lds4(HP + 52, hbuf + 25088 + w * 1024 + lane * 16);
                if (step == 1) PUSH_ACK();
                wg_fence();
                FOR14(if constexpr (t >= 8) mma_rs56<1, t * 128>(acc, HP[4 * t], HP[4 * t + 1], HP[4 * t + 2], HP[4 * t + 3], 1, t < 12 ? d0 : d1));
                wg_commit();
                R_NEXT();
                F2_TURN(0)
                F2_PEER()
                F2_TURN(1)
                F2_PEER()
                F2_TURN(2)
                if (step == 1) STAMP(64);
                slice_check<PL(3)>(v0, ps, lane, tag);
                slice_check<PL(4)>(v1, ps, lane, tag);
#pragma unroll
                for (int i = 0; i < 14; i++) { res[2 * i] = bf_lo(v0[i]) + bf_lo(v1[i]); res[2 * i + 1] = bf_hi(v0[i]) + bf_hi(v1[i]); }
                slice_load<PL(2)>(X, ps, lane);
                if (step == 1) STAMP(65);
                F2_PEER()
                if (step == 1) STAMP(66);
                poll_cnt(cx(2 * ((pr + 1) & 3) + hr), seq);
                if (step == 1) STAMP(67);
                slice_load<PL(5)>(v0, ps, lane);
                x_fix(X, xbits);
                slice_check<PL(5)>(v0, ps, lane, tag);
                if (lane < TDEF) mbar_arrive(BAR(B_EMPTY + (slot + NST - 3 - lane) % NST));
#pragma unroll
                for (int i = 0; i < 14; i++) { res[2 * i] += bf_lo(v0[i]); res[2 * i + 1] += bf_hi(v0[i]); }
                STAMP(11 + so);
                wg_wait<0>();
                R_RELEASE(2);
                STAMP(12 + so);
                WSUM(85 + 7 * (step >> 1));
#pragma unroll
                for (int i = 0; i < 14; i++) X[i] = pack2(fmaf(res[2 * i] + acc[2 * i], 0.5f, bf_lo(X[i])), fmaf(res[2 * i + 1] + acc[2 * i + 1], 0.5f, bf_hi(X[i])));
            }
        }
        {
            const int m = lane >> 3, rr = lane & 7;
            const uint32_t ob = hbuf + w * 2048, rowa = ob + (rr + 8 * (m & 1)) * 112 + (m >> 1) * 16;
#pragma unroll
            for (int j = 0; j < 3; j++) stsm4(rowa + 32 * j, X[4 * j], X[4 * j + 1], X[4 * j + 2], X[4 * j + 3]);
            asm volatile("stmatrix.sync.aligned.m8n8.x2.shared.b16 [%0], {%1,%2};" ::"r"(ob + (rr + 8 * (m & 1)) * 112 + 96), "r"(X[12]), "r"(X[13]) : "memory");
            fence_async();
            __syncwarp();
            if (lane == 0) {
                asm volatile("cp.async.bulk.tensor.2d.global.shared::cta.bulk_group [%0, {%2, %3}], [%1];" ::"l"(&maps.out), "r"(ob), "r"(56 * sl), "r"(tile * 128 + wu * 16) : "memory");
                asm volatile("cp.async.bulk.commit_group;" ::: "memory");
                asm volatile("cp.async.bulk.wait_group.read 0;" ::: "memory");
            }
        }
        STAMP(50);
        GSTAMP(61);
        PDUMP();
    }
}

#undef g
#undef pr
#undef c
#undef t128

typedef CUresult (*EncodeFn)(CUtensorMap*, CUtensorMapDataType, cuuint32_t, void*, const cuuint64_t*, const cuuint64_t*, const cuuint32_t*,
                             const cuuint32_t*, CUtensorMapInterleave, CUtensorMapSwizzle, CUtensorMapL2promotion, CUtensorMapFloatOOBfill);

static void make_map(EncodeFn enc, CUtensorMap* m, const void* p, uint64_t cols, uint64_t rows, uint32_t bc, uint32_t br, CUtensorMapSwizzle sw) {
    cuuint64_t gd[2] = {cols, rows};
    cuuint64_t gs[1] = {cols * 2};
    cuuint32_t bd[2] = {bc, br};
    cuuint32_t es[2] = {1, 1};
    enc(m, CU_TENSOR_MAP_DATA_TYPE_BFLOAT16, 2, const_cast<void*>(p), gd, gs, bd, es, CU_TENSOR_MAP_INTERLEAVE_NONE, sw,
        CU_TENSOR_MAP_L2_PROMOTION_L2_128B, CU_TENSOR_MAP_FLOAT_OOB_FILL_NONE);
}

extern "C" void kernel_launch(void* const* d_in, const int* in_sizes, int n_in, void* d_out, int out_size) {
    (void)in_sizes; (void)n_in; (void)out_size;
    static EncodeFn enc = nullptr;
    static Scratch* scratch = nullptr;
    if (!enc) {
        void* fn = nullptr;
        cudaDriverEntryPointQueryResult qr;
        cudaGetDriverEntryPoint("cuTensorMapEncodeTiled", &fn, cudaEnableDefault, &qr);
        enc = (EncodeFn)fn;
        cudaGetSymbolAddress((void**)&scratch, g_scratch);
        cudaFuncSetAttribute(fused_kernel, cudaFuncAttributeMaxDynamicSharedMemorySize, SMEM_BYTES);
    }
    Maps maps;
    {
        cuuint64_t gd[3] = {64, 2048, 7};
        cuuint64_t gs[2] = {896, 128};
        cuuint32_t bd[3] = {64, 32, 7};
        cuuint32_t es[3] = {1, 1, 1};
        enc(&maps.x, CU_TENSOR_MAP_DATA_TYPE_BFLOAT16, 3, d_in[0], gd, gs, bd, es, CU_TENSOR_MAP_INTERLEAVE_NONE, CU_TENSOR_MAP_SWIZZLE_128B,
            CU_TENSOR_MAP_L2_PROMOTION_L2_128B, CU_TENSOR_MAP_FLOAT_OOB_FILL_NONE);
    }
    make_map(enc, &maps.out, d_out, 448, 2048, 56, 16, CU_TENSOR_MAP_SWIZZLE_NONE);
    make_map(enc, &maps.qkv, d_in[1], 1344, 448, 64, 112, CU_TENSOR_MAP_SWIZZLE_128B);
    make_map(enc, &maps.wo, d_in[3], 448, 448, 64, 112, CU_TENSOR_MAP_SWIZZLE_128B);
    make_map(enc, &maps.wg, d_in[5], 1792, 448, 64, 112, CU_TENSOR_MAP_SWIZZLE_128B);
    make_map(enc, &maps.wu, d_in[6], 1792, 448, 64, 112, CU_TENSOR_MAP_SWIZZLE_128B);
    make_map(enc, &maps.wg32, d_in[5], 1792, 448, 32, 112, CU_TENSOR_MAP_SWIZZLE_64B);
    make_map(enc, &maps.wu32, d_in[6], 1792, 448, 32, 112, CU_TENSOR_MAP_SWIZZLE_64B);
    make_map(enc, &maps.wd, d_in[7], 448, 1792, 64, 112, CU_TENSOR_MAP_SWIZZLE_128B);
    fused_kernel<<<128, 384, SMEM_BYTES>>>(scratch, (const __nv_bfloat16*)d_in[0], (const __nv_bfloat16*)d_in[2], 7, (const __nv_bfloat16*)d_in[5],
                                           (const __nv_bfloat16*)d_in[6], (const __nv_bfloat16*)d_in[7], maps);
}
```

```cpp
#include <cuda_runtime.h>
#include <cuda.h>
#include <cuda_bf16.h>
#include <stdint.h>
#include <type_traits>

#define PPF 2
#define PKP 0
#define TDEF 1
#define TMPF 0
#define NORM1 0
#define LPARK 1
#define PFN 9
#define XG3 1
#define ACAN 0
#define SPLIT0 1
#define OT 2
#define F2PP 0
#define PPK 2
#define QE 1
#define OST 1
#define PP

namespace {

constexpr uint32_t STAGE = 28672, HALF = 14336;
constexpr int NST = 5;
constexpr uint32_t OFF_H = NST * STAGE;
constexpr uint32_t OFF_KVB = OFF_H + 2 * STAGE;
constexpr uint32_t OFF_WPHI = OFF_KVB + 16384;
constexpr uint32_t OFF_XR = OFF_WPHI + 7168;
constexpr uint32_t OFF_BAR = OFF_XR + 6144;
constexpr uint32_t SMEM_BYTES = OFF_BAR + 384 + 1408;
constexpr int B_EMPTY = NST, B_RECV = 2 * NST, B_RECV2 = B_RECV + 2, B_PACK = B_RECV2 + 2, B_GAT = B_PACK + 1, B_LATE = B_GAT + 16, B_ACK = B_LATE + 1, B_ACK2 = B_ACK + 2, B_COUNT = B_ACK2 + 2;

constexpr int PACK = 14 + 4 * PKP;

struct Maps { CUtensorMap x, qkv, wo, wg, wu, wg32, wu32, wd, out; };

}

constexpr int PLANE = 16 * 2 * 8 * 512;
struct Scratch {
    uint4 ex[6 * PLANE];
    uint4 kv1[8 * 16 * 16 * 32];
    uint4 kv2[8 * 512];
    uint32_t c1[8 * 8 * 16 * 32];
    uint32_t cw[8 * 32];
    uint4 wp[8 * 32 * (HALF / 16)];
};
__device__ __align__(1024) Scratch g_scratch;
#define g_ex (sc->ex)
#define g_kv1 (sc->kv1)
#define g_kv2 (sc->kv2)
#define g_c1 (sc->c1)
#define g_cw (sc->cw)
#define g_wp (sc->wp)
#define STAMP(i)
#define GSTAMP(i)
#define PDUMP()
#define ASTAMP(i)

namespace {

__device__ __forceinline__ int fresh_tid() { int t; asm volatile("mov.u32 %0, %%tid.x;" : "=r"(t)); return t; }
template <int N> __device__ __forceinline__ void kill(uint32_t* v) {
#pragma unroll
    for (int i = 0; i < N; i++) v[i] = 0;
}
template <int N> __device__ __forceinline__ void kill(float* v) {
#pragma unroll
    for (int i = 0; i < N; i++) v[i] = 0.f;
}
__device__ __forceinline__ uint32_t s2u(const void* p) { return (uint32_t)__cvta_generic_to_shared(p); }
__device__ __forceinline__ void mbar_init(uint32_t a, uint32_t c) { asm volatile("mbarrier.init.shared::cta.b64 [%0], %1;" ::"r"(a), "r"(c) : "memory"); }
__device__ __forceinline__ void mbar_expect_tx(uint32_t a, uint32_t b) { asm volatile("mbarrier.arrive.expect_tx.shared::cta.b64 _, [%0], %1;" ::"r"(a), "r"(b) : "memory"); }
__device__ __forceinline__ void mbar_arrive(uint32_t a) { asm volatile("mbarrier.arrive.shared::cta.b64 _, [%0];" ::"r"(a) : "memory"); }
#define GIVE_UP(id) "trap;\n"
#define SPIN_MAX "0x400000"
#define SPIN_TAIL(id) "add.u32 n, n, 1;\n setp.lt.u32 p, n, " SPIN_MAX ";\n @p bra.uni LP;\n" GIVE_UP(id) " DN:\n }"
__device__ __forceinline__ void mbar_wait(uint32_t a, uint32_t ph) {
    asm volatile("{ .reg .pred p; .reg .b32 n; mov.u32 n, 0;\n LP:\n"
                 "mbarrier.try_wait.parity.shared::cta.b64 p, [%0], %1;\n @p bra DN;\n"
                 "add.u32 n, n, 1;\n setp.lt.u32 p, n, " SPIN_MAX ";\n @p bra LP;\n"
                 GIVE_UP("")
                 " DN:\n }" ::"r"(a), "r"(ph) : "memory");
}
#define ELECT "{ .reg .pred e; elect.sync _|e, 0xffffffff; @e "
__device__ __forceinline__ void tma2d(uint32_t dst, const CUtensorMap* m, int c0, int c1, uint32_t bar) {
    asm volatile(ELECT "cp.async.bulk.tensor.2d.shared::cluster.global.mbarrier::complete_tx::bytes [%0], [%1, {%3, %4}], [%2]; }" ::"r"(dst), "l"(m), "r"(bar), "r"(c0), "r"(c1) : "memory");
}
__device__ __forceinline__ void tma3x(uint32_t dst, const CUtensorMap* m, int row, uint32_t bar) {
    asm volatile(ELECT "cp.async.bulk.tensor.3d.shared::cluster.global.mbarrier::complete_tx::bytes [%0], [%1, {0, %3, 0}], [%2]; }" ::"r"(dst), "l"(m), "r"(bar), "r"(row) : "memory");
}
template <int OFF>
__device__ __forceinline__ void ld_pkt(uint32_t* v, const uint4* p) {
    asm volatile("{ .reg .b128 t; ld.relaxed.gpu.global.b128 t, [%4+%5]; mov.b128 {%0,%1,%2,%3}, t; }" : "=r"(v[0]), "=r"(v[1]), "=r"(v[2]), "=r"(v[3]) : "l"(p), "n"(OFF * 16) : "memory");
}
template <int OFF>
__device__ __forceinline__ void st_pkt(uint4* p, uint32_t a, uint32_t b, uint32_t c, uint32_t d) {
    asm volatile("{ .reg .b128 t; mov.b128 t, {%1,%2,%3,%4}; st.relaxed.gpu.global.b128 [%0+%5], t; }" ::"l"(p), "r"(a), "r"(b), "r"(c), "r"(d), "n"(OFF * 16) : "memory");
}
__device__ __forceinline__ uint32_t pack2(float lo, float hi) {
    uint32_t r;
    asm("cvt.rn.bf16x2.f32 %0, %1, %2;" : "=r"(r) : "f"(hi), "f"(lo));
    return r;
}
__device__ __forceinline__ float bf_lo(uint32_t w) { return __uint_as_float(w << 16); }
__device__ __forceinline__ float bf_hi(uint32_t w) { return __uint_as_float(w & 0xffff0000u); }
__device__ __forceinline__ uint32_t settag(uint32_t w, uint32_t tag) { return (w & ~1u) | tag; }
__device__ __forceinline__ float ex2(float x) { float y; asm("ex2.approx.ftz.f32 %0, %1;" : "=f"(y) : "f"(x)); return y; }
__device__ __forceinline__ float rcp(float x) { float y; asm("rcp.approx.ftz.f32 %0, %1;" : "=f"(y) : "f"(x)); return y; }
__device__ __forceinline__ float tanh_hw(float x) { float y; asm("tanh.approx.f32 %0, %1;" : "=f"(y) : "f"(x)); return y; }
__device__ __forceinline__ void stsm4(uint32_t addr, uint32_t a, uint32_t b, uint32_t c, uint32_t d) {
    asm volatile("stmatrix.sync.aligned.m8n8.x4.shared.b16 [%0], {%1,%2,%3,%4};" ::"r"(addr), "r"(a), "r"(b), "r"(c), "r"(d) : "memory");
}
__device__ __forceinline__ void fence_async() { asm volatile("fence.proxy.async.shared::cta;" ::: "memory"); }
__device__ __forceinline__ void bar_sync(int id, int n) { asm volatile("bar.sync %0, %1;" ::"r"(id), "r"(n) : "memory"); }
__device__ __forceinline__ void bar_arrive(int id, int n) { asm volatile("bar.arrive %0, %1;" ::"r"(id), "r"(n) : "memory"); }
__device__ __forceinline__ void wg_fence() { asm volatile("wgmma.fence.sync.aligned;" ::: "memory"); }
__device__ __forceinline__ void wg_commit() { asm volatile("wgmma.commit_group.sync.aligned;" ::: "memory"); }
template <int N> __device__ __forceinline__ void wg_wait() { asm volatile("wgmma.wait_group.sync.aligned %0;" ::"n"(N) : "memory"); }

constexpr uint32_t SB0 = 1024;
__host__ __device__ constexpr uint32_t dlo(uint32_t off, uint32_t lbo) { return ((SB0 + off) >> 4) | ((lbo >> 4) << 16); }
__host__ __device__ constexpr uint32_t dhi(uint32_t sbo, uint32_t sw) { return (sbo >> 4) | (sw << 30); }
__device__ __forceinline__ uint64_t dbase(uint32_t lo, uint32_t hi) { uint64_t d; asm volatile("mov.b64 %0, {%1, %2};" : "=l"(d) : "r"(lo), "r"(hi)); return d; }
#define BASE128(off, lbo, adj) dbase(dlo(off, lbo) + (adj), dhi(1024, 1))
#define BASE64(off, lbo, adj) dbase(dlo(off, lbo) + (adj), dhi(512, 2))

#define ACC4(d, o) "+f"(d[o]), "+f"(d[o + 1]), "+f"(d[o + 2]), "+f"(d[o + 3])
#define ACC28(d) ACC4(d, 0), ACC4(d, 4), ACC4(d, 8), ACC4(d, 12), ACC4(d, 16), ACC4(d, 20), ACC4(d, 24)
#define ACC32(d, o) ACC4(d, o), ACC4(d, o + 4), ACC4(d, o + 8), ACC4(d, o + 12), ACC4(d, o + 16), ACC4(d, o + 20), ACC4(d, o + 24), ACC4(d, o + 28)

template <int TB, uint64_t D>
__device__ __forceinline__ void mma_rs56(float* d, uint32_t a0, uint32_t a1, uint32_t a2, uint32_t a3, int sd, uint64_t base) {
    asm volatile("{ .reg .pred p; .reg .b64 db; setp.ne.b32 p, %32, 0; add.u64 db, %33, %34;\n"
                 "wgmma.mma_async.sync.aligned.m64n56k16.f32.bf16.bf16 "
                 "{%0,%1,%2,%3,%4,%5,%6,%7,%8,%9,%10,%11,%12,%13,%14,%15,%16,%17,%18,%19,%20,%21,%22,%23,%24,%25,%26,%27}, "
                 "{%28,%29,%30,%31}, db, p, 1, 1, %35; }\n"
                 : ACC28(d)
                 : "r"(a0), "r"(a1), "r"(a2), "r"(a3), "r"(sd), "l"(base), "n"(D), "n"(TB));
}
template <int TB, uint64_t D>
__device__ __forceinline__ void mma_rs64(float* d, uint32_t a0, uint32_t a1, uint32_t a2, uint32_t a3, int sd, uint64_t base) {
    asm volatile("{ .reg .pred p; .reg .b64 db; setp.ne.b32 p, %36, 0; add.u64 db, %37, %38;\n"
                 "wgmma.mma_async.sync.aligned.m64n64k16.f32.bf16.bf16 "
                 "{%0,%1,%2,%3,%4,%5,%6,%7,%8,%9,%10,%11,%12,%13,%14,%15,%16,%17,%18,%19,%20,%21,%22,%23,%24,%25,%26,%27,%28,%29,%30,%31}, "
                 "{%32,%33,%34,%35}, db, p, 1, 1, %39; }\n"
                 : ACC32(d, 0)
                 : "r"(a0), "r"(a1), "r"(a2), "r"(a3), "r"(sd), "l"(base), "n"(D), "n"(TB));
}
template <int TB, uint64_t D>
__device__ __forceinline__ void mma_rs128(float* d, uint32_t a0, uint32_t a1, uint32_t a2, uint32_t a3, int sd, uint64_t base) {
    asm volatile("{ .reg .pred p; .reg .b64 db; setp.ne.b32 p, %68, 0; add.u64 db, %69, %70;\n"
                 "wgmma.mma_async.sync.aligned.m64n128k16.f32.bf16.bf16 "
                 "{%0,%1,%2,%3,%4,%5,%6,%7,%8,%9,%10,%11,%12,%13,%14,%15,%16,%17,%18,%19,%20,%21,%22,%23,%24,%25,%26,%27,%28,%29,%30,%31,%32,%33,%34,%35,%36,%37,%38,%39,%40,%41,%42,%43,%44,%45,%46,%47,%48,%49,%50,%51,%52,%53,%54,%55,%56,%57,%58,%59,%60,%61,%62,%63}, "
                 "{%64,%65,%66,%67}, db, p, 1, 1, %71; }\n"
                 : ACC32(d, 0), ACC32(d, 32)
                 : "r"(a0), "r"(a1), "r"(a2), "r"(a3), "r"(sd), "l"(base), "n"(D), "n"(TB));
}
template <uint64_t DA, uint64_t DB>
__device__ __forceinline__ void mma_ss56_tt(float* d, int sd, uint64_t ba, uint64_t bb) {
    asm volatile("{ .reg .pred p; .reg .b64 da, db; setp.ne.b32 p, %28, 0; add.u64 da, %29, %31; add.u64 db, %30, %32;\n"
                 "wgmma.mma_async.sync.aligned.m64n56k16.f32.bf16.bf16 "
                 "{%0,%1,%2,%3,%4,%5,%6,%7,%8,%9,%10,%11,%12,%13,%14,%15,%16,%17,%18,%19,%20,%21,%22,%23,%24,%25,%26,%27}, "
                 "da, db, p, 1, 1, 1, 1; }\n"
                 : ACC28(d)
                 : "r"(sd), "l"(ba), "l"(bb), "n"(DA), "n"(DB));
}
template <int... I> struct Seq {};
template <class F, int... I> __device__ __forceinline__ void static_for_impl(F&& f, Seq<I...>) { (f(std::integral_constant<int, I>{}), ...); }
#define FOR7(...) static_for_impl([&](auto T_) { constexpr int t = decltype(T_)::value; __VA_ARGS__; }, Seq<0, 1, 2, 3, 4, 5, 6>{})
#define FOR8(...) static_for_impl([&](auto T_) { constexpr int t = decltype(T_)::value; __VA_ARGS__; }, Seq<0, 1, 2, 3, 4, 5, 6, 7>{})
#define FOR14(...) static_for_impl([&](auto T_) { constexpr int t = decltype(T_)::value; __VA_ARGS__; }, Seq<0, 1, 2, 3, 4, 5, 6, 7, 8, 9, 10, 11, 12, 13>{})

__device__ __forceinline__ int kblk(int p, int b) { return b == 0 ? p : b - (b <= p); }
__host__ __device__ constexpr int krow(int t) { return t < 3 ? 16 * t : (t < 6 ? 56 + 16 * (t - 3) : 48); }
#define AQ(A, b, t) ((t) < 3 ? A[2 * (b)][4 * (t)] : (t) < 6 ? A[2 * (b) + 1][4 * ((t) - 3)] : A[2 * (b)][12]), \
                    ((t) < 3 ? A[2 * (b)][4 * (t) + 1] : (t) < 6 ? A[2 * (b) + 1][4 * ((t) - 3) + 1] : A[2 * (b)][13]), \
                    ((t) < 3 ? A[2 * (b)][4 * (t) + 2] : (t) < 6 ? A[2 * (b) + 1][4 * ((t) - 3) + 2] : A[2 * (b) + 1][12]), \
                    ((t) < 3 ? A[2 * (b)][4 * (t) + 3] : (t) < 6 ? A[2 * (b) + 1][4 * ((t) - 3) + 3] : A[2 * (b) + 1][13])
#define D128(off, t) ((uint64_t)(((off) + krow(t) * 128) >> 4) + ((uint64_t)((t) == 6 ? (7168 - 1024) >> 4 : 0) << 32))
#define D64(off, t) ((uint64_t)(((off) + krow(t) * 64) >> 4) + ((uint64_t)((t) == 6 ? (3584 - 512) >> 4 : 0) << 32))

#define PL(k) (((k) - 3) * PLANE)
__device__ __forceinline__ void st_word(uint32_t* p, uint32_t v) { asm volatile("st.relaxed.gpu.global.u32 [%0], %1;" ::"l"(p), "r"(v) : "memory"); }
__device__ __forceinline__ uint32_t ld_word(const uint32_t* p) { uint32_t v; asm volatile("ld.relaxed.gpu.global.u32 %0, [%1];" : "=r"(v) : "l"(p) : "memory"); return v; }
__device__ __forceinline__ void tag_slice(uint32_t* w, uint32_t tag) { w[0] = settag(w[0], tag); w[4] = settag(w[4], tag); w[8] = settag(w[8], tag); w[12] = settag(w[12], tag); }
template <int O>
__device__ __forceinline__ void send_slice(uint4* dst, int lane, const uint32_t* w) {
    st_pkt<O>(dst, w[0], w[1], w[2], w[3]);
    st_pkt<O + 32>(dst, w[4], w[5], w[6], w[7]);
    st_pkt<O + 64>(dst, w[8], w[9], w[10], w[11]);
    asm volatile("{ .reg .b64 t; mov.b64 t, {%1,%2}; st.relaxed.gpu.global.b64 [%0+%3], t; }" ::"l"((char*)dst - lane * 8), "r"(w[12]), "r"(w[13]), "n"(16 * (O + 96)) : "memory");
}
#define RW4(v, o) "+r"(v[o]), "+r"(v[(o) + 1]), "+r"(v[(o) + 2]), "+r"(v[(o) + 3])
#define RW2(v, o) "+r"(v[o]), "+r"(v[(o) + 1])
#define WR4(v, o) "=&r"(v[o]), "=&r"(v[(o) + 1]), "=&r"(v[(o) + 2]), "=&r"(v[(o) + 3])
#define LDP(a, b, c, d, addr, off) "ld.relaxed.gpu.global.b128 q, [" addr "+" off "];\n mov.b128 {" a "," b "," c "," d "}, q;\n"
#define LDH(a, b, addr, off) "ld.relaxed.gpu.global.b64 h, [" addr "+" off "];\n mov.b64 {" a "," b "}, h;\n"
#define VOTE_OK "and.b32 t, t, 1;\n setp.ne.u32 p, t, 0;\n vote.sync.any.pred p, p, 0xffffffff;\n @!p bra.uni DN;\n"
#define CHK(x, tag) "lop3.b32 t, " x ", " tag ", t, 0xBE;\n"
__device__ __forceinline__ void check_cnt(uint32_t v, const uint32_t* p, uint32_t target) {
    asm volatile("{ .reg .pred p; .reg .b32 n, t; mov.u32 n, 0; mov.u32 t, %2;\n LP:\n"
                 "sub.s32 t, t, %1;\n setp.lt.s32 p, t, 0;\n vote.sync.any.pred p, p, 0xffffffff;\n @!p bra.uni DN;\n ld.relaxed.gpu.global.u32 t, [%0];\n" SPIN_TAIL("7")
                 ::"l"(p), "r"(target), "r"(v) : "memory");
}
__device__ __forceinline__ void poll_cnt(const uint32_t* p, uint32_t target) {
    asm volatile("{ .reg .pred p; .reg .b32 n, t; mov.u32 n, 0;\n LP:\n"
                 "ld.relaxed.gpu.global.u32 t, [%0];\n sub.s32 t, t, %1;\n setp.lt.s32 p, t, 0;\n vote.sync.any.pred p, p, 0xffffffff;\n @!p bra.uni DN;\n" SPIN_TAIL("1")
                 ::"l"(p), "r"(target) : "memory");
}
template <int STR>
__device__ __forceinline__ void poll4_kv(uint32_t* v, const uint4* p, uint32_t tag) {
    asm volatile("{ .reg .pred p; .reg .b32 n, t; .reg .b128 q; mov.u32 n, 0;\n LP:\n"
                 LDP("%0", "%1", "%2", "%3", "%16", "0") LDP("%4", "%5", "%6", "%7", "%16", "%18")
                 LDP("%8", "%9", "%10", "%11", "%16", "%19") LDP("%12", "%13", "%14", "%15", "%16", "%20")
                 "xor.b32 t, %0, %17;\n" CHK("%4", "%17") CHK("%8", "%17") CHK("%12", "%17") VOTE_OK SPIN_TAIL("2")
                 : WR4(v, 0), WR4(v, 4), WR4(v, 8), WR4(v, 12)
                 : "l"(p), "r"(tag), "n"(16 * STR), "n"(32 * STR), "n"(48 * STR)
                 : "memory");
}
template <int B>
__device__ __forceinline__ void blk_load(uint32_t (&A)[8][14], const uint4* src, int lane) {
    ld_pkt<0>(&A[2 * B][0], src); ld_pkt<32>(&A[2 * B][4], src); ld_pkt<64>(&A[2 * B][8], src);
    ld_pkt<512>(&A[2 * B + 1][0], src); ld_pkt<544>(&A[2 * B + 1][4], src); ld_pkt<576>(&A[2 * B + 1][8], src);
    asm volatile("{ .reg .b64 h;\n" LDH("%0", "%1", "%4", "1536") LDH("%2", "%3", "%4", "9728") "}"
                 : "=&r"(A[2 * B][12]), "=&r"(A[2 * B][13]), "=&r"(A[2 * B + 1][12]), "=&r"(A[2 * B + 1][13])
                 : "l"((const char*)src - lane * 8) : "memory");
}
template <int B>
__device__ __forceinline__ void blk_check(uint32_t (&A)[8][14], const uint4* src, int lane, uint32_t tag) {
    asm volatile("{ .reg .pred p; .reg .b32 n, t; .reg .b128 q; .reg .b64 h, a8; mov.u32 n, 0;\n LP:\n"
                 "xor.b32 t, %0, %30;\n" CHK("%4", "%30") CHK("%8", "%30") CHK("%12", "%30") CHK("%16", "%30") CHK("%20", "%30") CHK("%24", "%30") CHK("%26", "%30") VOTE_OK
                 LDP("%0", "%1", "%2", "%3", "%28", "0") LDP("%4", "%5", "%6", "%7", "%28", "512") LDP("%8", "%9", "%10", "%11", "%28", "1024")
                 LDP("%12", "%13", "%14", "%15", "%28", "8192") LDP("%16", "%17", "%18", "%19", "%28", "8704") LDP("%20", "%21", "%22", "%23", "%28", "9216")
                 "mad.wide.s32 a8, %29, -8, %28;\n" LDH("%24", "%25", "a8", "1536") LDH("%26", "%27", "a8", "9728") SPIN_TAIL("3")
                 "\n and.b32 %0, %0, -2; and.b32 %4, %4, -2; and.b32 %8, %8, -2; and.b32 %12, %12, -2; and.b32 %16, %16, -2; and.b32 %20, %20, -2; and.b32 %24, %24, -2; and.b32 %26, %26, -2;"
                 : RW4(A[2 * B], 0), RW4(A[2 * B], 4), RW4(A[2 * B], 8), RW4(A[2 * B + 1], 0), RW4(A[2 * B + 1], 4), RW4(A[2 * B + 1], 8),
                   RW2(A[2 * B], 12), RW2(A[2 * B + 1], 12)
                 : "l"(src), "r"(lane), "r"(tag)
                 : "memory");
}
__device__ __forceinline__ void st_async4(uint32_t a, uint32_t x, uint32_t y, uint32_t z, uint32_t w, uint32_t bar) {
    asm volatile("st.async.weak.shared::cluster.mbarrier::complete_tx::bytes.v4.b32 [%0], {%1,%2,%3,%4}, [%5];" ::"r"(a), "r"(x), "r"(y), "r"(z), "r"(w), "r"(bar) : "memory");
}
__device__ __forceinline__ uint32_t mapa(uint32_t a, uint32_t cta) { uint32_t r; asm("mapa.shared::cluster.u32 %0, %1, %2;" : "=r"(r) : "r"(a), "r"(cta)); return r; }
__device__ __forceinline__ void stat_load(uint32_t* v, const uint4* p) { ld_pkt<0>(v, p); ld_pkt<512>(v + 4, p); }
__device__ __forceinline__ void stat_check(uint32_t* v, const uint4* p, uint32_t tag) {
    asm volatile("{ .reg .pred p; .reg .b32 n, t; .reg .b128 q; mov.u32 n, 0;\n LP:\n"
                 "xor.b32 t, %3, %9;\n" CHK("%7", "%9") VOTE_OK
                 LDP("%0", "%1", "%2", "%3", "%8", "0") LDP("%4", "%5", "%6", "%7", "%8", "8192") SPIN_TAIL("4")
                 : RW4(v, 0), RW4(v, 4) : "l"(p), "r"(tag) : "memory");
}
__device__ __forceinline__ uint32_t x_bits(const uint32_t* X) {
    uint32_t r;
    asm volatile("{ .reg .b32 a, b; prmt.b32 a, %1, %2, 0x0040; prmt.b32 b, %3, %4, 0x0040; prmt.b32 %0, a, b, 0x5410; }" : "=r"(r) : "r"(X[0]), "r"(X[4]), "r"(X[8]), "r"(X[12]));
    return r;
}
template <int O>
__device__ __forceinline__ void slice_load(uint32_t* v, const uint4* p, int lane) {
    ld_pkt<O>(v, p); ld_pkt<O + 32>(v + 4, p); ld_pkt<O + 64>(v + 8, p);
    asm volatile("{ .reg .b64 h;\n" LDH("%0", "%1", "%2", "%3") "}" : "=r"(v[12]), "=r"(v[13]) : "l"((const char*)p - lane * 8), "n"(16 * (O + 96)) : "memory");
}
template <int O>
__device__ __forceinline__ void slice_check(uint32_t* v, const uint4* p, int lane, uint32_t tag) {
    asm volatile("{ .reg .pred p; .reg .b32 n, t; .reg .b128 q; .reg .b64 h; mov.u32 n, 0;\n LP:\n"
                 "xor.b32 t, %0, %16;\n" CHK("%4", "%16") CHK("%8", "%16") CHK("%12", "%16") VOTE_OK
                 LDP("%0", "%1", "%2", "%3", "%14", "%17") LDP("%4", "%5", "%6", "%7", "%14", "%18") LDP("%8", "%9", "%10", "%11", "%14", "%19")
                 LDH("%12", "%13", "%15", "%20") SPIN_TAIL("5")
                 : RW4(v, 0), RW4(v, 4), RW4(v, 8), RW2(v, 12)
                 : "l"(p), "l"((const char*)p - lane * 8), "r"(tag), "n"(16 * O), "n"(16 * (O + 32)), "n"(16 * (O + 64)), "n"(16 * (O + 96))
                 : "memory");
}
__device__ __forceinline__ void x_fix(uint32_t* X, uint32_t bits) {
    X[0] = __byte_perm(X[0], bits, 0x3214); X[4] = __byte_perm(X[4], bits, 0x3215); X[8] = __byte_perm(X[8], bits, 0x3216); X[12] = __byte_perm(X[12], bits, 0x3217);
}
__device__ __forceinline__ void sts4(uint32_t a, uint32_t x, uint32_t y, uint32_t z, uint32_t w) {
    asm volatile("st.shared.v4.u32 [%0], {%1,%2,%3,%4};" ::"r"(a), "r"(x), "r"(y), "r"(z), "r"(w) : "memory");
}
__device__ __forceinline__ void lds4(uint32_t* v, uint32_t a) {
    asm volatile("ld.shared.v4.u32 {%0,%1,%2,%3}, [%4];" : "=r"(v[0]), "=r"(v[1]), "=r"(v[2]), "=r"(v[3]) : "r"(a) : "memory");
}
struct LnCoef { uint32_t hi, lo, sh; };
__device__ __forceinline__ LnCoef ln_coef(float sum, float sq) {
    sum += __shfl_xor_sync(0xffffffffu, sum, 1); sq += __shfl_xor_sync(0xffffffffu, sq, 1);
    sum += __shfl_xor_sync(0xffffffffu, sum, 2); sq += __shfl_xor_sync(0xffffffffu, sq, 2);
    const float mean = sum * (1.f / 448.f);
    const float var = fmaxf(fmaf(-mean, mean, sq * (1.f / 448.f)), 0.f);
    const float sc = rsqrtf(var + 1e-5f);
    LnCoef r;
    r.hi = pack2(sc, sc);
    const float lo = sc - bf_lo(r.hi), sh = -mean * sc;
    r.lo = pack2(lo, lo);
    r.sh = pack2(sh, sh);
    return r;
}
template <int B>
__device__ __forceinline__ void normalize(uint32_t (&A)[8][14], const LnCoef& c0, const LnCoef& c1) {
#pragma unroll
    for (int s = 2 * B; s < 2 * B + 2; s++)
#pragma unroll
        for (int i = 0; i < 14; i++) {
            const LnCoef& k = (i & 1) ? c1 : c0;
            asm("{ .reg .b32 t; fma.rn.bf16x2 t, %0, %2, %3; fma.rn.bf16x2 %0, %0, %1, t; }" : "+r"(A[s][i]) : "r"(k.hi), "r"(k.lo), "r"(k.sh));
        }
}
__device__ __forceinline__ void slice_stats(const uint32_t* w, float* st) {
    float a = 0.f, b = 0.f, p = 0.f, q = 0.f;
#pragma unroll
    for (int i = 0; i < 7; i++) {
        const float e0 = bf_lo(w[2 * i]), e1 = bf_hi(w[2 * i]), e2 = bf_lo(w[2 * i + 1]), e3 = bf_hi(w[2 * i + 1]);
        a += e0 + e1; b += e2 + e3;
        p = fmaf(e0, e0, p); p = fmaf(e1, e1, p); q = fmaf(e2, e2, q); q = fmaf(e3, e3, q);
    }
    a += __shfl_xor_sync(0xffffffffu, a, 1); p += __shfl_xor_sync(0xffffffffu, p, 1); b += __shfl_xor_sync(0xffffffffu, b, 1); q += __shfl_xor_sync(0xffffffffu, q, 1);
    a += __shfl_xor_sync(0xffffffffu, a, 2); p += __shfl_xor_sync(0xffffffffu, p, 2); b += __shfl_xor_sync(0xffffffffu, b, 2); q += __shfl_xor_sync(0xffffffffu, q, 2);
    st[0] = a; st[1] = p; st[2] = b; st[3] = q;
}
__device__ __forceinline__ void dual_softmax(const float* p, uint32_t* out) {
    constexpr float L = 1.4426950408889634f;
#pragma unroll
    for (int r = 0; r < 2; r++) {
        float mx = fmaxf(p[2 * r], p[2 * r + 1]), mn = fminf(p[2 * r], p[2 * r + 1]);
#pragma unroll
        for (int i = 1; i < 7; i++) {
            mx = fmaxf(mx, fmaxf(p[4 * i + 2 * r], p[4 * i + 2 * r + 1]));
            mn = fminf(mn, fminf(p[4 * i + 2 * r], p[4 * i + 2 * r + 1]));
        }
        mx = fmaxf(mx, __shfl_xor_sync(0xffffffffu, mx, 1));
        mn = fminf(mn, __shfl_xor_sync(0xffffffffu, mn, 1));
        const float bx = -mx * L, bn = mn * L;
        float ep[14], en[14], sp = 0.f, sn = 0.f;
#pragma unroll
        for (int i = 0; i < 14; i++) {
            const float v = p[4 * (i >> 1) + 2 * r + (i & 1)];
            ep[i] = ex2(fmaf(v, L, bx));
            en[i] = ex2(fmaf(v, -L, bn));
            sp += ep[i]; sn += en[i];
        }
        sp += __shfl_xor_sync(0xffffffffu, sp, 1);
        sn += __shfl_xor_sync(0xffffffffu, sn, 1);
        const float ip = rcp(sp), in = rcp(sn);
#pragma unroll
        for (int i = 0; i < 7; i++) {
            out[4 * i + r] = pack2(ep[2 * i] * ip, ep[2 * i + 1] * ip);
            out[4 * i + 2 + r] = pack2(en[2 * i] * in, en[2 * i + 1] * in);
        }
    }
}
__device__ __forceinline__ float geglu(float g, float u) {
    const float t = tanh_hw(g * fmaf(g * g, 0.7978845608028654f * 0.044715f, 0.7978845608028654f));
    const float gu = g * u;
    return fmaf(t, gu, gu);
}
__device__ __forceinline__ void phi_gemm(const float* t, float* p) {
    uint32_t w[14];
#pragma unroll
    for (int i = 0; i < 14; i++) w[i] = pack2(t[2 * i], t[2 * i + 1]);
    const uint64_t db = BASE128(OFF_WPHI, 16, 0);
    wg_fence();
    mma_rs56<0, 0>(p, w[0], w[1], w[2], w[3], 0, db);
    mma_rs56<0, 2>(p, w[4], w[5], w[6], w[7], 1, db);
    mma_rs56<0, 4>(p, w[8], w[9], w[10], w[11], 1, db);
    mma_rs56<0, 6>(p, w[12], w[13], 0u, 0u, 1, db);
    wg_commit();
    wg_wait<0>();
}

}

#define BAR(i) (bars + 8 * (i))
#define R_WAIT() mbar_wait(BAR(slot), ph)
#define WSUM(i)
#define R_ADJ (slot * (STAGE >> 4))
#define R_NEXT() do { eb2 = eb1; eb1 = BAR(B_EMPTY + slot); if (++slot == NST) { slot = 0; ph ^= 1; } } while (0)
#define R_RELEASE(k) do { if (lane == 0) mbar_arrive((k) == 1 ? eb1 : eb2); } while (0)
#define PUSH_BEGIN() do { mbar_wait(BAR(B_ACK + wgi), ackph); ackph ^= 1; } while (0)
#define PUSH_ACK() do { __syncwarp(); if (lane == 0) asm volatile("mbarrier.arrive.shared::cluster.b64 _, [%0];" ::"r"(mapa(BAR(B_ACK + wgi), hr ^ 1)) : "memory"); } while (0)

__global__ void __cluster_dims__(2, 1, 1) __launch_bounds__(384, 1)
fused_kernel(Scratch* const sc, const __nv_bfloat16* __restrict__ x_in, const __nv_bfloat16* __restrict__ w_phi, const int trips,
             const __nv_bfloat16* __restrict__ wg, const __nv_bfloat16* __restrict__ wu, const __nv_bfloat16* __restrict__ wd,
             const __grid_constant__ Maps maps) {
    extern __shared__ __align__(1024) unsigned char smem_raw[];
    const uint32_t sb = s2u(smem_raw);
    const uint32_t bars = sb + OFF_BAR;
    const int wgi = __shfl_sync(0xffffffffu, threadIdx.x >> 7, 0);
    const int hr = blockIdx.x & 1, ck = blockIdx.x >> 1;
    const int gp = (ck - 4) & 7, q7 = ((ck - 36) * 37) >> 8;
    const int pr = __shfl_sync(0xffffffffu, ck < 4 ? ck : (ck < 36 ? (ck - 4) >> 3 : q7), 0);
    const int tile = __shfl_sync(0xffffffffu, ck < 4 ? 0 : (ck < 36 ? (gp ? 2 * gp : 1) : 2 * (ck - 36 - 7 * q7) + 3), 0);
    const int sl = 2 * pr + hr;
    STAMP(0);
    GSTAMP(60);
    if (threadIdx.x == 256) {
#pragma unroll
        for (int i = 0; i < NST; i++) mbar_init(BAR(i), 1);
        asm volatile("fence.mbarrier_init.release.cluster;" ::: "memory");
    }
    if (threadIdx.x == 288) {
        if ((sb & 0x3FFFF) != SB0) asm volatile("trap;");
#pragma unroll
        for (int i = NST; i < B_COUNT; i++) mbar_init(BAR(i), i >= B_ACK ? 4 : (i < B_RECV || i == B_LATE ? 8 : 1));
        asm volatile("fence.mbarrier_init.release.cluster;" ::: "memory");
    }
    __syncwarp();
    asm volatile("barrier.cluster.arrive.relaxed.aligned;" ::: "memory");

    if (wgi == 2) {
        asm volatile("setmaxnreg.dec.sync.aligned.u32 40;");
        const int t128 = fresh_tid() & 127, w = __shfl_sync(0xffffffffu, t128 >> 5, 0), lane = t128 & 31;
        uint32_t e0[2] = {0, 0}, e1[2] = {0, 0}, cw_target = 0, kseq;
        if (w == 0) {
#pragma unroll 1
            for (int n = 0; n < NST; n++) {
                const uint32_t dst = sb + n * STAGE, fb = BAR(n);
                asm volatile(ELECT "mbarrier.arrive.expect_tx.shared::cta.b64 _, [%0], %1; }" ::"r"(fb), "r"(n < 2 ? 2 * STAGE : STAGE) : "memory");
                if (n < 2) {
                    tma3x(sb + OFF_H + n * STAGE, &maps.x, tile * 128 + n * 64, fb);
                    tma3x(dst, &maps.x, tile * 128 + n * 64 + 32, fb);
                } else {
                    if (n == 3) mbar_wait(BAR(1), 0);
                    const int ra = 112 * (n - 2);
                    tma2d(dst, &maps.qkv, 448 + 56 * sl, ra, fb);
                    tma2d(dst + HALF, &maps.qkv, 896 + 56 * sl, ra, fb);
                }
            }
            asm volatile("barrier.cluster.wait.aligned;" ::: "memory");
            kseq = ld_word(g_c1 + (sl * 8 * 16 + tile) * 32);
            cw_target = (ld_word(g_cw + sl * 32) & ~15u) + 16;
#pragma unroll 1
            for (int k = 0; k < 2; k++) {
                const int n = t128 + 32 * k;
                int m = n - 2 - (n > PACK);
                const bool packed = m >= 30 ? (m < 38 || m >= 52) : m >= 22;
                if (m >= 30) m -= 30;
                if (n == PACK) m = tile < 8 ? tile : tile + 14;
                const int rot = n < 8 ? 0 : pr;
                const int ra = 112 * kblk(rot, m & 3), rb = 112 * kblk(rot, 2 * m & 3), rc = 112 * kblk(rot, (2 * m + 1) & 3);
                int kind = 0, m0, m1, c0, c1, r0, r1;
                if (m < 4) { m0 = m1 = 1; c0 = 448 + 56 * sl; c1 = c0 + 448; r0 = r1 = ra; }
                else if (m < 8) { m0 = m1 = m < 6 ? 1 : 2; c0 = c1 = 56 * sl; r0 = rb; r1 = rc; }
                else if (m < 20) { m0 = 3; m1 = 4; c0 = c1 = 224 * sl + 32 * hr + 64 * ((m - 8) >> 2); r0 = r1 = ra; }
                else if (m < 22) { kind = 2; m0 = 5; m1 = 6; c0 = c1 = 224 * sl + (hr ? 0 : 192); r0 = rb; r1 = rc; }
                else { m0 = m1 = 7; c0 = c1 = 56 * (2 * ((pr + (m >> 1) - 10) & 3) + hr); r0 = 224 * (sl ^ (m & 1)); r1 = r0 + 112; }
                if (packed) { kind = 1; r0 = sl * 16 + (m < 8 ? m : m - 14); r1 = 0; }
                e0[0] = e0[1]; e1[0] = e1[1];
                e0[1] = kind | (m0 << 2) | (m1 << 6) | (c0 << 10) | (c1 << 21);
                e1[1] = r0 | (r1 << 16);
            }
        } else {
            const int j = t128 - 32;
            kseq = ld_word(g_c1 + (sl * 8 * 16 + tile) * 32);
            asm volatile("barrier.cluster.wait.aligned;" ::: "memory");
            uint2 wv[7];
            const int k = j < 56 ? j : 55, hh = k >= 28;
#pragma unroll
            for (int i = 0; i < 7; i++) wv[i] = __ldg(reinterpret_cast<const uint2*>(w_phi + (sl * 56 + k) * 28) + i);
#pragma unroll 1
            for (int i = j; i < 7168 / 16; i += 96) sts4(sb + OFF_WPHI + i * 16, 0, 0, 0, 0);
            bar_sync(5, 96);
            if (j < 56) {
                uint32_t a4[4];
#pragma unroll
                for (int q = 0; q < 4; q++) a4[q] = sb + OFF_WPHI + (4 * hh + q) * 128 + ((((k >> 3) ^ (4 * hh + q)) & 7) << 4) + (k & 7) * 2;
                FOR14(const uint32_t v = (t & 1) ? wv[t >> 1].y : wv[t >> 1].x;
                      asm volatile("{ .reg .b16 l, h; mov.b32 {l, h}, %2; st.shared.u16 [%0+%3], l; st.shared.u16 [%1+%3], h; }"
                                   ::"r"(a4[t >= 7 ? 2 : 0]), "r"(a4[t >= 7 ? 3 : 1]), "r"(v), "n"((t % 7) * 1024) : "memory"));
            }
            __syncwarp();
            fence_async();
            kseq = __shfl_sync(0xffffffffu, kseq, 0);
            bar_arrive(1, 224);
            bar_arrive(9, 224);
        }
        kseq = __shfl_sync(0xffffffffu, kseq, 0);
        int slot = 0, ph = 0, n = NST;
#pragma unroll 1
        for (int layer = 0; layer < 3; layer++) {
            if (w == 0) {
                const int nend = layer == 0 ? 11 : (layer == 1 ? 42 : 63);
#pragma unroll 1
                for (; n < nend; n++) {
                const uint32_t w0 = __shfl_sync(0xffffffffu, n < 32 ? e0[0] : e0[1], n & 31), w1 = __shfl_sync(0xffffffffu, n < 32 ? e1[0] : e1[1], n & 31);
                const uint32_t dst = sb + slot * STAGE, fb = BAR(n == PACK ? B_PACK : slot);
                const CUtensorMap* m0 = &maps.x + ((w0 >> 2) & 15);
                const CUtensorMap* m1 = &maps.x + ((w0 >> 6) & 15);
                const int c0 = (w0 >> 10) & 2047, c1 = w0 >> 21, r0 = w1 & 0xffff, r1 = w1 >> 16;
                if (n == 25) {
                    int it = 0;
                    uint32_t v;
                    do { asm volatile("ld.acquire.gpu.global.u32 %0, [%1];" : "=r"(v) : "l"(g_cw + sl * 32) : "memory"); } while ((int)(v - cw_target) < 0 && ++it < 0x400000);
                    asm volatile("fence.proxy.async.global;" ::: "memory");
                    __syncwarp();
                }
                mbar_wait(BAR(B_EMPTY + slot), ph);
                __syncwarp();
                asm volatile(ELECT "mbarrier.arrive.expect_tx.shared::cta.b64 _, [%0], %1; }" ::"r"(fb), "r"(STAGE) : "memory");
                if ((w0 & 3) == 0) {
                    tma2d(dst, m0, c0, r0, fb);
                    tma2d(dst + HALF, m1, c1, r1, fb);
                } else if (w0 & 1) {
                    asm volatile(ELECT "cp.async.bulk.shared::cluster.global.mbarrier::complete_tx::bytes [%0], [%1], %2, [%3]; }"
                                 ::"r"(dst), "l"(reinterpret_cast<const char*>(g_wp) + (size_t)r0 * STAGE), "r"(STAGE), "r"(fb) : "memory");
                } else {
                    tma2d(dst, m0, c0, r0, fb); tma2d(dst + 7168, m0, c0, r1, fb);
                    tma2d(dst + HALF, m1, c0, r0, fb); tma2d(dst + HALF + 7168, m1, c0, r1, fb);
                }
                if (n == PFN) {
                    const int b = blockIdx.x;
                    asm volatile(ELECT "cp.async.bulk.prefetch.L2.global [%0], %1; }" ::"l"(wg + b * 6272), "r"(12544) : "memory");
                    asm volatile(ELECT "cp.async.bulk.prefetch.L2.global [%0], %1; }" ::"l"(wu + b * 6272), "r"(12544) : "memory");
                    asm volatile(ELECT "cp.async.bulk.prefetch.L2.global [%0], %1; }" ::"l"(wd + b * 6272), "r"(12544) : "memory");
                }
                if (n == PACK) asm volatile(ELECT "mbarrier.arrive.shared::cta.b64 _, [%0]; }" ::"r"(BAR(slot)) : "memory");
                if (++slot == NST) { slot = 0; ph ^= 1; }
                }
            } else if (w == 1 && layer == 1) {
                constexpr int ps = PACK % NST;
                mbar_wait(BAR(B_PACK), 0);
                asm volatile("{ .reg .pred e; elect.sync _|e, 0xffffffff;\n"
                             "@e cp.async.bulk.global.shared::cta.bulk_group [%0], [%1], %2;\n"
                             "@e cp.async.bulk.commit_group;\n"
                             "@e cp.async.bulk.wait_group.read 0;\n"
                             "@e mbarrier.arrive.shared::cta.b64 _, [%3], 8;\n"
                             "@e cp.async.bulk.wait_group 0;\n"
                             "@e fence.proxy.async.global;\n"
                             "@e red.release.gpu.global.add.u32 [%4], 1; }"
                             ::"l"(reinterpret_cast<char*>(g_wp) + (size_t)(sl * 16 + tile) * STAGE), "r"(sb + ps * STAGE), "r"(STAGE), "r"(BAR(B_EMPTY + ps)), "l"(g_cw + sl * 32) : "memory");
                __syncwarp();
            }
            if (layer < 2) {
            const uint32_t tag = layer ^ 1;
            kseq++;
            bar_sync(7, 384);
            ASTAMP(0);
            if (tile < 15) {
                const int sq = lane >> 3, pk = 8 * w + (lane & (tile == 14 ? 3 : 7));
                uint32_t v[16];
                if (layer == 0) poll_cnt(g_c1 + ((sl * 8 + (w >> 1) * 4 + (tile >> 2)) * 16 + (lane & 15)) * 32, kseq);
                ASTAMP(1);
                poll4_kv<32>(v, g_kv1 + ((sl * 16 + tile) * 16 + 4 * sq) * 32 + pk, tag);
#pragma unroll
                for (int k = 0; k < 4; k++) {
                    float lo = (bf_lo(v[k]) + bf_lo(v[4 + k])) + (bf_lo(v[8 + k]) + bf_lo(v[12 + k]));
                    float hi = (bf_hi(v[k]) + bf_hi(v[4 + k])) + (bf_hi(v[8 + k]) + bf_hi(v[12 + k]));
                    lo += __shfl_xor_sync(0xffffffffu, lo, 8); hi += __shfl_xor_sync(0xffffffffu, hi, 8);
                    lo += __shfl_xor_sync(0xffffffffu, lo, 16); hi += __shfl_xor_sync(0xffffffffu, hi, 16);
                    v[k] = pack2(lo, hi);
                }
                if (sq == 0) st_pkt<0>(g_kv2 + sl * 512 + 32 * tile + pk, settag(v[0], tag), v[1], v[2], v[3]);
            }
            ASTAMP(2);
            {
                const int item = t128 < 112 ? t128 : 112 + (t128 & 3), d = item >> 1;
                const int cc = t128 < 112 ? 2 * (d >= 28) + (item & 1) : item - 112;
                const int r = t128 < 112 ? d : 56 + (cc >> 1) + 2 * ((t128 - 112) >> 2);
                uint32_t ra = sb + OFF_KVB + r * 128 + 4 * cc, rx = (r & 7) << 4;
                asm volatile("" : "+r"(ra), "+r"(rx));
                FOR14(asm volatile("st.shared.u32 [%0+%2], %1;" ::"r"((ra ^ 8) + (((t & 7) << 4) ^ rx)), "r"(0), "n"((t >> 3) * 8192) : "memory"));
                uint32_t v[16];
                asm volatile("" : "+r"(ra), "+r"(rx));
                poll4_kv<8>(v, g_kv2 + sl * 512 + (item >> 3) * 32 + (item & 7), tag);
                FOR14(asm volatile("st.shared.u32 [%0+%2], %1;" ::"r"(ra + (((t & 7) << 4) ^ rx)), "r"(v[t < 7 ? t : t + 1]), "n"((t >> 3) * 8192) : "memory"));
                fence_async();
            }
            bar_arrive(3, 384);
            ASTAMP(3);
            }
        }
    } else {
        asm volatile("setmaxnreg.inc.sync.aligned.u32 232;");
        int lane = fresh_tid() & 31, prf = pr;
#define pr prf
#define g (lane >> 2)
#define c (lane & 3)
#define t128 (w * 32 + lane)
        const int wu = __shfl_sync(0xffffffffu, fresh_tid() >> 5, 0), w = wu & 3;
        const uint32_t xoff = __shfl_sync(0xffffffffu, (3 * PLANE + ((tile * 2 + wgi) * 8) * 512 + w * 128) * 16, 0);
        char* xu = reinterpret_cast<char*>(g_ex) + xoff;
#define FRESH() asm volatile("" : "+l"(xu), "+r"(lane), "+r"(prf))
#define xp0 (reinterpret_cast<uint4*>(xu) + lane)
        const uint32_t hbuf = sb + OFF_H + wgi * STAGE;
        uint32_t slot = 0, ph = 0, eb1 = 0, eb2 = 0, ackph = 0, rcvph = 0, gatph = 0, swp = 0;
        uint32_t ppid = 6;
#define cx(s) (reinterpret_cast<uint32_t*>(reinterpret_cast<uint4*>(xu) + PL(1) + 112 + (s) * 512))
#define stp (reinterpret_cast<uint4*>(xu) + g + PL(0) + 112)
        uint32_t seq = ld_word(cx(sl));
        uint32_t kseq = ld_word(g_c1 + ((sl * 8 + wu) * 16 + tile) * 32);
        uint32_t stag = ld_word(reinterpret_cast<const uint32_t*>(stp + sl * 512) + 3) & 1;
        asm volatile("barrier.cluster.wait.aligned;" ::: "memory");
        STAMP(1);
        uint32_t X[14];
        const uint32_t x0row = (w < 2 ? hbuf : sb + wgi * STAGE) + ((w & 1) * 16 + (lane & 15)) * 128;
        mbar_wait(BAR(wgi), 0);
        STAMP(51);
#pragma unroll
        for (int j = 0; j < 4; j++) {
            const int G = 7 * sl + min(2 * j + (lane >> 4), 6);
            uint32_t q2, q3;
            asm volatile("ldmatrix.sync.aligned.m8n8.x4.shared.b16 {%0,%1,%2,%3}, [%4];" : "=r"(X[4 * j]), "=r"(X[4 * j + 1]), "=r"(q2), "=r"(q3)
                         : "r"(x0row + (G >> 3) * 4096 + (((G ^ lane) & 7) << 4)) : "memory");
            if (j < 3) { X[(4 * j + 2) % 14] = q2; X[(4 * j + 3) % 14] = q3; }
        }
#define PUSH_SLICE(W)                                                                          \
    {                                                                                          \
        if (t128 == 0) mbar_expect_tx(BAR(B_RECV + wgi), 7168);                                \
        PUSH_BEGIN();                                                                          \
        const uint32_t ra = mapa(hbuf + 24576 + t128 * 16, hr ^ 1), rb = mapa(sb + OFF_XR + wgi * 3072, hr ^ 1), rbar = mapa(BAR(B_RECV + wgi), hr ^ 1); \
        st_async4(ra, W[0], W[1], W[2], W[3], rbar);                                           \
        st_async4(ra + 2048, W[4], W[5], W[6], W[7], rbar);                                    \
        st_async4(rb + t128 * 16, W[8], W[9], W[10], W[11], rbar);                             \
        asm volatile("st.async.weak.shared::cluster.mbarrier::complete_tx::bytes.v2.b32 [%0], {%1,%2}, [%3];" ::"r"(rb + 2048 + t128 * 8), "r"(W[12]), "r"(W[13]), "r"(rbar) : "memory"); \
    }
#define PULL_SLICE(W)                                                                          \
    {                                                                                          \
        uint32_t t0, t1;                                                                       \
        mbar_wait(BAR(B_RECV + wgi), rcvph);                                                   \
        rcvph ^= 1;                                                                            \
        lds4(&A[1][0], hbuf + 24576 + t128 * 16);                                              \
        lds4(&A[1][4], hbuf + 26624 + t128 * 16);                                              \
        lds4(&A[1][8], sb + OFF_XR + wgi * 3072 + t128 * 16);                                  \
        asm volatile("ld.shared.v2.u32 {%0,%1}, [%2];" : "=r"(t0), "=r"(t1) : "r"(sb + OFF_XR + wgi * 3072 + 2048 + t128 * 8) : "memory"); \
        _Pragma("unroll") for (int i = 0; i < 12; i++) A[0][i] = (i & 3) ? W[i] : W[i] & ~1u;  \
        A[1][0] &= ~1u; A[1][4] &= ~1u; A[1][8] &= ~1u;                                        \
        A[0][12] = (hr ? t0 : W[12]) & ~1u; A[0][13] = hr ? t1 : W[13];                        \
        A[1][12] = (hr ? W[12] : t0) & ~1u; A[1][13] = hr ? W[13] : t1;                        \
        asm volatile("" : RW4(A[0], 0), RW4(A[0], 4), RW4(A[0], 8), RW2(A[0], 12), RW4(A[1], 0), RW4(A[1], 4), RW4(A[1], 8), RW2(A[1], 12)); \
        swp = hr * 448;                                                                        \
    }
#define SWB(b, t, db, sh) ((b) == 0 && (t) < 6 ? ((t) < 3 ? db##p : db##m) : db)
#define DECL_DB(b, MK, lbo, sh) const uint64_t db = MK(0, lbo, R_ADJ), dbp = (b) == 0 ? MK(0, lbo, R_ADJ + (swp >> (sh))) : db, dbm = (b) == 0 ? MK(0, lbo, R_ADJ - (swp >> (sh))) : db;
#define PPB 2
#define PP_WAIT() if (wgi == 1) { bar_sync(ppid, 256); ppid ^= 14; }
#define PP_GO() if (wgi == 0) { bar_arrive(ppid, 256); ppid ^= 14; }
#define GAT_DST(B, s2) ((B) == 1 ? hbuf + w * 3584 + (s2) * 1792 : ((s2) ? sb + OFF_KVB + wgi * 8192 : hbuf + 14336) + w * 1792)
#define GAT_ISSUE(B, base)                                                                     \
    {                                                                                          \
        const char* gs = xu + ((base) + kblk(pr, B) * 1024) * 16;                              \
        asm volatile("{ .reg .pred e; elect.sync _|e, 0xffffffff;\n"                           \
                     "@e mbarrier.arrive.expect_tx.shared::cta.b64 _, [%3], 3584;\n"           \
                     "@e cp.async.bulk.shared::cluster.global.mbarrier::complete_tx::bytes [%0], [%2], 1792, [%3];\n" \
                     "@e cp.async.bulk.shared::cluster.global.mbarrier::complete_tx::bytes [%1], [%2+8192], 1792, [%3]; }" \
                     ::"r"(GAT_DST(B, 0)), "r"(GAT_DST(B, 1)), "l"(gs), "r"(BAR(B_GAT + wu * 2 + ((B) >> 1))) : "memory"); \
        __syncwarp();                                                                          \
    }
#define GAT_FETCH(B)                                                                           \
    {                                                                                          \
        mbar_wait(BAR(B_GAT + wu * 2 + ((B) >> 1)), (gatph >> (B)) & 1);                          \
        gatph ^= 1 << (B);                                                                     \
        _Pragma("unroll") for (int s2 = 0; s2 < 2; s2++) {                                     \
            const uint32_t ga = GAT_DST(B, s2) + lane * 16;                                    \
            lds4(&A[2 * (B) + s2][0], ga); lds4(&A[2 * (B) + s2][4], ga + 512); lds4(&A[2 * (B) + s2][8], ga + 1024); \
            asm volatile("ld.shared.v2.u32 {%0,%1}, [%2];" : "=r"(A[2 * (B) + s2][12]), "=r"(A[2 * (B) + s2][13]) : "r"(ga - lane * 8 + 1536) : "memory"); \
        }                                                                                      \
    }
#define LATE_ARRIVE() do { if (lane == 0) mbar_arrive(BAR(B_LATE)); } while (0)
#define LATE_WAIT() do { mbar_wait(BAR(B_LATE), gatph & 1); gatph ^= 1; } while (0)
#define PT 3
#define PREP(b, t, remote)                                                                     \
    if constexpr ((b) < 3 && (t) == PT) {                                                      \
        wg_commit();                                                                           \
        STAMP(74 + 6 * (step & 1) + 2 * (b));                                                  \
        if (remote) {                                                                          \
            if constexpr ((b) == 0) { blk_load<2>(A, BLK(xsrc, 2), lane); GAT_FETCH(1) }       \
            blk_check<((b) + 1) & 3>(A, BLK(xsrc, (b) + 1), lane, xtag);                       \
            if constexpr ((b) == 0 && XG3 == 0) blk_load<3>(A, BLK(xsrc, 3), lane); \
            if constexpr ((b) == 0 && XG3 == 2) GAT_ISSUE(3, (step & 1) ? PL(2) : PL(0))                        \
        }                                                                                      \
        STAMP(75 + 6 * (step & 1) + 2 * (b));                                                  \
        normalize<((b) + 1) & 3>(A, k0, k1);                                                   \
        asm volatile("" : RW4(A[(2 * (b) + 2) & 7], 0), RW4(A[(2 * (b) + 2) & 7], 4), RW4(A[(2 * (b) + 2) & 7], 8), RW2(A[(2 * (b) + 2) & 7], 12), \
                          RW4(A[(2 * (b) + 3) & 7], 0), RW4(A[(2 * (b) + 3) & 7], 4), RW4(A[(2 * (b) + 3) & 7], 8), RW2(A[(2 * (b) + 3) & 7], 12)); \
        wg_fence();                                                                            \
    }
#define X0_BLOCK(b)                                                                            \
    { const int rr = lane & 7, hi = lane >> 4;                                                 \
    const uint32_t rowa = (w < 2 ? hbuf : sb + wgi * STAGE) + ((w & 1) * 16 + (lane & 15)) * 128; \
    FOR7(constexpr int G = 14 * (b) + (t < 3 ? 2 * t : (t < 6 ? 2 * t + 1 : 6));               \
         uint32_t q0, q1, q2, q3;                                                              \
         const uint32_t ad = t < 6 ? rowa + (((((G & 7) + hi) ^ rr) & 7) << 4) + ((G & 7) == 7 ? hi * 4096 : 0) : rowa + ((G + 7 * hi) >> 3) * 4096 + ((((G + 7 * hi) ^ rr) & 7) << 4); \
         asm volatile("ldmatrix.sync.aligned.m8n8.x4.shared.b16 {%0,%1,%2,%3}, [%4+%5];" : "=r"(q0), "=r"(q1), "=r"(q2), "=r"(q3) \
                      : "r"(ad), "n"(t < 6 ? (G >> 3) * 4096 : 0) : "memory");                 \
         if (t < 3) { A[2 * (b)][4 * t] = q0; A[2 * (b)][4 * t + 1] = q1; A[2 * (b)][4 * t + 2] = q2; A[2 * (b)][4 * t + 3] = q3; } \
         else if (t < 6) { A[2 * (b) + 1][(4 * t - 12) & 15] = q0; A[2 * (b) + 1][((4 * t - 12) & 15) + 1] = q1; A[2 * (b) + 1][((4 * t - 12) & 15) + 2] = q2; A[2 * (b) + 1][((4 * t - 12) & 15) + 3] = q3; } \
         else { A[2 * (b)][12] = q0; A[2 * (b)][13] = q1; A[2 * (b) + 1][12] = q2; A[2 * (b) + 1][13] = q3; }); }
#define BLK(base, b) ((base) + kblk(pr, b) * 1024)

#pragma unroll 1
        for (int step = 0; step < 4; step++) {
            FRESH();
            const uint32_t tag = (step >> 1) ^ 1;
            const int so = (step >> 1) * 24 + (step & 1) * 12;
            (void)so;
            uint32_t A[8][14];
            uint4* const xsrc = xp0 + ((step & 1) ? PL(2) : PL(0));
            const uint32_t xtag = (step & 1) ? tag : ((seq >> 3) & 1) ^ 1;
            uint32_t xbits;
            {
                float st[4];
                slice_stats(X, st);
                stag ^= 1;
                xbits = x_bits(X);
                tag_slice(X, xtag);
                if (step) send_slice<0>(xsrc + sl * 512, lane, X);
                if (c == 0) st_pkt<0>(stp + sl * 512, __float_as_uint(st[0]), __float_as_uint(st[1]), __float_as_uint(st[2]), settag(__float_as_uint(st[3]), stag));
            }
            STAMP(2 + so);
            uint32_t sv[8];
            if (step == 0) {
                X0_BLOCK(0) X0_BLOCK(1) X0_BLOCK(2) X0_BLOCK(3)
                mbar_wait(BAR(wgi ^ 1), 0);
                R_NEXT();
                R_NEXT();
                R_RELEASE(2);
                stat_load(sv, stp + c * 1024);
                stat_check(sv, stp + c * 1024, stag);
                STAMP(52 + step);
            } else {
                kill<14>(A[2]); kill<14>(A[3]); kill<14>(A[4]); kill<14>(A[5]); kill<14>(A[6]); kill<14>(A[7]);
                PUSH_SLICE(X)
                stat_load(sv, stp + c * 1024);
                PULL_SLICE(X)
                stat_check(sv, stp + c * 1024, stag);
                STAMP(52 + step);
                GAT_ISSUE(1, (step & 1) ? PL(2) : PL(0))
                if (XG3 == 1) GAT_ISSUE(3, (step & 1) ? PL(2) : PL(0))
            }
            LnCoef k0, k1;
            {
                k0 = ln_coef(__uint_as_float(sv[0]) + __uint_as_float(sv[4]), __uint_as_float(sv[1]) + __uint_as_float(sv[5]));
                k1 = ln_coef(__uint_as_float(sv[2]) + __uint_as_float(sv[6]), __uint_as_float(sv[3] & ~1u) + __uint_as_float(sv[7] & ~1u));
            }
            STAMP(3 + so);
            GSTAMP(70 + step);

            if ((step & 1) == 0) {
                float tq[28];
                {
                    float av[28];
#define KV_BLOCK(b)                                                                           \
    if ((b) == 1) R_RELEASE(2);                                                               \
    if ((b) == 2) { if (!XG3) PUSH_ACK(); wg_wait<2>(); R_RELEASE(2); if (XG3 && step) GAT_FETCH(3) } \
    if ((b) == 3 && XG3) PUSH_ACK();                                                          \
    R_WAIT();                                                                                 \
    if ((b) == PPK) { PP_WAIT() }                                                             \
    { DECL_DB(b, BASE128, 16, 0)                                                              \
    wg_fence();                                                                               \
    FOR7(mma_rs56<1, D128(0, t)>(tq, AQ(A, b, t), (b) + t > 0, SWB(b, t, db, 0));             \
         mma_rs56<1, D128(HALF, t)>(av, AQ(A, b, t), (b) + t > 0, SWB(b, t, db, 0));          \
         PREP(b, t, step)); }                                                                 \
    wg_commit();                                                                              \
    if ((b) == 3 && PPK < 4) { PP_GO() }                                                      \
    R_NEXT();
                    normalize<0>(A, k0, k1);
                    KV_BLOCK(0) KV_BLOCK(1) KV_BLOCK(2) KV_BLOCK(3)
                    wg_wait<0>();
                    if (lane < 3) mbar_arrive(BAR(B_EMPTY + (slot + NST - 1 - lane) % NST));
                    STAMP(4 + so);
                    WSUM(80 + 7 * (step >> 1));
                    const int m = lane >> 3, rr = lane & 7;
                    const uint32_t rowa = hbuf + 16384 + (w * 16 + rr + 8 * (m & 1)) * 128;
                    const uint32_t one = c == 0 ? 0x00003f80u : 0u;
                    if (step == 0) { bar_sync(wgi ? 9 : 1, 224); }
#pragma unroll
                    for (int j = 0; j < 4; j++) {
                        const uint32_t a = rowa + (((2 * j + (m >> 1)) ^ rr) << 4);
                        if (j < 3) stsm4(a, pack2(av[8 * j], av[8 * j + 1]), pack2(av[8 * j + 2], av[8 * j + 3]), pack2(av[8 * j + 4], av[8 * j + 5]), pack2(av[8 * j + 6], av[8 * j + 7]));
                        else stsm4(a, pack2(av[24], av[25]), pack2(av[26], av[27]), one, one);
                    }
                }
                uint32_t PH[28];
                int it = 1;
#pragma unroll 1
                do {
                    float pp[28];
                    phi_gemm(tq, pp);
                    dual_softmax(pp, PH);
                    if (((trips >> (it + 1)) & 1) == 0) continue;
                    {
                        const int m = lane >> 3, rr = lane & 7;
                        const uint32_t rowa = hbuf + (w * 16 + rr + 8 * (m & 1)) * 128;
#pragma unroll
                        for (int j = 0; j < 7; j++) {
                            const int cg = 2 * j + (m >> 1), hi = cg >= 7;
                            stsm4(rowa + hi * 8192 + (((cg - 7 * hi) ^ rr) << 4), PH[4 * j], PH[4 * j + 1], PH[4 * j + 2], PH[4 * j + 3]);
                        }
                    }
                    fence_async();
                    STAMP(5 + so);
#define Q_STAGE(b0)                                                                           \
    R_WAIT();                                                                                 \
    { DECL_DB(b0, BASE128, 16, 0)                                                             \
    wg_fence();                                                                               \
    FOR7(mma_rs56<1, D128(0, t)>(tq, AQ(A, b0, t), (b0) + t > 0, SWB(b0, t, db, 0)));         \
    FOR7(mma_rs56<1, D128(HALF, t)>(tq, AQ(A, (b0) + 1, t), 1, db)); }                        \
    wg_commit();                                                                              \
    R_NEXT();
                    if (QE && wgi == 0) { kill<28>(tq); Q_STAGE(0) Q_STAGE(2) wg_wait<1>(); R_RELEASE(2); wg_wait<0>(); R_RELEASE(1); }
                    bar_sync(2, 256);
                    float kv[28];
                    const uint64_t da = BASE128(OFF_H + 16384, 16, 0), dbk = BASE128(OFF_H, 16, wgi * 512);
                    wg_fence();
                    FOR8(constexpr uint64_t o = ((t >> 2) * STAGE + (t & 3) * 2048) >> 4; mma_ss56_tt<o, o>(kv, t > 0, da, dbk));
                    wg_commit();
                    wg_wait<0>();
#pragma unroll
                    for (int hf = 0; hf < 2; hf++) {
                        const int d = 16 * w + g + 8 * hf;
                        if ((d < 56 && (d >= 28) == (c >= 2)) || d == 56) {
                            const int item = d < 56 ? 2 * d + (c & 1) : 112 + c;
                            uint4* dst = g_kv1 + ((sl * 16 + (item >> 3)) * 16 + tile) * 32 + wgi * 16 + (item & 7);
#define KVW(i) pack2(kv[4 * (i) + 2 * hf], kv[4 * (i) + 2 * hf + 1])
                            st_pkt<0>(dst, settag(KVW(0), tag), KVW(1), KVW(2), KVW(3));
                            st_pkt<8>(dst, settag(KVW(4), tag), KVW(5), KVW(6), 0u);
                        }
                    }
                    __syncwarp();
                    kseq++;
                    if (lane == 0) st_word(g_c1 + ((sl * 8 + wu) * 16 + tile) * 32, kseq);
                    bar_arrive(7, 384);
                    STAMP(6 + so);
                    if (!QE || wgi == 1) { kill<28>(tq); Q_STAGE(0) Q_STAGE(2) wg_wait<1>(); R_RELEASE(2); wg_wait<0>(); R_RELEASE(1); }
                    STAMP(7 + so);
                    kill<28>(PH);
                } while (((trips >> (++it)) & 1));
                STAMP(8 + so);
                FRESH();
                if (step) {
                    slice_load<PL(0)>(X, xp0 + sl * 512, lane);
                } else {
                    const uint32_t* xp = reinterpret_cast<const uint32_t*>(x_in + (size_t)(tile * 128 + wu * 16 + g) * 448 + 56 * sl + 2 * c);
#pragma unroll
                    for (int i = 0; i < 7; i++) { X[2 * i] = __ldg(xp + 4 * i); X[2 * i + 1] = __ldg(xp + 4 * i + 8 * 224); }
                }
                bar_sync(3, 384);
                STAMP(9 + so);
                const uint4* const osrc = xp0 + PL(1);
                {
                    float nm[32];
                    const uint64_t db = BASE128(OFF_KVB, 16, 0);
                    wg_fence();
                    FOR7(mma_rs64<0, ((t >> 2) * 8192 + (t & 3) * 32) / 16>(nm, PH[4 * t], PH[4 * t + 1], PH[4 * t + 2], PH[4 * t + 3], t > 0, db));
                    wg_commit();
                    wg_wait<0>();
                    LATE_ARRIVE();
                    const float i00 = rcp(nm[28] + 1e-6f), i01 = rcp(nm[29] + 1e-6f), i10 = rcp(nm[30] + 1e-6f), i11 = rcp(nm[31] + 1e-6f);
                    const float m0 = c >= 2 ? i01 : i00, m1 = c >= 2 ? i11 : i10;
                    uint32_t O[14];
#pragma unroll
                    for (int i = 0; i < 7; i++) {
                        const float f0 = i < 3 ? i00 : (i > 3 ? i01 : m0), f1 = i < 3 ? i10 : (i > 3 ? i11 : m1);
                        O[2 * i] = pack2(nm[4 * i] * f0, nm[4 * i + 1] * f0);
                        O[2 * i + 1] = pack2(nm[4 * i + 2] * f1, nm[4 * i + 3] * f1);
                    }
                    if (OST) { PP_WAIT() }
                    tag_slice(O, tag);
                    send_slice<PL(1)>(xp0 + sl * 512, lane, O);
                    seq++;
                    if (lane == 0) st_word(cx(sl), seq);
                    STAMP(10 + so);
                    PUSH_SLICE(O)
                    if (OST == 1) { PP_GO() }
                    const uint32_t cv = ld_word(cx(lane & 7));
                    PULL_SLICE(O)
                    LATE_WAIT();
                    check_cnt(cv, cx(lane & 7), seq);
                    if (OST == 2) { PP_GO() }
                    STAMP(56 + (step >> 1));
                    GAT_ISSUE(1, PL(1))
                    GAT_ISSUE(3, PL(1))
                    blk_load<2>(A, BLK(osrc, 2), lane);
                }
                float ao[28];
#define WO_BLOCK(b)                                                                           \
    if ((b) > 0) blk_check<b>(A, BLK(osrc, b), lane, tag);                                    \
    if (((b) & 1) == 0) R_WAIT();                                                             \
    { DECL_DB(b, BASE128, 16, 0)                                                              \
    wg_fence();                                                                               \
    FOR7(mma_rs56<1, D128(((b) & 1) * HALF, t)>(ao, AQ(A, b, t), (b) + t > 0, SWB(b, t, db, 0))); } \
    wg_commit();                                                                              \
    if ((b) & 1) R_NEXT();
                WO_BLOCK(0)
                STAMP(11 + so);
                GAT_FETCH(1)
                WO_BLOCK(1)
                WO_BLOCK(2)
                GAT_FETCH(3)
                WO_BLOCK(3)
                PUSH_ACK();
                wg_wait<0>();
                R_RELEASE(2);
                STAMP(12 + so);
                WSUM(86 + 7 * (step >> 1));
                x_fix(X, xbits);
#pragma unroll
                for (int i = 0; i < 14; i++) X[i] = pack2(bf_lo(X[i]) + ao[2 * i], bf_hi(X[i]) + ao[2 * i + 1]);
            } else {
                uint32_t H[56];
                float ag[64];
#define F1_EPI(dst, ng, ag)                                                                    \
    _Pragma("unroll") for (int i = 0; i < 2 * (ng); i++)                                       \
        (dst)[i] = pack2(geglu(ag[2 * i], ag[4 * (ng) + 2 * i]), geglu(ag[2 * i + 1], ag[4 * (ng) + 2 * i + 1]));
#define H_PUSH(h0, off) st_async4(rem_h + (off), H[h0], H[(h0) + 1], H[(h0) + 2], H[(h0) + 3], mapa(BAR(B_RECV2 + wgi), hr ^ 1));
#define F1_BLOCK(b, first)                                                                     \
    if ((first) && (b) == 1) R_RELEASE(2);                                                     \
    if ((first) && (b) == 2 + (XG3 != 0)) PUSH_ACK();                                          \
    if ((first) && (b) == 2 && XG3) GAT_FETCH(3)                                               \
    R_WAIT();                                                                                  \
    if ((b) == ((first) ? PPF : PPB)) { PP_WAIT() }                                            \
    { DECL_DB(b, BASE128, HALF, 0)                                                             \
    wg_fence();                                                                                \
    FOR7(mma_rs128<1, D128(0, t)>(ag, AQ(A, b, t), (b) + t > 0, SWB(b, t, db, 0));             \
         if constexpr (first) { PREP(b, t, true) }); }                                         \
    wg_commit();                                                                               \
    if ((b) == 3) { PP_GO() }                                                                  \
    if ((b) > 0) { wg_wait<1>(); R_RELEASE(1); }       \
    R_NEXT();
                normalize<0>(A, k0, k1);
                F1_BLOCK(0, true) F1_BLOCK(1, true) F1_BLOCK(2, true) F1_BLOCK(3, true)
                if (t128 == 0) { mbar_expect_tx(BAR(B_RECV + wgi), 16384); mbar_expect_tx(BAR(B_RECV2 + wgi), 12288); }
                PUSH_BEGIN();
                wg_wait<0>();
                R_RELEASE(1);
                int p = 0;
#pragma unroll 1
                do {
                    F1_EPI(H + 32, 8, ag)
                    STAMP(4 + p + so);
                    WSUM(81 + p + 7 * (step >> 1));
                    if (((trips >> (p + 1)) & 1) == 0) continue;
                    if (step == 1 && p == PKP) R_NEXT();
                    kill<64>(ag);
                    F1_BLOCK(0, false)
                    {
                        const uint32_t pk = (p ? hbuf + 16384 : sb + OFF_KVB + wgi * 8192) + w * 2048;
#pragma unroll
                        for (int k = 0; k < 4; k++) sts4(pk + k * 512 + lane * 16, H[32 + 4 * k], H[33 + 4 * k], H[34 + 4 * k], H[35 + 4 * k]);
                        fence_async();
                        __syncwarp();
                        asm volatile(ELECT "cp.async.bulk.shared::cluster.shared::cta.mbarrier::complete_tx::bytes [%0], [%1], 2048, [%2]; }"
                                     ::"r"(mapa(hbuf + p * 8192 + w * 2048, hr ^ 1)), "r"(pk), "r"(mapa(BAR(B_RECV + wgi), hr ^ 1)) : "memory");
                    }
                    F1_BLOCK(1, false) F1_BLOCK(2, false) F1_BLOCK(3, false)
                    wg_wait<0>();
                    R_RELEASE(1);
                    kill<16>(H + 32);
                } while (((trips >> (++p)) & 1));
#pragma unroll
                for (int k = 0; k < 4; k++) lds4(H + 16 + 4 * k, hbuf + 16384 + w * 2048 + k * 512 + lane * 16);
                __syncwarp();
                if (lane == 0) asm volatile("mbarrier.arrive.shared::cluster.b64 _, [%0];" ::"r"(mapa(BAR(B_ACK2 + wgi), hr ^ 1)) : "memory");
                const uint32_t rem_h = mapa(hbuf + w * 2048 + lane * 16, hr ^ 1);
#define F1_LAST(b0)                                                                            \
    R_WAIT();                                                                                  \
    if (b0) { PP_WAIT() }                                                                      \
    { DECL_DB(b0, BASE64, HALF, 1)                                                             \
    wg_fence();                                                                                \
    FOR7(mma_rs64<1, D64(0, t)>(al, AQ(A, b0, t), (b0) + t > 0, SWB(b0, t, db, 1)));           \
    FOR7(mma_rs64<1, D64(7168, t)>(al, AQ(A, (b0) + 1, t), 1, db)); }                          \
    wg_commit();                                                                               \
    if (b0) { PP_GO() }                                                                        \
    R_NEXT();
                float al[32];
                F1_LAST(0)
                mbar_wait(BAR(B_RECV + wgi), rcvph);
                rcvph ^= 1;
                mbar_wait(BAR(B_ACK2 + wgi), step >> 1);
                H_PUSH(32, 16384) H_PUSH(36, 16896)
                F1_LAST(2)
                H_PUSH(40, 17408) H_PUSH(44, 17920)
                wg_wait<1>();
                R_RELEASE(2);
                wg_wait<0>();
                R_RELEASE(1);
                uint32_t HP[56];
#pragma unroll
                for (int k = 0; k < 4; k++) lds4(H + 4 * k, sb + OFF_KVB + wgi * 8192 + w * 2048 + k * 512 + lane * 16);
#pragma unroll
                for (int t = 0; t < 8; t++) lds4(HP + 4 * t, hbuf + (t >> 2) * 8192 + w * 2048 + (t & 3) * 512 + lane * 16);
                F1_EPI(H + 48, 4, al)
                H_PUSH(48, 24576 - w * 1024) H_PUSH(52, 25088 - w * 1024)
                STAMP(7 + so);
                WSUM(84 + 7 * (step >> 1));
                FRESH();
                float acc[28];
                const uint32_t roA = hr ? 256u : 0u, roB = hr ? (uint32_t)-1536 : 0u;
                const uint32_t rpA = hr ? 0u : 256u, rpB = hr ? 0u : (uint32_t)-1536;
                float res[28];
                uint32_t v0[14], v1[14], P[14];
                const uint4* ps = xp0 + sl * 512;
#define F2_OWN_A()                                                                             \
    R_WAIT();                                                                                  \
    d0 = BASE128(0, 16, R_ADJ + roA); d1 = BASE128(0, 16, R_ADJ + roB);                        \
    wg_fence();                                                                                \
    FOR14(if constexpr (t < OT) mma_rs56<1, t * 128>(acc, H[4 * t], H[4 * t + 1], H[4 * t + 2], H[4 * t + 3], t > 0, d0)); \
    wg_commit();
#define F2_OWN_B()                                                                             \
    wg_fence();                                                                                \
    FOR14(if constexpr (t >= OT) mma_rs56<1, t * 128>(acc, H[4 * t], H[4 * t + 1], H[4 * t + 2], H[4 * t + 3], 1, t < 12 ? d0 : d1)); \
    wg_commit();                                                                               \
    R_NEXT();
#define F2_PEER()                                                                              \
    R_WAIT();                                                                                  \
    if (F2PP) { PP_WAIT() }                                                                    \
    d0 = BASE128(0, 16, R_ADJ + rpA); d1 = BASE128(0, 16, R_ADJ + rpB);                        \
    wg_fence();                                                                                \
    FOR14(mma_rs56<1, t * 128>(acc, HP[4 * t], HP[4 * t + 1], HP[4 * t + 2], HP[4 * t + 3], 1, t < 12 ? d0 : d1)); \
    wg_commit();                                                                               \
    if (F2PP) { PP_GO() }                                                                      \
    R_NEXT();
#define F2_TURN(u)                                                                             \
    wg_wait<1>();                                                                              \
    if ((u) < 2 || TDEF < 2) R_RELEASE(2);                                                     \
    wg_wait<0>();                                                                              \
    if ((u) < 2 || TDEF < 1) R_RELEASE(1);                                                     \
    _Pragma("unroll") for (int i = 0; i < 14; i++) P[i] = pack2(acc[2 * i], acc[2 * i + 1]);   \
    tag_slice(P, tag);                                                                         \
    asm volatile("" : RW4(P, 0), RW4(P, 4), RW4(P, 8), RW2(P, 12));                            \
    kill<28>(acc);                                                                             \
    F2_OWN_A()                                                                                 \
    if ((u) == 2) { slice_load<PL(3)>(v0, ps, lane); slice_load<PL(4)>(v1, ps, lane); } \
    send_slice<PL(3 + (u))>(xp0 + (2 * ((pr + (u) + 1) & 3) + hr) * 512, lane, P);             \
    seq++;                                                                                     \
    if (lane == 0) st_word(cx(sl), seq);                                                       \
    __syncwarp();                                                                              \
    STAMP(8 + (u) + so);                                                                       \
    F2_OWN_B()
                uint64_t d0, d1;
                F2_OWN_A()
                F2_OWN_B()
                R_WAIT();
                d0 = BASE128(0, 16, R_ADJ + rpA); d1 = BASE128(0, 16, R_ADJ + rpB);
                wg_fence();
                FOR8(mma_rs56<1, t * 128>(acc, HP[4 * t], HP[4 * t + 1], HP[4 * t + 2], HP[4 * t + 3], 1, d0));
                wg_commit();
                mbar_wait(BAR(B_RECV2 + wgi), step >> 1);
#pragma unroll
                for (int k = 0; k < 4; k++) lds4(HP + 32 + 4 * k, hbuf + 16384 + w * 2048 + k * 512 + lane * 16);
                lds4(HP + 48, hbuf + 24576 + w * 1024 + lane * 16);
                lds4(HP + 52, hbuf + 25088 + w * 1024 + lane * 16);
                if (step == 1) PUSH_ACK();
                wg_fence();
                FOR14(if constexpr (t >= 8) mma_rs56<1, t * 128>(acc, HP[4 * t], HP[4 * t + 1], HP[4 * t + 2], HP[4 * t + 3], 1, t < 12 ? d0 : d1));
                wg_commit();
                R_NEXT();
                F2_TURN(0)
                F2_PEER()
                F2_TURN(1)
                F2_PEER()
                F2_TURN(2)
                if (step == 1) STAMP(64);
                slice_check<PL(3)>(v0, ps, lane, tag);
                slice_check<PL(4)>(v1, ps, lane, tag);
#pragma unroll
                for (int i = 0; i < 14; i++) { res[2 * i] = bf_lo(v0[i]) + bf_lo(v1[i]); res[2 * i + 1] = bf_hi(v0[i]) + bf_hi(v1[i]); }
                slice_load<PL(2)>(X, ps, lane);
                if (step == 1) STAMP(65);
                F2_PEER()
                if (step == 1) STAMP(66);
                poll_cnt(cx(2 * ((pr + 1) & 3) + hr), seq);
                if (step == 1) STAMP(67);
                slice_load<PL(5)>(v0, ps, lane);
                x_fix(X, xbits);
                slice_check<PL(5)>(v0, ps, lane, tag);
                if (lane < TDEF) mbar_arrive(BAR(B_EMPTY + (slot + NST - 3 - lane) % NST));
#pragma unroll
                for (int i = 0; i < 14; i++) { res[2 * i] += bf_lo(v0[i]); res[2 * i + 1] += bf_hi(v0[i]); }
                STAMP(11 + so);
                wg_wait<0>();
                R_RELEASE(2);
                STAMP(12 + so);
                WSUM(85 + 7 * (step >> 1));
#pragma unroll
                for (int i = 0; i < 14; i++) X[i] = pack2(fmaf(res[2 * i] + acc[2 * i], 0.5f, bf_lo(X[i])), fmaf(res[2 * i + 1] + acc[2 * i + 1], 0.5f, bf_hi(X[i])));
            }
        }
        {
            const int m = lane >> 3, rr = lane & 7;
            const uint32_t ob = hbuf + w * 2048, rowa = ob + (rr + 8 * (m & 1)) * 112 + (m >> 1) * 16;
#pragma unroll
            for (int j = 0; j < 3; j++) stsm4(rowa + 32 * j, X[4 * j], X[4 * j + 1], X[4 * j + 2], X[4 * j + 3]);
            asm volatile("stmatrix.sync.aligned.m8n8.x2.shared.b16 [%0], {%1,%2};" ::"r"(ob + (rr + 8 * (m & 1)) * 112 + 96), "r"(X[12]), "r"(X[13]) : "memory");
            fence_async();
            __syncwarp();
            if (lane == 0) {
                asm volatile("cp.async.bulk.tensor.2d.global.shared::cta.bulk_group [%0, {%2, %3}], [%1];" ::"l"(&maps.out), "r"(ob), "r"(56 * sl), "r"(tile * 128 + wu * 16) : "memory");
                asm volatile("cp.async.bulk.commit_group;" ::: "memory");
                asm volatile("cp.async.bulk.wait_group.read 0;" ::: "memory");
            }
        }
        STAMP(50);
        GSTAMP(61);
        PDUMP();
    }
}

#undef g
#undef pr
#undef c
#undef t128

typedef CUresult (*EncodeFn)(CUtensorMap*, CUtensorMapDataType, cuuint32_t, void*, const cuuint64_t*, const cuuint64_t*, const cuuint32_t*,
                             const cuuint32_t*, CUtensorMapInterleave, CUtensorMapSwizzle, CUtensorMapL2promotion, CUtensorMapFloatOOBfill);

static void make_map(EncodeFn enc, CUtensorMap* m, const void* p, uint64_t cols, uint64_t rows, uint32_t bc, uint32_t br, CUtensorMapSwizzle sw) {
    cuuint64_t gd[2] = {cols, rows};
    cuuint64_t gs[1] = {cols * 2};
    cuuint32_t bd[2] = {bc, br};
    cuuint32_t es[2] = {1, 1};
    enc(m, CU_TENSOR_MAP_DATA_TYPE_BFLOAT16, 2, const_cast<void*>(p), gd, gs, bd, es, CU_TENSOR_MAP_INTERLEAVE_NONE, sw,
        CU_TENSOR_MAP_L2_PROMOTION_L2_128B, CU_TENSOR_MAP_FLOAT_OOB_FILL_NONE);
}

extern "C" void kernel_launch(void* const* d_in, const int* in_sizes, int n_in, void* d_out, int out_size) {
    (void)in_sizes; (void)n_in; (void)out_size;
    static EncodeFn enc = nullptr;
    static Scratch* scratch = nullptr;
    if (!enc) {
        void* fn = nullptr;
        cudaDriverEntryPointQueryResult qr;
        cudaGetDriverEntryPoint("cuTensorMapEncodeTiled", &fn, cudaEnableDefault, &qr);
        enc = (EncodeFn)fn;
        cudaGetSymbolAddress((void**)&scratch, g_scratch);
        cudaFuncSetAttribute(fused_kernel, cudaFuncAttributeMaxDynamicSharedMemorySize, SMEM_BYTES);
    }
    Maps maps;
    {
        cuuint64_t gd[3] = {64, 2048, 7};
        cuuint64_t gs[2] = {896, 128};
        cuuint32_t bd[3] = {64, 32, 7};
        cuuint32_t es[3] = {1, 1, 1};
        enc(&maps.x, CU_TENSOR_MAP_DATA_TYPE_BFLOAT16, 3, d_in[0], gd, gs, bd, es, CU_TENSOR_MAP_INTERLEAVE_NONE, CU_TENSOR_MAP_SWIZZLE_128B,
            CU_TENSOR_MAP_L2_PROMOTION_L2_128B, CU_TENSOR_MAP_FLOAT_OOB_FILL_NONE);
    }
    make_map(enc, &maps.out, d_out, 448, 2048, 56, 16, CU_TENSOR_MAP_SWIZZLE_NONE);
    make_map(enc, &maps.qkv, d_in[1], 1344, 448, 64, 112, CU_TENSOR_MAP_SWIZZLE_128B);
    make_map(enc, &maps.wo, d_in[3], 448, 448, 64, 112, CU_TENSOR_MAP_SWIZZLE_128B);
    make_map(enc, &maps.wg, d_in[5], 1792, 448, 64, 112, CU_TENSOR_MAP_SWIZZLE_128B);
    make_map(enc, &maps.wu, d_in[6], 1792, 448, 64, 112, CU_TENSOR_MAP_SWIZZLE_128B);
    make_map(enc, &maps.wg32, d_in[5], 1792, 448, 32, 112, CU_TENSOR_MAP_SWIZZLE_64B);
    make_map(enc, &maps.wu32, d_in[6], 1792, 448, 32, 112, CU_TENSOR_MAP_SWIZZLE_64B);
    make_map(enc, &maps.wd, d_in[7], 448, 1792, 64, 112, CU_TENSOR_MAP_SWIZZLE_128B);
    fused_kernel<<<128, 384, SMEM_BYTES>>>(scratch, (const __nv_bfloat16*)d_in[0], (const __nv_bfloat16*)d_in[2], 7, (const __nv_bfloat16*)d_in[5],
                                           (const __nv_bfloat16*)d_in[6], (const __nv_bfloat16*)d_in[7], maps);
}
```

```cpp
#include <cuda_runtime.h>
#include <cuda.h>
#include <cuda_bf16.h>
#include <stdint.h>
#include <type_traits>

#define PPF 2
#define PKP 0
#define TDEF 1
#define TMPF 0
#define NORM1 0
#define LPARK 1
#define PFN 9
#define ACAN 0
#define SPLIT0 1
#define OT 2
#define F2PP 0
#define PPK 2
#define QE 1
#define OST 1
#define PP

namespace {

constexpr uint32_t STAGE = 28672, HALF = 14336;
constexpr int NST = 5;
constexpr uint32_t OFF_H = NST * STAGE;
constexpr uint32_t OFF_KVB = OFF_H + 2 * STAGE;
constexpr uint32_t OFF_WPHI = OFF_KVB + 16384;
constexpr uint32_t OFF_XR = OFF_WPHI + 7168;
constexpr uint32_t OFF_BAR = OFF_XR + 6144;
constexpr uint32_t SMEM_BYTES = OFF_BAR + 384 + 1408;
constexpr int B_EMPTY = NST, B_RECV = 2 * NST, B_RECV2 = B_RECV + 2, B_PACK = B_RECV2 + 2, B_GAT = B_PACK + 1, B_LATE = B_GAT + 16, B_ACK = B_LATE + 1, B_ACK2 = B_ACK + 2, B_COUNT = B_ACK2 + 2;

constexpr int PACK = 14 + 4 * PKP;

struct Maps { CUtensorMap x, qkv, wo, wg, wu, wg32, wu32, wd, out; };

}

constexpr int PLANE = 16 * 2 * 8 * 512;
struct Scratch {
    uint4 ex[6 * PLANE];
    uint4 kv1[8 * 16 * 16 * 32];
    uint4 kv2[8 * 512];
    uint32_t c1[8 * 8 * 16 * 32];
    uint32_t cw[8 * 32];
    uint4 wp[8 * 32 * (HALF / 16)];
};
__device__ __align__(1024) Scratch g_scratch;
#define g_ex (sc->ex)
#define g_kv1 (sc->kv1)
#define g_kv2 (sc->kv2)
#define g_c1 (sc->c1)
#define g_cw (sc->cw)
#define g_wp (sc->wp)
#define STAMP(i)
#define GSTAMP(i)
#define PDUMP()
#define ASTAMP(i)

namespace {

__device__ __forceinline__ int fresh_tid() { int t; asm volatile("mov.u32 %0, %%tid.x;" : "=r"(t)); return t; }
template <int N> __device__ __forceinline__ void kill(uint32_t* v) {
#pragma unroll
    for (int i = 0; i < N; i++) v[i] = 0;
}
template <int N> __device__ __forceinline__ void kill(float* v) {
#pragma unroll
    for (int i = 0; i < N; i++) v[i] = 0.f;
}
__device__ __forceinline__ uint32_t s2u(const void* p) { return (uint32_t)__cvta_generic_to_shared(p); }
__device__ __forceinline__ void mbar_init(uint32_t a, uint32_t c) { asm volatile("mbarrier.init.shared::cta.b64 [%0], %1;" ::"r"(a), "r"(c) : "memory"); }
__device__ __forceinline__ void mbar_expect_tx(uint32_t a, uint32_t b) { asm volatile("mbarrier.arrive.expect_tx.shared::cta.b64 _, [%0], %1;" ::"r"(a), "r"(b) : "memory"); }
__device__ __forceinline__ void mbar_arrive(uint32_t a) { asm volatile("mbarrier.arrive.shared::cta.b64 _, [%0];" ::"r"(a) : "memory"); }
#define GIVE_UP(id) "trap;\n"
#define SPIN_MAX "0x400000"
#define SPIN_TAIL(id) "add.u32 n, n, 1;\n setp.lt.u32 p, n, " SPIN_MAX ";\n @p bra.uni LP;\n" GIVE_UP(id) " DN:\n }"
__device__ __forceinline__ void mbar_wait(uint32_t a, uint32_t ph) {
    asm volatile("{ .reg .pred p; .reg .b32 n; mov.u32 n, 0;\n LP:\n"
                 "mbarrier.try_wait.parity.shared::cta.b64 p, [%0], %1;\n @p bra DN;\n"
                 "add.u32 n, n, 1;\n setp.lt.u32 p, n, " SPIN_MAX ";\n @p bra LP;\n"
                 GIVE_UP("")
                 " DN:\n }" ::"r"(a), "r"(ph) : "memory");
}
#define ELECT "{ .reg .pred e; elect.sync _|e, 0xffffffff; @e "
__device__ __forceinline__ void tma2d(uint32_t dst, const CUtensorMap* m, int c0, int c1, uint32_t bar) {
    asm volatile(ELECT "cp.async.bulk.tensor.2d.shared::cluster.global.mbarrier::complete_tx::bytes [%0], [%1, {%3, %4}], [%2]; }" ::"r"(dst), "l"(m), "r"(bar), "r"(c0), "r"(c1) : "memory");
}
__device__ __forceinline__ void tma3x(uint32_t dst, const CUtensorMap* m, int row, uint32_t bar) {
    asm volatile(ELECT "cp.async.bulk.tensor.3d.shared::cluster.global.mbarrier::complete_tx::bytes [%0], [%1, {0, %3, 0}], [%2]; }" ::"r"(dst), "l"(m), "r"(bar), "r"(row) : "memory");
}
template <int OFF>
__device__ __forceinline__ void ld_pkt(uint32_t* v, const uint4* p) {
    asm volatile("{ .reg .b128 t; ld.relaxed.gpu.global.b128 t, [%4+%5]; mov.b128 {%0,%1,%2,%3}, t; }" : "=r"(v[0]), "=r"(v[1]), "=r"(v[2]), "=r"(v[3]) : "l"(p), "n"(OFF * 16) : "memory");
}
template <int OFF>
__device__ __forceinline__ void st_pkt(uint4* p, uint32_t a, uint32_t b, uint32_t c, uint32_t d) {
    asm volatile("{ .reg .b128 t; mov.b128 t, {%1,%2,%3,%4}; st.relaxed.gpu.global.b128 [%0+%5], t; }" ::"l"(p), "r"(a), "r"(b), "r"(c), "r"(d), "n"(OFF * 16) : "memory");
}
__device__ __forceinline__ uint32_t pack2(float lo, float hi) {
    uint32_t r;
    asm("cvt.rn.bf16x2.f32 %0, %1, %2;" : "=r"(r) : "f"(hi), "f"(lo));
    return r;
}
__device__ __forceinline__ float bf_lo(uint32_t w) { return __uint_as_float(w << 16); }
__device__ __forceinline__ float bf_hi(uint32_t w) { return __uint_as_float(w & 0xffff0000u); }
__device__ __forceinline__ uint32_t settag(uint32_t w, uint32_t tag) { return (w & ~1u) | tag; }
__device__ __forceinline__ float ex2(float x) { float y; asm("ex2.approx.ftz.f32 %0, %1;" : "=f"(y) : "f"(x)); return y; }
__device__ __forceinline__ float rcp(float x) { float y; asm("rcp.approx.ftz.f32 %0, %1;" : "=f"(y) : "f"(x)); return y; }
__device__ __forceinline__ float tanh_hw(float x) { float y; asm("tanh.approx.f32 %0, %1;" : "=f"(y) : "f"(x)); return y; }
__device__ __forceinline__ void stsm4(uint32_t addr, uint32_t a, uint32_t b, uint32_t c, uint32_t d) {
    asm volatile("stmatrix.sync.aligned.m8n8.x4.shared.b16 [%0], {%1,%2,%3,%4};" ::"r"(addr), "r"(a), "r"(b), "r"(c), "r"(d) : "memory");
}
__device__ __forceinline__ void fence_async() { asm volatile("fence.proxy.async.shared::cta;" ::: "memory"); }
__device__ __forceinline__ void bar_sync(int id, int n) { asm volatile("bar.sync %0, %1;" ::"r"(id), "r"(n) : "memory"); }
__device__ __forceinline__ void bar_arrive(int id, int n) { asm volatile("bar.arrive %0, %1;" ::"r"(id), "r"(n) : "memory"); }
__device__ __forceinline__ void wg_fence() { asm volatile("wgmma.fence.sync.aligned;" ::: "memory"); }
__device__ __forceinline__ void wg_commit() { asm volatile("wgmma.commit_group.sync.aligned;" ::: "memory"); }
template <int N> __device__ __forceinline__ void wg_wait() { asm volatile("wgmma.wait_group.sync.aligned %0;" ::"n"(N) : "memory"); }

constexpr uint32_t SB0 = 1024;
__host__ __device__ constexpr uint32_t dlo(uint32_t off, uint32_t lbo) { return ((SB0 + off) >> 4) | ((lbo >> 4) << 16); }
__host__ __device__ constexpr uint32_t dhi(uint32_t sbo, uint32_t sw) { return (sbo >> 4) | (sw << 30); }
__device__ __forceinline__ uint64_t dbase(uint32_t lo, uint32_t hi) { uint64_t d; asm volatile("mov.b64 %0, {%1, %2};" : "=l"(d) : "r"(lo), "r"(hi)); return d; }
#define BASE128(off, lbo, adj) dbase(dlo(off, lbo) + (adj), dhi(1024, 1))
#define BASE64(off, lbo, adj) dbase(dlo(off, lbo) + (adj), dhi(512, 2))

#define ACC4(d, o) "+f"(d[o]), "+f"(d[o + 1]), "+f"(d[o + 2]), "+f"(d[o + 3])
#define ACC28(d) ACC4(d, 0), ACC4(d, 4), ACC4(d, 8), ACC4(d, 12), ACC4(d, 16), ACC4(d, 20), ACC4(d, 24)
#define ACC32(d, o) ACC4(d, o), ACC4(d, o + 4), ACC4(d, o + 8), ACC4(d, o + 12), ACC4(d, o + 16), ACC4(d, o + 20), ACC4(d, o + 24), ACC4(d, o + 28)

template <int TB, uint64_t D>
__device__ __forceinline__ void mma_rs56(float* d, uint32_t a0, uint32_t a1, uint32_t a2, uint32_t a3, int sd, uint64_t base) {
    asm volatile("{ .reg .pred p; .reg .b64 db; setp.ne.b32 p, %32, 0; add.u64 db, %33, %34;\n"
                 "wgmma.mma_async.sync.aligned.m64n56k16.f32.bf16.bf16 "
                 "{%0,%1,%2,%3,%4,%5,%6,%7,%8,%9,%10,%11,%12,%13,%14,%15,%16,%17,%18,%19,%20,%21,%22,%23,%24,%25,%26,%27}, "
                 "{%28,%29,%30,%31}, db, p, 1, 1, %35; }\n"
                 : ACC28(d)
                 : "r"(a0), "r"(a1), "r"(a2), "r"(a3), "r"(sd), "l"(base), "n"(D), "n"(TB));
}
template <int TB, uint64_t D>
__device__ __forceinline__ void mma_rs64(float* d, uint32_t a0, uint32_t a1, uint32_t a2, uint32_t a3, int sd, uint64_t base) {
    asm volatile("{ .reg .pred p; .reg .b64 db; setp.ne.b32 p, %36, 0; add.u64 db, %37, %38;\n"
                 "wgmma.mma_async.sync.aligned.m64n64k16.f32.bf16.bf16 "
                 "{%0,%1,%2,%3,%4,%5,%6,%7,%8,%9,%10,%11,%12,%13,%14,%15,%16,%17,%18,%19,%20,%21,%22,%23,%24,%25,%26,%27,%28,%29,%30,%31}, "
                 "{%32,%33,%34,%35}, db, p, 1, 1, %39; }\n"
                 : ACC32(d, 0)
                 : "r"(a0), "r"(a1), "r"(a2), "r"(a3), "r"(sd), "l"(base), "n"(D), "n"(TB));
}
template <int TB, uint64_t D>
__device__ __forceinline__ void mma_rs128(float* d, uint32_t a0, uint32_t a1, uint32_t a2, uint32_t a3, int sd, uint64_t base) {
    asm volatile("{ .reg .pred p; .reg .b64 db; setp.ne.b32 p, %68, 0; add.u64 db, %69, %70;\n"
                 "wgmma.mma_async.sync.aligned.m64n128k16.f32.bf16.bf16 "
                 "{%0,%1,%2,%3,%4,%5,%6,%7,%8,%9,%10,%11,%12,%13,%14,%15,%16,%17,%18,%19,%20,%21,%22,%23,%24,%25,%26,%27,%28,%29,%30,%31,%32,%33,%34,%35,%36,%37,%38,%39,%40,%41,%42,%43,%44,%45,%46,%47,%48,%49,%50,%51,%52,%53,%54,%55,%56,%57,%58,%59,%60,%61,%62,%63}, "
                 "{%64,%65,%66,%67}, db, p, 1, 1, %71; }\n"
                 : ACC32(d, 0), ACC32(d, 32)
                 : "r"(a0), "r"(a1), "r"(a2), "r"(a3), "r"(sd), "l"(base), "n"(D), "n"(TB));
}
template <uint64_t DA, uint64_t DB>
__device__ __forceinline__ void mma_ss56_tt(float* d, int sd, uint64_t ba, uint64_t bb) {
    asm volatile("{ .reg .pred p; .reg .b64 da, db; setp.ne.b32 p, %28, 0; add.u64 da, %29, %31; add.u64 db, %30, %32;\n"
                 "wgmma.mma_async.sync.aligned.m64n56k16.f32.bf16.bf16 "
                 "{%0,%1,%2,%3,%4,%5,%6,%7,%8,%9,%10,%11,%12,%13,%14,%15,%16,%17,%18,%19,%20,%21,%22,%23,%24,%25,%26,%27}, "
                 "da, db, p, 1, 1, 1, 1; }\n"
                 : ACC28(d)
                 : "r"(sd), "l"(ba), "l"(bb), "n"(DA), "n"(DB));
}
template <int... I> struct Seq {};
template <class F, int... I> __device__ __forceinline__ void static_for_impl(F&& f, Seq<I...>) { (f(std::integral_constant<int, I>{}), ...); }
#define FOR7(...) static_for_impl([&](auto T_) { constexpr int t = decltype(T_)::value; __VA_ARGS__; }, Seq<0, 1, 2, 3, 4, 5, 6>{})
#define FOR8(...) static_for_impl([&](auto T_) { constexpr int t = decltype(T_)::value; __VA_ARGS__; }, Seq<0, 1, 2, 3, 4, 5, 6, 7>{})
#define FOR14(...) static_for_impl([&](auto T_) { constexpr int t = decltype(T_)::value; __VA_ARGS__; }, Seq<0, 1, 2, 3, 4, 5, 6, 7, 8, 9, 10, 11, 12, 13>{})

__device__ __forceinline__ int kblk(int p, int b) { return b == 0 ? p : b - (b <= p); }
__host__ __device__ constexpr int krow(int t) { return t < 3 ? 16 * t : (t < 6 ? 56 + 16 * (t - 3) : 48); }
#define AQ(A, b, t) ((t) < 3 ? A[2 * (b)][4 * (t)] : (t) < 6 ? A[2 * (b) + 1][4 * ((t) - 3)] : A[2 * (b)][12]), \
                    ((t) < 3 ? A[2 * (b)][4 * (t) + 1] : (t) < 6 ? A[2 * (b) + 1][4 * ((t) - 3) + 1] : A[2 * (b)][13]), \
                    ((t) < 3 ? A[2 * (b)][4 * (t) + 2] : (t) < 6 ? A[2 * (b) + 1][4 * ((t) - 3) + 2] : A[2 * (b) + 1][12]), \
                    ((t) < 3 ? A[2 * (b)][4 * (t) + 3] : (t) < 6 ? A[2 * (b) + 1][4 * ((t) - 3) + 3] : A[2 * (b) + 1][13])
#define D128(off, t) ((uint64_t)(((off) + krow(t) * 128) >> 4) + ((uint64_t)((t) == 6 ? (7168 - 1024) >> 4 : 0) << 32))
#define D64(off, t) ((uint64_t)(((off) + krow(t) * 64) >> 4) + ((uint64_t)((t) == 6 ? (3584 - 512) >> 4 : 0) << 32))

#define PL(k) (((k) - 3) * PLANE)
__device__ __forceinline__ void st_word(uint32_t* p, uint32_t v) { asm volatile("st.relaxed.gpu.global.u32 [%0], %1;" ::"l"(p), "r"(v) : "memory"); }
__device__ __forceinline__ uint32_t ld_word(const uint32_t* p) { uint32_t v; asm volatile("ld.relaxed.gpu.global.u32 %0, [%1];" : "=r"(v) : "l"(p) : "memory"); return v; }
__device__ __forceinline__ void tag_slice(uint32_t* w, uint32_t tag) { w[0] = settag(w[0], tag); w[4] = settag(w[4], tag); w[8] = settag(w[8], tag); w[12] = settag(w[12], tag); }
template <int O>
__device__ __forceinline__ void send_slice(uint4* dst, int lane, const uint32_t* w) {
    st_pkt<O>(dst, w[0], w[1], w[2], w[3]);
    st_pkt<O + 32>(dst, w[4], w[5], w[6], w[7]);
    st_pkt<O + 64>(dst, w[8], w[9], w[10], w[11]);
    asm volatile("{ .reg .b64 t; mov.b64 t, {%1,%2}; st.relaxed.gpu.global.b64 [%0+%3], t; }" ::"l"((char*)dst - lane * 8), "r"(w[12]), "r"(w[13]), "n"(16 * (O + 96)) : "memory");
}
#define RW4(v, o) "+r"(v[o]), "+r"(v[(o) + 1]), "+r"(v[(o) + 2]), "+r"(v[(o) + 3])
#define RW2(v, o) "+r"(v[o]), "+r"(v[(o) + 1])
#define WR4(v, o) "=&r"(v[o]), "=&r"(v[(o) + 1]), "=&r"(v[(o) + 2]), "=&r"(v[(o) + 3])
#define LDP(a, b, c, d, addr, off) "ld.relaxed.gpu.global.b128 q, [" addr "+" off "];\n mov.b128 {" a "," b "," c "," d "}, q;\n"
#define LDH(a, b, addr, off) "ld.relaxed.gpu.global.b64 h, [" addr "+" off "];\n mov.b64 {" a "," b "}, h;\n"
#define VOTE_OK "and.b32 t, t, 1;\n setp.ne.u32 p, t, 0;\n vote.sync.any.pred p, p, 0xffffffff;\n @!p bra.uni DN;\n"
#define CHK(x, tag) "lop3.b32 t, " x ", " tag ", t, 0xBE;\n"
__device__ __forceinline__ void check_cnt(uint32_t v, const uint32_t* p, uint32_t target) {
    asm volatile("{ .reg .pred p; .reg .b32 n, t; mov.u32 n, 0; mov.u32 t, %2;\n LP:\n"
                 "sub.s32 t, t, %1;\n setp.lt.s32 p, t, 0;\n vote.sync.any.pred p, p, 0xffffffff;\n @!p bra.uni DN;\n ld.relaxed.gpu.global.u32 t, [%0];\n" SPIN_TAIL("7")
                 ::"l"(p), "r"(target), "r"(v) : "memory");
}
__device__ __forceinline__ void poll_cnt(const uint32_t* p, uint32_t target) {
    asm volatile("{ .reg .pred p; .reg .b32 n, t; mov.u32 n, 0;\n LP:\n"
                 "ld.relaxed.gpu.global.u32 t, [%0];\n sub.s32 t, t, %1;\n setp.lt.s32 p, t, 0;\n vote.sync.any.pred p, p, 0xffffffff;\n @!p bra.uni DN;\n" SPIN_TAIL("1")
                 ::"l"(p), "r"(target) : "memory");
}
template <int STR>
__device__ __forceinline__ void poll4_kv(uint32_t* v, const uint4* p, uint32_t tag) {
    asm volatile("{ .reg .pred p; .reg .b32 n, t; .reg .b128 q; mov.u32 n, 0;\n LP:\n"
                 LDP("%0", "%1", "%2", "%3", "%16", "0") LDP("%4", "%5", "%6", "%7", "%16", "%18")
                 LDP("%8", "%9", "%10", "%11", "%16", "%19") LDP("%12", "%13", "%14", "%15", "%16", "%20")
                 "xor.b32 t, %0, %17;\n" CHK("%4", "%17") CHK("%8", "%17") CHK("%12", "%17") VOTE_OK SPIN_TAIL("2")
                 : WR4(v, 0), WR4(v, 4), WR4(v, 8), WR4(v, 12)
                 : "l"(p), "r"(tag), "n"(16 * STR), "n"(32 * STR), "n"(48 * STR)
                 : "memory");
}
template <int B>
__device__ __forceinline__ void blk_load(uint32_t (&A)[8][14], const uint4* src, int lane) {
    ld_pkt<0>(&A[2 * B][0], src); ld_pkt<32>(&A[2 * B][4], src); ld_pkt<64>(&A[2 * B][8], src);
    ld_pkt<512>(&A[2 * B + 1][0], src); ld_pkt<544>(&A[2 * B + 1][4], src); ld_pkt<576>(&A[2 * B + 1][8], src);
    asm volatile("{ .reg .b64 h;\n" LDH("%0", "%1", "%4", "1536") LDH("%2", "%3", "%4", "9728") "}"
                 : "=&r"(A[2 * B][12]), "=&r"(A[2 * B][13]), "=&r"(A[2 * B + 1][12]), "=&r"(A[2 * B + 1][13])
                 : "l"((const char*)src - lane * 8) : "memory");
}
template <int B>
__device__ __forceinline__ void blk_check(uint32_t (&A)[8][14], const uint4* src, int lane, uint32_t tag) {
    asm volatile("{ .reg .pred p; .reg .b32 n, t; .reg .b128 q; .reg .b64 h, a8; mov.u32 n, 0;\n LP:\n"
                 "xor.b32 t, %0, %30;\n" CHK("%4", "%30") CHK("%8", "%30") CHK("%12", "%30") CHK("%16", "%30") CHK("%20", "%30") CHK("%24", "%30") CHK("%26", "%30") VOTE_OK
                 LDP("%0", "%1", "%2", "%3", "%28", "0") LDP("%4", "%5", "%6", "%7", "%28", "512") LDP("%8", "%9", "%10", "%11", "%28", "1024")
                 LDP("%12", "%13", "%14", "%15", "%28", "8192") LDP("%16", "%17", "%18", "%19", "%28", "8704") LDP("%20", "%21", "%22", "%23", "%28", "9216")
                 "mad.wide.s32 a8, %29, -8, %28;\n" LDH("%24", "%25", "a8", "1536") LDH("%26", "%27", "a8", "9728") SPIN_TAIL("3")
                 "\n and.b32 %0, %0, -2; and.b32 %4, %4, -2; and.b32 %8, %8, -2; and.b32 %12, %12, -2; and.b32 %16, %16, -2; and.b32 %20, %20, -2; and.b32 %24, %24, -2; and.b32 %26, %26, -2;"
                 : RW4(A[2 * B], 0), RW4(A[2 * B], 4), RW4(A[2 * B], 8), RW4(A[2 * B + 1], 0), RW4(A[2 * B + 1], 4), RW4(A[2 * B + 1], 8),
                   RW2(A[2 * B], 12), RW2(A[2 * B + 1], 12)
                 : "l"(src), "r"(lane), "r"(tag)
                 : "memory");
}
__device__ __forceinline__ void st_async4(uint32_t a, uint32_t x, uint32_t y, uint32_t z, uint32_t w, uint32_t bar) {
    asm volatile("st.async.weak.shared::cluster.mbarrier::complete_tx::bytes.v4.b32 [%0], {%1,%2,%3,%4}, [%5];" ::"r"(a), "r"(x), "r"(y), "r"(z), "r"(w), "r"(bar) : "memory");
}
__device__ __forceinline__ uint32_t mapa(uint32_t a, uint32_t cta) { uint32_t r; asm("mapa.shared::cluster.u32 %0, %1, %2;" : "=r"(r) : "r"(a), "r"(cta)); return r; }
__device__ __forceinline__ void stat_load(uint32_t* v, const uint4* p) { ld_pkt<0>(v, p); ld_pkt<512>(v + 4, p); }
__device__ __forceinline__ void stat_check(uint32_t* v, const uint4* p, uint32_t tag) {
    asm volatile("{ .reg .pred p; .reg .b32 n, t; .reg .b128 q; mov.u32 n, 0;\n LP:\n"
                 "xor.b32 t, %3, %9;\n" CHK("%7", "%9") VOTE_OK
                 LDP("%0", "%1", "%2", "%3", "%8", "0") LDP("%4", "%5", "%6", "%7", "%8", "8192") SPIN_TAIL("4")
                 : RW4(v, 0), RW4(v, 4) : "l"(p), "r"(tag) : "memory");
}
__device__ __forceinline__ uint32_t x_bits(const uint32_t* X) {
    uint32_t r;
    asm volatile("{ .reg .b32 a, b; prmt.b32 a, %1, %2, 0x0040; prmt.b32 b, %3, %4, 0x0040; prmt.b32 %0, a, b, 0x5410; }" : "=r"(r) : "r"(X[0]), "r"(X[4]), "r"(X[8]), "r"(X[12]));
    return r;
}
template <int O>
__device__ __forceinline__ void slice_load(uint32_t* v, const uint4* p, int lane) {
    ld_pkt<O>(v, p); ld_pkt<O + 32>(v + 4, p); ld_pkt<O + 64>(v + 8, p);
    asm volatile("{ .reg .b64 h;\n" LDH("%0", "%1", "%2", "%3") "}" : "=r"(v[12]), "=r"(v[13]) : "l"((const char*)p - lane * 8), "n"(16 * (O + 96)) : "memory");
}
template <int O>
__device__ __forceinline__ void slice_check(uint32_t* v, const uint4* p, int lane, uint32_t tag) {
    asm volatile("{ .reg .pred p; .reg .b32 n, t; .reg .b128 q; .reg .b64 h; mov.u32 n, 0;\n LP:\n"
                 "xor.b32 t, %0, %16;\n" CHK("%4", "%16") CHK("%8", "%16") CHK("%12", "%16") VOTE_OK
                 LDP("%0", "%1", "%2", "%3", "%14", "%17") LDP("%4", "%5", "%6", "%7", "%14", "%18") LDP("%8", "%9", "%10", "%11", "%14", "%19")
                 LDH("%12", "%13", "%15", "%20") SPIN_TAIL("5")
                 : RW4(v, 0), RW4(v, 4), RW4(v, 8), RW2(v, 12)
                 : "l"(p), "l"((const char*)p - lane * 8), "r"(tag), "n"(16 * O), "n"(16 * (O + 32)), "n"(16 * (O + 64)), "n"(16 * (O + 96))
                 : "memory");
}
__device__ __forceinline__ void x_fix(uint32_t* X, uint32_t bits) {
    X[0] = __byte_perm(X[0], bits, 0x3214); X[4] = __byte_perm(X[4], bits, 0x3215); X[8] = __byte_perm(X[8], bits, 0x3216); X[12] = __byte_perm(X[12], bits, 0x3217);
}
__device__ __forceinline__ void sts4(uint32_t a, uint32_t x, uint32_t y, uint32_t z, uint32_t w) {
    asm volatile("st.shared.v4.u32 [%0], {%1,%2,%3,%4};" ::"r"(a), "r"(x), "r"(y), "r"(z), "r"(w) : "memory");
}
__device__ __forceinline__ void lds4(uint32_t* v, uint32_t a) {
    asm volatile("ld.shared.v4.u32 {%0,%1,%2,%3}, [%4];" : "=r"(v[0]), "=r"(v[1]), "=r"(v[2]), "=r"(v[3]) : "r"(a) : "memory");
}
struct LnCoef { uint32_t hi, lo, sh; };
__device__ __forceinline__ LnCoef ln_coef(float sum, float sq) {
    sum += __shfl_xor_sync(0xffffffffu, sum, 1); sq += __shfl_xor_sync(0xffffffffu, sq, 1);
    sum += __shfl_xor_sync(0xffffffffu, sum, 2); sq += __shfl_xor_sync(0xffffffffu, sq, 2);
    const float mean = sum * (1.f / 448.f);
    const float var = fmaxf(fmaf(-mean, mean, sq * (1.f / 448.f)), 0.f);
    const float sc = rsqrtf(var + 1e-5f);
    LnCoef r;
    r.hi = pack2(sc, sc);
    const float lo = sc - bf_lo(r.hi), sh = -mean * sc;
    r.lo = pack2(lo, lo);
    r.sh = pack2(sh, sh);
    return r;
}
template <int B>
__device__ __forceinline__ void normalize(uint32_t (&A)[8][14], const LnCoef& c0, const LnCoef& c1) {
#pragma unroll
    for (int s = 2 * B; s < 2 * B + 2; s++)
#pragma unroll
        for (int i = 0; i < 14; i++) {
            const LnCoef& k = (i & 1) ? c1 : c0;
            asm("{ .reg .b32 t; fma.rn.bf16x2 t, %0, %2, %3; fma.rn.bf16x2 %0, %0, %1, t; }" : "+r"(A[s][i]) : "r"(k.hi), "r"(k.lo), "r"(k.sh));
        }
}
__device__ __forceinline__ void slice_stats(const uint32_t* w, float* st) {
    float a = 0.f, b = 0.f, p = 0.f, q = 0.f;
#pragma unroll
    for (int i = 0; i < 7; i++) {
        const float e0 = bf_lo(w[2 * i]), e1 = bf_hi(w[2 * i]), e2 = bf_lo(w[2 * i + 1]), e3 = bf_hi(w[2 * i + 1]);
        a += e0 + e1; b += e2 + e3;
        p = fmaf(e0, e0, p); p = fmaf(e1, e1, p); q = fmaf(e2, e2, q); q = fmaf(e3, e3, q);
    }
    a += __shfl_xor_sync(0xffffffffu, a, 1); p += __shfl_xor_sync(0xffffffffu, p, 1); b += __shfl_xor_sync(0xffffffffu, b, 1); q += __shfl_xor_sync(0xffffffffu, q, 1);
    a += __shfl_xor_sync(0xffffffffu, a, 2); p += __shfl_xor_sync(0xffffffffu, p, 2); b += __shfl_xor_sync(0xffffffffu, b, 2); q += __shfl_xor_sync(0xffffffffu, q, 2);
    st[0] = a; st[1] = p; st[2] = b; st[3] = q;
}
__device__ __forceinline__ void dual_softmax(const float* p, uint32_t* out) {
    constexpr float L = 1.4426950408889634f;
#pragma unroll
    for (int r = 0; r < 2; r++) {
        float mx = fmaxf(p[2 * r], p[2 * r + 1]), mn = fminf(p[2 * r], p[2 * r + 1]);
#pragma unroll
        for (int i = 1; i < 7; i++) {
            mx = fmaxf(mx, fmaxf(p[4 * i + 2 * r], p[4 * i + 2 * r + 1]));
            mn = fminf(mn, fminf(p[4 * i + 2 * r], p[4 * i + 2 * r + 1]));
        }
        mx = fmaxf(mx, __shfl_xor_sync(0xffffffffu, mx, 1));
        mn = fminf(mn, __shfl_xor_sync(0xffffffffu, mn, 1));
        const float bx = -mx * L, bn = mn * L;
        float ep[14], en[14], sp = 0.f, sn = 0.f;
#pragma unroll
        for (int i = 0; i < 14; i++) {
            const float v = p[4 * (i >> 1) + 2 * r + (i & 1)];
            ep[i] = ex2(fmaf(v, L, bx));
            en[i] = ex2(fmaf(v, -L, bn));
            sp += ep[i]; sn += en[i];
        }
        sp += __shfl_xor_sync(0xffffffffu, sp, 1);
        sn += __shfl_xor_sync(0xffffffffu, sn, 1);
        const float ip = rcp(sp), in = rcp(sn);
#pragma unroll
        for (int i = 0; i < 7; i++) {
            out[4 * i + r] = pack2(ep[2 * i] * ip, ep[2 * i + 1] * ip);
            out[4 * i + 2 + r] = pack2(en[2 * i] * in, en[2 * i + 1] * in);
        }
    }
}
__device__ __forceinline__ float geglu(float g, float u) {
    const float t = tanh_hw(g * fmaf(g * g, 0.7978845608028654f * 0.044715f, 0.7978845608028654f));
    const float gu = g * u;
    return fmaf(t, gu, gu);
}
__device__ __forceinline__ void phi_gemm(const float* t, float* p) {
    uint32_t w[14];
#pragma unroll
    for (int i = 0; i < 14; i++) w[i] = pack2(t[2 * i], t[2 * i + 1]);
    const uint64_t db = BASE128(OFF_WPHI, 16, 0);
    wg_fence();
    mma_rs56<0, 0>(p, w[0], w[1], w[2], w[3], 0, db);
    mma_rs56<0, 2>(p, w[4], w[5], w[6], w[7], 1, db);
    mma_rs56<0, 4>(p, w[8], w[9], w[10], w[11], 1, db);
    mma_rs56<0, 6>(p, w[12], w[13], 0u, 0u, 1, db);
    wg_commit();
    wg_wait<0>();
}

}

#define BAR(i) (bars + 8 * (i))
#define R_WAIT() mbar_wait(BAR(slot), ph)
#define WSUM(i)
#define R_ADJ (slot * (STAGE >> 4))
#define R_NEXT() do { eb2 = eb1; eb1 = BAR(B_EMPTY + slot); if (++slot == NST) { slot = 0; ph ^= 1; } } while (0)
#define R_RELEASE(k) do { if (lane == 0) mbar_arrive((k) == 1 ? eb1 : eb2); } while (0)
#define PUSH_BEGIN() do { mbar_wait(BAR(B_ACK + wgi), ackph); ackph ^= 1; } while (0)
#define PUSH_ACK() do { __syncwarp(); if (lane == 0) asm volatile("mbarrier.arrive.shared::cluster.b64 _, [%0];" ::"r"(mapa(BAR(B_ACK + wgi), hr ^ 1)) : "memory"); } while (0)

__global__ void __cluster_dims__(2, 1, 1) __launch_bounds__(384, 1)
fused_kernel(Scratch* const sc, const __nv_bfloat16* __restrict__ x_in, const __nv_bfloat16* __restrict__ w_phi, const int trips,
             const __nv_bfloat16* __restrict__ wg, const __nv_bfloat16* __restrict__ wu, const __nv_bfloat16* __restrict__ wd,
             const __grid_constant__ Maps maps) {
    extern __shared__ __align__(1024) unsigned char smem_raw[];
    const uint32_t sb = s2u(smem_raw);
    const uint32_t bars = sb + OFF_BAR;
    const int wgi = __shfl_sync(0xffffffffu, threadIdx.x >> 7, 0);
    const int hr = blockIdx.x & 1, ck = blockIdx.x >> 1;
    const int gp = (ck - 4) & 7, q7 = ((ck - 36) * 37) >> 8;
    const int pr = __shfl_sync(0xffffffffu, ck < 4 ? ck : (ck < 36 ? (ck - 4) >> 3 : q7), 0);
    const int tile = __shfl_sync(0xffffffffu, ck < 4 ? 0 : (ck < 36 ? (gp ? 2 * gp : 1) : 2 * (ck - 36 - 7 * q7) + 3), 0);
    const int sl = 2 * pr + hr;
    STAMP(0);
    GSTAMP(60);
    if (threadIdx.x == 256) {
#pragma unroll
        for (int i = 0; i < NST; i++) mbar_init(BAR(i), 1);
        asm volatile("fence.mbarrier_init.release.cluster;" ::: "memory");
    }
    if (threadIdx.x == 288) {
        if ((sb & 0x3FFFF) != SB0) asm volatile("trap;");
#pragma unroll
        for (int i = NST; i < B_COUNT; i++) mbar_init(BAR(i), i >= B_ACK ? 4 : (i < B_RECV || i == B_LATE ? 8 : 1));
        asm volatile("fence.mbarrier_init.release.cluster;" ::: "memory");
    }
    __syncwarp();
    asm volatile("barrier.cluster.arrive.relaxed.aligned;" ::: "memory");

    if (wgi == 2) {
        asm volatile("setmaxnreg.dec.sync.aligned.u32 40;");
        const int t128 = fresh_tid() & 127, w = __shfl_sync(0xffffffffu, t128 >> 5, 0), lane = t128 & 31;
        uint32_t e0[2] = {0, 0}, e1[2] = {0, 0}, cw_target = 0, kseq;
        if (w == 0) {
#pragma unroll 1
            for (int n = 0; n < NST; n++) {
                const uint32_t dst = sb + n * STAGE, fb = BAR(n);
                asm volatile(ELECT "mbarrier.arrive.expect_tx.shared::cta.b64 _, [%0], %1; }" ::"r"(fb), "r"(n < 2 ? 2 * STAGE : STAGE) : "memory");
                if (n < 2) {
                    tma3x(sb + OFF_H + n * STAGE, &maps.x, tile * 128 + n * 64, fb);
                    tma3x(dst, &maps.x, tile * 128 + n * 64 + 32, fb);
                } else {
                    if (n == 3) mbar_wait(BAR(1), 0);
                    const int ra = 112 * (n - 2);
                    tma2d(dst, &maps.qkv, 448 + 56 * sl, ra, fb);
                    tma2d(dst + HALF, &maps.qkv, 896 + 56 * sl, ra, fb);
                }
            }
            asm volatile("barrier.cluster.wait.aligned;" ::: "memory");
            kseq = ld_word(g_c1 + (sl * 8 * 16 + tile) * 32);
            cw_target = (ld_word(g_cw + sl * 32) & ~15u) + 16;
#pragma unroll 1
            for (int k = 0; k < 2; k++) {
                const int n = t128 + 32 * k;
                int m = n - 2 - (n > PACK);
                const bool packed = m >= 30 ? (m < 38 || m >= 52) : m >= 22;
                if (m >= 30) m -= 30;
                if (n == PACK) m = tile < 8 ? tile : tile + 14;
                const int rot = n < 8 ? 0 : pr;
                const int ra = 112 * kblk(rot, m & 3), rb = 112 * kblk(rot, 2 * m & 3), rc = 112 * kblk(rot, (2 * m + 1) & 3);
                int kind = 0, m0, m1, c0, c1, r0, r1;
                if (m < 4) { m0 = m1 = 1; c0 = 448 + 56 * sl; c1 = c0 + 448; r0 = r1 = ra; }
                else if (m < 8) { m0 = m1 = m < 6 ? 1 : 2; c0 = c1 = 56 * sl; r0 = rb; r1 = rc; }
                else if (m < 20) { m0 = 3; m1 = 4; c0 = c1 = 224 * sl + 32 * hr + 64 * ((m - 8) >> 2); r0 = r1 = ra; }
                else if (m < 22) { kind = 2; m0 = 5; m1 = 6; c0 = c1 = 224 * sl + (hr ? 0 : 192); r0 = rb; r1 = rc; }
                else { m0 = m1 = 7; c0 = c1 = 56 * (2 * ((pr + (m >> 1) - 10) & 3) + hr); r0 = 224 * (sl ^ (m & 1)); r1 = r0 + 112; }
                if (packed) { kind = 1; r0 = sl * 16 + (m < 8 ? m : m - 14); r1 = 0; }
                e0[0] = e0[1]; e1[0] = e1[1];
                e0[1] = kind | (m0 << 2) | (m1 << 6) | (c0 << 10) | (c1 << 21);
                e1[1] = r0 | (r1 << 16);
            }
        } else {
            const int j = t128 - 32;
            kseq = ld_word(g_c1 + (sl * 8 * 16 + tile) * 32);
            asm volatile("barrier.cluster.wait.aligned;" ::: "memory");
            uint2 wv[7];
            const int k = j < 56 ? j : 55, hh = k >= 28;
#pragma unroll
            for (int i = 0; i < 7; i++) wv[i] = __ldg(reinterpret_cast<const uint2*>(w_phi + (sl * 56 + k) * 28) + i);
#pragma unroll 1
            for (int i = j; i < 7168 / 16; i += 96) sts4(sb + OFF_WPHI + i * 16, 0, 0, 0, 0);
            bar_sync(5, 96);
            if (j < 56) {
                uint32_t a4[4];
#pragma unroll
                for (int q = 0; q < 4; q++) a4[q] = sb + OFF_WPHI + (4 * hh + q) * 128 + ((((k >> 3) ^ (4 * hh + q)) & 7) << 4) + (k & 7) * 2;
                FOR14(const uint32_t v = (t & 1) ? wv[t >> 1].y : wv[t >> 1].x;
                      asm volatile("{ .reg .b16 l, h; mov.b32 {l, h}, %2; st.shared.u16 [%0+%3], l; st.shared.u16 [%1+%3], h; }"
                                   ::"r"(a4[t >= 7 ? 2 : 0]), "r"(a4[t >= 7 ? 3 : 1]), "r"(v), "n"((t % 7) * 1024) : "memory"));
            }
            __syncwarp();
            fence_async();
            kseq = __shfl_sync(0xffffffffu, kseq, 0);
            bar_arrive(1, 224);
            bar_arrive(9, 224);
        }
        kseq = __shfl_sync(0xffffffffu, kseq, 0);
        int slot = 0, ph = 0, n = NST;
#pragma unroll 1
        for (int layer = 0; layer < 3; layer++) {
            if (w == 0) {
                const int nend = layer == 0 ? 11 : (layer == 1 ? 42 : 63);
#pragma unroll 1
                for (; n < nend; n++) {
                const uint32_t w0 = __shfl_sync(0xffffffffu, n < 32 ? e0[0] : e0[1], n & 31), w1 = __shfl_sync(0xffffffffu, n < 32 ? e1[0] : e1[1], n & 31);
                const uint32_t dst = sb + slot * STAGE, fb = BAR(n == PACK ? B_PACK : slot);
                const CUtensorMap* m0 = &maps.x + ((w0 >> 2) & 15);
                const CUtensorMap* m1 = &maps.x + ((w0 >> 6) & 15);
                const int c0 = (w0 >> 10) & 2047, c1 = w0 >> 21, r0 = w1 & 0xffff, r1 = w1 >> 16;
                if (n == 25) {
                    int it = 0;
                    uint32_t v;
                    do { asm volatile("ld.acquire.gpu.global.u32 %0, [%1];" : "=r"(v) : "l"(g_cw + sl * 32) : "memory"); } while ((int)(v - cw_target) < 0 && ++it < 0x400000);
                    asm volatile("fence.proxy.async.global;" ::: "memory");
                    __syncwarp();
                }
                mbar_wait(BAR(B_EMPTY + slot), ph);
                __syncwarp();
                asm volatile(ELECT "mbarrier.arrive.expect_tx.shared::cta.b64 _, [%0], %1; }" ::"r"(fb), "r"(STAGE) : "memory");
                if ((w0 & 3) == 0) {
                    tma2d(dst, m0, c0, r0, fb);
                    tma2d(dst + HALF, m1, c1, r1, fb);
                } else if (w0 & 1) {
                    asm volatile(ELECT "cp.async.bulk.shared::cluster.global.mbarrier::complete_tx::bytes [%0], [%1], %2, [%3]; }"
                                 ::"r"(dst), "l"(reinterpret_cast<const char*>(g_wp) + (size_t)r0 * STAGE), "r"(STAGE), "r"(fb) : "memory");
                } else {
                    tma2d(dst, m0, c0, r0, fb); tma2d(dst + 7168, m0, c0, r1, fb);
                    tma2d(dst + HALF, m1, c0, r0, fb); tma2d(dst + HALF + 7168, m1, c0, r1, fb);
                }
                if (n == PFN) {
                    const int b = blockIdx.x;
                    asm volatile(ELECT "cp.async.bulk.prefetch.L2.global [%0], %1; }" ::"l"(wg + b * 6272), "r"(12544) : "memory");
                    asm volatile(ELECT "cp.async.bulk.prefetch.L2.global [%0], %1; }" ::"l"(wu + b * 6272), "r"(12544) : "memory");
                    asm volatile(ELECT "cp.async.bulk.prefetch.L2.global [%0], %1; }" ::"l"(wd + b * 6272), "r"(12544) : "memory");
                }
                if (n == PACK) asm volatile(ELECT "mbarrier.arrive.shared::cta.b64 _, [%0]; }" ::"r"(BAR(slot)) : "memory");
                if (++slot == NST) { slot = 0; ph ^= 1; }
                }
            } else if (w == 1 && layer == 1) {
                constexpr int ps = PACK % NST;
                mbar_wait(BAR(B_PACK), 0);
                asm volatile("{ .reg .pred e; elect.sync _|e, 0xffffffff;\n"
                             "@e cp.async.bulk.global.shared::cta.bulk_group [%0], [%1], %2;\n"
                             "@e cp.async.bulk.commit_group;\n"
                             "@e cp.async.bulk.wait_group.read 0;\n"
                             "@e mbarrier.arrive.shared::cta.b64 _, [%3], 8;\n"
                             "@e cp.async.bulk.wait_group 0;\n"
                             "@e fence.proxy.async.global;\n"
                             "@e red.release.gpu.global.add.u32 [%4], 1; }"
                             ::"l"(reinterpret_cast<char*>(g_wp) + (size_t)(sl * 16 + tile) * STAGE), "r"(sb + ps * STAGE), "r"(STAGE), "r"(BAR(B_EMPTY + ps)), "l"(g_cw + sl * 32) : "memory");
                __syncwarp();
            }
            if (layer < 2) {
            const uint32_t tag = layer ^ 1;
            kseq++;
            bar_sync(7, 384);
            ASTAMP(0);
            if (tile < 15) {
                const int sq = lane >> 3, pk = 8 * w + (lane & (tile == 14 ? 3 : 7));
                uint32_t v[16];
                if (layer == 0) poll_cnt(g_c1 + ((sl * 8 + (w >> 1) * 4 + (tile >> 2)) * 16 + (lane & 15)) * 32, kseq);
                ASTAMP(1);
                poll4_kv<32>(v, g_kv1 + ((sl * 16 + tile) * 16 + 4 * sq) * 32 + pk, tag);
#pragma unroll
                for (int k = 0; k < 4; k++) {
                    float lo = (bf_lo(v[k]) + bf_lo(v[4 + k])) + (bf_lo(v[8 + k]) + bf_lo(v[12 + k]));
                    float hi = (bf_hi(v[k]) + bf_hi(v[4 + k])) + (bf_hi(v[8 + k]) + bf_hi(v[12 + k]));
                    lo += __shfl_xor_sync(0xffffffffu, lo, 8); hi += __shfl_xor_sync(0xffffffffu, hi, 8);
                    lo += __shfl_xor_sync(0xffffffffu, lo, 16); hi += __shfl_xor_sync(0xffffffffu, hi, 16);
                    v[k] = pack2(lo, hi);
                }
                if (sq == 0) st_pkt<0>(g_kv2 + sl * 512 + 32 * tile + pk, settag(v[0], tag), v[1], v[2], v[3]);
            }
            ASTAMP(2);
            {
                const int item = t128 < 112 ? t128 : 112 + (t128 & 3), d = item >> 1;
                const int cc = t128 < 112 ? 2 * (d >= 28) + (item & 1) : item - 112;
                const int r = t128 < 112 ? d : 56 + (cc >> 1) + 2 * ((t128 - 112) >> 2);
                uint32_t ra = sb + OFF_KVB + r * 128 + 4 * cc, rx = (r & 7) << 4;
                asm volatile("" : "+r"(ra), "+r"(rx));
                FOR14(asm volatile("st.shared.u32 [%0+%2], %1;" ::"r"((ra ^ 8) + (((t & 7) << 4) ^ rx)), "r"(0), "n"((t >> 3) * 8192) : "memory"));
                uint32_t v[16];
                asm volatile("" : "+r"(ra), "+r"(rx));
                poll4_kv<8>(v, g_kv2 + sl * 512 + (item >> 3) * 32 + (item & 7), tag);
                FOR14(asm volatile("st.shared.u32 [%0+%2], %1;" ::"r"(ra + (((t & 7) << 4) ^ rx)), "r"(v[t < 7 ? t : t + 1]), "n"((t >> 3) * 8192) : "memory"));
                fence_async();
            }
            bar_arrive(3, 384);
            ASTAMP(3);
            }
        }
    } else {
        asm volatile("setmaxnreg.inc.sync.aligned.u32 232;");
        int lane = fresh_tid() & 31, prf = pr;
#define pr prf
#define g (lane >> 2)
#define c (lane & 3)
#define t128 (w * 32 + lane)
        const int wu = __shfl_sync(0xffffffffu, fresh_tid() >> 5, 0), w = wu & 3;
        const uint32_t xoff = __shfl_sync(0xffffffffu, (3 * PLANE + ((tile * 2 + wgi) * 8) * 512 + w * 128) * 16, 0);
        char* xu = reinterpret_cast<char*>(g_ex) + xoff;
#define FRESH() asm volatile("" : "+l"(xu), "+r"(lane), "+r"(prf))
#define xp0 (reinterpret_cast<uint4*>(xu) + lane)
        const uint32_t hbuf = sb + OFF_H + wgi * STAGE;
        uint32_t slot = 0, ph = 0, eb1 = 0, eb2 = 0, ackph = 0, rcvph = 0, gatph = 0, swp = 0;
        uint32_t ppid = 6;
#define cx(s) (reinterpret_cast<uint32_t*>(reinterpret_cast<uint4*>(xu) + PL(1) + 112 + (s) * 512))
#define stp (reinterpret_cast<uint4*>(xu) + g + PL(0) + 112)
        uint32_t seq = ld_word(cx(sl));
        uint32_t kseq = ld_word(g_c1 + ((sl * 8 + wu) * 16 + tile) * 32);
        uint32_t stag = ld_word(reinterpret_cast<const uint32_t*>(stp + sl * 512) + 3) & 1;
        asm volatile("barrier.cluster.wait.aligned;" ::: "memory");
        STAMP(1);
        uint32_t X[14];
        const uint32_t x0row = (w < 2 ? hbuf : sb + wgi * STAGE) + ((w & 1) * 16 + (lane & 15)) * 128;
        mbar_wait(BAR(wgi), 0);
        STAMP(51);
#pragma unroll
        for (int j = 0; j < 4; j++) {
            const int G = 7 * sl + min(2 * j + (lane >> 4), 6);
            uint32_t q2, q3;
            asm volatile("ldmatrix.sync.aligned.m8n8.x4.shared.b16 {%0,%1,%2,%3}, [%4];" : "=r"(X[4 * j]), "=r"(X[4 * j + 1]), "=r"(q2), "=r"(q3)
                         : "r"(x0row + (G >> 3) * 4096 + (((G ^ lane) & 7) << 4)) : "memory");
            if (j < 3) { X[(4 * j + 2) % 14] = q2; X[(4 * j + 3) % 14] = q3; }
        }
#define PUSH_SLICE(W)                                                                          \
    {                                                                                          \
        if (t128 == 0) mbar_expect_tx(BAR(B_RECV + wgi), 7168);                                \
        PUSH_BEGIN();                                                                          \
        const uint32_t ra = mapa(hbuf + 24576 + t128 * 16, hr ^ 1), rb = mapa(sb + OFF_XR + wgi * 3072, hr ^ 1), rbar = mapa(BAR(B_RECV + wgi), hr ^ 1); \
        st_async4(ra, W[0], W[1], W[2], W[3], rbar);                                           \
        st_async4(ra + 2048, W[4], W[5], W[6], W[7], rbar);                                    \
        st_async4(rb + t128 * 16, W[8], W[9], W[10], W[11], rbar);                             \
        asm volatile("st.async.weak.shared::cluster.mbarrier::complete_tx::bytes.v2.b32 [%0], {%1,%2}, [%3];" ::"r"(rb + 2048 + t128 * 8), "r"(W[12]), "r"(W[13]), "r"(rbar) : "memory"); \
    }
#define PULL_SLICE(W)                                                                          \
    {                                                                                          \
        uint32_t t0, t1;                                                                       \
        mbar_wait(BAR(B_RECV + wgi), rcvph);                                                   \
        rcvph ^= 1;                                                                            \
        lds4(&A[1][0], hbuf + 24576 + t128 * 16);                                              \
        lds4(&A[1][4], hbuf + 26624 + t128 * 16);                                              \
        lds4(&A[1][8], sb + OFF_XR + wgi * 3072 + t128 * 16);                                  \
        asm volatile("ld.shared.v2.u32 {%0,%1}, [%2];" : "=r"(t0), "=r"(t1) : "r"(sb + OFF_XR + wgi * 3072 + 2048 + t128 * 8) : "memory"); \
        _Pragma("unroll") for (int i = 0; i < 12; i++) A[0][i] = (i & 3) ? W[i] : W[i] & ~1u;  \
        A[1][0] &= ~1u; A[1][4] &= ~1u; A[1][8] &= ~1u;                                        \
        A[0][12] = (hr ? t0 : W[12]) & ~1u; A[0][13] = hr ? t1 : W[13];                        \
        A[1][12] = (hr ? W[12] : t0) & ~1u; A[1][13] = hr ? W[13] : t1;                        \
        asm volatile("" : RW4(A[0], 0), RW4(A[0], 4), RW4(A[0], 8), RW2(A[0], 12), RW4(A[1], 0), RW4(A[1], 4), RW4(A[1], 8), RW2(A[1], 12)); \
        swp = hr * 448;                                                                        \
    }
#define SWB(b, t, db, sh) ((b) == 0 && (t) < 6 ? ((t) < 3 ? db##p : db##m) : db)
#define DECL_DB(b, MK, lbo, sh) const uint64_t db = MK(0, lbo, R_ADJ), dbp = (b) == 0 ? MK(0, lbo, R_ADJ + (swp >> (sh))) : db, dbm = (b) == 0 ? MK(0, lbo, R_ADJ - (swp >> (sh))) : db;
#define PPB 2
#define PP_WAIT() if (wgi == 1) { bar_sync(ppid, 256); ppid ^= 14; }
#define PP_GO() if (wgi == 0) { bar_arrive(ppid, 256); ppid ^= 14; }
#define GAT_DST(B, s2) ((B) == 1 ? hbuf + w * 3584 + (s2) * 1792 : ((s2) ? sb + OFF_KVB + wgi * 8192 : hbuf + 14336) + w * 1792)
#define GAT_ISSUE(B, base)                                                                     \
    {                                                                                          \
        const char* gs = xu + ((base) + kblk(pr, B) * 1024) * 16;                              \
        asm volatile("{ .reg .pred e; elect.sync _|e, 0xffffffff;\n"                           \
                     "@e mbarrier.arrive.expect_tx.shared::cta.b64 _, [%3], 3584;\n"           \
                     "@e cp.async.bulk.shared::cluster.global.mbarrier::complete_tx::bytes [%0], [%2], 1792, [%3];\n" \
                     "@e cp.async.bulk.shared::cluster.global.mbarrier::complete_tx::bytes [%1], [%2+8192], 1792, [%3]; }" \
                     ::"r"(GAT_DST(B, 0)), "r"(GAT_DST(B, 1)), "l"(gs), "r"(BAR(B_GAT + wu * 2 + ((B) >> 1))) : "memory"); \
        __syncwarp();                                                                          \
    }
#define GAT_FETCH(B)                                                                           \
    {                                                                                          \
        mbar_wait(BAR(B_GAT + wu * 2 + ((B) >> 1)), (gatph >> (B)) & 1);                          \
        gatph ^= 1 << (B);                                                                     \
        _Pragma("unroll") for (int s2 = 0; s2 < 2; s2++) {                                     \
            const uint32_t ga = GAT_DST(B, s2) + lane * 16;                                    \
            lds4(&A[2 * (B) + s2][0], ga); lds4(&A[2 * (B) + s2][4], ga + 512); lds4(&A[2 * (B) + s2][8], ga + 1024); \
            asm volatile("ld.shared.v2.u32 {%0,%1}, [%2];" : "=r"(A[2 * (B) + s2][12]), "=r"(A[2 * (B) + s2][13]) : "r"(ga - lane * 8 + 1536) : "memory"); \
        }                                                                                      \
    }
#define LATE_ARRIVE() do { if (lane == 0) mbar_arrive(BAR(B_LATE)); } while (0)
#define LATE_WAIT() do { mbar_wait(BAR(B_LATE), gatph & 1); gatph ^= 1; } while (0)
#define PT 3
#define PREP(b, t, remote)                                                                     \
    if constexpr ((b) < 3 && (t) == PT) {                                                      \
        wg_commit();                                                                           \
        STAMP(74 + 6 * (step & 1) + 2 * (b));                                                  \
        if (remote) {                                                                          \
            if constexpr ((b) == 0) { blk_load<2>(A, BLK(xsrc, 2), lane); GAT_FETCH(1) }       \
            blk_check<((b) + 1) & 3>(A, BLK(xsrc, (b) + 1), lane, xtag);                       \
            if constexpr ((b) == 0) blk_load<3>(A, BLK(xsrc, 3), lane);                        \
        }                                                                                      \
        STAMP(75 + 6 * (step & 1) + 2 * (b));                                                  \
        normalize<((b) + 1) & 3>(A, k0, k1);                                                   \
        asm volatile("" : RW4(A[(2 * (b) + 2) & 7], 0), RW4(A[(2 * (b) + 2) & 7], 4), RW4(A[(2 * (b) + 2) & 7], 8), RW2(A[(2 * (b) + 2) & 7], 12), \
                          RW4(A[(2 * (b) + 3) & 7], 0), RW4(A[(2 * (b) + 3) & 7], 4), RW4(A[(2 * (b) + 3) & 7], 8), RW2(A[(2 * (b) + 3) & 7], 12)); \
        wg_fence();                                                                            \
    }
#define X0_BLOCK(b)                                                                            \
    { const int rr = lane & 7, hi = lane >> 4;                                                 \
    const uint32_t rowa = (w < 2 ? hbuf : sb + wgi * STAGE) + ((w & 1) * 16 + (lane & 15)) * 128; \
    FOR7(constexpr int G = 14 * (b) + (t < 3 ? 2 * t : (t < 6 ? 2 * t + 1 : 6));               \
         uint32_t q0, q1, q2, q3;                                                              \
         const uint32_t ad = t < 6 ? rowa + (((((G & 7) + hi) ^ rr) & 7) << 4) + ((G & 7) == 7 ? hi * 4096 : 0) : rowa + ((G + 7 * hi) >> 3) * 4096 + ((((G + 7 * hi) ^ rr) & 7) << 4); \
         asm volatile("ldmatrix.sync.aligned.m8n8.x4.shared.b16 {%0,%1,%2,%3}, [%4+%5];" : "=r"(q0), "=r"(q1), "=r"(q2), "=r"(q3) \
                      : "r"(ad), "n"(t < 6 ? (G >> 3) * 4096 : 0) : "memory");                 \
         if (t < 3) { A[2 * (b)][4 * t] = q0; A[2 * (b)][4 * t + 1] = q1; A[2 * (b)][4 * t + 2] = q2; A[2 * (b)][4 * t + 3] = q3; } \
         else if (t < 6) { A[2 * (b) + 1][(4 * t - 12) & 15] = q0; A[2 * (b) + 1][((4 * t - 12) & 15) + 1] = q1; A[2 * (b) + 1][((4 * t - 12) & 15) + 2] = q2; A[2 * (b) + 1][((4 * t - 12) & 15) + 3] = q3; } \
         else { A[2 * (b)][12] = q0; A[2 * (b)][13] = q1; A[2 * (b) + 1][12] = q2; A[2 * (b) + 1][13] = q3; }); }
#define BLK(base, b) ((base) + kblk(pr, b) * 1024)

#pragma unroll 1
        for (int step = 0; step < 4; step++) {
            FRESH();
            const uint32_t tag = (step >> 1) ^ 1;
            const int so = (step >> 1) * 24 + (step & 1) * 12;
            (void)so;
            uint32_t A[8][14];
            uint4* const xsrc = xp0 + ((step & 1) ? PL(2) : PL(0));
            const uint32_t xtag = (step & 1) ? tag : ((seq >> 3) & 1) ^ 1;
            uint32_t xbits;
            {
                float st[4];
                slice_stats(X, st);
                stag ^= 1;
                xbits = x_bits(X);
                tag_slice(X, xtag);
                if (step) send_slice<0>(xsrc + sl * 512, lane, X);
                if (c == 0) st_pkt<0>(stp + sl * 512, __float_as_uint(st[0]), __float_as_uint(st[1]), __float_as_uint(st[2]), settag(__float_as_uint(st[3]), stag));
            }
            STAMP(2 + so);
            uint32_t sv[8];
            if (step == 0) {
                X0_BLOCK(0) X0_BLOCK(1) X0_BLOCK(2) X0_BLOCK(3)
                mbar_wait(BAR(wgi ^ 1), 0);
                R_NEXT();
                R_NEXT();
                R_RELEASE(2);
                stat_load(sv, stp + c * 1024);
                stat_check(sv, stp + c * 1024, stag);
                STAMP(52 + step);
            } else {
                kill<14>(A[2]); kill<14>(A[3]); kill<14>(A[4]); kill<14>(A[5]); kill<14>(A[6]); kill<14>(A[7]);
                PUSH_SLICE(X)
                stat_load(sv, stp + c * 1024);
                PULL_SLICE(X)
                stat_check(sv, stp + c * 1024, stag);
                STAMP(52 + step);
                GAT_ISSUE(1, (step & 1) ? PL(2) : PL(0))
            }
            LnCoef k0, k1;
            {
                k0 = ln_coef(__uint_as_float(sv[0]) + __uint_as_float(sv[4]), __uint_as_float(sv[1]) + __uint_as_float(sv[5]));
                k1 = ln_coef(__uint_as_float(sv[2]) + __uint_as_float(sv[6]), __uint_as_float(sv[3] & ~1u) + __uint_as_float(sv[7] & ~1u));
            }
            STAMP(3 + so);
            GSTAMP(70 + step);

            if ((step & 1) == 0) {
                float tq[28];
                {
                    float av[28];
#define KV_BLOCK(b)                                                                           \
    if ((b) == 1) R_RELEASE(2);                                                               \
    if ((b) == 2) { PUSH_ACK(); wg_wait<2>(); R_RELEASE(2); }                                 \
    R_WAIT();                                                                                 \
    if ((b) == PPK) { PP_WAIT() }                                                             \
    { DECL_DB(b, BASE128, 16, 0)                                                              \
    wg_fence();                                                                               \
    FOR7(mma_rs56<1, D128(0, t)>(tq, AQ(A, b, t), (b) + t > 0, SWB(b, t, db, 0));             \
         mma_rs56<1, D128(HALF, t)>(av, AQ(A, b, t), (b) + t > 0, SWB(b, t, db, 0));          \
         PREP(b, t, step)); }                                                                 \
    wg_commit();                                                                              \
    if ((b) == 3 && PPK < 4) { PP_GO() }                                                      \
    R_NEXT();
                    normalize<0>(A, k0, k1);
                    KV_BLOCK(0) KV_BLOCK(1) KV_BLOCK(2) KV_BLOCK(3)
                    wg_wait<0>();
                    if (lane < 3) mbar_arrive(BAR(B_EMPTY + (slot + NST - 1 - lane) % NST));
                    STAMP(4 + so);
                    WSUM(80 + 7 * (step >> 1));
                    const int m = lane >> 3, rr = lane & 7;
                    const uint32_t rowa = hbuf + 16384 + (w * 16 + rr + 8 * (m & 1)) * 128;
                    const uint32_t one = c == 0 ? 0x00003f80u : 0u;
                    if (step == 0) { bar_sync(wgi ? 9 : 1, 224); }
#pragma unroll
                    for (int j = 0; j < 4; j++) {
                        const uint32_t a = rowa + (((2 * j + (m >> 1)) ^ rr) << 4);
                        if (j < 3) stsm4(a, pack2(av[8 * j], av[8 * j + 1]), pack2(av[8 * j + 2], av[8 * j + 3]), pack2(av[8 * j + 4], av[8 * j + 5]), pack2(av[8 * j + 6], av[8 * j + 7]));
                        else stsm4(a, pack2(av[24], av[25]), pack2(av[26], av[27]), one, one);
                    }
                }
                uint32_t PH[28];
                int it = 1;
#pragma unroll 1
                do {
                    float pp[28];
                    phi_gemm(tq, pp);
                    dual_softmax(pp, PH);
                    if (((trips >> (it + 1)) & 1) == 0) continue;
                    {
                        const int m = lane >> 3, rr = lane & 7;
                        const uint32_t rowa = hbuf + (w * 16 + rr + 8 * (m & 1)) * 128;
#pragma unroll
                        for (int j = 0; j < 7; j++) {
                            const int cg = 2 * j + (m >> 1), hi = cg >= 7;
                            stsm4(rowa + hi * 8192 + (((cg - 7 * hi) ^ rr) << 4), PH[4 * j], PH[4 * j + 1], PH[4 * j + 2], PH[4 * j + 3]);
                        }
                    }
                    fence_async();
                    STAMP(5 + so);
#define Q_STAGE(b0)                                                                           \
    R_WAIT();                                                                                 \
    { DECL_DB(b0, BASE128, 16, 0)                                                             \
    wg_fence();                                                                               \
    FOR7(mma_rs56<1, D128(0, t)>(tq, AQ(A, b0, t), (b0) + t > 0, SWB(b0, t, db, 0)));         \
    FOR7(mma_rs56<1, D128(HALF, t)>(tq, AQ(A, (b0) + 1, t), 1, db)); }                        \
    wg_commit();                                                                              \
    R_NEXT();
                    if (QE && wgi == 0) { kill<28>(tq); Q_STAGE(0) Q_STAGE(2) wg_wait<1>(); R_RELEASE(2); wg_wait<0>(); R_RELEASE(1); }
                    bar_sync(2, 256);
                    float kv[28];
                    const uint64_t da = BASE128(OFF_H + 16384, 16, 0), dbk = BASE128(OFF_H, 16, wgi * 512);
                    wg_fence();
                    FOR8(constexpr uint64_t o = ((t >> 2) * STAGE + (t & 3) * 2048) >> 4; mma_ss56_tt<o, o>(kv, t > 0, da, dbk));
                    wg_commit();
                    wg_wait<0>();
#pragma unroll
                    for (int hf = 0; hf < 2; hf++) {
                        const int d = 16 * w + g + 8 * hf;
                        if ((d < 56 && (d >= 28) == (c >= 2)) || d == 56) {
                            const int item = d < 56 ? 2 * d + (c & 1) : 112 + c;
                            uint4* dst = g_kv1 + ((sl * 16 + (item >> 3)) * 16 + tile) * 32 + wgi * 16 + (item & 7);
#define KVW(i) pack2(kv[4 * (i) + 2 * hf], kv[4 * (i) + 2 * hf + 1])
                            st_pkt<0>(dst, settag(KVW(0), tag), KVW(1), KVW(2), KVW(3));
                            st_pkt<8>(dst, settag(KVW(4), tag), KVW(5), KVW(6), 0u);
                        }
                    }
                    __syncwarp();
                    kseq++;
                    if (lane == 0) st_word(g_c1 + ((sl * 8 + wu) * 16 + tile) * 32, kseq);
                    bar_arrive(7, 384);
                    STAMP(6 + so);
                    if (!QE || wgi == 1) { kill<28>(tq); Q_STAGE(0) Q_STAGE(2) wg_wait<1>(); R_RELEASE(2); wg_wait<0>(); R_RELEASE(1); }
                    STAMP(7 + so);
                    kill<28>(PH);
                } while (((trips >> (++it)) & 1));
                STAMP(8 + so);
                FRESH();
                if (step) {
                    slice_load<PL(0)>(X, xp0 + sl * 512, lane);
                } else {
                    const uint32_t* xp = reinterpret_cast<const uint32_t*>(x_in + (size_t)(tile * 128 + wu * 16 + g) * 448 + 56 * sl + 2 * c);
#pragma unroll
                    for (int i = 0; i < 7; i++) { X[2 * i] = __ldg(xp + 4 * i); X[2 * i + 1] = __ldg(xp + 4 * i + 8 * 224); }
                }
                bar_sync(3, 384);
                STAMP(9 + so);
                const uint4* const osrc = xp0 + PL(1);
                {
                    float nm[32];
                    const uint64_t db = BASE128(OFF_KVB, 16, 0);
                    wg_fence();
                    FOR7(mma_rs64<0, ((t >> 2) * 8192 + (t & 3) * 32) / 16>(nm, PH[4 * t], PH[4 * t + 1], PH[4 * t + 2], PH[4 * t + 3], t > 0, db));
                    wg_commit();
                    wg_wait<0>();
                    LATE_ARRIVE();
                    const float i00 = rcp(nm[28] + 1e-6f), i01 = rcp(nm[29] + 1e-6f), i10 = rcp(nm[30] + 1e-6f), i11 = rcp(nm[31] + 1e-6f);
                    const float m0 = c >= 2 ? i01 : i00, m1 = c >= 2 ? i11 : i10;
                    uint32_t O[14];
#pragma unroll
                    for (int i = 0; i < 7; i++) {
                        const float f0 = i < 3 ? i00 : (i > 3 ? i01 : m0), f1 = i < 3 ? i10 : (i > 3 ? i11 : m1);
                        O[2 * i] = pack2(nm[4 * i] * f0, nm[4 * i + 1] * f0);
                        O[2 * i + 1] = pack2(nm[4 * i + 2] * f1, nm[4 * i + 3] * f1);
                    }
                    if (OST) { PP_WAIT() }
                    tag_slice(O, tag);
                    send_slice<PL(1)>(xp0 + sl * 512, lane, O);
                    seq++;
                    if (lane == 0) st_word(cx(sl), seq);
                    STAMP(10 + so);
                    if (OST == 4) { PP_GO() }
                    PUSH_SLICE(O)
                    if (OST == 1) { PP_GO() }
                    const uint32_t cv = ld_word(cx(lane & 7));
                    PULL_SLICE(O)
                    if (OST == 3) { PP_GO() }
                    LATE_WAIT();
                    check_cnt(cv, cx(lane & 7), seq);
                    if (OST == 2) { PP_GO() }
                    STAMP(56 + (step >> 1));
                    GAT_ISSUE(1, PL(1))
                    GAT_ISSUE(3, PL(1))
                    blk_load<2>(A, BLK(osrc, 2), lane);
                }
                float ao[28];
#define WO_BLOCK(b)                                                                           \
    if ((b) > 0) blk_check<b>(A, BLK(osrc, b), lane, tag);                                    \
    if (((b) & 1) == 0) R_WAIT();                                                             \
    { DECL_DB(b, BASE128, 16, 0)                                                              \
    wg_fence();                                                                               \
    FOR7(mma_rs56<1, D128(((b) & 1) * HALF, t)>(ao, AQ(A, b, t), (b) + t > 0, SWB(b, t, db, 0))); } \
    wg_commit();                                                                              \
    if ((b) & 1) R_NEXT();
                WO_BLOCK(0)
                STAMP(11 + so);
                GAT_FETCH(1)
                WO_BLOCK(1)
                WO_BLOCK(2)
                GAT_FETCH(3)
                WO_BLOCK(3)
                PUSH_ACK();
                wg_wait<0>();
                R_RELEASE(2);
                STAMP(12 + so);
                WSUM(86 + 7 * (step >> 1));
                x_fix(X, xbits);
#pragma unroll
                for (int i = 0; i < 14; i++) X[i] = pack2(bf_lo(X[i]) + ao[2 * i], bf_hi(X[i]) + ao[2 * i + 1]);
            } else {
                uint32_t H[56];
                float ag[64];
#define F1_EPI(dst, ng, ag)                                                                    \
    _Pragma("unroll") for (int i = 0; i < 2 * (ng); i++)                                       \
        (dst)[i] = pack2(geglu(ag[2 * i], ag[4 * (ng) + 2 * i]), geglu(ag[2 * i + 1], ag[4 * (ng) + 2 * i + 1]));
#define H_PUSH(h0, off) st_async4(rem_h + (off), H[h0], H[(h0) + 1], H[(h0) + 2], H[(h0) + 3], mapa(BAR(B_RECV2 + wgi), hr ^ 1));
#define F1_BLOCK(b, first)                                                                     \
    if ((first) && (b) == 1) R_RELEASE(2);                                                     \
    if ((first) && (b) == 2) PUSH_ACK();                                                       \
    R_WAIT();                                                                                  \
    if ((b) == ((first) ? PPF : PPB)) { PP_WAIT() }                                            \
    { DECL_DB(b, BASE128, HALF, 0)                                                             \
    wg_fence();                                                                                \
    FOR7(mma_rs128<1, D128(0, t)>(ag, AQ(A, b, t), (b) + t > 0, SWB(b, t, db, 0));             \
         if constexpr (first) { PREP(b, t, true) }); }                                         \
    wg_commit();                                                                               \
    if ((b) == 3) { PP_GO() }                                                                  \
    if ((b) > 0) { wg_wait<1>(); R_RELEASE(1); }       \
    R_NEXT();
                normalize<0>(A, k0, k1);
                F1_BLOCK(0, true) F1_BLOCK(1, true) F1_BLOCK(2, true) F1_BLOCK(3, true)
                if (t128 == 0) { mbar_expect_tx(BAR(B_RECV + wgi), 16384); mbar_expect_tx(BAR(B_RECV2 + wgi), 12288); }
                PUSH_BEGIN();
                wg_wait<0>();
                R_RELEASE(1);
                int p = 0;
#pragma unroll 1
                do {
                    F1_EPI(H + 32, 8, ag)
                    STAMP(4 + p + so);
                    WSUM(81 + p + 7 * (step >> 1));
                    if (((trips >> (p + 1)) & 1) == 0) continue;
                    if (step == 1 && p == PKP) R_NEXT();
                    kill<64>(ag);
                    F1_BLOCK(0, false)
                    {
                        const uint32_t pk = (p ? hbuf + 16384 : sb + OFF_KVB + wgi * 8192) + w * 2048;
#pragma unroll
                        for (int k = 0; k < 4; k++) sts4(pk + k * 512 + lane * 16, H[32 + 4 * k], H[33 + 4 * k], H[34 + 4 * k], H[35 + 4 * k]);
                        fence_async();
                        __syncwarp();
                        asm volatile(ELECT "cp.async.bulk.shared::cluster.shared::cta.mbarrier::complete_tx::bytes [%0], [%1], 2048, [%2]; }"
                                     ::"r"(mapa(hbuf + p * 8192 + w * 2048, hr ^ 1)), "r"(pk), "r"(mapa(BAR(B_RECV + wgi), hr ^ 1)) : "memory");
                    }
                    F1_BLOCK(1, false) F1_BLOCK(2, false) F1_BLOCK(3, false)
                    wg_wait<0>();
                    R_RELEASE(1);
                    kill<16>(H + 32);
                } while (((trips >> (++p)) & 1));
#pragma unroll
                for (int k = 0; k < 4; k++) lds4(H + 16 + 4 * k, hbuf + 16384 + w * 2048 + k * 512 + lane * 16);
                __syncwarp();
                if (lane == 0) asm volatile("mbarrier.arrive.shared::cluster.b64 _, [%0];" ::"r"(mapa(BAR(B_ACK2 + wgi), hr ^ 1)) : "memory");
                const uint32_t rem_h = mapa(hbuf + w * 2048 + lane * 16, hr ^ 1);
#define F1_LAST(b0)                                                                            \
    R_WAIT();                                                                                  \
    if (b0) { PP_WAIT() }                                                                      \
    { DECL_DB(b0, BASE64, HALF, 1)                                                             \
    wg_fence();                                                                                \
    FOR7(mma_rs64<1, D64(0, t)>(al, AQ(A, b0, t), (b0) + t > 0, SWB(b0, t, db, 1)));           \
    FOR7(mma_rs64<1, D64(7168, t)>(al, AQ(A, (b0) + 1, t), 1, db)); }                          \
    wg_commit();                                                                               \
    if (b0) { PP_GO() }                                                                        \
    R_NEXT();
                float al[32];
                F1_LAST(0)
                mbar_wait(BAR(B_RECV + wgi), rcvph);
                rcvph ^= 1;
                mbar_wait(BAR(B_ACK2 + wgi), step >> 1);
                H_PUSH(32, 16384) H_PUSH(36, 16896)
                F1_LAST(2)
                H_PUSH(40, 17408) H_PUSH(44, 17920)
                wg_wait<1>();
                R_RELEASE(2);
                wg_wait<0>();
                R_RELEASE(1);
                uint32_t HP[56];
#pragma unroll
                for (int k = 0; k < 4; k++) lds4(H + 4 * k, sb + OFF_KVB + wgi * 8192 + w * 2048 + k * 512 + lane * 16);
#pragma unroll
                for (int t = 0; t < 8; t++) lds4(HP + 4 * t, hbuf + (t >> 2) * 8192 + w * 2048 + (t & 3) * 512 + lane * 16);
                F1_EPI(H + 48, 4, al)
                H_PUSH(48, 24576 - w * 1024) H_PUSH(52, 25088 - w * 1024)
                STAMP(7 + so);
                WSUM(84 + 7 * (step >> 1));
                FRESH();
                float acc[28];
                const uint32_t roA = hr ? 256u : 0u, roB = hr ? (uint32_t)-1536 : 0u;
                const uint32_t rpA = hr ? 0u : 256u, rpB = hr ? 0u : (uint32_t)-1536;
                float res[28];
                uint32_t v0[14], v1[14], P[14];
                const uint4* ps = xp0 + sl * 512;
#define F2_OWN_A()                                                                             \
    R_WAIT();                                                                                  \
    d0 = BASE128(0, 16, R_ADJ + roA); d1 = BASE128(0, 16, R_ADJ + roB);                        \
    wg_fence();                                                                                \
    FOR14(if constexpr (t < OT) mma_rs56<1, t * 128>(acc, H[4 * t], H[4 * t + 1], H[4 * t + 2], H[4 * t + 3], t > 0, d0)); \
    wg_commit();
#define F2_OWN_B()                                                                             \
    wg_fence();                                                                                \
    FOR14(if constexpr (t >= OT) mma_rs56<1, t * 128>(acc, H[4 * t], H[4 * t + 1], H[4 * t + 2], H[4 * t + 3], 1, t < 12 ? d0 : d1)); \
    wg_commit();                                                                               \
    R_NEXT();
#define F2_PEER()                                                                              \
    R_WAIT();                                                                                  \
    if (F2PP) { PP_WAIT() }                                                                    \
    d0 = BASE128(0, 16, R_ADJ + rpA); d1 = BASE128(0, 16, R_ADJ + rpB);                        \
    wg_fence();                                                                                \
    FOR14(mma_rs56<1, t * 128>(acc, HP[4 * t], HP[4 * t + 1], HP[4 * t + 2], HP[4 * t + 3], 1, t < 12 ? d0 : d1)); \
    wg_commit();                                                                               \
    if (F2PP) { PP_GO() }                                                                      \
    R_NEXT();
#define F2_TURN(u)                                                                             \
    wg_wait<1>();                                                                              \
    if ((u) < 2 || TDEF < 2) R_RELEASE(2);                                                     \
    wg_wait<0>();                                                                              \
    if ((u) < 2 || TDEF < 1) R_RELEASE(1);                                                     \
    _Pragma("unroll") for (int i = 0; i < 14; i++) P[i] = pack2(acc[2 * i], acc[2 * i + 1]);   \
    tag_slice(P, tag);                                                                         \
    asm volatile("" : RW4(P, 0), RW4(P, 4), RW4(P, 8), RW2(P, 12));                            \
    kill<28>(acc);                                                                             \
    F2_OWN_A()                                                                                 \
    if ((u) == 2) { slice_load<PL(3)>(v0, ps, lane); slice_load<PL(4)>(v1, ps, lane); } \
    send_slice<PL(3 + (u))>(xp0 + (2 * ((pr + (u) + 1) & 3) + hr) * 512, lane, P);             \
    seq++;                                                                                     \
    if (lane == 0) st_word(cx(sl), seq);                                                       \
    __syncwarp();                                                                              \
    STAMP(8 + (u) + so);                                                                       \
    F2_OWN_B()
                uint64_t d0, d1;
                F2_OWN_A()
                F2_OWN_B()
                R_WAIT();
                d0 = BASE128(0, 16, R_ADJ + rpA); d1 = BASE128(0, 16, R_ADJ + rpB);
                wg_fence();
                FOR8(mma_rs56<1, t * 128>(acc, HP[4 * t], HP[4 * t + 1], HP[4 * t + 2], HP[4 * t + 3], 1, d0));
                wg_commit();
                mbar_wait(BAR(B_RECV2 + wgi), step >> 1);
#pragma unroll
                for (int k = 0; k < 4; k++) lds4(HP + 32 + 4 * k, hbuf + 16384 + w * 2048 + k * 512 + lane * 16);
                lds4(HP + 48, hbuf + 24576 + w * 1024 + lane * 16);
                lds4(HP + 52, hbuf + 25088 + w * 1024 + lane * 16);
                if (step == 1) PUSH_ACK();
                wg_fence();
                FOR14(if constexpr (t >= 8) mma_rs56<1, t * 128>(acc, HP[4 * t], HP[4 * t + 1], HP[4 * t + 2], HP[4 * t + 3], 1, t < 12 ? d0 : d1));
                wg_commit();
                R_NEXT();
                F2_TURN(0)
                F2_PEER()
                F2_TURN(1)
                F2_PEER()
                F2_TURN(2)
                if (step == 1) STAMP(64);
                slice_check<PL(3)>(v0, ps, lane, tag);
                slice_check<PL(4)>(v1, ps, lane, tag);
#pragma unroll
                for (int i = 0; i < 14; i++) { res[2 * i] = bf_lo(v0[i]) + bf_lo(v1[i]); res[2 * i + 1] = bf_hi(v0[i]) + bf_hi(v1[i]); }
                slice_load<PL(2)>(X, ps, lane);
                if (step == 1) STAMP(65);
                F2_PEER()
                if (step == 1) STAMP(66);
                poll_cnt(cx(2 * ((pr + 1) & 3) + hr), seq);
                if (step == 1) STAMP(67);
                slice_load<PL(5)>(v0, ps, lane);
                x_fix(X, xbits);
                slice_check<PL(5)>(v0, ps, lane, tag);
                if (lane < TDEF) mbar_arrive(BAR(B_EMPTY + (slot + NST - 3 - lane) % NST));
#pragma unroll
                for (int i = 0; i < 14; i++) { res[2 * i] += bf_lo(v0[i]); res[2 * i + 1] += bf_hi(v0[i]); }
                STAMP(11 + so);
                wg_wait<0>();
                R_RELEASE(2);
                STAMP(12 + so);
                WSUM(85 + 7 * (step >> 1));
#pragma unroll
                for (int i = 0; i < 14; i++) X[i] = pack2(fmaf(res[2 * i] + acc[2 * i], 0.5f, bf_lo(X[i])), fmaf(res[2 * i + 1] + acc[2 * i + 1], 0.5f, bf_hi(X[i])));
            }
        }
        {
            const int m = lane >> 3, rr = lane & 7;
            const uint32_t ob = hbuf + w * 2048, rowa = ob + (rr + 8 * (m & 1)) * 112 + (m >> 1) * 16;
#pragma unroll
            for (int j = 0; j < 3; j++) stsm4(rowa + 32 * j, X[4 * j], X[4 * j + 1], X[4 * j + 2], X[4 * j + 3]);
            asm volatile("stmatrix.sync.aligned.m8n8.x2.shared.b16 [%0], {%1,%2};" ::"r"(ob + (rr + 8 * (m & 1)) * 112 + 96), "r"(X[12]), "r"(X[13]) : "memory");
            fence_async();
            __syncwarp();
            if (lane == 0) {
                asm volatile("cp.async.bulk.tensor.2d.global.shared::cta.bulk_group [%0, {%2, %3}], [%1];" ::"l"(&maps.out), "r"(ob), "r"(56 * sl), "r"(tile * 128 + wu * 16) : "memory");
                asm volatile("cp.async.bulk.commit_group;" ::: "memory");
                asm volatile("cp.async.bulk.wait_group.read 0;" ::: "memory");
            }
        }
        STAMP(50);
        GSTAMP(61);
        PDUMP();
    }
}

#undef g
#undef pr
#undef c
#undef t128

typedef CUresult (*EncodeFn)(CUtensorMap*, CUtensorMapDataType, cuuint32_t, void*, const cuuint64_t*, const cuuint64_t*, const cuuint32_t*,
                             const cuuint32_t*, CUtensorMapInterleave, CUtensorMapSwizzle, CUtensorMapL2promotion, CUtensorMapFloatOOBfill);

static void make_map(EncodeFn enc, CUtensorMap* m, const void* p, uint64_t cols, uint64_t rows, uint32_t bc, uint32_t br, CUtensorMapSwizzle sw) {
    cuuint64_t gd[2] = {cols, rows};
    cuuint64_t gs[1] = {cols * 2};
    cuuint32_t bd[2] = {bc, br};
    cuuint32_t es[2] = {1, 1};
    enc(m, CU_TENSOR_MAP_DATA_TYPE_BFLOAT16, 2, const_cast<void*>(p), gd, gs, bd, es, CU_TENSOR_MAP_INTERLEAVE_NONE, sw,
        CU_TENSOR_MAP_L2_PROMOTION_L2_128B, CU_TENSOR_MAP_FLOAT_OOB_FILL_NONE);
}

extern "C" void kernel_launch(void* const* d_in, const int* in_sizes, int n_in, void* d_out, int out_size) {
    (void)in_sizes; (void)n_in; (void)out_size;
    static EncodeFn enc = nullptr;
    static Scratch* scratch = nullptr;
    if (!enc) {
        void* fn = nullptr;
        cudaDriverEntryPointQueryResult qr;
        cudaGetDriverEntryPoint("cuTensorMapEncodeTiled", &fn, cudaEnableDefault, &qr);
        enc = (EncodeFn)fn;
        cudaGetSymbolAddress((void**)&scratch, g_scratch);
        cudaFuncSetAttribute(fused_kernel, cudaFuncAttributeMaxDynamicSharedMemorySize, SMEM_BYTES);
    }
    Maps maps;
    {
        cuuint64_t gd[3] = {64, 2048, 7};
        cuuint64_t gs[2] = {896, 128};
        cuuint32_t bd[3] = {64, 32, 7};
        cuuint32_t es[3] = {1, 1, 1};
        enc(&maps.x, CU_TENSOR_MAP_DATA_TYPE_BFLOAT16, 3, d_in[0], gd, gs, bd, es, CU_TENSOR_MAP_INTERLEAVE_NONE, CU_TENSOR_MAP_SWIZZLE_128B,
            CU_TENSOR_MAP_L2_PROMOTION_L2_128B, CU_TENSOR_MAP_FLOAT_OOB_FILL_NONE);
    }
    make_map(enc, &maps.out, d_out, 448, 2048, 56, 16, CU_TENSOR_MAP_SWIZZLE_NONE);
    make_map(enc, &maps.qkv, d_in[1], 1344, 448, 64, 112, CU_TENSOR_MAP_SWIZZLE_128B);
    make_map(enc, &maps.wo, d_in[3], 448, 448, 64, 112, CU_TENSOR_MAP_SWIZZLE_128B);
    make_map(enc, &maps.wg, d_in[5], 1792, 448, 64, 112, CU_TENSOR_MAP_SWIZZLE_128B);
    make_map(enc, &maps.wu, d_in[6], 1792, 448, 64, 112, CU_TENSOR_MAP_SWIZZLE_128B);
    make_map(enc, &maps.wg32, d_in[5], 1792, 448, 32, 112, CU_TENSOR_MAP_SWIZZLE_64B);
    make_map(enc, &maps.wu32, d_in[6], 1792, 448, 32, 112, CU_TENSOR_MAP_SWIZZLE_64B);
    make_map(enc, &maps.wd, d_in[7], 448, 1792, 64, 112, CU_TENSOR_MAP_SWIZZLE_128B);
    fused_kernel<<<128, 384, SMEM_BYTES>>>(scratch, (const __nv_bfloat16*)d_in[0], (const __nv_bfloat16*)d_in[2], 7, (const __nv_bfloat16*)d_in[5],
                                           (const __nv_bfloat16*)d_in[6], (const __nv_bfloat16*)d_in[7], maps);
}
```

```cpp
#include <cuda_runtime.h>
#include <cuda.h>
#include <cuda_bf16.h>
#include <stdint.h>
#include <type_traits>

#define PPF 2
#define PKP 0
#define TDEF 1
#define TMPF 0
#define NORM1 0
#define LPARK 1
#define PFN 9
#define VW 0
#define QPP 0
#define ACAN 0
#define SPLIT0 1
#define OT 2
#define F2PP 0
#define PPK 2
#define QE 1
#define OST 1
#define PP

namespace {

constexpr uint32_t STAGE = 28672, HALF = 14336;
constexpr int NST = 5;
constexpr uint32_t OFF_H = NST * STAGE;
constexpr uint32_t OFF_KVB = OFF_H + 2 * STAGE;
constexpr uint32_t OFF_WPHI = OFF_KVB + 16384;
constexpr uint32_t OFF_XR = OFF_WPHI + 7168;
constexpr uint32_t OFF_BAR = OFF_XR + 6144;
constexpr uint32_t SMEM_BYTES = OFF_BAR + 384 + 1408;
constexpr int B_EMPTY = NST, B_RECV = 2 * NST, B_RECV2 = B_RECV + 2, B_PACK = B_RECV2 + 2, B_GAT = B_PACK + 1, B_LATE = B_GAT + 16, B_ACK = B_LATE + 1, B_ACK2 = B_ACK + 2, B_COUNT = B_ACK2 + 2;

constexpr int PACK = 14 + 4 * PKP;

struct Maps { CUtensorMap x, qkv, wo, wg, wu, wg32, wu32, wd, out; };

}

constexpr int PLANE = 16 * 2 * 8 * 512;
struct Scratch {
    uint4 ex[6 * PLANE];
    uint4 kv1[8 * 16 * 16 * 32];
    uint4 kv2[8 * 512];
    uint32_t c1[8 * 8 * 16 * 32];
    uint32_t cw[8 * 32];
    uint4 wp[8 * 32 * (HALF / 16)];
};
__device__ __align__(1024) Scratch g_scratch;
#define g_ex (sc->ex)
#define g_kv1 (sc->kv1)
#define g_kv2 (sc->kv2)
#define g_c1 (sc->c1)
#define g_cw (sc->cw)
#define g_wp (sc->wp)
#define STAMP(i)
#define GSTAMP(i)
#define PDUMP()
#define ASTAMP(i)

namespace {

__device__ __forceinline__ int fresh_tid() { int t; asm volatile("mov.u32 %0, %%tid.x;" : "=r"(t)); return t; }
template <int N> __device__ __forceinline__ void kill(uint32_t* v) {
#pragma unroll
    for (int i = 0; i < N; i++) v[i] = 0;
}
template <int N> __device__ __forceinline__ void kill(float* v) {
#pragma unroll
    for (int i = 0; i < N; i++) v[i] = 0.f;
}
__device__ __forceinline__ uint32_t s2u(const void* p) { return (uint32_t)__cvta_generic_to_shared(p); }
__device__ __forceinline__ void mbar_init(uint32_t a, uint32_t c) { asm volatile("mbarrier.init.shared::cta.b64 [%0], %1;" ::"r"(a), "r"(c) : "memory"); }
__device__ __forceinline__ void mbar_expect_tx(uint32_t a, uint32_t b) { asm volatile("mbarrier.arrive.expect_tx.shared::cta.b64 _, [%0], %1;" ::"r"(a), "r"(b) : "memory"); }
__device__ __forceinline__ void mbar_arrive(uint32_t a) { asm volatile("mbarrier.arrive.shared::cta.b64 _, [%0];" ::"r"(a) : "memory"); }
#define GIVE_UP(id) "trap;\n"
#define SPIN_MAX "0x400000"
#define SPIN_TAIL(id) "add.u32 n, n, 1;\n setp.lt.u32 p, n, " SPIN_MAX ";\n @p bra.uni LP;\n" GIVE_UP(id) " DN:\n }"
__device__ __forceinline__ void mbar_wait(uint32_t a, uint32_t ph) {
    asm volatile("{ .reg .pred p; .reg .b32 n; mov.u32 n, 0;\n LP:\n"
                 "mbarrier.try_wait.parity.shared::cta.b64 p, [%0], %1;\n @p bra DN;\n"
                 "add.u32 n, n, 1;\n setp.lt.u32 p, n, " SPIN_MAX ";\n @p bra LP;\n"
                 GIVE_UP("")
                 " DN:\n }" ::"r"(a), "r"(ph) : "memory");
}
#define ELECT "{ .reg .pred e; elect.sync _|e, 0xffffffff; @e "
__device__ __forceinline__ void tma2d(uint32_t dst, const CUtensorMap* m, int c0, int c1, uint32_t bar) {
    asm volatile(ELECT "cp.async.bulk.tensor.2d.shared::cluster.global.mbarrier::complete_tx::bytes [%0], [%1, {%3, %4}], [%2]; }" ::"r"(dst), "l"(m), "r"(bar), "r"(c0), "r"(c1) : "memory");
}
__device__ __forceinline__ void tma3x(uint32_t dst, const CUtensorMap* m, int row, uint32_t bar) {
    asm volatile(ELECT "cp.async.bulk.tensor.3d.shared::cluster.global.mbarrier::complete_tx::bytes [%0], [%1, {0, %3, 0}], [%2]; }" ::"r"(dst), "l"(m), "r"(bar), "r"(row) : "memory");
}
template <int OFF>
__device__ __forceinline__ void ld_pkt(uint32_t* v, const uint4* p) {
    asm volatile("{ .reg .b128 t; ld.relaxed.gpu.global.b128 t, [%4+%5]; mov.b128 {%0,%1,%2,%3}, t; }" : "=r"(v[0]), "=r"(v[1]), "=r"(v[2]), "=r"(v[3]) : "l"(p), "n"(OFF * 16) : "memory");
}
template <int OFF>
__device__ __forceinline__ void st_pkt(uint4* p, uint32_t a, uint32_t b, uint32_t c, uint32_t d) {
    asm volatile("{ .reg .b128 t; mov.b128 t, {%1,%2,%3,%4}; st.relaxed.gpu.global.b128 [%0+%5], t; }" ::"l"(p), "r"(a), "r"(b), "r"(c), "r"(d), "n"(OFF * 16) : "memory");
}
__device__ __forceinline__ uint32_t pack2(float lo, float hi) {
    uint32_t r;
    asm("cvt.rn.bf16x2.f32 %0, %1, %2;" : "=r"(r) : "f"(hi), "f"(lo));
    return r;
}
__device__ __forceinline__ float bf_lo(uint32_t w) { return __uint_as_float(w << 16); }
__device__ __forceinline__ float bf_hi(uint32_t w) { return __uint_as_float(w & 0xffff0000u); }
__device__ __forceinline__ uint32_t settag(uint32_t w, uint32_t tag) { return (w & ~1u) | tag; }
__device__ __forceinline__ float ex2(float x) { float y; asm("ex2.approx.ftz.f32 %0, %1;" : "=f"(y) : "f"(x)); return y; }
__device__ __forceinline__ float rcp(float x) { float y; asm("rcp.approx.ftz.f32 %0, %1;" : "=f"(y) : "f"(x)); return y; }
__device__ __forceinline__ float tanh_hw(float x) { float y; asm("tanh.approx.f32 %0, %1;" : "=f"(y) : "f"(x)); return y; }
__device__ __forceinline__ void stsm4(uint32_t addr, uint32_t a, uint32_t b, uint32_t c, uint32_t d) {
    asm volatile("stmatrix.sync.aligned.m8n8.x4.shared.b16 [%0], {%1,%2,%3,%4};" ::"r"(addr), "r"(a), "r"(b), "r"(c), "r"(d) : "memory");
}
__device__ __forceinline__ void fence_async() { asm volatile("fence.proxy.async.shared::cta;" ::: "memory"); }
__device__ __forceinline__ void bar_sync(int id, int n) { asm volatile("bar.sync %0, %1;" ::"r"(id), "r"(n) : "memory"); }
__device__ __forceinline__ void bar_arrive(int id, int n) { asm volatile("bar.arrive %0, %1;" ::"r"(id), "r"(n) : "memory"); }
__device__ __forceinline__ void wg_fence() { asm volatile("wgmma.fence.sync.aligned;" ::: "memory"); }
__device__ __forceinline__ void wg_commit() { asm volatile("wgmma.commit_group.sync.aligned;" ::: "memory"); }
template <int N> __device__ __forceinline__ void wg_wait() { asm volatile("wgmma.wait_group.sync.aligned %0;" ::"n"(N) : "memory"); }

constexpr uint32_t SB0 = 1024;
__host__ __device__ constexpr uint32_t dlo(uint32_t off, uint32_t lbo) { return ((SB0 + off) >> 4) | ((lbo >> 4) << 16); }
__host__ __device__ constexpr uint32_t dhi(uint32_t sbo, uint32_t sw) { return (sbo >> 4) | (sw << 30); }
__device__ __forceinline__ uint64_t dbase(uint32_t lo, uint32_t hi) { uint64_t d; asm volatile("mov.b64 %0, {%1, %2};" : "=l"(d) : "r"(lo), "r"(hi)); return d; }
#define BASE128(off, lbo, adj) dbase(dlo(off, lbo) + (adj), dhi(1024, 1))
#define BASE64(off, lbo, adj) dbase(dlo(off, lbo) + (adj), dhi(512, 2))

#define ACC4(d, o) "+f"(d[o]), "+f"(d[o + 1]), "+f"(d[o + 2]), "+f"(d[o + 3])
#define ACC28(d) ACC4(d, 0), ACC4(d, 4), ACC4(d, 8), ACC4(d, 12), ACC4(d, 16), ACC4(d, 20), ACC4(d, 24)
#define ACC32(d, o) ACC4(d, o), ACC4(d, o + 4), ACC4(d, o + 8), ACC4(d, o + 12), ACC4(d, o + 16), ACC4(d, o + 20), ACC4(d, o + 24), ACC4(d, o + 28)

template <int TB, uint64_t D>
__device__ __forceinline__ void mma_rs56(float* d, uint32_t a0, uint32_t a1, uint32_t a2, uint32_t a3, int sd, uint64_t base) {
    asm volatile("{ .reg .pred p; .reg .b64 db; setp.ne.b32 p, %32, 0; add.u64 db, %33, %34;\n"
                 "wgmma.mma_async.sync.aligned.m64n56k16.f32.bf16.bf16 "
                 "{%0,%1,%2,%3,%4,%5,%6,%7,%8,%9,%10,%11,%12,%13,%14,%15,%16,%17,%18,%19,%20,%21,%22,%23,%24,%25,%26,%27}, "
                 "{%28,%29,%30,%31}, db, p, 1, 1, %35; }\n"
                 : ACC28(d)
                 : "r"(a0), "r"(a1), "r"(a2), "r"(a3), "r"(sd), "l"(base), "n"(D), "n"(TB));
}
template <int TB, uint64_t D>
__device__ __forceinline__ void mma_rs64(float* d, uint32_t a0, uint32_t a1, uint32_t a2, uint32_t a3, int sd, uint64_t base) {
    asm volatile("{ .reg .pred p; .reg .b64 db; setp.ne.b32 p, %36, 0; add.u64 db, %37, %38;\n"
                 "wgmma.mma_async.sync.aligned.m64n64k16.f32.bf16.bf16 "
                 "{%0,%1,%2,%3,%4,%5,%6,%7,%8,%9,%10,%11,%12,%13,%14,%15,%16,%17,%18,%19,%20,%21,%22,%23,%24,%25,%26,%27,%28,%29,%30,%31}, "
                 "{%32,%33,%34,%35}, db, p, 1, 1, %39; }\n"
                 : ACC32(d, 0)
                 : "r"(a0), "r"(a1), "r"(a2), "r"(a3), "r"(sd), "l"(base), "n"(D), "n"(TB));
}
template <int TB, uint64_t D>
__device__ __forceinline__ void mma_rs128(float* d, uint32_t a0, uint32_t a1, uint32_t a2, uint32_t a3, int sd, uint64_t base) {
    asm volatile("{ .reg .pred p; .reg .b64 db; setp.ne.b32 p, %68, 0; add.u64 db, %69, %70;\n"
                 "wgmma.mma_async.sync.aligned.m64n128k16.f32.bf16.bf16 "
                 "{%0,%1,%2,%3,%4,%5,%6,%7,%8,%9,%10,%11,%12,%13,%14,%15,%16,%17,%18,%19,%20,%21,%22,%23,%24,%25,%26,%27,%28,%29,%30,%31,%32,%33,%34,%35,%36,%37,%38,%39,%40,%41,%42,%43,%44,%45,%46,%47,%48,%49,%50,%51,%52,%53,%54,%55,%56,%57,%58,%59,%60,%61,%62,%63}, "
                 "{%64,%65,%66,%67}, db, p, 1, 1, %71; }\n"
                 : ACC32(d, 0), ACC32(d, 32)
                 : "r"(a0), "r"(a1), "r"(a2), "r"(a3), "r"(sd), "l"(base), "n"(D), "n"(TB));
}
template <uint64_t DA, uint64_t DB>
__device__ __forceinline__ void mma_ss56_tt(float* d, int sd, uint64_t ba, uint64_t bb) {
    asm volatile("{ .reg .pred p; .reg .b64 da, db; setp.ne.b32 p, %28, 0; add.u64 da, %29, %31; add.u64 db, %30, %32;\n"
                 "wgmma.mma_async.sync.aligned.m64n56k16.f32.bf16.bf16 "
                 "{%0,%1,%2,%3,%4,%5,%6,%7,%8,%9,%10,%11,%12,%13,%14,%15,%16,%17,%18,%19,%20,%21,%22,%23,%24,%25,%26,%27}, "
                 "da, db, p, 1, 1, 1, 1; }\n"
                 : ACC28(d)
                 : "r"(sd), "l"(ba), "l"(bb), "n"(DA), "n"(DB));
}
template <int... I> struct Seq {};
template <class F, int... I> __device__ __forceinline__ void static_for_impl(F&& f, Seq<I...>) { (f(std::integral_constant<int, I>{}), ...); }
#define FOR7(...) static_for_impl([&](auto T_) { constexpr int t = decltype(T_)::value; __VA_ARGS__; }, Seq<0, 1, 2, 3, 4, 5, 6>{})
#define FOR8(...) static_for_impl([&](auto T_) { constexpr int t = decltype(T_)::value; __VA_ARGS__; }, Seq<0, 1, 2, 3, 4, 5, 6, 7>{})
#define FOR14(...) static_for_impl([&](auto T_) { constexpr int t = decltype(T_)::value; __VA_ARGS__; }, Seq<0, 1, 2, 3, 4, 5, 6, 7, 8, 9, 10, 11, 12, 13>{})

__device__ __forceinline__ int kblk(int p, int b) { return b == 0 ? p : b - (b <= p); }
__host__ __device__ constexpr int krow(int t) { return t < 3 ? 16 * t : (t < 6 ? 56 + 16 * (t - 3) : 48); }
#define AQ(A, b, t) ((t) < 3 ? A[2 * (b)][4 * (t)] : (t) < 6 ? A[2 * (b) + 1][4 * ((t) - 3)] : A[2 * (b)][12]), \
                    ((t) < 3 ? A[2 * (b)][4 * (t) + 1] : (t) < 6 ? A[2 * (b) + 1][4 * ((t) - 3) + 1] : A[2 * (b)][13]), \
                    ((t) < 3 ? A[2 * (b)][4 * (t) + 2] : (t) < 6 ? A[2 * (b) + 1][4 * ((t) - 3) + 2] : A[2 * (b) + 1][12]), \
                    ((t) < 3 ? A[2 * (b)][4 * (t) + 3] : (t) < 6 ? A[2 * (b) + 1][4 * ((t) - 3) + 3] : A[2 * (b) + 1][13])
#define D128(off, t) ((uint64_t)(((off) + krow(t) * 128) >> 4) + ((uint64_t)((t) == 6 ? (7168 - 1024) >> 4 : 0) << 32))
#define D64(off, t) ((uint64_t)(((off) + krow(t) * 64) >> 4) + ((uint64_t)((t) == 6 ? (3584 - 512) >> 4 : 0) << 32))

#define PL(k) (((k) - 3) * PLANE)
__device__ __forceinline__ void st_word(uint32_t* p, uint32_t v) { asm volatile("st.relaxed.gpu.global.u32 [%0], %1;" ::"l"(p), "r"(v) : "memory"); }
__device__ __forceinline__ uint32_t ld_word(const uint32_t* p) { uint32_t v; asm volatile("ld.relaxed.gpu.global.u32 %0, [%1];" : "=r"(v) : "l"(p) : "memory"); return v; }
__device__ __forceinline__ void tag_slice(uint32_t* w, uint32_t tag) { w[0] = settag(w[0], tag); w[4] = settag(w[4], tag); w[8] = settag(w[8], tag); w[12] = settag(w[12], tag); }
template <int O>
__device__ __forceinline__ void send_slice(uint4* dst, int lane, const uint32_t* w) {
    st_pkt<O>(dst, w[0], w[1], w[2], w[3]);
    st_pkt<O + 32>(dst, w[4], w[5], w[6], w[7]);
    st_pkt<O + 64>(dst, w[8], w[9], w[10], w[11]);
    asm volatile("{ .reg .b64 t; mov.b64 t, {%1,%2}; st.relaxed.gpu.global.b64 [%0+%3], t; }" ::"l"((char*)dst - lane * 8), "r"(w[12]), "r"(w[13]), "n"(16 * (O + 96)) : "memory");
}
#define RW4(v, o) "+r"(v[o]), "+r"(v[(o) + 1]), "+r"(v[(o) + 2]), "+r"(v[(o) + 3])
#define RW2(v, o) "+r"(v[o]), "+r"(v[(o) + 1])
#define WR4(v, o) "=&r"(v[o]), "=&r"(v[(o) + 1]), "=&r"(v[(o) + 2]), "=&r"(v[(o) + 3])
#define LDP(a, b, c, d, addr, off) "ld.relaxed.gpu.global.b128 q, [" addr "+" off "];\n mov.b128 {" a "," b "," c "," d "}, q;\n"
#define LDH(a, b, addr, off) "ld.relaxed.gpu.global.b64 h, [" addr "+" off "];\n mov.b64 {" a "," b "}, h;\n"
#define VOTE_OK "and.b32 t, t, 1;\n setp.ne.u32 p, t, 0;\n vote.sync.any.pred p, p, 0xffffffff;\n @!p bra.uni DN;\n"
#define CHK(x, tag) "lop3.b32 t, " x ", " tag ", t, 0xBE;\n"
__device__ __forceinline__ void check_cnt(uint32_t v, const uint32_t* p, uint32_t target) {
    asm volatile("{ .reg .pred p; .reg .b32 n, t; mov.u32 n, 0; mov.u32 t, %2;\n LP:\n"
                 "sub.s32 t, t, %1;\n setp.lt.s32 p, t, 0;\n vote.sync.any.pred p, p, 0xffffffff;\n @!p bra.uni DN;\n ld.relaxed.gpu.global.u32 t, [%0];\n" SPIN_TAIL("7")
                 ::"l"(p), "r"(target), "r"(v) : "memory");
}
__device__ __forceinline__ void poll_cnt(const uint32_t* p, uint32_t target) {
    asm volatile("{ .reg .pred p; .reg .b32 n, t; mov.u32 n, 0;\n LP:\n"
                 "ld.relaxed.gpu.global.u32 t, [%0];\n sub.s32 t, t, %1;\n setp.lt.s32 p, t, 0;\n vote.sync.any.pred p, p, 0xffffffff;\n @!p bra.uni DN;\n" SPIN_TAIL("1")
                 ::"l"(p), "r"(target) : "memory");
}
template <int STR>
__device__ __forceinline__ void poll4_kv(uint32_t* v, const uint4* p, uint32_t tag) {
    asm volatile("{ .reg .pred p; .reg .b32 n, t; .reg .b128 q; mov.u32 n, 0;\n LP:\n"
                 LDP("%0", "%1", "%2", "%3", "%16", "0") LDP("%4", "%5", "%6", "%7", "%16", "%18")
                 LDP("%8", "%9", "%10", "%11", "%16", "%19") LDP("%12", "%13", "%14", "%15", "%16", "%20")
                 "xor.b32 t, %0, %17;\n" CHK("%4", "%17") CHK("%8", "%17") CHK("%12", "%17") VOTE_OK SPIN_TAIL("2")
                 : WR4(v, 0), WR4(v, 4), WR4(v, 8), WR4(v, 12)
                 : "l"(p), "r"(tag), "n"(16 * STR), "n"(32 * STR), "n"(48 * STR)
                 : "memory");
}
template <int B>
__device__ __forceinline__ void blk_load(uint32_t (&A)[8][14], const uint4* src, int lane) {
    ld_pkt<0>(&A[2 * B][0], src); ld_pkt<32>(&A[2 * B][4], src); ld_pkt<64>(&A[2 * B][8], src);
    ld_pkt<512>(&A[2 * B + 1][0], src); ld_pkt<544>(&A[2 * B + 1][4], src); ld_pkt<576>(&A[2 * B + 1][8], src);
    asm volatile("{ .reg .b64 h;\n" LDH("%0", "%1", "%4", "1536") LDH("%2", "%3", "%4", "9728") "}"
                 : "=&r"(A[2 * B][12]), "=&r"(A[2 * B][13]), "=&r"(A[2 * B + 1][12]), "=&r"(A[2 * B + 1][13])
                 : "l"((const char*)src - lane * 8) : "memory");
}
template <int B>
__device__ __forceinline__ void blk_check(uint32_t (&A)[8][14], const uint4* src, int lane, uint32_t tag) {
    asm volatile("{ .reg .pred p; .reg .b32 n, t; .reg .b128 q; .reg .b64 h, a8; mov.u32 n, 0;\n LP:\n"
                 "xor.b32 t, %0, %30;\n" CHK("%4", "%30") CHK("%8", "%30") CHK("%12", "%30") CHK("%16", "%30") CHK("%20", "%30") CHK("%24", "%30") CHK("%26", "%30") VOTE_OK
                 LDP("%0", "%1", "%2", "%3", "%28", "0") LDP("%4", "%5", "%6", "%7", "%28", "512") LDP("%8", "%9", "%10", "%11", "%28", "1024")
                 LDP("%12", "%13", "%14", "%15", "%28", "8192") LDP("%16", "%17", "%18", "%19", "%28", "8704") LDP("%20", "%21", "%22", "%23", "%28", "9216")
                 "mad.wide.s32 a8, %29, -8, %28;\n" LDH("%24", "%25", "a8", "1536") LDH("%26", "%27", "a8", "9728") SPIN_TAIL("3")
                 "\n and.b32 %0, %0, -2; and.b32 %4, %4, -2; and.b32 %8, %8, -2; and.b32 %12, %12, -2; and.b32 %16, %16, -2; and.b32 %20, %20, -2; and.b32 %24, %24, -2; and.b32 %26, %26, -2;"
                 : RW4(A[2 * B], 0), RW4(A[2 * B], 4), RW4(A[2 * B], 8), RW4(A[2 * B + 1], 0), RW4(A[2 * B + 1], 4), RW4(A[2 * B + 1], 8),
                   RW2(A[2 * B], 12), RW2(A[2 * B + 1], 12)
                 : "l"(src), "r"(lane), "r"(tag)
                 : "memory");
}
__device__ __forceinline__ void st_async4(uint32_t a, uint32_t x, uint32_t y, uint32_t z, uint32_t w, uint32_t bar) {
    asm volatile("st.async.weak.shared::cluster.mbarrier::complete_tx::bytes.v4.b32 [%0], {%1,%2,%3,%4}, [%5];" ::"r"(a), "r"(x), "r"(y), "r"(z), "r"(w), "r"(bar) : "memory");
}
__device__ __forceinline__ uint32_t mapa(uint32_t a, uint32_t cta) { uint32_t r; asm("mapa.shared::cluster.u32 %0, %1, %2;" : "=r"(r) : "r"(a), "r"(cta)); return r; }
__device__ __forceinline__ void stat_load(uint32_t* v, const uint4* p) { ld_pkt<0>(v, p); ld_pkt<512>(v + 4, p); }
__device__ __forceinline__ void stat_check(uint32_t* v, const uint4* p, uint32_t tag) {
    asm volatile("{ .reg .pred p; .reg .b32 n, t; .reg .b128 q; mov.u32 n, 0;\n LP:\n"
                 "xor.b32 t, %3, %9;\n" CHK("%7", "%9") VOTE_OK
                 LDP("%0", "%1", "%2", "%3", "%8", "0") LDP("%4", "%5", "%6", "%7", "%8", "8192") SPIN_TAIL("4")
                 : RW4(v, 0), RW4(v, 4) : "l"(p), "r"(tag) : "memory");
}
__device__ __forceinline__ uint32_t x_bits(const uint32_t* X) {
    uint32_t r;
    asm volatile("{ .reg .b32 a, b; prmt.b32 a, %1, %2, 0x0040; prmt.b32 b, %3, %4, 0x0040; prmt.b32 %0, a, b, 0x5410; }" : "=r"(r) : "r"(X[0]), "r"(X[4]), "r"(X[8]), "r"(X[12]));
    return r;
}
template <int O>
__device__ __forceinline__ void slice_load(uint32_t* v, const uint4* p, int lane) {
    ld_pkt<O>(v, p); ld_pkt<O + 32>(v + 4, p); ld_pkt<O + 64>(v + 8, p);
    asm volatile("{ .reg .b64 h;\n" LDH("%0", "%1", "%2", "%3") "}" : "=r"(v[12]), "=r"(v[13]) : "l"((const char*)p - lane * 8), "n"(16 * (O + 96)) : "memory");
}
template <int O>
__device__ __forceinline__ void slice_check(uint32_t* v, const uint4* p, int lane, uint32_t tag) {
    asm volatile("{ .reg .pred p; .reg .b32 n, t; .reg .b128 q; .reg .b64 h; mov.u32 n, 0;\n LP:\n"
                 "xor.b32 t, %0, %16;\n" CHK("%4", "%16") CHK("%8", "%16") CHK("%12", "%16") VOTE_OK
                 LDP("%0", "%1", "%2", "%3", "%14", "%17") LDP("%4", "%5", "%6", "%7", "%14", "%18") LDP("%8", "%9", "%10", "%11", "%14", "%19")
                 LDH("%12", "%13", "%15", "%20") SPIN_TAIL("5")
                 : RW4(v, 0), RW4(v, 4), RW4(v, 8), RW2(v, 12)
                 : "l"(p), "l"((const char*)p - lane * 8), "r"(tag), "n"(16 * O), "n"(16 * (O + 32)), "n"(16 * (O + 64)), "n"(16 * (O + 96))
                 : "memory");
}
__device__ __forceinline__ void x_fix(uint32_t* X, uint32_t bits) {
    X[0] = __byte_perm(X[0], bits, 0x3214); X[4] = __byte_perm(X[4], bits, 0x3215); X[8] = __byte_perm(X[8], bits, 0x3216); X[12] = __byte_perm(X[12], bits, 0x3217);
}
__device__ __forceinline__ void sts4(uint32_t a, uint32_t x, uint32_t y, uint32_t z, uint32_t w) {
    asm volatile("st.shared.v4.u32 [%0], {%1,%2,%3,%4};" ::"r"(a), "r"(x), "r"(y), "r"(z), "r"(w) : "memory");
}
__device__ __forceinline__ void lds4(uint32_t* v, uint32_t a) {
    asm volatile("ld.shared.v4.u32 {%0,%1,%2,%3}, [%4];" : "=r"(v[0]), "=r"(v[1]), "=r"(v[2]), "=r"(v[3]) : "r"(a) : "memory");
}
struct LnCoef { uint32_t hi, lo, sh; };
__device__ __forceinline__ LnCoef ln_coef(float sum, float sq) {
    sum += __shfl_xor_sync(0xffffffffu, sum, 1); sq += __shfl_xor_sync(0xffffffffu, sq, 1);
    sum += __shfl_xor_sync(0xffffffffu, sum, 2); sq += __shfl_xor_sync(0xffffffffu, sq, 2);
    const float mean = sum * (1.f / 448.f);
    const float var = fmaxf(fmaf(-mean, mean, sq * (1.f / 448.f)), 0.f);
    const float sc = rsqrtf(var + 1e-5f);
    LnCoef r;
    r.hi = pack2(sc, sc);
    const float lo = sc - bf_lo(r.hi), sh = -mean * sc;
    r.lo = pack2(lo, lo);
    r.sh = pack2(sh, sh);
    return r;
}
template <int B>
__device__ __forceinline__ void normalize(uint32_t (&A)[8][14], const LnCoef& c0, const LnCoef& c1) {
#pragma unroll
    for (int s = 2 * B; s < 2 * B + 2; s++)
#pragma unroll
        for (int i = 0; i < 14; i++) {
            const LnCoef& k = (i & 1) ? c1 : c0;
            asm("{ .reg .b32 t; fma.rn.bf16x2 t, %0, %2, %3; fma.rn.bf16x2 %0, %0, %1, t; }" : "+r"(A[s][i]) : "r"(k.hi), "r"(k.lo), "r"(k.sh));
        }
}
__device__ __forceinline__ void slice_stats(const uint32_t* w, float* st) {
    float a = 0.f, b = 0.f, p = 0.f, q = 0.f;
#pragma unroll
    for (int i = 0; i < 7; i++) {
        const float e0 = bf_lo(w[2 * i]), e1 = bf_hi(w[2 * i]), e2 = bf_lo(w[2 * i + 1]), e3 = bf_hi(w[2 * i + 1]);
        a += e0 + e1; b += e2 + e3;
        p = fmaf(e0, e0, p); p = fmaf(e1, e1, p); q = fmaf(e2, e2, q); q = fmaf(e3, e3, q);
    }
    a += __shfl_xor_sync(0xffffffffu, a, 1); p += __shfl_xor_sync(0xffffffffu, p, 1); b += __shfl_xor_sync(0xffffffffu, b, 1); q += __shfl_xor_sync(0xffffffffu, q, 1);
    a += __shfl_xor_sync(0xffffffffu, a, 2); p += __shfl_xor_sync(0xffffffffu, p, 2); b += __shfl_xor_sync(0xffffffffu, b, 2); q += __shfl_xor_sync(0xffffffffu, q, 2);
    st[0] = a; st[1] = p; st[2] = b; st[3] = q;
}
__device__ __forceinline__ void dual_softmax(const float* p, uint32_t* out) {
    constexpr float L = 1.4426950408889634f;
#pragma unroll
    for (int r = 0; r < 2; r++) {
        float mx = fmaxf(p[2 * r], p[2 * r + 1]), mn = fminf(p[2 * r], p[2 * r + 1]);
#pragma unroll
        for (int i = 1; i < 7; i++) {
            mx = fmaxf(mx, fmaxf(p[4 * i + 2 * r], p[4 * i + 2 * r + 1]));
            mn = fminf(mn, fminf(p[4 * i + 2 * r], p[4 * i + 2 * r + 1]));
        }
        mx = fmaxf(mx, __shfl_xor_sync(0xffffffffu, mx, 1));
        mn = fminf(mn, __shfl_xor_sync(0xffffffffu, mn, 1));
        const float bx = -mx * L, bn = mn * L;
        float ep[14], en[14], sp = 0.f, sn = 0.f;
#pragma unroll
        for (int i = 0; i < 14; i++) {
            const float v = p[4 * (i >> 1) + 2 * r + (i & 1)];
            ep[i] = ex2(fmaf(v, L, bx));
            en[i] = ex2(fmaf(v, -L, bn));
            sp += ep[i]; sn += en[i];
        }
        sp += __shfl_xor_sync(0xffffffffu, sp, 1);
        sn += __shfl_xor_sync(0xffffffffu, sn, 1);
        const float ip = rcp(sp), in = rcp(sn);
#pragma unroll
        for (int i = 0; i < 7; i++) {
            out[4 * i + r] = pack2(ep[2 * i] * ip, ep[2 * i + 1] * ip);
            out[4 * i + 2 + r] = pack2(en[2 * i] * in, en[2 * i + 1] * in);
        }
    }
}
__device__ __forceinline__ float geglu(float g, float u) {
    const float t = tanh_hw(g * fmaf(g * g, 0.7978845608028654f * 0.044715f, 0.7978845608028654f));
    const float gu = g * u;
    return fmaf(t, gu, gu);
}
__device__ __forceinline__ void phi_gemm(const float* t, float* p) {
    uint32_t w[14];
#pragma unroll
    for (int i = 0; i < 14; i++) w[i] = pack2(t[2 * i], t[2 * i + 1]);
    const uint64_t db = BASE128(OFF_WPHI, 16, 0);
    wg_fence();
    mma_rs56<0, 0>(p, w[0], w[1], w[2], w[3], 0, db);
    mma_rs56<0, 2>(p, w[4], w[5], w[6], w[7], 1, db);
    mma_rs56<0, 4>(p, w[8], w[9], w[10], w[11], 1, db);
    mma_rs56<0, 6>(p, w[12], w[13], 0u, 0u, 1, db);
    wg_commit();
    wg_wait<0>();
}

}

#define BAR(i) (bars + 8 * (i))
#define R_WAIT() mbar_wait(BAR(slot), ph)
#define WSUM(i)
#define R_ADJ (slot * (STAGE >> 4))
#define R_NEXT() do { eb2 = eb1; eb1 = BAR(B_EMPTY + slot); if (++slot == NST) { slot = 0; ph ^= 1; } } while (0)
#define R_RELEASE(k) do { if (lane == 0) mbar_arrive((k) == 1 ? eb1 : eb2); } while (0)
#define PUSH_BEGIN() do { mbar_wait(BAR(B_ACK + wgi), ackph); ackph ^= 1; } while (0)
#define PUSH_ACK() do { __syncwarp(); if (lane == 0) asm volatile("mbarrier.arrive.shared::cluster.b64 _, [%0];" ::"r"(mapa(BAR(B_ACK + wgi), hr ^ 1)) : "memory"); } while (0)

__global__ void __cluster_dims__(2, 1, 1) __launch_bounds__(384, 1)
fused_kernel(Scratch* const sc, const __nv_bfloat16* __restrict__ x_in, const __nv_bfloat16* __restrict__ w_phi, const int trips,
             const __nv_bfloat16* __restrict__ wg, const __nv_bfloat16* __restrict__ wu, const __nv_bfloat16* __restrict__ wd,
             const __grid_constant__ Maps maps) {
    extern __shared__ __align__(1024) unsigned char smem_raw[];
    const uint32_t sb = s2u(smem_raw);
    const uint32_t bars = sb + OFF_BAR;
    const int wgi = __shfl_sync(0xffffffffu, threadIdx.x >> 7, 0);
    const int hr = blockIdx.x & 1, ck = blockIdx.x >> 1;
    const int gp = (ck - 4) & 7, q7 = ((ck - 36) * 37) >> 8;
    const int pr = __shfl_sync(0xffffffffu, ck < 4 ? ck : (ck < 36 ? (ck - 4) >> 3 : q7), 0);
    const int tile = __shfl_sync(0xffffffffu, ck < 4 ? 0 : (ck < 36 ? (gp ? 2 * gp : 1) : 2 * (ck - 36 - 7 * q7) + 3), 0);
    const int sl = 2 * pr + hr;
    STAMP(0);
    GSTAMP(60);
    if (threadIdx.x == 256) {
#pragma unroll
        for (int i = 0; i < NST; i++) mbar_init(BAR(i), 1);
        asm volatile("fence.mbarrier_init.release.cluster;" ::: "memory");
    }
    if (threadIdx.x == 288) {
        if ((sb & 0x3FFFF) != SB0) asm volatile("trap;");
#pragma unroll
        for (int i = NST; i < B_COUNT; i++) mbar_init(BAR(i), i >= B_ACK ? 4 : (i < B_RECV || i == B_LATE ? 8 : 1));
        asm volatile("fence.mbarrier_init.release.cluster;" ::: "memory");
    }
    __syncwarp();
    asm volatile("barrier.cluster.arrive.relaxed.aligned;" ::: "memory");

    if (wgi == 2) {
        asm volatile("setmaxnreg.dec.sync.aligned.u32 40;");
        const int t128 = fresh_tid() & 127, w = __shfl_sync(0xffffffffu, t128 >> 5, 0), lane = t128 & 31;
        uint32_t e0[2] = {0, 0}, e1[2] = {0, 0}, cw_target = 0, kseq;
        if (w == 0) {
#pragma unroll 1
            for (int n = 0; n < NST; n++) {
                const uint32_t dst = sb + n * STAGE, fb = BAR(n);
                asm volatile(ELECT "mbarrier.arrive.expect_tx.shared::cta.b64 _, [%0], %1; }" ::"r"(fb), "r"(n < 2 ? 2 * STAGE : STAGE) : "memory");
                if (n < 2) {
                    tma3x(sb + OFF_H + n * STAGE, &maps.x, tile * 128 + n * 64, fb);
                    tma3x(dst, &maps.x, tile * 128 + n * 64 + 32, fb);
                } else {
                    if (n == 3) mbar_wait(BAR(1), 0);
                    const int c0 = (n < 4 ? 448 : 896) + 56 * sl, r0 = 224 * (n & 1);
                    tma2d(dst, &maps.qkv, c0, r0, fb);
                    tma2d(dst + HALF, &maps.qkv, c0, r0 + 112, fb);
                }
            }
            asm volatile("barrier.cluster.wait.aligned;" ::: "memory");
            kseq = ld_word(g_c1 + (sl * 8 * 16 + tile) * 32);
            cw_target = (ld_word(g_cw + sl * 32) & ~15u) + 16;
#pragma unroll 1
            for (int k = 0; k < 2; k++) {
                const int n = t128 + 32 * k;
                int m = n - 2 - (n > PACK);
                const bool packed = m >= 30 ? (m < 38 || m >= 52) : m >= 22;
                if (m >= 30) m -= 30;
                if (n == PACK) m = tile < 8 ? tile : tile + 14;
                const int rot = n < 8 ? 0 : pr;
                const int ra = 112 * kblk(rot, m & 3), rb = 112 * kblk(rot, 2 * m & 3), rc = 112 * kblk(rot, (2 * m + 1) & 3);
                int kind = 0, m0, m1, c0, c1, r0, r1;
                if (m < 8) { m0 = m1 = m < 6 ? 1 : 2; c0 = c1 = (m < 2 ? 448 : (m < 4 ? 896 : 0)) + 56 * sl; r0 = rb; r1 = rc; }
                else if (m < 20) { m0 = 3; m1 = 4; c0 = c1 = 224 * sl + 32 * hr + 64 * ((m - 8) >> 2); r0 = r1 = ra; }
                else if (m < 22) { kind = 2; m0 = 5; m1 = 6; c0 = c1 = 224 * sl + (hr ? 0 : 192); r0 = rb; r1 = rc; }
                else { m0 = m1 = 7; c0 = c1 = 56 * (2 * ((pr + (m >> 1) - 10) & 3) + hr); r0 = 224 * (sl ^ (m & 1)); r1 = r0 + 112; }
                if (packed) { kind = 1; r0 = sl * 16 + (m < 8 ? m : m - 14); r1 = 0; }
                e0[0] = e0[1]; e1[0] = e1[1];
                e0[1] = kind | (m0 << 2) | (m1 << 6) | (c0 << 10) | (c1 << 21);
                e1[1] = r0 | (r1 << 16);
            }
        } else {
            const int j = t128 - 32;
            kseq = ld_word(g_c1 + (sl * 8 * 16 + tile) * 32);
            asm volatile("barrier.cluster.wait.aligned;" ::: "memory");
            uint2 wv[7];
            const int k = j < 56 ? j : 55, hh = k >= 28;
#pragma unroll
            for (int i = 0; i < 7; i++) wv[i] = __ldg(reinterpret_cast<const uint2*>(w_phi + (sl * 56 + k) * 28) + i);
#pragma unroll 1
            for (int i = j; i < 7168 / 16; i += 96) sts4(sb + OFF_WPHI + i * 16, 0, 0, 0, 0);
            bar_sync(5, 96);
            if (j < 56) {
                uint32_t a4[4];
#pragma unroll
                for (int q = 0; q < 4; q++) a4[q] = sb + OFF_WPHI + (4 * hh + q) * 128 + ((((k >> 3) ^ (4 * hh + q)) & 7) << 4) + (k & 7) * 2;
                FOR14(const uint32_t v = (t & 1) ? wv[t >> 1].y : wv[t >> 1].x;
                      asm volatile("{ .reg .b16 l, h; mov.b32 {l, h}, %2; st.shared.u16 [%0+%3], l; st.shared.u16 [%1+%3], h; }"
                                   ::"r"(a4[t >= 7 ? 2 : 0]), "r"(a4[t >= 7 ? 3 : 1]), "r"(v), "n"((t % 7) * 1024) : "memory"));
            }
            __syncwarp();
            fence_async();
            kseq = __shfl_sync(0xffffffffu, kseq, 0);
            bar_arrive(1, 224);
            bar_arrive(9, 224);
        }
        kseq = __shfl_sync(0xffffffffu, kseq, 0);
        int slot = 0, ph = 0, n = NST;
#pragma unroll 1
        for (int layer = 0; layer < 3; layer++) {
            if (w == 0) {
                const int nend = layer == 0 ? 11 : (layer == 1 ? 42 : 63);
#pragma unroll 1
                for (; n < nend; n++) {
                const uint32_t w0 = __shfl_sync(0xffffffffu, n < 32 ? e0[0] : e0[1], n & 31), w1 = __shfl_sync(0xffffffffu, n < 32 ? e1[0] : e1[1], n & 31);
                const uint32_t dst = sb + slot * STAGE, fb = BAR(n == PACK ? B_PACK : slot);
                const CUtensorMap* m0 = &maps.x + ((w0 >> 2) & 15);
                const CUtensorMap* m1 = &maps.x + ((w0 >> 6) & 15);
                const int c0 = (w0 >> 10) & 2047, c1 = w0 >> 21, r0 = w1 & 0xffff, r1 = w1 >> 16;
                if (n == 25) {
                    int it = 0;
                    uint32_t v;
                    do { asm volatile("ld.acquire.gpu.global.u32 %0, [%1];" : "=r"(v) : "l"(g_cw + sl * 32) : "memory"); } while ((int)(v - cw_target) < 0 && ++it < 0x400000);
                    asm volatile("fence.proxy.async.global;" ::: "memory");
                    __syncwarp();
                }
                mbar_wait(BAR(B_EMPTY + slot), ph);
                __syncwarp();
                asm volatile(ELECT "mbarrier.arrive.expect_tx.shared::cta.b64 _, [%0], %1; }" ::"r"(fb), "r"(STAGE) : "memory");
                if ((w0 & 3) == 0) {
                    tma2d(dst, m0, c0, r0, fb);
                    tma2d(dst + HALF, m1, c1, r1, fb);
                } else if (w0 & 1) {
                    asm volatile(ELECT "cp.async.bulk.shared::cluster.global.mbarrier::complete_tx::bytes [%0], [%1], %2, [%3]; }"
                                 ::"r"(dst), "l"(reinterpret_cast<const char*>(g_wp) + (size_t)r0 * STAGE), "r"(STAGE), "r"(fb) : "memory");
                } else {
                    tma2d(dst, m0, c0, r0, fb); tma2d(dst + 7168, m0, c0, r1, fb);
                    tma2d(dst + HALF, m1, c0, r0, fb); tma2d(dst + HALF + 7168, m1, c0, r1, fb);
                }
                if (n == PFN) {
                    const int b = blockIdx.x;
                    asm volatile(ELECT "cp.async.bulk.prefetch.L2.global [%0], %1; }" ::"l"(wg + b * 6272), "r"(12544) : "memory");
                    asm volatile(ELECT "cp.async.bulk.prefetch.L2.global [%0], %1; }" ::"l"(wu + b * 6272), "r"(12544) : "memory");
                    asm volatile(ELECT "cp.async.bulk.prefetch.L2.global [%0], %1; }" ::"l"(wd + b * 6272), "r"(12544) : "memory");
                }
                if (n == PACK) asm volatile(ELECT "mbarrier.arrive.shared::cta.b64 _, [%0]; }" ::"r"(BAR(slot)) : "memory");
                if (++slot == NST) { slot = 0; ph ^= 1; }
                }
            } else if (w == 1 && layer == 1) {
                constexpr int ps = PACK % NST;
                mbar_wait(BAR(B_PACK), 0);
                asm volatile("{ .reg .pred e; elect.sync _|e, 0xffffffff;\n"
                             "@e cp.async.bulk.global.shared::cta.bulk_group [%0], [%1], %2;\n"
                             "@e cp.async.bulk.commit_group;\n"
                             "@e cp.async.bulk.wait_group.read 0;\n"
                             "@e mbarrier.arrive.shared::cta.b64 _, [%3], 8;\n"
                             "@e cp.async.bulk.wait_group 0;\n"
                             "@e fence.proxy.async.global;\n"
                             "@e red.release.gpu.global.add.u32 [%4], 1; }"
                             ::"l"(reinterpret_cast<char*>(g_wp) + (size_t)(sl * 16 + tile) * STAGE), "r"(sb + ps * STAGE), "r"(STAGE), "r"(BAR(B_EMPTY + ps)), "l"(g_cw + sl * 32) : "memory");
                __syncwarp();
            }
            if (layer < 2) {
            const uint32_t tag = layer ^ 1;
            kseq++;
            bar_sync(7, 384);
            ASTAMP(0);
            if (tile < 15) {
                const int sq = lane >> 3, pk = 8 * w + (lane & (tile == 14 ? 3 : 7));
                uint32_t v[16];
                if (layer == 0) poll_cnt(g_c1 + ((sl * 8 + (w >> 1) * 4 + (tile >> 2)) * 16 + (lane & 15)) * 32, kseq);
                ASTAMP(1);
                poll4_kv<32>(v, g_kv1 + ((sl * 16 + tile) * 16 + 4 * sq) * 32 + pk, tag);
#pragma unroll
                for (int k = 0; k < 4; k++) {
                    float lo = (bf_lo(v[k]) + bf_lo(v[4 + k])) + (bf_lo(v[8 + k]) + bf_lo(v[12 + k]));
                    float hi = (bf_hi(v[k]) + bf_hi(v[4 + k])) + (bf_hi(v[8 + k]) + bf_hi(v[12 + k]));
                    lo += __shfl_xor_sync(0xffffffffu, lo, 8); hi += __shfl_xor_sync(0xffffffffu, hi, 8);
                    lo += __shfl_xor_sync(0xffffffffu, lo, 16); hi += __shfl_xor_sync(0xffffffffu, hi, 16);
                    v[k] = pack2(lo, hi);
                }
                if (sq == 0) st_pkt<0>(g_kv2 + sl * 512 + 32 * tile + pk, settag(v[0], tag), v[1], v[2], v[3]);
            }
            ASTAMP(2);
            {
                const int item = t128 < 112 ? t128 : 112 + (t128 & 3), d = item >> 1;
                const int cc = t128 < 112 ? 2 * (d >= 28) + (item & 1) : item - 112;
                const int r = t128 < 112 ? d : 56 + (cc >> 1) + 2 * ((t128 - 112) >> 2);
                uint32_t ra = sb + OFF_KVB + r * 128 + 4 * cc, rx = (r & 7) << 4;
                asm volatile("" : "+r"(ra), "+r"(rx));
                FOR14(asm volatile("st.shared.u32 [%0+%2], %1;" ::"r"((ra ^ 8) + (((t & 7) << 4) ^ rx)), "r"(0), "n"((t >> 3) * 8192) : "memory"));
                uint32_t v[16];
                asm volatile("" : "+r"(ra), "+r"(rx));
                poll4_kv<8>(v, g_kv2 + sl * 512 + (item >> 3) * 32 + (item & 7), tag);
                FOR14(asm volatile("st.shared.u32 [%0+%2], %1;" ::"r"(ra + (((t & 7) << 4) ^ rx)), "r"(v[t < 7 ? t : t + 1]), "n"((t >> 3) * 8192) : "memory"));
                fence_async();
            }
            bar_arrive(3, 384);
            ASTAMP(3);
            }
        }
    } else {
        asm volatile("setmaxnreg.inc.sync.aligned.u32 232;");
        int lane = fresh_tid() & 31, prf = pr;
#define pr prf
#define g (lane >> 2)
#define c (lane & 3)
#define t128 (w * 32 + lane)
        const int wu = __shfl_sync(0xffffffffu, fresh_tid() >> 5, 0), w = wu & 3;
        const uint32_t xoff = __shfl_sync(0xffffffffu, (3 * PLANE + ((tile * 2 + wgi) * 8) * 512 + w * 128) * 16, 0);
        char* xu = reinterpret_cast<char*>(g_ex) + xoff;
#define FRESH() asm volatile("" : "+l"(xu), "+r"(lane), "+r"(prf))
#define xp0 (reinterpret_cast<uint4*>(xu) + lane)
        const uint32_t hbuf = sb + OFF_H + wgi * STAGE;
        uint32_t slot = 0, ph = 0, eb1 = 0, eb2 = 0, ackph = 0, rcvph = 0, gatph = 0, swp = 0;
        uint32_t ppid = 6;
#define cx(s) (reinterpret_cast<uint32_t*>(reinterpret_cast<uint4*>(xu) + PL(1) + 112 + (s) * 512))
#define stp (reinterpret_cast<uint4*>(xu) + g + PL(0) + 112)
        uint32_t seq = ld_word(cx(sl));
        uint32_t kseq = ld_word(g_c1 + ((sl * 8 + wu) * 16 + tile) * 32);
        uint32_t stag = ld_word(reinterpret_cast<const uint32_t*>(stp + sl * 512) + 3) & 1;
        asm volatile("barrier.cluster.wait.aligned;" ::: "memory");
        STAMP(1);
        uint32_t X[14];
        const uint32_t x0row = (w < 2 ? hbuf : sb + wgi * STAGE) + ((w & 1) * 16 + (lane & 15)) * 128;
        mbar_wait(BAR(wgi), 0);
        STAMP(51);
#pragma unroll
        for (int j = 0; j < 4; j++) {
            const int G = 7 * sl + min(2 * j + (lane >> 4), 6);
            uint32_t q2, q3;
            asm volatile("ldmatrix.sync.aligned.m8n8.x4.shared.b16 {%0,%1,%2,%3}, [%4];" : "=r"(X[4 * j]), "=r"(X[4 * j + 1]), "=r"(q2), "=r"(q3)
                         : "r"(x0row + (G >> 3) * 4096 + (((G ^ lane) & 7) << 4)) : "memory");
            if (j < 3) { X[(4 * j + 2) % 14] = q2; X[(4 * j + 3) % 14] = q3; }
        }
#define PUSH_SLICE(W)                                                                          \
    {                                                                                          \
        if (t128 == 0) mbar_expect_tx(BAR(B_RECV + wgi), 7168);                                \
        PUSH_BEGIN();                                                                          \
        const uint32_t ra = mapa(hbuf + 24576 + t128 * 16, hr ^ 1), rb = mapa(sb + OFF_XR + wgi * 3072, hr ^ 1), rbar = mapa(BAR(B_RECV + wgi), hr ^ 1); \
        st_async4(ra, W[0], W[1], W[2], W[3], rbar);                                           \
        st_async4(ra + 2048, W[4], W[5], W[6], W[7], rbar);                                    \
        st_async4(rb + t128 * 16, W[8], W[9], W[10], W[11], rbar);                             \
        asm volatile("st.async.weak.shared::cluster.mbarrier::complete_tx::bytes.v2.b32 [%0], {%1,%2}, [%3];" ::"r"(rb + 2048 + t128 * 8), "r"(W[12]), "r"(W[13]), "r"(rbar) : "memory"); \
    }
#define PULL_SLICE(W)                                                                          \
    {                                                                                          \
        uint32_t t0, t1;                                                                       \
        mbar_wait(BAR(B_RECV + wgi), rcvph);                                                   \
        rcvph ^= 1;                                                                            \
        lds4(&A[1][0], hbuf + 24576 + t128 * 16);                                              \
        lds4(&A[1][4], hbuf + 26624 + t128 * 16);                                              \
        lds4(&A[1][8], sb + OFF_XR + wgi * 3072 + t128 * 16);                                  \
        asm volatile("ld.shared.v2.u32 {%0,%1}, [%2];" : "=r"(t0), "=r"(t1) : "r"(sb + OFF_XR + wgi * 3072 + 2048 + t128 * 8) : "memory"); \
        _Pragma("unroll") for (int i = 0; i < 12; i++) A[0][i] = (i & 3) ? W[i] : W[i] & ~1u;  \
        A[1][0] &= ~1u; A[1][4] &= ~1u; A[1][8] &= ~1u;                                        \
        A[0][12] = (hr ? t0 : W[12]) & ~1u; A[0][13] = hr ? t1 : W[13];                        \
        A[1][12] = (hr ? W[12] : t0) & ~1u; A[1][13] = hr ? W[13] : t1;                        \
        asm volatile("" : RW4(A[0], 0), RW4(A[0], 4), RW4(A[0], 8), RW2(A[0], 12), RW4(A[1], 0), RW4(A[1], 4), RW4(A[1], 8), RW2(A[1], 12)); \
        swp = hr * 448;                                                                        \
    }
#define SWB(b, t, db, sh) ((b) == 0 && (t) < 6 ? ((t) < 3 ? db##p : db##m) : db)
#define DECL_DB(b, MK, lbo, sh) const uint64_t db = MK(0, lbo, R_ADJ), dbp = (b) == 0 ? MK(0, lbo, R_ADJ + (swp >> (sh))) : db, dbm = (b) == 0 ? MK(0, lbo, R_ADJ - (swp >> (sh))) : db;
#define PPB 2
#define PP_WAIT() if (wgi == 1) { bar_sync(ppid, 256); ppid ^= 14; }
#define PP_GO() if (wgi == 0) { bar_arrive(ppid, 256); ppid ^= 14; }
#define GAT_DST(B, s2) ((B) == 1 ? hbuf + w * 3584 + (s2) * 1792 : ((s2) ? sb + OFF_KVB + wgi * 8192 : hbuf + 14336) + w * 1792)
#define GAT_ISSUE(B, base)                                                                     \
    {                                                                                          \
        const char* gs = xu + ((base) + kblk(pr, B) * 1024) * 16;                              \
        asm volatile("{ .reg .pred e; elect.sync _|e, 0xffffffff;\n"                           \
                     "@e mbarrier.arrive.expect_tx.shared::cta.b64 _, [%3], 3584;\n"           \
                     "@e cp.async.bulk.shared::cluster.global.mbarrier::complete_tx::bytes [%0], [%2], 1792, [%3];\n" \
                     "@e cp.async.bulk.shared::cluster.global.mbarrier::complete_tx::bytes [%1], [%2+8192], 1792, [%3]; }" \
                     ::"r"(GAT_DST(B, 0)), "r"(GAT_DST(B, 1)), "l"(gs), "r"(BAR(B_GAT + wu * 2 + ((B) >> 1))) : "memory"); \
        __syncwarp();                                                                          \
    }
#define GAT_FETCH(B)                                                                           \
    {                                                                                          \
        mbar_wait(BAR(B_GAT + wu * 2 + ((B) >> 1)), (gatph >> (B)) & 1);                          \
        gatph ^= 1 << (B);                                                                     \
        _Pragma("unroll") for (int s2 = 0; s2 < 2; s2++) {                                     \
            const uint32_t ga = GAT_DST(B, s2) + lane * 16;                                    \
            lds4(&A[2 * (B) + s2][0], ga); lds4(&A[2 * (B) + s2][4], ga + 512); lds4(&A[2 * (B) + s2][8], ga + 1024); \
            asm volatile("ld.shared.v2.u32 {%0,%1}, [%2];" : "=r"(A[2 * (B) + s2][12]), "=r"(A[2 * (B) + s2][13]) : "r"(ga - lane * 8 + 1536) : "memory"); \
        }                                                                                      \
    }
#define LATE_ARRIVE() do { if (lane == 0) mbar_arrive(BAR(B_LATE)); } while (0)
#define LATE_WAIT() do { mbar_wait(BAR(B_LATE), gatph & 1); gatph ^= 1; } while (0)
#define PT 3
#define PREP(b, t, remote)                                                                     \
    if constexpr ((b) < 3 && (t) == PT) {                                                      \
        wg_commit();                                                                           \
        STAMP(74 + 6 * (step & 1) + 2 * (b));                                                  \
        if (remote) {                                                                          \
            if constexpr ((b) == 0) { blk_load<2>(A, BLK(xsrc, 2), lane); GAT_FETCH(1) }       \
            blk_check<((b) + 1) & 3>(A, BLK(xsrc, (b) + 1), lane, xtag);                       \
            if constexpr ((b) == 0) blk_load<3>(A, BLK(xsrc, 3), lane);                        \
        }                                                                                      \
        STAMP(75 + 6 * (step & 1) + 2 * (b));                                                  \
        normalize<((b) + 1) & 3>(A, k0, k1);                                                   \
        asm volatile("" : RW4(A[(2 * (b) + 2) & 7], 0), RW4(A[(2 * (b) + 2) & 7], 4), RW4(A[(2 * (b) + 2) & 7], 8), RW2(A[(2 * (b) + 2) & 7], 12), \
                          RW4(A[(2 * (b) + 3) & 7], 0), RW4(A[(2 * (b) + 3) & 7], 4), RW4(A[(2 * (b) + 3) & 7], 8), RW2(A[(2 * (b) + 3) & 7], 12)); \
        wg_fence();                                                                            \
    }
#define X0_BLOCK(b)                                                                            \
    { const int rr = lane & 7, hi = lane >> 4;                                                 \
    const uint32_t rowa = (w < 2 ? hbuf : sb + wgi * STAGE) + ((w & 1) * 16 + (lane & 15)) * 128; \
    FOR7(constexpr int G = 14 * (b) + (t < 3 ? 2 * t : (t < 6 ? 2 * t + 1 : 6));               \
         uint32_t q0, q1, q2, q3;                                                              \
         const uint32_t ad = t < 6 ? rowa + (((((G & 7) + hi) ^ rr) & 7) << 4) + ((G & 7) == 7 ? hi * 4096 : 0) : rowa + ((G + 7 * hi) >> 3) * 4096 + ((((G + 7 * hi) ^ rr) & 7) << 4); \
         asm volatile("ldmatrix.sync.aligned.m8n8.x4.shared.b16 {%0,%1,%2,%3}, [%4+%5];" : "=r"(q0), "=r"(q1), "=r"(q2), "=r"(q3) \
                      : "r"(ad), "n"(t < 6 ? (G >> 3) * 4096 : 0) : "memory");                 \
         if (t < 3) { A[2 * (b)][4 * t] = q0; A[2 * (b)][4 * t + 1] = q1; A[2 * (b)][4 * t + 2] = q2; A[2 * (b)][4 * t + 3] = q3; } \
         else if (t < 6) { A[2 * (b) + 1][(4 * t - 12) & 15] = q0; A[2 * (b) + 1][((4 * t - 12) & 15) + 1] = q1; A[2 * (b) + 1][((4 * t - 12) & 15) + 2] = q2; A[2 * (b) + 1][((4 * t - 12) & 15) + 3] = q3; } \
         else { A[2 * (b)][12] = q0; A[2 * (b)][13] = q1; A[2 * (b) + 1][12] = q2; A[2 * (b) + 1][13] = q3; }); }
#define BLK(base, b) ((base) + kblk(pr, b) * 1024)

#pragma unroll 1
        for (int step = 0; step < 4; step++) {
            FRESH();
            const uint32_t tag = (step >> 1) ^ 1;
            const int so = (step >> 1) * 24 + (step & 1) * 12;
            (void)so;
            uint32_t A[8][14];
            uint4* const xsrc = xp0 + ((step & 1) ? PL(2) : PL(0));
            const uint32_t xtag = (step & 1) ? tag : ((seq >> 3) & 1) ^ 1;
            uint32_t xbits;
            {
                float st[4];
                slice_stats(X, st);
                stag ^= 1;
                xbits = x_bits(X);
                tag_slice(X, xtag);
                if (step) send_slice<0>(xsrc + sl * 512, lane, X);
                if (c == 0) st_pkt<0>(stp + sl * 512, __float_as_uint(st[0]), __float_as_uint(st[1]), __float_as_uint(st[2]), settag(__float_as_uint(st[3]), stag));
            }
            STAMP(2 + so);
            uint32_t sv[8];
            if (step == 0) {
                X0_BLOCK(0) X0_BLOCK(1) X0_BLOCK(2) X0_BLOCK(3)
                mbar_wait(BAR(wgi ^ 1), 0);
                R_NEXT();
                R_NEXT();
                R_RELEASE(2);
                stat_load(sv, stp + c * 1024);
                stat_check(sv, stp + c * 1024, stag);
                STAMP(52 + step);
            } else {
                kill<14>(A[2]); kill<14>(A[3]); kill<14>(A[4]); kill<14>(A[5]); kill<14>(A[6]); kill<14>(A[7]);
                PUSH_SLICE(X)
                stat_load(sv, stp + c * 1024);
                PULL_SLICE(X)
                stat_check(sv, stp + c * 1024, stag);
                STAMP(52 + step);
                GAT_ISSUE(1, (step & 1) ? PL(2) : PL(0))
            }
            LnCoef k0, k1;
            {
                k0 = ln_coef(__uint_as_float(sv[0]) + __uint_as_float(sv[4]), __uint_as_float(sv[1]) + __uint_as_float(sv[5]));
                k1 = ln_coef(__uint_as_float(sv[2]) + __uint_as_float(sv[6]), __uint_as_float(sv[3] & ~1u) + __uint_as_float(sv[7] & ~1u));
            }
            STAMP(3 + so);
            GSTAMP(70 + step);

            if ((step & 1) == 0) {
                float tq[28];
#define K_BLOCK(b)                                                                            \
    if ((b) == 1) R_RELEASE(1);                                                               \
    if ((b) == 2) PUSH_ACK();                                                                 \
    if ((b) == 3) { wg_wait<2>(); R_RELEASE(1); }                                             \
    if (((b) & 1) == 0) R_WAIT();                                                             \
    { DECL_DB(b, BASE128, 16, 0)                                                              \
    wg_fence();                                                                               \
    FOR7(mma_rs56<1, D128(((b) & 1) * HALF, t)>(tq, AQ(A, b, t), (b) + t > 0, SWB(b, t, db, 0)); \
         PREP(b, t, step)); }                                                                 \
    wg_commit();                                                                              \
    if ((b) & 1) R_NEXT();
#define P_STAGE(acc, b0)                                                                      \
    R_WAIT();                                                                                 \
    { DECL_DB(b0, BASE128, 16, 0)                                                             \
    wg_fence();                                                                               \
    FOR7(mma_rs56<1, D128(0, t)>(acc, AQ(A, b0, t), (b0) + t > 0, SWB(b0, t, db, 0)));        \
    FOR7(mma_rs56<1, D128(HALF, t)>(acc, AQ(A, (b0) + 1, t), 1, db)); }                       \
    wg_commit();                                                                              \
    R_NEXT();
#define PROJECT(acc) P_STAGE(acc, 0) P_STAGE(acc, 2) wg_wait<1>(); R_RELEASE(2); wg_wait<0>(); R_RELEASE(1);
#define V_PASS()                                                                              \
    {                                                                                         \
        float av[28];                                                                         \
        PROJECT(av)                                                                           \
        const int m = lane >> 3, rr = lane & 7;                                               \
        const uint32_t rowa = hbuf + 16384 + (w * 16 + rr + 8 * (m & 1)) * 128;               \
        const uint32_t one = c == 0 ? 0x00003f80u : 0u;                                       \
        _Pragma("unroll") for (int j = 0; j < 4; j++) {                                       \
            const uint32_t a = rowa + (((2 * j + (m >> 1)) ^ rr) << 4);                       \
            if (j < 3) stsm4(a, pack2(av[8 * j], av[8 * j + 1]), pack2(av[8 * j + 2], av[8 * j + 3]), pack2(av[8 * j + 4], av[8 * j + 5]), pack2(av[8 * j + 6], av[8 * j + 7])); \
            else stsm4(a, pack2(av[24], av[25]), pack2(av[26], av[27]), one, one);            \
        }                                                                                     \
    }
                normalize<0>(A, k0, k1);
                K_BLOCK(0) K_BLOCK(1) K_BLOCK(2) K_BLOCK(3)
                wg_wait<0>();
                R_RELEASE(1);
                STAMP(4 + so);
                if (step == 0) { bar_sync(wgi ? 9 : 1, 224); }
                if (wgi == VW) V_PASS()
                uint32_t PH[28];
                int it = 1;
#pragma unroll 1
                do {
                    float pp[28];
                    phi_gemm(tq, pp);
                    dual_softmax(pp, PH);
                    if (((trips >> (it + 1)) & 1) == 0) continue;
                    {
                        const int m = lane >> 3, rr = lane & 7;
                        const uint32_t rowa = hbuf + (w * 16 + rr + 8 * (m & 1)) * 128;
#pragma unroll
                        for (int j = 0; j < 7; j++) {
                            const int cg = 2 * j + (m >> 1), hi = cg >= 7;
                            stsm4(rowa + hi * 8192 + (((cg - 7 * hi) ^ rr) << 4), PH[4 * j], PH[4 * j + 1], PH[4 * j + 2], PH[4 * j + 3]);
                        }
                    }
                    STAMP(5 + so);
                    if (wgi != VW) V_PASS()
                    fence_async();
                    bar_sync(2, 256);
                    float kv[28];
                    const uint64_t da = BASE128(OFF_H + 16384, 16, 0), dbk = BASE128(OFF_H, 16, wgi * 512);
                    wg_fence();
                    FOR8(constexpr uint64_t o = ((t >> 2) * STAGE + (t & 3) * 2048) >> 4; mma_ss56_tt<o, o>(kv, t > 0, da, dbk));
                    wg_commit();
                    wg_wait<0>();
#pragma unroll
                    for (int hf = 0; hf < 2; hf++) {
                        const int d = 16 * w + g + 8 * hf;
                        if ((d < 56 && (d >= 28) == (c >= 2)) || d == 56) {
                            const int item = d < 56 ? 2 * d + (c & 1) : 112 + c;
                            uint4* dst = g_kv1 + ((sl * 16 + (item >> 3)) * 16 + tile) * 32 + wgi * 16 + (item & 7);
#define KVW(i) pack2(kv[4 * (i) + 2 * hf], kv[4 * (i) + 2 * hf + 1])
                            st_pkt<0>(dst, settag(KVW(0), tag), KVW(1), KVW(2), KVW(3));
                            st_pkt<8>(dst, settag(KVW(4), tag), KVW(5), KVW(6), 0u);
                        }
                    }
                    __syncwarp();
                    kseq++;
                    if (lane == 0) st_word(g_c1 + ((sl * 8 + wu) * 16 + tile) * 32, kseq);
                    bar_arrive(7, 384);
                    STAMP(6 + so);
                    kill<28>(tq);
                    if (QPP) { PP_WAIT() }
                    P_STAGE(tq, 0) P_STAGE(tq, 2)
                    if (QPP) { PP_GO() }
                    wg_wait<1>(); R_RELEASE(2); wg_wait<0>(); R_RELEASE(1);
                    STAMP(7 + so);
                    kill<28>(PH);
                } while (((trips >> (++it)) & 1));
                STAMP(8 + so);
                FRESH();
                if (step) {
                    slice_load<PL(0)>(X, xp0 + sl * 512, lane);
                } else {
                    const uint32_t* xp = reinterpret_cast<const uint32_t*>(x_in + (size_t)(tile * 128 + wu * 16 + g) * 448 + 56 * sl + 2 * c);
#pragma unroll
                    for (int i = 0; i < 7; i++) { X[2 * i] = __ldg(xp + 4 * i); X[2 * i + 1] = __ldg(xp + 4 * i + 8 * 224); }
                }
                bar_sync(3, 384);
                STAMP(9 + so);
                const uint4* const osrc = xp0 + PL(1);
                {
                    float nm[32];
                    const uint64_t db = BASE128(OFF_KVB, 16, 0);
                    wg_fence();
                    FOR7(mma_rs64<0, ((t >> 2) * 8192 + (t & 3) * 32) / 16>(nm, PH[4 * t], PH[4 * t + 1], PH[4 * t + 2], PH[4 * t + 3], t > 0, db));
                    wg_commit();
                    wg_wait<0>();
                    LATE_ARRIVE();
                    const float i00 = rcp(nm[28] + 1e-6f), i01 = rcp(nm[29] + 1e-6f), i10 = rcp(nm[30] + 1e-6f), i11 = rcp(nm[31] + 1e-6f);
                    const float m0 = c >= 2 ? i01 : i00, m1 = c >= 2 ? i11 : i10;
                    uint32_t O[14];
#pragma unroll
                    for (int i = 0; i < 7; i++) {
                        const float f0 = i < 3 ? i00 : (i > 3 ? i01 : m0), f1 = i < 3 ? i10 : (i > 3 ? i11 : m1);
                        O[2 * i] = pack2(nm[4 * i] * f0, nm[4 * i + 1] * f0);
                        O[2 * i + 1] = pack2(nm[4 * i + 2] * f1, nm[4 * i + 3] * f1);
                    }
                    if (OST) { PP_WAIT() }
                    tag_slice(O, tag);
                    send_slice<PL(1)>(xp0 + sl * 512, lane, O);
                    seq++;
                    if (lane == 0) st_word(cx(sl), seq);
                    STAMP(10 + so);
                    PUSH_SLICE(O)
                    if (OST == 1) { PP_GO() }
                    const uint32_t cv = ld_word(cx(lane & 7));
                    PULL_SLICE(O)
                    LATE_WAIT();
                    check_cnt(cv, cx(lane & 7), seq);
                    if (OST == 2) { PP_GO() }
                    STAMP(56 + (step >> 1));
                    GAT_ISSUE(1, PL(1))
                    GAT_ISSUE(3, PL(1))
                    blk_load<2>(A, BLK(osrc, 2), lane);
                }
                float ao[28];
#define WO_BLOCK(b)                                                                           \
    if ((b) > 0) blk_check<b>(A, BLK(osrc, b), lane, tag);                                    \
    if (((b) & 1) == 0) R_WAIT();                                                             \
    { DECL_DB(b, BASE128, 16, 0)                                                              \
    wg_fence();                                                                               \
    FOR7(mma_rs56<1, D128(((b) & 1) * HALF, t)>(ao, AQ(A, b, t), (b) + t > 0, SWB(b, t, db, 0))); } \
    wg_commit();                                                                              \
    if ((b) & 1) R_NEXT();
                WO_BLOCK(0)
                STAMP(11 + so);
                GAT_FETCH(1)
                WO_BLOCK(1)
                WO_BLOCK(2)
                GAT_FETCH(3)
                WO_BLOCK(3)
                PUSH_ACK();
                wg_wait<0>();
                R_RELEASE(2);
                STAMP(12 + so);
                WSUM(86 + 7 * (step >> 1));
                x_fix(X, xbits);
#pragma unroll
                for (int i = 0; i < 14; i++) X[i] = pack2(bf_lo(X[i]) + ao[2 * i], bf_hi(X[i]) + ao[2 * i + 1]);
            } else {
                uint32_t H[56];
                float ag[64];
#define F1_EPI(dst, ng, ag)                                                                    \
    _Pragma("unroll") for (int i = 0; i < 2 * (ng); i++)                                       \
        (dst)[i] = pack2(geglu(ag[2 * i], ag[4 * (ng) + 2 * i]), geglu(ag[2 * i + 1], ag[4 * (ng) + 2 * i + 1]));
#define H_PUSH(h0, off) st_async4(rem_h + (off), H[h0], H[(h0) + 1], H[(h0) + 2], H[(h0) + 3], mapa(BAR(B_RECV2 + wgi), hr ^ 1));
#define F1_BLOCK(b, first)                                                                     \
    if ((first) && (b) == 1) R_RELEASE(2);                                                     \
    if ((first) && (b) == 2) PUSH_ACK();                                                       \
    R_WAIT();                                                                                  \
    if ((b) == ((first) ? PPF : PPB)) { PP_WAIT() }                                            \
    { DECL_DB(b, BASE128, HALF, 0)                                                             \
    wg_fence();                                                                                \
    FOR7(mma_rs128<1, D128(0, t)>(ag, AQ(A, b, t), (b) + t > 0, SWB(b, t, db, 0));             \
         if constexpr (first) { PREP(b, t, true) }); }                                         \
    wg_commit();                                                                               \
    if ((b) == 3) { PP_GO() }                                                                  \
    if ((b) > 0) { wg_wait<1>(); R_RELEASE(1); }       \
    R_NEXT();
                normalize<0>(A, k0, k1);
                F1_BLOCK(0, true) F1_BLOCK(1, true) F1_BLOCK(2, true) F1_BLOCK(3, true)
                if (t128 == 0) { mbar_expect_tx(BAR(B_RECV + wgi), 16384); mbar_expect_tx(BAR(B_RECV2 + wgi), 12288); }
                PUSH_BEGIN();
                wg_wait<0>();
                R_RELEASE(1);
                int p = 0;
#pragma unroll 1
                do {
                    F1_EPI(H + 32, 8, ag)
                    STAMP(4 + p + so);
                    WSUM(81 + p + 7 * (step >> 1));
                    if (((trips >> (p + 1)) & 1) == 0) continue;
                    if (step == 1 && p == PKP) R_NEXT();
                    kill<64>(ag);
                    F1_BLOCK(0, false)
                    {
                        const uint32_t pk = (p ? hbuf + 16384 : sb + OFF_KVB + wgi * 8192) + w * 2048;
#pragma unroll
                        for (int k = 0; k < 4; k++) sts4(pk + k * 512 + lane * 16, H[32 + 4 * k], H[33 + 4 * k], H[34 + 4 * k], H[35 + 4 * k]);
                        fence_async();
                        __syncwarp();
                        asm volatile(ELECT "cp.async.bulk.shared::cluster.shared::cta.mbarrier::complete_tx::bytes [%0], [%1], 2048, [%2]; }"
                                     ::"r"(mapa(hbuf + p * 8192 + w * 2048, hr ^ 1)), "r"(pk), "r"(mapa(BAR(B_RECV + wgi), hr ^ 1)) : "memory");
                    }
                    F1_BLOCK(1, false) F1_BLOCK(2, false) F1_BLOCK(3, false)
                    wg_wait<0>();
                    R_RELEASE(1);
                    kill<16>(H + 32);
                } while (((trips >> (++p)) & 1));
#pragma unroll
                for (int k = 0; k < 4; k++) lds4(H + 16 + 4 * k, hbuf + 16384 + w * 2048 + k * 512 + lane * 16);
                __syncwarp();
                if (lane == 0) asm volatile("mbarrier.arrive.shared::cluster.b64 _, [%0];" ::"r"(mapa(BAR(B_ACK2 + wgi), hr ^ 1)) : "memory");
                const uint32_t rem_h = mapa(hbuf + w * 2048 + lane * 16, hr ^ 1);
#define F1_LAST(b0)                                                                            \
    R_WAIT();                                                                                  \
    if (b0) { PP_WAIT() }                                                                      \
    { DECL_DB(b0, BASE64, HALF, 1)                                                             \
    wg_fence();                                                                                \
    FOR7(mma_rs64<1, D64(0, t)>(al, AQ(A, b0, t), (b0) + t > 0, SWB(b0, t, db, 1)));           \
    FOR7(mma_rs64<1, D64(7168, t)>(al, AQ(A, (b0) + 1, t), 1, db)); }                          \
    wg_commit();                                                                               \
    if (b0) { PP_GO() }                                                                        \
    R_NEXT();
                float al[32];
                F1_LAST(0)
                mbar_wait(BAR(B_RECV + wgi), rcvph);
                rcvph ^= 1;
                mbar_wait(BAR(B_ACK2 + wgi), step >> 1);
                H_PUSH(32, 16384) H_PUSH(36, 16896)
                F1_LAST(2)
                H_PUSH(40, 17408) H_PUSH(44, 17920)
                wg_wait<1>();
                R_RELEASE(2);
                wg_wait<0>();
                R_RELEASE(1);
                uint32_t HP[56];
#pragma unroll
                for (int k = 0; k < 4; k++) lds4(H + 4 * k, sb + OFF_KVB + wgi * 8192 + w * 2048 + k * 512 + lane * 16);
#pragma unroll
                for (int t = 0; t < 8; t++) lds4(HP + 4 * t, hbuf + (t >> 2) * 8192 + w * 2048 + (t & 3) * 512 + lane * 16);
                F1_EPI(H + 48, 4, al)
                H_PUSH(48, 24576 - w * 1024) H_PUSH(52, 25088 - w * 1024)
                STAMP(7 + so);
                WSUM(84 + 7 * (step >> 1));
                FRESH();
                float acc[28];
                const uint32_t roA = hr ? 256u : 0u, roB = hr ? (uint32_t)-1536 : 0u;
                const uint32_t rpA = hr ? 0u : 256u, rpB = hr ? 0u : (uint32_t)-1536;
                float res[28];
                uint32_t v0[14], v1[14], P[14];
                const uint4* ps = xp0 + sl * 512;
#define F2_OWN_A()                                                                             \
    R_WAIT();                                                                                  \
    d0 = BASE128(0, 16, R_ADJ + roA); d1 = BASE128(0, 16, R_ADJ + roB);                        \
    wg_fence();                                                                                \
    FOR14(if constexpr (t < OT) mma_rs56<1, t * 128>(acc, H[4 * t], H[4 * t + 1], H[4 * t + 2], H[4 * t + 3], t > 0, d0)); \
    wg_commit();
#define F2_OWN_B()                                                                             \
    wg_fence();                                                                                \
    FOR14(if constexpr (t >= OT) mma_rs56<1, t * 128>(acc, H[4 * t], H[4 * t + 1], H[4 * t + 2], H[4 * t + 3], 1, t < 12 ? d0 : d1)); \
    wg_commit();                                                                               \
    R_NEXT();
#define F2_PEER()                                                                              \
    R_WAIT();                                                                                  \
    if (F2PP) { PP_WAIT() }                                                                    \
    d0 = BASE128(0, 16, R_ADJ + rpA); d1 = BASE128(0, 16, R_ADJ + rpB);                        \
    wg_fence();                                                                                \
    FOR14(mma_rs56<1, t * 128>(acc, HP[4 * t], HP[4 * t + 1], HP[4 * t + 2], HP[4 * t + 3], 1, t < 12 ? d0 : d1)); \
    wg_commit();                                                                               \
    if (F2PP) { PP_GO() }                                                                      \
    R_NEXT();
#define F2_TURN(u)                                                                             \
    wg_wait<1>();                                                                              \
    if ((u) < 2 || TDEF < 2) R_RELEASE(2);                                                     \
    wg_wait<0>();                                                                              \
    if ((u) < 2 || TDEF < 1) R_RELEASE(1);                                                     \
    _Pragma("unroll") for (int i = 0; i < 14; i++) P[i] = pack2(acc[2 * i], acc[2 * i + 1]);   \
    tag_slice(P, tag);                                                                         \
    asm volatile("" : RW4(P, 0), RW4(P, 4), RW4(P, 8), RW2(P, 12));                            \
    kill<28>(acc);                                                                             \
    F2_OWN_A()                                                                                 \
    if ((u) == 2) { slice_load<PL(3)>(v0, ps, lane); slice_load<PL(4)>(v1, ps, lane); } \
    send_slice<PL(3 + (u))>(xp0 + (2 * ((pr + (u) + 1) & 3) + hr) * 512, lane, P);             \
    seq++;                                                                                     \
    if (lane == 0) st_word(cx(sl), seq);                                                       \
    __syncwarp();                                                                              \
    STAMP(8 + (u) + so);                                                                       \
    F2_OWN_B()
                uint64_t d0, d1;
                F2_OWN_A()
                F2_OWN_B()
                R_WAIT();
                d0 = BASE128(0, 16, R_ADJ + rpA); d1 = BASE128(0, 16, R_ADJ + rpB);
                wg_fence();
                FOR8(mma_rs56<1, t * 128>(acc, HP[4 * t], HP[4 * t + 1], HP[4 * t + 2], HP[4 * t + 3], 1, d0));
                wg_commit();
                mbar_wait(BAR(B_RECV2 + wgi), step >> 1);
#pragma unroll
                for (int k = 0; k < 4; k++) lds4(HP + 32 + 4 * k, hbuf + 16384 + w * 2048 + k * 512 + lane * 16);
                lds4(HP + 48, hbuf + 24576 + w * 1024 + lane * 16);
                lds4(HP + 52, hbuf + 25088 + w * 1024 + lane * 16);
                if (step == 1) PUSH_ACK();
                wg_fence();
                FOR14(if constexpr (t >= 8) mma_rs56<1, t * 128>(acc, HP[4 * t], HP[4 * t + 1], HP[4 * t + 2], HP[4 * t + 3], 1, t < 12 ? d0 : d1));
                wg_commit();
                R_NEXT();
                F2_TURN(0)
                F2_PEER()
                F2_TURN(1)
                F2_PEER()
                F2_TURN(2)
                if (step == 1) STAMP(64);
                slice_check<PL(3)>(v0, ps, lane, tag);
                slice_check<PL(4)>(v1, ps, lane, tag);
#pragma unroll
                for (int i = 0; i < 14; i++) { res[2 * i] = bf_lo(v0[i]) + bf_lo(v1[i]); res[2 * i + 1] = bf_hi(v0[i]) + bf_hi(v1[i]); }
                slice_load<PL(2)>(X, ps, lane);
                if (step == 1) STAMP(65);
                F2_PEER()
                if (step == 1) STAMP(66);
                poll_cnt(cx(2 * ((pr + 1) & 3) + hr), seq);
                if (step == 1) STAMP(67);
                slice_load<PL(5)>(v0, ps, lane);
                x_fix(X, xbits);
                slice_check<PL(5)>(v0, ps, lane, tag);
                if (lane < TDEF) mbar_arrive(BAR(B_EMPTY + (slot + NST - 3 - lane) % NST));
#pragma unroll
                for (int i = 0; i < 14; i++) { res[2 * i] += bf_lo(v0[i]); res[2 * i + 1] += bf_hi(v0[i]); }
                STAMP(11 + so);
                wg_wait<0>();
                R_RELEASE(2);
                STAMP(12 + so);
                WSUM(85 + 7 * (step >> 1));
#pragma unroll
                for (int i = 0; i < 14; i++) X[i] = pack2(fmaf(res[2 * i] + acc[2 * i], 0.5f, bf_lo(X[i])), fmaf(res[2 * i + 1] + acc[2 * i + 1], 0.5f, bf_hi(X[i])));
            }
        }
        {
            const int m = lane >> 3, rr = lane & 7;
            const uint32_t ob = hbuf + w * 2048, rowa = ob + (rr + 8 * (m & 1)) * 112 + (m >> 1) * 16;
#pragma unroll
            for (int j = 0; j < 3; j++) stsm4(rowa + 32 * j, X[4 * j], X[4 * j + 1], X[4 * j + 2], X[4 * j + 3]);
            asm volatile("stmatrix.sync.aligned.m8n8.x2.shared.b16 [%0], {%1,%2};" ::"r"(ob + (rr + 8 * (m & 1)) * 112 + 96), "r"(X[12]), "r"(X[13]) : "memory");
            fence_async();
            __syncwarp();
            if (lane == 0) {
                asm volatile("cp.async.bulk.tensor.2d.global.shared::cta.bulk_group [%0, {%2, %3}], [%1];" ::"l"(&maps.out), "r"(ob), "r"(56 * sl), "r"(tile * 128 + wu * 16) : "memory");
                asm volatile("cp.async.bulk.commit_group;" ::: "memory");
                asm volatile("cp.async.bulk.wait_group.read 0;" ::: "memory");
            }
        }
        STAMP(50);
        GSTAMP(61);
        PDUMP();
    }
}

#undef g
#undef pr
#undef c
#undef t128

typedef CUresult (*EncodeFn)(CUtensorMap*, CUtensorMapDataType, cuuint32_t, void*, const cuuint64_t*, const cuuint64_t*, const cuuint32_t*,
                             const cuuint32_t*, CUtensorMapInterleave, CUtensorMapSwizzle, CUtensorMapL2promotion, CUtensorMapFloatOOBfill);

static void make_map(EncodeFn enc, CUtensorMap* m, const void* p, uint64_t cols, uint64_t rows, uint32_t bc, uint32_t br, CUtensorMapSwizzle sw) {
    cuuint64_t gd[2] = {cols, rows};
    cuuint64_t gs[1] = {cols * 2};
    cuuint32_t bd[2] = {bc, br};
    cuuint32_t es[2] = {1, 1};
    enc(m, CU_TENSOR_MAP_DATA_TYPE_BFLOAT16, 2, const_cast<void*>(p), gd, gs, bd, es, CU_TENSOR_MAP_INTERLEAVE_NONE, sw,
        CU_TENSOR_MAP_L2_PROMOTION_L2_128B, CU_TENSOR_MAP_FLOAT_OOB_FILL_NONE);
}

extern "C" void kernel_launch(void* const* d_in, const int* in_sizes, int n_in, void* d_out, int out_size) {
    (void)in_sizes; (void)n_in; (void)out_size;
    static EncodeFn enc = nullptr;
    static Scratch* scratch = nullptr;
    if (!enc) {
        void* fn = nullptr;
        cudaDriverEntryPointQueryResult qr;
        cudaGetDriverEntryPoint("cuTensorMapEncodeTiled", &fn, cudaEnableDefault, &qr);
        enc = (EncodeFn)fn;
        cudaGetSymbolAddress((void**)&scratch, g_scratch);
        cudaFuncSetAttribute(fused_kernel, cudaFuncAttributeMaxDynamicSharedMemorySize, SMEM_BYTES);
    }
    Maps maps;
    {
        cuuint64_t gd[3] = {64, 2048, 7};
        cuuint64_t gs[2] = {896, 128};
        cuuint32_t bd[3] = {64, 32, 7};
        cuuint32_t es[3] = {1, 1, 1};
        enc(&maps.x, CU_TENSOR_MAP_DATA_TYPE_BFLOAT16, 3, d_in[0], gd, gs, bd, es, CU_TENSOR_MAP_INTERLEAVE_NONE, CU_TENSOR_MAP_SWIZZLE_128B,
            CU_TENSOR_MAP_L2_PROMOTION_L2_128B, CU_TENSOR_MAP_FLOAT_OOB_FILL_NONE);
    }
    make_map(enc, &maps.out, d_out, 448, 2048, 56, 16, CU_TENSOR_MAP_SWIZZLE_NONE);
    make_map(enc, &maps.qkv, d_in[1], 1344, 448, 64, 112, CU_TENSOR_MAP_SWIZZLE_128B);
    make_map(enc, &maps.wo, d_in[3], 448, 448, 64, 112, CU_TENSOR_MAP_SWIZZLE_128B);
    make_map(enc, &maps.wg, d_in[5], 1792, 448, 64, 112, CU_TENSOR_MAP_SWIZZLE_128B);
    make_map(enc, &maps.wu, d_in[6], 1792, 448, 64, 112, CU_TENSOR_MAP_SWIZZLE_128B);
    make_map(enc, &maps.wg32, d_in[5], 1792, 448, 32, 112, CU_TENSOR_MAP_SWIZZLE_64B);
    make_map(enc, &maps.wu32, d_in[6], 1792, 448, 32, 112, CU_TENSOR_MAP_SWIZZLE_64B);
    make_map(enc, &maps.wd, d_in[7], 448, 1792, 64, 112, CU_TENSOR_MAP_SWIZZLE_128B);
    fused_kernel<<<128, 384, SMEM_BYTES>>>(scratch, (const __nv_bfloat16*)d_in[0], (const __nv_bfloat16*)d_in[2], 7, (const __nv_bfloat16*)d_in[5],
                                           (const __nv_bfloat16*)d_in[6], (const __nv_bfloat16*)d_in[7], maps);
}
```

```cpp
#include <cuda_runtime.h>
#include <cuda.h>
#include <cuda_bf16.h>
#include <stdint.h>
#include <type_traits>

#define PPF 2
#define PKP 0
#define TDEF 1
#define TMPF 0
#define NORM1 0
#define LPARK 1
#define PFN 9
#define VW 1
#define QPP 1
#define XG3 2
#define XT (XG3 == 1 || XG3 == 2)
#define ACAN 0
#define SPLIT0 1
#define OT 2
#define F2PP 0
#define PPK 2
#define QE 1
#define OST 1
#define PP

namespace {

constexpr uint32_t STAGE = 28672, HALF = 14336;
constexpr int NST = 5;
constexpr uint32_t OFF_H = NST * STAGE;
constexpr uint32_t OFF_KVB = OFF_H + 2 * STAGE;
constexpr uint32_t OFF_WPHI = OFF_KVB + 16384;
constexpr uint32_t OFF_XR = OFF_WPHI + 7168;
constexpr uint32_t OFF_BAR = OFF_XR + 6144;
constexpr uint32_t SMEM_BYTES = OFF_BAR + 384 + 1408;
constexpr int B_EMPTY = NST, B_RECV = 2 * NST, B_RECV2 = B_RECV + 2, B_PACK = B_RECV2 + 2, B_GAT = B_PACK + 1, B_LATE = B_GAT + 16, B_ACK = B_LATE + 1, B_ACK2 = B_ACK + 2, B_COUNT = B_ACK2 + 2;

constexpr int PACK = 14 + 4 * PKP;

struct Maps { CUtensorMap x, qkv, wo, wg, wu, wg32, wu32, wd, out; };

}

constexpr int PLANE = 16 * 2 * 8 * 512;
struct Scratch {
    uint4 ex[6 * PLANE];
    uint4 kv1[8 * 16 * 16 * 32];
    uint4 kv2[8 * 512];
    uint32_t c1[8 * 8 * 16 * 32];
    uint32_t cw[8 * 32];
    uint4 wp[8 * 32 * (HALF / 16)];
};
__device__ __align__(1024) Scratch g_scratch;
#define g_ex (sc->ex)
#define g_kv1 (sc->kv1)
#define g_kv2 (sc->kv2)
#define g_c1 (sc->c1)
#define g_cw (sc->cw)
#define g_wp (sc->wp)
#define STAMP(i)
#define GSTAMP(i)
#define PDUMP()
#define ASTAMP(i)

namespace {

__device__ __forceinline__ int fresh_tid() { int t; asm volatile("mov.u32 %0, %%tid.x;" : "=r"(t)); return t; }
template <int N> __device__ __forceinline__ void kill(uint32_t* v) {
#pragma unroll
    for (int i = 0; i < N; i++) v[i] = 0;
}
template <int N> __device__ __forceinline__ void kill(float* v) {
#pragma unroll
    for (int i = 0; i < N; i++) v[i] = 0.f;
}
__device__ __forceinline__ uint32_t s2u(const void* p) { return (uint32_t)__cvta_generic_to_shared(p); }
__device__ __forceinline__ void mbar_init(uint32_t a, uint32_t c) { asm volatile("mbarrier.init.shared::cta.b64 [%0], %1;" ::"r"(a), "r"(c) : "memory"); }
__device__ __forceinline__ void mbar_expect_tx(uint32_t a, uint32_t b) { asm volatile("mbarrier.arrive.expect_tx.shared::cta.b64 _, [%0], %1;" ::"r"(a), "r"(b) : "memory"); }
__device__ __forceinline__ void mbar_arrive(uint32_t a) { asm volatile("mbarrier.arrive.shared::cta.b64 _, [%0];" ::"r"(a) : "memory"); }
#define GIVE_UP(id) "trap;\n"
#define SPIN_MAX "0x400000"
#define SPIN_TAIL(id) "add.u32 n, n, 1;\n setp.lt.u32 p, n, " SPIN_MAX ";\n @p bra.uni LP;\n" GIVE_UP(id) " DN:\n }"
__device__ __forceinline__ void mbar_wait(uint32_t a, uint32_t ph) {
    asm volatile("{ .reg .pred p; .reg .b32 n; mov.u32 n, 0;\n LP:\n"
                 "mbarrier.try_wait.parity.shared::cta.b64 p, [%0], %1;\n @p bra DN;\n"
                 "add.u32 n, n, 1;\n setp.lt.u32 p, n, " SPIN_MAX ";\n @p bra LP;\n"
                 GIVE_UP("")
                 " DN:\n }" ::"r"(a), "r"(ph) : "memory");
}
__device__ __forceinline__ void mbar_wait_b(uint32_t a, uint32_t ph, uint32_t& spins) {
    asm volatile("{ .reg .pred p;\n LP:\n"
                 "mbarrier.try_wait.parity.shared::cta.b64 p, [%1], %2;\n @p bra DN;\n"
                 "add.u32 %0, %0, 1;\n setp.lt.u32 p, %0, 0x1000000;\n @p bra LP;\n trap;\n DN:\n }" : "+r"(spins) : "r"(a), "r"(ph) : "memory");
}
#define ELECT "{ .reg .pred e; elect.sync _|e, 0xffffffff; @e "
__device__ __forceinline__ void tma2d(uint32_t dst, const CUtensorMap* m, int c0, int c1, uint32_t bar) {
    asm volatile(ELECT "cp.async.bulk.tensor.2d.shared::cluster.global.mbarrier::complete_tx::bytes [%0], [%1, {%3, %4}], [%2]; }" ::"r"(dst), "l"(m), "r"(bar), "r"(c0), "r"(c1) : "memory");
}
__device__ __forceinline__ void tma3x(uint32_t dst, const CUtensorMap* m, int row, uint32_t bar) {
    asm volatile(ELECT "cp.async.bulk.tensor.3d.shared::cluster.global.mbarrier::complete_tx::bytes [%0], [%1, {0, %3, 0}], [%2]; }" ::"r"(dst), "l"(m), "r"(bar), "r"(row) : "memory");
}
template <int OFF>
__device__ __forceinline__ void ld_pkt(uint32_t* v, const uint4* p) {
    asm volatile("{ .reg .b128 t; ld.relaxed.gpu.global.b128 t, [%4+%5]; mov.b128 {%0,%1,%2,%3}, t; }" : "=r"(v[0]), "=r"(v[1]), "=r"(v[2]), "=r"(v[3]) : "l"(p), "n"(OFF * 16) : "memory");
}
template <int OFF>
__device__ __forceinline__ void st_pkt(uint4* p, uint32_t a, uint32_t b, uint32_t c, uint32_t d) {
    asm volatile("{ .reg .b128 t; mov.b128 t, {%1,%2,%3,%4}; st.relaxed.gpu.global.b128 [%0+%5], t; }" ::"l"(p), "r"(a), "r"(b), "r"(c), "r"(d), "n"(OFF * 16) : "memory");
}
__device__ __forceinline__ uint32_t pack2(float lo, float hi) {
    uint32_t r;
    asm("cvt.rn.bf16x2.f32 %0, %1, %2;" : "=r"(r) : "f"(hi), "f"(lo));
    return r;
}
__device__ __forceinline__ float bf_lo(uint32_t w) { return __uint_as_float(w << 16); }
__device__ __forceinline__ float bf_hi(uint32_t w) { return __uint_as_float(w & 0xffff0000u); }
__device__ __forceinline__ uint32_t settag(uint32_t w, uint32_t tag) { return (w & ~1u) | tag; }
__device__ __forceinline__ float ex2(float x) { float y; asm("ex2.approx.ftz.f32 %0, %1;" : "=f"(y) : "f"(x)); return y; }
__device__ __forceinline__ float rcp(float x) { float y; asm("rcp.approx.ftz.f32 %0, %1;" : "=f"(y) : "f"(x)); return y; }
__device__ __forceinline__ float tanh_hw(float x) { float y; asm("tanh.approx.f32 %0, %1;" : "=f"(y) : "f"(x)); return y; }
__device__ __forceinline__ void stsm4(uint32_t addr, uint32_t a, uint32_t b, uint32_t c, uint32_t d) {
    asm volatile("stmatrix.sync.aligned.m8n8.x4.shared.b16 [%0], {%1,%2,%3,%4};" ::"r"(addr), "r"(a), "r"(b), "r"(c), "r"(d) : "memory");
}
__device__ __forceinline__ void fence_async() { asm volatile("fence.proxy.async.shared::cta;" ::: "memory"); }
__device__ __forceinline__ void bar_sync(int id, int n) { asm volatile("bar.sync %0, %1;" ::"r"(id), "r"(n) : "memory"); }
__device__ __forceinline__ void bar_arrive(int id, int n) { asm volatile("bar.arrive %0, %1;" ::"r"(id), "r"(n) : "memory"); }
__device__ __forceinline__ void wg_fence() { asm volatile("wgmma.fence.sync.aligned;" ::: "memory"); }
__device__ __forceinline__ void wg_commit() { asm volatile("wgmma.commit_group.sync.aligned;" ::: "memory"); }
template <int N> __device__ __forceinline__ void wg_wait() { asm volatile("wgmma.wait_group.sync.aligned %0;" ::"n"(N) : "memory"); }

constexpr uint32_t SB0 = 1024;
__host__ __device__ constexpr uint32_t dlo(uint32_t off, uint32_t lbo) { return ((SB0 + off) >> 4) | ((lbo >> 4) << 16); }
__host__ __device__ constexpr uint32_t dhi(uint32_t sbo, uint32_t sw) { return (sbo >> 4) | (sw << 30); }
__device__ __forceinline__ uint64_t dbase(uint32_t lo, uint32_t hi) { uint64_t d; asm volatile("mov.b64 %0, {%1, %2};" : "=l"(d) : "r"(lo), "r"(hi)); return d; }
#define BASE128(off, lbo, adj) dbase(dlo(off, lbo) + (adj), dhi(1024, 1))
#define BASE64(off, lbo, adj) dbase(dlo(off, lbo) + (adj), dhi(512, 2))

#define ACC4(d, o) "+f"(d[o]), "+f"(d[o + 1]), "+f"(d[o + 2]), "+f"(d[o + 3])
#define ACC28(d) ACC4(d, 0), ACC4(d, 4), ACC4(d, 8), ACC4(d, 12), ACC4(d, 16), ACC4(d, 20), ACC4(d, 24)
#define ACC32(d, o) ACC4(d, o), ACC4(d, o + 4), ACC4(d, o + 8), ACC4(d, o + 12), ACC4(d, o + 16), ACC4(d, o + 20), ACC4(d, o + 24), ACC4(d, o + 28)

template <int TB, uint64_t D>
__device__ __forceinline__ void mma_rs56(float* d, uint32_t a0, uint32_t a1, uint32_t a2, uint32_t a3, int sd, uint64_t base) {
    asm volatile("{ .reg .pred p; .reg .b64 db; setp.ne.b32 p, %32, 0; add.u64 db, %33, %34;\n"
                 "wgmma.mma_async.sync.aligned.m64n56k16.f32.bf16.bf16 "
                 "{%0,%1,%2,%3,%4,%5,%6,%7,%8,%9,%10,%11,%12,%13,%14,%15,%16,%17,%18,%19,%20,%21,%22,%23,%24,%25,%26,%27}, "
                 "{%28,%29,%30,%31}, db, p, 1, 1, %35; }\n"
                 : ACC28(d)
                 : "r"(a0), "r"(a1), "r"(a2), "r"(a3), "r"(sd), "l"(base), "n"(D), "n"(TB));
}
template <int TB, uint64_t D>
__device__ __forceinline__ void mma_rs64(float* d, uint32_t a0, uint32_t a1, uint32_t a2, uint32_t a3, int sd, uint64_t base) {
    asm volatile("{ .reg .pred p; .reg .b64 db; setp.ne.b32 p, %36, 0; add.u64 db, %37, %38;\n"
                 "wgmma.mma_async.sync.aligned.m64n64k16.f32.bf16.bf16 "
                 "{%0,%1,%2,%3,%4,%5,%6,%7,%8,%9,%10,%11,%12,%13,%14,%15,%16,%17,%18,%19,%20,%21,%22,%23,%24,%25,%26,%27,%28,%29,%30,%31}, "
                 "{%32,%33,%34,%35}, db, p, 1, 1, %39; }\n"
                 : ACC32(d, 0)
                 : "r"(a0), "r"(a1), "r"(a2), "r"(a3), "r"(sd), "l"(base), "n"(D), "n"(TB));
}
template <int TB, uint64_t D>
__device__ __forceinline__ void mma_rs128(float* d, uint32_t a0, uint32_t a1, uint32_t a2, uint32_t a3, int sd, uint64_t base) {
    asm volatile("{ .reg .pred p; .reg .b64 db; setp.ne.b32 p, %68, 0; add.u64 db, %69, %70;\n"
                 "wgmma.mma_async.sync.aligned.m64n128k16.f32.bf16.bf16 "
                 "{%0,%1,%2,%3,%4,%5,%6,%7,%8,%9,%10,%11,%12,%13,%14,%15,%16,%17,%18,%19,%20,%21,%22,%23,%24,%25,%26,%27,%28,%29,%30,%31,%32,%33,%34,%35,%36,%37,%38,%39,%40,%41,%42,%43,%44,%45,%46,%47,%48,%49,%50,%51,%52,%53,%54,%55,%56,%57,%58,%59,%60,%61,%62,%63}, "
                 "{%64,%65,%66,%67}, db, p, 1, 1, %71; }\n"
                 : ACC32(d, 0), ACC32(d, 32)
                 : "r"(a0), "r"(a1), "r"(a2), "r"(a3), "r"(sd), "l"(base), "n"(D), "n"(TB));
}
template <uint64_t DA, uint64_t DB>
__device__ __forceinline__ void mma_ss56_tt(float* d, int sd, uint64_t ba, uint64_t bb) {
    asm volatile("{ .reg .pred p; .reg .b64 da, db; setp.ne.b32 p, %28, 0; add.u64 da, %29, %31; add.u64 db, %30, %32;\n"
                 "wgmma.mma_async.sync.aligned.m64n56k16.f32.bf16.bf16 "
                 "{%0,%1,%2,%3,%4,%5,%6,%7,%8,%9,%10,%11,%12,%13,%14,%15,%16,%17,%18,%19,%20,%21,%22,%23,%24,%25,%26,%27}, "
                 "da, db, p, 1, 1, 1, 1; }\n"
                 : ACC28(d)
                 : "r"(sd), "l"(ba), "l"(bb), "n"(DA), "n"(DB));
}
template <int... I> struct Seq {};
template <class F, int... I> __device__ __forceinline__ void static_for_impl(F&& f, Seq<I...>) { (f(std::integral_constant<int, I>{}), ...); }
#define FOR7(...) static_for_impl([&](auto T_) { constexpr int t = decltype(T_)::value; __VA_ARGS__; }, Seq<0, 1, 2, 3, 4, 5, 6>{})
#define FOR8(...) static_for_impl([&](auto T_) { constexpr int t = decltype(T_)::value; __VA_ARGS__; }, Seq<0, 1, 2, 3, 4, 5, 6, 7>{})
#define FOR14(...) static_for_impl([&](auto T_) { constexpr int t = decltype(T_)::value; __VA_ARGS__; }, Seq<0, 1, 2, 3, 4, 5, 6, 7, 8, 9, 10, 11, 12, 13>{})

__device__ __forceinline__ int kblk(int p, int b) { return b == 0 ? p : b - (b <= p); }
__host__ __device__ constexpr int krow(int t) { return t < 3 ? 16 * t : (t < 6 ? 56 + 16 * (t - 3) : 48); }
#define AQ(A, b, t) ((t) < 3 ? A[2 * (b)][4 * (t)] : (t) < 6 ? A[2 * (b) + 1][4 * ((t) - 3)] : A[2 * (b)][12]), \
                    ((t) < 3 ? A[2 * (b)][4 * (t) + 1] : (t) < 6 ? A[2 * (b) + 1][4 * ((t) - 3) + 1] : A[2 * (b)][13]), \
                    ((t) < 3 ? A[2 * (b)][4 * (t) + 2] : (t) < 6 ? A[2 * (b) + 1][4 * ((t) - 3) + 2] : A[2 * (b) + 1][12]), \
                    ((t) < 3 ? A[2 * (b)][4 * (t) + 3] : (t) < 6 ? A[2 * (b) + 1][4 * ((t) - 3) + 3] : A[2 * (b) + 1][13])
#define D128(off, t) ((uint64_t)(((off) + krow(t) * 128) >> 4) + ((uint64_t)((t) == 6 ? (7168 - 1024) >> 4 : 0) << 32))
#define D64(off, t) ((uint64_t)(((off) + krow(t) * 64) >> 4) + ((uint64_t)((t) == 6 ? (3584 - 512) >> 4 : 0) << 32))

#define PL(k) (((k) - 3) * PLANE)
__device__ __forceinline__ void st_word(uint32_t* p, uint32_t v) { asm volatile("st.relaxed.gpu.global.u32 [%0], %1;" ::"l"(p), "r"(v) : "memory"); }
__device__ __forceinline__ uint32_t ld_word(const uint32_t* p) { uint32_t v; asm volatile("ld.relaxed.gpu.global.u32 %0, [%1];" : "=r"(v) : "l"(p) : "memory"); return v; }
__device__ __forceinline__ void tag_slice(uint32_t* w, uint32_t tag) { w[0] = settag(w[0], tag); w[4] = settag(w[4], tag); w[8] = settag(w[8], tag); w[12] = settag(w[12], tag); }
template <int O>
__device__ __forceinline__ void send_slice(uint4* dst, int lane, const uint32_t* w) {
    st_pkt<O>(dst, w[0], w[1], w[2], w[3]);
    st_pkt<O + 32>(dst, w[4], w[5], w[6], w[7]);
    st_pkt<O + 64>(dst, w[8], w[9], w[10], w[11]);
    asm volatile("{ .reg .b64 t; mov.b64 t, {%1,%2}; st.relaxed.gpu.global.b64 [%0+%3], t; }" ::"l"((char*)dst - lane * 8), "r"(w[12]), "r"(w[13]), "n"(16 * (O + 96)) : "memory");
}
struct Wide { unsigned __int128 q[3]; uint64_t h; };
__device__ __forceinline__ Wide widen(const uint32_t* w) {
    Wide r;
#pragma unroll
    for (int k = 0; k < 3; k++) asm volatile("mov.b128 %0, {%1,%2,%3,%4};" : "=q"(r.q[k]) : "r"(w[4 * k]), "r"(w[4 * k + 1]), "r"(w[4 * k + 2]), "r"(w[4 * k + 3]));
    asm volatile("mov.b64 %0, {%1,%2};" : "=l"(r.h) : "r"(w[12]), "r"(w[13]));
    return r;
}
template <int O>
__device__ __forceinline__ void send_wide(uint4* dst, int lane, const Wide& v) {
    asm volatile("st.relaxed.gpu.global.b128 [%0+%4], %1;\n st.relaxed.gpu.global.b128 [%0+%5], %2;\n st.relaxed.gpu.global.b128 [%0+%6], %3;"
                 ::"l"(dst), "q"(v.q[0]), "q"(v.q[1]), "q"(v.q[2]), "n"(16 * O), "n"(16 * (O + 32)), "n"(16 * (O + 64)) : "memory");
    asm volatile("st.relaxed.gpu.global.b64 [%0+%2], %1;" ::"l"((char*)dst - lane * 8), "l"(v.h), "n"(16 * (O + 96)) : "memory");
}
#define RW4(v, o) "+r"(v[o]), "+r"(v[(o) + 1]), "+r"(v[(o) + 2]), "+r"(v[(o) + 3])
#define RW2(v, o) "+r"(v[o]), "+r"(v[(o) + 1])
#define WR4(v, o) "=&r"(v[o]), "=&r"(v[(o) + 1]), "=&r"(v[(o) + 2]), "=&r"(v[(o) + 3])
#define LDP(a, b, c, d, addr, off) "ld.relaxed.gpu.global.b128 q, [" addr "+" off "];\n mov.b128 {" a "," b "," c "," d "}, q;\n"
#define LDH(a, b, addr, off) "ld.relaxed.gpu.global.b64 h, [" addr "+" off "];\n mov.b64 {" a "," b "}, h;\n"
#define VOTE_OK "and.b32 t, t, 1;\n setp.ne.u32 p, t, 0;\n vote.sync.any.pred p, p, 0xffffffff;\n @!p bra.uni DN;\n"
#define CHK(x, tag) "lop3.b32 t, " x ", " tag ", t, 0xBE;\n"
__device__ __forceinline__ void check_cnt(uint32_t v, const uint32_t* p, uint32_t target) {
    asm volatile("{ .reg .pred p; .reg .b32 n, t; mov.u32 n, 0; mov.u32 t, %2;\n LP:\n"
                 "sub.s32 t, t, %1;\n setp.lt.s32 p, t, 0;\n vote.sync.any.pred p, p, 0xffffffff;\n @!p bra.uni DN;\n ld.relaxed.gpu.global.u32 t, [%0];\n" SPIN_TAIL("7")
                 ::"l"(p), "r"(target), "r"(v) : "memory");
}
__device__ __forceinline__ void poll_cnt(const uint32_t* p, uint32_t target) {
    asm volatile("{ .reg .pred p; .reg .b32 n, t; mov.u32 n, 0;\n LP:\n"
                 "ld.relaxed.gpu.global.u32 t, [%0];\n sub.s32 t, t, %1;\n setp.lt.s32 p, t, 0;\n vote.sync.any.pred p, p, 0xffffffff;\n @!p bra.uni DN;\n" SPIN_TAIL("1")
                 ::"l"(p), "r"(target) : "memory");
}
template <int STR>
__device__ __forceinline__ void poll4_kv(uint32_t* v, const uint4* p, uint32_t tag) {
    asm volatile("{ .reg .pred p; .reg .b32 n, t; .reg .b128 q; mov.u32 n, 0;\n LP:\n"
                 LDP("%0", "%1", "%2", "%3", "%16", "0") LDP("%4", "%5", "%6", "%7", "%16", "%18")
                 LDP("%8", "%9", "%10", "%11", "%16", "%19") LDP("%12", "%13", "%14", "%15", "%16", "%20")
                 "xor.b32 t, %0, %17;\n" CHK("%4", "%17") CHK("%8", "%17") CHK("%12", "%17") VOTE_OK SPIN_TAIL("2")
                 : WR4(v, 0), WR4(v, 4), WR4(v, 8), WR4(v, 12)
                 : "l"(p), "r"(tag), "n"(16 * STR), "n"(32 * STR), "n"(48 * STR)
                 : "memory");
}
template <int B>
__device__ __forceinline__ void blk_load(uint32_t (&A)[8][14], const uint4* src, int lane) {
    ld_pkt<0>(&A[2 * B][0], src); ld_pkt<32>(&A[2 * B][4], src); ld_pkt<64>(&A[2 * B][8], src);
    ld_pkt<512>(&A[2 * B + 1][0], src); ld_pkt<544>(&A[2 * B + 1][4], src); ld_pkt<576>(&A[2 * B + 1][8], src);
    asm volatile("{ .reg .b64 h;\n" LDH("%0", "%1", "%4", "1536") LDH("%2", "%3", "%4", "9728") "}"
                 : "=&r"(A[2 * B][12]), "=&r"(A[2 * B][13]), "=&r"(A[2 * B + 1][12]), "=&r"(A[2 * B + 1][13])
                 : "l"((const char*)src - lane * 8) : "memory");
}
#define BLK_TEST "xor.b32 t, %0, %30;\n" CHK("%4", "%30") CHK("%8", "%30") CHK("%12", "%30") CHK("%16", "%30") CHK("%20", "%30") CHK("%24", "%30") CHK("%26", "%30") VOTE_OK
template <int B>
__device__ __forceinline__ void blk_check(uint32_t (&A)[8][14], const uint4* src, int lane, uint32_t tag) {
    asm volatile("{ .reg .pred p; .reg .b32 n, t; .reg .b128 q; .reg .b64 h, a8;\n" BLK_TEST
                 "mov.u32 n, 0;\n mad.wide.s32 a8, %29, -8, %28;\n LP:\n"
                 LDP("%0", "%1", "%2", "%3", "%28", "0") LDP("%4", "%5", "%6", "%7", "%28", "512") LDP("%8", "%9", "%10", "%11", "%28", "1024")
                 LDP("%12", "%13", "%14", "%15", "%28", "8192") LDP("%16", "%17", "%18", "%19", "%28", "8704") LDP("%20", "%21", "%22", "%23", "%28", "9216")
                 LDH("%24", "%25", "a8", "1536") LDH("%26", "%27", "a8", "9728") BLK_TEST SPIN_TAIL("3")
                 "\n and.b32 %0, %0, -2; and.b32 %4, %4, -2; and.b32 %8, %8, -2; and.b32 %12, %12, -2; and.b32 %16, %16, -2; and.b32 %20, %20, -2; and.b32 %24, %24, -2; and.b32 %26, %26, -2;"
                 : RW4(A[2 * B], 0), RW4(A[2 * B], 4), RW4(A[2 * B], 8), RW4(A[2 * B + 1], 0), RW4(A[2 * B + 1], 4), RW4(A[2 * B + 1], 8),
                   RW2(A[2 * B], 12), RW2(A[2 * B + 1], 12)
                 : "l"(src), "r"(lane), "r"(tag)
                 : "memory");
}
__device__ __forceinline__ void st_async4(uint32_t a, uint32_t x, uint32_t y, uint32_t z, uint32_t w, uint32_t bar) {
    asm volatile("st.async.weak.shared::cluster.mbarrier::complete_tx::bytes.v4.b32 [%0], {%1,%2,%3,%4}, [%5];" ::"r"(a), "r"(x), "r"(y), "r"(z), "r"(w), "r"(bar) : "memory");
}
__device__ __forceinline__ uint32_t mapa(uint32_t a, uint32_t cta) { uint32_t r; asm("mapa.shared::cluster.u32 %0, %1, %2;" : "=r"(r) : "r"(a), "r"(cta)); return r; }
__device__ __forceinline__ void stat_load(uint32_t* v, const uint4* p) { ld_pkt<0>(v, p); ld_pkt<512>(v + 4, p); }
__device__ __forceinline__ void stat_check(uint32_t* v, const uint4* p, uint32_t tag) {
    asm volatile("{ .reg .pred p; .reg .b32 n, t; .reg .b128 q; mov.u32 n, 0;\n LP:\n"
                 "xor.b32 t, %3, %9;\n" CHK("%7", "%9") VOTE_OK
                 LDP("%0", "%1", "%2", "%3", "%8", "0") LDP("%4", "%5", "%6", "%7", "%8", "8192") SPIN_TAIL("4")
                 : RW4(v, 0), RW4(v, 4) : "l"(p), "r"(tag) : "memory");
}
__device__ __forceinline__ uint32_t x_bits(const uint32_t* X) {
    uint32_t r;
    asm volatile("{ .reg .b32 a, b; prmt.b32 a, %1, %2, 0x0040; prmt.b32 b, %3, %4, 0x0040; prmt.b32 %0, a, b, 0x5410; }" : "=r"(r) : "r"(X[0]), "r"(X[4]), "r"(X[8]), "r"(X[12]));
    return r;
}
template <int O>
__device__ __forceinline__ void slice_load(uint32_t* v, const uint4* p, int lane) {
    ld_pkt<O>(v, p); ld_pkt<O + 32>(v + 4, p); ld_pkt<O + 64>(v + 8, p);
    asm volatile("{ .reg .b64 h;\n" LDH("%0", "%1", "%2", "%3") "}" : "=r"(v[12]), "=r"(v[13]) : "l"((const char*)p - lane * 8), "n"(16 * (O + 96)) : "memory");
}
#define SLICE_TEST "xor.b32 t, %0, %16;\n" CHK("%4", "%16") CHK("%8", "%16") CHK("%12", "%16") VOTE_OK
template <int O>
__device__ __forceinline__ void slice_check(uint32_t* v, const uint4* p, int lane, uint32_t tag) {
    asm volatile("{ .reg .pred p; .reg .b32 n, t; .reg .b128 q; .reg .b64 h;\n" SLICE_TEST "mov.u32 n, 0;\n LP:\n"
                 LDP("%0", "%1", "%2", "%3", "%14", "%17") LDP("%4", "%5", "%6", "%7", "%14", "%18") LDP("%8", "%9", "%10", "%11", "%14", "%19")
                 LDH("%12", "%13", "%15", "%20") SLICE_TEST SPIN_TAIL("5")
                 : RW4(v, 0), RW4(v, 4), RW4(v, 8), RW2(v, 12)
                 : "l"(p), "l"((const char*)p - lane * 8), "r"(tag), "n"(16 * O), "n"(16 * (O + 32)), "n"(16 * (O + 64)), "n"(16 * (O + 96))
                 : "memory");
}
__device__ __forceinline__ void x_fix(uint32_t* X, uint32_t bits) {
    X[0] = __byte_perm(X[0], bits, 0x3214); X[4] = __byte_perm(X[4], bits, 0x3215); X[8] = __byte_perm(X[8], bits, 0x3216); X[12] = __byte_perm(X[12], bits, 0x3217);
}
__device__ __forceinline__ void sts4(uint32_t a, uint32_t x, uint32_t y, uint32_t z, uint32_t w) {
    asm volatile("st.shared.v4.u32 [%0], {%1,%2,%3,%4};" ::"r"(a), "r"(x), "r"(y), "r"(z), "r"(w) : "memory");
}
__device__ __forceinline__ void lds4(uint32_t* v, uint32_t a) {
    asm volatile("ld.shared.v4.u32 {%0,%1,%2,%3}, [%4];" : "=r"(v[0]), "=r"(v[1]), "=r"(v[2]), "=r"(v[3]) : "r"(a) : "memory");
}
struct LnCoef { uint32_t hi, lo, sh; };
__device__ __forceinline__ LnCoef ln_coef(float sum, float sq) {
    sum += __shfl_xor_sync(0xffffffffu, sum, 1); sq += __shfl_xor_sync(0xffffffffu, sq, 1);
    sum += __shfl_xor_sync(0xffffffffu, sum, 2); sq += __shfl_xor_sync(0xffffffffu, sq, 2);
    const float mean = sum * (1.f / 448.f);
    const float var = fmaxf(fmaf(-mean, mean, sq * (1.f / 448.f)), 0.f);
    const float sc = rsqrtf(var + 1e-5f);
    LnCoef r;
    r.hi = pack2(sc, sc);
    const float lo = sc - bf_lo(r.hi), sh = -mean * sc;
    r.lo = pack2(lo, lo);
    r.sh = pack2(sh, sh);
    return r;
}
template <int B>
__device__ __forceinline__ void normalize(uint32_t (&A)[8][14], const LnCoef& c0, const LnCoef& c1) {
#pragma unroll
    for (int s = 2 * B; s < 2 * B + 2; s++)
#pragma unroll
        for (int i = 0; i < 14; i++) {
            const LnCoef& k = (i & 1) ? c1 : c0;
            asm("{ .reg .b32 t; fma.rn.bf16x2 t, %0, %2, %3; fma.rn.bf16x2 %0, %0, %1, t; }" : "+r"(A[s][i]) : "r"(k.hi), "r"(k.lo), "r"(k.sh));
        }
}
__device__ __forceinline__ void slice_stats(const uint32_t* w, float* st) {
    float a = 0.f, b = 0.f, p = 0.f, q = 0.f;
#pragma unroll
    for (int i = 0; i < 7; i++) {
        const float e0 = bf_lo(w[2 * i]), e1 = bf_hi(w[2 * i]), e2 = bf_lo(w[2 * i + 1]), e3 = bf_hi(w[2 * i + 1]);
        a += e0 + e1; b += e2 + e3;
        p = fmaf(e0, e0, p); p = fmaf(e1, e1, p); q = fmaf(e2, e2, q); q = fmaf(e3, e3, q);
    }
    a += __shfl_xor_sync(0xffffffffu, a, 1); p += __shfl_xor_sync(0xffffffffu, p, 1); b += __shfl_xor_sync(0xffffffffu, b, 1); q += __shfl_xor_sync(0xffffffffu, q, 1);
    a += __shfl_xor_sync(0xffffffffu, a, 2); p += __shfl_xor_sync(0xffffffffu, p, 2); b += __shfl_xor_sync(0xffffffffu, b, 2); q += __shfl_xor_sync(0xffffffffu, q, 2);
    st[0] = a; st[1] = p; st[2] = b; st[3] = q;
}
__device__ __forceinline__ void dual_softmax(const float* p, uint32_t* out) {
    constexpr float L = 1.4426950408889634f;
#pragma unroll
    for (int r = 0; r < 2; r++) {
        float mx = fmaxf(p[2 * r], p[2 * r + 1]), mn = fminf(p[2 * r], p[2 * r + 1]);
#pragma unroll
        for (int i = 1; i < 7; i++) {
            mx = fmaxf(mx, fmaxf(p[4 * i + 2 * r], p[4 * i + 2 * r + 1]));
            mn = fminf(mn, fminf(p[4 * i + 2 * r], p[4 * i + 2 * r + 1]));
        }
        mx = fmaxf(mx, __shfl_xor_sync(0xffffffffu, mx, 1));
        mn = fminf(mn, __shfl_xor_sync(0xffffffffu, mn, 1));
        const float bx = -mx * L, bn = mn * L;
        float ep[14], en[14], sp = 0.f, sn = 0.f;
#pragma unroll
        for (int i = 0; i < 14; i++) {
            const float v = p[4 * (i >> 1) + 2 * r + (i & 1)];
            ep[i] = ex2(fmaf(v, L, bx));
            en[i] = ex2(fmaf(v, -L, bn));
            sp += ep[i]; sn += en[i];
        }
        sp += __shfl_xor_sync(0xffffffffu, sp, 1);
        sn += __shfl_xor_sync(0xffffffffu, sn, 1);
        const float ip = rcp(sp), in = rcp(sn);
#pragma unroll
        for (int i = 0; i < 7; i++) {
            out[4 * i + r] = pack2(ep[2 * i] * ip, ep[2 * i + 1] * ip);
            out[4 * i + 2 + r] = pack2(en[2 * i] * in, en[2 * i + 1] * in);
        }
    }
}
__device__ __forceinline__ float geglu(float g, float u) {
    const float t = tanh_hw(g * fmaf(g * g, 0.7978845608028654f * 0.044715f, 0.7978845608028654f));
    const float gu = g * u;
    return fmaf(t, gu, gu);
}
__device__ __forceinline__ void phi_gemm(const float* t, float* p) {
    uint32_t w[14];
#pragma unroll
    for (int i = 0; i < 14; i++) w[i] = pack2(t[2 * i], t[2 * i + 1]);
    const uint64_t db = BASE128(OFF_WPHI, 16, 0);
    wg_fence();
    mma_rs56<0, 0>(p, w[0], w[1], w[2], w[3], 0, db);
    mma_rs56<0, 2>(p, w[4], w[5], w[6], w[7], 1, db);
    mma_rs56<0, 4>(p, w[8], w[9], w[10], w[11], 1, db);
    mma_rs56<0, 6>(p, w[12], w[13], 0u, 0u, 1, db);
    wg_commit();
    wg_wait<0>();
}

}

#define BAR(i) (bars + 8 * (i))
#define R_WAIT() mbar_wait_b(BAR(slot), ph, spins)
#define WSUM(i)
#define R_ADJ (slot * (STAGE >> 4))
#define R_NEXT() do { eb2 = eb1; eb1 = BAR(B_EMPTY + slot); if (++slot == NST) { slot = 0; ph ^= 1; } } while (0)
#define R_RELEASE(k) do { if (lane == 0) mbar_arrive((k) == 1 ? eb1 : eb2); } while (0)
#define PUSH_BEGIN() do { mbar_wait_b(BAR(B_ACK + wgi), ackph, spins); ackph ^= 1; } while (0)
#define PUSH_ACK() do { __syncwarp(); if (lane == 0) asm volatile("mbarrier.arrive.shared::cluster.b64 _, [%0];" ::"r"(mapa(BAR(B_ACK + wgi), hr ^ 1)) : "memory"); } while (0)

__global__ void __cluster_dims__(2, 1, 1) __launch_bounds__(384, 1)
fused_kernel(Scratch* const sc, const __nv_bfloat16* __restrict__ x_in, const __nv_bfloat16* __restrict__ w_phi, const int trips,
             const __nv_bfloat16* __restrict__ wg, const __nv_bfloat16* __restrict__ wu, const __nv_bfloat16* __restrict__ wd,
             const __grid_constant__ Maps maps) {
    extern __shared__ __align__(1024) unsigned char smem_raw[];
    const uint32_t sb = s2u(smem_raw);
    const uint32_t bars = sb + OFF_BAR;
    const int wgi = __shfl_sync(0xffffffffu, threadIdx.x >> 7, 0);
    const int hr = blockIdx.x & 1, ck = blockIdx.x >> 1;
    const int gp = (ck - 4) & 7, q7 = ((ck - 36) * 37) >> 8;
    const int pr = __shfl_sync(0xffffffffu, ck < 4 ? ck : (ck < 36 ? (ck - 4) >> 3 : q7), 0);
    const int tile = __shfl_sync(0xffffffffu, ck < 4 ? 0 : (ck < 36 ? (gp ? 2 * gp : 1) : 2 * (ck - 36 - 7 * q7) + 3), 0);
    const int sl = 2 * pr + hr;
    STAMP(0);
    GSTAMP(60);
    if (threadIdx.x == 256) {
#pragma unroll
        for (int i = 0; i < NST; i++) mbar_init(BAR(i), 1);
        asm volatile("fence.mbarrier_init.release.cluster;" ::: "memory");
    }
    if (threadIdx.x == 288) {
        if ((sb & 0x3FFFF) != SB0) asm volatile("trap;");
#pragma unroll
        for (int i = NST; i < B_COUNT; i++) mbar_init(BAR(i), i >= B_ACK ? 4 : (i < B_RECV || i == B_LATE ? 8 : 1));
        asm volatile("fence.mbarrier_init.release.cluster;" ::: "memory");
    }
    __syncwarp();
    asm volatile("barrier.cluster.arrive.relaxed.aligned;" ::: "memory");

    if (wgi == 2) {
        asm volatile("setmaxnreg.dec.sync.aligned.u32 40;");
        const int t128 = fresh_tid() & 127, w = __shfl_sync(0xffffffffu, t128 >> 5, 0), lane = t128 & 31;
        uint32_t e0[2] = {0, 0}, e1[2] = {0, 0}, cw_target = 0, kseq;
        if (w == 0) {
#pragma unroll 1
            for (int n = 0; n < NST; n++) {
                const uint32_t dst = sb + n * STAGE, fb = BAR(n);
                asm volatile(ELECT "mbarrier.arrive.expect_tx.shared::cta.b64 _, [%0], %1; }" ::"r"(fb), "r"(n < 2 ? 2 * STAGE : STAGE) : "memory");
                if (n < 2) {
                    tma3x(sb + OFF_H + n * STAGE, &maps.x, tile * 128 + n * 64, fb);
                    tma3x(dst, &maps.x, tile * 128 + n * 64 + 32, fb);
                } else {
                    if (n == 3) mbar_wait(BAR(1), 0);
                    const int c0 = (n < 4 ? 448 : 896) + 56 * sl, r0 = 224 * (n & 1);
                    tma2d(dst, &maps.qkv, c0, r0, fb);
                    tma2d(dst + HALF, &maps.qkv, c0, r0 + 112, fb);
                }
            }
            asm volatile("barrier.cluster.wait.aligned;" ::: "memory");
            kseq = ld_word(g_c1 + (sl * 8 * 16 + tile) * 32);
            cw_target = (ld_word(g_cw + sl * 32) & ~15u) + 16;
#pragma unroll 1
            for (int k = 0; k < 2; k++) {
                const int n = t128 + 32 * k;
                int m = n - 2 - (n > PACK);
                const bool packed = m >= 30 ? (m < 38 || m >= 52) : m >= 22;
                if (m >= 30) m -= 30;
                if (n == PACK) m = tile < 8 ? tile : tile + 14;
                const int rot = n < 8 ? 0 : pr;
                const int ra = 112 * kblk(rot, m & 3), rb = 112 * kblk(rot, 2 * m & 3), rc = 112 * kblk(rot, (2 * m + 1) & 3);
                int kind = 0, m0, m1, c0, c1, r0, r1;
                if (m < 8) { m0 = m1 = m < 6 ? 1 : 2; c0 = c1 = (m < 2 ? 448 : (m < 4 ? 896 : 0)) + 56 * sl; r0 = rb; r1 = rc; }
                else if (m < 20) { m0 = 3; m1 = 4; c0 = c1 = 224 * sl + 32 * hr + 64 * ((m - 8) >> 2); r0 = r1 = ra; }
                else if (m < 22) { kind = 2; m0 = 5; m1 = 6; c0 = c1 = 224 * sl + (hr ? 0 : 192); r0 = rb; r1 = rc; }
                else { m0 = m1 = 7; c0 = c1 = 56 * (2 * ((pr + (m >> 1) - 10) & 3) + hr); r0 = 224 * (sl ^ (m & 1)); r1 = r0 + 112; }
                if (packed) { kind = 1; r0 = sl * 16 + (m < 8 ? m : m - 14); r1 = 0; }
                e0[0] = e0[1]; e1[0] = e1[1];
                e0[1] = kind | (m0 << 2) | (m1 << 6) | (c0 << 10) | (c1 << 21);
                e1[1] = r0 | (r1 << 16);
            }
        } else {
            const int j = t128 - 32;
            kseq = ld_word(g_c1 + (sl * 8 * 16 + tile) * 32);
            asm volatile("barrier.cluster.wait.aligned;" ::: "memory");
            uint2 wv[7];
            const int k = j < 56 ? j : 55, hh = k >= 28;
#pragma unroll
            for (int i = 0; i < 7; i++) wv[i] = __ldg(reinterpret_cast<const uint2*>(w_phi + (sl * 56 + k) * 28) + i);
#pragma unroll 1
            for (int i = j; i < 7168 / 16; i += 96) sts4(sb + OFF_WPHI + i * 16, 0, 0, 0, 0);
            bar_sync(5, 96);
            if (j < 56) {
                uint32_t a4[4];
#pragma unroll
                for (int q = 0; q < 4; q++) a4[q] = sb + OFF_WPHI + (4 * hh + q) * 128 + ((((k >> 3) ^ (4 * hh + q)) & 7) << 4) + (k & 7) * 2;
                FOR14(const uint32_t v = (t & 1) ? wv[t >> 1].y : wv[t >> 1].x;
                      asm volatile("{ .reg .b16 l, h; mov.b32 {l, h}, %2; st.shared.u16 [%0+%3], l; st.shared.u16 [%1+%3], h; }"
                                   ::"r"(a4[t >= 7 ? 2 : 0]), "r"(a4[t >= 7 ? 3 : 1]), "r"(v), "n"((t % 7) * 1024) : "memory"));
            }
            __syncwarp();
            fence_async();
            kseq = __shfl_sync(0xffffffffu, kseq, 0);
            bar_arrive(1, 224);
            bar_arrive(9, 224);
        }
        kseq = __shfl_sync(0xffffffffu, kseq, 0);
        int slot = 0, ph = 0, n = NST;
#pragma unroll 1
        for (int layer = 0; layer < 3; layer++) {
            if (w == 0) {
                const int nend = layer == 0 ? 11 : (layer == 1 ? 42 : 63);
#pragma unroll 1
                for (; n < nend; n++) {
                const uint32_t w0 = __shfl_sync(0xffffffffu, n < 32 ? e0[0] : e0[1], n & 31), w1 = __shfl_sync(0xffffffffu, n < 32 ? e1[0] : e1[1], n & 31);
                const uint32_t dst = sb + slot * STAGE, fb = BAR(n == PACK ? B_PACK : slot);
                const CUtensorMap* m0 = &maps.x + ((w0 >> 2) & 15);
                const CUtensorMap* m1 = &maps.x + ((w0 >> 6) & 15);
                const int c0 = (w0 >> 10) & 2047, c1 = w0 >> 21, r0 = w1 & 0xffff, r1 = w1 >> 16;
                if (n == 25) {
                    int it = 0;
                    uint32_t v;
                    do { asm volatile("ld.acquire.gpu.global.u32 %0, [%1];" : "=r"(v) : "l"(g_cw + sl * 32) : "memory"); } while ((int)(v - cw_target) < 0 && ++it < 0x400000);
                    asm volatile("fence.proxy.async.global;" ::: "memory");
                    __syncwarp();
                }
                mbar_wait(BAR(B_EMPTY + slot), ph);
                __syncwarp();
                asm volatile(ELECT "mbarrier.arrive.expect_tx.shared::cta.b64 _, [%0], %1; }" ::"r"(fb), "r"(STAGE) : "memory");
                if ((w0 & 3) == 0) {
                    tma2d(dst, m0, c0, r0, fb);
                    tma2d(dst + HALF, m1, c1, r1, fb);
                } else if (w0 & 1) {
                    asm volatile(ELECT "cp.async.bulk.shared::cluster.global.mbarrier::complete_tx::bytes [%0], [%1], %2, [%3]; }"
                                 ::"r"(dst), "l"(reinterpret_cast<const char*>(g_wp) + (size_t)r0 * STAGE), "r"(STAGE), "r"(fb) : "memory");
                } else {
                    tma2d(dst, m0, c0, r0, fb); tma2d(dst + 7168, m0, c0, r1, fb);
                    tma2d(dst + HALF, m1, c0, r0, fb); tma2d(dst + HALF + 7168, m1, c0, r1, fb);
                }
                if (n == PFN) {
                    const int b = blockIdx.x;
                    asm volatile(ELECT "cp.async.bulk.prefetch.L2.global [%0], %1; }" ::"l"(wg + b * 6272), "r"(12544) : "memory");
                    asm volatile(ELECT "cp.async.bulk.prefetch.L2.global [%0], %1; }" ::"l"(wu + b * 6272), "r"(12544) : "memory");
                    asm volatile(ELECT "cp.async.bulk.prefetch.L2.global [%0], %1; }" ::"l"(wd + b * 6272), "r"(12544) : "memory");
                }
                if (n == PACK) asm volatile(ELECT "mbarrier.arrive.shared::cta.b64 _, [%0]; }" ::"r"(BAR(slot)) : "memory");
                if (++slot == NST) { slot = 0; ph ^= 1; }
                }
            } else if (w == 1 && layer == 1) {
                constexpr int ps = PACK % NST;
                mbar_wait(BAR(B_PACK), 0);
                asm volatile("{ .reg .pred e; elect.sync _|e, 0xffffffff;\n"
                             "@e cp.async.bulk.global.shared::cta.bulk_group [%0], [%1], %2;\n"
                             "@e cp.async.bulk.commit_group;\n"
                             "@e cp.async.bulk.wait_group.read 0;\n"
                             "@e mbarrier.arrive.shared::cta.b64 _, [%3], 8;\n"
                             "@e cp.async.bulk.wait_group 0;\n"
                             "@e fence.proxy.async.global;\n"
                             "@e red.release.gpu.global.add.u32 [%4], 1; }"
                             ::"l"(reinterpret_cast<char*>(g_wp) + (size_t)(sl * 16 + tile) * STAGE), "r"(sb + ps * STAGE), "r"(STAGE), "r"(BAR(B_EMPTY + ps)), "l"(g_cw + sl * 32) : "memory");
                __syncwarp();
            }
            if (layer < 2) {
            const uint32_t tag = layer ^ 1;
            kseq++;
            bar_sync(7, 384);
            ASTAMP(0);
            if (tile < 15) {
                const int sq = lane >> 3, pk = 8 * w + (lane & (tile == 14 ? 3 : 7));
                uint32_t v[16];
                if (layer == 0) poll_cnt(g_c1 + ((sl * 8 + (w >> 1) * 4 + (tile >> 2)) * 16 + (lane & 15)) * 32, kseq);
                ASTAMP(1);
                poll4_kv<32>(v, g_kv1 + ((sl * 16 + tile) * 16 + 4 * sq) * 32 + pk, tag);
#pragma unroll
                for (int k = 0; k < 4; k++) {
                    float lo = (bf_lo(v[k]) + bf_lo(v[4 + k])) + (bf_lo(v[8 + k]) + bf_lo(v[12 + k]));
                    float hi = (bf_hi(v[k]) + bf_hi(v[4 + k])) + (bf_hi(v[8 + k]) + bf_hi(v[12 + k]));
                    lo += __shfl_xor_sync(0xffffffffu, lo, 8); hi += __shfl_xor_sync(0xffffffffu, hi, 8);
                    lo += __shfl_xor_sync(0xffffffffu, lo, 16); hi += __shfl_xor_sync(0xffffffffu, hi, 16);
                    v[k] = pack2(lo, hi);
                }
                if (sq == 0) st_pkt<0>(g_kv2 + sl * 512 + 32 * tile + pk, settag(v[0], tag), v[1], v[2], v[3]);
            }
            ASTAMP(2);
            {
                const int item = t128 < 112 ? t128 : 112 + (t128 & 3), d = item >> 1;
                const int cc = t128 < 112 ? 2 * (d >= 28) + (item & 1) : item - 112;
                const int r = t128 < 112 ? d : 56 + (cc >> 1) + 2 * ((t128 - 112) >> 2);
                uint32_t ra = sb + OFF_KVB + r * 128 + 4 * cc, rx = (r & 7) << 4;
                asm volatile("" : "+r"(ra), "+r"(rx));
                FOR14(asm volatile("st.shared.u32 [%0+%2], %1;" ::"r"((ra ^ 8) + (((t & 7) << 4) ^ rx)), "r"(0), "n"((t >> 3) * 8192) : "memory"));
                uint32_t v[16];
                asm volatile("" : "+r"(ra), "+r"(rx));
                poll4_kv<8>(v, g_kv2 + sl * 512 + (item >> 3) * 32 + (item & 7), tag);
                FOR14(asm volatile("st.shared.u32 [%0+%2], %1;" ::"r"(ra + (((t & 7) << 4) ^ rx)), "r"(v[t < 7 ? t : t + 1]), "n"((t >> 3) * 8192) : "memory"));
                fence_async();
            }
            bar_arrive(3, 384);
            ASTAMP(3);
            }
        }
    } else {
        asm volatile("setmaxnreg.inc.sync.aligned.u32 232;");
        int lane = fresh_tid() & 31, prf = pr;
#define pr prf
#define g (lane >> 2)
#define c (lane & 3)
#define t128 (w * 32 + lane)
        const int wu = __shfl_sync(0xffffffffu, fresh_tid() >> 5, 0), w = wu & 3;
        const uint32_t xoff = __shfl_sync(0xffffffffu, (3 * PLANE + ((tile * 2 + wgi) * 8) * 512 + w * 128) * 16, 0);
        char* xu = reinterpret_cast<char*>(g_ex) + xoff;
#define FRESH() asm volatile("" : "+l"(xu), "+r"(lane), "+r"(prf))
#define xp0 (reinterpret_cast<uint4*>(xu) + lane)
        const uint32_t hbuf = sb + OFF_H + wgi * STAGE;
        uint32_t spins = 0, slot = 0, ph = 0, eb1 = 0, eb2 = 0, ackph = 0, rcvph = 0, gatph = 0, swp = 0;
        uint32_t ppid = 6;
#define cx(s) (reinterpret_cast<uint32_t*>(reinterpret_cast<uint4*>(xu) + PL(1) + 112 + (s) * 512))
#define stp (reinterpret_cast<uint4*>(xu) + g + PL(0) + 112)
        uint32_t seq = ld_word(cx(sl));
        uint32_t kseq = ld_word(g_c1 + ((sl * 8 + wu) * 16 + tile) * 32);
        uint32_t stag = ld_word(reinterpret_cast<const uint32_t*>(stp + sl * 512) + 3) & 1;
        asm volatile("barrier.cluster.wait.aligned;" ::: "memory");
        STAMP(1);
        uint32_t X[14];
        const uint32_t x0row = (w < 2 ? hbuf : sb + wgi * STAGE) + ((w & 1) * 16 + (lane & 15)) * 128;
        mbar_wait_b(BAR(wgi), 0, spins);
        STAMP(51);
#pragma unroll
        for (int j = 0; j < 4; j++) {
            const int G = 7 * sl + min(2 * j + (lane >> 4), 6);
            uint32_t q2, q3;
            asm volatile("ldmatrix.sync.aligned.m8n8.x4.shared.b16 {%0,%1,%2,%3}, [%4];" : "=r"(X[4 * j]), "=r"(X[4 * j + 1]), "=r"(q2), "=r"(q3)
                         : "r"(x0row + (G >> 3) * 4096 + (((G ^ lane) & 7) << 4)) : "memory");
            if (j < 3) { X[(4 * j + 2) % 14] = q2; X[(4 * j + 3) % 14] = q3; }
        }
#define PUSH_SLICE(W)                                                                          \
    {                                                                                          \
        if (t128 == 0) mbar_expect_tx(BAR(B_RECV + wgi), 7168);                                \
        PUSH_BEGIN();                                                                          \
        const uint32_t ra = mapa(hbuf + 24576 + t128 * 16, hr ^ 1), rb = mapa(sb + OFF_XR + wgi * 3072, hr ^ 1), rbar = mapa(BAR(B_RECV + wgi), hr ^ 1); \
        st_async4(ra, W[0], W[1], W[2], W[3], rbar);                                           \
        st_async4(ra + 2048, W[4], W[5], W[6], W[7], rbar);                                    \
        st_async4(rb + t128 * 16, W[8], W[9], W[10], W[11], rbar);                             \
        asm volatile("st.async.weak.shared::cluster.mbarrier::complete_tx::bytes.v2.b32 [%0], {%1,%2}, [%3];" ::"r"(rb + 2048 + t128 * 8), "r"(W[12]), "r"(W[13]), "r"(rbar) : "memory"); \
    }
#define PULL_SLICE(W)                                                                          \
    {                                                                                          \
        uint32_t t0, t1;                                                                       \
        mbar_wait_b(BAR(B_RECV + wgi), rcvph, spins);                                                   \
        rcvph ^= 1;                                                                            \
        lds4(&A[1][0], hbuf + 24576 + t128 * 16);                                              \
        lds4(&A[1][4], hbuf + 26624 + t128 * 16);                                              \
        lds4(&A[1][8], sb + OFF_XR + wgi * 3072 + t128 * 16);                                  \
        asm volatile("ld.shared.v2.u32 {%0,%1}, [%2];" : "=r"(t0), "=r"(t1) : "r"(sb + OFF_XR + wgi * 3072 + 2048 + t128 * 8) : "memory"); \
        _Pragma("unroll") for (int i = 0; i < 12; i++) A[0][i] = (i & 3) ? W[i] : W[i] & ~1u;  \
        A[1][0] &= ~1u; A[1][4] &= ~1u; A[1][8] &= ~1u;                                        \
        A[0][12] = (hr ? t0 : W[12]) & ~1u; A[0][13] = hr ? t1 : W[13];                        \
        A[1][12] = (hr ? W[12] : t0) & ~1u; A[1][13] = hr ? W[13] : t1;                        \
        asm volatile("" : RW4(A[0], 0), RW4(A[0], 4), RW4(A[0], 8), RW2(A[0], 12), RW4(A[1], 0), RW4(A[1], 4), RW4(A[1], 8), RW2(A[1], 12)); \
        swp = hr * 448;                                                                        \
    }
#define SWB(b, t, db, sh) ((b) == 0 && (t) < 6 ? ((t) < 3 ? db##p : db##m) : db)
#define DECL_DB(b, MK, lbo, sh) const uint64_t db = MK(0, lbo, R_ADJ), dbp = (b) == 0 ? MK(0, lbo, R_ADJ + (swp >> (sh))) : db, dbm = (b) == 0 ? MK(0, lbo, R_ADJ - (swp >> (sh))) : db;
#define PPB 2
#define PP_WAIT() if (wgi == 1) { bar_sync(ppid, 256); ppid ^= 14; }
#define PP_GO() if (wgi == 0) { bar_arrive(ppid, 256); ppid ^= 14; }
#define GAT_DST(B, s2) ((B) == 1 ? hbuf + w * 3584 + (s2) * 1792 : ((s2) ? sb + OFF_KVB + wgi * 8192 : hbuf + 14336) + w * 1792)
#define GAT_ISSUE(B, base)                                                                     \
    {                                                                                          \
        const char* gs = xu + ((base) + kblk(pr, B) * 1024) * 16;                              \
        asm volatile("{ .reg .pred e; elect.sync _|e, 0xffffffff;\n"                           \
                     "@e mbarrier.arrive.expect_tx.shared::cta.b64 _, [%3], 3584;\n"           \
                     "@e cp.async.bulk.shared::cluster.global.mbarrier::complete_tx::bytes [%0], [%2], 1792, [%3];\n" \
                     "@e cp.async.bulk.shared::cluster.global.mbarrier::complete_tx::bytes [%1], [%2+8192], 1792, [%3]; }" \
                     ::"r"(GAT_DST(B, 0)), "r"(GAT_DST(B, 1)), "l"(gs), "r"(BAR(B_GAT + wu * 2 + ((B) >> 1))) : "memory"); \
        __syncwarp();                                                                          \
    }
#define GAT_FETCH(B)                                                                           \
    {                                                                                          \
        mbar_wait_b(BAR(B_GAT + wu * 2 + ((B) >> 1)), (gatph >> (B)) & 1, spins);                          \
        gatph ^= 1 << (B);                                                                     \
        _Pragma("unroll") for (int s2 = 0; s2 < 2; s2++) {                                     \
            const uint32_t ga = GAT_DST(B, s2) + lane * 16;                                    \
            lds4(&A[2 * (B) + s2][0], ga); lds4(&A[2 * (B) + s2][4], ga + 512); lds4(&A[2 * (B) + s2][8], ga + 1024); \
            asm volatile("ld.shared.v2.u32 {%0,%1}, [%2];" : "=r"(A[2 * (B) + s2][12]), "=r"(A[2 * (B) + s2][13]) : "r"(ga - lane * 8 + 1536) : "memory"); \
        }                                                                                      \
    }
#define LATE_ARRIVE() do { if (lane == 0) mbar_arrive(BAR(B_LATE)); } while (0)
#define LATE_WAIT() do { mbar_wait_b(BAR(B_LATE), gatph & 1, spins); gatph ^= 1; } while (0)
#define PT 3
#define PREP(b, t, remote)                                                                     \
    if constexpr ((b) < 3 && (t) == PT) {                                                      \
        wg_commit();                                                                           \
        STAMP(74 + 6 * (step & 1) + 2 * (b));                                                  \
        if (remote) {                                                                          \
            if constexpr ((b) == 0) { blk_load<2>(A, BLK(xsrc, 2), lane); if (XG3 == 3) blk_load<3>(A, BLK(xsrc, 3), lane); GAT_FETCH(1) }       \
            blk_check<((b) + 1) & 3>(A, BLK(xsrc, (b) + 1), lane, xtag);                       \
            if constexpr ((b) == 0 && XG3 == 0) blk_load<3>(A, BLK(xsrc, 3), lane); \
            if constexpr ((b) == 0 && XG3 == 2) GAT_ISSUE(3, (step & 1) ? PL(2) : PL(0))                        \
        }                                                                                      \
        STAMP(75 + 6 * (step & 1) + 2 * (b));                                                  \
        normalize<((b) + 1) & 3>(A, k0, k1);                                                   \
        asm volatile("" : RW4(A[(2 * (b) + 2) & 7], 0), RW4(A[(2 * (b) + 2) & 7], 4), RW4(A[(2 * (b) + 2) & 7], 8), RW2(A[(2 * (b) + 2) & 7], 12), \
                          RW4(A[(2 * (b) + 3) & 7], 0), RW4(A[(2 * (b) + 3) & 7], 4), RW4(A[(2 * (b) + 3) & 7], 8), RW2(A[(2 * (b) + 3) & 7], 12)); \
        wg_fence();                                                                            \
    }
#define X0_BLOCK(b)                                                                            \
    { const int rr = lane & 7, hi = lane >> 4;                                                 \
    const uint32_t rowa = (w < 2 ? hbuf : sb + wgi * STAGE) + ((w & 1) * 16 + (lane & 15)) * 128; \
    FOR7(constexpr int G = 14 * (b) + (t < 3 ? 2 * t : (t < 6 ? 2 * t + 1 : 6));               \
         uint32_t q0, q1, q2, q3;                                                              \
         const uint32_t ad = t < 6 ? rowa + (((((G & 7) + hi) ^ rr) & 7) << 4) + ((G & 7) == 7 ? hi * 4096 : 0) : rowa + ((G + 7 * hi) >> 3) * 4096 + ((((G + 7 * hi) ^ rr) & 7) << 4); \
         asm volatile("ldmatrix.sync.aligned.m8n8.x4.shared.b16 {%0,%1,%2,%3}, [%4+%5];" : "=r"(q0), "=r"(q1), "=r"(q2), "=r"(q3) \
                      : "r"(ad), "n"(t < 6 ? (G >> 3) * 4096 : 0) : "memory");                 \
         if (t < 3) { A[2 * (b)][4 * t] = q0; A[2 * (b)][4 * t + 1] = q1; A[2 * (b)][4 * t + 2] = q2; A[2 * (b)][4 * t + 3] = q3; } \
         else if (t < 6) { A[2 * (b) + 1][(4 * t - 12) & 15] = q0; A[2 * (b) + 1][((4 * t - 12) & 15) + 1] = q1; A[2 * (b) + 1][((4 * t - 12) & 15) + 2] = q2; A[2 * (b) + 1][((4 * t - 12) & 15) + 3] = q3; } \
         else { A[2 * (b)][12] = q0; A[2 * (b)][13] = q1; A[2 * (b) + 1][12] = q2; A[2 * (b) + 1][13] = q3; }); }
#define BLK(base, b) ((base) + kblk(pr, b) * 1024)

#pragma unroll 1
        for (int step = 0; step < 4; step++) {
            FRESH();
            const uint32_t tag = (step >> 1) ^ 1;
            const int so = (step >> 1) * 24 + (step & 1) * 12;
            (void)so;
            uint32_t A[8][14];
            uint4* const xsrc = xp0 + ((step & 1) ? PL(2) : PL(0));
            const uint32_t xtag = (step & 1) ? tag : ((seq >> 3) & 1) ^ 1;
            uint32_t xbits;
            {
                float st[4];
                slice_stats(X, st);
                stag ^= 1;
                xbits = x_bits(X);
                tag_slice(X, xtag);
                if (step) send_slice<0>(xsrc + sl * 512, lane, X);
                if (c == 0) st_pkt<0>(stp + sl * 512, __float_as_uint(st[0]), __float_as_uint(st[1]), __float_as_uint(st[2]), settag(__float_as_uint(st[3]), stag));
            }
            STAMP(2 + so);
            uint32_t sv[8];
            if (step == 0) {
                X0_BLOCK(0) X0_BLOCK(1) X0_BLOCK(2) X0_BLOCK(3)
                mbar_wait_b(BAR(wgi ^ 1), 0, spins);
                R_NEXT();
                R_NEXT();
                R_RELEASE(2);
                stat_load(sv, stp + c * 1024);
                stat_check(sv, stp + c * 1024, stag);
                STAMP(52 + step);
            } else {
                kill<14>(A[2]); kill<14>(A[3]); kill<14>(A[4]); kill<14>(A[5]); kill<14>(A[6]); kill<14>(A[7]);
                PUSH_SLICE(X)
                stat_load(sv, stp + c * 1024);
                PULL_SLICE(X)
                stat_check(sv, stp + c * 1024, stag);
                STAMP(52 + step);
                GAT_ISSUE(1, (step & 1) ? PL(2) : PL(0))
                if (XG3 == 1) GAT_ISSUE(3, (step & 1) ? PL(2) : PL(0))
            }
            LnCoef k0, k1;
            {
                k0 = ln_coef(__uint_as_float(sv[0]) + __uint_as_float(sv[4]), __uint_as_float(sv[1]) + __uint_as_float(sv[5]));
                k1 = ln_coef(__uint_as_float(sv[2]) + __uint_as_float(sv[6]), __uint_as_float(sv[3] & ~1u) + __uint_as_float(sv[7] & ~1u));
            }
            STAMP(3 + so);
            GSTAMP(70 + step);

            if ((step & 1) == 0) {
                float tq[28];
#define K_BLOCK(b)                                                                            \
    if ((b) == 1) R_RELEASE(1);                                                               \
    if ((b) == 2 + XT) PUSH_ACK();                                                            \
    if ((b) == 2 && XT && step) GAT_FETCH(3)                                                  \
    if ((b) == 3) { wg_wait<2>(); R_RELEASE(1); }                                             \
    if (((b) & 1) == 0) R_WAIT();                                                             \
    { DECL_DB(b, BASE128, 16, 0)                                                              \
    wg_fence();                                                                               \
    FOR7(mma_rs56<1, D128(((b) & 1) * HALF, t)>(tq, AQ(A, b, t), (b) + t > 0, SWB(b, t, db, 0)); \
         PREP(b, t, step)); }                                                                 \
    wg_commit();                                                                              \
    if ((b) & 1) R_NEXT();
#define P_STAGE(acc, b0)                                                                      \
    R_WAIT();                                                                                 \
    { DECL_DB(b0, BASE128, 16, 0)                                                             \
    wg_fence();                                                                               \
    FOR7(mma_rs56<1, D128(0, t)>(acc, AQ(A, b0, t), (b0) + t > 0, SWB(b0, t, db, 0)));        \
    FOR7(mma_rs56<1, D128(HALF, t)>(acc, AQ(A, (b0) + 1, t), 1, db)); }                       \
    wg_commit();                                                                              \
    R_NEXT();
#define PROJECT(acc) P_STAGE(acc, 0) P_STAGE(acc, 2) wg_wait<1>(); R_RELEASE(2); wg_wait<0>(); R_RELEASE(1);
#define V_PASS()                                                                              \
    {                                                                                         \
        float av[28];                                                                         \
        PROJECT(av)                                                                           \
        const int m = lane >> 3, rr = lane & 7;                                               \
        const uint32_t rowa = hbuf + 16384 + (w * 16 + rr + 8 * (m & 1)) * 128;               \
        const uint32_t one = c == 0 ? 0x00003f80u : 0u;                                       \
        _Pragma("unroll") for (int j = 0; j < 4; j++) {                                       \
            const uint32_t a = rowa + (((2 * j + (m >> 1)) ^ rr) << 4);                       \
            if (j < 3) stsm4(a, pack2(av[8 * j], av[8 * j + 1]), pack2(av[8 * j + 2], av[8 * j + 3]), pack2(av[8 * j + 4], av[8 * j + 5]), pack2(av[8 * j + 6], av[8 * j + 7])); \
            else stsm4(a, pack2(av[24], av[25]), pack2(av[26], av[27]), one, one);            \
        }                                                                                     \
    }
                normalize<0>(A, k0, k1);
                K_BLOCK(0) K_BLOCK(1) K_BLOCK(2) K_BLOCK(3)
                wg_wait<0>();
                R_RELEASE(1);
                STAMP(4 + so);
                if (step == 0) { bar_sync(wgi ? 9 : 1, 224); }
                if (wgi == VW) V_PASS()
                uint32_t PH[28];
                int it = 1;
#pragma unroll 1
                do {
                    float pp[28];
                    phi_gemm(tq, pp);
                    dual_softmax(pp, PH);
                    if (((trips >> (it + 1)) & 1) == 0) continue;
                    {
                        const int m = lane >> 3, rr = lane & 7;
                        const uint32_t rowa = hbuf + (w * 16 + rr + 8 * (m & 1)) * 128;
#pragma unroll
                        for (int j = 0; j < 7; j++) {
                            const int cg = 2 * j + (m >> 1), hi = cg >= 7;
                            stsm4(rowa + hi * 8192 + (((cg - 7 * hi) ^ rr) << 4), PH[4 * j], PH[4 * j + 1], PH[4 * j + 2], PH[4 * j + 3]);
                        }
                    }
                    STAMP(5 + so);
                    if (wgi != VW) V_PASS()
                    fence_async();
                    bar_sync(2, 256);
                    float kv[28];
                    const uint64_t da = BASE128(OFF_H + 16384, 16, 0), dbk = BASE128(OFF_H, 16, wgi * 512);
                    wg_fence();
                    FOR8(constexpr uint64_t o = ((t >> 2) * STAGE + (t & 3) * 2048) >> 4; mma_ss56_tt<o, o>(kv, t > 0, da, dbk));
                    wg_commit();
                    wg_wait<0>();
#pragma unroll
                    for (int hf = 0; hf < 2; hf++) {
                        const int d = 16 * w + g + 8 * hf;
                        if ((d < 56 && (d >= 28) == (c >= 2)) || d == 56) {
                            const int item = d < 56 ? 2 * d + (c & 1) : 112 + c;
                            uint4* dst = g_kv1 + ((sl * 16 + (item >> 3)) * 16 + tile) * 32 + wgi * 16 + (item & 7);
#define KVW(i) pack2(kv[4 * (i) + 2 * hf], kv[4 * (i) + 2 * hf + 1])
                            st_pkt<0>(dst, settag(KVW(0), tag), KVW(1), KVW(2), KVW(3));
                            st_pkt<8>(dst, settag(KVW(4), tag), KVW(5), KVW(6), 0u);
                        }
                    }
                    __syncwarp();
                    kseq++;
                    if (lane == 0) st_word(g_c1 + ((sl * 8 + wu) * 16 + tile) * 32, kseq);
                    bar_arrive(7, 384);
                    STAMP(6 + so);
                    kill<28>(tq);
                    if (QPP) { PP_WAIT() }
                    P_STAGE(tq, 0) P_STAGE(tq, 2)
                    if (QPP) { PP_GO() }
                    wg_wait<1>(); R_RELEASE(2); wg_wait<0>(); R_RELEASE(1);
                    STAMP(7 + so);
                    kill<28>(PH);
                } while (((trips >> (++it)) & 1));
                STAMP(8 + so);
                FRESH();
                if (step) {
                    slice_load<PL(0)>(X, xp0 + sl * 512, lane);
                } else {
                    const uint32_t* xp = reinterpret_cast<const uint32_t*>(x_in + (size_t)(tile * 128 + wu * 16 + g) * 448 + 56 * sl + 2 * c);
#pragma unroll
                    for (int i = 0; i < 7; i++) { X[2 * i] = __ldg(xp + 4 * i); X[2 * i + 1] = __ldg(xp + 4 * i + 8 * 224); }
                }
                bar_sync(3, 384);
                STAMP(9 + so);
                const uint4* const osrc = xp0 + PL(1);
                {
                    float nm[32];
                    const uint64_t db = BASE128(OFF_KVB, 16, 0);
                    wg_fence();
                    FOR7(mma_rs64<0, ((t >> 2) * 8192 + (t & 3) * 32) / 16>(nm, PH[4 * t], PH[4 * t + 1], PH[4 * t + 2], PH[4 * t + 3], t > 0, db));
                    wg_commit();
                    wg_wait<0>();
                    LATE_ARRIVE();
                    const float i00 = rcp(nm[28] + 1e-6f), i01 = rcp(nm[29] + 1e-6f), i10 = rcp(nm[30] + 1e-6f), i11 = rcp(nm[31] + 1e-6f);
                    const float m0 = c >= 2 ? i01 : i00, m1 = c >= 2 ? i11 : i10;
                    uint32_t O[14];
#pragma unroll
                    for (int i = 0; i < 7; i++) {
                        const float f0 = i < 3 ? i00 : (i > 3 ? i01 : m0), f1 = i < 3 ? i10 : (i > 3 ? i11 : m1);
                        O[2 * i] = pack2(nm[4 * i] * f0, nm[4 * i + 1] * f0);
                        O[2 * i + 1] = pack2(nm[4 * i + 2] * f1, nm[4 * i + 3] * f1);
                    }
                    if (OST) { PP_WAIT() }
                    tag_slice(O, tag);
                    send_slice<PL(1)>(xp0 + sl * 512, lane, O);
                    seq++;
                    if (lane == 0) st_word(cx(sl), seq);
                    STAMP(10 + so);
                    PUSH_SLICE(O)
                    if (OST == 1) { PP_GO() }
                    const uint32_t cv = ld_word(cx(lane & 7));
                    PULL_SLICE(O)
                    LATE_WAIT();
                    check_cnt(cv, cx(lane & 7), seq);
                    if (OST == 2) { PP_GO() }
                    STAMP(56 + (step >> 1));
                    GAT_ISSUE(1, PL(1))
                    GAT_ISSUE(3, PL(1))
                    blk_load<2>(A, BLK(osrc, 2), lane);
                }
                float ao[28];
#define WO_BLOCK(b)                                                                           \
    if ((b) > 0) blk_check<b>(A, BLK(osrc, b), lane, tag);                                    \
    if (((b) & 1) == 0) R_WAIT();                                                             \
    { DECL_DB(b, BASE128, 16, 0)                                                              \
    wg_fence();                                                                               \
    FOR7(mma_rs56<1, D128(((b) & 1) * HALF, t)>(ao, AQ(A, b, t), (b) + t > 0, SWB(b, t, db, 0))); } \
    wg_commit();                                                                              \
    if ((b) & 1) R_NEXT();
                WO_BLOCK(0)
                STAMP(11 + so);
                GAT_FETCH(1)
                WO_BLOCK(1)
                WO_BLOCK(2)
                GAT_FETCH(3)
                WO_BLOCK(3)
                PUSH_ACK();
                wg_wait<0>();
                R_RELEASE(2);
                STAMP(12 + so);
                WSUM(86 + 7 * (step >> 1));
                x_fix(X, xbits);
#pragma unroll
                for (int i = 0; i < 14; i++) X[i] = pack2(bf_lo(X[i]) + ao[2 * i], bf_hi(X[i]) + ao[2 * i + 1]);
            } else {
                uint32_t H[56];
                float ag[64];
#define F1_EPI(dst, ng, ag)                                                                    \
    _Pragma("unroll") for (int i = 0; i < 2 * (ng); i++)                                       \
        (dst)[i] = pack2(geglu(ag[2 * i], ag[4 * (ng) + 2 * i]), geglu(ag[2 * i + 1], ag[4 * (ng) + 2 * i + 1]));
#define H_PUSH(h0, off) st_async4(rem_h + (off), H[h0], H[(h0) + 1], H[(h0) + 2], H[(h0) + 3], mapa(BAR(B_RECV2 + wgi), hr ^ 1));
#define F1_BLOCK(b, first)                                                                     \
    if ((first) && (b) == 1) R_RELEASE(2);                                                     \
    if ((first) && (b) == 2 + XT) PUSH_ACK();                                                  \
    if ((first) && (b) == 2 && XT) GAT_FETCH(3)                                                \
    R_WAIT();                                                                                  \
    if ((b) == ((first) ? PPF : PPB)) { PP_WAIT() }                                            \
    { DECL_DB(b, BASE128, HALF, 0)                                                             \
    wg_fence();                                                                                \
    FOR7(mma_rs128<1, D128(0, t)>(ag, AQ(A, b, t), (b) + t > 0, SWB(b, t, db, 0));             \
         if constexpr (first) { PREP(b, t, true) }); }                                         \
    wg_commit();                                                                               \
    if ((b) == 3) { PP_GO() }                                                                  \
    if ((b) > 0) { wg_wait<1>(); R_RELEASE(1); }       \
    R_NEXT();
                normalize<0>(A, k0, k1);
                F1_BLOCK(0, true) F1_BLOCK(1, true) F1_BLOCK(2, true) F1_BLOCK(3, true)
                if (t128 == 0) { mbar_expect_tx(BAR(B_RECV + wgi), 16384); mbar_expect_tx(BAR(B_RECV2 + wgi), 12288); }
                PUSH_BEGIN();
                wg_wait<0>();
                R_RELEASE(1);
                int p = 0;
#pragma unroll 1
                do {
                    F1_EPI(H + 32, 8, ag)
                    STAMP(4 + p + so);
                    WSUM(81 + p + 7 * (step >> 1));
                    if (((trips >> (p + 1)) & 1) == 0) continue;
                    if (step == 1 && p == PKP) R_NEXT();
                    kill<64>(ag);
                    F1_BLOCK(0, false)
                    {
                        const uint32_t pk = (p ? hbuf + 16384 : sb + OFF_KVB + wgi * 8192) + w * 2048;
#pragma unroll
                        for (int k = 0; k < 4; k++) sts4(pk + k * 512 + lane * 16, H[32 + 4 * k], H[33 + 4 * k], H[34 + 4 * k], H[35 + 4 * k]);
                        fence_async();
                        __syncwarp();
                        asm volatile(ELECT "cp.async.bulk.shared::cluster.shared::cta.mbarrier::complete_tx::bytes [%0], [%1], 2048, [%2]; }"
                                     ::"r"(mapa(hbuf + p * 8192 + w * 2048, hr ^ 1)), "r"(pk), "r"(mapa(BAR(B_RECV + wgi), hr ^ 1)) : "memory");
                    }
                    F1_BLOCK(1, false) F1_BLOCK(2, false) F1_BLOCK(3, false)
                    wg_wait<0>();
                    R_RELEASE(1);
                    kill<16>(H + 32);
                } while (((trips >> (++p)) & 1));
#pragma unroll
                for (int k = 0; k < 4; k++) lds4(H + 16 + 4 * k, hbuf + 16384 + w * 2048 + k * 512 + lane * 16);
                __syncwarp();
                if (lane == 0) asm volatile("mbarrier.arrive.shared::cluster.b64 _, [%0];" ::"r"(mapa(BAR(B_ACK2 + wgi), hr ^ 1)) : "memory");
                const uint32_t rem_h = mapa(hbuf + w * 2048 + lane * 16, hr ^ 1);
#define F1_LAST(b0)                                                                            \
    R_WAIT();                                                                                  \
    if (b0) { PP_WAIT() }                                                                      \
    { DECL_DB(b0, BASE64, HALF, 1)                                                             \
    wg_fence();                                                                                \
    FOR7(mma_rs64<1, D64(0, t)>(al, AQ(A, b0, t), (b0) + t > 0, SWB(b0, t, db, 1)));           \
    FOR7(mma_rs64<1, D64(7168, t)>(al, AQ(A, (b0) + 1, t), 1, db)); }                          \
    wg_commit();                                                                               \
    if (b0) { PP_GO() }                                                                        \
    R_NEXT();
                float al[32];
                F1_LAST(0)
                mbar_wait_b(BAR(B_RECV + wgi), rcvph, spins);
                rcvph ^= 1;
                mbar_wait_b(BAR(B_ACK2 + wgi), step >> 1, spins);
                H_PUSH(32, 16384) H_PUSH(36, 16896)
                F1_LAST(2)
                H_PUSH(40, 17408) H_PUSH(44, 17920)
                wg_wait<1>();
                R_RELEASE(2);
                wg_wait<0>();
                R_RELEASE(1);
                uint32_t HP[56];
#pragma unroll
                for (int k = 0; k < 4; k++) lds4(H + 4 * k, sb + OFF_KVB + wgi * 8192 + w * 2048 + k * 512 + lane * 16);
#pragma unroll
                for (int t = 0; t < 8; t++) lds4(HP + 4 * t, hbuf + (t >> 2) * 8192 + w * 2048 + (t & 3) * 512 + lane * 16);
                F1_EPI(H + 48, 4, al)
                H_PUSH(48, 24576 - w * 1024) H_PUSH(52, 25088 - w * 1024)
                STAMP(7 + so);
                WSUM(84 + 7 * (step >> 1));
                FRESH();
                float acc[28];
                const uint32_t roA = hr ? 256u : 0u, roB = hr ? (uint32_t)-1536 : 0u;
                const uint32_t rpA = hr ? 0u : 256u, rpB = hr ? 0u : (uint32_t)-1536;
                float res[28];
                uint32_t v0[14], v1[14], P[14];
                Wide PW;
                const uint4* ps = xp0 + sl * 512;
#define F2_OWN_A()                                                                             \
    R_WAIT();                                                                                  \
    d0 = BASE128(0, 16, R_ADJ + roA); d1 = BASE128(0, 16, R_ADJ + roB);                        \
    wg_fence();                                                                                \
    FOR14(if constexpr (t < OT) mma_rs56<1, t * 128>(acc, H[4 * t], H[4 * t + 1], H[4 * t + 2], H[4 * t + 3], t > 0, d0)); \
    wg_commit();
#define F2_OWN_B()                                                                             \
    wg_fence();                                                                                \
    FOR14(if constexpr (t >= OT) mma_rs56<1, t * 128>(acc, H[4 * t], H[4 * t + 1], H[4 * t + 2], H[4 * t + 3], 1, t < 12 ? d0 : d1)); \
    wg_commit();                                                                               \
    R_NEXT();
#define F2_PEER()                                                                              \
    R_WAIT();                                                                                  \
    if (F2PP) { PP_WAIT() }                                                                    \
    d0 = BASE128(0, 16, R_ADJ + rpA); d1 = BASE128(0, 16, R_ADJ + rpB);                        \
    wg_fence();                                                                                \
    FOR14(mma_rs56<1, t * 128>(acc, HP[4 * t], HP[4 * t + 1], HP[4 * t + 2], HP[4 * t + 3], 1, t < 12 ? d0 : d1)); \
    wg_commit();                                                                               \
    if (F2PP) { PP_GO() }                                                                      \
    R_NEXT();
#define F2_TURN(u)                                                                             \
    wg_wait<1>();                                                                              \
    if ((u) < 2 || TDEF < 2) R_RELEASE(2);                                                     \
    wg_wait<0>();                                                                              \
    if ((u) < 2 || TDEF < 1) R_RELEASE(1);                                                     \
    _Pragma("unroll") for (int i = 0; i < 14; i++) P[i] = pack2(acc[2 * i], acc[2 * i + 1]);   \
    tag_slice(P, tag);                                                                         \
    PW = widen(P);                                                                             \
    kill<28>(acc);                                                                             \
    F2_OWN_A()                                                                                 \
    if ((u) == 2) { slice_load<PL(3)>(v0, ps, lane); slice_load<PL(4)>(v1, ps, lane); } \
    send_wide<PL(3 + (u))>(xp0 + (2 * ((pr + (u) + 1) & 3) + hr) * 512, lane, PW);             \
    seq++;                                                                                     \
    if (lane == 0) st_word(cx(sl), seq);                                                       \
    __syncwarp();                                                                              \
    STAMP(8 + (u) + so);                                                                       \
    F2_OWN_B()
                uint64_t d0, d1;
                F2_OWN_A()
                F2_OWN_B()
                R_WAIT();
                d0 = BASE128(0, 16, R_ADJ + rpA); d1 = BASE128(0, 16, R_ADJ + rpB);
                wg_fence();
                FOR8(mma_rs56<1, t * 128>(acc, HP[4 * t], HP[4 * t + 1], HP[4 * t + 2], HP[4 * t + 3], 1, d0));
                wg_commit();
                mbar_wait_b(BAR(B_RECV2 + wgi), step >> 1, spins);
#pragma unroll
                for (int k = 0; k < 4; k++) lds4(HP + 32 + 4 * k, hbuf + 16384 + w * 2048 + k * 512 + lane * 16);
                lds4(HP + 48, hbuf + 24576 + w * 1024 + lane * 16);
                lds4(HP + 52, hbuf + 25088 + w * 1024 + lane * 16);
                if (step == 1) PUSH_ACK();
                wg_fence();
                FOR14(if constexpr (t >= 8) mma_rs56<1, t * 128>(acc, HP[4 * t], HP[4 * t + 1], HP[4 * t + 2], HP[4 * t + 3], 1, t < 12 ? d0 : d1));
                wg_commit();
                R_NEXT();
                F2_TURN(0)
                F2_PEER()
                F2_TURN(1)
                F2_PEER()
                F2_TURN(2)
                if (step == 1) STAMP(64);
                slice_check<PL(3)>(v0, ps, lane, tag);
                slice_check<PL(4)>(v1, ps, lane, tag);
#pragma unroll
                for (int i = 0; i < 14; i++) { res[2 * i] = bf_lo(v0[i]) + bf_lo(v1[i]); res[2 * i + 1] = bf_hi(v0[i]) + bf_hi(v1[i]); }
                slice_load<PL(2)>(X, ps, lane);
                if (step == 1) STAMP(65);
                F2_PEER()
                if (step == 1) STAMP(66);
                poll_cnt(cx(2 * ((pr + 1) & 3) + hr), seq);
                if (step == 1) STAMP(67);
                slice_load<PL(5)>(v0, ps, lane);
                x_fix(X, xbits);
                slice_check<PL(5)>(v0, ps, lane, tag);
                if (lane < TDEF) mbar_arrive(BAR(B_EMPTY + (slot + NST - 3 - lane) % NST));
#pragma unroll
                for (int i = 0; i < 14; i++) { res[2 * i] += bf_lo(v0[i]); res[2 * i + 1] += bf_hi(v0[i]); }
                STAMP(11 + so);
                wg_wait<0>();
                R_RELEASE(2);
                STAMP(12 + so);
                WSUM(85 + 7 * (step >> 1));
#pragma unroll
                for (int i = 0; i < 14; i++) X[i] = pack2(fmaf(res[2 * i] + acc[2 * i], 0.5f, bf_lo(X[i])), fmaf(res[2 * i + 1] + acc[2 * i + 1], 0.5f, bf_hi(X[i])));
            }
        }
        {
            const int m = lane >> 3, rr = lane & 7;
            const uint32_t ob = hbuf + w * 2048, rowa = ob + (rr + 8 * (m & 1)) * 112 + (m >> 1) * 16;
#pragma unroll
            for (int j = 0; j < 3; j++) stsm4(rowa + 32 * j, X[4 * j], X[4 * j + 1], X[4 * j + 2], X[4 * j + 3]);
            asm volatile("stmatrix.sync.aligned.m8n8.x2.shared.b16 [%0], {%1,%2};" ::"r"(ob + (rr + 8 * (m & 1)) * 112 + 96), "r"(X[12]), "r"(X[13]) : "memory");
            fence_async();
            __syncwarp();
            if (lane == 0) {
                asm volatile("cp.async.bulk.tensor.2d.global.shared::cta.bulk_group [%0, {%2, %3}], [%1];" ::"l"(&maps.out), "r"(ob), "r"(56 * sl), "r"(tile * 128 + wu * 16) : "memory");
                asm volatile("cp.async.bulk.commit_group;" ::: "memory");
                asm volatile("cp.async.bulk.wait_group.read 0;" ::: "memory");
            }
        }
        STAMP(50);
        GSTAMP(61);
        PDUMP();
    }
}

#undef g
#undef pr
#undef c
#undef t128

typedef CUresult (*EncodeFn)(CUtensorMap*, CUtensorMapDataType, cuuint32_t, void*, const cuuint64_t*, const cuuint64_t*, const cuuint32_t*,
                             const cuuint32_t*, CUtensorMapInterleave, CUtensorMapSwizzle, CUtensorMapL2promotion, CUtensorMapFloatOOBfill);

static void make_map(EncodeFn enc, CUtensorMap* m, const void* p, uint64_t cols, uint64_t rows, uint32_t bc, uint32_t br, CUtensorMapSwizzle sw) {
    cuuint64_t gd[2] = {cols, rows};
    cuuint64_t gs[1] = {cols * 2};
    cuuint32_t bd[2] = {bc, br};
    cuuint32_t es[2] = {1, 1};
    enc(m, CU_TENSOR_MAP_DATA_TYPE_BFLOAT16, 2, const_cast<void*>(p), gd, gs, bd, es, CU_TENSOR_MAP_INTERLEAVE_NONE, sw,
        CU_TENSOR_MAP_L2_PROMOTION_L2_128B, CU_TENSOR_MAP_FLOAT_OOB_FILL_NONE);
}

extern "C" void kernel_launch(void* const* d_in, const int* in_sizes, int n_in, void* d_out, int out_size) {
    (void)in_sizes; (void)n_in; (void)out_size;
    static EncodeFn enc = nullptr;
    static Scratch* scratch = nullptr;
    if (!enc) {
        void* fn = nullptr;
        cudaDriverEntryPointQueryResult qr;
        cudaGetDriverEntryPoint("cuTensorMapEncodeTiled", &fn, cudaEnableDefault, &qr);
        enc = (EncodeFn)fn;
        cudaGetSymbolAddress((void**)&scratch, g_scratch);
        cudaFuncSetAttribute(fused_kernel, cudaFuncAttributeMaxDynamicSharedMemorySize, SMEM_BYTES);
    }
    Maps maps;
    {
        cuuint64_t gd[3] = {64, 2048, 7};
        cuuint64_t gs[2] = {896, 128};
        cuuint32_t bd[3] = {64, 32, 7};
        cuuint32_t es[3] = {1, 1, 1};
        enc(&maps.x, CU_TENSOR_MAP_DATA_TYPE_BFLOAT16, 3, d_in[0], gd, gs, bd, es, CU_TENSOR_MAP_INTERLEAVE_NONE, CU_TENSOR_MAP_SWIZZLE_128B,
            CU_TENSOR_MAP_L2_PROMOTION_L2_128B, CU_TENSOR_MAP_FLOAT_OOB_FILL_NONE);
    }
    make_map(enc, &maps.out, d_out, 448, 2048, 56, 16, CU_TENSOR_MAP_SWIZZLE_NONE);
    make_map(enc, &maps.qkv, d_in[1], 1344, 448, 64, 112, CU_TENSOR_MAP_SWIZZLE_128B);
    make_map(enc, &maps.wo, d_in[3], 448, 448, 64, 112, CU_TENSOR_MAP_SWIZZLE_128B);
    make_map(enc, &maps.wg, d_in[5], 1792, 448, 64, 112, CU_TENSOR_MAP_SWIZZLE_128B);
    make_map(enc, &maps.wu, d_in[6], 1792, 448, 64, 112, CU_TENSOR_MAP_SWIZZLE_128B);
    make_map(enc, &maps.wg32, d_in[5], 1792, 448, 32, 112, CU_TENSOR_MAP_SWIZZLE_64B);
    make_map(enc, &maps.wu32, d_in[6], 1792, 448, 32, 112, CU_TENSOR_MAP_SWIZZLE_64B);
    make_map(enc, &maps.wd, d_in[7], 448, 1792, 64, 112, CU_TENSOR_MAP_SWIZZLE_128B);
    fused_kernel<<<128, 384, SMEM_BYTES>>>(scratch, (const __nv_bfloat16*)d_in[0], (const __nv_bfloat16*)d_in[2], 7, (const __nv_bfloat16*)d_in[5],
                                           (const __nv_bfloat16*)d_in[6], (const __nv_bfloat16*)d_in[7], maps);
}
```

```cpp
#include <cuda_runtime.h>
#include <cuda.h>
#include <cuda_bf16.h>
#include <stdint.h>
#include <type_traits>

#define PPF 2
#define PKP 0
#define TDEF 1
#define TMPF 0
#define LPARK 1
#define PFN 9
#define VW 1
#define QPP 1
#define XG3 2
#define XT (XG3 == 1 || XG3 == 2)
#define ACAN 0
#define SPLIT0 1
#define OT 2
#define F2PP 0
#define PPK 2
#define QE 1
#define OST 1
#define PP

namespace {

constexpr uint32_t STAGE = 28672, HALF = 14336;
constexpr int NST = 5;
constexpr uint32_t OFF_H = NST * STAGE;
constexpr uint32_t OFF_KVB = OFF_H + 2 * STAGE;
constexpr uint32_t OFF_WPHI = OFF_KVB + 16384;
constexpr uint32_t OFF_BAR = OFF_WPHI + 7168;
constexpr uint32_t SMEM_BYTES = OFF_BAR + 384 + 1408;
constexpr int B_EMPTY = NST, B_RECV = 2 * NST, B_RECV2 = B_RECV + 2, B_PACK = B_RECV2 + 2, B_GAT = B_PACK + 1, B_LATE = B_GAT + 16, B_ACK = B_LATE + 1, B_ACK2 = B_ACK + 2, B_COUNT = B_ACK2 + 2;

constexpr int PACK = 14 + 4 * PKP;

struct Maps { CUtensorMap x, qkv, wo, wg, wu, wg32, wu32, wd, out; };

}

constexpr int PLANE = 16 * 2 * 8 * 512;
struct Scratch {
    uint4 ex[6 * PLANE];
    uint4 kv1[8 * 16 * 16 * 32];
    uint4 kv2[8 * 512];
    uint32_t c1[8 * 8 * 16 * 32];
    uint32_t cw[8 * 32];
    uint4 wp[8 * 32 * (HALF / 16)];
};
__device__ __align__(1024) Scratch g_scratch;
#define g_ex (sc->ex)
#define g_kv1 (sc->kv1)
#define g_kv2 (sc->kv2)
#define g_c1 (sc->c1)
#define g_cw (sc->cw)
#define g_wp (sc->wp)
#define STAMP(i)
#define GSTAMP(i)
#define PDUMP()
#define ASTAMP(i)

namespace {

__device__ __forceinline__ int fresh_tid() { int t; asm volatile("mov.u32 %0, %%tid.x;" : "=r"(t)); return t; }
template <int N> __device__ __forceinline__ void kill(uint32_t* v) {
#pragma unroll
    for (int i = 0; i < N; i++) v[i] = 0;
}
template <int N> __device__ __forceinline__ void kill(float* v) {
#pragma unroll
    for (int i = 0; i < N; i++) v[i] = 0.f;
}
__device__ __forceinline__ uint32_t s2u(const void* p) { return (uint32_t)__cvta_generic_to_shared(p); }
__device__ __forceinline__ void mbar_init(uint32_t a, uint32_t c) { asm volatile("mbarrier.init.shared::cta.b64 [%0], %1;" ::"r"(a), "r"(c) : "memory"); }
__device__ __forceinline__ void mbar_expect_tx(uint32_t a, uint32_t b) { asm volatile("mbarrier.arrive.expect_tx.shared::cta.b64 _, [%0], %1;" ::"r"(a), "r"(b) : "memory"); }
__device__ __forceinline__ void mbar_arrive(uint32_t a) { asm volatile("mbarrier.arrive.shared::cta.b64 _, [%0];" ::"r"(a) : "memory"); }
#define GIVE_UP(id) "trap;\n"
#define SPIN_MAX "0x400000"
#define SPIN_TAIL(id) "add.u32 n, n, 1;\n setp.lt.u32 p, n, " SPIN_MAX ";\n @p bra.uni LP;\n" GIVE_UP(id) " DN:\n }"
__device__ __forceinline__ void mbar_wait(uint32_t a, uint32_t ph) {
    asm volatile("{ .reg .pred p; .reg .b32 n; mov.u32 n, 0;\n LP:\n"
                 "mbarrier.try_wait.parity.shared::cta.b64 p, [%0], %1;\n @p bra DN;\n"
                 "add.u32 n, n, 1;\n setp.lt.u32 p, n, " SPIN_MAX ";\n @p bra LP;\n"
                 GIVE_UP("")
                 " DN:\n }" ::"r"(a), "r"(ph) : "memory");
}
#define ELECT "{ .reg .pred e; elect.sync _|e, 0xffffffff; @e "
__device__ __forceinline__ void tma2d(uint32_t dst, const CUtensorMap* m, int c0, int c1, uint32_t bar) {
    asm volatile(ELECT "cp.async.bulk.tensor.2d.shared::cluster.global.mbarrier::complete_tx::bytes [%0], [%1, {%3, %4}], [%2]; }" ::"r"(dst), "l"(m), "r"(bar), "r"(c0), "r"(c1) : "memory");
}
__device__ __forceinline__ void tma3x(uint32_t dst, const CUtensorMap* m, int row, uint32_t bar) {
    asm volatile(ELECT "cp.async.bulk.tensor.3d.shared::cluster.global.mbarrier::complete_tx::bytes [%0], [%1, {0, %3, 0}], [%2]; }" ::"r"(dst), "l"(m), "r"(bar), "r"(row) : "memory");
}
template <int OFF>
__device__ __forceinline__ void ld_pkt(uint32_t* v, const uint4* p) {
    asm volatile("{ .reg .b128 t; ld.relaxed.gpu.global.b128 t, [%4+%5]; mov.b128 {%0,%1,%2,%3}, t; }" : "=r"(v[0]), "=r"(v[1]), "=r"(v[2]), "=r"(v[3]) : "l"(p), "n"(OFF * 16) : "memory");
}
template <int OFF>
__device__ __forceinline__ void st_pkt(uint4* p, uint32_t a, uint32_t b, uint32_t c, uint32_t d) {
    asm volatile("{ .reg .b128 t; mov.b128 t, {%1,%2,%3,%4}; st.relaxed.gpu.global.b128 [%0+%5], t; }" ::"l"(p), "r"(a), "r"(b), "r"(c), "r"(d), "n"(OFF * 16) : "memory");
}
__device__ __forceinline__ uint32_t pack2(float lo, float hi) {
    uint32_t r;
    asm("cvt.rn.bf16x2.f32 %0, %1, %2;" : "=r"(r) : "f"(hi), "f"(lo));
    return r;
}
__device__ __forceinline__ float bf_lo(uint32_t w) { return __uint_as_float(w << 16); }
__device__ __forceinline__ float bf_hi(uint32_t w) { return __uint_as_float(w & 0xffff0000u); }
__device__ __forceinline__ uint32_t settag(uint32_t w, uint32_t tag) { return (w & ~1u) | tag; }
__device__ __forceinline__ float ex2(float x) { float y; asm("ex2.approx.ftz.f32 %0, %1;" : "=f"(y) : "f"(x)); return y; }
__device__ __forceinline__ float rcp(float x) { float y; asm("rcp.approx.ftz.f32 %0, %1;" : "=f"(y) : "f"(x)); return y; }
__device__ __forceinline__ float tanh_hw(float x) { float y; asm("tanh.approx.f32 %0, %1;" : "=f"(y) : "f"(x)); return y; }
__device__ __forceinline__ void stsm4(uint32_t addr, uint32_t a, uint32_t b, uint32_t c, uint32_t d) {
    asm volatile("stmatrix.sync.aligned.m8n8.x4.shared.b16 [%0], {%1,%2,%3,%4};" ::"r"(addr), "r"(a), "r"(b), "r"(c), "r"(d) : "memory");
}
__device__ __forceinline__ void fence_async() { asm volatile("fence.proxy.async.shared::cta;" ::: "memory"); }
__device__ __forceinline__ void bar_sync(int id, int n) { asm volatile("bar.sync %0, %1;" ::"r"(id), "r"(n) : "memory"); }
__device__ __forceinline__ void bar_arrive(int id, int n) { asm volatile("bar.arrive %0, %1;" ::"r"(id), "r"(n) : "memory"); }
__device__ __forceinline__ void wg_fence() { asm volatile("wgmma.fence.sync.aligned;" ::: "memory"); }
__device__ __forceinline__ void wg_commit() { asm volatile("wgmma.commit_group.sync.aligned;" ::: "memory"); }
template <int N> __device__ __forceinline__ void wg_wait() { asm volatile("wgmma.wait_group.sync.aligned %0;" ::"n"(N) : "memory"); }

constexpr uint32_t SB0 = 1024;
__host__ __device__ constexpr uint32_t dlo(uint32_t off, uint32_t lbo) { return ((SB0 + off) >> 4) | ((lbo >> 4) << 16); }
__host__ __device__ constexpr uint32_t dhi(uint32_t sbo, uint32_t sw) { return (sbo >> 4) | (sw << 30); }
__device__ __forceinline__ uint64_t dbase(uint32_t lo, uint32_t hi) { uint64_t d; asm volatile("mov.b64 %0, {%1, %2};" : "=l"(d) : "r"(lo), "r"(hi)); return d; }
#define BASE128(off, lbo, adj) dbase(dlo(off, lbo) + (adj), dhi(1024, 1))
#define BASE64(off, lbo, adj) dbase(dlo(off, lbo) + (adj), dhi(512, 2))

#define ACC4(d, o) "+f"(d[o]), "+f"(d[o + 1]), "+f"(d[o + 2]), "+f"(d[o + 3])
#define ACC28(d) ACC4(d, 0), ACC4(d, 4), ACC4(d, 8), ACC4(d, 12), ACC4(d, 16), ACC4(d, 20), ACC4(d, 24)
#define ACC32(d, o) ACC4(d, o), ACC4(d, o + 4), ACC4(d, o + 8), ACC4(d, o + 12), ACC4(d, o + 16), ACC4(d, o + 20), ACC4(d, o + 24), ACC4(d, o + 28)

template <int TB, uint64_t D>
__device__ __forceinline__ void mma_rs56(float* d, uint32_t a0, uint32_t a1, uint32_t a2, uint32_t a3, int sd, uint64_t base) {
    asm volatile("{ .reg .pred p; .reg .b64 db; setp.ne.b32 p, %32, 0; add.u64 db, %33, %34;\n"
                 "wgmma.mma_async.sync.aligned.m64n56k16.f32.bf16.bf16 "
                 "{%0,%1,%2,%3,%4,%5,%6,%7,%8,%9,%10,%11,%12,%13,%14,%15,%16,%17,%18,%19,%20,%21,%22,%23,%24,%25,%26,%27}, "
                 "{%28,%29,%30,%31}, db, p, 1, 1, %35; }\n"
                 : ACC28(d)
                 : "r"(a0), "r"(a1), "r"(a2), "r"(a3), "r"(sd), "l"(base), "n"(D), "n"(TB));
}
template <int TB, uint64_t D>
__device__ __forceinline__ void mma_rs64(float* d, uint32_t a0, uint32_t a1, uint32_t a2, uint32_t a3, int sd, uint64_t base) {
    asm volatile("{ .reg .pred p; .reg .b64 db; setp.ne.b32 p, %36, 0; add.u64 db, %37, %38;\n"
                 "wgmma.mma_async.sync.aligned.m64n64k16.f32.bf16.bf16 "
                 "{%0,%1,%2,%3,%4,%5,%6,%7,%8,%9,%10,%11,%12,%13,%14,%15,%16,%17,%18,%19,%20,%21,%22,%23,%24,%25,%26,%27,%28,%29,%30,%31}, "
                 "{%32,%33,%34,%35}, db, p, 1, 1, %39; }\n"
                 : ACC32(d, 0)
                 : "r"(a0), "r"(a1), "r"(a2), "r"(a3), "r"(sd), "l"(base), "n"(D), "n"(TB));
}
template <int TB, uint64_t D>
__device__ __forceinline__ void mma_rs128(float* d, uint32_t a0, uint32_t a1, uint32_t a2, uint32_t a3, int sd, uint64_t base) {
    asm volatile("{ .reg .pred p; .reg .b64 db; setp.ne.b32 p, %68, 0; add.u64 db, %69, %70;\n"
                 "wgmma.mma_async.sync.aligned.m64n128k16.f32.bf16.bf16 "
                 "{%0,%1,%2,%3,%4,%5,%6,%7,%8,%9,%10,%11,%12,%13,%14,%15,%16,%17,%18,%19,%20,%21,%22,%23,%24,%25,%26,%27,%28,%29,%30,%31,%32,%33,%34,%35,%36,%37,%38,%39,%40,%41,%42,%43,%44,%45,%46,%47,%48,%49,%50,%51,%52,%53,%54,%55,%56,%57,%58,%59,%60,%61,%62,%63}, "
                 "{%64,%65,%66,%67}, db, p, 1, 1, %71; }\n"
                 : ACC32(d, 0), ACC32(d, 32)
                 : "r"(a0), "r"(a1), "r"(a2), "r"(a3), "r"(sd), "l"(base), "n"(D), "n"(TB));
}
template <uint64_t DA, uint64_t DB>
__device__ __forceinline__ void mma_ss56_tt(float* d, int sd, uint64_t ba, uint64_t bb) {
    asm volatile("{ .reg .pred p; .reg .b64 da, db; setp.ne.b32 p, %28, 0; add.u64 da, %29, %31; add.u64 db, %30, %32;\n"
                 "wgmma.mma_async.sync.aligned.m64n56k16.f32.bf16.bf16 "
                 "{%0,%1,%2,%3,%4,%5,%6,%7,%8,%9,%10,%11,%12,%13,%14,%15,%16,%17,%18,%19,%20,%21,%22,%23,%24,%25,%26,%27}, "
                 "da, db, p, 1, 1, 1, 1; }\n"
                 : ACC28(d)
                 : "r"(sd), "l"(ba), "l"(bb), "n"(DA), "n"(DB));
}
template <int... I> struct Seq {};
template <class F, int... I> __device__ __forceinline__ void static_for_impl(F&& f, Seq<I...>) { (f(std::integral_constant<int, I>{}), ...); }
#define FOR7(...) static_for_impl([&](auto T_) { constexpr int t = decltype(T_)::value; __VA_ARGS__; }, Seq<0, 1, 2, 3, 4, 5, 6>{})
#define FOR8(...) static_for_impl([&](auto T_) { constexpr int t = decltype(T_)::value; __VA_ARGS__; }, Seq<0, 1, 2, 3, 4, 5, 6, 7>{})
#define FOR14(...) static_for_impl([&](auto T_) { constexpr int t = decltype(T_)::value; __VA_ARGS__; }, Seq<0, 1, 2, 3, 4, 5, 6, 7, 8, 9, 10, 11, 12, 13>{})

__device__ __forceinline__ int kblk(int p, int b) { return b == 0 ? p : b - (b <= p); }
__host__ __device__ constexpr int krow(int t) { return t < 3 ? 16 * t : (t < 6 ? 56 + 16 * (t - 3) : 48); }
#define AQ(A, b, t) ((t) < 3 ? A[2 * (b)][4 * (t)] : (t) < 6 ? A[2 * (b) + 1][4 * ((t) - 3)] : A[2 * (b)][12]), \
                    ((t) < 3 ? A[2 * (b)][4 * (t) + 1] : (t) < 6 ? A[2 * (b) + 1][4 * ((t) - 3) + 1] : A[2 * (b)][13]), \
                    ((t) < 3 ? A[2 * (b)][4 * (t) + 2] : (t) < 6 ? A[2 * (b) + 1][4 * ((t) - 3) + 2] : A[2 * (b) + 1][12]), \
                    ((t) < 3 ? A[2 * (b)][4 * (t) + 3] : (t) < 6 ? A[2 * (b) + 1][4 * ((t) - 3) + 3] : A[2 * (b) + 1][13])
#define D128(off, t) ((uint64_t)(((off) + krow(t) * 128) >> 4) + ((uint64_t)((t) == 6 ? (7168 - 1024) >> 4 : 0) << 32))
#define D64(off, t) ((uint64_t)(((off) + krow(t) * 64) >> 4) + ((uint64_t)((t) == 6 ? (3584 - 512) >> 4 : 0) << 32))

#define PL(k) (((k) - 3) * PLANE)
__device__ __forceinline__ void st_word(uint32_t* p, uint32_t v) { asm volatile("st.relaxed.gpu.global.u32 [%0], %1;" ::"l"(p), "r"(v) : "memory"); }
__device__ __forceinline__ uint32_t ld_word(const uint32_t* p) { uint32_t v; asm volatile("ld.relaxed.gpu.global.u32 %0, [%1];" : "=r"(v) : "l"(p) : "memory"); return v; }
__device__ __forceinline__ void tag_slice(uint32_t* w, uint32_t tag) { w[0] = settag(w[0], tag); w[4] = settag(w[4], tag); w[8] = settag(w[8], tag); w[12] = settag(w[12], tag); }
template <int O>
__device__ __forceinline__ void send_slice(uint4* dst, int lane, const uint32_t* w) {
    st_pkt<O>(dst, w[0], w[1], w[2], w[3]);
    st_pkt<O + 32>(dst, w[4], w[5], w[6], w[7]);
    st_pkt<O + 64>(dst, w[8], w[9], w[10], w[11]);
    asm volatile("{ .reg .b64 t; mov.b64 t, {%1,%2}; st.relaxed.gpu.global.b64 [%0+%3], t; }" ::"l"((char*)dst - lane * 8), "r"(w[12]), "r"(w[13]), "n"(16 * (O + 96)) : "memory");
}
struct Wide { unsigned __int128 q[3]; uint64_t h; };
__device__ __forceinline__ Wide widen(const uint32_t* w) {
    Wide r;
#pragma unroll
    for (int k = 0; k < 3; k++) asm volatile("mov.b128 %0, {%1,%2,%3,%4};" : "=q"(r.q[k]) : "r"(w[4 * k]), "r"(w[4 * k + 1]), "r"(w[4 * k + 2]), "r"(w[4 * k + 3]));
    asm volatile("mov.b64 %0, {%1,%2};" : "=l"(r.h) : "r"(w[12]), "r"(w[13]));
    return r;
}
template <int O>
__device__ __forceinline__ void send_wide(uint4* dst, int lane, const Wide& v) {
    asm volatile("st.relaxed.gpu.global.b128 [%0+%4], %1;\n st.relaxed.gpu.global.b128 [%0+%5], %2;\n st.relaxed.gpu.global.b128 [%0+%6], %3;"
                 ::"l"(dst), "q"(v.q[0]), "q"(v.q[1]), "q"(v.q[2]), "n"(16 * O), "n"(16 * (O + 32)), "n"(16 * (O + 64)) : "memory");
    asm volatile("st.relaxed.gpu.global.b64 [%0+%2], %1;" ::"l"((char*)dst - lane * 8), "l"(v.h), "n"(16 * (O + 96)) : "memory");
}
#define RW4(v, o) "+r"(v[o]), "+r"(v[(o) + 1]), "+r"(v[(o) + 2]), "+r"(v[(o) + 3])
#define RW2(v, o) "+r"(v[o]), "+r"(v[(o) + 1])
#define WR4(v, o) "=&r"(v[o]), "=&r"(v[(o) + 1]), "=&r"(v[(o) + 2]), "=&r"(v[(o) + 3])
#define LDP(a, b, c, d, addr, off) "ld.relaxed.gpu.global.b128 q, [" addr "+" off "];\n mov.b128 {" a "," b "," c "," d "}, q;\n"
#define LDH(a, b, addr, off) "ld.relaxed.gpu.global.b64 h, [" addr "+" off "];\n mov.b64 {" a "," b "}, h;\n"
#define VOTE_OK "and.b32 t, t, 1;\n setp.ne.u32 p, t, 0;\n vote.sync.any.pred p, p, 0xffffffff;\n @!p bra.uni DN;\n"
#define CHK(x, tag) "lop3.b32 t, " x ", " tag ", t, 0xBE;\n"
__device__ __forceinline__ void check_cnt(uint32_t v, const uint32_t* p, uint32_t target) {
    asm volatile("{ .reg .pred p; .reg .b32 n, t; mov.u32 n, 0; mov.u32 t, %2;\n LP:\n"
                 "sub.s32 t, t, %1;\n setp.lt.s32 p, t, 0;\n vote.sync.any.pred p, p, 0xffffffff;\n @!p bra.uni DN;\n ld.relaxed.gpu.global.u32 t, [%0];\n" SPIN_TAIL("7")
                 ::"l"(p), "r"(target), "r"(v) : "memory");
}
__device__ __forceinline__ void poll_cnt(const uint32_t* p, uint32_t target) {
    asm volatile("{ .reg .pred p; .reg .b32 n, t; mov.u32 n, 0;\n LP:\n"
                 "ld.relaxed.gpu.global.u32 t, [%0];\n sub.s32 t, t, %1;\n setp.lt.s32 p, t, 0;\n vote.sync.any.pred p, p, 0xffffffff;\n @!p bra.uni DN;\n" SPIN_TAIL("1")
                 ::"l"(p), "r"(target) : "memory");
}
template <int STR>
__device__ __forceinline__ void poll4_kv(uint32_t* v, const uint4* p, uint32_t tag) {
    asm volatile("{ .reg .pred p; .reg .b32 n, t; .reg .b128 q; mov.u32 n, 0;\n LP:\n"
                 LDP("%0", "%1", "%2", "%3", "%16", "0") LDP("%4", "%5", "%6", "%7", "%16", "%18")
                 LDP("%8", "%9", "%10", "%11", "%16", "%19") LDP("%12", "%13", "%14", "%15", "%16", "%20")
                 "xor.b32 t, %0, %17;\n" CHK("%4", "%17") CHK("%8", "%17") CHK("%12", "%17") VOTE_OK SPIN_TAIL("2")
                 : WR4(v, 0), WR4(v, 4), WR4(v, 8), WR4(v, 12)
                 : "l"(p), "r"(tag), "n"(16 * STR), "n"(32 * STR), "n"(48 * STR)
                 : "memory");
}
template <int B>
__device__ __forceinline__ void blk_load(uint32_t (&A)[8][14], const uint4* src, int lane) {
    ld_pkt<0>(&A[2 * B][0], src); ld_pkt<32>(&A[2 * B][4], src); ld_pkt<64>(&A[2 * B][8], src);
    ld_pkt<512>(&A[2 * B + 1][0], src); ld_pkt<544>(&A[2 * B + 1][4], src); ld_pkt<576>(&A[2 * B + 1][8], src);
    asm volatile("{ .reg .b64 h;\n" LDH("%0", "%1", "%4", "1536") LDH("%2", "%3", "%4", "9728") "}"
                 : "=&r"(A[2 * B][12]), "=&r"(A[2 * B][13]), "=&r"(A[2 * B + 1][12]), "=&r"(A[2 * B + 1][13])
                 : "l"((const char*)src - lane * 8) : "memory");
}
#define BLK_TEST "xor.b32 t, %0, %30;\n" CHK("%4", "%30") CHK("%8", "%30") CHK("%12", "%30") CHK("%16", "%30") CHK("%20", "%30") CHK("%24", "%30") CHK("%26", "%30") VOTE_OK
template <int B>
__device__ __forceinline__ void blk_check(uint32_t (&A)[8][14], const uint4* src, int lane, uint32_t tag) {
    asm volatile("{ .reg .pred p; .reg .b32 n, t; .reg .b128 q; .reg .b64 h, a8;\n" BLK_TEST
                 "mov.u32 n, 0;\n mad.wide.s32 a8, %29, -8, %28;\n LP:\n"
                 LDP("%0", "%1", "%2", "%3", "%28", "0") LDP("%4", "%5", "%6", "%7", "%28", "512") LDP("%8", "%9", "%10", "%11", "%28", "1024")
                 LDP("%12", "%13", "%14", "%15", "%28", "8192") LDP("%16", "%17", "%18", "%19", "%28", "8704") LDP("%20", "%21", "%22", "%23", "%28", "9216")
                 LDH("%24", "%25", "a8", "1536") LDH("%26", "%27", "a8", "9728") BLK_TEST SPIN_TAIL("3")
                 "\n and.b32 %0, %0, -2; and.b32 %4, %4, -2; and.b32 %8, %8, -2; and.b32 %12, %12, -2; and.b32 %16, %16, -2; and.b32 %20, %20, -2; and.b32 %24, %24, -2; and.b32 %26, %26, -2;"
                 : RW4(A[2 * B], 0), RW4(A[2 * B], 4), RW4(A[2 * B], 8), RW4(A[2 * B + 1], 0), RW4(A[2 * B + 1], 4), RW4(A[2 * B + 1], 8),
                   RW2(A[2 * B], 12), RW2(A[2 * B + 1], 12)
                 : "l"(src), "r"(lane), "r"(tag)
                 : "memory");
}
__device__ __forceinline__ void st_async4(uint32_t a, uint32_t x, uint32_t y, uint32_t z, uint32_t w, uint32_t bar) {
    asm volatile("st.async.weak.shared::cluster.mbarrier::complete_tx::bytes.v4.b32 [%0], {%1,%2,%3,%4}, [%5];" ::"r"(a), "r"(x), "r"(y), "r"(z), "r"(w), "r"(bar) : "memory");
}
__device__ __forceinline__ uint32_t mapa(uint32_t a, uint32_t cta) { uint32_t r; asm("mapa.shared::cluster.u32 %0, %1, %2;" : "=r"(r) : "r"(a), "r"(cta)); return r; }
__device__ __forceinline__ void stat_load(uint32_t* v, const uint4* p) { ld_pkt<0>(v, p); ld_pkt<512>(v + 4, p); }
__device__ __forceinline__ void stat_check(uint32_t* v, const uint4* p, uint32_t tag) {
    asm volatile("{ .reg .pred p; .reg .b32 n, t; .reg .b128 q; mov.u32 n, 0;\n LP:\n"
                 "xor.b32 t, %3, %9;\n" CHK("%7", "%9") VOTE_OK
                 LDP("%0", "%1", "%2", "%3", "%8", "0") LDP("%4", "%5", "%6", "%7", "%8", "8192") SPIN_TAIL("4")
                 : RW4(v, 0), RW4(v, 4) : "l"(p), "r"(tag) : "memory");
}
__device__ __forceinline__ uint32_t x_bits(const uint32_t* X) {
    uint32_t r;
    asm volatile("{ .reg .b32 a, b; prmt.b32 a, %1, %2, 0x0040; prmt.b32 b, %3, %4, 0x0040; prmt.b32 %0, a, b, 0x5410; }" : "=r"(r) : "r"(X[0]), "r"(X[4]), "r"(X[8]), "r"(X[12]));
    return r;
}
template <int O>
__device__ __forceinline__ void slice_load(uint32_t* v, const uint4* p, int lane) {
    ld_pkt<O>(v, p); ld_pkt<O + 32>(v + 4, p); ld_pkt<O + 64>(v + 8, p);
    asm volatile("{ .reg .b64 h;\n" LDH("%0", "%1", "%2", "%3") "}" : "=r"(v[12]), "=r"(v[13]) : "l"((const char*)p - lane * 8), "n"(16 * (O + 96)) : "memory");
}
#define SLICE_TEST "xor.b32 t, %0, %16;\n" CHK("%4", "%16") CHK("%8", "%16") CHK("%12", "%16") VOTE_OK
template <int O>
__device__ __forceinline__ void slice_check(uint32_t* v, const uint4* p, int lane, uint32_t tag) {
    asm volatile("{ .reg .pred p; .reg .b32 n, t; .reg .b128 q; .reg .b64 h;\n" SLICE_TEST "mov.u32 n, 0;\n LP:\n"
                 LDP("%0", "%1", "%2", "%3", "%14", "%17") LDP("%4", "%5", "%6", "%7", "%14", "%18") LDP("%8", "%9", "%10", "%11", "%14", "%19")
                 LDH("%12", "%13", "%15", "%20") SLICE_TEST SPIN_TAIL("5")
                 : RW4(v, 0), RW4(v, 4), RW4(v, 8), RW2(v, 12)
                 : "l"(p), "l"((const char*)p - lane * 8), "r"(tag), "n"(16 * O), "n"(16 * (O + 32)), "n"(16 * (O + 64)), "n"(16 * (O + 96))
                 : "memory");
}
__device__ __forceinline__ void x_fix(uint32_t* X, uint32_t bits) {
    X[0] = __byte_perm(X[0], bits, 0x3214); X[4] = __byte_perm(X[4], bits, 0x3215); X[8] = __byte_perm(X[8], bits, 0x3216); X[12] = __byte_perm(X[12], bits, 0x3217);
}
__device__ __forceinline__ void sts4(uint32_t a, uint32_t x, uint32_t y, uint32_t z, uint32_t w) {
    asm volatile("st.shared.v4.u32 [%0], {%1,%2,%3,%4};" ::"r"(a), "r"(x), "r"(y), "r"(z), "r"(w) : "memory");
}
__device__ __forceinline__ void lds4(uint32_t* v, uint32_t a) {
    asm volatile("ld.shared.v4.u32 {%0,%1,%2,%3}, [%4];" : "=r"(v[0]), "=r"(v[1]), "=r"(v[2]), "=r"(v[3]) : "r"(a) : "memory");
}
struct LnCoef { uint32_t hi, lo, sh; };
__device__ __forceinline__ LnCoef ln_coef(float sum, float sq) {
    sum += __shfl_xor_sync(0xffffffffu, sum, 1); sq += __shfl_xor_sync(0xffffffffu, sq, 1);
    sum += __shfl_xor_sync(0xffffffffu, sum, 2); sq += __shfl_xor_sync(0xffffffffu, sq, 2);
    const float mean = sum * (1.f / 448.f);
    const float var = fmaxf(fmaf(-mean, mean, sq * (1.f / 448.f)), 0.f);
    const float sc = rsqrtf(var + 1e-5f);
    LnCoef r;
    r.hi = pack2(sc, sc);
    const float lo = sc - bf_lo(r.hi), sh = -mean * sc;
    r.lo = pack2(lo, lo);
    r.sh = pack2(sh, sh);
    return r;
}
template <int W0, int W1>
__device__ __forceinline__ void normalize(uint32_t (&A)[8][14], const LnCoef& c0, const LnCoef& c1) {
#pragma unroll
    for (int i = W0; i < W1; i++) {
        const LnCoef& k = (i & 1) ? c1 : c0;
        asm("{ .reg .b32 t; fma.rn.bf16x2 t, %0, %2, %3; fma.rn.bf16x2 %0, %0, %1, t; }" : "+r"(A[i / 14][i % 14]) : "r"(k.hi), "r"(k.lo), "r"(k.sh));
    }
}
__device__ __forceinline__ void slice_stats(const uint32_t* w, float* st) {
    float a = 0.f, b = 0.f, p = 0.f, q = 0.f;
#pragma unroll
    for (int i = 0; i < 7; i++) {
        const float e0 = bf_lo(w[2 * i]), e1 = bf_hi(w[2 * i]), e2 = bf_lo(w[2 * i + 1]), e3 = bf_hi(w[2 * i + 1]);
        a += e0 + e1; b += e2 + e3;
        p = fmaf(e0, e0, p); p = fmaf(e1, e1, p); q = fmaf(e2, e2, q); q = fmaf(e3, e3, q);
    }
    a += __shfl_xor_sync(0xffffffffu, a, 1); p += __shfl_xor_sync(0xffffffffu, p, 1); b += __shfl_xor_sync(0xffffffffu, b, 1); q += __shfl_xor_sync(0xffffffffu, q, 1);
    a += __shfl_xor_sync(0xffffffffu, a, 2); p += __shfl_xor_sync(0xffffffffu, p, 2); b += __shfl_xor_sync(0xffffffffu, b, 2); q += __shfl_xor_sync(0xffffffffu, q, 2);
    st[0] = a; st[1] = p; st[2] = b; st[3] = q;
}
__device__ __forceinline__ void dual_softmax(const float* p, uint32_t* out) {
    constexpr float L = 1.4426950408889634f;
#pragma unroll
    for (int r = 0; r < 2; r++) {
        float mx = fmaxf(p[2 * r], p[2 * r + 1]), mn = fminf(p[2 * r], p[2 * r + 1]);
#pragma unroll
        for (int i = 1; i < 7; i++) {
            mx = fmaxf(mx, fmaxf(p[4 * i + 2 * r], p[4 * i + 2 * r + 1]));
            mn = fminf(mn, fminf(p[4 * i + 2 * r], p[4 * i + 2 * r + 1]));
        }
        mx = fmaxf(mx, __shfl_xor_sync(0xffffffffu, mx, 1));
        mn = fminf(mn, __shfl_xor_sync(0xffffffffu, mn, 1));
        const float bx = -mx * L, bn = mn * L;
        float ep[14], en[14], sp = 0.f, sn = 0.f;
#pragma unroll
        for (int i = 0; i < 14; i++) {
            const float v = p[4 * (i >> 1) + 2 * r + (i & 1)];
            ep[i] = ex2(fmaf(v, L, bx));
            en[i] = ex2(fmaf(v, -L, bn));
            sp += ep[i]; sn += en[i];
        }
        sp += __shfl_xor_sync(0xffffffffu, sp, 1);
        sn += __shfl_xor_sync(0xffffffffu, sn, 1);
        const float ip = rcp(sp), in = rcp(sn);
#pragma unroll
        for (int i = 0; i < 7; i++) {
            out[4 * i + r] = pack2(ep[2 * i] * ip, ep[2 * i + 1] * ip);
            out[4 * i + 2 + r] = pack2(en[2 * i] * in, en[2 * i + 1] * in);
        }
    }
}
__device__ __forceinline__ float geglu(float g, float u) {
    const float t = tanh_hw(g * fmaf(g * g, 0.7978845608028654f * 0.044715f, 0.7978845608028654f));
    const float gu = g * u;
    return fmaf(t, gu, gu);
}
__device__ __forceinline__ void phi_gemm(const float* t, float* p) {
    uint32_t w[14];
#pragma unroll
    for (int i = 0; i < 14; i++) w[i] = pack2(t[2 * i], t[2 * i + 1]);
    const uint64_t db = BASE128(OFF_WPHI, 16, 0);
    wg_fence();
    mma_rs56<0, 0>(p, w[0], w[1], w[2], w[3], 0, db);
    mma_rs56<0, 2>(p, w[4], w[5], w[6], w[7], 1, db);
    mma_rs56<0, 4>(p, w[8], w[9], w[10], w[11], 1, db);
    mma_rs56<0, 6>(p, w[12], w[13], 0u, 0u, 1, db);
    wg_commit();
    wg_wait<0>();
}

}

#define BAR(i) (bars + 8 * (i))
#define R_WAIT() mbar_wait(BAR(slot), ph)
#define WSUM(i)
#define R_ADJ (slot * (STAGE >> 4))
#define R_NEXT() do { eb2 = eb1; eb1 = BAR(B_EMPTY + slot); if (++slot == NST) { slot = 0; ph ^= 1; } } while (0)
#define R_RELEASE(k) do { if (lane == 0) mbar_arrive((k) == 1 ? eb1 : eb2); } while (0)
#define PUSH_BEGIN() mbar_wait(BAR(B_ACK + wgi), step >> 1)
#define PUSH_ACK() do { __syncwarp(); if (lane == 0) asm volatile("mbarrier.arrive.shared::cluster.b64 _, [%0];" ::"r"(mapa(BAR(B_ACK + wgi), hr ^ 1)) : "memory"); } while (0)

__global__ void __cluster_dims__(2, 1, 1) __launch_bounds__(384, 1)
fused_kernel(Scratch* const sc, const __nv_bfloat16* __restrict__ x_in, const __nv_bfloat16* __restrict__ w_phi, const int trips,
             const __nv_bfloat16* __restrict__ wg, const __nv_bfloat16* __restrict__ wu, const __nv_bfloat16* __restrict__ wd,
             const __grid_constant__ Maps maps) {
    extern __shared__ __align__(1024) unsigned char smem_raw[];
    const uint32_t sb = s2u(smem_raw);
    const uint32_t bars = sb + OFF_BAR;
    const int wgi = __shfl_sync(0xffffffffu, threadIdx.x >> 7, 0);
    const int hr = blockIdx.x & 1, ck = blockIdx.x >> 1;
    const int gp = (ck - 4) & 7, q7 = ((ck - 36) * 37) >> 8;
    const int pr = __shfl_sync(0xffffffffu, ck < 4 ? ck : (ck < 36 ? (ck - 4) >> 3 : q7), 0);
    const int tile = __shfl_sync(0xffffffffu, ck < 4 ? 0 : (ck < 36 ? (gp ? 2 * gp : 1) : 2 * (ck - 36 - 7 * q7) + 3), 0);
    const int sl = 2 * pr + hr;
    STAMP(0);
    GSTAMP(60);
    if (threadIdx.x == 256) {
#pragma unroll
        for (int i = 0; i < NST; i++) mbar_init(BAR(i), 1);
        asm volatile("fence.mbarrier_init.release.cluster;" ::: "memory");
    }
    if (threadIdx.x == 288) {
        if ((sb & 0x3FFFF) != SB0) asm volatile("trap;");
#pragma unroll
        for (int i = NST; i < B_COUNT; i++) mbar_init(BAR(i), i >= B_ACK ? 4 : (i < B_RECV || i == B_LATE ? 8 : 1));
        asm volatile("fence.mbarrier_init.release.cluster;" ::: "memory");
    }
    __syncwarp();
    asm volatile("barrier.cluster.arrive.relaxed.aligned;" ::: "memory");

    if (wgi == 2) {
        asm volatile("setmaxnreg.dec.sync.aligned.u32 40;");
        const int t128 = fresh_tid() & 127, w = __shfl_sync(0xffffffffu, t128 >> 5, 0), lane = t128 & 31;
        uint32_t e0[2] = {0, 0}, e1[2] = {0, 0}, cw_target = 0, kseq;
        if (w == 0) {
#pragma unroll 1
            for (int n = 0; n < NST; n++) {
                const uint32_t dst = sb + n * STAGE, fb = BAR(n);
                asm volatile(ELECT "mbarrier.arrive.expect_tx.shared::cta.b64 _, [%0], %1; }" ::"r"(fb), "r"(n < 2 ? 2 * STAGE : STAGE) : "memory");
                if (n < 2) {
                    tma3x(sb + OFF_H + n * STAGE, &maps.x, tile * 128 + n * 64, fb);
                    tma3x(dst, &maps.x, tile * 128 + n * 64 + 32, fb);
                } else {
                    if (n == 3) mbar_wait(BAR(1), 0);
                    const int c0 = (n < 4 ? 448 : 896) + 56 * sl, r0 = 224 * (n & 1);
                    tma2d(dst, &maps.qkv, c0, r0, fb);
                    tma2d(dst + HALF, &maps.qkv, c0, r0 + 112, fb);
                }
            }
            asm volatile("barrier.cluster.wait.aligned;" ::: "memory");
            kseq = ld_word(g_c1 + (sl * 8 * 16 + tile) * 32);
            cw_target = (ld_word(g_cw + sl * 32) & ~15u) + 16;
#pragma unroll 1
            for (int k = 0; k < 2; k++) {
                const int n = t128 + 32 * k;
                int m = n - 2 - (n > PACK);
                const bool packed = m >= 30 ? (m < 38 || m >= 52) : m >= 22;
                if (m >= 30) m -= 30;
                if (n == PACK) m = tile < 8 ? tile : tile + 14;
                const int rot = n < 8 ? 0 : pr;
                const int ra = 112 * kblk(rot, m & 3), rb = 112 * kblk(rot, 2 * m & 3), rc = 112 * kblk(rot, (2 * m + 1) & 3);
                int kind = 0, m0, m1, c0, c1, r0, r1;
                if (m < 8) { m0 = m1 = m < 6 ? 1 : 2; c0 = c1 = (m < 2 ? 448 : (m < 4 ? 896 : 0)) + 56 * sl; r0 = rb; r1 = rc; }
                else if (m < 20) { m0 = 3; m1 = 4; c0 = c1 = 224 * sl + 32 * hr + 64 * ((m - 8) >> 2); r0 = r1 = ra; }
                else if (m < 22) { kind = 2; m0 = 5; m1 = 6; c0 = c1 = 224 * sl + (hr ? 0 : 192); r0 = rb; r1 = rc; }
                else { m0 = m1 = 7; c0 = c1 = 56 * (2 * ((pr + (m >> 1) - 10) & 3) + hr); r0 = 224 * (sl ^ (m & 1)); r1 = r0 + 112; }
                if (packed) { kind = 1; r0 = sl * 16 + (m < 8 ? m : m - 14); r1 = 0; }
                e0[0] = e0[1]; e1[0] = e1[1];
                e0[1] = kind | (m0 << 2) | (m1 << 6) | (c0 << 10) | (c1 << 21);
                e1[1] = r0 | (r1 << 16);
            }
        } else {
            const int j = t128 - 32;
            kseq = ld_word(g_c1 + (sl * 8 * 16 + tile) * 32);
            asm volatile("barrier.cluster.wait.aligned;" ::: "memory");
            uint2 wv[7];
            const int k = j < 56 ? j : 55, hh = k >= 28;
#pragma unroll
            for (int i = 0; i < 7; i++) wv[i] = __ldg(reinterpret_cast<const uint2*>(w_phi + (sl * 56 + k) * 28) + i);
#pragma unroll 1
            for (int i = j; i < 7168 / 16; i += 96) sts4(sb + OFF_WPHI + i * 16, 0, 0, 0, 0);
            bar_sync(5, 96);
            if (j < 56) {
                uint32_t a4[4];
#pragma unroll
                for (int q = 0; q < 4; q++) a4[q] = sb + OFF_WPHI + (4 * hh + q) * 128 + ((((k >> 3) ^ (4 * hh + q)) & 7) << 4) + (k & 7) * 2;
                FOR14(const uint32_t v = (t & 1) ? wv[t >> 1].y : wv[t >> 1].x;
                      asm volatile("{ .reg .b16 l, h; mov.b32 {l, h}, %2; st.shared.u16 [%0+%3], l; st.shared.u16 [%1+%3], h; }"
                                   ::"r"(a4[t >= 7 ? 2 : 0]), "r"(a4[t >= 7 ? 3 : 1]), "r"(v), "n"((t % 7) * 1024) : "memory"));
            }
            __syncwarp();
            fence_async();
            kseq = __shfl_sync(0xffffffffu, kseq, 0);
            bar_arrive(1, 224);
            bar_arrive(9, 224);
        }
        kseq = __shfl_sync(0xffffffffu, kseq, 0);
        int slot = 0, ph = 0, n = NST;
#pragma unroll 1
        for (int layer = 0; layer < 3; layer++) {
            if (w == 0) {
                const int nend = layer == 0 ? 11 : (layer == 1 ? 42 : 63);
#pragma unroll 1
                for (; n < nend; n++) {
                const uint32_t w0 = __shfl_sync(0xffffffffu, n < 32 ? e0[0] : e0[1], n & 31), w1 = __shfl_sync(0xffffffffu, n < 32 ? e1[0] : e1[1], n & 31);
                const uint32_t dst = sb + slot * STAGE, fb = BAR(n == PACK ? B_PACK : slot);
                const CUtensorMap* m0 = &maps.x + ((w0 >> 2) & 15);
                const CUtensorMap* m1 = &maps.x + ((w0 >> 6) & 15);
                const int c0 = (w0 >> 10) & 2047, c1 = w0 >> 21, r0 = w1 & 0xffff, r1 = w1 >> 16;
                if (n == 25) {
                    int it = 0;
                    uint32_t v;
                    do { asm volatile("ld.acquire.gpu.global.u32 %0, [%1];" : "=r"(v) : "l"(g_cw + sl * 32) : "memory"); } while ((int)(v - cw_target) < 0 && ++it < 0x400000);
                    asm volatile("fence.proxy.async.global;" ::: "memory");
                    __syncwarp();
                }
                mbar_wait(BAR(B_EMPTY + slot), ph);
                __syncwarp();
                asm volatile(ELECT "mbarrier.arrive.expect_tx.shared::cta.b64 _, [%0], %1; }" ::"r"(fb), "r"(STAGE) : "memory");
                if ((w0 & 3) == 0) {
                    tma2d(dst, m0, c0, r0, fb);
                    tma2d(dst + HALF, m1, c1, r1, fb);
                } else if (w0 & 1) {
                    asm volatile(ELECT "cp.async.bulk.shared::cluster.global.mbarrier::complete_tx::bytes [%0], [%1], %2, [%3]; }"
                                 ::"r"(dst), "l"(reinterpret_cast<const char*>(g_wp) + (size_t)r0 * STAGE), "r"(STAGE), "r"(fb) : "memory");
                } else {
                    tma2d(dst, m0, c0, r0, fb); tma2d(dst + 7168, m0, c0, r1, fb);
                    tma2d(dst + HALF, m1, c0, r0, fb); tma2d(dst + HALF + 7168, m1, c0, r1, fb);
                }
                if (n == PFN) {
                    const int b = blockIdx.x;
                    asm volatile(ELECT "cp.async.bulk.prefetch.L2.global [%0], %1; }" ::"l"(wg + b * 6272), "r"(12544) : "memory");
                    asm volatile(ELECT "cp.async.bulk.prefetch.L2.global [%0], %1; }" ::"l"(wu + b * 6272), "r"(12544) : "memory");
                    asm volatile(ELECT "cp.async.bulk.prefetch.L2.global [%0], %1; }" ::"l"(wd + b * 6272), "r"(12544) : "memory");
                }
                if (n == PACK) asm volatile(ELECT "mbarrier.arrive.shared::cta.b64 _, [%0]; }" ::"r"(BAR(slot)) : "memory");
                if (++slot == NST) { slot = 0; ph ^= 1; }
                }
            } else if (w == 1 && layer == 1) {
                constexpr int ps = PACK % NST;
                mbar_wait(BAR(B_PACK), 0);
                asm volatile("{ .reg .pred e; elect.sync _|e, 0xffffffff;\n"
                             "@e cp.async.bulk.global.shared::cta.bulk_group [%0], [%1], %2;\n"
                             "@e cp.async.bulk.commit_group;\n"
                             "@e cp.async.bulk.wait_group.read 0;\n"
                             "@e mbarrier.arrive.shared::cta.b64 _, [%3], 8;\n"
                             "@e cp.async.bulk.wait_group 0;\n"
                             "@e fence.proxy.async.global;\n"
                             "@e red.release.gpu.global.add.u32 [%4], 1; }"
                             ::"l"(reinterpret_cast<char*>(g_wp) + (size_t)(sl * 16 + tile) * STAGE), "r"(sb + ps * STAGE), "r"(STAGE), "r"(BAR(B_EMPTY + ps)), "l"(g_cw + sl * 32) : "memory");
                __syncwarp();
            }
            if (layer < 2) {
            const uint32_t tag = layer ^ 1;
            kseq++;
            bar_sync(7, 384);
            ASTAMP(0);
            if (tile < 15) {
                const int sq = lane >> 3, pk = 8 * w + (lane & (tile == 14 ? 3 : 7));
                uint32_t v[16];
                if (layer == 0) poll_cnt(g_c1 + ((sl * 8 + (w >> 1) * 4 + (tile >> 2)) * 16 + (lane & 15)) * 32, kseq);
                ASTAMP(1);
                poll4_kv<32>(v, g_kv1 + ((sl * 16 + tile) * 16 + 4 * sq) * 32 + pk, tag);
#pragma unroll
                for (int k = 0; k < 4; k++) {
                    float lo = (bf_lo(v[k]) + bf_lo(v[4 + k])) + (bf_lo(v[8 + k]) + bf_lo(v[12 + k]));
                    float hi = (bf_hi(v[k]) + bf_hi(v[4 + k])) + (bf_hi(v[8 + k]) + bf_hi(v[12 + k]));
                    lo += __shfl_xor_sync(0xffffffffu, lo, 8); hi += __shfl_xor_sync(0xffffffffu, hi, 8);
                    lo += __shfl_xor_sync(0xffffffffu, lo, 16); hi += __shfl_xor_sync(0xffffffffu, hi, 16);
                    v[k] = pack2(lo, hi);
                }
                if (sq == 0) st_pkt<0>(g_kv2 + sl * 512 + 32 * tile + pk, settag(v[0], tag), v[1], v[2], v[3]);
            }
            ASTAMP(2);
            {
                const int item = t128 < 112 ? t128 : 112 + (t128 & 3), d = item >> 1;
                const int cc = t128 < 112 ? 2 * (d >= 28) + (item & 1) : item - 112;
                const int r = t128 < 112 ? d : 56 + (cc >> 1) + 2 * ((t128 - 112) >> 2);
                uint32_t ra = sb + OFF_KVB + r * 128 + 4 * cc, rx = (r & 7) << 4;
                asm volatile("" : "+r"(ra), "+r"(rx));
                FOR14(asm volatile("st.shared.u32 [%0+%2], %1;" ::"r"((ra ^ 8) + (((t & 7) << 4) ^ rx)), "r"(0), "n"((t >> 3) * 8192) : "memory"));
                uint32_t v[16];
                asm volatile("" : "+r"(ra), "+r"(rx));
                poll4_kv<8>(v, g_kv2 + sl * 512 + (item >> 3) * 32 + (item & 7), tag);
                FOR14(asm volatile("st.shared.u32 [%0+%2], %1;" ::"r"(ra + (((t & 7) << 4) ^ rx)), "r"(v[t < 7 ? t : t + 1]), "n"((t >> 3) * 8192) : "memory"));
                fence_async();
            }
            bar_arrive(3, 384);
            ASTAMP(3);
            }
        }
    } else {
        asm volatile("setmaxnreg.inc.sync.aligned.u32 232;");
        int lane = fresh_tid() & 31, prf = pr;
#define pr prf
#define g (lane >> 2)
#define c (lane & 3)
#define t128 (w * 32 + lane)
        const int wu = __shfl_sync(0xffffffffu, fresh_tid() >> 5, 0), w = wu & 3;
        const uint32_t xoff = __shfl_sync(0xffffffffu, (3 * PLANE + ((tile * 2 + wgi) * 8) * 512 + w * 128) * 16, 0);
        char* xu = reinterpret_cast<char*>(g_ex) + xoff;
#define FRESH() asm volatile("" : "+l"(xu), "+r"(lane), "+r"(prf))
#define xp0 (reinterpret_cast<uint4*>(xu) + lane)
        const uint32_t hbuf = sb + OFF_H + wgi * STAGE;
        uint32_t slot = 0, ph = 0, eb1 = 0, eb2 = 0, gatph = 0, swp = 0;
        uint32_t ppid = 6;
#define cx(s) (reinterpret_cast<uint32_t*>(reinterpret_cast<uint4*>(xu) + PL(1) + 112 + (s) * 512))
#define stp (reinterpret_cast<uint4*>(xu) + g + PL(0) + 112)
        uint32_t seq = ld_word(cx(sl));
        uint32_t kseq = ld_word(g_c1 + ((sl * 8 + wu) * 16 + tile) * 32);
        uint32_t stag = ld_word(reinterpret_cast<const uint32_t*>(stp + sl * 512) + 3) & 1;
        asm volatile("barrier.cluster.wait.aligned;" ::: "memory");
        STAMP(1);
        uint32_t X[14];
        const uint32_t x0row = (w < 2 ? hbuf : sb + wgi * STAGE) + ((w & 1) * 16 + (lane & 15)) * 128;
        mbar_wait(BAR(wgi), 0);
        STAMP(51);
#pragma unroll
        for (int j = 0; j < 4; j++) {
            const int G = 7 * sl + min(2 * j + (lane >> 4), 6);
            uint32_t q2, q3;
            asm volatile("ldmatrix.sync.aligned.m8n8.x4.shared.b16 {%0,%1,%2,%3}, [%4];" : "=r"(X[4 * j]), "=r"(X[4 * j + 1]), "=r"(q2), "=r"(q3)
                         : "r"(x0row + (G >> 3) * 4096 + (((G ^ lane) & 7) << 4)) : "memory");
            if (j < 3) { X[(4 * j + 2) % 14] = q2; X[(4 * j + 3) % 14] = q3; }
        }
#define OWN_SLICE(W)                                                                           \
    _Pragma("unroll") for (int i = 0; i < 14; i++) A[0][i] = (i & 3) ? W[i] : W[i] & ~1u;      \
    swp = hr * 448;
#define SWB(b, t, db, sh) ((b) == 0 && (t) < 6 ? ((t) < 3 ? db##p : db##m) : db)
#define DECL_DB(b, MK, lbo, sh) const uint64_t db = MK(0, lbo, R_ADJ), dbp = (b) == 0 ? MK(0, lbo, R_ADJ + (swp >> (sh))) : db, dbm = (b) == 0 ? MK(0, lbo, R_ADJ - (swp >> (sh))) : db;
#define PPB 2
#define PP_WAIT() if (wgi == 1) { bar_sync(ppid, 256); ppid ^= 14; }
#define PP_GO() if (wgi == 0) { bar_arrive(ppid, 256); ppid ^= 14; }
#define BULK(dst, src) "@e cp.async.bulk.shared::cluster.global.mbarrier::complete_tx::bytes [" dst "], [" src "], 1792, [%0];\n"
#define GAT_ISSUE1(base)                                                                       \
    asm volatile("{ .reg .pred e; elect.sync _|e, 0xffffffff;\n @e mbarrier.arrive.expect_tx.shared::cta.b64 _, [%0], 5376;\n" \
                 BULK("%1", "%2") BULK("%1+1792", "%3") BULK("%1+3584", "%3+8192") "}"         \
                 ::"r"(BAR(B_GAT + wu * 2)), "r"(hbuf + w * 5376), "l"(xu + ((base) + (sl ^ 1) * 512) * 16), "l"(xu + ((base) + kblk(pr, 1) * 1024) * 16) : "memory"); \
    __syncwarp();
#define GAT_ISSUE3(base)                                                                       \
    asm volatile("{ .reg .pred e; elect.sync _|e, 0xffffffff;\n @e mbarrier.arrive.expect_tx.shared::cta.b64 _, [%0], 3584;\n" \
                 BULK("%1", "%3") BULK("%2", "%3+8192") "}"                                    \
                 ::"r"(BAR(B_GAT + wu * 2 + 1)), "r"(hbuf + 21504 + w * 1792), "r"(sb + OFF_KVB + wgi * 8192 + w * 1792), "l"(xu + ((base) + kblk(pr, 3) * 1024) * 16) : "memory"); \
    __syncwarp();
#define LDS_SLICE(V, addr)                                                                     \
    { const uint32_t ga = (addr) + lane * 16;                                                  \
      lds4(&(V)[0], ga); lds4(&(V)[4], ga + 512); lds4(&(V)[8], ga + 1024);                    \
      asm volatile("ld.shared.v2.u32 {%0,%1}, [%2];" : "=r"((V)[12]), "=r"((V)[13]) : "r"(ga - lane * 8 + 1536) : "memory"); }
#define GAT_FETCH1(src, tg)                                                                    \
    {                                                                                          \
        mbar_wait(BAR(B_GAT + wu * 2), (gatph >> 1) & 1);                                      \
        gatph ^= 2;                                                                            \
        LDS_SLICE(A[1], hbuf + w * 5376) LDS_SLICE(A[2], hbuf + w * 5376 + 1792) LDS_SLICE(A[3], hbuf + w * 5376 + 3584) \
        slice_check<0>(A[1], (src) + (sl ^ 1) * 512, lane, tg);                                \
        A[1][0] &= ~1u; A[1][4] &= ~1u; A[1][8] &= ~1u;                                        \
        const uint32_t t0 = A[1][12] & ~1u, t1 = A[1][13], u0 = A[0][12], u1 = A[0][13];       \
        A[0][12] = hr ? t0 : u0; A[0][13] = hr ? t1 : u1; A[1][12] = hr ? u0 : t0; A[1][13] = hr ? u1 : t1; \
    }
#define GAT_FETCH3()                                                                           \
    {                                                                                          \
        mbar_wait(BAR(B_GAT + wu * 2 + 1), (gatph >> 3) & 1);                                  \
        gatph ^= 8;                                                                            \
        LDS_SLICE(A[6], hbuf + 21504 + w * 1792) LDS_SLICE(A[7], sb + OFF_KVB + wgi * 8192 + w * 1792) \
    }
#define LATE_ARRIVE() do { if (lane == 0) mbar_arrive(BAR(B_LATE)); } while (0)
#define LATE_WAIT() do { mbar_wait(BAR(B_LATE), gatph & 1); gatph ^= 1; } while (0)
#define PT 3
#define PIN(V) asm volatile("" : RW4(V, 0), RW4(V, 4), RW4(V, 8), RW2(V, 12));
#define PREP(b, t, remote)                                                                     \
    if constexpr ((b) < 3 && (t) == ((b) ? PT : 2)) {                                          \
        wg_commit();                                                                           \
        STAMP(74 + 6 * (step & 1) + 2 * (b));                                                  \
        if (remote) {                                                                          \
            if constexpr ((b) == 0) { blk_load<2>(A, BLK(xsrc, 2), lane); GAT_FETCH1(xsrc, xtag) } \
            blk_check<((b) + 1) & 3>(A, BLK(xsrc, (b) + 1), lane, xtag);                       \
            if constexpr ((b) == 0) { GAT_ISSUE3((step & 1) ? PL(2) : PL(0)) }                 \
        }                                                                                      \
        STAMP(75 + 6 * (step & 1) + 2 * (b));                                                  \
        if constexpr ((b) == 0) { normalize<12, 28>(A, k0, k1); PIN(A[0]) PIN(A[1]) wg_fence(); } \
        else { normalize<28 * ((b) + 1), 28 * ((b) + 2)>(A, k0, k1); PIN(A[(2 * (b) + 2) & 7]) PIN(A[(2 * (b) + 3) & 7]) wg_fence(); } \
    }                                                                                          \
    if constexpr ((b) == 0 && (t) == 4) { wg_commit(); normalize<28, 56>(A, k0, k1); PIN(A[2]) PIN(A[3]) wg_fence(); }
#define X0_BLOCK(b)                                                                            \
    { const int rr = lane & 7, hi = lane >> 4;                                                 \
    const uint32_t rowa = (w < 2 ? hbuf : sb + wgi * STAGE) + ((w & 1) * 16 + (lane & 15)) * 128; \
    FOR7(constexpr int G = 14 * (b) + (t < 3 ? 2 * t : (t < 6 ? 2 * t + 1 : 6));               \
         uint32_t q0, q1, q2, q3;                                                              \
         const uint32_t ad = t < 6 ? rowa + (((((G & 7) + hi) ^ rr) & 7) << 4) + ((G & 7) == 7 ? hi * 4096 : 0) : rowa + ((G + 7 * hi) >> 3) * 4096 + ((((G + 7 * hi) ^ rr) & 7) << 4); \
         asm volatile("ldmatrix.sync.aligned.m8n8.x4.shared.b16 {%0,%1,%2,%3}, [%4+%5];" : "=r"(q0), "=r"(q1), "=r"(q2), "=r"(q3) \
                      : "r"(ad), "n"(t < 6 ? (G >> 3) * 4096 : 0) : "memory");                 \
         if (t < 3) { A[2 * (b)][4 * t] = q0; A[2 * (b)][4 * t + 1] = q1; A[2 * (b)][4 * t + 2] = q2; A[2 * (b)][4 * t + 3] = q3; } \
         else if (t < 6) { A[2 * (b) + 1][(4 * t - 12) & 15] = q0; A[2 * (b) + 1][((4 * t - 12) & 15) + 1] = q1; A[2 * (b) + 1][((4 * t - 12) & 15) + 2] = q2; A[2 * (b) + 1][((4 * t - 12) & 15) + 3] = q3; } \
         else { A[2 * (b)][12] = q0; A[2 * (b)][13] = q1; A[2 * (b) + 1][12] = q2; A[2 * (b) + 1][13] = q3; }); }
#define BLK(base, b) ((base) + kblk(pr, b) * 1024)

#pragma unroll 1
        for (int step = 0; step < 4; step++) {
            FRESH();
            const uint32_t tag = (step >> 1) ^ 1;
            const int so = (step >> 1) * 24 + (step & 1) * 12;
            (void)so;
            uint32_t A[8][14];
            uint4* const xsrc = xp0 + ((step & 1) ? PL(2) : PL(0));
            const uint32_t xtag = (step & 1) ? tag : ((seq >> 3) & 1) ^ 1;
            uint32_t xbits;
            {
                float st[4];
                slice_stats(X, st);
                stag ^= 1;
                xbits = x_bits(X);
                tag_slice(X, xtag);
                if (step) send_slice<0>(xsrc + sl * 512, lane, X);
                if (c == 0) st_pkt<0>(stp + sl * 512, __float_as_uint(st[0]), __float_as_uint(st[1]), __float_as_uint(st[2]), settag(__float_as_uint(st[3]), stag));
            }
            STAMP(2 + so);
            uint32_t sv[8];
            if (step == 0) {
                X0_BLOCK(0) X0_BLOCK(1) X0_BLOCK(2) X0_BLOCK(3)
                mbar_wait(BAR(wgi ^ 1), 0);
                R_NEXT();
                R_NEXT();
                R_RELEASE(2);
                stat_load(sv, stp + c * 1024);
                stat_check(sv, stp + c * 1024, stag);
                STAMP(52 + step);
            } else {
                kill<14>(A[1]); kill<14>(A[2]); kill<14>(A[3]); kill<14>(A[4]); kill<14>(A[5]); kill<14>(A[6]); kill<14>(A[7]);
                stat_load(sv, stp + c * 1024);
                OWN_SLICE(X)
                stat_check(sv, stp + c * 1024, stag);
                STAMP(52 + step);
                GAT_ISSUE1((step & 1) ? PL(2) : PL(0))
            }
            LnCoef k0, k1;
            {
                k0 = ln_coef(__uint_as_float(sv[0]) + __uint_as_float(sv[4]), __uint_as_float(sv[1]) + __uint_as_float(sv[5]));
                k1 = ln_coef(__uint_as_float(sv[2]) + __uint_as_float(sv[6]), __uint_as_float(sv[3] & ~1u) + __uint_as_float(sv[7] & ~1u));
            }
            STAMP(3 + so);
            GSTAMP(70 + step);

            if ((step & 1) == 0) {
                float tq[28];
#define K_BLOCK(b)                                                                            \
    if ((b) == 1) R_RELEASE(1);                                                               \
    if ((b) == 2 && step) GAT_FETCH3()                                                        \
    if ((b) == 3) { wg_wait<2>(); R_RELEASE(1); }                                             \
    if (((b) & 1) == 0) R_WAIT();                                                             \
    { DECL_DB(b, BASE128, 16, 0)                                                              \
    wg_fence();                                                                               \
    FOR7(mma_rs56<1, D128(((b) & 1) * HALF, t)>(tq, AQ(A, b, t), (b) + t > 0, SWB(b, t, db, 0)); \
         PREP(b, t, step)); }                                                                 \
    wg_commit();                                                                              \
    if ((b) & 1) R_NEXT();
#define P_STAGE(acc, b0)                                                                      \
    R_WAIT();                                                                                 \
    { DECL_DB(b0, BASE128, 16, 0)                                                             \
    wg_fence();                                                                               \
    FOR7(mma_rs56<1, D128(0, t)>(acc, AQ(A, b0, t), (b0) + t > 0, SWB(b0, t, db, 0)));        \
    FOR7(mma_rs56<1, D128(HALF, t)>(acc, AQ(A, (b0) + 1, t), 1, db)); }                       \
    wg_commit();                                                                              \
    R_NEXT();
#define PROJECT(acc) P_STAGE(acc, 0) P_STAGE(acc, 2) wg_wait<1>(); R_RELEASE(2); wg_wait<0>(); R_RELEASE(1);
#define V_PASS()                                                                              \
    {                                                                                         \
        float av[28];                                                                         \
        PROJECT(av)                                                                           \
        const int m = lane >> 3, rr = lane & 7;                                               \
        const uint32_t rowa = hbuf + 16384 + (w * 16 + rr + 8 * (m & 1)) * 128;               \
        const uint32_t one = c == 0 ? 0x00003f80u : 0u;                                       \
        _Pragma("unroll") for (int j = 0; j < 4; j++) {                                       \
            const uint32_t a = rowa + (((2 * j + (m >> 1)) ^ rr) << 4);                       \
            if (j < 3) stsm4(a, pack2(av[8 * j], av[8 * j + 1]), pack2(av[8 * j + 2], av[8 * j + 3]), pack2(av[8 * j + 4], av[8 * j + 5]), pack2(av[8 * j + 6], av[8 * j + 7])); \
            else stsm4(a, pack2(av[24], av[25]), pack2(av[26], av[27]), one, one);            \
        }                                                                                     \
    }
                normalize<0, 12>(A, k0, k1);
                K_BLOCK(0) K_BLOCK(1) K_BLOCK(2) K_BLOCK(3)
                wg_wait<0>();
                R_RELEASE(1);
                STAMP(4 + so);
                if (step == 0) { bar_sync(wgi ? 9 : 1, 224); }
                if (wgi == VW) V_PASS()
                uint32_t PH[28];
                int it = 1;
#pragma unroll 1
                do {
                    float pp[28];
                    phi_gemm(tq, pp);
                    dual_softmax(pp, PH);
                    if (((trips >> (it + 1)) & 1) == 0) continue;
                    {
                        const int m = lane >> 3, rr = lane & 7;
                        const uint32_t rowa = hbuf + (w * 16 + rr + 8 * (m & 1)) * 128;
#pragma unroll
                        for (int j = 0; j < 7; j++) {
                            const int cg = 2 * j + (m >> 1), hi = cg >= 7;
                            stsm4(rowa + hi * 8192 + (((cg - 7 * hi) ^ rr) << 4), PH[4 * j], PH[4 * j + 1], PH[4 * j + 2], PH[4 * j + 3]);
                        }
                    }
                    STAMP(5 + so);
                    if (wgi != VW) V_PASS()
                    fence_async();
                    bar_sync(2, 256);
                    float kv[28];
                    const uint64_t da = BASE128(OFF_H + 16384, 16, 0), dbk = BASE128(OFF_H, 16, wgi * 512);
                    wg_fence();
                    FOR8(constexpr uint64_t o = ((t >> 2) * STAGE + (t & 3) * 2048) >> 4; mma_ss56_tt<o, o>(kv, t > 0, da, dbk));
                    wg_commit();
                    wg_wait<0>();
#pragma unroll
                    for (int hf = 0; hf < 2; hf++) {
                        const int d = 16 * w + g + 8 * hf;
                        if ((d < 56 && (d >= 28) == (c >= 2)) || d == 56) {
                            const int item = d < 56 ? 2 * d + (c & 1) : 112 + c;
                            uint4* dst = g_kv1 + ((sl * 16 + (item >> 3)) * 16 + tile) * 32 + wgi * 16 + (item & 7);
#define KVW(i) pack2(kv[4 * (i) + 2 * hf], kv[4 * (i) + 2 * hf + 1])
                            st_pkt<0>(dst, settag(KVW(0), tag), KVW(1), KVW(2), KVW(3));
                            st_pkt<8>(dst, settag(KVW(4), tag), KVW(5), KVW(6), 0u);
                        }
                    }
                    __syncwarp();
                    kseq++;
                    if (lane == 0) st_word(g_c1 + ((sl * 8 + wu) * 16 + tile) * 32, kseq);
                    bar_arrive(7, 384);
                    STAMP(6 + so);
                    kill<28>(tq);
                    if (QPP) { PP_WAIT() }
                    P_STAGE(tq, 0) P_STAGE(tq, 2)
                    if (QPP) { PP_GO() }
                    wg_wait<1>(); R_RELEASE(2); wg_wait<0>(); R_RELEASE(1);
                    STAMP(7 + so);
                    kill<28>(PH);
                } while (((trips >> (++it)) & 1));
                STAMP(8 + so);
                FRESH();
                if (step) {
                    slice_load<PL(0)>(X, xp0 + sl * 512, lane);
                } else {
                    const uint32_t* xp = reinterpret_cast<const uint32_t*>(x_in + (size_t)(tile * 128 + wu * 16 + g) * 448 + 56 * sl + 2 * c);
#pragma unroll
                    for (int i = 0; i < 7; i++) { X[2 * i] = __ldg(xp + 4 * i); X[2 * i + 1] = __ldg(xp + 4 * i + 8 * 224); }
                }
                bar_sync(3, 384);
                STAMP(9 + so);
                const uint4* const osrc = xp0 + PL(1);
                {
                    float nm[32];
                    const uint64_t db = BASE128(OFF_KVB, 16, 0);
                    wg_fence();
                    FOR7(mma_rs64<0, ((t >> 2) * 8192 + (t & 3) * 32) / 16>(nm, PH[4 * t], PH[4 * t + 1], PH[4 * t + 2], PH[4 * t + 3], t > 0, db));
                    wg_commit();
                    wg_wait<0>();
                    LATE_ARRIVE();
                    const float i00 = rcp(nm[28] + 1e-6f), i01 = rcp(nm[29] + 1e-6f), i10 = rcp(nm[30] + 1e-6f), i11 = rcp(nm[31] + 1e-6f);
                    const float m0 = c >= 2 ? i01 : i00, m1 = c >= 2 ? i11 : i10;
                    uint32_t O[14];
#pragma unroll
                    for (int i = 0; i < 7; i++) {
                        const float f0 = i < 3 ? i00 : (i > 3 ? i01 : m0), f1 = i < 3 ? i10 : (i > 3 ? i11 : m1);
                        O[2 * i] = pack2(nm[4 * i] * f0, nm[4 * i + 1] * f0);
                        O[2 * i + 1] = pack2(nm[4 * i + 2] * f1, nm[4 * i + 3] * f1);
                    }
                    if (OST) { PP_WAIT() }
                    tag_slice(O, tag);
                    send_slice<PL(1)>(xp0 + sl * 512, lane, O);
                    seq++;
                    if (lane == 0) st_word(cx(sl), seq);
                    STAMP(10 + so);
                    if (OST) { PP_GO() }
                    OWN_SLICE(O)
                    PIN(A[0])
                }
                float ao[28];
#define WO_BLOCK(b)                                                                           \
    if ((b) > 0) blk_check<b>(A, BLK(osrc, b), lane, tag);                                    \
    if (((b) & 1) == 0) R_WAIT();                                                             \
    { DECL_DB(b, BASE128, 16, 0)                                                              \
    wg_fence();                                                                               \
    FOR7(mma_rs56<1, D128(((b) & 1) * HALF, t)>(ao, AQ(A, b, t), (b) + t > 0, SWB(b, t, db, 0))); } \
    wg_commit();                                                                              \
    if ((b) & 1) R_NEXT();
                {
                    const uint32_t cv = ld_word(cx(lane & 7));
                    R_WAIT();
                    DECL_DB(0, BASE128, 16, 0)
                    wg_fence();
                    FOR7(if constexpr (t < 3) mma_rs56<1, D128(0, t)>(ao, AQ(A, 0, t), t > 0, dbp));
                    wg_commit();
                    LATE_WAIT();
                    check_cnt(cv, cx(lane & 7), seq);
                    STAMP(56 + (step >> 1));
                    GAT_ISSUE1(PL(1))
                    GAT_ISSUE3(PL(1))
                    blk_load<2>(A, BLK(osrc, 2), lane);
                    STAMP(11 + so);
                    GAT_FETCH1(osrc, tag)
                    PIN(A[0]) PIN(A[1])
                    wg_fence();
                    FOR7(if constexpr (t >= 3) mma_rs56<1, D128(0, t)>(ao, AQ(A, 0, t), 1, SWB(0, t, db, 0)));
                    wg_commit();
                }
                WO_BLOCK(1)
                WO_BLOCK(2)
                GAT_FETCH3()
                WO_BLOCK(3)
                wg_wait<0>();
                R_RELEASE(2);
                STAMP(12 + so);
                WSUM(86 + 7 * (step >> 1));
                x_fix(X, xbits);
#pragma unroll
                for (int i = 0; i < 14; i++) X[i] = pack2(bf_lo(X[i]) + ao[2 * i], bf_hi(X[i]) + ao[2 * i + 1]);
            } else {
                uint32_t H[56];
                float ag[64];
#define F1_EPI(dst, ng, ag)                                                                    \
    _Pragma("unroll") for (int i = 0; i < 2 * (ng); i++)                                       \
        (dst)[i] = pack2(geglu(ag[2 * i], ag[4 * (ng) + 2 * i]), geglu(ag[2 * i + 1], ag[4 * (ng) + 2 * i + 1]));
#define H_PUSH(h0, off) st_async4(rem_h + (off), H[h0], H[(h0) + 1], H[(h0) + 2], H[(h0) + 3], mapa(BAR(B_RECV2 + wgi), hr ^ 1));
#define F1_BLOCK(b, first)                                                                     \
    if ((first) && (b) == 1) R_RELEASE(2);                                                     \
    if ((first) && (b) == 3) PUSH_ACK();                                                       \
    if ((first) && (b) == 2) GAT_FETCH3()                                                      \
    R_WAIT();                                                                                  \
    if ((b) == ((first) ? PPF : PPB)) { PP_WAIT() }                                            \
    { DECL_DB(b, BASE128, HALF, 0)                                                             \
    wg_fence();                                                                                \
    FOR7(mma_rs128<1, D128(0, t)>(ag, AQ(A, b, t), (b) + t > 0, SWB(b, t, db, 0));             \
         if constexpr (first) { PREP(b, t, true) }); }                                         \
    wg_commit();                                                                               \
    if ((b) == 3) { PP_GO() }                                                                  \
    if ((b) > 0) { wg_wait<1>(); R_RELEASE(1); }       \
    R_NEXT();
                normalize<0, 12>(A, k0, k1);
                F1_BLOCK(0, true) F1_BLOCK(1, true) F1_BLOCK(2, true) F1_BLOCK(3, true)
                if (t128 == 0) { mbar_expect_tx(BAR(B_RECV + wgi), 16384); mbar_expect_tx(BAR(B_RECV2 + wgi), 12288); }
                PUSH_BEGIN();
                wg_wait<0>();
                R_RELEASE(1);
                int p = 0;
#pragma unroll 1
                do {
                    F1_EPI(H + 32, 8, ag)
                    STAMP(4 + p + so);
                    WSUM(81 + p + 7 * (step >> 1));
                    if (((trips >> (p + 1)) & 1) == 0) continue;
                    if (step == 1 && p == PKP) R_NEXT();
                    kill<64>(ag);
                    F1_BLOCK(0, false)
                    {
                        const uint32_t pk = (p ? hbuf + 16384 : sb + OFF_KVB + wgi * 8192) + w * 2048;
#pragma unroll
                        for (int k = 0; k < 4; k++) sts4(pk + k * 512 + lane * 16, H[32 + 4 * k], H[33 + 4 * k], H[34 + 4 * k], H[35 + 4 * k]);
                        fence_async();
                        __syncwarp();
                        asm volatile(ELECT "cp.async.bulk.shared::cluster.shared::cta.mbarrier::complete_tx::bytes [%0], [%1], 2048, [%2]; }"
                                     ::"r"(mapa(hbuf + p * 8192 + w * 2048, hr ^ 1)), "r"(pk), "r"(mapa(BAR(B_RECV + wgi), hr ^ 1)) : "memory");
                    }
                    F1_BLOCK(1, false) F1_BLOCK(2, false) F1_BLOCK(3, false)
                    wg_wait<0>();
                    R_RELEASE(1);
                    kill<16>(H + 32);
                } while (((trips >> (++p)) & 1));
#pragma unroll
                for (int k = 0; k < 4; k++) lds4(H + 16 + 4 * k, hbuf + 16384 + w * 2048 + k * 512 + lane * 16);
                __syncwarp();
                if (lane == 0) asm volatile("mbarrier.arrive.shared::cluster.b64 _, [%0];" ::"r"(mapa(BAR(B_ACK2 + wgi), hr ^ 1)) : "memory");
                const uint32_t rem_h = mapa(hbuf + w * 2048 + lane * 16, hr ^ 1);
#define F1_LAST(b0)                                                                            \
    R_WAIT();                                                                                  \
    if (b0) { PP_WAIT() }                                                                      \
    { DECL_DB(b0, BASE64, HALF, 1)                                                             \
    wg_fence();                                                                                \
    FOR7(mma_rs64<1, D64(0, t)>(al, AQ(A, b0, t), (b0) + t > 0, SWB(b0, t, db, 1)));           \
    FOR7(mma_rs64<1, D64(7168, t)>(al, AQ(A, (b0) + 1, t), 1, db)); }                          \
    wg_commit();                                                                               \
    if (b0) { PP_GO() }                                                                        \
    R_NEXT();
                float al[32];
                F1_LAST(0)
                mbar_wait(BAR(B_RECV + wgi), step >> 1);
                mbar_wait(BAR(B_ACK2 + wgi), step >> 1);
                H_PUSH(32, 16384) H_PUSH(36, 16896)
                F1_LAST(2)
                H_PUSH(40, 17408) H_PUSH(44, 17920)
                wg_wait<1>();
                R_RELEASE(2);
                wg_wait<0>();
                R_RELEASE(1);
                uint32_t HP[56];
#pragma unroll
                for (int k = 0; k < 4; k++) lds4(H + 4 * k, sb + OFF_KVB + wgi * 8192 + w * 2048 + k * 512 + lane * 16);
#pragma unroll
                for (int t = 0; t < 8; t++) lds4(HP + 4 * t, hbuf + (t >> 2) * 8192 + w * 2048 + (t & 3) * 512 + lane * 16);
                F1_EPI(H + 48, 4, al)
                H_PUSH(48, 24576 - w * 1024) H_PUSH(52, 25088 - w * 1024)
                STAMP(7 + so);
                WSUM(84 + 7 * (step >> 1));
                FRESH();
                float acc[28];
                const uint32_t roA = hr ? 256u : 0u, roB = hr ? (uint32_t)-1536 : 0u;
                const uint32_t rpA = hr ? 0u : 256u, rpB = hr ? 0u : (uint32_t)-1536;
                float res[28];
                uint32_t v0[14], v1[14], P[14];
                Wide PW;
                const uint4* ps = xp0 + sl * 512;
#define F2_OWN_A()                                                                             \
    R_WAIT();                                                                                  \
    d0 = BASE128(0, 16, R_ADJ + roA); d1 = BASE128(0, 16, R_ADJ + roB);                        \
    wg_fence();                                                                                \
    FOR14(if constexpr (t < OT) mma_rs56<1, t * 128>(acc, H[4 * t], H[4 * t + 1], H[4 * t + 2], H[4 * t + 3], t > 0, d0)); \
    wg_commit();
#define F2_OWN_B()                                                                             \
    wg_fence();                                                                                \
    FOR14(if constexpr (t >= OT) mma_rs56<1, t * 128>(acc, H[4 * t], H[4 * t + 1], H[4 * t + 2], H[4 * t + 3], 1, t < 12 ? d0 : d1)); \
    wg_commit();                                                                               \
    R_NEXT();
#define F2_PEER()                                                                              \
    R_WAIT();                                                                                  \
    if (F2PP) { PP_WAIT() }                                                                    \
    d0 = BASE128(0, 16, R_ADJ + rpA); d1 = BASE128(0, 16, R_ADJ + rpB);                        \
    wg_fence();                                                                                \
    FOR14(mma_rs56<1, t * 128>(acc, HP[4 * t], HP[4 * t + 1], HP[4 * t + 2], HP[4 * t + 3], 1, t < 12 ? d0 : d1)); \
    wg_commit();                                                                               \
    if (F2PP) { PP_GO() }                                                                      \
    R_NEXT();
#define F2_TURN(u)                                                                             \
    wg_wait<1>();                                                                              \
    if ((u) < 2 || TDEF < 2) R_RELEASE(2);                                                     \
    wg_wait<0>();                                                                              \
    if ((u) < 2 || TDEF < 1) R_RELEASE(1);                                                     \
    _Pragma("unroll") for (int i = 0; i < 14; i++) P[i] = pack2(acc[2 * i], acc[2 * i + 1]);   \
    tag_slice(P, tag);                                                                         \
    PW = widen(P);                                                                             \
    kill<28>(acc);                                                                             \
    F2_OWN_A()                                                                                 \
    if ((u) == 2) { slice_load<PL(3)>(v0, ps, lane); slice_load<PL(4)>(v1, ps, lane); } \
    send_wide<PL(3 + (u))>(xp0 + (2 * ((pr + (u) + 1) & 3) + hr) * 512, lane, PW);             \
    seq++;                                                                                     \
    if (lane == 0) st_word(cx(sl), seq);                                                       \
    __syncwarp();                                                                              \
    STAMP(8 + (u) + so);                                                                       \
    F2_OWN_B()
                uint64_t d0, d1;
                F2_OWN_A()
                F2_OWN_B()
                R_WAIT();
                d0 = BASE128(0, 16, R_ADJ + rpA); d1 = BASE128(0, 16, R_ADJ + rpB);
                wg_fence();
                FOR8(mma_rs56<1, t * 128>(acc, HP[4 * t], HP[4 * t + 1], HP[4 * t + 2], HP[4 * t + 3], 1, d0));
                wg_commit();
                mbar_wait(BAR(B_RECV2 + wgi), step >> 1);
#pragma unroll
                for (int k = 0; k < 4; k++) lds4(HP + 32 + 4 * k, hbuf + 16384 + w * 2048 + k * 512 + lane * 16);
                lds4(HP + 48, hbuf + 24576 + w * 1024 + lane * 16);
                lds4(HP + 52, hbuf + 25088 + w * 1024 + lane * 16);
                wg_fence();
                FOR14(if constexpr (t >= 8) mma_rs56<1, t * 128>(acc, HP[4 * t], HP[4 * t + 1], HP[4 * t + 2], HP[4 * t + 3], 1, t < 12 ? d0 : d1));
                wg_commit();
                R_NEXT();
                F2_TURN(0)
                F2_PEER()
                F2_TURN(1)
                F2_PEER()
                F2_TURN(2)
                if (step == 1) STAMP(64);
                slice_check<PL(3)>(v0, ps, lane, tag);
                slice_check<PL(4)>(v1, ps, lane, tag);
#pragma unroll
                for (int i = 0; i < 14; i++) { res[2 * i] = bf_lo(v0[i]) + bf_lo(v1[i]); res[2 * i + 1] = bf_hi(v0[i]) + bf_hi(v1[i]); }
                slice_load<PL(2)>(X, ps, lane);
                if (step == 1) STAMP(65);
                F2_PEER()
                if (step == 1) STAMP(66);
                poll_cnt(cx(2 * ((pr + 1) & 3) + hr), seq);
                if (step == 1) STAMP(67);
                slice_load<PL(5)>(v0, ps, lane);
                x_fix(X, xbits);
                slice_check<PL(5)>(v0, ps, lane, tag);
                if (lane < TDEF) mbar_arrive(BAR(B_EMPTY + (slot + NST - 3 - lane) % NST));
#pragma unroll
                for (int i = 0; i < 14; i++) { res[2 * i] += bf_lo(v0[i]); res[2 * i + 1] += bf_hi(v0[i]); }
                STAMP(11 + so);
                wg_wait<0>();
                R_RELEASE(2);
                STAMP(12 + so);
                WSUM(85 + 7 * (step >> 1));
#pragma unroll
                for (int i = 0; i < 14; i++) X[i] = pack2(fmaf(res[2 * i] + acc[2 * i], 0.5f, bf_lo(X[i])), fmaf(res[2 * i + 1] + acc[2 * i + 1], 0.5f, bf_hi(X[i])));
            }
        }
        {
            const int m = lane >> 3, rr = lane & 7;
            const uint32_t ob = hbuf + w * 2048, rowa = ob + (rr + 8 * (m & 1)) * 112 + (m >> 1) * 16;
#pragma unroll
            for (int j = 0; j < 3; j++) stsm4(rowa + 32 * j, X[4 * j], X[4 * j + 1], X[4 * j + 2], X[4 * j + 3]);
            asm volatile("stmatrix.sync.aligned.m8n8.x2.shared.b16 [%0], {%1,%2};" ::"r"(ob + (rr + 8 * (m & 1)) * 112 + 96), "r"(X[12]), "r"(X[13]) : "memory");
            fence_async();
            __syncwarp();
            if (lane == 0) {
                asm volatile("cp.async.bulk.tensor.2d.global.shared::cta.bulk_group [%0, {%2, %3}], [%1];" ::"l"(&maps.out), "r"(ob), "r"(56 * sl), "r"(tile * 128 + wu * 16) : "memory");
                asm volatile("cp.async.bulk.commit_group;" ::: "memory");
                asm volatile("cp.async.bulk.wait_group.read 0;" ::: "memory");
            }
        }
        STAMP(50);
        GSTAMP(61);
        PDUMP();
    }
}

#undef g
#undef pr
#undef c
#undef t128

typedef CUresult (*EncodeFn)(CUtensorMap*, CUtensorMapDataType, cuuint32_t, void*, const cuuint64_t*, const cuuint64_t*, const cuuint32_t*,
                             const cuuint32_t*, CUtensorMapInterleave, CUtensorMapSwizzle, CUtensorMapL2promotion, CUtensorMapFloatOOBfill);

static void make_map(EncodeFn enc, CUtensorMap* m, const void* p, uint64_t cols, uint64_t rows, uint32_t bc, uint32_t br, CUtensorMapSwizzle sw) {
    cuuint64_t gd[2] = {cols, rows};
    cuuint64_t gs[1] = {cols * 2};
    cuuint32_t bd[2] = {bc, br};
    cuuint32_t es[2] = {1, 1};
    enc(m, CU_TENSOR_MAP_DATA_TYPE_BFLOAT16, 2, const_cast<void*>(p), gd, gs, bd, es, CU_TENSOR_MAP_INTERLEAVE_NONE, sw,
        CU_TENSOR_MAP_L2_PROMOTION_L2_128B, CU_TENSOR_MAP_FLOAT_OOB_FILL_NONE);
}

extern "C" void kernel_launch(void* const* d_in, const int* in_sizes, int n_in, void* d_out, int out_size) {
    (void)in_sizes; (void)n_in; (void)out_size;
    static EncodeFn enc = nullptr;
    static Scratch* scratch = nullptr;
    if (!enc) {
        void* fn = nullptr;
        cudaDriverEntryPointQueryResult qr;
        cudaGetDriverEntryPoint("cuTensorMapEncodeTiled", &fn, cudaEnableDefault, &qr);
        enc = (EncodeFn)fn;
        cudaGetSymbolAddress((void**)&scratch, g_scratch);
        cudaFuncSetAttribute(fused_kernel, cudaFuncAttributeMaxDynamicSharedMemorySize, SMEM_BYTES);
    }
    Maps maps;
    {
        cuuint64_t gd[3] = {64, 2048, 7};
        cuuint64_t gs[2] = {896, 128};
        cuuint32_t bd[3] = {64, 32, 7};
        cuuint32_t es[3] = {1, 1, 1};
        enc(&maps.x, CU_TENSOR_MAP_DATA_TYPE_BFLOAT16, 3, d_in[0], gd, gs, bd, es, CU_TENSOR_MAP_INTERLEAVE_NONE, CU_TENSOR_MAP_SWIZZLE_128B,
            CU_TENSOR_MAP_L2_PROMOTION_L2_128B, CU_TENSOR_MAP_FLOAT_OOB_FILL_NONE);
    }
    make_map(enc, &maps.out, d_out, 448, 2048, 56, 16, CU_TENSOR_MAP_SWIZZLE_NONE);
    make_map(enc, &maps.qkv, d_in[1], 1344, 448, 64, 112, CU_TENSOR_MAP_SWIZZLE_128B);
    make_map(enc, &maps.wo, d_in[3], 448, 448, 64, 112, CU_TENSOR_MAP_SWIZZLE_128B);
    make_map(enc, &maps.wg, d_in[5], 1792, 448, 64, 112, CU_TENSOR_MAP_SWIZZLE_128B);
    make_map(enc, &maps.wu, d_in[6], 1792, 448, 64, 112, CU_TENSOR_MAP_SWIZZLE_128B);
    make_map(enc, &maps.wg32, d_in[5], 1792, 448, 32, 112, CU_TENSOR_MAP_SWIZZLE_64B);
    make_map(enc, &maps.wu32, d_in[6], 1792, 448, 32, 112, CU_TENSOR_MAP_SWIZZLE_64B);
    make_map(enc, &maps.wd, d_in[7], 448, 1792, 64, 112, CU_TENSOR_MAP_SWIZZLE_128B);
    fused_kernel<<<128, 384, SMEM_BYTES>>>(scratch, (const __nv_bfloat16*)d_in[0], (const __nv_bfloat16*)d_in[2], 7, (const __nv_bfloat16*)d_in[5],
                                           (const __nv_bfloat16*)d_in[6], (const __nv_bfloat16*)d_in[7], maps);
}
```

```cpp
#include <cuda_runtime.h>
#include <cuda.h>
#include <cuda_bf16.h>
#include <stdint.h>
#include <type_traits>

#define PPF 2
#define PKP 0
#define TDEF 1
#define TMPF 0
#define NORM1 0
#define LPARK 1
#define PFN 9
#define VW 1
#define QPP 1
#define XG3 2
#define XT (XG3 == 1 || XG3 == 2 || XG3 >= 4)
#define ACAN 0
#define SPLIT0 1
#define OT 2
#define F2PP 0
#define PPK 2
#define QE 1
#define OST 1
#define PP

namespace {

constexpr uint32_t STAGE = 28672, HALF = 14336;
constexpr int NST = 5;
constexpr uint32_t OFF_H = NST * STAGE;
constexpr uint32_t OFF_KVB = OFF_H + 2 * STAGE;
constexpr uint32_t OFF_WPHI = OFF_KVB + 16384;
constexpr uint32_t OFF_XR = OFF_WPHI + 7168;
constexpr uint32_t OFF_BAR = OFF_XR + 6144;
constexpr uint32_t SMEM_BYTES = OFF_BAR + 384 + 1408;
constexpr int B_EMPTY = NST, B_RECV = 2 * NST, B_RECV2 = B_RECV + 2, B_PACK = B_RECV2 + 2, B_GAT = B_PACK + 1, B_LATE = B_GAT + 16, B_ACK = B_LATE + 1, B_ACK2 = B_ACK + 2, B_COUNT = B_ACK2 + 2;

constexpr int PACK = 14 + 4 * PKP;

struct Maps { CUtensorMap x, qkv, wo, wg, wu, wg32, wu32, wd, out; };

}

constexpr int PLANE = 16 * 2 * 8 * 512;
struct Scratch {
    uint4 ex[6 * PLANE];
    uint4 kv1[8 * 16 * 16 * 32];
    uint4 kv2[8 * 512];
    uint32_t c1[8 * 8 * 16 * 32];
    uint32_t cw[8 * 32];
    uint4 wp[8 * 32 * (HALF / 16)];
};
__device__ __align__(1024) Scratch g_scratch;
#define g_ex (sc->ex)
#define g_kv1 (sc->kv1)
#define g_kv2 (sc->kv2)
#define g_c1 (sc->c1)
#define g_cw (sc->cw)
#define g_wp (sc->wp)
#define STAMP(i)
#define GSTAMP(i)
#define PDUMP()
#define ASTAMP(i)

namespace {

__device__ __forceinline__ int fresh_tid() { int t; asm volatile("mov.u32 %0, %%tid.x;" : "=r"(t)); return t; }
template <int N> __device__ __forceinline__ void kill(uint32_t* v) {
#pragma unroll
    for (int i = 0; i < N; i++) v[i] = 0;
}
template <int N> __device__ __forceinline__ void kill(float* v) {
#pragma unroll
    for (int i = 0; i < N; i++) v[i] = 0.f;
}
__device__ __forceinline__ uint32_t s2u(const void* p) { return (uint32_t)__cvta_generic_to_shared(p); }
__device__ __forceinline__ void mbar_init(uint32_t a, uint32_t c) { asm volatile("mbarrier.init.shared::cta.b64 [%0], %1;" ::"r"(a), "r"(c) : "memory"); }
__device__ __forceinline__ void mbar_expect_tx(uint32_t a, uint32_t b) { asm volatile("mbarrier.arrive.expect_tx.shared::cta.b64 _, [%0], %1;" ::"r"(a), "r"(b) : "memory"); }
__device__ __forceinline__ void mbar_arrive(uint32_t a) { asm volatile("mbarrier.arrive.shared::cta.b64 _, [%0];" ::"r"(a) : "memory"); }
#define GIVE_UP(id) "trap;\n"
#define SPIN_MAX "0x400000"
#define SPIN_TAIL(id) "add.u32 n, n, 1;\n setp.lt.u32 p, n, " SPIN_MAX ";\n @p bra.uni LP;\n" GIVE_UP(id) " DN:\n }"
__device__ __forceinline__ void mbar_wait(uint32_t a, uint32_t ph) {
    asm volatile("{ .reg .pred p; .reg .b32 n; mov.u32 n, 0;\n LP:\n"
                 "mbarrier.try_wait.parity.shared::cta.b64 p, [%0], %1;\n @p bra DN;\n"
                 "add.u32 n, n, 1;\n setp.lt.u32 p, n, " SPIN_MAX ";\n @p bra LP;\n"
                 GIVE_UP("")
                 " DN:\n }" ::"r"(a), "r"(ph) : "memory");
}
#define ELECT "{ .reg .pred e; elect.sync _|e, 0xffffffff; @e "
__device__ __forceinline__ void tma2d(uint32_t dst, const CUtensorMap* m, int c0, int c1, uint32_t bar) {
    asm volatile(ELECT "cp.async.bulk.tensor.2d.shared::cluster.global.mbarrier::complete_tx::bytes [%0], [%1, {%3, %4}], [%2]; }" ::"r"(dst), "l"(m), "r"(bar), "r"(c0), "r"(c1) : "memory");
}
__device__ __forceinline__ void tma3x(uint32_t dst, const CUtensorMap* m, int row, uint32_t bar) {
    asm volatile(ELECT "cp.async.bulk.tensor.3d.shared::cluster.global.mbarrier::complete_tx::bytes [%0], [%1, {0, %3, 0}], [%2]; }" ::"r"(dst), "l"(m), "r"(bar), "r"(row) : "memory");
}
template <int OFF>
__device__ __forceinline__ void ld_pkt(uint32_t* v, const uint4* p) {
    asm volatile("{ .reg .b128 t; ld.relaxed.gpu.global.b128 t, [%4+%5]; mov.b128 {%0,%1,%2,%3}, t; }" : "=r"(v[0]), "=r"(v[1]), "=r"(v[2]), "=r"(v[3]) : "l"(p), "n"(OFF * 16) : "memory");
}
template <int OFF>
__device__ __forceinline__ void st_pkt(uint4* p, uint32_t a, uint32_t b, uint32_t c, uint32_t d) {
    asm volatile("{ .reg .b128 t; mov.b128 t, {%1,%2,%3,%4}; st.relaxed.gpu.global.b128 [%0+%5], t; }" ::"l"(p), "r"(a), "r"(b), "r"(c), "r"(d), "n"(OFF * 16) : "memory");
}
__device__ __forceinline__ uint32_t pack2(float lo, float hi) {
    uint32_t r;
    asm("cvt.rn.bf16x2.f32 %0, %1, %2;" : "=r"(r) : "f"(hi), "f"(lo));
    return r;
}
__device__ __forceinline__ float bf_lo(uint32_t w) { return __uint_as_float(w << 16); }
__device__ __forceinline__ float bf_hi(uint32_t w) { return __uint_as_float(w & 0xffff0000u); }
__device__ __forceinline__ uint32_t settag(uint32_t w, uint32_t tag) { return (w & ~1u) | tag; }
__device__ __forceinline__ float ex2(float x) { float y; asm("ex2.approx.ftz.f32 %0, %1;" : "=f"(y) : "f"(x)); return y; }
__device__ __forceinline__ float rcp(float x) { float y; asm("rcp.approx.ftz.f32 %0, %1;" : "=f"(y) : "f"(x)); return y; }
__device__ __forceinline__ float tanh_hw(float x) { float y; asm("tanh.approx.f32 %0, %1;" : "=f"(y) : "f"(x)); return y; }
__device__ __forceinline__ void stsm4(uint32_t addr, uint32_t a, uint32_t b, uint32_t c, uint32_t d) {
    asm volatile("stmatrix.sync.aligned.m8n8.x4.shared.b16 [%0], {%1,%2,%3,%4};" ::"r"(addr), "r"(a), "r"(b), "r"(c), "r"(d) : "memory");
}
__device__ __forceinline__ void fence_async() { asm volatile("fence.proxy.async.shared::cta;" ::: "memory"); }
__device__ __forceinline__ void bar_sync(int id, int n) { asm volatile("bar.sync %0, %1;" ::"r"(id), "r"(n) : "memory"); }
__device__ __forceinline__ void bar_arrive(int id, int n) { asm volatile("bar.arrive %0, %1;" ::"r"(id), "r"(n) : "memory"); }
__device__ __forceinline__ void wg_fence() { asm volatile("wgmma.fence.sync.aligned;" ::: "memory"); }
__device__ __forceinline__ void wg_commit() { asm volatile("wgmma.commit_group.sync.aligned;" ::: "memory"); }
template <int N> __device__ __forceinline__ void wg_wait() { asm volatile("wgmma.wait_group.sync.aligned %0;" ::"n"(N) : "memory"); }

constexpr uint32_t SB0 = 1024;
__host__ __device__ constexpr uint32_t dlo(uint32_t off, uint32_t lbo) { return ((SB0 + off) >> 4) | ((lbo >> 4) << 16); }
__host__ __device__ constexpr uint32_t dhi(uint32_t sbo, uint32_t sw) { return (sbo >> 4) | (sw << 30); }
__device__ __forceinline__ uint64_t dbase(uint32_t lo, uint32_t hi) { uint64_t d; asm volatile("mov.b64 %0, {%1, %2};" : "=l"(d) : "r"(lo), "r"(hi)); return d; }
#define BASE128(off, lbo, adj) dbase(dlo(off, lbo) + (adj), dhi(1024, 1))
#define BASE64(off, lbo, adj) dbase(dlo(off, lbo) + (adj), dhi(512, 2))

#define ACC4(d, o) "+f"(d[o]), "+f"(d[o + 1]), "+f"(d[o + 2]), "+f"(d[o + 3])
#define ACC28(d) ACC4(d, 0), ACC4(d, 4), ACC4(d, 8), ACC4(d, 12), ACC4(d, 16), ACC4(d, 20), ACC4(d, 24)
#define ACC32(d, o) ACC4(d, o), ACC4(d, o + 4), ACC4(d, o + 8), ACC4(d, o + 12), ACC4(d, o + 16), ACC4(d, o + 20), ACC4(d, o + 24), ACC4(d, o + 28)

template <int TB, uint64_t D>
__device__ __forceinline__ void mma_rs56(float* d, uint32_t a0, uint32_t a1, uint32_t a2, uint32_t a3, int sd, uint64_t base) {
    asm volatile("{ .reg .pred p; .reg .b64 db; setp.ne.b32 p, %32, 0; add.u64 db, %33, %34;\n"
                 "wgmma.mma_async.sync.aligned.m64n56k16.f32.bf16.bf16 "
                 "{%0,%1,%2,%3,%4,%5,%6,%7,%8,%9,%10,%11,%12,%13,%14,%15,%16,%17,%18,%19,%20,%21,%22,%23,%24,%25,%26,%27}, "
                 "{%28,%29,%30,%31}, db, p, 1, 1, %35; }\n"
                 : ACC28(d)
                 : "r"(a0), "r"(a1), "r"(a2), "r"(a3), "r"(sd), "l"(base), "n"(D), "n"(TB));
}
template <int TB, uint64_t D>
__device__ __forceinline__ void mma_rs64(float* d, uint32_t a0, uint32_t a1, uint32_t a2, uint32_t a3, int sd, uint64_t base) {
    asm volatile("{ .reg .pred p; .reg .b64 db; setp.ne.b32 p, %36, 0; add.u64 db, %37, %38;\n"
                 "wgmma.mma_async.sync.aligned.m64n64k16.f32.bf16.bf16 "
                 "{%0,%1,%2,%3,%4,%5,%6,%7,%8,%9,%10,%11,%12,%13,%14,%15,%16,%17,%18,%19,%20,%21,%22,%23,%24,%25,%26,%27,%28,%29,%30,%31}, "
                 "{%32,%33,%34,%35}, db, p, 1, 1, %39; }\n"
                 : ACC32(d, 0)
                 : "r"(a0), "r"(a1), "r"(a2), "r"(a3), "r"(sd), "l"(base), "n"(D), "n"(TB));
}
template <int TB, uint64_t D>
__device__ __forceinline__ void mma_rs128(float* d, uint32_t a0, uint32_t a1, uint32_t a2, uint32_t a3, int sd, uint64_t base) {
    asm volatile("{ .reg .pred p; .reg .b64 db; setp.ne.b32 p, %68, 0; add.u64 db, %69, %70;\n"
                 "wgmma.mma_async.sync.aligned.m64n128k16.f32.bf16.bf16 "
                 "{%0,%1,%2,%3,%4,%5,%6,%7,%8,%9,%10,%11,%12,%13,%14,%15,%16,%17,%18,%19,%20,%21,%22,%23,%24,%25,%26,%27,%28,%29,%30,%31,%32,%33,%34,%35,%36,%37,%38,%39,%40,%41,%42,%43,%44,%45,%46,%47,%48,%49,%50,%51,%52,%53,%54,%55,%56,%57,%58,%59,%60,%61,%62,%63}, "
                 "{%64,%65,%66,%67}, db, p, 1, 1, %71; }\n"
                 : ACC32(d, 0), ACC32(d, 32)
                 : "r"(a0), "r"(a1), "r"(a2), "r"(a3), "r"(sd), "l"(base), "n"(D), "n"(TB));
}
template <uint64_t DA, uint64_t DB>
__device__ __forceinline__ void mma_ss56_tt(float* d, int sd, uint64_t ba, uint64_t bb) {
    asm volatile("{ .reg .pred p; .reg .b64 da, db; setp.ne.b32 p, %28, 0; add.u64 da, %29, %31; add.u64 db, %30, %32;\n"
                 "wgmma.mma_async.sync.aligned.m64n56k16.f32.bf16.bf16 "
                 "{%0,%1,%2,%3,%4,%5,%6,%7,%8,%9,%10,%11,%12,%13,%14,%15,%16,%17,%18,%19,%20,%21,%22,%23,%24,%25,%26,%27}, "
                 "da, db, p, 1, 1, 1, 1; }\n"
                 : ACC28(d)
                 : "r"(sd), "l"(ba), "l"(bb), "n"(DA), "n"(DB));
}
template <int... I> struct Seq {};
template <class F, int... I> __device__ __forceinline__ void static_for_impl(F&& f, Seq<I...>) { (f(std::integral_constant<int, I>{}), ...); }
#define FOR7(...) static_for_impl([&](auto T_) { constexpr int t = decltype(T_)::value; __VA_ARGS__; }, Seq<0, 1, 2, 3, 4, 5, 6>{})
#define FOR8(...) static_for_impl([&](auto T_) { constexpr int t = decltype(T_)::value; __VA_ARGS__; }, Seq<0, 1, 2, 3, 4, 5, 6, 7>{})
#define FOR14(...) static_for_impl([&](auto T_) { constexpr int t = decltype(T_)::value; __VA_ARGS__; }, Seq<0, 1, 2, 3, 4, 5, 6, 7, 8, 9, 10, 11, 12, 13>{})

__device__ __forceinline__ int kblk(int p, int b) { return b == 0 ? p : b - (b <= p); }
__host__ __device__ constexpr int krow(int t) { return t < 3 ? 16 * t : (t < 6 ? 56 + 16 * (t - 3) : 48); }
#define AQ(A, b, t) ((t) < 3 ? A[2 * (b)][4 * (t)] : (t) < 6 ? A[2 * (b) + 1][4 * ((t) - 3)] : A[2 * (b)][12]), \
                    ((t) < 3 ? A[2 * (b)][4 * (t) + 1] : (t) < 6 ? A[2 * (b) + 1][4 * ((t) - 3) + 1] : A[2 * (b)][13]), \
                    ((t) < 3 ? A[2 * (b)][4 * (t) + 2] : (t) < 6 ? A[2 * (b) + 1][4 * ((t) - 3) + 2] : A[2 * (b) + 1][12]), \
                    ((t) < 3 ? A[2 * (b)][4 * (t) + 3] : (t) < 6 ? A[2 * (b) + 1][4 * ((t) - 3) + 3] : A[2 * (b) + 1][13])
#define D128(off, t) ((uint64_t)(((off) + krow(t) * 128) >> 4) + ((uint64_t)((t) == 6 ? (7168 - 1024) >> 4 : 0) << 32))
#define D64(off, t) ((uint64_t)(((off) + krow(t) * 64) >> 4) + ((uint64_t)((t) == 6 ? (3584 - 512) >> 4 : 0) << 32))

#define PL(k) (((k) - 3) * PLANE)
__device__ __forceinline__ void st_word(uint32_t* p, uint32_t v) { asm volatile("st.relaxed.gpu.global.u32 [%0], %1;" ::"l"(p), "r"(v) : "memory"); }
__device__ __forceinline__ uint32_t ld_word(const uint32_t* p) { uint32_t v; asm volatile("ld.relaxed.gpu.global.u32 %0, [%1];" : "=r"(v) : "l"(p) : "memory"); return v; }
__device__ __forceinline__ void tag_slice(uint32_t* w, uint32_t tag) { w[0] = settag(w[0], tag); w[4] = settag(w[4], tag); w[8] = settag(w[8], tag); w[12] = settag(w[12], tag); }
template <int O>
__device__ __forceinline__ void send_slice(uint4* dst, int lane, const uint32_t* w) {
    st_pkt<O>(dst, w[0], w[1], w[2], w[3]);
    st_pkt<O + 32>(dst, w[4], w[5], w[6], w[7]);
    st_pkt<O + 64>(dst, w[8], w[9], w[10], w[11]);
    asm volatile("{ .reg .b64 t; mov.b64 t, {%1,%2}; st.relaxed.gpu.global.b64 [%0+%3], t; }" ::"l"((char*)dst - lane * 8), "r"(w[12]), "r"(w[13]), "n"(16 * (O + 96)) : "memory");
}
struct Wide { unsigned __int128 q[3]; uint64_t h; };
__device__ __forceinline__ Wide widen(const uint32_t* w) {
    Wide r;
#pragma unroll
    for (int k = 0; k < 3; k++) asm volatile("mov.b128 %0, {%1,%2,%3,%4};" : "=q"(r.q[k]) : "r"(w[4 * k]), "r"(w[4 * k + 1]), "r"(w[4 * k + 2]), "r"(w[4 * k + 3]));
    asm volatile("mov.b64 %0, {%1,%2};" : "=l"(r.h) : "r"(w[12]), "r"(w[13]));
    return r;
}
template <int O>
__device__ __forceinline__ void send_wide(uint4* dst, int lane, const Wide& v) {
    asm volatile("st.relaxed.gpu.global.b128 [%0+%4], %1;\n st.relaxed.gpu.global.b128 [%0+%5], %2;\n st.relaxed.gpu.global.b128 [%0+%6], %3;"
                 ::"l"(dst), "q"(v.q[0]), "q"(v.q[1]), "q"(v.q[2]), "n"(16 * O), "n"(16 * (O + 32)), "n"(16 * (O + 64)) : "memory");
    asm volatile("st.relaxed.gpu.global.b64 [%0+%2], %1;" ::"l"((char*)dst - lane * 8), "l"(v.h), "n"(16 * (O + 96)) : "memory");
}
#define RW4(v, o) "+r"(v[o]), "+r"(v[(o) + 1]), "+r"(v[(o) + 2]), "+r"(v[(o) + 3])
#define RW2(v, o) "+r"(v[o]), "+r"(v[(o) + 1])
#define WR4(v, o) "=&r"(v[o]), "=&r"(v[(o) + 1]), "=&r"(v[(o) + 2]), "=&r"(v[(o) + 3])
#define LDP(a, b, c, d, addr, off) "ld.relaxed.gpu.global.b128 q, [" addr "+" off "];\n mov.b128 {" a "," b "," c "," d "}, q;\n"
#define LDH(a, b, addr, off) "ld.relaxed.gpu.global.b64 h, [" addr "+" off "];\n mov.b64 {" a "," b "}, h;\n"
#define VOTE_OK "and.b32 t, t, 1;\n setp.ne.u32 p, t, 0;\n vote.sync.any.pred p, p, 0xffffffff;\n @!p bra.uni DN;\n"
#define CHK(x, tag) "lop3.b32 t, " x ", " tag ", t, 0xBE;\n"
__device__ __forceinline__ void check_cnt(uint32_t v, const uint32_t* p, uint32_t target) {
    asm volatile("{ .reg .pred p; .reg .b32 n, t; mov.u32 n, 0; mov.u32 t, %2;\n LP:\n"
                 "sub.s32 t, t, %1;\n setp.lt.s32 p, t, 0;\n vote.sync.any.pred p, p, 0xffffffff;\n @!p bra.uni DN;\n ld.relaxed.gpu.global.u32 t, [%0];\n" SPIN_TAIL("7")
                 ::"l"(p), "r"(target), "r"(v) : "memory");
}
__device__ __forceinline__ void poll_cnt(const uint32_t* p, uint32_t target) {
    asm volatile("{ .reg .pred p; .reg .b32 n, t; mov.u32 n, 0;\n LP:\n"
                 "ld.relaxed.gpu.global.u32 t, [%0];\n sub.s32 t, t, %1;\n setp.lt.s32 p, t, 0;\n vote.sync.any.pred p, p, 0xffffffff;\n @!p bra.uni DN;\n" SPIN_TAIL("1")
                 ::"l"(p), "r"(target) : "memory");
}
template <int STR>
__device__ __forceinline__ void poll4_kv(uint32_t* v, const uint4* p, uint32_t tag) {
    asm volatile("{ .reg .pred p; .reg .b32 n, t; .reg .b128 q; mov.u32 n, 0;\n LP:\n"
                 LDP("%0", "%1", "%2", "%3", "%16", "0") LDP("%4", "%5", "%6", "%7", "%16", "%18")
                 LDP("%8", "%9", "%10", "%11", "%16", "%19") LDP("%12", "%13", "%14", "%15", "%16", "%20")
                 "xor.b32 t, %0, %17;\n" CHK("%4", "%17") CHK("%8", "%17") CHK("%12", "%17") VOTE_OK SPIN_TAIL("2")
                 : WR4(v, 0), WR4(v, 4), WR4(v, 8), WR4(v, 12)
                 : "l"(p), "r"(tag), "n"(16 * STR), "n"(32 * STR), "n"(48 * STR)
                 : "memory");
}
template <int B>
__device__ __forceinline__ void blk_load(uint32_t (&A)[8][14], const uint4* src, int lane) {
    ld_pkt<0>(&A[2 * B][0], src); ld_pkt<32>(&A[2 * B][4], src); ld_pkt<64>(&A[2 * B][8], src);
    ld_pkt<512>(&A[2 * B + 1][0], src); ld_pkt<544>(&A[2 * B + 1][4], src); ld_pkt<576>(&A[2 * B + 1][8], src);
    asm volatile("{ .reg .b64 h;\n" LDH("%0", "%1", "%4", "1536") LDH("%2", "%3", "%4", "9728") "}"
                 : "=&r"(A[2 * B][12]), "=&r"(A[2 * B][13]), "=&r"(A[2 * B + 1][12]), "=&r"(A[2 * B + 1][13])
                 : "l"((const char*)src - lane * 8) : "memory");
}
#define BLK_TEST "xor.b32 t, %0, %30;\n" CHK("%4", "%30") CHK("%8", "%30") CHK("%12", "%30") CHK("%16", "%30") CHK("%20", "%30") CHK("%24", "%30") CHK("%26", "%30") VOTE_OK
template <int B>
__device__ __forceinline__ void blk_check(uint32_t (&A)[8][14], const uint4* src, int lane, uint32_t tag) {
    asm volatile("{ .reg .pred p; .reg .b32 n, t; .reg .b128 q; .reg .b64 h, a8;\n" BLK_TEST
                 "mov.u32 n, 0;\n mad.wide.s32 a8, %29, -8, %28;\n LP:\n"
                 LDP("%0", "%1", "%2", "%3", "%28", "0") LDP("%4", "%5", "%6", "%7", "%28", "512") LDP("%8", "%9", "%10", "%11", "%28", "1024")
                 LDP("%12", "%13", "%14", "%15", "%28", "8192") LDP("%16", "%17", "%18", "%19", "%28", "8704") LDP("%20", "%21", "%22", "%23", "%28", "9216")
                 LDH("%24", "%25", "a8", "1536") LDH("%26", "%27", "a8", "9728") BLK_TEST SPIN_TAIL("3")
                 "\n and.b32 %0, %0, -2; and.b32 %4, %4, -2; and.b32 %8, %8, -2; and.b32 %12, %12, -2; and.b32 %16, %16, -2; and.b32 %20, %20, -2; and.b32 %24, %24, -2; and.b32 %26, %26, -2;"
                 : RW4(A[2 * B], 0), RW4(A[2 * B], 4), RW4(A[2 * B], 8), RW4(A[2 * B + 1], 0), RW4(A[2 * B + 1], 4), RW4(A[2 * B + 1], 8),
                   RW2(A[2 * B], 12), RW2(A[2 * B + 1], 12)
                 : "l"(src), "r"(lane), "r"(tag)
                 : "memory");
}
__device__ __forceinline__ void st_async4(uint32_t a, uint32_t x, uint32_t y, uint32_t z, uint32_t w, uint32_t bar) {
    asm volatile("st.async.weak.shared::cluster.mbarrier::complete_tx::bytes.v4.b32 [%0], {%1,%2,%3,%4}, [%5];" ::"r"(a), "r"(x), "r"(y), "r"(z), "r"(w), "r"(bar) : "memory");
}
__device__ __forceinline__ uint32_t mapa(uint32_t a, uint32_t cta) { uint32_t r; asm("mapa.shared::cluster.u32 %0, %1, %2;" : "=r"(r) : "r"(a), "r"(cta)); return r; }
__device__ __forceinline__ void stat_load(uint32_t* v, const uint4* p) { ld_pkt<0>(v, p); ld_pkt<512>(v + 4, p); }
__device__ __forceinline__ void stat_check(uint32_t* v, const uint4* p, uint32_t tag) {
    asm volatile("{ .reg .pred p; .reg .b32 n, t; .reg .b128 q; mov.u32 n, 0;\n LP:\n"
                 "xor.b32 t, %3, %9;\n" CHK("%7", "%9") VOTE_OK
                 LDP("%0", "%1", "%2", "%3", "%8", "0") LDP("%4", "%5", "%6", "%7", "%8", "8192") SPIN_TAIL("4")
                 : RW4(v, 0), RW4(v, 4) : "l"(p), "r"(tag) : "memory");
}
__device__ __forceinline__ uint32_t x_bits(const uint32_t* X) {
    uint32_t r;
    asm volatile("{ .reg .b32 a, b; prmt.b32 a, %1, %2, 0x0040; prmt.b32 b, %3, %4, 0x0040; prmt.b32 %0, a, b, 0x5410; }" : "=r"(r) : "r"(X[0]), "r"(X[4]), "r"(X[8]), "r"(X[12]));
    return r;
}
template <int O>
__device__ __forceinline__ void slice_load(uint32_t* v, const uint4* p, int lane) {
    ld_pkt<O>(v, p); ld_pkt<O + 32>(v + 4, p); ld_pkt<O + 64>(v + 8, p);
    asm volatile("{ .reg .b64 h;\n" LDH("%0", "%1", "%2", "%3") "}" : "=r"(v[12]), "=r"(v[13]) : "l"((const char*)p - lane * 8), "n"(16 * (O + 96)) : "memory");
}
#define SLICE_TEST "xor.b32 t, %0, %16;\n" CHK("%4", "%16") CHK("%8", "%16") CHK("%12", "%16") VOTE_OK
template <int O>
__device__ __forceinline__ void slice_check(uint32_t* v, const uint4* p, int lane, uint32_t tag) {
    asm volatile("{ .reg .pred p; .reg .b32 n, t; .reg .b128 q; .reg .b64 h;\n" SLICE_TEST "mov.u32 n, 0;\n LP:\n"
                 LDP("%0", "%1", "%2", "%3", "%14", "%17") LDP("%4", "%5", "%6", "%7", "%14", "%18") LDP("%8", "%9", "%10", "%11", "%14", "%19")
                 LDH("%12", "%13", "%15", "%20") SLICE_TEST SPIN_TAIL("5")
                 : RW4(v, 0), RW4(v, 4), RW4(v, 8), RW2(v, 12)
                 : "l"(p), "l"((const char*)p - lane * 8), "r"(tag), "n"(16 * O), "n"(16 * (O + 32)), "n"(16 * (O + 64)), "n"(16 * (O + 96))
                 : "memory");
}
__device__ __forceinline__ void x_fix(uint32_t* X, uint32_t bits) {
    X[0] = __byte_perm(X[0], bits, 0x3214); X[4] = __byte_perm(X[4], bits, 0x3215); X[8] = __byte_perm(X[8], bits, 0x3216); X[12] = __byte_perm(X[12], bits, 0x3217);
}
__device__ __forceinline__ void sts4(uint32_t a, uint32_t x, uint32_t y, uint32_t z, uint32_t w) {
    asm volatile("st.shared.v4.u32 [%0], {%1,%2,%3,%4};" ::"r"(a), "r"(x), "r"(y), "r"(z), "r"(w) : "memory");
}
__device__ __forceinline__ void lds4(uint32_t* v, uint32_t a) {
    asm volatile("ld.shared.v4.u32 {%0,%1,%2,%3}, [%4];" : "=r"(v[0]), "=r"(v[1]), "=r"(v[2]), "=r"(v[3]) : "r"(a) : "memory");
}
struct LnCoef { uint32_t hi, lo, sh; };
__device__ __forceinline__ LnCoef ln_coef(float sum, float sq) {
    sum += __shfl_xor_sync(0xffffffffu, sum, 1); sq += __shfl_xor_sync(0xffffffffu, sq, 1);
    sum += __shfl_xor_sync(0xffffffffu, sum, 2); sq += __shfl_xor_sync(0xffffffffu, sq, 2);
    const float mean = sum * (1.f / 448.f);
    const float var = fmaxf(fmaf(-mean, mean, sq * (1.f / 448.f)), 0.f);
    const float sc = rsqrtf(var + 1e-5f);
    LnCoef r;
    r.hi = pack2(sc, sc);
    const float lo = sc - bf_lo(r.hi), sh = -mean * sc;
    r.lo = pack2(lo, lo);
    r.sh = pack2(sh, sh);
    return r;
}
template <int B>
__device__ __forceinline__ void normalize(uint32_t (&A)[8][14], const LnCoef& c0, const LnCoef& c1) {
#pragma unroll
    for (int s = 2 * B; s < 2 * B + 2; s++)
#pragma unroll
        for (int i = 0; i < 14; i++) {
            const LnCoef& k = (i & 1) ? c1 : c0;
            asm("{ .reg .b32 t; fma.rn.bf16x2 t, %0, %2, %3; fma.rn.bf16x2 %0, %0, %1, t; }" : "+r"(A[s][i]) : "r"(k.hi), "r"(k.lo), "r"(k.sh));
        }
}
__device__ __forceinline__ void slice_stats(const uint32_t* w, float* st) {
    float a = 0.f, b = 0.f, p = 0.f, q = 0.f;
#pragma unroll
    for (int i = 0; i < 7; i++) {
        const float e0 = bf_lo(w[2 * i]), e1 = bf_hi(w[2 * i]), e2 = bf_lo(w[2 * i + 1]), e3 = bf_hi(w[2 * i + 1]);
        a += e0 + e1; b += e2 + e3;
        p = fmaf(e0, e0, p); p = fmaf(e1, e1, p); q = fmaf(e2, e2, q); q = fmaf(e3, e3, q);
    }
    a += __shfl_xor_sync(0xffffffffu, a, 1); p += __shfl_xor_sync(0xffffffffu, p, 1); b += __shfl_xor_sync(0xffffffffu, b, 1); q += __shfl_xor_sync(0xffffffffu, q, 1);
    a += __shfl_xor_sync(0xffffffffu, a, 2); p += __shfl_xor_sync(0xffffffffu, p, 2); b += __shfl_xor_sync(0xffffffffu, b, 2); q += __shfl_xor_sync(0xffffffffu, q, 2);
    st[0] = a; st[1] = p; st[2] = b; st[3] = q;
}
__device__ __forceinline__ void dual_softmax(const float* p, uint32_t* out) {
    constexpr float L = 1.4426950408889634f;
#pragma unroll
    for (int r = 0; r < 2; r++) {
        float mx = fmaxf(p[2 * r], p[2 * r + 1]), mn = fminf(p[2 * r], p[2 * r + 1]);
#pragma unroll
        for (int i = 1; i < 7; i++) {
            mx = fmaxf(mx, fmaxf(p[4 * i + 2 * r], p[4 * i + 2 * r + 1]));
            mn = fminf(mn, fminf(p[4 * i + 2 * r], p[4 * i + 2 * r + 1]));
        }
        mx = fmaxf(mx, __shfl_xor_sync(0xffffffffu, mx, 1));
        mn = fminf(mn, __shfl_xor_sync(0xffffffffu, mn, 1));
        const float bx = -mx * L, bn = mn * L;
        float ep[14], en[14], sp = 0.f, sn = 0.f;
#pragma unroll
        for (int i = 0; i < 14; i++) {
            const float v = p[4 * (i >> 1) + 2 * r + (i & 1)];
            ep[i] = ex2(fmaf(v, L, bx));
            en[i] = ex2(fmaf(v, -L, bn));
            sp += ep[i]; sn += en[i];
        }
        sp += __shfl_xor_sync(0xffffffffu, sp, 1);
        sn += __shfl_xor_sync(0xffffffffu, sn, 1);
        const float ip = rcp(sp), in = rcp(sn);
#pragma unroll
        for (int i = 0; i < 7; i++) {
            out[4 * i + r] = pack2(ep[2 * i] * ip, ep[2 * i + 1] * ip);
            out[4 * i + 2 + r] = pack2(en[2 * i] * in, en[2 * i + 1] * in);
        }
    }
}
__device__ __forceinline__ float geglu(float g, float u) {
    const float t = tanh_hw(g * fmaf(g * g, 0.7978845608028654f * 0.044715f, 0.7978845608028654f));
    const float gu = g * u;
    return fmaf(t, gu, gu);
}
__device__ __forceinline__ void phi_gemm(const float* t, float* p) {
    uint32_t w[14];
#pragma unroll
    for (int i = 0; i < 14; i++) w[i] = pack2(t[2 * i], t[2 * i + 1]);
    const uint64_t db = BASE128(OFF_WPHI, 16, 0);
    wg_fence();
    mma_rs56<0, 0>(p, w[0], w[1], w[2], w[3], 0, db);
    mma_rs56<0, 2>(p, w[4], w[5], w[6], w[7], 1, db);
    mma_rs56<0, 4>(p, w[8], w[9], w[10], w[11], 1, db);
    mma_rs56<0, 6>(p, w[12], w[13], 0u, 0u, 1, db);
    wg_commit();
    wg_wait<0>();
}

}

#define BAR(i) (bars + 8 * (i))
#define R_WAIT() mbar_wait(BAR(slot), ph)
#define WSUM(i)
#define R_ADJ (slot * (STAGE >> 4))
#define R_NEXT() do { eb2 = eb1; eb1 = BAR(B_EMPTY + slot); if (++slot == NST) { slot = 0; ph ^= 1; } } while (0)
#define R_RELEASE(k) do { if (lane == 0) mbar_arrive((k) == 1 ? eb1 : eb2); } while (0)
#define PUSH_BEGIN() do { mbar_wait(BAR(B_ACK + wgi), ackph); ackph ^= 1; } while (0)
#define PUSH_ACK() do { __syncwarp(); if (lane == 0) asm volatile("mbarrier.arrive.shared::cluster.b64 _, [%0];" ::"r"(mapa(BAR(B_ACK + wgi), hr ^ 1)) : "memory"); } while (0)

__global__ void __cluster_dims__(2, 1, 1) __launch_bounds__(384, 1)
fused_kernel(Scratch* const sc, const __nv_bfloat16* __restrict__ x_in, const __nv_bfloat16* __restrict__ w_phi, const int trips,
             const __nv_bfloat16* __restrict__ wg, const __nv_bfloat16* __restrict__ wu, const __nv_bfloat16* __restrict__ wd,
             const __grid_constant__ Maps maps) {
    extern __shared__ __align__(1024) unsigned char smem_raw[];
    const uint32_t sb = s2u(smem_raw);
    const uint32_t bars = sb + OFF_BAR;
    const int wgi = __shfl_sync(0xffffffffu, threadIdx.x >> 7, 0);
    const int hr = blockIdx.x & 1, ck = blockIdx.x >> 1;
    const int gp = (ck - 4) & 7, q7 = ((ck - 36) * 37) >> 8;
    const int pr = __shfl_sync(0xffffffffu, ck < 4 ? ck : (ck < 36 ? (ck - 4) >> 3 : q7), 0);
    const int tile = __shfl_sync(0xffffffffu, ck < 4 ? 0 : (ck < 36 ? (gp ? 2 * gp : 1) : 2 * (ck - 36 - 7 * q7) + 3), 0);
    const int sl = 2 * pr + hr;
    STAMP(0);
    GSTAMP(60);
    if (threadIdx.x == 256) {
#pragma unroll
        for (int i = 0; i < NST; i++) mbar_init(BAR(i), 1);
        asm volatile("fence.mbarrier_init.release.cluster;" ::: "memory");
    }
    if (threadIdx.x == 288) {
        if ((sb & 0x3FFFF) != SB0) asm volatile("trap;");
#pragma unroll
        for (int i = NST; i < B_COUNT; i++) mbar_init(BAR(i), i >= B_ACK ? 4 : (i < B_RECV || i == B_LATE ? 8 : 1));
        asm volatile("fence.mbarrier_init.release.cluster;" ::: "memory");
    }
    __syncwarp();
    asm volatile("barrier.cluster.arrive.relaxed.aligned;" ::: "memory");

    if (wgi == 2) {
        asm volatile("setmaxnreg.dec.sync.aligned.u32 40;");
        const int t128 = fresh_tid() & 127, w = __shfl_sync(0xffffffffu, t128 >> 5, 0), lane = t128 & 31;
        uint32_t e0[2] = {0, 0}, e1[2] = {0, 0}, cw_target = 0, kseq;
        if (w == 0) {
#pragma unroll 1
            for (int n = 0; n < NST; n++) {
                const uint32_t dst = sb + n * STAGE, fb = BAR(n);
                asm volatile(ELECT "mbarrier.arrive.expect_tx.shared::cta.b64 _, [%0], %1; }" ::"r"(fb), "r"(n < 2 ? 2 * STAGE : STAGE) : "memory");
                if (n < 2) {
                    tma3x(sb + OFF_H + n * STAGE, &maps.x, tile * 128 + n * 64, fb);
                    tma3x(dst, &maps.x, tile * 128 + n * 64 + 32, fb);
                } else {
                    if (n == 3) mbar_wait(BAR(1), 0);
                    const int c0 = (n < 4 ? 448 : 896) + 56 * sl, r0 = 224 * (n & 1);
                    tma2d(dst, &maps.qkv, c0, r0, fb);
                    tma2d(dst + HALF, &maps.qkv, c0, r0 + 112, fb);
                }
            }
            asm volatile("barrier.cluster.wait.aligned;" ::: "memory");
            kseq = ld_word(g_c1 + (sl * 8 * 16 + tile) * 32);
            cw_target = (ld_word(g_cw + sl * 32) & ~15u) + 16;
#pragma unroll 1
            for (int k = 0; k < 2; k++) {
                const int n = t128 + 32 * k;
                int m = n - 2 - (n > PACK);
                const bool packed = m >= 30 ? (m < 38 || m >= 52) : m >= 22;
                if (m >= 30) m -= 30;
                if (n == PACK) m = tile < 8 ? tile : tile + 14;
                const int rot = n < 8 ? 0 : pr;
                const int ra = 112 * kblk(rot, m & 3), rb = 112 * kblk(rot, 2 * m & 3), rc = 112 * kblk(rot, (2 * m + 1) & 3);
                int kind = 0, m0, m1, c0, c1, r0, r1;
                if (m < 8) { m0 = m1 = m < 6 ? 1 : 2; c0 = c1 = (m < 2 ? 448 : (m < 4 ? 896 : 0)) + 56 * sl; r0 = rb; r1 = rc; }
                else if (m < 20) { m0 = 3; m1 = 4; c0 = c1 = 224 * sl + 32 * hr + 64 * ((m - 8) >> 2); r0 = r1 = ra; }
                else if (m < 22) { kind = 2; m0 = 5; m1 = 6; c0 = c1 = 224 * sl + (hr ? 0 : 192); r0 = rb; r1 = rc; }
                else { m0 = m1 = 7; c0 = c1 = 56 * (2 * ((pr + (m >> 1) - 10) & 3) + hr); r0 = 224 * (sl ^ (m & 1)); r1 = r0 + 112; }
                if (packed) { kind = 1; r0 = sl * 16 + (m < 8 ? m : m - 14); r1 = 0; }
                e0[0] = e0[1]; e1[0] = e1[1];
                e0[1] = kind | (m0 << 2) | (m1 << 6) | (c0 << 10) | (c1 << 21);
                e1[1] = r0 | (r1 << 16);
            }
        } else {
            const int j = t128 - 32;
            kseq = ld_word(g_c1 + (sl * 8 * 16 + tile) * 32);
            asm volatile("barrier.cluster.wait.aligned;" ::: "memory");
            uint2 wv[7];
            const int k = j < 56 ? j : 55, hh = k >= 28;
#pragma unroll
            for (int i = 0; i < 7; i++) wv[i] = __ldg(reinterpret_cast<const uint2*>(w_phi + (sl * 56 + k) * 28) + i);
#pragma unroll 1
            for (int i = j; i < 7168 / 16; i += 96) sts4(sb + OFF_WPHI + i * 16, 0, 0, 0, 0);
            bar_sync(5, 96);
            if (j < 56) {
                uint32_t a4[4];
#pragma unroll
                for (int q = 0; q < 4; q++) a4[q] = sb + OFF_WPHI + (4 * hh + q) * 128 + ((((k >> 3) ^ (4 * hh + q)) & 7) << 4) + (k & 7) * 2;
                FOR14(const uint32_t v = (t & 1) ? wv[t >> 1].y : wv[t >> 1].x;
                      asm volatile("{ .reg .b16 l, h; mov.b32 {l, h}, %2; st.shared.u16 [%0+%3], l; st.shared.u16 [%1+%3], h; }"
                                   ::"r"(a4[t >= 7 ? 2 : 0]), "r"(a4[t >= 7 ? 3 : 1]), "r"(v), "n"((t % 7) * 1024) : "memory"));
            }
            __syncwarp();
            fence_async();
            kseq = __shfl_sync(0xffffffffu, kseq, 0);
            bar_arrive(1, 224);
            bar_arrive(9, 224);
        }
        kseq = __shfl_sync(0xffffffffu, kseq, 0);
        int slot = 0, ph = 0, n = NST;
#pragma unroll 1
        for (int layer = 0; layer < 3; layer++) {
            if (w == 0) {
                const int nend = layer == 0 ? 11 : (layer == 1 ? 42 : 63);
#pragma unroll 1
                for (; n < nend; n++) {
                const uint32_t w0 = __shfl_sync(0xffffffffu, n < 32 ? e0[0] : e0[1], n & 31), w1 = __shfl_sync(0xffffffffu, n < 32 ? e1[0] : e1[1], n & 31);
                const uint32_t dst = sb + slot * STAGE, fb = BAR(n == PACK ? B_PACK : slot);
                const CUtensorMap* m0 = &maps.x + ((w0 >> 2) & 15);
                const CUtensorMap* m1 = &maps.x + ((w0 >> 6) & 15);
                const int c0 = (w0 >> 10) & 2047, c1 = w0 >> 21, r0 = w1 & 0xffff, r1 = w1 >> 16;
                if (n == 25) {
                    int it = 0;
                    uint32_t v;
                    do { asm volatile("ld.acquire.gpu.global.u32 %0, [%1];" : "=r"(v) : "l"(g_cw + sl * 32) : "memory"); } while ((int)(v - cw_target) < 0 && ++it < 0x400000);
                    asm volatile("fence.proxy.async.global;" ::: "memory");
                    __syncwarp();
                }
                mbar_wait(BAR(B_EMPTY + slot), ph);
                __syncwarp();
                asm volatile(ELECT "mbarrier.arrive.expect_tx.shared::cta.b64 _, [%0], %1; }" ::"r"(fb), "r"(STAGE) : "memory");
                if ((w0 & 3) == 0) {
                    tma2d(dst, m0, c0, r0, fb);
                    tma2d(dst + HALF, m1, c1, r1, fb);
                } else if (w0 & 1) {
                    asm volatile(ELECT "cp.async.bulk.shared::cluster.global.mbarrier::complete_tx::bytes [%0], [%1], %2, [%3]; }"
                                 ::"r"(dst), "l"(reinterpret_cast<const char*>(g_wp) + (size_t)r0 * STAGE), "r"(STAGE), "r"(fb) : "memory");
                } else {
                    tma2d(dst, m0, c0, r0, fb); tma2d(dst + 7168, m0, c0, r1, fb);
                    tma2d(dst + HALF, m1, c0, r0, fb); tma2d(dst + HALF + 7168, m1, c0, r1, fb);
                }
                if (n == PFN) {
                    const int b = blockIdx.x;
                    asm volatile(ELECT "cp.async.bulk.prefetch.L2.global [%0], %1; }" ::"l"(wg + b * 6272), "r"(12544) : "memory");
                    asm volatile(ELECT "cp.async.bulk.prefetch.L2.global [%0], %1; }" ::"l"(wu + b * 6272), "r"(12544) : "memory");
                    asm volatile(ELECT "cp.async.bulk.prefetch.L2.global [%0], %1; }" ::"l"(wd + b * 6272), "r"(12544) : "memory");
                }
                if (n == PACK) asm volatile(ELECT "mbarrier.arrive.shared::cta.b64 _, [%0]; }" ::"r"(BAR(slot)) : "memory");
                if (++slot == NST) { slot = 0; ph ^= 1; }
                }
            } else if (w == 1 && layer == 1) {
                constexpr int ps = PACK % NST;
                mbar_wait(BAR(B_PACK), 0);
                asm volatile("{ .reg .pred e; elect.sync _|e, 0xffffffff;\n"
                             "@e cp.async.bulk.global.shared::cta.bulk_group [%0], [%1], %2;\n"
                             "@e cp.async.bulk.commit_group;\n"
                             "@e cp.async.bulk.wait_group.read 0;\n"
                             "@e mbarrier.arrive.shared::cta.b64 _, [%3], 8;\n"
                             "@e cp.async.bulk.wait_group 0;\n"
                             "@e fence.proxy.async.global;\n"
                             "@e red.release.gpu.global.add.u32 [%4], 1; }"
                             ::"l"(reinterpret_cast<char*>(g_wp) + (size_t)(sl * 16 + tile) * STAGE), "r"(sb + ps * STAGE), "r"(STAGE), "r"(BAR(B_EMPTY + ps)), "l"(g_cw + sl * 32) : "memory");
                __syncwarp();
            }
            if (layer < 2) {
            const uint32_t tag = layer ^ 1;
            kseq++;
            bar_sync(7, 384);
            ASTAMP(0);
            if (tile < 15) {
                const int sq = lane >> 3, pk = 8 * w + (lane & (tile == 14 ? 3 : 7));
                uint32_t v[16];
                if (layer == 0) poll_cnt(g_c1 + ((sl * 8 + (w >> 1) * 4 + (tile >> 2)) * 16 + (lane & 15)) * 32, kseq);
                ASTAMP(1);
                poll4_kv<32>(v, g_kv1 + ((sl * 16 + tile) * 16 + 4 * sq) * 32 + pk, tag);
#pragma unroll
                for (int k = 0; k < 4; k++) {
                    float lo = (bf_lo(v[k]) + bf_lo(v[4 + k])) + (bf_lo(v[8 + k]) + bf_lo(v[12 + k]));
                    float hi = (bf_hi(v[k]) + bf_hi(v[4 + k])) + (bf_hi(v[8 + k]) + bf_hi(v[12 + k]));
                    lo += __shfl_xor_sync(0xffffffffu, lo, 8); hi += __shfl_xor_sync(0xffffffffu, hi, 8);
                    lo += __shfl_xor_sync(0xffffffffu, lo, 16); hi += __shfl_xor_sync(0xffffffffu, hi, 16);
                    v[k] = pack2(lo, hi);
                }
                if (sq == 0) st_pkt<0>(g_kv2 + sl * 512 + 32 * tile + pk, settag(v[0], tag), v[1], v[2], v[3]);
            }
            ASTAMP(2);
            {
                const int item = t128 < 112 ? t128 : 112 + (t128 & 3), d = item >> 1;
                const int cc = t128 < 112 ? 2 * (d >= 28) + (item & 1) : item - 112;
                const int r = t128 < 112 ? d : 56 + (cc >> 1) + 2 * ((t128 - 112) >> 2);
                uint32_t ra = sb + OFF_KVB + r * 128 + 4 * cc, rx = (r & 7) << 4;
                asm volatile("" : "+r"(ra), "+r"(rx));
                FOR14(asm volatile("st.shared.u32 [%0+%2], %1;" ::"r"((ra ^ 8) + (((t & 7) << 4) ^ rx)), "r"(0), "n"((t >> 3) * 8192) : "memory"));
                uint32_t v[16];
                asm volatile("" : "+r"(ra), "+r"(rx));
                poll4_kv<8>(v, g_kv2 + sl * 512 + (item >> 3) * 32 + (item & 7), tag);
                FOR14(asm volatile("st.shared.u32 [%0+%2], %1;" ::"r"(ra + (((t & 7) << 4) ^ rx)), "r"(v[t < 7 ? t : t + 1]), "n"((t >> 3) * 8192) : "memory"));
                fence_async();
            }
            bar_arrive(3, 384);
            ASTAMP(3);
            }
        }
    } else {
        asm volatile("setmaxnreg.inc.sync.aligned.u32 232;");
        int lane = fresh_tid() & 31, prf = pr;
#define pr prf
#define g (lane >> 2)
#define c (lane & 3)
#define t128 (w * 32 + lane)
        const int wu = __shfl_sync(0xffffffffu, fresh_tid() >> 5, 0), w = wu & 3;
        const uint32_t xoff = __shfl_sync(0xffffffffu, (3 * PLANE + ((tile * 2 + wgi) * 8) * 512 + w * 128) * 16, 0);
        char* xu = reinterpret_cast<char*>(g_ex) + xoff;
#define FRESH() asm volatile("" : "+l"(xu), "+r"(lane), "+r"(prf))
#define xp0 (reinterpret_cast<uint4*>(xu) + lane)
        const uint32_t hbuf = sb + OFF_H + wgi * STAGE;
        uint32_t slot = 0, ph = 0, eb1 = 0, eb2 = 0, ackph = 0, rcvph = 0, gatph = 0, swp = 0;
        uint32_t ppid = 6;
#define cx(s) (reinterpret_cast<uint32_t*>(reinterpret_cast<uint4*>(xu) + PL(1) + 112 + (s) * 512))
#define stp (reinterpret_cast<uint4*>(xu) + g + PL(0) + 112)
        uint32_t seq = ld_word(cx(sl));
        uint32_t kseq = ld_word(g_c1 + ((sl * 8 + wu) * 16 + tile) * 32);
        uint32_t stag = ld_word(reinterpret_cast<const uint32_t*>(stp + sl * 512) + 3) & 1;
        asm volatile("barrier.cluster.wait.aligned;" ::: "memory");
        STAMP(1);
        uint32_t X[14];
        const uint32_t x0row = (w < 2 ? hbuf : sb + wgi * STAGE) + ((w & 1) * 16 + (lane & 15)) * 128;
        mbar_wait(BAR(wgi), 0);
        STAMP(51);
#pragma unroll
        for (int j = 0; j < 4; j++) {
            const int G = 7 * sl + min(2 * j + (lane >> 4), 6);
            uint32_t q2, q3;
            asm volatile("ldmatrix.sync.aligned.m8n8.x4.shared.b16 {%0,%1,%2,%3}, [%4];" : "=r"(X[4 * j]), "=r"(X[4 * j + 1]), "=r"(q2), "=r"(q3)
                         : "r"(x0row + (G >> 3) * 4096 + (((G ^ lane) & 7) << 4)) : "memory");
            if (j < 3) { X[(4 * j + 2) % 14] = q2; X[(4 * j + 3) % 14] = q3; }
        }
#define PUSH_SLICE(W)                                                                          \
    {                                                                                          \
        if (t128 == 0) mbar_expect_tx(BAR(B_RECV + wgi), 7168);                                \
        PUSH_BEGIN();                                                                          \
        const uint32_t ra = mapa(hbuf + 24576 + t128 * 16, hr ^ 1), rb = mapa(sb + OFF_XR + wgi * 3072, hr ^ 1), rbar = mapa(BAR(B_RECV + wgi), hr ^ 1); \
        st_async4(ra, W[0], W[1], W[2], W[3], rbar);                                           \
        st_async4(ra + 2048, W[4], W[5], W[6], W[7], rbar);                                    \
        st_async4(rb + t128 * 16, W[8], W[9], W[10], W[11], rbar);                             \
        asm volatile("st.async.weak.shared::cluster.mbarrier::complete_tx::bytes.v2.b32 [%0], {%1,%2}, [%3];" ::"r"(rb + 2048 + t128 * 8), "r"(W[12]), "r"(W[13]), "r"(rbar) : "memory"); \
    }
#define PULL_SLICE(W)                                                                          \
    {                                                                                          \
        uint32_t t0, t1;                                                                       \
        mbar_wait(BAR(B_RECV + wgi), rcvph);                                                   \
        rcvph ^= 1;                                                                            \
        lds4(&A[1][0], hbuf + 24576 + t128 * 16);                                              \
        lds4(&A[1][4], hbuf + 26624 + t128 * 16);                                              \
        lds4(&A[1][8], sb + OFF_XR + wgi * 3072 + t128 * 16);                                  \
        asm volatile("ld.shared.v2.u32 {%0,%1}, [%2];" : "=r"(t0), "=r"(t1) : "r"(sb + OFF_XR + wgi * 3072 + 2048 + t128 * 8) : "memory"); \
        _Pragma("unroll") for (int i = 0; i < 12; i++) A[0][i] = (i & 3) ? W[i] : W[i] & ~1u;  \
        A[1][0] &= ~1u; A[1][4] &= ~1u; A[1][8] &= ~1u;                                        \
        A[0][12] = (hr ? t0 : W[12]) & ~1u; A[0][13] = hr ? t1 : W[13];                        \
        A[1][12] = (hr ? W[12] : t0) & ~1u; A[1][13] = hr ? W[13] : t1;                        \
        asm volatile("" : RW4(A[0], 0), RW4(A[0], 4), RW4(A[0], 8), RW2(A[0], 12), RW4(A[1], 0), RW4(A[1], 4), RW4(A[1], 8), RW2(A[1], 12)); \
        swp = hr * 448;                                                                        \
    }
#define SWB(b, t, db, sh) ((b) == 0 && (t) < 6 ? ((t) < 3 ? db##p : db##m) : db)
#define DECL_DB(b, MK, lbo, sh) const uint64_t db = MK(0, lbo, R_ADJ), dbp = (b) == 0 ? MK(0, lbo, R_ADJ + (swp >> (sh))) : db, dbm = (b) == 0 ? MK(0, lbo, R_ADJ - (swp >> (sh))) : db;
#define PPB 2
#define PP_WAIT() if (wgi == 1) { bar_sync(ppid, 256); ppid ^= 14; }
#define PP_GO() if (wgi == 0) { bar_arrive(ppid, 256); ppid ^= 14; }
#define GAT_DST(B, s2) ((B) == 1 ? hbuf + w * 3584 + (s2) * 1792 : ((s2) ? sb + OFF_KVB + wgi * 8192 : hbuf + 14336) + w * 1792)
#define GAT_ISSUE(B, base)                                                                     \
    {                                                                                          \
        const char* gs = xu + ((base) + kblk(pr, B) * 1024) * 16;                              \
        asm volatile("{ .reg .pred e; elect.sync _|e, 0xffffffff;\n"                           \
                     "@e mbarrier.arrive.expect_tx.shared::cta.b64 _, [%3], 3584;\n"           \
                     "@e cp.async.bulk.shared::cluster.global.mbarrier::complete_tx::bytes [%0], [%2], 1792, [%3];\n" \
                     "@e cp.async.bulk.shared::cluster.global.mbarrier::complete_tx::bytes [%1], [%2+8192], 1792, [%3]; }" \
                     ::"r"(GAT_DST(B, 0)), "r"(GAT_DST(B, 1)), "l"(gs), "r"(BAR(B_GAT + wu * 2 + ((B) >> 1))) : "memory"); \
        __syncwarp();                                                                          \
    }
#define GAT_FETCH(B)                                                                           \
    {                                                                                          \
        mbar_wait(BAR(B_GAT + wu * 2 + ((B) >> 1)), (gatph >> (B)) & 1);                          \
        gatph ^= 1 << (B);                                                                     \
        _Pragma("unroll") for (int s2 = 0; s2 < 2; s2++) {                                     \
            const uint32_t ga = GAT_DST(B, s2) + lane * 16;                                    \
            lds4(&A[2 * (B) + s2][0], ga); lds4(&A[2 * (B) + s2][4], ga + 512); lds4(&A[2 * (B) + s2][8], ga + 1024); \
            asm volatile("ld.shared.v2.u32 {%0,%1}, [%2];" : "=r"(A[2 * (B) + s2][12]), "=r"(A[2 * (B) + s2][13]) : "r"(ga - lane * 8 + 1536) : "memory"); \
        }                                                                                      \
    }
#define LATE_ARRIVE() do { if (lane == 0) mbar_arrive(BAR(B_LATE)); } while (0)
#define LATE_WAIT() do { mbar_wait(BAR(B_LATE), gatph & 1); gatph ^= 1; } while (0)
#define PT 3
#define PREP(b, t, remote)                                                                     \
    if constexpr ((b) < 3 && (t) == PT) {                                                      \
        wg_commit();                                                                           \
        STAMP(74 + 6 * (step & 1) + 2 * (b));                                                  \
        if (remote) {                                                                          \
            if constexpr ((b) == 0) { blk_load<2>(A, BLK(xsrc, 2), lane); if (XG3 == 3) blk_load<3>(A, BLK(xsrc, 3), lane); if (XG3 == 5) GAT_ISSUE(3, (step & 1) ? PL(2) : PL(0)) GAT_FETCH(1) }       \
            blk_check<((b) + 1) & 3>(A, BLK(xsrc, (b) + 1), lane, xtag);                       \
            if constexpr ((b) == 0 && XG3 == 0) blk_load<3>(A, BLK(xsrc, 3), lane); \
            if constexpr ((b) == 0 && XG3 == 2) GAT_ISSUE(3, (step & 1) ? PL(2) : PL(0))                        \
        }                                                                                      \
        STAMP(75 + 6 * (step & 1) + 2 * (b));                                                  \
        normalize<((b) + 1) & 3>(A, k0, k1);                                                   \
        asm volatile("" : RW4(A[(2 * (b) + 2) & 7], 0), RW4(A[(2 * (b) + 2) & 7], 4), RW4(A[(2 * (b) + 2) & 7], 8), RW2(A[(2 * (b) + 2) & 7], 12), \
                          RW4(A[(2 * (b) + 3) & 7], 0), RW4(A[(2 * (b) + 3) & 7], 4), RW4(A[(2 * (b) + 3) & 7], 8), RW2(A[(2 * (b) + 3) & 7], 12)); \
        wg_fence();                                                                            \
    }
#define X0_BLOCK(b)                                                                            \
    { const int rr = lane & 7, hi = lane >> 4;                                                 \
    const uint32_t rowa = (w < 2 ? hbuf : sb + wgi * STAGE) + ((w & 1) * 16 + (lane & 15)) * 128; \
    FOR7(constexpr int G = 14 * (b) + (t < 3 ? 2 * t : (t < 6 ? 2 * t + 1 : 6));               \
         uint32_t q0, q1, q2, q3;                                                              \
         const uint32_t ad = t < 6 ? rowa + (((((G & 7) + hi) ^ rr) & 7) << 4) + ((G & 7) == 7 ? hi * 4096 : 0) : rowa + ((G + 7 * hi) >> 3) * 4096 + ((((G + 7 * hi) ^ rr) & 7) << 4); \
         asm volatile("ldmatrix.sync.aligned.m8n8.x4.shared.b16 {%0,%1,%2,%3}, [%4+%5];" : "=r"(q0), "=r"(q1), "=r"(q2), "=r"(q3) \
                      : "r"(ad), "n"(t < 6 ? (G >> 3) * 4096 : 0) : "memory");                 \
         if (t < 3) { A[2 * (b)][4 * t] = q0; A[2 * (b)][4 * t + 1] = q1; A[2 * (b)][4 * t + 2] = q2; A[2 * (b)][4 * t + 3] = q3; } \
         else if (t < 6) { A[2 * (b) + 1][(4 * t - 12) & 15] = q0; A[2 * (b) + 1][((4 * t - 12) & 15) + 1] = q1; A[2 * (b) + 1][((4 * t - 12) & 15) + 2] = q2; A[2 * (b) + 1][((4 * t - 12) & 15) + 3] = q3; } \
         else { A[2 * (b)][12] = q0; A[2 * (b)][13] = q1; A[2 * (b) + 1][12] = q2; A[2 * (b) + 1][13] = q3; }); }
#define BLK(base, b) ((base) + kblk(pr, b) * 1024)

#pragma unroll 1
        for (int step = 0; step < 4; step++) {
            FRESH();
            const uint32_t tag = (step >> 1) ^ 1;
            const int so = (step >> 1) * 24 + (step & 1) * 12;
            (void)so;
            uint32_t A[8][14];
            uint4* const xsrc = xp0 + ((step & 1) ? PL(2) : PL(0));
            const uint32_t xtag = (step & 1) ? tag : ((seq >> 3) & 1) ^ 1;
            uint32_t xbits;
            {
                float st[4];
                slice_stats(X, st);
                stag ^= 1;
                xbits = x_bits(X);
                tag_slice(X, xtag);
                if (step) send_slice<0>(xsrc + sl * 512, lane, X);
                if (c == 0) st_pkt<0>(stp + sl * 512, __float_as_uint(st[0]), __float_as_uint(st[1]), __float_as_uint(st[2]), settag(__float_as_uint(st[3]), stag));
            }
            STAMP(2 + so);
            uint32_t sv[8];
            if (step == 0) {
                X0_BLOCK(0) X0_BLOCK(1) X0_BLOCK(2) X0_BLOCK(3)
                mbar_wait(BAR(wgi ^ 1), 0);
                R_NEXT();
                R_NEXT();
                R_RELEASE(2);
                stat_load(sv, stp + c * 1024);
                stat_check(sv, stp + c * 1024, stag);
                STAMP(52 + step);
            } else {
                kill<14>(A[2]); kill<14>(A[3]); kill<14>(A[4]); kill<14>(A[5]); kill<14>(A[6]); kill<14>(A[7]);
                PUSH_SLICE(X)
                stat_load(sv, stp + c * 1024);
                PULL_SLICE(X)
                stat_check(sv, stp + c * 1024, stag);
                STAMP(52 + step);
                GAT_ISSUE(1, (step & 1) ? PL(2) : PL(0))
                if (XG3 == 1) GAT_ISSUE(3, (step & 1) ? PL(2) : PL(0))
            }
            LnCoef k0, k1;
            {
                k0 = ln_coef(__uint_as_float(sv[0]) + __uint_as_float(sv[4]), __uint_as_float(sv[1]) + __uint_as_float(sv[5]));
                k1 = ln_coef(__uint_as_float(sv[2]) + __uint_as_float(sv[6]), __uint_as_float(sv[3] & ~1u) + __uint_as_float(sv[7] & ~1u));
            }
            if (XG3 == 4 && step) GAT_ISSUE(3, (step & 1) ? PL(2) : PL(0))
            STAMP(3 + so);
            GSTAMP(70 + step);

            if ((step & 1) == 0) {
                float tq[28];
#define K_BLOCK(b)                                                                            \
    if ((b) == 1) R_RELEASE(1);                                                               \
    if ((b) == 2 + XT) PUSH_ACK();                                                            \
    if ((b) == 2 && XT && step) GAT_FETCH(3)                                                  \
    if ((b) == 3) { wg_wait<2>(); R_RELEASE(1); }                                             \
    if (((b) & 1) == 0) R_WAIT();                                                             \
    { DECL_DB(b, BASE128, 16, 0)                                                              \
    wg_fence();                                                                               \
    FOR7(mma_rs56<1, D128(((b) & 1) * HALF, t)>(tq, AQ(A, b, t), (b) + t > 0, SWB(b, t, db, 0)); \
         PREP(b, t, step)); }                                                                 \
    wg_commit();                                                                              \
    if ((b) & 1) R_NEXT();
#define P_STAGE(acc, b0)                                                                      \
    R_WAIT();                                                                                 \
    { DECL_DB(b0, BASE128, 16, 0)                                                             \
    wg_fence();                                                                               \
    FOR7(mma_rs56<1, D128(0, t)>(acc, AQ(A, b0, t), (b0) + t > 0, SWB(b0, t, db, 0)));        \
    FOR7(mma_rs56<1, D128(HALF, t)>(acc, AQ(A, (b0) + 1, t), 1, db)); }                       \
    wg_commit();                                                                              \
    R_NEXT();
#define PROJECT(acc) P_STAGE(acc, 0) P_STAGE(acc, 2) wg_wait<1>(); R_RELEASE(2); wg_wait<0>(); R_RELEASE(1);
#define V_PASS()                                                                              \
    {                                                                                         \
        float av[28];                                                                         \
        PROJECT(av)                                                                           \
        const int m = lane >> 3, rr = lane & 7;                                               \
        const uint32_t rowa = hbuf + 16384 + (w * 16 + rr + 8 * (m & 1)) * 128;               \
        const uint32_t one = c == 0 ? 0x00003f80u : 0u;                                       \
        _Pragma("unroll") for (int j = 0; j < 4; j++) {                                       \
            const uint32_t a = rowa + (((2 * j + (m >> 1)) ^ rr) << 4);                       \
            if (j < 3) stsm4(a, pack2(av[8 * j], av[8 * j + 1]), pack2(av[8 * j + 2], av[8 * j + 3]), pack2(av[8 * j + 4], av[8 * j + 5]), pack2(av[8 * j + 6], av[8 * j + 7])); \
            else stsm4(a, pack2(av[24], av[25]), pack2(av[26], av[27]), one, one);            \
        }                                                                                     \
    }
                normalize<0>(A, k0, k1);
                K_BLOCK(0) K_BLOCK(1) K_BLOCK(2) K_BLOCK(3)
                wg_wait<0>();
                R_RELEASE(1);
                STAMP(4 + so);
                if (step == 0) { bar_sync(wgi ? 9 : 1, 224); }
                if (wgi == VW) V_PASS()
                uint32_t PH[28];
                int it = 1;
#pragma unroll 1
                do {
                    float pp[28];
                    phi_gemm(tq, pp);
                    dual_softmax(pp, PH);
                    if (((trips >> (it + 1)) & 1) == 0) continue;
                    {
                        const int m = lane >> 3, rr = lane & 7;
                        const uint32_t rowa = hbuf + (w * 16 + rr + 8 * (m & 1)) * 128;
#pragma unroll
                        for (int j = 0; j < 7; j++) {
                            const int cg = 2 * j + (m >> 1), hi = cg >= 7;
                            stsm4(rowa + hi * 8192 + (((cg - 7 * hi) ^ rr) << 4), PH[4 * j], PH[4 * j + 1], PH[4 * j + 2], PH[4 * j + 3]);
                        }
                    }
                    STAMP(5 + so);
                    if (wgi != VW) V_PASS()
                    fence_async();
                    bar_sync(2, 256);
                    float kv[28];
                    const uint64_t da = BASE128(OFF_H + 16384, 16, 0), dbk = BASE128(OFF_H, 16, wgi * 512);
                    wg_fence();
                    FOR8(constexpr uint64_t o = ((t >> 2) * STAGE + (t & 3) * 2048) >> 4; mma_ss56_tt<o, o>(kv, t > 0, da, dbk));
                    wg_commit();
                    wg_wait<0>();
#pragma unroll
                    for (int hf = 0; hf < 2; hf++) {
                        const int d = 16 * w + g + 8 * hf;
                        if ((d < 56 && (d >= 28) == (c >= 2)) || d == 56) {
                            const int item = d < 56 ? 2 * d + (c & 1) : 112 + c;
                            uint4* dst = g_kv1 + ((sl * 16 + (item >> 3)) * 16 + tile) * 32 + wgi * 16 + (item & 7);
#define KVW(i) pack2(kv[4 * (i) + 2 * hf], kv[4 * (i) + 2 * hf + 1])
                            st_pkt<0>(dst, settag(KVW(0), tag), KVW(1), KVW(2), KVW(3));
                            st_pkt<8>(dst, settag(KVW(4), tag), KVW(5), KVW(6), 0u);
                        }
                    }
                    __syncwarp();
                    kseq++;
                    if (lane == 0) st_word(g_c1 + ((sl * 8 + wu) * 16 + tile) * 32, kseq);
                    bar_arrive(7, 384);
                    STAMP(6 + so);
                    kill<28>(tq);
                    if (QPP) { PP_WAIT() }
                    P_STAGE(tq, 0) P_STAGE(tq, 2)
                    if (QPP) { PP_GO() }
                    wg_wait<1>(); R_RELEASE(2); wg_wait<0>(); R_RELEASE(1);
                    STAMP(7 + so);
                    kill<28>(PH);
                } while (((trips >> (++it)) & 1));
                STAMP(8 + so);
                FRESH();
                if (step) {
                    slice_load<PL(0)>(X, xp0 + sl * 512, lane);
                } else {
                    const uint32_t* xp = reinterpret_cast<const uint32_t*>(x_in + (size_t)(tile * 128 + wu * 16 + g) * 448 + 56 * sl + 2 * c);
#pragma unroll
                    for (int i = 0; i < 7; i++) { X[2 * i] = __ldg(xp + 4 * i); X[2 * i + 1] = __ldg(xp + 4 * i + 8 * 224); }
                }
                bar_sync(3, 384);
                STAMP(9 + so);
                const uint4* const osrc = xp0 + PL(1);
                {
                    float nm[32];
                    const uint64_t db = BASE128(OFF_KVB, 16, 0);
                    wg_fence();
                    FOR7(mma_rs64<0, ((t >> 2) * 8192 + (t & 3) * 32) / 16>(nm, PH[4 * t], PH[4 * t + 1], PH[4 * t + 2], PH[4 * t + 3], t > 0, db));
                    wg_commit();
                    wg_wait<0>();
                    LATE_ARRIVE();
                    const float i00 = rcp(nm[28] + 1e-6f), i01 = rcp(nm[29] + 1e-6f), i10 = rcp(nm[30] + 1e-6f), i11 = rcp(nm[31] + 1e-6f);
                    const float m0 = c >= 2 ? i01 : i00, m1 = c >= 2 ? i11 : i10;
                    uint32_t O[14];
#pragma unroll
                    for (int i = 0; i < 7; i++) {
                        const float f0 = i < 3 ? i00 : (i > 3 ? i01 : m0), f1 = i < 3 ? i10 : (i > 3 ? i11 : m1);
                        O[2 * i] = pack2(nm[4 * i] * f0, nm[4 * i + 1] * f0);
                        O[2 * i + 1] = pack2(nm[4 * i + 2] * f1, nm[4 * i + 3] * f1);
                    }
                    if (OST) { PP_WAIT() }
                    tag_slice(O, tag);
                    send_slice<PL(1)>(xp0 + sl * 512, lane, O);
                    seq++;
                    if (lane == 0) st_word(cx(sl), seq);
                    STAMP(10 + so);
                    PUSH_SLICE(O)
                    if (OST == 1) { PP_GO() }
                    const uint32_t cv = ld_word(cx(lane & 7));
                    PULL_SLICE(O)
                    LATE_WAIT();
                    check_cnt(cv, cx(lane & 7), seq);
                    if (OST == 2) { PP_GO() }
                    STAMP(56 + (step >> 1));
                    GAT_ISSUE(1, PL(1))
                    GAT_ISSUE(3, PL(1))
                    blk_load<2>(A, BLK(osrc, 2), lane);
                }
                float ao[28];
#define WO_BLOCK(b)                                                                           \
    if ((b) > 0) blk_check<b>(A, BLK(osrc, b), lane, tag);                                    \
    if (((b) & 1) == 0) R_WAIT();                                                             \
    { DECL_DB(b, BASE128, 16, 0)                                                              \
    wg_fence();                                                                               \
    FOR7(mma_rs56<1, D128(((b) & 1) * HALF, t)>(ao, AQ(A, b, t), (b) + t > 0, SWB(b, t, db, 0))); } \
    wg_commit();                                                                              \
    if ((b) & 1) R_NEXT();
                WO_BLOCK(0)
                STAMP(11 + so);
                GAT_FETCH(1)
                WO_BLOCK(1)
                WO_BLOCK(2)
                GAT_FETCH(3)
                WO_BLOCK(3)
                PUSH_ACK();
                wg_wait<0>();
                R_RELEASE(2);
                STAMP(12 + so);
                WSUM(86 + 7 * (step >> 1));
                x_fix(X, xbits);
#pragma unroll
                for (int i = 0; i < 14; i++) X[i] = pack2(bf_lo(X[i]) + ao[2 * i], bf_hi(X[i]) + ao[2 * i + 1]);
            } else {
                uint32_t H[56];
                float ag[64];
#define F1_EPI(dst, ng, ag)                                                                    \
    _Pragma("unroll") for (int i = 0; i < 2 * (ng); i++)                                       \
        (dst)[i] = pack2(geglu(ag[2 * i], ag[4 * (ng) + 2 * i]), geglu(ag[2 * i + 1], ag[4 * (ng) + 2 * i + 1]));
#define H_PUSH(h0, off) st_async4(rem_h + (off), H[h0], H[(h0) + 1], H[(h0) + 2], H[(h0) + 3], mapa(BAR(B_RECV2 + wgi), hr ^ 1));
#define F1_BLOCK(b, first)                                                                     \
    if ((first) && (b) == 1) R_RELEASE(2);                                                     \
    if ((first) && (b) == 2 + XT) PUSH_ACK();                                                  \
    if ((first) && (b) == 2 && XT) GAT_FETCH(3)                                                \
    R_WAIT();                                                                                  \
    if ((b) == ((first) ? PPF : PPB)) { PP_WAIT() }                                            \
    { DECL_DB(b, BASE128, HALF, 0)                                                             \
    wg_fence();                                                                                \
    FOR7(mma_rs128<1, D128(0, t)>(ag, AQ(A, b, t), (b) + t > 0, SWB(b, t, db, 0));             \
         if constexpr (first) { PREP(b, t, true) }); }                                         \
    wg_commit();                                                                               \
    if ((b) == 3) { PP_GO() }                                                                  \
    if ((b) > 0) { wg_wait<1>(); R_RELEASE(1); }       \
    R_NEXT();
                normalize<0>(A, k0, k1);
                F1_BLOCK(0, true) F1_BLOCK(1, true) F1_BLOCK(2, true) F1_BLOCK(3, true)
                if (t128 == 0) { mbar_expect_tx(BAR(B_RECV + wgi), 16384); mbar_expect_tx(BAR(B_RECV2 + wgi), 12288); }
                PUSH_BEGIN();
                wg_wait<0>();
                R_RELEASE(1);
                int p = 0;
#pragma unroll 1
                do {
                    F1_EPI(H + 32, 8, ag)
                    STAMP(4 + p + so);
                    WSUM(81 + p + 7 * (step >> 1));
                    if (((trips >> (p + 1)) & 1) == 0) continue;
                    if (step == 1 && p == PKP) R_NEXT();
                    kill<64>(ag);
                    F1_BLOCK(0, false)
                    {
                        const uint32_t pk = (p ? hbuf + 16384 : sb + OFF_KVB + wgi * 8192) + w * 2048;
#pragma unroll
                        for (int k = 0; k < 4; k++) sts4(pk + k * 512 + lane * 16, H[32 + 4 * k], H[33 + 4 * k], H[34 + 4 * k], H[35 + 4 * k]);
                        fence_async();
                        __syncwarp();
                        asm volatile(ELECT "cp.async.bulk.shared::cluster.shared::cta.mbarrier::complete_tx::bytes [%0], [%1], 2048, [%2]; }"
                                     ::"r"(mapa(hbuf + p * 8192 + w * 2048, hr ^ 1)), "r"(pk), "r"(mapa(BAR(B_RECV + wgi), hr ^ 1)) : "memory");
                    }
                    F1_BLOCK(1, false) F1_BLOCK(2, false) F1_BLOCK(3, false)
                    wg_wait<0>();
                    R_RELEASE(1);
                    kill<16>(H + 32);
                } while (((trips >> (++p)) & 1));
#pragma unroll
                for (int k = 0; k < 4; k++) lds4(H + 16 + 4 * k, hbuf + 16384 + w * 2048 + k * 512 + lane * 16);
                __syncwarp();
                if (lane == 0) asm volatile("mbarrier.arrive.shared::cluster.b64 _, [%0];" ::"r"(mapa(BAR(B_ACK2 + wgi), hr ^ 1)) : "memory");
                const uint32_t rem_h = mapa(hbuf + w * 2048 + lane * 16, hr ^ 1);
#define F1_LAST(b0)                                                                            \
    R_WAIT();                                                                                  \
    if (b0) { PP_WAIT() }                                                                      \
    { DECL_DB(b0, BASE64, HALF, 1)                                                             \
    wg_fence();                                                                                \
    FOR7(mma_rs64<1, D64(0, t)>(al, AQ(A, b0, t), (b0) + t > 0, SWB(b0, t, db, 1)));           \
    FOR7(mma_rs64<1, D64(7168, t)>(al, AQ(A, (b0) + 1, t), 1, db)); }                          \
    wg_commit();                                                                               \
    if (b0) { PP_GO() }                                                                        \
    R_NEXT();
                float al[32];
                F1_LAST(0)
                mbar_wait(BAR(B_RECV + wgi), rcvph);
                rcvph ^= 1;
                mbar_wait(BAR(B_ACK2 + wgi), step >> 1);
                H_PUSH(32, 16384) H_PUSH(36, 16896)
                F1_LAST(2)
                H_PUSH(40, 17408) H_PUSH(44, 17920)
                wg_wait<1>();
                R_RELEASE(2);
                wg_wait<0>();
                R_RELEASE(1);
                uint32_t HP[56];
#pragma unroll
                for (int k = 0; k < 4; k++) lds4(H + 4 * k, sb + OFF_KVB + wgi * 8192 + w * 2048 + k * 512 + lane * 16);
#pragma unroll
                for (int t = 0; t < 8; t++) lds4(HP + 4 * t, hbuf + (t >> 2) * 8192 + w * 2048 + (t & 3) * 512 + lane * 16);
                F1_EPI(H + 48, 4, al)
                H_PUSH(48, 24576 - w * 1024) H_PUSH(52, 25088 - w * 1024)
                STAMP(7 + so);
                WSUM(84 + 7 * (step >> 1));
                FRESH();
                float acc[28];
                const uint32_t roA = hr ? 256u : 0u, roB = hr ? (uint32_t)-1536 : 0u;
                const uint32_t rpA = hr ? 0u : 256u, rpB = hr ? 0u : (uint32_t)-1536;
                float res[28];
                uint32_t v0[14], v1[14], P[14];
                Wide PW;
                const uint4* ps = xp0 + sl * 512;
#define F2_OWN_A()                                                                             \
    R_WAIT();                                                                                  \
    d0 = BASE128(0, 16, R_ADJ + roA); d1 = BASE128(0, 16, R_ADJ + roB);                        \
    wg_fence();                                                                                \
    FOR14(if constexpr (t < OT) mma_rs56<1, t * 128>(acc, H[4 * t], H[4 * t + 1], H[4 * t + 2], H[4 * t + 3], t > 0, d0)); \
    wg_commit();
#define F2_OWN_B()                                                                             \
    wg_fence();                                                                                \
    FOR14(if constexpr (t >= OT) mma_rs56<1, t * 128>(acc, H[4 * t], H[4 * t + 1], H[4 * t + 2], H[4 * t + 3], 1, t < 12 ? d0 : d1)); \
    wg_commit();                                                                               \
    R_NEXT();
#define F2_PEER()                                                                              \
    R_WAIT();                                                                                  \
    if (F2PP) { PP_WAIT() }                                                                    \
    d0 = BASE128(0, 16, R_ADJ + rpA); d1 = BASE128(0, 16, R_ADJ + rpB);                        \
    wg_fence();                                                                                \
    FOR14(mma_rs56<1, t * 128>(acc, HP[4 * t], HP[4 * t + 1], HP[4 * t + 2], HP[4 * t + 3], 1, t < 12 ? d0 : d1)); \
    wg_commit();                                                                               \
    if (F2PP) { PP_GO() }                                                                      \
    R_NEXT();
#define F2_TURN(u)                                                                             \
    wg_wait<1>();                                                                              \
    if ((u) < 2 || TDEF < 2) R_RELEASE(2);                                                     \
    wg_wait<0>();                                                                              \
    if ((u) < 2 || TDEF < 1) R_RELEASE(1);                                                     \
    _Pragma("unroll") for (int i = 0; i < 14; i++) P[i] = pack2(acc[2 * i], acc[2 * i + 1]);   \
    tag_slice(P, tag);                                                                         \
    PW = widen(P);                                                                             \
    kill<28>(acc);                                                                             \
    F2_OWN_A()                                                                                 \
    if ((u) == 2) { slice_load<PL(3)>(v0, ps, lane); slice_load<PL(4)>(v1, ps, lane); } \
    send_wide<PL(3 + (u))>(xp0 + (2 * ((pr + (u) + 1) & 3) + hr) * 512, lane, PW);             \
    seq++;                                                                                     \
    if (lane == 0) st_word(cx(sl), seq);                                                       \
    __syncwarp();                                                                              \
    STAMP(8 + (u) + so);                                                                       \
    F2_OWN_B()
                uint64_t d0, d1;
                F2_OWN_A()
                F2_OWN_B()
                R_WAIT();
                d0 = BASE128(0, 16, R_ADJ + rpA); d1 = BASE128(0, 16, R_ADJ + rpB);
                wg_fence();
                FOR8(mma_rs56<1, t * 128>(acc, HP[4 * t], HP[4 * t + 1], HP[4 * t + 2], HP[4 * t + 3], 1, d0));
                wg_commit();
                mbar_wait(BAR(B_RECV2 + wgi), step >> 1);
#pragma unroll
                for (int k = 0; k < 4; k++) lds4(HP + 32 + 4 * k, hbuf + 16384 + w * 2048 + k * 512 + lane * 16);
                lds4(HP + 48, hbuf + 24576 + w * 1024 + lane * 16);
                lds4(HP + 52, hbuf + 25088 + w * 1024 + lane * 16);
                if (step == 1) PUSH_ACK();
                wg_fence();
                FOR14(if constexpr (t >= 8) mma_rs56<1, t * 128>(acc, HP[4 * t], HP[4 * t + 1], HP[4 * t + 2], HP[4 * t + 3], 1, t < 12 ? d0 : d1));
                wg_commit();
                R_NEXT();
                F2_TURN(0)
                F2_PEER()
                F2_TURN(1)
                F2_PEER()
                F2_TURN(2)
                if (step == 1) STAMP(64);
                slice_check<PL(3)>(v0, ps, lane, tag);
                slice_check<PL(4)>(v1, ps, lane, tag);
#pragma unroll
                for (int i = 0; i < 14; i++) { res[2 * i] = bf_lo(v0[i]) + bf_lo(v1[i]); res[2 * i + 1] = bf_hi(v0[i]) + bf_hi(v1[i]); }
                slice_load<PL(2)>(X, ps, lane);
                if (step == 1) STAMP(65);
                F2_PEER()
                if (step == 1) STAMP(66);
                poll_cnt(cx(2 * ((pr + 1) & 3) + hr), seq);
                if (step == 1) STAMP(67);
                slice_load<PL(5)>(v0, ps, lane);
                x_fix(X, xbits);
                slice_check<PL(5)>(v0, ps, lane, tag);
                if (lane < TDEF) mbar_arrive(BAR(B_EMPTY + (slot + NST - 3 - lane) % NST));
#pragma unroll
                for (int i = 0; i < 14; i++) { res[2 * i] += bf_lo(v0[i]); res[2 * i + 1] += bf_hi(v0[i]); }
                STAMP(11 + so);
                wg_wait<0>();
                R_RELEASE(2);
                STAMP(12 + so);
                WSUM(85 + 7 * (step >> 1));
#pragma unroll
                for (int i = 0; i < 14; i++) X[i] = pack2(fmaf(res[2 * i] + acc[2 * i], 0.5f, bf_lo(X[i])), fmaf(res[2 * i + 1] + acc[2 * i + 1], 0.5f, bf_hi(X[i])));
            }
        }
        {
            const int m = lane >> 3, rr = lane & 7;
            const uint32_t ob = hbuf + w * 2048, rowa = ob + (rr + 8 * (m & 1)) * 112 + (m >> 1) * 16;
#pragma unroll
            for (int j = 0; j < 3; j++) stsm4(rowa + 32 * j, X[4 * j], X[4 * j + 1], X[4 * j + 2], X[4 * j + 3]);
            asm volatile("stmatrix.sync.aligned.m8n8.x2.shared.b16 [%0], {%1,%2};" ::"r"(ob + (rr + 8 * (m & 1)) * 112 + 96), "r"(X[12]), "r"(X[13]) : "memory");
            fence_async();
            __syncwarp();
            if (lane == 0) {
                asm volatile("cp.async.bulk.tensor.2d.global.shared::cta.bulk_group [%0, {%2, %3}], [%1];" ::"l"(&maps.out), "r"(ob), "r"(56 * sl), "r"(tile * 128 + wu * 16) : "memory");
                asm volatile("cp.async.bulk.commit_group;" ::: "memory");
                asm volatile("cp.async.bulk.wait_group.read 0;" ::: "memory");
            }
        }
        STAMP(50);
        GSTAMP(61);
        PDUMP();
    }
}

#undef g
#undef pr
#undef c
#undef t128

typedef CUresult (*EncodeFn)(CUtensorMap*, CUtensorMapDataType, cuuint32_t, void*, const cuuint64_t*, const cuuint64_t*, const cuuint32_t*,
                             const cuuint32_t*, CUtensorMapInterleave, CUtensorMapSwizzle, CUtensorMapL2promotion, CUtensorMapFloatOOBfill);

static void make_map(EncodeFn enc, CUtensorMap* m, const void* p, uint64_t cols, uint64_t rows, uint32_t bc, uint32_t br, CUtensorMapSwizzle sw) {
    cuuint64_t gd[2] = {cols, rows};
    cuuint64_t gs[1] = {cols * 2};
    cuuint32_t bd[2] = {bc, br};
    cuuint32_t es[2] = {1, 1};
    enc(m, CU_TENSOR_MAP_DATA_TYPE_BFLOAT16, 2, const_cast<void*>(p), gd, gs, bd, es, CU_TENSOR_MAP_INTERLEAVE_NONE, sw,
        CU_TENSOR_MAP_L2_PROMOTION_L2_128B, CU_TENSOR_MAP_FLOAT_OOB_FILL_NONE);
}

extern "C" void kernel_launch(void* const* d_in, const int* in_sizes, int n_in, void* d_out, int out_size) {
    (void)in_sizes; (void)n_in; (void)out_size;
    static EncodeFn enc = nullptr;
    static Scratch* scratch = nullptr;
    if (!enc) {
        void* fn = nullptr;
        cudaDriverEntryPointQueryResult qr;
        cudaGetDriverEntryPoint("cuTensorMapEncodeTiled", &fn, cudaEnableDefault, &qr);
        enc = (EncodeFn)fn;
        cudaGetSymbolAddress((void**)&scratch, g_scratch);
        cudaFuncSetAttribute(fused_kernel, cudaFuncAttributeMaxDynamicSharedMemorySize, SMEM_BYTES);
    }
    Maps maps;
    {
        cuuint64_t gd[3] = {64, 2048, 7};
        cuuint64_t gs[2] = {896, 128};
        cuuint32_t bd[3] = {64, 32, 7};
        cuuint32_t es[3] = {1, 1, 1};
        enc(&maps.x, CU_TENSOR_MAP_DATA_TYPE_BFLOAT16, 3, d_in[0], gd, gs, bd, es, CU_TENSOR_MAP_INTERLEAVE_NONE, CU_TENSOR_MAP_SWIZZLE_128B,
            CU_TENSOR_MAP_L2_PROMOTION_L2_128B, CU_TENSOR_MAP_FLOAT_OOB_FILL_NONE);
    }
    make_map(enc, &maps.out, d_out, 448, 2048, 56, 16, CU_TENSOR_MAP_SWIZZLE_NONE);
    make_map(enc, &maps.qkv, d_in[1], 1344, 448, 64, 112, CU_TENSOR_MAP_SWIZZLE_128B);
    make_map(enc, &maps.wo, d_in[3], 448, 448, 64, 112, CU_TENSOR_MAP_SWIZZLE_128B);
    make_map(enc, &maps.wg, d_in[5], 1792, 448, 64, 112, CU_TENSOR_MAP_SWIZZLE_128B);
    make_map(enc, &maps.wu, d_in[6], 1792, 448, 64, 112, CU_TENSOR_MAP_SWIZZLE_128B);
    make_map(enc, &maps.wg32, d_in[5], 1792, 448, 32, 112, CU_TENSOR_MAP_SWIZZLE_64B);
    make_map(enc, &maps.wu32, d_in[6], 1792, 448, 32, 112, CU_TENSOR_MAP_SWIZZLE_64B);
    make_map(enc, &maps.wd, d_in[7], 448, 1792, 64, 112, CU_TENSOR_MAP_SWIZZLE_128B);
    fused_kernel<<<128, 384, SMEM_BYTES>>>(scratch, (const __nv_bfloat16*)d_in[0], (const __nv_bfloat16*)d_in[2], 7, (const __nv_bfloat16*)d_in[5],
                                           (const __nv_bfloat16*)d_in[6], (const __nv_bfloat16*)d_in[7], maps);
}
```

```cpp
#include <cuda_runtime.h>
#include <cuda.h>
#include <cuda_bf16.h>
#include <stdint.h>
#include <type_traits>

#define PPF 2
#define PKP 0
#define TDEF 1
#define TMPF 0
#define NORM1 0
#define LPARK 1
#define PFN 9
#define VW 1
#define QPP 1
#define XG3 2
#define XT (XG3 == 1 || XG3 == 2)
#define PF 3
#define ACAN 0
#define SPLIT0 1
#define OT 2
#define F2PP 0
#define PPK 2
#define QE 1
#define OST 1
#define PP

namespace {

constexpr uint32_t STAGE = 28672, HALF = 14336;
constexpr int NST = 5;
constexpr uint32_t OFF_H = NST * STAGE;
constexpr uint32_t OFF_KVB = OFF_H + 2 * STAGE;
constexpr uint32_t OFF_WPHI = OFF_KVB + 16384;
constexpr uint32_t OFF_XR = OFF_WPHI + 7168;
constexpr uint32_t OFF_BAR = OFF_XR + 6144;
constexpr uint32_t SMEM_BYTES = OFF_BAR + 384 + 1408;
constexpr int B_EMPTY = NST, B_RECV = 2 * NST, B_RECV2 = B_RECV + 2, B_PACK = B_RECV2 + 2, B_GAT = B_PACK + 1, B_LATE = B_GAT + 16, B_ACK = B_LATE + 1, B_ACK2 = B_ACK + 2, B_COUNT = B_ACK2 + 2;

constexpr int PACK = 14 + 4 * PKP;

struct Maps { CUtensorMap x, qkv, wo, wg, wu, wg32, wu32, wd, out; };

}

constexpr int PLANE = 16 * 2 * 8 * 512;
struct Scratch {
    uint4 ex[6 * PLANE];
    uint4 kv1[8 * 16 * 16 * 32];
    uint4 kv2[8 * 512];
    uint32_t c1[8 * 8 * 16 * 32];
    uint32_t cw[8 * 32];
    uint4 wp[8 * 32 * (HALF / 16)];
};
__device__ __align__(1024) Scratch g_scratch;
#define g_ex (sc->ex)
#define g_kv1 (sc->kv1)
#define g_kv2 (sc->kv2)
#define g_c1 (sc->c1)
#define g_cw (sc->cw)
#define g_wp (sc->wp)
#define STAMP(i)
#define GSTAMP(i)
#define PDUMP()
#define ASTAMP(i)

namespace {

__device__ __forceinline__ int fresh_tid() { int t; asm volatile("mov.u32 %0, %%tid.x;" : "=r"(t)); return t; }
template <int N> __device__ __forceinline__ void kill(uint32_t* v) {
#pragma unroll
    for (int i = 0; i < N; i++) v[i] = 0;
}
template <int N> __device__ __forceinline__ void kill(float* v) {
#pragma unroll
    for (int i = 0; i < N; i++) v[i] = 0.f;
}
__device__ __forceinline__ uint32_t s2u(const void* p) { return (uint32_t)__cvta_generic_to_shared(p); }
__device__ __forceinline__ void mbar_init(uint32_t a, uint32_t c) { asm volatile("mbarrier.init.shared::cta.b64 [%0], %1;" ::"r"(a), "r"(c) : "memory"); }
__device__ __forceinline__ void mbar_expect_tx(uint32_t a, uint32_t b) { asm volatile("mbarrier.arrive.expect_tx.shared::cta.b64 _, [%0], %1;" ::"r"(a), "r"(b) : "memory"); }
__device__ __forceinline__ void mbar_arrive(uint32_t a) { asm volatile("mbarrier.arrive.shared::cta.b64 _, [%0];" ::"r"(a) : "memory"); }
#define GIVE_UP(id) "trap;\n"
#define SPIN_MAX "0x400000"
#define SPIN_TAIL(id) "add.u32 n, n, 1;\n setp.lt.u32 p, n, " SPIN_MAX ";\n @p bra.uni LP;\n" GIVE_UP(id) " DN:\n }"
__device__ __forceinline__ void mbar_wait(uint32_t a, uint32_t ph) {
    asm volatile("{ .reg .pred p; .reg .b32 n; mov.u32 n, 0;\n LP:\n"
                 "mbarrier.try_wait.parity.shared::cta.b64 p, [%0], %1;\n @p bra DN;\n"
                 "add.u32 n, n, 1;\n setp.lt.u32 p, n, " SPIN_MAX ";\n @p bra LP;\n"
                 GIVE_UP("")
                 " DN:\n }" ::"r"(a), "r"(ph) : "memory");
}
#define ELECT "{ .reg .pred e; elect.sync _|e, 0xffffffff; @e "
__device__ __forceinline__ void tma2d(uint32_t dst, const CUtensorMap* m, int c0, int c1, uint32_t bar) {
    asm volatile(ELECT "cp.async.bulk.tensor.2d.shared::cluster.global.mbarrier::complete_tx::bytes [%0], [%1, {%3, %4}], [%2]; }" ::"r"(dst), "l"(m), "r"(bar), "r"(c0), "r"(c1) : "memory");
}
__device__ __forceinline__ void tma3x(uint32_t dst, const CUtensorMap* m, int row, uint32_t bar) {
    asm volatile(ELECT "cp.async.bulk.tensor.3d.shared::cluster.global.mbarrier::complete_tx::bytes [%0], [%1, {0, %3, 0}], [%2]; }" ::"r"(dst), "l"(m), "r"(bar), "r"(row) : "memory");
}
template <int OFF>
__device__ __forceinline__ void ld_pkt(uint32_t* v, const uint4* p) {
    asm volatile("{ .reg .b128 t; ld.relaxed.gpu.global.b128 t, [%4+%5]; mov.b128 {%0,%1,%2,%3}, t; }" : "=r"(v[0]), "=r"(v[1]), "=r"(v[2]), "=r"(v[3]) : "l"(p), "n"(OFF * 16) : "memory");
}
template <int OFF>
__device__ __forceinline__ void st_pkt(uint4* p, uint32_t a, uint32_t b, uint32_t c, uint32_t d) {
    asm volatile("{ .reg .b128 t; mov.b128 t, {%1,%2,%3,%4}; st.relaxed.gpu.global.b128 [%0+%5], t; }" ::"l"(p), "r"(a), "r"(b), "r"(c), "r"(d), "n"(OFF * 16) : "memory");
}
__device__ __forceinline__ uint32_t pack2(float lo, float hi) {
    uint32_t r;
    asm("cvt.rn.bf16x2.f32 %0, %1, %2;" : "=r"(r) : "f"(hi), "f"(lo));
    return r;
}
__device__ __forceinline__ float bf_lo(uint32_t w) { return __uint_as_float(w << 16); }
__device__ __forceinline__ float bf_hi(uint32_t w) { return __uint_as_float(w & 0xffff0000u); }
__device__ __forceinline__ uint32_t settag(uint32_t w, uint32_t tag) { return (w & ~1u) | tag; }
__device__ __forceinline__ float ex2(float x) { float y; asm("ex2.approx.ftz.f32 %0, %1;" : "=f"(y) : "f"(x)); return y; }
__device__ __forceinline__ float rcp(float x) { float y; asm("rcp.approx.ftz.f32 %0, %1;" : "=f"(y) : "f"(x)); return y; }
__device__ __forceinline__ float tanh_hw(float x) { float y; asm("tanh.approx.f32 %0, %1;" : "=f"(y) : "f"(x)); return y; }
__device__ __forceinline__ void stsm4(uint32_t addr, uint32_t a, uint32_t b, uint32_t c, uint32_t d) {
    asm volatile("stmatrix.sync.aligned.m8n8.x4.shared.b16 [%0], {%1,%2,%3,%4};" ::"r"(addr), "r"(a), "r"(b), "r"(c), "r"(d) : "memory");
}
__device__ __forceinline__ void fence_async() { asm volatile("fence.proxy.async.shared::cta;" ::: "memory"); }
__device__ __forceinline__ void bar_sync(int id, int n) { asm volatile("bar.sync %0, %1;" ::"r"(id), "r"(n) : "memory"); }
__device__ __forceinline__ void bar_arrive(int id, int n) { asm volatile("bar.arrive %0, %1;" ::"r"(id), "r"(n) : "memory"); }
__device__ __forceinline__ void wg_fence() { asm volatile("wgmma.fence.sync.aligned;" ::: "memory"); }
__device__ __forceinline__ void wg_commit() { asm volatile("wgmma.commit_group.sync.aligned;" ::: "memory"); }
template <int N> __device__ __forceinline__ void wg_wait() { asm volatile("wgmma.wait_group.sync.aligned %0;" ::"n"(N) : "memory"); }

constexpr uint32_t SB0 = 1024;
__host__ __device__ constexpr uint32_t dlo(uint32_t off, uint32_t lbo) { return ((SB0 + off) >> 4) | ((lbo >> 4) << 16); }
__host__ __device__ constexpr uint32_t dhi(uint32_t sbo, uint32_t sw) { return (sbo >> 4) | (sw << 30); }
__device__ __forceinline__ uint64_t dbase(uint32_t lo, uint32_t hi) { uint64_t d; asm volatile("mov.b64 %0, {%1, %2};" : "=l"(d) : "r"(lo), "r"(hi)); return d; }
#define BASE128(off, lbo, adj) dbase(dlo(off, lbo) + (adj), dhi(1024, 1))
#define BASE64(off, lbo, adj) dbase(dlo(off, lbo) + (adj), dhi(512, 2))

#define ACC4(d, o) "+f"(d[o]), "+f"(d[o + 1]), "+f"(d[o + 2]), "+f"(d[o + 3])
#define ACC28(d) ACC4(d, 0), ACC4(d, 4), ACC4(d, 8), ACC4(d, 12), ACC4(d, 16), ACC4(d, 20), ACC4(d, 24)
#define ACC32(d, o) ACC4(d, o), ACC4(d, o + 4), ACC4(d, o + 8), ACC4(d, o + 12), ACC4(d, o + 16), ACC4(d, o + 20), ACC4(d, o + 24), ACC4(d, o + 28)

template <int TB, uint64_t D>
__device__ __forceinline__ void mma_rs56(float* d, uint32_t a0, uint32_t a1, uint32_t a2, uint32_t a3, int sd, uint64_t base) {
    asm volatile("{ .reg .pred p; .reg .b64 db; setp.ne.b32 p, %32, 0; add.u64 db, %33, %34;\n"
                 "wgmma.mma_async.sync.aligned.m64n56k16.f32.bf16.bf16 "
                 "{%0,%1,%2,%3,%4,%5,%6,%7,%8,%9,%10,%11,%12,%13,%14,%15,%16,%17,%18,%19,%20,%21,%22,%23,%24,%25,%26,%27}, "
                 "{%28,%29,%30,%31}, db, p, 1, 1, %35; }\n"
                 : ACC28(d)
                 : "r"(a0), "r"(a1), "r"(a2), "r"(a3), "r"(sd), "l"(base), "n"(D), "n"(TB));
}
template <int TB, uint64_t D>
__device__ __forceinline__ void mma_rs64(float* d, uint32_t a0, uint32_t a1, uint32_t a2, uint32_t a3, int sd, uint64_t base) {
    asm volatile("{ .reg .pred p; .reg .b64 db; setp.ne.b32 p, %36, 0; add.u64 db, %37, %38;\n"
                 "wgmma.mma_async.sync.aligned.m64n64k16.f32.bf16.bf16 "
                 "{%0,%1,%2,%3,%4,%5,%6,%7,%8,%9,%10,%11,%12,%13,%14,%15,%16,%17,%18,%19,%20,%21,%22,%23,%24,%25,%26,%27,%28,%29,%30,%31}, "
                 "{%32,%33,%34,%35}, db, p, 1, 1, %39; }\n"
                 : ACC32(d, 0)
                 : "r"(a0), "r"(a1), "r"(a2), "r"(a3), "r"(sd), "l"(base), "n"(D), "n"(TB));
}
template <int TB, uint64_t D>
__device__ __forceinline__ void mma_rs128(float* d, uint32_t a0, uint32_t a1, uint32_t a2, uint32_t a3, int sd, uint64_t base) {
    asm volatile("{ .reg .pred p; .reg .b64 db; setp.ne.b32 p, %68, 0; add.u64 db, %69, %70;\n"
                 "wgmma.mma_async.sync.aligned.m64n128k16.f32.bf16.bf16 "
                 "{%0,%1,%2,%3,%4,%5,%6,%7,%8,%9,%10,%11,%12,%13,%14,%15,%16,%17,%18,%19,%20,%21,%22,%23,%24,%25,%26,%27,%28,%29,%30,%31,%32,%33,%34,%35,%36,%37,%38,%39,%40,%41,%42,%43,%44,%45,%46,%47,%48,%49,%50,%51,%52,%53,%54,%55,%56,%57,%58,%59,%60,%61,%62,%63}, "
                 "{%64,%65,%66,%67}, db, p, 1, 1, %71; }\n"
                 : ACC32(d, 0), ACC32(d, 32)
                 : "r"(a0), "r"(a1), "r"(a2), "r"(a3), "r"(sd), "l"(base), "n"(D), "n"(TB));
}
template <uint64_t DA, uint64_t DB>
__device__ __forceinline__ void mma_ss56_tt(float* d, int sd, uint64_t ba, uint64_t bb) {
    asm volatile("{ .reg .pred p; .reg .b64 da, db; setp.ne.b32 p, %28, 0; add.u64 da, %29, %31; add.u64 db, %30, %32;\n"
                 "wgmma.mma_async.sync.aligned.m64n56k16.f32.bf16.bf16 "
                 "{%0,%1,%2,%3,%4,%5,%6,%7,%8,%9,%10,%11,%12,%13,%14,%15,%16,%17,%18,%19,%20,%21,%22,%23,%24,%25,%26,%27}, "
                 "da, db, p, 1, 1, 1, 1; }\n"
                 : ACC28(d)
                 : "r"(sd), "l"(ba), "l"(bb), "n"(DA), "n"(DB));
}
template <int... I> struct Seq {};
template <class F, int... I> __device__ __forceinline__ void static_for_impl(F&& f, Seq<I...>) { (f(std::integral_constant<int, I>{}), ...); }
#define FOR7(...) static_for_impl([&](auto T_) { constexpr int t = decltype(T_)::value; __VA_ARGS__; }, Seq<0, 1, 2, 3, 4, 5, 6>{})
#define FOR8(...) static_for_impl([&](auto T_) { constexpr int t = decltype(T_)::value; __VA_ARGS__; }, Seq<0, 1, 2, 3, 4, 5, 6, 7>{})
#define FOR14(...) static_for_impl([&](auto T_) { constexpr int t = decltype(T_)::value; __VA_ARGS__; }, Seq<0, 1, 2, 3, 4, 5, 6, 7, 8, 9, 10, 11, 12, 13>{})

__device__ __forceinline__ int kblk(int p, int b) { return b == 0 ? p : b - (b <= p); }
__host__ __device__ constexpr int krow(int t) { return t < 3 ? 16 * t : (t < 6 ? 56 + 16 * (t - 3) : 48); }
#define AQ(A, b, t) ((t) < 3 ? A[2 * (b)][4 * (t)] : (t) < 6 ? A[2 * (b) + 1][4 * ((t) - 3)] : A[2 * (b)][12]), \
                    ((t) < 3 ? A[2 * (b)][4 * (t) + 1] : (t) < 6 ? A[2 * (b) + 1][4 * ((t) - 3) + 1] : A[2 * (b)][13]), \
                    ((t) < 3 ? A[2 * (b)][4 * (t) + 2] : (t) < 6 ? A[2 * (b) + 1][4 * ((t) - 3) + 2] : A[2 * (b) + 1][12]), \
                    ((t) < 3 ? A[2 * (b)][4 * (t) + 3] : (t) < 6 ? A[2 * (b) + 1][4 * ((t) - 3) + 3] : A[2 * (b) + 1][13])
#define D128(off, t) ((uint64_t)(((off) + krow(t) * 128) >> 4) + ((uint64_t)((t) == 6 ? (7168 - 1024) >> 4 : 0) << 32))
#define D64(off, t) ((uint64_t)(((off) + krow(t) * 64) >> 4) + ((uint64_t)((t) == 6 ? (3584 - 512) >> 4 : 0) << 32))

#define PL(k) (((k) - 3) * PLANE)
__device__ __forceinline__ void st_word(uint32_t* p, uint32_t v) { asm volatile("st.relaxed.gpu.global.u32 [%0], %1;" ::"l"(p), "r"(v) : "memory"); }
__device__ __forceinline__ uint32_t ld_word(const uint32_t* p) { uint32_t v; asm volatile("ld.relaxed.gpu.global.u32 %0, [%1];" : "=r"(v) : "l"(p) : "memory"); return v; }
__device__ __forceinline__ void tag_slice(uint32_t* w, uint32_t tag) { w[0] = settag(w[0], tag); w[4] = settag(w[4], tag); w[8] = settag(w[8], tag); w[12] = settag(w[12], tag); }
template <int O>
__device__ __forceinline__ void send_slice(uint4* dst, int lane, const uint32_t* w) {
    st_pkt<O>(dst, w[0], w[1], w[2], w[3]);
    st_pkt<O + 32>(dst, w[4], w[5], w[6], w[7]);
    st_pkt<O + 64>(dst, w[8], w[9], w[10], w[11]);
    asm volatile("{ .reg .b64 t; mov.b64 t, {%1,%2}; st.relaxed.gpu.global.b64 [%0+%3], t; }" ::"l"((char*)dst - lane * 8), "r"(w[12]), "r"(w[13]), "n"(16 * (O + 96)) : "memory");
}
struct Wide { unsigned __int128 q[3]; uint64_t h; };
__device__ __forceinline__ Wide widen(const uint32_t* w) {
    Wide r;
#pragma unroll
    for (int k = 0; k < 3; k++) asm volatile("mov.b128 %0, {%1,%2,%3,%4};" : "=q"(r.q[k]) : "r"(w[4 * k]), "r"(w[4 * k + 1]), "r"(w[4 * k + 2]), "r"(w[4 * k + 3]));
    asm volatile("mov.b64 %0, {%1,%2};" : "=l"(r.h) : "r"(w[12]), "r"(w[13]));
    return r;
}
template <int O>
__device__ __forceinline__ void send_wide(uint4* dst, int lane, const Wide& v) {
    asm volatile("st.relaxed.gpu.global.b128 [%0+%4], %1;\n st.relaxed.gpu.global.b128 [%0+%5], %2;\n st.relaxed.gpu.global.b128 [%0+%6], %3;"
                 ::"l"(dst), "q"(v.q[0]), "q"(v.q[1]), "q"(v.q[2]), "n"(16 * O), "n"(16 * (O + 32)), "n"(16 * (O + 64)) : "memory");
    asm volatile("st.relaxed.gpu.global.b64 [%0+%2], %1;" ::"l"((char*)dst - lane * 8), "l"(v.h), "n"(16 * (O + 96)) : "memory");
}
#define RW4(v, o) "+r"(v[o]), "+r"(v[(o) + 1]), "+r"(v[(o) + 2]), "+r"(v[(o) + 3])
#define RW2(v, o) "+r"(v[o]), "+r"(v[(o) + 1])
#define WR4(v, o) "=&r"(v[o]), "=&r"(v[(o) + 1]), "=&r"(v[(o) + 2]), "=&r"(v[(o) + 3])
#define LDP(a, b, c, d, addr, off) "ld.relaxed.gpu.global.b128 q, [" addr "+" off "];\n mov.b128 {" a "," b "," c "," d "}, q;\n"
#define LDH(a, b, addr, off) "ld.relaxed.gpu.global.b64 h, [" addr "+" off "];\n mov.b64 {" a "," b "}, h;\n"
#define VOTE_OK "and.b32 t, t, 1;\n setp.ne.u32 p, t, 0;\n vote.sync.any.pred p, p, 0xffffffff;\n @!p bra.uni DN;\n"
#define CHK(x, tag) "lop3.b32 t, " x ", " tag ", t, 0xBE;\n"
__device__ __forceinline__ void check_cnt(uint32_t v, const uint32_t* p, uint32_t target) {
    asm volatile("{ .reg .pred p; .reg .b32 n, t; mov.u32 n, 0; mov.u32 t, %2;\n LP:\n"
                 "sub.s32 t, t, %1;\n setp.lt.s32 p, t, 0;\n vote.sync.any.pred p, p, 0xffffffff;\n @!p bra.uni DN;\n ld.relaxed.gpu.global.u32 t, [%0];\n" SPIN_TAIL("7")
                 ::"l"(p), "r"(target), "r"(v) : "memory");
}
__device__ __forceinline__ void poll_cnt(const uint32_t* p, uint32_t target) {
    asm volatile("{ .reg .pred p; .reg .b32 n, t; mov.u32 n, 0;\n LP:\n"
                 "ld.relaxed.gpu.global.u32 t, [%0];\n sub.s32 t, t, %1;\n setp.lt.s32 p, t, 0;\n vote.sync.any.pred p, p, 0xffffffff;\n @!p bra.uni DN;\n" SPIN_TAIL("1")
                 ::"l"(p), "r"(target) : "memory");
}
template <int STR>
__device__ __forceinline__ void poll4_kv(uint32_t* v, const uint4* p, uint32_t tag) {
    asm volatile("{ .reg .pred p; .reg .b32 n, t; .reg .b128 q; mov.u32 n, 0;\n LP:\n"
                 LDP("%0", "%1", "%2", "%3", "%16", "0") LDP("%4", "%5", "%6", "%7", "%16", "%18")
                 LDP("%8", "%9", "%10", "%11", "%16", "%19") LDP("%12", "%13", "%14", "%15", "%16", "%20")
                 "xor.b32 t, %0, %17;\n" CHK("%4", "%17") CHK("%8", "%17") CHK("%12", "%17") VOTE_OK SPIN_TAIL("2")
                 : WR4(v, 0), WR4(v, 4), WR4(v, 8), WR4(v, 12)
                 : "l"(p), "r"(tag), "n"(16 * STR), "n"(32 * STR), "n"(48 * STR)
                 : "memory");
}
template <int B>
__device__ __forceinline__ void blk_load(uint32_t (&A)[8][14], const uint4* src, int lane) {
    ld_pkt<0>(&A[2 * B][0], src); ld_pkt<32>(&A[2 * B][4], src); ld_pkt<64>(&A[2 * B][8], src);
    ld_pkt<512>(&A[2 * B + 1][0], src); ld_pkt<544>(&A[2 * B + 1][4], src); ld_pkt<576>(&A[2 * B + 1][8], src);
    asm volatile("{ .reg .b64 h;\n" LDH("%0", "%1", "%4", "1536") LDH("%2", "%3", "%4", "9728") "}"
                 : "=&r"(A[2 * B][12]), "=&r"(A[2 * B][13]), "=&r"(A[2 * B + 1][12]), "=&r"(A[2 * B + 1][13])
                 : "l"((const char*)src - lane * 8) : "memory");
}
#define BLK_TEST "xor.b32 t, %0, %30;\n" CHK("%4", "%30") CHK("%8", "%30") CHK("%12", "%30") CHK("%16", "%30") CHK("%20", "%30") CHK("%24", "%30") CHK("%26", "%30") VOTE_OK
template <int B>
__device__ __forceinline__ void blk_check(uint32_t (&A)[8][14], const uint4* src, int lane, uint32_t tag) {
    asm volatile("{ .reg .pred p; .reg .b32 n, t; .reg .b128 q; .reg .b64 h, a8;\n" BLK_TEST
                 "mov.u32 n, 0;\n mad.wide.s32 a8, %29, -8, %28;\n LP:\n"
                 LDP("%0", "%1", "%2", "%3", "%28", "0") LDP("%4", "%5", "%6", "%7", "%28", "512") LDP("%8", "%9", "%10", "%11", "%28", "1024")
                 LDP("%12", "%13", "%14", "%15", "%28", "8192") LDP("%16", "%17", "%18", "%19", "%28", "8704") LDP("%20", "%21", "%22", "%23", "%28", "9216")
                 LDH("%24", "%25", "a8", "1536") LDH("%26", "%27", "a8", "9728") BLK_TEST SPIN_TAIL("3")
                 "\n and.b32 %0, %0, -2; and.b32 %4, %4, -2; and.b32 %8, %8, -2; and.b32 %12, %12, -2; and.b32 %16, %16, -2; and.b32 %20, %20, -2; and.b32 %24, %24, -2; and.b32 %26, %26, -2;"
                 : RW4(A[2 * B], 0), RW4(A[2 * B], 4), RW4(A[2 * B], 8), RW4(A[2 * B + 1], 0), RW4(A[2 * B + 1], 4), RW4(A[2 * B + 1], 8),
                   RW2(A[2 * B], 12), RW2(A[2 * B + 1], 12)
                 : "l"(src), "r"(lane), "r"(tag)
                 : "memory");
}
__device__ __forceinline__ void st_async4(uint32_t a, uint32_t x, uint32_t y, uint32_t z, uint32_t w, uint32_t bar) {
    asm volatile("st.async.weak.shared::cluster.mbarrier::complete_tx::bytes.v4.b32 [%0], {%1,%2,%3,%4}, [%5];" ::"r"(a), "r"(x), "r"(y), "r"(z), "r"(w), "r"(bar) : "memory");
}
__device__ __forceinline__ uint32_t mapa(uint32_t a, uint32_t cta) { uint32_t r; asm("mapa.shared::cluster.u32 %0, %1, %2;" : "=r"(r) : "r"(a), "r"(cta)); return r; }
__device__ __forceinline__ void stat_load(uint32_t* v, const uint4* p) { ld_pkt<0>(v, p); ld_pkt<512>(v + 4, p); }
__device__ __forceinline__ void stat_check(uint32_t* v, const uint4* p, uint32_t tag) {
    asm volatile("{ .reg .pred p; .reg .b32 n, t; .reg .b128 q; mov.u32 n, 0;\n LP:\n"
                 "xor.b32 t, %3, %9;\n" CHK("%7", "%9") VOTE_OK
                 LDP("%0", "%1", "%2", "%3", "%8", "0") LDP("%4", "%5", "%6", "%7", "%8", "8192") SPIN_TAIL("4")
                 : RW4(v, 0), RW4(v, 4) : "l"(p), "r"(tag) : "memory");
}
__device__ __forceinline__ uint32_t x_bits(const uint32_t* X) {
    uint32_t r;
    asm volatile("{ .reg .b32 a, b; prmt.b32 a, %1, %2, 0x0040; prmt.b32 b, %3, %4, 0x0040; prmt.b32 %0, a, b, 0x5410; }" : "=r"(r) : "r"(X[0]), "r"(X[4]), "r"(X[8]), "r"(X[12]));
    return r;
}
template <int O>
__device__ __forceinline__ void slice_load(uint32_t* v, const uint4* p, int lane) {
    ld_pkt<O>(v, p); ld_pkt<O + 32>(v + 4, p); ld_pkt<O + 64>(v + 8, p);
    asm volatile("{ .reg .b64 h;\n" LDH("%0", "%1", "%2", "%3") "}" : "=r"(v[12]), "=r"(v[13]) : "l"((const char*)p - lane * 8), "n"(16 * (O + 96)) : "memory");
}
#define SLICE_TEST "xor.b32 t, %0, %16;\n" CHK("%4", "%16") CHK("%8", "%16") CHK("%12", "%16") VOTE_OK
template <int O>
__device__ __forceinline__ void slice_check(uint32_t* v, const uint4* p, int lane, uint32_t tag) {
    asm volatile("{ .reg .pred p; .reg .b32 n, t; .reg .b128 q; .reg .b64 h;\n" SLICE_TEST "mov.u32 n, 0;\n LP:\n"
                 LDP("%0", "%1", "%2", "%3", "%14", "%17") LDP("%4", "%5", "%6", "%7", "%14", "%18") LDP("%8", "%9", "%10", "%11", "%14", "%19")
                 LDH("%12", "%13", "%15", "%20") SLICE_TEST SPIN_TAIL("5")
                 : RW4(v, 0), RW4(v, 4), RW4(v, 8), RW2(v, 12)
                 : "l"(p), "l"((const char*)p - lane * 8), "r"(tag), "n"(16 * O), "n"(16 * (O + 32)), "n"(16 * (O + 64)), "n"(16 * (O + 96))
                 : "memory");
}
__device__ __forceinline__ void x_fix(uint32_t* X, uint32_t bits) {
    X[0] = __byte_perm(X[0], bits, 0x3214); X[4] = __byte_perm(X[4], bits, 0x3215); X[8] = __byte_perm(X[8], bits, 0x3216); X[12] = __byte_perm(X[12], bits, 0x3217);
}
__device__ __forceinline__ void sts4(uint32_t a, uint32_t x, uint32_t y, uint32_t z, uint32_t w) {
    asm volatile("st.shared.v4.u32 [%0], {%1,%2,%3,%4};" ::"r"(a), "r"(x), "r"(y), "r"(z), "r"(w) : "memory");
}
__device__ __forceinline__ void lds4(uint32_t* v, uint32_t a) {
    asm volatile("ld.shared.v4.u32 {%0,%1,%2,%3}, [%4];" : "=r"(v[0]), "=r"(v[1]), "=r"(v[2]), "=r"(v[3]) : "r"(a) : "memory");
}
struct LnCoef { uint32_t hi, lo, sh; };
__device__ __forceinline__ LnCoef ln_coef(float sum, float sq) {
    sum += __shfl_xor_sync(0xffffffffu, sum, 1); sq += __shfl_xor_sync(0xffffffffu, sq, 1);
    sum += __shfl_xor_sync(0xffffffffu, sum, 2); sq += __shfl_xor_sync(0xffffffffu, sq, 2);
    const float mean = sum * (1.f / 448.f);
    const float var = fmaxf(fmaf(-mean, mean, sq * (1.f / 448.f)), 0.f);
    const float sc = rsqrtf(var + 1e-5f);
    LnCoef r;
    r.hi = pack2(sc, sc);
    const float lo = sc - bf_lo(r.hi), sh = -mean * sc;
    r.lo = pack2(lo, lo);
    r.sh = pack2(sh, sh);
    return r;
}
template <int B>
__device__ __forceinline__ void normalize(uint32_t (&A)[8][14], const LnCoef& c0, const LnCoef& c1) {
#pragma unroll
    for (int s = 2 * B; s < 2 * B + 2; s++)
#pragma unroll
        for (int i = 0; i < 14; i++) {
            const LnCoef& k = (i & 1) ? c1 : c0;
            asm("{ .reg .b32 t; fma.rn.bf16x2 t, %0, %2, %3; fma.rn.bf16x2 %0, %0, %1, t; }" : "+r"(A[s][i]) : "r"(k.hi), "r"(k.lo), "r"(k.sh));
        }
}
__device__ __forceinline__ void slice_stats(const uint32_t* w, float* st) {
    float a = 0.f, b = 0.f, p = 0.f, q = 0.f;
#pragma unroll
    for (int i = 0; i < 7; i++) {
        const float e0 = bf_lo(w[2 * i]), e1 = bf_hi(w[2 * i]), e2 = bf_lo(w[2 * i + 1]), e3 = bf_hi(w[2 * i + 1]);
        a += e0 + e1; b += e2 + e3;
        p = fmaf(e0, e0, p); p = fmaf(e1, e1, p); q = fmaf(e2, e2, q); q = fmaf(e3, e3, q);
    }
    a += __shfl_xor_sync(0xffffffffu, a, 1); p += __shfl_xor_sync(0xffffffffu, p, 1); b += __shfl_xor_sync(0xffffffffu, b, 1); q += __shfl_xor_sync(0xffffffffu, q, 1);
    a += __shfl_xor_sync(0xffffffffu, a, 2); p += __shfl_xor_sync(0xffffffffu, p, 2); b += __shfl_xor_sync(0xffffffffu, b, 2); q += __shfl_xor_sync(0xffffffffu, q, 2);
    st[0] = a; st[1] = p; st[2] = b; st[3] = q;
}
__device__ __forceinline__ void dual_softmax(const float* p, uint32_t* out) {
    constexpr float L = 1.4426950408889634f;
#pragma unroll
    for (int r = 0; r < 2; r++) {
        float mx = fmaxf(p[2 * r], p[2 * r + 1]), mn = fminf(p[2 * r], p[2 * r + 1]);
#pragma unroll
        for (int i = 1; i < 7; i++) {
            mx = fmaxf(mx, fmaxf(p[4 * i + 2 * r], p[4 * i + 2 * r + 1]));
            mn = fminf(mn, fminf(p[4 * i + 2 * r], p[4 * i + 2 * r + 1]));
        }
        mx = fmaxf(mx, __shfl_xor_sync(0xffffffffu, mx, 1));
        mn = fminf(mn, __shfl_xor_sync(0xffffffffu, mn, 1));
        const float bx = -mx * L, bn = mn * L;
        float ep[14], en[14], sp = 0.f, sn = 0.f;
#pragma unroll
        for (int i = 0; i < 14; i++) {
            const float v = p[4 * (i >> 1) + 2 * r + (i & 1)];
            ep[i] = ex2(fmaf(v, L, bx));
            en[i] = ex2(fmaf(v, -L, bn));
            sp += ep[i]; sn += en[i];
        }
        sp += __shfl_xor_sync(0xffffffffu, sp, 1);
        sn += __shfl_xor_sync(0xffffffffu, sn, 1);
        const float ip = rcp(sp), in = rcp(sn);
#pragma unroll
        for (int i = 0; i < 7; i++) {
            out[4 * i + r] = pack2(ep[2 * i] * ip, ep[2 * i + 1] * ip);
            out[4 * i + 2 + r] = pack2(en[2 * i] * in, en[2 * i + 1] * in);
        }
    }
}
__device__ __forceinline__ float geglu(float g, float u) {
    const float t = tanh_hw(g * fmaf(g * g, 0.7978845608028654f * 0.044715f, 0.7978845608028654f));
    const float gu = g * u;
    return fmaf(t, gu, gu);
}
__device__ __forceinline__ void phi_gemm(const float* t, float* p) {
    uint32_t w[14];
#pragma unroll
    for (int i = 0; i < 14; i++) w[i] = pack2(t[2 * i], t[2 * i + 1]);
    const uint64_t db = BASE128(OFF_WPHI, 16, 0);
    wg_fence();
    mma_rs56<0, 0>(p, w[0], w[1], w[2], w[3], 0, db);
    mma_rs56<0, 2>(p, w[4], w[5], w[6], w[7], 1, db);
    mma_rs56<0, 4>(p, w[8], w[9], w[10], w[11], 1, db);
    mma_rs56<0, 6>(p, w[12], w[13], 0u, 0u, 1, db);
    wg_commit();
    wg_wait<0>();
}

}

#define BAR(i) (bars + 8 * (i))
#define R_WAIT() mbar_wait(BAR(slot), ph)
#define WSUM(i)
#define R_ADJ (slot * (STAGE >> 4))
#define R_NEXT() do { eb2 = eb1; eb1 = BAR(B_EMPTY + slot); if (++slot == NST) { slot = 0; ph ^= 1; } } while (0)
#define R_RELEASE(k) do { if (lane == 0) mbar_arrive((k) == 1 ? eb1 : eb2); } while (0)
#define PUSH_BEGIN() do { mbar_wait(BAR(B_ACK + wgi), ackph); ackph ^= 1; } while (0)
#define PUSH_ACK() do { __syncwarp(); if (lane == 0) asm volatile("mbarrier.arrive.shared::cluster.b64 _, [%0];" ::"r"(mapa(BAR(B_ACK + wgi), hr ^ 1)) : "memory"); } while (0)

__global__ void __cluster_dims__(2, 1, 1) __launch_bounds__(384, 1)
fused_kernel(Scratch* const sc, const __nv_bfloat16* __restrict__ x_in, const __nv_bfloat16* __restrict__ w_phi, const int trips,
             const __nv_bfloat16* __restrict__ wg, const __nv_bfloat16* __restrict__ wu, const __nv_bfloat16* __restrict__ wd,
             const __grid_constant__ Maps maps) {
    extern __shared__ __align__(1024) unsigned char smem_raw[];
    const uint32_t sb = s2u(smem_raw);
    const uint32_t bars = sb + OFF_BAR;
    const int wgi = __shfl_sync(0xffffffffu, threadIdx.x >> 7, 0);
    const int hr = blockIdx.x & 1, ck = blockIdx.x >> 1;
    const int gp = (ck - 4) & 7, q7 = ((ck - 36) * 37) >> 8;
    const int pr = __shfl_sync(0xffffffffu, ck < 4 ? ck : (ck < 36 ? (ck - 4) >> 3 : q7), 0);
    const int tile = __shfl_sync(0xffffffffu, ck < 4 ? 0 : (ck < 36 ? (gp ? 2 * gp : 1) : 2 * (ck - 36 - 7 * q7) + 3), 0);
    const int sl = 2 * pr + hr;
    STAMP(0);
    GSTAMP(60);
    if (threadIdx.x == 256) {
#pragma unroll
        for (int i = 0; i < NST; i++) mbar_init(BAR(i), 1);
        asm volatile("fence.mbarrier_init.release.cluster;" ::: "memory");
    }
    if (threadIdx.x == 288) {
        if ((sb & 0x3FFFF) != SB0) asm volatile("trap;");
#pragma unroll
        for (int i = NST; i < B_COUNT; i++) mbar_init(BAR(i), i >= B_ACK ? 4 : (i < B_RECV || i == B_LATE ? 8 : 1));
        asm volatile("fence.mbarrier_init.release.cluster;" ::: "memory");
    }
    __syncwarp();
    asm volatile("barrier.cluster.arrive.relaxed.aligned;" ::: "memory");

    if (wgi == 2) {
        asm volatile("setmaxnreg.dec.sync.aligned.u32 40;");
        const int t128 = fresh_tid() & 127, w = __shfl_sync(0xffffffffu, t128 >> 5, 0), lane = t128 & 31;
        uint32_t e0[2] = {0, 0}, e1[2] = {0, 0}, cw_target = 0, kseq;
        if (w == 0) {
#pragma unroll 1
            for (int n = 0; n < NST; n++) {
                const uint32_t dst = sb + n * STAGE, fb = BAR(n);
                asm volatile(ELECT "mbarrier.arrive.expect_tx.shared::cta.b64 _, [%0], %1; }" ::"r"(fb), "r"(n < 2 ? 2 * STAGE : STAGE) : "memory");
                if (n < 2) {
                    tma3x(sb + OFF_H + n * STAGE, &maps.x, tile * 128 + n * 64, fb);
                    tma3x(dst, &maps.x, tile * 128 + n * 64 + 32, fb);
                } else {
                    if (n == 3) mbar_wait(BAR(1), 0);
                    const int c0 = (n < 4 ? 448 : 896) + 56 * sl, r0 = 224 * (n & 1);
                    tma2d(dst, &maps.qkv, c0, r0, fb);
                    tma2d(dst + HALF, &maps.qkv, c0, r0 + 112, fb);
                }
            }
            asm volatile("barrier.cluster.wait.aligned;" ::: "memory");
            kseq = ld_word(g_c1 + (sl * 8 * 16 + tile) * 32);
            cw_target = (ld_word(g_cw + sl * 32) & ~15u) + 16;
#pragma unroll 1
            for (int k = 0; k < 2; k++) {
                const int n = t128 + 32 * k;
                int m = n - 2 - (n > PACK);
                const bool packed = m >= 30 ? (m < 38 || m >= 52) : m >= 22;
                if (m >= 30) m -= 30;
                if (n == PACK) m = tile < 8 ? tile : tile + 14;
                const int rot = n < 8 ? 0 : pr;
                const int ra = 112 * kblk(rot, m & 3), rb = 112 * kblk(rot, 2 * m & 3), rc = 112 * kblk(rot, (2 * m + 1) & 3);
                int kind = 0, m0, m1, c0, c1, r0, r1;
                if (m < 8) { m0 = m1 = m < 6 ? 1 : 2; c0 = c1 = (m < 2 ? 448 : (m < 4 ? 896 : 0)) + 56 * sl; r0 = rb; r1 = rc; }
                else if (m < 20) { m0 = 3; m1 = 4; c0 = c1 = 224 * sl + 32 * hr + 64 * ((m - 8) >> 2); r0 = r1 = ra; }
                else if (m < 22) { kind = 2; m0 = 5; m1 = 6; c0 = c1 = 224 * sl + (hr ? 0 : 192); r0 = rb; r1 = rc; }
                else { m0 = m1 = 7; c0 = c1 = 56 * (2 * ((pr + (m >> 1) - 10) & 3) + hr); r0 = 224 * (sl ^ (m & 1)); r1 = r0 + 112; }
                if (packed) { kind = 1; r0 = sl * 16 + (m < 8 ? m : m - 14); r1 = 0; }
                e0[0] = e0[1]; e1[0] = e1[1];
                e0[1] = kind | (m0 << 2) | (m1 << 6) | (c0 << 10) | (c1 << 21);
                e1[1] = r0 | (r1 << 16);
            }
        } else {
            const int j = t128 - 32;
            kseq = ld_word(g_c1 + (sl * 8 * 16 + tile) * 32);
            asm volatile("barrier.cluster.wait.aligned;" ::: "memory");
            uint2 wv[7];
            const int k = j < 56 ? j : 55, hh = k >= 28;
#pragma unroll
            for (int i = 0; i < 7; i++) wv[i] = __ldg(reinterpret_cast<const uint2*>(w_phi + (sl * 56 + k) * 28) + i);
#pragma unroll 1
            for (int i = j; i < 7168 / 16; i += 96) sts4(sb + OFF_WPHI + i * 16, 0, 0, 0, 0);
            bar_sync(5, 96);
            if (j < 56) {
                uint32_t a4[4];
#pragma unroll
                for (int q = 0; q < 4; q++) a4[q] = sb + OFF_WPHI + (4 * hh + q) * 128 + ((((k >> 3) ^ (4 * hh + q)) & 7) << 4) + (k & 7) * 2;
                FOR14(const uint32_t v = (t & 1) ? wv[t >> 1].y : wv[t >> 1].x;
                      asm volatile("{ .reg .b16 l, h; mov.b32 {l, h}, %2; st.shared.u16 [%0+%3], l; st.shared.u16 [%1+%3], h; }"
                                   ::"r"(a4[t >= 7 ? 2 : 0]), "r"(a4[t >= 7 ? 3 : 1]), "r"(v), "n"((t % 7) * 1024) : "memory"));
            }
            __syncwarp();
            fence_async();
            kseq = __shfl_sync(0xffffffffu, kseq, 0);
            bar_arrive(1, 224);
            bar_arrive(9, 224);
        }
        kseq = __shfl_sync(0xffffffffu, kseq, 0);
        int slot = 0, ph = 0, n = NST;
#pragma unroll 1
        for (int layer = 0; layer < 3; layer++) {
            if (w == 0) {
                const int nend = layer == 0 ? 11 : (layer == 1 ? 42 : 63);
#pragma unroll 1
                for (; n < nend; n++) {
                const uint32_t w0 = __shfl_sync(0xffffffffu, n < 32 ? e0[0] : e0[1], n & 31), w1 = __shfl_sync(0xffffffffu, n < 32 ? e1[0] : e1[1], n & 31);
                const uint32_t dst = sb + slot * STAGE, fb = BAR(n == PACK ? B_PACK : slot);
                const CUtensorMap* m0 = &maps.x + ((w0 >> 2) & 15);
                const CUtensorMap* m1 = &maps.x + ((w0 >> 6) & 15);
                const int c0 = (w0 >> 10) & 2047, c1 = w0 >> 21, r0 = w1 & 0xffff, r1 = w1 >> 16;
                if (n == 25) {
                    int it = 0;
                    uint32_t v;
                    do { asm volatile("ld.acquire.gpu.global.u32 %0, [%1];" : "=r"(v) : "l"(g_cw + sl * 32) : "memory"); } while ((int)(v - cw_target) < 0 && ++it < 0x400000);
                    asm volatile("fence.proxy.async.global;" ::: "memory");
                    __syncwarp();
                }
                mbar_wait(BAR(B_EMPTY + slot), ph);
                __syncwarp();
                asm volatile(ELECT "mbarrier.arrive.expect_tx.shared::cta.b64 _, [%0], %1; }" ::"r"(fb), "r"(STAGE) : "memory");
                if ((w0 & 3) == 0) {
                    tma2d(dst, m0, c0, r0, fb);
                    tma2d(dst + HALF, m1, c1, r1, fb);
                } else if (w0 & 1) {
                    asm volatile(ELECT "cp.async.bulk.shared::cluster.global.mbarrier::complete_tx::bytes [%0], [%1], %2, [%3]; }"
                                 ::"r"(dst), "l"(reinterpret_cast<const char*>(g_wp) + (size_t)r0 * STAGE), "r"(STAGE), "r"(fb) : "memory");
                } else {
                    tma2d(dst, m0, c0, r0, fb); tma2d(dst + 7168, m0, c0, r1, fb);
                    tma2d(dst + HALF, m1, c0, r0, fb); tma2d(dst + HALF + 7168, m1, c0, r1, fb);
                }
                if (n == PFN) {
                    const int b = blockIdx.x;
                    asm volatile(ELECT "cp.async.bulk.prefetch.L2.global [%0], %1; }" ::"l"(wg + b * 6272), "r"(12544) : "memory");
                    asm volatile(ELECT "cp.async.bulk.prefetch.L2.global [%0], %1; }" ::"l"(wu + b * 6272), "r"(12544) : "memory");
                    asm volatile(ELECT "cp.async.bulk.prefetch.L2.global [%0], %1; }" ::"l"(wd + b * 6272), "r"(12544) : "memory");
                }
                if (n == PACK) asm volatile(ELECT "mbarrier.arrive.shared::cta.b64 _, [%0]; }" ::"r"(BAR(slot)) : "memory");
                if (++slot == NST) { slot = 0; ph ^= 1; }
                }
            } else if (w == 1 && layer == 1) {
                constexpr int ps = PACK % NST;
                mbar_wait(BAR(B_PACK), 0);
                asm volatile("{ .reg .pred e; elect.sync _|e, 0xffffffff;\n"
                             "@e cp.async.bulk.global.shared::cta.bulk_group [%0], [%1], %2;\n"
                             "@e cp.async.bulk.commit_group;\n"
                             "@e cp.async.bulk.wait_group.read 0;\n"
                             "@e mbarrier.arrive.shared::cta.b64 _, [%3], 8;\n"
                             "@e cp.async.bulk.wait_group 0;\n"
                             "@e fence.proxy.async.global;\n"
                             "@e red.release.gpu.global.add.u32 [%4], 1; }"
                             ::"l"(reinterpret_cast<char*>(g_wp) + (size_t)(sl * 16 + tile) * STAGE), "r"(sb + ps * STAGE), "r"(STAGE), "r"(BAR(B_EMPTY + ps)), "l"(g_cw + sl * 32) : "memory");
                __syncwarp();
            }
            if (layer < 2) {
            const uint32_t tag = layer ^ 1;
            kseq++;
            bar_sync(7, 384);
            ASTAMP(0);
            if (tile < 15) {
                const int sq = lane >> 3, pk = 8 * w + (lane & (tile == 14 ? 3 : 7));
                uint32_t v[16];
                if (layer == 0) poll_cnt(g_c1 + ((sl * 8 + (w >> 1) * 4 + (tile >> 2)) * 16 + (lane & 15)) * 32, kseq);
                ASTAMP(1);
                poll4_kv<32>(v, g_kv1 + ((sl * 16 + tile) * 16 + 4 * sq) * 32 + pk, tag);
#pragma unroll
                for (int k = 0; k < 4; k++) {
                    float lo = (bf_lo(v[k]) + bf_lo(v[4 + k])) + (bf_lo(v[8 + k]) + bf_lo(v[12 + k]));
                    float hi = (bf_hi(v[k]) + bf_hi(v[4 + k])) + (bf_hi(v[8 + k]) + bf_hi(v[12 + k]));
                    lo += __shfl_xor_sync(0xffffffffu, lo, 8); hi += __shfl_xor_sync(0xffffffffu, hi, 8);
                    lo += __shfl_xor_sync(0xffffffffu, lo, 16); hi += __shfl_xor_sync(0xffffffffu, hi, 16);
                    v[k] = pack2(lo, hi);
                }
                if (sq == 0) st_pkt<0>(g_kv2 + sl * 512 + 32 * tile + pk, settag(v[0], tag), v[1], v[2], v[3]);
            }
            ASTAMP(2);
            {
                const int item = t128 < 112 ? t128 : 112 + (t128 & 3), d = item >> 1;
                const int cc = t128 < 112 ? 2 * (d >= 28) + (item & 1) : item - 112;
                const int r = t128 < 112 ? d : 56 + (cc >> 1) + 2 * ((t128 - 112) >> 2);
                uint32_t ra = sb + OFF_KVB + r * 128 + 4 * cc, rx = (r & 7) << 4;
                asm volatile("" : "+r"(ra), "+r"(rx));
                FOR14(asm volatile("st.shared.u32 [%0+%2], %1;" ::"r"((ra ^ 8) + (((t & 7) << 4) ^ rx)), "r"(0), "n"((t >> 3) * 8192) : "memory"));
                uint32_t v[16];
                asm volatile("" : "+r"(ra), "+r"(rx));
                poll4_kv<8>(v, g_kv2 + sl * 512 + (item >> 3) * 32 + (item & 7), tag);
                FOR14(asm volatile("st.shared.u32 [%0+%2], %1;" ::"r"(ra + (((t & 7) << 4) ^ rx)), "r"(v[t < 7 ? t : t + 1]), "n"((t >> 3) * 8192) : "memory"));
                fence_async();
            }
            bar_arrive(3, 384);
            ASTAMP(3);
            }
        }
    } else {
        asm volatile("setmaxnreg.inc.sync.aligned.u32 232;");
        int lane = fresh_tid() & 31, prf = pr;
#define pr prf
#define g (lane >> 2)
#define c (lane & 3)
#define t128 (w * 32 + lane)
        const int wu = __shfl_sync(0xffffffffu, fresh_tid() >> 5, 0), w = wu & 3;
        const uint32_t xoff = __shfl_sync(0xffffffffu, (3 * PLANE + ((tile * 2 + wgi) * 8) * 512 + w * 128) * 16, 0);
        char* xu = reinterpret_cast<char*>(g_ex) + xoff;
#define FRESH() asm volatile("" : "+l"(xu), "+r"(lane), "+r"(prf))
#define xp0 (reinterpret_cast<uint4*>(xu) + lane)
        const uint32_t hbuf = sb + OFF_H + wgi * STAGE;
        uint32_t slot = 0, ph = 0, eb1 = 0, eb2 = 0, ackph = 0, rcvph = 0, gatph = 0, swp = 0;
        uint32_t ppid = 6;
#define cx(s) (reinterpret_cast<uint32_t*>(reinterpret_cast<uint4*>(xu) + PL(1) + 112 + (s) * 512))
#define stp (reinterpret_cast<uint4*>(xu) + g + PL(0) + 112)
        uint32_t seq = ld_word(cx(sl));
        uint32_t kseq = ld_word(g_c1 + ((sl * 8 + wu) * 16 + tile) * 32);
        uint32_t stag = ld_word(reinterpret_cast<const uint32_t*>(stp + sl * 512) + 3) & 1;
        asm volatile("barrier.cluster.wait.aligned;" ::: "memory");
        STAMP(1);
        uint32_t X[14];
        const uint32_t x0row = (w < 2 ? hbuf : sb + wgi * STAGE) + ((w & 1) * 16 + (lane & 15)) * 128;
        mbar_wait(BAR(wgi), 0);
        STAMP(51);
#pragma unroll
        for (int j = 0; j < 4; j++) {
            const int G = 7 * sl + min(2 * j + (lane >> 4), 6);
            uint32_t q2, q3;
            asm volatile("ldmatrix.sync.aligned.m8n8.x4.shared.b16 {%0,%1,%2,%3}, [%4];" : "=r"(X[4 * j]), "=r"(X[4 * j + 1]), "=r"(q2), "=r"(q3)
                         : "r"(x0row + (G >> 3) * 4096 + (((G ^ lane) & 7) << 4)) : "memory");
            if (j < 3) { X[(4 * j + 2) % 14] = q2; X[(4 * j + 3) % 14] = q3; }
        }
#define PUSH_SLICE(W)                                                                          \
    {                                                                                          \
        if (t128 == 0) mbar_expect_tx(BAR(B_RECV + wgi), 7168);                                \
        PUSH_BEGIN();                                                                          \
        const uint32_t ra = mapa(hbuf + 24576 + t128 * 16, hr ^ 1), rb = mapa(sb + OFF_XR + wgi * 3072, hr ^ 1), rbar = mapa(BAR(B_RECV + wgi), hr ^ 1); \
        st_async4(ra, W[0], W[1], W[2], W[3], rbar);                                           \
        st_async4(ra + 2048, W[4], W[5], W[6], W[7], rbar);                                    \
        st_async4(rb + t128 * 16, W[8], W[9], W[10], W[11], rbar);                             \
        asm volatile("st.async.weak.shared::cluster.mbarrier::complete_tx::bytes.v2.b32 [%0], {%1,%2}, [%3];" ::"r"(rb + 2048 + t128 * 8), "r"(W[12]), "r"(W[13]), "r"(rbar) : "memory"); \
    }
#define PULL_SLICE(W)                                                                          \
    {                                                                                          \
        uint32_t t0, t1;                                                                       \
        mbar_wait(BAR(B_RECV + wgi), rcvph);                                                   \
        rcvph ^= 1;                                                                            \
        lds4(&A[1][0], hbuf + 24576 + t128 * 16);                                              \
        lds4(&A[1][4], hbuf + 26624 + t128 * 16);                                              \
        lds4(&A[1][8], sb + OFF_XR + wgi * 3072 + t128 * 16);                                  \
        asm volatile("ld.shared.v2.u32 {%0,%1}, [%2];" : "=r"(t0), "=r"(t1) : "r"(sb + OFF_XR + wgi * 3072 + 2048 + t128 * 8) : "memory"); \
        _Pragma("unroll") for (int i = 0; i < 12; i++) A[0][i] = (i & 3) ? W[i] : W[i] & ~1u;  \
        A[1][0] &= ~1u; A[1][4] &= ~1u; A[1][8] &= ~1u;                                        \
        A[0][12] = (hr ? t0 : W[12]) & ~1u; A[0][13] = hr ? t1 : W[13];                        \
        A[1][12] = (hr ? W[12] : t0) & ~1u; A[1][13] = hr ? W[13] : t1;                        \
        asm volatile("" : RW4(A[0], 0), RW4(A[0], 4), RW4(A[0], 8), RW2(A[0], 12), RW4(A[1], 0), RW4(A[1], 4), RW4(A[1], 8), RW2(A[1], 12)); \
        swp = hr * 448;                                                                        \
    }
#define SWB(b, t, db, sh) ((b) == 0 && (t) < 6 ? ((t) < 3 ? db##p : db##m) : db)
#define DECL_DB(b, MK, lbo, sh) const uint64_t db = MK(0, lbo, R_ADJ), dbp = (b) == 0 ? MK(0, lbo, R_ADJ + (swp >> (sh))) : db, dbm = (b) == 0 ? MK(0, lbo, R_ADJ - (swp >> (sh))) : db;
#define PPB 2
#define PP_WAIT() if (wgi == 1) { bar_sync(ppid, 256); ppid ^= 14; }
#define PP_GO() if (wgi == 0) { bar_arrive(ppid, 256); ppid ^= 14; }
#define GAT_DST(B, s2) ((B) == 1 ? hbuf + w * 3584 + (s2) * 1792 : ((s2) ? sb + OFF_KVB + wgi * 8192 : hbuf + 14336) + w * 1792)
#define GAT_ISSUE(B, base)                                                                     \
    {                                                                                          \
        const char* gs = xu + ((base) + kblk(pr, B) * 1024) * 16;                              \
        asm volatile("{ .reg .pred e; elect.sync _|e, 0xffffffff;\n"                           \
                     "@e mbarrier.arrive.expect_tx.shared::cta.b64 _, [%3], 3584;\n"           \
                     "@e cp.async.bulk.shared::cluster.global.mbarrier::complete_tx::bytes [%0], [%2], 1792, [%3];\n" \
                     "@e cp.async.bulk.shared::cluster.global.mbarrier::complete_tx::bytes [%1], [%2+8192], 1792, [%3]; }" \
                     ::"r"(GAT_DST(B, 0)), "r"(GAT_DST(B, 1)), "l"(gs), "r"(BAR(B_GAT + wu * 2 + ((B) >> 1))) : "memory"); \
        __syncwarp();                                                                          \
    }
#define GAT_FETCH(B)                                                                           \
    {                                                                                          \
        mbar_wait(BAR(B_GAT + wu * 2 + ((B) >> 1)), (gatph >> (B)) & 1);                          \
        gatph ^= 1 << (B);                                                                     \
        _Pragma("unroll") for (int s2 = 0; s2 < 2; s2++) {                                     \
            const uint32_t ga = GAT_DST(B, s2) + lane * 16;                                    \
            lds4(&A[2 * (B) + s2][0], ga); lds4(&A[2 * (B) + s2][4], ga + 512); lds4(&A[2 * (B) + s2][8], ga + 1024); \
            asm volatile("ld.shared.v2.u32 {%0,%1}, [%2];" : "=r"(A[2 * (B) + s2][12]), "=r"(A[2 * (B) + s2][13]) : "r"(ga - lane * 8 + 1536) : "memory"); \
        }                                                                                      \
    }
#define LATE_ARRIVE() do { if (lane == 0) mbar_arrive(BAR(B_LATE)); } while (0)
#define LATE_WAIT() do { mbar_wait(BAR(B_LATE), gatph & 1); gatph ^= 1; } while (0)
#define PT 3
#define PREP(b, t, remote)                                                                     \
    if constexpr ((b) < 3 && (t) == PT) {                                                      \
        wg_commit();                                                                           \
        STAMP(74 + 6 * (step & 1) + 2 * (b));                                                  \
        if (remote) {                                                                          \
            if constexpr ((b) == 0) { blk_load<2>(A, BLK(xsrc, 2), lane); if (XG3 == 3) blk_load<3>(A, BLK(xsrc, 3), lane); GAT_FETCH(1) }       \
            blk_check<((b) + 1) & 3>(A, BLK(xsrc, (b) + 1), lane, xtag);                       \
            if constexpr ((b) == 0 && XG3 == 0) blk_load<3>(A, BLK(xsrc, 3), lane); \
            if constexpr ((b) == 0 && XG3 == 2) GAT_ISSUE(3, (step & 1) ? PL(2) : PL(0))                        \
        }                                                                                      \
        STAMP(75 + 6 * (step & 1) + 2 * (b));                                                  \
        normalize<((b) + 1) & 3>(A, k0, k1);                                                   \
        asm volatile("" : RW4(A[(2 * (b) + 2) & 7], 0), RW4(A[(2 * (b) + 2) & 7], 4), RW4(A[(2 * (b) + 2) & 7], 8), RW2(A[(2 * (b) + 2) & 7], 12), \
                          RW4(A[(2 * (b) + 3) & 7], 0), RW4(A[(2 * (b) + 3) & 7], 4), RW4(A[(2 * (b) + 3) & 7], 8), RW2(A[(2 * (b) + 3) & 7], 12)); \
        wg_fence();                                                                            \
    }
#define X0_BLOCK(b)                                                                            \
    { const int rr = lane & 7, hi = lane >> 4;                                                 \
    const uint32_t rowa = (w < 2 ? hbuf : sb + wgi * STAGE) + ((w & 1) * 16 + (lane & 15)) * 128; \
    FOR7(constexpr int G = 14 * (b) + (t < 3 ? 2 * t : (t < 6 ? 2 * t + 1 : 6));               \
         uint32_t q0, q1, q2, q3;                                                              \
         const uint32_t ad = t < 6 ? rowa + (((((G & 7) + hi) ^ rr) & 7) << 4) + ((G & 7) == 7 ? hi * 4096 : 0) : rowa + ((G + 7 * hi) >> 3) * 4096 + ((((G + 7 * hi) ^ rr) & 7) << 4); \
         asm volatile("ldmatrix.sync.aligned.m8n8.x4.shared.b16 {%0,%1,%2,%3}, [%4+%5];" : "=r"(q0), "=r"(q1), "=r"(q2), "=r"(q3) \
                      : "r"(ad), "n"(t < 6 ? (G >> 3) * 4096 : 0) : "memory");                 \
         if (t < 3) { A[2 * (b)][4 * t] = q0; A[2 * (b)][4 * t + 1] = q1; A[2 * (b)][4 * t + 2] = q2; A[2 * (b)][4 * t + 3] = q3; } \
         else if (t < 6) { A[2 * (b) + 1][(4 * t - 12) & 15] = q0; A[2 * (b) + 1][((4 * t - 12) & 15) + 1] = q1; A[2 * (b) + 1][((4 * t - 12) & 15) + 2] = q2; A[2 * (b) + 1][((4 * t - 12) & 15) + 3] = q3; } \
         else { A[2 * (b)][12] = q0; A[2 * (b)][13] = q1; A[2 * (b) + 1][12] = q2; A[2 * (b) + 1][13] = q3; }); }
#define BLK(base, b) ((base) + kblk(pr, b) * 1024)

#pragma unroll 1
        for (int step = 0; step < 4; step++) {
            FRESH();
            const uint32_t tag = (step >> 1) ^ 1;
            const int so = (step >> 1) * 24 + (step & 1) * 12;
            (void)so;
            uint32_t A[8][14];
            uint4* const xsrc = xp0 + ((step & 1) ? PL(2) : PL(0));
            const uint32_t xtag = (step & 1) ? tag : ((seq >> 3) & 1) ^ 1;
            uint32_t xbits;
            {
                float st[4];
                slice_stats(X, st);
                stag ^= 1;
                xbits = x_bits(X);
                tag_slice(X, xtag);
                if (step) send_slice<0>(xsrc + sl * 512, lane, X);
                if (c == 0) st_pkt<0>(stp + sl * 512, __float_as_uint(st[0]), __float_as_uint(st[1]), __float_as_uint(st[2]), settag(__float_as_uint(st[3]), stag));
            }
            STAMP(2 + so);
            uint32_t sv[8];
            if (step == 0) {
                X0_BLOCK(0) X0_BLOCK(1) X0_BLOCK(2) X0_BLOCK(3)
                mbar_wait(BAR(wgi ^ 1), 0);
                R_NEXT();
                R_NEXT();
                R_RELEASE(2);
                stat_load(sv, stp + c * 1024);
                stat_check(sv, stp + c * 1024, stag);
                STAMP(52 + step);
            } else {
                kill<14>(A[2]); kill<14>(A[3]); kill<14>(A[4]); kill<14>(A[5]); kill<14>(A[6]); kill<14>(A[7]);
                PUSH_SLICE(X)
                stat_load(sv, stp + c * 1024);
                if (!(PF & 1)) PULL_SLICE(X)
                stat_check(sv, stp + c * 1024, stag);
                STAMP(52 + step);
                GAT_ISSUE(1, (step & 1) ? PL(2) : PL(0))
                if (PF & 1) PULL_SLICE(X)
                if (XG3 == 1) GAT_ISSUE(3, (step & 1) ? PL(2) : PL(0))
            }
            LnCoef k0, k1;
            {
                k0 = ln_coef(__uint_as_float(sv[0]) + __uint_as_float(sv[4]), __uint_as_float(sv[1]) + __uint_as_float(sv[5]));
                k1 = ln_coef(__uint_as_float(sv[2]) + __uint_as_float(sv[6]), __uint_as_float(sv[3] & ~1u) + __uint_as_float(sv[7] & ~1u));
            }
            STAMP(3 + so);
            GSTAMP(70 + step);

            if ((step & 1) == 0) {
                float tq[28];
#define K_BLOCK(b)                                                                            \
    if ((b) == 1) R_RELEASE(1);                                                               \
    if ((b) == 2 + XT) PUSH_ACK();                                                            \
    if ((b) == 2 && XT && step) GAT_FETCH(3)                                                  \
    if ((b) == 3) { wg_wait<2>(); R_RELEASE(1); }                                             \
    if (((b) & 1) == 0) R_WAIT();                                                             \
    { DECL_DB(b, BASE128, 16, 0)                                                              \
    wg_fence();                                                                               \
    FOR7(mma_rs56<1, D128(((b) & 1) * HALF, t)>(tq, AQ(A, b, t), (b) + t > 0, SWB(b, t, db, 0)); \
         PREP(b, t, step)); }                                                                 \
    wg_commit();                                                                              \
    if ((b) & 1) R_NEXT();
#define P_STAGE(acc, b0)                                                                      \
    R_WAIT();                                                                                 \
    { DECL_DB(b0, BASE128, 16, 0)                                                             \
    wg_fence();                                                                               \
    FOR7(mma_rs56<1, D128(0, t)>(acc, AQ(A, b0, t), (b0) + t > 0, SWB(b0, t, db, 0)));        \
    FOR7(mma_rs56<1, D128(HALF, t)>(acc, AQ(A, (b0) + 1, t), 1, db)); }                       \
    wg_commit();                                                                              \
    R_NEXT();
#define PROJECT(acc) P_STAGE(acc, 0) P_STAGE(acc, 2) wg_wait<1>(); R_RELEASE(2); wg_wait<0>(); R_RELEASE(1);
#define V_PASS()                                                                              \
    {                                                                                         \
        float av[28];                                                                         \
        PROJECT(av)                                                                           \
        const int m = lane >> 3, rr = lane & 7;                                               \
        const uint32_t rowa = hbuf + 16384 + (w * 16 + rr + 8 * (m & 1)) * 128;               \
        const uint32_t one = c == 0 ? 0x00003f80u : 0u;                                       \
        _Pragma("unroll") for (int j = 0; j < 4; j++) {                                       \
            const uint32_t a = rowa + (((2 * j + (m >> 1)) ^ rr) << 4);                       \
            if (j < 3) stsm4(a, pack2(av[8 * j], av[8 * j + 1]), pack2(av[8 * j + 2], av[8 * j + 3]), pack2(av[8 * j + 4], av[8 * j + 5]), pack2(av[8 * j + 6], av[8 * j + 7])); \
            else stsm4(a, pack2(av[24], av[25]), pack2(av[26], av[27]), one, one);            \
        }                                                                                     \
    }
                normalize<0>(A, k0, k1);
                K_BLOCK(0) K_BLOCK(1) K_BLOCK(2) K_BLOCK(3)
                wg_wait<0>();
                R_RELEASE(1);
                STAMP(4 + so);
                if (step == 0) { bar_sync(wgi ? 9 : 1, 224); }
                if (wgi == VW) V_PASS()
                uint32_t PH[28];
                int it = 1;
#pragma unroll 1
                do {
                    float pp[28];
                    phi_gemm(tq, pp);
                    dual_softmax(pp, PH);
                    if (((trips >> (it + 1)) & 1) == 0) continue;
                    {
                        const int m = lane >> 3, rr = lane & 7;
                        const uint32_t rowa = hbuf + (w * 16 + rr + 8 * (m & 1)) * 128;
#pragma unroll
                        for (int j = 0; j < 7; j++) {
                            const int cg = 2 * j + (m >> 1), hi = cg >= 7;
                            stsm4(rowa + hi * 8192 + (((cg - 7 * hi) ^ rr) << 4), PH[4 * j], PH[4 * j + 1], PH[4 * j + 2], PH[4 * j + 3]);
                        }
                    }
                    STAMP(5 + so);
                    if (wgi != VW) V_PASS()
                    fence_async();
                    bar_sync(2, 256);
                    float kv[28];
                    const uint64_t da = BASE128(OFF_H + 16384, 16, 0), dbk = BASE128(OFF_H, 16, wgi * 512);
                    wg_fence();
                    FOR8(constexpr uint64_t o = ((t >> 2) * STAGE + (t & 3) * 2048) >> 4; mma_ss56_tt<o, o>(kv, t > 0, da, dbk));
                    wg_commit();
                    wg_wait<0>();
#pragma unroll
                    for (int hf = 0; hf < 2; hf++) {
                        const int d = 16 * w + g + 8 * hf;
                        if ((d < 56 && (d >= 28) == (c >= 2)) || d == 56) {
                            const int item = d < 56 ? 2 * d + (c & 1) : 112 + c;
                            uint4* dst = g_kv1 + ((sl * 16 + (item >> 3)) * 16 + tile) * 32 + wgi * 16 + (item & 7);
#define KVW(i) pack2(kv[4 * (i) + 2 * hf], kv[4 * (i) + 2 * hf + 1])
                            st_pkt<0>(dst, settag(KVW(0), tag), KVW(1), KVW(2), KVW(3));
                            st_pkt<8>(dst, settag(KVW(4), tag), KVW(5), KVW(6), 0u);
                        }
                    }
                    __syncwarp();
                    kseq++;
                    if (lane == 0) st_word(g_c1 + ((sl * 8 + wu) * 16 + tile) * 32, kseq);
                    bar_arrive(7, 384);
                    STAMP(6 + so);
                    kill<28>(tq);
                    if (QPP) { PP_WAIT() }
                    P_STAGE(tq, 0) P_STAGE(tq, 2)
                    if (QPP) { PP_GO() }
                    wg_wait<1>(); R_RELEASE(2); wg_wait<0>(); R_RELEASE(1);
                    STAMP(7 + so);
                    kill<28>(PH);
                } while (((trips >> (++it)) & 1));
                STAMP(8 + so);
                FRESH();
                if (step) {
                    slice_load<PL(0)>(X, xp0 + sl * 512, lane);
                } else {
                    const uint32_t* xp = reinterpret_cast<const uint32_t*>(x_in + (size_t)(tile * 128 + wu * 16 + g) * 448 + 56 * sl + 2 * c);
#pragma unroll
                    for (int i = 0; i < 7; i++) { X[2 * i] = __ldg(xp + 4 * i); X[2 * i + 1] = __ldg(xp + 4 * i + 8 * 224); }
                }
                bar_sync(3, 384);
                STAMP(9 + so);
                const uint4* const osrc = xp0 + PL(1);
                {
                    float nm[32];
                    const uint64_t db = BASE128(OFF_KVB, 16, 0);
                    wg_fence();
                    FOR7(mma_rs64<0, ((t >> 2) * 8192 + (t & 3) * 32) / 16>(nm, PH[4 * t], PH[4 * t + 1], PH[4 * t + 2], PH[4 * t + 3], t > 0, db));
                    wg_commit();
                    wg_wait<0>();
                    LATE_ARRIVE();
                    const float i00 = rcp(nm[28] + 1e-6f), i01 = rcp(nm[29] + 1e-6f), i10 = rcp(nm[30] + 1e-6f), i11 = rcp(nm[31] + 1e-6f);
                    const float m0 = c >= 2 ? i01 : i00, m1 = c >= 2 ? i11 : i10;
                    uint32_t O[14];
#pragma unroll
                    for (int i = 0; i < 7; i++) {
                        const float f0 = i < 3 ? i00 : (i > 3 ? i01 : m0), f1 = i < 3 ? i10 : (i > 3 ? i11 : m1);
                        O[2 * i] = pack2(nm[4 * i] * f0, nm[4 * i + 1] * f0);
                        O[2 * i + 1] = pack2(nm[4 * i + 2] * f1, nm[4 * i + 3] * f1);
                    }
                    if (OST) { PP_WAIT() }
                    tag_slice(O, tag);
                    send_slice<PL(1)>(xp0 + sl * 512, lane, O);
                    seq++;
                    if (lane == 0) st_word(cx(sl), seq);
                    STAMP(10 + so);
                    PUSH_SLICE(O)
                    if (OST == 1) { PP_GO() }
                    const uint32_t cv = ld_word(cx(lane & 7));
                    if (!(PF & 2)) PULL_SLICE(O)
                    LATE_WAIT();
                    check_cnt(cv, cx(lane & 7), seq);
                    if (OST == 2) { PP_GO() }
                    STAMP(56 + (step >> 1));
                    GAT_ISSUE(1, PL(1))
                    GAT_ISSUE(3, PL(1))
                    if ((PF & 6) == 2) PULL_SLICE(O)
                    blk_load<2>(A, BLK(osrc, 2), lane);
                    if ((PF & 6) == 6) PULL_SLICE(O)
                }
                float ao[28];
#define WO_BLOCK(b)                                                                           \
    if ((b) > 0) blk_check<b>(A, BLK(osrc, b), lane, tag);                                    \
    if (((b) & 1) == 0) R_WAIT();                                                             \
    { DECL_DB(b, BASE128, 16, 0)                                                              \
    wg_fence();                                                                               \
    FOR7(mma_rs56<1, D128(((b) & 1) * HALF, t)>(ao, AQ(A, b, t), (b) + t > 0, SWB(b, t, db, 0))); } \
    wg_commit();                                                                              \
    if ((b) & 1) R_NEXT();
                WO_BLOCK(0)
                STAMP(11 + so);
                GAT_FETCH(1)
                WO_BLOCK(1)
                WO_BLOCK(2)
                GAT_FETCH(3)
                WO_BLOCK(3)
                PUSH_ACK();
                wg_wait<0>();
                R_RELEASE(2);
                STAMP(12 + so);
                WSUM(86 + 7 * (step >> 1));
                x_fix(X, xbits);
#pragma unroll
                for (int i = 0; i < 14; i++) X[i] = pack2(bf_lo(X[i]) + ao[2 * i], bf_hi(X[i]) + ao[2 * i + 1]);
            } else {
                uint32_t H[56];
                float ag[64];
#define F1_EPI(dst, ng, ag)                                                                    \
    _Pragma("unroll") for (int i = 0; i < 2 * (ng); i++)                                       \
        (dst)[i] = pack2(geglu(ag[2 * i], ag[4 * (ng) + 2 * i]), geglu(ag[2 * i + 1], ag[4 * (ng) + 2 * i + 1]));
#define H_PUSH(h0, off) st_async4(rem_h + (off), H[h0], H[(h0) + 1], H[(h0) + 2], H[(h0) + 3], mapa(BAR(B_RECV2 + wgi), hr ^ 1));
#define F1_BLOCK(b, first)                                                                     \
    if ((first) && (b) == 1) R_RELEASE(2);                                                     \
    if ((first) && (b) == 2 + XT) PUSH_ACK();                                                  \
    if ((first) && (b) == 2 && XT) GAT_FETCH(3)                                                \
    R_WAIT();                                                                                  \
    if ((b) == ((first) ? PPF : PPB)) { PP_WAIT() }                                            \
    { DECL_DB(b, BASE128, HALF, 0)                                                             \
    wg_fence();                                                                                \
    FOR7(mma_rs128<1, D128(0, t)>(ag, AQ(A, b, t), (b) + t > 0, SWB(b, t, db, 0));             \
         if constexpr (first) { PREP(b, t, true) }); }                                         \
    wg_commit();                                                                               \
    if ((b) == 3) { PP_GO() }                                                                  \
    if ((b) > 0) { wg_wait<1>(); R_RELEASE(1); }       \
    R_NEXT();
                normalize<0>(A, k0, k1);
                F1_BLOCK(0, true) F1_BLOCK(1, true) F1_BLOCK(2, true) F1_BLOCK(3, true)
                if (t128 == 0) { mbar_expect_tx(BAR(B_RECV + wgi), 16384); mbar_expect_tx(BAR(B_RECV2 + wgi), 12288); }
                PUSH_BEGIN();
                wg_wait<0>();
                R_RELEASE(1);
                int p = 0;
#pragma unroll 1
                do {
                    F1_EPI(H + 32, 8, ag)
                    STAMP(4 + p + so);
                    WSUM(81 + p + 7 * (step >> 1));
                    if (((trips >> (p + 1)) & 1) == 0) continue;
                    if (step == 1 && p == PKP) R_NEXT();
                    kill<64>(ag);
                    F1_BLOCK(0, false)
                    {
                        const uint32_t pk = (p ? hbuf + 16384 : sb + OFF_KVB + wgi * 8192) + w * 2048;
#pragma unroll
                        for (int k = 0; k < 4; k++) sts4(pk + k * 512 + lane * 16, H[32 + 4 * k], H[33 + 4 * k], H[34 + 4 * k], H[35 + 4 * k]);
                        fence_async();
                        __syncwarp();
                        asm volatile(ELECT "cp.async.bulk.shared::cluster.shared::cta.mbarrier::complete_tx::bytes [%0], [%1], 2048, [%2]; }"
                                     ::"r"(mapa(hbuf + p * 8192 + w * 2048, hr ^ 1)), "r"(pk), "r"(mapa(BAR(B_RECV + wgi), hr ^ 1)) : "memory");
                    }
                    F1_BLOCK(1, false) F1_BLOCK(2, false) F1_BLOCK(3, false)
                    wg_wait<0>();
                    R_RELEASE(1);
                    kill<16>(H + 32);
                } while (((trips >> (++p)) & 1));
#pragma unroll
                for (int k = 0; k < 4; k++) lds4(H + 16 + 4 * k, hbuf + 16384 + w * 2048 + k * 512 + lane * 16);
                __syncwarp();
                if (lane == 0) asm volatile("mbarrier.arrive.shared::cluster.b64 _, [%0];" ::"r"(mapa(BAR(B_ACK2 + wgi), hr ^ 1)) : "memory");
                const uint32_t rem_h = mapa(hbuf + w * 2048 + lane * 16, hr ^ 1);
#define F1_LAST(b0)                                                                            \
    R_WAIT();                                                                                  \
    if (b0) { PP_WAIT() }                                                                      \
    { DECL_DB(b0, BASE64, HALF, 1)                                                             \
    wg_fence();                                                                                \
    FOR7(mma_rs64<1, D64(0, t)>(al, AQ(A, b0, t), (b0) + t > 0, SWB(b0, t, db, 1)));           \
    FOR7(mma_rs64<1, D64(7168, t)>(al, AQ(A, (b0) + 1, t), 1, db)); }                          \
    wg_commit();                                                                               \
    if (b0) { PP_GO() }                                                                        \
    R_NEXT();
                float al[32];
                F1_LAST(0)
                mbar_wait(BAR(B_RECV + wgi), rcvph);
                rcvph ^= 1;
                mbar_wait(BAR(B_ACK2 + wgi), step >> 1);
                H_PUSH(32, 16384) H_PUSH(36, 16896)
                F1_LAST(2)
                H_PUSH(40, 17408) H_PUSH(44, 17920)
                wg_wait<1>();
                R_RELEASE(2);
                wg_wait<0>();
                R_RELEASE(1);
                uint32_t HP[56];
#pragma unroll
                for (int k = 0; k < 4; k++) lds4(H + 4 * k, sb + OFF_KVB + wgi * 8192 + w * 2048 + k * 512 + lane * 16);
#pragma unroll
                for (int t = 0; t < 8; t++) lds4(HP + 4 * t, hbuf + (t >> 2) * 8192 + w * 2048 + (t & 3) * 512 + lane * 16);
                F1_EPI(H + 48, 4, al)
                H_PUSH(48, 24576 - w * 1024) H_PUSH(52, 25088 - w * 1024)
                STAMP(7 + so);
                WSUM(84 + 7 * (step >> 1));
                FRESH();
                float acc[28];
                const uint32_t roA = hr ? 256u : 0u, roB = hr ? (uint32_t)-1536 : 0u;
                const uint32_t rpA = hr ? 0u : 256u, rpB = hr ? 0u : (uint32_t)-1536;
                float res[28];
                uint32_t v0[14], v1[14], P[14];
                Wide PW;
                const uint4* ps = xp0 + sl * 512;
#define F2_OWN_A()                                                                             \
    R_WAIT();                                                                                  \
    d0 = BASE128(0, 16, R_ADJ + roA); d1 = BASE128(0, 16, R_ADJ + roB);                        \
    wg_fence();                                                                                \
    FOR14(if constexpr (t < OT) mma_rs56<1, t * 128>(acc, H[4 * t], H[4 * t + 1], H[4 * t + 2], H[4 * t + 3], t > 0, d0)); \
    wg_commit();
#define F2_OWN_B()                                                                             \
    wg_fence();                                                                                \
    FOR14(if constexpr (t >= OT) mma_rs56<1, t * 128>(acc, H[4 * t], H[4 * t + 1], H[4 * t + 2], H[4 * t + 3], 1, t < 12 ? d0 : d1)); \
    wg_commit();                                                                               \
    R_NEXT();
#define F2_PEER()                                                                              \
    R_WAIT();                                                                                  \
    if (F2PP) { PP_WAIT() }                                                                    \
    d0 = BASE128(0, 16, R_ADJ + rpA); d1 = BASE128(0, 16, R_ADJ + rpB);                        \
    wg_fence();                                                                                \
    FOR14(mma_rs56<1, t * 128>(acc, HP[4 * t], HP[4 * t + 1], HP[4 * t + 2], HP[4 * t + 3], 1, t < 12 ? d0 : d1)); \
    wg_commit();                                                                               \
    if (F2PP) { PP_GO() }                                                                      \
    R_NEXT();
#define F2_TURN(u)                                                                             \
    wg_wait<1>();                                                                              \
    if ((u) < 2 || TDEF < 2) R_RELEASE(2);                                                     \
    wg_wait<0>();                                                                              \
    if ((u) < 2 || TDEF < 1) R_RELEASE(1);                                                     \
    _Pragma("unroll") for (int i = 0; i < 14; i++) P[i] = pack2(acc[2 * i], acc[2 * i + 1]);   \
    tag_slice(P, tag);                                                                         \
    PW = widen(P);                                                                             \
    kill<28>(acc);                                                                             \
    F2_OWN_A()                                                                                 \
    if ((u) == 2) { slice_load<PL(3)>(v0, ps, lane); slice_load<PL(4)>(v1, ps, lane); } \
    send_wide<PL(3 + (u))>(xp0 + (2 * ((pr + (u) + 1) & 3) + hr) * 512, lane, PW);             \
    seq++;                                                                                     \
    if (lane == 0) st_word(cx(sl), seq);                                                       \
    __syncwarp();                                                                              \
    STAMP(8 + (u) + so);                                                                       \
    F2_OWN_B()
                uint64_t d0, d1;
                F2_OWN_A()
                F2_OWN_B()
                R_WAIT();
                d0 = BASE128(0, 16, R_ADJ + rpA); d1 = BASE128(0, 16, R_ADJ + rpB);
                wg_fence();
                FOR8(mma_rs56<1, t * 128>(acc, HP[4 * t], HP[4 * t + 1], HP[4 * t + 2], HP[4 * t + 3], 1, d0));
                wg_commit();
                mbar_wait(BAR(B_RECV2 + wgi), step >> 1);
#pragma unroll
                for (int k = 0; k < 4; k++) lds4(HP + 32 + 4 * k, hbuf + 16384 + w * 2048 + k * 512 + lane * 16);
                lds4(HP + 48, hbuf + 24576 + w * 1024 + lane * 16);
                lds4(HP + 52, hbuf + 25088 + w * 1024 + lane * 16);
                if (step == 1) PUSH_ACK();
                wg_fence();
                FOR14(if constexpr (t >= 8) mma_rs56<1, t * 128>(acc, HP[4 * t], HP[4 * t + 1], HP[4 * t + 2], HP[4 * t + 3], 1, t < 12 ? d0 : d1));
                wg_commit();
                R_NEXT();
                F2_TURN(0)
                F2_PEER()
                F2_TURN(1)
                F2_PEER()
                F2_TURN(2)
                if (step == 1) STAMP(64);
                slice_check<PL(3)>(v0, ps, lane, tag);
                slice_check<PL(4)>(v1, ps, lane, tag);
#pragma unroll
                for (int i = 0; i < 14; i++) { res[2 * i] = bf_lo(v0[i]) + bf_lo(v1[i]); res[2 * i + 1] = bf_hi(v0[i]) + bf_hi(v1[i]); }
                slice_load<PL(2)>(X, ps, lane);
                if (step == 1) STAMP(65);
                F2_PEER()
                if (step == 1) STAMP(66);
                poll_cnt(cx(2 * ((pr + 1) & 3) + hr), seq);
                if (step == 1) STAMP(67);
                slice_load<PL(5)>(v0, ps, lane);
                x_fix(X, xbits);
                slice_check<PL(5)>(v0, ps, lane, tag);
                if (lane < TDEF) mbar_arrive(BAR(B_EMPTY + (slot + NST - 3 - lane) % NST));
#pragma unroll
                for (int i = 0; i < 14; i++) { res[2 * i] += bf_lo(v0[i]); res[2 * i + 1] += bf_hi(v0[i]); }
                STAMP(11 + so);
                wg_wait<0>();
                R_RELEASE(2);
                STAMP(12 + so);
                WSUM(85 + 7 * (step >> 1));
#pragma unroll
                for (int i = 0; i < 14; i++) X[i] = pack2(fmaf(res[2 * i] + acc[2 * i], 0.5f, bf_lo(X[i])), fmaf(res[2 * i + 1] + acc[2 * i + 1], 0.5f, bf_hi(X[i])));
            }
        }
        {
            const int m = lane >> 3, rr = lane & 7;
            const uint32_t ob = hbuf + w * 2048, rowa = ob + (rr + 8 * (m & 1)) * 112 + (m >> 1) * 16;
#pragma unroll
            for (int j = 0; j < 3; j++) stsm4(rowa + 32 * j, X[4 * j], X[4 * j + 1], X[4 * j + 2], X[4 * j + 3]);
            asm volatile("stmatrix.sync.aligned.m8n8.x2.shared.b16 [%0], {%1,%2};" ::"r"(ob + (rr + 8 * (m & 1)) * 112 + 96), "r"(X[12]), "r"(X[13]) : "memory");
            fence_async();
            __syncwarp();
            if (lane == 0) {
                asm volatile("cp.async.bulk.tensor.2d.global.shared::cta.bulk_group [%0, {%2, %3}], [%1];" ::"l"(&maps.out), "r"(ob), "r"(56 * sl), "r"(tile * 128 + wu * 16) : "memory");
                asm volatile("cp.async.bulk.commit_group;" ::: "memory");
                asm volatile("cp.async.bulk.wait_group.read 0;" ::: "memory");
            }
        }
        STAMP(50);
        GSTAMP(61);
        PDUMP();
    }
}

#undef g
#undef pr
#undef c
#undef t128

typedef CUresult (*EncodeFn)(CUtensorMap*, CUtensorMapDataType, cuuint32_t, void*, const cuuint64_t*, const cuuint64_t*, const cuuint32_t*,
                             const cuuint32_t*, CUtensorMapInterleave, CUtensorMapSwizzle, CUtensorMapL2promotion, CUtensorMapFloatOOBfill);

static void make_map(EncodeFn enc, CUtensorMap* m, const void* p, uint64_t cols, uint64_t rows, uint32_t bc, uint32_t br, CUtensorMapSwizzle sw) {
    cuuint64_t gd[2] = {cols, rows};
    cuuint64_t gs[1] = {cols * 2};
    cuuint32_t bd[2] = {bc, br};
    cuuint32_t es[2] = {1, 1};
    enc(m, CU_TENSOR_MAP_DATA_TYPE_BFLOAT16, 2, const_cast<void*>(p), gd, gs, bd, es, CU_TENSOR_MAP_INTERLEAVE_NONE, sw,
        CU_TENSOR_MAP_L2_PROMOTION_L2_128B, CU_TENSOR_MAP_FLOAT_OOB_FILL_NONE);
}

extern "C" void kernel_launch(void* const* d_in, const int* in_sizes, int n_in, void* d_out, int out_size) {
    (void)in_sizes; (void)n_in; (void)out_size;
    static EncodeFn enc = nullptr;
    static Scratch* scratch = nullptr;
    if (!enc) {
        void* fn = nullptr;
        cudaDriverEntryPointQueryResult qr;
        cudaGetDriverEntryPoint("cuTensorMapEncodeTiled", &fn, cudaEnableDefault, &qr);
        enc = (EncodeFn)fn;
        cudaGetSymbolAddress((void**)&scratch, g_scratch);
        cudaFuncSetAttribute(fused_kernel, cudaFuncAttributeMaxDynamicSharedMemorySize, SMEM_BYTES);
    }
    Maps maps;
    {
        cuuint64_t gd[3] = {64, 2048, 7};
        cuuint64_t gs[2] = {896, 128};
        cuuint32_t bd[3] = {64, 32, 7};
        cuuint32_t es[3] = {1, 1, 1};
        enc(&maps.x, CU_TENSOR_MAP_DATA_TYPE_BFLOAT16, 3, d_in[0], gd, gs, bd, es, CU_TENSOR_MAP_INTERLEAVE_NONE, CU_TENSOR_MAP_SWIZZLE_128B,
            CU_TENSOR_MAP_L2_PROMOTION_L2_128B, CU_TENSOR_MAP_FLOAT_OOB_FILL_NONE);
    }
    make_map(enc, &maps.out, d_out, 448, 2048, 56, 16, CU_TENSOR_MAP_SWIZZLE_NONE);
    make_map(enc, &maps.qkv, d_in[1], 1344, 448, 64, 112, CU_TENSOR_MAP_SWIZZLE_128B);
    make_map(enc, &maps.wo, d_in[3], 448, 448, 64, 112, CU_TENSOR_MAP_SWIZZLE_128B);
    make_map(enc, &maps.wg, d_in[5], 1792, 448, 64, 112, CU_TENSOR_MAP_SWIZZLE_128B);
    make_map(enc, &maps.wu, d_in[6], 1792, 448, 64, 112, CU_TENSOR_MAP_SWIZZLE_128B);
    make_map(enc, &maps.wg32, d_in[5], 1792, 448, 32, 112, CU_TENSOR_MAP_SWIZZLE_64B);
    make_map(enc, &maps.wu32, d_in[6], 1792, 448, 32, 112, CU_TENSOR_MAP_SWIZZLE_64B);
    make_map(enc, &maps.wd, d_in[7], 448, 1792, 64, 112, CU_TENSOR_MAP_SWIZZLE_128B);
    fused_kernel<<<128, 384, SMEM_BYTES>>>(scratch, (const __nv_bfloat16*)d_in[0], (const __nv_bfloat16*)d_in[2], 7, (const __nv_bfloat16*)d_in[5],
                                           (const __nv_bfloat16*)d_in[6], (const __nv_bfloat16*)d_in[7], maps);
}
```

```cpp
#include <cuda_runtime.h>
#include <cuda.h>
#include <cuda_bf16.h>
#include <stdint.h>
#include <type_traits>

#define PPF 2
#define PKP 0
#define TDEF 1
#define TMPF 0
#define NORM1 0
#define LPARK 1
#define PFN 9
#define VW 1
#define QPP 1
#define XG3 2
#define XT (XG3 == 1 || XG3 == 2)
#define PFI 0
#define ACAN 0
#define SPLIT0 1
#define OT 2
#define F2PP 0
#define PPK 2
#define QE 1
#define OST 1
#define PP

namespace {

constexpr uint32_t STAGE = 28672, HALF = 14336;
constexpr int NST = 5;
constexpr uint32_t OFF_H = NST * STAGE;
constexpr uint32_t OFF_KVB = OFF_H + 2 * STAGE;
constexpr uint32_t OFF_WPHI = OFF_KVB + 16384;
constexpr uint32_t OFF_XR = OFF_WPHI + 7168;
constexpr uint32_t OFF_BAR = OFF_XR + 6144;
constexpr uint32_t SMEM_BYTES = OFF_BAR + 384 + 1408;
constexpr int B_EMPTY = NST, B_RECV = 2 * NST, B_RECV2 = B_RECV + 2, B_PACK = B_RECV2 + 2, B_GAT = B_PACK + 1, B_LATE = B_GAT + 16, B_ACK = B_LATE + 1, B_ACK2 = B_ACK + 2, B_COUNT = B_ACK2 + 2;

constexpr int PACK = 14 + 4 * PKP;

struct Maps { CUtensorMap x, qkv, wo, wg, wu, wg32, wu32, wd, out; };

}

constexpr int PLANE = 16 * 2 * 8 * 512;
struct Scratch {
    uint4 ex[6 * PLANE];
    uint4 kv1[8 * 16 * 16 * 32];
    uint4 kv2[8 * 512];
    uint32_t c1[8 * 8 * 16 * 32];
    uint32_t cw[8 * 32];
    uint4 wp[8 * 32 * (HALF / 16)];
};
__device__ __align__(1024) Scratch g_scratch;
#define g_ex (sc->ex)
#define g_kv1 (sc->kv1)
#define g_kv2 (sc->kv2)
#define g_c1 (sc->c1)
#define g_cw (sc->cw)
#define g_wp (sc->wp)
#define STAMP(i)
#define GSTAMP(i)
#define PDUMP()
#define ASTAMP(i)

namespace {

__device__ __forceinline__ int fresh_tid() { int t; asm volatile("mov.u32 %0, %%tid.x;" : "=r"(t)); return t; }
template <int N> __device__ __forceinline__ void kill(uint32_t* v) {
#pragma unroll
    for (int i = 0; i < N; i++) v[i] = 0;
}
template <int N> __device__ __forceinline__ void kill(float* v) {
#pragma unroll
    for (int i = 0; i < N; i++) v[i] = 0.f;
}
__device__ __forceinline__ uint32_t s2u(const void* p) { return (uint32_t)__cvta_generic_to_shared(p); }
__device__ __forceinline__ void mbar_init(uint32_t a, uint32_t c) { asm volatile("mbarrier.init.shared::cta.b64 [%0], %1;" ::"r"(a), "r"(c) : "memory"); }
__device__ __forceinline__ void mbar_expect_tx(uint32_t a, uint32_t b) { asm volatile("mbarrier.arrive.expect_tx.shared::cta.b64 _, [%0], %1;" ::"r"(a), "r"(b) : "memory"); }
__device__ __forceinline__ void mbar_arrive(uint32_t a) { asm volatile("mbarrier.arrive.shared::cta.b64 _, [%0];" ::"r"(a) : "memory"); }
#define GIVE_UP(id) "trap;\n"
#define SPIN_MAX "0x400000"
#define SPIN_TAIL(id) "add.u32 n, n, 1;\n setp.lt.u32 p, n, " SPIN_MAX ";\n @p bra.uni LP;\n" GIVE_UP(id) " DN:\n }"
__device__ __forceinline__ void mbar_wait(uint32_t a, uint32_t ph) {
    asm volatile("{ .reg .pred p; .reg .b32 n; mov.u32 n, 0;\n LP:\n"
                 "mbarrier.try_wait.parity.shared::cta.b64 p, [%0], %1;\n @p bra DN;\n"
                 "add.u32 n, n, 1;\n setp.lt.u32 p, n, " SPIN_MAX ";\n @p bra LP;\n"
                 GIVE_UP("")
                 " DN:\n }" ::"r"(a), "r"(ph) : "memory");
}
#define ELECT "{ .reg .pred e; elect.sync _|e, 0xffffffff; @e "
__device__ __forceinline__ void tma2d(uint32_t dst, const CUtensorMap* m, int c0, int c1, uint32_t bar) {
    asm volatile(ELECT "cp.async.bulk.tensor.2d.shared::cluster.global.mbarrier::complete_tx::bytes [%0], [%1, {%3, %4}], [%2]; }" ::"r"(dst), "l"(m), "r"(bar), "r"(c0), "r"(c1) : "memory");
}
__device__ __forceinline__ void tma3x(uint32_t dst, const CUtensorMap* m, int row, uint32_t bar) {
    asm volatile(ELECT "cp.async.bulk.tensor.3d.shared::cluster.global.mbarrier::complete_tx::bytes [%0], [%1, {0, %3, 0}], [%2]; }" ::"r"(dst), "l"(m), "r"(bar), "r"(row) : "memory");
}
template <int OFF>
__device__ __forceinline__ void ld_pkt(uint32_t* v, const uint4* p) {
    asm volatile("{ .reg .b128 t; ld.relaxed.gpu.global.b128 t, [%4+%5]; mov.b128 {%0,%1,%2,%3}, t; }" : "=r"(v[0]), "=r"(v[1]), "=r"(v[2]), "=r"(v[3]) : "l"(p), "n"(OFF * 16) : "memory");
}
template <int OFF>
__device__ __forceinline__ void st_pkt(uint4* p, uint32_t a, uint32_t b, uint32_t c, uint32_t d) {
    asm volatile("{ .reg .b128 t; mov.b128 t, {%1,%2,%3,%4}; st.relaxed.gpu.global.b128 [%0+%5], t; }" ::"l"(p), "r"(a), "r"(b), "r"(c), "r"(d), "n"(OFF * 16) : "memory");
}
__device__ __forceinline__ uint32_t pack2(float lo, float hi) {
    uint32_t r;
    asm("cvt.rn.bf16x2.f32 %0, %1, %2;" : "=r"(r) : "f"(hi), "f"(lo));
    return r;
}
__device__ __forceinline__ float bf_lo(uint32_t w) { return __uint_as_float(w << 16); }
__device__ __forceinline__ float bf_hi(uint32_t w) { return __uint_as_float(w & 0xffff0000u); }
__device__ __forceinline__ uint32_t settag(uint32_t w, uint32_t tag) { return (w & ~1u) | tag; }
__device__ __forceinline__ float ex2(float x) { float y; asm("ex2.approx.ftz.f32 %0, %1;" : "=f"(y) : "f"(x)); return y; }
__device__ __forceinline__ float rcp(float x) { float y; asm("rcp.approx.ftz.f32 %0, %1;" : "=f"(y) : "f"(x)); return y; }
__device__ __forceinline__ float tanh_hw(float x) { float y; asm("tanh.approx.f32 %0, %1;" : "=f"(y) : "f"(x)); return y; }
__device__ __forceinline__ void stsm4(uint32_t addr, uint32_t a, uint32_t b, uint32_t c, uint32_t d) {
    asm volatile("stmatrix.sync.aligned.m8n8.x4.shared.b16 [%0], {%1,%2,%3,%4};" ::"r"(addr), "r"(a), "r"(b), "r"(c), "r"(d) : "memory");
}
__device__ __forceinline__ void fence_async() { asm volatile("fence.proxy.async.shared::cta;" ::: "memory"); }
__device__ __forceinline__ void bar_sync(int id, int n) { asm volatile("bar.sync %0, %1;" ::"r"(id), "r"(n) : "memory"); }
__device__ __forceinline__ void bar_arrive(int id, int n) { asm volatile("bar.arrive %0, %1;" ::"r"(id), "r"(n) : "memory"); }
__device__ __forceinline__ void wg_fence() { asm volatile("wgmma.fence.sync.aligned;" ::: "memory"); }
__device__ __forceinline__ void wg_commit() { asm volatile("wgmma.commit_group.sync.aligned;" ::: "memory"); }
template <int N> __device__ __forceinline__ void wg_wait() { asm volatile("wgmma.wait_group.sync.aligned %0;" ::"n"(N) : "memory"); }

constexpr uint32_t SB0 = 1024;
__host__ __device__ constexpr uint32_t dlo(uint32_t off, uint32_t lbo) { return ((SB0 + off) >> 4) | ((lbo >> 4) << 16); }
__host__ __device__ constexpr uint32_t dhi(uint32_t sbo, uint32_t sw) { return (sbo >> 4) | (sw << 30); }
__device__ __forceinline__ uint64_t dbase(uint32_t lo, uint32_t hi) { uint64_t d; asm volatile("mov.b64 %0, {%1, %2};" : "=l"(d) : "r"(lo), "r"(hi)); return d; }
#define BASE128(off, lbo, adj) dbase(dlo(off, lbo) + (adj), dhi(1024, 1))
#define BASE64(off, lbo, adj) dbase(dlo(off, lbo) + (adj), dhi(512, 2))

#define ACC4(d, o) "+f"(d[o]), "+f"(d[o + 1]), "+f"(d[o + 2]), "+f"(d[o + 3])
#define ACC28(d) ACC4(d, 0), ACC4(d, 4), ACC4(d, 8), ACC4(d, 12), ACC4(d, 16), ACC4(d, 20), ACC4(d, 24)
#define ACC32(d, o) ACC4(d, o), ACC4(d, o + 4), ACC4(d, o + 8), ACC4(d, o + 12), ACC4(d, o + 16), ACC4(d, o + 20), ACC4(d, o + 24), ACC4(d, o + 28)

template <int TB, uint64_t D>
__device__ __forceinline__ void mma_rs56(float* d, uint32_t a0, uint32_t a1, uint32_t a2, uint32_t a3, int sd, uint64_t base) {
    asm volatile("{ .reg .pred p; .reg .b64 db; setp.ne.b32 p, %32, 0; add.u64 db, %33, %34;\n"
                 "wgmma.mma_async.sync.aligned.m64n56k16.f32.bf16.bf16 "
                 "{%0,%1,%2,%3,%4,%5,%6,%7,%8,%9,%10,%11,%12,%13,%14,%15,%16,%17,%18,%19,%20,%21,%22,%23,%24,%25,%26,%27}, "
                 "{%28,%29,%30,%31}, db, p, 1, 1, %35; }\n"
                 : ACC28(d)
                 : "r"(a0), "r"(a1), "r"(a2), "r"(a3), "r"(sd), "l"(base), "n"(D), "n"(TB));
}
template <int TB, uint64_t D>
__device__ __forceinline__ void mma_rs64(float* d, uint32_t a0, uint32_t a1, uint32_t a2, uint32_t a3, int sd, uint64_t base) {
    asm volatile("{ .reg .pred p; .reg .b64 db; setp.ne.b32 p, %36, 0; add.u64 db, %37, %38;\n"
                 "wgmma.mma_async.sync.aligned.m64n64k16.f32.bf16.bf16 "
                 "{%0,%1,%2,%3,%4,%5,%6,%7,%8,%9,%10,%11,%12,%13,%14,%15,%16,%17,%18,%19,%20,%21,%22,%23,%24,%25,%26,%27,%28,%29,%30,%31}, "
                 "{%32,%33,%34,%35}, db, p, 1, 1, %39; }\n"
                 : ACC32(d, 0)
                 : "r"(a0), "r"(a1), "r"(a2), "r"(a3), "r"(sd), "l"(base), "n"(D), "n"(TB));
}
template <int TB, uint64_t D>
__device__ __forceinline__ void mma_rs128(float* d, uint32_t a0, uint32_t a1, uint32_t a2, uint32_t a3, int sd, uint64_t base) {
    asm volatile("{ .reg .pred p; .reg .b64 db; setp.ne.b32 p, %68, 0; add.u64 db, %69, %70;\n"
                 "wgmma.mma_async.sync.aligned.m64n128k16.f32.bf16.bf16 "
                 "{%0,%1,%2,%3,%4,%5,%6,%7,%8,%9,%10,%11,%12,%13,%14,%15,%16,%17,%18,%19,%20,%21,%22,%23,%24,%25,%26,%27,%28,%29,%30,%31,%32,%33,%34,%35,%36,%37,%38,%39,%40,%41,%42,%43,%44,%45,%46,%47,%48,%49,%50,%51,%52,%53,%54,%55,%56,%57,%58,%59,%60,%61,%62,%63}, "
                 "{%64,%65,%66,%67}, db, p, 1, 1, %71; }\n"
                 : ACC32(d, 0), ACC32(d, 32)
                 : "r"(a0), "r"(a1), "r"(a2), "r"(a3), "r"(sd), "l"(base), "n"(D), "n"(TB));
}
template <uint64_t DA, uint64_t DB>
__device__ __forceinline__ void mma_ss56_tt(float* d, int sd, uint64_t ba, uint64_t bb) {
    asm volatile("{ .reg .pred p; .reg .b64 da, db; setp.ne.b32 p, %28, 0; add.u64 da, %29, %31; add.u64 db, %30, %32;\n"
                 "wgmma.mma_async.sync.aligned.m64n56k16.f32.bf16.bf16 "
                 "{%0,%1,%2,%3,%4,%5,%6,%7,%8,%9,%10,%11,%12,%13,%14,%15,%16,%17,%18,%19,%20,%21,%22,%23,%24,%25,%26,%27}, "
                 "da, db, p, 1, 1, 1, 1; }\n"
                 : ACC28(d)
                 : "r"(sd), "l"(ba), "l"(bb), "n"(DA), "n"(DB));
}
template <int... I> struct Seq {};
template <class F, int... I> __device__ __forceinline__ void static_for_impl(F&& f, Seq<I...>) { (f(std::integral_constant<int, I>{}), ...); }
#define FOR7(...) static_for_impl([&](auto T_) { constexpr int t = decltype(T_)::value; __VA_ARGS__; }, Seq<0, 1, 2, 3, 4, 5, 6>{})
#define FOR8(...) static_for_impl([&](auto T_) { constexpr int t = decltype(T_)::value; __VA_ARGS__; }, Seq<0, 1, 2, 3, 4, 5, 6, 7>{})
#define FOR14(...) static_for_impl([&](auto T_) { constexpr int t = decltype(T_)::value; __VA_ARGS__; }, Seq<0, 1, 2, 3, 4, 5, 6, 7, 8, 9, 10, 11, 12, 13>{})

__device__ __forceinline__ int kblk(int p, int b) { return b == 0 ? p : b - (b <= p); }
__host__ __device__ constexpr int krow(int t) { return t < 3 ? 16 * t : (t < 6 ? 56 + 16 * (t - 3) : 48); }
#define AQ(A, b, t) ((t) < 3 ? A[2 * (b)][4 * (t)] : (t) < 6 ? A[2 * (b) + 1][4 * ((t) - 3)] : A[2 * (b)][12]), \
                    ((t) < 3 ? A[2 * (b)][4 * (t) + 1] : (t) < 6 ? A[2 * (b) + 1][4 * ((t) - 3) + 1] : A[2 * (b)][13]), \
                    ((t) < 3 ? A[2 * (b)][4 * (t) + 2] : (t) < 6 ? A[2 * (b) + 1][4 * ((t) - 3) + 2] : A[2 * (b) + 1][12]), \
                    ((t) < 3 ? A[2 * (b)][4 * (t) + 3] : (t) < 6 ? A[2 * (b) + 1][4 * ((t) - 3) + 3] : A[2 * (b) + 1][13])
#define D128(off, t) ((uint64_t)(((off) + krow(t) * 128) >> 4) + ((uint64_t)((t) == 6 ? (7168 - 1024) >> 4 : 0) << 32))
#define D64(off, t) ((uint64_t)(((off) + krow(t) * 64) >> 4) + ((uint64_t)((t) == 6 ? (3584 - 512) >> 4 : 0) << 32))

#define PL(k) (((k) - 3) * PLANE)
__device__ __forceinline__ void st_word(uint32_t* p, uint32_t v) { asm volatile("st.relaxed.gpu.global.u32 [%0], %1;" ::"l"(p), "r"(v) : "memory"); }
__device__ __forceinline__ uint32_t ld_word(const uint32_t* p) { uint32_t v; asm volatile("ld.relaxed.gpu.global.u32 %0, [%1];" : "=r"(v) : "l"(p) : "memory"); return v; }
__device__ __forceinline__ void tag_slice(uint32_t* w, uint32_t tag) { w[0] = settag(w[0], tag); w[4] = settag(w[4], tag); w[8] = settag(w[8], tag); w[12] = settag(w[12], tag); }
template <int O>
__device__ __forceinline__ void send_slice(uint4* dst, int lane, const uint32_t* w) {
    st_pkt<O>(dst, w[0], w[1], w[2], w[3]);
    st_pkt<O + 32>(dst, w[4], w[5], w[6], w[7]);
    st_pkt<O + 64>(dst, w[8], w[9], w[10], w[11]);
    asm volatile("{ .reg .b64 t; mov.b64 t, {%1,%2}; st.relaxed.gpu.global.b64 [%0+%3], t; }" ::"l"((char*)dst - lane * 8), "r"(w[12]), "r"(w[13]), "n"(16 * (O + 96)) : "memory");
}
struct Wide { unsigned __int128 q[3]; uint64_t h; };
__device__ __forceinline__ Wide widen(const uint32_t* w) {
    Wide r;
#pragma unroll
    for (int k = 0; k < 3; k++) asm volatile("mov.b128 %0, {%1,%2,%3,%4};" : "=q"(r.q[k]) : "r"(w[4 * k]), "r"(w[4 * k + 1]), "r"(w[4 * k + 2]), "r"(w[4 * k + 3]));
    asm volatile("mov.b64 %0, {%1,%2};" : "=l"(r.h) : "r"(w[12]), "r"(w[13]));
    return r;
}
template <int O>
__device__ __forceinline__ void send_wide(uint4* dst, int lane, const Wide& v) {
    asm volatile("st.relaxed.gpu.global.b128 [%0+%4], %1;\n st.relaxed.gpu.global.b128 [%0+%5], %2;\n st.relaxed.gpu.global.b128 [%0+%6], %3;"
                 ::"l"(dst), "q"(v.q[0]), "q"(v.q[1]), "q"(v.q[2]), "n"(16 * O), "n"(16 * (O + 32)), "n"(16 * (O + 64)) : "memory");
    asm volatile("st.relaxed.gpu.global.b64 [%0+%2], %1;" ::"l"((char*)dst - lane * 8), "l"(v.h), "n"(16 * (O + 96)) : "memory");
}
#define RW4(v, o) "+r"(v[o]), "+r"(v[(o) + 1]), "+r"(v[(o) + 2]), "+r"(v[(o) + 3])
#define RW2(v, o) "+r"(v[o]), "+r"(v[(o) + 1])
#define WR4(v, o) "=&r"(v[o]), "=&r"(v[(o) + 1]), "=&r"(v[(o) + 2]), "=&r"(v[(o) + 3])
#define LDP(a, b, c, d, addr, off) "ld.relaxed.gpu.global.b128 q, [" addr "+" off "];\n mov.b128 {" a "," b "," c "," d "}, q;\n"
#define LDH(a, b, addr, off) "ld.relaxed.gpu.global.b64 h, [" addr "+" off "];\n mov.b64 {" a "," b "}, h;\n"
#define VOTE_OK "and.b32 t, t, 1;\n setp.ne.u32 p, t, 0;\n vote.sync.any.pred p, p, 0xffffffff;\n @!p bra.uni DN;\n"
#define CHK(x, tag) "lop3.b32 t, " x ", " tag ", t, 0xBE;\n"
__device__ __forceinline__ void check_cnt(uint32_t v, const uint32_t* p, uint32_t target) {
    asm volatile("{ .reg .pred p; .reg .b32 n, t; mov.u32 n, 0; mov.u32 t, %2;\n LP:\n"
                 "sub.s32 t, t, %1;\n setp.lt.s32 p, t, 0;\n vote.sync.any.pred p, p, 0xffffffff;\n @!p bra.uni DN;\n ld.relaxed.gpu.global.u32 t, [%0];\n" SPIN_TAIL("7")
                 ::"l"(p), "r"(target), "r"(v) : "memory");
}
__device__ __forceinline__ void poll_cnt(const uint32_t* p, uint32_t target) {
    asm volatile("{ .reg .pred p; .reg .b32 n, t; mov.u32 n, 0;\n LP:\n"
                 "ld.relaxed.gpu.global.u32 t, [%0];\n sub.s32 t, t, %1;\n setp.lt.s32 p, t, 0;\n vote.sync.any.pred p, p, 0xffffffff;\n @!p bra.uni DN;\n" SPIN_TAIL("1")
                 ::"l"(p), "r"(target) : "memory");
}
template <int STR>
__device__ __forceinline__ void poll4_kv(uint32_t* v, const uint4* p, uint32_t tag) {
    asm volatile("{ .reg .pred p; .reg .b32 n, t; .reg .b128 q; mov.u32 n, 0;\n LP:\n"
                 LDP("%0", "%1", "%2", "%3", "%16", "0") LDP("%4", "%5", "%6", "%7", "%16", "%18")
                 LDP("%8", "%9", "%10", "%11", "%16", "%19") LDP("%12", "%13", "%14", "%15", "%16", "%20")
                 "xor.b32 t, %0, %17;\n" CHK("%4", "%17") CHK("%8", "%17") CHK("%12", "%17") VOTE_OK SPIN_TAIL("2")
                 : WR4(v, 0), WR4(v, 4), WR4(v, 8), WR4(v, 12)
                 : "l"(p), "r"(tag), "n"(16 * STR), "n"(32 * STR), "n"(48 * STR)
                 : "memory");
}
template <int B>
__device__ __forceinline__ void blk_load(uint32_t (&A)[8][14], const uint4* src, int lane) {
    ld_pkt<0>(&A[2 * B][0], src); ld_pkt<32>(&A[2 * B][4], src); ld_pkt<64>(&A[2 * B][8], src);
    ld_pkt<512>(&A[2 * B + 1][0], src); ld_pkt<544>(&A[2 * B + 1][4], src); ld_pkt<576>(&A[2 * B + 1][8], src);
    asm volatile("{ .reg .b64 h;\n" LDH("%0", "%1", "%4", "1536") LDH("%2", "%3", "%4", "9728") "}"
                 : "=&r"(A[2 * B][12]), "=&r"(A[2 * B][13]), "=&r"(A[2 * B + 1][12]), "=&r"(A[2 * B + 1][13])
                 : "l"((const char*)src - lane * 8) : "memory");
}
#define BLK_TEST "xor.b32 t, %0, %30;\n" CHK("%4", "%30") CHK("%8", "%30") CHK("%12", "%30") CHK("%16", "%30") CHK("%20", "%30") CHK("%24", "%30") CHK("%26", "%30") VOTE_OK
template <int B>
__device__ __forceinline__ void blk_check(uint32_t (&A)[8][14], const uint4* src, int lane, uint32_t tag) {
    asm volatile("{ .reg .pred p; .reg .b32 n, t; .reg .b128 q; .reg .b64 h, a8;\n" BLK_TEST
                 "mov.u32 n, 0;\n mad.wide.s32 a8, %29, -8, %28;\n LP:\n"
                 LDP("%0", "%1", "%2", "%3", "%28", "0") LDP("%4", "%5", "%6", "%7", "%28", "512") LDP("%8", "%9", "%10", "%11", "%28", "1024")
                 LDP("%12", "%13", "%14", "%15", "%28", "8192") LDP("%16", "%17", "%18", "%19", "%28", "8704") LDP("%20", "%21", "%22", "%23", "%28", "9216")
                 LDH("%24", "%25", "a8", "1536") LDH("%26", "%27", "a8", "9728") BLK_TEST SPIN_TAIL("3")
                 "\n and.b32 %0, %0, -2; and.b32 %4, %4, -2; and.b32 %8, %8, -2; and.b32 %12, %12, -2; and.b32 %16, %16, -2; and.b32 %20, %20, -2; and.b32 %24, %24, -2; and.b32 %26, %26, -2;"
                 : RW4(A[2 * B], 0), RW4(A[2 * B], 4), RW4(A[2 * B], 8), RW4(A[2 * B + 1], 0), RW4(A[2 * B + 1], 4), RW4(A[2 * B + 1], 8),
                   RW2(A[2 * B], 12), RW2(A[2 * B + 1], 12)
                 : "l"(src), "r"(lane), "r"(tag)
                 : "memory");
}
__device__ __forceinline__ void st_async4(uint32_t a, uint32_t x, uint32_t y, uint32_t z, uint32_t w, uint32_t bar) {
    asm volatile("st.async.weak.shared::cluster.mbarrier::complete_tx::bytes.v4.b32 [%0], {%1,%2,%3,%4}, [%5];" ::"r"(a), "r"(x), "r"(y), "r"(z), "r"(w), "r"(bar) : "memory");
}
__device__ __forceinline__ uint32_t mapa(uint32_t a, uint32_t cta) { uint32_t r; asm("mapa.shared::cluster.u32 %0, %1, %2;" : "=r"(r) : "r"(a), "r"(cta)); return r; }
__device__ __forceinline__ void stat_load(uint32_t* v, const uint4* p) { ld_pkt<0>(v, p); ld_pkt<512>(v + 4, p); }
__device__ __forceinline__ void stat_check(uint32_t* v, const uint4* p, uint32_t tag) {
    asm volatile("{ .reg .pred p; .reg .b32 n, t; .reg .b128 q; mov.u32 n, 0;\n LP:\n"
                 "xor.b32 t, %3, %9;\n" CHK("%7", "%9") VOTE_OK
                 LDP("%0", "%1", "%2", "%3", "%8", "0") LDP("%4", "%5", "%6", "%7", "%8", "8192") SPIN_TAIL("4")
                 : RW4(v, 0), RW4(v, 4) : "l"(p), "r"(tag) : "memory");
}
__device__ __forceinline__ uint32_t x_bits(const uint32_t* X) {
    uint32_t r;
    asm volatile("{ .reg .b32 a, b; prmt.b32 a, %1, %2, 0x0040; prmt.b32 b, %3, %4, 0x0040; prmt.b32 %0, a, b, 0x5410; }" : "=r"(r) : "r"(X[0]), "r"(X[4]), "r"(X[8]), "r"(X[12]));
    return r;
}
template <int O>
__device__ __forceinline__ void slice_load(uint32_t* v, const uint4* p, int lane) {
    ld_pkt<O>(v, p); ld_pkt<O + 32>(v + 4, p); ld_pkt<O + 64>(v + 8, p);
    asm volatile("{ .reg .b64 h;\n" LDH("%0", "%1", "%2", "%3") "}" : "=r"(v[12]), "=r"(v[13]) : "l"((const char*)p - lane * 8), "n"(16 * (O + 96)) : "memory");
}
#define SLICE_TEST "xor.b32 t, %0, %16;\n" CHK("%4", "%16") CHK("%8", "%16") CHK("%12", "%16") VOTE_OK
template <int O>
__device__ __forceinline__ void slice_check(uint32_t* v, const uint4* p, int lane, uint32_t tag) {
    asm volatile("{ .reg .pred p; .reg .b32 n, t; .reg .b128 q; .reg .b64 h;\n" SLICE_TEST "mov.u32 n, 0;\n LP:\n"
                 LDP("%0", "%1", "%2", "%3", "%14", "%17") LDP("%4", "%5", "%6", "%7", "%14", "%18") LDP("%8", "%9", "%10", "%11", "%14", "%19")
                 LDH("%12", "%13", "%15", "%20") SLICE_TEST SPIN_TAIL("5")
                 : RW4(v, 0), RW4(v, 4), RW4(v, 8), RW2(v, 12)
                 : "l"(p), "l"((const char*)p - lane * 8), "r"(tag), "n"(16 * O), "n"(16 * (O + 32)), "n"(16 * (O + 64)), "n"(16 * (O + 96))
                 : "memory");
}
__device__ __forceinline__ void x_fix(uint32_t* X, uint32_t bits) {
    X[0] = __byte_perm(X[0], bits, 0x3214); X[4] = __byte_perm(X[4], bits, 0x3215); X[8] = __byte_perm(X[8], bits, 0x3216); X[12] = __byte_perm(X[12], bits, 0x3217);
}
__device__ __forceinline__ void sts4(uint32_t a, uint32_t x, uint32_t y, uint32_t z, uint32_t w) {
    asm volatile("st.shared.v4.u32 [%0], {%1,%2,%3,%4};" ::"r"(a), "r"(x), "r"(y), "r"(z), "r"(w) : "memory");
}
__device__ __forceinline__ void lds4(uint32_t* v, uint32_t a) {
    asm volatile("ld.shared.v4.u32 {%0,%1,%2,%3}, [%4];" : "=r"(v[0]), "=r"(v[1]), "=r"(v[2]), "=r"(v[3]) : "r"(a) : "memory");
}
struct LnCoef { uint32_t hi, lo, sh; };
__device__ __forceinline__ LnCoef ln_coef(float sum, float sq) {
    sum += __shfl_xor_sync(0xffffffffu, sum, 1); sq += __shfl_xor_sync(0xffffffffu, sq, 1);
    sum += __shfl_xor_sync(0xffffffffu, sum, 2); sq += __shfl_xor_sync(0xffffffffu, sq, 2);
    const float mean = sum * (1.f / 448.f);
    const float var = fmaxf(fmaf(-mean, mean, sq * (1.f / 448.f)), 0.f);
    const float sc = rsqrtf(var + 1e-5f);
    LnCoef r;
    r.hi = pack2(sc, sc);
    const float lo = sc - bf_lo(r.hi), sh = -mean * sc;
    r.lo = pack2(lo, lo);
    r.sh = pack2(sh, sh);
    return r;
}
template <int B>
__device__ __forceinline__ void normalize(uint32_t (&A)[8][14], const LnCoef& c0, const LnCoef& c1) {
#pragma unroll
    for (int s = 2 * B; s < 2 * B + 2; s++)
#pragma unroll
        for (int i = 0; i < 14; i++) {
            const LnCoef& k = (i & 1) ? c1 : c0;
            asm("{ .reg .b32 t; fma.rn.bf16x2 t, %0, %2, %3; fma.rn.bf16x2 %0, %0, %1, t; }" : "+r"(A[s][i]) : "r"(k.hi), "r"(k.lo), "r"(k.sh));
        }
}
__device__ __forceinline__ void slice_stats(const uint32_t* w, float* st) {
    float a = 0.f, b = 0.f, p = 0.f, q = 0.f;
#pragma unroll
    for (int i = 0; i < 7; i++) {
        const float e0 = bf_lo(w[2 * i]), e1 = bf_hi(w[2 * i]), e2 = bf_lo(w[2 * i + 1]), e3 = bf_hi(w[2 * i + 1]);
        a += e0 + e1; b += e2 + e3;
        p = fmaf(e0, e0, p); p = fmaf(e1, e1, p); q = fmaf(e2, e2, q); q = fmaf(e3, e3, q);
    }
    a += __shfl_xor_sync(0xffffffffu, a, 1); p += __shfl_xor_sync(0xffffffffu, p, 1); b += __shfl_xor_sync(0xffffffffu, b, 1); q += __shfl_xor_sync(0xffffffffu, q, 1);
    a += __shfl_xor_sync(0xffffffffu, a, 2); p += __shfl_xor_sync(0xffffffffu, p, 2); b += __shfl_xor_sync(0xffffffffu, b, 2); q += __shfl_xor_sync(0xffffffffu, q, 2);
    st[0] = a; st[1] = p; st[2] = b; st[3] = q;
}
__device__ __forceinline__ void dual_softmax(const float* p, uint32_t* out) {
    constexpr float L = 1.4426950408889634f;
#pragma unroll
    for (int r = 0; r < 2; r++) {
        float mx = fmaxf(p[2 * r], p[2 * r + 1]), mn = fminf(p[2 * r], p[2 * r + 1]);
#pragma unroll
        for (int i = 1; i < 7; i++) {
            mx = fmaxf(mx, fmaxf(p[4 * i + 2 * r], p[4 * i + 2 * r + 1]));
            mn = fminf(mn, fminf(p[4 * i + 2 * r], p[4 * i + 2 * r + 1]));
        }
        mx = fmaxf(mx, __shfl_xor_sync(0xffffffffu, mx, 1));
        mn = fminf(mn, __shfl_xor_sync(0xffffffffu, mn, 1));
        const float bx = -mx * L, bn = mn * L;
        float ep[14], en[14], sp = 0.f, sn = 0.f;
#pragma unroll
        for (int i = 0; i < 14; i++) {
            const float v = p[4 * (i >> 1) + 2 * r + (i & 1)];
            ep[i] = ex2(fmaf(v, L, bx));
            en[i] = ex2(fmaf(v, -L, bn));
            sp += ep[i]; sn += en[i];
        }
        sp += __shfl_xor_sync(0xffffffffu, sp, 1);
        sn += __shfl_xor_sync(0xffffffffu, sn, 1);
        const float ip = rcp(sp), in = rcp(sn);
#pragma unroll
        for (int i = 0; i < 7; i++) {
            out[4 * i + r] = pack2(ep[2 * i] * ip, ep[2 * i + 1] * ip);
            out[4 * i + 2 + r] = pack2(en[2 * i] * in, en[2 * i + 1] * in);
        }
    }
}
__device__ __forceinline__ float geglu(float g, float u) {
    const float t = tanh_hw(g * fmaf(g * g, 0.7978845608028654f * 0.044715f, 0.7978845608028654f));
    const float gu = g * u;
    return fmaf(t, gu, gu);
}
__device__ __forceinline__ void phi_gemm(const float* t, float* p) {
    uint32_t w[14];
#pragma unroll
    for (int i = 0; i < 14; i++) w[i] = pack2(t[2 * i], t[2 * i + 1]);
    const uint64_t db = BASE128(OFF_WPHI, 16, 0);
    wg_fence();
    mma_rs56<0, 0>(p, w[0], w[1], w[2], w[3], 0, db);
    mma_rs56<0, 2>(p, w[4], w[5], w[6], w[7], 1, db);
    mma_rs56<0, 4>(p, w[8], w[9], w[10], w[11], 1, db);
    mma_rs56<0, 6>(p, w[12], w[13], 0u, 0u, 1, db);
    wg_commit();
    wg_wait<0>();
}

}

#define BAR(i) (bars + 8 * (i))
#define R_WAIT() mbar_wait(BAR(slot), ph)
#define WSUM(i)
#define R_ADJ (slot * (STAGE >> 4))
#define R_NEXT() do { eb2 = eb1; eb1 = BAR(B_EMPTY + slot); if (++slot == NST) { slot = 0; ph ^= 1; } } while (0)
#define R_RELEASE(k) do { if (lane == 0) mbar_arrive((k) == 1 ? eb1 : eb2); } while (0)
#define PUSH_BEGIN() do { mbar_wait(BAR(B_ACK + wgi), ackph); ackph ^= 1; } while (0)
#define PUSH_ACK() do { __syncwarp(); if (lane == 0) asm volatile("mbarrier.arrive.shared::cluster.b64 _, [%0];" ::"r"(mapa(BAR(B_ACK + wgi), hr ^ 1)) : "memory"); } while (0)

__global__ void __cluster_dims__(2, 1, 1) __launch_bounds__(384, 1)
fused_kernel(Scratch* const sc, const __nv_bfloat16* __restrict__ x_in, const __nv_bfloat16* __restrict__ w_phi, const int trips,
             const __nv_bfloat16* __restrict__ wg, const __nv_bfloat16* __restrict__ wu, const __nv_bfloat16* __restrict__ wd,
             const __grid_constant__ Maps maps) {
    extern __shared__ __align__(1024) unsigned char smem_raw[];
    const uint32_t sb = s2u(smem_raw);
    const uint32_t bars = sb + OFF_BAR;
    const int wgi = __shfl_sync(0xffffffffu, threadIdx.x >> 7, 0);
    const int hr = blockIdx.x & 1, ck = blockIdx.x >> 1;
    const int gp = (ck - 4) & 7, q7 = ((ck - 36) * 37) >> 8;
    const int pr = __shfl_sync(0xffffffffu, ck < 4 ? ck : (ck < 36 ? (ck - 4) >> 3 : q7), 0);
    const int tile = __shfl_sync(0xffffffffu, ck < 4 ? 0 : (ck < 36 ? (gp ? 2 * gp : 1) : 2 * (ck - 36 - 7 * q7) + 3), 0);
    const int sl = 2 * pr + hr;
    STAMP(0);
    GSTAMP(60);
    if (threadIdx.x == 256) {
#pragma unroll
        for (int i = 0; i < NST; i++) mbar_init(BAR(i), 1);
        asm volatile("fence.mbarrier_init.release.cluster;" ::: "memory");
    }
    if (threadIdx.x == 288) {
        if ((sb & 0x3FFFF) != SB0) asm volatile("trap;");
#pragma unroll
        for (int i = NST; i < B_COUNT; i++) mbar_init(BAR(i), i >= B_ACK ? 4 : (i < B_RECV || i == B_LATE ? 8 : 1));
        asm volatile("fence.mbarrier_init.release.cluster;" ::: "memory");
    }
    __syncwarp();
    asm volatile("barrier.cluster.arrive.relaxed.aligned;" ::: "memory");

    if (wgi == 2) {
        asm volatile("setmaxnreg.dec.sync.aligned.u32 40;");
        const int t128 = fresh_tid() & 127, w = __shfl_sync(0xffffffffu, t128 >> 5, 0), lane = t128 & 31;
        uint32_t e0[2] = {0, 0}, e1[2] = {0, 0}, cw_target = 0, kseq;
        if (w == 0) {
#pragma unroll 1
            for (int n = 0; n < NST; n++) {
                const uint32_t dst = sb + n * STAGE, fb = BAR(n);
                asm volatile(ELECT "mbarrier.arrive.expect_tx.shared::cta.b64 _, [%0], %1; }" ::"r"(fb), "r"(n < 2 ? 2 * STAGE : STAGE) : "memory");
                if (n < 2) {
                    tma3x(sb + OFF_H + n * STAGE, &maps.x, tile * 128 + n * 64, fb);
                    tma3x(dst, &maps.x, tile * 128 + n * 64 + 32, fb);
                } else {
                    if (n == 3) mbar_wait(BAR(1), 0);
                    const int c0 = (n < 4 ? 448 : 896) + 56 * sl, r0 = 224 * (n & 1);
                    tma2d(dst, &maps.qkv, c0, r0, fb);
                    tma2d(dst + HALF, &maps.qkv, c0, r0 + 112, fb);
                }
            }
            asm volatile("barrier.cluster.wait.aligned;" ::: "memory");
            kseq = ld_word(g_c1 + (sl * 8 * 16 + tile) * 32);
            cw_target = (ld_word(g_cw + sl * 32) & ~15u) + 16;
#pragma unroll 1
            for (int k = 0; k < 2; k++) {
                const int n = t128 + 32 * k;
                int m = n - 2 - (n > PACK);
                const bool packed = m >= 30 ? (m < 38 || m >= 52) : m >= 22;
                if (m >= 30) m -= 30;
                if (n == PACK) m = tile < 8 ? tile : tile + 14;
                const int rot = n < 8 ? 0 : pr;
                const int ra = 112 * kblk(rot, m & 3), rb = 112 * kblk(rot, 2 * m & 3), rc = 112 * kblk(rot, (2 * m + 1) & 3);
                int kind = 0, m0, m1, c0, c1, r0, r1;
                if (m < 8) { m0 = m1 = m < 6 ? 1 : 2; c0 = c1 = (m < 2 ? 448 : (m < 4 ? 896 : 0)) + 56 * sl; r0 = rb; r1 = rc; }
                else if (m < 20) { m0 = 3; m1 = 4; c0 = c1 = 224 * sl + 32 * hr + 64 * ((m - 8) >> 2); r0 = r1 = ra; }
                else if (m < 22) { kind = 2; m0 = 5; m1 = 6; c0 = c1 = 224 * sl + (hr ? 0 : 192); r0 = rb; r1 = rc; }
                else { m0 = m1 = 7; c0 = c1 = 56 * (2 * ((pr + (m >> 1) - 10) & 3) + hr); r0 = 224 * (sl ^ (m & 1)); r1 = r0 + 112; }
                if (packed) { kind = 1; r0 = sl * 16 + (m < 8 ? m : m - 14); r1 = 0; }
                e0[0] = e0[1]; e1[0] = e1[1];
                e0[1] = kind | (m0 << 2) | (m1 << 6) | (c0 << 10) | (c1 << 21);
                e1[1] = r0 | (r1 << 16);
            }
        } else {
            const int j = t128 - 32;
            kseq = ld_word(g_c1 + (sl * 8 * 16 + tile) * 32);
            asm volatile("barrier.cluster.wait.aligned;" ::: "memory");
            uint2 wv[7];
            const int k = j < 56 ? j : 55, hh = k >= 28;
#pragma unroll
            for (int i = 0; i < 7; i++) wv[i] = __ldg(reinterpret_cast<const uint2*>(w_phi + (sl * 56 + k) * 28) + i);
#pragma unroll 1
            for (int i = j; i < 7168 / 16; i += 96) sts4(sb + OFF_WPHI + i * 16, 0, 0, 0, 0);
            bar_sync(5, 96);
            if (j < 56) {
                uint32_t a4[4];
#pragma unroll
                for (int q = 0; q < 4; q++) a4[q] = sb + OFF_WPHI + (4 * hh + q) * 128 + ((((k >> 3) ^ (4 * hh + q)) & 7) << 4) + (k & 7) * 2;
                FOR14(const uint32_t v = (t & 1) ? wv[t >> 1].y : wv[t >> 1].x;
                      asm volatile("{ .reg .b16 l, h; mov.b32 {l, h}, %2; st.shared.u16 [%0+%3], l; st.shared.u16 [%1+%3], h; }"
                                   ::"r"(a4[t >= 7 ? 2 : 0]), "r"(a4[t >= 7 ? 3 : 1]), "r"(v), "n"((t % 7) * 1024) : "memory"));
            }
            __syncwarp();
            fence_async();
            kseq = __shfl_sync(0xffffffffu, kseq, 0);
            bar_arrive(1, 224);
            bar_arrive(9, 224);
        }
        kseq = __shfl_sync(0xffffffffu, kseq, 0);
        int slot = 0, ph = 0, n = NST;
#pragma unroll 1
        for (int layer = 0; layer < 3; layer++) {
            if (w == 0) {
                const int nend = layer == 0 ? 11 : (layer == 1 ? 42 : 63);
#pragma unroll 1
                for (; n < nend; n++) {
                const uint32_t w0 = __shfl_sync(0xffffffffu, n < 32 ? e0[0] : e0[1], n & 31), w1 = __shfl_sync(0xffffffffu, n < 32 ? e1[0] : e1[1], n & 31);
                const uint32_t dst = sb + slot * STAGE, fb = BAR(n == PACK ? B_PACK : slot);
                const CUtensorMap* m0 = &maps.x + ((w0 >> 2) & 15);
                const CUtensorMap* m1 = &maps.x + ((w0 >> 6) & 15);
                const int c0 = (w0 >> 10) & 2047, c1 = w0 >> 21, r0 = w1 & 0xffff, r1 = w1 >> 16;
                if (n == 25) {
                    int it = 0;
                    uint32_t v;
                    do { asm volatile("ld.acquire.gpu.global.u32 %0, [%1];" : "=r"(v) : "l"(g_cw + sl * 32) : "memory"); } while ((int)(v - cw_target) < 0 && ++it < 0x400000);
                    asm volatile("fence.proxy.async.global;" ::: "memory");
                    __syncwarp();
                }
                mbar_wait(BAR(B_EMPTY + slot), ph);
                __syncwarp();
                asm volatile(ELECT "mbarrier.arrive.expect_tx.shared::cta.b64 _, [%0], %1; }" ::"r"(fb), "r"(STAGE) : "memory");
                if ((w0 & 3) == 0) {
                    tma2d(dst, m0, c0, r0, fb);
                    tma2d(dst + HALF, m1, c1, r1, fb);
                } else if (w0 & 1) {
                    asm volatile(ELECT "cp.async.bulk.shared::cluster.global.mbarrier::complete_tx::bytes [%0], [%1], %2, [%3]; }"
                                 ::"r"(dst), "l"(reinterpret_cast<const char*>(g_wp) + (size_t)r0 * STAGE), "r"(STAGE), "r"(fb) : "memory");
                } else {
                    tma2d(dst, m0, c0, r0, fb); tma2d(dst + 7168, m0, c0, r1, fb);
                    tma2d(dst + HALF, m1, c0, r0, fb); tma2d(dst + HALF + 7168, m1, c0, r1, fb);
                }
                if (n == PFN) {
                    const int b = blockIdx.x;
                    asm volatile(ELECT "cp.async.bulk.prefetch.L2.global [%0], %1; }" ::"l"(wg + b * 6272), "r"(12544) : "memory");
                    asm volatile(ELECT "cp.async.bulk.prefetch.L2.global [%0], %1; }" ::"l"(wu + b * 6272), "r"(12544) : "memory");
                    asm volatile(ELECT "cp.async.bulk.prefetch.L2.global [%0], %1; }" ::"l"(wd + b * 6272), "r"(12544) : "memory");
                }
                if (n == PACK) asm volatile(ELECT "mbarrier.arrive.shared::cta.b64 _, [%0]; }" ::"r"(BAR(slot)) : "memory");
                if (++slot == NST) { slot = 0; ph ^= 1; }
                }
            } else if (w == 1 && layer == 1) {
                constexpr int ps = PACK % NST;
                mbar_wait(BAR(B_PACK), 0);
                asm volatile("{ .reg .pred e; elect.sync _|e, 0xffffffff;\n"
                             "@e cp.async.bulk.global.shared::cta.bulk_group [%0], [%1], %2;\n"
                             "@e cp.async.bulk.commit_group;\n"
                             "@e cp.async.bulk.wait_group.read 0;\n"
                             "@e mbarrier.arrive.shared::cta.b64 _, [%3], 8;\n"
                             "@e cp.async.bulk.wait_group 0;\n"
                             "@e fence.proxy.async.global;\n"
                             "@e red.release.gpu.global.add.u32 [%4], 1; }"
                             ::"l"(reinterpret_cast<char*>(g_wp) + (size_t)(sl * 16 + tile) * STAGE), "r"(sb + ps * STAGE), "r"(STAGE), "r"(BAR(B_EMPTY + ps)), "l"(g_cw + sl * 32) : "memory");
                __syncwarp();
            }
            if (layer < 2) {
            const uint32_t tag = layer ^ 1;
            kseq++;
            bar_sync(7, 384);
            ASTAMP(0);
            if (tile < 15) {
                const int sq = lane >> 3, pk = 8 * w + (lane & (tile == 14 ? 3 : 7));
                uint32_t v[16];
                if (layer == 0) poll_cnt(g_c1 + ((sl * 8 + (w >> 1) * 4 + (tile >> 2)) * 16 + (lane & 15)) * 32, kseq);
                ASTAMP(1);
                poll4_kv<32>(v, g_kv1 + ((sl * 16 + tile) * 16 + 4 * sq) * 32 + pk, tag);
#pragma unroll
                for (int k = 0; k < 4; k++) {
                    float lo = (bf_lo(v[k]) + bf_lo(v[4 + k])) + (bf_lo(v[8 + k]) + bf_lo(v[12 + k]));
                    float hi = (bf_hi(v[k]) + bf_hi(v[4 + k])) + (bf_hi(v[8 + k]) + bf_hi(v[12 + k]));
                    lo += __shfl_xor_sync(0xffffffffu, lo, 8); hi += __shfl_xor_sync(0xffffffffu, hi, 8);
                    lo += __shfl_xor_sync(0xffffffffu, lo, 16); hi += __shfl_xor_sync(0xffffffffu, hi, 16);
                    v[k] = pack2(lo, hi);
                }
                if (sq == 0) st_pkt<0>(g_kv2 + sl * 512 + 32 * tile + pk, settag(v[0], tag), v[1], v[2], v[3]);
            }
            ASTAMP(2);
            {
                const int item = t128 < 112 ? t128 : 112 + (t128 & 3), d = item >> 1;
                const int cc = t128 < 112 ? 2 * (d >= 28) + (item & 1) : item - 112;
                const int r = t128 < 112 ? d : 56 + (cc >> 1) + 2 * ((t128 - 112) >> 2);
                uint32_t ra = sb + OFF_KVB + r * 128 + 4 * cc, rx = (r & 7) << 4;
                asm volatile("" : "+r"(ra), "+r"(rx));
                FOR14(asm volatile("st.shared.u32 [%0+%2], %1;" ::"r"((ra ^ 8) + (((t & 7) << 4) ^ rx)), "r"(0), "n"((t >> 3) * 8192) : "memory"));
                uint32_t v[16];
                asm volatile("" : "+r"(ra), "+r"(rx));
                poll4_kv<8>(v, g_kv2 + sl * 512 + (item >> 3) * 32 + (item & 7), tag);
                FOR14(asm volatile("st.shared.u32 [%0+%2], %1;" ::"r"(ra + (((t & 7) << 4) ^ rx)), "r"(v[t < 7 ? t : t + 1]), "n"((t >> 3) * 8192) : "memory"));
                fence_async();
            }
            bar_arrive(3, 384);
            ASTAMP(3);
            }
        }
    } else {
        asm volatile("setmaxnreg.inc.sync.aligned.u32 232;");
        int lane = fresh_tid() & 31, prf = pr;
#define pr prf
#define g (lane >> 2)
#define c (lane & 3)
#define t128 (w * 32 + lane)
        const int wu = __shfl_sync(0xffffffffu, fresh_tid() >> 5, 0), w = wu & 3;
        const uint32_t xoff = __shfl_sync(0xffffffffu, (3 * PLANE + ((tile * 2 + wgi) * 8) * 512 + w * 128) * 16, 0);
        char* xu = reinterpret_cast<char*>(g_ex) + xoff;
#define FRESH() asm volatile("" : "+l"(xu), "+r"(lane), "+r"(prf))
#define xp0 (reinterpret_cast<uint4*>(xu) + lane)
        const uint32_t hbuf = sb + OFF_H + wgi * STAGE;
        uint32_t slot = 0, ph = 0, eb1 = 0, eb2 = 0, ackph = 0, rcvph = 0, gatph = 0, swp = 0;
        uint32_t ppid = 6;
#define cx(s) (reinterpret_cast<uint32_t*>(reinterpret_cast<uint4*>(xu) + PL(1) + 112 + (s) * 512))
#define stp (reinterpret_cast<uint4*>(xu) + g + PL(0) + 112)
        uint32_t seq = ld_word(cx(sl));
        uint32_t kseq = ld_word(g_c1 + ((sl * 8 + wu) * 16 + tile) * 32);
        uint32_t stag = ld_word(reinterpret_cast<const uint32_t*>(stp + sl * 512) + 3) & 1;
        asm volatile("barrier.cluster.wait.aligned;" ::: "memory");
        STAMP(1);
        uint32_t X[14];
        const uint32_t x0row = (w < 2 ? hbuf : sb + wgi * STAGE) + ((w & 1) * 16 + (lane & 15)) * 128;
        mbar_wait(BAR(wgi), 0);
        STAMP(51);
#pragma unroll
        for (int j = 0; j < 4; j++) {
            const int G = 7 * sl + min(2 * j + (lane >> 4), 6);
            uint32_t q2, q3;
            asm volatile("ldmatrix.sync.aligned.m8n8.x4.shared.b16 {%0,%1,%2,%3}, [%4];" : "=r"(X[4 * j]), "=r"(X[4 * j + 1]), "=r"(q2), "=r"(q3)
                         : "r"(x0row + (G >> 3) * 4096 + (((G ^ lane) & 7) << 4)) : "memory");
            if (j < 3) { X[(4 * j + 2) % 14] = q2; X[(4 * j + 3) % 14] = q3; }
        }
#define PUSH_SLICE(W)                                                                          \
    {                                                                                          \
        if (t128 == 0) mbar_expect_tx(BAR(B_RECV + wgi), 7168);                                \
        PUSH_BEGIN();                                                                          \
        const uint32_t ra = mapa(hbuf + 24576 + t128 * 16, hr ^ 1), rb = mapa(sb + OFF_XR + wgi * 3072, hr ^ 1), rbar = mapa(BAR(B_RECV + wgi), hr ^ 1); \
        st_async4(ra, W[0], W[1], W[2], W[3], rbar);                                           \
        st_async4(ra + 2048, W[4], W[5], W[6], W[7], rbar);                                    \
        st_async4(rb + t128 * 16, W[8], W[9], W[10], W[11], rbar);                             \
        asm volatile("st.async.weak.shared::cluster.mbarrier::complete_tx::bytes.v2.b32 [%0], {%1,%2}, [%3];" ::"r"(rb + 2048 + t128 * 8), "r"(W[12]), "r"(W[13]), "r"(rbar) : "memory"); \
    }
#define PULL_SLICE(W)                                                                          \
    {                                                                                          \
        uint32_t t0, t1;                                                                       \
        mbar_wait(BAR(B_RECV + wgi), rcvph);                                                   \
        rcvph ^= 1;                                                                            \
        lds4(&A[1][0], hbuf + 24576 + t128 * 16);                                              \
        lds4(&A[1][4], hbuf + 26624 + t128 * 16);                                              \
        lds4(&A[1][8], sb + OFF_XR + wgi * 3072 + t128 * 16);                                  \
        asm volatile("ld.shared.v2.u32 {%0,%1}, [%2];" : "=r"(t0), "=r"(t1) : "r"(sb + OFF_XR + wgi * 3072 + 2048 + t128 * 8) : "memory"); \
        _Pragma("unroll") for (int i = 0; i < 12; i++) A[0][i] = (i & 3) ? W[i] : W[i] & ~1u;  \
        A[1][0] &= ~1u; A[1][4] &= ~1u; A[1][8] &= ~1u;                                        \
        A[0][12] = (hr ? t0 : W[12]) & ~1u; A[0][13] = hr ? t1 : W[13];                        \
        A[1][12] = (hr ? W[12] : t0) & ~1u; A[1][13] = hr ? W[13] : t1;                        \
        asm volatile("" : RW4(A[0], 0), RW4(A[0], 4), RW4(A[0], 8), RW2(A[0], 12), RW4(A[1], 0), RW4(A[1], 4), RW4(A[1], 8), RW2(A[1], 12)); \
        swp = hr * 448;                                                                        \
    }
#define SWB(b, t, db, sh) ((b) == 0 && (t) < 6 ? ((t) < 3 ? db##p : db##m) : db)
#define DECL_DB(b, MK, lbo, sh) const uint64_t db = MK(0, lbo, R_ADJ), dbp = (b) == 0 ? MK(0, lbo, R_ADJ + (swp >> (sh))) : db, dbm = (b) == 0 ? MK(0, lbo, R_ADJ - (swp >> (sh))) : db;
#define PPB 2
#define PP_WAIT() if (wgi == 1) { bar_sync(ppid, 256); ppid ^= 14; }
#define PP_GO() if (wgi == 0) { bar_arrive(ppid, 256); ppid ^= 14; }
#define GAT_DST(B, s2) ((B) == 1 ? hbuf + w * 3584 + (s2) * 1792 : ((s2) ? sb + OFF_KVB + wgi * 8192 : hbuf + 14336) + w * 1792)
#define GAT_ISSUE(B, base)                                                                     \
    {                                                                                          \
        const char* gs = xu + ((base) + kblk(pr, B) * 1024) * 16;                              \
        asm volatile("{ .reg .pred e; elect.sync _|e, 0xffffffff;\n"                           \
                     "@e mbarrier.arrive.expect_tx.shared::cta.b64 _, [%3], 3584;\n"           \
                     "@e cp.async.bulk.shared::cluster.global.mbarrier::complete_tx::bytes [%0], [%2], 1792, [%3];\n" \
                     "@e cp.async.bulk.shared::cluster.global.mbarrier::complete_tx::bytes [%1], [%2+8192], 1792, [%3]; }" \
                     ::"r"(GAT_DST(B, 0)), "r"(GAT_DST(B, 1)), "l"(gs), "r"(BAR(B_GAT + wu * 2 + ((B) >> 1))) : "memory"); \
        __syncwarp();                                                                          \
    }
#define GAT_FETCH(B)                                                                           \
    {                                                                                          \
        mbar_wait(BAR(B_GAT + wu * 2 + ((B) >> 1)), (gatph >> (B)) & 1);                          \
        gatph ^= 1 << (B);                                                                     \
        _Pragma("unroll") for (int s2 = 0; s2 < 2; s2++) {                                     \
            const uint32_t ga = GAT_DST(B, s2) + lane * 16;                                    \
            lds4(&A[2 * (B) + s2][0], ga); lds4(&A[2 * (B) + s2][4], ga + 512); lds4(&A[2 * (B) + s2][8], ga + 1024); \
            asm volatile("ld.shared.v2.u32 {%0,%1}, [%2];" : "=r"(A[2 * (B) + s2][12]), "=r"(A[2 * (B) + s2][13]) : "r"(ga - lane * 8 + 1536) : "memory"); \
        }                                                                                      \
    }
#define LATE_ARRIVE() do { if (lane == 0) mbar_arrive(BAR(B_LATE)); } while (0)
#define LATE_WAIT() do { mbar_wait(BAR(B_LATE), gatph & 1); gatph ^= 1; } while (0)
#define PT 3
#define PREP(b, t, remote)                                                                     \
    if constexpr ((b) < 3 && (t) == PT) {                                                      \
        wg_commit();                                                                           \
        STAMP(74 + 6 * (step & 1) + 2 * (b));                                                  \
        if (remote) {                                                                          \
            if constexpr ((b) == 0) { blk_load<2>(A, BLK(xsrc, 2), lane); if (XG3 == 3) blk_load<3>(A, BLK(xsrc, 3), lane); GAT_FETCH(1) }       \
            blk_check<((b) + 1) & 3>(A, BLK(xsrc, (b) + 1), lane, xtag);                       \
            if constexpr ((b) == 0 && XG3 == 0) blk_load<3>(A, BLK(xsrc, 3), lane); \
            if constexpr ((b) == 0 && XG3 == 2) GAT_ISSUE(3, (step & 1) ? PL(2) : PL(0))                        \
        }                                                                                      \
        STAMP(75 + 6 * (step & 1) + 2 * (b));                                                  \
        normalize<((b) + 1) & 3>(A, k0, k1);                                                   \
        asm volatile("" : RW4(A[(2 * (b) + 2) & 7], 0), RW4(A[(2 * (b) + 2) & 7], 4), RW4(A[(2 * (b) + 2) & 7], 8), RW2(A[(2 * (b) + 2) & 7], 12), \
                          RW4(A[(2 * (b) + 3) & 7], 0), RW4(A[(2 * (b) + 3) & 7], 4), RW4(A[(2 * (b) + 3) & 7], 8), RW2(A[(2 * (b) + 3) & 7], 12)); \
        wg_fence();                                                                            \
    }
#define X0_BLOCK(b)                                                                            \
    { const int rr = lane & 7, hi = lane >> 4;                                                 \
    const uint32_t rowa = (w < 2 ? hbuf : sb + wgi * STAGE) + ((w & 1) * 16 + (lane & 15)) * 128; \
    FOR7(constexpr int G = 14 * (b) + (t < 3 ? 2 * t : (t < 6 ? 2 * t + 1 : 6));               \
         uint32_t q0, q1, q2, q3;                                                              \
         const uint32_t ad = t < 6 ? rowa + (((((G & 7) + hi) ^ rr) & 7) << 4) + ((G & 7) == 7 ? hi * 4096 : 0) : rowa + ((G + 7 * hi) >> 3) * 4096 + ((((G + 7 * hi) ^ rr) & 7) << 4); \
         asm volatile("ldmatrix.sync.aligned.m8n8.x4.shared.b16 {%0,%1,%2,%3}, [%4+%5];" : "=r"(q0), "=r"(q1), "=r"(q2), "=r"(q3) \
                      : "r"(ad), "n"(t < 6 ? (G >> 3) * 4096 : 0) : "memory");                 \
         if (t < 3) { A[2 * (b)][4 * t] = q0; A[2 * (b)][4 * t + 1] = q1; A[2 * (b)][4 * t + 2] = q2; A[2 * (b)][4 * t + 3] = q3; } \
         else if (t < 6) { A[2 * (b) + 1][(4 * t - 12) & 15] = q0; A[2 * (b) + 1][((4 * t - 12) & 15) + 1] = q1; A[2 * (b) + 1][((4 * t - 12) & 15) + 2] = q2; A[2 * (b) + 1][((4 * t - 12) & 15) + 3] = q3; } \
         else { A[2 * (b)][12] = q0; A[2 * (b)][13] = q1; A[2 * (b) + 1][12] = q2; A[2 * (b) + 1][13] = q3; }); }
#define BLK(base, b) ((base) + kblk(pr, b) * 1024)

#pragma unroll 1
        for (int step = 0; step < 4; step++) {
            FRESH();
            const uint32_t tag = (step >> 1) ^ 1;
            const int so = (step >> 1) * 24 + (step & 1) * 12;
            (void)so;
            uint32_t A[8][14];
            uint4* const xsrc = xp0 + ((step & 1) ? PL(2) : PL(0));
            const uint32_t xtag = (step & 1) ? tag : ((seq >> 3) & 1) ^ 1;
            uint32_t xbits;
            {
                float st[4];
                if ((PFI & 4) && step) PUSH_SLICE(X)
                slice_stats(X, st);
                stag ^= 1;
                xbits = x_bits(X);
                tag_slice(X, xtag);
                if (step) {
                    if (PFI & 1) PUSH_SLICE(X)
                    send_slice<0>(xsrc + sl * 512, lane, X);
                }
                if (c == 0) st_pkt<0>(stp + sl * 512, __float_as_uint(st[0]), __float_as_uint(st[1]), __float_as_uint(st[2]), settag(__float_as_uint(st[3]), stag));
            }
            STAMP(2 + so);
            uint32_t sv[8];
            if (step == 0) {
                X0_BLOCK(0) X0_BLOCK(1) X0_BLOCK(2) X0_BLOCK(3)
                mbar_wait(BAR(wgi ^ 1), 0);
                R_NEXT();
                R_NEXT();
                R_RELEASE(2);
                stat_load(sv, stp + c * 1024);
                stat_check(sv, stp + c * 1024, stag);
                STAMP(52 + step);
            } else {
                kill<14>(A[2]); kill<14>(A[3]); kill<14>(A[4]); kill<14>(A[5]); kill<14>(A[6]); kill<14>(A[7]);
                if (!(PFI & 5)) PUSH_SLICE(X)
                stat_load(sv, stp + c * 1024);
                PULL_SLICE(X)
                stat_check(sv, stp + c * 1024, stag);
                STAMP(52 + step);
                GAT_ISSUE(1, (step & 1) ? PL(2) : PL(0))
                if (XG3 == 1) GAT_ISSUE(3, (step & 1) ? PL(2) : PL(0))
            }
            LnCoef k0, k1;
            {
                k0 = ln_coef(__uint_as_float(sv[0]) + __uint_as_float(sv[4]), __uint_as_float(sv[1]) + __uint_as_float(sv[5]));
                k1 = ln_coef(__uint_as_float(sv[2]) + __uint_as_float(sv[6]), __uint_as_float(sv[3] & ~1u) + __uint_as_float(sv[7] & ~1u));
            }
            STAMP(3 + so);
            GSTAMP(70 + step);

            if ((step & 1) == 0) {
                float tq[28];
#define K_BLOCK(b)                                                                            \
    if ((b) == 1) R_RELEASE(1);                                                               \
    if ((b) == 2 + XT) PUSH_ACK();                                                            \
    if ((b) == 2 && XT && step) GAT_FETCH(3)                                                  \
    if ((b) == 3) { wg_wait<2>(); R_RELEASE(1); }                                             \
    if (((b) & 1) == 0) R_WAIT();                                                             \
    { DECL_DB(b, BASE128, 16, 0)                                                              \
    wg_fence();                                                                               \
    FOR7(mma_rs56<1, D128(((b) & 1) * HALF, t)>(tq, AQ(A, b, t), (b) + t > 0, SWB(b, t, db, 0)); \
         PREP(b, t, step)); }                                                                 \
    wg_commit();                                                                              \
    if ((b) & 1) R_NEXT();
#define P_STAGE(acc, b0)                                                                      \
    R_WAIT();                                                                                 \
    { DECL_DB(b0, BASE128, 16, 0)                                                             \
    wg_fence();                                                                               \
    FOR7(mma_rs56<1, D128(0, t)>(acc, AQ(A, b0, t), (b0) + t > 0, SWB(b0, t, db, 0)));        \
    FOR7(mma_rs56<1, D128(HALF, t)>(acc, AQ(A, (b0) + 1, t), 1, db)); }                       \
    wg_commit();                                                                              \
    R_NEXT();
#define PROJECT(acc) P_STAGE(acc, 0) P_STAGE(acc, 2) wg_wait<1>(); R_RELEASE(2); wg_wait<0>(); R_RELEASE(1);
#define V_PASS()                                                                              \
    {                                                                                         \
        float av[28];                                                                         \
        PROJECT(av)                                                                           \
        const int m = lane >> 3, rr = lane & 7;                                               \
        const uint32_t rowa = hbuf + 16384 + (w * 16 + rr + 8 * (m & 1)) * 128;               \
        const uint32_t one = c == 0 ? 0x00003f80u : 0u;                                       \
        _Pragma("unroll") for (int j = 0; j < 4; j++) {                                       \
            const uint32_t a = rowa + (((2 * j + (m >> 1)) ^ rr) << 4);                       \
            if (j < 3) stsm4(a, pack2(av[8 * j], av[8 * j + 1]), pack2(av[8 * j + 2], av[8 * j + 3]), pack2(av[8 * j + 4], av[8 * j + 5]), pack2(av[8 * j + 6], av[8 * j + 7])); \
            else stsm4(a, pack2(av[24], av[25]), pack2(av[26], av[27]), one, one);            \
        }                                                                                     \
    }
                normalize<0>(A, k0, k1);
                K_BLOCK(0) K_BLOCK(1) K_BLOCK(2) K_BLOCK(3)
                wg_wait<0>();
                R_RELEASE(1);
                STAMP(4 + so);
                if (step == 0) { bar_sync(wgi ? 9 : 1, 224); }
                if (wgi == VW) V_PASS()
                uint32_t PH[28];
                int it = 1;
#pragma unroll 1
                do {
                    float pp[28];
                    phi_gemm(tq, pp);
                    dual_softmax(pp, PH);
                    if (((trips >> (it + 1)) & 1) == 0) continue;
                    {
                        const int m = lane >> 3, rr = lane & 7;
                        const uint32_t rowa = hbuf + (w * 16 + rr + 8 * (m & 1)) * 128;
#pragma unroll
                        for (int j = 0; j < 7; j++) {
                            const int cg = 2 * j + (m >> 1), hi = cg >= 7;
                            stsm4(rowa + hi * 8192 + (((cg - 7 * hi) ^ rr) << 4), PH[4 * j], PH[4 * j + 1], PH[4 * j + 2], PH[4 * j + 3]);
                        }
                    }
                    STAMP(5 + so);
                    if (wgi != VW) V_PASS()
                    fence_async();
                    bar_sync(2, 256);
                    float kv[28];
                    const uint64_t da = BASE128(OFF_H + 16384, 16, 0), dbk = BASE128(OFF_H, 16, wgi * 512);
                    wg_fence();
                    FOR8(constexpr uint64_t o = ((t >> 2) * STAGE + (t & 3) * 2048) >> 4; mma_ss56_tt<o, o>(kv, t > 0, da, dbk));
                    wg_commit();
                    wg_wait<0>();
#pragma unroll
                    for (int hf = 0; hf < 2; hf++) {
                        const int d = 16 * w + g + 8 * hf;
                        if ((d < 56 && (d >= 28) == (c >= 2)) || d == 56) {
                            const int item = d < 56 ? 2 * d + (c & 1) : 112 + c;
                            uint4* dst = g_kv1 + ((sl * 16 + (item >> 3)) * 16 + tile) * 32 + wgi * 16 + (item & 7);
#define KVW(i) pack2(kv[4 * (i) + 2 * hf], kv[4 * (i) + 2 * hf + 1])
                            st_pkt<0>(dst, settag(KVW(0), tag), KVW(1), KVW(2), KVW(3));
                            st_pkt<8>(dst, settag(KVW(4), tag), KVW(5), KVW(6), 0u);
                        }
                    }
                    __syncwarp();
                    kseq++;
                    if (lane == 0) st_word(g_c1 + ((sl * 8 + wu) * 16 + tile) * 32, kseq);
                    bar_arrive(7, 384);
                    STAMP(6 + so);
                    kill<28>(tq);
                    if (QPP) { PP_WAIT() }
                    P_STAGE(tq, 0) P_STAGE(tq, 2)
                    if (QPP) { PP_GO() }
                    wg_wait<1>(); R_RELEASE(2); wg_wait<0>(); R_RELEASE(1);
                    STAMP(7 + so);
                    kill<28>(PH);
                } while (((trips >> (++it)) & 1));
                STAMP(8 + so);
                FRESH();
                if (step) {
                    slice_load<PL(0)>(X, xp0 + sl * 512, lane);
                } else {
                    const uint32_t* xp = reinterpret_cast<const uint32_t*>(x_in + (size_t)(tile * 128 + wu * 16 + g) * 448 + 56 * sl + 2 * c);
#pragma unroll
                    for (int i = 0; i < 7; i++) { X[2 * i] = __ldg(xp + 4 * i); X[2 * i + 1] = __ldg(xp + 4 * i + 8 * 224); }
                }
                bar_sync(3, 384);
                STAMP(9 + so);
                const uint4* const osrc = xp0 + PL(1);
                {
                    float nm[32];
                    const uint64_t db = BASE128(OFF_KVB, 16, 0);
                    wg_fence();
                    FOR7(mma_rs64<0, ((t >> 2) * 8192 + (t & 3) * 32) / 16>(nm, PH[4 * t], PH[4 * t + 1], PH[4 * t + 2], PH[4 * t + 3], t > 0, db));
                    wg_commit();
                    wg_wait<0>();
                    LATE_ARRIVE();
                    const float i00 = rcp(nm[28] + 1e-6f), i01 = rcp(nm[29] + 1e-6f), i10 = rcp(nm[30] + 1e-6f), i11 = rcp(nm[31] + 1e-6f);
                    const float m0 = c >= 2 ? i01 : i00, m1 = c >= 2 ? i11 : i10;
                    uint32_t O[14];
#pragma unroll
                    for (int i = 0; i < 7; i++) {
                        const float f0 = i < 3 ? i00 : (i > 3 ? i01 : m0), f1 = i < 3 ? i10 : (i > 3 ? i11 : m1);
                        O[2 * i] = pack2(nm[4 * i] * f0, nm[4 * i + 1] * f0);
                        O[2 * i + 1] = pack2(nm[4 * i + 2] * f1, nm[4 * i + 3] * f1);
                    }
                    if (OST) { PP_WAIT() }
                    tag_slice(O, tag);
                    if (PFI & 2) PUSH_SLICE(O)
                    send_slice<PL(1)>(xp0 + sl * 512, lane, O);
                    seq++;
                    if (lane == 0) st_word(cx(sl), seq);
                    STAMP(10 + so);
                    if (!(PFI & 2)) PUSH_SLICE(O)
                    if (OST == 1) { PP_GO() }
                    const uint32_t cv = ld_word(cx(lane & 7));
                    PULL_SLICE(O)
                    LATE_WAIT();
                    check_cnt(cv, cx(lane & 7), seq);
                    if (OST == 2) { PP_GO() }
                    STAMP(56 + (step >> 1));
                    GAT_ISSUE(1, PL(1))
                    GAT_ISSUE(3, PL(1))
                    blk_load<2>(A, BLK(osrc, 2), lane);
                }
                float ao[28];
#define WO_BLOCK(b)                                                                           \
    if ((b) > 0) blk_check<b>(A, BLK(osrc, b), lane, tag);                                    \
    if (((b) & 1) == 0) R_WAIT();                                                             \
    { DECL_DB(b, BASE128, 16, 0)                                                              \
    wg_fence();                                                                               \
    FOR7(mma_rs56<1, D128(((b) & 1) * HALF, t)>(ao, AQ(A, b, t), (b) + t > 0, SWB(b, t, db, 0))); } \
    wg_commit();                                                                              \
    if ((b) & 1) R_NEXT();
                WO_BLOCK(0)
                STAMP(11 + so);
                GAT_FETCH(1)
                WO_BLOCK(1)
                WO_BLOCK(2)
                GAT_FETCH(3)
                WO_BLOCK(3)
                PUSH_ACK();
                wg_wait<0>();
                R_RELEASE(2);
                STAMP(12 + so);
                WSUM(86 + 7 * (step >> 1));
                x_fix(X, xbits);
#pragma unroll
                for (int i = 0; i < 14; i++) X[i] = pack2(bf_lo(X[i]) + ao[2 * i], bf_hi(X[i]) + ao[2 * i + 1]);
            } else {
                uint32_t H[56];
                float ag[64];
#define F1_EPI(dst, ng, ag)                                                                    \
    _Pragma("unroll") for (int i = 0; i < 2 * (ng); i++)                                       \
        (dst)[i] = pack2(geglu(ag[2 * i], ag[4 * (ng) + 2 * i]), geglu(ag[2 * i + 1], ag[4 * (ng) + 2 * i + 1]));
#define H_PUSH(h0, off) st_async4(rem_h + (off), H[h0], H[(h0) + 1], H[(h0) + 2], H[(h0) + 3], mapa(BAR(B_RECV2 + wgi), hr ^ 1));
#define F1_BLOCK(b, first)                                                                     \
    if ((first) && (b) == 1) R_RELEASE(2);                                                     \
    if ((first) && (b) == 2 + XT) PUSH_ACK();                                                  \
    if ((first) && (b) == 2 && XT) GAT_FETCH(3)                                                \
    R_WAIT();                                                                                  \
    if ((b) == ((first) ? PPF : PPB)) { PP_WAIT() }                                            \
    { DECL_DB(b, BASE128, HALF, 0)                                                             \
    wg_fence();                                                                                \
    FOR7(mma_rs128<1, D128(0, t)>(ag, AQ(A, b, t), (b) + t > 0, SWB(b, t, db, 0));             \
         if constexpr (first) { PREP(b, t, true) }); }                                         \
    wg_commit();                                                                               \
    if ((b) == 3) { PP_GO() }                                                                  \
    if ((b) > 0) { wg_wait<1>(); R_RELEASE(1); }       \
    R_NEXT();
                normalize<0>(A, k0, k1);
                F1_BLOCK(0, true) F1_BLOCK(1, true) F1_BLOCK(2, true) F1_BLOCK(3, true)
                if (t128 == 0) { mbar_expect_tx(BAR(B_RECV + wgi), 16384); mbar_expect_tx(BAR(B_RECV2 + wgi), 12288); }
                PUSH_BEGIN();
                wg_wait<0>();
                R_RELEASE(1);
                int p = 0;
#pragma unroll 1
                do {
                    F1_EPI(H + 32, 8, ag)
                    STAMP(4 + p + so);
                    WSUM(81 + p + 7 * (step >> 1));
                    if (((trips >> (p + 1)) & 1) == 0) continue;
                    if (step == 1 && p == PKP) R_NEXT();
                    kill<64>(ag);
                    F1_BLOCK(0, false)
                    {
                        const uint32_t pk = (p ? hbuf + 16384 : sb + OFF_KVB + wgi * 8192) + w * 2048;
#pragma unroll
                        for (int k = 0; k < 4; k++) sts4(pk + k * 512 + lane * 16, H[32 + 4 * k], H[33 + 4 * k], H[34 + 4 * k], H[35 + 4 * k]);
                        fence_async();
                        __syncwarp();
                        asm volatile(ELECT "cp.async.bulk.shared::cluster.shared::cta.mbarrier::complete_tx::bytes [%0], [%1], 2048, [%2]; }"
                                     ::"r"(mapa(hbuf + p * 8192 + w * 2048, hr ^ 1)), "r"(pk), "r"(mapa(BAR(B_RECV + wgi), hr ^ 1)) : "memory");
                    }
                    F1_BLOCK(1, false) F1_BLOCK(2, false) F1_BLOCK(3, false)
                    wg_wait<0>();
                    R_RELEASE(1);
                    kill<16>(H + 32);
                } while (((trips >> (++p)) & 1));
#pragma unroll
                for (int k = 0; k < 4; k++) lds4(H + 16 + 4 * k, hbuf + 16384 + w * 2048 + k * 512 + lane * 16);
                __syncwarp();
                if (lane == 0) asm volatile("mbarrier.arrive.shared::cluster.b64 _, [%0];" ::"r"(mapa(BAR(B_ACK2 + wgi), hr ^ 1)) : "memory");
                const uint32_t rem_h = mapa(hbuf + w * 2048 + lane * 16, hr ^ 1);
#define F1_LAST(b0)                                                                            \
    R_WAIT();                                                                                  \
    if (b0) { PP_WAIT() }                                                                      \
    { DECL_DB(b0, BASE64, HALF, 1)                                                             \
    wg_fence();                                                                                \
    FOR7(mma_rs64<1, D64(0, t)>(al, AQ(A, b0, t), (b0) + t > 0, SWB(b0, t, db, 1)));           \
    FOR7(mma_rs64<1, D64(7168, t)>(al, AQ(A, (b0) + 1, t), 1, db)); }                          \
    wg_commit();                                                                               \
    if (b0) { PP_GO() }                                                                        \
    R_NEXT();
                float al[32];
                F1_LAST(0)
                mbar_wait(BAR(B_RECV + wgi), rcvph);
                rcvph ^= 1;
                mbar_wait(BAR(B_ACK2 + wgi), step >> 1);
                H_PUSH(32, 16384) H_PUSH(36, 16896)
                F1_LAST(2)
                H_PUSH(40, 17408) H_PUSH(44, 17920)
                wg_wait<1>();
                R_RELEASE(2);
                wg_wait<0>();
                R_RELEASE(1);
                uint32_t HP[56];
#pragma unroll
                for (int k = 0; k < 4; k++) lds4(H + 4 * k, sb + OFF_KVB + wgi * 8192 + w * 2048 + k * 512 + lane * 16);
#pragma unroll
                for (int t = 0; t < 8; t++) lds4(HP + 4 * t, hbuf + (t >> 2) * 8192 + w * 2048 + (t & 3) * 512 + lane * 16);
                F1_EPI(H + 48, 4, al)
                H_PUSH(48, 24576 - w * 1024) H_PUSH(52, 25088 - w * 1024)
                STAMP(7 + so);
                WSUM(84 + 7 * (step >> 1));
                FRESH();
                float acc[28];
                const uint32_t roA = hr ? 256u : 0u, roB = hr ? (uint32_t)-1536 : 0u;
                const uint32_t rpA = hr ? 0u : 256u, rpB = hr ? 0u : (uint32_t)-1536;
                float res[28];
                uint32_t v0[14], v1[14], P[14];
                Wide PW;
                const uint4* ps = xp0 + sl * 512;
#define F2_OWN_A()                                                                             \
    R_WAIT();                                                                                  \
    d0 = BASE128(0, 16, R_ADJ + roA); d1 = BASE128(0, 16, R_ADJ + roB);                        \
    wg_fence();                                                                                \
    FOR14(if constexpr (t < OT) mma_rs56<1, t * 128>(acc, H[4 * t], H[4 * t + 1], H[4 * t + 2], H[4 * t + 3], t > 0, d0)); \
    wg_commit();
#define F2_OWN_B()                                                                             \
    wg_fence();                                                                                \
    FOR14(if constexpr (t >= OT) mma_rs56<1, t * 128>(acc, H[4 * t], H[4 * t + 1], H[4 * t + 2], H[4 * t + 3], 1, t < 12 ? d0 : d1)); \
    wg_commit();                                                                               \
    R_NEXT();
#define F2_PEER()                                                                              \
    R_WAIT();                                                                                  \
    if (F2PP) { PP_WAIT() }                                                                    \
    d0 = BASE128(0, 16, R_ADJ + rpA); d1 = BASE128(0, 16, R_ADJ + rpB);                        \
    wg_fence();                                                                                \
    FOR14(mma_rs56<1, t * 128>(acc, HP[4 * t], HP[4 * t + 1], HP[4 * t + 2], HP[4 * t + 3], 1, t < 12 ? d0 : d1)); \
    wg_commit();                                                                               \
    if (F2PP) { PP_GO() }                                                                      \
    R_NEXT();
#define F2_TURN(u)                                                                             \
    wg_wait<1>();                                                                              \
    if ((u) < 2 || TDEF < 2) R_RELEASE(2);                                                     \
    wg_wait<0>();                                                                              \
    if ((u) < 2 || TDEF < 1) R_RELEASE(1);                                                     \
    _Pragma("unroll") for (int i = 0; i < 14; i++) P[i] = pack2(acc[2 * i], acc[2 * i + 1]);   \
    tag_slice(P, tag);                                                                         \
    PW = widen(P);                                                                             \
    kill<28>(acc);                                                                             \
    F2_OWN_A()                                                                                 \
    if ((u) == 2) { slice_load<PL(3)>(v0, ps, lane); slice_load<PL(4)>(v1, ps, lane); } \
    send_wide<PL(3 + (u))>(xp0 + (2 * ((pr + (u) + 1) & 3) + hr) * 512, lane, PW);             \
    seq++;                                                                                     \
    if (lane == 0) st_word(cx(sl), seq);                                                       \
    __syncwarp();                                                                              \
    STAMP(8 + (u) + so);                                                                       \
    F2_OWN_B()
                uint64_t d0, d1;
                F2_OWN_A()
                F2_OWN_B()
                R_WAIT();
                d0 = BASE128(0, 16, R_ADJ + rpA); d1 = BASE128(0, 16, R_ADJ + rpB);
                wg_fence();
                FOR8(mma_rs56<1, t * 128>(acc, HP[4 * t], HP[4 * t + 1], HP[4 * t + 2], HP[4 * t + 3], 1, d0));
                wg_commit();
                mbar_wait(BAR(B_RECV2 + wgi), step >> 1);
#pragma unroll
                for (int k = 0; k < 4; k++) lds4(HP + 32 + 4 * k, hbuf + 16384 + w * 2048 + k * 512 + lane * 16);
                lds4(HP + 48, hbuf + 24576 + w * 1024 + lane * 16);
                lds4(HP + 52, hbuf + 25088 + w * 1024 + lane * 16);
                if (step == 1) PUSH_ACK();
                wg_fence();
                FOR14(if constexpr (t >= 8) mma_rs56<1, t * 128>(acc, HP[4 * t], HP[4 * t + 1], HP[4 * t + 2], HP[4 * t + 3], 1, t < 12 ? d0 : d1));
                wg_commit();
                R_NEXT();
                F2_TURN(0)
                F2_PEER()
                F2_TURN(1)
                F2_PEER()
                F2_TURN(2)
                if (step == 1) STAMP(64);
                slice_check<PL(3)>(v0, ps, lane, tag);
                slice_check<PL(4)>(v1, ps, lane, tag);
#pragma unroll
                for (int i = 0; i < 14; i++) { res[2 * i] = bf_lo(v0[i]) + bf_lo(v1[i]); res[2 * i + 1] = bf_hi(v0[i]) + bf_hi(v1[i]); }
                slice_load<PL(2)>(X, ps, lane);
                if (step == 1) STAMP(65);
                F2_PEER()
                if (step == 1) STAMP(66);
                poll_cnt(cx(2 * ((pr + 1) & 3) + hr), seq);
                if (step == 1) STAMP(67);
                slice_load<PL(5)>(v0, ps, lane);
                x_fix(X, xbits);
                slice_check<PL(5)>(v0, ps, lane, tag);
                if (lane < TDEF) mbar_arrive(BAR(B_EMPTY + (slot + NST - 3 - lane) % NST));
#pragma unroll
                for (int i = 0; i < 14; i++) { res[2 * i] += bf_lo(v0[i]); res[2 * i + 1] += bf_hi(v0[i]); }
                STAMP(11 + so);
                wg_wait<0>();
                R_RELEASE(2);
                STAMP(12 + so);
                WSUM(85 + 7 * (step >> 1));
#pragma unroll
                for (int i = 0; i < 14; i++) X[i] = pack2(fmaf(res[2 * i] + acc[2 * i], 0.5f, bf_lo(X[i])), fmaf(res[2 * i + 1] + acc[2 * i + 1], 0.5f, bf_hi(X[i])));
            }
        }
        {
            const int m = lane >> 3, rr = lane & 7;
            const uint32_t ob = hbuf + w * 2048, rowa = ob + (rr + 8 * (m & 1)) * 112 + (m >> 1) * 16;
#pragma unroll
            for (int j = 0; j < 3; j++) stsm4(rowa + 32 * j, X[4 * j], X[4 * j + 1], X[4 * j + 2], X[4 * j + 3]);
            asm volatile("stmatrix.sync.aligned.m8n8.x2.shared.b16 [%0], {%1,%2};" ::"r"(ob + (rr + 8 * (m & 1)) * 112 + 96), "r"(X[12]), "r"(X[13]) : "memory");
            fence_async();
            __syncwarp();
            if (lane == 0) {
                asm volatile("cp.async.bulk.tensor.2d.global.shared::cta.bulk_group [%0, {%2, %3}], [%1];" ::"l"(&maps.out), "r"(ob), "r"(56 * sl), "r"(tile * 128 + wu * 16) : "memory");
                asm volatile("cp.async.bulk.commit_group;" ::: "memory");
                asm volatile("cp.async.bulk.wait_group.read 0;" ::: "memory");
            }
        }
        STAMP(50);
        GSTAMP(61);
        PDUMP();
    }
}

#undef g
#undef pr
#undef c
#undef t128

typedef CUresult (*EncodeFn)(CUtensorMap*, CUtensorMapDataType, cuuint32_t, void*, const cuuint64_t*, const cuuint64_t*, const cuuint32_t*,
                             const cuuint32_t*, CUtensorMapInterleave, CUtensorMapSwizzle, CUtensorMapL2promotion, CUtensorMapFloatOOBfill);

static void make_map(EncodeFn enc, CUtensorMap* m, const void* p, uint64_t cols, uint64_t rows, uint32_t bc, uint32_t br, CUtensorMapSwizzle sw) {
    cuuint64_t gd[2] = {cols, rows};
    cuuint64_t gs[1] = {cols * 2};
    cuuint32_t bd[2] = {bc, br};
    cuuint32_t es[2] = {1, 1};
    enc(m, CU_TENSOR_MAP_DATA_TYPE_BFLOAT16, 2, const_cast<void*>(p), gd, gs, bd, es, CU_TENSOR_MAP_INTERLEAVE_NONE, sw,
        CU_TENSOR_MAP_L2_PROMOTION_L2_128B, CU_TENSOR_MAP_FLOAT_OOB_FILL_NONE);
}

extern "C" void kernel_launch(void* const* d_in, const int* in_sizes, int n_in, void* d_out, int out_size) {
    (void)in_sizes; (void)n_in; (void)out_size;
    static EncodeFn enc = nullptr;
    static Scratch* scratch = nullptr;
    if (!enc) {
        void* fn = nullptr;
        cudaDriverEntryPointQueryResult qr;
        cudaGetDriverEntryPoint("cuTensorMapEncodeTiled", &fn, cudaEnableDefault, &qr);
        enc = (EncodeFn)fn;
        cudaGetSymbolAddress((void**)&scratch, g_scratch);
        cudaFuncSetAttribute(fused_kernel, cudaFuncAttributeMaxDynamicSharedMemorySize, SMEM_BYTES);
    }
    Maps maps;
    {
        cuuint64_t gd[3] = {64, 2048, 7};
        cuuint64_t gs[2] = {896, 128};
        cuuint32_t bd[3] = {64, 32, 7};
        cuuint32_t es[3] = {1, 1, 1};
        enc(&maps.x, CU_TENSOR_MAP_DATA_TYPE_BFLOAT16, 3, d_in[0], gd, gs, bd, es, CU_TENSOR_MAP_INTERLEAVE_NONE, CU_TENSOR_MAP_SWIZZLE_128B,
            CU_TENSOR_MAP_L2_PROMOTION_L2_128B, CU_TENSOR_MAP_FLOAT_OOB_FILL_NONE);
    }
    make_map(enc, &maps.out, d_out, 448, 2048, 56, 16, CU_TENSOR_MAP_SWIZZLE_NONE);
    make_map(enc, &maps.qkv, d_in[1], 1344, 448, 64, 112, CU_TENSOR_MAP_SWIZZLE_128B);
    make_map(enc, &maps.wo, d_in[3], 448, 448, 64, 112, CU_TENSOR_MAP_SWIZZLE_128B);
    make_map(enc, &maps.wg, d_in[5], 1792, 448, 64, 112, CU_TENSOR_MAP_SWIZZLE_128B);
    make_map(enc, &maps.wu, d_in[6], 1792, 448, 64, 112, CU_TENSOR_MAP_SWIZZLE_128B);
    make_map(enc, &maps.wg32, d_in[5], 1792, 448, 32, 112, CU_TENSOR_MAP_SWIZZLE_64B);
    make_map(enc, &maps.wu32, d_in[6], 1792, 448, 32, 112, CU_TENSOR_MAP_SWIZZLE_64B);
    make_map(enc, &maps.wd, d_in[7], 448, 1792, 64, 112, CU_TENSOR_MAP_SWIZZLE_128B);
    fused_kernel<<<128, 384, SMEM_BYTES>>>(scratch, (const __nv_bfloat16*)d_in[0], (const __nv_bfloat16*)d_in[2], 7, (const __nv_bfloat16*)d_in[5],
                                           (const __nv_bfloat16*)d_in[6], (const __nv_bfloat16*)d_in[7], maps);
}
```

```cpp
#include <cuda_runtime.h>
#include <cuda.h>
#include <cuda_bf16.h>
#include <stdint.h>
#include <type_traits>

#define PPF 2
#define PKP 0
#define TDEF 1
#define TMPF 0
#define NORM1 0
#define LPARK 1
#define PFN 9
#define VW 1
#define QPP 1
#define XG3 2
#define XT (XG3 == 1 || XG3 == 2)
#define F3P 0
#define PT0 3
#define ACAN 0
#define SPLIT0 1
#define OT 2
#define F2PP 0
#define PPK 2
#define QE 1
#define OST 1
#define PP

namespace {

constexpr uint32_t STAGE = 28672, HALF = 14336;
constexpr int NST = 5;
constexpr uint32_t OFF_H = NST * STAGE;
constexpr uint32_t OFF_KVB = OFF_H + 2 * STAGE;
constexpr uint32_t OFF_WPHI = OFF_KVB + 16384;
constexpr uint32_t OFF_XR = OFF_WPHI + 7168;
constexpr uint32_t OFF_BAR = OFF_XR + 6144;
constexpr uint32_t SMEM_BYTES = OFF_BAR + 384 + 1408;
constexpr int B_EMPTY = NST, B_RECV = 2 * NST, B_RECV2 = B_RECV + 2, B_PACK = B_RECV2 + 2, B_GAT = B_PACK + 1, B_LATE = B_GAT + 16, B_ACK = B_LATE + 1, B_ACK2 = B_ACK + 2, B_COUNT = B_ACK2 + 2;

constexpr int PACK = 14 + 4 * PKP;

struct Maps { CUtensorMap x, qkv, wo, wg, wu, wg32, wu32, wd, out; };

}

constexpr int PLANE = 16 * 2 * 8 * 512;
struct Scratch {
    uint4 ex[6 * PLANE];
    uint4 kv1[8 * 16 * 16 * 32];
    uint4 kv2[8 * 512];
    uint32_t c1[8 * 8 * 16 * 32];
    uint32_t cw[8 * 32];
    uint4 wp[8 * 32 * (HALF / 16)];
};
__device__ __align__(1024) Scratch g_scratch;
#define g_ex (sc->ex)
#define g_kv1 (sc->kv1)
#define g_kv2 (sc->kv2)
#define g_c1 (sc->c1)
#define g_cw (sc->cw)
#define g_wp (sc->wp)
#define STAMP(i)
#define GSTAMP(i)
#define PDUMP()
#define ASTAMP(i)

namespace {

__device__ __forceinline__ int fresh_tid() { int t; asm volatile("mov.u32 %0, %%tid.x;" : "=r"(t)); return t; }
template <int N> __device__ __forceinline__ void kill(uint32_t* v) {
#pragma unroll
    for (int i = 0; i < N; i++) v[i] = 0;
}
template <int N> __device__ __forceinline__ void kill(float* v) {
#pragma unroll
    for (int i = 0; i < N; i++) v[i] = 0.f;
}
__device__ __forceinline__ uint32_t s2u(const void* p) { return (uint32_t)__cvta_generic_to_shared(p); }
__device__ __forceinline__ void mbar_init(uint32_t a, uint32_t c) { asm volatile("mbarrier.init.shared::cta.b64 [%0], %1;" ::"r"(a), "r"(c) : "memory"); }
__device__ __forceinline__ void mbar_expect_tx(uint32_t a, uint32_t b) { asm volatile("mbarrier.arrive.expect_tx.shared::cta.b64 _, [%0], %1;" ::"r"(a), "r"(b) : "memory"); }
__device__ __forceinline__ void mbar_arrive(uint32_t a) { asm volatile("mbarrier.arrive.shared::cta.b64 _, [%0];" ::"r"(a) : "memory"); }
#define GIVE_UP(id) "trap;\n"
#define SPIN_MAX "0x400000"
#define SPIN_TAIL(id) "add.u32 n, n, 1;\n setp.lt.u32 p, n, " SPIN_MAX ";\n @p bra.uni LP;\n" GIVE_UP(id) " DN:\n }"
__device__ __forceinline__ void mbar_wait(uint32_t a, uint32_t ph) {
    asm volatile("{ .reg .pred p; .reg .b32 n; mov.u32 n, 0;\n LP:\n"
                 "mbarrier.try_wait.parity.shared::cta.b64 p, [%0], %1;\n @p bra DN;\n"
                 "add.u32 n, n, 1;\n setp.lt.u32 p, n, " SPIN_MAX ";\n @p bra LP;\n"
                 GIVE_UP("")
                 " DN:\n }" ::"r"(a), "r"(ph) : "memory");
}
#define ELECT "{ .reg .pred e; elect.sync _|e, 0xffffffff; @e "
__device__ __forceinline__ void tma2d(uint32_t dst, const CUtensorMap* m, int c0, int c1, uint32_t bar) {
    asm volatile(ELECT "cp.async.bulk.tensor.2d.shared::cluster.global.mbarrier::complete_tx::bytes [%0], [%1, {%3, %4}], [%2]; }" ::"r"(dst), "l"(m), "r"(bar), "r"(c0), "r"(c1) : "memory");
}
__device__ __forceinline__ void tma3x(uint32_t dst, const CUtensorMap* m, int row, uint32_t bar) {
    asm volatile(ELECT "cp.async.bulk.tensor.3d.shared::cluster.global.mbarrier::complete_tx::bytes [%0], [%1, {0, %3, 0}], [%2]; }" ::"r"(dst), "l"(m), "r"(bar), "r"(row) : "memory");
}
template <int OFF>
__device__ __forceinline__ void ld_pkt(uint32_t* v, const uint4* p) {
    asm volatile("{ .reg .b128 t; ld.relaxed.gpu.global.b128 t, [%4+%5]; mov.b128 {%0,%1,%2,%3}, t; }" : "=r"(v[0]), "=r"(v[1]), "=r"(v[2]), "=r"(v[3]) : "l"(p), "n"(OFF * 16) : "memory");
}
template <int OFF>
__device__ __forceinline__ void st_pkt(uint4* p, uint32_t a, uint32_t b, uint32_t c, uint32_t d) {
    asm volatile("{ .reg .b128 t; mov.b128 t, {%1,%2,%3,%4}; st.relaxed.gpu.global.b128 [%0+%5], t; }" ::"l"(p), "r"(a), "r"(b), "r"(c), "r"(d), "n"(OFF * 16) : "memory");
}
__device__ __forceinline__ uint32_t pack2(float lo, float hi) {
    uint32_t r;
    asm("cvt.rn.bf16x2.f32 %0, %1, %2;" : "=r"(r) : "f"(hi), "f"(lo));
    return r;
}
__device__ __forceinline__ float bf_lo(uint32_t w) { return __uint_as_float(w << 16); }
__device__ __forceinline__ float bf_hi(uint32_t w) { return __uint_as_float(w & 0xffff0000u); }
__device__ __forceinline__ uint32_t settag(uint32_t w, uint32_t tag) { return (w & ~1u) | tag; }
__device__ __forceinline__ float ex2(float x) { float y; asm("ex2.approx.ftz.f32 %0, %1;" : "=f"(y) : "f"(x)); return y; }
__device__ __forceinline__ float rcp(float x) { float y; asm("rcp.approx.ftz.f32 %0, %1;" : "=f"(y) : "f"(x)); return y; }
__device__ __forceinline__ float tanh_hw(float x) { float y; asm("tanh.approx.f32 %0, %1;" : "=f"(y) : "f"(x)); return y; }
__device__ __forceinline__ void stsm4(uint32_t addr, uint32_t a, uint32_t b, uint32_t c, uint32_t d) {
    asm volatile("stmatrix.sync.aligned.m8n8.x4.shared.b16 [%0], {%1,%2,%3,%4};" ::"r"(addr), "r"(a), "r"(b), "r"(c), "r"(d) : "memory");
}
__device__ __forceinline__ void fence_async() { asm volatile("fence.proxy.async.shared::cta;" ::: "memory"); }
__device__ __forceinline__ void bar_sync(int id, int n) { asm volatile("bar.sync %0, %1;" ::"r"(id), "r"(n) : "memory"); }
__device__ __forceinline__ void bar_arrive(int id, int n) { asm volatile("bar.arrive %0, %1;" ::"r"(id), "r"(n) : "memory"); }
__device__ __forceinline__ void wg_fence() { asm volatile("wgmma.fence.sync.aligned;" ::: "memory"); }
__device__ __forceinline__ void wg_commit() { asm volatile("wgmma.commit_group.sync.aligned;" ::: "memory"); }
template <int N> __device__ __forceinline__ void wg_wait() { asm volatile("wgmma.wait_group.sync.aligned %0;" ::"n"(N) : "memory"); }

constexpr uint32_t SB0 = 1024;
__host__ __device__ constexpr uint32_t dlo(uint32_t off, uint32_t lbo) { return ((SB0 + off) >> 4) | ((lbo >> 4) << 16); }
__host__ __device__ constexpr uint32_t dhi(uint32_t sbo, uint32_t sw) { return (sbo >> 4) | (sw << 30); }
__device__ __forceinline__ uint64_t dbase(uint32_t lo, uint32_t hi) { uint64_t d; asm volatile("mov.b64 %0, {%1, %2};" : "=l"(d) : "r"(lo), "r"(hi)); return d; }
#define BASE128(off, lbo, adj) dbase(dlo(off, lbo) + (adj), dhi(1024, 1))
#define BASE64(off, lbo, adj) dbase(dlo(off, lbo) + (adj), dhi(512, 2))

#define ACC4(d, o) "+f"(d[o]), "+f"(d[o + 1]), "+f"(d[o + 2]), "+f"(d[o + 3])
#define ACC28(d) ACC4(d, 0), ACC4(d, 4), ACC4(d, 8), ACC4(d, 12), ACC4(d, 16), ACC4(d, 20), ACC4(d, 24)
#define ACC32(d, o) ACC4(d, o), ACC4(d, o + 4), ACC4(d, o + 8), ACC4(d, o + 12), ACC4(d, o + 16), ACC4(d, o + 20), ACC4(d, o + 24), ACC4(d, o + 28)

template <int TB, uint64_t D>
__device__ __forceinline__ void mma_rs56(float* d, uint32_t a0, uint32_t a1, uint32_t a2, uint32_t a3, int sd, uint64_t base) {
    asm volatile("{ .reg .pred p; .reg .b64 db; setp.ne.b32 p, %32, 0; add.u64 db, %33, %34;\n"
                 "wgmma.mma_async.sync.aligned.m64n56k16.f32.bf16.bf16 "
                 "{%0,%1,%2,%3,%4,%5,%6,%7,%8,%9,%10,%11,%12,%13,%14,%15,%16,%17,%18,%19,%20,%21,%22,%23,%24,%25,%26,%27}, "
                 "{%28,%29,%30,%31}, db, p, 1, 1, %35; }\n"
                 : ACC28(d)
                 : "r"(a0), "r"(a1), "r"(a2), "r"(a3), "r"(sd), "l"(base), "n"(D), "n"(TB));
}
template <int TB, uint64_t D>
__device__ __forceinline__ void mma_rs64(float* d, uint32_t a0, uint32_t a1, uint32_t a2, uint32_t a3, int sd, uint64_t base) {
    asm volatile("{ .reg .pred p; .reg .b64 db; setp.ne.b32 p, %36, 0; add.u64 db, %37, %38;\n"
                 "wgmma.mma_async.sync.aligned.m64n64k16.f32.bf16.bf16 "
                 "{%0,%1,%2,%3,%4,%5,%6,%7,%8,%9,%10,%11,%12,%13,%14,%15,%16,%17,%18,%19,%20,%21,%22,%23,%24,%25,%26,%27,%28,%29,%30,%31}, "
                 "{%32,%33,%34,%35}, db, p, 1, 1, %39; }\n"
                 : ACC32(d, 0)
                 : "r"(a0), "r"(a1), "r"(a2), "r"(a3), "r"(sd), "l"(base), "n"(D), "n"(TB));
}
template <int TB, uint64_t D>
__device__ __forceinline__ void mma_rs128(float* d, uint32_t a0, uint32_t a1, uint32_t a2, uint32_t a3, int sd, uint64_t base) {
    asm volatile("{ .reg .pred p; .reg .b64 db; setp.ne.b32 p, %68, 0; add.u64 db, %69, %70;\n"
                 "wgmma.mma_async.sync.aligned.m64n128k16.f32.bf16.bf16 "
                 "{%0,%1,%2,%3,%4,%5,%6,%7,%8,%9,%10,%11,%12,%13,%14,%15,%16,%17,%18,%19,%20,%21,%22,%23,%24,%25,%26,%27,%28,%29,%30,%31,%32,%33,%34,%35,%36,%37,%38,%39,%40,%41,%42,%43,%44,%45,%46,%47,%48,%49,%50,%51,%52,%53,%54,%55,%56,%57,%58,%59,%60,%61,%62,%63}, "
                 "{%64,%65,%66,%67}, db, p, 1, 1, %71; }\n"
                 : ACC32(d, 0), ACC32(d, 32)
                 : "r"(a0), "r"(a1), "r"(a2), "r"(a3), "r"(sd), "l"(base), "n"(D), "n"(TB));
}
template <uint64_t DA, uint64_t DB>
__device__ __forceinline__ void mma_ss56_tt(float* d, int sd, uint64_t ba, uint64_t bb) {
    asm volatile("{ .reg .pred p; .reg .b64 da, db; setp.ne.b32 p, %28, 0; add.u64 da, %29, %31; add.u64 db, %30, %32;\n"
                 "wgmma.mma_async.sync.aligned.m64n56k16.f32.bf16.bf16 "
                 "{%0,%1,%2,%3,%4,%5,%6,%7,%8,%9,%10,%11,%12,%13,%14,%15,%16,%17,%18,%19,%20,%21,%22,%23,%24,%25,%26,%27}, "
                 "da, db, p, 1, 1, 1, 1; }\n"
                 : ACC28(d)
                 : "r"(sd), "l"(ba), "l"(bb), "n"(DA), "n"(DB));
}
template <int... I> struct Seq {};
template <class F, int... I> __device__ __forceinline__ void static_for_impl(F&& f, Seq<I...>) { (f(std::integral_constant<int, I>{}), ...); }
#define FOR7(...) static_for_impl([&](auto T_) { constexpr int t = decltype(T_)::value; __VA_ARGS__; }, Seq<0, 1, 2, 3, 4, 5, 6>{})
#define FOR8(...) static_for_impl([&](auto T_) { constexpr int t = decltype(T_)::value; __VA_ARGS__; }, Seq<0, 1, 2, 3, 4, 5, 6, 7>{})
#define FOR14(...) static_for_impl([&](auto T_) { constexpr int t = decltype(T_)::value; __VA_ARGS__; }, Seq<0, 1, 2, 3, 4, 5, 6, 7, 8, 9, 10, 11, 12, 13>{})

__device__ __forceinline__ int kblk(int p, int b) { return b == 0 ? p : b - (b <= p); }
__host__ __device__ constexpr int krow(int t) { return t < 3 ? 16 * t : (t < 6 ? 56 + 16 * (t - 3) : 48); }
#define AQ(A, b, t) ((t) < 3 ? A[2 * (b)][4 * (t)] : (t) < 6 ? A[2 * (b) + 1][4 * ((t) - 3)] : A[2 * (b)][12]), \
                    ((t) < 3 ? A[2 * (b)][4 * (t) + 1] : (t) < 6 ? A[2 * (b) + 1][4 * ((t) - 3) + 1] : A[2 * (b)][13]), \
                    ((t) < 3 ? A[2 * (b)][4 * (t) + 2] : (t) < 6 ? A[2 * (b) + 1][4 * ((t) - 3) + 2] : A[2 * (b) + 1][12]), \
                    ((t) < 3 ? A[2 * (b)][4 * (t) + 3] : (t) < 6 ? A[2 * (b) + 1][4 * ((t) - 3) + 3] : A[2 * (b) + 1][13])
#define D128(off, t) ((uint64_t)(((off) + krow(t) * 128) >> 4) + ((uint64_t)((t) == 6 ? (7168 - 1024) >> 4 : 0) << 32))
#define D64(off, t) ((uint64_t)(((off) + krow(t) * 64) >> 4) + ((uint64_t)((t) == 6 ? (3584 - 512) >> 4 : 0) << 32))

#define PL(k) (((k) - 3) * PLANE)
__device__ __forceinline__ void st_word(uint32_t* p, uint32_t v) { asm volatile("st.relaxed.gpu.global.u32 [%0], %1;" ::"l"(p), "r"(v) : "memory"); }
__device__ __forceinline__ uint32_t ld_word(const uint32_t* p) { uint32_t v; asm volatile("ld.relaxed.gpu.global.u32 %0, [%1];" : "=r"(v) : "l"(p) : "memory"); return v; }
__device__ __forceinline__ void tag_slice(uint32_t* w, uint32_t tag) { w[0] = settag(w[0], tag); w[4] = settag(w[4], tag); w[8] = settag(w[8], tag); w[12] = settag(w[12], tag); }
template <int O>
__device__ __forceinline__ void send_slice(uint4* dst, int lane, const uint32_t* w) {
    st_pkt<O>(dst, w[0], w[1], w[2], w[3]);
    st_pkt<O + 32>(dst, w[4], w[5], w[6], w[7]);
    st_pkt<O + 64>(dst, w[8], w[9], w[10], w[11]);
    asm volatile("{ .reg .b64 t; mov.b64 t, {%1,%2}; st.relaxed.gpu.global.b64 [%0+%3], t; }" ::"l"((char*)dst - lane * 8), "r"(w[12]), "r"(w[13]), "n"(16 * (O + 96)) : "memory");
}
struct Wide { unsigned __int128 q[3]; uint64_t h; };
__device__ __forceinline__ Wide widen(const uint32_t* w) {
    Wide r;
#pragma unroll
    for (int k = 0; k < 3; k++) asm volatile("mov.b128 %0, {%1,%2,%3,%4};" : "=q"(r.q[k]) : "r"(w[4 * k]), "r"(w[4 * k + 1]), "r"(w[4 * k + 2]), "r"(w[4 * k + 3]));
    asm volatile("mov.b64 %0, {%1,%2};" : "=l"(r.h) : "r"(w[12]), "r"(w[13]));
    return r;
}
template <int O>
__device__ __forceinline__ void send_wide(uint4* dst, int lane, const Wide& v) {
    asm volatile("st.relaxed.gpu.global.b128 [%0+%4], %1;\n st.relaxed.gpu.global.b128 [%0+%5], %2;\n st.relaxed.gpu.global.b128 [%0+%6], %3;"
                 ::"l"(dst), "q"(v.q[0]), "q"(v.q[1]), "q"(v.q[2]), "n"(16 * O), "n"(16 * (O + 32)), "n"(16 * (O + 64)) : "memory");
    asm volatile("st.relaxed.gpu.global.b64 [%0+%2], %1;" ::"l"((char*)dst - lane * 8), "l"(v.h), "n"(16 * (O + 96)) : "memory");
}
#define RW4(v, o) "+r"(v[o]), "+r"(v[(o) + 1]), "+r"(v[(o) + 2]), "+r"(v[(o) + 3])
#define RW2(v, o) "+r"(v[o]), "+r"(v[(o) + 1])
#define WR4(v, o) "=&r"(v[o]), "=&r"(v[(o) + 1]), "=&r"(v[(o) + 2]), "=&r"(v[(o) + 3])
#define LDP(a, b, c, d, addr, off) "ld.relaxed.gpu.global.b128 q, [" addr "+" off "];\n mov.b128 {" a "," b "," c "," d "}, q;\n"
#define LDH(a, b, addr, off) "ld.relaxed.gpu.global.b64 h, [" addr "+" off "];\n mov.b64 {" a "," b "}, h;\n"
#define VOTE_OK "and.b32 t, t, 1;\n setp.ne.u32 p, t, 0;\n vote.sync.any.pred p, p, 0xffffffff;\n @!p bra.uni DN;\n"
#define CHK(x, tag) "lop3.b32 t, " x ", " tag ", t, 0xBE;\n"
__device__ __forceinline__ void check_cnt(uint32_t v, const uint32_t* p, uint32_t target) {
    asm volatile("{ .reg .pred p; .reg .b32 n, t; mov.u32 n, 0; mov.u32 t, %2;\n LP:\n"
                 "sub.s32 t, t, %1;\n setp.lt.s32 p, t, 0;\n vote.sync.any.pred p, p, 0xffffffff;\n @!p bra.uni DN;\n ld.relaxed.gpu.global.u32 t, [%0];\n" SPIN_TAIL("7")
                 ::"l"(p), "r"(target), "r"(v) : "memory");
}
__device__ __forceinline__ void poll_cnt(const uint32_t* p, uint32_t target) {
    asm volatile("{ .reg .pred p; .reg .b32 n, t; mov.u32 n, 0;\n LP:\n"
                 "ld.relaxed.gpu.global.u32 t, [%0];\n sub.s32 t, t, %1;\n setp.lt.s32 p, t, 0;\n vote.sync.any.pred p, p, 0xffffffff;\n @!p bra.uni DN;\n" SPIN_TAIL("1")
                 ::"l"(p), "r"(target) : "memory");
}
template <int STR>
__device__ __forceinline__ void poll4_kv(uint32_t* v, const uint4* p, uint32_t tag) {
    asm volatile("{ .reg .pred p; .reg .b32 n, t; .reg .b128 q; mov.u32 n, 0;\n LP:\n"
                 LDP("%0", "%1", "%2", "%3", "%16", "0") LDP("%4", "%5", "%6", "%7", "%16", "%18")
                 LDP("%8", "%9", "%10", "%11", "%16", "%19") LDP("%12", "%13", "%14", "%15", "%16", "%20")
                 "xor.b32 t, %0, %17;\n" CHK("%4", "%17") CHK("%8", "%17") CHK("%12", "%17") VOTE_OK SPIN_TAIL("2")
                 : WR4(v, 0), WR4(v, 4), WR4(v, 8), WR4(v, 12)
                 : "l"(p), "r"(tag), "n"(16 * STR), "n"(32 * STR), "n"(48 * STR)
                 : "memory");
}
template <int B>
__device__ __forceinline__ void blk_load(uint32_t (&A)[8][14], const uint4* src, int lane) {
    ld_pkt<0>(&A[2 * B][0], src); ld_pkt<32>(&A[2 * B][4], src); ld_pkt<64>(&A[2 * B][8], src);
    ld_pkt<512>(&A[2 * B + 1][0], src); ld_pkt<544>(&A[2 * B + 1][4], src); ld_pkt<576>(&A[2 * B + 1][8], src);
    asm volatile("{ .reg .b64 h;\n" LDH("%0", "%1", "%4", "1536") LDH("%2", "%3", "%4", "9728") "}"
                 : "=&r"(A[2 * B][12]), "=&r"(A[2 * B][13]), "=&r"(A[2 * B + 1][12]), "=&r"(A[2 * B + 1][13])
                 : "l"((const char*)src - lane * 8) : "memory");
}
#define BLK_TEST "xor.b32 t, %0, %30;\n" CHK("%4", "%30") CHK("%8", "%30") CHK("%12", "%30") CHK("%16", "%30") CHK("%20", "%30") CHK("%24", "%30") CHK("%26", "%30") VOTE_OK
template <int B>
__device__ __forceinline__ void blk_check(uint32_t (&A)[8][14], const uint4* src, int lane, uint32_t tag) {
    asm volatile("{ .reg .pred p; .reg .b32 n, t; .reg .b128 q; .reg .b64 h, a8;\n" BLK_TEST
                 "mov.u32 n, 0;\n mad.wide.s32 a8, %29, -8, %28;\n LP:\n"
                 LDP("%0", "%1", "%2", "%3", "%28", "0") LDP("%4", "%5", "%6", "%7", "%28", "512") LDP("%8", "%9", "%10", "%11", "%28", "1024")
                 LDP("%12", "%13", "%14", "%15", "%28", "8192") LDP("%16", "%17", "%18", "%19", "%28", "8704") LDP("%20", "%21", "%22", "%23", "%28", "9216")
                 LDH("%24", "%25", "a8", "1536") LDH("%26", "%27", "a8", "9728") BLK_TEST SPIN_TAIL("3")
                 "\n and.b32 %0, %0, -2; and.b32 %4, %4, -2; and.b32 %8, %8, -2; and.b32 %12, %12, -2; and.b32 %16, %16, -2; and.b32 %20, %20, -2; and.b32 %24, %24, -2; and.b32 %26, %26, -2;"
                 : RW4(A[2 * B], 0), RW4(A[2 * B], 4), RW4(A[2 * B], 8), RW4(A[2 * B + 1], 0), RW4(A[2 * B + 1], 4), RW4(A[2 * B + 1], 8),
                   RW2(A[2 * B], 12), RW2(A[2 * B + 1], 12)
                 : "l"(src), "r"(lane), "r"(tag)
                 : "memory");
}
__device__ __forceinline__ void st_async4(uint32_t a, uint32_t x, uint32_t y, uint32_t z, uint32_t w, uint32_t bar) {
    asm volatile("st.async.weak.shared::cluster.mbarrier::complete_tx::bytes.v4.b32 [%0], {%1,%2,%3,%4}, [%5];" ::"r"(a), "r"(x), "r"(y), "r"(z), "r"(w), "r"(bar) : "memory");
}
__device__ __forceinline__ uint32_t mapa(uint32_t a, uint32_t cta) { uint32_t r; asm("mapa.shared::cluster.u32 %0, %1, %2;" : "=r"(r) : "r"(a), "r"(cta)); return r; }
__device__ __forceinline__ void stat_load(uint32_t* v, const uint4* p) { ld_pkt<0>(v, p); ld_pkt<512>(v + 4, p); }
__device__ __forceinline__ void stat_check(uint32_t* v, const uint4* p, uint32_t tag) {
    asm volatile("{ .reg .pred p; .reg .b32 n, t; .reg .b128 q; mov.u32 n, 0;\n LP:\n"
                 "xor.b32 t, %3, %9;\n" CHK("%7", "%9") VOTE_OK
                 LDP("%0", "%1", "%2", "%3", "%8", "0") LDP("%4", "%5", "%6", "%7", "%8", "8192") SPIN_TAIL("4")
                 : RW4(v, 0), RW4(v, 4) : "l"(p), "r"(tag) : "memory");
}
__device__ __forceinline__ uint32_t x_bits(const uint32_t* X) {
    uint32_t r;
    asm volatile("{ .reg .b32 a, b; prmt.b32 a, %1, %2, 0x0040; prmt.b32 b, %3, %4, 0x0040; prmt.b32 %0, a, b, 0x5410; }" : "=r"(r) : "r"(X[0]), "r"(X[4]), "r"(X[8]), "r"(X[12]));
    return r;
}
template <int O>
__device__ __forceinline__ void slice_load(uint32_t* v, const uint4* p, int lane) {
    ld_pkt<O>(v, p); ld_pkt<O + 32>(v + 4, p); ld_pkt<O + 64>(v + 8, p);
    asm volatile("{ .reg .b64 h;\n" LDH("%0", "%1", "%2", "%3") "}" : "=r"(v[12]), "=r"(v[13]) : "l"((const char*)p - lane * 8), "n"(16 * (O + 96)) : "memory");
}
#define SLICE_TEST "xor.b32 t, %0, %16;\n" CHK("%4", "%16") CHK("%8", "%16") CHK("%12", "%16") VOTE_OK
template <int O>
__device__ __forceinline__ void slice_check(uint32_t* v, const uint4* p, int lane, uint32_t tag) {
    asm volatile("{ .reg .pred p; .reg .b32 n, t; .reg .b128 q; .reg .b64 h;\n" SLICE_TEST "mov.u32 n, 0;\n LP:\n"
                 LDP("%0", "%1", "%2", "%3", "%14", "%17") LDP("%4", "%5", "%6", "%7", "%14", "%18") LDP("%8", "%9", "%10", "%11", "%14", "%19")
                 LDH("%12", "%13", "%15", "%20") SLICE_TEST SPIN_TAIL("5")
                 : RW4(v, 0), RW4(v, 4), RW4(v, 8), RW2(v, 12)
                 : "l"(p), "l"((const char*)p - lane * 8), "r"(tag), "n"(16 * O), "n"(16 * (O + 32)), "n"(16 * (O + 64)), "n"(16 * (O + 96))
                 : "memory");
}
__device__ __forceinline__ void x_fix(uint32_t* X, uint32_t bits) {
    X[0] = __byte_perm(X[0], bits, 0x3214); X[4] = __byte_perm(X[4], bits, 0x3215); X[8] = __byte_perm(X[8], bits, 0x3216); X[12] = __byte_perm(X[12], bits, 0x3217);
}
__device__ __forceinline__ void sts4(uint32_t a, uint32_t x, uint32_t y, uint32_t z, uint32_t w) {
    asm volatile("st.shared.v4.u32 [%0], {%1,%2,%3,%4};" ::"r"(a), "r"(x), "r"(y), "r"(z), "r"(w) : "memory");
}
__device__ __forceinline__ void lds4(uint32_t* v, uint32_t a) {
    asm volatile("ld.shared.v4.u32 {%0,%1,%2,%3}, [%4];" : "=r"(v[0]), "=r"(v[1]), "=r"(v[2]), "=r"(v[3]) : "r"(a) : "memory");
}
struct LnCoef { uint32_t hi, lo, sh; };
__device__ __forceinline__ LnCoef ln_coef(float sum, float sq) {
    sum += __shfl_xor_sync(0xffffffffu, sum, 1); sq += __shfl_xor_sync(0xffffffffu, sq, 1);
    sum += __shfl_xor_sync(0xffffffffu, sum, 2); sq += __shfl_xor_sync(0xffffffffu, sq, 2);
    const float mean = sum * (1.f / 448.f);
    const float var = fmaxf(fmaf(-mean, mean, sq * (1.f / 448.f)), 0.f);
    const float sc = rsqrtf(var + 1e-5f);
    LnCoef r;
    r.hi = pack2(sc, sc);
    const float lo = sc - bf_lo(r.hi), sh = -mean * sc;
    r.lo = pack2(lo, lo);
    r.sh = pack2(sh, sh);
    return r;
}
template <int B>
__device__ __forceinline__ void normalize(uint32_t (&A)[8][14], const LnCoef& c0, const LnCoef& c1) {
#pragma unroll
    for (int s = 2 * B; s < 2 * B + 2; s++)
#pragma unroll
        for (int i = 0; i < 14; i++) {
            const LnCoef& k = (i & 1) ? c1 : c0;
            asm("{ .reg .b32 t; fma.rn.bf16x2 t, %0, %2, %3; fma.rn.bf16x2 %0, %0, %1, t; }" : "+r"(A[s][i]) : "r"(k.hi), "r"(k.lo), "r"(k.sh));
        }
}
__device__ __forceinline__ void slice_stats(const uint32_t* w, float* st) {
    float a = 0.f, b = 0.f, p = 0.f, q = 0.f;
#pragma unroll
    for (int i = 0; i < 7; i++) {
        const float e0 = bf_lo(w[2 * i]), e1 = bf_hi(w[2 * i]), e2 = bf_lo(w[2 * i + 1]), e3 = bf_hi(w[2 * i + 1]);
        a += e0 + e1; b += e2 + e3;
        p = fmaf(e0, e0, p); p = fmaf(e1, e1, p); q = fmaf(e2, e2, q); q = fmaf(e3, e3, q);
    }
    a += __shfl_xor_sync(0xffffffffu, a, 1); p += __shfl_xor_sync(0xffffffffu, p, 1); b += __shfl_xor_sync(0xffffffffu, b, 1); q += __shfl_xor_sync(0xffffffffu, q, 1);
    a += __shfl_xor_sync(0xffffffffu, a, 2); p += __shfl_xor_sync(0xffffffffu, p, 2); b += __shfl_xor_sync(0xffffffffu, b, 2); q += __shfl_xor_sync(0xffffffffu, q, 2);
    st[0] = a; st[1] = p; st[2] = b; st[3] = q;
}
__device__ __forceinline__ void dual_softmax(const float* p, uint32_t* out) {
    constexpr float L = 1.4426950408889634f;
#pragma unroll
    for (int r = 0; r < 2; r++) {
        float mx = fmaxf(p[2 * r], p[2 * r + 1]), mn = fminf(p[2 * r], p[2 * r + 1]);
#pragma unroll
        for (int i = 1; i < 7; i++) {
            mx = fmaxf(mx, fmaxf(p[4 * i + 2 * r], p[4 * i + 2 * r + 1]));
            mn = fminf(mn, fminf(p[4 * i + 2 * r], p[4 * i + 2 * r + 1]));
        }
        mx = fmaxf(mx, __shfl_xor_sync(0xffffffffu, mx, 1));
        mn = fminf(mn, __shfl_xor_sync(0xffffffffu, mn, 1));
        const float bx = -mx * L, bn = mn * L;
        float ep[14], en[14], sp = 0.f, sn = 0.f;
#pragma unroll
        for (int i = 0; i < 14; i++) {
            const float v = p[4 * (i >> 1) + 2 * r + (i & 1)];
            ep[i] = ex2(fmaf(v, L, bx));
            en[i] = ex2(fmaf(v, -L, bn));
            sp += ep[i]; sn += en[i];
        }
        sp += __shfl_xor_sync(0xffffffffu, sp, 1);
        sn += __shfl_xor_sync(0xffffffffu, sn, 1);
        const float ip = rcp(sp), in = rcp(sn);
#pragma unroll
        for (int i = 0; i < 7; i++) {
            out[4 * i + r] = pack2(ep[2 * i] * ip, ep[2 * i + 1] * ip);
            out[4 * i + 2 + r] = pack2(en[2 * i] * in, en[2 * i + 1] * in);
        }
    }
}
__device__ __forceinline__ float geglu(float g, float u) {
    const float t = tanh_hw(g * fmaf(g * g, 0.7978845608028654f * 0.044715f, 0.7978845608028654f));
    const float gu = g * u;
    return fmaf(t, gu, gu);
}
__device__ __forceinline__ void phi_gemm(const float* t, float* p) {
    uint32_t w[14];
#pragma unroll
    for (int i = 0; i < 14; i++) w[i] = pack2(t[2 * i], t[2 * i + 1]);
    const uint64_t db = BASE128(OFF_WPHI, 16, 0);
    wg_fence();
    mma_rs56<0, 0>(p, w[0], w[1], w[2], w[3], 0, db);
    mma_rs56<0, 2>(p, w[4], w[5], w[6], w[7], 1, db);
    mma_rs56<0, 4>(p, w[8], w[9], w[10], w[11], 1, db);
    mma_rs56<0, 6>(p, w[12], w[13], 0u, 0u, 1, db);
    wg_commit();
    wg_wait<0>();
}

}

#define BAR(i) (bars + 8 * (i))
#define R_WAIT() mbar_wait(BAR(slot), ph)
#define WSUM(i)
#define R_ADJ (slot * (STAGE >> 4))
#define R_NEXT() do { eb2 = eb1; eb1 = BAR(B_EMPTY + slot); if (++slot == NST) { slot = 0; ph ^= 1; } } while (0)
#define R_RELEASE(k) do { if (lane == 0) mbar_arrive((k) == 1 ? eb1 : eb2); } while (0)
#define PUSH_BEGIN() do { mbar_wait(BAR(B_ACK + wgi), ackph); ackph ^= 1; } while (0)
#define PUSH_ACK() do { __syncwarp(); if (lane == 0) asm volatile("mbarrier.arrive.shared::cluster.b64 _, [%0];" ::"r"(mapa(BAR(B_ACK + wgi), hr ^ 1)) : "memory"); } while (0)

__global__ void __cluster_dims__(2, 1, 1) __launch_bounds__(384, 1)
fused_kernel(Scratch* const sc, const __nv_bfloat16* __restrict__ x_in, const __nv_bfloat16* __restrict__ w_phi, const int trips,
             const __nv_bfloat16* __restrict__ wg, const __nv_bfloat16* __restrict__ wu, const __nv_bfloat16* __restrict__ wd,
             const __grid_constant__ Maps maps) {
    extern __shared__ __align__(1024) unsigned char smem_raw[];
    const uint32_t sb = s2u(smem_raw);
    const uint32_t bars = sb + OFF_BAR;
    const int wgi = __shfl_sync(0xffffffffu, threadIdx.x >> 7, 0);
    const int hr = blockIdx.x & 1, ck = blockIdx.x >> 1;
    const int gp = (ck - 4) & 7, q7 = ((ck - 36) * 37) >> 8;
    const int pr = __shfl_sync(0xffffffffu, ck < 4 ? ck : (ck < 36 ? (ck - 4) >> 3 : q7), 0);
    const int tile = __shfl_sync(0xffffffffu, ck < 4 ? 0 : (ck < 36 ? (gp ? 2 * gp : 1) : 2 * (ck - 36 - 7 * q7) + 3), 0);
    const int sl = 2 * pr + hr;
    STAMP(0);
    GSTAMP(60);
    if (threadIdx.x == 256) {
#pragma unroll
        for (int i = 0; i < NST; i++) mbar_init(BAR(i), 1);
        asm volatile("fence.mbarrier_init.release.cluster;" ::: "memory");
    }
    if (threadIdx.x == 288) {
        if ((sb & 0x3FFFF) != SB0) asm volatile("trap;");
#pragma unroll
        for (int i = NST; i < B_COUNT; i++) mbar_init(BAR(i), i >= B_ACK ? 4 : (i < B_RECV || i == B_LATE ? 8 : 1));
        asm volatile("fence.mbarrier_init.release.cluster;" ::: "memory");
    }
    __syncwarp();
    asm volatile("barrier.cluster.arrive.relaxed.aligned;" ::: "memory");

    if (wgi == 2) {
        asm volatile("setmaxnreg.dec.sync.aligned.u32 40;");
        const int t128 = fresh_tid() & 127, w = __shfl_sync(0xffffffffu, t128 >> 5, 0), lane = t128 & 31;
        uint32_t e0[2] = {0, 0}, e1[2] = {0, 0}, cw_target = 0, kseq;
        if (w == 0) {
#pragma unroll 1
            for (int n = 0; n < NST; n++) {
                const uint32_t dst = sb + n * STAGE, fb = BAR(n);
                asm volatile(ELECT "mbarrier.arrive.expect_tx.shared::cta.b64 _, [%0], %1; }" ::"r"(fb), "r"(n < 2 ? 2 * STAGE : STAGE) : "memory");
                if (n < 2) {
                    tma3x(sb + OFF_H + n * STAGE, &maps.x, tile * 128 + n * 64, fb);
                    tma3x(dst, &maps.x, tile * 128 + n * 64 + 32, fb);
                } else {
                    if (n == 3) mbar_wait(BAR(1), 0);
                    const int c0 = (n < 4 ? 448 : 896) + 56 * sl, r0 = 224 * (n & 1);
                    tma2d(dst, &maps.qkv, c0, r0, fb);
                    tma2d(dst + HALF, &maps.qkv, c0, r0 + 112, fb);
                }
            }
            asm volatile("barrier.cluster.wait.aligned;" ::: "memory");
            kseq = ld_word(g_c1 + (sl * 8 * 16 + tile) * 32);
            cw_target = (ld_word(g_cw + sl * 32) & ~15u) + 16;
#pragma unroll 1
            for (int k = 0; k < 2; k++) {
                const int n = t128 + 32 * k;
                int m = n - 2 - (n > PACK);
                const bool packed = m >= 30 ? (m < 38 || m >= 52) : m >= 22;
                if (m >= 30) m -= 30;
                if (n == PACK) m = tile < 8 ? tile : tile + 14;
                const int rot = n < 8 ? 0 : pr;
                const int ra = 112 * kblk(rot, m & 3), rb = 112 * kblk(rot, 2 * m & 3), rc = 112 * kblk(rot, (2 * m + 1) & 3);
                int kind = 0, m0, m1, c0, c1, r0, r1;
                if (m < 8) { m0 = m1 = m < 6 ? 1 : 2; c0 = c1 = (m < 2 ? 448 : (m < 4 ? 896 : 0)) + 56 * sl; r0 = rb; r1 = rc; }
                else if (m < 20) { m0 = 3; m1 = 4; c0 = c1 = 224 * sl + 32 * hr + 64 * ((m - 8) >> 2); r0 = r1 = ra; }
                else if (m < 22) { kind = 2; m0 = 5; m1 = 6; c0 = c1 = 224 * sl + (hr ? 0 : 192); r0 = rb; r1 = rc; }
                else { m0 = m1 = 7; c0 = c1 = 56 * (2 * ((pr + (m >> 1) - 10) & 3) + hr); r0 = 224 * (sl ^ (m & 1)); r1 = r0 + 112; }
                if (packed) { kind = 1; r0 = sl * 16 + (m < 8 ? m : m - 14); r1 = 0; }
                e0[0] = e0[1]; e1[0] = e1[1];
                e0[1] = kind | (m0 << 2) | (m1 << 6) | (c0 << 10) | (c1 << 21);
                e1[1] = r0 | (r1 << 16);
            }
        } else {
            const int j = t128 - 32;
            kseq = ld_word(g_c1 + (sl * 8 * 16 + tile) * 32);
            asm volatile("barrier.cluster.wait.aligned;" ::: "memory");
            uint2 wv[7];
            const int k = j < 56 ? j : 55, hh = k >= 28;
#pragma unroll
            for (int i = 0; i < 7; i++) wv[i] = __ldg(reinterpret_cast<const uint2*>(w_phi + (sl * 56 + k) * 28) + i);
#pragma unroll 1
            for (int i = j; i < 7168 / 16; i += 96) sts4(sb + OFF_WPHI + i * 16, 0, 0, 0, 0);
            bar_sync(5, 96);
            if (j < 56) {
                uint32_t a4[4];
#pragma unroll
                for (int q = 0; q < 4; q++) a4[q] = sb + OFF_WPHI + (4 * hh + q) * 128 + ((((k >> 3) ^ (4 * hh + q)) & 7) << 4) + (k & 7) * 2;
                FOR14(const uint32_t v = (t & 1) ? wv[t >> 1].y : wv[t >> 1].x;
                      asm volatile("{ .reg .b16 l, h; mov.b32 {l, h}, %2; st.shared.u16 [%0+%3], l; st.shared.u16 [%1+%3], h; }"
                                   ::"r"(a4[t >= 7 ? 2 : 0]), "r"(a4[t >= 7 ? 3 : 1]), "r"(v), "n"((t % 7) * 1024) : "memory"));
            }
            __syncwarp();
            fence_async();
            kseq = __shfl_sync(0xffffffffu, kseq, 0);
            bar_arrive(1, 224);
            bar_arrive(9, 224);
        }
        kseq = __shfl_sync(0xffffffffu, kseq, 0);
        int slot = 0, ph = 0, n = NST;
#pragma unroll 1
        for (int layer = 0; layer < 3; layer++) {
            if (w == 0) {
                const int nend = layer == 0 ? 11 : (layer == 1 ? 42 : 63);
#pragma unroll 1
                for (; n < nend; n++) {
                const uint32_t w0 = __shfl_sync(0xffffffffu, n < 32 ? e0[0] : e0[1], n & 31), w1 = __shfl_sync(0xffffffffu, n < 32 ? e1[0] : e1[1], n & 31);
                const uint32_t dst = sb + slot * STAGE, fb = BAR(n == PACK ? B_PACK : slot);
                const CUtensorMap* m0 = &maps.x + ((w0 >> 2) & 15);
                const CUtensorMap* m1 = &maps.x + ((w0 >> 6) & 15);
                const int c0 = (w0 >> 10) & 2047, c1 = w0 >> 21, r0 = w1 & 0xffff, r1 = w1 >> 16;
                if (n == 25) {
                    int it = 0;
                    uint32_t v;
                    do { asm volatile("ld.acquire.gpu.global.u32 %0, [%1];" : "=r"(v) : "l"(g_cw + sl * 32) : "memory"); } while ((int)(v - cw_target) < 0 && ++it < 0x400000);
                    asm volatile("fence.proxy.async.global;" ::: "memory");
                    __syncwarp();
                }
                mbar_wait(BAR(B_EMPTY + slot), ph);
                __syncwarp();
                asm volatile(ELECT "mbarrier.arrive.expect_tx.shared::cta.b64 _, [%0], %1; }" ::"r"(fb), "r"(STAGE) : "memory");
                if ((w0 & 3) == 0) {
                    tma2d(dst, m0, c0, r0, fb);
                    tma2d(dst + HALF, m1, c1, r1, fb);
                } else if (w0 & 1) {
                    asm volatile(ELECT "cp.async.bulk.shared::cluster.global.mbarrier::complete_tx::bytes [%0], [%1], %2, [%3]; }"
                                 ::"r"(dst), "l"(reinterpret_cast<const char*>(g_wp) + (size_t)r0 * STAGE), "r"(STAGE), "r"(fb) : "memory");
                } else {
                    tma2d(dst, m0, c0, r0, fb); tma2d(dst + 7168, m0, c0, r1, fb);
                    tma2d(dst + HALF, m1, c0, r0, fb); tma2d(dst + HALF + 7168, m1, c0, r1, fb);
                }
                if (n == PFN) {
                    const int b = blockIdx.x;
                    asm volatile(ELECT "cp.async.bulk.prefetch.L2.global [%0], %1; }" ::"l"(wg + b * 6272), "r"(12544) : "memory");
                    asm volatile(ELECT "cp.async.bulk.prefetch.L2.global [%0], %1; }" ::"l"(wu + b * 6272), "r"(12544) : "memory");
                    asm volatile(ELECT "cp.async.bulk.prefetch.L2.global [%0], %1; }" ::"l"(wd + b * 6272), "r"(12544) : "memory");
                }
                if (n == PACK) asm volatile(ELECT "mbarrier.arrive.shared::cta.b64 _, [%0]; }" ::"r"(BAR(slot)) : "memory");
                if (++slot == NST) { slot = 0; ph ^= 1; }
                }
            } else if (w == 1 && layer == 1) {
                constexpr int ps = PACK % NST;
                mbar_wait(BAR(B_PACK), 0);
                asm volatile("{ .reg .pred e; elect.sync _|e, 0xffffffff;\n"
                             "@e cp.async.bulk.global.shared::cta.bulk_group [%0], [%1], %2;\n"
                             "@e cp.async.bulk.commit_group;\n"
                             "@e cp.async.bulk.wait_group.read 0;\n"
                             "@e mbarrier.arrive.shared::cta.b64 _, [%3], 8;\n"
                             "@e cp.async.bulk.wait_group 0;\n"
                             "@e fence.proxy.async.global;\n"
                             "@e red.release.gpu.global.add.u32 [%4], 1; }"
                             ::"l"(reinterpret_cast<char*>(g_wp) + (size_t)(sl * 16 + tile) * STAGE), "r"(sb + ps * STAGE), "r"(STAGE), "r"(BAR(B_EMPTY + ps)), "l"(g_cw + sl * 32) : "memory");
                __syncwarp();
            }
            if (layer < 2) {
            const uint32_t tag = layer ^ 1;
            kseq++;
            bar_sync(7, 384);
            ASTAMP(0);
            if (tile < 15) {
                const int sq = lane >> 3, pk = 8 * w + (lane & (tile == 14 ? 3 : 7));
                uint32_t v[16];
                if (layer == 0) poll_cnt(g_c1 + ((sl * 8 + (w >> 1) * 4 + (tile >> 2)) * 16 + (lane & 15)) * 32, kseq);
                ASTAMP(1);
                poll4_kv<32>(v, g_kv1 + ((sl * 16 + tile) * 16 + 4 * sq) * 32 + pk, tag);
#pragma unroll
                for (int k = 0; k < 4; k++) {
                    float lo = (bf_lo(v[k]) + bf_lo(v[4 + k])) + (bf_lo(v[8 + k]) + bf_lo(v[12 + k]));
                    float hi = (bf_hi(v[k]) + bf_hi(v[4 + k])) + (bf_hi(v[8 + k]) + bf_hi(v[12 + k]));
                    lo += __shfl_xor_sync(0xffffffffu, lo, 8); hi += __shfl_xor_sync(0xffffffffu, hi, 8);
                    lo += __shfl_xor_sync(0xffffffffu, lo, 16); hi += __shfl_xor_sync(0xffffffffu, hi, 16);
                    v[k] = pack2(lo, hi);
                }
                if (sq == 0) st_pkt<0>(g_kv2 + sl * 512 + 32 * tile + pk, settag(v[0], tag), v[1], v[2], v[3]);
            }
            ASTAMP(2);
            {
                const int item = t128 < 112 ? t128 : 112 + (t128 & 3), d = item >> 1;
                const int cc = t128 < 112 ? 2 * (d >= 28) + (item & 1) : item - 112;
                const int r = t128 < 112 ? d : 56 + (cc >> 1) + 2 * ((t128 - 112) >> 2);
                uint32_t ra = sb + OFF_KVB + r * 128 + 4 * cc, rx = (r & 7) << 4;
                asm volatile("" : "+r"(ra), "+r"(rx));
                FOR14(asm volatile("st.shared.u32 [%0+%2], %1;" ::"r"((ra ^ 8) + (((t & 7) << 4) ^ rx)), "r"(0), "n"((t >> 3) * 8192) : "memory"));
                uint32_t v[16];
                asm volatile("" : "+r"(ra), "+r"(rx));
                poll4_kv<8>(v, g_kv2 + sl * 512 + (item >> 3) * 32 + (item & 7), tag);
                FOR14(asm volatile("st.shared.u32 [%0+%2], %1;" ::"r"(ra + (((t & 7) << 4) ^ rx)), "r"(v[t < 7 ? t : t + 1]), "n"((t >> 3) * 8192) : "memory"));
                fence_async();
            }
            bar_arrive(3, 384);
            ASTAMP(3);
            }
        }
    } else {
        asm volatile("setmaxnreg.inc.sync.aligned.u32 232;");
        int lane = fresh_tid() & 31, prf = pr;
#define pr prf
#define g (lane >> 2)
#define c (lane & 3)
#define t128 (w * 32 + lane)
        const int wu = __shfl_sync(0xffffffffu, fresh_tid() >> 5, 0), w = wu & 3;
        const uint32_t xoff = __shfl_sync(0xffffffffu, (3 * PLANE + ((tile * 2 + wgi) * 8) * 512 + w * 128) * 16, 0);
        char* xu = reinterpret_cast<char*>(g_ex) + xoff;
#define FRESH() asm volatile("" : "+l"(xu), "+r"(lane), "+r"(prf))
#define xp0 (reinterpret_cast<uint4*>(xu) + lane)
        const uint32_t hbuf = sb + OFF_H + wgi * STAGE;
        uint32_t slot = 0, ph = 0, eb1 = 0, eb2 = 0, ackph = 0, rcvph = 0, gatph = 0, swp = 0;
        uint32_t ppid = 6;
#define cx(s) (reinterpret_cast<uint32_t*>(reinterpret_cast<uint4*>(xu) + PL(1) + 112 + (s) * 512))
#define stp (reinterpret_cast<uint4*>(xu) + g + PL(0) + 112)
        uint32_t seq = ld_word(cx(sl));
        uint32_t kseq = ld_word(g_c1 + ((sl * 8 + wu) * 16 + tile) * 32);
        uint32_t stag = ld_word(reinterpret_cast<const uint32_t*>(stp + sl * 512) + 3) & 1;
        asm volatile("barrier.cluster.wait.aligned;" ::: "memory");
        STAMP(1);
        uint32_t X[14];
        const uint32_t x0row = (w < 2 ? hbuf : sb + wgi * STAGE) + ((w & 1) * 16 + (lane & 15)) * 128;
        mbar_wait(BAR(wgi), 0);
        STAMP(51);
#pragma unroll
        for (int j = 0; j < 4; j++) {
            const int G = 7 * sl + min(2 * j + (lane >> 4), 6);
            uint32_t q2, q3;
            asm volatile("ldmatrix.sync.aligned.m8n8.x4.shared.b16 {%0,%1,%2,%3}, [%4];" : "=r"(X[4 * j]), "=r"(X[4 * j + 1]), "=r"(q2), "=r"(q3)
                         : "r"(x0row + (G >> 3) * 4096 + (((G ^ lane) & 7) << 4)) : "memory");
            if (j < 3) { X[(4 * j + 2) % 14] = q2; X[(4 * j + 3) % 14] = q3; }
        }
#define PUSH_SLICE(W)                                                                          \
    {                                                                                          \
        if (t128 == 0) mbar_expect_tx(BAR(B_RECV + wgi), 7168);                                \
        PUSH_BEGIN();                                                                          \
        const uint32_t ra = mapa(hbuf + 24576 + t128 * 16, hr ^ 1), rb = mapa(sb + OFF_XR + wgi * 3072, hr ^ 1), rbar = mapa(BAR(B_RECV + wgi), hr ^ 1); \
        st_async4(ra, W[0], W[1], W[2], W[3], rbar);                                           \
        st_async4(ra + 2048, W[4], W[5], W[6], W[7], rbar);                                    \
        st_async4(rb + t128 * 16, W[8], W[9], W[10], W[11], rbar);                             \
        asm volatile("st.async.weak.shared::cluster.mbarrier::complete_tx::bytes.v2.b32 [%0], {%1,%2}, [%3];" ::"r"(rb + 2048 + t128 * 8), "r"(W[12]), "r"(W[13]), "r"(rbar) : "memory"); \
    }
#define PULL_SLICE(W)                                                                          \
    {                                                                                          \
        uint32_t t0, t1;                                                                       \
        mbar_wait(BAR(B_RECV + wgi), rcvph);                                                   \
        rcvph ^= 1;                                                                            \
        lds4(&A[1][0], hbuf + 24576 + t128 * 16);                                              \
        lds4(&A[1][4], hbuf + 26624 + t128 * 16);                                              \
        lds4(&A[1][8], sb + OFF_XR + wgi * 3072 + t128 * 16);                                  \
        asm volatile("ld.shared.v2.u32 {%0,%1}, [%2];" : "=r"(t0), "=r"(t1) : "r"(sb + OFF_XR + wgi * 3072 + 2048 + t128 * 8) : "memory"); \
        _Pragma("unroll") for (int i = 0; i < 12; i++) A[0][i] = (i & 3) ? W[i] : W[i] & ~1u;  \
        A[1][0] &= ~1u; A[1][4] &= ~1u; A[1][8] &= ~1u;                                        \
        A[0][12] = (hr ? t0 : W[12]) & ~1u; A[0][13] = hr ? t1 : W[13];                        \
        A[1][12] = (hr ? W[12] : t0) & ~1u; A[1][13] = hr ? W[13] : t1;                        \
        asm volatile("" : RW4(A[0], 0), RW4(A[0], 4), RW4(A[0], 8), RW2(A[0], 12), RW4(A[1], 0), RW4(A[1], 4), RW4(A[1], 8), RW2(A[1], 12)); \
        swp = hr * 448;                                                                        \
    }
#define SWB(b, t, db, sh) ((b) == 0 && (t) < 6 ? ((t) < 3 ? db##p : db##m) : db)
#define DECL_DB(b, MK, lbo, sh) const uint64_t db = MK(0, lbo, R_ADJ), dbp = (b) == 0 ? MK(0, lbo, R_ADJ + (swp >> (sh))) : db, dbm = (b) == 0 ? MK(0, lbo, R_ADJ - (swp >> (sh))) : db;
#define PPB 2
#define PP_WAIT() if (wgi == 1) { bar_sync(ppid, 256); ppid ^= 14; }
#define PP_GO() if (wgi == 0) { bar_arrive(ppid, 256); ppid ^= 14; }
#define GAT_DST(B, s2) ((B) == 1 ? hbuf + w * 3584 + (s2) * 1792 : ((s2) ? sb + OFF_KVB + wgi * 8192 : hbuf + 14336) + w * 1792)
#define GAT_ISSUE(B, base)                                                                     \
    {                                                                                          \
        const char* gs = xu + ((base) + kblk(pr, B) * 1024) * 16;                              \
        asm volatile("{ .reg .pred e; elect.sync _|e, 0xffffffff;\n"                           \
                     "@e mbarrier.arrive.expect_tx.shared::cta.b64 _, [%3], 3584;\n"           \
                     "@e cp.async.bulk.shared::cluster.global.mbarrier::complete_tx::bytes [%0], [%2], 1792, [%3];\n" \
                     "@e cp.async.bulk.shared::cluster.global.mbarrier::complete_tx::bytes [%1], [%2+8192], 1792, [%3]; }" \
                     ::"r"(GAT_DST(B, 0)), "r"(GAT_DST(B, 1)), "l"(gs), "r"(BAR(B_GAT + wu * 2 + ((B) >> 1))) : "memory"); \
        __syncwarp();                                                                          \
    }
#define GAT_FETCH(B)                                                                           \
    {                                                                                          \
        mbar_wait(BAR(B_GAT + wu * 2 + ((B) >> 1)), (gatph >> (B)) & 1);                          \
        gatph ^= 1 << (B);                                                                     \
        _Pragma("unroll") for (int s2 = 0; s2 < 2; s2++) {                                     \
            const uint32_t ga = GAT_DST(B, s2) + lane * 16;                                    \
            lds4(&A[2 * (B) + s2][0], ga); lds4(&A[2 * (B) + s2][4], ga + 512); lds4(&A[2 * (B) + s2][8], ga + 1024); \
            asm volatile("ld.shared.v2.u32 {%0,%1}, [%2];" : "=r"(A[2 * (B) + s2][12]), "=r"(A[2 * (B) + s2][13]) : "r"(ga - lane * 8 + 1536) : "memory"); \
        }                                                                                      \
    }
#define LATE_ARRIVE() do { if (lane == 0) mbar_arrive(BAR(B_LATE)); } while (0)
#define LATE_WAIT() do { mbar_wait(BAR(B_LATE), gatph & 1); gatph ^= 1; } while (0)
#define PT 3
#define PREP(b, t, remote)                                                                     \
    if constexpr ((b) < 3 && (t) == ((b) ? PT : PT0)) {                                                      \
        wg_commit();                                                                           \
        STAMP(74 + 6 * (step & 1) + 2 * (b));                                                  \
        if (remote) {                                                                          \
            if constexpr ((b) == 0) { blk_load<2>(A, BLK(xsrc, 2), lane); if (XG3 == 3) blk_load<3>(A, BLK(xsrc, 3), lane); GAT_FETCH(1) }       \
            if constexpr ((b) == 2 && F3P) GAT_FETCH(3)                                        \
            blk_check<((b) + 1) & 3>(A, BLK(xsrc, (b) + 1), lane, xtag);                       \
            if constexpr ((b) == 0 && XG3 == 0) blk_load<3>(A, BLK(xsrc, 3), lane); \
            if constexpr ((b) == 0 && XG3 == 2) GAT_ISSUE(3, (step & 1) ? PL(2) : PL(0))                        \
        }                                                                                      \
        STAMP(75 + 6 * (step & 1) + 2 * (b));                                                  \
        normalize<((b) + 1) & 3>(A, k0, k1);                                                   \
        asm volatile("" : RW4(A[(2 * (b) + 2) & 7], 0), RW4(A[(2 * (b) + 2) & 7], 4), RW4(A[(2 * (b) + 2) & 7], 8), RW2(A[(2 * (b) + 2) & 7], 12), \
                          RW4(A[(2 * (b) + 3) & 7], 0), RW4(A[(2 * (b) + 3) & 7], 4), RW4(A[(2 * (b) + 3) & 7], 8), RW2(A[(2 * (b) + 3) & 7], 12)); \
        wg_fence();                                                                            \
    }
#define X0_BLOCK(b)                                                                            \
    { const int rr = lane & 7, hi = lane >> 4;                                                 \
    const uint32_t rowa = (w < 2 ? hbuf : sb + wgi * STAGE) + ((w & 1) * 16 + (lane & 15)) * 128; \
    FOR7(constexpr int G = 14 * (b) + (t < 3 ? 2 * t : (t < 6 ? 2 * t + 1 : 6));               \
         uint32_t q0, q1, q2, q3;                                                              \
         const uint32_t ad = t < 6 ? rowa + (((((G & 7) + hi) ^ rr) & 7) << 4) + ((G & 7) == 7 ? hi * 4096 : 0) : rowa + ((G + 7 * hi) >> 3) * 4096 + ((((G + 7 * hi) ^ rr) & 7) << 4); \
         asm volatile("ldmatrix.sync.aligned.m8n8.x4.shared.b16 {%0,%1,%2,%3}, [%4+%5];" : "=r"(q0), "=r"(q1), "=r"(q2), "=r"(q3) \
                      : "r"(ad), "n"(t < 6 ? (G >> 3) * 4096 : 0) : "memory");                 \
         if (t < 3) { A[2 * (b)][4 * t] = q0; A[2 * (b)][4 * t + 1] = q1; A[2 * (b)][4 * t + 2] = q2; A[2 * (b)][4 * t + 3] = q3; } \
         else if (t < 6) { A[2 * (b) + 1][(4 * t - 12) & 15] = q0; A[2 * (b) + 1][((4 * t - 12) & 15) + 1] = q1; A[2 * (b) + 1][((4 * t - 12) & 15) + 2] = q2; A[2 * (b) + 1][((4 * t - 12) & 15) + 3] = q3; } \
         else { A[2 * (b)][12] = q0; A[2 * (b)][13] = q1; A[2 * (b) + 1][12] = q2; A[2 * (b) + 1][13] = q3; }); }
#define BLK(base, b) ((base) + kblk(pr, b) * 1024)

#pragma unroll 1
        for (int step = 0; step < 4; step++) {
            FRESH();
            const uint32_t tag = (step >> 1) ^ 1;
            const int so = (step >> 1) * 24 + (step & 1) * 12;
            (void)so;
            uint32_t A[8][14];
            uint4* const xsrc = xp0 + ((step & 1) ? PL(2) : PL(0));
            const uint32_t xtag = (step & 1) ? tag : ((seq >> 3) & 1) ^ 1;
            uint32_t xbits;
            {
                float st[4];
                slice_stats(X, st);
                stag ^= 1;
                xbits = x_bits(X);
                tag_slice(X, xtag);
                if (step) send_slice<0>(xsrc + sl * 512, lane, X);
                if (c == 0) st_pkt<0>(stp + sl * 512, __float_as_uint(st[0]), __float_as_uint(st[1]), __float_as_uint(st[2]), settag(__float_as_uint(st[3]), stag));
            }
            STAMP(2 + so);
            uint32_t sv[8];
            if (step == 0) {
                X0_BLOCK(0) X0_BLOCK(1) X0_BLOCK(2) X0_BLOCK(3)
                mbar_wait(BAR(wgi ^ 1), 0);
                R_NEXT();
                R_NEXT();
                R_RELEASE(2);
                stat_load(sv, stp + c * 1024);
                stat_check(sv, stp + c * 1024, stag);
                STAMP(52 + step);
            } else {
                kill<14>(A[2]); kill<14>(A[3]); kill<14>(A[4]); kill<14>(A[5]); kill<14>(A[6]); kill<14>(A[7]);
                PUSH_SLICE(X)
                stat_load(sv, stp + c * 1024);
                PULL_SLICE(X)
                stat_check(sv, stp + c * 1024, stag);
                STAMP(52 + step);
                GAT_ISSUE(1, (step & 1) ? PL(2) : PL(0))
                if (XG3 == 1) GAT_ISSUE(3, (step & 1) ? PL(2) : PL(0))
            }
            LnCoef k0, k1;
            {
                k0 = ln_coef(__uint_as_float(sv[0]) + __uint_as_float(sv[4]), __uint_as_float(sv[1]) + __uint_as_float(sv[5]));
                k1 = ln_coef(__uint_as_float(sv[2]) + __uint_as_float(sv[6]), __uint_as_float(sv[3] & ~1u) + __uint_as_float(sv[7] & ~1u));
            }
            STAMP(3 + so);
            GSTAMP(70 + step);

            if ((step & 1) == 0) {
                float tq[28];
#define K_BLOCK(b)                                                                            \
    if ((b) == 1) R_RELEASE(1);                                                               \
    if ((b) == 2 + XT) PUSH_ACK();                                                            \
    if ((b) == 2 && XT && step && !F3P) GAT_FETCH(3)                                                  \
    if ((b) == 3) { wg_wait<2>(); R_RELEASE(1); }                                             \
    if (((b) & 1) == 0) R_WAIT();                                                             \
    { DECL_DB(b, BASE128, 16, 0)                                                              \
    wg_fence();                                                                               \
    FOR7(mma_rs56<1, D128(((b) & 1) * HALF, t)>(tq, AQ(A, b, t), (b) + t > 0, SWB(b, t, db, 0)); \
         PREP(b, t, step)); }                                                                 \
    wg_commit();                                                                              \
    if ((b) & 1) R_NEXT();
#define P_STAGE(acc, b0)                                                                      \
    R_WAIT();                                                                                 \
    { DECL_DB(b0, BASE128, 16, 0)                                                             \
    wg_fence();                                                                               \
    FOR7(mma_rs56<1, D128(0, t)>(acc, AQ(A, b0, t), (b0) + t > 0, SWB(b0, t, db, 0)));        \
    FOR7(mma_rs56<1, D128(HALF, t)>(acc, AQ(A, (b0) + 1, t), 1, db)); }                       \
    wg_commit();                                                                              \
    R_NEXT();
#define PROJECT(acc) P_STAGE(acc, 0) P_STAGE(acc, 2) wg_wait<1>(); R_RELEASE(2); wg_wait<0>(); R_RELEASE(1);
#define V_PASS()                                                                              \
    {                                                                                         \
        float av[28];                                                                         \
        PROJECT(av)                                                                           \
        const int m = lane >> 3, rr = lane & 7;                                               \
        const uint32_t rowa = hbuf + 16384 + (w * 16 + rr + 8 * (m & 1)) * 128;               \
        const uint32_t one = c == 0 ? 0x00003f80u : 0u;                                       \
        _Pragma("unroll") for (int j = 0; j < 4; j++) {                                       \
            const uint32_t a = rowa + (((2 * j + (m >> 1)) ^ rr) << 4);                       \
            if (j < 3) stsm4(a, pack2(av[8 * j], av[8 * j + 1]), pack2(av[8 * j + 2], av[8 * j + 3]), pack2(av[8 * j + 4], av[8 * j + 5]), pack2(av[8 * j + 6], av[8 * j + 7])); \
            else stsm4(a, pack2(av[24], av[25]), pack2(av[26], av[27]), one, one);            \
        }                                                                                     \
    }
                normalize<0>(A, k0, k1);
                K_BLOCK(0) K_BLOCK(1) K_BLOCK(2) K_BLOCK(3)
                wg_wait<0>();
                R_RELEASE(1);
                STAMP(4 + so);
                if (step == 0) { bar_sync(wgi ? 9 : 1, 224); }
                if (wgi == VW) V_PASS()
                uint32_t PH[28];
                int it = 1;
#pragma unroll 1
                do {
                    float pp[28];
                    phi_gemm(tq, pp);
                    dual_softmax(pp, PH);
                    if (((trips >> (it + 1)) & 1) == 0) continue;
                    {
                        const int m = lane >> 3, rr = lane & 7;
                        const uint32_t rowa = hbuf + (w * 16 + rr + 8 * (m & 1)) * 128;
#pragma unroll
                        for (int j = 0; j < 7; j++) {
                            const int cg = 2 * j + (m >> 1), hi = cg >= 7;
                            stsm4(rowa + hi * 8192 + (((cg - 7 * hi) ^ rr) << 4), PH[4 * j], PH[4 * j + 1], PH[4 * j + 2], PH[4 * j + 3]);
                        }
                    }
                    STAMP(5 + so);
                    if (wgi != VW) V_PASS()
                    fence_async();
                    bar_sync(2, 256);
                    float kv[28];
                    const uint64_t da = BASE128(OFF_H + 16384, 16, 0), dbk = BASE128(OFF_H, 16, wgi * 512);
                    wg_fence();
                    FOR8(constexpr uint64_t o = ((t >> 2) * STAGE + (t & 3) * 2048) >> 4; mma_ss56_tt<o, o>(kv, t > 0, da, dbk));
                    wg_commit();
                    wg_wait<0>();
#pragma unroll
                    for (int hf = 0; hf < 2; hf++) {
                        const int d = 16 * w + g + 8 * hf;
                        if ((d < 56 && (d >= 28) == (c >= 2)) || d == 56) {
                            const int item = d < 56 ? 2 * d + (c & 1) : 112 + c;
                            uint4* dst = g_kv1 + ((sl * 16 + (item >> 3)) * 16 + tile) * 32 + wgi * 16 + (item & 7);
#define KVW(i) pack2(kv[4 * (i) + 2 * hf], kv[4 * (i) + 2 * hf + 1])
                            st_pkt<0>(dst, settag(KVW(0), tag), KVW(1), KVW(2), KVW(3));
                            st_pkt<8>(dst, settag(KVW(4), tag), KVW(5), KVW(6), 0u);
                        }
                    }
                    __syncwarp();
                    kseq++;
                    if (lane == 0) st_word(g_c1 + ((sl * 8 + wu) * 16 + tile) * 32, kseq);
                    bar_arrive(7, 384);
                    STAMP(6 + so);
                    kill<28>(tq);
                    if (QPP) { PP_WAIT() }
                    P_STAGE(tq, 0) P_STAGE(tq, 2)
                    if (QPP) { PP_GO() }
                    wg_wait<1>(); R_RELEASE(2); wg_wait<0>(); R_RELEASE(1);
                    STAMP(7 + so);
                    kill<28>(PH);
                } while (((trips >> (++it)) & 1));
                STAMP(8 + so);
                FRESH();
                if (step) {
                    slice_load<PL(0)>(X, xp0 + sl * 512, lane);
                } else {
                    const uint32_t* xp = reinterpret_cast<const uint32_t*>(x_in + (size_t)(tile * 128 + wu * 16 + g) * 448 + 56 * sl + 2 * c);
#pragma unroll
                    for (int i = 0; i < 7; i++) { X[2 * i] = __ldg(xp + 4 * i); X[2 * i + 1] = __ldg(xp + 4 * i + 8 * 224); }
                }
                bar_sync(3, 384);
                STAMP(9 + so);
                const uint4* const osrc = xp0 + PL(1);
                {
                    float nm[32];
                    const uint64_t db = BASE128(OFF_KVB, 16, 0);
                    wg_fence();
                    FOR7(mma_rs64<0, ((t >> 2) * 8192 + (t & 3) * 32) / 16>(nm, PH[4 * t], PH[4 * t + 1], PH[4 * t + 2], PH[4 * t + 3], t > 0, db));
                    wg_commit();
                    wg_wait<0>();
                    LATE_ARRIVE();
                    const float i00 = rcp(nm[28] + 1e-6f), i01 = rcp(nm[29] + 1e-6f), i10 = rcp(nm[30] + 1e-6f), i11 = rcp(nm[31] + 1e-6f);
                    const float m0 = c >= 2 ? i01 : i00, m1 = c >= 2 ? i11 : i10;
                    uint32_t O[14];
#pragma unroll
                    for (int i = 0; i < 7; i++) {
                        const float f0 = i < 3 ? i00 : (i > 3 ? i01 : m0), f1 = i < 3 ? i10 : (i > 3 ? i11 : m1);
                        O[2 * i] = pack2(nm[4 * i] * f0, nm[4 * i + 1] * f0);
                        O[2 * i + 1] = pack2(nm[4 * i + 2] * f1, nm[4 * i + 3] * f1);
                    }
                    if (OST) { PP_WAIT() }
                    tag_slice(O, tag);
                    send_slice<PL(1)>(xp0 + sl * 512, lane, O);
                    seq++;
                    if (lane == 0) st_word(cx(sl), seq);
                    STAMP(10 + so);
                    PUSH_SLICE(O)
                    if (OST == 1) { PP_GO() }
                    const uint32_t cv = ld_word(cx(lane & 7));
                    PULL_SLICE(O)
                    LATE_WAIT();
                    check_cnt(cv, cx(lane & 7), seq);
                    if (OST == 2) { PP_GO() }
                    STAMP(56 + (step >> 1));
                    GAT_ISSUE(1, PL(1))
                    GAT_ISSUE(3, PL(1))
                    blk_load<2>(A, BLK(osrc, 2), lane);
                }
                float ao[28];
#define WO_BLOCK(b)                                                                           \
    if ((b) > 0) blk_check<b>(A, BLK(osrc, b), lane, tag);                                    \
    if (((b) & 1) == 0) R_WAIT();                                                             \
    { DECL_DB(b, BASE128, 16, 0)                                                              \
    wg_fence();                                                                               \
    FOR7(mma_rs56<1, D128(((b) & 1) * HALF, t)>(ao, AQ(A, b, t), (b) + t > 0, SWB(b, t, db, 0))); } \
    wg_commit();                                                                              \
    if ((b) & 1) R_NEXT();
                WO_BLOCK(0)
                STAMP(11 + so);
                GAT_FETCH(1)
                WO_BLOCK(1)
                WO_BLOCK(2)
                GAT_FETCH(3)
                WO_BLOCK(3)
                PUSH_ACK();
                wg_wait<0>();
                R_RELEASE(2);
                STAMP(12 + so);
                WSUM(86 + 7 * (step >> 1));
                x_fix(X, xbits);
#pragma unroll
                for (int i = 0; i < 14; i++) X[i] = pack2(bf_lo(X[i]) + ao[2 * i], bf_hi(X[i]) + ao[2 * i + 1]);
            } else {
                uint32_t H[56];
                float ag[64];
#define F1_EPI(dst, ng, ag)                                                                    \
    _Pragma("unroll") for (int i = 0; i < 2 * (ng); i++)                                       \
        (dst)[i] = pack2(geglu(ag[2 * i], ag[4 * (ng) + 2 * i]), geglu(ag[2 * i + 1], ag[4 * (ng) + 2 * i + 1]));
#define H_PUSH(h0, off) st_async4(rem_h + (off), H[h0], H[(h0) + 1], H[(h0) + 2], H[(h0) + 3], mapa(BAR(B_RECV2 + wgi), hr ^ 1));
#define F1_BLOCK(b, first)                                                                     \
    if ((first) && (b) == 1) R_RELEASE(2);                                                     \
    if ((first) && (b) == 2 + XT) PUSH_ACK();                                                  \
    if ((first) && (b) == 2 && XT && !F3P) GAT_FETCH(3)                                                \
    R_WAIT();                                                                                  \
    if ((b) == ((first) ? PPF : PPB)) { PP_WAIT() }                                            \
    { DECL_DB(b, BASE128, HALF, 0)                                                             \
    wg_fence();                                                                                \
    FOR7(mma_rs128<1, D128(0, t)>(ag, AQ(A, b, t), (b) + t > 0, SWB(b, t, db, 0));             \
         if constexpr (first) { PREP(b, t, true) }); }                                         \
    wg_commit();                                                                               \
    if ((b) == 3) { PP_GO() }                                                                  \
    if ((b) > 0) { wg_wait<1>(); R_RELEASE(1); }       \
    R_NEXT();
                normalize<0>(A, k0, k1);
                F1_BLOCK(0, true) F1_BLOCK(1, true) F1_BLOCK(2, true) F1_BLOCK(3, true)
                if (t128 == 0) { mbar_expect_tx(BAR(B_RECV + wgi), 16384); mbar_expect_tx(BAR(B_RECV2 + wgi), 12288); }
                PUSH_BEGIN();
                wg_wait<0>();
                R_RELEASE(1);
                int p = 0;
#pragma unroll 1
                do {
                    F1_EPI(H + 32, 8, ag)
                    STAMP(4 + p + so);
                    WSUM(81 + p + 7 * (step >> 1));
                    if (((trips >> (p + 1)) & 1) == 0) continue;
                    if (step == 1 && p == PKP) R_NEXT();
                    kill<64>(ag);
                    F1_BLOCK(0, false)
                    {
                        const uint32_t pk = (p ? hbuf + 16384 : sb + OFF_KVB + wgi * 8192) + w * 2048;
#pragma unroll
                        for (int k = 0; k < 4; k++) sts4(pk + k * 512 + lane * 16, H[32 + 4 * k], H[33 + 4 * k], H[34 + 4 * k], H[35 + 4 * k]);
                        fence_async();
                        __syncwarp();
                        asm volatile(ELECT "cp.async.bulk.shared::cluster.shared::cta.mbarrier::complete_tx::bytes [%0], [%1], 2048, [%2]; }"
                                     ::"r"(mapa(hbuf + p * 8192 + w * 2048, hr ^ 1)), "r"(pk), "r"(mapa(BAR(B_RECV + wgi), hr ^ 1)) : "memory");
                    }
                    F1_BLOCK(1, false) F1_BLOCK(2, false) F1_BLOCK(3, false)
                    wg_wait<0>();
                    R_RELEASE(1);
                    kill<16>(H + 32);
                } while (((trips >> (++p)) & 1));
#pragma unroll
                for (int k = 0; k < 4; k++) lds4(H + 16 + 4 * k, hbuf + 16384 + w * 2048 + k * 512 + lane * 16);
                __syncwarp();
                if (lane == 0) asm volatile("mbarrier.arrive.shared::cluster.b64 _, [%0];" ::"r"(mapa(BAR(B_ACK2 + wgi), hr ^ 1)) : "memory");
                const uint32_t rem_h = mapa(hbuf + w * 2048 + lane * 16, hr ^ 1);
#define F1_LAST(b0)                                                                            \
    R_WAIT();                                                                                  \
    if (b0) { PP_WAIT() }                                                                      \
    { DECL_DB(b0, BASE64, HALF, 1)                                                             \
    wg_fence();                                                                                \
    FOR7(mma_rs64<1, D64(0, t)>(al, AQ(A, b0, t), (b0) + t > 0, SWB(b0, t, db, 1)));           \
    FOR7(mma_rs64<1, D64(7168, t)>(al, AQ(A, (b0) + 1, t), 1, db)); }                          \
    wg_commit();                                                                               \
    if (b0) { PP_GO() }                                                                        \
    R_NEXT();
                float al[32];
                F1_LAST(0)
                mbar_wait(BAR(B_RECV + wgi), rcvph);
                rcvph ^= 1;
                mbar_wait(BAR(B_ACK2 + wgi), step >> 1);
                H_PUSH(32, 16384) H_PUSH(36, 16896)
                F1_LAST(2)
                H_PUSH(40, 17408) H_PUSH(44, 17920)
                wg_wait<1>();
                R_RELEASE(2);
                wg_wait<0>();
                R_RELEASE(1);
                uint32_t HP[56];
#pragma unroll
                for (int k = 0; k < 4; k++) lds4(H + 4 * k, sb + OFF_KVB + wgi * 8192 + w * 2048 + k * 512 + lane * 16);
#pragma unroll
                for (int t = 0; t < 8; t++) lds4(HP + 4 * t, hbuf + (t >> 2) * 8192 + w * 2048 + (t & 3) * 512 + lane * 16);
                F1_EPI(H + 48, 4, al)
                H_PUSH(48, 24576 - w * 1024) H_PUSH(52, 25088 - w * 1024)
                STAMP(7 + so);
                WSUM(84 + 7 * (step >> 1));
                FRESH();
                float acc[28];
                const uint32_t roA = hr ? 256u : 0u, roB = hr ? (uint32_t)-1536 : 0u;
                const uint32_t rpA = hr ? 0u : 256u, rpB = hr ? 0u : (uint32_t)-1536;
                float res[28];
                uint32_t v0[14], v1[14], P[14];
                Wide PW;
                const uint4* ps = xp0 + sl * 512;
#define F2_OWN_A()                                                                             \
    R_WAIT();                                                                                  \
    d0 = BASE128(0, 16, R_ADJ + roA); d1 = BASE128(0, 16, R_ADJ + roB);                        \
    wg_fence();                                                                                \
    FOR14(if constexpr (t < OT) mma_rs56<1, t * 128>(acc, H[4 * t], H[4 * t + 1], H[4 * t + 2], H[4 * t + 3], t > 0, d0)); \
    wg_commit();
#define F2_OWN_B()                                                                             \
    wg_fence();                                                                                \
    FOR14(if constexpr (t >= OT) mma_rs56<1, t * 128>(acc, H[4 * t], H[4 * t + 1], H[4 * t + 2], H[4 * t + 3], 1, t < 12 ? d0 : d1)); \
    wg_commit();                                                                               \
    R_NEXT();
#define F2_PEER()                                                                              \
    R_WAIT();                                                                                  \
    if (F2PP) { PP_WAIT() }                                                                    \
    d0 = BASE128(0, 16, R_ADJ + rpA); d1 = BASE128(0, 16, R_ADJ + rpB);                        \
    wg_fence();                                                                                \
    FOR14(mma_rs56<1, t * 128>(acc, HP[4 * t], HP[4 * t + 1], HP[4 * t + 2], HP[4 * t + 3], 1, t < 12 ? d0 : d1)); \
    wg_commit();                                                                               \
    if (F2PP) { PP_GO() }                                                                      \
    R_NEXT();
#define F2_TURN(u)                                                                             \
    wg_wait<1>();                                                                              \
    if ((u) < 2 || TDEF < 2) R_RELEASE(2);                                                     \
    wg_wait<0>();                                                                              \
    if ((u) < 2 || TDEF < 1) R_RELEASE(1);                                                     \
    _Pragma("unroll") for (int i = 0; i < 14; i++) P[i] = pack2(acc[2 * i], acc[2 * i + 1]);   \
    tag_slice(P, tag);                                                                         \
    PW = widen(P);                                                                             \
    kill<28>(acc);                                                                             \
    F2_OWN_A()                                                                                 \
    if ((u) == 2) { slice_load<PL(3)>(v0, ps, lane); slice_load<PL(4)>(v1, ps, lane); } \
    send_wide<PL(3 + (u))>(xp0 + (2 * ((pr + (u) + 1) & 3) + hr) * 512, lane, PW);             \
    seq++;                                                                                     \
    if (lane == 0) st_word(cx(sl), seq);                                                       \
    __syncwarp();                                                                              \
    STAMP(8 + (u) + so);                                                                       \
    F2_OWN_B()
                uint64_t d0, d1;
                F2_OWN_A()
                F2_OWN_B()
                R_WAIT();
                d0 = BASE128(0, 16, R_ADJ + rpA); d1 = BASE128(0, 16, R_ADJ + rpB);
                wg_fence();
                FOR8(mma_rs56<1, t * 128>(acc, HP[4 * t], HP[4 * t + 1], HP[4 * t + 2], HP[4 * t + 3], 1, d0));
                wg_commit();
                mbar_wait(BAR(B_RECV2 + wgi), step >> 1);
#pragma unroll
                for (int k = 0; k < 4; k++) lds4(HP + 32 + 4 * k, hbuf + 16384 + w * 2048 + k * 512 + lane * 16);
                lds4(HP + 48, hbuf + 24576 + w * 1024 + lane * 16);
                lds4(HP + 52, hbuf + 25088 + w * 1024 + lane * 16);
                if (step == 1) PUSH_ACK();
                wg_fence();
                FOR14(if constexpr (t >= 8) mma_rs56<1, t * 128>(acc, HP[4 * t], HP[4 * t + 1], HP[4 * t + 2], HP[4 * t + 3], 1, t < 12 ? d0 : d1));
                wg_commit();
                R_NEXT();
                F2_TURN(0)
                F2_PEER()
                F2_TURN(1)
                F2_PEER()
                F2_TURN(2)
                if (step == 1) STAMP(64);
                slice_check<PL(3)>(v0, ps, lane, tag);
                slice_check<PL(4)>(v1, ps, lane, tag);
#pragma unroll
                for (int i = 0; i < 14; i++) { res[2 * i] = bf_lo(v0[i]) + bf_lo(v1[i]); res[2 * i + 1] = bf_hi(v0[i]) + bf_hi(v1[i]); }
                slice_load<PL(2)>(X, ps, lane);
                if (step == 1) STAMP(65);
                F2_PEER()
                if (step == 1) STAMP(66);
                poll_cnt(cx(2 * ((pr + 1) & 3) + hr), seq);
                if (step == 1) STAMP(67);
                slice_load<PL(5)>(v0, ps, lane);
                x_fix(X, xbits);
                slice_check<PL(5)>(v0, ps, lane, tag);
                if (lane < TDEF) mbar_arrive(BAR(B_EMPTY + (slot + NST - 3 - lane) % NST));
#pragma unroll
                for (int i = 0; i < 14; i++) { res[2 * i] += bf_lo(v0[i]); res[2 * i + 1] += bf_hi(v0[i]); }
                STAMP(11 + so);
                wg_wait<0>();
                R_RELEASE(2);
                STAMP(12 + so);
                WSUM(85 + 7 * (step >> 1));
#pragma unroll
                for (int i = 0; i < 14; i++) X[i] = pack2(fmaf(res[2 * i] + acc[2 * i], 0.5f, bf_lo(X[i])), fmaf(res[2 * i + 1] + acc[2 * i + 1], 0.5f, bf_hi(X[i])));
            }
        }
        {
            const int m = lane >> 3, rr = lane & 7;
            const uint32_t ob = hbuf + w * 2048, rowa = ob + (rr + 8 * (m & 1)) * 112 + (m >> 1) * 16;
#pragma unroll
            for (int j = 0; j < 3; j++) stsm4(rowa + 32 * j, X[4 * j], X[4 * j + 1], X[4 * j + 2], X[4 * j + 3]);
            asm volatile("stmatrix.sync.aligned.m8n8.x2.shared.b16 [%0], {%1,%2};" ::"r"(ob + (rr + 8 * (m & 1)) * 112 + 96), "r"(X[12]), "r"(X[13]) : "memory");
            fence_async();
            __syncwarp();
            if (lane == 0) {
                asm volatile("cp.async.bulk.tensor.2d.global.shared::cta.bulk_group [%0, {%2, %3}], [%1];" ::"l"(&maps.out), "r"(ob), "r"(56 * sl), "r"(tile * 128 + wu * 16) : "memory");
                asm volatile("cp.async.bulk.commit_group;" ::: "memory");
                asm volatile("cp.async.bulk.wait_group.read 0;" ::: "memory");
            }
        }
        STAMP(50);
        GSTAMP(61);
        PDUMP();
    }
}

#undef g
#undef pr
#undef c
#undef t128

typedef CUresult (*EncodeFn)(CUtensorMap*, CUtensorMapDataType, cuuint32_t, void*, const cuuint64_t*, const cuuint64_t*, const cuuint32_t*,
                             const cuuint32_t*, CUtensorMapInterleave, CUtensorMapSwizzle, CUtensorMapL2promotion, CUtensorMapFloatOOBfill);

static void make_map(EncodeFn enc, CUtensorMap* m, const void* p, uint64_t cols, uint64_t rows, uint32_t bc, uint32_t br, CUtensorMapSwizzle sw) {
    cuuint64_t gd[2] = {cols, rows};
    cuuint64_t gs[1] = {cols * 2};
    cuuint32_t bd[2] = {bc, br};
    cuuint32_t es[2] = {1, 1};
    enc(m, CU_TENSOR_MAP_DATA_TYPE_BFLOAT16, 2, const_cast<void*>(p), gd, gs, bd, es, CU_TENSOR_MAP_INTERLEAVE_NONE, sw,
        CU_TENSOR_MAP_L2_PROMOTION_L2_128B, CU_TENSOR_MAP_FLOAT_OOB_FILL_NONE);
}

extern "C" void kernel_launch(void* const* d_in, const int* in_sizes, int n_in, void* d_out, int out_size) {
    (void)in_sizes; (void)n_in; (void)out_size;
    static EncodeFn enc = nullptr;
    static Scratch* scratch = nullptr;
    if (!enc) {
        void* fn = nullptr;
        cudaDriverEntryPointQueryResult qr;
        cudaGetDriverEntryPoint("cuTensorMapEncodeTiled", &fn, cudaEnableDefault, &qr);
        enc = (EncodeFn)fn;
        cudaGetSymbolAddress((void**)&scratch, g_scratch);
        cudaFuncSetAttribute(fused_kernel, cudaFuncAttributeMaxDynamicSharedMemorySize, SMEM_BYTES);
    }
    Maps maps;
    {
        cuuint64_t gd[3] = {64, 2048, 7};
        cuuint64_t gs[2] = {896, 128};
        cuuint32_t bd[3] = {64, 32, 7};
        cuuint32_t es[3] = {1, 1, 1};
        enc(&maps.x, CU_TENSOR_MAP_DATA_TYPE_BFLOAT16, 3, d_in[0], gd, gs, bd, es, CU_TENSOR_MAP_INTERLEAVE_NONE, CU_TENSOR_MAP_SWIZZLE_128B,
            CU_TENSOR_MAP_L2_PROMOTION_L2_128B, CU_TENSOR_MAP_FLOAT_OOB_FILL_NONE);
    }
    make_map(enc, &maps.out, d_out, 448, 2048, 56, 16, CU_TENSOR_MAP_SWIZZLE_NONE);
    make_map(enc, &maps.qkv, d_in[1], 1344, 448, 64, 112, CU_TENSOR_MAP_SWIZZLE_128B);
    make_map(enc, &maps.wo, d_in[3], 448, 448, 64, 112, CU_TENSOR_MAP_SWIZZLE_128B);
    make_map(enc, &maps.wg, d_in[5], 1792, 448, 64, 112, CU_TENSOR_MAP_SWIZZLE_128B);
    make_map(enc, &maps.wu, d_in[6], 1792, 448, 64, 112, CU_TENSOR_MAP_SWIZZLE_128B);
    make_map(enc, &maps.wg32, d_in[5], 1792, 448, 32, 112, CU_TENSOR_MAP_SWIZZLE_64B);
    make_map(enc, &maps.wu32, d_in[6], 1792, 448, 32, 112, CU_TENSOR_MAP_SWIZZLE_64B);
    make_map(enc, &maps.wd, d_in[7], 448, 1792, 64, 112, CU_TENSOR_MAP_SWIZZLE_128B);
    fused_kernel<<<128, 384, SMEM_BYTES>>>(scratch, (const __nv_bfloat16*)d_in[0], (const __nv_bfloat16*)d_in[2], 7, (const __nv_bfloat16*)d_in[5],
                                           (const __nv_bfloat16*)d_in[6], (const __nv_bfloat16*)d_in[7], maps);
}
```

```cpp
#include <cuda_runtime.h>
#include <cuda.h>
#include <cuda_bf16.h>
#include <stdint.h>
#include <type_traits>

#define PPF 2
#define PKP 0
#define TDEF 1
#define TMPF 0
#define NORM1 0
#define LPARK 1
#define PFN 9
#define VW 1
#define QPP 1
#define XG3 2
#define XT (XG3 == 1 || XG3 == 2)
#define ACAN 0
#define SPLIT0 1
#define OT 2
#define F2PP 0
#define PPK 2
#define QE 1
#define OST 1
#define PP

namespace {

constexpr uint32_t STAGE = 28672, HALF = 14336;
constexpr int NST = 5;
constexpr uint32_t OFF_H = NST * STAGE;
constexpr uint32_t OFF_KVB = OFF_H + 2 * STAGE;
constexpr uint32_t OFF_WPHI = OFF_KVB + 16384;
constexpr uint32_t OFF_XR = OFF_WPHI + 7168;
constexpr uint32_t OFF_BAR = OFF_XR + 6144;
constexpr uint32_t SMEM_BYTES = OFF_BAR + 384 + 1408;
constexpr int B_EMPTY = NST, B_RECV = 2 * NST, B_RECV2 = B_RECV + 2, B_PACK = B_RECV2 + 2, B_GAT = B_PACK + 1, B_LATE = B_GAT + 16, B_ACK = B_LATE + 1, B_ACK2 = B_ACK + 2, B_COUNT = B_ACK2 + 2;

constexpr int PACK = 14 + 4 * PKP;

struct Maps { CUtensorMap x, qkv, wo, wg, wu, wg32, wu32, wd, out; };

}

constexpr int PLANE = 16 * 2 * 8 * 512;
struct Scratch {
    uint4 ex[6 * PLANE];
    uint4 kv1[8 * 16 * 16 * 32];
    uint4 kv2[8 * 512];
    uint32_t c1[8 * 8 * 16 * 32];
    uint32_t cw[8 * 32];
    uint4 wp[8 * 32 * (HALF / 16)];
};
__device__ __align__(1024) Scratch g_scratch;
#define g_ex (sc->ex)
#define g_kv1 (sc->kv1)
#define g_kv2 (sc->kv2)
#define g_c1 (sc->c1)
#define g_cw (sc->cw)
#define g_wp (sc->wp)
#define STAMP(i)
#define GSTAMP(i)
#define PDUMP()
#define ASTAMP(i)

namespace {

__device__ __forceinline__ int fresh_tid() { int t; asm volatile("mov.u32 %0, %%tid.x;" : "=r"(t)); return t; }
template <int N> __device__ __forceinline__ void kill(uint32_t* v) {
#pragma unroll
    for (int i = 0; i < N; i++) v[i] = 0;
}
template <int N> __device__ __forceinline__ void kill(float* v) {
#pragma unroll
    for (int i = 0; i < N; i++) v[i] = 0.f;
}
__device__ __forceinline__ uint32_t s2u(const void* p) { return (uint32_t)__cvta_generic_to_shared(p); }
__device__ __forceinline__ void mbar_init(uint32_t a, uint32_t c) { asm volatile("mbarrier.init.shared::cta.b64 [%0], %1;" ::"r"(a), "r"(c) : "memory"); }
__device__ __forceinline__ void mbar_expect_tx(uint32_t a, uint32_t b) { asm volatile("mbarrier.arrive.expect_tx.shared::cta.b64 _, [%0], %1;" ::"r"(a), "r"(b) : "memory"); }
__device__ __forceinline__ void mbar_arrive(uint32_t a) { asm volatile("mbarrier.arrive.shared::cta.b64 _, [%0];" ::"r"(a) : "memory"); }
#define GIVE_UP(id) "trap;\n"
#define SPIN_MAX "0x400000"
#define SPIN_TAIL(id) "add.u32 n, n, 1;\n setp.lt.u32 p, n, " SPIN_MAX ";\n @p bra.uni LP;\n" GIVE_UP(id) " DN:\n }"
__device__ __forceinline__ void mbar_wait(uint32_t a, uint32_t ph) {
    asm volatile("{ .reg .pred p; .reg .b32 n; mov.u32 n, 0;\n LP:\n"
                 "mbarrier.try_wait.parity.shared::cta.b64 p, [%0], %1;\n @p bra DN;\n"
                 "add.u32 n, n, 1;\n setp.lt.u32 p, n, " SPIN_MAX ";\n @p bra LP;\n"
                 GIVE_UP("")
                 " DN:\n }" ::"r"(a), "r"(ph) : "memory");
}
#define ELECT "{ .reg .pred e; elect.sync _|e, 0xffffffff; @e "
__device__ __forceinline__ void tma2d(uint32_t dst, const CUtensorMap* m, int c0, int c1, uint32_t bar) {
    asm volatile(ELECT "cp.async.bulk.tensor.2d.shared::cluster.global.mbarrier::complete_tx::bytes [%0], [%1, {%3, %4}], [%2]; }" ::"r"(dst), "l"(m), "r"(bar), "r"(c0), "r"(c1) : "memory");
}
__device__ __forceinline__ void tma3x(uint32_t dst, const CUtensorMap* m, int row, uint32_t bar) {
    asm volatile(ELECT "cp.async.bulk.tensor.3d.shared::cluster.global.mbarrier::complete_tx::bytes [%0], [%1, {0, %3, 0}], [%2]; }" ::"r"(dst), "l"(m), "r"(bar), "r"(row) : "memory");
}
template <int OFF>
__device__ __forceinline__ void ld_pkt(uint32_t* v, const uint4* p) {
    asm volatile("{ .reg .b128 t; ld.relaxed.gpu.global.b128 t, [%4+%5]; mov.b128 {%0,%1,%2,%3}, t; }" : "=r"(v[0]), "=r"(v[1]), "=r"(v[2]), "=r"(v[3]) : "l"(p), "n"(OFF * 16) : "memory");
}
template <int OFF>
__device__ __forceinline__ void st_pkt(uint4* p, uint32_t a, uint32_t b, uint32_t c, uint32_t d) {
    asm volatile("{ .reg .b128 t; mov.b128 t, {%1,%2,%3,%4}; st.relaxed.gpu.global.b128 [%0+%5], t; }" ::"l"(p), "r"(a), "r"(b), "r"(c), "r"(d), "n"(OFF * 16) : "memory");
}
__device__ __forceinline__ uint32_t pack2(float lo, float hi) {
    uint32_t r;
    asm("cvt.rn.bf16x2.f32 %0, %1, %2;" : "=r"(r) : "f"(hi), "f"(lo));
    return r;
}
__device__ __forceinline__ float bf_lo(uint32_t w) { return __uint_as_float(w << 16); }
__device__ __forceinline__ float bf_hi(uint32_t w) { return __uint_as_float(w & 0xffff0000u); }
__device__ __forceinline__ uint32_t settag(uint32_t w, uint32_t tag) { return (w & ~1u) | tag; }
__device__ __forceinline__ float ex2(float x) { float y; asm("ex2.approx.ftz.f32 %0, %1;" : "=f"(y) : "f"(x)); return y; }
__device__ __forceinline__ float rcp(float x) { float y; asm("rcp.approx.ftz.f32 %0, %1;" : "=f"(y) : "f"(x)); return y; }
__device__ __forceinline__ float tanh_hw(float x) { float y; asm("tanh.approx.f32 %0, %1;" : "=f"(y) : "f"(x)); return y; }
__device__ __forceinline__ void stsm4(uint32_t addr, uint32_t a, uint32_t b, uint32_t c, uint32_t d) {
    asm volatile("stmatrix.sync.aligned.m8n8.x4.shared.b16 [%0], {%1,%2,%3,%4};" ::"r"(addr), "r"(a), "r"(b), "r"(c), "r"(d) : "memory");
}
__device__ __forceinline__ void fence_async() { asm volatile("fence.proxy.async.shared::cta;" ::: "memory"); }
__device__ __forceinline__ void bar_sync(int id, int n) { asm volatile("bar.sync %0, %1;" ::"r"(id), "r"(n) : "memory"); }
__device__ __forceinline__ void bar_arrive(int id, int n) { asm volatile("bar.arrive %0, %1;" ::"r"(id), "r"(n) : "memory"); }
__device__ __forceinline__ void wg_fence() { asm volatile("wgmma.fence.sync.aligned;" ::: "memory"); }
__device__ __forceinline__ void wg_commit() { asm volatile("wgmma.commit_group.sync.aligned;" ::: "memory"); }
template <int N> __device__ __forceinline__ void wg_wait() { asm volatile("wgmma.wait_group.sync.aligned %0;" ::"n"(N) : "memory"); }

constexpr uint32_t SB0 = 1024;
__host__ __device__ constexpr uint32_t dlo(uint32_t off, uint32_t lbo) { return ((SB0 + off) >> 4) | ((lbo >> 4) << 16); }
__host__ __device__ constexpr uint32_t dhi(uint32_t sbo, uint32_t sw) { return (sbo >> 4) | (sw << 30); }
__device__ __forceinline__ uint64_t dbase(uint32_t lo, uint32_t hi) { uint64_t d; asm volatile("mov.b64 %0, {%1, %2};" : "=l"(d) : "r"(lo), "r"(hi)); return d; }
#define BASE128(off, lbo, adj) dbase(dlo(off, lbo) + (adj), dhi(1024, 1))
#define BASE64(off, lbo, adj) dbase(dlo(off, lbo) + (adj), dhi(512, 2))

#define ACC4(d, o) "+f"(d[o]), "+f"(d[o + 1]), "+f"(d[o + 2]), "+f"(d[o + 3])
#define ACC28(d) ACC4(d, 0), ACC4(d, 4), ACC4(d, 8), ACC4(d, 12), ACC4(d, 16), ACC4(d, 20), ACC4(d, 24)
#define ACC32(d, o) ACC4(d, o), ACC4(d, o + 4), ACC4(d, o + 8), ACC4(d, o + 12), ACC4(d, o + 16), ACC4(d, o + 20), ACC4(d, o + 24), ACC4(d, o + 28)

template <int TB, uint64_t D>
__device__ __forceinline__ void mma_rs56(float* d, uint32_t a0, uint32_t a1, uint32_t a2, uint32_t a3, int sd, uint64_t base) {
    asm volatile("{ .reg .pred p; .reg .b64 db; setp.ne.b32 p, %32, 0; add.u64 db, %33, %34;\n"
                 "wgmma.mma_async.sync.aligned.m64n56k16.f32.bf16.bf16 "
                 "{%0,%1,%2,%3,%4,%5,%6,%7,%8,%9,%10,%11,%12,%13,%14,%15,%16,%17,%18,%19,%20,%21,%22,%23,%24,%25,%26,%27}, "
                 "{%28,%29,%30,%31}, db, p, 1, 1, %35; }\n"
                 : ACC28(d)
                 : "r"(a0), "r"(a1), "r"(a2), "r"(a3), "r"(sd), "l"(base), "n"(D), "n"(TB));
}
template <int TB, uint64_t D>
__device__ __forceinline__ void mma_rs64(float* d, uint32_t a0, uint32_t a1, uint32_t a2, uint32_t a3, int sd, uint64_t base) {
    asm volatile("{ .reg .pred p; .reg .b64 db; setp.ne.b32 p, %36, 0; add.u64 db, %37, %38;\n"
                 "wgmma.mma_async.sync.aligned.m64n64k16.f32.bf16.bf16 "
                 "{%0,%1,%2,%3,%4,%5,%6,%7,%8,%9,%10,%11,%12,%13,%14,%15,%16,%17,%18,%19,%20,%21,%22,%23,%24,%25,%26,%27,%28,%29,%30,%31}, "
                 "{%32,%33,%34,%35}, db, p, 1, 1, %39; }\n"
                 : ACC32(d, 0)
                 : "r"(a0), "r"(a1), "r"(a2), "r"(a3), "r"(sd), "l"(base), "n"(D), "n"(TB));
}
template <int TB, uint64_t D>
__device__ __forceinline__ void mma_rs128(float* d, uint32_t a0, uint32_t a1, uint32_t a2, uint32_t a3, int sd, uint64_t base) {
    asm volatile("{ .reg .pred p; .reg .b64 db; setp.ne.b32 p, %68, 0; add.u64 db, %69, %70;\n"
                 "wgmma.mma_async.sync.aligned.m64n128k16.f32.bf16.bf16 "
                 "{%0,%1,%2,%3,%4,%5,%6,%7,%8,%9,%10,%11,%12,%13,%14,%15,%16,%17,%18,%19,%20,%21,%22,%23,%24,%25,%26,%27,%28,%29,%30,%31,%32,%33,%34,%35,%36,%37,%38,%39,%40,%41,%42,%43,%44,%45,%46,%47,%48,%49,%50,%51,%52,%53,%54,%55,%56,%57,%58,%59,%60,%61,%62,%63}, "
                 "{%64,%65,%66,%67}, db, p, 1, 1, %71; }\n"
                 : ACC32(d, 0), ACC32(d, 32)
                 : "r"(a0), "r"(a1), "r"(a2), "r"(a3), "r"(sd), "l"(base), "n"(D), "n"(TB));
}
template <uint64_t DA, uint64_t DB>
__device__ __forceinline__ void mma_ss56_tt(float* d, int sd, uint64_t ba, uint64_t bb) {
    asm volatile("{ .reg .pred p; .reg .b64 da, db; setp.ne.b32 p, %28, 0; add.u64 da, %29, %31; add.u64 db, %30, %32;\n"
                 "wgmma.mma_async.sync.aligned.m64n56k16.f32.bf16.bf16 "
                 "{%0,%1,%2,%3,%4,%5,%6,%7,%8,%9,%10,%11,%12,%13,%14,%15,%16,%17,%18,%19,%20,%21,%22,%23,%24,%25,%26,%27}, "
                 "da, db, p, 1, 1, 1, 1; }\n"
                 : ACC28(d)
                 : "r"(sd), "l"(ba), "l"(bb), "n"(DA), "n"(DB));
}
template <int... I> struct Seq {};
template <class F, int... I> __device__ __forceinline__ void static_for_impl(F&& f, Seq<I...>) { (f(std::integral_constant<int, I>{}), ...); }
#define FOR7(...) static_for_impl([&](auto T_) { constexpr int t = decltype(T_)::value; __VA_ARGS__; }, Seq<0, 1, 2, 3, 4, 5, 6>{})
#define FOR8(...) static_for_impl([&](auto T_) { constexpr int t = decltype(T_)::value; __VA_ARGS__; }, Seq<0, 1, 2, 3, 4, 5, 6, 7>{})
#define FOR14(...) static_for_impl([&](auto T_) { constexpr int t = decltype(T_)::value; __VA_ARGS__; }, Seq<0, 1, 2, 3, 4, 5, 6, 7, 8, 9, 10, 11, 12, 13>{})

__device__ __forceinline__ int kblk(int p, int b) { return b == 0 ? p : b - (b <= p); }
__host__ __device__ constexpr int krow(int t) { return t < 3 ? 16 * t : (t < 6 ? 56 + 16 * (t - 3) : 48); }
#define AQ(A, b, t) ((t) < 3 ? A[2 * (b)][4 * (t)] : (t) < 6 ? A[2 * (b) + 1][4 * ((t) - 3)] : A[2 * (b)][12]), \
                    ((t) < 3 ? A[2 * (b)][4 * (t) + 1] : (t) < 6 ? A[2 * (b) + 1][4 * ((t) - 3) + 1] : A[2 * (b)][13]), \
                    ((t) < 3 ? A[2 * (b)][4 * (t) + 2] : (t) < 6 ? A[2 * (b) + 1][4 * ((t) - 3) + 2] : A[2 * (b) + 1][12]), \
                    ((t) < 3 ? A[2 * (b)][4 * (t) + 3] : (t) < 6 ? A[2 * (b) + 1][4 * ((t) - 3) + 3] : A[2 * (b) + 1][13])
#define D128(off, t) ((uint64_t)(((off) + krow(t) * 128) >> 4) + ((uint64_t)((t) == 6 ? (7168 - 1024) >> 4 : 0) << 32))
#define D64(off, t) ((uint64_t)(((off) + krow(t) * 64) >> 4) + ((uint64_t)((t) == 6 ? (3584 - 512) >> 4 : 0) << 32))

#define PL(k) (((k) - 3) * PLANE)
__device__ __forceinline__ void st_word(uint32_t* p, uint32_t v) { asm volatile("st.relaxed.gpu.global.u32 [%0], %1;" ::"l"(p), "r"(v) : "memory"); }
__device__ __forceinline__ uint32_t ld_word(const uint32_t* p) { uint32_t v; asm volatile("ld.relaxed.gpu.global.u32 %0, [%1];" : "=r"(v) : "l"(p) : "memory"); return v; }
__device__ __forceinline__ void tag_slice(uint32_t* w, uint32_t tag) { w[0] = settag(w[0], tag); w[4] = settag(w[4], tag); w[8] = settag(w[8], tag); w[12] = settag(w[12], tag); }
template <int O>
__device__ __forceinline__ void send_slice(uint4* dst, int lane, const uint32_t* w) {
    st_pkt<O>(dst, w[0], w[1], w[2], w[3]);
    st_pkt<O + 32>(dst, w[4], w[5], w[6], w[7]);
    st_pkt<O + 64>(dst, w[8], w[9], w[10], w[11]);
    asm volatile("{ .reg .b64 t; mov.b64 t, {%1,%2}; st.relaxed.gpu.global.b64 [%0+%3], t; }" ::"l"((char*)dst - lane * 8), "r"(w[12]), "r"(w[13]), "n"(16 * (O + 96)) : "memory");
}
struct Wide { unsigned __int128 q[3]; uint64_t h; };
__device__ __forceinline__ Wide widen(const uint32_t* w) {
    Wide r;
#pragma unroll
    for (int k = 0; k < 3; k++) asm volatile("mov.b128 %0, {%1,%2,%3,%4};" : "=q"(r.q[k]) : "r"(w[4 * k]), "r"(w[4 * k + 1]), "r"(w[4 * k + 2]), "r"(w[4 * k + 3]));
    asm volatile("mov.b64 %0, {%1,%2};" : "=l"(r.h) : "r"(w[12]), "r"(w[13]));
    return r;
}
template <int O>
__device__ __forceinline__ void send_wide(uint4* dst, int lane, const Wide& v) {
    asm volatile("st.relaxed.gpu.global.b128 [%0+%4], %1;\n st.relaxed.gpu.global.b128 [%0+%5], %2;\n st.relaxed.gpu.global.b128 [%0+%6], %3;"
                 ::"l"(dst), "q"(v.q[0]), "q"(v.q[1]), "q"(v.q[2]), "n"(16 * O), "n"(16 * (O + 32)), "n"(16 * (O + 64)) : "memory");
    asm volatile("st.relaxed.gpu.global.b64 [%0+%2], %1;" ::"l"((char*)dst - lane * 8), "l"(v.h), "n"(16 * (O + 96)) : "memory");
}
#define RW4(v, o) "+r"(v[o]), "+r"(v[(o) + 1]), "+r"(v[(o) + 2]), "+r"(v[(o) + 3])
#define RW2(v, o) "+r"(v[o]), "+r"(v[(o) + 1])
#define WR4(v, o) "=&r"(v[o]), "=&r"(v[(o) + 1]), "=&r"(v[(o) + 2]), "=&r"(v[(o) + 3])
#define LDP(a, b, c, d, addr, off) "ld.relaxed.gpu.global.b128 q, [" addr "+" off "];\n mov.b128 {" a "," b "," c "," d "}, q;\n"
#define LDH(a, b, addr, off) "ld.relaxed.gpu.global.b64 h, [" addr "+" off "];\n mov.b64 {" a "," b "}, h;\n"
#define VOTE_OK "and.b32 t, t, 1;\n setp.ne.u32 p, t, 0;\n vote.sync.any.pred p, p, 0xffffffff;\n @!p bra.uni DN;\n"
#define CHK(x, tag) "lop3.b32 t, " x ", " tag ", t, 0xBE;\n"
__device__ __forceinline__ void check_cnt(uint32_t v, const uint32_t* p, uint32_t target) {
    asm volatile("{ .reg .pred p; .reg .b32 n, t; mov.u32 n, 0; mov.u32 t, %2;\n LP:\n"
                 "sub.s32 t, t, %1;\n setp.lt.s32 p, t, 0;\n vote.sync.any.pred p, p, 0xffffffff;\n @!p bra.uni DN;\n ld.relaxed.gpu.global.u32 t, [%0];\n" SPIN_TAIL("7")
                 ::"l"(p), "r"(target), "r"(v) : "memory");
}
__device__ __forceinline__ void poll_cnt(const uint32_t* p, uint32_t target) {
    asm volatile("{ .reg .pred p; .reg .b32 n, t; mov.u32 n, 0;\n LP:\n"
                 "ld.relaxed.gpu.global.u32 t, [%0];\n sub.s32 t, t, %1;\n setp.lt.s32 p, t, 0;\n vote.sync.any.pred p, p, 0xffffffff;\n @!p bra.uni DN;\n" SPIN_TAIL("1")
                 ::"l"(p), "r"(target) : "memory");
}
template <int STR>
__device__ __forceinline__ void poll4_kv(uint32_t* v, const uint4* p, uint32_t tag) {
    asm volatile("{ .reg .pred p; .reg .b32 n, t; .reg .b128 q; mov.u32 n, 0;\n LP:\n"
                 LDP("%0", "%1", "%2", "%3", "%16", "0") LDP("%4", "%5", "%6", "%7", "%16", "%18")
                 LDP("%8", "%9", "%10", "%11", "%16", "%19") LDP("%12", "%13", "%14", "%15", "%16", "%20")
                 "xor.b32 t, %0, %17;\n" CHK("%4", "%17") CHK("%8", "%17") CHK("%12", "%17") VOTE_OK SPIN_TAIL("2")
                 : WR4(v, 0), WR4(v, 4), WR4(v, 8), WR4(v, 12)
                 : "l"(p), "r"(tag), "n"(16 * STR), "n"(32 * STR), "n"(48 * STR)
                 : "memory");
}
template <int B>
__device__ __forceinline__ void blk_load(uint32_t (&A)[8][14], const uint4* src, int lane) {
    ld_pkt<0>(&A[2 * B][0], src); ld_pkt<32>(&A[2 * B][4], src); ld_pkt<64>(&A[2 * B][8], src);
    ld_pkt<512>(&A[2 * B + 1][0], src); ld_pkt<544>(&A[2 * B + 1][4], src); ld_pkt<576>(&A[2 * B + 1][8], src);
    asm volatile("{ .reg .b64 h;\n" LDH("%0", "%1", "%4", "1536") LDH("%2", "%3", "%4", "9728") "}"
                 : "=&r"(A[2 * B][12]), "=&r"(A[2 * B][13]), "=&r"(A[2 * B + 1][12]), "=&r"(A[2 * B + 1][13])
                 : "l"((const char*)src - lane * 8) : "memory");
}
#define BLK_TEST "xor.b32 t, %0, %30;\n" CHK("%4", "%30") CHK("%8", "%30") CHK("%12", "%30") CHK("%16", "%30") CHK("%20", "%30") CHK("%24", "%30") CHK("%26", "%30") VOTE_OK
template <int B>
__device__ __forceinline__ void blk_check(uint32_t (&A)[8][14], const uint4* src, int lane, uint32_t tag) {
    asm volatile("{ .reg .pred p; .reg .b32 n, t; .reg .b128 q; .reg .b64 h, a8;\n" BLK_TEST
                 "mov.u32 n, 0;\n mad.wide.s32 a8, %29, -8, %28;\n LP:\n"
                 LDP("%0", "%1", "%2", "%3", "%28", "0") LDP("%4", "%5", "%6", "%7", "%28", "512") LDP("%8", "%9", "%10", "%11", "%28", "1024")
                 LDP("%12", "%13", "%14", "%15", "%28", "8192") LDP("%16", "%17", "%18", "%19", "%28", "8704") LDP("%20", "%21", "%22", "%23", "%28", "9216")
                 LDH("%24", "%25", "a8", "1536") LDH("%26", "%27", "a8", "9728") BLK_TEST SPIN_TAIL("3")
                 "\n and.b32 %0, %0, -2; and.b32 %4, %4, -2; and.b32 %8, %8, -2; and.b32 %12, %12, -2; and.b32 %16, %16, -2; and.b32 %20, %20, -2; and.b32 %24, %24, -2; and.b32 %26, %26, -2;"
                 : RW4(A[2 * B], 0), RW4(A[2 * B], 4), RW4(A[2 * B], 8), RW4(A[2 * B + 1], 0), RW4(A[2 * B + 1], 4), RW4(A[2 * B + 1], 8),
                   RW2(A[2 * B], 12), RW2(A[2 * B + 1], 12)
                 : "l"(src), "r"(lane), "r"(tag)
                 : "memory");
}
__device__ __forceinline__ void st_async4(uint32_t a, uint32_t x, uint32_t y, uint32_t z, uint32_t w, uint32_t bar) {
    asm volatile("st.async.weak.shared::cluster.mbarrier::complete_tx::bytes.v4.b32 [%0], {%1,%2,%3,%4}, [%5];" ::"r"(a), "r"(x), "r"(y), "r"(z), "r"(w), "r"(bar) : "memory");
}
__device__ __forceinline__ uint32_t mapa(uint32_t a, uint32_t cta) { uint32_t r; asm("mapa.shared::cluster.u32 %0, %1, %2;" : "=r"(r) : "r"(a), "r"(cta)); return r; }
__device__ __forceinline__ void stat_load(uint32_t* v, const uint4* p) { ld_pkt<0>(v, p); ld_pkt<512>(v + 4, p); }
__device__ __forceinline__ void stat_check(uint32_t* v, const uint4* p, uint32_t tag) {
    asm volatile("{ .reg .pred p; .reg .b32 n, t; .reg .b128 q; mov.u32 n, 0;\n LP:\n"
                 "xor.b32 t, %3, %9;\n" CHK("%7", "%9") VOTE_OK
                 LDP("%0", "%1", "%2", "%3", "%8", "0") LDP("%4", "%5", "%6", "%7", "%8", "8192") SPIN_TAIL("4")
                 : RW4(v, 0), RW4(v, 4) : "l"(p), "r"(tag) : "memory");
}
__device__ __forceinline__ uint32_t x_bits(const uint32_t* X) {
    uint32_t r;
    asm volatile("{ .reg .b32 a, b; prmt.b32 a, %1, %2, 0x0040; prmt.b32 b, %3, %4, 0x0040; prmt.b32 %0, a, b, 0x5410; }" : "=r"(r) : "r"(X[0]), "r"(X[4]), "r"(X[8]), "r"(X[12]));
    return r;
}
template <int O>
__device__ __forceinline__ void slice_load(uint32_t* v, const uint4* p, int lane) {
    ld_pkt<O>(v, p); ld_pkt<O + 32>(v + 4, p); ld_pkt<O + 64>(v + 8, p);
    asm volatile("{ .reg .b64 h;\n" LDH("%0", "%1", "%2", "%3") "}" : "=r"(v[12]), "=r"(v[13]) : "l"((const char*)p - lane * 8), "n"(16 * (O + 96)) : "memory");
}
#define SLICE_TEST "xor.b32 t, %0, %16;\n" CHK("%4", "%16") CHK("%8", "%16") CHK("%12", "%16") VOTE_OK
template <int O>
__device__ __forceinline__ void slice_check(uint32_t* v, const uint4* p, int lane, uint32_t tag) {
    asm volatile("{ .reg .pred p; .reg .b32 n, t; .reg .b128 q; .reg .b64 h;\n" SLICE_TEST "mov.u32 n, 0;\n LP:\n"
                 LDP("%0", "%1", "%2", "%3", "%14", "%17") LDP("%4", "%5", "%6", "%7", "%14", "%18") LDP("%8", "%9", "%10", "%11", "%14", "%19")
                 LDH("%12", "%13", "%15", "%20") SLICE_TEST SPIN_TAIL("5")
                 : RW4(v, 0), RW4(v, 4), RW4(v, 8), RW2(v, 12)
                 : "l"(p), "l"((const char*)p - lane * 8), "r"(tag), "n"(16 * O), "n"(16 * (O + 32)), "n"(16 * (O + 64)), "n"(16 * (O + 96))
                 : "memory");
}
__device__ __forceinline__ void x_fix(uint32_t* X, uint32_t bits) {
    X[0] = __byte_perm(X[0], bits, 0x3214); X[4] = __byte_perm(X[4], bits, 0x3215); X[8] = __byte_perm(X[8], bits, 0x3216); X[12] = __byte_perm(X[12], bits, 0x3217);
}
__device__ __forceinline__ void sts4(uint32_t a, uint32_t x, uint32_t y, uint32_t z, uint32_t w) {
    asm volatile("st.shared.v4.u32 [%0], {%1,%2,%3,%4};" ::"r"(a), "r"(x), "r"(y), "r"(z), "r"(w) : "memory");
}
__device__ __forceinline__ void lds4(uint32_t* v, uint32_t a) {
    asm volatile("ld.shared.v4.u32 {%0,%1,%2,%3}, [%4];" : "=r"(v[0]), "=r"(v[1]), "=r"(v[2]), "=r"(v[3]) : "r"(a) : "memory");
}
struct LnCoef { uint32_t hi, lo, sh; };
__device__ __forceinline__ LnCoef ln_coef(float sum, float sq) {
    sum += __shfl_xor_sync(0xffffffffu, sum, 1); sq += __shfl_xor_sync(0xffffffffu, sq, 1);
    sum += __shfl_xor_sync(0xffffffffu, sum, 2); sq += __shfl_xor_sync(0xffffffffu, sq, 2);
    const float mean = sum * (1.f / 448.f);
    const float var = fmaxf(fmaf(-mean, mean, sq * (1.f / 448.f)), 0.f);
    const float sc = rsqrtf(var + 1e-5f);
    LnCoef r;
    r.hi = pack2(sc, sc);
    const float lo = sc - bf_lo(r.hi), sh = -mean * sc;
    r.lo = pack2(lo, lo);
    r.sh = pack2(sh, sh);
    return r;
}
template <int B>
__device__ __forceinline__ void normalize(uint32_t (&A)[8][14], const LnCoef& c0, const LnCoef& c1) {
#pragma unroll
    for (int s = 2 * B; s < 2 * B + 2; s++)
#pragma unroll
        for (int i = 0; i < 14; i++) {
            const LnCoef& k = (i & 1) ? c1 : c0;
            asm("{ .reg .b32 t; fma.rn.bf16x2 t, %0, %2, %3; fma.rn.bf16x2 %0, %0, %1, t; }" : "+r"(A[s][i]) : "r"(k.hi), "r"(k.lo), "r"(k.sh));
        }
}
__device__ __forceinline__ void slice_stats(const uint32_t* w, float* st) {
    float a = 0.f, b = 0.f, p = 0.f, q = 0.f;
#pragma unroll
    for (int i = 0; i < 7; i++) {
        const float e0 = bf_lo(w[2 * i]), e1 = bf_hi(w[2 * i]), e2 = bf_lo(w[2 * i + 1]), e3 = bf_hi(w[2 * i + 1]);
        a += e0 + e1; b += e2 + e3;
        p = fmaf(e0, e0, p); p = fmaf(e1, e1, p); q = fmaf(e2, e2, q); q = fmaf(e3, e3, q);
    }
    a += __shfl_xor_sync(0xffffffffu, a, 1); p += __shfl_xor_sync(0xffffffffu, p, 1); b += __shfl_xor_sync(0xffffffffu, b, 1); q += __shfl_xor_sync(0xffffffffu, q, 1);
    a += __shfl_xor_sync(0xffffffffu, a, 2); p += __shfl_xor_sync(0xffffffffu, p, 2); b += __shfl_xor_sync(0xffffffffu, b, 2); q += __shfl_xor_sync(0xffffffffu, q, 2);
    st[0] = a; st[1] = p; st[2] = b; st[3] = q;
}
__device__ __forceinline__ void dual_softmax(const float* p, uint32_t* out) {
    constexpr float L = 1.4426950408889634f;
#pragma unroll
    for (int r = 0; r < 2; r++) {
        float mx = fmaxf(p[2 * r], p[2 * r + 1]), mn = fminf(p[2 * r], p[2 * r + 1]);
#pragma unroll
        for (int i = 1; i < 7; i++) {
            mx = fmaxf(mx, fmaxf(p[4 * i + 2 * r], p[4 * i + 2 * r + 1]));
            mn = fminf(mn, fminf(p[4 * i + 2 * r], p[4 * i + 2 * r + 1]));
        }
        mx = fmaxf(mx, __shfl_xor_sync(0xffffffffu, mx, 1));
        mn = fminf(mn, __shfl_xor_sync(0xffffffffu, mn, 1));
        const float bx = -mx * L, bn = mn * L;
        float ep[14], en[14], sp = 0.f, sn = 0.f;
#pragma unroll
        for (int i = 0; i < 14; i++) {
            const float v = p[4 * (i >> 1) + 2 * r + (i & 1)];
            ep[i] = ex2(fmaf(v, L, bx));
            en[i] = ex2(fmaf(v, -L, bn));
            sp += ep[i]; sn += en[i];
        }
        sp += __shfl_xor_sync(0xffffffffu, sp, 1);
        sn += __shfl_xor_sync(0xffffffffu, sn, 1);
        const float ip = rcp(sp), in = rcp(sn);
#pragma unroll
        for (int i = 0; i < 7; i++) {
            out[4 * i + r] = pack2(ep[2 * i] * ip, ep[2 * i + 1] * ip);
            out[4 * i + 2 + r] = pack2(en[2 * i] * in, en[2 * i + 1] * in);
        }
    }
}
__device__ __forceinline__ float geglu(float g, float u) {
    const float t = tanh_hw(g * fmaf(g * g, 0.7978845608028654f * 0.044715f, 0.7978845608028654f));
    const float gu = g * u;
    return fmaf(t, gu, gu);
}
__device__ __forceinline__ void phi_gemm(const float* t, float* p) {
    uint32_t w[14];
#pragma unroll
    for (int i = 0; i < 14; i++) w[i] = pack2(t[2 * i], t[2 * i + 1]);
    const uint64_t db = BASE128(OFF_WPHI, 16, 0);
    wg_fence();
    mma_rs56<0, 0>(p, w[0], w[1], w[2], w[3], 0, db);
    mma_rs56<0, 2>(p, w[4], w[5], w[6], w[7], 1, db);
    mma_rs56<0, 4>(p, w[8], w[9], w[10], w[11], 1, db);
    mma_rs56<0, 6>(p, w[12], w[13], 0u, 0u, 1, db);
    wg_commit();
    wg_wait<0>();
}

}

#define BAR(i) (bars + 8 * (i))
#define R_WAIT() mbar_wait(BAR(slot), ph)
#define WSUM(i)
#define R_ADJ (slot * (STAGE >> 4))
#define R_NEXT() do { eb2 = eb1; eb1 = BAR(B_EMPTY + slot); if (++slot == NST) { slot = 0; ph ^= 1; } } while (0)
#define R_RELEASE(k) do { if (lane == 0) mbar_arrive((k) == 1 ? eb1 : eb2); } while (0)
#define PUSH_BEGIN() do { mbar_wait(BAR(B_ACK + wgi), ackph); ackph ^= 1; } while (0)
#define PUSH_ACK() do { __syncwarp(); if (lane == 0) asm volatile("mbarrier.arrive.shared::cluster.b64 _, [%0];" ::"r"(mapa(BAR(B_ACK + wgi), hr ^ 1)) : "memory"); } while (0)

__global__ void __cluster_dims__(2, 1, 1) __launch_bounds__(384, 1)
fused_kernel(Scratch* const sc, const __nv_bfloat16* __restrict__ x_in, const __nv_bfloat16* __restrict__ w_phi, const int trips,
             const __nv_bfloat16* __restrict__ wg, const __nv_bfloat16* __restrict__ wu, const __nv_bfloat16* __restrict__ wd,
             const __grid_constant__ Maps maps) {
    extern __shared__ __align__(1024) unsigned char smem_raw[];
    const uint32_t sb = s2u(smem_raw);
    const uint32_t bars = sb + OFF_BAR;
    const int wgi = __shfl_sync(0xffffffffu, threadIdx.x >> 7, 0);
    const int hr = blockIdx.x & 1, ck = blockIdx.x >> 1;
    const int gp = (ck - 4) & 7, q7 = ((ck - 36) * 37) >> 8;
    const int pr = __shfl_sync(0xffffffffu, ck < 4 ? ck : (ck < 36 ? (ck - 4) >> 3 : q7), 0);
    const int tile = __shfl_sync(0xffffffffu, ck < 4 ? 0 : (ck < 36 ? (gp ? 2 * gp : 1) : 2 * (ck - 36 - 7 * q7) + 3), 0);
    const int sl = 2 * pr + hr;
    STAMP(0);
    GSTAMP(60);
    if (threadIdx.x == 256) {
#pragma unroll
        for (int i = 0; i < NST; i++) mbar_init(BAR(i), 1);
        asm volatile("fence.mbarrier_init.release.cluster;" ::: "memory");
    }
    if (threadIdx.x == 288) {
        if ((sb & 0x3FFFF) != SB0) asm volatile("trap;");
#pragma unroll
        for (int i = NST; i < B_COUNT; i++) mbar_init(BAR(i), i >= B_ACK ? 4 : (i < B_RECV || i == B_LATE ? 8 : 1));
        asm volatile("fence.mbarrier_init.release.cluster;" ::: "memory");
    }
    __syncwarp();
    asm volatile("barrier.cluster.arrive.relaxed.aligned;" ::: "memory");

    if (wgi == 2) {
        asm volatile("setmaxnreg.dec.sync.aligned.u32 40;");
        const int t128 = fresh_tid() & 127, w = __shfl_sync(0xffffffffu, t128 >> 5, 0), lane = t128 & 31;
        uint32_t e0[2] = {0, 0}, e1[2] = {0, 0}, cw_target = 0, kseq;
        if (w == 0) {
#pragma unroll 1
            for (int n = 0; n < NST; n++) {
                const uint32_t dst = sb + n * STAGE, fb = BAR(n);
                asm volatile(ELECT "mbarrier.arrive.expect_tx.shared::cta.b64 _, [%0], %1; }" ::"r"(fb), "r"(n < 2 ? 2 * STAGE : STAGE) : "memory");
                if (n < 2) {
                    tma3x(sb + OFF_H + n * STAGE, &maps.x, tile * 128 + n * 64, fb);
                    tma3x(dst, &maps.x, tile * 128 + n * 64 + 32, fb);
                } else {
                    if (n == 3) mbar_wait(BAR(1), 0);
                    const int c0 = (n < 4 ? 448 : 896) + 56 * sl, r0 = 224 * (n & 1);
                    tma2d(dst, &maps.qkv, c0, r0, fb);
                    tma2d(dst + HALF, &maps.qkv, c0, r0 + 112, fb);
                }
            }
            asm volatile("barrier.cluster.wait.aligned;" ::: "memory");
            kseq = ld_word(g_c1 + (sl * 8 * 16 + tile) * 32);
            cw_target = (ld_word(g_cw + sl * 32) & ~15u) + 16;
#pragma unroll 1
            for (int k = 0; k < 2; k++) {
                const int n = t128 + 32 * k;
                int m = n - 2 - (n > PACK);
                const bool packed = m >= 30 ? (m < 38 || m >= 52) : m >= 22;
                if (m >= 30) m -= 30;
                if (n == PACK) m = tile < 8 ? tile : tile + 14;
                const int rot = n < 8 ? 0 : pr;
                const int ra = 112 * kblk(rot, m & 3), rb = 112 * kblk(rot, 2 * m & 3), rc = 112 * kblk(rot, (2 * m + 1) & 3);
                int kind = 0, m0, m1, c0, c1, r0, r1;
                if (m < 8) { m0 = m1 = m < 6 ? 1 : 2; c0 = c1 = (m < 2 ? 448 : (m < 4 ? 896 : 0)) + 56 * sl; r0 = rb; r1 = rc; }
                else if (m < 20) { m0 = 3; m1 = 4; c0 = c1 = 224 * sl + 32 * hr + 64 * ((m - 8) >> 2); r0 = r1 = ra; }
                else if (m < 22) { kind = 2; m0 = 5; m1 = 6; c0 = c1 = 224 * sl + (hr ? 0 : 192); r0 = rb; r1 = rc; }
                else { m0 = m1 = 7; c0 = c1 = 56 * (2 * ((pr + (m >> 1) - 10) & 3) + hr); r0 = 224 * (sl ^ (m & 1)); r1 = r0 + 112; }
                if (packed) { kind = 1; r0 = sl * 16 + (m < 8 ? m : m - 14); r1 = 0; }
                e0[0] = e0[1]; e1[0] = e1[1];
                e0[1] = kind | (m0 << 2) | (m1 << 6) | (c0 << 10) | (c1 << 21);
                e1[1] = r0 | (r1 << 16);
            }
        } else {
            const int j = t128 - 32;
            kseq = ld_word(g_c1 + (sl * 8 * 16 + tile) * 32);
            asm volatile("barrier.cluster.wait.aligned;" ::: "memory");
            uint2 wv[7];
            const int k = j < 56 ? j : 55, hh = k >= 28;
#pragma unroll
            for (int i = 0; i < 7; i++) wv[i] = __ldg(reinterpret_cast<const uint2*>(w_phi + (sl * 56 + k) * 28) + i);
#pragma unroll 1
            for (int i = j; i < 7168 / 16; i += 96) sts4(sb + OFF_WPHI + i * 16, 0, 0, 0, 0);
            bar_sync(5, 96);
            if (j < 56) {
                uint32_t a4[4];
#pragma unroll
                for (int q = 0; q < 4; q++) a4[q] = sb + OFF_WPHI + (4 * hh + q) * 128 + ((((k >> 3) ^ (4 * hh + q)) & 7) << 4) + (k & 7) * 2;
                FOR14(const uint32_t v = (t & 1) ? wv[t >> 1].y : wv[t >> 1].x;
                      asm volatile("{ .reg .b16 l, h; mov.b32 {l, h}, %2; st.shared.u16 [%0+%3], l; st.shared.u16 [%1+%3], h; }"
                                   ::"r"(a4[t >= 7 ? 2 : 0]), "r"(a4[t >= 7 ? 3 : 1]), "r"(v), "n"((t % 7) * 1024) : "memory"));
            }
            __syncwarp();
            fence_async();
            kseq = __shfl_sync(0xffffffffu, kseq, 0);
            bar_arrive(1, 224);
            bar_arrive(9, 224);
        }
        kseq = __shfl_sync(0xffffffffu, kseq, 0);
        int slot = 0, ph = 0, n = NST;
#pragma unroll 1
        for (int layer = 0; layer < 3; layer++) {
            if (w == 0) {
                const int nend = layer == 0 ? 11 : (layer == 1 ? 42 : 63);
#pragma unroll 1
                for (; n < nend; n++) {
                const uint32_t w0 = __shfl_sync(0xffffffffu, n < 32 ? e0[0] : e0[1], n & 31), w1 = __shfl_sync(0xffffffffu, n < 32 ? e1[0] : e1[1], n & 31);
                const uint32_t dst = sb + slot * STAGE, fb = BAR(n == PACK ? B_PACK : slot);
                const CUtensorMap* m0 = &maps.x + ((w0 >> 2) & 15);
                const CUtensorMap* m1 = &maps.x + ((w0 >> 6) & 15);
                const int c0 = (w0 >> 10) & 2047, c1 = w0 >> 21, r0 = w1 & 0xffff, r1 = w1 >> 16;
                if (n == 25) {
                    int it = 0;
                    uint32_t v;
                    do { asm volatile("ld.acquire.gpu.global.u32 %0, [%1];" : "=r"(v) : "l"(g_cw + sl * 32) : "memory"); } while ((int)(v - cw_target) < 0 && ++it < 0x400000);
                    asm volatile("fence.proxy.async.global;" ::: "memory");
                    __syncwarp();
                }
                mbar_wait(BAR(B_EMPTY + slot), ph);
                __syncwarp();
                asm volatile(ELECT "mbarrier.arrive.expect_tx.shared::cta.b64 _, [%0], %1; }" ::"r"(fb), "r"(STAGE) : "memory");
                if ((w0 & 3) == 0) {
                    tma2d(dst, m0, c0, r0, fb);
                    tma2d(dst + HALF, m1, c1, r1, fb);
                } else if (w0 & 1) {
                    asm volatile(ELECT "cp.async.bulk.shared::cluster.global.mbarrier::complete_tx::bytes [%0], [%1], %2, [%3]; }"
                                 ::"r"(dst), "l"(reinterpret_cast<const char*>(g_wp) + (size_t)r0 * STAGE), "r"(STAGE), "r"(fb) : "memory");
                } else {
                    tma2d(dst, m0, c0, r0, fb); tma2d(dst + 7168, m0, c0, r1, fb);
                    tma2d(dst + HALF, m1, c0, r0, fb); tma2d(dst + HALF + 7168, m1, c0, r1, fb);
                }
                if (n == PFN) {
                    const int b = blockIdx.x;
                    asm volatile(ELECT "cp.async.bulk.prefetch.L2.global [%0], %1; }" ::"l"(wg + b * 6272), "r"(12544) : "memory");
                    asm volatile(ELECT "cp.async.bulk.prefetch.L2.global [%0], %1; }" ::"l"(wu + b * 6272), "r"(12544) : "memory");
                    asm volatile(ELECT "cp.async.bulk.prefetch.L2.global [%0], %1; }" ::"l"(wd + b * 6272), "r"(12544) : "memory");
                }
                if (n == PACK) asm volatile(ELECT "mbarrier.arrive.shared::cta.b64 _, [%0]; }" ::"r"(BAR(slot)) : "memory");
                if (++slot == NST) { slot = 0; ph ^= 1; }
                }
            } else if (w == 1 && layer == 1) {
                constexpr int ps = PACK % NST;
                mbar_wait(BAR(B_PACK), 0);
                asm volatile("{ .reg .pred e; elect.sync _|e, 0xffffffff;\n"
                             "@e cp.async.bulk.global.shared::cta.bulk_group [%0], [%1], %2;\n"
                             "@e cp.async.bulk.commit_group;\n"
                             "@e cp.async.bulk.wait_group.read 0;\n"
                             "@e mbarrier.arrive.shared::cta.b64 _, [%3], 8;\n"
                             "@e cp.async.bulk.wait_group 0;\n"
                             "@e fence.proxy.async.global;\n"
                             "@e red.release.gpu.global.add.u32 [%4], 1; }"
                             ::"l"(reinterpret_cast<char*>(g_wp) + (size_t)(sl * 16 + tile) * STAGE), "r"(sb + ps * STAGE), "r"(STAGE), "r"(BAR(B_EMPTY + ps)), "l"(g_cw + sl * 32) : "memory");
                __syncwarp();
            }
            if (layer < 2) {
            const uint32_t tag = layer ^ 1;
            kseq++;
            bar_sync(7, 384);
            ASTAMP(0);
            if (tile < 15) {
                const int sq = lane >> 3, pk = 8 * w + (lane & (tile == 14 ? 3 : 7));
                uint32_t v[16];
                if (layer == 0) poll_cnt(g_c1 + ((sl * 8 + (w >> 1) * 4 + (tile >> 2)) * 16 + (lane & 15)) * 32, kseq);
                ASTAMP(1);
                poll4_kv<32>(v, g_kv1 + ((sl * 16 + tile) * 16 + 4 * sq) * 32 + pk, tag);
#pragma unroll
                for (int k = 0; k < 4; k++) {
                    float lo = (bf_lo(v[k]) + bf_lo(v[4 + k])) + (bf_lo(v[8 + k]) + bf_lo(v[12 + k]));
                    float hi = (bf_hi(v[k]) + bf_hi(v[4 + k])) + (bf_hi(v[8 + k]) + bf_hi(v[12 + k]));
                    lo += __shfl_xor_sync(0xffffffffu, lo, 8); hi += __shfl_xor_sync(0xffffffffu, hi, 8);
                    lo += __shfl_xor_sync(0xffffffffu, lo, 16); hi += __shfl_xor_sync(0xffffffffu, hi, 16);
                    v[k] = pack2(lo, hi);
                }
                if (sq == 0) st_pkt<0>(g_kv2 + sl * 512 + 32 * tile + pk, settag(v[0], tag), v[1], v[2], v[3]);
            }
            ASTAMP(2);
            {
                const int item = t128 < 112 ? t128 : 112 + (t128 & 3), d = item >> 1;
                const int cc = t128 < 112 ? 2 * (d >= 28) + (item & 1) : item - 112;
                const int r = t128 < 112 ? d : 56 + (cc >> 1) + 2 * ((t128 - 112) >> 2);
                uint32_t ra = sb + OFF_KVB + r * 128 + 4 * cc, rx = (r & 7) << 4;
                asm volatile("" : "+r"(ra), "+r"(rx));
                FOR14(asm volatile("st.shared.u32 [%0+%2], %1;" ::"r"((ra ^ 8) + (((t & 7) << 4) ^ rx)), "r"(0), "n"((t >> 3) * 8192) : "memory"));
                uint32_t v[16];
                asm volatile("" : "+r"(ra), "+r"(rx));
                poll4_kv<8>(v, g_kv2 + sl * 512 + (item >> 3) * 32 + (item & 7), tag);
                FOR14(asm volatile("st.shared.u32 [%0+%2], %1;" ::"r"(ra + (((t & 7) << 4) ^ rx)), "r"(v[t < 7 ? t : t + 1]), "n"((t >> 3) * 8192) : "memory"));
                fence_async();
            }
            bar_arrive(3, 384);
            ASTAMP(3);
            }
        }
    } else {
        asm volatile("setmaxnreg.inc.sync.aligned.u32 232;");
        int lane = fresh_tid() & 31, prf = pr;
#define pr prf
#define g (lane >> 2)
#define c (lane & 3)
#define t128 (w * 32 + lane)
        const int wu = __shfl_sync(0xffffffffu, fresh_tid() >> 5, 0), w = wu & 3;
        const uint32_t xoff = __shfl_sync(0xffffffffu, (3 * PLANE + ((tile * 2 + wgi) * 8) * 512 + w * 128) * 16, 0);
        char* xu = reinterpret_cast<char*>(g_ex) + xoff;
#define FRESH() asm volatile("" : "+l"(xu), "+r"(lane), "+r"(prf))
#define xp0 (reinterpret_cast<uint4*>(xu) + lane)
        const uint32_t hbuf = sb + OFF_H + wgi * STAGE;
        uint32_t slot = 0, ph = 0, eb1 = 0, eb2 = 0, ackph = 0, rcvph = 0, gatph = 0, swp = 0;
        uint32_t ppid = 6;
#define cx(s) (reinterpret_cast<uint32_t*>(reinterpret_cast<uint4*>(xu) + PL(1) + 112 + (s) * 512))
#define stp (reinterpret_cast<uint4*>(xu) + g + PL(0) + 112)
        uint32_t seq = ld_word(cx(sl));
        uint32_t kseq = ld_word(g_c1 + ((sl * 8 + wu) * 16 + tile) * 32);
        uint32_t stag = ld_word(reinterpret_cast<const uint32_t*>(stp + sl * 512) + 3) & 1;
        asm volatile("barrier.cluster.wait.aligned;" ::: "memory");
        STAMP(1);
        uint32_t X[14];
        const uint32_t x0row = (w < 2 ? hbuf : sb + wgi * STAGE) + ((w & 1) * 16 + (lane & 15)) * 128;
        mbar_wait(BAR(wgi), 0);
        STAMP(51);
#pragma unroll
        for (int j = 0; j < 4; j++) {
            const int G = 7 * sl + min(2 * j + (lane >> 4), 6);
            uint32_t q2, q3;
            asm volatile("ldmatrix.sync.aligned.m8n8.x4.shared.b16 {%0,%1,%2,%3}, [%4];" : "=r"(X[4 * j]), "=r"(X[4 * j + 1]), "=r"(q2), "=r"(q3)
                         : "r"(x0row + (G >> 3) * 4096 + (((G ^ lane) & 7) << 4)) : "memory");
            if (j < 3) { X[(4 * j + 2) % 14] = q2; X[(4 * j + 3) % 14] = q3; }
        }
#define PUSH_SLICE(W)                                                                          \
    {                                                                                          \
        if (t128 == 0) mbar_expect_tx(BAR(B_RECV + wgi), 7168);                                \
        PUSH_BEGIN();                                                                          \
        const uint32_t ra = mapa(hbuf + 24576 + t128 * 16, hr ^ 1), rb = mapa(sb + OFF_XR + wgi * 3072, hr ^ 1), rbar = mapa(BAR(B_RECV + wgi), hr ^ 1); \
        st_async4(ra, W[0], W[1], W[2], W[3], rbar);                                           \
        st_async4(ra + 2048, W[4], W[5], W[6], W[7], rbar);                                    \
        st_async4(rb + t128 * 16, W[8], W[9], W[10], W[11], rbar);                             \
        asm volatile("st.async.weak.shared::cluster.mbarrier::complete_tx::bytes.v2.b32 [%0], {%1,%2}, [%3];" ::"r"(rb + 2048 + t128 * 8), "r"(W[12]), "r"(W[13]), "r"(rbar) : "memory"); \
    }
#define PULL_SLICE(W)                                                                          \
    {                                                                                          \
        uint32_t t0, t1;                                                                       \
        mbar_wait(BAR(B_RECV + wgi), rcvph);                                                   \
        rcvph ^= 1;                                                                            \
        lds4(&A[1][0], hbuf + 24576 + t128 * 16);                                              \
        lds4(&A[1][4], hbuf + 26624 + t128 * 16);                                              \
        lds4(&A[1][8], sb + OFF_XR + wgi * 3072 + t128 * 16);                                  \
        asm volatile("ld.shared.v2.u32 {%0,%1}, [%2];" : "=r"(t0), "=r"(t1) : "r"(sb + OFF_XR + wgi * 3072 + 2048 + t128 * 8) : "memory"); \
        _Pragma("unroll") for (int i = 0; i < 12; i++) A[0][i] = (i & 3) ? W[i] : W[i] & ~1u;  \
        A[1][0] &= ~1u; A[1][4] &= ~1u; A[1][8] &= ~1u;                                        \
        A[0][12] = (hr ? t0 : W[12]) & ~1u; A[0][13] = hr ? t1 : W[13];                        \
        A[1][12] = (hr ? W[12] : t0) & ~1u; A[1][13] = hr ? W[13] : t1;                        \
        asm volatile("" : RW4(A[0], 0), RW4(A[0], 4), RW4(A[0], 8), RW2(A[0], 12), RW4(A[1], 0), RW4(A[1], 4), RW4(A[1], 8), RW2(A[1], 12)); \
        swp = hr * 448;                                                                        \
    }
#define SWB(b, t, db, sh) ((b) == 0 && (t) < 6 ? ((t) < 3 ? db##p : db##m) : db)
#define DECL_DB(b, MK, lbo, sh) const uint64_t db = MK(0, lbo, R_ADJ), dbp = (b) == 0 ? MK(0, lbo, R_ADJ + (swp >> (sh))) : db, dbm = (b) == 0 ? MK(0, lbo, R_ADJ - (swp >> (sh))) : db;
#define PPB 2
#define PP_WAIT() if (wgi == 1) { bar_sync(ppid, 256); ppid ^= 14; }
#define PP_GO() if (wgi == 0) { bar_arrive(ppid, 256); ppid ^= 14; }
#define GAT_DST(B, s2) ((B) == 1 ? hbuf + w * 3584 + (s2) * 1792 : ((s2) ? sb + OFF_KVB + wgi * 8192 : hbuf + 14336) + w * 1792)
#define GAT_ISSUE(B, base)                                                                     \
    {                                                                                          \
        const char* gs = xu + ((base) + kblk(pr, B) * 1024) * 16;                              \
        asm volatile("{ .reg .pred e; elect.sync _|e, 0xffffffff;\n"                           \
                     "@e mbarrier.arrive.expect_tx.shared::cta.b64 _, [%3], 3584;\n"           \
                     "@e cp.async.bulk.shared::cluster.global.mbarrier::complete_tx::bytes [%0], [%2], 1792, [%3];\n" \
                     "@e cp.async.bulk.shared::cluster.global.mbarrier::complete_tx::bytes [%1], [%2+8192], 1792, [%3]; }" \
                     ::"r"(GAT_DST(B, 0)), "r"(GAT_DST(B, 1)), "l"(gs), "r"(BAR(B_GAT + wu * 2 + ((B) >> 1))) : "memory"); \
        __syncwarp();                                                                          \
    }
#define GAT_FETCH(B)                                                                           \
    {                                                                                          \
        mbar_wait(BAR(B_GAT + wu * 2 + ((B) >> 1)), (gatph >> (B)) & 1);                          \
        gatph ^= 1 << (B);                                                                     \
        _Pragma("unroll") for (int s2 = 0; s2 < 2; s2++) {                                     \
            const uint32_t ga = GAT_DST(B, s2) + lane * 16;                                    \
            lds4(&A[2 * (B) + s2][0], ga); lds4(&A[2 * (B) + s2][4], ga + 512); lds4(&A[2 * (B) + s2][8], ga + 1024); \
            asm volatile("ld.shared.v2.u32 {%0,%1}, [%2];" : "=r"(A[2 * (B) + s2][12]), "=r"(A[2 * (B) + s2][13]) : "r"(ga - lane * 8 + 1536) : "memory"); \
        }                                                                                      \
    }
#define LATE_ARRIVE() do { if (lane == 0) mbar_arrive(BAR(B_LATE)); } while (0)
#define LATE_WAIT() do { mbar_wait(BAR(B_LATE), gatph & 1); gatph ^= 1; } while (0)
#define PT 3
#define PREP(b, t, remote)                                                                     \
    if constexpr ((b) < 3 && (t) == PT) {                                                      \
        wg_commit();                                                                           \
        STAMP(74 + 6 * (step & 1) + 2 * (b));                                                  \
        if (remote) {                                                                          \
            if constexpr ((b) == 0) { blk_load<2>(A, BLK(xsrc, 2), lane); if (XG3 == 3) blk_load<3>(A, BLK(xsrc, 3), lane); GAT_FETCH(1) }       \
            blk_check<((b) + 1) & 3>(A, BLK(xsrc, (b) + 1), lane, xtag);                       \
            if constexpr ((b) == 0 && XG3 == 0) blk_load<3>(A, BLK(xsrc, 3), lane); \
            if constexpr ((b) == 0 && XG3 == 2) GAT_ISSUE(3, (step & 1) ? PL(2) : PL(0))                        \
        }                                                                                      \
        STAMP(75 + 6 * (step & 1) + 2 * (b));                                                  \
        normalize<((b) + 1) & 3>(A, k0, k1);                                                   \
        asm volatile("" : RW4(A[(2 * (b) + 2) & 7], 0), RW4(A[(2 * (b) + 2) & 7], 4), RW4(A[(2 * (b) + 2) & 7], 8), RW2(A[(2 * (b) + 2) & 7], 12), \
                          RW4(A[(2 * (b) + 3) & 7], 0), RW4(A[(2 * (b) + 3) & 7], 4), RW4(A[(2 * (b) + 3) & 7], 8), RW2(A[(2 * (b) + 3) & 7], 12)); \
        wg_fence();                                                                            \
    }
#define X0_BLOCK(b)                                                                            \
    { const int rr = lane & 7, hi = lane >> 4;                                                 \
    const uint32_t rowa = (w < 2 ? hbuf : sb + wgi * STAGE) + ((w & 1) * 16 + (lane & 15)) * 128; \
    FOR7(constexpr int G = 14 * (b) + (t < 3 ? 2 * t : (t < 6 ? 2 * t + 1 : 6));               \
         uint32_t q0, q1, q2, q3;                                                              \
         const uint32_t ad = t < 6 ? rowa + (((((G & 7) + hi) ^ rr) & 7) << 4) + ((G & 7) == 7 ? hi * 4096 : 0) : rowa + ((G + 7 * hi) >> 3) * 4096 + ((((G + 7 * hi) ^ rr) & 7) << 4); \
         asm volatile("ldmatrix.sync.aligned.m8n8.x4.shared.b16 {%0,%1,%2,%3}, [%4+%5];" : "=r"(q0), "=r"(q1), "=r"(q2), "=r"(q3) \
                      : "r"(ad), "n"(t < 6 ? (G >> 3) * 4096 : 0) : "memory");                 \
         if (t < 3) { A[2 * (b)][4 * t] = q0; A[2 * (b)][4 * t + 1] = q1; A[2 * (b)][4 * t + 2] = q2; A[2 * (b)][4 * t + 3] = q3; } \
         else if (t < 6) { A[2 * (b) + 1][(4 * t - 12) & 15] = q0; A[2 * (b) + 1][((4 * t - 12) & 15) + 1] = q1; A[2 * (b) + 1][((4 * t - 12) & 15) + 2] = q2; A[2 * (b) + 1][((4 * t - 12) & 15) + 3] = q3; } \
         else { A[2 * (b)][12] = q0; A[2 * (b)][13] = q1; A[2 * (b) + 1][12] = q2; A[2 * (b) + 1][13] = q3; }); }
#define BLK(base, b) ((base) + kblk(pr, b) * 1024)

#pragma unroll 1
        for (int step = 0; step < 4; step++) {
            FRESH();
            const uint32_t tag = (step >> 1) ^ 1;
            const int so = (step >> 1) * 24 + (step & 1) * 12;
            (void)so;
            uint32_t A[8][14];
            uint4* const xsrc = xp0 + ((step & 1) ? PL(2) : PL(0));
            const uint32_t xtag = (step & 1) ? tag : ((seq >> 3) & 1) ^ 1;
            uint32_t xbits;
            {
                float st[4];
                slice_stats(X, st);
                stag ^= 1;
                xbits = x_bits(X);
                tag_slice(X, xtag);
                if (step) send_slice<0>(xsrc + sl * 512, lane, X);
                if (c == 0) st_pkt<0>(stp + sl * 512, __float_as_uint(st[0]), __float_as_uint(st[1]), __float_as_uint(st[2]), settag(__float_as_uint(st[3]), stag));
            }
            STAMP(2 + so);
            uint32_t sv[8];
            if (step == 0) {
                X0_BLOCK(0) X0_BLOCK(1) X0_BLOCK(2) X0_BLOCK(3)
                mbar_wait(BAR(wgi ^ 1), 0);
                R_NEXT();
                R_NEXT();
                R_RELEASE(2);
                stat_load(sv, stp + c * 1024);
                stat_check(sv, stp + c * 1024, stag);
                STAMP(52 + step);
            } else {
                kill<14>(A[2]); kill<14>(A[3]); kill<14>(A[4]); kill<14>(A[5]); kill<14>(A[6]); kill<14>(A[7]);
                PUSH_SLICE(X)
                stat_load(sv, stp + c * 1024);
                PULL_SLICE(X)
                stat_check(sv, stp + c * 1024, stag);
                STAMP(52 + step);
                GAT_ISSUE(1, (step & 1) ? PL(2) : PL(0))
                if (XG3 == 1) GAT_ISSUE(3, (step & 1) ? PL(2) : PL(0))
            }
            LnCoef k0, k1;
            {
                k0 = ln_coef(__uint_as_float(sv[0]) + __uint_as_float(sv[4]), __uint_as_float(sv[1]) + __uint_as_float(sv[5]));
                k1 = ln_coef(__uint_as_float(sv[2]) + __uint_as_float(sv[6]), __uint_as_float(sv[3] & ~1u) + __uint_as_float(sv[7] & ~1u));
            }
            STAMP(3 + so);
            GSTAMP(70 + step);

            if ((step & 1) == 0) {
                float tq[28];
#define K_BLOCK(b)                                                                            \
    if ((b) == 1) R_RELEASE(1);                                                               \
    if ((b) == 2 + XT) PUSH_ACK();                                                            \
    if ((b) == 2 && XT && step) GAT_FETCH(3)                                                  \
    if ((b) == 3) { wg_wait<2>(); R_RELEASE(1); }                                             \
    if (((b) & 1) == 0) R_WAIT();                                                             \
    { DECL_DB(b, BASE128, 16, 0)                                                              \
    wg_fence();                                                                               \
    FOR7(mma_rs56<1, D128(((b) & 1) * HALF, t)>(tq, AQ(A, b, t), (b) + t > 0, SWB(b, t, db, 0)); \
         PREP(b, t, step)); }                                                                 \
    wg_commit();                                                                              \
    if ((b) & 1) R_NEXT();
#define P_STAGE(acc, b0)                                                                      \
    R_WAIT();                                                                                 \
    { DECL_DB(b0, BASE128, 16, 0)                                                             \
    wg_fence();                                                                               \
    FOR7(mma_rs56<1, D128(0, t)>(acc, AQ(A, b0, t), (b0) + t > 0, SWB(b0, t, db, 0)));        \
    FOR7(mma_rs56<1, D128(HALF, t)>(acc, AQ(A, (b0) + 1, t), 1, db)); }                       \
    wg_commit();                                                                              \
    R_NEXT();
#define PROJECT(acc) P_STAGE(acc, 0) P_STAGE(acc, 2) wg_wait<1>(); R_RELEASE(2); wg_wait<0>(); R_RELEASE(1);
#define V_PASS()                                                                              \
    {                                                                                         \
        float av[28];                                                                         \
        PROJECT(av)                                                                           \
        const int m = lane >> 3, rr = lane & 7;                                               \
        const uint32_t rowa = hbuf + 16384 + (w * 16 + rr + 8 * (m & 1)) * 128;               \
        const uint32_t one = c == 0 ? 0x00003f80u : 0u;                                       \
        _Pragma("unroll") for (int j = 0; j < 4; j++) {                                       \
            const uint32_t a = rowa + (((2 * j + (m >> 1)) ^ rr) << 4);                       \
            if (j < 3) stsm4(a, pack2(av[8 * j], av[8 * j + 1]), pack2(av[8 * j + 2], av[8 * j + 3]), pack2(av[8 * j + 4], av[8 * j + 5]), pack2(av[8 * j + 6], av[8 * j + 7])); \
            else stsm4(a, pack2(av[24], av[25]), pack2(av[26], av[27]), one, one);            \
        }                                                                                     \
    }
                normalize<0>(A, k0, k1);
                K_BLOCK(0) K_BLOCK(1) K_BLOCK(2) K_BLOCK(3)
                wg_wait<0>();
                R_RELEASE(1);
                STAMP(4 + so);
                if (step == 0) { bar_sync(wgi ? 9 : 1, 224); }
                if (wgi == VW) V_PASS()
                uint32_t PH[28];
                int it = 1;
#pragma unroll 1
                do {
                    float pp[28];
                    phi_gemm(tq, pp);
                    dual_softmax(pp, PH);
                    if (((trips >> (it + 1)) & 1) == 0) continue;
                    {
                        const int m = lane >> 3, rr = lane & 7;
                        const uint32_t rowa = hbuf + (w * 16 + rr + 8 * (m & 1)) * 128;
#pragma unroll
                        for (int j = 0; j < 7; j++) {
                            const int cg = 2 * j + (m >> 1), hi = cg >= 7;
                            stsm4(rowa + hi * 8192 + (((cg - 7 * hi) ^ rr) << 4), PH[4 * j], PH[4 * j + 1], PH[4 * j + 2], PH[4 * j + 3]);
                        }
                    }
                    STAMP(5 + so);
                    if (wgi != VW) V_PASS()
                    fence_async();
                    bar_sync(2, 256);
                    float kv[28];
                    const uint64_t da = BASE128(OFF_H + 16384, 16, 0), dbk = BASE128(OFF_H, 16, wgi * 512);
                    wg_fence();
                    FOR8(constexpr uint64_t o = ((t >> 2) * STAGE + (t & 3) * 2048) >> 4; mma_ss56_tt<o, o>(kv, t > 0, da, dbk));
                    wg_commit();
                    wg_wait<0>();
#pragma unroll
                    for (int hf = 0; hf < 2; hf++) {
                        const int d = 16 * w + g + 8 * hf;
                        if ((d < 56 && (d >= 28) == (c >= 2)) || d == 56) {
                            const int item = d < 56 ? 2 * d + (c & 1) : 112 + c;
                            uint4* dst = g_kv1 + ((sl * 16 + (item >> 3)) * 16 + tile) * 32 + wgi * 16 + (item & 7);
#define KVW(i) pack2(kv[4 * (i) + 2 * hf], kv[4 * (i) + 2 * hf + 1])
                            st_pkt<0>(dst, settag(KVW(0), tag), KVW(1), KVW(2), KVW(3));
                            st_pkt<8>(dst, settag(KVW(4), tag), KVW(5), KVW(6), 0u);
                        }
                    }
                    __syncwarp();
                    kseq++;
                    if (lane == 0) st_word(g_c1 + ((sl * 8 + wu) * 16 + tile) * 32, kseq);
                    bar_arrive(7, 384);
                    STAMP(6 + so);
                    kill<28>(tq);
                    if (QPP) { PP_WAIT() }
                    P_STAGE(tq, 0) P_STAGE(tq, 2)
                    if (QPP) { PP_GO() }
                    wg_wait<1>(); R_RELEASE(2); wg_wait<0>(); R_RELEASE(1);
                    STAMP(7 + so);
                    kill<28>(PH);
                } while (((trips >> (++it)) & 1));
                STAMP(8 + so);
                FRESH();
                if (step) {
                    slice_load<PL(0)>(X, xp0 + sl * 512, lane);
                } else {
                    const uint32_t* xp = reinterpret_cast<const uint32_t*>(x_in + (size_t)(tile * 128 + wu * 16 + g) * 448 + 56 * sl + 2 * c);
#pragma unroll
                    for (int i = 0; i < 7; i++) { X[2 * i] = __ldg(xp + 4 * i); X[2 * i + 1] = __ldg(xp + 4 * i + 8 * 224); }
                }
                bar_sync(3, 384);
                STAMP(9 + so);
                const uint4* const osrc = xp0 + PL(1);
                {
                    float nm[32];
                    const uint64_t db = BASE128(OFF_KVB, 16, 0);
                    wg_fence();
                    FOR7(mma_rs64<0, ((t >> 2) * 8192 + (t & 3) * 32) / 16>(nm, PH[4 * t], PH[4 * t + 1], PH[4 * t + 2], PH[4 * t + 3], t > 0, db));
                    wg_commit();
                    wg_wait<0>();
                    LATE_ARRIVE();
                    const float i00 = rcp(nm[28] + 1e-6f), i01 = rcp(nm[29] + 1e-6f), i10 = rcp(nm[30] + 1e-6f), i11 = rcp(nm[31] + 1e-6f);
                    const float m0 = c >= 2 ? i01 : i00, m1 = c >= 2 ? i11 : i10;
                    uint32_t O[14];
#pragma unroll
                    for (int i = 0; i < 7; i++) {
                        const float f0 = i < 3 ? i00 : (i > 3 ? i01 : m0), f1 = i < 3 ? i10 : (i > 3 ? i11 : m1);
                        O[2 * i] = pack2(nm[4 * i] * f0, nm[4 * i + 1] * f0);
                        O[2 * i + 1] = pack2(nm[4 * i + 2] * f1, nm[4 * i + 3] * f1);
                    }
                    if (OST) { PP_WAIT() }
                    tag_slice(O, tag);
                    send_slice<PL(1)>(xp0 + sl * 512, lane, O);
                    seq++;
                    if (lane == 0) st_word(cx(sl), seq);
                    STAMP(10 + so);
                    PUSH_SLICE(O)
                    if (OST == 1) { PP_GO() }
                    const uint32_t cv = ld_word(cx(lane & 7));
                    PULL_SLICE(O)
                    LATE_WAIT();
                    check_cnt(cv, cx(lane & 7), seq);
                    if (OST == 2) { PP_GO() }
                    STAMP(56 + (step >> 1));
                    GAT_ISSUE(1, PL(1))
                    GAT_ISSUE(3, PL(1))
                    blk_load<2>(A, BLK(osrc, 2), lane);
                }
                float ao[28];
#define WO_BLOCK(b)                                                                           \
    if ((b) > 0) blk_check<b>(A, BLK(osrc, b), lane, tag);                                    \
    if (((b) & 1) == 0) R_WAIT();                                                             \
    { DECL_DB(b, BASE128, 16, 0)                                                              \
    wg_fence();                                                                               \
    FOR7(mma_rs56<1, D128(((b) & 1) * HALF, t)>(ao, AQ(A, b, t), (b) + t > 0, SWB(b, t, db, 0))); } \
    wg_commit();                                                                              \
    if ((b) & 1) R_NEXT();
                WO_BLOCK(0)
                STAMP(11 + so);
                GAT_FETCH(1)
                WO_BLOCK(1)
                WO_BLOCK(2)
                GAT_FETCH(3)
                WO_BLOCK(3)
                PUSH_ACK();
                wg_wait<0>();
                R_RELEASE(2);
                STAMP(12 + so);
                WSUM(86 + 7 * (step >> 1));
                x_fix(X, xbits);
#pragma unroll
                for (int i = 0; i < 14; i++) X[i] = pack2(bf_lo(X[i]) + ao[2 * i], bf_hi(X[i]) + ao[2 * i + 1]);
            } else {
                uint32_t H[56];
                float ag[64];
#define F1_EPI(dst, ng, ag)                                                                    \
    _Pragma("unroll") for (int i = 0; i < 2 * (ng); i++)                                       \
        (dst)[i] = pack2(geglu(ag[2 * i], ag[4 * (ng) + 2 * i]), geglu(ag[2 * i + 1], ag[4 * (ng) + 2 * i + 1]));
#define H_PUSH(h0, off) st_async4(rem_h + (off), H[h0], H[(h0) + 1], H[(h0) + 2], H[(h0) + 3], mapa(BAR(B_RECV2 + wgi), hr ^ 1));
#define F1_BLOCK(b, first)                                                                     \
    if ((first) && (b) == 1) R_RELEASE(2);                                                     \
    if ((first) && (b) == 2 + XT) PUSH_ACK();                                                  \
    if ((first) && (b) == 2 && XT) GAT_FETCH(3)                                                \
    R_WAIT();                                                                                  \
    if ((b) == ((first) ? PPF : PPB)) { PP_WAIT() }                                            \
    { DECL_DB(b, BASE128, HALF, 0)                                                             \
    wg_fence();                                                                                \
    FOR7(mma_rs128<1, D128(0, t)>(ag, AQ(A, b, t), (b) + t > 0, SWB(b, t, db, 0));             \
         if constexpr (first) { PREP(b, t, true) }); }                                         \
    wg_commit();                                                                               \
    if ((b) == 3) { PP_GO() }                                                                  \
    if ((b) > 0) { wg_wait<1>(); R_RELEASE(1); }       \
    R_NEXT();
                normalize<0>(A, k0, k1);
                F1_BLOCK(0, true) F1_BLOCK(1, true) F1_BLOCK(2, true) F1_BLOCK(3, true)
                if (t128 == 0) { mbar_expect_tx(BAR(B_RECV + wgi), 16384); mbar_expect_tx(BAR(B_RECV2 + wgi), 12288); }
                PUSH_BEGIN();
                wg_wait<0>();
                R_RELEASE(1);
                int p = 0;
#pragma unroll 1
                do {
                    F1_EPI(H + 32, 8, ag)
                    STAMP(4 + p + so);
                    WSUM(81 + p + 7 * (step >> 1));
                    if (((trips >> (p + 1)) & 1) == 0) continue;
                    if (step == 1 && p == PKP) R_NEXT();
                    kill<64>(ag);
                    F1_BLOCK(0, false)
                    {
                        const uint32_t pk = (p ? hbuf + 16384 : sb + OFF_KVB + wgi * 8192) + w * 2048;
#pragma unroll
                        for (int k = 0; k < 4; k++) sts4(pk + k * 512 + lane * 16, H[32 + 4 * k], H[33 + 4 * k], H[34 + 4 * k], H[35 + 4 * k]);
                        fence_async();
                        __syncwarp();
                        asm volatile(ELECT "cp.async.bulk.shared::cluster.shared::cta.mbarrier::complete_tx::bytes [%0], [%1], 2048, [%2]; }"
                                     ::"r"(mapa(hbuf + p * 8192 + w * 2048, hr ^ 1)), "r"(pk), "r"(mapa(BAR(B_RECV + wgi), hr ^ 1)) : "memory");
                    }
                    F1_BLOCK(1, false) F1_BLOCK(2, false) F1_BLOCK(3, false)
                    wg_wait<0>();
                    R_RELEASE(1);
                    kill<16>(H + 32);
                } while (((trips >> (++p)) & 1));
#pragma unroll
                for (int k = 0; k < 4; k++) lds4(H + 16 + 4 * k, hbuf + 16384 + w * 2048 + k * 512 + lane * 16);
                __syncwarp();
                if (lane == 0) asm volatile("mbarrier.arrive.shared::cluster.b64 _, [%0];" ::"r"(mapa(BAR(B_ACK2 + wgi), hr ^ 1)) : "memory");
                const uint32_t rem_h = mapa(hbuf + w * 2048 + lane * 16, hr ^ 1);
#define F1_LAST(b0)                                                                            \
    R_WAIT();                                                                                  \
    if (b0) { PP_WAIT() }                                                                      \
    { DECL_DB(b0, BASE64, HALF, 1)                                                             \
    wg_fence();                                                                                \
    FOR7(mma_rs64<1, D64(0, t)>(al, AQ(A, b0, t), (b0) + t > 0, SWB(b0, t, db, 1)));           \
    FOR7(mma_rs64<1, D64(7168, t)>(al, AQ(A, (b0) + 1, t), 1, db)); }                          \
    wg_commit();                                                                               \
    if (b0) { PP_GO() }                                                                        \
    R_NEXT();
                float al[32];
                F1_LAST(0)
                mbar_wait(BAR(B_RECV + wgi), rcvph);
                rcvph ^= 1;
                mbar_wait(BAR(B_ACK2 + wgi), step >> 1);
                H_PUSH(32, 16384) H_PUSH(36, 16896)
                F1_LAST(2)
                H_PUSH(40, 17408) H_PUSH(44, 17920)
                wg_wait<1>();
                R_RELEASE(2);
                wg_wait<0>();
                R_RELEASE(1);
                uint32_t HP[56];
#pragma unroll
                for (int k = 0; k < 4; k++) lds4(H + 4 * k, sb + OFF_KVB + wgi * 8192 + w * 2048 + k * 512 + lane * 16);
#pragma unroll
                for (int t = 0; t < 8; t++) lds4(HP + 4 * t, hbuf + (t >> 2) * 8192 + w * 2048 + (t & 3) * 512 + lane * 16);
                F1_EPI(H + 48, 4, al)
                H_PUSH(48, 24576 - w * 1024) H_PUSH(52, 25088 - w * 1024)
                STAMP(7 + so);
                WSUM(84 + 7 * (step >> 1));
                FRESH();
                float acc[28];
                const uint32_t roA = hr ? 256u : 0u, roB = hr ? (uint32_t)-1536 : 0u;
                const uint32_t rpA = hr ? 0u : 256u, rpB = hr ? 0u : (uint32_t)-1536;
                float res[28];
                uint32_t v0[14], v1[14], P[14];
                Wide PW;
                const uint4* ps = xp0 + sl * 512;
#define F2_OWN_A()                                                                             \
    R_WAIT();                                                                                  \
    d0 = BASE128(0, 16, R_ADJ + roA); d1 = BASE128(0, 16, R_ADJ + roB);                        \
    wg_fence();                                                                                \
    FOR14(if constexpr (t < OT) mma_rs56<1, t * 128>(acc, H[4 * t], H[4 * t + 1], H[4 * t + 2], H[4 * t + 3], t > 0, d0)); \
    wg_commit();
#define F2_OWN_B()                                                                             \
    wg_fence();                                                                                \
    FOR14(if constexpr (t >= OT) mma_rs56<1, t * 128>(acc, H[4 * t], H[4 * t + 1], H[4 * t + 2], H[4 * t + 3], 1, t < 12 ? d0 : d1)); \
    wg_commit();                                                                               \
    R_NEXT();
#define F2_PEER()                                                                              \
    R_WAIT();                                                                                  \
    if (F2PP) { PP_WAIT() }                                                                    \
    d0 = BASE128(0, 16, R_ADJ + rpA); d1 = BASE128(0, 16, R_ADJ + rpB);                        \
    wg_fence();                                                                                \
    FOR14(mma_rs56<1, t * 128>(acc, HP[4 * t], HP[4 * t + 1], HP[4 * t + 2], HP[4 * t + 3], 1, t < 12 ? d0 : d1)); \
    wg_commit();                                                                               \
    if (F2PP) { PP_GO() }                                                                      \
    R_NEXT();
#define F2_TURN(u)                                                                             \
    wg_wait<1>();                                                                              \
    if ((u) < 2 || TDEF < 2) R_RELEASE(2);                                                     \
    wg_wait<0>();                                                                              \
    if ((u) < 2 || TDEF < 1) R_RELEASE(1);                                                     \
    _Pragma("unroll") for (int i = 0; i < 14; i++) P[i] = pack2(acc[2 * i], acc[2 * i + 1]);   \
    tag_slice(P, tag);                                                                         \
    PW = widen(P);                                                                             \
    kill<28>(acc);                                                                             \
    F2_OWN_A()                                                                                 \
    if ((u) == 2) { slice_load<PL(3)>(v0, ps, lane); slice_load<PL(4)>(v1, ps, lane); } \
    send_wide<PL(3 + (u))>(xp0 + (2 * ((pr + (u) + 1) & 3) + hr) * 512, lane, PW);             \
    seq++;                                                                                     \
    if (lane == 0) st_word(cx(sl), seq);                                                       \
    __syncwarp();                                                                              \
    STAMP(8 + (u) + so);                                                                       \
    F2_OWN_B()
                uint64_t d0, d1;
                F2_OWN_A()
                F2_OWN_B()
                R_WAIT();
                d0 = BASE128(0, 16, R_ADJ + rpA); d1 = BASE128(0, 16, R_ADJ + rpB);
                wg_fence();
                FOR8(mma_rs56<1, t * 128>(acc, HP[4 * t], HP[4 * t + 1], HP[4 * t + 2], HP[4 * t + 3], 1, d0));
                wg_commit();
                mbar_wait(BAR(B_RECV2 + wgi), step >> 1);
#pragma unroll
                for (int k = 0; k < 4; k++) lds4(HP + 32 + 4 * k, hbuf + 16384 + w * 2048 + k * 512 + lane * 16);
                lds4(HP + 48, hbuf + 24576 + w * 1024 + lane * 16);
                lds4(HP + 52, hbuf + 25088 + w * 1024 + lane * 16);
                if (step == 1) PUSH_ACK();
                wg_fence();
                FOR14(if constexpr (t >= 8) mma_rs56<1, t * 128>(acc, HP[4 * t], HP[4 * t + 1], HP[4 * t + 2], HP[4 * t + 3], 1, t < 12 ? d0 : d1));
                wg_commit();
                R_NEXT();
                F2_TURN(0)
                F2_PEER()
                F2_TURN(1)
                F2_PEER()
                F2_TURN(2)
                if (step == 1) STAMP(64);
                slice_check<PL(3)>(v0, ps, lane, tag);
                slice_check<PL(4)>(v1, ps, lane, tag);
#pragma unroll
                for (int i = 0; i < 14; i++) { res[2 * i] = bf_lo(v0[i]) + bf_lo(v1[i]); res[2 * i + 1] = bf_hi(v0[i]) + bf_hi(v1[i]); }
                slice_load<PL(2)>(X, ps, lane);
                if (step == 1) STAMP(65);
                F2_PEER()
                if (step == 1) STAMP(66);
                poll_cnt(cx(2 * ((pr + 1) & 3) + hr), seq);
                if (step == 1) STAMP(67);
                slice_load<PL(5)>(v0, ps, lane);
                x_fix(X, xbits);
                slice_check<PL(5)>(v0, ps, lane, tag);
                if (lane < TDEF) mbar_arrive(BAR(B_EMPTY + (slot + NST - 3 - lane) % NST));
#pragma unroll
                for (int i = 0; i < 14; i++) { res[2 * i] += bf_lo(v0[i]); res[2 * i + 1] += bf_hi(v0[i]); }
                STAMP(11 + so);
                wg_wait<0>();
                R_RELEASE(2);
                STAMP(12 + so);
                WSUM(85 + 7 * (step >> 1));
#pragma unroll
                for (int i = 0; i < 14; i++) X[i] = pack2(fmaf(res[2 * i] + acc[2 * i], 0.5f, bf_lo(X[i])), fmaf(res[2 * i + 1] + acc[2 * i + 1], 0.5f, bf_hi(X[i])));
            }
        }
        {
            const int m = lane >> 3, rr = lane & 7;
            const uint32_t ob = hbuf + w * 2048, rowa = ob + (rr + 8 * (m & 1)) * 112 + (m >> 1) * 16;
#pragma unroll
            for (int j = 0; j < 3; j++) stsm4(rowa + 32 * j, X[4 * j], X[4 * j + 1], X[4 * j + 2], X[4 * j + 3]);
            asm volatile("stmatrix.sync.aligned.m8n8.x2.shared.b16 [%0], {%1,%2};" ::"r"(ob + (rr + 8 * (m & 1)) * 112 + 96), "r"(X[12]), "r"(X[13]) : "memory");
            fence_async();
            __syncwarp();
            if (lane == 0) {
                asm volatile("cp.async.bulk.tensor.2d.global.shared::cta.bulk_group [%0, {%2, %3}], [%1];" ::"l"(&maps.out), "r"(ob), "r"(56 * sl), "r"(tile * 128 + wu * 16) : "memory");
                asm volatile("cp.async.bulk.commit_group;" ::: "memory");
                asm volatile("cp.async.bulk.wait_group.read 0;" ::: "memory");
            }
        }
        STAMP(50);
        GSTAMP(61);
        PDUMP();
    }
}

#undef g
#undef pr
#undef c
#undef t128

typedef CUresult (*EncodeFn)(CUtensorMap*, CUtensorMapDataType, cuuint32_t, void*, const cuuint64_t*, const cuuint64_t*, const cuuint32_t*,
                             const cuuint32_t*, CUtensorMapInterleave, CUtensorMapSwizzle, CUtensorMapL2promotion, CUtensorMapFloatOOBfill);

static void make_map(EncodeFn enc, CUtensorMap* m, const void* p, uint64_t cols, uint64_t rows, uint32_t bc, uint32_t br, CUtensorMapSwizzle sw) {
    cuuint64_t gd[2] = {cols, rows};
    cuuint64_t gs[1] = {cols * 2};
    cuuint32_t bd[2] = {bc, br};
    cuuint32_t es[2] = {1, 1};
    enc(m, CU_TENSOR_MAP_DATA_TYPE_BFLOAT16, 2, const_cast<void*>(p), gd, gs, bd, es, CU_TENSOR_MAP_INTERLEAVE_NONE, sw,
        CU_TENSOR_MAP_L2_PROMOTION_L2_128B, CU_TENSOR_MAP_FLOAT_OOB_FILL_NONE);
}

extern "C" void kernel_launch(void* const* d_in, const int* in_sizes, int n_in, void* d_out, int out_size) {
    (void)in_sizes; (void)n_in; (void)out_size;
    static EncodeFn enc = nullptr;
    static Scratch* scratch = nullptr;
    if (!enc) {
        void* fn = nullptr;
        cudaDriverEntryPointQueryResult qr;
        cudaGetDriverEntryPoint("cuTensorMapEncodeTiled", &fn, cudaEnableDefault, &qr);
        enc = (EncodeFn)fn;
        cudaGetSymbolAddress((void**)&scratch, g_scratch);
        cudaFuncSetAttribute(fused_kernel, cudaFuncAttributeMaxDynamicSharedMemorySize, SMEM_BYTES);
    }
    Maps maps;
    {
        cuuint64_t gd[3] = {64, 2048, 7};
        cuuint64_t gs[2] = {896, 128};
        cuuint32_t bd[3] = {64, 32, 7};
        cuuint32_t es[3] = {1, 1, 1};
        enc(&maps.x, CU_TENSOR_MAP_DATA_TYPE_BFLOAT16, 3, d_in[0], gd, gs, bd, es, CU_TENSOR_MAP_INTERLEAVE_NONE, CU_TENSOR_MAP_SWIZZLE_128B,
            CU_TENSOR_MAP_L2_PROMOTION_L2_128B, CU_TENSOR_MAP_FLOAT_OOB_FILL_NONE);
    }
    make_map(enc, &maps.out, d_out, 448, 2048, 56, 16, CU_TENSOR_MAP_SWIZZLE_NONE);
    make_map(enc, &maps.qkv, d_in[1], 1344, 448, 64, 112, CU_TENSOR_MAP_SWIZZLE_128B);
    make_map(enc, &maps.wo, d_in[3], 448, 448, 64, 112, CU_TENSOR_MAP_SWIZZLE_128B);
    make_map(enc, &maps.wg, d_in[5], 1792, 448, 64, 112, CU_TENSOR_MAP_SWIZZLE_128B);
    make_map(enc, &maps.wu, d_in[6], 1792, 448, 64, 112, CU_TENSOR_MAP_SWIZZLE_128B);
    make_map(enc, &maps.wg32, d_in[5], 1792, 448, 32, 112, CU_TENSOR_MAP_SWIZZLE_64B);
    make_map(enc, &maps.wu32, d_in[6], 1792, 448, 32, 112, CU_TENSOR_MAP_SWIZZLE_64B);
    make_map(enc, &maps.wd, d_in[7], 448, 1792, 64, 112, CU_TENSOR_MAP_SWIZZLE_128B);
    fused_kernel<<<128, 384, SMEM_BYTES>>>(scratch, (const __nv_bfloat16*)d_in[0], (const __nv_bfloat16*)d_in[2], 7, (const __nv_bfloat16*)d_in[5],
                                           (const __nv_bfloat16*)d_in[6], (const __nv_bfloat16*)d_in[7], maps);
}
```
